```python
import torch

def _softmax(x, axis=-1):
    return torch.softmax(x, dim=axis)

def _gelu(x):
    return torch.nn.functional.gelu(x, approximate='tanh')

def _silu(x):
    return torch.nn.functional.silu(x)

def _sigmoid(x):
    return torch.sigmoid(x)

def _layernorm(x, axis=-1, eps=1e-05):
    m = x.mean(dim=axis, keepdim=True)
    v = x.var(dim=axis, keepdim=True, unbiased=False)
    return (x - m) / torch.sqrt(v + eps)

def _scatter_add(tgt, idx, src, axis=0):
    return tgt.clone().index_add_(axis, idx, src)

def _segment_sum(src, seg, n):
    out = torch.zeros((n,) + src.shape[1:], dtype=src.dtype)
    return out.index_add_(0, seg, src)

def _pad(x, pw):
    flat = tuple((v for pair in reversed(pw) for v in pair))
    return torch.nn.functional.pad(x, flat)
kernel_name = 'adaLN_cond__mha_block_cached__moe_arch_mod__prompt'

def setup_inputs():

    _w = lambda a: (lambda t: t.to(torch.bfloat16) if t.is_floating_point() else t)(torch.as_tensor(a))

    def _A_setup():
        B, Sq, D = (1, 2048, 1024)
        H, Sk, Dh = (32, 2048, 128)
        return {'x': _w((lambda *s: torch.randn(*s, dtype=torch.bfloat16) * 0.1)(B, Sq, D)), 'k_cache': _w((lambda *s: torch.randn(*s, dtype=torch.bfloat16) * 0.8)(B, H, Sk, Dh)), 'v_cache': _w((lambda *s: torch.randn(*s, dtype=torch.bfloat16) * 0.8)(B, H, Sk, Dh)), 'wq': _w((lambda *s: torch.randn(*s, dtype=torch.bfloat16) * 0.8)(D, H * Dh) * D ** (-0.5)), 'wo': _w((lambda *s: torch.randn(*s, dtype=torch.bfloat16) * 0.8)(H * Dh, D) * (H * Dh) ** (-0.5))}
    _A_in = _A_setup()

    def _B_setup():
        B, S, D, F, C = (1, 2048, 1024, 3584, 2)
        return {'x': _w((lambda *s: torch.randn(*s, dtype=torch.bfloat16) * 0.1)(B, S, D)), 'w_r': _w((lambda *s: torch.randn(*s, dtype=torch.bfloat16) * 3.2)(D)), 'w_gate': _w((lambda *s: torch.randn(*s, dtype=torch.bfloat16) * 0.2)(D, F)), 'w_up': _w((lambda *s: torch.randn(*s, dtype=torch.bfloat16) * 0.2)(D, F)), 'w_down': _w((lambda *s: torch.randn(*s, dtype=torch.bfloat16) * 0.2)(F, D))}
    _B_in = _B_setup()
    return {'A_x': _A_in['x'], 'A_k_cache': _A_in['k_cache'], 'A_v_cache': _A_in['v_cache'], 'A_wq': _A_in['wq'], 'A_wo': _A_in['wo'], 'B_x': _B_in['x'], 'B_w_r': _B_in['w_r'], 'B_w_gate': _B_in['w_gate'], 'B_w_up': _B_in['w_up'], 'B_w_down': _B_in['w_down'], 'c': _w((lambda *s: torch.randn(*s, dtype=torch.bfloat16) * 0.2)(1, 1024) * 8.0), 'w_mod': _w((lambda *s: torch.randn(*s, dtype=torch.bfloat16) * 0.2)(1024, 6 * 1024) * 1024 ** (-0.5) * 8.0)}

def reference(A_x, A_k_cache, A_v_cache, A_wq, A_wo, B_x, B_w_r, B_w_gate, B_w_up, B_w_down, c, w_mod):

    def _A_ref(x, k_cache, v_cache, wq, wo):
        B, Sq, D = x.shape
        H, Dh = (32, 128)
        q = (lambda x, *d: x.permute(*d))((x @ wq).reshape(B, Sq, H, Dh), 0, 2, 1, 3)
        scores = torch.einsum('bhqd,bhkd->bhqk', q, k_cache) * Dh ** (-0.5)
        p = _softmax(scores, axis=-1)
        o = torch.einsum('bhqk,bhkd->bhqd', p, v_cache)
        return (lambda x, *d: x.permute(*d))(o, 0, 2, 1, 3).reshape(B, Sq, H * Dh) @ wo

    def _B_ref(x, w_r, w_gate, w_up, w_down):
        B, S, D = x.shape
        C = 2
        r = x @ w_r
        idx = torch.argsort(-r, axis=-1)[:, :C]
        idx_e = (lambda x, n, axis: torch.repeat_interleave(x, n, dim=axis))(idx.reshape(B, C, 1), D, axis=2)
        x_sel = (lambda x, i, axis: torch.take_along_dim(x, i, dim=axis))(x, idx_e, axis=1)
        g = _silu(x_sel @ w_gate)
        u = x_sel @ w_up
        y = g * u @ w_down
        r_sel = _sigmoid((lambda x, i, axis: torch.take_along_dim(x, i, dim=axis))(r, idx, axis=1))
        y = y * r_sel.reshape(B, C, 1)
        b_off = (torch.arange(B) * S).reshape(B, 1)
        flat_idx = (idx + b_off).reshape(B * C)
        zero = (x * 0.0).reshape(B * S, D)
        upd = _scatter_add(zero, flat_idx, y.reshape(B * C, D), axis=0)
        return x + upd.reshape(B, S, D)
    x = A_x
    mod = (_silu(c) @ w_mod).reshape(c.shape[0], 6, 1, -1)
    sa, ca, ga, sb, cb, gb = (mod[:, 0].clone(), mod[:, 1].clone(), mod[:, 2].clone(), mod[:, 3].clone(), mod[:, 4].clone(), mod[:, 5].clone())
    h = _layernorm(x, axis=-1) * (1 + ca) + sa
    x = x + ga * _A_ref(h, A_k_cache, A_v_cache, A_wq, A_wo)
    h = _layernorm(x, axis=-1) * (1 + cb) + sb
    x = x + gb * _B_ref(h, B_w_r, B_w_gate, B_w_up, B_w_down)
    return x
```

```cpp
#include <cuda_runtime.h>
#include <cuda_bf16.h>
#include <cuda.h>
#include <stdint.h>

namespace {

typedef __nv_bfloat16 bf16;

constexpr int T_SEQ = 2048, T_D = 1024, T_NH = 32, T_DH = 128, T_DQKV = 4096, T_F = 3584;

__device__ __align__(1024) uint4 g_pre[(16 + 128) * 2048];
#define g_h (reinterpret_cast<bf16*>(g_pre + 16 * 2048))
__device__ __align__(1024) bf16 g_o[T_SEQ * T_DQKV];
__device__ __align__(16) uint8_t g_col[8 * 1536];
__device__ __align__(16) float g_scal[64];
__device__ __align__(16) unsigned int g_hcnt[17 * 32];
__device__ __align__(128) float g_modpart[4 * 2 * T_D];
struct __align__(2048) TailMail {
  float4 part1[T_SEQ * 8];
  uint32_t key[256];
  uint4 cand[16 * 2 * 2 * 128];
  uint32_t cnt[32];
  float ypart[(T_F / 32) * 2 * T_D];
};
__device__ TailMail g_mail;
#define g_part1 g_mail.part1
#define g_key g_mail.key
#define g_cand g_mail.cand
#define CNT_Y (g_mail.cnt)
#define g_ypart g_mail.ypart

__device__ __forceinline__ uint32_t smem_u32(const void* p) { return (uint32_t)__cvta_generic_to_shared(p); }
__device__ __forceinline__ void mbar_init(uint32_t bar, uint32_t cnt) { asm volatile("mbarrier.init.shared::cta.b64 [%0], %1;" :: "r"(bar), "r"(cnt)); }
__device__ __forceinline__ void mbar_expect_tx(uint32_t bar, uint32_t bytes) { asm volatile("mbarrier.arrive.expect_tx.shared::cta.b64 _, [%0], %1;" :: "r"(bar), "r"(bytes) : "memory"); }
__device__ __forceinline__ void mbar_arrive(uint32_t bar) { asm volatile("mbarrier.arrive.shared::cta.b64 _, [%0];" :: "r"(bar) : "memory"); }
__device__ __forceinline__ void mbar_wait(uint32_t bar, uint32_t parity) {
  asm volatile("{\n.reg .pred p;\nLAB_WAIT:\nmbarrier.try_wait.parity.shared::cta.b64 p, [%0], %1;\n@!p bra LAB_WAIT;\n}\n" :: "r"(bar), "r"(parity) : "memory");
}
__device__ __forceinline__ bool mbar_test(uint32_t bar, uint32_t parity) {
  uint32_t r; asm volatile("{\n.reg .pred p;\nmbarrier.test_wait.parity.shared::cta.b64 p, [%1], %2;\nselp.u32 %0, 1, 0, p;\n}\n" : "=r"(r) : "r"(bar), "r"(parity) : "memory");
  return r != 0;
}
__device__ __forceinline__ void fence_mbar_init() { asm volatile("fence.mbarrier_init.release.cluster;" ::: "memory"); }
__device__ __forceinline__ void tma_load_2d(uint32_t dst, const CUtensorMap* map, int c0, int c1, uint32_t bar) {
  asm volatile("cp.async.bulk.tensor.2d.shared::cluster.global.mbarrier::complete_tx::bytes [%0], [%1, {%3, %4}], [%2];"
    :: "r"(dst), "l"(map), "r"(bar), "r"(c0), "r"(c1) : "memory");
}
__device__ __forceinline__ uint64_t policy_evict_first() {
  uint64_t p; asm volatile("createpolicy.fractional.L2::evict_first.b64 %0, 1.0;" : "=l"(p)); return p;
}
__device__ __forceinline__ void tma_load_2d_hint(uint32_t dst, const CUtensorMap* map, int c0, int c1, uint32_t bar, uint64_t pol) {
  asm volatile("cp.async.bulk.tensor.2d.shared::cluster.global.mbarrier::complete_tx::bytes.L2::cache_hint [%0], [%1, {%3, %4}], [%2], %5;"
    :: "r"(dst), "l"(map), "r"(bar), "r"(c0), "r"(c1), "l"(pol) : "memory");
}
__device__ __forceinline__ void tma_store_2d(const CUtensorMap* map, uint32_t src, int c0, int c1) {
  asm volatile("cp.async.bulk.tensor.2d.global.shared::cta.bulk_group [%0, {%2, %3}], [%1];" :: "l"(map), "r"(src), "r"(c0), "r"(c1) : "memory");
}
__device__ __forceinline__ void prefetch_tmap(const CUtensorMap* map) { asm volatile("prefetch.tensormap [%0];" :: "l"(map) : "memory"); }
__device__ __forceinline__ void l2_prefetch_bulk(const void* p, uint32_t bytes) {
  asm volatile("cp.async.bulk.prefetch.L2.global [%0], %1;" :: "l"(p), "r"(bytes) : "memory");
}
__device__ __forceinline__ void bulk_commit() { asm volatile("cp.async.bulk.commit_group;" ::: "memory"); }
template<int N> __device__ __forceinline__ void bulk_wait_read() { asm volatile("cp.async.bulk.wait_group.read %0;" :: "n"(N) : "memory"); }
template<int N> __device__ __forceinline__ void bulk_wait() { asm volatile("cp.async.bulk.wait_group %0;" :: "n"(N) : "memory"); }
__device__ __forceinline__ void named_bar_sync(int id, int nthreads) { asm volatile("bar.sync %0, %1;" :: "r"(id), "r"(nthreads) : "memory"); }
__device__ __forceinline__ void named_bar_arrive(int id, int nthreads) { asm volatile("bar.arrive %0, %1;" :: "r"(id), "r"(nthreads) : "memory"); }
__device__ __forceinline__ void wgmma_fence() { asm volatile("wgmma.fence.sync.aligned;" ::: "memory"); }
__device__ __forceinline__ void wgmma_commit() { asm volatile("wgmma.commit_group.sync.aligned;" ::: "memory"); }
template<int N> __device__ __forceinline__ void wgmma_wait() { asm volatile("wgmma.wait_group.sync.aligned %0;" :: "n"(N) : "memory"); }
template<int R> __device__ __forceinline__ void reg_alloc() { asm volatile("setmaxnreg.inc.sync.aligned.u32 %0;" :: "n"(R)); }
template<int R> __device__ __forceinline__ void reg_dealloc() { asm volatile("setmaxnreg.dec.sync.aligned.u32 %0;" :: "n"(R)); }
__device__ __forceinline__ bool elect_one() {
  uint32_t pred; asm volatile("{\n.reg .pred p;\nelect.sync _|p, 0xffffffff;\nselp.u32 %0, 1, 0, p;\n}\n" : "=r"(pred)); return pred != 0;
}
__device__ __forceinline__ uint32_t pack_bf16(float lo, float hi) {
  uint32_t r; asm("cvt.rn.bf16x2.f32 %0, %1, %2;" : "=r"(r) : "f"(hi), "f"(lo)); return r;
}
__device__ __forceinline__ void stmatrix_x4(uint32_t addr, uint32_t r0, uint32_t r1, uint32_t r2, uint32_t r3) {
  asm volatile("stmatrix.sync.aligned.m8n8.x4.shared.b16 [%0], {%1, %2, %3, %4};" :: "r"(addr), "r"(r0), "r"(r1), "r"(r2), "r"(r3) : "memory");
}
__device__ __forceinline__ void fence_proxy_async() { asm volatile("fence.proxy.async.shared::cta;" ::: "memory"); }
__device__ __forceinline__ float ex2_approx(float x) { float y; asm("ex2.approx.ftz.f32 %0, %1;" : "=f"(y) : "f"(x)); return y; }
template<int N> __device__ __forceinline__ void fence_regs(float (&r)[N]) {
  #pragma unroll
  for (int i = 0; i < N; i++) asm volatile("" : "+f"(r[i]) :: "memory");
}
template<int N> __device__ __forceinline__ void zero_regs(float (&r)[N]) {
  #pragma unroll
  for (int i = 0; i < N; i += 2) asm volatile("mov.b64 {%0, %1}, 0;" : "=f"(r[i]), "=f"(r[i + 1]));
}
__device__ __forceinline__ float rbf(float x) { return __uint_as_float(pack_bf16(0.f, x)); }
__device__ __forceinline__ float bflo(uint32_t v) { return __uint_as_float(v << 16); }
__device__ __forceinline__ float bfhi(uint32_t v) { return __uint_as_float(v & 0xffff0000u); }

#define TL_START(k) do {} while (0)
#define TL_END(k, cond) do {} while (0)
#define TL_CTA(i, cond) do {} while (0)
#define FS(slot, k) do {} while (0)
#define TL_MARK2(k, cond) do {} while (0)
#define TL_CLK(k, i, cond) do {} while (0)

template <int OFFA, int OFFB>
__device__ __forceinline__ void wgmma_m64n256k16_ss_tb(float (&d)[128], uint32_t a_lo, uint32_t b_lo, int scaleD) {
  asm volatile("{\n.reg .pred p;\n.reg .b32 ta, tb;\n.reg .b64 da, db;\nsetp.ne.b32 p, %130, 0;\n"
    "add.u32 ta, %128, %131;\nadd.u32 tb, %129, %132;\n"
    "mov.b64 da, {ta, 0x40000040};\nmov.b64 db, {tb, 0x40000040};\n"
    "wgmma.mma_async.sync.aligned.m64n256k16.f32.bf16.bf16 "
    "{%0, %1, %2, %3, %4, %5, %6, %7, %8, %9, %10, %11, %12, %13, %14, %15, %16, %17, %18, %19, %20, %21, %22, %23, %24, %25, %26, %27, %28, %29, %30, %31, %32, %33, %34, %35, %36, %37, %38, %39, %40, %41, %42, %43, %44, %45, %46, %47, %48, %49, %50, %51, %52, %53, %54, %55, %56, %57, %58, %59, %60, %61, %62, %63, %64, %65, %66, %67, %68, %69, %70, %71, %72, %73, %74, %75, %76, %77, %78, %79, %80, %81, %82, %83, %84, %85, %86, %87, %88, %89, %90, %91, %92, %93, %94, %95, %96, %97, %98, %99, %100, %101, %102, %103, %104, %105, %106, %107, %108, %109, %110, %111, %112, %113, %114, %115, %116, %117, %118, %119, %120, %121, %122, %123, %124, %125, %126, %127}, "
    "da, db, p, 1, 1, 0, 1;\n}\n"
    : "+f"(d[0]), "+f"(d[1]), "+f"(d[2]), "+f"(d[3]), "+f"(d[4]), "+f"(d[5]), "+f"(d[6]), "+f"(d[7]), "+f"(d[8]), "+f"(d[9]), "+f"(d[10]), "+f"(d[11]), "+f"(d[12]), "+f"(d[13]), "+f"(d[14]), "+f"(d[15]), "+f"(d[16]), "+f"(d[17]), "+f"(d[18]), "+f"(d[19]), "+f"(d[20]), "+f"(d[21]), "+f"(d[22]), "+f"(d[23]), "+f"(d[24]), "+f"(d[25]), "+f"(d[26]), "+f"(d[27]), "+f"(d[28]), "+f"(d[29]), "+f"(d[30]), "+f"(d[31]), "+f"(d[32]), "+f"(d[33]), "+f"(d[34]), "+f"(d[35]), "+f"(d[36]), "+f"(d[37]), "+f"(d[38]), "+f"(d[39]), "+f"(d[40]), "+f"(d[41]), "+f"(d[42]), "+f"(d[43]), "+f"(d[44]), "+f"(d[45]), "+f"(d[46]), "+f"(d[47]), "+f"(d[48]), "+f"(d[49]), "+f"(d[50]), "+f"(d[51]), "+f"(d[52]), "+f"(d[53]), "+f"(d[54]), "+f"(d[55]), "+f"(d[56]), "+f"(d[57]), "+f"(d[58]), "+f"(d[59]), "+f"(d[60]), "+f"(d[61]), "+f"(d[62]), "+f"(d[63]), "+f"(d[64]), "+f"(d[65]), "+f"(d[66]), "+f"(d[67]), "+f"(d[68]), "+f"(d[69]), "+f"(d[70]), "+f"(d[71]), "+f"(d[72]), "+f"(d[73]), "+f"(d[74]), "+f"(d[75]), "+f"(d[76]), "+f"(d[77]), "+f"(d[78]), "+f"(d[79]), "+f"(d[80]), "+f"(d[81]), "+f"(d[82]), "+f"(d[83]), "+f"(d[84]), "+f"(d[85]), "+f"(d[86]), "+f"(d[87]), "+f"(d[88]), "+f"(d[89]), "+f"(d[90]), "+f"(d[91]), "+f"(d[92]), "+f"(d[93]), "+f"(d[94]), "+f"(d[95]), "+f"(d[96]), "+f"(d[97]), "+f"(d[98]), "+f"(d[99]), "+f"(d[100]), "+f"(d[101]), "+f"(d[102]), "+f"(d[103]), "+f"(d[104]), "+f"(d[105]), "+f"(d[106]), "+f"(d[107]), "+f"(d[108]), "+f"(d[109]), "+f"(d[110]), "+f"(d[111]), "+f"(d[112]), "+f"(d[113]), "+f"(d[114]), "+f"(d[115]), "+f"(d[116]), "+f"(d[117]), "+f"(d[118]), "+f"(d[119]), "+f"(d[120]), "+f"(d[121]), "+f"(d[122]), "+f"(d[123]), "+f"(d[124]), "+f"(d[125]), "+f"(d[126]), "+f"(d[127])
    : "r"(a_lo), "r"(b_lo), "r"(scaleD), "n"(OFFA), "n"(OFFB));
}

template <int OFFA, int OFFB>
__device__ __forceinline__ void wgmma_m64n128k16_ss_tb(float (&d)[64], uint32_t a_lo, uint32_t b_lo, int scaleD) {
  asm volatile("{\n.reg .pred p;\n.reg .b32 ta, tb;\n.reg .b64 da, db;\nsetp.ne.b32 p, %66, 0;\n"
    "add.u32 ta, %64, %67;\nadd.u32 tb, %65, %68;\n"
    "mov.b64 da, {ta, 0x40000040};\nmov.b64 db, {tb, 0x40000040};\n"
    "wgmma.mma_async.sync.aligned.m64n128k16.f32.bf16.bf16 "
    "{%0, %1, %2, %3, %4, %5, %6, %7, %8, %9, %10, %11, %12, %13, %14, %15, %16, %17, %18, %19, %20, %21, %22, %23, %24, %25, %26, %27, %28, %29, %30, %31, %32, %33, %34, %35, %36, %37, %38, %39, %40, %41, %42, %43, %44, %45, %46, %47, %48, %49, %50, %51, %52, %53, %54, %55, %56, %57, %58, %59, %60, %61, %62, %63}, "
    "da, db, p, 1, 1, 0, 1;\n}\n"
    : "+f"(d[0]), "+f"(d[1]), "+f"(d[2]), "+f"(d[3]), "+f"(d[4]), "+f"(d[5]), "+f"(d[6]), "+f"(d[7]), "+f"(d[8]), "+f"(d[9]), "+f"(d[10]), "+f"(d[11]), "+f"(d[12]), "+f"(d[13]), "+f"(d[14]), "+f"(d[15]), "+f"(d[16]), "+f"(d[17]), "+f"(d[18]), "+f"(d[19]), "+f"(d[20]), "+f"(d[21]), "+f"(d[22]), "+f"(d[23]), "+f"(d[24]), "+f"(d[25]), "+f"(d[26]), "+f"(d[27]), "+f"(d[28]), "+f"(d[29]), "+f"(d[30]), "+f"(d[31]), "+f"(d[32]), "+f"(d[33]), "+f"(d[34]), "+f"(d[35]), "+f"(d[36]), "+f"(d[37]), "+f"(d[38]), "+f"(d[39]), "+f"(d[40]), "+f"(d[41]), "+f"(d[42]), "+f"(d[43]), "+f"(d[44]), "+f"(d[45]), "+f"(d[46]), "+f"(d[47]), "+f"(d[48]), "+f"(d[49]), "+f"(d[50]), "+f"(d[51]), "+f"(d[52]), "+f"(d[53]), "+f"(d[54]), "+f"(d[55]), "+f"(d[56]), "+f"(d[57]), "+f"(d[58]), "+f"(d[59]), "+f"(d[60]), "+f"(d[61]), "+f"(d[62]), "+f"(d[63])
    : "r"(a_lo), "r"(b_lo), "r"(scaleD), "n"(OFFA), "n"(OFFB));
}

template <int OFFB>
__device__ __forceinline__ void wgmma_m64n128k16_rs_tb(float (&d)[64], uint32_t a0, uint32_t a1, uint32_t a2, uint32_t a3, uint32_t b_lo, int scaleD) {
  asm volatile("{\n.reg .pred p;\n.reg .b32 tb;\n.reg .b64 db;\nsetp.ne.b32 p, %69, 0;\n"
    "add.u32 tb, %68, %70;\n"
    "mov.b64 db, {tb, 0x40000040};\n"
    "wgmma.mma_async.sync.aligned.m64n128k16.f32.bf16.bf16 "
    "{%0, %1, %2, %3, %4, %5, %6, %7, %8, %9, %10, %11, %12, %13, %14, %15, %16, %17, %18, %19, %20, %21, %22, %23, %24, %25, %26, %27, %28, %29, %30, %31, %32, %33, %34, %35, %36, %37, %38, %39, %40, %41, %42, %43, %44, %45, %46, %47, %48, %49, %50, %51, %52, %53, %54, %55, %56, %57, %58, %59, %60, %61, %62, %63}, "
    "{%64, %65, %66, %67}, db, p, 1, 1, 1;\n}\n"
    : "+f"(d[0]), "+f"(d[1]), "+f"(d[2]), "+f"(d[3]), "+f"(d[4]), "+f"(d[5]), "+f"(d[6]), "+f"(d[7]), "+f"(d[8]), "+f"(d[9]), "+f"(d[10]), "+f"(d[11]), "+f"(d[12]), "+f"(d[13]), "+f"(d[14]), "+f"(d[15]), "+f"(d[16]), "+f"(d[17]), "+f"(d[18]), "+f"(d[19]), "+f"(d[20]), "+f"(d[21]), "+f"(d[22]), "+f"(d[23]), "+f"(d[24]), "+f"(d[25]), "+f"(d[26]), "+f"(d[27]), "+f"(d[28]), "+f"(d[29]), "+f"(d[30]), "+f"(d[31]), "+f"(d[32]), "+f"(d[33]), "+f"(d[34]), "+f"(d[35]), "+f"(d[36]), "+f"(d[37]), "+f"(d[38]), "+f"(d[39]), "+f"(d[40]), "+f"(d[41]), "+f"(d[42]), "+f"(d[43]), "+f"(d[44]), "+f"(d[45]), "+f"(d[46]), "+f"(d[47]), "+f"(d[48]), "+f"(d[49]), "+f"(d[50]), "+f"(d[51]), "+f"(d[52]), "+f"(d[53]), "+f"(d[54]), "+f"(d[55]), "+f"(d[56]), "+f"(d[57]), "+f"(d[58]), "+f"(d[59]), "+f"(d[60]), "+f"(d[61]), "+f"(d[62]), "+f"(d[63])
    : "r"(a0), "r"(a1), "r"(a2), "r"(a3), "r"(b_lo), "r"(scaleD), "n"(OFFB));
}

template <int OFFB>
__device__ __forceinline__ void wgmma_m64n128k16_rs(float (&d)[64], uint32_t a0, uint32_t a1, uint32_t a2, uint32_t a3, uint32_t b_lo, int scaleD) {
  asm volatile("{\n.reg .pred p;\n.reg .b32 tb;\n.reg .b64 db;\nsetp.ne.b32 p, %69, 0;\n"
    "add.u32 tb, %68, %70;\n"
    "mov.b64 db, {tb, 0x40000040};\n"
    "wgmma.mma_async.sync.aligned.m64n128k16.f32.bf16.bf16 "
    "{%0, %1, %2, %3, %4, %5, %6, %7, %8, %9, %10, %11, %12, %13, %14, %15, %16, %17, %18, %19, %20, %21, %22, %23, %24, %25, %26, %27, %28, %29, %30, %31, %32, %33, %34, %35, %36, %37, %38, %39, %40, %41, %42, %43, %44, %45, %46, %47, %48, %49, %50, %51, %52, %53, %54, %55, %56, %57, %58, %59, %60, %61, %62, %63}, "
    "{%64, %65, %66, %67}, db, p, 1, 1, 0;\n}\n"
    : "+f"(d[0]), "+f"(d[1]), "+f"(d[2]), "+f"(d[3]), "+f"(d[4]), "+f"(d[5]), "+f"(d[6]), "+f"(d[7]), "+f"(d[8]), "+f"(d[9]), "+f"(d[10]), "+f"(d[11]), "+f"(d[12]), "+f"(d[13]), "+f"(d[14]), "+f"(d[15]), "+f"(d[16]), "+f"(d[17]), "+f"(d[18]), "+f"(d[19]), "+f"(d[20]), "+f"(d[21]), "+f"(d[22]), "+f"(d[23]), "+f"(d[24]), "+f"(d[25]), "+f"(d[26]), "+f"(d[27]), "+f"(d[28]), "+f"(d[29]), "+f"(d[30]), "+f"(d[31]), "+f"(d[32]), "+f"(d[33]), "+f"(d[34]), "+f"(d[35]), "+f"(d[36]), "+f"(d[37]), "+f"(d[38]), "+f"(d[39]), "+f"(d[40]), "+f"(d[41]), "+f"(d[42]), "+f"(d[43]), "+f"(d[44]), "+f"(d[45]), "+f"(d[46]), "+f"(d[47]), "+f"(d[48]), "+f"(d[49]), "+f"(d[50]), "+f"(d[51]), "+f"(d[52]), "+f"(d[53]), "+f"(d[54]), "+f"(d[55]), "+f"(d[56]), "+f"(d[57]), "+f"(d[58]), "+f"(d[59]), "+f"(d[60]), "+f"(d[61]), "+f"(d[62]), "+f"(d[63])
    : "r"(a0), "r"(a1), "r"(a2), "r"(a3), "r"(b_lo), "r"(scaleD), "n"(OFFB));
}

__device__ __forceinline__ uint4 ldg_nc_v4(const void* p) {
  uint4 v;
    asm volatile("{\n.reg .b64 pol;\ncreatepolicy.fractional.L2::evict_first.b64 pol, 1.0;\n"
                 "ld.global.nc.L1::no_allocate.L2::cache_hint.v4.u32 {%0, %1, %2, %3}, [%4], pol;\n}\n" : "=r"(v.x), "=r"(v.y), "=r"(v.z), "=r"(v.w) : "l"(p));
  return v;
}
__device__ __forceinline__ uint64_t pol_normal() {
  uint64_t p; asm volatile("createpolicy.fractional.L2::evict_normal.b64 %0, 1.0;" : "=l"(p)); return p;
}
__device__ __forceinline__ void unpack8(const uint4& u, float (&v)[8]) {
  v[0] = bflo(u.x); v[1] = bfhi(u.x); v[2] = bflo(u.y); v[3] = bfhi(u.y);
  v[4] = bflo(u.z); v[5] = bfhi(u.z); v[6] = bflo(u.w); v[7] = bfhi(u.w);
}
__device__ __forceinline__ void fma8(float (&acc)[8], float s, const uint4& w) {
  acc[0] = fmaf(s, bflo(w.x), acc[0]); acc[1] = fmaf(s, bfhi(w.x), acc[1]); acc[2] = fmaf(s, bflo(w.y), acc[2]); acc[3] = fmaf(s, bfhi(w.y), acc[3]);
  acc[4] = fmaf(s, bflo(w.z), acc[4]); acc[5] = fmaf(s, bfhi(w.z), acc[5]); acc[6] = fmaf(s, bflo(w.w), acc[6]); acc[7] = fmaf(s, bfhi(w.w), acc[7]);
}
__device__ __forceinline__ float rcp_approx(float x) { float y; asm("rcp.approx.ftz.f32 %0, %1;" : "=f"(y) : "f"(x)); return y; }
__device__ __forceinline__ float sigmoid_f(float v) { return rcp_approx(1.0f + ex2_approx(v * -1.4426950408889634f)); }
__device__ __forceinline__ float silu_bf(float v) { return rbf(v * sigmoid_f(v)); }
__device__ __forceinline__ uint32_t rank_key(float r, int idx) {
  const uint32_t b = __float_as_uint(r) >> 16;
  const uint32_t u = (r != r) ? 0u : ((b & 0x8000u) ? (~b & 0xffffu) : (b | 0x8000u));
  return (u << 16) | (0xffffu - (uint32_t)idx);
}
__device__ __forceinline__ void warp_top2(uint32_t& k1, uint32_t& k2) {
  const uint32_t m1 = __reduce_max_sync(0xffffffffu, k1);
  k2 = __reduce_max_sync(0xffffffffu, k1 == m1 ? k2 : k1);
  k1 = m1;
}
__device__ __forceinline__ uint32_t bmul2(uint32_t a, uint32_t b) { uint32_t r; asm("mul.rn.bf16x2 %0, %1, %2;" : "=r"(r) : "r"(a), "r"(b)); return r; }
__device__ __forceinline__ uint32_t badd2(uint32_t a, uint32_t b) { uint32_t r; asm("add.rn.bf16x2 %0, %1, %2;" : "=r"(r) : "r"(a), "r"(b)); return r; }
__device__ __forceinline__ uint32_t bsub2(uint32_t a, uint32_t b) { uint32_t r; asm("sub.rn.bf16x2 %0, %1, %2;" : "=r"(r) : "r"(a), "r"(b)); return r; }
__device__ __forceinline__ float sqrt_approx(float x) { float y; asm("sqrt.approx.f32 %0, %1;" : "=f"(y) : "f"(x)); return y; }
__device__ __forceinline__ uint32_t ln_norm2(uint32_t x1, uint32_t mb2, float inv) {
  const uint32_t d = bsub2(x1, mb2);
  return pack_bf16(bflo(d) * inv, bfhi(d) * inv);
}
__device__ __forceinline__ uint32_t ln_mod2(uint32_t x1, uint32_t mb2, float inv, uint32_t c1, uint32_t sb) { return badd2(bmul2(ln_norm2(x1, mb2, inv), c1), sb); }
__device__ __forceinline__ void ldmatrix_x4(uint32_t addr, uint32_t& r0, uint32_t& r1, uint32_t& r2, uint32_t& r3) {
  asm volatile("ldmatrix.sync.aligned.m8n8.x4.shared.b16 {%0, %1, %2, %3}, [%4];" : "=r"(r0), "=r"(r1), "=r"(r2), "=r"(r3) : "r"(addr) : "memory");
}
__device__ __forceinline__ uint4 ldg_stream_v4(const void* p, uint64_t pol) {
  uint4 v; asm volatile("ld.global.nc.L1::no_allocate.L2::cache_hint.L2::128B.v4.u32 {%0, %1, %2, %3}, [%4], %5;" : "=r"(v.x), "=r"(v.y), "=r"(v.z), "=r"(v.w) : "l"(p), "l"(pol)); return v;
}
__device__ __forceinline__ void bulk_load_hint(uint32_t dst, const void* src, uint32_t bytes, uint32_t bar, uint64_t pol) {
  asm volatile("cp.async.bulk.shared::cluster.global.mbarrier::complete_tx::bytes.L2::cache_hint [%0], [%1], %2, [%3], %4;"
    :: "r"(dst), "l"(src), "r"(bytes), "r"(bar), "l"(pol) : "memory");
}
__device__ __forceinline__ void red_release_add(unsigned int* p, unsigned int v) { asm volatile("red.release.gpu.global.add.u32 [%0], %1;" :: "l"(p), "r"(v) : "memory"); }
__device__ __forceinline__ unsigned int ld_acquire(const unsigned int* p) { unsigned int v; asm volatile("ld.acquire.gpu.global.u32 %0, [%1];" : "=r"(v) : "l"(p) : "memory"); return v; }
__device__ __forceinline__ void spin_until(const unsigned int* p, unsigned int target) {
  #pragma unroll 1
  for (unsigned int i = 0; i < (1u << 22); i++) { if (ld_acquire(p) >= target) return; }
}
__device__ __forceinline__ float lds_f32(uint32_t a) { float v; asm volatile("ld.shared.f32 %0, [%1];" : "=f"(v) : "r"(a) : "memory"); return v; }
__device__ __forceinline__ float2 lds_f32x2(uint32_t a) { float2 v; asm volatile("ld.shared.v2.f32 {%0, %1}, [%2];" : "=f"(v.x), "=f"(v.y) : "r"(a) : "memory"); return v; }
__device__ __forceinline__ uint2 lds_u32x2(uint32_t a) { uint2 v; asm volatile("ld.shared.v2.u32 {%0, %1}, [%2];" : "=r"(v.x), "=r"(v.y) : "r"(a) : "memory"); return v; }
__device__ __forceinline__ uint32_t lds_u32(uint32_t a) { uint32_t v; asm volatile("ld.shared.u32 %0, [%1];" : "=r"(v) : "r"(a) : "memory"); return v; }
__device__ __forceinline__ void sts_u32(uint32_t a, uint32_t v) { asm volatile("st.shared.u32 [%0], %1;" :: "r"(a), "r"(v) : "memory"); }
__device__ __forceinline__ void sts_u32x2(uint32_t a, uint32_t x, uint32_t y) { asm volatile("st.shared.v2.u32 [%0], {%1, %2};" :: "r"(a), "r"(x), "r"(y) : "memory"); }
__device__ __forceinline__ void sts_f32(uint32_t a, float v) { asm volatile("st.shared.f32 [%0], %1;" :: "r"(a), "f"(v) : "memory"); }
__device__ __forceinline__ void sts_f32x2(uint32_t a, float x, float y) { asm volatile("st.shared.v2.f32 [%0], {%1, %2};" :: "r"(a), "f"(x), "f"(y) : "memory"); }
__device__ __forceinline__ void sts_f32x4(uint32_t a, float x, float y, float z, float w) { asm volatile("st.shared.v4.f32 [%0], {%1, %2, %3, %4};" :: "r"(a), "f"(x), "f"(y), "f"(z), "f"(w) : "memory"); }

__device__ __forceinline__ uint4 lds_u32x4(uint32_t a) { uint4 v; asm volatile("ld.shared.v4.u32 {%0, %1, %2, %3}, [%4];" : "=r"(v.x), "=r"(v.y), "=r"(v.z), "=r"(v.w) : "r"(a) : "memory"); return v; }
__device__ __forceinline__ void sts_u32x4(uint32_t a, uint32_t x, uint32_t y, uint32_t z, uint32_t w) { asm volatile("st.shared.v4.u32 [%0], {%1, %2, %3, %4};" :: "r"(a), "r"(x), "r"(y), "r"(z), "r"(w) : "memory"); }
__device__ __forceinline__ void st_tagged(float* p, float v) {
  const uint32_t b = __float_as_uint(v);
  asm volatile("st.relaxed.gpu.global.u32 [%0], %1;" :: "l"(p), "r"(b == 0u ? 0x80000000u : b) : "memory");
}
__device__ __forceinline__ void st_tagged4(float* p, float x, float y, float z, float w) {
  const uint32_t a = __float_as_uint(x), b = __float_as_uint(y), c = __float_as_uint(z), d = __float_as_uint(w);
  asm volatile("st.relaxed.gpu.global.v4.u32 [%0], {%1, %2, %3, %4};" :: "l"(p), "r"(a == 0u ? 0x80000000u : a), "r"(b == 0u ? 0x80000000u : b),
               "r"(c == 0u ? 0x80000000u : c), "r"(d == 0u ? 0x80000000u : d) : "memory");
}
__device__ __forceinline__ void st_relaxed2(void* p, uint32_t a, uint32_t b) { asm volatile("st.relaxed.gpu.global.v2.u32 [%0], {%1, %2};" :: "l"(p), "r"(a), "r"(b) : "memory"); }
__device__ __forceinline__ float4 ld_tagged4(const float* p) {
  float4 v; asm volatile("ld.relaxed.gpu.global.v4.f32 {%0, %1, %2, %3}, [%4];" : "=f"(v.x), "=f"(v.y), "=f"(v.z), "=f"(v.w) : "l"(p) : "memory"); return v;
}
__device__ __forceinline__ bool tagged4(const float4& v) {
  return __float_as_uint(v.x) != 0u && __float_as_uint(v.y) != 0u && __float_as_uint(v.z) != 0u && __float_as_uint(v.w) != 0u;
}
__device__ __forceinline__ void hint_arrive(uint32_t* p) { asm volatile("red.relaxed.gpu.global.add.u32 [%0], 1;" :: "l"(p) : "memory"); }
__device__ __forceinline__ void hint_wait(const uint32_t* p, uint32_t target) {
  uint32_t v = 0u;
  #pragma unroll 1
  for (unsigned int i = 0; i < (1u << 22) && v < target; i++) asm volatile("ld.relaxed.gpu.global.u32 %0, [%1];" : "=r"(v) : "l"(p) : "memory");
}
__device__ __forceinline__ void fence_proxy_async_global() { asm volatile("fence.proxy.async.global;" ::: "memory"); }

constexpr int H_SPLIT = 1;
constexpr int PRE_B = 2;
__device__ __forceinline__ void load_parts(float4 (&pa)[4], float4 (&pb)[4], int t2) {
  #pragma unroll
  for (int k = 0; k < 4; k++) { pa[k] = ld_tagged4(g_modpart + k * 2 * T_D + t2 * 8); pb[k] = ld_tagged4(g_modpart + k * 2 * T_D + t2 * 8 + 4); }
}
__device__ __forceinline__ void finish_parts(float4 (&pa)[4], float4 (&pb)[4], int t2, uint32_t tab) {
  #pragma unroll 1
  for (unsigned int spin = 0; spin < (1u << 22); spin++) {
    bool ok = true;
    #pragma unroll
    for (int k = 0; k < 4; k++) ok &= tagged4(pa[k]) & tagged4(pb[k]);
    if (ok) break;
    load_parts(pa, pb, t2);
  }
  #pragma unroll
  for (int k = 1; k < 4; k++) {
    pa[0].x += pa[k].x; pa[0].y += pa[k].y; pa[0].z += pa[k].z; pa[0].w += pa[k].w;
    pb[0].x += pb[k].x; pb[0].y += pb[k].y; pb[0].z += pb[k].z; pb[0].w += pb[k].w;
  }
  uint32_t m0 = pack_bf16(pa[0].x, pa[0].y), m1 = pack_bf16(pa[0].z, pa[0].w), m2 = pack_bf16(pb[0].x, pb[0].y), m3 = pack_bf16(pb[0].z, pb[0].w);
  if (t2 >= 128) { m0 = badd2(m0, 0x3F803F80u); m1 = badd2(m1, 0x3F803F80u); m2 = badd2(m2, 0x3F803F80u); m3 = badd2(m3, 0x3F803F80u); }
  sts_u32x4(tab + t2 * 16, m0, m1, m2, m3);
}
__device__ __forceinline__ void head_phase(uint32_t scr, uint32_t xs, uint32_t b_x, uint32_t b_go, uint32_t b_head, int t2, uint32_t zero, const bf16* __restrict__ x, const bf16* __restrict__ cvec, const bf16* __restrict__ w_mod) {
  const int lane = t2 & 31, w8 = t2 >> 5;
  const int cb = blockIdx.x & 31, ks = blockIdx.x >> 5;
  uint4 w[8], xv[2][4];
  const float cv = __bfloat162float(cvec[ks * 256 + t2]);
  #pragma unroll
  for (int i = 0; i < 8; i++) w[i] = ldg_nc_v4(w_mod + (size_t)(ks * 256 + (t2 >> 3) + 32 * i) * (6 * T_D) + cb * 64 + (t2 & 7) * 8);
  const int row0 = blockIdx.x * 16 + 2 * w8;
  sts_f32(scr + t2 * 4, silu_bf(cv));
  #pragma unroll 1
  for (uint32_t i = 0; i <= zero; i++) named_bar_sync(6, 384);
  TL_MARK2(1, t2 == 0);
  {
    float acc[8];
    #pragma unroll
    for (int j = 0; j < 8; j++) acc[j] = 0.f;
    #pragma unroll
    for (int i = 0; i < 8; i++) {
      fma8(acc, lds_f32(scr + ((t2 >> 3) + 32 * i) * 4), w[i]);
      if (i == 0 && t2 == 0) {
        mbar_expect_tx(b_x + (__float_as_uint(acc[0]) & zero), 32768);
        bulk_load_hint(xs, x + (size_t)blockIdx.x * 16 * T_D, 32768, b_x, policy_evict_first());
      }
    }
    #pragma unroll
    for (int j = 0; j < 4; j++) { const bool up = lane & 16; acc[j] = (up ? acc[4 + j] : acc[j]) + __shfl_xor_sync(0xffffffffu, up ? acc[j] : acc[4 + j], 16); }
    #pragma unroll
    for (int j = 0; j < 2; j++) { const bool up = lane & 8; acc[j] = (up ? acc[2 + j] : acc[j]) + __shfl_xor_sync(0xffffffffu, up ? acc[j] : acc[2 + j], 8); }
    sts_f32x2(scr + 1024 + w8 * 256 + (lane & 7) * 32 + (lane >> 3) * 8, acc[0], acc[1]);
  }
  named_bar_sync(5, 256);
  if (t2 < 64) {
    float sum = 0.f;
    #pragma unroll
    for (int i = 0; i < 8; i++) sum += lds_f32(scr + 1024 + i * 256 + t2 * 4);
    st_tagged(g_modpart + ks * 2 * T_D + cb * 64 + t2, sum);
    TL_MARK2(2, t2 == 0);
  }
  mbar_wait(b_x, 0);
  const bool first_cols = (t2 & 127) < 32;
  float4 pa[4], pb[4];
  if (first_cols) load_parts(pa, pb, t2);
  #pragma unroll
  for (int r = 0; r < 2; r++)
    #pragma unroll
    for (int j = 0; j < 4; j++) xv[r][j] = lds_u32x4(xs + (2 * w8 + r) * 2048 + j * 512 + lane * 16);
  #pragma unroll
  for (int r = 0; r < 2; r++) {
    float v[4][8], sum = 0.f;
    #pragma unroll
    for (int j = 0; j < 4; j++) {
      unpack8(xv[r][j], v[j]);
      sum += ((v[j][0] + v[j][1]) + (v[j][2] + v[j][3])) + ((v[j][4] + v[j][5]) + (v[j][6] + v[j][7]));
    }
    #pragma unroll
    for (int o = 16; o > 0; o >>= 1) sum += __shfl_xor_sync(0xffffffffu, sum, o);
    const float mean = sum * (1.0f / T_D);
    float q = 0.f;
    #pragma unroll
    for (int j = 0; j < 4; j++)
      #pragma unroll
      for (int i = 0; i < 8; i++) { const float d = v[j][i] - mean; q = fmaf(d, d, q); }
    #pragma unroll
    for (int o = 16; o > 0; o >>= 1) q += __shfl_xor_sync(0xffffffffu, q, o);
    const uint32_t mb2 = pack_bf16(mean, mean);
    const float inv = rcp_approx(rbf(sqrt_approx(rbf(rbf(q * (1.0f / T_D)) + 1e-05f))));
    #pragma unroll
    for (int j = 0; j < 4; j++) {
      xv[r][j].x = ln_norm2(xv[r][j].x, mb2, inv); xv[r][j].y = ln_norm2(xv[r][j].y, mb2, inv);
      xv[r][j].z = ln_norm2(xv[r][j].z, mb2, inv); xv[r][j].w = ln_norm2(xv[r][j].w, mb2, inv);
    }
  }
  TL_MARK2(5, t2 == 0);
  if (first_cols) finish_parts(pa, pb, t2, scr + 8192);
  named_bar_sync(5, 256);
  TL_MARK2(7, t2 == 0);
  #pragma unroll
  for (int j = 0; j < 4; j++) {
    if (j == 1) {
      named_bar_sync(5, 256);
      TL_MARK2(18, t2 == 0);
      if (t2 == 0) red_release_add(&g_hcnt[32 * (1 + (blockIdx.x >> 3))], 1u);
      TL_MARK2(11, t2 == 0);
      if (!first_cols) { load_parts(pa, pb, t2); finish_parts(pa, pb, t2, scr + 8192); }
      named_bar_sync(5, 256);
      TL_MARK2(6, t2 == 0);
    }
    const uint4 sa = lds_u32x4(scr + 8192 + (j * 32 + lane) * 16), c1 = lds_u32x4(scr + 8192 + 2048 + (j * 32 + lane) * 16);
    #pragma unroll
    for (int r = 0; r < 2; r++) {
      xv[r][j].x = badd2(bmul2(xv[r][j].x, c1.x), sa.x); xv[r][j].y = badd2(bmul2(xv[r][j].y, c1.y), sa.y);
      xv[r][j].z = badd2(bmul2(xv[r][j].z, c1.z), sa.z); xv[r][j].w = badd2(bmul2(xv[r][j].w, c1.w), sa.w);
      if (j == 0) *reinterpret_cast<uint4*>(g_h + (size_t)(row0 + r) * T_D + lane * 8) = xv[r][0];
    }
  }
  __syncwarp();
  if (lane == 0) mbar_arrive(b_head + (xv[1][3].w & zero));
  mbar_wait(b_go, 0);
  #pragma unroll
  for (int j = 1; j < 4; j++)
    #pragma unroll
    for (int r = 0; r < 2; r++) *reinterpret_cast<uint4*>(g_h + (size_t)(row0 + r) * T_D + j * 256 + lane * 8) = xv[r][j];
  named_bar_arrive(8, 288);
}

__device__ __forceinline__ void mod_rest(uint32_t scr, uint32_t b_go, int t, const bf16* __restrict__ cvec, const bf16* __restrict__ w_mod, const bf16* __restrict__ w_r) {
  const int lane = t & 31;
  #pragma unroll 1
  for (int i = t; i < T_D; i += 64) asm volatile("prefetch.global.L2 [%0];" :: "l"(w_mod + (size_t)i * (6 * T_D) + 2 * T_D + blockIdx.x * 32));
  #pragma unroll 1
  for (int i = t; i < T_D / 2; i += 64) {
    const uint32_t c2 = *reinterpret_cast<const uint32_t*>(cvec + 2 * i);
    sts_u32(scr + i * 4, pack_bf16(silu_bf(bflo(c2)), silu_bf(bfhi(c2))));
  }
  named_bar_sync(11, 64);
  mbar_wait(b_go, 0);
  const bf16* wp = w_mod + (size_t)(2 * (t >> 2)) * (6 * T_D) + 2 * T_D + blockIdx.x * 32 + (t & 3) * 8;
  float acc[8];
  #pragma unroll
  for (int i = 0; i < 8; i++) acc[i] = 0.f;
  #pragma unroll 1
  for (int i = 0; i < 32; i += 2) {
    const uint4 w0 = ldg_nc_v4(wp), w1 = ldg_nc_v4(wp + 6 * T_D), w2 = ldg_nc_v4(wp + 32 * 6 * T_D), w3 = ldg_nc_v4(wp + 33 * 6 * T_D);
    wp += 64 * 6 * T_D;
    const uint32_t s0 = lds_u32(scr + (i * 16 + (t >> 2)) * 4), s1 = lds_u32(scr + (i * 16 + 16 + (t >> 2)) * 4);
    fma8(acc, bflo(s0), w0); fma8(acc, bfhi(s0), w1); fma8(acc, bflo(s1), w2); fma8(acc, bfhi(s1), w3);
  }
  #pragma unroll
  for (int j = 0; j < 4; j++) { const bool up = lane & 16; acc[j] = (up ? acc[4 + j] : acc[j]) + __shfl_xor_sync(0xffffffffu, up ? acc[j] : acc[4 + j], 16); }
  #pragma unroll
  for (int j = 0; j < 2; j++) { const bool up = lane & 8; acc[j] = (up ? acc[2 + j] : acc[j]) + __shfl_xor_sync(0xffffffffu, up ? acc[j] : acc[2 + j], 8); }
  { const bool up = lane & 4; acc[0] = (up ? acc[1] : acc[0]) + __shfl_xor_sync(0xffffffffu, up ? acc[0] : acc[1], 4); }
  if (t >= 32) sts_f32(scr + 2048 + lane * 4, acc[0]);
  named_bar_sync(11, 64);
  if (t < 32) {
    const int kind = blockIdx.x >> 5;
    float v = rbf(acc[0] + lds_f32(scr + 2048 + lane * 4));
    const int col = (blockIdx.x & 31) * 32 + (lane & 3) * 8 + (lane >> 2);
    uint8_t* dst = g_col + (col >> 7) * 1536;
    if (kind == 2) v = rbf(1.0f + v);
    float vw = v * __bfloat162float(w_r[col]);
    if (kind == 2) {
      const int c = col & 127, i = (c & ~15) + ((c >> 1) & 3) * 4 + ((c >> 3) & 1) * 2 + (c & 1);
      reinterpret_cast<bf16*>(dst)[i] = __float2bfloat16_rn(vw);
      reinterpret_cast<bf16*>(dst)[128 + i] = __float2bfloat16_rn(vw - rbf(vw));
    }
    reinterpret_cast<bf16*>(dst + 512 + (kind & 1) * 512 + (kind >> 1) * 256)[col & 127] = __float2bfloat16_rn(v);
    #pragma unroll
    for (int o = 16; o > 0; o >>= 1) vw += __shfl_xor_sync(0xffffffffu, vw, o);
    if (lane == 0 && (kind == 1 || kind == 2)) g_scal[95 - blockIdx.x] = vw;
  }
  #pragma unroll 1
  for (int i = blockIdx.x * 64 + t; i < (int)(sizeof(g_mail) / 16); i += 128 * 64) reinterpret_cast<uint4*>(&g_mail)[i] = make_uint4(0u, 0u, 0u, 0u);
  named_bar_sync(11, 64);
}

#define HPOL_A pol_normal()
#define HPOL_B pol_normal()
#define HMAP_A &tmOl
#define HMAP_B &tmWo
#define MOD_AT b_ob
constexpr int AT_NBLK = T_SEQ / 128;
constexpr float AT_HEAD = 7.0f;
constexpr int WO_LATE = 12;
constexpr int QP_STAG = 3;
constexpr int AT_SPLIT = 28, AT_PIN = 8, PINB = 4;
constexpr int AT_NFULL = 124;
constexpr int AT_PREG = 40, AT_CREG = 232;
constexpr uint32_t AT_SQ = 5 * 32768;
constexpr float AT_C = 0.08838834764831845f * 1.4426950408889634f;
constexpr float AT_RAW_LO = -16.0f, AT_RAW_HI = 24.0f;
constexpr float AT_RAW_SUM = 281474976710656.0f, AT_RAW_MIN = 9.094947017729282e-13f;
constexpr uint32_t AT_SBAR = AT_SQ + 65536 + 256;
constexpr uint32_t AT_SMEM = AT_SQ + 65536 + 3072;

__device__ __forceinline__ uint32_t ring_slot(uint32_t t) { return t - 5u * ((t * 205u) >> 10); }
__device__ __forceinline__ uint32_t qp_pos(uint32_t j, uint32_t it) { return 4u * it + (j & 3u) + ((j & 3u) == 3u ? it : 0u); }
__device__ __forceinline__ uint32_t ring_par(uint32_t t) { return ((t * 205u) >> 10) & 1u; }
__device__ __forceinline__ void softmax_rowmax(const float (&s)[64], float& mx0, float& mx1) {
  float a0 = fmaxf(s[0], s[1]), a1 = fmaxf(s[4], s[5]), a2 = fmaxf(s[8], s[9]), a3 = fmaxf(s[12], s[13]);
  float b0 = fmaxf(s[2], s[3]), b1 = fmaxf(s[6], s[7]), b2 = fmaxf(s[10], s[11]), b3 = fmaxf(s[14], s[15]);
  #pragma unroll
  for (int j = 4; j < 16; j += 4) {
    a0 = fmaxf(a0, fmaxf(s[4 * j + 0], s[4 * j + 1]));  b0 = fmaxf(b0, fmaxf(s[4 * j + 2], s[4 * j + 3]));
    a1 = fmaxf(a1, fmaxf(s[4 * j + 4], s[4 * j + 5]));  b1 = fmaxf(b1, fmaxf(s[4 * j + 6], s[4 * j + 7]));
    a2 = fmaxf(a2, fmaxf(s[4 * j + 8], s[4 * j + 9]));  b2 = fmaxf(b2, fmaxf(s[4 * j + 10], s[4 * j + 11]));
    a3 = fmaxf(a3, fmaxf(s[4 * j + 12], s[4 * j + 13])); b3 = fmaxf(b3, fmaxf(s[4 * j + 14], s[4 * j + 15]));
  }
  mx0 = fmaxf(fmaxf(a0, a1), fmaxf(a2, a3));
  mx1 = fmaxf(fmaxf(b0, b1), fmaxf(b2, b3));
  mx0 = fmaxf(mx0, __shfl_xor_sync(0xffffffffu, mx0, 1));
  mx1 = fmaxf(mx1, __shfl_xor_sync(0xffffffffu, mx1, 1));
  mx0 = fmaxf(mx0, __shfl_xor_sync(0xffffffffu, mx0, 2));
  mx1 = fmaxf(mx1, __shfl_xor_sync(0xffffffffu, mx1, 2));
}
__device__ __forceinline__ void softmax_sub(float (&s)[64], float mc0, float mc1) {
  #pragma unroll
  for (int j = 0; j < 16; j++) { s[4 * j] -= mc0; s[4 * j + 1] -= mc0; s[4 * j + 2] -= mc1; s[4 * j + 3] -= mc1; }
}
template <int LO, int HI>
__device__ __forceinline__ void softmax_exp(float (&s)[64]) {
  #pragma unroll
  for (int i = LO; i < HI; i++) s[i] = ex2_approx(s[i]);
}
__device__ __forceinline__ bool softmax_mode(const float (&s)[64], float& mc0, float& mc1) {
  softmax_rowmax(s, mc0, mc1);
  const bool raw = __all_sync(0xffffffffu, mc0 >= AT_RAW_LO && mc0 <= AT_RAW_HI && mc1 >= AT_RAW_LO && mc1 <= AT_RAW_HI);
  mc0 += AT_HEAD; mc1 += AT_HEAD;
  return raw;
}
__device__ __forceinline__ void rowsum_p(const uint32_t (&p)[32], uint32_t& t0, uint32_t& t1) {
  uint32_t a[16];
  #pragma unroll
  for (int i = 0; i < 8; i++) { a[2 * i] = badd2(p[4 * i], p[4 * i + 2]); a[2 * i + 1] = badd2(p[4 * i + 1], p[4 * i + 3]); }
  #pragma unroll
  for (int i = 0; i < 4; i++) { a[2 * i] = badd2(a[4 * i], a[4 * i + 2]); a[2 * i + 1] = badd2(a[4 * i + 1], a[4 * i + 3]); }
  t0 = badd2(badd2(a[0], a[2]), badd2(a[4], a[6]));
  t1 = badd2(badd2(a[1], a[3]), badd2(a[5], a[7]));
}
__device__ __forceinline__ void add_rowsum(const uint32_t (&p)[32], float& l0, float& l1) {
  uint32_t t0, t1;
  rowsum_p(p, t0, t1);
  l0 += bflo(t0) + bfhi(t0); l1 += bflo(t1) + bfhi(t1);
}
__device__ __forceinline__ void pack_p(uint32_t (&p)[32], const float (&s)[64]) {
  #pragma unroll
  for (int i = 0; i < 32; i++) p[i] = pack_bf16(s[2 * i], s[2 * i + 1]);
}
__device__ __noinline__ void attn_rows_exact(uint32_t sq, uint32_t so, int warp, int lane, const bf16* __restrict__ kh, const bf16* __restrict__ vh) {
  #pragma unroll 1
  for (int r = 16 * warp; r < 16 * warp + 16; r++) {
    const uint32_t ad = (lane >> 4) * 16384 + r * 128 + ((((lane & 15) >> 1) ^ (r & 7)) << 4) + (lane & 1) * 8;
    uint2 qv; asm volatile("ld.shared.v2.u32 {%0, %1}, [%2];" : "=r"(qv.x), "=r"(qv.y) : "r"(sq + ad) : "memory");
    const float q0 = bflo(qv.x), q1 = bfhi(qv.x), q2 = bflo(qv.y), q3 = bfhi(qv.y);
    float m = -INFINITY, l = 0.f, o0 = 0.f, o1 = 0.f, o2 = 0.f, o3 = 0.f;
    #pragma unroll 1
    for (int key = 0; key < T_SEQ; key++) {
      const uint2 kv = *reinterpret_cast<const uint2*>(kh + (size_t)key * T_DH + lane * 4);
      const uint2 vv = *reinterpret_cast<const uint2*>(vh + (size_t)key * T_DH + lane * 4);
      float sc = (q0 * bflo(kv.x) + q1 * bfhi(kv.x)) + (q2 * bflo(kv.y) + q3 * bfhi(kv.y));
      #pragma unroll
      for (int o = 16; o > 0; o >>= 1) sc += __shfl_xor_sync(0xffffffffu, sc, o);
      const float mn = fmaxf(m, sc);
      const float al = (m == mn) ? 1.0f : ex2_approx(m - mn), p = rbf(ex2_approx(sc - mn));
      m = mn;
      l = fmaf(l, al, p);
      o0 = fmaf(o0, al, p * bflo(vv.x)); o1 = fmaf(o1, al, p * bfhi(vv.x));
      o2 = fmaf(o2, al, p * bflo(vv.y)); o3 = fmaf(o3, al, p * bfhi(vv.y));
    }
    const float inv = rcp_approx(l);
    asm volatile("st.shared.v2.u32 [%0], {%1, %2};" :: "r"(so + ad), "r"(pack_bf16(o0 * inv, o1 * inv)), "r"(pack_bf16(o2 * inv, o3 * inv)) : "memory");
  }
}
__device__ __forceinline__ void issue_qk(float (&s)[64], const uint32_t (&q)[32], uint32_t k_lo) {
  wgmma_fence();
  wgmma_m64n128k16_rs<0>(s, q[0], q[1], q[2], q[3], k_lo, 0);
  wgmma_m64n128k16_rs<2>(s, q[4], q[5], q[6], q[7], k_lo, 1);
  wgmma_m64n128k16_rs<4>(s, q[8], q[9], q[10], q[11], k_lo, 1);
  wgmma_m64n128k16_rs<6>(s, q[12], q[13], q[14], q[15], k_lo, 1);
  wgmma_m64n128k16_rs<1024>(s, q[16], q[17], q[18], q[19], k_lo, 1);
  wgmma_m64n128k16_rs<1026>(s, q[20], q[21], q[22], q[23], k_lo, 1);
  wgmma_m64n128k16_rs<1028>(s, q[24], q[25], q[26], q[27], k_lo, 1);
  wgmma_m64n128k16_rs<1030>(s, q[28], q[29], q[30], q[31], k_lo, 1);
  wgmma_commit();
}
__device__ __forceinline__ void issue_pv(float (&o)[64], const uint32_t (&p)[32], uint32_t v_lo, int accumulate) {
  wgmma_fence();
  wgmma_m64n128k16_rs_tb<0>(o, p[0], p[1], p[2], p[3], v_lo, accumulate);
  wgmma_m64n128k16_rs_tb<128>(o, p[4], p[5], p[6], p[7], v_lo, 1);
  wgmma_m64n128k16_rs_tb<256>(o, p[8], p[9], p[10], p[11], v_lo, 1);
  wgmma_m64n128k16_rs_tb<384>(o, p[12], p[13], p[14], p[15], v_lo, 1);
  wgmma_m64n128k16_rs_tb<512>(o, p[16], p[17], p[18], p[19], v_lo, 1);
  wgmma_m64n128k16_rs_tb<640>(o, p[20], p[21], p[22], p[23], v_lo, 1);
  wgmma_m64n128k16_rs_tb<768>(o, p[24], p[25], p[26], p[27], v_lo, 1);
  wgmma_m64n128k16_rs_tb<896>(o, p[28], p[29], p[30], p[31], v_lo, 1);
  wgmma_commit();
}
__device__ __forceinline__ void rescale_o(float (&o)[64], float al0, float al1) {
  #pragma unroll
  for (int j = 0; j < 16; j++) { o[4 * j] *= al0; o[4 * j + 1] *= al0; o[4 * j + 2] *= al1; o[4 * j + 3] *= al1; }
}

__device__ __forceinline__ void stage_o(const float (&o)[64], float i0, float i1, uint32_t dst, int lane) {
  #pragma unroll
  for (int J = 0; J < 16; J += 2)
    stmatrix_x4(dst + (J >> 3) * 16384 + ((((J & 7) + (lane >> 4)) ^ (lane & 7)) << 4),
                pack_bf16(o[4 * J + 0] * i0, o[4 * J + 1] * i0), pack_bf16(o[4 * J + 2] * i1, o[4 * J + 3] * i1),
                pack_bf16(o[4 * J + 4] * i0, o[4 * J + 5] * i0), pack_bf16(o[4 * J + 6] * i1, o[4 * J + 7] * i1));
}
__device__ __forceinline__ bool finish_l(float& l0, float& l1) {
  l0 += __shfl_xor_sync(0xffffffffu, l0, 1); l1 += __shfl_xor_sync(0xffffffffu, l1, 1);
  l0 += __shfl_xor_sync(0xffffffffu, l0, 2); l1 += __shfl_xor_sync(0xffffffffu, l1, 2);
  const bool redo = __any_sync(0xffffffffu, !(l0 <= AT_RAW_SUM && l1 <= AT_RAW_SUM && l0 >= AT_RAW_MIN && l1 >= AT_RAW_MIN));
  l0 = rcp_approx(l0); l1 = rcp_approx(l1);
  return redo;
}
template <int J0>
__device__ __forceinline__ void stage_q(const float (&acc)[128], float c, uint32_t dst, int lane) {
  #pragma unroll
  for (int J = J0; J < J0 + 16; J += 2)
    stmatrix_x4(dst + (J >> 3) * 16384 + ((((J & 7) + (lane >> 4)) ^ (lane & 7)) << 4),
                pack_bf16(acc[4 * J + 0] * c, acc[4 * J + 1] * c), pack_bf16(acc[4 * J + 2] * c, acc[4 * J + 3] * c),
                pack_bf16(acc[4 * J + 4] * c, acc[4 * J + 5] * c), pack_bf16(acc[4 * J + 6] * c, acc[4 * J + 7] * c));
}
__device__ __forceinline__ void store_o(const CUtensorMap* tmO, uint32_t src, int head, int row) {
  tma_store_2d(tmO, src, head * T_DH, row);
  tma_store_2d(tmO, src + 16384, head * T_DH + 64, row);
  bulk_commit();
}
__device__ __forceinline__ void mma_bf16(float (&d)[4], uint32_t a0, uint32_t a1, uint32_t a2, uint32_t a3, uint32_t b0, uint32_t b1) {
  asm volatile("mma.sync.aligned.m16n8k16.row.col.f32.bf16.bf16.f32 {%0, %1, %2, %3}, {%4, %5, %6, %7}, {%8, %9}, {%0, %1, %2, %3};"
               : "+f"(d[0]), "+f"(d[1]), "+f"(d[2]), "+f"(d[3]) : "r"(a0), "r"(a1), "r"(a2), "r"(a3), "r"(b0), "r"(b1));
}
struct GemvSel { uint32_t lo0, hi0, lo1, hi1; };
__device__ __forceinline__ GemvSel gemv_sel(int lane) {
  const uint32_t lo = (lane & 8) ? 0x1044u : 0x4410u, hi = (lane & 8) ? 0x3244u : 0x4432u;
  GemvSel s; s.lo0 = (lane & 16) ? 0x4444u : lo; s.hi0 = (lane & 16) ? 0x4444u : hi; s.lo1 = (lane & 16) ? lo : 0x4444u; s.hi1 = (lane & 16) ? hi : 0x4444u;
  return s;
}
#define GEMV_B0(j, h, s) __byte_perm((j) < 2 ? (h).x : (h).y, 0u, ((j) & 1) ? (s).hi0 : (s).lo0)
#define GEMV_B1(j, h, s) __byte_perm((j) < 2 ? (h).x : (h).y, 0u, ((j) & 1) ? (s).hi1 : (s).lo1)
__device__ __forceinline__ float4 gemv_out(const float (&d)[4], int lane) {
  const bool tk = lane & 1;
  const float r0 = __shfl_xor_sync(0xffffffffu, tk ? d[0] : d[1], 1), r1 = __shfl_xor_sync(0xffffffffu, tk ? d[2] : d[3], 1);
  return tk ? make_float4(r0, d[1], r1, d[3]) : make_float4(d[0], r0, d[2], r1);
}
#define OG_NG 8
#define OG_PRE 10
#define OG_JOBS 7
#define OG_GRP ((64 - OG_PRE) / OG_NG)
constexpr int OG_ST = 5, OG_NKB = T_DQKV / 64 - OG_PRE, OG_MOE = T_F / 32;
__device__ __forceinline__ int pre_kb(int i) { return (i >> 1) * 4 + (i & 1); }
__device__ __forceinline__ int own_kb(int i) { return i < (OG_PRE & ~1) ? pre_kb(i) + 2 : i + OG_PRE; }
constexpr int OG_POS = 8;
constexpr uint32_t OG_STAGE = 32768;
constexpr uint32_t OG_SWD = AT_SQ;
constexpr uint32_t OG_SCOL = AT_SBAR + 512;
constexpr uint32_t OG_SMISC = AT_SBAR + 2048;
#define OG_PAT (OG_NKB - 5)
constexpr int OG_XPOS = OG_POS + OG_NKB + 1;
constexpr uint32_t OG_XSLOT = (OG_XPOS % OG_ST) * OG_STAGE;
constexpr uint32_t OG_OSLOT = ((OG_XPOS + 1) % OG_ST) * OG_STAGE;
constexpr uint32_t OG_SH2 = ((OG_XPOS + 2) % OG_ST) * OG_STAGE;
constexpr uint32_t OG_SRED = ((OG_XPOS + 3) % OG_ST) * OG_STAGE;
constexpr uint32_t OG_SSTAT = OG_SRED + 16384;
constexpr uint32_t OG_SGU = OG_SRED + 8192;
constexpr uint32_t OG_SFIN = OG_SGU + 256;
#define OGM 2
#define OG_MT(b) (((b) >> OGM) & 15)
#define OG_NT(b) (((b) & ((1 << OGM) - 1)) + (((b) >> (4 + OGM)) << OGM))
#define TAIL_SETUP \
  const uint32_t bar_full = sbase + AT_SBAR, bar_empty = bar_full + 40; \
  const uint32_t bar_wd = bar_full + 168, bar_col = bar_full + 176, bar_out = bar_full + 184, bar_end = bar_full + 192; \
  const uint32_t bar_key = bar_full + 200, bar_h2 = bar_full + 208, bar_sel = bar_full + 216; \
  const int mt = OG_MT(blockIdx.x), nt = OG_NT(blockIdx.x); \
  const int m0 = mt * 128, n0 = nt * 128; \
  const bool has_moe = (int)blockIdx.x < OG_MOE; \
  (void)bar_empty; (void)bar_wd; (void)bar_col; (void)bar_out; (void)bar_end; (void)bar_key; (void)bar_h2; (void)bar_sel; (void)m0; (void)n0; (void)has_moe;

__device__ __forceinline__ void tail_producer(uint32_t sbase, uint32_t ph, uint32_t obpar, uint64_t pol, const CUtensorMap* tmA, const CUtensorMap* tmB,
                                              const CUtensorMap* tmX, const bf16* __restrict__ w_down) {
  TAIL_SETUP
  const uint32_t b_q0 = bar_full + 80, b_ob = bar_full + 96, b_acq = bar_full + 264;
  uint32_t stage = OG_POS % OG_ST;
  if (has_moe) mbar_expect_tx(bar_wd, 65536);
  mbar_expect_tx(bar_col, 1536);
  int wdk = 6;
  #pragma unroll 1
  for (int kb = 0; kb <= OG_NKB + 1; kb++) {
    const uint32_t fb = bar_full + 8 * stage, sa = sbase + stage * OG_STAGE, sb = sa + 16384;
    mbar_wait(bar_empty + 8 * stage, ph);
    mbar_expect_tx(fb, OG_STAGE);
    if (kb == OG_PAT) {
      mbar_wait(b_acq + 8, 0);
      fence_proxy_async_global();
      bulk_load_hint(sa, g_pre + (mt * 8 + nt) * 2048, 32768, fb, pol);
    } else {
      const bool xt = kb > OG_NKB;
      const int k0 = own_kb(kb - (kb > OG_PAT)) * 64;
      if (!xt) tma_load_2d_hint(sb + 8192, tmB, n0 + 64, k0, fb, pol);
      tma_load_2d_hint(sb, xt ? tmX : tmB, xt ? n0 + 64 : n0, xt ? m0 : k0, fb, pol);
      if (kb == 0 || kb == 32 - OG_PRE) { mbar_wait(b_acq, kb != 0); fence_proxy_async_global(); }
      tma_load_2d_hint(sa, xt ? tmX : tmA, xt ? n0 : k0, m0, fb, pol);
    }
    if (kb == 32 - OG_PRE) bulk_load_hint(sbase + OG_SCOL, g_col + nt * 1536, 1536, bar_col, pol);
    if (kb == 6) { mbar_wait(b_q0, obpar); mbar_wait(b_ob, obpar); }
    if (has_moe && kb == wdk && kb < 6 + 8 * OG_GRP) {
      const int i = (kb - 6) / OG_GRP;
      bulk_load_hint(sbase + OG_SWD + i * 8224, (const uint8_t*)w_down + (size_t)blockIdx.x * 65536 + i * 8192, 8192, bar_wd, pol);
      wdk += OG_GRP;
    }
    if (++stage == OG_ST) { stage = 0; ph ^= 1; }
  }
}

__device__ __forceinline__ uint32_t bfma2(uint32_t a, uint32_t b, uint32_t c) { uint32_t r; asm("fma.rn.bf16x2 %0, %1, %2, %3;" : "=r"(r) : "r"(a), "r"(b), "r"(c)); return r; }
__device__ __forceinline__ uint32_t out2(uint32_t x1, uint32_t mb2, uint32_t ih, uint32_t il, uint32_t c1, uint32_t sb, uint32_t gb) {
  const uint32_t d = bsub2(x1, mb2);
  const uint32_t h2 = badd2(bmul2(bfma2(d, ih, bmul2(d, il)), c1), sb);
  return badd2(x1, bmul2(gb, bfma2(h2, 0u, h2)));
}
__device__ __forceinline__ void tail_exchange(uint32_t sbase, const CUtensorMap* tmOut, bf16* __restrict__ out) {
    TAIL_SETUP
    const int lane = threadIdx.x & 31;
    if (threadIdx.x >= 96) {
      mbar_wait(bar_full + 264, 0); mbar_wait(bar_full + 264, 1);
      float a = g_scal[lane], b = g_scal[32 + lane];
      #pragma unroll
      for (int o = 16; o > 0; o >>= 1) { a += __shfl_xor_sync(0xffffffffu, a, o); b += __shfl_xor_sync(0xffffffffu, b, o); }
      if (lane == 0) { sts_f32x2(sbase + OG_SMISC, a, b); mbar_arrive(bar_col); }
    }
    mbar_wait(bar_end, 0);
    TL_MARK2(22, lane == 0);
    if (threadIdx.x < 32) {
      uint32_t k1 = 0u, k2 = 0u;
      #pragma unroll 1
      for (unsigned int spin = 0; spin < (1u << 22) && k1 == 0u; spin++) asm volatile("ld.relaxed.gpu.global.u32 %0, [%1];" : "=r"(k1) : "l"(g_key + lane) : "memory");
      __syncwarp();
      TL_MARK2(28, lane == 0);
      warp_top2(k1, k2);
      if (lane == 0) {
        const uint32_t r1 = 0xffffu - (k1 & 0xffffu), r2 = 0xffffu - (k2 & 0xffffu);
        sts_u32x4(sbase + OG_SMISC + 64, r1, r2, (r1 >> 7) * 2, (r2 >> 7) * 2 + ((r1 >> 7) == (r2 >> 7)));
        mbar_arrive(bar_sel);
      }
    } else if (threadIdx.x < 96) {
          mbar_wait(bar_key, 0);
          const uint4 kk = lds_u32x4(sbase + OG_SSTAT + 1024 + lane * 16);
          uint32_t k1 = max(kk.x, kk.y), k2 = min(kk.x, kk.y);
          k2 = max(max(k2, min(kk.z, kk.w)), min(k1, max(kk.z, kk.w))); k1 = max(k1, max(kk.z, kk.w));
          warp_top2(k1, k2);
          if (threadIdx.x < 64) {
            if (lane == 0 && nt == (mt & 7)) st_relaxed2(g_key + mt * 2, k1, k2);
            TL_MARK2(27, lane == 0);
          } else {
            const uint32_t r = (~((lane & 16) ? k2 : k1)) & 127u, ch = lane & 15;
            const uint2 st = lds_u32x2(sbase + OG_SSTAT + r * 8);
            const uint4 xc = lds_u32x4(sbase + OG_XSLOT + (ch >> 3) * 16384 + r * 128 + (((ch ^ r) & 7) << 4));
            const uint4 c1 = lds_u32x4(sbase + OG_SCOL + 768 + ch * 16), sh = lds_u32x4(sbase + OG_SCOL + 1024 + ch * 16);
            const float inr = __uint_as_float(st.y);
            float* dst = reinterpret_cast<float*>(g_cand + (mt * 2 + (lane >> 4)) * 256 + nt * 16 + ch);
            st_tagged4(dst + 512, __uint_as_float(ln_mod2(xc.x, st.x, inr, c1.x, sh.x)), __uint_as_float(ln_mod2(xc.y, st.x, inr, c1.y, sh.y)),
                       __uint_as_float(ln_mod2(xc.z, st.x, inr, c1.z, sh.z)), __uint_as_float(ln_mod2(xc.w, st.x, inr, c1.w, sh.w)));
            st_tagged4(dst, __uint_as_float(xc.x), __uint_as_float(xc.y), __uint_as_float(xc.z), __uint_as_float(xc.w));
          }
    }
    mbar_wait(bar_sel, 0);
    const int sel0 = (int)lds_u32(sbase + OG_SMISC + 64), sel1 = (int)lds_u32(sbase + OG_SMISC + 68);
    mbar_wait(bar_out, 0);
    if ((sel0 >> 7) == mt || (sel1 >> 7) == mt) {
      #pragma unroll 2
      for (int i = 0; i < 16; i++) {
        const int r = i * 8 + (threadIdx.x >> 4), ch = threadIdx.x & 15;
        if (m0 + r != sel0 && m0 + r != sel1)
          *reinterpret_cast<uint4*>(out + (size_t)(m0 + r) * T_D + n0 + ch * 8) =
              lds_u32x4(sbase + OG_OSLOT + (ch >> 3) * 16384 + r * 128 + (((ch & 7) ^ (r & 7)) << 4));
      }
    } else if (threadIdx.x == 0) {
      tma_store_2d(tmOut, sbase + OG_OSLOT, n0, m0);
      tma_store_2d(tmOut, sbase + OG_OSLOT + 16384, n0 + 64, m0);
      bulk_commit();
    }
    if (blockIdx.x == 0 && threadIdx.x < 34) *reinterpret_cast<uint4*>(g_hcnt + 32 * (threadIdx.x >> 1) + 4 * (threadIdx.x & 1)) = make_uint4(0u, 0u, 0u, 0u);
    if (threadIdx.x < 64) g_modpart[blockIdx.x * 64 + threadIdx.x] = 0.f;
    {
      const int tk = blockIdx.x >> 6, c0 = (blockIdx.x & 63) * 16;
      const uint32_t gb2 = *reinterpret_cast<const uint32_t*>(g_col + (c0 >> 7) * 1536 + 512 + 768 + ((c0 & 127) + (threadIdx.x & 14)) * 2);
      const uint32_t* xp = reinterpret_cast<const uint32_t*>(g_cand + lds_u32(sbase + OG_SMISC + 72 + tk * 4) * 256) + ((c0 + (threadIdx.x & 14)) >> 1);
      uint32_t x2 = 0u;
      #pragma unroll 1
      for (unsigned int spin = 0; spin < (1u << 20) && x2 == 0u; spin++) asm volatile("ld.relaxed.gpu.global.u32 %0, [%1];" : "=r"(x2) : "l"(xp) : "memory");
      const float* src = g_ypart + (size_t)((threadIdx.x >> 2) * 2 + tk) * T_D + c0 + (threadIdx.x & 3) * 4;
      const bool four = threadIdx.x < (OG_MOE - 96) * 4;
      mbar_wait(bar_h2, 0);
      if (threadIdx.x == 0) hint_wait(CNT_Y, (uint32_t)OG_MOE);
      named_bar_sync(10, 128);
      float4 p0, p1, p2, p3;
      #pragma unroll 1
      for (unsigned int spin = 0; spin < (1u << 20); spin++) {
        p0 = ld_tagged4(src); p1 = ld_tagged4(src + 64 * T_D); p2 = ld_tagged4(src + 128 * T_D); p3 = ld_tagged4(four ? src + 192 * T_D : src);
        if (tagged4(p0) && tagged4(p1) && tagged4(p2) && tagged4(p3)) break;
      }
      if (four) { p2.x += p3.x; p2.y += p3.y; p2.z += p3.z; p2.w += p3.w; }
      p0.x = (p0.x + p1.x) + p2.x; p0.y = (p0.y + p1.y) + p2.y; p0.z = (p0.z + p1.z) + p2.z; p0.w = (p0.w + p1.w) + p2.w;
      #pragma unroll
      for (int o = 4; o <= 16; o <<= 1) {
        p0.x += __shfl_xor_sync(0xffffffffu, p0.x, o); p0.y += __shfl_xor_sync(0xffffffffu, p0.y, o);
        p0.z += __shfl_xor_sync(0xffffffffu, p0.z, o); p0.w += __shfl_xor_sync(0xffffffffu, p0.w, o);
      }
      if (lane < 4) sts_f32x4(sbase + OG_SFIN + (threadIdx.x >> 5) * 64 + lane * 16, p0.x, p0.y, p0.z, p0.w);
      named_bar_sync(10, 128);
      TL_MARK2(21, threadIdx.x == 0);
      if (threadIdx.x < 16) {
        const uint32_t ya = sbase + OG_SFIN + threadIdx.x * 4, rp = sbase + OG_SMISC + 192 + tk * 16;
        float y = (lds_f32(ya) + lds_f32(ya + 64)) + (lds_f32(ya + 128) + lds_f32(ya + 192));
        const float r = rbf((lds_f32(rp) + lds_f32(rp + 4)) + (lds_f32(rp + 8) + lds_f32(rp + 12)));
        const float rs = rbf(sigmoid_f(r));
        const uint32_t h2p = lds_u32(sbase + OG_SH2 + tk * 2048 + (c0 + (threadIdx.x & 14)) * 2);
        const float fh = (lane & 1) ? bfhi(h2p) : bflo(h2p);
        y = rbf(y);
        y = rbf(y * rs);
        const float upd = rbf(rbf(fh * 0.0f) + y);
        out[(size_t)(tk ? sel1 : sel0) * T_D + c0 + threadIdx.x] =
            __float2bfloat16_rn(((lane & 1) ? bfhi(x2) : bflo(x2)) + rbf(((lane & 1) ? bfhi(gb2) : bflo(gb2)) * rbf(fh + upd)));
      }
      if (threadIdx.x == 0) bulk_wait_read<0>();
    }
    TL_END(4, threadIdx.x == 0);
}

__device__ __forceinline__ void tail_consumer(uint32_t sbase, int cwg, const bf16* __restrict__ w_r, const bf16* __restrict__ w_gate, const bf16* __restrict__ w_up) {
    TAIL_SETUP
    const int tid = threadIdx.x & 127, t2 = threadIdx.x - 128;
    const int warp = tid >> 5, lane = tid & 31, w8 = t2 >> 5;
    const uint32_t dbase = (sbase & 0x3FFFFu) >> 4;
    const uint32_t a_base = dbase + ((cwg * 8192) >> 4) + (1u << 16);
    const uint32_t b_base = dbase + (16384 >> 4) + (512u << 16);
    TL_MARK2(25, threadIdx.x == 128);
    const uint64_t pol = policy_evict_first();
    const bf16* pw = ((lane & 16) ? w_up : w_gate) + (size_t)(w8 * 128 + (lane & 3) * 4) * T_F + (has_moe ? blockIdx.x : 0) * 32 + ((lane >> 2) & 3) * 8;
    uint4 wv[32];
    float acc[64];
    {
      uint32_t stage = OG_POS % OG_ST, phase = (OG_POS / OG_ST) & 1, prev = 0;
      #pragma unroll
      for (int g = 0; g <= OG_NG; g++) {
        if (g == OG_NG) {
          mbar_wait(bar_full + 8 * stage, phase);
          wgmma_wait<0>();
          fence_regs(acc);
          if (tid == 0) mbar_arrive(bar_empty + 8 * prev);
          #pragma unroll
          for (int i = 0; i < 8; i++) {
            const uint4 pre = lds_u32x4(sbase + stage * OG_STAGE + w8 * 2048 + (i >> 2) * 16384 + (i & 3) * 512 + lane * 16);
            acc[8 * i] += bflo(pre.x); acc[8 * i + 1] += bfhi(pre.x); acc[8 * i + 2] += bflo(pre.y); acc[8 * i + 3] += bfhi(pre.y);
            acc[8 * i + 4] += bflo(pre.z); acc[8 * i + 5] += bfhi(pre.z); acc[8 * i + 6] += bflo(pre.w); acc[8 * i + 7] += bfhi(pre.w);
          }
          named_bar_sync(3 + cwg, 128);
          prev = stage;
          if (++stage == OG_ST) { stage = 0; phase ^= 1; }
        }
        #pragma unroll
        for (int j = 0; j < 4 && g < OG_NG; j++) wv[4 * g + j] = ldg_stream_v4(pw + (size_t)(16 * g + j) * T_F, pol);
        #pragma unroll 1
        for (int kb = g == OG_NG ? OG_PAT : g * OG_GRP; kb < (g == OG_NG ? OG_NKB : g == OG_NG - 1 ? OG_PAT : (g + 1) * OG_GRP); kb++) {
          mbar_wait(bar_full + 8 * stage, phase);
          const uint32_t a_lo = a_base + stage * (OG_STAGE >> 4), b_lo = b_base + stage * (OG_STAGE >> 4);
          wgmma_fence();
          wgmma_m64n128k16_ss_tb<0, 0>(acc, a_lo, b_lo, kb != 0);
          wgmma_m64n128k16_ss_tb<2, 128>(acc, a_lo, b_lo, 1);
          wgmma_m64n128k16_ss_tb<4, 256>(acc, a_lo, b_lo, 1);
          wgmma_m64n128k16_ss_tb<6, 384>(acc, a_lo, b_lo, 1);
          wgmma_commit();
          wgmma_wait<1>();
          if (kb > 0 && tid == 0) mbar_arrive(bar_empty + 8 * prev);
          prev = stage;
          if (++stage == OG_ST) { stage = 0; phase ^= 1; }
        }
      }
    }
    mbar_wait(bar_col, 0);
    mbar_wait(bar_full + 8 * (OG_XPOS % OG_ST), (OG_XPOS / OG_ST) & 1);
    wgmma_wait<0>();
    fence_regs(acc);
    if (tid == 0) mbar_arrive(bar_end);
    TL_MARK2(9, lane == 0);
    const int q2 = 2 * (lane & 3);
    const uint32_t frag = (64 * cwg + 16 * warp + (lane & 7) + 8 * ((lane >> 3) & 1)) * 128;
    const int fsw = lane & 7, fhi = lane >> 4;
    {
      float dl[4] = {0.f, 0.f, 0.f, 0.f}, da[4] = {0.f, 0.f, 0.f, 0.f}, db[4] = {0.f, 0.f, 0.f, 0.f};
      const uint32_t tb = sbase + OG_SCOL + (lane & 8) * 32 + (lane & 3) * 8, g = lane >> 2;
      const uint32_t msk = (g == 1 || g == 2) ? 0xffffffffu : 0u, one = g == 0 ? 0x3F803F80u : 0u;
      #pragma unroll
      for (int J = 0; J < 16; J += 2) {
        const uint32_t ad = sbase + OG_XSLOT + (J >> 3) * 16384 + frag + ((((J & 7) + fhi) ^ fsw) << 4);
        uint32_t xr[4];
        ldmatrix_x4(ad, xr[0], xr[1], xr[2], xr[3]);
        const uint2 cw = lds_u32x2(tb + J * 16);
        #pragma unroll
        for (int h = 0; h < 2; h++) {
          const uint32_t ga = lds_u32(sbase + OG_SCOL + 512 + (8 * (J + h) + q2) * 2);
          xr[2 * h] = badd2(xr[2 * h], bmul2(ga, pack_bf16(acc[4 * (J + h)], acc[4 * (J + h) + 1])));
          xr[2 * h + 1] = badd2(xr[2 * h + 1], bmul2(ga, pack_bf16(acc[4 * (J + h) + 2], acc[4 * (J + h) + 3])));
        }
        stmatrix_x4(ad, xr[0], xr[1], xr[2], xr[3]);
        mma_bf16(dl, xr[0], xr[1], xr[2], xr[3], (cw.x & msk) | one, (cw.y & msk) | one);
        mma_bf16(da, xr[0], xr[1], xr[2], xr[3], xr[0], xr[2]);
        mma_bf16(db, xr[0], xr[1], xr[2], xr[3], xr[1], xr[3]);
      }
      {
        const int dsrc = (lane & ~3) + (g >> 1);
        const float qa = __shfl_sync(0xffffffffu, (g & 1) ? da[1] : da[0], dsrc), qb = __shfl_sync(0xffffffffu, (g & 1) ? db[3] : db[2], dsrc);
        const float e0 = __shfl_xor_sync(0xffffffffu, (lane & 1) ? dl[0] : dl[2], 1), e1 = __shfl_xor_sync(0xffffffffu, dl[3], 1);
        if ((lane & 3) < 2) {
          const bool hi = lane & 1;
          st_tagged4(reinterpret_cast<float*>(g_part1 + ((mt * 8 + w8) * 8 + nt) * 16 + g + (hi ? 8 : 0)),
                     hi ? e0 : dl[0], hi ? qb : qa, hi ? e1 + dl[2] : dl[1] + e0, 1.0f);
        }
      }
    }
    TL_MARK2(10, lane == 0);
    const uint4 wrv = ldg_nc_v4(w_r + tid * 8);
    uint4 wd[16];
    if (has_moe) mbar_wait(bar_wd, 0);
    #pragma unroll
    for (int i = 0; i < 16; i++) wd[i] = lds_u32x4(sbase + OG_SWD + (((i >> 2) & 1) * 4 + (lane & 3)) * 8224 + (i & 3) * 2048 + w8 * 256 + (i >> 3) * 128 + (lane >> 2) * 16);
    {
      const float* src = reinterpret_cast<const float*>(g_part1 + ((mt * 8 + w8) * 8 + (lane & 1) * 4) * 16 + (lane >> 1));
      float4 v, v1, v2, v3;
      #pragma unroll 1
      for (unsigned int spin = 0; spin < (1u << 22); spin++) {
        v = ld_tagged4(src); v1 = ld_tagged4(src + 64); v2 = ld_tagged4(src + 128); v3 = ld_tagged4(src + 192);
        if (tagged4(v) & tagged4(v1) & tagged4(v2) & tagged4(v3)) break;
        __nanosleep(100);
      }
      __syncwarp();
      TL_MARK2(26, lane == 0);
      v.x = (v.x + v1.x) + (v2.x + v3.x); v.y = (v.y + v1.y) + (v2.y + v3.y); v.z = (v.z + v1.z) + (v2.z + v3.z);
      v.x += __shfl_xor_sync(0xffffffffu, v.x, 1); v.y += __shfl_xor_sync(0xffffffffu, v.y, 1); v.z += __shfl_xor_sync(0xffffffffu, v.z, 1);
      const float mean = v.x * (1.0f / T_D);
      const float var = fmaxf(fmaf(-mean, mean, v.y * (1.0f / T_D)), 0.f);
      const uint32_t mb2 = pack_bf16(mean, mean);
      const float inv = rcp_approx(rbf(sqrt_approx(rbf(rbf(var) + 1e-05f))));
      {
        const float2 sc = lds_f32x2(sbase + OG_SMISC);
        const uint32_t key = rank_key(rbf(fmaf(fmaf(-bflo(mb2), sc.x, v.z), inv, sc.y)), m0 + 16 * w8 + (lane >> 1));
        mbar_wait(bar_end, 0);
        if (lane & 1) sts_u32(sbase + OG_SSTAT + 1024 + (16 * w8 + (lane >> 1)) * 4, key);
        else sts_u32x2(sbase + OG_SSTAT + (16 * w8 + (lane >> 1)) * 8, mb2, __float_as_uint(inv));
        __syncwarp();
        if (lane == 0) mbar_arrive(bar_key);
      }
      const uint32_t ih = pack_bf16(inv, inv), il = pack_bf16(inv - bflo(ih), inv - bflo(ih));
      const uint32_t mba = __shfl_sync(0xffffffffu, mb2, 2 * (lane >> 2)), mbb = __shfl_sync(0xffffffffu, mb2, 2 * (lane >> 2) + 16);
      const uint32_t iha = __shfl_sync(0xffffffffu, ih, 2 * (lane >> 2)), ihb = __shfl_sync(0xffffffffu, ih, 2 * (lane >> 2) + 16);
      const uint32_t ila = __shfl_sync(0xffffffffu, il, 2 * (lane >> 2)), ilb = __shfl_sync(0xffffffffu, il, 2 * (lane >> 2) + 16);
      #pragma unroll 2
      for (int J = 0; J < 16; J += 2) {
        const uint32_t off = (J >> 3) * 16384 + frag + ((((J & 7) + fhi) ^ fsw) << 4);
        uint32_t xr[4];
        ldmatrix_x4(sbase + OG_XSLOT + off, xr[0], xr[1], xr[2], xr[3]);
        #pragma unroll
        for (int h = 0; h < 2; h++) {
          const uint32_t ca = sbase + OG_SCOL + 512 + (8 * (J + h) + q2) * 2;
          const uint32_t c1 = lds_u32(ca + 256), sh = lds_u32(ca + 512), gb = lds_u32(ca + 768);
          xr[2 * h] = out2(xr[2 * h], mba, iha, ila, c1, sh, gb);
          xr[2 * h + 1] = out2(xr[2 * h + 1], mbb, ihb, ilb, c1, sh, gb);
        }
        stmatrix_x4(sbase + OG_OSLOT + off, xr[0], xr[1], xr[2], xr[3]);
      }
      fence_proxy_async();
      __syncwarp();
      if (lane == 0) mbar_arrive(bar_out);
      TL_MARK2(24, lane == 0);
    }
    {
      mbar_wait(bar_sel, 0);
      TL_MARK2(12, lane == 0);
      const float* src = reinterpret_cast<const float*>(g_cand + lds_u32(sbase + OG_SMISC + 72 + cwg * 4) * 256 + 128 + tid);
      float4 hf;
      #pragma unroll 1
      for (unsigned int spin = 0; spin < (1u << 20); spin++) { hf = ld_tagged4(src); if (tagged4(hf)) break; }
      const uint4 hv = make_uint4(__float_as_uint(hf.x), __float_as_uint(hf.y), __float_as_uint(hf.z), __float_as_uint(hf.w));
      sts_u32x4(sbase + OG_SH2 + t2 * 16, hv.x, hv.y, hv.z, hv.w);
      float v[8], wr[8];
      unpack8(hv, v); unpack8(wrv, wr);
      float r = 0.f;
      #pragma unroll
      for (int i = 0; i < 8; i++) r = fmaf(v[i], wr[i], r);
      #pragma unroll
      for (int o = 16; o > 0; o >>= 1) r += __shfl_xor_sync(0xffffffffu, r, o);
      if (lane == 0) sts_f32(sbase + OG_SMISC + 192 + w8 * 4, r);
    }
    named_bar_sync(9, 256);
    if (t2 == 0) mbar_arrive(bar_h2);
    TL_MARK2(13, lane == 0);
    if (has_moe) {
      const GemvSel sel = gemv_sel(lane);
      {
        float d[4][4];
        #pragma unroll
        for (int c = 0; c < 4; c++) { d[c][0] = 0.f; d[c][1] = 0.f; d[c][2] = 0.f; d[c][3] = 0.f; }
        #pragma unroll
        for (int st = 0; st < 8; st++) {
          const uint2 hb = lds_u32x2(sbase + OG_SH2 + ((lane >> 2) & 1) * 2048 + (w8 * 128 + st * 16 + (lane & 3) * 4) * 2);
          #pragma unroll
          for (int j = 0; j < 4; j++) mma_bf16(d[j], wv[4 * st + j].x, wv[4 * st + j].y, wv[4 * st + j].z, wv[4 * st + j].w, GEMV_B0(j, hb, sel), GEMV_B1(j, hb, sel));
        }
        #pragma unroll
        for (int e = 0; e < 4; e++) d[0][e] = (d[0][e] + d[1][e]) + (d[2][e] + d[3][e]);
        const float4 r = gemv_out(d[0], lane);
        sts_f32x4(sbase + OG_SRED + w8 * 512 + (((lane >> 4) * 2 + (lane & 1)) * 32 + ((lane >> 2) & 3) * 8 + (lane & 2) * 2) * 4, r.x, r.y, r.z, r.w);
      }
      named_bar_sync(9, 256);
      if (t2 < 64) {
        float gp[8], up[8];
        #pragma unroll
        for (int w = 0; w < 8; w++) { gp[w] = lds_f32(sbase + OG_SRED + w * 512 + t2 * 4); up[w] = lds_f32(sbase + OG_SRED + w * 512 + 256 + t2 * 4); }
        const float gs = ((gp[0] + gp[1]) + (gp[2] + gp[3])) + ((gp[4] + gp[5]) + (gp[6] + gp[7]));
        const float us = ((up[0] + up[1]) + (up[2] + up[3])) + ((up[4] + up[5]) + (up[6] + up[7]));
        asm volatile("st.shared.u16 [%0], %1;" :: "r"(sbase + OG_SGU + t2 * 2), "h"((uint16_t)pack_bf16(silu_bf(rbf(gs)) * rbf(us), 0.f)) : "memory");
      }
      named_bar_sync(9, 256);
      TL_MARK2(20, threadIdx.x == 128);
      float d[4][4];
      #pragma unroll
      for (int c = 0; c < 4; c++) { d[c][0] = 0.f; d[c][1] = 0.f; d[c][2] = 0.f; d[c][3] = 0.f; }
      #pragma unroll
      for (int st = 0; st < 2; st++) {
        const uint2 g = lds_u32x2(sbase + OG_SGU + ((lane >> 2) & 1) * 64 + st * 32 + (lane & 3) * 8);
        #pragma unroll
        for (int j = 0; j < 4; j++) {
          const uint32_t b0 = GEMV_B0(j, g, sel), b1 = GEMV_B1(j, g, sel);
          mma_bf16(d[j & 1], wd[4 * st + j].x, wd[4 * st + j].y, wd[4 * st + j].z, wd[4 * st + j].w, b0, b1);
          mma_bf16(d[2 + (j & 1)], wd[8 + 4 * st + j].x, wd[8 + 4 * st + j].y, wd[8 + 4 * st + j].z, wd[8 + 4 * st + j].w, b0, b1);
        }
      }
      #pragma unroll
      for (int e = 0; e < 4; e++) { d[0][e] += d[1][e]; d[2][e] += d[3][e]; }
      const float4 y0 = gemv_out(d[0], lane), y1 = gemv_out(d[2], lane);
      float* yp = g_ypart + (size_t)(blockIdx.x * 2 + (lane & 1)) * T_D + w8 * 128 + (lane >> 2) * 8 + (lane & 2) * 2;
      st_tagged4(yp, y0.x, y0.y, y0.z, y0.w);
      st_tagged4(yp + 64, y1.x, y1.y, y1.z, y1.w);
      named_bar_sync(9, 256);
      if (t2 == 0) hint_arrive(CNT_Y);
    }
    TL_MARK2(14, threadIdx.x == 128);
    TL_CLK(4, 1, threadIdx.x == 128);
}

#define OG_JOBS2 (16 - OG_JOBS)
__device__ __forceinline__ int help_njobs() { return blockIdx.x < 128 ? OG_JOBS : OG_JOBS2; }
__device__ __forceinline__ int help_job(int i) {
  const int h = (int)blockIdx.x - AT_NFULL;
  return i == 0 ? h : 7 + i + (h < 4 ? h * (OG_JOBS - 1) : 4 * (OG_JOBS - 1) + (h - 4) * (15 - OG_JOBS));
}
__device__ __noinline__ void store_warp(uint32_t sbase, const CUtensorMap* tmO, int item0, int n_items) {
  if (elect_one()) {
    const uint32_t bars = sbase + AT_SBAR, b_q0 = bars + 80, b_ob = bars + 96, b_ordy = bars + 104, b_acq = bars + 264;
    const unsigned int* cnt = &g_hcnt[32 * (1 + OG_MT(blockIdx.x)) + 2];
    #pragma unroll 1
    for (int q = 0; q < 4 * n_items; q++) {
      const int item = item0 + (q >> 2) * 128, h = (q >> 1) & 1, w = q & 1;
      const bool last = (q >> 2) == n_items - 1;
      mbar_wait(b_ordy + 8 * (q & 3), q >> 2);
      store_o(tmO, (h ? (last ? sbase + AT_SQ + 32768 : sbase + 2 * 32768) : sbase + AT_SQ) + w * 8192, (item >> 4) * 2 + h, (item & 15) * 128 + w * 64);
      if (w) {
        bulk_wait_read<0>();
        mbar_arrive(h ? b_ob : b_q0);
        bulk_wait<0>();
        fence_proxy_async_global();
        red_release_add(&g_hcnt[32 * (1 + (item & 15)) + 2 + (item >> 7)], h ? 1u : 256u);
        if (blockIdx.x < 128 && q == (n_items == 2 ? 5 : 3)) { spin_until(cnt, 0x808u); mbar_arrive(b_acq); }
      }
    }
    if (n_items == 1) {
      #pragma unroll 1
      for (int i = 0; i < help_njobs(); i++) {
        mbar_wait(b_acq + 16, i & 1);
        red_release_add(&g_hcnt[32 * (1 + (help_job(i) >> 2)) + 4 + (help_job(i) & 3)], 1u);
        if (i == 0) { spin_until(&g_hcnt[0], 132u); mbar_arrive(b_acq + 32); }
      }
    }
    if (blockIdx.x < 128) {
      spin_until(&g_hcnt[0], 132u); spin_until(cnt + 1, 0x808u); mbar_arrive(b_acq);
      #pragma unroll 1
      for (unsigned int i = 0; i < (1u << 22); i++) {
        if (ld_acquire(cnt + 2 + (OG_NT(blockIdx.x) >> 1)) >= 1u) break;
      }
      mbar_arrive(b_acq + 8);
    }
  }
}

__global__ void __launch_bounds__(384, 1)
fused_kernel(const __grid_constant__ CUtensorMap tmH, const __grid_constant__ CUtensorMap tmW, const __grid_constant__ CUtensorMap tmK,
            const __grid_constant__ CUtensorMap tmV, const __grid_constant__ CUtensorMap tmO, const __grid_constant__ CUtensorMap tmOl, const __grid_constant__ CUtensorMap tmWo,
            const __grid_constant__ CUtensorMap tmX, const __grid_constant__ CUtensorMap tmOut, uint32_t zero,
            const uint8_t* __restrict__ pf_wo, const bf16* __restrict__ kc, const bf16* __restrict__ vc,
            const bf16* __restrict__ x, const bf16* __restrict__ cvec, const bf16* __restrict__ w_mod, const bf16* __restrict__ w_r,
            const bf16* __restrict__ w_gate, const bf16* __restrict__ w_up, const bf16* __restrict__ w_down, bf16* __restrict__ out)
{
  extern __shared__ __align__(1024) uint8_t smem_raw[];
  const uint32_t sbase = smem_u32(smem_raw);
  const uint32_t bars = sbase + AT_SBAR;
  const uint32_t b_full = bars, b_empty = bars + 40;
  const uint32_t b_q0 = bars + 80, b_q1 = bars + 88;
  const uint32_t b_ob = bars + 96;
  const uint32_t b_ordy = bars + 104;
  const uint32_t b_pin = bars + 136;
  const uint32_t b_head = bars + 144;
  const uint32_t b_go = bars + 152;
  const uint32_t b_x = bars + 160;
  const int wg = __shfl_sync(0xffffffffu, threadIdx.x >> 7, 0);
  const bool single = blockIdx.x >= AT_NFULL;
  const int item0 = __shfl_sync(0xffffffffu, blockIdx.x < 128 ? (int)blockIdx.x : (int)blockIdx.x + 124, 0), n_items = __shfl_sync(0xffffffffu, single ? 1 : 2, 0);
  TL_START(3);
  if (threadIdx.x == 0) {
    if (sbase & 1023u) __trap();
    for (int i = 0; i < 5; i++) { mbar_init(b_full + 8 * i, 1); mbar_init(b_empty + 8 * i, 2); }
    mbar_init(b_q0, 1); mbar_init(b_q1, 8); mbar_init(b_ob, 1);
    for (int i = 0; i < 4; i++) mbar_init(b_ordy + 8 * i, 4);
    mbar_init(b_pin, 1); mbar_init(b_head, blockIdx.x < 128 ? 8 : 1); mbar_init(b_go, 1); mbar_init(b_x, 1);
    mbar_init(bars + 168, 1); mbar_init(bars + 176, 2); mbar_init(bars + 184, 8); mbar_init(bars + 192, 2);
    mbar_init(bars + 200, 8); mbar_init(bars + 208, 1); mbar_init(bars + 216, 1); mbar_init(bars + 264, 1); mbar_init(bars + 272, 1); mbar_init(bars + 280, 8); mbar_init(bars + 288, 1); mbar_init(bars + 296, 1);
    fence_mbar_init();
  }

  if (wg == 0) {
    reg_dealloc<AT_PREG>();
    if (threadIdx.x < 32) { __syncwarp(); named_bar_arrive(6, 384); }
    if (threadIdx.x >= 64) {
      named_bar_sync(6, 384);
      if (blockIdx.x < 128 && threadIdx.x >= 96) {
        named_bar_sync(8, 288);
        if (threadIdx.x == 96) red_release_add(&g_hcnt[32 * (1 + (blockIdx.x >> 3)) + 1], 1u);
      }
      if (blockIdx.x < 128) {
        mbar_wait(b_q0, 0);
        mod_rest(sbase + OG_SCOL, b_q1, threadIdx.x - 64, cvec, w_mod, w_r);
      }
      if (threadIdx.x == 64) { mbar_wait(bars + 288, 0); red_release_add(&g_hcnt[0], 1u); }
      __syncwarp();
    } else if (threadIdx.x >= 32) {
      named_bar_sync(6, 384);
      store_warp(sbase, &tmO, item0, n_items);
      __syncwarp();
    } else {
     if (elect_one()) {
      const uint64_t pol = policy_evict_first();
      prefetch_tmap(&tmW); prefetch_tmap(&tmH); prefetch_tmap(&tmWo); prefetch_tmap(&tmOl);
      uint32_t slot = 0, ph = 1;
      #pragma unroll 1
      for (int it = 0; it < n_items; it++) {
        const int item = item0 + it * 128, hp = item >> 4, qt = item & 15;
        const bool first = it == 0;
        #pragma unroll 1
        for (int j = 0; j < T_D / 64; j++) {
          const uint32_t sl = ring_slot(qp_pos(j, it)), fb = b_full + 8 * sl;
          mbar_wait(b_empty + 8 * sl, ring_par(qp_pos(j, it)) ^ ((j >> 2) & 1) ^ 1);
          mbar_expect_tx(fb, 49152);
          #pragma unroll 1
          for (int c = 0; c < 4; c++) tma_load_2d_hint(sbase + sl * 32768 + c * 8192, &tmW, hp * 256 + c * 64, j * 64, fb, pol);
          if (first && j < PRE_B) {
            if (j == PRE_B - 1) {
              spin_until(&g_hcnt[32 * (1 + qt)], 8u);
              TL_MARK2(16, true);
              fence_proxy_async_global();
              TL_MARK2(17, true);
              #pragma unroll 1
              for (int i = 0; i < PRE_B; i++) tma_load_2d(sbase + AT_SQ + i * 16384, &tmH, i * 64, qt * 128, b_full + 8 * i);
              mbar_arrive(b_go);
            }
          } else {
            if (first && j == 3) mbar_wait(b_head, 0);
            if (first && j == 4 * H_SPLIT) { spin_until(&g_hcnt[32 * (1 + qt) + 1], 8u); fence_proxy_async_global(); }
            if (!first && (j == 0 || j == 2)) mbar_wait(j ? b_q1 : b_q0, 0);
            tma_load_2d_hint(sbase + AT_SQ + (j & 3) * 16384, &tmH, j * 64, qt * 128, fb, first ? pol_normal() : pol);
          }
        }
        #pragma unroll 1
        for (int j = 0; j < 4 * AT_NBLK; j++) {
          const bool isv = (j > 0 && !(j & 1)) || j == 4 * AT_NBLK - 1;
          const int row = hp * 2 * T_SEQ + (isv ? (j - 1) >> 1 : (j + 1) >> 1) * 128;
          const uint32_t fb = b_full + 8 * slot;
          mbar_wait(b_empty + 8 * slot, ph);
          if (!first && j == 3) mbar_wait(b_ob, 0);
          if (j == 4 && it == n_items - 1) mbar_arrive(bars + 288);
          mbar_expect_tx(fb, 32768);
          tma_load_2d_hint(sbase + slot * 32768, isv ? &tmV : &tmK, 0, row, fb, pol);
          tma_load_2d_hint(sbase + slot * 32768 + 16384, isv ? &tmV : &tmK, 64, row, fb, pol);
          if (it == 1 && isv && j >= 2 * WO_LATE && j < 2 * WO_LATE + 32 && blockIdx.x < 64)
            l2_prefetch_bulk(pf_wo + (size_t)blockIdx.x * 131072 + ((j >> 1) - WO_LATE) * 8192, 8192);
          if (++slot == 5) { slot = 0; ph ^= 1; }
        }
      }
      if (single) {
        mbar_wait(b_q0, 0); mbar_wait(b_ob, 0);
        const int nj = help_njobs() * OG_PRE;
        int ji = 0, job = help_job(0), kk = 0;
        #pragma unroll 1
        for (int j = 0; j < nj; j++) {
          const uint32_t sl = ring_slot(qp_pos(j, 1)), fb = b_full + 8 * sl;
          mbar_wait(b_empty + 8 * sl, ring_par(qp_pos(j, 1)) ^ ((j >> 2) & 1) ^ 1);
          mbar_expect_tx(fb, 49152);
          #pragma unroll 1
          for (int c = 0; c < 4; c++) tma_load_2d_hint(sbase + sl * 32768 + c * 8192, HMAP_B, (job & 3) * 256 + c * 64, pre_kb(kk) * 64, fb, HPOL_B);
          if (kk == 0) { spin_until(&g_hcnt[32 * (1 + (job >> 2)) + 2], 0x800u); fence_proxy_async_global(); }
          tma_load_2d_hint(sbase + AT_SQ + (j & 3) * 16384, HMAP_A, pre_kb(kk) * 64, (job >> 2) * 128, fb, HPOL_A);
          if (++kk == OG_PRE) { kk = 0; job = help_job(++ji); }
        }
      }
      if (blockIdx.x < 128) {
        if (single) mbar_wait(b_x, 1);
        tail_producer(sbase, 0, n_items - 1, pol, &tmOl, &tmWo, &tmX, w_down);
      }
     }
    }
    __syncwarp();
    if (blockIdx.x < 128) tail_exchange(sbase, &tmOut, out);
  } else {
    if (blockIdx.x < 128) head_phase(sbase + AT_SQ + 49152, sbase + 4 * 32768, b_x, b_go, b_head, threadIdx.x - 128, zero, x, cvec, w_mod);
    else { named_bar_sync(6, 384); if (threadIdx.x == 128) mbar_arrive(b_head); }
    TL_MARK2(0, threadIdx.x == 128);
    reg_alloc<AT_CREG>();
    const int cwg = wg - 1;
    const int tid = threadIdx.x & 127;
    const int warp = tid >> 5, lane = tid & 31;
    const uint32_t dbase = (sbase & 0x3FFFFu) >> 4;
    const uint32_t k_base = dbase + (1u << 16);
    const uint32_t v_base = dbase + (1024u << 16);
    const uint32_t w_base = dbase + (512u << 16);
    const uint32_t q_lo = dbase + ((AT_SQ + cwg * 8192) >> 4) + (1u << 16);
    const uint32_t frag = cwg * 8192 + (16 * warp + (lane & 7) + 8 * ((lane >> 3) & 1)) * 128;
    if (cwg == 1) named_bar_arrive(1, 256);
    bool raw = false;
    #pragma unroll 1
    for (int it = 0; it < n_items; it++) {
      const int item = item0 + it * 128, hp = item >> 4;
      const bool more = it + 1 < n_items;
      constexpr int nkb = T_D / 64;
      const int ta = __shfl_sync(0xffffffffu, 4 * it, 0);
      float acc[128];
      {
        FS(2 * it, 0);
        #pragma unroll
        for (int i = 0; i < 128; i++) acc[i] = 0.f;
        fence_regs(acc);
        #pragma unroll 1
        for (int j = 0; j < nkb; j++) {
          const uint32_t slot = ring_slot(qp_pos(j, ta >> 2));
          mbar_wait(b_full + 8 * slot, ring_par(qp_pos(j, ta >> 2)) ^ ((j >> 2) & 1));
          if (QP_STAG > 0 && cwg == 1 && j == nkb - QP_STAG) named_bar_sync(7, 256);
          const uint32_t a_lo = q_lo + (j & 3) * 1024, b_lo = w_base + slot * 2048;
          wgmma_fence();
          wgmma_m64n256k16_ss_tb<0, 0>(acc, a_lo, b_lo, 1);
          wgmma_m64n256k16_ss_tb<2, 128>(acc, a_lo, b_lo, 1);
          wgmma_m64n256k16_ss_tb<4, 256>(acc, a_lo, b_lo, 1);
          wgmma_m64n256k16_ss_tb<6, 384>(acc, a_lo, b_lo, 1);
          wgmma_commit();
          if (QP_STAG > 0 && cwg == 0 && j == nkb - 1) named_bar_arrive(7, 256);
          if (j > 0) {
            wgmma_wait<1>();
            if (tid == 0) mbar_arrive(b_empty + 8 * ring_slot(qp_pos(j - 1, ta >> 2)));
          }
        }
        wgmma_wait<0>();
        fence_regs(acc);
        FS(2 * it, 1);
        TL_MARK2(29, threadIdx.x == 256 && it == 0);
        if (tid == 0) mbar_arrive(b_empty + 24);
      }
      float o[64], s[64];
      uint32_t p[32], q[32];
      #pragma unroll
      for (int i = 0; i < 32; i++) q[i] = pack_bf16(acc[2 * i] * AT_C, acc[2 * i + 1] * AT_C);
      zero_regs(s);
      const uint32_t sq = sbase + AT_SQ + cwg * 8192;
      const bool last_wg1 = cwg == 1 && !more;
      float mc0, mc1, al0 = 1.0f, al1 = 1.0f, l0 = 0.f, l1 = 0.f, lp0 = 0.f, lp1 = 0.f;
      bool redo0 = false;
      FS(2 * it, 2);
      mbar_wait(b_full + 8 * ring_slot(ta), ring_par(ta));
      named_bar_sync(1 + cwg, 256);
      FS(2 * it, 3);
      issue_qk(s, q, k_base + ring_slot(ta) * 2048);
      named_bar_arrive(1 + (cwg ^ 1), 256);
      bool ready = mbar_test(b_full + 8 * ring_slot(ta + 1), ring_par(ta + 1)) & mbar_test(b_full + 8 * ring_slot(ta + 2), ring_par(ta + 2));
      stage_q<16>(acc, AT_C, sbase + AT_SQ + frag, lane);
      wgmma_wait<0>();
      fence_regs(s);
      if (tid == 0) mbar_arrive(b_empty + 8 * ring_slot(ta));
      mc0 = 0.f; mc1 = 0.f;
      if (!raw) {
        raw = softmax_mode(s, mc0, mc1);
        if (__builtin_expect(!raw, 0)) softmax_sub(s, mc0, mc1);
      }
      softmax_exp<0, 64>(s);
      #pragma unroll
      for (int J = 0; J < 16; J += 2)
        stmatrix_x4(sbase + AT_SQ + frag + (J >> 3) * 16384 + ((((J & 7) + (lane >> 4)) ^ (lane & 7)) << 4), q[2 * J], q[2 * J + 1], q[2 * J + 2], q[2 * J + 3]);
      pack_p(p, s);
      zero_regs(o);
      FS(2 * it, 4);
      uint32_t ks = ring_slot(ta + 1), vs = ring_slot(ta + 2), kp = ring_par(ta + 1), vp = ring_par(ta + 2);
      auto finish_head = [&]() {
        FS(2 * it, 5);
        redo0 = finish_l(lp0, lp1);
        if (!redo0) {
          stage_o(o, lp0, lp1, sbase + AT_SQ + frag, lane);
          fence_proxy_async();
          __syncwarp();
          if (lane == 0) mbar_arrive(b_ordy + 8 * cwg);
        }
        FS(2 * it + 1, 4);
      };
      if (!ready) { mbar_wait(b_full + 8 * ks, kp); mbar_wait(b_full + 8 * vs, vp); }
      #pragma unroll 1
      for (int n = 1; n < 2 * AT_NBLK; n++) {
        named_bar_sync(1 + cwg, 256);
        issue_qk(s, q, k_base + ks * 2048);
        if (n == AT_NBLK + 1) finish_head();
        issue_pv(o, p, v_base + vs * 2048, (n & 15) != 1);
        if (!(last_wg1 && n == 2 * AT_NBLK - 1)) named_bar_arrive(1 + (cwg ^ 1), 256);
        wgmma_wait<1>();
        fence_regs(s);
        if (tid == 0) mbar_arrive(b_empty + 8 * ks);
        if (__builtin_expect(!raw || (n + 1) >> 1 == AT_NBLK / 2, 0)) {
          if (n == AT_NBLK - 1) {
            #pragma unroll
            for (int J = 0; J < 16; J += 2)
              ldmatrix_x4(sbase + AT_SQ + 32768 + frag + (J >> 3) * 16384 + ((((J & 7) + (lane >> 4)) ^ (lane & 7)) << 4), q[2 * J], q[2 * J + 1], q[2 * J + 2], q[2 * J + 3]);
          }
          if (!raw) {
            const float m0 = mc0, m1 = mc1;
            const bool ok = softmax_mode(s, mc0, mc1);
            if (n == AT_NBLK) raw = ok;
            else {
              mc0 = mc0 - AT_HEAD > m0 ? mc0 : m0; mc1 = mc1 - AT_HEAD > m1 ? mc1 : m1;
              al0 = ex2_approx(m0 - mc0); al1 = ex2_approx(m1 - mc1);
            }
            if (!raw) softmax_sub(s, mc0, mc1);
          }
        }
        softmax_exp<0, AT_SPLIT>(s);
        add_rowsum(p, l0, l1);
        if (tid == 0) {
          uint32_t dep = zero & __float_as_uint(l0) & __float_as_uint(l1);
          #pragma unroll
          for (int i = AT_SPLIT - AT_PIN - PINB; i < AT_SPLIT - PINB; i += 2) dep &= __float_as_uint(s[i]) & __float_as_uint(s[i + 1]);
          mbar_arrive(b_pin + dep);
        }
        wgmma_wait<0>();
        fence_regs(o);
        if (tid == 0) mbar_arrive(b_empty + 8 * vs);
        ks += 2; if (ks >= 5) { ks -= 5; kp ^= 1; }
        vs += 2; if (vs >= 5) { vs -= 5; vp ^= 1; }
        ready = mbar_test(b_full + 8 * ks, kp) & mbar_test(b_full + 8 * vs, vp);
        softmax_exp<AT_SPLIT, 64>(s);
        pack_p(p, s);
        if (n == AT_NBLK) { lp0 = l0; lp1 = l1; l0 = 0.f; l1 = 0.f; }
        if (__builtin_expect(!raw || !ready, 0)) {
        if (!raw && __any_sync(0xffffffffu, al0 != 1.0f || al1 != 1.0f)) {
          rescale_o(o, al0, al1);
          l0 *= al0; l1 *= al1;
          al0 = 1.0f; al1 = 1.0f;
        }
        if (!ready && n < 2 * AT_NBLK - 1) {
          mbar_wait(b_full + 8 * ks, kp);
          mbar_wait(b_full + 8 * vs, vp);
        }
        }
      }
      FS(2 * it + 1, 5);
      const uint32_t vl = ring_slot(ta + 63);
      vs = ring_slot(ta + 62);
      const uint32_t ob = more ? sbase + vs * 32768 : sbase + AT_SQ + 32768;
      mbar_wait(b_full + 8 * vl, ring_par(ta + 63));
      issue_pv(o, p, v_base + vl * 2048, 1);
      add_rowsum(p, l0, l1);
      const bool overflow = finish_l(l0, l1);
      if (!overflow && lane == 0) mbar_arrive(b_q1);
      mbar_wait(b_empty + 8 * vs, ring_par(ta + 62));
      wgmma_wait<0>();
      fence_regs(o);
      if (tid == 0) mbar_arrive(b_empty + 8 * vl);
      FS(2 * it + 1, 6);
      if (overflow) {
        attn_rows_exact(sq + 32768, ob + cwg * 8192, warp, lane, kc + (size_t)(hp * 2 + 1) * T_SEQ * T_DH, vc + (size_t)(hp * 2 + 1) * T_SEQ * T_DH);
        __syncwarp();
        if (lane == 0) mbar_arrive(b_q1);
      } else stage_o(o, l0, l1, ob + frag, lane);
      if (redo0) attn_rows_exact(sq, sq, warp, lane, kc + (size_t)(hp * 2) * T_SEQ * T_DH, vc + (size_t)(hp * 2) * T_SEQ * T_DH);
      fence_proxy_async();
      __syncwarp();
      if (lane == 0) {
        if (redo0) mbar_arrive(b_ordy + 8 * cwg);
        mbar_arrive(b_ordy + 16 + 8 * cwg);
      }
      if (redo0 || overflow) raw = false;
      named_bar_sync(3 + cwg, 128);
      FS(2 * it + 1, 7);
    }
    if (single) {
      float acc[128];
      #pragma unroll
      for (int i = 0; i < 128; i++) acc[i] = 0.f;
      fence_regs(acc);
      uint32_t j = 0;
      #pragma unroll 1
      for (int ji = 0; ji < help_njobs(); ji++) {
        #pragma unroll 1
        for (int kk = 0; kk < OG_PRE; kk++, j++) {
          const uint32_t slot = ring_slot(qp_pos(j, 1));
          mbar_wait(b_full + 8 * slot, ring_par(qp_pos(j, 1)) ^ ((j >> 2) & 1));
          const uint32_t a_lo = q_lo + (j & 3) * 1024, b_lo = w_base + slot * 2048;
          wgmma_fence();
          wgmma_m64n256k16_ss_tb<0, 0>(acc, a_lo, b_lo, kk != 0);
          wgmma_m64n256k16_ss_tb<2, 128>(acc, a_lo, b_lo, 1);
          wgmma_m64n256k16_ss_tb<4, 256>(acc, a_lo, b_lo, 1);
          wgmma_m64n256k16_ss_tb<6, 384>(acc, a_lo, b_lo, 1);
          wgmma_commit();
          if (kk > 0) {
            wgmma_wait<1>();
            if (tid == 0) mbar_arrive(b_empty + 8 * ring_slot(qp_pos(j - 1, 1)));
          }
        }
        wgmma_wait<0>();
        fence_regs(acc);
        if (tid == 0) mbar_arrive(b_empty + 8 * ring_slot(qp_pos(j - 1, 1)));
        if (ji == 1) mbar_wait(bars + 296, 0);
        uint4* dst = g_pre + help_job(ji) * 4096 + (cwg * 4 + warp) * 128 + lane;
        #pragma unroll
        for (int i = 0; i < 16; i++)
          dst[(i >> 2) * 1024 + (i & 3) * 32] = make_uint4(pack_bf16(acc[8 * i], acc[8 * i + 1]), pack_bf16(acc[8 * i + 2], acc[8 * i + 3]),
                                                           pack_bf16(acc[8 * i + 4], acc[8 * i + 5]), pack_bf16(acc[8 * i + 6], acc[8 * i + 7]));
        __syncwarp();
        if (lane == 0) mbar_arrive(bars + 280);
      }
      named_bar_sync(5, 256);
      if (threadIdx.x == 128) {
        #pragma unroll 1
        for (int i = 0; i < 5; i++) {
          constexpr int n = OG_JOBS * OG_PRE;
          const int used = i == 3 ? 0 : (n + 3 - (i == 4 ? 3 : i)) / 4;
          if ((used ^ (i < 4)) & 1) {
            mbar_arrive(b_full + 8 * ring_slot(4 + i));
            mbar_arrive(b_empty + 8 * ring_slot(4 + i)); mbar_arrive(b_empty + 8 * ring_slot(4 + i));
          }
        }
        mbar_arrive(b_x);
      }
      named_bar_sync(5, 256);
    }
    TL_CLK(3, 1, threadIdx.x == 128);
    TL_CTA(1, threadIdx.x == 256);
    TL_END(3, tid == 0);
    TL_MARK2(19, tid == 0 && !single);
    if (blockIdx.x < 128) {
      tail_consumer(sbase, cwg, w_r, w_gate, w_up);
    }
  }
}

typedef CUresult (*PFN_encodeTiled)(CUtensorMap*, CUtensorMapDataType, cuuint32_t, void*, const cuuint64_t*, const cuuint64_t*,
                                    const cuuint32_t*, const cuuint32_t*, CUtensorMapInterleave, CUtensorMapSwizzle,
                                    CUtensorMapL2promotion, CUtensorMapFloatOOBfill);

CUtensorMap make_map_2d(PFN_encodeTiled enc, const void* ptr, uint64_t inner, uint64_t outer, uint64_t stride_bytes, uint32_t box_inner, uint32_t box_outer) {
  CUtensorMap m;
  cuuint64_t gd[2] = {inner, outer}; cuuint64_t gs[1] = {stride_bytes};
  cuuint32_t bx[2] = {box_inner, box_outer}; cuuint32_t es[2] = {1, 1};
  enc(&m, CU_TENSOR_MAP_DATA_TYPE_BFLOAT16, 2, const_cast<void*>(ptr), gd, gs, bx, es, CU_TENSOR_MAP_INTERLEAVE_NONE,
      CU_TENSOR_MAP_SWIZZLE_128B, CU_TENSOR_MAP_L2_PROMOTION_L2_128B, CU_TENSOR_MAP_FLOAT_OOB_FILL_NONE);
  return m;
}

}

extern "C" void kernel_launch(void* const* d_in, const int* in_sizes, int n_in, void* d_out, int out_size) {
  const bf16* x      = (const bf16*)d_in[0];
  const bf16* kc     = (const bf16*)d_in[1];
  const bf16* vc     = (const bf16*)d_in[2];
  const bf16* wq     = (const bf16*)d_in[3];
  const bf16* wo     = (const bf16*)d_in[4];
  const bf16* w_r    = (const bf16*)d_in[6];
  const bf16* w_gate = (const bf16*)d_in[7];
  const bf16* w_up   = (const bf16*)d_in[8];
  const bf16* w_down = (const bf16*)d_in[9];
  const bf16* cvec   = (const bf16*)d_in[10];
  const bf16* w_mod  = (const bf16*)d_in[11];
  bf16* out = (bf16*)d_out;

  static PFN_encodeTiled enc = nullptr;
  static void *p_h = nullptr, *p_o = nullptr;
  if (!enc) {
    void* fn = nullptr; cudaDriverEntryPointQueryResult qres;
    cudaGetDriverEntryPoint("cuTensorMapEncodeTiled", &fn, cudaEnableDefault, &qres);
    enc = (PFN_encodeTiled)fn;
    cudaGetSymbolAddress(&p_h, g_pre);
    p_h = (uint4*)p_h + 16 * 2048;
    cudaGetSymbolAddress(&p_o, g_o);
    cudaFuncSetAttribute(fused_kernel, cudaFuncAttributeMaxDynamicSharedMemorySize, (int)AT_SMEM);
  }
  const CUtensorMap tm_h   = make_map_2d(enc, p_h, T_D, T_SEQ, T_D * 2, 64, 128);
  const CUtensorMap tm_wq  = make_map_2d(enc, wq, T_DQKV, T_D, T_DQKV * 2, 64, 64);
  const CUtensorMap tm_k   = make_map_2d(enc, kc, T_DH, (uint64_t)T_NH * T_SEQ, T_DH * 2, 64, 128);
  const CUtensorMap tm_v   = make_map_2d(enc, vc, T_DH, (uint64_t)T_NH * T_SEQ, T_DH * 2, 64, 128);
  const CUtensorMap tm_ost = make_map_2d(enc, p_o, T_DQKV, T_SEQ, T_DQKV * 2, 64, 64);
  const CUtensorMap tm_old = make_map_2d(enc, p_o, T_DQKV, T_SEQ, T_DQKV * 2, 64, 128);
  const CUtensorMap tm_wo  = make_map_2d(enc, wo, T_D, T_DQKV, T_D * 2, 64, 64);
  const CUtensorMap tm_x   = make_map_2d(enc, x, T_D, T_SEQ, T_D * 2, 64, 128);

  const CUtensorMap tm_out = make_map_2d(enc, out, T_D, T_SEQ, T_D * 2, 64, 128);

  fused_kernel<<<132, 384, AT_SMEM, cudaStreamPerThread>>>(tm_h, tm_wq, tm_k, tm_v, tm_ost, tm_old, tm_wo, tm_x, tm_out, 0u, (const uint8_t*)wo, kc, vc, x, cvec, w_mod,
             w_r, w_gate, w_up, w_down, out);
}
```

```cpp
#include <cuda_runtime.h>
#include <cuda_bf16.h>
#include <cuda.h>
#include <stdint.h>

namespace {

typedef __nv_bfloat16 bf16;

constexpr int T_SEQ = 2048, T_D = 1024, T_NH = 32, T_DH = 128, T_DQKV = 4096, T_F = 3584;

#define PRE_X 2
__device__ __align__(1024) uint4 g_pre[(16 * PRE_X + 128) * 2048];
#define g_h (reinterpret_cast<bf16*>(g_pre + 16 * PRE_X * 2048))
__device__ __align__(1024) bf16 g_o[T_SEQ * T_DQKV];
__device__ __align__(16) uint8_t g_col[8 * 1536];
__device__ __align__(16) float g_scal[64];
__device__ __align__(16) unsigned int g_hcnt[17 * 32];
__device__ __align__(128) float g_modpart[4 * 2 * T_D];
struct __align__(2048) TailMail {
  float4 part1[T_SEQ * 8];
  uint32_t key[256];
  uint4 cand[16 * 2 * 2 * 128];
  uint32_t cnt[32];
  float ypart[(T_F / 32) * 2 * T_D];
};
__device__ TailMail g_mail;
#define g_part1 g_mail.part1
#define g_key g_mail.key
#define g_cand g_mail.cand
#define CNT_Y (g_mail.cnt)
#define g_ypart g_mail.ypart

__device__ __forceinline__ uint32_t smem_u32(const void* p) { return (uint32_t)__cvta_generic_to_shared(p); }
__device__ __forceinline__ void mbar_init(uint32_t bar, uint32_t cnt) { asm volatile("mbarrier.init.shared::cta.b64 [%0], %1;" :: "r"(bar), "r"(cnt)); }
__device__ __forceinline__ void mbar_expect_tx(uint32_t bar, uint32_t bytes) { asm volatile("mbarrier.arrive.expect_tx.shared::cta.b64 _, [%0], %1;" :: "r"(bar), "r"(bytes) : "memory"); }
__device__ __forceinline__ void mbar_arrive(uint32_t bar) { asm volatile("mbarrier.arrive.shared::cta.b64 _, [%0];" :: "r"(bar) : "memory"); }
__device__ __forceinline__ void mbar_wait(uint32_t bar, uint32_t parity) {
  asm volatile("{\n.reg .pred p;\nLAB_WAIT:\nmbarrier.try_wait.parity.shared::cta.b64 p, [%0], %1;\n@!p bra LAB_WAIT;\n}\n" :: "r"(bar), "r"(parity) : "memory");
}
__device__ __forceinline__ bool mbar_test(uint32_t bar, uint32_t parity) {
  uint32_t r; asm volatile("{\n.reg .pred p;\nmbarrier.test_wait.parity.shared::cta.b64 p, [%1], %2;\nselp.u32 %0, 1, 0, p;\n}\n" : "=r"(r) : "r"(bar), "r"(parity) : "memory");
  return r != 0;
}
__device__ __forceinline__ void fence_mbar_init() { asm volatile("fence.mbarrier_init.release.cluster;" ::: "memory"); }
__device__ __forceinline__ void tma_load_2d(uint32_t dst, const CUtensorMap* map, int c0, int c1, uint32_t bar) {
  asm volatile("cp.async.bulk.tensor.2d.shared::cluster.global.mbarrier::complete_tx::bytes [%0], [%1, {%3, %4}], [%2];"
    :: "r"(dst), "l"(map), "r"(bar), "r"(c0), "r"(c1) : "memory");
}
__device__ __forceinline__ uint64_t policy_evict_first() {
  uint64_t p; asm volatile("createpolicy.fractional.L2::evict_first.b64 %0, 1.0;" : "=l"(p)); return p;
}
__device__ __forceinline__ void tma_load_2d_hint(uint32_t dst, const CUtensorMap* map, int c0, int c1, uint32_t bar, uint64_t pol) {
  asm volatile("cp.async.bulk.tensor.2d.shared::cluster.global.mbarrier::complete_tx::bytes.L2::cache_hint [%0], [%1, {%3, %4}], [%2], %5;"
    :: "r"(dst), "l"(map), "r"(bar), "r"(c0), "r"(c1), "l"(pol) : "memory");
}
__device__ __forceinline__ void tma_load_3d_hint(uint32_t dst, const CUtensorMap* map, int c1, int c2, uint32_t bar, uint64_t pol) {
  asm volatile("cp.async.bulk.tensor.3d.shared::cluster.global.mbarrier::complete_tx::bytes.L2::cache_hint [%0], [%1, {%3, %4, %5}], [%2], %6;"
    :: "r"(dst), "l"(map), "r"(bar), "n"(0), "r"(c1), "r"(c2), "l"(pol) : "memory");
}
__device__ __forceinline__ void tma_store_2d(const CUtensorMap* map, uint32_t src, int c0, int c1) {
  asm volatile("cp.async.bulk.tensor.2d.global.shared::cta.bulk_group [%0, {%2, %3}], [%1];" :: "l"(map), "r"(src), "r"(c0), "r"(c1) : "memory");
}
__device__ __forceinline__ void prefetch_tmap(const CUtensorMap* map) { asm volatile("prefetch.tensormap [%0];" :: "l"(map) : "memory"); }
__device__ __forceinline__ void l2_prefetch_bulk(const void* p, uint32_t bytes) {
  asm volatile("cp.async.bulk.prefetch.L2.global [%0], %1;" :: "l"(p), "r"(bytes) : "memory");
}
__device__ __forceinline__ void bulk_commit() { asm volatile("cp.async.bulk.commit_group;" ::: "memory"); }
template<int N> __device__ __forceinline__ void bulk_wait_read() { asm volatile("cp.async.bulk.wait_group.read %0;" :: "n"(N) : "memory"); }
template<int N> __device__ __forceinline__ void bulk_wait() { asm volatile("cp.async.bulk.wait_group %0;" :: "n"(N) : "memory"); }
__device__ __forceinline__ void named_bar_sync(int id, int nthreads) { asm volatile("bar.sync %0, %1;" :: "r"(id), "r"(nthreads) : "memory"); }
__device__ __forceinline__ void named_bar_arrive(int id, int nthreads) { asm volatile("bar.arrive %0, %1;" :: "r"(id), "r"(nthreads) : "memory"); }
__device__ __forceinline__ void wgmma_fence() { asm volatile("wgmma.fence.sync.aligned;" ::: "memory"); }
__device__ __forceinline__ void wgmma_commit() { asm volatile("wgmma.commit_group.sync.aligned;" ::: "memory"); }
template<int N> __device__ __forceinline__ void wgmma_wait() { asm volatile("wgmma.wait_group.sync.aligned %0;" :: "n"(N) : "memory"); }
template<int R> __device__ __forceinline__ void reg_alloc() { asm volatile("setmaxnreg.inc.sync.aligned.u32 %0;" :: "n"(R)); }
template<int R> __device__ __forceinline__ void reg_dealloc() { asm volatile("setmaxnreg.dec.sync.aligned.u32 %0;" :: "n"(R)); }
__device__ __forceinline__ bool elect_one() {
  uint32_t pred; asm volatile("{\n.reg .pred p;\nelect.sync _|p, 0xffffffff;\nselp.u32 %0, 1, 0, p;\n}\n" : "=r"(pred)); return pred != 0;
}
__device__ __forceinline__ uint32_t pack_bf16(float lo, float hi) {
  uint32_t r; asm("cvt.rn.bf16x2.f32 %0, %1, %2;" : "=r"(r) : "f"(hi), "f"(lo)); return r;
}
__device__ __forceinline__ void stmatrix_x4(uint32_t addr, uint32_t r0, uint32_t r1, uint32_t r2, uint32_t r3) {
  asm volatile("stmatrix.sync.aligned.m8n8.x4.shared.b16 [%0], {%1, %2, %3, %4};" :: "r"(addr), "r"(r0), "r"(r1), "r"(r2), "r"(r3) : "memory");
}
__device__ __forceinline__ void fence_proxy_async() { asm volatile("fence.proxy.async.shared::cta;" ::: "memory"); }
__device__ __forceinline__ float ex2_approx(float x) { float y; asm("ex2.approx.ftz.f32 %0, %1;" : "=f"(y) : "f"(x)); return y; }
template<int N> __device__ __forceinline__ void fence_regs(float (&r)[N]) {
  #pragma unroll
  for (int i = 0; i < N; i++) asm volatile("" : "+f"(r[i]) :: "memory");
}
template<int N> __device__ __forceinline__ void zero_regs(float (&r)[N]) {
  #pragma unroll
  for (int i = 0; i < N; i += 2) asm volatile("mov.b64 {%0, %1}, 0;" : "=f"(r[i]), "=f"(r[i + 1]));
}
__device__ __forceinline__ float rbf(float x) { return __uint_as_float(pack_bf16(0.f, x)); }
__device__ __forceinline__ float bflo(uint32_t v) { return __uint_as_float(v << 16); }
__device__ __forceinline__ float bfhi(uint32_t v) { return __uint_as_float(v & 0xffff0000u); }

#define TL_START(k) do {} while (0)
#define TL_END(k, cond) do {} while (0)
#define TL_CTA(i, cond) do {} while (0)
#define FS(slot, k) do {} while (0)
#define TL_MARK2(k, cond) do {} while (0)
#define TL_CLK(k, i, cond) do {} while (0)

template <int OFFA, int OFFB>
__device__ __forceinline__ void wgmma_m64n256k16_ss_tb(float (&d)[128], uint32_t a_lo, uint32_t b_lo, int scaleD) {
  asm volatile("{\n.reg .pred p;\n.reg .b32 ta, tb;\n.reg .b64 da, db;\nsetp.ne.b32 p, %130, 0;\n"
    "add.u32 ta, %128, %131;\nadd.u32 tb, %129, %132;\n"
    "mov.b64 da, {ta, 0x40000040};\nmov.b64 db, {tb, 0x40000040};\n"
    "wgmma.mma_async.sync.aligned.m64n256k16.f32.bf16.bf16 "
    "{%0, %1, %2, %3, %4, %5, %6, %7, %8, %9, %10, %11, %12, %13, %14, %15, %16, %17, %18, %19, %20, %21, %22, %23, %24, %25, %26, %27, %28, %29, %30, %31, %32, %33, %34, %35, %36, %37, %38, %39, %40, %41, %42, %43, %44, %45, %46, %47, %48, %49, %50, %51, %52, %53, %54, %55, %56, %57, %58, %59, %60, %61, %62, %63, %64, %65, %66, %67, %68, %69, %70, %71, %72, %73, %74, %75, %76, %77, %78, %79, %80, %81, %82, %83, %84, %85, %86, %87, %88, %89, %90, %91, %92, %93, %94, %95, %96, %97, %98, %99, %100, %101, %102, %103, %104, %105, %106, %107, %108, %109, %110, %111, %112, %113, %114, %115, %116, %117, %118, %119, %120, %121, %122, %123, %124, %125, %126, %127}, "
    "da, db, p, 1, 1, 0, 1;\n}\n"
    : "+f"(d[0]), "+f"(d[1]), "+f"(d[2]), "+f"(d[3]), "+f"(d[4]), "+f"(d[5]), "+f"(d[6]), "+f"(d[7]), "+f"(d[8]), "+f"(d[9]), "+f"(d[10]), "+f"(d[11]), "+f"(d[12]), "+f"(d[13]), "+f"(d[14]), "+f"(d[15]), "+f"(d[16]), "+f"(d[17]), "+f"(d[18]), "+f"(d[19]), "+f"(d[20]), "+f"(d[21]), "+f"(d[22]), "+f"(d[23]), "+f"(d[24]), "+f"(d[25]), "+f"(d[26]), "+f"(d[27]), "+f"(d[28]), "+f"(d[29]), "+f"(d[30]), "+f"(d[31]), "+f"(d[32]), "+f"(d[33]), "+f"(d[34]), "+f"(d[35]), "+f"(d[36]), "+f"(d[37]), "+f"(d[38]), "+f"(d[39]), "+f"(d[40]), "+f"(d[41]), "+f"(d[42]), "+f"(d[43]), "+f"(d[44]), "+f"(d[45]), "+f"(d[46]), "+f"(d[47]), "+f"(d[48]), "+f"(d[49]), "+f"(d[50]), "+f"(d[51]), "+f"(d[52]), "+f"(d[53]), "+f"(d[54]), "+f"(d[55]), "+f"(d[56]), "+f"(d[57]), "+f"(d[58]), "+f"(d[59]), "+f"(d[60]), "+f"(d[61]), "+f"(d[62]), "+f"(d[63]), "+f"(d[64]), "+f"(d[65]), "+f"(d[66]), "+f"(d[67]), "+f"(d[68]), "+f"(d[69]), "+f"(d[70]), "+f"(d[71]), "+f"(d[72]), "+f"(d[73]), "+f"(d[74]), "+f"(d[75]), "+f"(d[76]), "+f"(d[77]), "+f"(d[78]), "+f"(d[79]), "+f"(d[80]), "+f"(d[81]), "+f"(d[82]), "+f"(d[83]), "+f"(d[84]), "+f"(d[85]), "+f"(d[86]), "+f"(d[87]), "+f"(d[88]), "+f"(d[89]), "+f"(d[90]), "+f"(d[91]), "+f"(d[92]), "+f"(d[93]), "+f"(d[94]), "+f"(d[95]), "+f"(d[96]), "+f"(d[97]), "+f"(d[98]), "+f"(d[99]), "+f"(d[100]), "+f"(d[101]), "+f"(d[102]), "+f"(d[103]), "+f"(d[104]), "+f"(d[105]), "+f"(d[106]), "+f"(d[107]), "+f"(d[108]), "+f"(d[109]), "+f"(d[110]), "+f"(d[111]), "+f"(d[112]), "+f"(d[113]), "+f"(d[114]), "+f"(d[115]), "+f"(d[116]), "+f"(d[117]), "+f"(d[118]), "+f"(d[119]), "+f"(d[120]), "+f"(d[121]), "+f"(d[122]), "+f"(d[123]), "+f"(d[124]), "+f"(d[125]), "+f"(d[126]), "+f"(d[127])
    : "r"(a_lo), "r"(b_lo), "r"(scaleD), "n"(OFFA), "n"(OFFB));
}

template <int OFFA, int OFFB>
__device__ __forceinline__ void wgmma_m64n128k16_ss_tb(float (&d)[64], uint32_t a_lo, uint32_t b_lo, int scaleD) {
  asm volatile("{\n.reg .pred p;\n.reg .b32 ta, tb;\n.reg .b64 da, db;\nsetp.ne.b32 p, %66, 0;\n"
    "add.u32 ta, %64, %67;\nadd.u32 tb, %65, %68;\n"
    "mov.b64 da, {ta, 0x40000040};\nmov.b64 db, {tb, 0x40000040};\n"
    "wgmma.mma_async.sync.aligned.m64n128k16.f32.bf16.bf16 "
    "{%0, %1, %2, %3, %4, %5, %6, %7, %8, %9, %10, %11, %12, %13, %14, %15, %16, %17, %18, %19, %20, %21, %22, %23, %24, %25, %26, %27, %28, %29, %30, %31, %32, %33, %34, %35, %36, %37, %38, %39, %40, %41, %42, %43, %44, %45, %46, %47, %48, %49, %50, %51, %52, %53, %54, %55, %56, %57, %58, %59, %60, %61, %62, %63}, "
    "da, db, p, 1, 1, 0, 1;\n}\n"
    : "+f"(d[0]), "+f"(d[1]), "+f"(d[2]), "+f"(d[3]), "+f"(d[4]), "+f"(d[5]), "+f"(d[6]), "+f"(d[7]), "+f"(d[8]), "+f"(d[9]), "+f"(d[10]), "+f"(d[11]), "+f"(d[12]), "+f"(d[13]), "+f"(d[14]), "+f"(d[15]), "+f"(d[16]), "+f"(d[17]), "+f"(d[18]), "+f"(d[19]), "+f"(d[20]), "+f"(d[21]), "+f"(d[22]), "+f"(d[23]), "+f"(d[24]), "+f"(d[25]), "+f"(d[26]), "+f"(d[27]), "+f"(d[28]), "+f"(d[29]), "+f"(d[30]), "+f"(d[31]), "+f"(d[32]), "+f"(d[33]), "+f"(d[34]), "+f"(d[35]), "+f"(d[36]), "+f"(d[37]), "+f"(d[38]), "+f"(d[39]), "+f"(d[40]), "+f"(d[41]), "+f"(d[42]), "+f"(d[43]), "+f"(d[44]), "+f"(d[45]), "+f"(d[46]), "+f"(d[47]), "+f"(d[48]), "+f"(d[49]), "+f"(d[50]), "+f"(d[51]), "+f"(d[52]), "+f"(d[53]), "+f"(d[54]), "+f"(d[55]), "+f"(d[56]), "+f"(d[57]), "+f"(d[58]), "+f"(d[59]), "+f"(d[60]), "+f"(d[61]), "+f"(d[62]), "+f"(d[63])
    : "r"(a_lo), "r"(b_lo), "r"(scaleD), "n"(OFFA), "n"(OFFB));
}

template <int OFFB>
__device__ __forceinline__ void wgmma_m64n128k16_rs_tb(float (&d)[64], uint32_t a0, uint32_t a1, uint32_t a2, uint32_t a3, uint32_t b_lo, int scaleD) {
  asm volatile("{\n.reg .pred p;\n.reg .b32 tb;\n.reg .b64 db;\nsetp.ne.b32 p, %69, 0;\n"
    "add.u32 tb, %68, %70;\n"
    "mov.b64 db, {tb, 0x40000040};\n"
    "wgmma.mma_async.sync.aligned.m64n128k16.f32.bf16.bf16 "
    "{%0, %1, %2, %3, %4, %5, %6, %7, %8, %9, %10, %11, %12, %13, %14, %15, %16, %17, %18, %19, %20, %21, %22, %23, %24, %25, %26, %27, %28, %29, %30, %31, %32, %33, %34, %35, %36, %37, %38, %39, %40, %41, %42, %43, %44, %45, %46, %47, %48, %49, %50, %51, %52, %53, %54, %55, %56, %57, %58, %59, %60, %61, %62, %63}, "
    "{%64, %65, %66, %67}, db, p, 1, 1, 1;\n}\n"
    : "+f"(d[0]), "+f"(d[1]), "+f"(d[2]), "+f"(d[3]), "+f"(d[4]), "+f"(d[5]), "+f"(d[6]), "+f"(d[7]), "+f"(d[8]), "+f"(d[9]), "+f"(d[10]), "+f"(d[11]), "+f"(d[12]), "+f"(d[13]), "+f"(d[14]), "+f"(d[15]), "+f"(d[16]), "+f"(d[17]), "+f"(d[18]), "+f"(d[19]), "+f"(d[20]), "+f"(d[21]), "+f"(d[22]), "+f"(d[23]), "+f"(d[24]), "+f"(d[25]), "+f"(d[26]), "+f"(d[27]), "+f"(d[28]), "+f"(d[29]), "+f"(d[30]), "+f"(d[31]), "+f"(d[32]), "+f"(d[33]), "+f"(d[34]), "+f"(d[35]), "+f"(d[36]), "+f"(d[37]), "+f"(d[38]), "+f"(d[39]), "+f"(d[40]), "+f"(d[41]), "+f"(d[42]), "+f"(d[43]), "+f"(d[44]), "+f"(d[45]), "+f"(d[46]), "+f"(d[47]), "+f"(d[48]), "+f"(d[49]), "+f"(d[50]), "+f"(d[51]), "+f"(d[52]), "+f"(d[53]), "+f"(d[54]), "+f"(d[55]), "+f"(d[56]), "+f"(d[57]), "+f"(d[58]), "+f"(d[59]), "+f"(d[60]), "+f"(d[61]), "+f"(d[62]), "+f"(d[63])
    : "r"(a0), "r"(a1), "r"(a2), "r"(a3), "r"(b_lo), "r"(scaleD), "n"(OFFB));
}

template <int OFFB>
__device__ __forceinline__ void wgmma_m64n128k16_rs(float (&d)[64], uint32_t a0, uint32_t a1, uint32_t a2, uint32_t a3, uint32_t b_lo, int scaleD) {
  asm volatile("{\n.reg .pred p;\n.reg .b32 tb;\n.reg .b64 db;\nsetp.ne.b32 p, %69, 0;\n"
    "add.u32 tb, %68, %70;\n"
    "mov.b64 db, {tb, 0x40000040};\n"
    "wgmma.mma_async.sync.aligned.m64n128k16.f32.bf16.bf16 "
    "{%0, %1, %2, %3, %4, %5, %6, %7, %8, %9, %10, %11, %12, %13, %14, %15, %16, %17, %18, %19, %20, %21, %22, %23, %24, %25, %26, %27, %28, %29, %30, %31, %32, %33, %34, %35, %36, %37, %38, %39, %40, %41, %42, %43, %44, %45, %46, %47, %48, %49, %50, %51, %52, %53, %54, %55, %56, %57, %58, %59, %60, %61, %62, %63}, "
    "{%64, %65, %66, %67}, db, p, 1, 1, 0;\n}\n"
    : "+f"(d[0]), "+f"(d[1]), "+f"(d[2]), "+f"(d[3]), "+f"(d[4]), "+f"(d[5]), "+f"(d[6]), "+f"(d[7]), "+f"(d[8]), "+f"(d[9]), "+f"(d[10]), "+f"(d[11]), "+f"(d[12]), "+f"(d[13]), "+f"(d[14]), "+f"(d[15]), "+f"(d[16]), "+f"(d[17]), "+f"(d[18]), "+f"(d[19]), "+f"(d[20]), "+f"(d[21]), "+f"(d[22]), "+f"(d[23]), "+f"(d[24]), "+f"(d[25]), "+f"(d[26]), "+f"(d[27]), "+f"(d[28]), "+f"(d[29]), "+f"(d[30]), "+f"(d[31]), "+f"(d[32]), "+f"(d[33]), "+f"(d[34]), "+f"(d[35]), "+f"(d[36]), "+f"(d[37]), "+f"(d[38]), "+f"(d[39]), "+f"(d[40]), "+f"(d[41]), "+f"(d[42]), "+f"(d[43]), "+f"(d[44]), "+f"(d[45]), "+f"(d[46]), "+f"(d[47]), "+f"(d[48]), "+f"(d[49]), "+f"(d[50]), "+f"(d[51]), "+f"(d[52]), "+f"(d[53]), "+f"(d[54]), "+f"(d[55]), "+f"(d[56]), "+f"(d[57]), "+f"(d[58]), "+f"(d[59]), "+f"(d[60]), "+f"(d[61]), "+f"(d[62]), "+f"(d[63])
    : "r"(a0), "r"(a1), "r"(a2), "r"(a3), "r"(b_lo), "r"(scaleD), "n"(OFFB));
}

__device__ __forceinline__ uint4 ldg_nc_v4(const void* p) {
  uint4 v;
    asm volatile("{\n.reg .b64 pol;\ncreatepolicy.fractional.L2::evict_first.b64 pol, 1.0;\n"
                 "ld.global.nc.L1::no_allocate.L2::cache_hint.v4.u32 {%0, %1, %2, %3}, [%4], pol;\n}\n" : "=r"(v.x), "=r"(v.y), "=r"(v.z), "=r"(v.w) : "l"(p));
  return v;
}
__device__ __forceinline__ uint64_t pol_normal() {
  uint64_t p; asm volatile("createpolicy.fractional.L2::evict_normal.b64 %0, 1.0;" : "=l"(p)); return p;
}
__device__ __forceinline__ void unpack8(const uint4& u, float (&v)[8]) {
  v[0] = bflo(u.x); v[1] = bfhi(u.x); v[2] = bflo(u.y); v[3] = bfhi(u.y);
  v[4] = bflo(u.z); v[5] = bfhi(u.z); v[6] = bflo(u.w); v[7] = bfhi(u.w);
}
__device__ __forceinline__ void fma8(float (&acc)[8], float s, const uint4& w) {
  acc[0] = fmaf(s, bflo(w.x), acc[0]); acc[1] = fmaf(s, bfhi(w.x), acc[1]); acc[2] = fmaf(s, bflo(w.y), acc[2]); acc[3] = fmaf(s, bfhi(w.y), acc[3]);
  acc[4] = fmaf(s, bflo(w.z), acc[4]); acc[5] = fmaf(s, bfhi(w.z), acc[5]); acc[6] = fmaf(s, bflo(w.w), acc[6]); acc[7] = fmaf(s, bfhi(w.w), acc[7]);
}
__device__ __forceinline__ float rcp_approx(float x) { float y; asm("rcp.approx.ftz.f32 %0, %1;" : "=f"(y) : "f"(x)); return y; }
__device__ __forceinline__ float sigmoid_f(float v) { return rcp_approx(1.0f + ex2_approx(v * -1.4426950408889634f)); }
__device__ __forceinline__ float silu_bf(float v) { return rbf(v * sigmoid_f(v)); }
__device__ __forceinline__ uint32_t rank_key(float r, int idx) {
  const uint32_t b = __float_as_uint(r) >> 16;
  const uint32_t u = (r != r) ? 0u : ((b & 0x8000u) ? (~b & 0xffffu) : (b | 0x8000u));
  return (u << 16) | (0xffffu - (uint32_t)idx);
}
__device__ __forceinline__ void warp_top2(uint32_t& k1, uint32_t& k2) {
  const uint32_t m1 = __reduce_max_sync(0xffffffffu, k1);
  k2 = __reduce_max_sync(0xffffffffu, k1 == m1 ? k2 : k1);
  k1 = m1;
}
__device__ __forceinline__ uint32_t bmul2(uint32_t a, uint32_t b) { uint32_t r; asm("mul.rn.bf16x2 %0, %1, %2;" : "=r"(r) : "r"(a), "r"(b)); return r; }
__device__ __forceinline__ uint32_t badd2(uint32_t a, uint32_t b) { uint32_t r; asm("add.rn.bf16x2 %0, %1, %2;" : "=r"(r) : "r"(a), "r"(b)); return r; }
__device__ __forceinline__ uint32_t bsub2(uint32_t a, uint32_t b) { uint32_t r; asm("sub.rn.bf16x2 %0, %1, %2;" : "=r"(r) : "r"(a), "r"(b)); return r; }
__device__ __forceinline__ float sqrt_approx(float x) { float y; asm("sqrt.approx.f32 %0, %1;" : "=f"(y) : "f"(x)); return y; }
__device__ __forceinline__ uint32_t ln_norm2(uint32_t x1, uint32_t mb2, float inv) {
  const uint32_t d = bsub2(x1, mb2);
  return pack_bf16(bflo(d) * inv, bfhi(d) * inv);
}
__device__ __forceinline__ uint32_t ln_mod2(uint32_t x1, uint32_t mb2, float inv, uint32_t c1, uint32_t sb) { return badd2(bmul2(ln_norm2(x1, mb2, inv), c1), sb); }
__device__ __forceinline__ void ldmatrix_x4(uint32_t addr, uint32_t& r0, uint32_t& r1, uint32_t& r2, uint32_t& r3) {
  asm volatile("ldmatrix.sync.aligned.m8n8.x4.shared.b16 {%0, %1, %2, %3}, [%4];" : "=r"(r0), "=r"(r1), "=r"(r2), "=r"(r3) : "r"(addr) : "memory");
}
__device__ __forceinline__ uint4 ldg_stream_v4(const void* p, uint64_t pol) {
  uint4 v; asm volatile("ld.global.nc.L1::no_allocate.L2::cache_hint.L2::128B.v4.u32 {%0, %1, %2, %3}, [%4], %5;" : "=r"(v.x), "=r"(v.y), "=r"(v.z), "=r"(v.w) : "l"(p), "l"(pol)); return v;
}
__device__ __forceinline__ void bulk_load_hint(uint32_t dst, const void* src, uint32_t bytes, uint32_t bar, uint64_t pol) {
  asm volatile("cp.async.bulk.shared::cluster.global.mbarrier::complete_tx::bytes.L2::cache_hint [%0], [%1], %2, [%3], %4;"
    :: "r"(dst), "l"(src), "r"(bytes), "r"(bar), "l"(pol) : "memory");
}
__device__ __forceinline__ void red_release_add(unsigned int* p, unsigned int v) { asm volatile("red.release.gpu.global.add.u32 [%0], %1;" :: "l"(p), "r"(v) : "memory"); }
__device__ __forceinline__ unsigned int ld_acquire(const unsigned int* p) { unsigned int v; asm volatile("ld.acquire.gpu.global.u32 %0, [%1];" : "=r"(v) : "l"(p) : "memory"); return v; }
__device__ __forceinline__ void spin_until(const unsigned int* p, unsigned int target) {
  #pragma unroll 1
  for (unsigned int i = 0; i < (1u << 22); i++) { if (ld_acquire(p) >= target) return; }
}
__device__ __forceinline__ float lds_f32(uint32_t a) { float v; asm volatile("ld.shared.f32 %0, [%1];" : "=f"(v) : "r"(a) : "memory"); return v; }
__device__ __forceinline__ float2 lds_f32x2(uint32_t a) { float2 v; asm volatile("ld.shared.v2.f32 {%0, %1}, [%2];" : "=f"(v.x), "=f"(v.y) : "r"(a) : "memory"); return v; }
__device__ __forceinline__ uint2 lds_u32x2(uint32_t a) { uint2 v; asm volatile("ld.shared.v2.u32 {%0, %1}, [%2];" : "=r"(v.x), "=r"(v.y) : "r"(a) : "memory"); return v; }
__device__ __forceinline__ uint32_t lds_u32(uint32_t a) { uint32_t v; asm volatile("ld.shared.u32 %0, [%1];" : "=r"(v) : "r"(a) : "memory"); return v; }
__device__ __forceinline__ void sts_u32(uint32_t a, uint32_t v) { asm volatile("st.shared.u32 [%0], %1;" :: "r"(a), "r"(v) : "memory"); }
__device__ __forceinline__ void sts_u32x2(uint32_t a, uint32_t x, uint32_t y) { asm volatile("st.shared.v2.u32 [%0], {%1, %2};" :: "r"(a), "r"(x), "r"(y) : "memory"); }
__device__ __forceinline__ void sts_f32(uint32_t a, float v) { asm volatile("st.shared.f32 [%0], %1;" :: "r"(a), "f"(v) : "memory"); }
__device__ __forceinline__ void sts_f32x2(uint32_t a, float x, float y) { asm volatile("st.shared.v2.f32 [%0], {%1, %2};" :: "r"(a), "f"(x), "f"(y) : "memory"); }
__device__ __forceinline__ void sts_f32x4(uint32_t a, float x, float y, float z, float w) { asm volatile("st.shared.v4.f32 [%0], {%1, %2, %3, %4};" :: "r"(a), "f"(x), "f"(y), "f"(z), "f"(w) : "memory"); }

__device__ __forceinline__ uint4 lds_u32x4(uint32_t a) { uint4 v; asm volatile("ld.shared.v4.u32 {%0, %1, %2, %3}, [%4];" : "=r"(v.x), "=r"(v.y), "=r"(v.z), "=r"(v.w) : "r"(a) : "memory"); return v; }
__device__ __forceinline__ void sts_u32x4(uint32_t a, uint32_t x, uint32_t y, uint32_t z, uint32_t w) { asm volatile("st.shared.v4.u32 [%0], {%1, %2, %3, %4};" :: "r"(a), "r"(x), "r"(y), "r"(z), "r"(w) : "memory"); }
__device__ __forceinline__ void st_tagged(float* p, float v) {
  const uint32_t b = __float_as_uint(v);
  asm volatile("st.relaxed.gpu.global.u32 [%0], %1;" :: "l"(p), "r"(b == 0u ? 0x80000000u : b) : "memory");
}
__device__ __forceinline__ void st_tagged4(float* p, float x, float y, float z, float w) {
  const uint32_t a = __float_as_uint(x), b = __float_as_uint(y), c = __float_as_uint(z), d = __float_as_uint(w);
  asm volatile("st.relaxed.gpu.global.v4.u32 [%0], {%1, %2, %3, %4};" :: "l"(p), "r"(a == 0u ? 0x80000000u : a), "r"(b == 0u ? 0x80000000u : b),
               "r"(c == 0u ? 0x80000000u : c), "r"(d == 0u ? 0x80000000u : d) : "memory");
}
__device__ __forceinline__ void st_relaxed2(void* p, uint32_t a, uint32_t b) { asm volatile("st.relaxed.gpu.global.v2.u32 [%0], {%1, %2};" :: "l"(p), "r"(a), "r"(b) : "memory"); }
__device__ __forceinline__ float4 ld_tagged4(const float* p) {
  float4 v; asm volatile("ld.relaxed.gpu.global.v4.f32 {%0, %1, %2, %3}, [%4];" : "=f"(v.x), "=f"(v.y), "=f"(v.z), "=f"(v.w) : "l"(p) : "memory"); return v;
}
__device__ __forceinline__ bool tagged4(const float4& v) {
  return __float_as_uint(v.x) != 0u && __float_as_uint(v.y) != 0u && __float_as_uint(v.z) != 0u && __float_as_uint(v.w) != 0u;
}
__device__ __forceinline__ void hint_arrive(uint32_t* p) { asm volatile("red.relaxed.gpu.global.add.u32 [%0], 1;" :: "l"(p) : "memory"); }
__device__ __forceinline__ void hint_wait(const uint32_t* p, uint32_t target) {
  uint32_t v = 0u;
  #pragma unroll 1
  for (unsigned int i = 0; i < (1u << 22) && v < target; i++) asm volatile("ld.relaxed.gpu.global.u32 %0, [%1];" : "=r"(v) : "l"(p) : "memory");
}
__device__ __forceinline__ void fence_proxy_async_global() { asm volatile("fence.proxy.async.global;" ::: "memory"); }

constexpr int H_SPLIT = 1;
constexpr int PRE_B = 2;
__device__ __forceinline__ void load_parts(float4 (&pa)[4], float4 (&pb)[4], int t2) {
  #pragma unroll
  for (int k = 0; k < 4; k++) { pa[k] = ld_tagged4(g_modpart + k * 2 * T_D + t2 * 8); pb[k] = ld_tagged4(g_modpart + k * 2 * T_D + t2 * 8 + 4); }
}
__device__ __forceinline__ void finish_parts(float4 (&pa)[4], float4 (&pb)[4], int t2, uint32_t tab) {
  #pragma unroll 1
  for (unsigned int spin = 0; spin < (1u << 22); spin++) {
    bool ok = true;
    #pragma unroll
    for (int k = 0; k < 4; k++) ok &= tagged4(pa[k]) & tagged4(pb[k]);
    if (__all_sync(0xffffffffu, ok)) break;
    load_parts(pa, pb, t2);
  }
  #pragma unroll
  for (int k = 1; k < 4; k++) {
    pa[0].x += pa[k].x; pa[0].y += pa[k].y; pa[0].z += pa[k].z; pa[0].w += pa[k].w;
    pb[0].x += pb[k].x; pb[0].y += pb[k].y; pb[0].z += pb[k].z; pb[0].w += pb[k].w;
  }
  uint32_t m0 = pack_bf16(pa[0].x, pa[0].y), m1 = pack_bf16(pa[0].z, pa[0].w), m2 = pack_bf16(pb[0].x, pb[0].y), m3 = pack_bf16(pb[0].z, pb[0].w);
  if (t2 >= 128) { m0 = badd2(m0, 0x3F803F80u); m1 = badd2(m1, 0x3F803F80u); m2 = badd2(m2, 0x3F803F80u); m3 = badd2(m3, 0x3F803F80u); }
  sts_u32x4(tab + t2 * 16, m0, m1, m2, m3);
}
__device__ __forceinline__ void head_phase(uint32_t scr, uint32_t xs, uint32_t b_x, uint32_t b_go, uint32_t b_head, int t2, uint32_t zero, const bf16* __restrict__ x, const bf16* __restrict__ cvec, const bf16* __restrict__ w_mod) {
  const int lane = t2 & 31, w8 = t2 >> 5;
  const int cb = blockIdx.x & 31, ks = blockIdx.x >> 5;
  uint4 w[8], xv[2][4];
  const float cv = __bfloat162float(cvec[ks * 256 + t2]);
  #pragma unroll
  for (int i = 0; i < 8; i++) w[i] = ldg_nc_v4(w_mod + (size_t)(ks * 256 + (t2 >> 3) + 32 * i) * (6 * T_D) + cb * 64 + (t2 & 7) * 8);
  const int row0 = blockIdx.x * 16 + 2 * w8;
  sts_f32(scr + t2 * 4, silu_bf(cv));
  #pragma unroll 1
  for (uint32_t i = 0; i <= zero; i++) named_bar_sync(6, 384);
  TL_MARK2(1, t2 == 0);
  {
    float acc[8];
    #pragma unroll
    for (int j = 0; j < 8; j++) acc[j] = 0.f;
    #pragma unroll
    for (int i = 0; i < 8; i++) {
      fma8(acc, lds_f32(scr + ((t2 >> 3) + 32 * i) * 4), w[i]);
      if (i == 0 && t2 == 0) {
        mbar_expect_tx(b_x + (__float_as_uint(acc[0]) & zero), 32768);
        bulk_load_hint(xs, x + (size_t)blockIdx.x * 16 * T_D, 32768, b_x, policy_evict_first());
      }
    }
    #pragma unroll
    for (int j = 0; j < 4; j++) { const bool up = lane & 16; acc[j] = (up ? acc[4 + j] : acc[j]) + __shfl_xor_sync(0xffffffffu, up ? acc[j] : acc[4 + j], 16); }
    #pragma unroll
    for (int j = 0; j < 2; j++) { const bool up = lane & 8; acc[j] = (up ? acc[2 + j] : acc[j]) + __shfl_xor_sync(0xffffffffu, up ? acc[j] : acc[2 + j], 8); }
    sts_f32x2(scr + 1024 + w8 * 256 + (lane & 7) * 32 + (lane >> 3) * 8, acc[0], acc[1]);
  }
  named_bar_sync(5, 256);
  if (t2 < 64) {
    float sum = 0.f;
    #pragma unroll
    for (int i = 0; i < 8; i++) sum += lds_f32(scr + 1024 + i * 256 + t2 * 4);
    st_tagged(g_modpart + ks * 2 * T_D + cb * 64 + t2, sum);
    TL_MARK2(2, t2 == 0);
  }
  mbar_wait(b_x, 0);
  const bool first_cols = (__shfl_sync(0xffffffffu, w8, 0) & 3) == 0;
  float4 pa[4], pb[4];
  pa[0].x = 0.f;
  if (first_cols) load_parts(pa, pb, t2);
  #pragma unroll
  for (int r = 0; r < 2; r++)
    #pragma unroll
    for (int j = 0; j < 4; j++) xv[r][j] = lds_u32x4(xs + (2 * w8 + r) * 2048 + j * 512 + lane * 16);
  #pragma unroll
  for (int r = 0; r < 2; r++) {
    float v[4][8], sum = 0.f;
    #pragma unroll
    for (int j = 0; j < 4; j++) {
      unpack8(xv[r][j], v[j]);
      sum += ((v[j][0] + v[j][1]) + (v[j][2] + v[j][3])) + ((v[j][4] + v[j][5]) + (v[j][6] + v[j][7]));
    }
    #pragma unroll
    for (int o = 16; o > 0; o >>= 1) sum += __shfl_xor_sync(0xffffffffu, sum, o);
    const float mean = sum * (1.0f / T_D);
    float q = 0.f;
    #pragma unroll
    for (int j = 0; j < 4; j++)
      #pragma unroll
      for (int i = 0; i < 8; i++) { const float d = v[j][i] - mean; q = fmaf(d, d, q); }
    #pragma unroll
    for (int o = 16; o > 0; o >>= 1) q += __shfl_xor_sync(0xffffffffu, q, o);
    const uint32_t mb2 = pack_bf16(mean, mean);
    const float inv = rcp_approx(rbf(sqrt_approx(rbf(rbf(q * (1.0f / T_D)) + 1e-05f))));
    #pragma unroll
    for (int j = 0; j < 4; j++) {
      xv[r][j].x = ln_norm2(xv[r][j].x, mb2, inv); xv[r][j].y = ln_norm2(xv[r][j].y, mb2, inv);
      xv[r][j].z = ln_norm2(xv[r][j].z, mb2, inv); xv[r][j].w = ln_norm2(xv[r][j].w, mb2, inv);
    }
  }
  TL_MARK2(5, t2 == 0);
  #pragma unroll 1
  for (int ph = 0; ph < 2; ph++) {
    if (first_cols == (ph == 0)) finish_parts(pa, pb, t2, scr + 8192);
    named_bar_sync(5, 256);
    if (ph) break;
    TL_MARK2(7, t2 == 0);
    const uint4 sa = lds_u32x4(scr + 8192 + lane * 16), c1 = lds_u32x4(scr + 8192 + 2048 + lane * 16);
    #pragma unroll
    for (int r = 0; r < 2; r++)
      *reinterpret_cast<uint4*>(g_h + (size_t)(row0 + r) * T_D + lane * 8) = make_uint4(badd2(bmul2(xv[r][0].x, c1.x), sa.x), badd2(bmul2(xv[r][0].y, c1.y), sa.y),
                                                                                        badd2(bmul2(xv[r][0].z, c1.z), sa.z), badd2(bmul2(xv[r][0].w, c1.w), sa.w));
    named_bar_sync(5, 256);
    TL_MARK2(18, t2 == 0);
    if (t2 == 0) red_release_add(&g_hcnt[32 * (1 + (blockIdx.x >> 3))], 1u);
    TL_MARK2(11, t2 == 0);
  }
  TL_MARK2(6, t2 == 0);
  #pragma unroll
  for (int j = 1; j < 4; j++) {
    const uint4 sa = lds_u32x4(scr + 8192 + (j * 32 + lane) * 16), c1 = lds_u32x4(scr + 8192 + 2048 + (j * 32 + lane) * 16);
    #pragma unroll
    for (int r = 0; r < 2; r++) {
      xv[r][j].x = badd2(bmul2(xv[r][j].x, c1.x), sa.x); xv[r][j].y = badd2(bmul2(xv[r][j].y, c1.y), sa.y);
      xv[r][j].z = badd2(bmul2(xv[r][j].z, c1.z), sa.z); xv[r][j].w = badd2(bmul2(xv[r][j].w, c1.w), sa.w);
    }
  }
  __syncwarp();
  if (lane == 0) mbar_arrive(b_head + (xv[1][3].w & zero));
  mbar_wait(b_go, 0);
  #pragma unroll
  for (int j = 1; j < 4; j++)
    #pragma unroll
    for (int r = 0; r < 2; r++) *reinterpret_cast<uint4*>(g_h + (size_t)(row0 + r) * T_D + j * 256 + lane * 8) = xv[r][j];
  named_bar_arrive(8, 288);
}

#define MOD_AT (b_empty + 8)
#define MOD_PF 0
#define MOD_SPLIT 16
__device__ __forceinline__ void mod_rest(uint32_t scr, uint32_t b_go, int t, const bf16* __restrict__ cvec, const bf16* __restrict__ w_mod, const bf16* __restrict__ w_r) {
  const int lane = t & 31;
  #pragma unroll 1
  for (int i = t; i < T_D / 2; i += 64) {
    const uint32_t c2 = *reinterpret_cast<const uint32_t*>(cvec + 2 * i);
    sts_u32(scr + i * 4, pack_bf16(silu_bf(bflo(c2)), silu_bf(bfhi(c2))));
  }
  named_bar_sync(11, 64);
  const bf16* wp = w_mod + (size_t)(2 * (t >> 2)) * (6 * T_D) + 2 * T_D + blockIdx.x * 32 + (t & 3) * 8;
  float acc[8];
  #pragma unroll
  for (int i = 0; i < 8; i++) acc[i] = 0.f;
  #pragma unroll 1
  for (int i = 0; i < 32; i += 2) {
    if (i == MOD_SPLIT) mbar_wait(b_go, 0);
    const uint4 w0 = ldg_nc_v4(wp), w1 = ldg_nc_v4(wp + 6 * T_D), w2 = ldg_nc_v4(wp + 32 * 6 * T_D), w3 = ldg_nc_v4(wp + 33 * 6 * T_D);
    wp += 64 * 6 * T_D;
    const uint32_t s0 = lds_u32(scr + (i * 16 + (t >> 2)) * 4), s1 = lds_u32(scr + (i * 16 + 16 + (t >> 2)) * 4);
    fma8(acc, bflo(s0), w0); fma8(acc, bfhi(s0), w1); fma8(acc, bflo(s1), w2); fma8(acc, bfhi(s1), w3);
  }
  #pragma unroll
  for (int j = 0; j < 4; j++) { const bool up = lane & 16; acc[j] = (up ? acc[4 + j] : acc[j]) + __shfl_xor_sync(0xffffffffu, up ? acc[j] : acc[4 + j], 16); }
  #pragma unroll
  for (int j = 0; j < 2; j++) { const bool up = lane & 8; acc[j] = (up ? acc[2 + j] : acc[j]) + __shfl_xor_sync(0xffffffffu, up ? acc[j] : acc[2 + j], 8); }
  { const bool up = lane & 4; acc[0] = (up ? acc[1] : acc[0]) + __shfl_xor_sync(0xffffffffu, up ? acc[0] : acc[1], 4); }
  if (t >= 32) sts_f32(scr + 2048 + lane * 4, acc[0]);
  named_bar_sync(11, 64);
  if (__shfl_sync(0xffffffffu, t, 0) < 32) {
    const int kind = blockIdx.x >> 5;
    float v = rbf(acc[0] + lds_f32(scr + 2048 + lane * 4));
    const int col = (blockIdx.x & 31) * 32 + (lane & 3) * 8 + (lane >> 2);
    uint8_t* dst = g_col + (col >> 7) * 1536;
    if (kind == 2) v = rbf(1.0f + v);
    float vw = v * __bfloat162float(w_r[col]);
    if (kind == 2) {
      const int c = col & 127, i = (c & ~15) + ((c >> 1) & 3) * 4 + ((c >> 3) & 1) * 2 + (c & 1);
      reinterpret_cast<bf16*>(dst)[i] = __float2bfloat16_rn(vw);
      reinterpret_cast<bf16*>(dst)[128 + i] = __float2bfloat16_rn(vw - rbf(vw));
    }
    reinterpret_cast<bf16*>(dst + 512 + (kind & 1) * 512 + (kind >> 1) * 256)[col & 127] = __float2bfloat16_rn(v);
    #pragma unroll
    for (int o = 16; o > 0; o >>= 1) vw += __shfl_xor_sync(0xffffffffu, vw, o);
    if (lane == 0 && (kind == 1 || kind == 2)) g_scal[95 - blockIdx.x] = vw;
  }
  #pragma unroll 1
  for (int i = blockIdx.x * 64 + t; i < (int)(sizeof(g_mail) / 16); i += 128 * 64) reinterpret_cast<uint4*>(&g_mail)[i] = make_uint4(0u, 0u, 0u, 0u);
  named_bar_sync(11, 64);
  if (t == 0) red_release_add(&g_hcnt[0], 1u);
}

#define HPOL_A pol_normal()
#define HPOL_B pol_normal()
#define HMAP_A &tmOl
#define HMAP_B &tmWo
constexpr int AT_NBLK = T_SEQ / 128;
constexpr float AT_HEAD = 7.0f;
constexpr int WO_LATE = 12;
constexpr int QP_STAG = 3;
constexpr int AT_SPLIT = 28, AT_PIN = 8, PINB = 4;
constexpr int AT_NFULL = 124;
constexpr int AT_PREG = 40, AT_CREG = 232;
constexpr uint32_t AT_SQ = 5 * 32768;
constexpr float AT_C = 0.08838834764831845f * 1.4426950408889634f;
constexpr float AT_RAW_LO = -16.0f, AT_RAW_HI = 24.0f;
constexpr float AT_RAW_SUM = 281474976710656.0f, AT_RAW_MIN = 9.094947017729282e-13f;
constexpr uint32_t AT_SBAR = AT_SQ + 65536 + 256;
constexpr uint32_t AT_SMEM = AT_SQ + 65536 + 3072;

__device__ __forceinline__ uint32_t ring_slot(uint32_t t) { return t - 5u * ((t * 205u) >> 10); }
__device__ __forceinline__ uint32_t qp_pos(uint32_t j, uint32_t it) { return 4u * it + (j & 3u) + ((j & 3u) == 3u ? it : 0u); }
__device__ __forceinline__ uint32_t ring_par(uint32_t t) { return ((t * 205u) >> 10) & 1u; }
__device__ __forceinline__ void softmax_rowmax(const float (&s)[64], float& mx0, float& mx1) {
  float a0 = fmaxf(s[0], s[1]), a1 = fmaxf(s[4], s[5]), a2 = fmaxf(s[8], s[9]), a3 = fmaxf(s[12], s[13]);
  float b0 = fmaxf(s[2], s[3]), b1 = fmaxf(s[6], s[7]), b2 = fmaxf(s[10], s[11]), b3 = fmaxf(s[14], s[15]);
  #pragma unroll
  for (int j = 4; j < 16; j += 4) {
    a0 = fmaxf(a0, fmaxf(s[4 * j + 0], s[4 * j + 1]));  b0 = fmaxf(b0, fmaxf(s[4 * j + 2], s[4 * j + 3]));
    a1 = fmaxf(a1, fmaxf(s[4 * j + 4], s[4 * j + 5]));  b1 = fmaxf(b1, fmaxf(s[4 * j + 6], s[4 * j + 7]));
    a2 = fmaxf(a2, fmaxf(s[4 * j + 8], s[4 * j + 9]));  b2 = fmaxf(b2, fmaxf(s[4 * j + 10], s[4 * j + 11]));
    a3 = fmaxf(a3, fmaxf(s[4 * j + 12], s[4 * j + 13])); b3 = fmaxf(b3, fmaxf(s[4 * j + 14], s[4 * j + 15]));
  }
  mx0 = fmaxf(fmaxf(a0, a1), fmaxf(a2, a3));
  mx1 = fmaxf(fmaxf(b0, b1), fmaxf(b2, b3));
  mx0 = fmaxf(mx0, __shfl_xor_sync(0xffffffffu, mx0, 1));
  mx1 = fmaxf(mx1, __shfl_xor_sync(0xffffffffu, mx1, 1));
  mx0 = fmaxf(mx0, __shfl_xor_sync(0xffffffffu, mx0, 2));
  mx1 = fmaxf(mx1, __shfl_xor_sync(0xffffffffu, mx1, 2));
}
__device__ __forceinline__ void softmax_sub(float (&s)[64], float mc0, float mc1) {
  #pragma unroll
  for (int j = 0; j < 16; j++) { s[4 * j] -= mc0; s[4 * j + 1] -= mc0; s[4 * j + 2] -= mc1; s[4 * j + 3] -= mc1; }
}
template <int LO, int HI>
__device__ __forceinline__ void softmax_exp(float (&s)[64]) {
  #pragma unroll
  for (int i = LO; i < HI; i++) s[i] = ex2_approx(s[i]);
}
__device__ __forceinline__ bool softmax_mode(const float (&s)[64], float& mc0, float& mc1) {
  softmax_rowmax(s, mc0, mc1);
  const bool raw = __all_sync(0xffffffffu, mc0 >= AT_RAW_LO && mc0 <= AT_RAW_HI && mc1 >= AT_RAW_LO && mc1 <= AT_RAW_HI);
  mc0 += AT_HEAD; mc1 += AT_HEAD;
  return raw;
}
__device__ __forceinline__ void rowsum_p(const uint32_t (&p)[32], uint32_t& t0, uint32_t& t1) {
  uint32_t a[16];
  #pragma unroll
  for (int i = 0; i < 8; i++) { a[2 * i] = badd2(p[4 * i], p[4 * i + 2]); a[2 * i + 1] = badd2(p[4 * i + 1], p[4 * i + 3]); }
  #pragma unroll
  for (int i = 0; i < 4; i++) { a[2 * i] = badd2(a[4 * i], a[4 * i + 2]); a[2 * i + 1] = badd2(a[4 * i + 1], a[4 * i + 3]); }
  t0 = badd2(badd2(a[0], a[2]), badd2(a[4], a[6]));
  t1 = badd2(badd2(a[1], a[3]), badd2(a[5], a[7]));
}
__device__ __forceinline__ void add_rowsum(const uint32_t (&p)[32], float& l0, float& l1) {
  uint32_t t0, t1;
  rowsum_p(p, t0, t1);
  l0 += bflo(t0) + bfhi(t0); l1 += bflo(t1) + bfhi(t1);
}
__device__ __forceinline__ void pack_p(uint32_t (&p)[32], const float (&s)[64]) {
  #pragma unroll
  for (int i = 0; i < 32; i++) p[i] = pack_bf16(s[2 * i], s[2 * i + 1]);
}
__device__ __noinline__ void attn_rows_exact(uint32_t sq, uint32_t so, int warp, int lane, const bf16* __restrict__ kh, const bf16* __restrict__ vh) {
  #pragma unroll 1
  for (int r = 16 * warp; r < 16 * warp + 16; r++) {
    const uint32_t ad = (lane >> 4) * 16384 + r * 128 + ((((lane & 15) >> 1) ^ (r & 7)) << 4) + (lane & 1) * 8;
    uint2 qv; asm volatile("ld.shared.v2.u32 {%0, %1}, [%2];" : "=r"(qv.x), "=r"(qv.y) : "r"(sq + ad) : "memory");
    const float q0 = bflo(qv.x), q1 = bfhi(qv.x), q2 = bflo(qv.y), q3 = bfhi(qv.y);
    float m = -INFINITY, l = 0.f, o0 = 0.f, o1 = 0.f, o2 = 0.f, o3 = 0.f;
    #pragma unroll 1
    for (int key = 0; key < T_SEQ; key++) {
      const uint2 kv = *reinterpret_cast<const uint2*>(kh + (size_t)key * T_DH + lane * 4);
      const uint2 vv = *reinterpret_cast<const uint2*>(vh + (size_t)key * T_DH + lane * 4);
      float sc = (q0 * bflo(kv.x) + q1 * bfhi(kv.x)) + (q2 * bflo(kv.y) + q3 * bfhi(kv.y));
      #pragma unroll
      for (int o = 16; o > 0; o >>= 1) sc += __shfl_xor_sync(0xffffffffu, sc, o);
      const float mn = fmaxf(m, sc);
      const float al = (m == mn) ? 1.0f : ex2_approx(m - mn), p = rbf(ex2_approx(sc - mn));
      m = mn;
      l = fmaf(l, al, p);
      o0 = fmaf(o0, al, p * bflo(vv.x)); o1 = fmaf(o1, al, p * bfhi(vv.x));
      o2 = fmaf(o2, al, p * bflo(vv.y)); o3 = fmaf(o3, al, p * bfhi(vv.y));
    }
    const float inv = rcp_approx(l);
    asm volatile("st.shared.v2.u32 [%0], {%1, %2};" :: "r"(so + ad), "r"(pack_bf16(o0 * inv, o1 * inv)), "r"(pack_bf16(o2 * inv, o3 * inv)) : "memory");
  }
}
__device__ __forceinline__ void issue_qk(float (&s)[64], const uint32_t (&q)[32], uint32_t k_lo) {
  wgmma_fence();
  wgmma_m64n128k16_rs<0>(s, q[0], q[1], q[2], q[3], k_lo, 0);
  wgmma_m64n128k16_rs<2>(s, q[4], q[5], q[6], q[7], k_lo, 1);
  wgmma_m64n128k16_rs<4>(s, q[8], q[9], q[10], q[11], k_lo, 1);
  wgmma_m64n128k16_rs<6>(s, q[12], q[13], q[14], q[15], k_lo, 1);
  wgmma_m64n128k16_rs<1024>(s, q[16], q[17], q[18], q[19], k_lo, 1);
  wgmma_m64n128k16_rs<1026>(s, q[20], q[21], q[22], q[23], k_lo, 1);
  wgmma_m64n128k16_rs<1028>(s, q[24], q[25], q[26], q[27], k_lo, 1);
  wgmma_m64n128k16_rs<1030>(s, q[28], q[29], q[30], q[31], k_lo, 1);
  wgmma_commit();
}
__device__ __forceinline__ void issue_pv(float (&o)[64], const uint32_t (&p)[32], uint32_t v_lo, int accumulate) {
  wgmma_fence();
  wgmma_m64n128k16_rs_tb<0>(o, p[0], p[1], p[2], p[3], v_lo, accumulate);
  wgmma_m64n128k16_rs_tb<128>(o, p[4], p[5], p[6], p[7], v_lo, 1);
  wgmma_m64n128k16_rs_tb<256>(o, p[8], p[9], p[10], p[11], v_lo, 1);
  wgmma_m64n128k16_rs_tb<384>(o, p[12], p[13], p[14], p[15], v_lo, 1);
  wgmma_m64n128k16_rs_tb<512>(o, p[16], p[17], p[18], p[19], v_lo, 1);
  wgmma_m64n128k16_rs_tb<640>(o, p[20], p[21], p[22], p[23], v_lo, 1);
  wgmma_m64n128k16_rs_tb<768>(o, p[24], p[25], p[26], p[27], v_lo, 1);
  wgmma_m64n128k16_rs_tb<896>(o, p[28], p[29], p[30], p[31], v_lo, 1);
  wgmma_commit();
}
__device__ __forceinline__ void rescale_o(float (&o)[64], float al0, float al1) {
  #pragma unroll
  for (int j = 0; j < 16; j++) { o[4 * j] *= al0; o[4 * j + 1] *= al0; o[4 * j + 2] *= al1; o[4 * j + 3] *= al1; }
}

__device__ __forceinline__ void stage_o(const float (&o)[64], float i0, float i1, uint32_t dst, int lane) {
  #pragma unroll
  for (int J = 0; J < 16; J += 2)
    stmatrix_x4(dst + (J >> 3) * 16384 + ((((J & 7) + (lane >> 4)) ^ (lane & 7)) << 4),
                pack_bf16(o[4 * J + 0] * i0, o[4 * J + 1] * i0), pack_bf16(o[4 * J + 2] * i1, o[4 * J + 3] * i1),
                pack_bf16(o[4 * J + 4] * i0, o[4 * J + 5] * i0), pack_bf16(o[4 * J + 6] * i1, o[4 * J + 7] * i1));
}
__device__ __forceinline__ bool finish_l(float& l0, float& l1) {
  l0 += __shfl_xor_sync(0xffffffffu, l0, 1); l1 += __shfl_xor_sync(0xffffffffu, l1, 1);
  l0 += __shfl_xor_sync(0xffffffffu, l0, 2); l1 += __shfl_xor_sync(0xffffffffu, l1, 2);
  const bool redo = __any_sync(0xffffffffu, !(l0 <= AT_RAW_SUM && l1 <= AT_RAW_SUM && l0 >= AT_RAW_MIN && l1 >= AT_RAW_MIN));
  l0 = rcp_approx(l0); l1 = rcp_approx(l1);
  return redo;
}
template <int J0>
__device__ __forceinline__ void stage_q(const float (&acc)[128], float c, uint32_t dst, int lane) {
  #pragma unroll
  for (int J = J0; J < J0 + 16; J += 2)
    stmatrix_x4(dst + (J >> 3) * 16384 + ((((J & 7) + (lane >> 4)) ^ (lane & 7)) << 4),
                pack_bf16(acc[4 * J + 0] * c, acc[4 * J + 1] * c), pack_bf16(acc[4 * J + 2] * c, acc[4 * J + 3] * c),
                pack_bf16(acc[4 * J + 4] * c, acc[4 * J + 5] * c), pack_bf16(acc[4 * J + 6] * c, acc[4 * J + 7] * c));
}
__device__ __forceinline__ void store_o(const CUtensorMap* tmO, uint32_t src, int head, int row) {
  tma_store_2d(tmO, src, head * T_DH, row);
  tma_store_2d(tmO, src + 16384, head * T_DH + 64, row);
  bulk_commit();
}
__device__ __forceinline__ void mma_bf16(float (&d)[4], uint32_t a0, uint32_t a1, uint32_t a2, uint32_t a3, uint32_t b0, uint32_t b1) {
  asm volatile("mma.sync.aligned.m16n8k16.row.col.f32.bf16.bf16.f32 {%0, %1, %2, %3}, {%4, %5, %6, %7}, {%8, %9}, {%0, %1, %2, %3};"
               : "+f"(d[0]), "+f"(d[1]), "+f"(d[2]), "+f"(d[3]) : "r"(a0), "r"(a1), "r"(a2), "r"(a3), "r"(b0), "r"(b1));
}
struct GemvSel { uint32_t lo0, hi0, lo1, hi1; };
__device__ __forceinline__ GemvSel gemv_sel(int lane) {
  const uint32_t lo = (lane & 8) ? 0x1044u : 0x4410u, hi = (lane & 8) ? 0x3244u : 0x4432u;
  GemvSel s; s.lo0 = (lane & 16) ? 0x4444u : lo; s.hi0 = (lane & 16) ? 0x4444u : hi; s.lo1 = (lane & 16) ? lo : 0x4444u; s.hi1 = (lane & 16) ? hi : 0x4444u;
  return s;
}
#define GEMV_B0(j, h, s) __byte_perm((j) < 2 ? (h).x : (h).y, 0u, ((j) & 1) ? (s).hi0 : (s).lo0)
#define GEMV_B1(j, h, s) __byte_perm((j) < 2 ? (h).x : (h).y, 0u, ((j) & 1) ? (s).hi1 : (s).lo1)
__device__ __forceinline__ float4 gemv_out(const float (&d)[4], int lane) {
  const bool tk = lane & 1;
  const float r0 = __shfl_xor_sync(0xffffffffu, tk ? d[0] : d[1], 1), r1 = __shfl_xor_sync(0xffffffffu, tk ? d[2] : d[3], 1);
  return tk ? make_float4(r0, d[1], r1, d[3]) : make_float4(d[0], r0, d[2], r1);
}
#define OG_NG 8
#define OG_PRE 10
#define OG_JOBS 7
#define OG_GRP 7
#define LD_FIRST 1
#define LD_STAG (OG_GRP / 2)
constexpr int OG_ST = 5, OG_NKB = T_DQKV / 64 - OG_PRE, OG_MOE = T_F / 32;
__device__ __forceinline__ int pre_loc(int job) {
  const int step = ((job >> 4) << 2) + (job & 3);
  return (step < OG_JOBS ? 2 * step : step < 2 * OG_JOBS ? 2 * (step - OG_JOBS) + 1 : step) * 4 + ((job >> 2) & 3);
}
__device__ __forceinline__ int pre_kb(int i) { return (i >> 1) * 4 + (i & 1); }
__device__ __forceinline__ int own_kb(int i) { return i < (OG_PRE & ~1) ? pre_kb(i) + 2 : i + OG_PRE; }
constexpr int OG_POS = 8;
constexpr uint32_t OG_STAGE = 32768;
constexpr uint32_t OG_SCOL = AT_SBAR + 512;
constexpr uint32_t OG_SMISC = AT_SBAR + 2048;
constexpr int OG_XPOS = OG_POS + OG_NKB;
constexpr uint32_t OG_SWD = AT_SQ, OG_PSLOT = AT_SQ;
constexpr uint32_t OG_XSLOT = (OG_XPOS % OG_ST) * OG_STAGE;
constexpr uint32_t OG_OSLOT = ((OG_XPOS + 1) % OG_ST) * OG_STAGE;
constexpr uint32_t OG_SH2 = ((OG_XPOS + 2) % OG_ST) * OG_STAGE;
constexpr uint32_t OG_SRED = ((OG_XPOS + 3) % OG_ST) * OG_STAGE;
constexpr uint32_t OG_SSTAT = OG_SRED + 16384;
constexpr uint32_t OG_SGU = OG_SRED + 8192;
constexpr uint32_t OG_SFIN = OG_SGU + 256;
#define OGM 2
#define OG_MT(b) (((b) >> OGM) & 15)
#define OG_NT(b) (((b) & ((1 << OGM) - 1)) + (((b) >> (4 + OGM)) << OGM))
#define TAIL_SETUP \
  const uint32_t bar_full = sbase + AT_SBAR, bar_empty = bar_full + 40; \
  const uint32_t bar_wd = bar_full + 168, bar_col = bar_full + 176, bar_out = bar_full + 184, bar_end = bar_full + 192; \
  const uint32_t bar_key = bar_full + 200, bar_h2 = bar_full + 208, bar_sel = bar_full + 216; \
  const int mt = OG_MT(blockIdx.x), nt = OG_NT(blockIdx.x); \
  const int m0 = mt * 128, n0 = nt * 128; \
  const bool has_moe = (int)blockIdx.x < OG_MOE; \
  (void)bar_empty; (void)bar_wd; (void)bar_col; (void)bar_out; (void)bar_end; (void)bar_key; (void)bar_h2; (void)bar_sel; (void)m0; (void)n0; (void)has_moe;

__device__ __forceinline__ void tail_producer(uint32_t sbase, uint32_t ph, uint64_t pol, const CUtensorMap* tmA, const CUtensorMap* tmB, const CUtensorMap* tmX) {
  TAIL_SETUP
  uint32_t stage = OG_POS % OG_ST;
  int kb = 0;
  #pragma unroll 1
  for (int seg = 0; seg < 2; seg++) {
    mbar_wait(bar_full + 264, seg);
    fence_proxy_async_global();
    const int end = seg == 0 ? 32 - OG_PRE : OG_NKB;
    #pragma unroll 1
    for (; kb < end; kb++) {
      const uint32_t fb = bar_full + 8 * stage, sa = sbase + stage * OG_STAGE;
      const int k0 = own_kb(kb) * 64;
      mbar_wait(bar_empty + 8 * stage, ph);
      mbar_expect_tx(fb, OG_STAGE);
      tma_load_3d_hint(sa + 16384, tmB, k0, 2 * nt, fb, pol);
      tma_load_2d_hint(sa, tmA, k0, m0, fb, pol);
      if (++stage == OG_ST) { stage = 0; ph ^= 1; }
    }
  }
  mbar_wait(bar_empty + 8 * (OG_XPOS % OG_ST), ph);
  mbar_expect_tx(bar_full + 8 * (OG_XPOS % OG_ST), OG_STAGE);
  tma_load_3d_hint(sbase + OG_XSLOT, tmX, m0, 2 * nt, bar_full + 8 * (OG_XPOS % OG_ST), pol);
}

__device__ __forceinline__ uint32_t bfma2(uint32_t a, uint32_t b, uint32_t c) { uint32_t r; asm("fma.rn.bf16x2 %0, %1, %2, %3;" : "=r"(r) : "r"(a), "r"(b), "r"(c)); return r; }
__device__ __forceinline__ uint32_t out2(uint32_t x1, uint32_t mb2, uint32_t ih, uint32_t il, uint32_t c1, uint32_t sb, uint32_t gb) {
  const uint32_t d = bsub2(x1, mb2);
  const uint32_t h2 = badd2(bmul2(bfma2(d, ih, bmul2(d, il)), c1), sb);
  return badd2(x1, bmul2(gb, bfma2(h2, 0u, h2)));
}
#define OGTIME gtime()
#define PRE_N 1
#define PRE_PACE 150
#define WD_PACE 300
__device__ __forceinline__ void tail_exchange(uint32_t sbase, const CUtensorMap* tmOut, const bf16* __restrict__ w_down, bf16* __restrict__ out) {
    TAIL_SETUP
    const int lane = threadIdx.x & 31, wi = __shfl_sync(0xffffffffu, threadIdx.x >> 5, 0);
    if (wi == 3) {
      mbar_wait(bar_full + 264, 0); mbar_wait(bar_full + 264, 1);
      float a = g_scal[lane], b = g_scal[32 + lane];
      #pragma unroll
      for (int i = 0; i < 3; i++) {
        const uint4 v = *reinterpret_cast<const uint4*>(g_col + nt * 1536 + i * 512 + lane * 16);
        sts_u32x4(sbase + OG_SCOL + i * 512 + lane * 16, v.x, v.y, v.z, v.w);
      }
      #pragma unroll
      for (int o = 16; o > 0; o >>= 1) { a += __shfl_xor_sync(0xffffffffu, a, o); b += __shfl_xor_sync(0xffffffffu, b, o); }
      if (lane == 0) { sts_f32x2(sbase + OG_SMISC, a, b); mbar_arrive(bar_col); }
    } else if (wi == 2) {
      if (elect_one()) {
        const uint32_t b_free = bar_full + (blockIdx.x < AT_NFULL ? 80 : 160);
        mbar_wait(b_free, 0); mbar_wait(b_free, 1);
        #pragma unroll 1
        for (unsigned int i = 0; i < (1u << 20) && ld_acquire(&g_hcnt[32 * (1 + mt) + 4 + (nt >> 1)]) == 0u; i++) __nanosleep(200);
        fence_proxy_async_global();
        mbar_expect_tx(bar_full + 272, 32768);
        #pragma unroll 1
        for (int i = 0; i < PRE_N; i++) {
          bulk_load_hint(sbase + OG_PSLOT + i * (32768 / PRE_N), g_pre + pre_loc(mt * 4 + (nt >> 1)) * 4096 + (nt & 1) * 2048 + i * (2048 / PRE_N), 32768 / PRE_N,
                         bar_full + 272, policy_evict_first());
          if (PRE_N > 1) __nanosleep(PRE_PACE);
        }
      }
      named_bar_sync(14, 32);
      if (has_moe) {
        mbar_wait(bar_full + 96, 1); mbar_wait(bar_full + 304, 0);
        const uint64_t pol = policy_evict_first();
        #pragma unroll 1
        for (int r = 0; r < 32; r++) {
          __nanosleep(WD_PACE);
          #pragma unroll
          for (int j = 0; j < 4; j++)
            asm volatile("cp.async.cg.shared.global.L2::cache_hint [%0], [%1], 16, %2;" :: "r"(sbase + OG_SWD + (4 * j + (lane >> 3)) * 4096 + r * 128 + (((lane ^ r) & 7) << 4)),
                         "l"((const uint8_t*)w_down + (size_t)blockIdx.x * 65536 + r * 2048 + j * 512 + lane * 16), "l"(pol) : "memory");
        }
        asm volatile("cp.async.wait_all;" ::: "memory");
        __syncwarp();
        if (lane == 0) mbar_arrive(bar_wd);
      }
    }
    mbar_wait(bar_end, 0);
    TL_MARK2(22, lane == 0);
    if (wi == 0) {
      uint32_t k1 = 0u, k2 = 0u;
      #pragma unroll 1
      for (unsigned int spin = 0; spin < (1u << 22) && __any_sync(0xffffffffu, k1 == 0u); spin++) asm volatile("ld.relaxed.gpu.global.u32 %0, [%1];" : "=r"(k1) : "l"(g_key + lane) : "memory");
      TL_MARK2(28, lane == 0);
      warp_top2(k1, k2);
      if (lane == 0) {
        const uint32_t r1 = 0xffffu - (k1 & 0xffffu), r2 = 0xffffu - (k2 & 0xffffu);
        sts_u32x4(sbase + OG_SMISC + 64, r1, r2, (r1 >> 7) * 2, (r2 >> 7) * 2 + ((r1 >> 7) == (r2 >> 7)));
        mbar_arrive(bar_sel);
      }
    } else if (wi < 3) {
          mbar_wait(bar_key, 0);
          const uint4 kk = lds_u32x4(sbase + OG_SSTAT + 1024 + lane * 16);
          uint32_t k1 = max(kk.x, kk.y), k2 = min(kk.x, kk.y);
          k2 = max(max(k2, min(kk.z, kk.w)), min(k1, max(kk.z, kk.w))); k1 = max(k1, max(kk.z, kk.w));
          warp_top2(k1, k2);
          if (wi == 1) {
            if (lane == 0 && nt == (mt & 7)) st_relaxed2(g_key + mt * 2, k1, k2);
            TL_MARK2(27, lane == 0);
          } else {
            const uint32_t r = (~((lane & 16) ? k2 : k1)) & 127u, ch = lane & 15;
            const uint2 st = lds_u32x2(sbase + OG_SSTAT + r * 8);
            const uint4 xc = lds_u32x4(sbase + OG_XSLOT + (ch >> 3) * 16384 + r * 128 + (((ch ^ r) & 7) << 4));
            const uint4 c1 = lds_u32x4(sbase + OG_SCOL + 768 + ch * 16), sh = lds_u32x4(sbase + OG_SCOL + 1024 + ch * 16);
            const float inr = __uint_as_float(st.y);
            float* dst = reinterpret_cast<float*>(g_cand + (mt * 2 + (lane >> 4)) * 256 + nt * 16 + ch);
            st_tagged4(dst + 512, __uint_as_float(ln_mod2(xc.x, st.x, inr, c1.x, sh.x)), __uint_as_float(ln_mod2(xc.y, st.x, inr, c1.y, sh.y)),
                       __uint_as_float(ln_mod2(xc.z, st.x, inr, c1.z, sh.z)), __uint_as_float(ln_mod2(xc.w, st.x, inr, c1.w, sh.w)));
            st_tagged4(dst, __uint_as_float(xc.x), __uint_as_float(xc.y), __uint_as_float(xc.z), __uint_as_float(xc.w));
          }
    }
    mbar_wait(bar_sel, 0);
    const int sel0 = (int)lds_u32(sbase + OG_SMISC + 64), sel1 = (int)lds_u32(sbase + OG_SMISC + 68);
    mbar_wait(bar_out, 0);
    if ((sel0 >> 7) == mt || (sel1 >> 7) == mt) {
      #pragma unroll 2
      for (int i = 0; i < 16; i++) {
        const int r = i * 8 + (threadIdx.x >> 4), ch = threadIdx.x & 15;
        if (m0 + r != sel0 && m0 + r != sel1)
          *reinterpret_cast<uint4*>(out + (size_t)(m0 + r) * T_D + n0 + ch * 8) =
              lds_u32x4(sbase + OG_OSLOT + (ch >> 3) * 16384 + r * 128 + (((ch & 7) ^ (r & 7)) << 4));
      }
    } else if (threadIdx.x == 0) {
      tma_store_2d(tmOut, sbase + OG_OSLOT, n0, m0);
      tma_store_2d(tmOut, sbase + OG_OSLOT + 16384, n0 + 64, m0);
      bulk_commit();
    }
    if (blockIdx.x == 0 && threadIdx.x < 34) *reinterpret_cast<uint4*>(g_hcnt + 32 * (threadIdx.x >> 1) + 4 * (threadIdx.x & 1)) = make_uint4(0u, 0u, 0u, 0u);
    if (threadIdx.x < 64) g_modpart[blockIdx.x * 64 + threadIdx.x] = 0.f;
    {
      const int tk = blockIdx.x >> 6, c0 = (blockIdx.x & 63) * 16;
      const uint32_t gb2 = *reinterpret_cast<const uint32_t*>(g_col + (c0 >> 7) * 1536 + 512 + 768 + ((c0 & 127) + (threadIdx.x & 14)) * 2);
      const uint32_t* xp = reinterpret_cast<const uint32_t*>(g_cand + lds_u32(sbase + OG_SMISC + 72 + tk * 4) * 256) + ((c0 + (threadIdx.x & 14)) >> 1);
      uint32_t x2 = 0u;
      #pragma unroll 1
      for (unsigned int spin = 0; spin < (1u << 20) && __any_sync(0xffffffffu, x2 == 0u); spin++) asm volatile("ld.relaxed.gpu.global.u32 %0, [%1];" : "=r"(x2) : "l"(xp) : "memory");
      const float* src = g_ypart + (size_t)((threadIdx.x >> 2) * 2 + tk) * T_D + c0 + (threadIdx.x & 3) * 4;
      const bool four = threadIdx.x < (OG_MOE - 96) * 4;
      mbar_wait(bar_h2, 0);
      if (threadIdx.x == 0) hint_wait(CNT_Y, (uint32_t)OG_MOE);
      named_bar_sync(10, 128);
      float4 p0, p1, p2, p3;
      #pragma unroll 1
      for (unsigned int spin = 0; spin < (1u << 20); spin++) {
        p0 = ld_tagged4(src); p1 = ld_tagged4(src + 64 * T_D); p2 = ld_tagged4(src + 128 * T_D); p3 = ld_tagged4(four ? src + 192 * T_D : src);
        if (__all_sync(0xffffffffu, tagged4(p0) & tagged4(p1) & tagged4(p2) & tagged4(p3))) break;
      }
      if (four) { p2.x += p3.x; p2.y += p3.y; p2.z += p3.z; p2.w += p3.w; }
      p0.x = (p0.x + p1.x) + p2.x; p0.y = (p0.y + p1.y) + p2.y; p0.z = (p0.z + p1.z) + p2.z; p0.w = (p0.w + p1.w) + p2.w;
      #pragma unroll
      for (int o = 4; o <= 16; o <<= 1) {
        p0.x += __shfl_xor_sync(0xffffffffu, p0.x, o); p0.y += __shfl_xor_sync(0xffffffffu, p0.y, o);
        p0.z += __shfl_xor_sync(0xffffffffu, p0.z, o); p0.w += __shfl_xor_sync(0xffffffffu, p0.w, o);
      }
      if (lane < 4) sts_f32x4(sbase + OG_SFIN + (threadIdx.x >> 5) * 64 + lane * 16, p0.x, p0.y, p0.z, p0.w);
      named_bar_sync(10, 128);
      TL_MARK2(21, threadIdx.x == 0);
      if (threadIdx.x < 16) {
        const uint32_t ya = sbase + OG_SFIN + threadIdx.x * 4, rp = sbase + OG_SMISC + 192 + tk * 16;
        float y = (lds_f32(ya) + lds_f32(ya + 64)) + (lds_f32(ya + 128) + lds_f32(ya + 192));
        const float r = rbf((lds_f32(rp) + lds_f32(rp + 4)) + (lds_f32(rp + 8) + lds_f32(rp + 12)));
        const float rs = rbf(sigmoid_f(r));
        const uint32_t h2p = lds_u32(sbase + OG_SH2 + tk * 2048 + (c0 + (threadIdx.x & 14)) * 2);
        const float fh = (lane & 1) ? bfhi(h2p) : bflo(h2p);
        y = rbf(y);
        y = rbf(y * rs);
        const float upd = rbf(rbf(fh * 0.0f) + y);
        out[(size_t)(tk ? sel1 : sel0) * T_D + c0 + threadIdx.x] =
            __float2bfloat16_rn(((lane & 1) ? bfhi(x2) : bflo(x2)) + rbf(((lane & 1) ? bfhi(gb2) : bflo(gb2)) * rbf(fh + upd)));
      }
      if (threadIdx.x == 0) bulk_wait_read<0>();
    }
    TL_END(4, threadIdx.x == 0);
}

__device__ __forceinline__ void tail_consumer(uint32_t sbase, int cwg, const bf16* __restrict__ w_r, const bf16* __restrict__ w_gate, const bf16* __restrict__ w_up) {
    TAIL_SETUP
    const int tid = threadIdx.x & 127, t2 = threadIdx.x - 128;
    const int warp = tid >> 5, lane = tid & 31, w8 = t2 >> 5;
    const uint32_t dbase = (sbase & 0x3FFFFu) >> 4;
    const uint32_t a_base = dbase + ((cwg * 8192) >> 4) + (1u << 16);
    const uint32_t b_base = dbase + (16384 >> 4) + (512u << 16);
    TL_MARK2(25, threadIdx.x == 128);
    const uint64_t pol = policy_evict_first();
    const bf16* pw = ((lane & 16) ? w_up : w_gate) + (size_t)(w8 * 128 + (lane & 3) * 4) * T_F + (has_moe ? blockIdx.x : 0) * 32 + ((lane >> 2) & 3) * 8;
    uint4 wv[32];
    float acc[64];
    if (has_moe) mbar_wait(bar_full + 272, 0);
    #pragma unroll
    for (int i = 0; i < 8; i++) {
      uint4 pre = lds_u32x4(sbase + OG_PSLOT + w8 * 2048 + (i >> 2) * 16384 + (i & 3) * 512 + lane * 16);
      if (!has_moe) pre = make_uint4(0u, 0u, 0u, 0u);
      acc[8 * i] = bflo(pre.x); acc[8 * i + 1] = bfhi(pre.x); acc[8 * i + 2] = bflo(pre.y); acc[8 * i + 3] = bfhi(pre.y);
      acc[8 * i + 4] = bflo(pre.z); acc[8 * i + 5] = bfhi(pre.z); acc[8 * i + 6] = bflo(pre.w); acc[8 * i + 7] = bfhi(pre.w);
    }
    __syncwarp();
    if (lane == 0) mbar_arrive(bar_full + 304);
    {
      uint32_t stage = OG_POS % OG_ST, phase = (OG_POS / OG_ST) & 1, prev = 12;
      int kb = 0;
      #pragma unroll
      for (int g = 0; g <= OG_NG; g++) {
        const int end = g == OG_NG ? OG_NKB : LD_FIRST + g * OG_GRP + LD_STAG * cwg;
        #pragma unroll 1
        do {
          mbar_wait(bar_full + 8 * stage, phase);
          const uint32_t a_lo = a_base + stage * (OG_STAGE >> 4), b_lo = b_base + stage * (OG_STAGE >> 4);
          wgmma_fence();
          wgmma_m64n128k16_ss_tb<0, 0>(acc, a_lo, b_lo, 1);
          wgmma_m64n128k16_ss_tb<2, 128>(acc, a_lo, b_lo, 1);
          wgmma_m64n128k16_ss_tb<4, 256>(acc, a_lo, b_lo, 1);
          wgmma_m64n128k16_ss_tb<6, 384>(acc, a_lo, b_lo, 1);
          wgmma_commit();
          wgmma_wait<1>();
          if (tid == 0) mbar_arrive(bar_empty + 8 * prev);
          prev = stage;
          if (++stage == OG_ST) { stage = 0; phase ^= 1; }
        } while (++kb < end);
        #pragma unroll
        for (int j = 4 * g; j < 4 * g + 4 && j < 32; j++) wv[j] = ldg_stream_v4(pw + (size_t)(16 * (j >> 2) + (j & 3)) * T_F, pol);
      }
    }
    mbar_wait(bar_col, 0);
    mbar_wait(bar_full + 8 * (OG_XPOS % OG_ST), (OG_XPOS / OG_ST) & 1);
    if (__builtin_expect(!has_moe, 0)) {
      mbar_wait(bar_full + 272, 0);
      #pragma unroll
      for (int i = 0; i < 8; i++) wv[i] = lds_u32x4(sbase + OG_PSLOT + w8 * 2048 + (i >> 2) * 16384 + (i & 3) * 512 + lane * 16);
    }
    wgmma_wait<0>();
    fence_regs(acc);
    if (__builtin_expect(!has_moe, 0)) {
      #pragma unroll
      for (int i = 0; i < 8; i++) {
        acc[8 * i] += bflo(wv[i].x); acc[8 * i + 1] += bfhi(wv[i].x); acc[8 * i + 2] += bflo(wv[i].y); acc[8 * i + 3] += bfhi(wv[i].y);
        acc[8 * i + 4] += bflo(wv[i].z); acc[8 * i + 5] += bfhi(wv[i].z); acc[8 * i + 6] += bflo(wv[i].w); acc[8 * i + 7] += bfhi(wv[i].w);
      }
    }
    if (tid == 0) mbar_arrive(bar_end);
    TL_MARK2(9, lane == 0);
    const int q2 = 2 * (lane & 3);
    const uint32_t frag = (64 * cwg + 16 * warp + (lane & 7) + 8 * ((lane >> 3) & 1)) * 128;
    const int fsw = lane & 7, fhi = lane >> 4;
    {
      float dl[4] = {0.f, 0.f, 0.f, 0.f}, da[4] = {0.f, 0.f, 0.f, 0.f}, db[4] = {0.f, 0.f, 0.f, 0.f};
      const uint32_t tb = sbase + OG_SCOL + (lane & 8) * 32 + (lane & 3) * 8, g = lane >> 2;
      const uint32_t msk = (g == 1 || g == 2) ? 0xffffffffu : 0u, one = g == 0 ? 0x3F803F80u : 0u;
      #pragma unroll
      for (int J = 0; J < 16; J += 2) {
        const uint32_t ad = sbase + OG_XSLOT + (J >> 3) * 16384 + frag + ((((J & 7) + fhi) ^ fsw) << 4);
        uint32_t xr[4];
        ldmatrix_x4(ad, xr[0], xr[1], xr[2], xr[3]);
        const uint2 cw = lds_u32x2(tb + J * 16);
        #pragma unroll
        for (int h = 0; h < 2; h++) {
          const uint32_t ga = lds_u32(sbase + OG_SCOL + 512 + (8 * (J + h) + q2) * 2);
          xr[2 * h] = badd2(xr[2 * h], bmul2(ga, pack_bf16(acc[4 * (J + h)], acc[4 * (J + h) + 1])));
          xr[2 * h + 1] = badd2(xr[2 * h + 1], bmul2(ga, pack_bf16(acc[4 * (J + h) + 2], acc[4 * (J + h) + 3])));
        }
        stmatrix_x4(ad, xr[0], xr[1], xr[2], xr[3]);
        mma_bf16(dl, xr[0], xr[1], xr[2], xr[3], (cw.x & msk) | one, (cw.y & msk) | one);
        mma_bf16(da, xr[0], xr[1], xr[2], xr[3], xr[0], xr[2]);
        mma_bf16(db, xr[0], xr[1], xr[2], xr[3], xr[1], xr[3]);
      }
      {
        const int dsrc = (lane & ~3) + (g >> 1);
        const float qa = __shfl_sync(0xffffffffu, (g & 1) ? da[1] : da[0], dsrc), qb = __shfl_sync(0xffffffffu, (g & 1) ? db[3] : db[2], dsrc);
        const float e0 = __shfl_xor_sync(0xffffffffu, (lane & 1) ? dl[0] : dl[2], 1), e1 = __shfl_xor_sync(0xffffffffu, dl[3], 1);
        if ((lane & 3) < 2) {
          const bool hi = lane & 1;
          st_tagged4(reinterpret_cast<float*>(g_part1 + ((mt * 8 + w8) * 8 + nt) * 16 + g + (hi ? 8 : 0)),
                     hi ? e0 : dl[0], hi ? qb : qa, hi ? e1 + dl[2] : dl[1] + e0, 1.0f);
        }
      }
    }
    TL_MARK2(10, lane == 0);
    const uint4 wrv = ldg_nc_v4(w_r + tid * 8);
    uint4 wd[16];
    if (has_moe) mbar_wait(bar_wd, 0);
    #pragma unroll
    for (int i = 0; i < 16; i++) wd[i] = lds_u32x4(sbase + OG_SWD + w8 * 8192 + (i >> 3) * 4096 + (i & 6) * 512 + (i & 1) * 128 + (lane & 3) * 256 + (((lane >> 2) ^ (2 * (lane & 3) + (i & 1))) << 4));
    {
      const float* src = reinterpret_cast<const float*>(g_part1 + ((mt * 8 + w8) * 8 + (lane & 1) * 4) * 16 + (lane >> 1));
      float4 v, v1, v2, v3;
      #pragma unroll 1
      for (unsigned int spin = 0; spin < (1u << 22); spin++) {
        v = ld_tagged4(src); v1 = ld_tagged4(src + 64); v2 = ld_tagged4(src + 128); v3 = ld_tagged4(src + 192);
        if (__all_sync(0xffffffffu, tagged4(v) & tagged4(v1) & tagged4(v2) & tagged4(v3))) break;
        __nanosleep(100);
      }
      __syncwarp();
      TL_MARK2(26, lane == 0);
      v.x = (v.x + v1.x) + (v2.x + v3.x); v.y = (v.y + v1.y) + (v2.y + v3.y); v.z = (v.z + v1.z) + (v2.z + v3.z);
      v.x += __shfl_xor_sync(0xffffffffu, v.x, 1); v.y += __shfl_xor_sync(0xffffffffu, v.y, 1); v.z += __shfl_xor_sync(0xffffffffu, v.z, 1);
      const float mean = v.x * (1.0f / T_D);
      const float var = fmaxf(fmaf(-mean, mean, v.y * (1.0f / T_D)), 0.f);
      const uint32_t mb2 = pack_bf16(mean, mean);
      const float inv = rcp_approx(rbf(sqrt_approx(rbf(rbf(var) + 1e-05f))));
      {
        const float2 sc = lds_f32x2(sbase + OG_SMISC);
        const uint32_t key = rank_key(rbf(fmaf(fmaf(-bflo(mb2), sc.x, v.z), inv, sc.y)), m0 + 16 * w8 + (lane >> 1));
        mbar_wait(bar_end, 0);
        if (lane & 1) sts_u32(sbase + OG_SSTAT + 1024 + (16 * w8 + (lane >> 1)) * 4, key);
        else sts_u32x2(sbase + OG_SSTAT + (16 * w8 + (lane >> 1)) * 8, mb2, __float_as_uint(inv));
        __syncwarp();
        if (lane == 0) mbar_arrive(bar_key);
      }
      const uint32_t ih = pack_bf16(inv, inv), il = pack_bf16(inv - bflo(ih), inv - bflo(ih));
      const uint32_t mba = __shfl_sync(0xffffffffu, mb2, 2 * (lane >> 2)), mbb = __shfl_sync(0xffffffffu, mb2, 2 * (lane >> 2) + 16);
      const uint32_t iha = __shfl_sync(0xffffffffu, ih, 2 * (lane >> 2)), ihb = __shfl_sync(0xffffffffu, ih, 2 * (lane >> 2) + 16);
      const uint32_t ila = __shfl_sync(0xffffffffu, il, 2 * (lane >> 2)), ilb = __shfl_sync(0xffffffffu, il, 2 * (lane >> 2) + 16);
      #pragma unroll 2
      for (int J = 0; J < 16; J += 2) {
        const uint32_t off = (J >> 3) * 16384 + frag + ((((J & 7) + fhi) ^ fsw) << 4);
        uint32_t xr[4];
        ldmatrix_x4(sbase + OG_XSLOT + off, xr[0], xr[1], xr[2], xr[3]);
        #pragma unroll
        for (int h = 0; h < 2; h++) {
          const uint32_t ca = sbase + OG_SCOL + 512 + (8 * (J + h) + q2) * 2;
          const uint32_t c1 = lds_u32(ca + 256), sh = lds_u32(ca + 512), gb = lds_u32(ca + 768);
          xr[2 * h] = out2(xr[2 * h], mba, iha, ila, c1, sh, gb);
          xr[2 * h + 1] = out2(xr[2 * h + 1], mbb, ihb, ilb, c1, sh, gb);
        }
        stmatrix_x4(sbase + OG_OSLOT + off, xr[0], xr[1], xr[2], xr[3]);
      }
      fence_proxy_async();
      __syncwarp();
      if (lane == 0) mbar_arrive(bar_out);
      TL_MARK2(24, lane == 0);
    }
    {
      mbar_wait(bar_sel, 0);
      TL_MARK2(12, lane == 0);
      const float* src = reinterpret_cast<const float*>(g_cand + lds_u32(sbase + OG_SMISC + 72 + cwg * 4) * 256 + 128 + tid);
      float4 hf;
      #pragma unroll 1
      for (unsigned int spin = 0; spin < (1u << 20); spin++) { hf = ld_tagged4(src); if (__all_sync(0xffffffffu, tagged4(hf))) break; }
      const uint4 hv = make_uint4(__float_as_uint(hf.x), __float_as_uint(hf.y), __float_as_uint(hf.z), __float_as_uint(hf.w));
      sts_u32x4(sbase + OG_SH2 + t2 * 16, hv.x, hv.y, hv.z, hv.w);
      float v[8], wr[8];
      unpack8(hv, v); unpack8(wrv, wr);
      float r = 0.f;
      #pragma unroll
      for (int i = 0; i < 8; i++) r = fmaf(v[i], wr[i], r);
      #pragma unroll
      for (int o = 16; o > 0; o >>= 1) r += __shfl_xor_sync(0xffffffffu, r, o);
      if (lane == 0) sts_f32(sbase + OG_SMISC + 192 + w8 * 4, r);
    }
    named_bar_sync(9, 256);
    if (t2 == 0) mbar_arrive(bar_h2);
    TL_MARK2(13, lane == 0);
    if (has_moe) {
      const GemvSel sel = gemv_sel(lane);
      {
        float d[4][4];
        #pragma unroll
        for (int c = 0; c < 4; c++) { d[c][0] = 0.f; d[c][1] = 0.f; d[c][2] = 0.f; d[c][3] = 0.f; }
        #pragma unroll
        for (int st = 0; st < 8; st++) {
          const uint2 hb = lds_u32x2(sbase + OG_SH2 + ((lane >> 2) & 1) * 2048 + (w8 * 128 + st * 16 + (lane & 3) * 4) * 2);
          #pragma unroll
          for (int j = 0; j < 4; j++) mma_bf16(d[j], wv[4 * st + j].x, wv[4 * st + j].y, wv[4 * st + j].z, wv[4 * st + j].w, GEMV_B0(j, hb, sel), GEMV_B1(j, hb, sel));
        }
        #pragma unroll
        for (int e = 0; e < 4; e++) d[0][e] = (d[0][e] + d[1][e]) + (d[2][e] + d[3][e]);
        const float4 r = gemv_out(d[0], lane);
        sts_f32x4(sbase + OG_SRED + w8 * 512 + (((lane >> 4) * 2 + (lane & 1)) * 32 + ((lane >> 2) & 3) * 8 + (lane & 2) * 2) * 4, r.x, r.y, r.z, r.w);
      }
      named_bar_sync(9, 256);
      if (t2 < 64) {
        float gp[8], up[8];
        #pragma unroll
        for (int w = 0; w < 8; w++) { gp[w] = lds_f32(sbase + OG_SRED + w * 512 + t2 * 4); up[w] = lds_f32(sbase + OG_SRED + w * 512 + 256 + t2 * 4); }
        const float gs = ((gp[0] + gp[1]) + (gp[2] + gp[3])) + ((gp[4] + gp[5]) + (gp[6] + gp[7]));
        const float us = ((up[0] + up[1]) + (up[2] + up[3])) + ((up[4] + up[5]) + (up[6] + up[7]));
        asm volatile("st.shared.u16 [%0], %1;" :: "r"(sbase + OG_SGU + ((t2 & ~15) + ((t2 >> 1) & 3) * 4 + ((t2 >> 3) & 1) * 2 + (t2 & 1)) * 2), "h"((uint16_t)pack_bf16(silu_bf(rbf(gs)) * rbf(us), 0.f)) : "memory");
      }
      named_bar_sync(9, 256);
      TL_MARK2(20, threadIdx.x == 128);
      float d[4][4];
      #pragma unroll
      for (int c = 0; c < 4; c++) { d[c][0] = 0.f; d[c][1] = 0.f; d[c][2] = 0.f; d[c][3] = 0.f; }
      #pragma unroll
      for (int st = 0; st < 2; st++) {
        const uint2 g = lds_u32x2(sbase + OG_SGU + ((lane >> 2) & 1) * 64 + st * 32 + (lane & 3) * 8);
        #pragma unroll
        for (int j = 0; j < 4; j++) {
          const uint32_t b0 = GEMV_B0(j, g, sel), b1 = GEMV_B1(j, g, sel);
          mma_bf16(d[j & 1], wd[4 * st + j].x, wd[4 * st + j].y, wd[4 * st + j].z, wd[4 * st + j].w, b0, b1);
          mma_bf16(d[2 + (j & 1)], wd[8 + 4 * st + j].x, wd[8 + 4 * st + j].y, wd[8 + 4 * st + j].z, wd[8 + 4 * st + j].w, b0, b1);
        }
      }
      #pragma unroll
      for (int e = 0; e < 4; e++) { d[0][e] += d[1][e]; d[2][e] += d[3][e]; }
      const float4 y0 = gemv_out(d[0], lane), y1 = gemv_out(d[2], lane);
      float* yp = g_ypart + (size_t)(blockIdx.x * 2 + (lane & 1)) * T_D + w8 * 128 + (lane >> 2) * 8 + (lane & 2) * 2;
      st_tagged4(yp, y0.x, y0.y, y0.z, y0.w);
      st_tagged4(yp + 64, y1.x, y1.y, y1.z, y1.w);
      named_bar_sync(9, 256);
      if (t2 == 0) hint_arrive(CNT_Y);
    }
    TL_MARK2(14, threadIdx.x == 128);
    TL_CLK(4, 1, threadIdx.x == 128);
}

#define OG_JOBS2 (16 - OG_JOBS)
__device__ __forceinline__ int help_njobs() { return blockIdx.x < 128 ? OG_JOBS : OG_JOBS2; }
__device__ __forceinline__ int help_job(int i) {
  const int step = i + (blockIdx.x < 128 ? 0 : OG_JOBS);
  return (step & ~3) * 4 + (blockIdx.x & 3) * 4 + (step & 3);
}
__device__ __noinline__ void store_warp(uint32_t sbase, const CUtensorMap* tmO, int item0, int n_items) {
  if (elect_one()) {
    const uint32_t bars = sbase + AT_SBAR, b_q0 = bars + 80, b_ob = bars + 96, b_ordy = bars + 104, b_acq = bars + 264;
    const unsigned int* cnt = &g_hcnt[32 * (1 + OG_MT(blockIdx.x)) + 2];
    #pragma unroll 1
    for (int q = 0; q < 4 * n_items; q++) {
      const int item = item0 + (q >> 2) * 128, h = (q >> 1) & 1, w = q & 1;
      const bool last = (q >> 2) == n_items - 1;
      if (q == 4 * n_items - 4) { mbar_wait(bars + 288, 0); red_release_add(&g_hcnt[1], 1u); }
      mbar_wait(b_ordy + 8 * (q & 3), q >> 2);
      store_o(tmO, (h ? (last ? sbase + AT_SQ + 32768 : sbase + 2 * 32768) : sbase + AT_SQ) + w * 8192, (item >> 4) * 2 + h, (item & 15) * 128 + w * 64);
      if (w) {
        bulk_wait_read<0>();
        mbar_arrive(h ? b_ob : b_q0);
        bulk_wait<0>();
        fence_proxy_async_global();
        red_release_add(&g_hcnt[32 * (1 + (item & 15)) + 2 + (item >> 7)], h ? 1u : 256u);
        if (blockIdx.x < 128 && q == (n_items == 2 ? 5 : 3)) { spin_until(cnt, 0x808u); mbar_arrive(b_acq); }
      }
    }
    if (n_items == 1) {
      #pragma unroll 1
      for (int i = 0; i < help_njobs(); i++) {
        mbar_wait(b_acq + 16, i & 1);
        red_release_add(&g_hcnt[32 * (1 + (help_job(i) >> 2)) + 4 + (help_job(i) & 3)], 1u);
        if (i == PRE_X - 1) { spin_until(&g_hcnt[1], 132u); mbar_arrive(b_acq + 32); }
      }
    }
    if (blockIdx.x < 128) { spin_until(&g_hcnt[0], 128u); spin_until(cnt + 1, 0x808u); mbar_arrive(b_acq); }
  }
}

__global__ void __launch_bounds__(384, 1)
fused_kernel(const __grid_constant__ CUtensorMap tmH, const __grid_constant__ CUtensorMap tmW, const __grid_constant__ CUtensorMap tmK,
            const __grid_constant__ CUtensorMap tmV, const __grid_constant__ CUtensorMap tmO, const __grid_constant__ CUtensorMap tmOl, const __grid_constant__ CUtensorMap tmWo,
            const __grid_constant__ CUtensorMap tmX, const __grid_constant__ CUtensorMap tmOut, uint32_t zero,
            const uint8_t* __restrict__ pf_wo, const bf16* __restrict__ kc, const bf16* __restrict__ vc,
            const bf16* __restrict__ x, const bf16* __restrict__ cvec, const bf16* __restrict__ w_mod, const bf16* __restrict__ w_r,
            const bf16* __restrict__ w_gate, const bf16* __restrict__ w_up, const bf16* __restrict__ w_down, bf16* __restrict__ out)
{
  extern __shared__ __align__(1024) uint8_t smem_raw[];
  const uint32_t sbase = smem_u32(smem_raw);
  const uint32_t bars = sbase + AT_SBAR;
  const uint32_t b_full = bars, b_empty = bars + 40;
  const uint32_t b_q0 = bars + 80, b_q1 = bars + 88;
  const uint32_t b_ob = bars + 96;
  const uint32_t b_ordy = bars + 104;
  const uint32_t b_pin = bars + 136;
  const uint32_t b_head = bars + 144;
  const uint32_t b_go = bars + 152;
  const uint32_t b_x = bars + 160;
  const int wg = __shfl_sync(0xffffffffu, threadIdx.x >> 7, 0);
  const bool single = blockIdx.x >= AT_NFULL;
  const int item0 = __shfl_sync(0xffffffffu, blockIdx.x < 128 ? (int)blockIdx.x : (int)blockIdx.x + 124, 0), n_items = __shfl_sync(0xffffffffu, single ? 1 : 2, 0);
  TL_START(3);
  if (threadIdx.x == 0) {
    if (sbase & 1023u) __trap();
    for (int i = 0; i < 5; i++) { mbar_init(b_full + 8 * i, 1); mbar_init(b_empty + 8 * i, 2); }
    mbar_init(b_q0, 1); mbar_init(b_q1, 8); mbar_init(b_ob, 1);
    for (int i = 0; i < 4; i++) mbar_init(b_ordy + 8 * i, 4);
    mbar_init(b_pin, 1); mbar_init(b_head, blockIdx.x < 128 ? 8 : 1); mbar_init(b_go, 1); mbar_init(b_x, 1);
    mbar_init(bars + 168, 1); mbar_init(bars + 176, 1); mbar_init(bars + 184, 8); mbar_init(bars + 192, 2);
    mbar_init(bars + 200, 8); mbar_init(bars + 208, 1); mbar_init(bars + 216, 1); mbar_init(bars + 264, 1); mbar_init(bars + 272, 1); mbar_init(bars + 280, 8); mbar_init(bars + 288, 1); mbar_init(bars + 296, 1); mbar_init(bars + 304, 8);
    fence_mbar_init();
  }

  if (wg == 0) {
    reg_dealloc<AT_PREG>();
    if (threadIdx.x < 32) { __syncwarp(); named_bar_arrive(6, 384); }
    if (threadIdx.x >= 64) {
      named_bar_sync(6, 384);
      if (blockIdx.x < 128 && threadIdx.x >= 96) {
        named_bar_sync(8, 288);
        if (threadIdx.x == 96) red_release_add(&g_hcnt[32 * (1 + (blockIdx.x >> 3)) + 1], 1u);
      }
      if (blockIdx.x < 128) {
        mbar_wait(MOD_AT, 0);
        mod_rest(sbase + OG_SCOL, b_q1, threadIdx.x - 64, cvec, w_mod, w_r);
      }
    } else if (threadIdx.x >= 32) {
      named_bar_sync(6, 384);
      store_warp(sbase, &tmO, item0, n_items);
      __syncwarp();
    } else {
     if (elect_one()) {
      const uint64_t pol = policy_evict_first();
      prefetch_tmap(&tmW); prefetch_tmap(&tmH); prefetch_tmap(&tmWo); prefetch_tmap(&tmOl);
      uint32_t slot = 0, ph = 1;
      #pragma unroll 1
      for (int it = 0; it < n_items; it++) {
        const int item = item0 + it * 128, hp = item >> 4, qt = item & 15;
        const bool first = it == 0;
        #pragma unroll 1
        for (int j = 0; j < T_D / 64; j++) {
          const uint32_t sl = ring_slot(qp_pos(j, it)), fb = b_full + 8 * sl;
          mbar_wait(b_empty + 8 * sl, ring_par(qp_pos(j, it)) ^ ((j >> 2) & 1) ^ 1);
          mbar_expect_tx(fb, 49152);
          #pragma unroll 1
          for (int c = 0; c < 4; c++) tma_load_2d_hint(sbase + sl * 32768 + c * 8192, &tmW, hp * 256 + c * 64, j * 64, fb, pol);
          if (first && j < PRE_B) {
            if (j == PRE_B - 1) {
              spin_until(&g_hcnt[32 * (1 + qt)], 8u);
              TL_MARK2(16, true);
              fence_proxy_async_global();
              TL_MARK2(17, true);
              #pragma unroll 1
              for (int i = 0; i < PRE_B; i++) tma_load_2d(sbase + AT_SQ + i * 16384, &tmH, i * 64, qt * 128, b_full + 8 * i);
              mbar_arrive(b_go);
            }
          } else {
            if (first && j == 3) mbar_wait(b_head, 0);
            if (first && j == 4 * H_SPLIT) { spin_until(&g_hcnt[32 * (1 + qt) + 1], 8u); fence_proxy_async_global(); }
            if (!first && (j == 0 || j == 2)) mbar_wait(j ? b_q1 : b_q0, 0);
            tma_load_2d_hint(sbase + AT_SQ + (j & 3) * 16384, &tmH, j * 64, qt * 128, fb, first ? pol_normal() : pol);
          }
        }
        #pragma unroll 1
        for (int j = 0; j < 4 * AT_NBLK; j++) {
          const bool isv = (j > 0 && !(j & 1)) || j == 4 * AT_NBLK - 1;
          const int row = hp * 2 * T_SEQ + (isv ? (j - 1) >> 1 : (j + 1) >> 1) * 128;
          const uint32_t fb = b_full + 8 * slot;
          mbar_wait(b_empty + 8 * slot, ph);
          if (!first && j == 3) mbar_wait(b_ob, 0);
          if (j == 4 && it == n_items - 1) mbar_arrive(bars + 288);
          mbar_expect_tx(fb, 32768);
          tma_load_2d_hint(sbase + slot * 32768, isv ? &tmV : &tmK, 0, row, fb, pol);
          tma_load_2d_hint(sbase + slot * 32768 + 16384, isv ? &tmV : &tmK, 64, row, fb, pol);
          if (it == 1 && isv && j >= 2 * WO_LATE && j < 2 * WO_LATE + 32 && blockIdx.x < 64)
            l2_prefetch_bulk(pf_wo + (size_t)blockIdx.x * 131072 + ((j >> 1) - WO_LATE) * 8192, 8192);
          if (++slot == 5) { slot = 0; ph ^= 1; }
        }
      }
      if (__builtin_expect(single, 0)) {
        #pragma unroll 1
        for (int i = 0; i < 4; i++) spin_until(&g_hcnt[32 * (1 + 4 * i + (blockIdx.x & 3)) + 2], 0x800u);
        fence_proxy_async_global();
        const int nj = help_njobs() * OG_PRE;
        int ji = 0, job = help_job(0), kk = 0;
        #pragma unroll 1
        for (int j = 0; j < nj; j++) {
          const uint32_t sl = ring_slot(qp_pos(j, 1)), fb = b_full + 8 * sl;
          mbar_wait(b_empty + 8 * sl, ring_par(qp_pos(j, 1)) ^ ((j >> 2) & 1) ^ 1);
          mbar_expect_tx(fb, 49152);
          tma_load_3d_hint(sbase + sl * 32768, &tmWo, pre_kb(kk) * 64, (job & 3) * 4, fb, HPOL_B);
          tma_load_3d_hint(sbase + sl * 32768 + 16384, &tmWo, pre_kb(kk) * 64, (job & 3) * 4 + 2, fb, HPOL_B);
          if (j == 0 || j == 2) mbar_wait(j ? b_ob : b_q0, 0);
          tma_load_2d_hint(sbase + AT_SQ + (j & 3) * 16384, HMAP_A, pre_kb(kk) * 64, (job >> 2) * 128, fb, HPOL_A);
          if (++kk == OG_PRE) { kk = 0; job = help_job(++ji); }
        }
      }
      if (blockIdx.x < 128) {
        if (single) mbar_wait(b_x, 1);
        tail_producer(sbase, 0, pol, &tmOl, &tmWo, &tmX);
      }
     }
    }
    named_bar_sync(12 + (threadIdx.x >> 5), 32);
    if (blockIdx.x < 128) tail_exchange(sbase, &tmOut, w_down, out);
  } else {
    if (blockIdx.x < 128) head_phase(sbase + AT_SQ + 49152, sbase + 4 * 32768, b_x, b_go, b_head, threadIdx.x - 128, zero, x, cvec, w_mod);
    else { named_bar_sync(6, 384); if (threadIdx.x == 128) mbar_arrive(b_head); }
    TL_MARK2(0, threadIdx.x == 128);
    reg_alloc<AT_CREG>();
    const int cwg = wg - 1;
    const int tid = threadIdx.x & 127;
    const int warp = tid >> 5, lane = tid & 31;
    const uint32_t dbase = (sbase & 0x3FFFFu) >> 4;
    const uint32_t k_base = dbase + (1u << 16);
    const uint32_t v_base = dbase + (1024u << 16);
    const uint32_t w_base = dbase + (512u << 16);
    const uint32_t q_lo = dbase + ((AT_SQ + cwg * 8192) >> 4) + (1u << 16);
    const uint32_t frag = cwg * 8192 + (16 * warp + (lane & 7) + 8 * ((lane >> 3) & 1)) * 128;
    if (cwg == 1) named_bar_arrive(1, 256);
    bool raw = false;
    #pragma unroll 1
    for (int it = 0; it < n_items; it++) {
      const int item = item0 + it * 128, hp = item >> 4;
      const bool more = it + 1 < n_items;
      constexpr int nkb = T_D / 64;
      const int ta = __shfl_sync(0xffffffffu, 4 * it, 0);
      float acc[128];
      {
        FS(2 * it, 0);
        #pragma unroll
        for (int i = 0; i < 128; i++) acc[i] = 0.f;
        fence_regs(acc);
        #pragma unroll 1
        for (int j = 0; j < nkb; j++) {
          const uint32_t slot = ring_slot(qp_pos(j, ta >> 2));
          mbar_wait(b_full + 8 * slot, ring_par(qp_pos(j, ta >> 2)) ^ ((j >> 2) & 1));
          if (QP_STAG > 0 && cwg == 1 && j == nkb - QP_STAG) named_bar_sync(7, 256);
          const uint32_t a_lo = q_lo + (j & 3) * 1024, b_lo = w_base + slot * 2048;
          wgmma_fence();
          wgmma_m64n256k16_ss_tb<0, 0>(acc, a_lo, b_lo, 1);
          wgmma_m64n256k16_ss_tb<2, 128>(acc, a_lo, b_lo, 1);
          wgmma_m64n256k16_ss_tb<4, 256>(acc, a_lo, b_lo, 1);
          wgmma_m64n256k16_ss_tb<6, 384>(acc, a_lo, b_lo, 1);
          wgmma_commit();
          if (QP_STAG > 0 && cwg == 0 && j == nkb - 1) named_bar_arrive(7, 256);
          if (j > 0) {
            wgmma_wait<1>();
            if (tid == 0) mbar_arrive(b_empty + 8 * ring_slot(qp_pos(j - 1, ta >> 2)));
          }
        }
        wgmma_wait<0>();
        fence_regs(acc);
        FS(2 * it, 1);
        TL_MARK2(29, threadIdx.x == 256 && it == 0);
        if (tid == 0) mbar_arrive(b_empty + 24);
      }
      float o[64], s[64];
      uint32_t p[32], q[32];
      #pragma unroll
      for (int i = 0; i < 32; i++) q[i] = pack_bf16(acc[2 * i] * AT_C, acc[2 * i + 1] * AT_C);
      zero_regs(s);
      const uint32_t sq = sbase + AT_SQ + cwg * 8192;
      const bool last_wg1 = cwg == 1 && !more;
      float mc0, mc1, al0 = 1.0f, al1 = 1.0f, l0 = 0.f, l1 = 0.f, lp0 = 0.f, lp1 = 0.f;
      bool redo0 = false;
      FS(2 * it, 2);
      mbar_wait(b_full + 8 * ring_slot(ta), ring_par(ta));
      named_bar_sync(1 + cwg, 256);
      FS(2 * it, 3);
      issue_qk(s, q, k_base + ring_slot(ta) * 2048);
      named_bar_arrive(1 + (cwg ^ 1), 256);
      bool ready = mbar_test(b_full + 8 * ring_slot(ta + 1), ring_par(ta + 1)) & mbar_test(b_full + 8 * ring_slot(ta + 2), ring_par(ta + 2));
      stage_q<16>(acc, AT_C, sbase + AT_SQ + frag, lane);
      wgmma_wait<0>();
      fence_regs(s);
      if (tid == 0) mbar_arrive(b_empty + 8 * ring_slot(ta));
      mc0 = 0.f; mc1 = 0.f;
      if (!raw) {
        raw = softmax_mode(s, mc0, mc1);
        if (__builtin_expect(!raw, 0)) softmax_sub(s, mc0, mc1);
      }
      softmax_exp<0, 64>(s);
      #pragma unroll
      for (int J = 0; J < 16; J += 2)
        stmatrix_x4(sbase + AT_SQ + frag + (J >> 3) * 16384 + ((((J & 7) + (lane >> 4)) ^ (lane & 7)) << 4), q[2 * J], q[2 * J + 1], q[2 * J + 2], q[2 * J + 3]);
      pack_p(p, s);
      zero_regs(o);
      FS(2 * it, 4);
      uint32_t ks = ring_slot(ta + 1), vs = ring_slot(ta + 2), kp = ring_par(ta + 1), vp = ring_par(ta + 2);
      auto finish_head = [&]() {
        FS(2 * it, 5);
        redo0 = finish_l(lp0, lp1);
        if (!redo0) {
          stage_o(o, lp0, lp1, sbase + AT_SQ + frag, lane);
          fence_proxy_async();
          __syncwarp();
          if (lane == 0) mbar_arrive(b_ordy + 8 * cwg);
        }
        FS(2 * it + 1, 4);
      };
      if (!ready) { mbar_wait(b_full + 8 * ks, kp); mbar_wait(b_full + 8 * vs, vp); }
      #pragma unroll 1
      for (int n = 1; n < 2 * AT_NBLK; n++) {
        named_bar_sync(1 + cwg, 256);
        issue_qk(s, q, k_base + ks * 2048);
        if (n == AT_NBLK + 1) finish_head();
        issue_pv(o, p, v_base + vs * 2048, (n & 15) != 1);
        if (!(last_wg1 && n == 2 * AT_NBLK - 1)) named_bar_arrive(1 + (cwg ^ 1), 256);
        wgmma_wait<1>();
        fence_regs(s);
        if (tid == 0) mbar_arrive(b_empty + 8 * ks);
        if (__builtin_expect(!raw || (n + 1) >> 1 == AT_NBLK / 2, 0)) {
          if (n == AT_NBLK - 1) {
            #pragma unroll
            for (int J = 0; J < 16; J += 2)
              ldmatrix_x4(sbase + AT_SQ + 32768 + frag + (J >> 3) * 16384 + ((((J & 7) + (lane >> 4)) ^ (lane & 7)) << 4), q[2 * J], q[2 * J + 1], q[2 * J + 2], q[2 * J + 3]);
          }
          if (!raw) {
            const float m0 = mc0, m1 = mc1;
            const bool ok = softmax_mode(s, mc0, mc1);
            if (n == AT_NBLK) raw = ok;
            else {
              mc0 = mc0 - AT_HEAD > m0 ? mc0 : m0; mc1 = mc1 - AT_HEAD > m1 ? mc1 : m1;
              al0 = ex2_approx(m0 - mc0); al1 = ex2_approx(m1 - mc1);
            }
            if (!raw) softmax_sub(s, mc0, mc1);
          }
        }
        softmax_exp<0, AT_SPLIT>(s);
        add_rowsum(p, l0, l1);
        if (tid == 0) {
          uint32_t dep = zero & __float_as_uint(l0) & __float_as_uint(l1);
          #pragma unroll
          for (int i = AT_SPLIT - AT_PIN - PINB; i < AT_SPLIT - PINB; i += 2) dep &= __float_as_uint(s[i]) & __float_as_uint(s[i + 1]);
          mbar_arrive(b_pin + dep);
        }
        wgmma_wait<0>();
        fence_regs(o);
        if (tid == 0) mbar_arrive(b_empty + 8 * vs);
        ks += 2; if (ks >= 5) { ks -= 5; kp ^= 1; }
        vs += 2; if (vs >= 5) { vs -= 5; vp ^= 1; }
        ready = mbar_test(b_full + 8 * ks, kp) & mbar_test(b_full + 8 * vs, vp);
        softmax_exp<AT_SPLIT, 64>(s);
        pack_p(p, s);
        if (n == AT_NBLK) { lp0 = l0; lp1 = l1; l0 = 0.f; l1 = 0.f; }
        if (__builtin_expect(!raw || !ready, 0)) {
        if (!raw && __any_sync(0xffffffffu, al0 != 1.0f || al1 != 1.0f)) {
          rescale_o(o, al0, al1);
          l0 *= al0; l1 *= al1;
          al0 = 1.0f; al1 = 1.0f;
        }
        if (!ready && n < 2 * AT_NBLK - 1) {
          mbar_wait(b_full + 8 * ks, kp);
          mbar_wait(b_full + 8 * vs, vp);
        }
        }
      }
      FS(2 * it + 1, 5);
      const uint32_t vl = ring_slot(ta + 63);
      vs = ring_slot(ta + 62);
      const uint32_t ob = more ? sbase + vs * 32768 : sbase + AT_SQ + 32768;
      mbar_wait(b_full + 8 * vl, ring_par(ta + 63));
      issue_pv(o, p, v_base + vl * 2048, 1);
      add_rowsum(p, l0, l1);
      const bool overflow = finish_l(l0, l1);
      if (!overflow && lane == 0) mbar_arrive(b_q1);
      mbar_wait(b_empty + 8 * vs, ring_par(ta + 62));
      wgmma_wait<0>();
      fence_regs(o);
      if (tid == 0) mbar_arrive(b_empty + 8 * vl);
      FS(2 * it + 1, 6);
      if (overflow) {
        attn_rows_exact(sq + 32768, ob + cwg * 8192, warp, lane, kc + (size_t)(hp * 2 + 1) * T_SEQ * T_DH, vc + (size_t)(hp * 2 + 1) * T_SEQ * T_DH);
        __syncwarp();
        if (lane == 0) mbar_arrive(b_q1);
      } else stage_o(o, l0, l1, ob + frag, lane);
      if (redo0) attn_rows_exact(sq, sq, warp, lane, kc + (size_t)(hp * 2) * T_SEQ * T_DH, vc + (size_t)(hp * 2) * T_SEQ * T_DH);
      fence_proxy_async();
      __syncwarp();
      if (lane == 0) {
        if (redo0) mbar_arrive(b_ordy + 8 * cwg);
        mbar_arrive(b_ordy + 16 + 8 * cwg);
      }
      if (redo0 || overflow) raw = false;
      named_bar_sync(3 + cwg, 128);
      FS(2 * it + 1, 7);
    }
    if (__builtin_expect(single, 0)) {
      float acc[128];
      uint32_t j = 0, pk[64];
      #pragma unroll
      for (int i = 0; i < 64; i++) asm volatile("" : "=f"(acc[2 * i]), "=f"(acc[2 * i + 1]), "=r"(pk[i]));
      uint4* dst = g_pre;
      auto put = [&](bool last) {
        #pragma unroll
        for (int i = 0; i < 4; i++) dst[i * 32] = make_uint4(pk[4 * i], pk[4 * i + 1], pk[4 * i + 2], pk[4 * i + 3]);
        dst += 1024;
        #pragma unroll
        for (int i = 0; i < 48; i++) asm volatile("mov.b32 %0, %1;" : "=r"(pk[i]) : "r"(pk[i + 16]));
        __syncwarp();
        if (last && lane == 0) mbar_arrive(bars + 280);
      };
      #pragma unroll 1
      for (int ji = 0; ji < help_njobs(); ji++) {
        #pragma unroll 1
        for (int kk = 0; kk < OG_PRE; kk++, j++) {
          const uint32_t slot = ring_slot(qp_pos(j, 1));
          mbar_wait(b_full + 8 * slot, ring_par(qp_pos(j, 1)) ^ ((j >> 2) & 1));
          const uint32_t a_lo = q_lo + (j & 3) * 1024, b_lo = w_base + slot * 2048;
          wgmma_fence();
          wgmma_m64n256k16_ss_tb<0, 0>(acc, a_lo, b_lo, kk != 0);
          wgmma_m64n256k16_ss_tb<2, 128>(acc, a_lo, b_lo, 1);
          wgmma_m64n256k16_ss_tb<4, 256>(acc, a_lo, b_lo, 1);
          wgmma_m64n256k16_ss_tb<6, 384>(acc, a_lo, b_lo, 1);
          wgmma_commit();
          if (ji > 0 && kk < 4) put(kk == 3);
          wgmma_wait<1>();
          if (kk > 0 && tid == 0) mbar_arrive(b_empty + 8 * ring_slot(qp_pos(j - 1, 1)));
        }
        wgmma_wait<0>();
        fence_regs(acc);
        if (tid == 0) mbar_arrive(b_empty + 8 * ring_slot(qp_pos(j - 1, 1)));
        #pragma unroll
        for (int i = 0; i < 64; i++) pk[i] = pack_bf16(acc[2 * i], acc[2 * i + 1]);
        if (ji == PRE_X) mbar_wait(bars + 296, 0);
        dst = g_pre + pre_loc(help_job(ji)) * 4096 + (cwg * 4 + warp) * 128 + lane;
      }
      #pragma unroll
      for (int i = 0; i < 16; i++) dst[(i >> 2) * 1024 + (i & 3) * 32] = make_uint4(pk[4 * i], pk[4 * i + 1], pk[4 * i + 2], pk[4 * i + 3]);
      __syncwarp();
      if (lane == 0) mbar_arrive(bars + 280);
      named_bar_sync(5, 256);
      if (threadIdx.x == 128) {
        #pragma unroll 1
        for (int i = 0; i < 5; i++) {
          constexpr int n = OG_JOBS * OG_PRE;
          const int used = i == 3 ? 0 : (n + 3 - (i == 4 ? 3 : i)) / 4;
          if ((used ^ (i < 4)) & 1) {
            mbar_arrive(b_full + 8 * ring_slot(4 + i));
            mbar_arrive(b_empty + 8 * ring_slot(4 + i)); mbar_arrive(b_empty + 8 * ring_slot(4 + i));
          }
        }
        mbar_arrive(b_x);
      }
      named_bar_sync(5, 256);
    }
    TL_CLK(3, 1, threadIdx.x == 128);
    TL_CTA(1, threadIdx.x == 256);
    TL_END(3, tid == 0);
    TL_MARK2(19, tid == 0 && !single);
    if (blockIdx.x < 128) {
      tail_consumer(sbase, cwg, w_r, w_gate, w_up);
    }
  }
}

typedef CUresult (*PFN_encodeTiled)(CUtensorMap*, CUtensorMapDataType, cuuint32_t, void*, const cuuint64_t*, const cuuint64_t*,
                                    const cuuint32_t*, const cuuint32_t*, CUtensorMapInterleave, CUtensorMapSwizzle,
                                    CUtensorMapL2promotion, CUtensorMapFloatOOBfill);

CUtensorMap make_map_2d(PFN_encodeTiled enc, const void* ptr, uint64_t inner, uint64_t outer, uint64_t stride_bytes, uint32_t box_inner, uint32_t box_outer) {
  CUtensorMap m;
  cuuint64_t gd[2] = {inner, outer}; cuuint64_t gs[1] = {stride_bytes};
  cuuint32_t bx[2] = {box_inner, box_outer}; cuuint32_t es[2] = {1, 1};
  enc(&m, CU_TENSOR_MAP_DATA_TYPE_BFLOAT16, 2, const_cast<void*>(ptr), gd, gs, bx, es, CU_TENSOR_MAP_INTERLEAVE_NONE,
      CU_TENSOR_MAP_SWIZZLE_128B, CU_TENSOR_MAP_L2_PROMOTION_L2_128B, CU_TENSOR_MAP_FLOAT_OOB_FILL_NONE);
  return m;
}

CUtensorMap make_map_3d(PFN_encodeTiled enc, const void* ptr, uint64_t cols, uint64_t rows, uint32_t box_rows, uint32_t chunks) {
  CUtensorMap m;
  cuuint64_t gd[3] = {64, rows, cols / 64}; cuuint64_t gs[2] = {cols * 2, 128};
  cuuint32_t bx[3] = {64, box_rows, chunks}; cuuint32_t es[3] = {1, 1, 1};
  enc(&m, CU_TENSOR_MAP_DATA_TYPE_BFLOAT16, 3, const_cast<void*>(ptr), gd, gs, bx, es, CU_TENSOR_MAP_INTERLEAVE_NONE,
      CU_TENSOR_MAP_SWIZZLE_128B, CU_TENSOR_MAP_L2_PROMOTION_L2_128B, CU_TENSOR_MAP_FLOAT_OOB_FILL_NONE);
  return m;
}

}

extern "C" void kernel_launch(void* const* d_in, const int* in_sizes, int n_in, void* d_out, int out_size) {
  const bf16* x      = (const bf16*)d_in[0];
  const bf16* kc     = (const bf16*)d_in[1];
  const bf16* vc     = (const bf16*)d_in[2];
  const bf16* wq     = (const bf16*)d_in[3];
  const bf16* wo     = (const bf16*)d_in[4];
  const bf16* w_r    = (const bf16*)d_in[6];
  const bf16* w_gate = (const bf16*)d_in[7];
  const bf16* w_up   = (const bf16*)d_in[8];
  const bf16* w_down = (const bf16*)d_in[9];
  const bf16* cvec   = (const bf16*)d_in[10];
  const bf16* w_mod  = (const bf16*)d_in[11];
  bf16* out = (bf16*)d_out;

  static PFN_encodeTiled enc = nullptr;
  static void *p_h = nullptr, *p_o = nullptr;
  if (!enc) {
    void* fn = nullptr; cudaDriverEntryPointQueryResult qres;
    cudaGetDriverEntryPoint("cuTensorMapEncodeTiled", &fn, cudaEnableDefault, &qres);
    enc = (PFN_encodeTiled)fn;
    cudaGetSymbolAddress(&p_h, g_pre);
    p_h = (uint4*)p_h + 16 * PRE_X * 2048;
    cudaGetSymbolAddress(&p_o, g_o);
    cudaFuncSetAttribute(fused_kernel, cudaFuncAttributeMaxDynamicSharedMemorySize, (int)AT_SMEM);
  }
  const CUtensorMap tm_h   = make_map_2d(enc, p_h, T_D, T_SEQ, T_D * 2, 64, 128);
  const CUtensorMap tm_wq  = make_map_2d(enc, wq, T_DQKV, T_D, T_DQKV * 2, 64, 64);
  const CUtensorMap tm_k   = make_map_2d(enc, kc, T_DH, (uint64_t)T_NH * T_SEQ, T_DH * 2, 64, 128);
  const CUtensorMap tm_v   = make_map_2d(enc, vc, T_DH, (uint64_t)T_NH * T_SEQ, T_DH * 2, 64, 128);
  const CUtensorMap tm_ost = make_map_2d(enc, p_o, T_DQKV, T_SEQ, T_DQKV * 2, 64, 64);
  const CUtensorMap tm_old = make_map_2d(enc, p_o, T_DQKV, T_SEQ, T_DQKV * 2, 64, 128);
  const CUtensorMap tm_wo  = make_map_3d(enc, wo, T_D, T_DQKV, 64, 2);
  const CUtensorMap tm_x   = make_map_3d(enc, x, T_D, T_SEQ, 128, 2);

  const CUtensorMap tm_out = make_map_2d(enc, out, T_D, T_SEQ, T_D * 2, 64, 128);

  fused_kernel<<<132, 384, AT_SMEM, cudaStreamPerThread>>>(tm_h, tm_wq, tm_k, tm_v, tm_ost, tm_old, tm_wo, tm_x, tm_out, 0u, (const uint8_t*)wo, kc, vc, x, cvec, w_mod,
             w_r, w_gate, w_up, w_down, out);
}
```

```cpp
#include <cuda_runtime.h>
#include <cuda_bf16.h>
#include <cuda.h>
#include <stdint.h>

namespace {

typedef __nv_bfloat16 bf16;

constexpr int T_SEQ = 2048, T_D = 1024, T_NH = 32, T_DH = 128, T_DQKV = 4096, T_F = 3584;

#define PRE_X 2
__device__ __align__(1024) uint4 g_pre[(16 * PRE_X + 128) * 2048];
#define g_h (reinterpret_cast<bf16*>(g_pre + 16 * PRE_X * 2048))
__device__ __align__(1024) bf16 g_o[T_SEQ * T_DQKV];
__device__ __align__(16) uint8_t g_col[8 * 1536];
__device__ __align__(16) float g_scal[64];
__device__ __align__(16) unsigned int g_hcnt[17 * 32];
__device__ unsigned int g_smid[160], g_tmax[128];
__device__ __align__(128) float g_modpart[4 * 2 * T_D];
struct __align__(2048) TailMail {
  float4 part1[T_SEQ * 8];
  uint32_t key[256];
  uint4 cand[16 * 2 * 2 * 128];
  uint32_t cnt[32];
  float ypart[(T_F / 32) * 2 * T_D];
};
__device__ TailMail g_mail;
#define g_part1 g_mail.part1
#define g_key g_mail.key
#define g_cand g_mail.cand
#define CNT_Y (g_mail.cnt)
#define g_ypart g_mail.ypart

__device__ __forceinline__ uint32_t smem_u32(const void* p) { return (uint32_t)__cvta_generic_to_shared(p); }
__device__ __forceinline__ void mbar_init(uint32_t bar, uint32_t cnt) { asm volatile("mbarrier.init.shared::cta.b64 [%0], %1;" :: "r"(bar), "r"(cnt)); }
__device__ __forceinline__ void mbar_expect_tx(uint32_t bar, uint32_t bytes) { asm volatile("mbarrier.arrive.expect_tx.shared::cta.b64 _, [%0], %1;" :: "r"(bar), "r"(bytes) : "memory"); }
__device__ __forceinline__ void mbar_arrive(uint32_t bar) { asm volatile("mbarrier.arrive.shared::cta.b64 _, [%0];" :: "r"(bar) : "memory"); }
__device__ __forceinline__ void mbar_wait(uint32_t bar, uint32_t parity) {
  asm volatile("{\n.reg .pred p;\nLAB_WAIT:\nmbarrier.try_wait.parity.shared::cta.b64 p, [%0], %1;\n@!p bra LAB_WAIT;\n}\n" :: "r"(bar), "r"(parity) : "memory");
}
__device__ __forceinline__ bool mbar_test(uint32_t bar, uint32_t parity) {
  uint32_t r; asm volatile("{\n.reg .pred p;\nmbarrier.test_wait.parity.shared::cta.b64 p, [%1], %2;\nselp.u32 %0, 1, 0, p;\n}\n" : "=r"(r) : "r"(bar), "r"(parity) : "memory");
  return r != 0;
}
__device__ __forceinline__ uint32_t clock_lo() { uint32_t c; asm volatile("mov.u32 %0, %%clock;" : "=r"(c)); return c; }
__device__ __forceinline__ void fence_mbar_init() { asm volatile("fence.mbarrier_init.release.cluster;" ::: "memory"); }
__device__ __forceinline__ void tma_load_2d(uint32_t dst, const CUtensorMap* map, int c0, int c1, uint32_t bar) {
  asm volatile("cp.async.bulk.tensor.2d.shared::cluster.global.mbarrier::complete_tx::bytes [%0], [%1, {%3, %4}], [%2];"
    :: "r"(dst), "l"(map), "r"(bar), "r"(c0), "r"(c1) : "memory");
}
__device__ __forceinline__ uint64_t policy_evict_first() {
  uint64_t p; asm volatile("createpolicy.fractional.L2::evict_first.b64 %0, 1.0;" : "=l"(p)); return p;
}
__device__ __forceinline__ void tma_load_2d_hint(uint32_t dst, const CUtensorMap* map, int c0, int c1, uint32_t bar, uint64_t pol) {
  asm volatile("cp.async.bulk.tensor.2d.shared::cluster.global.mbarrier::complete_tx::bytes.L2::cache_hint [%0], [%1, {%3, %4}], [%2], %5;"
    :: "r"(dst), "l"(map), "r"(bar), "r"(c0), "r"(c1), "l"(pol) : "memory");
}
__device__ __forceinline__ void tma_load_3d_hint(uint32_t dst, const CUtensorMap* map, int c1, int c2, uint32_t bar, uint64_t pol) {
  asm volatile("cp.async.bulk.tensor.3d.shared::cluster.global.mbarrier::complete_tx::bytes.L2::cache_hint [%0], [%1, {%3, %4, %5}], [%2], %6;"
    :: "r"(dst), "l"(map), "r"(bar), "n"(0), "r"(c1), "r"(c2), "l"(pol) : "memory");
}
__device__ __forceinline__ void tma_store_2d(const CUtensorMap* map, uint32_t src, int c0, int c1) {
  asm volatile("cp.async.bulk.tensor.2d.global.shared::cta.bulk_group [%0, {%2, %3}], [%1];" :: "l"(map), "r"(src), "r"(c0), "r"(c1) : "memory");
}
__device__ __forceinline__ void prefetch_tmap(const CUtensorMap* map) { asm volatile("prefetch.tensormap [%0];" :: "l"(map) : "memory"); }
__device__ __forceinline__ void l2_prefetch_bulk(const void* p, uint32_t bytes) {
  asm volatile("cp.async.bulk.prefetch.L2.global [%0], %1;" :: "l"(p), "r"(bytes) : "memory");
}
__device__ __forceinline__ void bulk_commit() { asm volatile("cp.async.bulk.commit_group;" ::: "memory"); }
template<int N> __device__ __forceinline__ void bulk_wait_read() { asm volatile("cp.async.bulk.wait_group.read %0;" :: "n"(N) : "memory"); }
template<int N> __device__ __forceinline__ void bulk_wait() { asm volatile("cp.async.bulk.wait_group %0;" :: "n"(N) : "memory"); }
__device__ __forceinline__ void named_bar_sync(int id, int nthreads) { asm volatile("bar.sync %0, %1;" :: "r"(id), "r"(nthreads) : "memory"); }
__device__ __forceinline__ void named_bar_arrive(int id, int nthreads) { asm volatile("bar.arrive %0, %1;" :: "r"(id), "r"(nthreads) : "memory"); }
__device__ __forceinline__ void wgmma_fence() { asm volatile("wgmma.fence.sync.aligned;" ::: "memory"); }
__device__ __forceinline__ void wgmma_commit() { asm volatile("wgmma.commit_group.sync.aligned;" ::: "memory"); }
template<int N> __device__ __forceinline__ void wgmma_wait() { asm volatile("wgmma.wait_group.sync.aligned %0;" :: "n"(N) : "memory"); }
template<int R> __device__ __forceinline__ void reg_alloc() { asm volatile("setmaxnreg.inc.sync.aligned.u32 %0;" :: "n"(R)); }
template<int R> __device__ __forceinline__ void reg_dealloc() { asm volatile("setmaxnreg.dec.sync.aligned.u32 %0;" :: "n"(R)); }
__device__ __forceinline__ bool elect_one() {
  uint32_t pred; asm volatile("{\n.reg .pred p;\nelect.sync _|p, 0xffffffff;\nselp.u32 %0, 1, 0, p;\n}\n" : "=r"(pred)); return pred != 0;
}
__device__ __forceinline__ uint32_t pack_bf16(float lo, float hi) {
  uint32_t r; asm("cvt.rn.bf16x2.f32 %0, %1, %2;" : "=r"(r) : "f"(hi), "f"(lo)); return r;
}
__device__ __forceinline__ void stmatrix_x4(uint32_t addr, uint32_t r0, uint32_t r1, uint32_t r2, uint32_t r3) {
  asm volatile("stmatrix.sync.aligned.m8n8.x4.shared.b16 [%0], {%1, %2, %3, %4};" :: "r"(addr), "r"(r0), "r"(r1), "r"(r2), "r"(r3) : "memory");
}
__device__ __forceinline__ void fence_proxy_async() { asm volatile("fence.proxy.async.shared::cta;" ::: "memory"); }
__device__ __forceinline__ float ex2_approx(float x) { float y; asm("ex2.approx.ftz.f32 %0, %1;" : "=f"(y) : "f"(x)); return y; }
template<int N> __device__ __forceinline__ void fence_regs(float (&r)[N]) {
  #pragma unroll
  for (int i = 0; i < N; i++) asm volatile("" : "+f"(r[i]) :: "memory");
}
template<int N> __device__ __forceinline__ void zero_regs(float (&r)[N]) {
  #pragma unroll
  for (int i = 0; i < N; i += 2) asm volatile("mov.b64 {%0, %1}, 0;" : "=f"(r[i]), "=f"(r[i + 1]));
}
__device__ __forceinline__ float rbf(float x) { return __uint_as_float(pack_bf16(0.f, x)); }
__device__ __forceinline__ float bflo(uint32_t v) { return __uint_as_float(v << 16); }
__device__ __forceinline__ float bfhi(uint32_t v) { return __uint_as_float(v & 0xffff0000u); }

#define TL_START(k) do {} while (0)
#define TL_END(k, cond) do {} while (0)
#define TL_CTA(i, cond) do {} while (0)
#define FS(slot, k) do {} while (0)
#define TL_MARK2(k, cond) do {} while (0)
#define TL_CLK(k, i, cond) do {} while (0)

template <int OFFA, int OFFB>
__device__ __forceinline__ void wgmma_m64n256k16_ss_tb(float (&d)[128], uint32_t a_lo, uint32_t b_lo, int scaleD) {
  asm volatile("{\n.reg .pred p;\n.reg .b32 ta, tb;\n.reg .b64 da, db;\nsetp.ne.b32 p, %130, 0;\n"
    "add.u32 ta, %128, %131;\nadd.u32 tb, %129, %132;\n"
    "mov.b64 da, {ta, 0x40000040};\nmov.b64 db, {tb, 0x40000040};\n"
    "wgmma.mma_async.sync.aligned.m64n256k16.f32.bf16.bf16 "
    "{%0, %1, %2, %3, %4, %5, %6, %7, %8, %9, %10, %11, %12, %13, %14, %15, %16, %17, %18, %19, %20, %21, %22, %23, %24, %25, %26, %27, %28, %29, %30, %31, %32, %33, %34, %35, %36, %37, %38, %39, %40, %41, %42, %43, %44, %45, %46, %47, %48, %49, %50, %51, %52, %53, %54, %55, %56, %57, %58, %59, %60, %61, %62, %63, %64, %65, %66, %67, %68, %69, %70, %71, %72, %73, %74, %75, %76, %77, %78, %79, %80, %81, %82, %83, %84, %85, %86, %87, %88, %89, %90, %91, %92, %93, %94, %95, %96, %97, %98, %99, %100, %101, %102, %103, %104, %105, %106, %107, %108, %109, %110, %111, %112, %113, %114, %115, %116, %117, %118, %119, %120, %121, %122, %123, %124, %125, %126, %127}, "
    "da, db, p, 1, 1, 0, 1;\n}\n"
    : "+f"(d[0]), "+f"(d[1]), "+f"(d[2]), "+f"(d[3]), "+f"(d[4]), "+f"(d[5]), "+f"(d[6]), "+f"(d[7]), "+f"(d[8]), "+f"(d[9]), "+f"(d[10]), "+f"(d[11]), "+f"(d[12]), "+f"(d[13]), "+f"(d[14]), "+f"(d[15]), "+f"(d[16]), "+f"(d[17]), "+f"(d[18]), "+f"(d[19]), "+f"(d[20]), "+f"(d[21]), "+f"(d[22]), "+f"(d[23]), "+f"(d[24]), "+f"(d[25]), "+f"(d[26]), "+f"(d[27]), "+f"(d[28]), "+f"(d[29]), "+f"(d[30]), "+f"(d[31]), "+f"(d[32]), "+f"(d[33]), "+f"(d[34]), "+f"(d[35]), "+f"(d[36]), "+f"(d[37]), "+f"(d[38]), "+f"(d[39]), "+f"(d[40]), "+f"(d[41]), "+f"(d[42]), "+f"(d[43]), "+f"(d[44]), "+f"(d[45]), "+f"(d[46]), "+f"(d[47]), "+f"(d[48]), "+f"(d[49]), "+f"(d[50]), "+f"(d[51]), "+f"(d[52]), "+f"(d[53]), "+f"(d[54]), "+f"(d[55]), "+f"(d[56]), "+f"(d[57]), "+f"(d[58]), "+f"(d[59]), "+f"(d[60]), "+f"(d[61]), "+f"(d[62]), "+f"(d[63]), "+f"(d[64]), "+f"(d[65]), "+f"(d[66]), "+f"(d[67]), "+f"(d[68]), "+f"(d[69]), "+f"(d[70]), "+f"(d[71]), "+f"(d[72]), "+f"(d[73]), "+f"(d[74]), "+f"(d[75]), "+f"(d[76]), "+f"(d[77]), "+f"(d[78]), "+f"(d[79]), "+f"(d[80]), "+f"(d[81]), "+f"(d[82]), "+f"(d[83]), "+f"(d[84]), "+f"(d[85]), "+f"(d[86]), "+f"(d[87]), "+f"(d[88]), "+f"(d[89]), "+f"(d[90]), "+f"(d[91]), "+f"(d[92]), "+f"(d[93]), "+f"(d[94]), "+f"(d[95]), "+f"(d[96]), "+f"(d[97]), "+f"(d[98]), "+f"(d[99]), "+f"(d[100]), "+f"(d[101]), "+f"(d[102]), "+f"(d[103]), "+f"(d[104]), "+f"(d[105]), "+f"(d[106]), "+f"(d[107]), "+f"(d[108]), "+f"(d[109]), "+f"(d[110]), "+f"(d[111]), "+f"(d[112]), "+f"(d[113]), "+f"(d[114]), "+f"(d[115]), "+f"(d[116]), "+f"(d[117]), "+f"(d[118]), "+f"(d[119]), "+f"(d[120]), "+f"(d[121]), "+f"(d[122]), "+f"(d[123]), "+f"(d[124]), "+f"(d[125]), "+f"(d[126]), "+f"(d[127])
    : "r"(a_lo), "r"(b_lo), "r"(scaleD), "n"(OFFA), "n"(OFFB));
}

template <int OFFA, int OFFB>
__device__ __forceinline__ void wgmma_m64n128k16_ss_tb(float (&d)[64], uint32_t a_lo, uint32_t b_lo, int scaleD) {
  asm volatile("{\n.reg .pred p;\n.reg .b32 ta, tb;\n.reg .b64 da, db;\nsetp.ne.b32 p, %66, 0;\n"
    "add.u32 ta, %64, %67;\nadd.u32 tb, %65, %68;\n"
    "mov.b64 da, {ta, 0x40000040};\nmov.b64 db, {tb, 0x40000040};\n"
    "wgmma.mma_async.sync.aligned.m64n128k16.f32.bf16.bf16 "
    "{%0, %1, %2, %3, %4, %5, %6, %7, %8, %9, %10, %11, %12, %13, %14, %15, %16, %17, %18, %19, %20, %21, %22, %23, %24, %25, %26, %27, %28, %29, %30, %31, %32, %33, %34, %35, %36, %37, %38, %39, %40, %41, %42, %43, %44, %45, %46, %47, %48, %49, %50, %51, %52, %53, %54, %55, %56, %57, %58, %59, %60, %61, %62, %63}, "
    "da, db, p, 1, 1, 0, 1;\n}\n"
    : "+f"(d[0]), "+f"(d[1]), "+f"(d[2]), "+f"(d[3]), "+f"(d[4]), "+f"(d[5]), "+f"(d[6]), "+f"(d[7]), "+f"(d[8]), "+f"(d[9]), "+f"(d[10]), "+f"(d[11]), "+f"(d[12]), "+f"(d[13]), "+f"(d[14]), "+f"(d[15]), "+f"(d[16]), "+f"(d[17]), "+f"(d[18]), "+f"(d[19]), "+f"(d[20]), "+f"(d[21]), "+f"(d[22]), "+f"(d[23]), "+f"(d[24]), "+f"(d[25]), "+f"(d[26]), "+f"(d[27]), "+f"(d[28]), "+f"(d[29]), "+f"(d[30]), "+f"(d[31]), "+f"(d[32]), "+f"(d[33]), "+f"(d[34]), "+f"(d[35]), "+f"(d[36]), "+f"(d[37]), "+f"(d[38]), "+f"(d[39]), "+f"(d[40]), "+f"(d[41]), "+f"(d[42]), "+f"(d[43]), "+f"(d[44]), "+f"(d[45]), "+f"(d[46]), "+f"(d[47]), "+f"(d[48]), "+f"(d[49]), "+f"(d[50]), "+f"(d[51]), "+f"(d[52]), "+f"(d[53]), "+f"(d[54]), "+f"(d[55]), "+f"(d[56]), "+f"(d[57]), "+f"(d[58]), "+f"(d[59]), "+f"(d[60]), "+f"(d[61]), "+f"(d[62]), "+f"(d[63])
    : "r"(a_lo), "r"(b_lo), "r"(scaleD), "n"(OFFA), "n"(OFFB));
}

template <int OFFB>
__device__ __forceinline__ void wgmma_m64n128k16_rs_tb(float (&d)[64], uint32_t a0, uint32_t a1, uint32_t a2, uint32_t a3, uint32_t b_lo, int scaleD) {
  asm volatile("{\n.reg .pred p;\n.reg .b32 tb;\n.reg .b64 db;\nsetp.ne.b32 p, %69, 0;\n"
    "add.u32 tb, %68, %70;\n"
    "mov.b64 db, {tb, 0x40000040};\n"
    "wgmma.mma_async.sync.aligned.m64n128k16.f32.bf16.bf16 "
    "{%0, %1, %2, %3, %4, %5, %6, %7, %8, %9, %10, %11, %12, %13, %14, %15, %16, %17, %18, %19, %20, %21, %22, %23, %24, %25, %26, %27, %28, %29, %30, %31, %32, %33, %34, %35, %36, %37, %38, %39, %40, %41, %42, %43, %44, %45, %46, %47, %48, %49, %50, %51, %52, %53, %54, %55, %56, %57, %58, %59, %60, %61, %62, %63}, "
    "{%64, %65, %66, %67}, db, p, 1, 1, 1;\n}\n"
    : "+f"(d[0]), "+f"(d[1]), "+f"(d[2]), "+f"(d[3]), "+f"(d[4]), "+f"(d[5]), "+f"(d[6]), "+f"(d[7]), "+f"(d[8]), "+f"(d[9]), "+f"(d[10]), "+f"(d[11]), "+f"(d[12]), "+f"(d[13]), "+f"(d[14]), "+f"(d[15]), "+f"(d[16]), "+f"(d[17]), "+f"(d[18]), "+f"(d[19]), "+f"(d[20]), "+f"(d[21]), "+f"(d[22]), "+f"(d[23]), "+f"(d[24]), "+f"(d[25]), "+f"(d[26]), "+f"(d[27]), "+f"(d[28]), "+f"(d[29]), "+f"(d[30]), "+f"(d[31]), "+f"(d[32]), "+f"(d[33]), "+f"(d[34]), "+f"(d[35]), "+f"(d[36]), "+f"(d[37]), "+f"(d[38]), "+f"(d[39]), "+f"(d[40]), "+f"(d[41]), "+f"(d[42]), "+f"(d[43]), "+f"(d[44]), "+f"(d[45]), "+f"(d[46]), "+f"(d[47]), "+f"(d[48]), "+f"(d[49]), "+f"(d[50]), "+f"(d[51]), "+f"(d[52]), "+f"(d[53]), "+f"(d[54]), "+f"(d[55]), "+f"(d[56]), "+f"(d[57]), "+f"(d[58]), "+f"(d[59]), "+f"(d[60]), "+f"(d[61]), "+f"(d[62]), "+f"(d[63])
    : "r"(a0), "r"(a1), "r"(a2), "r"(a3), "r"(b_lo), "r"(scaleD), "n"(OFFB));
}

template <int OFFB>
__device__ __forceinline__ void wgmma_m64n128k16_rs(float (&d)[64], uint32_t a0, uint32_t a1, uint32_t a2, uint32_t a3, uint32_t b_lo, int scaleD) {
  asm volatile("{\n.reg .pred p;\n.reg .b32 tb;\n.reg .b64 db;\nsetp.ne.b32 p, %69, 0;\n"
    "add.u32 tb, %68, %70;\n"
    "mov.b64 db, {tb, 0x40000040};\n"
    "wgmma.mma_async.sync.aligned.m64n128k16.f32.bf16.bf16 "
    "{%0, %1, %2, %3, %4, %5, %6, %7, %8, %9, %10, %11, %12, %13, %14, %15, %16, %17, %18, %19, %20, %21, %22, %23, %24, %25, %26, %27, %28, %29, %30, %31, %32, %33, %34, %35, %36, %37, %38, %39, %40, %41, %42, %43, %44, %45, %46, %47, %48, %49, %50, %51, %52, %53, %54, %55, %56, %57, %58, %59, %60, %61, %62, %63}, "
    "{%64, %65, %66, %67}, db, p, 1, 1, 0;\n}\n"
    : "+f"(d[0]), "+f"(d[1]), "+f"(d[2]), "+f"(d[3]), "+f"(d[4]), "+f"(d[5]), "+f"(d[6]), "+f"(d[7]), "+f"(d[8]), "+f"(d[9]), "+f"(d[10]), "+f"(d[11]), "+f"(d[12]), "+f"(d[13]), "+f"(d[14]), "+f"(d[15]), "+f"(d[16]), "+f"(d[17]), "+f"(d[18]), "+f"(d[19]), "+f"(d[20]), "+f"(d[21]), "+f"(d[22]), "+f"(d[23]), "+f"(d[24]), "+f"(d[25]), "+f"(d[26]), "+f"(d[27]), "+f"(d[28]), "+f"(d[29]), "+f"(d[30]), "+f"(d[31]), "+f"(d[32]), "+f"(d[33]), "+f"(d[34]), "+f"(d[35]), "+f"(d[36]), "+f"(d[37]), "+f"(d[38]), "+f"(d[39]), "+f"(d[40]), "+f"(d[41]), "+f"(d[42]), "+f"(d[43]), "+f"(d[44]), "+f"(d[45]), "+f"(d[46]), "+f"(d[47]), "+f"(d[48]), "+f"(d[49]), "+f"(d[50]), "+f"(d[51]), "+f"(d[52]), "+f"(d[53]), "+f"(d[54]), "+f"(d[55]), "+f"(d[56]), "+f"(d[57]), "+f"(d[58]), "+f"(d[59]), "+f"(d[60]), "+f"(d[61]), "+f"(d[62]), "+f"(d[63])
    : "r"(a0), "r"(a1), "r"(a2), "r"(a3), "r"(b_lo), "r"(scaleD), "n"(OFFB));
}

__device__ __forceinline__ uint4 ldg_nc_v4(const void* p) {
  uint4 v;
    asm volatile("{\n.reg .b64 pol;\ncreatepolicy.fractional.L2::evict_first.b64 pol, 1.0;\n"
                 "ld.global.nc.L1::no_allocate.L2::cache_hint.v4.u32 {%0, %1, %2, %3}, [%4], pol;\n}\n" : "=r"(v.x), "=r"(v.y), "=r"(v.z), "=r"(v.w) : "l"(p));
  return v;
}
__device__ __forceinline__ uint64_t pol_normal() {
  uint64_t p; asm volatile("createpolicy.fractional.L2::evict_normal.b64 %0, 1.0;" : "=l"(p)); return p;
}
__device__ __forceinline__ void unpack8(const uint4& u, float (&v)[8]) {
  v[0] = bflo(u.x); v[1] = bfhi(u.x); v[2] = bflo(u.y); v[3] = bfhi(u.y);
  v[4] = bflo(u.z); v[5] = bfhi(u.z); v[6] = bflo(u.w); v[7] = bfhi(u.w);
}
__device__ __forceinline__ void fma8(float (&acc)[8], float s, const uint4& w) {
  acc[0] = fmaf(s, bflo(w.x), acc[0]); acc[1] = fmaf(s, bfhi(w.x), acc[1]); acc[2] = fmaf(s, bflo(w.y), acc[2]); acc[3] = fmaf(s, bfhi(w.y), acc[3]);
  acc[4] = fmaf(s, bflo(w.z), acc[4]); acc[5] = fmaf(s, bfhi(w.z), acc[5]); acc[6] = fmaf(s, bflo(w.w), acc[6]); acc[7] = fmaf(s, bfhi(w.w), acc[7]);
}
__device__ __forceinline__ float rcp_approx(float x) { float y; asm("rcp.approx.ftz.f32 %0, %1;" : "=f"(y) : "f"(x)); return y; }
__device__ __forceinline__ float sigmoid_f(float v) { return rcp_approx(1.0f + ex2_approx(v * -1.4426950408889634f)); }
__device__ __forceinline__ float silu_bf(float v) { return rbf(v * sigmoid_f(v)); }
__device__ __forceinline__ uint32_t rank_key(float r, int idx) {
  const uint32_t b = __float_as_uint(r) >> 16;
  const uint32_t u = (r != r) ? 0u : ((b & 0x8000u) ? (~b & 0xffffu) : (b | 0x8000u));
  return (u << 16) | (0xffffu - (uint32_t)idx);
}
__device__ __forceinline__ void warp_top2(uint32_t& k1, uint32_t& k2) {
  const uint32_t m1 = __reduce_max_sync(0xffffffffu, k1);
  k2 = __reduce_max_sync(0xffffffffu, k1 == m1 ? k2 : k1);
  k1 = m1;
}
__device__ __forceinline__ uint32_t bmul2(uint32_t a, uint32_t b) { uint32_t r; asm("mul.rn.bf16x2 %0, %1, %2;" : "=r"(r) : "r"(a), "r"(b)); return r; }
__device__ __forceinline__ uint32_t badd2(uint32_t a, uint32_t b) { uint32_t r; asm("add.rn.bf16x2 %0, %1, %2;" : "=r"(r) : "r"(a), "r"(b)); return r; }
__device__ __forceinline__ uint32_t bsub2(uint32_t a, uint32_t b) { uint32_t r; asm("sub.rn.bf16x2 %0, %1, %2;" : "=r"(r) : "r"(a), "r"(b)); return r; }
__device__ __forceinline__ float sqrt_approx(float x) { float y; asm("sqrt.approx.f32 %0, %1;" : "=f"(y) : "f"(x)); return y; }
__device__ __forceinline__ uint32_t ln_norm2(uint32_t x1, uint32_t mb2, float inv) {
  const uint32_t d = bsub2(x1, mb2);
  return pack_bf16(bflo(d) * inv, bfhi(d) * inv);
}
__device__ __forceinline__ uint32_t ln_mod2(uint32_t x1, uint32_t mb2, float inv, uint32_t c1, uint32_t sb) { return badd2(bmul2(ln_norm2(x1, mb2, inv), c1), sb); }
__device__ __forceinline__ void ldmatrix_x4(uint32_t addr, uint32_t& r0, uint32_t& r1, uint32_t& r2, uint32_t& r3) {
  asm volatile("ldmatrix.sync.aligned.m8n8.x4.shared.b16 {%0, %1, %2, %3}, [%4];" : "=r"(r0), "=r"(r1), "=r"(r2), "=r"(r3) : "r"(addr) : "memory");
}
__device__ __forceinline__ uint4 ldg_stream_v4(const void* p, uint64_t pol) {
  uint4 v; asm volatile("ld.global.nc.L1::no_allocate.L2::cache_hint.L2::128B.v4.u32 {%0, %1, %2, %3}, [%4], %5;" : "=r"(v.x), "=r"(v.y), "=r"(v.z), "=r"(v.w) : "l"(p), "l"(pol)); return v;
}
__device__ __forceinline__ void bulk_load_hint(uint32_t dst, const void* src, uint32_t bytes, uint32_t bar, uint64_t pol) {
  asm volatile("cp.async.bulk.shared::cluster.global.mbarrier::complete_tx::bytes.L2::cache_hint [%0], [%1], %2, [%3], %4;"
    :: "r"(dst), "l"(src), "r"(bytes), "r"(bar), "l"(pol) : "memory");
}
__device__ __forceinline__ void red_release_add(unsigned int* p, unsigned int v) { asm volatile("red.release.gpu.global.add.u32 [%0], %1;" :: "l"(p), "r"(v) : "memory"); }
__device__ __forceinline__ unsigned int ld_acquire(const unsigned int* p) { unsigned int v; asm volatile("ld.acquire.gpu.global.u32 %0, [%1];" : "=r"(v) : "l"(p) : "memory"); return v; }
__device__ __forceinline__ void spin_until(const unsigned int* p, unsigned int target) {
  #pragma unroll 1
  for (unsigned int i = 0; i < (1u << 22); i++) { if (ld_acquire(p) >= target) return; }
}
__device__ __forceinline__ float lds_f32(uint32_t a) { float v; asm volatile("ld.shared.f32 %0, [%1];" : "=f"(v) : "r"(a) : "memory"); return v; }
__device__ __forceinline__ float2 lds_f32x2(uint32_t a) { float2 v; asm volatile("ld.shared.v2.f32 {%0, %1}, [%2];" : "=f"(v.x), "=f"(v.y) : "r"(a) : "memory"); return v; }
__device__ __forceinline__ uint2 lds_u32x2(uint32_t a) { uint2 v; asm volatile("ld.shared.v2.u32 {%0, %1}, [%2];" : "=r"(v.x), "=r"(v.y) : "r"(a) : "memory"); return v; }
__device__ __forceinline__ uint32_t lds_u32(uint32_t a) { uint32_t v; asm volatile("ld.shared.u32 %0, [%1];" : "=r"(v) : "r"(a) : "memory"); return v; }
__device__ __forceinline__ void sts_u32(uint32_t a, uint32_t v) { asm volatile("st.shared.u32 [%0], %1;" :: "r"(a), "r"(v) : "memory"); }
__device__ __forceinline__ void sts_u32x2(uint32_t a, uint32_t x, uint32_t y) { asm volatile("st.shared.v2.u32 [%0], {%1, %2};" :: "r"(a), "r"(x), "r"(y) : "memory"); }
__device__ __forceinline__ void sts_f32(uint32_t a, float v) { asm volatile("st.shared.f32 [%0], %1;" :: "r"(a), "f"(v) : "memory"); }
__device__ __forceinline__ void sts_f32x2(uint32_t a, float x, float y) { asm volatile("st.shared.v2.f32 [%0], {%1, %2};" :: "r"(a), "f"(x), "f"(y) : "memory"); }
__device__ __forceinline__ void sts_f32x4(uint32_t a, float x, float y, float z, float w) { asm volatile("st.shared.v4.f32 [%0], {%1, %2, %3, %4};" :: "r"(a), "f"(x), "f"(y), "f"(z), "f"(w) : "memory"); }

__device__ __forceinline__ uint4 lds_u32x4(uint32_t a) { uint4 v; asm volatile("ld.shared.v4.u32 {%0, %1, %2, %3}, [%4];" : "=r"(v.x), "=r"(v.y), "=r"(v.z), "=r"(v.w) : "r"(a) : "memory"); return v; }
__device__ __forceinline__ void sts_u32x4(uint32_t a, uint32_t x, uint32_t y, uint32_t z, uint32_t w) { asm volatile("st.shared.v4.u32 [%0], {%1, %2, %3, %4};" :: "r"(a), "r"(x), "r"(y), "r"(z), "r"(w) : "memory"); }
__device__ __forceinline__ void st_tagged(float* p, float v) {
  const uint32_t b = __float_as_uint(v);
  asm volatile("st.relaxed.gpu.global.u32 [%0], %1;" :: "l"(p), "r"(b == 0u ? 0x80000000u : b) : "memory");
}
__device__ __forceinline__ void st_tagged4(float* p, float x, float y, float z, float w) {
  const uint32_t a = __float_as_uint(x), b = __float_as_uint(y), c = __float_as_uint(z), d = __float_as_uint(w);
  asm volatile("st.relaxed.gpu.global.v4.u32 [%0], {%1, %2, %3, %4};" :: "l"(p), "r"(a == 0u ? 0x80000000u : a), "r"(b == 0u ? 0x80000000u : b),
               "r"(c == 0u ? 0x80000000u : c), "r"(d == 0u ? 0x80000000u : d) : "memory");
}
__device__ __forceinline__ void st_relaxed2(void* p, uint32_t a, uint32_t b) { asm volatile("st.relaxed.gpu.global.v2.u32 [%0], {%1, %2};" :: "l"(p), "r"(a), "r"(b) : "memory"); }
__device__ __forceinline__ float4 ld_tagged4(const float* p) {
  float4 v; asm volatile("ld.relaxed.gpu.global.v4.f32 {%0, %1, %2, %3}, [%4];" : "=f"(v.x), "=f"(v.y), "=f"(v.z), "=f"(v.w) : "l"(p) : "memory"); return v;
}
__device__ __forceinline__ bool tagged4(const float4& v) {
  return __float_as_uint(v.x) != 0u && __float_as_uint(v.y) != 0u && __float_as_uint(v.z) != 0u && __float_as_uint(v.w) != 0u;
}
__device__ __forceinline__ void hint_arrive(uint32_t* p) { asm volatile("red.relaxed.gpu.global.add.u32 [%0], 1;" :: "l"(p) : "memory"); }
__device__ __forceinline__ void hint_wait(const uint32_t* p, uint32_t target) {
  uint32_t v = 0u;
  #pragma unroll 1
  for (unsigned int i = 0; i < (1u << 22) && v < target; i++) asm volatile("ld.relaxed.gpu.global.u32 %0, [%1];" : "=r"(v) : "l"(p) : "memory");
}
__device__ __forceinline__ void fence_proxy_async_global() { asm volatile("fence.proxy.async.global;" ::: "memory"); }

constexpr int H_SPLIT = 1;
constexpr int PRE_B = 2;
__device__ __forceinline__ void load_parts(float4 (&pa)[4], float4 (&pb)[4], int t2) {
  #pragma unroll
  for (int k = 0; k < 4; k++) { pa[k] = ld_tagged4(g_modpart + k * 2 * T_D + t2 * 8); pb[k] = ld_tagged4(g_modpart + k * 2 * T_D + t2 * 8 + 4); }
}
__device__ __forceinline__ void finish_parts(float4 (&pa)[4], float4 (&pb)[4], int t2, uint32_t tab) {
  #pragma unroll 1
  for (unsigned int spin = 0; spin < (1u << 22); spin++) {
    bool ok = true;
    #pragma unroll
    for (int k = 0; k < 4; k++) ok &= tagged4(pa[k]) & tagged4(pb[k]);
    if (__all_sync(0xffffffffu, ok)) break;
    load_parts(pa, pb, t2);
  }
  #pragma unroll
  for (int k = 1; k < 4; k++) {
    pa[0].x += pa[k].x; pa[0].y += pa[k].y; pa[0].z += pa[k].z; pa[0].w += pa[k].w;
    pb[0].x += pb[k].x; pb[0].y += pb[k].y; pb[0].z += pb[k].z; pb[0].w += pb[k].w;
  }
  uint32_t m0 = pack_bf16(pa[0].x, pa[0].y), m1 = pack_bf16(pa[0].z, pa[0].w), m2 = pack_bf16(pb[0].x, pb[0].y), m3 = pack_bf16(pb[0].z, pb[0].w);
  if (t2 >= 128) { m0 = badd2(m0, 0x3F803F80u); m1 = badd2(m1, 0x3F803F80u); m2 = badd2(m2, 0x3F803F80u); m3 = badd2(m3, 0x3F803F80u); }
  sts_u32x4(tab + t2 * 16, m0, m1, m2, m3);
}
__device__ __forceinline__ void head_phase(uint32_t scr, uint32_t xs, uint32_t b_x, uint32_t b_go, uint32_t b_head, int t2, uint32_t zero, const bf16* __restrict__ x, const bf16* __restrict__ cvec, const bf16* __restrict__ w_mod) {
  const int lane = t2 & 31, w8 = t2 >> 5;
  const int cb = blockIdx.x & 31, ks = blockIdx.x >> 5;
  uint4 w[8], xv[2][4];
  const float cv = __bfloat162float(cvec[ks * 256 + t2]);
  #pragma unroll
  for (int i = 0; i < 8; i++) w[i] = ldg_nc_v4(w_mod + (size_t)(ks * 256 + (t2 >> 3) + 32 * i) * (6 * T_D) + cb * 64 + (t2 & 7) * 8);
  const int row0 = blockIdx.x * 16 + 2 * w8;
  sts_f32(scr + t2 * 4, silu_bf(cv));
  #pragma unroll 1
  for (uint32_t i = 0; i <= zero; i++) named_bar_sync(6, 384);
  TL_MARK2(1, t2 == 0);
  {
    float acc[8];
    #pragma unroll
    for (int j = 0; j < 8; j++) acc[j] = 0.f;
    #pragma unroll
    for (int i = 0; i < 8; i++) {
      fma8(acc, lds_f32(scr + ((t2 >> 3) + 32 * i) * 4), w[i]);
      if (i == 0 && t2 == 0) {
        mbar_expect_tx(b_x + (__float_as_uint(acc[0]) & zero), 32768);
        bulk_load_hint(xs, x + (size_t)blockIdx.x * 16 * T_D, 32768, b_x, policy_evict_first());
      }
    }
    #pragma unroll
    for (int j = 0; j < 4; j++) { const bool up = lane & 16; acc[j] = (up ? acc[4 + j] : acc[j]) + __shfl_xor_sync(0xffffffffu, up ? acc[j] : acc[4 + j], 16); }
    #pragma unroll
    for (int j = 0; j < 2; j++) { const bool up = lane & 8; acc[j] = (up ? acc[2 + j] : acc[j]) + __shfl_xor_sync(0xffffffffu, up ? acc[j] : acc[2 + j], 8); }
    sts_f32x2(scr + 1024 + w8 * 256 + (lane & 7) * 32 + (lane >> 3) * 8, acc[0], acc[1]);
  }
  named_bar_sync(5, 256);
  if (t2 < 64) {
    float sum = 0.f;
    #pragma unroll
    for (int i = 0; i < 8; i++) sum += lds_f32(scr + 1024 + i * 256 + t2 * 4);
    st_tagged(g_modpart + ks * 2 * T_D + cb * 64 + t2, sum);
    TL_MARK2(2, t2 == 0);
  }
  mbar_wait(b_x, 0);
  const bool first_cols = (__shfl_sync(0xffffffffu, w8, 0) & 3) == 0;
  float4 pa[4], pb[4];
  pa[0].x = 0.f;
  if (first_cols) load_parts(pa, pb, t2);
  #pragma unroll
  for (int r = 0; r < 2; r++)
    #pragma unroll
    for (int j = 0; j < 4; j++) xv[r][j] = lds_u32x4(xs + (2 * w8 + r) * 2048 + j * 512 + lane * 16);
  #pragma unroll
  for (int r = 0; r < 2; r++) {
    float v[4][8], sum = 0.f;
    #pragma unroll
    for (int j = 0; j < 4; j++) {
      unpack8(xv[r][j], v[j]);
      sum += ((v[j][0] + v[j][1]) + (v[j][2] + v[j][3])) + ((v[j][4] + v[j][5]) + (v[j][6] + v[j][7]));
    }
    #pragma unroll
    for (int o = 16; o > 0; o >>= 1) sum += __shfl_xor_sync(0xffffffffu, sum, o);
    const float mean = sum * (1.0f / T_D);
    float q = 0.f;
    #pragma unroll
    for (int j = 0; j < 4; j++)
      #pragma unroll
      for (int i = 0; i < 8; i++) { const float d = v[j][i] - mean; q = fmaf(d, d, q); }
    #pragma unroll
    for (int o = 16; o > 0; o >>= 1) q += __shfl_xor_sync(0xffffffffu, q, o);
    const uint32_t mb2 = pack_bf16(mean, mean);
    const float inv = rcp_approx(rbf(sqrt_approx(rbf(rbf(q * (1.0f / T_D)) + 1e-05f))));
    #pragma unroll
    for (int j = 0; j < 4; j++) {
      xv[r][j].x = ln_norm2(xv[r][j].x, mb2, inv); xv[r][j].y = ln_norm2(xv[r][j].y, mb2, inv);
      xv[r][j].z = ln_norm2(xv[r][j].z, mb2, inv); xv[r][j].w = ln_norm2(xv[r][j].w, mb2, inv);
    }
  }
  TL_MARK2(5, t2 == 0);
  #pragma unroll 1
  for (int ph = 0; ph < 2; ph++) {
    if (first_cols == (ph == 0)) finish_parts(pa, pb, t2, scr + 8192);
    named_bar_sync(5, 256);
    if (ph) break;
    TL_MARK2(7, t2 == 0);
    const uint4 sa = lds_u32x4(scr + 8192 + lane * 16), c1 = lds_u32x4(scr + 8192 + 2048 + lane * 16);
    #pragma unroll
    for (int r = 0; r < 2; r++)
      *reinterpret_cast<uint4*>(g_h + (size_t)(row0 + r) * T_D + lane * 8) = make_uint4(badd2(bmul2(xv[r][0].x, c1.x), sa.x), badd2(bmul2(xv[r][0].y, c1.y), sa.y),
                                                                                        badd2(bmul2(xv[r][0].z, c1.z), sa.z), badd2(bmul2(xv[r][0].w, c1.w), sa.w));
    named_bar_sync(5, 256);
    TL_MARK2(18, t2 == 0);
    if (t2 == 0) red_release_add(&g_hcnt[32 * (1 + (blockIdx.x >> 3))], 1u);
    TL_MARK2(11, t2 == 0);
  }
  TL_MARK2(6, t2 == 0);
  #pragma unroll
  for (int j = 1; j < 4; j++) {
    const uint4 sa = lds_u32x4(scr + 8192 + (j * 32 + lane) * 16), c1 = lds_u32x4(scr + 8192 + 2048 + (j * 32 + lane) * 16);
    #pragma unroll
    for (int r = 0; r < 2; r++) {
      xv[r][j].x = badd2(bmul2(xv[r][j].x, c1.x), sa.x); xv[r][j].y = badd2(bmul2(xv[r][j].y, c1.y), sa.y);
      xv[r][j].z = badd2(bmul2(xv[r][j].z, c1.z), sa.z); xv[r][j].w = badd2(bmul2(xv[r][j].w, c1.w), sa.w);
    }
  }
  __syncwarp();
  if (lane == 0) mbar_arrive(b_head + (xv[1][3].w & zero));
  mbar_wait(b_go, 0);
  #pragma unroll
  for (int j = 1; j < 4; j++)
    #pragma unroll
    for (int r = 0; r < 2; r++) *reinterpret_cast<uint4*>(g_h + (size_t)(row0 + r) * T_D + j * 256 + lane * 8) = xv[r][j];
  named_bar_arrive(8, 288);
}

#define MOD_AT (b_empty + 8)
#define MOD_PF 0
#define MOD_SPLIT 16
__device__ __forceinline__ void mod_rest(uint32_t scr, uint32_t b_go, int t, const bf16* __restrict__ cvec, const bf16* __restrict__ w_mod, const bf16* __restrict__ w_r) {
  const int lane = t & 31;
  #pragma unroll 1
  for (int i = t; i < T_D / 2; i += 64) {
    const uint32_t c2 = *reinterpret_cast<const uint32_t*>(cvec + 2 * i);
    sts_u32(scr + i * 4, pack_bf16(silu_bf(bflo(c2)), silu_bf(bfhi(c2))));
  }
  named_bar_sync(11, 64);
  const bf16* wp = w_mod + (size_t)(2 * (t >> 2)) * (6 * T_D) + 2 * T_D + blockIdx.x * 32 + (t & 3) * 8;
  float acc[8];
  #pragma unroll
  for (int i = 0; i < 8; i++) acc[i] = 0.f;
  #pragma unroll 1
  for (int i = 0; i < 32; i += 2) {
    if (i == MOD_SPLIT) mbar_wait(b_go, 0);
    const uint4 w0 = ldg_nc_v4(wp), w1 = ldg_nc_v4(wp + 6 * T_D), w2 = ldg_nc_v4(wp + 32 * 6 * T_D), w3 = ldg_nc_v4(wp + 33 * 6 * T_D);
    wp += 64 * 6 * T_D;
    const uint32_t s0 = lds_u32(scr + (i * 16 + (t >> 2)) * 4), s1 = lds_u32(scr + (i * 16 + 16 + (t >> 2)) * 4);
    fma8(acc, bflo(s0), w0); fma8(acc, bfhi(s0), w1); fma8(acc, bflo(s1), w2); fma8(acc, bfhi(s1), w3);
  }
  #pragma unroll
  for (int j = 0; j < 4; j++) { const bool up = lane & 16; acc[j] = (up ? acc[4 + j] : acc[j]) + __shfl_xor_sync(0xffffffffu, up ? acc[j] : acc[4 + j], 16); }
  #pragma unroll
  for (int j = 0; j < 2; j++) { const bool up = lane & 8; acc[j] = (up ? acc[2 + j] : acc[j]) + __shfl_xor_sync(0xffffffffu, up ? acc[j] : acc[2 + j], 8); }
  { const bool up = lane & 4; acc[0] = (up ? acc[1] : acc[0]) + __shfl_xor_sync(0xffffffffu, up ? acc[0] : acc[1], 4); }
  if (t >= 32) sts_f32(scr + 2048 + lane * 4, acc[0]);
  named_bar_sync(11, 64);
  if (__shfl_sync(0xffffffffu, t, 0) < 32) {
    const int kind = blockIdx.x >> 5;
    float v = rbf(acc[0] + lds_f32(scr + 2048 + lane * 4));
    const int col = (blockIdx.x & 31) * 32 + (lane & 3) * 8 + (lane >> 2);
    uint8_t* dst = g_col + (col >> 7) * 1536;
    if (kind == 2) v = rbf(1.0f + v);
    float vw = v * __bfloat162float(w_r[col]);
    if (kind == 2) {
      const int c = col & 127, i = (c & ~15) + ((c >> 1) & 3) * 4 + ((c >> 3) & 1) * 2 + (c & 1);
      reinterpret_cast<bf16*>(dst)[i] = __float2bfloat16_rn(vw);
      reinterpret_cast<bf16*>(dst)[128 + i] = __float2bfloat16_rn(vw - rbf(vw));
    }
    reinterpret_cast<bf16*>(dst + 512 + (kind & 1) * 512 + (kind >> 1) * 256)[col & 127] = __float2bfloat16_rn(v);
    #pragma unroll
    for (int o = 16; o > 0; o >>= 1) vw += __shfl_xor_sync(0xffffffffu, vw, o);
    if (lane == 0 && (kind == 1 || kind == 2)) g_scal[95 - blockIdx.x] = vw;
  }
  #pragma unroll 1
  for (int i = blockIdx.x * 64 + t; i < (int)(sizeof(g_mail) / 16); i += 128 * 64) reinterpret_cast<uint4*>(&g_mail)[i] = make_uint4(0u, 0u, 0u, 0u);
  named_bar_sync(11, 64);
  if (t == 0) red_release_add(&g_hcnt[0], 1u);
}

#define HPOL_A pol_normal()
#define HPOL_B pol_normal()
#define HMAP_A &tmOl
#define HMAP_B &tmWo
constexpr int AT_NBLK = T_SEQ / 128;
constexpr float AT_HEAD = 7.0f;
constexpr int WO_LATE = 12;
constexpr int QP_STAG = 3;
constexpr int AT_SPLIT = 28, AT_PIN = 8, PINB = 4;
constexpr int AT_NFULL = 124;
constexpr int AT_PREG = 40, AT_CREG = 232;
constexpr uint32_t AT_SQ = 5 * 32768;
constexpr float AT_C = 0.08838834764831845f * 1.4426950408889634f;
constexpr float AT_RAW_LO = -16.0f, AT_RAW_HI = 24.0f;
constexpr float AT_RAW_SUM = 281474976710656.0f, AT_RAW_MIN = 9.094947017729282e-13f;
constexpr uint32_t AT_SBAR = AT_SQ + 65536 + 256;
constexpr uint32_t AT_SMEM = AT_SQ + 65536 + 3072;

__device__ __forceinline__ uint32_t ring_slot(uint32_t t) { return t - 5u * ((t * 205u) >> 10); }
__device__ __forceinline__ uint32_t qp_pos(uint32_t j, uint32_t it) { return 4u * it + (j & 3u) + ((j & 3u) == 3u ? it : 0u); }
__device__ __forceinline__ uint32_t ring_par(uint32_t t) { return ((t * 205u) >> 10) & 1u; }
__device__ __forceinline__ void softmax_rowmax(const float (&s)[64], float& mx0, float& mx1) {
  float a0 = fmaxf(s[0], s[1]), a1 = fmaxf(s[4], s[5]), a2 = fmaxf(s[8], s[9]), a3 = fmaxf(s[12], s[13]);
  float b0 = fmaxf(s[2], s[3]), b1 = fmaxf(s[6], s[7]), b2 = fmaxf(s[10], s[11]), b3 = fmaxf(s[14], s[15]);
  #pragma unroll
  for (int j = 4; j < 16; j += 4) {
    a0 = fmaxf(a0, fmaxf(s[4 * j + 0], s[4 * j + 1]));  b0 = fmaxf(b0, fmaxf(s[4 * j + 2], s[4 * j + 3]));
    a1 = fmaxf(a1, fmaxf(s[4 * j + 4], s[4 * j + 5]));  b1 = fmaxf(b1, fmaxf(s[4 * j + 6], s[4 * j + 7]));
    a2 = fmaxf(a2, fmaxf(s[4 * j + 8], s[4 * j + 9]));  b2 = fmaxf(b2, fmaxf(s[4 * j + 10], s[4 * j + 11]));
    a3 = fmaxf(a3, fmaxf(s[4 * j + 12], s[4 * j + 13])); b3 = fmaxf(b3, fmaxf(s[4 * j + 14], s[4 * j + 15]));
  }
  mx0 = fmaxf(fmaxf(a0, a1), fmaxf(a2, a3));
  mx1 = fmaxf(fmaxf(b0, b1), fmaxf(b2, b3));
  mx0 = fmaxf(mx0, __shfl_xor_sync(0xffffffffu, mx0, 1));
  mx1 = fmaxf(mx1, __shfl_xor_sync(0xffffffffu, mx1, 1));
  mx0 = fmaxf(mx0, __shfl_xor_sync(0xffffffffu, mx0, 2));
  mx1 = fmaxf(mx1, __shfl_xor_sync(0xffffffffu, mx1, 2));
}
__device__ __forceinline__ void softmax_sub(float (&s)[64], float mc0, float mc1) {
  #pragma unroll
  for (int j = 0; j < 16; j++) { s[4 * j] -= mc0; s[4 * j + 1] -= mc0; s[4 * j + 2] -= mc1; s[4 * j + 3] -= mc1; }
}
template <int LO, int HI>
__device__ __forceinline__ void softmax_exp(float (&s)[64]) {
  #pragma unroll
  for (int i = LO; i < HI; i++) s[i] = ex2_approx(s[i]);
}
__device__ __forceinline__ bool softmax_mode(const float (&s)[64], float& mc0, float& mc1) {
  softmax_rowmax(s, mc0, mc1);
  const bool raw = __all_sync(0xffffffffu, mc0 >= AT_RAW_LO && mc0 <= AT_RAW_HI && mc1 >= AT_RAW_LO && mc1 <= AT_RAW_HI);
  mc0 += AT_HEAD; mc1 += AT_HEAD;
  return raw;
}
__device__ __forceinline__ void rowsum_p(const uint32_t (&p)[32], uint32_t& t0, uint32_t& t1) {
  uint32_t a[16];
  #pragma unroll
  for (int i = 0; i < 8; i++) { a[2 * i] = badd2(p[4 * i], p[4 * i + 2]); a[2 * i + 1] = badd2(p[4 * i + 1], p[4 * i + 3]); }
  #pragma unroll
  for (int i = 0; i < 4; i++) { a[2 * i] = badd2(a[4 * i], a[4 * i + 2]); a[2 * i + 1] = badd2(a[4 * i + 1], a[4 * i + 3]); }
  t0 = badd2(badd2(a[0], a[2]), badd2(a[4], a[6]));
  t1 = badd2(badd2(a[1], a[3]), badd2(a[5], a[7]));
}
__device__ __forceinline__ void add_rowsum(const uint32_t (&p)[32], float& l0, float& l1) {
  uint32_t t0, t1;
  rowsum_p(p, t0, t1);
  l0 += bflo(t0) + bfhi(t0); l1 += bflo(t1) + bfhi(t1);
}
__device__ __forceinline__ void pack_p(uint32_t (&p)[32], const float (&s)[64]) {
  #pragma unroll
  for (int i = 0; i < 32; i++) p[i] = pack_bf16(s[2 * i], s[2 * i + 1]);
}
__device__ __noinline__ void attn_rows_exact(uint32_t sq, uint32_t so, int hsel, const bf16* __restrict__ kh, const bf16* __restrict__ vh) {
  const int warp = (threadIdx.x >> 5) & 3, lane = threadIdx.x & 31;
  const size_t hofs = (size_t)((blockIdx.x < 128 ? blockIdx.x >> 4 : 15) * 2 + hsel) * T_SEQ * T_DH;
  kh += hofs; vh += hofs;
  #pragma unroll 1
  for (int r = 16 * warp; r < 16 * warp + 16; r++) {
    const uint32_t ad = (lane >> 4) * 16384 + r * 128 + ((((lane & 15) >> 1) ^ (r & 7)) << 4) + (lane & 1) * 8;
    uint2 qv; asm volatile("ld.shared.v2.u32 {%0, %1}, [%2];" : "=r"(qv.x), "=r"(qv.y) : "r"(sq + ad) : "memory");
    const float q0 = bflo(qv.x), q1 = bfhi(qv.x), q2 = bflo(qv.y), q3 = bfhi(qv.y);
    float m = -INFINITY, l = 0.f, o0 = 0.f, o1 = 0.f, o2 = 0.f, o3 = 0.f;
    #pragma unroll 1
    for (int key = 0; key < T_SEQ; key++) {
      const uint2 kv = *reinterpret_cast<const uint2*>(kh + (size_t)key * T_DH + lane * 4);
      const uint2 vv = *reinterpret_cast<const uint2*>(vh + (size_t)key * T_DH + lane * 4);
      float sc = (q0 * bflo(kv.x) + q1 * bfhi(kv.x)) + (q2 * bflo(kv.y) + q3 * bfhi(kv.y));
      #pragma unroll
      for (int o = 16; o > 0; o >>= 1) sc += __shfl_xor_sync(0xffffffffu, sc, o);
      const float mn = fmaxf(m, sc);
      const float al = (m == mn) ? 1.0f : ex2_approx(m - mn), p = rbf(ex2_approx(sc - mn));
      m = mn;
      l = fmaf(l, al, p);
      o0 = fmaf(o0, al, p * bflo(vv.x)); o1 = fmaf(o1, al, p * bfhi(vv.x));
      o2 = fmaf(o2, al, p * bflo(vv.y)); o3 = fmaf(o3, al, p * bfhi(vv.y));
    }
    const float inv = rcp_approx(l);
    asm volatile("st.shared.v2.u32 [%0], {%1, %2};" :: "r"(so + ad), "r"(pack_bf16(o0 * inv, o1 * inv)), "r"(pack_bf16(o2 * inv, o3 * inv)) : "memory");
  }
}
__device__ __forceinline__ void issue_qk(float (&s)[64], const uint32_t (&q)[32], uint32_t k_lo) {
  wgmma_fence();
  wgmma_m64n128k16_rs<0>(s, q[0], q[1], q[2], q[3], k_lo, 0);
  wgmma_m64n128k16_rs<2>(s, q[4], q[5], q[6], q[7], k_lo, 1);
  wgmma_m64n128k16_rs<4>(s, q[8], q[9], q[10], q[11], k_lo, 1);
  wgmma_m64n128k16_rs<6>(s, q[12], q[13], q[14], q[15], k_lo, 1);
  wgmma_m64n128k16_rs<1024>(s, q[16], q[17], q[18], q[19], k_lo, 1);
  wgmma_m64n128k16_rs<1026>(s, q[20], q[21], q[22], q[23], k_lo, 1);
  wgmma_m64n128k16_rs<1028>(s, q[24], q[25], q[26], q[27], k_lo, 1);
  wgmma_m64n128k16_rs<1030>(s, q[28], q[29], q[30], q[31], k_lo, 1);
  wgmma_commit();
}
__device__ __forceinline__ void issue_pv(float (&o)[64], const uint32_t (&p)[32], uint32_t v_lo, int accumulate) {
  wgmma_fence();
  wgmma_m64n128k16_rs_tb<0>(o, p[0], p[1], p[2], p[3], v_lo, accumulate);
  wgmma_m64n128k16_rs_tb<128>(o, p[4], p[5], p[6], p[7], v_lo, 1);
  wgmma_m64n128k16_rs_tb<256>(o, p[8], p[9], p[10], p[11], v_lo, 1);
  wgmma_m64n128k16_rs_tb<384>(o, p[12], p[13], p[14], p[15], v_lo, 1);
  wgmma_m64n128k16_rs_tb<512>(o, p[16], p[17], p[18], p[19], v_lo, 1);
  wgmma_m64n128k16_rs_tb<640>(o, p[20], p[21], p[22], p[23], v_lo, 1);
  wgmma_m64n128k16_rs_tb<768>(o, p[24], p[25], p[26], p[27], v_lo, 1);
  wgmma_m64n128k16_rs_tb<896>(o, p[28], p[29], p[30], p[31], v_lo, 1);
  wgmma_commit();
}
__device__ __forceinline__ void block_end(uint32_t zero, uint32_t bar) {
  #pragma unroll 1
  for (uint32_t i = 0; i < zero; i++) mbar_arrive(bar);
}
__device__ __forceinline__ void rescale_o(float (&o)[64], float al0, float al1) {
  #pragma unroll
  for (int j = 0; j < 16; j++) { o[4 * j] *= al0; o[4 * j + 1] *= al0; o[4 * j + 2] *= al1; o[4 * j + 3] *= al1; }
}

__device__ __forceinline__ void stage_o(const float (&o)[64], float i0, float i1, uint32_t dst, int lane) {
  #pragma unroll
  for (int J = 0; J < 16; J += 2)
    stmatrix_x4(dst + (J >> 3) * 16384 + ((((J & 7) + (lane >> 4)) ^ (lane & 7)) << 4),
                pack_bf16(o[4 * J + 0] * i0, o[4 * J + 1] * i0), pack_bf16(o[4 * J + 2] * i1, o[4 * J + 3] * i1),
                pack_bf16(o[4 * J + 4] * i0, o[4 * J + 5] * i0), pack_bf16(o[4 * J + 6] * i1, o[4 * J + 7] * i1));
}
__device__ __forceinline__ bool finish_l(float& l0, float& l1) {
  l0 += __shfl_xor_sync(0xffffffffu, l0, 1); l1 += __shfl_xor_sync(0xffffffffu, l1, 1);
  l0 += __shfl_xor_sync(0xffffffffu, l0, 2); l1 += __shfl_xor_sync(0xffffffffu, l1, 2);
  const bool redo = __any_sync(0xffffffffu, !(l0 <= AT_RAW_SUM && l1 <= AT_RAW_SUM && l0 >= AT_RAW_MIN && l1 >= AT_RAW_MIN));
  l0 = rcp_approx(l0); l1 = rcp_approx(l1);
  return redo;
}
template <int J0>
__device__ __forceinline__ void stage_q(const float (&acc)[128], float c, uint32_t dst, int lane) {
  #pragma unroll
  for (int J = J0; J < J0 + 16; J += 2)
    stmatrix_x4(dst + (J >> 3) * 16384 + ((((J & 7) + (lane >> 4)) ^ (lane & 7)) << 4),
                pack_bf16(acc[4 * J + 0] * c, acc[4 * J + 1] * c), pack_bf16(acc[4 * J + 2] * c, acc[4 * J + 3] * c),
                pack_bf16(acc[4 * J + 4] * c, acc[4 * J + 5] * c), pack_bf16(acc[4 * J + 6] * c, acc[4 * J + 7] * c));
}
__device__ __forceinline__ void store_o(const CUtensorMap* tmO, uint32_t src, int head, int row) {
  tma_store_2d(tmO, src, head * T_DH, row);
  tma_store_2d(tmO, src + 16384, head * T_DH + 64, row);
  bulk_commit();
}
__device__ __forceinline__ void mma_bf16(float (&d)[4], uint32_t a0, uint32_t a1, uint32_t a2, uint32_t a3, uint32_t b0, uint32_t b1) {
  asm volatile("mma.sync.aligned.m16n8k16.row.col.f32.bf16.bf16.f32 {%0, %1, %2, %3}, {%4, %5, %6, %7}, {%8, %9}, {%0, %1, %2, %3};"
               : "+f"(d[0]), "+f"(d[1]), "+f"(d[2]), "+f"(d[3]) : "r"(a0), "r"(a1), "r"(a2), "r"(a3), "r"(b0), "r"(b1));
}
struct GemvSel { uint32_t lo0, hi0, lo1, hi1; };
__device__ __forceinline__ GemvSel gemv_sel(int lane) {
  const uint32_t lo = (lane & 8) ? 0x1044u : 0x4410u, hi = (lane & 8) ? 0x3244u : 0x4432u;
  GemvSel s; s.lo0 = (lane & 16) ? 0x4444u : lo; s.hi0 = (lane & 16) ? 0x4444u : hi; s.lo1 = (lane & 16) ? lo : 0x4444u; s.hi1 = (lane & 16) ? hi : 0x4444u;
  return s;
}
#define GEMV_B0(j, h, s) __byte_perm((j) < 2 ? (h).x : (h).y, 0u, ((j) & 1) ? (s).hi0 : (s).lo0)
#define GEMV_B1(j, h, s) __byte_perm((j) < 2 ? (h).x : (h).y, 0u, ((j) & 1) ? (s).hi1 : (s).lo1)
__device__ __forceinline__ float4 gemv_out(const float (&d)[4], int lane) {
  const bool tk = lane & 1;
  const float r0 = __shfl_xor_sync(0xffffffffu, tk ? d[0] : d[1], 1), r1 = __shfl_xor_sync(0xffffffffu, tk ? d[2] : d[3], 1);
  return tk ? make_float4(r0, d[1], r1, d[3]) : make_float4(d[0], r0, d[2], r1);
}
#define OG_NG 8
#define HOIST 1
#define PUT_N 2
#define H_STAG 2
#define NOZERO 1
#define PVPIN 0
#define QKPIN 0
#define ALIGN 1
#define AL_P 60
#define AL_SLEEP 1200
#define AL_MAX 800
#define AL_ADD 0
#define OG_PRE 10
#define OG_JOBS 7
#define OG_GRP 7
#define LD_FIRST 1
#define LD_STAG (OG_GRP / 2)
constexpr int OG_ST = 5, OG_NKB = T_DQKV / 64 - OG_PRE, OG_MOE = T_F / 32;
__device__ __forceinline__ int pre_loc(int job) {
  const int step = ((job >> 4) << 2) + (job & 3);
  return (step < OG_JOBS ? 2 * step : step < 2 * OG_JOBS ? 2 * (step - OG_JOBS) + 1 : step) * 4 + ((job >> 2) & 3);
}
__device__ __forceinline__ int pre_kb(int i) { return (i >> 1) * 4 + (i & 1); }
__device__ __forceinline__ int own_kb(int i) { return i < (OG_PRE & ~1) ? pre_kb(i) + 2 : i + OG_PRE; }
constexpr int OG_POS = 8;
constexpr uint32_t OG_STAGE = 32768;
constexpr uint32_t OG_SCOL = AT_SBAR + 512;
constexpr uint32_t OG_SMISC = AT_SBAR + 2048;
constexpr int OG_XPOS = OG_POS + OG_NKB;
constexpr uint32_t OG_SWD = AT_SQ, OG_PSLOT = AT_SQ;
constexpr uint32_t OG_XSLOT = (OG_XPOS % OG_ST) * OG_STAGE;
constexpr uint32_t OG_OSLOT = ((OG_XPOS + 1) % OG_ST) * OG_STAGE;
constexpr uint32_t OG_SH2 = ((OG_XPOS + 2) % OG_ST) * OG_STAGE;
constexpr uint32_t OG_SRED = ((OG_XPOS + 3) % OG_ST) * OG_STAGE;
constexpr uint32_t OG_SSTAT = OG_SRED + 16384;
constexpr uint32_t OG_SGU = OG_SRED + 8192;
constexpr uint32_t OG_SFIN = OG_SGU + 256;
#define OGM 2
#define OG_MT(b) (((b) >> OGM) & 15)
#define OG_NT(b) (((b) & ((1 << OGM) - 1)) + (((b) >> (4 + OGM)) << OGM))
#define TAIL_SETUP \
  const uint32_t bar_full = sbase + AT_SBAR, bar_empty = bar_full + 40; \
  const uint32_t bar_wd = bar_full + 168, bar_col = bar_full + 176, bar_out = bar_full + 184, bar_end = bar_full + 192; \
  const uint32_t bar_key = bar_full + 200, bar_h2 = bar_full + 208, bar_sel = bar_full + 216; \
  const int mt = OG_MT(blockIdx.x), nt = OG_NT(blockIdx.x); \
  const int m0 = mt * 128, n0 = nt * 128; \
  const bool has_moe = (int)blockIdx.x < OG_MOE; \
  (void)bar_empty; (void)bar_wd; (void)bar_col; (void)bar_out; (void)bar_end; (void)bar_key; (void)bar_h2; (void)bar_sel; (void)m0; (void)n0; (void)has_moe;

__device__ __forceinline__ void tail_producer(uint32_t sbase, uint32_t ph, uint64_t pol, const CUtensorMap* tmA, const CUtensorMap* tmB, const CUtensorMap* tmX) {
  TAIL_SETUP
  uint32_t stage = OG_POS % OG_ST;
  int kb = 0;
  #pragma unroll 1
  for (int seg = 0; seg < 2; seg++) {
    mbar_wait(bar_full + 264, seg);
    fence_proxy_async_global();
    const int end = seg == 0 ? 32 - OG_PRE : OG_NKB;
    #pragma unroll 1
    for (; kb < end; kb++) {
      const uint32_t fb = bar_full + 8 * stage, sa = sbase + stage * OG_STAGE;
      const int k0 = own_kb(kb) * 64;
      mbar_wait(bar_empty + 8 * stage, ph);
      mbar_expect_tx(fb, OG_STAGE);
      tma_load_3d_hint(sa + 16384, tmB, k0, 2 * nt, fb, pol);
      tma_load_2d_hint(sa, tmA, k0, m0, fb, pol);
      if (++stage == OG_ST) { stage = 0; ph ^= 1; }
    }
  }
  mbar_wait(bar_empty + 8 * (OG_XPOS % OG_ST), ph);
  mbar_expect_tx(bar_full + 8 * (OG_XPOS % OG_ST), OG_STAGE);
  tma_load_3d_hint(sbase + OG_XSLOT, tmX, m0, 2 * nt, bar_full + 8 * (OG_XPOS % OG_ST), pol);
}

__device__ __forceinline__ uint32_t bfma2(uint32_t a, uint32_t b, uint32_t c) { uint32_t r; asm("fma.rn.bf16x2 %0, %1, %2, %3;" : "=r"(r) : "r"(a), "r"(b), "r"(c)); return r; }
__device__ __forceinline__ uint32_t out2(uint32_t x1, uint32_t mb2, uint32_t ih, uint32_t il, uint32_t c1, uint32_t sb, uint32_t gb) {
  const uint32_t d = bsub2(x1, mb2);
  const uint32_t h2 = badd2(bmul2(bfma2(d, ih, bmul2(d, il)), c1), sb);
  return badd2(x1, bmul2(gb, bfma2(h2, 0u, h2)));
}
#define OGTIME gtime()
#define PRE_N 1
#define PRE_PACE 150
#define WD_PACE 300
__device__ __forceinline__ void tail_exchange(uint32_t sbase, const CUtensorMap* tmOut, const bf16* __restrict__ w_down, bf16* __restrict__ out) {
    TAIL_SETUP
    const int lane = threadIdx.x & 31, wi = __shfl_sync(0xffffffffu, threadIdx.x >> 5, 0);
    if (wi == 3) {
      mbar_wait(bar_full + 264, 0);
      if (blockIdx.x < AT_NFULL) {
        uint32_t a, b;
        asm volatile("ld.relaxed.gpu.global.u32 %0, [%1];" : "=r"(a) : "l"(g_smid + 32 + blockIdx.x - lane) : "memory");
        b = __shfl_down_sync(0xffffffffu, a, 1);
        unsigned int* tm = g_tmax + blockIdx.x - min((int)blockIdx.x, __ffs(__ballot_sync(0xffffffffu, b >= a)) - 1);
        mbar_wait(bar_full + 312, 0);
        if (lane == 0) {
          asm volatile("mov.u32 %0, %%globaltimer_lo;" : "=r"(a));
          asm volatile("red.relaxed.gpu.global.max.u32 [%0], %1;" :: "l"(tm), "r"(a) : "memory");
          __nanosleep(AL_SLEEP);
          asm volatile("ld.relaxed.gpu.global.u32 %0, [%1];" : "=r"(b) : "l"(tm) : "memory");
          b -= a;
          sts_u32(sbase + OG_SMISC + 32, (b < AL_MAX ? b * 13 / 8 : 0u) + AL_ADD);
          mbar_arrive(bar_full + 320);
        }
        named_bar_sync(15, 32);
      }
      mbar_wait(bar_full + 264, 1);
      float a = g_scal[lane], b = g_scal[32 + lane];
      #pragma unroll
      for (int i = 0; i < 3; i++) {
        const uint4 v = *reinterpret_cast<const uint4*>(g_col + nt * 1536 + i * 512 + lane * 16);
        sts_u32x4(sbase + OG_SCOL + i * 512 + lane * 16, v.x, v.y, v.z, v.w);
      }
      #pragma unroll
      for (int o = 16; o > 0; o >>= 1) { a += __shfl_xor_sync(0xffffffffu, a, o); b += __shfl_xor_sync(0xffffffffu, b, o); }
      if (lane == 0) { sts_f32x2(sbase + OG_SMISC, a, b); mbar_arrive(bar_col); }
    } else if (wi == 2) {
      if (elect_one()) {
        const uint32_t b_free = bar_full + (blockIdx.x < AT_NFULL ? 80 : 160);
        mbar_wait(b_free, 0); mbar_wait(b_free, 1);
        #pragma unroll 1
        for (unsigned int i = 0; i < (1u << 20) && ld_acquire(&g_hcnt[32 * (1 + mt) + 4 + (nt >> 1)]) == 0u; i++) __nanosleep(200);
        TL_MARK2(23, true);
        fence_proxy_async_global();
        TL_MARK2(4, true);
        mbar_expect_tx(bar_full + 272, 32768);
        #pragma unroll 1
        for (int i = 0; i < PRE_N; i++) {
          bulk_load_hint(sbase + OG_PSLOT + i * (32768 / PRE_N), g_pre + pre_loc(mt * 4 + (nt >> 1)) * 4096 + (nt & 1) * 2048 + i * (2048 / PRE_N), 32768 / PRE_N,
                         bar_full + 272, policy_evict_first());
          if (PRE_N > 1) __nanosleep(PRE_PACE);
        }
      }
      named_bar_sync(14, 32);
      if (has_moe) {
        mbar_wait(bar_full + 96, 1); mbar_wait(bar_full + 304, 0);
        const uint64_t pol = policy_evict_first();
        #pragma unroll 1
        for (int r = 0; r < 32; r++) {
          __nanosleep(WD_PACE);
          #pragma unroll
          for (int j = 0; j < 4; j++)
            asm volatile("cp.async.cg.shared.global.L2::cache_hint [%0], [%1], 16, %2;" :: "r"(sbase + OG_SWD + (4 * j + (lane >> 3)) * 4096 + r * 128 + (((lane ^ r) & 7) << 4)),
                         "l"((const uint8_t*)w_down + (size_t)blockIdx.x * 65536 + r * 2048 + j * 512 + lane * 16), "l"(pol) : "memory");
        }
        asm volatile("cp.async.wait_all;" ::: "memory");
        __syncwarp();
        if (lane == 0) mbar_arrive(bar_wd);
      }
    }
    mbar_wait(bar_end, 0);
    TL_MARK2(22, lane == 0);
    if (wi == 0) {
      uint32_t k1 = 0u, k2 = 0u;
      #pragma unroll 1
      for (unsigned int spin = 0; spin < (1u << 22) && __any_sync(0xffffffffu, k1 == 0u); spin++) asm volatile("ld.relaxed.gpu.global.u32 %0, [%1];" : "=r"(k1) : "l"(g_key + lane) : "memory");
      TL_MARK2(28, lane == 0);
      warp_top2(k1, k2);
      if (lane == 0) {
        const uint32_t r1 = 0xffffu - (k1 & 0xffffu), r2 = 0xffffu - (k2 & 0xffffu);
        sts_u32x4(sbase + OG_SMISC + 64, r1, r2, (r1 >> 7) * 2, (r2 >> 7) * 2 + ((r1 >> 7) == (r2 >> 7)));
        mbar_arrive(bar_sel);
      }
    } else if (wi < 3) {
          mbar_wait(bar_key, 0);
          const uint4 kk = lds_u32x4(sbase + OG_SSTAT + 1024 + lane * 16);
          uint32_t k1 = max(kk.x, kk.y), k2 = min(kk.x, kk.y);
          k2 = max(max(k2, min(kk.z, kk.w)), min(k1, max(kk.z, kk.w))); k1 = max(k1, max(kk.z, kk.w));
          warp_top2(k1, k2);
          if (wi == 1) {
            if (lane == 0 && nt == (mt & 7)) st_relaxed2(g_key + mt * 2, k1, k2);
            TL_MARK2(27, lane == 0);
          } else {
            const uint32_t r = (~((lane & 16) ? k2 : k1)) & 127u, ch = lane & 15;
            const uint2 st = lds_u32x2(sbase + OG_SSTAT + r * 8);
            const uint4 xc = lds_u32x4(sbase + OG_XSLOT + (ch >> 3) * 16384 + r * 128 + (((ch ^ r) & 7) << 4));
            const uint4 c1 = lds_u32x4(sbase + OG_SCOL + 768 + ch * 16), sh = lds_u32x4(sbase + OG_SCOL + 1024 + ch * 16);
            const float inr = __uint_as_float(st.y);
            float* dst = reinterpret_cast<float*>(g_cand + (mt * 2 + (lane >> 4)) * 256 + nt * 16 + ch);
            st_tagged4(dst + 512, __uint_as_float(ln_mod2(xc.x, st.x, inr, c1.x, sh.x)), __uint_as_float(ln_mod2(xc.y, st.x, inr, c1.y, sh.y)),
                       __uint_as_float(ln_mod2(xc.z, st.x, inr, c1.z, sh.z)), __uint_as_float(ln_mod2(xc.w, st.x, inr, c1.w, sh.w)));
            st_tagged4(dst, __uint_as_float(xc.x), __uint_as_float(xc.y), __uint_as_float(xc.z), __uint_as_float(xc.w));
          }
    }
    mbar_wait(bar_sel, 0);
    const int sel0 = (int)lds_u32(sbase + OG_SMISC + 64), sel1 = (int)lds_u32(sbase + OG_SMISC + 68);
    mbar_wait(bar_out, 0);
    if ((sel0 >> 7) == mt || (sel1 >> 7) == mt) {
      #pragma unroll 2
      for (int i = 0; i < 16; i++) {
        const int r = i * 8 + (threadIdx.x >> 4), ch = threadIdx.x & 15;
        if (m0 + r != sel0 && m0 + r != sel1)
          *reinterpret_cast<uint4*>(out + (size_t)(m0 + r) * T_D + n0 + ch * 8) =
              lds_u32x4(sbase + OG_OSLOT + (ch >> 3) * 16384 + r * 128 + (((ch & 7) ^ (r & 7)) << 4));
      }
    } else if (threadIdx.x == 0) {
      tma_store_2d(tmOut, sbase + OG_OSLOT, n0, m0);
      tma_store_2d(tmOut, sbase + OG_OSLOT + 16384, n0 + 64, m0);
      bulk_commit();
    }
    if (blockIdx.x == 0 && threadIdx.x < 68) *reinterpret_cast<uint4*>(g_hcnt + 32 * (threadIdx.x >> 2) + 4 * (threadIdx.x & 3)) = make_uint4(0u, 0u, 0u, 0u);
    if (threadIdx.x < 64) g_modpart[blockIdx.x * 64 + threadIdx.x] = 0.f;
    if (ALIGN && threadIdx.x == 64) g_tmax[blockIdx.x] = 0u;
    {
      const int tk = blockIdx.x >> 6, c0 = (blockIdx.x & 63) * 16;
      const uint32_t gb2 = *reinterpret_cast<const uint32_t*>(g_col + (c0 >> 7) * 1536 + 512 + 768 + ((c0 & 127) + (threadIdx.x & 14)) * 2);
      const uint32_t* xp = reinterpret_cast<const uint32_t*>(g_cand + lds_u32(sbase + OG_SMISC + 72 + tk * 4) * 256) + ((c0 + (threadIdx.x & 14)) >> 1);
      uint32_t x2 = 0u;
      #pragma unroll 1
      for (unsigned int spin = 0; spin < (1u << 20) && __any_sync(0xffffffffu, x2 == 0u); spin++) asm volatile("ld.relaxed.gpu.global.u32 %0, [%1];" : "=r"(x2) : "l"(xp) : "memory");
      const float* src = g_ypart + (size_t)((threadIdx.x >> 2) * 2 + tk) * T_D + c0 + (threadIdx.x & 3) * 4;
      const bool four = threadIdx.x < (OG_MOE - 96) * 4;
      mbar_wait(bar_h2, 0);
      if (threadIdx.x == 0) hint_wait(CNT_Y, (uint32_t)OG_MOE);
      named_bar_sync(10, 128);
      float4 p0, p1, p2, p3;
      #pragma unroll 1
      for (unsigned int spin = 0; spin < (1u << 20); spin++) {
        p0 = ld_tagged4(src); p1 = ld_tagged4(src + 64 * T_D); p2 = ld_tagged4(src + 128 * T_D); p3 = ld_tagged4(four ? src + 192 * T_D : src);
        if (__all_sync(0xffffffffu, tagged4(p0) & tagged4(p1) & tagged4(p2) & tagged4(p3))) break;
      }
      if (four) { p2.x += p3.x; p2.y += p3.y; p2.z += p3.z; p2.w += p3.w; }
      p0.x = (p0.x + p1.x) + p2.x; p0.y = (p0.y + p1.y) + p2.y; p0.z = (p0.z + p1.z) + p2.z; p0.w = (p0.w + p1.w) + p2.w;
      #pragma unroll
      for (int o = 4; o <= 16; o <<= 1) {
        p0.x += __shfl_xor_sync(0xffffffffu, p0.x, o); p0.y += __shfl_xor_sync(0xffffffffu, p0.y, o);
        p0.z += __shfl_xor_sync(0xffffffffu, p0.z, o); p0.w += __shfl_xor_sync(0xffffffffu, p0.w, o);
      }
      if (lane < 4) sts_f32x4(sbase + OG_SFIN + (threadIdx.x >> 5) * 64 + lane * 16, p0.x, p0.y, p0.z, p0.w);
      named_bar_sync(10, 128);
      TL_MARK2(21, threadIdx.x == 0);
      if (threadIdx.x < 16) {
        const uint32_t ya = sbase + OG_SFIN + threadIdx.x * 4, rp = sbase + OG_SMISC + 192 + tk * 16;
        float y = (lds_f32(ya) + lds_f32(ya + 64)) + (lds_f32(ya + 128) + lds_f32(ya + 192));
        const float r = rbf((lds_f32(rp) + lds_f32(rp + 4)) + (lds_f32(rp + 8) + lds_f32(rp + 12)));
        const float rs = rbf(sigmoid_f(r));
        const uint32_t h2p = lds_u32(sbase + OG_SH2 + tk * 2048 + (c0 + (threadIdx.x & 14)) * 2);
        const float fh = (lane & 1) ? bfhi(h2p) : bflo(h2p);
        y = rbf(y);
        y = rbf(y * rs);
        const float upd = rbf(rbf(fh * 0.0f) + y);
        out[(size_t)(tk ? sel1 : sel0) * T_D + c0 + threadIdx.x] =
            __float2bfloat16_rn(((lane & 1) ? bfhi(x2) : bflo(x2)) + rbf(((lane & 1) ? bfhi(gb2) : bflo(gb2)) * rbf(fh + upd)));
      }
      if (threadIdx.x == 0) bulk_wait_read<0>();
    }
    TL_END(4, threadIdx.x == 0);
}

__device__ __forceinline__ void load_pre(uint4* pre, uint32_t sbase, uint32_t buf, int t2) {
  mbar_wait(sbase + AT_SBAR + 272, 0);
  #pragma unroll
  for (int i = 0; i < 8; i++) pre[i] = lds_u32x4(sbase + buf + i * 4096 + t2 * 16);
}
__device__ __forceinline__ void tail_consumer(uint32_t sbase, const uint4 (&pre)[8], int cwg, const bf16* __restrict__ w_r, const bf16* __restrict__ w_gate, const bf16* __restrict__ w_up) {
    TAIL_SETUP
    const int tid = threadIdx.x & 127, t2 = threadIdx.x - 128;
    const int warp = tid >> 5, lane = tid & 31, w8 = t2 >> 5;
    const uint32_t dbase = (sbase & 0x3FFFFu) >> 4;
    const uint32_t a_base = dbase + ((cwg * 8192) >> 4) + (1u << 16);
    const uint32_t b_base = dbase + (16384 >> 4) + (512u << 16);
    TL_MARK2(25, threadIdx.x == 128);
    const uint64_t pol = policy_evict_first();
    const bf16* pw = ((lane & 16) ? w_up : w_gate) + (size_t)(w8 * 128 + (lane & 3) * 4) * T_F + (has_moe ? blockIdx.x : 0) * 32 + ((lane >> 2) & 3) * 8;
    uint4 wv[32];
    float acc[64];
    #pragma unroll
    for (int i = 0; i < 8; i++) {
      acc[8 * i] = bflo(pre[i].x); acc[8 * i + 1] = bfhi(pre[i].x); acc[8 * i + 2] = bflo(pre[i].y); acc[8 * i + 3] = bfhi(pre[i].y);
      acc[8 * i + 4] = bflo(pre[i].z); acc[8 * i + 5] = bfhi(pre[i].z); acc[8 * i + 6] = bflo(pre[i].w); acc[8 * i + 7] = bfhi(pre[i].w);
    }
    if (blockIdx.x < AT_NFULL) {
      const uint32_t c0 = clock_lo();
      mbar_wait(bar_full + 320, 0);
      const uint32_t d = lds_u32(sbase + OG_SMISC + 32);
      while (clock_lo() - c0 < d) {}
    }
    {
      uint32_t stage = OG_POS % OG_ST, phase = (OG_POS / OG_ST) & 1, prev = 12;
      int kb = 0;
      #pragma unroll
      for (int g = 0; g <= OG_NG; g++) {
        const int end = g == OG_NG ? OG_NKB : LD_FIRST + g * OG_GRP + LD_STAG * cwg;
        #pragma unroll 1
        do {
          mbar_wait(bar_full + 8 * stage, phase);
          const uint32_t a_lo = a_base + stage * (OG_STAGE >> 4), b_lo = b_base + stage * (OG_STAGE >> 4);
          wgmma_fence();
          wgmma_m64n128k16_ss_tb<0, 0>(acc, a_lo, b_lo, 1);
          wgmma_m64n128k16_ss_tb<2, 128>(acc, a_lo, b_lo, 1);
          wgmma_m64n128k16_ss_tb<4, 256>(acc, a_lo, b_lo, 1);
          wgmma_m64n128k16_ss_tb<6, 384>(acc, a_lo, b_lo, 1);
          wgmma_commit();
          wgmma_wait<1>();
          if (tid == 0) mbar_arrive(bar_empty + 8 * prev);
          prev = stage;
          if (++stage == OG_ST) { stage = 0; phase ^= 1; }
        } while (++kb < end);
        #pragma unroll
        for (int j = 4 * g; j < 4 * g + 4 && j < 32; j++) wv[j] = ldg_stream_v4(pw + (size_t)(16 * (j >> 2) + (j & 3)) * T_F, pol);
      }
    }
    mbar_wait(bar_col, 0);
    mbar_wait(bar_full + 8 * (OG_XPOS % OG_ST), (OG_XPOS / OG_ST) & 1);
    if (__builtin_expect(!has_moe, 0)) {
      load_pre(wv, sbase, AT_SQ, t2);
    }
    wgmma_wait<0>();
    fence_regs(acc);
    if (__builtin_expect(!has_moe, 0)) {
      #pragma unroll
      for (int i = 0; i < 8; i++) {
        acc[8 * i] += bflo(wv[i].x); acc[8 * i + 1] += bfhi(wv[i].x); acc[8 * i + 2] += bflo(wv[i].y); acc[8 * i + 3] += bfhi(wv[i].y);
        acc[8 * i + 4] += bflo(wv[i].z); acc[8 * i + 5] += bfhi(wv[i].z); acc[8 * i + 6] += bflo(wv[i].w); acc[8 * i + 7] += bfhi(wv[i].w);
      }
    }
    if (tid == 0) mbar_arrive(bar_end);
    TL_MARK2(9, lane == 0);
    const int q2 = 2 * (lane & 3);
    const uint32_t frag = (64 * cwg + 16 * warp + (lane & 7) + 8 * ((lane >> 3) & 1)) * 128;
    const int fsw = lane & 7, fhi = lane >> 4;
    {
      float dl[4] = {0.f, 0.f, 0.f, 0.f}, da[4] = {0.f, 0.f, 0.f, 0.f}, db[4] = {0.f, 0.f, 0.f, 0.f};
      const uint32_t tb = sbase + OG_SCOL + (lane & 8) * 32 + (lane & 3) * 8, g = lane >> 2;
      const uint32_t msk = (g == 1 || g == 2) ? 0xffffffffu : 0u, one = g == 0 ? 0x3F803F80u : 0u;
      #pragma unroll
      for (int J = 0; J < 16; J += 2) {
        const uint32_t ad = sbase + OG_XSLOT + (J >> 3) * 16384 + frag + ((((J & 7) + fhi) ^ fsw) << 4);
        uint32_t xr[4];
        ldmatrix_x4(ad, xr[0], xr[1], xr[2], xr[3]);
        const uint2 cw = lds_u32x2(tb + J * 16);
        #pragma unroll
        for (int h = 0; h < 2; h++) {
          const uint32_t ga = lds_u32(sbase + OG_SCOL + 512 + (8 * (J + h) + q2) * 2);
          xr[2 * h] = badd2(xr[2 * h], bmul2(ga, pack_bf16(acc[4 * (J + h)], acc[4 * (J + h) + 1])));
          xr[2 * h + 1] = badd2(xr[2 * h + 1], bmul2(ga, pack_bf16(acc[4 * (J + h) + 2], acc[4 * (J + h) + 3])));
        }
        stmatrix_x4(ad, xr[0], xr[1], xr[2], xr[3]);
        mma_bf16(dl, xr[0], xr[1], xr[2], xr[3], (cw.x & msk) | one, (cw.y & msk) | one);
        mma_bf16(da, xr[0], xr[1], xr[2], xr[3], xr[0], xr[2]);
        mma_bf16(db, xr[0], xr[1], xr[2], xr[3], xr[1], xr[3]);
      }
      {
        const int dsrc = (lane & ~3) + (g >> 1);
        const float qa = __shfl_sync(0xffffffffu, (g & 1) ? da[1] : da[0], dsrc), qb = __shfl_sync(0xffffffffu, (g & 1) ? db[3] : db[2], dsrc);
        const float e0 = __shfl_xor_sync(0xffffffffu, (lane & 1) ? dl[0] : dl[2], 1), e1 = __shfl_xor_sync(0xffffffffu, dl[3], 1);
        if ((lane & 3) < 2) {
          const bool hi = lane & 1;
          st_tagged4(reinterpret_cast<float*>(g_part1 + ((mt * 8 + w8) * 8 + nt) * 16 + g + (hi ? 8 : 0)),
                     hi ? e0 : dl[0], hi ? qb : qa, hi ? e1 + dl[2] : dl[1] + e0, 1.0f);
        }
      }
    }
    TL_MARK2(10, lane == 0);
    const uint4 wrv = ldg_nc_v4(w_r + tid * 8);
    uint4 wd[16];
    if (has_moe) mbar_wait(bar_wd, 0);
    #pragma unroll
    for (int i = 0; i < 16; i++) wd[i] = lds_u32x4(sbase + OG_SWD + w8 * 8192 + (i >> 3) * 4096 + (i & 6) * 512 + (i & 1) * 128 + (lane & 3) * 256 + (((lane >> 2) ^ (2 * (lane & 3) + (i & 1))) << 4));
    {
      const float* src = reinterpret_cast<const float*>(g_part1 + ((mt * 8 + w8) * 8 + (lane & 1) * 4) * 16 + (lane >> 1));
      float4 v, v1, v2, v3;
      #pragma unroll 1
      for (unsigned int spin = 0; spin < (1u << 22); spin++) {
        v = ld_tagged4(src); v1 = ld_tagged4(src + 64); v2 = ld_tagged4(src + 128); v3 = ld_tagged4(src + 192);
        if (__all_sync(0xffffffffu, tagged4(v) & tagged4(v1) & tagged4(v2) & tagged4(v3))) break;
        __nanosleep(100);
      }
      __syncwarp();
      TL_MARK2(26, lane == 0);
      v.x = (v.x + v1.x) + (v2.x + v3.x); v.y = (v.y + v1.y) + (v2.y + v3.y); v.z = (v.z + v1.z) + (v2.z + v3.z);
      v.x += __shfl_xor_sync(0xffffffffu, v.x, 1); v.y += __shfl_xor_sync(0xffffffffu, v.y, 1); v.z += __shfl_xor_sync(0xffffffffu, v.z, 1);
      const float mean = v.x * (1.0f / T_D);
      const float var = fmaxf(fmaf(-mean, mean, v.y * (1.0f / T_D)), 0.f);
      const uint32_t mb2 = pack_bf16(mean, mean);
      const float inv = rcp_approx(rbf(sqrt_approx(rbf(rbf(var) + 1e-05f))));
      {
        const float2 sc = lds_f32x2(sbase + OG_SMISC);
        const uint32_t key = rank_key(rbf(fmaf(fmaf(-bflo(mb2), sc.x, v.z), inv, sc.y)), m0 + 16 * w8 + (lane >> 1));
        mbar_wait(bar_end, 0);
        if (lane & 1) sts_u32(sbase + OG_SSTAT + 1024 + (16 * w8 + (lane >> 1)) * 4, key);
        else sts_u32x2(sbase + OG_SSTAT + (16 * w8 + (lane >> 1)) * 8, mb2, __float_as_uint(inv));
        __syncwarp();
        if (lane == 0) mbar_arrive(bar_key);
      }
      const uint32_t ih = pack_bf16(inv, inv), il = pack_bf16(inv - bflo(ih), inv - bflo(ih));
      const uint32_t mba = __shfl_sync(0xffffffffu, mb2, 2 * (lane >> 2)), mbb = __shfl_sync(0xffffffffu, mb2, 2 * (lane >> 2) + 16);
      const uint32_t iha = __shfl_sync(0xffffffffu, ih, 2 * (lane >> 2)), ihb = __shfl_sync(0xffffffffu, ih, 2 * (lane >> 2) + 16);
      const uint32_t ila = __shfl_sync(0xffffffffu, il, 2 * (lane >> 2)), ilb = __shfl_sync(0xffffffffu, il, 2 * (lane >> 2) + 16);
      #pragma unroll 2
      for (int J = 0; J < 16; J += 2) {
        const uint32_t off = (J >> 3) * 16384 + frag + ((((J & 7) + fhi) ^ fsw) << 4);
        uint32_t xr[4];
        ldmatrix_x4(sbase + OG_XSLOT + off, xr[0], xr[1], xr[2], xr[3]);
        #pragma unroll
        for (int h = 0; h < 2; h++) {
          const uint32_t ca = sbase + OG_SCOL + 512 + (8 * (J + h) + q2) * 2;
          const uint32_t c1 = lds_u32(ca + 256), sh = lds_u32(ca + 512), gb = lds_u32(ca + 768);
          xr[2 * h] = out2(xr[2 * h], mba, iha, ila, c1, sh, gb);
          xr[2 * h + 1] = out2(xr[2 * h + 1], mbb, ihb, ilb, c1, sh, gb);
        }
        stmatrix_x4(sbase + OG_OSLOT + off, xr[0], xr[1], xr[2], xr[3]);
      }
      fence_proxy_async();
      __syncwarp();
      if (lane == 0) mbar_arrive(bar_out);
      TL_MARK2(24, lane == 0);
    }
    {
      mbar_wait(bar_sel, 0);
      TL_MARK2(12, lane == 0);
      const float* src = reinterpret_cast<const float*>(g_cand + lds_u32(sbase + OG_SMISC + 72 + cwg * 4) * 256 + 128 + tid);
      float4 hf;
      #pragma unroll 1
      for (unsigned int spin = 0; spin < (1u << 20); spin++) { hf = ld_tagged4(src); if (__all_sync(0xffffffffu, tagged4(hf))) break; }
      const uint4 hv = make_uint4(__float_as_uint(hf.x), __float_as_uint(hf.y), __float_as_uint(hf.z), __float_as_uint(hf.w));
      sts_u32x4(sbase + OG_SH2 + t2 * 16, hv.x, hv.y, hv.z, hv.w);
      float v[8], wr[8];
      unpack8(hv, v); unpack8(wrv, wr);
      float r = 0.f;
      #pragma unroll
      for (int i = 0; i < 8; i++) r = fmaf(v[i], wr[i], r);
      #pragma unroll
      for (int o = 16; o > 0; o >>= 1) r += __shfl_xor_sync(0xffffffffu, r, o);
      if (lane == 0) sts_f32(sbase + OG_SMISC + 192 + w8 * 4, r);
    }
    named_bar_sync(9, 256);
    if (t2 == 0) mbar_arrive(bar_h2);
    TL_MARK2(13, lane == 0);
    if (has_moe) {
      const GemvSel sel = gemv_sel(lane);
      {
        float d[4][4];
        #pragma unroll
        for (int c = 0; c < 4; c++) { d[c][0] = 0.f; d[c][1] = 0.f; d[c][2] = 0.f; d[c][3] = 0.f; }
        #pragma unroll
        for (int st = 0; st < 8; st++) {
          const uint2 hb = lds_u32x2(sbase + OG_SH2 + ((lane >> 2) & 1) * 2048 + (w8 * 128 + st * 16 + (lane & 3) * 4) * 2);
          #pragma unroll
          for (int j = 0; j < 4; j++) mma_bf16(d[j], wv[4 * st + j].x, wv[4 * st + j].y, wv[4 * st + j].z, wv[4 * st + j].w, GEMV_B0(j, hb, sel), GEMV_B1(j, hb, sel));
        }
        #pragma unroll
        for (int e = 0; e < 4; e++) d[0][e] = (d[0][e] + d[1][e]) + (d[2][e] + d[3][e]);
        const float4 r = gemv_out(d[0], lane);
        sts_f32x4(sbase + OG_SRED + w8 * 512 + (((lane >> 4) * 2 + (lane & 1)) * 32 + ((lane >> 2) & 3) * 8 + (lane & 2) * 2) * 4, r.x, r.y, r.z, r.w);
      }
      named_bar_sync(9, 256);
      if (t2 < 64) {
        float gp[8], up[8];
        #pragma unroll
        for (int w = 0; w < 8; w++) { gp[w] = lds_f32(sbase + OG_SRED + w * 512 + t2 * 4); up[w] = lds_f32(sbase + OG_SRED + w * 512 + 256 + t2 * 4); }
        const float gs = ((gp[0] + gp[1]) + (gp[2] + gp[3])) + ((gp[4] + gp[5]) + (gp[6] + gp[7]));
        const float us = ((up[0] + up[1]) + (up[2] + up[3])) + ((up[4] + up[5]) + (up[6] + up[7]));
        asm volatile("st.shared.u16 [%0], %1;" :: "r"(sbase + OG_SGU + ((t2 & ~15) + ((t2 >> 1) & 3) * 4 + ((t2 >> 3) & 1) * 2 + (t2 & 1)) * 2), "h"((uint16_t)pack_bf16(silu_bf(rbf(gs)) * rbf(us), 0.f)) : "memory");
      }
      named_bar_sync(9, 256);
      TL_MARK2(20, threadIdx.x == 128);
      float d[4][4];
      #pragma unroll
      for (int c = 0; c < 4; c++) { d[c][0] = 0.f; d[c][1] = 0.f; d[c][2] = 0.f; d[c][3] = 0.f; }
      #pragma unroll
      for (int st = 0; st < 2; st++) {
        const uint2 g = lds_u32x2(sbase + OG_SGU + ((lane >> 2) & 1) * 64 + st * 32 + (lane & 3) * 8);
        #pragma unroll
        for (int j = 0; j < 4; j++) {
          const uint32_t b0 = GEMV_B0(j, g, sel), b1 = GEMV_B1(j, g, sel);
          mma_bf16(d[j & 1], wd[4 * st + j].x, wd[4 * st + j].y, wd[4 * st + j].z, wd[4 * st + j].w, b0, b1);
          mma_bf16(d[2 + (j & 1)], wd[8 + 4 * st + j].x, wd[8 + 4 * st + j].y, wd[8 + 4 * st + j].z, wd[8 + 4 * st + j].w, b0, b1);
        }
      }
      #pragma unroll
      for (int e = 0; e < 4; e++) { d[0][e] += d[1][e]; d[2][e] += d[3][e]; }
      const float4 y0 = gemv_out(d[0], lane), y1 = gemv_out(d[2], lane);
      float* yp = g_ypart + (size_t)(blockIdx.x * 2 + (lane & 1)) * T_D + w8 * 128 + (lane >> 2) * 8 + (lane & 2) * 2;
      st_tagged4(yp, y0.x, y0.y, y0.z, y0.w);
      st_tagged4(yp + 64, y1.x, y1.y, y1.z, y1.w);
      named_bar_sync(9, 256);
      if (t2 == 0) hint_arrive(CNT_Y);
    }
    TL_MARK2(14, threadIdx.x == 128);
    TL_CLK(4, 1, threadIdx.x == 128);
}

#define OG_JOBS2 (16 - OG_JOBS)
__device__ __forceinline__ int help_njobs() { return blockIdx.x < 128 ? OG_JOBS : OG_JOBS2; }
__device__ __forceinline__ int help_job(int i) {
  const int step = i + (blockIdx.x < 128 ? 0 : OG_JOBS);
  return (step & ~3) * 4 + (blockIdx.x & 3) * 4 + (step & 3);
}
__device__ __noinline__ void store_warp(uint32_t sbase, const CUtensorMap* tmO, int item0, int n_items) {
  if (elect_one()) {
    const uint32_t bars = sbase + AT_SBAR, b_q0 = bars + 80, b_ob = bars + 96, b_ordy = bars + 104, b_acq = bars + 264;
    const unsigned int* cnt = &g_hcnt[32 * (1 + OG_MT(blockIdx.x)) + 2];
    #pragma unroll 1
    for (int q = 0; q < 4 * n_items; q++) {
      const int item = item0 + (q >> 2) * 128, h = (q >> 1) & 1, w = q & 1;
      const bool last = (q >> 2) == n_items - 1;
      if (q == 4 * n_items - 4) { mbar_wait(bars + 288, 0); red_release_add(&g_hcnt[1], 1u); }
      mbar_wait(b_ordy + 8 * (q & 3), q >> 2);
      store_o(tmO, (h ? (last ? sbase + AT_SQ + 32768 : sbase + 2 * 32768) : sbase + AT_SQ) + w * 8192, (item >> 4) * 2 + h, (item & 15) * 128 + w * 64);
      if (w) {
        bulk_wait_read<0>();
        mbar_arrive(h ? b_ob : b_q0);
        bulk_wait<0>();
        fence_proxy_async_global();
        red_release_add(&g_hcnt[32 * (1 + (item & 15)) + 2 + (item >> 7)], h ? 1u : 256u);
        if (blockIdx.x < 128 && q == (n_items == 2 ? 5 : 3)) { spin_until(cnt, 0x808u); mbar_arrive(b_acq); }
      }
    }
    if (n_items == 1) {
      #pragma unroll 1
      for (int i = 0; i < help_njobs(); i++) {
        mbar_wait(b_acq + 16, i & 1);
        TL_MARK2(23, i == OG_JOBS - 1);
        red_release_add(&g_hcnt[32 * (1 + (help_job(i) >> 2)) + 4 + (help_job(i) & 3)], 1u);
        TL_MARK2(4, i == OG_JOBS - 1);
        if (i == PRE_X - 1) { spin_until(&g_hcnt[1], 132u); mbar_arrive(b_acq + 32); }
      }
    }
    if (blockIdx.x < 128) { spin_until(&g_hcnt[0], 128u); spin_until(cnt + 1, 0x808u); mbar_arrive(b_acq); }
  }
}

__global__ void __launch_bounds__(384, 1)
fused_kernel(const __grid_constant__ CUtensorMap tmH, const __grid_constant__ CUtensorMap tmW, const __grid_constant__ CUtensorMap tmK,
            const __grid_constant__ CUtensorMap tmV, const __grid_constant__ CUtensorMap tmO, const __grid_constant__ CUtensorMap tmOl, const __grid_constant__ CUtensorMap tmWo,
            const __grid_constant__ CUtensorMap tmX, const __grid_constant__ CUtensorMap tmOut, uint32_t zero,
            const uint8_t* __restrict__ pf_wo, const bf16* __restrict__ kc, const bf16* __restrict__ vc,
            const bf16* __restrict__ x, const bf16* __restrict__ cvec, const bf16* __restrict__ w_mod, const bf16* __restrict__ w_r,
            const bf16* __restrict__ w_gate, const bf16* __restrict__ w_up, const bf16* __restrict__ w_down, bf16* __restrict__ out)
{
  extern __shared__ __align__(1024) uint8_t smem_raw[];
  const uint32_t sbase = smem_u32(smem_raw);
  const uint32_t bars = sbase + AT_SBAR;
  const uint32_t b_full = bars, b_empty = bars + 40;
  const uint32_t b_q0 = bars + 80, b_q1 = bars + 88;
  const uint32_t b_ob = bars + 96;
  const uint32_t b_ordy = bars + 104;
  const uint32_t b_pin = bars + 136;
  const uint32_t b_head = bars + 144;
  const uint32_t b_go = bars + 152;
  const uint32_t b_x = bars + 160;
  const int wg = __shfl_sync(0xffffffffu, threadIdx.x >> 7, 0);
  const bool single = blockIdx.x >= AT_NFULL;
  const int item0 = __shfl_sync(0xffffffffu, blockIdx.x < 128 ? (int)blockIdx.x : (int)blockIdx.x + 124, 0), n_items = __shfl_sync(0xffffffffu, single ? 1 : 2, 0);
  TL_START(3);
  if (threadIdx.x == 0) {
    if (sbase & 1023u) __trap();
    for (int i = 0; i < 5; i++) { mbar_init(b_full + 8 * i, 1); mbar_init(b_empty + 8 * i, 2); }
    mbar_init(b_q0, 1); mbar_init(b_q1, 8); mbar_init(b_ob, 1);
    for (int i = 0; i < 4; i++) mbar_init(b_ordy + 8 * i, 4);
    mbar_init(b_pin, 1); mbar_init(b_head, blockIdx.x < 128 ? 8 : 1); mbar_init(b_go, 1); mbar_init(b_x, 1);
    mbar_init(bars + 168, 1); mbar_init(bars + 176, 1); mbar_init(bars + 184, 8); mbar_init(bars + 192, 2);
    mbar_init(bars + 200, 8); mbar_init(bars + 208, 1); mbar_init(bars + 216, 1); mbar_init(bars + 264, 1); mbar_init(bars + 272, 1); mbar_init(bars + 280, 8); mbar_init(bars + 288, 1); mbar_init(bars + 296, 1); mbar_init(bars + 304, 8); mbar_init(bars + 312, 1); mbar_init(bars + 320, 1);
    fence_mbar_init();
  }

  if (wg == 0) {
    reg_dealloc<AT_PREG>();
    if (threadIdx.x < 32) { __syncwarp(); named_bar_arrive(6, 384); }
    if (threadIdx.x >= 64) {
      named_bar_sync(6, 384);
      if (blockIdx.x < 128 && threadIdx.x >= 96) {
        named_bar_sync(8, 288);
        if (threadIdx.x == 96) red_release_add(&g_hcnt[32 * (1 + (blockIdx.x >> 3)) + 1], 1u);
      }
      if (blockIdx.x < 128) {
        mbar_wait(MOD_AT, 0);
        mod_rest(sbase + OG_SCOL, b_q1, threadIdx.x - 64, cvec, w_mod, w_r);
      }
    } else if (threadIdx.x >= 32) {
      named_bar_sync(6, 384);
      store_warp(sbase, &tmO, item0, n_items);
      __syncwarp();
    } else {
     if (elect_one()) {
      const uint64_t pol = policy_evict_first();
      prefetch_tmap(&tmW); prefetch_tmap(&tmH); prefetch_tmap(&tmWo); prefetch_tmap(&tmOl);
      uint32_t slot = 0, ph = 1;
      if (ALIGN) { uint32_t sm; asm volatile("mov.u32 %0, %%smid;" : "=r"(sm)); g_smid[32 + blockIdx.x] = sm; }
      #pragma unroll 1
      for (int it = 0; it < n_items; it++) {
        const int item = item0 + it * 128, hp = item >> 4, qt = item & 15;
        const bool first = it == 0;
        #pragma unroll 1
        for (int j = 0; j < T_D / 64; j++) {
          const uint32_t sl = ring_slot(qp_pos(j, it)), fb = b_full + 8 * sl;
          mbar_wait(b_empty + 8 * sl, ring_par(qp_pos(j, it)) ^ ((j >> 2) & 1) ^ 1);
          mbar_expect_tx(fb, 49152);
          #pragma unroll 1
          for (int c = 0; c < 4; c++) tma_load_2d_hint(sbase + sl * 32768 + c * 8192, &tmW, hp * 256 + c * 64, j * 64, fb, pol);
          if (first && j < PRE_B) {
            if (j == PRE_B - 1) {
              spin_until(&g_hcnt[32 * (1 + qt)], 8u);
              TL_MARK2(16, true);
              fence_proxy_async_global();
              TL_MARK2(17, true);
              #pragma unroll 1
              for (int i = 0; i < PRE_B; i++) tma_load_2d(sbase + AT_SQ + i * 16384, &tmH, i * 64, qt * 128, b_full + 8 * i);
              mbar_arrive(b_go);
            }
          } else {
            if (first && j == 3) mbar_wait(b_head, 0);
            if (first && j == 4 * H_SPLIT) { spin_until(&g_hcnt[32 * (1 + qt) + 1], 8u); fence_proxy_async_global(); }
            if (!first && (j == 0 || j == 2)) mbar_wait(j ? b_q1 : b_q0, 0);
            tma_load_2d_hint(sbase + AT_SQ + (j & 3) * 16384, &tmH, j * 64, qt * 128, fb, first ? pol_normal() : pol);
          }
        }
        #pragma unroll 1
        for (int j = 0; j < 4 * AT_NBLK; j++) {
          const bool isv = (j > 0 && !(j & 1)) || j == 4 * AT_NBLK - 1;
          const int row = hp * 2 * T_SEQ + (isv ? (j - 1) >> 1 : (j + 1) >> 1) * 128;
          const uint32_t fb = b_full + 8 * slot;
          mbar_wait(b_empty + 8 * slot, ph);
          if (!first && j == 3) mbar_wait(b_ob, 0);
          if (j == 4 && it == n_items - 1) mbar_arrive(bars + 288);
          if (ALIGN && j == AL_P && it == 1) mbar_arrive(bars + 312);
          mbar_expect_tx(fb, 32768);
          tma_load_2d_hint(sbase + slot * 32768, isv ? &tmV : &tmK, 0, row, fb, pol);
          tma_load_2d_hint(sbase + slot * 32768 + 16384, isv ? &tmV : &tmK, 64, row, fb, pol);
          if (it == 1 && isv && j >= 2 * WO_LATE && j < 2 * WO_LATE + 32 && blockIdx.x < 64)
            l2_prefetch_bulk(pf_wo + (size_t)blockIdx.x * 131072 + ((j >> 1) - WO_LATE) * 8192, 8192);
          if (++slot == 5) { slot = 0; ph ^= 1; }
        }
      }
      if (__builtin_expect(single, 0)) {
        #pragma unroll 1
        for (int i = 0; i < 4; i++) spin_until(&g_hcnt[32 * (1 + 4 * i + (blockIdx.x & 3)) + 2], 0x800u);
        fence_proxy_async_global();
        const int nj = help_njobs() * OG_PRE;
        int ji = 0, job = help_job(0), kk = 0;
        #pragma unroll 1
        for (int j = 0; j < nj; j++) {
          const uint32_t sl = ring_slot(qp_pos(j, 1)), fb = b_full + 8 * sl;
          mbar_wait(b_empty + 8 * sl, ring_par(qp_pos(j, 1)) ^ ((j >> 2) & 1) ^ 1);
          mbar_expect_tx(fb, 49152);
          tma_load_3d_hint(sbase + sl * 32768, &tmWo, pre_kb(kk) * 64, (job & 3) * 4, fb, HPOL_B);
          tma_load_3d_hint(sbase + sl * 32768 + 16384, &tmWo, pre_kb(kk) * 64, (job & 3) * 4 + 2, fb, HPOL_B);
          if (j == 0 || j == 2) mbar_wait(j ? b_ob : b_q0, 0);
          tma_load_2d_hint(sbase + AT_SQ + (j & 3) * 16384, HMAP_A, pre_kb(kk) * 64, (job >> 2) * 128, fb, HPOL_A);
          if (++kk == OG_PRE) { kk = 0; job = help_job(++ji); }
        }
      }
      if (blockIdx.x < 128) {
        if (single) mbar_wait(b_x, 1);
        tail_producer(sbase, 0, pol, &tmOl, &tmWo, &tmX);
      }
     }
    }
    named_bar_sync(12 + (threadIdx.x >> 5), 32);
    if (blockIdx.x < 128) tail_exchange(sbase, &tmOut, w_down, out);
  } else {
    if (blockIdx.x < 128) head_phase(sbase + AT_SQ + 49152, sbase + 4 * 32768, b_x, b_go, b_head, threadIdx.x - 128, zero, x, cvec, w_mod);
    else { named_bar_sync(6, 384); if (threadIdx.x == 128) mbar_arrive(b_head); }
    TL_MARK2(0, threadIdx.x == 128);
    reg_alloc<AT_CREG>();
    const int cwg = wg - 1;
    const int tid = threadIdx.x & 127;
    const int warp = tid >> 5, lane = tid & 31;
    const uint32_t dbase = (sbase & 0x3FFFFu) >> 4;
    const uint32_t k_base = dbase + (1u << 16);
    const uint32_t v_base = dbase + (1024u << 16);
    const uint32_t w_base = dbase + (512u << 16);
    const uint32_t q_lo = dbase + ((AT_SQ + cwg * 8192) >> 4) + (1u << 16);
    const uint32_t frag = cwg * 8192 + (16 * warp + (lane & 7) + 8 * ((lane >> 3) & 1)) * 128;
    if (cwg == 1) named_bar_arrive(1, 256);
    bool raw = false;
    uint4 pre[8];
    #pragma unroll 1
    for (int it = 0; it < n_items; it++) {
      const bool more = it + 1 < n_items;
      constexpr int nkb = T_D / 64;
      const int ta = __shfl_sync(0xffffffffu, 4 * it, 0);
      float acc[128];
      {
        FS(2 * it, 0);
        #pragma unroll
        for (int i = 0; i < 128; i++) asm volatile("" : "=f"(acc[i]));
        {
          const uint32_t slot = ring_slot(ta), b_lo = w_base + slot * 2048;
          mbar_wait(b_full + 8 * slot, ring_par(ta));
          wgmma_fence();
          wgmma_m64n256k16_ss_tb<0, 0>(acc, q_lo, b_lo, 0);
          wgmma_m64n256k16_ss_tb<2, 128>(acc, q_lo, b_lo, 1);
          wgmma_m64n256k16_ss_tb<4, 256>(acc, q_lo, b_lo, 1);
          wgmma_m64n256k16_ss_tb<6, 384>(acc, q_lo, b_lo, 1);
          wgmma_commit();
        }
        #pragma unroll 1
        for (int j = NOZERO; j < nkb; j++) {
          const uint32_t slot = ring_slot(qp_pos(j, ta >> 2));
          mbar_wait(b_full + 8 * slot, ring_par(qp_pos(j, ta >> 2)) ^ ((j >> 2) & 1));
          if (QP_STAG > 0 && cwg == 1 && j == nkb - QP_STAG) named_bar_sync(7, 256);
          const uint32_t a_lo = q_lo + (j & 3) * 1024, b_lo = w_base + slot * 2048;
          wgmma_fence();
          wgmma_m64n256k16_ss_tb<0, 0>(acc, a_lo, b_lo, 1);
          wgmma_m64n256k16_ss_tb<2, 128>(acc, a_lo, b_lo, 1);
          wgmma_m64n256k16_ss_tb<4, 256>(acc, a_lo, b_lo, 1);
          wgmma_m64n256k16_ss_tb<6, 384>(acc, a_lo, b_lo, 1);
          wgmma_commit();
          if (QP_STAG > 0 && cwg == 0 && j == nkb - 1) named_bar_arrive(7, 256);
          if (j > 0) {
            wgmma_wait<1>();
            if (tid == 0) mbar_arrive(b_empty + 8 * ring_slot(qp_pos(j - 1, ta >> 2)));
          }
        }
        wgmma_wait<0>();
        fence_regs(acc);
        FS(2 * it, 1);
        TL_MARK2(29, threadIdx.x == 256 && it == 0);
        if (tid == 0) mbar_arrive(b_empty + 24);
      }
      float o[64], s[64];
      uint32_t p[32], q[32];
      #pragma unroll
      for (int i = 0; i < 32; i++) q[i] = pack_bf16(acc[2 * i] * AT_C, acc[2 * i + 1] * AT_C);
      zero_regs(s);
      const uint32_t sq = sbase + AT_SQ + cwg * 8192;
      const bool last_wg1 = cwg == 1 && !more;
      float mc0, mc1, al0 = 1.0f, al1 = 1.0f, l0 = 0.f, l1 = 0.f, lp0 = 0.f, lp1 = 0.f;
      bool redo0 = false;
      FS(2 * it, 2);
      mbar_wait(b_full + 8 * ring_slot(ta), ring_par(ta));
      named_bar_sync(1 + cwg, 256);
      FS(2 * it, 3);
      issue_qk(s, q, k_base + ring_slot(ta) * 2048);
      named_bar_arrive(1 + (cwg ^ 1), 256);
      bool ready = mbar_test(b_full + 8 * ring_slot(ta + 1), ring_par(ta + 1)) & mbar_test(b_full + 8 * ring_slot(ta + 2), ring_par(ta + 2));
      stage_q<16>(acc, AT_C, sbase + AT_SQ + frag, lane);
      wgmma_wait<0>();
      fence_regs(s);
      if (tid == 0) mbar_arrive(b_empty + 8 * ring_slot(ta));
      mc0 = 0.f; mc1 = 0.f;
      if (!raw) {
        raw = softmax_mode(s, mc0, mc1);
        if (__builtin_expect(!raw, 0)) softmax_sub(s, mc0, mc1);
      }
      softmax_exp<0, 64>(s);
      #pragma unroll
      for (int J = 0; J < 16; J += 2)
        stmatrix_x4(sbase + AT_SQ + frag + (J >> 3) * 16384 + ((((J & 7) + (lane >> 4)) ^ (lane & 7)) << 4), q[2 * J], q[2 * J + 1], q[2 * J + 2], q[2 * J + 3]);
      pack_p(p, s);
      zero_regs(o);
      FS(2 * it, 4);
      uint32_t ks = ring_slot(ta + 1), vs = ring_slot(ta + 2), kp = ring_par(ta + 1), vp = ring_par(ta + 2);
      auto finish_head = [&]() {
        FS(2 * it, 5);
        redo0 = finish_l(lp0, lp1);
        if (!redo0) {
          stage_o(o, lp0, lp1, sbase + AT_SQ + frag, lane);
          fence_proxy_async();
          __syncwarp();
          if (lane == 0) mbar_arrive(b_ordy + 8 * cwg);
        }
        FS(2 * it + 1, 4);
      };
      if (!ready) { mbar_wait(b_full + 8 * ks, kp); mbar_wait(b_full + 8 * vs, vp); }
      #pragma unroll 1
      for (int n = 1; n < 2 * AT_NBLK; n++) {
        named_bar_sync(1 + cwg, 256);
        issue_qk(s, q, k_base + ks * 2048);
        if (n == AT_NBLK + 1) finish_head();
        issue_pv(o, p, v_base + vs * 2048, (n & 15) != 1);
        if (!(last_wg1 && n == 2 * AT_NBLK - 1)) named_bar_arrive(1 + (cwg ^ 1), 256);
        wgmma_wait<1>();
        fence_regs(s);
        if (tid == 0) mbar_arrive(b_empty + 8 * ks);
        if (__builtin_expect(!raw || (n + 1) >> 1 == AT_NBLK / 2, 0)) {
          if (n == AT_NBLK - 1) {
            #pragma unroll
            for (int J = 0; J < 16; J += 2)
              ldmatrix_x4(sbase + AT_SQ + 32768 + frag + (J >> 3) * 16384 + ((((J & 7) + (lane >> 4)) ^ (lane & 7)) << 4), q[2 * J], q[2 * J + 1], q[2 * J + 2], q[2 * J + 3]);
          }
          if (!raw) {
            const float m0 = mc0, m1 = mc1;
            const bool ok = softmax_mode(s, mc0, mc1);
            if (n == AT_NBLK) raw = ok;
            else {
              mc0 = mc0 - AT_HEAD > m0 ? mc0 : m0; mc1 = mc1 - AT_HEAD > m1 ? mc1 : m1;
              al0 = ex2_approx(m0 - mc0); al1 = ex2_approx(m1 - mc1);
            }
            if (!raw) softmax_sub(s, mc0, mc1);
          }
        }
        softmax_exp<0, AT_SPLIT>(s);
        add_rowsum(p, l0, l1);
        if (tid == 0) {
          uint32_t dep = zero & __float_as_uint(l0) & __float_as_uint(l1);
          #pragma unroll
          for (int i = AT_SPLIT - AT_PIN - PINB; i < AT_SPLIT - PINB; i += 2) dep &= __float_as_uint(s[i]) & __float_as_uint(s[i + 1]);
          mbar_arrive(b_pin + dep);
        }
        wgmma_wait<0>();
        fence_regs(o);
        if (tid == 0) mbar_arrive(b_empty + 8 * vs);
        ks += 2; if (ks >= 5) { ks -= 5; kp ^= 1; }
        vs += 2; if (vs >= 5) { vs -= 5; vp ^= 1; }
        ready = mbar_test(b_full + 8 * ks, kp) & mbar_test(b_full + 8 * vs, vp);
        softmax_exp<AT_SPLIT, 64>(s);
        pack_p(p, s);
        if (n == AT_NBLK) { lp0 = l0; lp1 = l1; l0 = 0.f; l1 = 0.f; }
        if (__builtin_expect(!raw || !ready, 0)) {
        if (!raw && __any_sync(0xffffffffu, al0 != 1.0f || al1 != 1.0f)) {
          rescale_o(o, al0, al1);
          l0 *= al0; l1 *= al1;
          al0 = 1.0f; al1 = 1.0f;
        }
        if (!ready && n < 2 * AT_NBLK - 1) {
          mbar_wait(b_full + 8 * ks, kp);
          mbar_wait(b_full + 8 * vs, vp);
        }
        }
      }
      FS(2 * it + 1, 5);
      const uint32_t vl = ring_slot(ta + 63);
      vs = ring_slot(ta + 62);
      const uint32_t ob = more ? sbase + vs * 32768 : sbase + AT_SQ + 32768;
      if (redo0) {
        attn_rows_exact(sq, sq, 4 * ta, kc, vc);
        fence_proxy_async();
        __syncwarp();
        if (lane == 0) mbar_arrive(b_ordy + 8 * cwg);
      }
      mbar_wait(b_full + 8 * vl, ring_par(ta + 63));
      issue_pv(o, p, v_base + vl * 2048, 1);
      add_rowsum(p, l0, l1);
      const bool overflow = finish_l(l0, l1);
      if (!overflow && lane == 0) mbar_arrive(b_q1);
      #pragma unroll
      for (int i = 0; i < 8; i++) asm volatile("mov.b64 {%0, %1}, 0;\nmov.b64 {%2, %3}, 0;" : "=r"(pre[i].x), "=r"(pre[i].y), "=r"(pre[i].z), "=r"(pre[i].w));
      if (HOIST && !more && blockIdx.x < OG_MOE) {
        load_pre(pre, sbase, AT_SQ, threadIdx.x - 128);
        __syncwarp();
        if (lane == 0) mbar_arrive(bars + 304);
      }
      mbar_wait(b_empty + 8 * vs, ring_par(ta + 62));
      wgmma_wait<0>();
      fence_regs(o);
      if (tid == 0) mbar_arrive(b_empty + 8 * vl);
      FS(2 * it + 1, 6);
      if (overflow) {
        attn_rows_exact(sq + 32768, ob + cwg * 8192, 4 * ta + 1, kc, vc);
        __syncwarp();
        if (lane == 0) mbar_arrive(b_q1);
      } else stage_o(o, l0, l1, ob + frag, lane);
      fence_proxy_async();
      __syncwarp();
      if (lane == 0) mbar_arrive(b_ordy + 16 + 8 * cwg);
      if (redo0 || overflow) raw = false;
      named_bar_sync(3 + cwg, 128);
      FS(2 * it + 1, 7);
    }
    if (__builtin_expect(single, 0)) {
      float acc[128];
      uint32_t j = 0, pk[64];
      #pragma unroll
      for (int i = 0; i < 64; i++) asm volatile("" : "=f"(acc[2 * i]), "=f"(acc[2 * i + 1]), "=r"(pk[i]));
      uint4* dst = g_pre;
      int left = 0;
      auto put = [&](bool last) {
        #pragma unroll
        for (int i = 0; i < PUT_N; i++) dst[i * 256] = make_uint4(pk[4 * i], pk[4 * i + 1], pk[4 * i + 2], pk[4 * i + 3]);
        dst += PUT_N * 256;
        #pragma unroll
        for (int i = 0; i < 64 - 4 * PUT_N; i++) asm volatile("mov.b32 %0, %1;" : "=r"(pk[i]) : "r"(pk[i + 4 * PUT_N]));
        __syncwarp();
        if (last && lane == 0) mbar_arrive(bars + 280);
      };
      #pragma unroll 1
      for (int ji = 0; ji < help_njobs(); ji++) {
        #pragma unroll 1
        for (int kk = 0; kk < OG_PRE; kk++, j++) {
          const uint32_t slot = ring_slot(qp_pos(j, 1));
          mbar_wait(b_full + 8 * slot, ring_par(qp_pos(j, 1)) ^ ((j >> 2) & 1));
          if (H_STAG > 0 && cwg == 1 && kk == OG_PRE - H_STAG) named_bar_sync(7, 256);
          const uint32_t a_lo = q_lo + (j & 3) * 1024, b_lo = w_base + slot * 2048;
          wgmma_fence();
          wgmma_m64n256k16_ss_tb<0, 0>(acc, a_lo, b_lo, kk != 0);
          wgmma_m64n256k16_ss_tb<2, 128>(acc, a_lo, b_lo, 1);
          wgmma_m64n256k16_ss_tb<4, 256>(acc, a_lo, b_lo, 1);
          wgmma_m64n256k16_ss_tb<6, 384>(acc, a_lo, b_lo, 1);
          wgmma_commit();
          if (H_STAG > 0 && cwg == 0 && kk == OG_PRE - 1) named_bar_arrive(7, 256);
          wgmma_wait<1>();
          if (kk > 0 && tid == 0) mbar_arrive(b_empty + 8 * ring_slot(qp_pos(j - 1, 1)));
          #pragma unroll 1
          for (int i = ji == OG_JOBS ? 0 : 16 / PUT_N - 1; i < 16 / PUT_N && left > 0; i++) put(--left == 0);
        }
        wgmma_wait<0>();
        fence_regs(acc);
        if (tid == 0) mbar_arrive(b_empty + 8 * ring_slot(qp_pos(j - 1, 1)));
        #pragma unroll
        for (int i = 0; i < 64; i++) pk[i] = pack_bf16(acc[2 * i], acc[2 * i + 1]);
        left = 16 / PUT_N;
        if (ji == PRE_X) mbar_wait(bars + 296, 0);
        dst = g_pre + pre_loc(help_job(ji)) * 4096 + threadIdx.x - 128;
      }
      #pragma unroll
      for (int i = 0; i < 16; i++) dst[i * 256] = make_uint4(pk[4 * i], pk[4 * i + 1], pk[4 * i + 2], pk[4 * i + 3]);
      __syncwarp();
      if (lane == 0) mbar_arrive(bars + 280);
      named_bar_sync(5, 256);
      if (threadIdx.x == 128) {
        #pragma unroll 1
        for (int i = 0; i < 5; i++) {
          constexpr int n = OG_JOBS * OG_PRE;
          const int used = i == 3 ? 0 : (n + 3 - (i == 4 ? 3 : i)) / 4;
          if ((used ^ (i < 4)) & 1) {
            mbar_arrive(b_full + 8 * ring_slot(4 + i));
            mbar_arrive(b_empty + 8 * ring_slot(4 + i)); mbar_arrive(b_empty + 8 * ring_slot(4 + i));
          }
        }
        mbar_arrive(b_x);
      }
      named_bar_sync(5, 256);
      #pragma unroll
      for (int i = 0; i < 8; i++) pre[i] = make_uint4(0u, 0u, 0u, 0u);
    }
    TL_CLK(3, 1, threadIdx.x == 128);
    TL_CTA(1, threadIdx.x == 256);
    TL_END(3, tid == 0);
    TL_MARK2(19, tid == 0 && !single);
    if (blockIdx.x < 128) {
      if (!HOIST && blockIdx.x < OG_MOE) {
        load_pre(pre, sbase, AT_SQ, threadIdx.x - 128);
        __syncwarp();
        if (lane == 0) mbar_arrive(bars + 304);
      }
      tail_consumer(sbase, pre, cwg, w_r, w_gate, w_up);
    }
  }
}

typedef CUresult (*PFN_encodeTiled)(CUtensorMap*, CUtensorMapDataType, cuuint32_t, void*, const cuuint64_t*, const cuuint64_t*,
                                    const cuuint32_t*, const cuuint32_t*, CUtensorMapInterleave, CUtensorMapSwizzle,
                                    CUtensorMapL2promotion, CUtensorMapFloatOOBfill);

CUtensorMap make_map_2d(PFN_encodeTiled enc, const void* ptr, uint64_t inner, uint64_t outer, uint64_t stride_bytes, uint32_t box_inner, uint32_t box_outer) {
  CUtensorMap m;
  cuuint64_t gd[2] = {inner, outer}; cuuint64_t gs[1] = {stride_bytes};
  cuuint32_t bx[2] = {box_inner, box_outer}; cuuint32_t es[2] = {1, 1};
  enc(&m, CU_TENSOR_MAP_DATA_TYPE_BFLOAT16, 2, const_cast<void*>(ptr), gd, gs, bx, es, CU_TENSOR_MAP_INTERLEAVE_NONE,
      CU_TENSOR_MAP_SWIZZLE_128B, CU_TENSOR_MAP_L2_PROMOTION_L2_128B, CU_TENSOR_MAP_FLOAT_OOB_FILL_NONE);
  return m;
}

CUtensorMap make_map_3d(PFN_encodeTiled enc, const void* ptr, uint64_t cols, uint64_t rows, uint32_t box_rows, uint32_t chunks) {
  CUtensorMap m;
  cuuint64_t gd[3] = {64, rows, cols / 64}; cuuint64_t gs[2] = {cols * 2, 128};
  cuuint32_t bx[3] = {64, box_rows, chunks}; cuuint32_t es[3] = {1, 1, 1};
  enc(&m, CU_TENSOR_MAP_DATA_TYPE_BFLOAT16, 3, const_cast<void*>(ptr), gd, gs, bx, es, CU_TENSOR_MAP_INTERLEAVE_NONE,
      CU_TENSOR_MAP_SWIZZLE_128B, CU_TENSOR_MAP_L2_PROMOTION_L2_128B, CU_TENSOR_MAP_FLOAT_OOB_FILL_NONE);
  return m;
}

}

extern "C" void kernel_launch(void* const* d_in, const int* in_sizes, int n_in, void* d_out, int out_size) {
  const bf16* x      = (const bf16*)d_in[0];
  const bf16* kc     = (const bf16*)d_in[1];
  const bf16* vc     = (const bf16*)d_in[2];
  const bf16* wq     = (const bf16*)d_in[3];
  const bf16* wo     = (const bf16*)d_in[4];
  const bf16* w_r    = (const bf16*)d_in[6];
  const bf16* w_gate = (const bf16*)d_in[7];
  const bf16* w_up   = (const bf16*)d_in[8];
  const bf16* w_down = (const bf16*)d_in[9];
  const bf16* cvec   = (const bf16*)d_in[10];
  const bf16* w_mod  = (const bf16*)d_in[11];
  bf16* out = (bf16*)d_out;

  static PFN_encodeTiled enc = nullptr;
  static void *p_h = nullptr, *p_o = nullptr;
  if (!enc) {
    void* fn = nullptr; cudaDriverEntryPointQueryResult qres;
    cudaGetDriverEntryPoint("cuTensorMapEncodeTiled", &fn, cudaEnableDefault, &qres);
    enc = (PFN_encodeTiled)fn;
    cudaGetSymbolAddress(&p_h, g_pre);
    p_h = (uint4*)p_h + 16 * PRE_X * 2048;
    cudaGetSymbolAddress(&p_o, g_o);
    cudaFuncSetAttribute(fused_kernel, cudaFuncAttributeMaxDynamicSharedMemorySize, (int)AT_SMEM);
  }
  const CUtensorMap tm_h   = make_map_2d(enc, p_h, T_D, T_SEQ, T_D * 2, 64, 128);
  const CUtensorMap tm_wq  = make_map_2d(enc, wq, T_DQKV, T_D, T_DQKV * 2, 64, 64);
  const CUtensorMap tm_k   = make_map_2d(enc, kc, T_DH, (uint64_t)T_NH * T_SEQ, T_DH * 2, 64, 128);
  const CUtensorMap tm_v   = make_map_2d(enc, vc, T_DH, (uint64_t)T_NH * T_SEQ, T_DH * 2, 64, 128);
  const CUtensorMap tm_ost = make_map_2d(enc, p_o, T_DQKV, T_SEQ, T_DQKV * 2, 64, 64);
  const CUtensorMap tm_old = make_map_2d(enc, p_o, T_DQKV, T_SEQ, T_DQKV * 2, 64, 128);
  const CUtensorMap tm_wo  = make_map_3d(enc, wo, T_D, T_DQKV, 64, 2);
  const CUtensorMap tm_x   = make_map_3d(enc, x, T_D, T_SEQ, 128, 2);

  const CUtensorMap tm_out = make_map_2d(enc, out, T_D, T_SEQ, T_D * 2, 64, 128);

  fused_kernel<<<132, 384, AT_SMEM, cudaStreamPerThread>>>(tm_h, tm_wq, tm_k, tm_v, tm_ost, tm_old, tm_wo, tm_x, tm_out, 0u, (const uint8_t*)wo, kc, vc, x, cvec, w_mod,
             w_r, w_gate, w_up, w_down, out);
}
```

```cpp
#include <cuda_runtime.h>
#include <cuda_bf16.h>
#include <cuda.h>
#include <stdint.h>

namespace {

typedef __nv_bfloat16 bf16;

constexpr int T_SEQ = 2048, T_D = 1024, T_NH = 32, T_DH = 128, T_DQKV = 4096, T_F = 3584;

#define PRE_X 2
__device__ __align__(1024) uint4 g_pre[(16 * PRE_X + 128) * 2048];
#define g_h (reinterpret_cast<bf16*>(g_pre + 16 * PRE_X * 2048))
__device__ __align__(1024) bf16 g_o[T_SEQ * T_DQKV];
__device__ __align__(16) uint8_t g_col[8 * 1536];
__device__ __align__(16) float g_scal[64];
__device__ __align__(16) unsigned int g_hcnt[17 * 32];
__device__ unsigned int g_smid[160], g_tmax[128];
__device__ __align__(128) float g_modpart[4 * 2 * T_D];
struct __align__(2048) TailMail {
  float4 part1[T_SEQ * 8];
  uint32_t key[256];
  uint4 cand[16 * 2 * 2 * 128];
  uint32_t cnt[32];
  float ypart[(T_F / 32) * 2 * T_D];
};
__device__ TailMail g_mail;
#define g_part1 g_mail.part1
#define g_key g_mail.key
#define g_cand g_mail.cand
#define CNT_Y (g_mail.cnt)
#define g_ypart g_mail.ypart

__device__ __forceinline__ uint32_t smem_u32(const void* p) { return (uint32_t)__cvta_generic_to_shared(p); }
__device__ __forceinline__ void mbar_init(uint32_t bar, uint32_t cnt) { asm volatile("mbarrier.init.shared::cta.b64 [%0], %1;" :: "r"(bar), "r"(cnt)); }
__device__ __forceinline__ void mbar_expect_tx(uint32_t bar, uint32_t bytes) { asm volatile("mbarrier.arrive.expect_tx.shared::cta.b64 _, [%0], %1;" :: "r"(bar), "r"(bytes) : "memory"); }
__device__ __forceinline__ void mbar_arrive(uint32_t bar) { asm volatile("mbarrier.arrive.shared::cta.b64 _, [%0];" :: "r"(bar) : "memory"); }
__device__ __forceinline__ void mbar_wait(uint32_t bar, uint32_t parity) {
  asm volatile("{\n.reg .pred p;\nLAB_WAIT:\nmbarrier.try_wait.parity.shared::cta.b64 p, [%0], %1;\n@!p bra LAB_WAIT;\n}\n" :: "r"(bar), "r"(parity) : "memory");
}
__device__ __forceinline__ bool mbar_test(uint32_t bar, uint32_t parity) {
  uint32_t r; asm volatile("{\n.reg .pred p;\nmbarrier.test_wait.parity.shared::cta.b64 p, [%1], %2;\nselp.u32 %0, 1, 0, p;\n}\n" : "=r"(r) : "r"(bar), "r"(parity) : "memory");
  return r != 0;
}
__device__ __forceinline__ uint32_t clock_lo() { uint32_t c; asm volatile("mov.u32 %0, %%clock;" : "=r"(c)); return c; }
__device__ __forceinline__ void fence_mbar_init() { asm volatile("fence.mbarrier_init.release.cluster;" ::: "memory"); }
__device__ __forceinline__ void tma_load_2d(uint32_t dst, const CUtensorMap* map, int c0, int c1, uint32_t bar) {
  asm volatile("cp.async.bulk.tensor.2d.shared::cluster.global.mbarrier::complete_tx::bytes [%0], [%1, {%3, %4}], [%2];"
    :: "r"(dst), "l"(map), "r"(bar), "r"(c0), "r"(c1) : "memory");
}
__device__ __forceinline__ uint64_t policy_evict_first() {
  uint64_t p; asm volatile("createpolicy.fractional.L2::evict_first.b64 %0, 1.0;" : "=l"(p)); return p;
}
__device__ __forceinline__ void tma_load_2d_hint(uint32_t dst, const CUtensorMap* map, int c0, int c1, uint32_t bar, uint64_t pol) {
  asm volatile("cp.async.bulk.tensor.2d.shared::cluster.global.mbarrier::complete_tx::bytes.L2::cache_hint [%0], [%1, {%3, %4}], [%2], %5;"
    :: "r"(dst), "l"(map), "r"(bar), "r"(c0), "r"(c1), "l"(pol) : "memory");
}
__device__ __forceinline__ void tma_load_3d_hint(uint32_t dst, const CUtensorMap* map, int c1, int c2, uint32_t bar, uint64_t pol) {
  asm volatile("cp.async.bulk.tensor.3d.shared::cluster.global.mbarrier::complete_tx::bytes.L2::cache_hint [%0], [%1, {%3, %4, %5}], [%2], %6;"
    :: "r"(dst), "l"(map), "r"(bar), "n"(0), "r"(c1), "r"(c2), "l"(pol) : "memory");
}
__device__ __forceinline__ void tma_store_2d(const CUtensorMap* map, uint32_t src, int c0, int c1) {
  asm volatile("cp.async.bulk.tensor.2d.global.shared::cta.bulk_group [%0, {%2, %3}], [%1];" :: "l"(map), "r"(src), "r"(c0), "r"(c1) : "memory");
}
__device__ __forceinline__ void prefetch_tmap(const CUtensorMap* map) { asm volatile("prefetch.tensormap [%0];" :: "l"(map) : "memory"); }
__device__ __forceinline__ void l2_prefetch_bulk(const void* p, uint32_t bytes) {
  asm volatile("cp.async.bulk.prefetch.L2.global [%0], %1;" :: "l"(p), "r"(bytes) : "memory");
}
__device__ __forceinline__ void bulk_commit() { asm volatile("cp.async.bulk.commit_group;" ::: "memory"); }
template<int N> __device__ __forceinline__ void bulk_wait_read() { asm volatile("cp.async.bulk.wait_group.read %0;" :: "n"(N) : "memory"); }
template<int N> __device__ __forceinline__ void bulk_wait() { asm volatile("cp.async.bulk.wait_group %0;" :: "n"(N) : "memory"); }
__device__ __forceinline__ void named_bar_sync(int id, int nthreads) { asm volatile("bar.sync %0, %1;" :: "r"(id), "r"(nthreads) : "memory"); }
__device__ __forceinline__ void named_bar_arrive(int id, int nthreads) { asm volatile("bar.arrive %0, %1;" :: "r"(id), "r"(nthreads) : "memory"); }
__device__ __forceinline__ void wgmma_fence() { asm volatile("wgmma.fence.sync.aligned;" ::: "memory"); }
__device__ __forceinline__ void wgmma_commit() { asm volatile("wgmma.commit_group.sync.aligned;" ::: "memory"); }
template<int N> __device__ __forceinline__ void wgmma_wait() { asm volatile("wgmma.wait_group.sync.aligned %0;" :: "n"(N) : "memory"); }
template<int R> __device__ __forceinline__ void reg_alloc() { asm volatile("setmaxnreg.inc.sync.aligned.u32 %0;" :: "n"(R)); }
template<int R> __device__ __forceinline__ void reg_dealloc() { asm volatile("setmaxnreg.dec.sync.aligned.u32 %0;" :: "n"(R)); }
__device__ __forceinline__ bool elect_one() {
  uint32_t pred; asm volatile("{\n.reg .pred p;\nelect.sync _|p, 0xffffffff;\nselp.u32 %0, 1, 0, p;\n}\n" : "=r"(pred)); return pred != 0;
}
__device__ __forceinline__ uint32_t pack_bf16(float lo, float hi) {
  uint32_t r; asm("cvt.rn.bf16x2.f32 %0, %1, %2;" : "=r"(r) : "f"(hi), "f"(lo)); return r;
}
__device__ __forceinline__ void stmatrix_x4(uint32_t addr, uint32_t r0, uint32_t r1, uint32_t r2, uint32_t r3) {
  asm volatile("stmatrix.sync.aligned.m8n8.x4.shared.b16 [%0], {%1, %2, %3, %4};" :: "r"(addr), "r"(r0), "r"(r1), "r"(r2), "r"(r3) : "memory");
}
__device__ __forceinline__ void fence_proxy_async() { asm volatile("fence.proxy.async.shared::cta;" ::: "memory"); }
__device__ __forceinline__ float ex2_approx(float x) { float y; asm("ex2.approx.ftz.f32 %0, %1;" : "=f"(y) : "f"(x)); return y; }
template<int N> __device__ __forceinline__ void fence_regs(float (&r)[N]) {
  #pragma unroll
  for (int i = 0; i < N; i++) asm volatile("" : "+f"(r[i]) :: "memory");
}
template<int N> __device__ __forceinline__ void zero_regs(float (&r)[N]) {
  #pragma unroll
  for (int i = 0; i < N; i += 2) asm volatile("mov.b64 {%0, %1}, 0;" : "=f"(r[i]), "=f"(r[i + 1]));
}
__device__ __forceinline__ float rbf(float x) { return __uint_as_float(pack_bf16(0.f, x)); }
__device__ __forceinline__ float bflo(uint32_t v) { return __uint_as_float(v << 16); }
__device__ __forceinline__ float bfhi(uint32_t v) { return __uint_as_float(v & 0xffff0000u); }

#define TL_START(k) do {} while (0)
#define TL_END(k, cond) do {} while (0)
#define TL_CTA(i, cond) do {} while (0)
#define FS(slot, k) do {} while (0)
#define TL_MARK2(k, cond) do {} while (0)
#define TL_CLK(k, i, cond) do {} while (0)

template <int OFFA, int OFFB>
__device__ __forceinline__ void wgmma_m64n256k16_ss_tb(float (&d)[128], uint32_t a_lo, uint32_t b_lo, int scaleD) {
  asm volatile("{\n.reg .pred p;\n.reg .b32 ta, tb;\n.reg .b64 da, db;\nsetp.ne.b32 p, %130, 0;\n"
    "add.u32 ta, %128, %131;\nadd.u32 tb, %129, %132;\n"
    "mov.b64 da, {ta, 0x40000040};\nmov.b64 db, {tb, 0x40000040};\n"
    "wgmma.mma_async.sync.aligned.m64n256k16.f32.bf16.bf16 "
    "{%0, %1, %2, %3, %4, %5, %6, %7, %8, %9, %10, %11, %12, %13, %14, %15, %16, %17, %18, %19, %20, %21, %22, %23, %24, %25, %26, %27, %28, %29, %30, %31, %32, %33, %34, %35, %36, %37, %38, %39, %40, %41, %42, %43, %44, %45, %46, %47, %48, %49, %50, %51, %52, %53, %54, %55, %56, %57, %58, %59, %60, %61, %62, %63, %64, %65, %66, %67, %68, %69, %70, %71, %72, %73, %74, %75, %76, %77, %78, %79, %80, %81, %82, %83, %84, %85, %86, %87, %88, %89, %90, %91, %92, %93, %94, %95, %96, %97, %98, %99, %100, %101, %102, %103, %104, %105, %106, %107, %108, %109, %110, %111, %112, %113, %114, %115, %116, %117, %118, %119, %120, %121, %122, %123, %124, %125, %126, %127}, "
    "da, db, p, 1, 1, 0, 1;\n}\n"
    : "+f"(d[0]), "+f"(d[1]), "+f"(d[2]), "+f"(d[3]), "+f"(d[4]), "+f"(d[5]), "+f"(d[6]), "+f"(d[7]), "+f"(d[8]), "+f"(d[9]), "+f"(d[10]), "+f"(d[11]), "+f"(d[12]), "+f"(d[13]), "+f"(d[14]), "+f"(d[15]), "+f"(d[16]), "+f"(d[17]), "+f"(d[18]), "+f"(d[19]), "+f"(d[20]), "+f"(d[21]), "+f"(d[22]), "+f"(d[23]), "+f"(d[24]), "+f"(d[25]), "+f"(d[26]), "+f"(d[27]), "+f"(d[28]), "+f"(d[29]), "+f"(d[30]), "+f"(d[31]), "+f"(d[32]), "+f"(d[33]), "+f"(d[34]), "+f"(d[35]), "+f"(d[36]), "+f"(d[37]), "+f"(d[38]), "+f"(d[39]), "+f"(d[40]), "+f"(d[41]), "+f"(d[42]), "+f"(d[43]), "+f"(d[44]), "+f"(d[45]), "+f"(d[46]), "+f"(d[47]), "+f"(d[48]), "+f"(d[49]), "+f"(d[50]), "+f"(d[51]), "+f"(d[52]), "+f"(d[53]), "+f"(d[54]), "+f"(d[55]), "+f"(d[56]), "+f"(d[57]), "+f"(d[58]), "+f"(d[59]), "+f"(d[60]), "+f"(d[61]), "+f"(d[62]), "+f"(d[63]), "+f"(d[64]), "+f"(d[65]), "+f"(d[66]), "+f"(d[67]), "+f"(d[68]), "+f"(d[69]), "+f"(d[70]), "+f"(d[71]), "+f"(d[72]), "+f"(d[73]), "+f"(d[74]), "+f"(d[75]), "+f"(d[76]), "+f"(d[77]), "+f"(d[78]), "+f"(d[79]), "+f"(d[80]), "+f"(d[81]), "+f"(d[82]), "+f"(d[83]), "+f"(d[84]), "+f"(d[85]), "+f"(d[86]), "+f"(d[87]), "+f"(d[88]), "+f"(d[89]), "+f"(d[90]), "+f"(d[91]), "+f"(d[92]), "+f"(d[93]), "+f"(d[94]), "+f"(d[95]), "+f"(d[96]), "+f"(d[97]), "+f"(d[98]), "+f"(d[99]), "+f"(d[100]), "+f"(d[101]), "+f"(d[102]), "+f"(d[103]), "+f"(d[104]), "+f"(d[105]), "+f"(d[106]), "+f"(d[107]), "+f"(d[108]), "+f"(d[109]), "+f"(d[110]), "+f"(d[111]), "+f"(d[112]), "+f"(d[113]), "+f"(d[114]), "+f"(d[115]), "+f"(d[116]), "+f"(d[117]), "+f"(d[118]), "+f"(d[119]), "+f"(d[120]), "+f"(d[121]), "+f"(d[122]), "+f"(d[123]), "+f"(d[124]), "+f"(d[125]), "+f"(d[126]), "+f"(d[127])
    : "r"(a_lo), "r"(b_lo), "r"(scaleD), "n"(OFFA), "n"(OFFB));
}

template <int OFFA, int OFFB>
__device__ __forceinline__ void wgmma_m64n128k16_ss_tb(float (&d)[64], uint32_t a_lo, uint32_t b_lo, int scaleD) {
  asm volatile("{\n.reg .pred p;\n.reg .b32 ta, tb;\n.reg .b64 da, db;\nsetp.ne.b32 p, %66, 0;\n"
    "add.u32 ta, %64, %67;\nadd.u32 tb, %65, %68;\n"
    "mov.b64 da, {ta, 0x40000040};\nmov.b64 db, {tb, 0x40000040};\n"
    "wgmma.mma_async.sync.aligned.m64n128k16.f32.bf16.bf16 "
    "{%0, %1, %2, %3, %4, %5, %6, %7, %8, %9, %10, %11, %12, %13, %14, %15, %16, %17, %18, %19, %20, %21, %22, %23, %24, %25, %26, %27, %28, %29, %30, %31, %32, %33, %34, %35, %36, %37, %38, %39, %40, %41, %42, %43, %44, %45, %46, %47, %48, %49, %50, %51, %52, %53, %54, %55, %56, %57, %58, %59, %60, %61, %62, %63}, "
    "da, db, p, 1, 1, 0, 1;\n}\n"
    : "+f"(d[0]), "+f"(d[1]), "+f"(d[2]), "+f"(d[3]), "+f"(d[4]), "+f"(d[5]), "+f"(d[6]), "+f"(d[7]), "+f"(d[8]), "+f"(d[9]), "+f"(d[10]), "+f"(d[11]), "+f"(d[12]), "+f"(d[13]), "+f"(d[14]), "+f"(d[15]), "+f"(d[16]), "+f"(d[17]), "+f"(d[18]), "+f"(d[19]), "+f"(d[20]), "+f"(d[21]), "+f"(d[22]), "+f"(d[23]), "+f"(d[24]), "+f"(d[25]), "+f"(d[26]), "+f"(d[27]), "+f"(d[28]), "+f"(d[29]), "+f"(d[30]), "+f"(d[31]), "+f"(d[32]), "+f"(d[33]), "+f"(d[34]), "+f"(d[35]), "+f"(d[36]), "+f"(d[37]), "+f"(d[38]), "+f"(d[39]), "+f"(d[40]), "+f"(d[41]), "+f"(d[42]), "+f"(d[43]), "+f"(d[44]), "+f"(d[45]), "+f"(d[46]), "+f"(d[47]), "+f"(d[48]), "+f"(d[49]), "+f"(d[50]), "+f"(d[51]), "+f"(d[52]), "+f"(d[53]), "+f"(d[54]), "+f"(d[55]), "+f"(d[56]), "+f"(d[57]), "+f"(d[58]), "+f"(d[59]), "+f"(d[60]), "+f"(d[61]), "+f"(d[62]), "+f"(d[63])
    : "r"(a_lo), "r"(b_lo), "r"(scaleD), "n"(OFFA), "n"(OFFB));
}

template <int OFFB>
__device__ __forceinline__ void wgmma_m64n128k16_rs_tb(float (&d)[64], uint32_t a0, uint32_t a1, uint32_t a2, uint32_t a3, uint32_t b_lo, int scaleD) {
  asm volatile("{\n.reg .pred p;\n.reg .b32 tb;\n.reg .b64 db;\nsetp.ne.b32 p, %69, 0;\n"
    "add.u32 tb, %68, %70;\n"
    "mov.b64 db, {tb, 0x40000040};\n"
    "wgmma.mma_async.sync.aligned.m64n128k16.f32.bf16.bf16 "
    "{%0, %1, %2, %3, %4, %5, %6, %7, %8, %9, %10, %11, %12, %13, %14, %15, %16, %17, %18, %19, %20, %21, %22, %23, %24, %25, %26, %27, %28, %29, %30, %31, %32, %33, %34, %35, %36, %37, %38, %39, %40, %41, %42, %43, %44, %45, %46, %47, %48, %49, %50, %51, %52, %53, %54, %55, %56, %57, %58, %59, %60, %61, %62, %63}, "
    "{%64, %65, %66, %67}, db, p, 1, 1, 1;\n}\n"
    : "+f"(d[0]), "+f"(d[1]), "+f"(d[2]), "+f"(d[3]), "+f"(d[4]), "+f"(d[5]), "+f"(d[6]), "+f"(d[7]), "+f"(d[8]), "+f"(d[9]), "+f"(d[10]), "+f"(d[11]), "+f"(d[12]), "+f"(d[13]), "+f"(d[14]), "+f"(d[15]), "+f"(d[16]), "+f"(d[17]), "+f"(d[18]), "+f"(d[19]), "+f"(d[20]), "+f"(d[21]), "+f"(d[22]), "+f"(d[23]), "+f"(d[24]), "+f"(d[25]), "+f"(d[26]), "+f"(d[27]), "+f"(d[28]), "+f"(d[29]), "+f"(d[30]), "+f"(d[31]), "+f"(d[32]), "+f"(d[33]), "+f"(d[34]), "+f"(d[35]), "+f"(d[36]), "+f"(d[37]), "+f"(d[38]), "+f"(d[39]), "+f"(d[40]), "+f"(d[41]), "+f"(d[42]), "+f"(d[43]), "+f"(d[44]), "+f"(d[45]), "+f"(d[46]), "+f"(d[47]), "+f"(d[48]), "+f"(d[49]), "+f"(d[50]), "+f"(d[51]), "+f"(d[52]), "+f"(d[53]), "+f"(d[54]), "+f"(d[55]), "+f"(d[56]), "+f"(d[57]), "+f"(d[58]), "+f"(d[59]), "+f"(d[60]), "+f"(d[61]), "+f"(d[62]), "+f"(d[63])
    : "r"(a0), "r"(a1), "r"(a2), "r"(a3), "r"(b_lo), "r"(scaleD), "n"(OFFB));
}

template <int OFFB>
__device__ __forceinline__ void wgmma_m64n128k16_rs(float (&d)[64], uint32_t a0, uint32_t a1, uint32_t a2, uint32_t a3, uint32_t b_lo, int scaleD) {
  asm volatile("{\n.reg .pred p;\n.reg .b32 tb;\n.reg .b64 db;\nsetp.ne.b32 p, %69, 0;\n"
    "add.u32 tb, %68, %70;\n"
    "mov.b64 db, {tb, 0x40000040};\n"
    "wgmma.mma_async.sync.aligned.m64n128k16.f32.bf16.bf16 "
    "{%0, %1, %2, %3, %4, %5, %6, %7, %8, %9, %10, %11, %12, %13, %14, %15, %16, %17, %18, %19, %20, %21, %22, %23, %24, %25, %26, %27, %28, %29, %30, %31, %32, %33, %34, %35, %36, %37, %38, %39, %40, %41, %42, %43, %44, %45, %46, %47, %48, %49, %50, %51, %52, %53, %54, %55, %56, %57, %58, %59, %60, %61, %62, %63}, "
    "{%64, %65, %66, %67}, db, p, 1, 1, 0;\n}\n"
    : "+f"(d[0]), "+f"(d[1]), "+f"(d[2]), "+f"(d[3]), "+f"(d[4]), "+f"(d[5]), "+f"(d[6]), "+f"(d[7]), "+f"(d[8]), "+f"(d[9]), "+f"(d[10]), "+f"(d[11]), "+f"(d[12]), "+f"(d[13]), "+f"(d[14]), "+f"(d[15]), "+f"(d[16]), "+f"(d[17]), "+f"(d[18]), "+f"(d[19]), "+f"(d[20]), "+f"(d[21]), "+f"(d[22]), "+f"(d[23]), "+f"(d[24]), "+f"(d[25]), "+f"(d[26]), "+f"(d[27]), "+f"(d[28]), "+f"(d[29]), "+f"(d[30]), "+f"(d[31]), "+f"(d[32]), "+f"(d[33]), "+f"(d[34]), "+f"(d[35]), "+f"(d[36]), "+f"(d[37]), "+f"(d[38]), "+f"(d[39]), "+f"(d[40]), "+f"(d[41]), "+f"(d[42]), "+f"(d[43]), "+f"(d[44]), "+f"(d[45]), "+f"(d[46]), "+f"(d[47]), "+f"(d[48]), "+f"(d[49]), "+f"(d[50]), "+f"(d[51]), "+f"(d[52]), "+f"(d[53]), "+f"(d[54]), "+f"(d[55]), "+f"(d[56]), "+f"(d[57]), "+f"(d[58]), "+f"(d[59]), "+f"(d[60]), "+f"(d[61]), "+f"(d[62]), "+f"(d[63])
    : "r"(a0), "r"(a1), "r"(a2), "r"(a3), "r"(b_lo), "r"(scaleD), "n"(OFFB));
}

__device__ __forceinline__ uint4 ldg_nc_v4(const void* p) {
  uint4 v;
    asm volatile("{\n.reg .b64 pol;\ncreatepolicy.fractional.L2::evict_first.b64 pol, 1.0;\n"
                 "ld.global.nc.L1::no_allocate.L2::cache_hint.v4.u32 {%0, %1, %2, %3}, [%4], pol;\n}\n" : "=r"(v.x), "=r"(v.y), "=r"(v.z), "=r"(v.w) : "l"(p));
  return v;
}
__device__ __forceinline__ uint64_t pol_normal() {
  uint64_t p; asm volatile("createpolicy.fractional.L2::evict_normal.b64 %0, 1.0;" : "=l"(p)); return p;
}
__device__ __forceinline__ void unpack8(const uint4& u, float (&v)[8]) {
  v[0] = bflo(u.x); v[1] = bfhi(u.x); v[2] = bflo(u.y); v[3] = bfhi(u.y);
  v[4] = bflo(u.z); v[5] = bfhi(u.z); v[6] = bflo(u.w); v[7] = bfhi(u.w);
}
__device__ __forceinline__ void fma8(float (&acc)[8], float s, const uint4& w) {
  acc[0] = fmaf(s, bflo(w.x), acc[0]); acc[1] = fmaf(s, bfhi(w.x), acc[1]); acc[2] = fmaf(s, bflo(w.y), acc[2]); acc[3] = fmaf(s, bfhi(w.y), acc[3]);
  acc[4] = fmaf(s, bflo(w.z), acc[4]); acc[5] = fmaf(s, bfhi(w.z), acc[5]); acc[6] = fmaf(s, bflo(w.w), acc[6]); acc[7] = fmaf(s, bfhi(w.w), acc[7]);
}
__device__ __forceinline__ float rcp_approx(float x) { float y; asm("rcp.approx.ftz.f32 %0, %1;" : "=f"(y) : "f"(x)); return y; }
__device__ __forceinline__ float sigmoid_f(float v) { return rcp_approx(1.0f + ex2_approx(v * -1.4426950408889634f)); }
__device__ __forceinline__ float silu_bf(float v) { return rbf(v * sigmoid_f(v)); }
__device__ __forceinline__ uint32_t rank_key(float r, int idx) {
  const uint32_t b = __float_as_uint(r) >> 16;
  const uint32_t u = (r != r) ? 0u : ((b & 0x8000u) ? (~b & 0xffffu) : (b | 0x8000u));
  return (u << 16) | (0xffffu - (uint32_t)idx);
}
__device__ __forceinline__ void warp_top2(uint32_t& k1, uint32_t& k2) {
  const uint32_t m1 = __reduce_max_sync(0xffffffffu, k1);
  k2 = __reduce_max_sync(0xffffffffu, k1 == m1 ? k2 : k1);
  k1 = m1;
}
__device__ __forceinline__ uint32_t bmul2(uint32_t a, uint32_t b) { uint32_t r; asm("mul.rn.bf16x2 %0, %1, %2;" : "=r"(r) : "r"(a), "r"(b)); return r; }
__device__ __forceinline__ uint32_t badd2(uint32_t a, uint32_t b) { uint32_t r; asm("add.rn.bf16x2 %0, %1, %2;" : "=r"(r) : "r"(a), "r"(b)); return r; }
__device__ __forceinline__ uint32_t bsub2(uint32_t a, uint32_t b) { uint32_t r; asm("sub.rn.bf16x2 %0, %1, %2;" : "=r"(r) : "r"(a), "r"(b)); return r; }
__device__ __forceinline__ float sqrt_approx(float x) { float y; asm("sqrt.approx.f32 %0, %1;" : "=f"(y) : "f"(x)); return y; }
__device__ __forceinline__ uint32_t ln_norm2(uint32_t x1, uint32_t mb2, float inv) {
  const uint32_t d = bsub2(x1, mb2);
  return pack_bf16(bflo(d) * inv, bfhi(d) * inv);
}
__device__ __forceinline__ uint32_t ln_mod2(uint32_t x1, uint32_t mb2, float inv, uint32_t c1, uint32_t sb) { return badd2(bmul2(ln_norm2(x1, mb2, inv), c1), sb); }
__device__ __forceinline__ void ldmatrix_x4(uint32_t addr, uint32_t& r0, uint32_t& r1, uint32_t& r2, uint32_t& r3) {
  asm volatile("ldmatrix.sync.aligned.m8n8.x4.shared.b16 {%0, %1, %2, %3}, [%4];" : "=r"(r0), "=r"(r1), "=r"(r2), "=r"(r3) : "r"(addr) : "memory");
}
__device__ __forceinline__ uint4 ldg_stream_v4(const void* p, uint64_t pol) {
  uint4 v; asm volatile("ld.global.nc.L1::no_allocate.L2::cache_hint.L2::128B.v4.u32 {%0, %1, %2, %3}, [%4], %5;" : "=r"(v.x), "=r"(v.y), "=r"(v.z), "=r"(v.w) : "l"(p), "l"(pol)); return v;
}
__device__ __forceinline__ void bulk_load_hint(uint32_t dst, const void* src, uint32_t bytes, uint32_t bar, uint64_t pol) {
  asm volatile("cp.async.bulk.shared::cluster.global.mbarrier::complete_tx::bytes.L2::cache_hint [%0], [%1], %2, [%3], %4;"
    :: "r"(dst), "l"(src), "r"(bytes), "r"(bar), "l"(pol) : "memory");
}
__device__ __forceinline__ void red_release_add(unsigned int* p, unsigned int v) { asm volatile("red.release.gpu.global.add.u32 [%0], %1;" :: "l"(p), "r"(v) : "memory"); }
__device__ __forceinline__ unsigned int ld_acquire(const unsigned int* p) { unsigned int v; asm volatile("ld.acquire.gpu.global.u32 %0, [%1];" : "=r"(v) : "l"(p) : "memory"); return v; }
__device__ __forceinline__ void spin_until(const unsigned int* p, unsigned int target) {
  #pragma unroll 1
  for (unsigned int i = 0; i < (1u << 22); i++) { if (ld_acquire(p) >= target) return; }
}
__device__ __forceinline__ float lds_f32(uint32_t a) { float v; asm volatile("ld.shared.f32 %0, [%1];" : "=f"(v) : "r"(a) : "memory"); return v; }
__device__ __forceinline__ float2 lds_f32x2(uint32_t a) { float2 v; asm volatile("ld.shared.v2.f32 {%0, %1}, [%2];" : "=f"(v.x), "=f"(v.y) : "r"(a) : "memory"); return v; }
__device__ __forceinline__ uint2 lds_u32x2(uint32_t a) { uint2 v; asm volatile("ld.shared.v2.u32 {%0, %1}, [%2];" : "=r"(v.x), "=r"(v.y) : "r"(a) : "memory"); return v; }
__device__ __forceinline__ uint32_t lds_u32(uint32_t a) { uint32_t v; asm volatile("ld.shared.u32 %0, [%1];" : "=r"(v) : "r"(a) : "memory"); return v; }
__device__ __forceinline__ void sts_u32(uint32_t a, uint32_t v) { asm volatile("st.shared.u32 [%0], %1;" :: "r"(a), "r"(v) : "memory"); }
__device__ __forceinline__ void sts_u32x2(uint32_t a, uint32_t x, uint32_t y) { asm volatile("st.shared.v2.u32 [%0], {%1, %2};" :: "r"(a), "r"(x), "r"(y) : "memory"); }
__device__ __forceinline__ void sts_f32(uint32_t a, float v) { asm volatile("st.shared.f32 [%0], %1;" :: "r"(a), "f"(v) : "memory"); }
__device__ __forceinline__ void sts_f32x2(uint32_t a, float x, float y) { asm volatile("st.shared.v2.f32 [%0], {%1, %2};" :: "r"(a), "f"(x), "f"(y) : "memory"); }
__device__ __forceinline__ void sts_f32x4(uint32_t a, float x, float y, float z, float w) { asm volatile("st.shared.v4.f32 [%0], {%1, %2, %3, %4};" :: "r"(a), "f"(x), "f"(y), "f"(z), "f"(w) : "memory"); }

__device__ __forceinline__ uint4 lds_u32x4(uint32_t a) { uint4 v; asm volatile("ld.shared.v4.u32 {%0, %1, %2, %3}, [%4];" : "=r"(v.x), "=r"(v.y), "=r"(v.z), "=r"(v.w) : "r"(a) : "memory"); return v; }
__device__ __forceinline__ void sts_u32x4(uint32_t a, uint32_t x, uint32_t y, uint32_t z, uint32_t w) { asm volatile("st.shared.v4.u32 [%0], {%1, %2, %3, %4};" :: "r"(a), "r"(x), "r"(y), "r"(z), "r"(w) : "memory"); }
__device__ __forceinline__ void st_tagged(float* p, float v) {
  const uint32_t b = __float_as_uint(v);
  asm volatile("st.relaxed.gpu.global.u32 [%0], %1;" :: "l"(p), "r"(b == 0u ? 0x80000000u : b) : "memory");
}
__device__ __forceinline__ void st_tagged4(float* p, float x, float y, float z, float w) {
  const uint32_t a = __float_as_uint(x), b = __float_as_uint(y), c = __float_as_uint(z), d = __float_as_uint(w);
  asm volatile("st.relaxed.gpu.global.v4.u32 [%0], {%1, %2, %3, %4};" :: "l"(p), "r"(a == 0u ? 0x80000000u : a), "r"(b == 0u ? 0x80000000u : b),
               "r"(c == 0u ? 0x80000000u : c), "r"(d == 0u ? 0x80000000u : d) : "memory");
}
__device__ __forceinline__ void st_relaxed2(void* p, uint32_t a, uint32_t b) { asm volatile("st.relaxed.gpu.global.v2.u32 [%0], {%1, %2};" :: "l"(p), "r"(a), "r"(b) : "memory"); }
__device__ __forceinline__ float4 ld_tagged4(const float* p) {
  float4 v; asm volatile("ld.relaxed.gpu.global.v4.f32 {%0, %1, %2, %3}, [%4];" : "=f"(v.x), "=f"(v.y), "=f"(v.z), "=f"(v.w) : "l"(p) : "memory"); return v;
}
__device__ __forceinline__ bool tagged4(const float4& v) {
  return __float_as_uint(v.x) != 0u && __float_as_uint(v.y) != 0u && __float_as_uint(v.z) != 0u && __float_as_uint(v.w) != 0u;
}
__device__ __forceinline__ void hint_arrive(uint32_t* p) { asm volatile("red.relaxed.gpu.global.add.u32 [%0], 1;" :: "l"(p) : "memory"); }
__device__ __forceinline__ void hint_wait(const uint32_t* p, uint32_t target) {
  uint32_t v = 0u;
  #pragma unroll 1
  for (unsigned int i = 0; i < (1u << 22) && v < target; i++) asm volatile("ld.relaxed.gpu.global.u32 %0, [%1];" : "=r"(v) : "l"(p) : "memory");
}
__device__ __forceinline__ void fence_proxy_async_global() { asm volatile("fence.proxy.async.global;" ::: "memory"); }

constexpr int H_SPLIT = 1;
constexpr int PRE_B = 2;
__device__ __forceinline__ void load_parts(float4 (&pa)[4], float4 (&pb)[4], int t2) {
  #pragma unroll
  for (int k = 0; k < 4; k++) { pa[k] = ld_tagged4(g_modpart + k * 2 * T_D + t2 * 8); pb[k] = ld_tagged4(g_modpart + k * 2 * T_D + t2 * 8 + 4); }
}
__device__ __forceinline__ void finish_parts(float4 (&pa)[4], float4 (&pb)[4], int t2, uint32_t tab) {
  #pragma unroll 1
  for (unsigned int spin = 0; spin < (1u << 22); spin++) {
    bool ok = true;
    #pragma unroll
    for (int k = 0; k < 4; k++) ok &= tagged4(pa[k]) & tagged4(pb[k]);
    if (__all_sync(0xffffffffu, ok)) break;
    load_parts(pa, pb, t2);
  }
  #pragma unroll
  for (int k = 1; k < 4; k++) {
    pa[0].x += pa[k].x; pa[0].y += pa[k].y; pa[0].z += pa[k].z; pa[0].w += pa[k].w;
    pb[0].x += pb[k].x; pb[0].y += pb[k].y; pb[0].z += pb[k].z; pb[0].w += pb[k].w;
  }
  uint32_t m0 = pack_bf16(pa[0].x, pa[0].y), m1 = pack_bf16(pa[0].z, pa[0].w), m2 = pack_bf16(pb[0].x, pb[0].y), m3 = pack_bf16(pb[0].z, pb[0].w);
  if (t2 >= 128) { m0 = badd2(m0, 0x3F803F80u); m1 = badd2(m1, 0x3F803F80u); m2 = badd2(m2, 0x3F803F80u); m3 = badd2(m3, 0x3F803F80u); }
  sts_u32x4(tab + t2 * 16, m0, m1, m2, m3);
}
__device__ __forceinline__ void head_phase(uint32_t scr, uint32_t xs, uint32_t b_x, uint32_t b_go, uint32_t b_head, int t2, uint32_t zero, const bf16* __restrict__ x, const bf16* __restrict__ cvec, const bf16* __restrict__ w_mod) {
  const int lane = t2 & 31, w8 = t2 >> 5;
  const int cb = blockIdx.x & 31, ks = blockIdx.x >> 5;
  uint4 w[8], xv[2][4];
  const float cv = __bfloat162float(cvec[ks * 256 + t2]);
  #pragma unroll
  for (int i = 0; i < 8; i++) w[i] = ldg_nc_v4(w_mod + (size_t)(ks * 256 + (t2 >> 3) + 32 * i) * (6 * T_D) + cb * 64 + (t2 & 7) * 8);
  const int row0 = blockIdx.x * 16 + 2 * w8;
  sts_f32(scr + t2 * 4, silu_bf(cv));
  #pragma unroll 1
  for (uint32_t i = 0; i <= zero; i++) named_bar_sync(6, 384);
  TL_MARK2(1, t2 == 0);
  {
    float acc[8];
    #pragma unroll
    for (int j = 0; j < 8; j++) acc[j] = 0.f;
    #pragma unroll
    for (int i = 0; i < 8; i++) {
      fma8(acc, lds_f32(scr + ((t2 >> 3) + 32 * i) * 4), w[i]);
      if (i == 0 && t2 == 0) {
        mbar_expect_tx(b_x + (__float_as_uint(acc[0]) & zero), 32768);
        bulk_load_hint(xs, x + (size_t)blockIdx.x * 16 * T_D, 32768, b_x, policy_evict_first());
      }
    }
    #pragma unroll
    for (int j = 0; j < 4; j++) { const bool up = lane & 16; acc[j] = (up ? acc[4 + j] : acc[j]) + __shfl_xor_sync(0xffffffffu, up ? acc[j] : acc[4 + j], 16); }
    #pragma unroll
    for (int j = 0; j < 2; j++) { const bool up = lane & 8; acc[j] = (up ? acc[2 + j] : acc[j]) + __shfl_xor_sync(0xffffffffu, up ? acc[j] : acc[2 + j], 8); }
    sts_f32x2(scr + 1024 + w8 * 256 + (lane & 7) * 32 + (lane >> 3) * 8, acc[0], acc[1]);
  }
  named_bar_sync(5, 256);
  if (t2 < 64) {
    float sum = 0.f;
    #pragma unroll
    for (int i = 0; i < 8; i++) sum += lds_f32(scr + 1024 + i * 256 + t2 * 4);
    st_tagged(g_modpart + ks * 2 * T_D + cb * 64 + t2, sum);
    TL_MARK2(2, t2 == 0);
  }
  mbar_wait(b_x, 0);
  const bool first_cols = (__shfl_sync(0xffffffffu, w8, 0) & 3) == 0;
  float4 pa[4], pb[4];
  pa[0].x = 0.f;
  if (first_cols) load_parts(pa, pb, t2);
  #pragma unroll
  for (int r = 0; r < 2; r++)
    #pragma unroll
    for (int j = 0; j < 4; j++) xv[r][j] = lds_u32x4(xs + (2 * w8 + r) * 2048 + j * 512 + lane * 16);
  #pragma unroll
  for (int r = 0; r < 2; r++) {
    float v[4][8], sum = 0.f;
    #pragma unroll
    for (int j = 0; j < 4; j++) {
      unpack8(xv[r][j], v[j]);
      sum += ((v[j][0] + v[j][1]) + (v[j][2] + v[j][3])) + ((v[j][4] + v[j][5]) + (v[j][6] + v[j][7]));
    }
    #pragma unroll
    for (int o = 16; o > 0; o >>= 1) sum += __shfl_xor_sync(0xffffffffu, sum, o);
    const float mean = sum * (1.0f / T_D);
    float q = 0.f;
    #pragma unroll
    for (int j = 0; j < 4; j++)
      #pragma unroll
      for (int i = 0; i < 8; i++) { const float d = v[j][i] - mean; q = fmaf(d, d, q); }
    #pragma unroll
    for (int o = 16; o > 0; o >>= 1) q += __shfl_xor_sync(0xffffffffu, q, o);
    const uint32_t mb2 = pack_bf16(mean, mean);
    const float inv = rcp_approx(rbf(sqrt_approx(rbf(rbf(q * (1.0f / T_D)) + 1e-05f))));
    #pragma unroll
    for (int j = 0; j < 4; j++) {
      xv[r][j].x = ln_norm2(xv[r][j].x, mb2, inv); xv[r][j].y = ln_norm2(xv[r][j].y, mb2, inv);
      xv[r][j].z = ln_norm2(xv[r][j].z, mb2, inv); xv[r][j].w = ln_norm2(xv[r][j].w, mb2, inv);
    }
  }
  TL_MARK2(5, t2 == 0);
  #pragma unroll 1
  for (int ph = 0; ph < 2; ph++) {
    if (first_cols == (ph == 0)) finish_parts(pa, pb, t2, scr + 8192);
    named_bar_sync(5, 256);
    if (ph) break;
    TL_MARK2(7, t2 == 0);
    const uint4 sa = lds_u32x4(scr + 8192 + lane * 16), c1 = lds_u32x4(scr + 8192 + 2048 + lane * 16);
    #pragma unroll
    for (int r = 0; r < 2; r++)
      *reinterpret_cast<uint4*>(g_h + (size_t)(row0 + r) * T_D + lane * 8) = make_uint4(badd2(bmul2(xv[r][0].x, c1.x), sa.x), badd2(bmul2(xv[r][0].y, c1.y), sa.y),
                                                                                        badd2(bmul2(xv[r][0].z, c1.z), sa.z), badd2(bmul2(xv[r][0].w, c1.w), sa.w));
    named_bar_sync(5, 256);
    TL_MARK2(18, t2 == 0);
    if (t2 == 0) red_release_add(&g_hcnt[32 * (1 + (blockIdx.x >> 3))], 1u);
    TL_MARK2(11, t2 == 0);
  }
  TL_MARK2(6, t2 == 0);
  #pragma unroll
  for (int j = 1; j < 4; j++) {
    const uint4 sa = lds_u32x4(scr + 8192 + (j * 32 + lane) * 16), c1 = lds_u32x4(scr + 8192 + 2048 + (j * 32 + lane) * 16);
    #pragma unroll
    for (int r = 0; r < 2; r++) {
      xv[r][j].x = badd2(bmul2(xv[r][j].x, c1.x), sa.x); xv[r][j].y = badd2(bmul2(xv[r][j].y, c1.y), sa.y);
      xv[r][j].z = badd2(bmul2(xv[r][j].z, c1.z), sa.z); xv[r][j].w = badd2(bmul2(xv[r][j].w, c1.w), sa.w);
    }
  }
  __syncwarp();
  if (lane == 0) mbar_arrive(b_head + (xv[1][3].w & zero));
  mbar_wait(b_go, 0);
  #pragma unroll
  for (int j = 1; j < 4; j++)
    #pragma unroll
    for (int r = 0; r < 2; r++) *reinterpret_cast<uint4*>(g_h + (size_t)(row0 + r) * T_D + j * 256 + lane * 8) = xv[r][j];
  named_bar_arrive(8, 288);
}

#define MOD_AT (b_empty + 8)
#define MOD_PF 0
#define MOD_SPLIT 16
__device__ __forceinline__ void mod_rest(uint32_t scr, uint32_t b_go, int t, const bf16* __restrict__ cvec, const bf16* __restrict__ w_mod, const bf16* __restrict__ w_r) {
  const int lane = t & 31;
  #pragma unroll 1
  for (int i = t; i < T_D / 2; i += 64) {
    const uint32_t c2 = *reinterpret_cast<const uint32_t*>(cvec + 2 * i);
    sts_u32(scr + i * 4, pack_bf16(silu_bf(bflo(c2)), silu_bf(bfhi(c2))));
  }
  named_bar_sync(11, 64);
  const bf16* wp = w_mod + (size_t)(2 * (t >> 2)) * (6 * T_D) + 2 * T_D + blockIdx.x * 32 + (t & 3) * 8;
  float acc[8];
  #pragma unroll
  for (int i = 0; i < 8; i++) acc[i] = 0.f;
  #pragma unroll 1
  for (int i = 0; i < 32; i += 2) {
    if (i == MOD_SPLIT) mbar_wait(b_go, 0);
    const uint4 w0 = ldg_nc_v4(wp), w1 = ldg_nc_v4(wp + 6 * T_D), w2 = ldg_nc_v4(wp + 32 * 6 * T_D), w3 = ldg_nc_v4(wp + 33 * 6 * T_D);
    wp += 64 * 6 * T_D;
    const uint32_t s0 = lds_u32(scr + (i * 16 + (t >> 2)) * 4), s1 = lds_u32(scr + (i * 16 + 16 + (t >> 2)) * 4);
    fma8(acc, bflo(s0), w0); fma8(acc, bfhi(s0), w1); fma8(acc, bflo(s1), w2); fma8(acc, bfhi(s1), w3);
  }
  #pragma unroll
  for (int j = 0; j < 4; j++) { const bool up = lane & 16; acc[j] = (up ? acc[4 + j] : acc[j]) + __shfl_xor_sync(0xffffffffu, up ? acc[j] : acc[4 + j], 16); }
  #pragma unroll
  for (int j = 0; j < 2; j++) { const bool up = lane & 8; acc[j] = (up ? acc[2 + j] : acc[j]) + __shfl_xor_sync(0xffffffffu, up ? acc[j] : acc[2 + j], 8); }
  { const bool up = lane & 4; acc[0] = (up ? acc[1] : acc[0]) + __shfl_xor_sync(0xffffffffu, up ? acc[0] : acc[1], 4); }
  if (t >= 32) sts_f32(scr + 2048 + lane * 4, acc[0]);
  named_bar_sync(11, 64);
  if (__shfl_sync(0xffffffffu, t, 0) < 32) {
    const int kind = blockIdx.x >> 5;
    float v = rbf(acc[0] + lds_f32(scr + 2048 + lane * 4));
    const int col = (blockIdx.x & 31) * 32 + (lane & 3) * 8 + (lane >> 2);
    uint8_t* dst = g_col + (col >> 7) * 1536;
    if (kind == 2) v = rbf(1.0f + v);
    float vw = v * __bfloat162float(w_r[col]);
    if (kind == 2) {
      const int c = col & 127, i = (c & ~15) + ((c >> 1) & 3) * 4 + ((c >> 3) & 1) * 2 + (c & 1);
      reinterpret_cast<bf16*>(dst)[i] = __float2bfloat16_rn(vw);
      reinterpret_cast<bf16*>(dst)[128 + i] = __float2bfloat16_rn(vw - rbf(vw));
    }
    reinterpret_cast<bf16*>(dst + 512 + (kind & 1) * 512 + (kind >> 1) * 256)[col & 127] = __float2bfloat16_rn(v);
    #pragma unroll
    for (int o = 16; o > 0; o >>= 1) vw += __shfl_xor_sync(0xffffffffu, vw, o);
    if (lane == 0 && (kind == 1 || kind == 2)) g_scal[95 - blockIdx.x] = vw;
  }
  #pragma unroll 1
  for (int i = blockIdx.x * 64 + t; i < (int)(sizeof(g_mail) / 16); i += 128 * 64) reinterpret_cast<uint4*>(&g_mail)[i] = make_uint4(0u, 0u, 0u, 0u);
  named_bar_sync(11, 64);
  if (t == 0) red_release_add(&g_hcnt[0], 1u);
}

#define HPOL_A pol_normal()
#define HPOL_B pol_normal()
#define HMAP_A &tmOl
#define HMAP_B &tmWo
constexpr int AT_NBLK = T_SEQ / 128;
constexpr float AT_HEAD = 7.0f;
#define WO_LATE 12
constexpr int QP_STAG = 3;
constexpr int AT_SPLIT = 28, AT_PIN = 8, PINB = 4;
constexpr int AT_NFULL = 124;
constexpr int AT_PREG = 40, AT_CREG = 232;
constexpr uint32_t AT_SQ = 5 * 32768;
constexpr float AT_C = 0.08838834764831845f * 1.4426950408889634f;
constexpr float AT_RAW_LO = -16.0f, AT_RAW_HI = 24.0f;
constexpr float AT_RAW_SUM = 281474976710656.0f, AT_RAW_MIN = 9.094947017729282e-13f;
constexpr uint32_t AT_SBAR = AT_SQ + 65536 + 256;
constexpr uint32_t AT_SMEM = AT_SQ + 65536 + 3072;

__device__ __forceinline__ uint32_t ring_slot(uint32_t t) { return t - 5u * ((t * 205u) >> 10); }
__device__ __forceinline__ uint32_t qp_pos(uint32_t j, uint32_t it) { return 4u * it + (j & 3u) + ((j & 3u) == 3u ? it : 0u); }
__device__ __forceinline__ uint32_t ring_par(uint32_t t) { return ((t * 205u) >> 10) & 1u; }
__device__ __forceinline__ void softmax_rowmax(const float (&s)[64], float& mx0, float& mx1) {
  float a0 = fmaxf(s[0], s[1]), a1 = fmaxf(s[4], s[5]), a2 = fmaxf(s[8], s[9]), a3 = fmaxf(s[12], s[13]);
  float b0 = fmaxf(s[2], s[3]), b1 = fmaxf(s[6], s[7]), b2 = fmaxf(s[10], s[11]), b3 = fmaxf(s[14], s[15]);
  #pragma unroll
  for (int j = 4; j < 16; j += 4) {
    a0 = fmaxf(a0, fmaxf(s[4 * j + 0], s[4 * j + 1]));  b0 = fmaxf(b0, fmaxf(s[4 * j + 2], s[4 * j + 3]));
    a1 = fmaxf(a1, fmaxf(s[4 * j + 4], s[4 * j + 5]));  b1 = fmaxf(b1, fmaxf(s[4 * j + 6], s[4 * j + 7]));
    a2 = fmaxf(a2, fmaxf(s[4 * j + 8], s[4 * j + 9]));  b2 = fmaxf(b2, fmaxf(s[4 * j + 10], s[4 * j + 11]));
    a3 = fmaxf(a3, fmaxf(s[4 * j + 12], s[4 * j + 13])); b3 = fmaxf(b3, fmaxf(s[4 * j + 14], s[4 * j + 15]));
  }
  mx0 = fmaxf(fmaxf(a0, a1), fmaxf(a2, a3));
  mx1 = fmaxf(fmaxf(b0, b1), fmaxf(b2, b3));
  mx0 = fmaxf(mx0, __shfl_xor_sync(0xffffffffu, mx0, 1));
  mx1 = fmaxf(mx1, __shfl_xor_sync(0xffffffffu, mx1, 1));
  mx0 = fmaxf(mx0, __shfl_xor_sync(0xffffffffu, mx0, 2));
  mx1 = fmaxf(mx1, __shfl_xor_sync(0xffffffffu, mx1, 2));
}
__device__ __forceinline__ void softmax_sub(float (&s)[64], float mc0, float mc1) {
  #pragma unroll
  for (int j = 0; j < 16; j++) { s[4 * j] -= mc0; s[4 * j + 1] -= mc0; s[4 * j + 2] -= mc1; s[4 * j + 3] -= mc1; }
}
template <int LO, int HI>
__device__ __forceinline__ void softmax_exp(float (&s)[64]) {
  #pragma unroll
  for (int i = LO; i < HI; i++) s[i] = ex2_approx(s[i]);
}
__device__ __forceinline__ bool softmax_mode(const float (&s)[64], float& mc0, float& mc1) {
  softmax_rowmax(s, mc0, mc1);
  const bool raw = __all_sync(0xffffffffu, mc0 >= AT_RAW_LO && mc0 <= AT_RAW_HI && mc1 >= AT_RAW_LO && mc1 <= AT_RAW_HI);
  mc0 += AT_HEAD; mc1 += AT_HEAD;
  return raw;
}
__device__ __forceinline__ void rowsum_p(const uint32_t (&p)[32], uint32_t& t0, uint32_t& t1) {
  uint32_t a[16];
  #pragma unroll
  for (int i = 0; i < 8; i++) { a[2 * i] = badd2(p[4 * i], p[4 * i + 2]); a[2 * i + 1] = badd2(p[4 * i + 1], p[4 * i + 3]); }
  #pragma unroll
  for (int i = 0; i < 4; i++) { a[2 * i] = badd2(a[4 * i], a[4 * i + 2]); a[2 * i + 1] = badd2(a[4 * i + 1], a[4 * i + 3]); }
  t0 = badd2(badd2(a[0], a[2]), badd2(a[4], a[6]));
  t1 = badd2(badd2(a[1], a[3]), badd2(a[5], a[7]));
}
__device__ __forceinline__ void add_rowsum(const uint32_t (&p)[32], float& l0, float& l1) {
  uint32_t t0, t1;
  rowsum_p(p, t0, t1);
  l0 += bflo(t0) + bfhi(t0); l1 += bflo(t1) + bfhi(t1);
}
__device__ __forceinline__ void pack_p(uint32_t (&p)[32], const float (&s)[64]) {
  #pragma unroll
  for (int i = 0; i < 32; i++) p[i] = pack_bf16(s[2 * i], s[2 * i + 1]);
}
__device__ __noinline__ void attn_rows_exact(uint32_t sq, uint32_t so, int hsel, const bf16* __restrict__ kh, const bf16* __restrict__ vh) {
  const int warp = (threadIdx.x >> 5) & 3, lane = threadIdx.x & 31;
  const size_t hofs = (size_t)((blockIdx.x < 128 ? blockIdx.x >> 4 : 15) * 2 + hsel) * T_SEQ * T_DH;
  kh += hofs; vh += hofs;
  #pragma unroll 1
  for (int r = 16 * warp; r < 16 * warp + 16; r++) {
    const uint32_t ad = (lane >> 4) * 16384 + r * 128 + ((((lane & 15) >> 1) ^ (r & 7)) << 4) + (lane & 1) * 8;
    uint2 qv; asm volatile("ld.shared.v2.u32 {%0, %1}, [%2];" : "=r"(qv.x), "=r"(qv.y) : "r"(sq + ad) : "memory");
    const float q0 = bflo(qv.x), q1 = bfhi(qv.x), q2 = bflo(qv.y), q3 = bfhi(qv.y);
    float m = -INFINITY, l = 0.f, o0 = 0.f, o1 = 0.f, o2 = 0.f, o3 = 0.f;
    #pragma unroll 1
    for (int key = 0; key < T_SEQ; key++) {
      const uint2 kv = *reinterpret_cast<const uint2*>(kh + (size_t)key * T_DH + lane * 4);
      const uint2 vv = *reinterpret_cast<const uint2*>(vh + (size_t)key * T_DH + lane * 4);
      float sc = (q0 * bflo(kv.x) + q1 * bfhi(kv.x)) + (q2 * bflo(kv.y) + q3 * bfhi(kv.y));
      #pragma unroll
      for (int o = 16; o > 0; o >>= 1) sc += __shfl_xor_sync(0xffffffffu, sc, o);
      const float mn = fmaxf(m, sc);
      const float al = (m == mn) ? 1.0f : ex2_approx(m - mn), p = rbf(ex2_approx(sc - mn));
      m = mn;
      l = fmaf(l, al, p);
      o0 = fmaf(o0, al, p * bflo(vv.x)); o1 = fmaf(o1, al, p * bfhi(vv.x));
      o2 = fmaf(o2, al, p * bflo(vv.y)); o3 = fmaf(o3, al, p * bfhi(vv.y));
    }
    const float inv = rcp_approx(l);
    asm volatile("st.shared.v2.u32 [%0], {%1, %2};" :: "r"(so + ad), "r"(pack_bf16(o0 * inv, o1 * inv)), "r"(pack_bf16(o2 * inv, o3 * inv)) : "memory");
  }
}
__device__ __forceinline__ void issue_qk(float (&s)[64], const uint32_t (&q)[32], uint32_t k_lo) {
  wgmma_fence();
  wgmma_m64n128k16_rs<0>(s, q[0], q[1], q[2], q[3], k_lo, 0);
  wgmma_m64n128k16_rs<2>(s, q[4], q[5], q[6], q[7], k_lo, 1);
  wgmma_m64n128k16_rs<4>(s, q[8], q[9], q[10], q[11], k_lo, 1);
  wgmma_m64n128k16_rs<6>(s, q[12], q[13], q[14], q[15], k_lo, 1);
  wgmma_m64n128k16_rs<1024>(s, q[16], q[17], q[18], q[19], k_lo, 1);
  wgmma_m64n128k16_rs<1026>(s, q[20], q[21], q[22], q[23], k_lo, 1);
  wgmma_m64n128k16_rs<1028>(s, q[24], q[25], q[26], q[27], k_lo, 1);
  wgmma_m64n128k16_rs<1030>(s, q[28], q[29], q[30], q[31], k_lo, 1);
  wgmma_commit();
}
__device__ __forceinline__ void issue_pv(float (&o)[64], const uint32_t (&p)[32], uint32_t v_lo, int accumulate) {
  wgmma_fence();
  wgmma_m64n128k16_rs_tb<0>(o, p[0], p[1], p[2], p[3], v_lo, accumulate);
  wgmma_m64n128k16_rs_tb<128>(o, p[4], p[5], p[6], p[7], v_lo, 1);
  wgmma_m64n128k16_rs_tb<256>(o, p[8], p[9], p[10], p[11], v_lo, 1);
  wgmma_m64n128k16_rs_tb<384>(o, p[12], p[13], p[14], p[15], v_lo, 1);
  wgmma_m64n128k16_rs_tb<512>(o, p[16], p[17], p[18], p[19], v_lo, 1);
  wgmma_m64n128k16_rs_tb<640>(o, p[20], p[21], p[22], p[23], v_lo, 1);
  wgmma_m64n128k16_rs_tb<768>(o, p[24], p[25], p[26], p[27], v_lo, 1);
  wgmma_m64n128k16_rs_tb<896>(o, p[28], p[29], p[30], p[31], v_lo, 1);
  wgmma_commit();
}
__device__ __forceinline__ void block_end(uint32_t zero, uint32_t bar) {
  #pragma unroll 1
  for (uint32_t i = 0; i < zero; i++) mbar_arrive(bar);
}
__device__ __forceinline__ void rescale_o(float (&o)[64], float al0, float al1) {
  #pragma unroll
  for (int j = 0; j < 16; j++) { o[4 * j] *= al0; o[4 * j + 1] *= al0; o[4 * j + 2] *= al1; o[4 * j + 3] *= al1; }
}

__device__ __forceinline__ void stage_o(const float (&o)[64], float i0, float i1, uint32_t dst, int lane) {
  #pragma unroll
  for (int J = 0; J < 16; J += 2)
    stmatrix_x4(dst + (J >> 3) * 16384 + ((((J & 7) + (lane >> 4)) ^ (lane & 7)) << 4),
                pack_bf16(o[4 * J + 0] * i0, o[4 * J + 1] * i0), pack_bf16(o[4 * J + 2] * i1, o[4 * J + 3] * i1),
                pack_bf16(o[4 * J + 4] * i0, o[4 * J + 5] * i0), pack_bf16(o[4 * J + 6] * i1, o[4 * J + 7] * i1));
}
__device__ __forceinline__ bool finish_l(float& l0, float& l1) {
  l0 += __shfl_xor_sync(0xffffffffu, l0, 1); l1 += __shfl_xor_sync(0xffffffffu, l1, 1);
  l0 += __shfl_xor_sync(0xffffffffu, l0, 2); l1 += __shfl_xor_sync(0xffffffffu, l1, 2);
  const bool redo = __any_sync(0xffffffffu, !(l0 <= AT_RAW_SUM && l1 <= AT_RAW_SUM && l0 >= AT_RAW_MIN && l1 >= AT_RAW_MIN));
  l0 = rcp_approx(l0); l1 = rcp_approx(l1);
  return redo;
}
template <int J0>
__device__ __forceinline__ void stage_q(const float (&acc)[128], float c, uint32_t dst, int lane) {
  #pragma unroll
  for (int J = J0; J < J0 + 16; J += 2)
    stmatrix_x4(dst + (J >> 3) * 16384 + ((((J & 7) + (lane >> 4)) ^ (lane & 7)) << 4),
                pack_bf16(acc[4 * J + 0] * c, acc[4 * J + 1] * c), pack_bf16(acc[4 * J + 2] * c, acc[4 * J + 3] * c),
                pack_bf16(acc[4 * J + 4] * c, acc[4 * J + 5] * c), pack_bf16(acc[4 * J + 6] * c, acc[4 * J + 7] * c));
}
__device__ __forceinline__ void store_o(const CUtensorMap* tmO, uint32_t src, int head, int row) {
  tma_store_2d(tmO, src, head * T_DH, row);
  tma_store_2d(tmO, src + 16384, head * T_DH + 64, row);
  bulk_commit();
}
__device__ __forceinline__ void mma_bf16(float (&d)[4], uint32_t a0, uint32_t a1, uint32_t a2, uint32_t a3, uint32_t b0, uint32_t b1) {
  asm volatile("mma.sync.aligned.m16n8k16.row.col.f32.bf16.bf16.f32 {%0, %1, %2, %3}, {%4, %5, %6, %7}, {%8, %9}, {%0, %1, %2, %3};"
               : "+f"(d[0]), "+f"(d[1]), "+f"(d[2]), "+f"(d[3]) : "r"(a0), "r"(a1), "r"(a2), "r"(a3), "r"(b0), "r"(b1));
}
struct GemvSel { uint32_t lo0, hi0, lo1, hi1; };
__device__ __forceinline__ GemvSel gemv_sel(int lane) {
  const uint32_t lo = (lane & 8) ? 0x1044u : 0x4410u, hi = (lane & 8) ? 0x3244u : 0x4432u;
  GemvSel s; s.lo0 = (lane & 16) ? 0x4444u : lo; s.hi0 = (lane & 16) ? 0x4444u : hi; s.lo1 = (lane & 16) ? lo : 0x4444u; s.hi1 = (lane & 16) ? hi : 0x4444u;
  return s;
}
#define GEMV_B0(j, h, s) __byte_perm((j) < 2 ? (h).x : (h).y, 0u, ((j) & 1) ? (s).hi0 : (s).lo0)
#define GEMV_B1(j, h, s) __byte_perm((j) < 2 ? (h).x : (h).y, 0u, ((j) & 1) ? (s).hi1 : (s).lo1)
__device__ __forceinline__ float4 gemv_out(const float (&d)[4], int lane) {
  const bool tk = lane & 1;
  const float r0 = __shfl_xor_sync(0xffffffffu, tk ? d[0] : d[1], 1), r1 = __shfl_xor_sync(0xffffffffu, tk ? d[2] : d[3], 1);
  return tk ? make_float4(r0, d[1], r1, d[3]) : make_float4(d[0], r0, d[2], r1);
}
#define OG_NG 8
#define HOIST 1
#define PUT_N 2
#define H_STAG 2
#define NOZERO 1
#define PVPIN 0
#define QKPIN 0
#define ALIGN 1
#define AL_P 60
#define AL_SLEEP 1200
#define AL_MAX 800
#define AL_ADD 0
#define X_PF 0
#define POLL_NS 200
#define KV3D 1
#define W3D 1
#define OG_PRE 10
#define OG_JOBS 7
#define OG_GRP 7
#define LD_FIRST 1
#define LD_STAG (OG_GRP / 2)
constexpr int OG_ST = 5, OG_NKB = T_DQKV / 64 - OG_PRE, OG_MOE = T_F / 32;
__device__ __forceinline__ int pre_loc(int job) {
  const int step = ((job >> 4) << 2) + (job & 3);
  return (step < OG_JOBS ? 2 * step : step < 2 * OG_JOBS ? 2 * (step - OG_JOBS) + 1 : step) * 4 + ((job >> 2) & 3);
}
__device__ __forceinline__ int pre_kb(int i) { return (i >> 1) * 4 + (i & 1); }
__device__ __forceinline__ int own_kb(int i) { return i < (OG_PRE & ~1) ? pre_kb(i) + 2 : i + OG_PRE; }
constexpr int OG_POS = 8;
constexpr uint32_t OG_STAGE = 32768;
constexpr uint32_t OG_SCOL = AT_SBAR + 512;
constexpr uint32_t OG_SMISC = AT_SBAR + 2048;
constexpr int OG_XPOS = OG_POS + OG_NKB;
constexpr uint32_t OG_SWD = AT_SQ, OG_PSLOT = AT_SQ;
constexpr uint32_t OG_XSLOT = (OG_XPOS % OG_ST) * OG_STAGE;
constexpr uint32_t OG_OSLOT = ((OG_XPOS + 1) % OG_ST) * OG_STAGE;
constexpr uint32_t OG_SH2 = ((OG_XPOS + 2) % OG_ST) * OG_STAGE;
constexpr uint32_t OG_SRED = ((OG_XPOS + 3) % OG_ST) * OG_STAGE;
constexpr uint32_t OG_SSTAT = OG_SRED + 16384;
constexpr uint32_t OG_SGU = OG_SRED + 8192;
constexpr uint32_t OG_SFIN = OG_SGU + 256;
#define OGM 2
#define OG_MT(b) (((b) >> OGM) & 15)
#define OG_NT(b) (((b) & ((1 << OGM) - 1)) + (((b) >> (4 + OGM)) << OGM))
#define TAIL_SETUP \
  const uint32_t bar_full = sbase + AT_SBAR, bar_empty = bar_full + 40; \
  const uint32_t bar_wd = bar_full + 168, bar_col = bar_full + 176, bar_out = bar_full + 184, bar_end = bar_full + 192; \
  const uint32_t bar_key = bar_full + 200, bar_h2 = bar_full + 208, bar_sel = bar_full + 216; \
  const int mt = OG_MT(blockIdx.x), nt = OG_NT(blockIdx.x); \
  const int m0 = mt * 128, n0 = nt * 128; \
  const bool has_moe = (int)blockIdx.x < OG_MOE; \
  (void)bar_empty; (void)bar_wd; (void)bar_col; (void)bar_out; (void)bar_end; (void)bar_key; (void)bar_h2; (void)bar_sel; (void)m0; (void)n0; (void)has_moe;

__device__ __forceinline__ void tail_producer(uint32_t sbase, uint32_t ph, uint64_t pol, const CUtensorMap* tmA, const CUtensorMap* tmB, const CUtensorMap* tmX) {
  TAIL_SETUP
  uint32_t stage = OG_POS % OG_ST;
  int kb = 0;
  #pragma unroll 1
  for (int seg = 0; seg < 2; seg++) {
    mbar_wait(bar_full + 264, seg);
    fence_proxy_async_global();
    const int end = seg == 0 ? 32 - OG_PRE : OG_NKB;
    #pragma unroll 1
    for (; kb < end; kb++) {
      const uint32_t fb = bar_full + 8 * stage, sa = sbase + stage * OG_STAGE;
      const int k0 = own_kb(kb) * 64;
      mbar_wait(bar_empty + 8 * stage, ph);
      mbar_expect_tx(fb, OG_STAGE);
      tma_load_3d_hint(sa + 16384, tmB, k0, 2 * nt, fb, pol);
      tma_load_2d_hint(sa, tmA, k0, m0, fb, pol);
      if (++stage == OG_ST) { stage = 0; ph ^= 1; }
    }
  }
  mbar_wait(bar_empty + 8 * (OG_XPOS % OG_ST), ph);
  mbar_expect_tx(bar_full + 8 * (OG_XPOS % OG_ST), OG_STAGE);
  tma_load_3d_hint(sbase + OG_XSLOT, tmX, m0, 2 * nt, bar_full + 8 * (OG_XPOS % OG_ST), pol);
}

__device__ __forceinline__ uint32_t bfma2(uint32_t a, uint32_t b, uint32_t c) { uint32_t r; asm("fma.rn.bf16x2 %0, %1, %2, %3;" : "=r"(r) : "r"(a), "r"(b), "r"(c)); return r; }
__device__ __forceinline__ uint32_t out2(uint32_t x1, uint32_t mb2, uint32_t ih, uint32_t il, uint32_t c1, uint32_t sb, uint32_t gb) {
  const uint32_t d = bsub2(x1, mb2);
  const uint32_t h2 = badd2(bmul2(bfma2(d, ih, bmul2(d, il)), c1), sb);
  return badd2(x1, bmul2(gb, bfma2(h2, 0u, h2)));
}
#define OGTIME gtime()
#define PRE_N 1
#define PRE_PACE 150
#define WD_PACE 300
__device__ __forceinline__ void tail_exchange(uint32_t sbase, const CUtensorMap* tmOut, const bf16* __restrict__ w_down, const bf16* __restrict__ w_r, bf16* __restrict__ out) {
    TAIL_SETUP
    const int lane = threadIdx.x & 31, wi = __shfl_sync(0xffffffffu, threadIdx.x >> 5, 0);
    if (wi == 3) {
      mbar_wait(bar_full + 264, 0);
      if (blockIdx.x < AT_NFULL) {
        uint32_t a, b;
        asm volatile("ld.relaxed.gpu.global.u32 %0, [%1];" : "=r"(a) : "l"(g_smid + 32 + blockIdx.x - lane) : "memory");
        b = __shfl_down_sync(0xffffffffu, a, 1);
        unsigned int* tm = g_tmax + blockIdx.x - min((int)blockIdx.x, __ffs(__ballot_sync(0xffffffffu, b >= a)) - 1);
        mbar_wait(bar_full + 312, 0);
        if (lane == 0) {
          asm volatile("mov.u32 %0, %%globaltimer_lo;" : "=r"(a));
          asm volatile("red.relaxed.gpu.global.max.u32 [%0], %1;" :: "l"(tm), "r"(a) : "memory");
          __nanosleep(AL_SLEEP);
          asm volatile("ld.relaxed.gpu.global.u32 %0, [%1];" : "=r"(b) : "l"(tm) : "memory");
          b -= a;
          sts_u32(sbase + OG_SMISC + 32, (b < AL_MAX ? b * 13 / 8 : 0u) + AL_ADD);
          mbar_arrive(bar_full + 320);
        }
        named_bar_sync(15, 32);
      }
      mbar_wait(bar_full + 264, 1);
      float a = g_scal[lane], b = g_scal[32 + lane];
      #pragma unroll
      for (int i = 0; i < 3; i++) {
        const uint4 v = *reinterpret_cast<const uint4*>(g_col + nt * 1536 + i * 512 + lane * 16);
        sts_u32x4(sbase + OG_SCOL + i * 512 + lane * 16, v.x, v.y, v.z, v.w);
      }
      #pragma unroll
      for (int o = 16; o > 0; o >>= 1) { a += __shfl_xor_sync(0xffffffffu, a, o); b += __shfl_xor_sync(0xffffffffu, b, o); }
      if (lane == 0) { sts_f32x2(sbase + OG_SMISC, a, b); mbar_arrive(bar_col); }
    } else if (wi == 2) {
      if (elect_one()) {
        const uint32_t b_free = bar_full + (blockIdx.x < AT_NFULL ? 80 : 160);
        mbar_wait(b_free, 0); mbar_wait(b_free, 1);
        #pragma unroll 1
        for (unsigned int i = 0; i < (1u << 20) && ld_acquire(&g_hcnt[32 * (1 + mt) + 4 + (nt >> 1)]) == 0u; i++) __nanosleep(POLL_NS);
        TL_MARK2(23, true);
        fence_proxy_async_global();
        TL_MARK2(4, true);
        mbar_expect_tx(bar_full + 272, 32768);
        #pragma unroll 1
        for (int i = 0; i < PRE_N; i++) {
          bulk_load_hint(sbase + OG_PSLOT + i * (32768 / PRE_N), g_pre + pre_loc(mt * 4 + (nt >> 1)) * 4096 + (nt & 1) * 2048 + i * (2048 / PRE_N), 32768 / PRE_N,
                         bar_full + 272, policy_evict_first());
          if (PRE_N > 1) __nanosleep(PRE_PACE);
        }
      }
      named_bar_sync(14, 32);
      if (has_moe) {
        mbar_wait(bar_full + 96, 1); mbar_wait(bar_full + 304, 0);
        const uint64_t pol = policy_evict_first();
        #pragma unroll 1
        for (int r = 0; r < 32; r++) {
          __nanosleep(WD_PACE);
          #pragma unroll
          for (int j = 0; j < 4; j++)
            asm volatile("cp.async.cg.shared.global.L2::cache_hint [%0], [%1], 16, %2;" :: "r"(sbase + OG_SWD + (4 * j + (lane >> 3)) * 4096 + r * 128 + (((lane ^ r) & 7) << 4)),
                         "l"((const uint8_t*)w_down + (size_t)blockIdx.x * 65536 + r * 2048 + j * 512 + lane * 16), "l"(pol) : "memory");
        }
        asm volatile("cp.async.wait_all;" ::: "memory");
        __syncwarp();
        if (lane == 0) mbar_arrive(bar_wd);
      }
    }
    const uint4 wrv = ldg_nc_v4(w_r + threadIdx.x * 8);
    mbar_wait(bar_end, 0);
    TL_MARK2(22, lane == 0);
    if (wi == 0) {
      uint32_t k1 = 0u, k2 = 0u;
      #pragma unroll 1
      for (unsigned int spin = 0; spin < (1u << 22) && __any_sync(0xffffffffu, k1 == 0u); spin++) asm volatile("ld.relaxed.gpu.global.u32 %0, [%1];" : "=r"(k1) : "l"(g_key + lane) : "memory");
      TL_MARK2(28, lane == 0);
      warp_top2(k1, k2);
      if (lane == 0) {
        const uint32_t r1 = 0xffffu - (k1 & 0xffffu), r2 = 0xffffu - (k2 & 0xffffu);
        sts_u32x4(sbase + OG_SMISC + 64, r1, r2, (r1 >> 7) * 2, (r2 >> 7) * 2 + ((r1 >> 7) == (r2 >> 7)));
        mbar_arrive(bar_sel);
      }
    } else if (wi < 3) {
          mbar_wait(bar_key, 0);
          const uint4 kk = lds_u32x4(sbase + OG_SSTAT + 1024 + lane * 16);
          uint32_t k1 = max(kk.x, kk.y), k2 = min(kk.x, kk.y);
          k2 = max(max(k2, min(kk.z, kk.w)), min(k1, max(kk.z, kk.w))); k1 = max(k1, max(kk.z, kk.w));
          warp_top2(k1, k2);
          if (wi == 1) {
            if (lane == 0 && nt == (mt & 7)) st_relaxed2(g_key + mt * 2, k1, k2);
            TL_MARK2(27, lane == 0);
          } else {
            const uint32_t r = (~((lane & 16) ? k2 : k1)) & 127u, ch = lane & 15;
            const uint2 st = lds_u32x2(sbase + OG_SSTAT + r * 8);
            const uint4 xc = lds_u32x4(sbase + OG_XSLOT + (ch >> 3) * 16384 + r * 128 + (((ch ^ r) & 7) << 4));
            const uint4 c1 = lds_u32x4(sbase + OG_SCOL + 768 + ch * 16), sh = lds_u32x4(sbase + OG_SCOL + 1024 + ch * 16);
            const float inr = __uint_as_float(st.y);
            float* dst = reinterpret_cast<float*>(g_cand + (mt * 2 + (lane >> 4)) * 256 + nt * 16 + ch);
            st_tagged4(dst + 512, __uint_as_float(ln_mod2(xc.x, st.x, inr, c1.x, sh.x)), __uint_as_float(ln_mod2(xc.y, st.x, inr, c1.y, sh.y)),
                       __uint_as_float(ln_mod2(xc.z, st.x, inr, c1.z, sh.z)), __uint_as_float(ln_mod2(xc.w, st.x, inr, c1.w, sh.w)));
            st_tagged4(dst, __uint_as_float(xc.x), __uint_as_float(xc.y), __uint_as_float(xc.z), __uint_as_float(xc.w));
          }
    }
    mbar_wait(bar_sel, 0);
    const uint4 sel = lds_u32x4(sbase + OG_SMISC + 64);
    const int sel0 = (int)sel.x, sel1 = (int)sel.y;
    {
      const float* src0 = reinterpret_cast<const float*>(g_cand + sel.z * 256 + 128 + threadIdx.x);
      const float* src1 = reinterpret_cast<const float*>(g_cand + sel.w * 256 + 128 + threadIdx.x);
      float4 h0, h1;
      #pragma unroll 1
      for (unsigned int spin = 0; spin < (1u << 20); spin++) { h0 = ld_tagged4(src0); h1 = ld_tagged4(src1); if (__all_sync(0xffffffffu, tagged4(h0) & tagged4(h1))) break; }
      sts_f32x4(sbase + OG_SH2 + threadIdx.x * 16, h0.x, h0.y, h0.z, h0.w);
      sts_f32x4(sbase + OG_SH2 + 2048 + threadIdx.x * 16, h1.x, h1.y, h1.z, h1.w);
      __syncwarp();
      if (lane == 0) mbar_arrive(bar_h2);
      TL_MARK2(12, lane == 0);
      if (blockIdx.x >> 6) h0 = h1;
      float v[8], wr[8];
      unpack8(make_uint4(__float_as_uint(h0.x), __float_as_uint(h0.y), __float_as_uint(h0.z), __float_as_uint(h0.w)), v); unpack8(wrv, wr);
      float r = 0.f;
      #pragma unroll
      for (int i = 0; i < 8; i++) r = fmaf(v[i], wr[i], r);
      #pragma unroll
      for (int o = 16; o > 0; o >>= 1) r += __shfl_xor_sync(0xffffffffu, r, o);
      if (lane == 0) sts_f32(sbase + OG_SMISC + 192 + wi * 4, r);
    }
    mbar_wait(bar_out, 0);
    if ((sel0 >> 7) == mt || (sel1 >> 7) == mt) {
      #pragma unroll 2
      for (int i = 0; i < 16; i++) {
        const int r = i * 8 + (threadIdx.x >> 4), ch = threadIdx.x & 15;
        if (m0 + r != sel0 && m0 + r != sel1)
          *reinterpret_cast<uint4*>(out + (size_t)(m0 + r) * T_D + n0 + ch * 8) =
              lds_u32x4(sbase + OG_OSLOT + (ch >> 3) * 16384 + r * 128 + (((ch & 7) ^ (r & 7)) << 4));
      }
    } else if (threadIdx.x == 0) {
      tma_store_2d(tmOut, sbase + OG_OSLOT, n0, m0);
      tma_store_2d(tmOut, sbase + OG_OSLOT + 16384, n0 + 64, m0);
      bulk_commit();
    }
    if (blockIdx.x == 0 && threadIdx.x < 68) *reinterpret_cast<uint4*>(g_hcnt + 32 * (threadIdx.x >> 2) + 4 * (threadIdx.x & 3)) = make_uint4(0u, 0u, 0u, 0u);
    if (threadIdx.x < 64) g_modpart[blockIdx.x * 64 + threadIdx.x] = 0.f;
    if (ALIGN && threadIdx.x == 64) g_tmax[blockIdx.x] = 0u;
    {
      const int tk = blockIdx.x >> 6, c0 = (blockIdx.x & 63) * 16;
      const uint32_t gb2 = *reinterpret_cast<const uint32_t*>(g_col + (c0 >> 7) * 1536 + 512 + 768 + ((c0 & 127) + (threadIdx.x & 14)) * 2);
      const uint32_t* xp = reinterpret_cast<const uint32_t*>(g_cand + (tk ? sel.w : sel.z) * 256) + ((c0 + (threadIdx.x & 14)) >> 1);
      uint32_t x2 = 0u;
      #pragma unroll 1
      for (unsigned int spin = 0; spin < (1u << 20) && __any_sync(0xffffffffu, x2 == 0u); spin++) asm volatile("ld.relaxed.gpu.global.u32 %0, [%1];" : "=r"(x2) : "l"(xp) : "memory");
      const float* src = g_ypart + (size_t)((threadIdx.x >> 2) * 2 + tk) * T_D + c0 + (threadIdx.x & 3) * 4;
      const bool four = threadIdx.x < (OG_MOE - 96) * 4;
      if (threadIdx.x == 0) hint_wait(CNT_Y, (uint32_t)OG_MOE);
      named_bar_sync(10, 128);
      float4 p0, p1, p2, p3;
      #pragma unroll 1
      for (unsigned int spin = 0; spin < (1u << 20); spin++) {
        p0 = ld_tagged4(src); p1 = ld_tagged4(src + 64 * T_D); p2 = ld_tagged4(src + 128 * T_D); p3 = ld_tagged4(four ? src + 192 * T_D : src);
        if (__all_sync(0xffffffffu, tagged4(p0) & tagged4(p1) & tagged4(p2) & tagged4(p3))) break;
      }
      if (four) { p2.x += p3.x; p2.y += p3.y; p2.z += p3.z; p2.w += p3.w; }
      p0.x = (p0.x + p1.x) + p2.x; p0.y = (p0.y + p1.y) + p2.y; p0.z = (p0.z + p1.z) + p2.z; p0.w = (p0.w + p1.w) + p2.w;
      #pragma unroll
      for (int o = 4; o <= 16; o <<= 1) {
        p0.x += __shfl_xor_sync(0xffffffffu, p0.x, o); p0.y += __shfl_xor_sync(0xffffffffu, p0.y, o);
        p0.z += __shfl_xor_sync(0xffffffffu, p0.z, o); p0.w += __shfl_xor_sync(0xffffffffu, p0.w, o);
      }
      if (lane < 4) sts_f32x4(sbase + OG_SFIN + (threadIdx.x >> 5) * 64 + lane * 16, p0.x, p0.y, p0.z, p0.w);
      named_bar_sync(10, 128);
      TL_MARK2(21, threadIdx.x == 0);
      if (threadIdx.x < 16) {
        const uint32_t ya = sbase + OG_SFIN + threadIdx.x * 4, rp = sbase + OG_SMISC + 192;
        float y = (lds_f32(ya) + lds_f32(ya + 64)) + (lds_f32(ya + 128) + lds_f32(ya + 192));
        const float r = rbf((lds_f32(rp) + lds_f32(rp + 4)) + (lds_f32(rp + 8) + lds_f32(rp + 12)));
        const float rs = rbf(sigmoid_f(r));
        const uint32_t h2p = lds_u32(sbase + OG_SH2 + tk * 2048 + (c0 + (threadIdx.x & 14)) * 2);
        const float fh = (lane & 1) ? bfhi(h2p) : bflo(h2p);
        y = rbf(y);
        y = rbf(y * rs);
        const float upd = rbf(rbf(fh * 0.0f) + y);
        out[(size_t)(tk ? sel1 : sel0) * T_D + c0 + threadIdx.x] =
            __float2bfloat16_rn(((lane & 1) ? bfhi(x2) : bflo(x2)) + rbf(((lane & 1) ? bfhi(gb2) : bflo(gb2)) * rbf(fh + upd)));
      }
      if (threadIdx.x == 0) bulk_wait_read<0>();
    }
    TL_END(4, threadIdx.x == 0);
}

__device__ __forceinline__ void load_pre(uint4* pre, uint32_t sbase, uint32_t buf, int t2) {
  mbar_wait(sbase + AT_SBAR + 272, 0);
  #pragma unroll
  for (int i = 0; i < 8; i++) pre[i] = lds_u32x4(sbase + buf + i * 4096 + t2 * 16);
}
__device__ __forceinline__ void tail_consumer(uint32_t sbase, const uint4 (&pre)[8], int cwg, const bf16* __restrict__ w_gate, const bf16* __restrict__ w_up) {
    TAIL_SETUP
    const int tid = threadIdx.x & 127, t2 = threadIdx.x - 128;
    const int warp = tid >> 5, lane = tid & 31, w8 = t2 >> 5;
    const uint32_t dbase = (sbase & 0x3FFFFu) >> 4;
    const uint32_t a_base = dbase + ((cwg * 8192) >> 4) + (1u << 16);
    const uint32_t b_base = dbase + (16384 >> 4) + (512u << 16);
    TL_MARK2(25, threadIdx.x == 128);
    const uint64_t pol = policy_evict_first();
    const bf16* pw = ((lane & 16) ? w_up : w_gate) + (size_t)(w8 * 128 + (lane & 3) * 4) * T_F + (has_moe ? blockIdx.x : 0) * 32 + ((lane >> 2) & 3) * 8;
    uint4 wv[32];
    float acc[64];
    #pragma unroll
    for (int i = 0; i < 8; i++) {
      acc[8 * i] = bflo(pre[i].x); acc[8 * i + 1] = bfhi(pre[i].x); acc[8 * i + 2] = bflo(pre[i].y); acc[8 * i + 3] = bfhi(pre[i].y);
      acc[8 * i + 4] = bflo(pre[i].z); acc[8 * i + 5] = bfhi(pre[i].z); acc[8 * i + 6] = bflo(pre[i].w); acc[8 * i + 7] = bfhi(pre[i].w);
    }
    if (blockIdx.x < AT_NFULL) {
      const uint32_t c0 = clock_lo();
      mbar_wait(bar_full + 320, 0);
      const uint32_t d = lds_u32(sbase + OG_SMISC + 32);
      while (clock_lo() - c0 < d) {}
    }
    {
      uint32_t stage = OG_POS % OG_ST, phase = (OG_POS / OG_ST) & 1, prev = 12;
      int kb = 0;
      #pragma unroll
      for (int g = 0; g <= OG_NG; g++) {
        const int end = g == OG_NG ? OG_NKB : LD_FIRST + g * OG_GRP + LD_STAG * cwg;
        #pragma unroll 1
        do {
          mbar_wait(bar_full + 8 * stage, phase);
          const uint32_t a_lo = a_base + stage * (OG_STAGE >> 4), b_lo = b_base + stage * (OG_STAGE >> 4);
          wgmma_fence();
          wgmma_m64n128k16_ss_tb<0, 0>(acc, a_lo, b_lo, 1);
          wgmma_m64n128k16_ss_tb<2, 128>(acc, a_lo, b_lo, 1);
          wgmma_m64n128k16_ss_tb<4, 256>(acc, a_lo, b_lo, 1);
          wgmma_m64n128k16_ss_tb<6, 384>(acc, a_lo, b_lo, 1);
          wgmma_commit();
          wgmma_wait<1>();
          if (tid == 0) mbar_arrive(bar_empty + 8 * prev);
          prev = stage;
          if (++stage == OG_ST) { stage = 0; phase ^= 1; }
        } while (++kb < end);
        #pragma unroll
        for (int j = 4 * g; j < 4 * g + 4 && j < 32; j++) wv[j] = ldg_stream_v4(pw + (size_t)(16 * (j >> 2) + (j & 3)) * T_F, pol);
      }
    }
    mbar_wait(bar_col, 0);
    mbar_wait(bar_full + 8 * (OG_XPOS % OG_ST), (OG_XPOS / OG_ST) & 1);
    if (__builtin_expect(!has_moe, 0)) {
      load_pre(wv, sbase, AT_SQ, t2);
    }
    wgmma_wait<0>();
    fence_regs(acc);
    if (__builtin_expect(!has_moe, 0)) {
      #pragma unroll
      for (int i = 0; i < 8; i++) {
        acc[8 * i] += bflo(wv[i].x); acc[8 * i + 1] += bfhi(wv[i].x); acc[8 * i + 2] += bflo(wv[i].y); acc[8 * i + 3] += bfhi(wv[i].y);
        acc[8 * i + 4] += bflo(wv[i].z); acc[8 * i + 5] += bfhi(wv[i].z); acc[8 * i + 6] += bflo(wv[i].w); acc[8 * i + 7] += bfhi(wv[i].w);
      }
    }
    if (tid == 0) mbar_arrive(bar_end);
    TL_MARK2(9, lane == 0);
    const int q2 = 2 * (lane & 3);
    const uint32_t frag = (64 * cwg + 16 * warp + (lane & 7) + 8 * ((lane >> 3) & 1)) * 128;
    const int fsw = lane & 7, fhi = lane >> 4;
    {
      float dl[4] = {0.f, 0.f, 0.f, 0.f}, da[4] = {0.f, 0.f, 0.f, 0.f}, db[4] = {0.f, 0.f, 0.f, 0.f};
      const uint32_t tb = sbase + OG_SCOL + (lane & 8) * 32 + (lane & 3) * 8, g = lane >> 2;
      const uint32_t msk = (g == 1 || g == 2) ? 0xffffffffu : 0u, one = g == 0 ? 0x3F803F80u : 0u;
      #pragma unroll
      for (int J = 0; J < 16; J += 2) {
        const uint32_t ad = sbase + OG_XSLOT + (J >> 3) * 16384 + frag + ((((J & 7) + fhi) ^ fsw) << 4);
        uint32_t xr[4];
        ldmatrix_x4(ad, xr[0], xr[1], xr[2], xr[3]);
        const uint2 cw = lds_u32x2(tb + J * 16);
        #pragma unroll
        for (int h = 0; h < 2; h++) {
          const uint32_t ga = lds_u32(sbase + OG_SCOL + 512 + (8 * (J + h) + q2) * 2);
          xr[2 * h] = badd2(xr[2 * h], bmul2(ga, pack_bf16(acc[4 * (J + h)], acc[4 * (J + h) + 1])));
          xr[2 * h + 1] = badd2(xr[2 * h + 1], bmul2(ga, pack_bf16(acc[4 * (J + h) + 2], acc[4 * (J + h) + 3])));
        }
        stmatrix_x4(ad, xr[0], xr[1], xr[2], xr[3]);
        mma_bf16(dl, xr[0], xr[1], xr[2], xr[3], (cw.x & msk) | one, (cw.y & msk) | one);
        mma_bf16(da, xr[0], xr[1], xr[2], xr[3], xr[0], xr[2]);
        mma_bf16(db, xr[0], xr[1], xr[2], xr[3], xr[1], xr[3]);
      }
      {
        const int dsrc = (lane & ~3) + (g >> 1);
        const float qa = __shfl_sync(0xffffffffu, (g & 1) ? da[1] : da[0], dsrc), qb = __shfl_sync(0xffffffffu, (g & 1) ? db[3] : db[2], dsrc);
        const float e0 = __shfl_xor_sync(0xffffffffu, (lane & 1) ? dl[0] : dl[2], 1), e1 = __shfl_xor_sync(0xffffffffu, dl[3], 1);
        if ((lane & 3) < 2) {
          const bool hi = lane & 1;
          st_tagged4(reinterpret_cast<float*>(g_part1 + ((mt * 8 + w8) * 8 + nt) * 16 + g + (hi ? 8 : 0)),
                     hi ? e0 : dl[0], hi ? qb : qa, hi ? e1 + dl[2] : dl[1] + e0, 1.0f);
        }
      }
    }
    TL_MARK2(10, lane == 0);
    uint4 wd[16];
    if (has_moe) mbar_wait(bar_wd, 0);
    #pragma unroll
    for (int i = 0; i < 16; i++) wd[i] = lds_u32x4(sbase + OG_SWD + w8 * 8192 + (i >> 3) * 4096 + (i & 6) * 512 + (i & 1) * 128 + (lane & 3) * 256 + (((lane >> 2) ^ (2 * (lane & 3) + (i & 1))) << 4));
    {
      const float* src = reinterpret_cast<const float*>(g_part1 + ((mt * 8 + w8) * 8 + (lane & 1) * 4) * 16 + (lane >> 1));
      float4 v, v1, v2, v3;
      #pragma unroll 1
      for (unsigned int spin = 0; spin < (1u << 22); spin++) {
        v = ld_tagged4(src); v1 = ld_tagged4(src + 64); v2 = ld_tagged4(src + 128); v3 = ld_tagged4(src + 192);
        if (__all_sync(0xffffffffu, tagged4(v) & tagged4(v1) & tagged4(v2) & tagged4(v3))) break;
        __nanosleep(100);
      }
      __syncwarp();
      TL_MARK2(26, lane == 0);
      v.x = (v.x + v1.x) + (v2.x + v3.x); v.y = (v.y + v1.y) + (v2.y + v3.y); v.z = (v.z + v1.z) + (v2.z + v3.z);
      v.x += __shfl_xor_sync(0xffffffffu, v.x, 1); v.y += __shfl_xor_sync(0xffffffffu, v.y, 1); v.z += __shfl_xor_sync(0xffffffffu, v.z, 1);
      const float mean = v.x * (1.0f / T_D);
      const float var = fmaxf(fmaf(-mean, mean, v.y * (1.0f / T_D)), 0.f);
      const uint32_t mb2 = pack_bf16(mean, mean);
      const float inv = rcp_approx(rbf(sqrt_approx(rbf(rbf(var) + 1e-05f))));
      {
        const float2 sc = lds_f32x2(sbase + OG_SMISC);
        const uint32_t key = rank_key(rbf(fmaf(fmaf(-bflo(mb2), sc.x, v.z), inv, sc.y)), m0 + 16 * w8 + (lane >> 1));
        mbar_wait(bar_end, 0);
        if (lane & 1) sts_u32(sbase + OG_SSTAT + 1024 + (16 * w8 + (lane >> 1)) * 4, key);
        else sts_u32x2(sbase + OG_SSTAT + (16 * w8 + (lane >> 1)) * 8, mb2, __float_as_uint(inv));
        __syncwarp();
        if (lane == 0) mbar_arrive(bar_key);
      }
      const uint32_t ih = pack_bf16(inv, inv), il = pack_bf16(inv - bflo(ih), inv - bflo(ih));
      const uint32_t mba = __shfl_sync(0xffffffffu, mb2, 2 * (lane >> 2)), mbb = __shfl_sync(0xffffffffu, mb2, 2 * (lane >> 2) + 16);
      const uint32_t iha = __shfl_sync(0xffffffffu, ih, 2 * (lane >> 2)), ihb = __shfl_sync(0xffffffffu, ih, 2 * (lane >> 2) + 16);
      const uint32_t ila = __shfl_sync(0xffffffffu, il, 2 * (lane >> 2)), ilb = __shfl_sync(0xffffffffu, il, 2 * (lane >> 2) + 16);
      #pragma unroll 2
      for (int J = 0; J < 16; J += 2) {
        const uint32_t off = (J >> 3) * 16384 + frag + ((((J & 7) + fhi) ^ fsw) << 4);
        uint32_t xr[4];
        ldmatrix_x4(sbase + OG_XSLOT + off, xr[0], xr[1], xr[2], xr[3]);
        #pragma unroll
        for (int h = 0; h < 2; h++) {
          const uint32_t ca = sbase + OG_SCOL + 512 + (8 * (J + h) + q2) * 2;
          const uint32_t c1 = lds_u32(ca + 256), sh = lds_u32(ca + 512), gb = lds_u32(ca + 768);
          xr[2 * h] = out2(xr[2 * h], mba, iha, ila, c1, sh, gb);
          xr[2 * h + 1] = out2(xr[2 * h + 1], mbb, ihb, ilb, c1, sh, gb);
        }
        stmatrix_x4(sbase + OG_OSLOT + off, xr[0], xr[1], xr[2], xr[3]);
      }
      fence_proxy_async();
      __syncwarp();
      if (lane == 0) mbar_arrive(bar_out);
      TL_MARK2(24, lane == 0);
    }
    if (has_moe) mbar_wait(bar_h2, 0);
    TL_MARK2(13, lane == 0);
    if (has_moe) {
      const GemvSel sel = gemv_sel(lane);
      {
        float d[4][4];
        #pragma unroll
        for (int c = 0; c < 4; c++) { d[c][0] = 0.f; d[c][1] = 0.f; d[c][2] = 0.f; d[c][3] = 0.f; }
        #pragma unroll
        for (int st = 0; st < 8; st++) {
          const uint2 hb = lds_u32x2(sbase + OG_SH2 + ((lane >> 2) & 1) * 2048 + (w8 * 128 + st * 16 + (lane & 3) * 4) * 2);
          #pragma unroll
          for (int j = 0; j < 4; j++) mma_bf16(d[j], wv[4 * st + j].x, wv[4 * st + j].y, wv[4 * st + j].z, wv[4 * st + j].w, GEMV_B0(j, hb, sel), GEMV_B1(j, hb, sel));
        }
        #pragma unroll
        for (int e = 0; e < 4; e++) d[0][e] = (d[0][e] + d[1][e]) + (d[2][e] + d[3][e]);
        const float4 r = gemv_out(d[0], lane);
        sts_f32x4(sbase + OG_SRED + w8 * 512 + (((lane >> 4) * 2 + (lane & 1)) * 32 + ((lane >> 2) & 3) * 8 + (lane & 2) * 2) * 4, r.x, r.y, r.z, r.w);
      }
      named_bar_sync(9, 256);
      if (t2 < 64) {
        float gp[8], up[8];
        #pragma unroll
        for (int w = 0; w < 8; w++) { gp[w] = lds_f32(sbase + OG_SRED + w * 512 + t2 * 4); up[w] = lds_f32(sbase + OG_SRED + w * 512 + 256 + t2 * 4); }
        const float gs = ((gp[0] + gp[1]) + (gp[2] + gp[3])) + ((gp[4] + gp[5]) + (gp[6] + gp[7]));
        const float us = ((up[0] + up[1]) + (up[2] + up[3])) + ((up[4] + up[5]) + (up[6] + up[7]));
        asm volatile("st.shared.u16 [%0], %1;" :: "r"(sbase + OG_SGU + ((t2 & ~15) + ((t2 >> 1) & 3) * 4 + ((t2 >> 3) & 1) * 2 + (t2 & 1)) * 2), "h"((uint16_t)pack_bf16(silu_bf(rbf(gs)) * rbf(us), 0.f)) : "memory");
      }
      named_bar_sync(9, 256);
      TL_MARK2(20, threadIdx.x == 128);
      float d[4][4];
      #pragma unroll
      for (int c = 0; c < 4; c++) { d[c][0] = 0.f; d[c][1] = 0.f; d[c][2] = 0.f; d[c][3] = 0.f; }
      #pragma unroll
      for (int st = 0; st < 2; st++) {
        const uint2 g = lds_u32x2(sbase + OG_SGU + ((lane >> 2) & 1) * 64 + st * 32 + (lane & 3) * 8);
        #pragma unroll
        for (int j = 0; j < 4; j++) {
          const uint32_t b0 = GEMV_B0(j, g, sel), b1 = GEMV_B1(j, g, sel);
          mma_bf16(d[j & 1], wd[4 * st + j].x, wd[4 * st + j].y, wd[4 * st + j].z, wd[4 * st + j].w, b0, b1);
          mma_bf16(d[2 + (j & 1)], wd[8 + 4 * st + j].x, wd[8 + 4 * st + j].y, wd[8 + 4 * st + j].z, wd[8 + 4 * st + j].w, b0, b1);
        }
      }
      #pragma unroll
      for (int e = 0; e < 4; e++) { d[0][e] += d[1][e]; d[2][e] += d[3][e]; }
      const float4 y0 = gemv_out(d[0], lane), y1 = gemv_out(d[2], lane);
      float* yp = g_ypart + (size_t)(blockIdx.x * 2 + (lane & 1)) * T_D + w8 * 128 + (lane >> 2) * 8 + (lane & 2) * 2;
      st_tagged4(yp, y0.x, y0.y, y0.z, y0.w);
      st_tagged4(yp + 64, y1.x, y1.y, y1.z, y1.w);
      named_bar_sync(9, 256);
      if (t2 == 0) hint_arrive(CNT_Y);
    }
    TL_MARK2(14, threadIdx.x == 128);
    TL_CLK(4, 1, threadIdx.x == 128);
}

#define OG_JOBS2 (16 - OG_JOBS)
__device__ __forceinline__ int help_njobs() { return blockIdx.x < 128 ? OG_JOBS : OG_JOBS2; }
__device__ __forceinline__ int help_job(int i) {
  const int step = i + (blockIdx.x < 128 ? 0 : OG_JOBS);
  return (step & ~3) * 4 + (blockIdx.x & 3) * 4 + (step & 3);
}
__device__ __noinline__ void store_warp(uint32_t sbase, const CUtensorMap* tmO, int item0, int n_items) {
  if (elect_one()) {
    const uint32_t bars = sbase + AT_SBAR, b_q0 = bars + 80, b_ob = bars + 96, b_ordy = bars + 104, b_acq = bars + 264;
    const unsigned int* cnt = &g_hcnt[32 * (1 + OG_MT(blockIdx.x)) + 2];
    #pragma unroll 1
    for (int q = 0; q < 4 * n_items; q++) {
      const int item = item0 + (q >> 2) * 128, h = (q >> 1) & 1, w = q & 1;
      const bool last = (q >> 2) == n_items - 1;
      if (q == 4 * n_items - 4) { mbar_wait(bars + 288, 0); red_release_add(&g_hcnt[1], 1u); }
      mbar_wait(b_ordy + 8 * (q & 3), q >> 2);
      store_o(tmO, (h ? (last ? sbase + AT_SQ + 32768 : sbase + 2 * 32768) : sbase + AT_SQ) + w * 8192, (item >> 4) * 2 + h, (item & 15) * 128 + w * 64);
      if (w) {
        bulk_wait_read<0>();
        mbar_arrive(h ? b_ob : b_q0);
        bulk_wait<0>();
        fence_proxy_async_global();
        red_release_add(&g_hcnt[32 * (1 + (item & 15)) + 2 + (item >> 7)], h ? 1u : 256u);
        if (blockIdx.x < 128 && q == (n_items == 2 ? 5 : 3)) { spin_until(cnt, 0x808u); mbar_arrive(b_acq); }
      }
    }
    if (n_items == 1) {
      #pragma unroll 1
      for (int i = 0; i < help_njobs(); i++) {
        mbar_wait(b_acq + 16, i & 1);
        TL_MARK2(23, i == OG_JOBS - 1);
        red_release_add(&g_hcnt[32 * (1 + (help_job(i) >> 2)) + 4 + (help_job(i) & 3)], 1u);
        TL_MARK2(4, i == OG_JOBS - 1);
        if (i == PRE_X - 1) { spin_until(&g_hcnt[1], 132u); mbar_arrive(b_acq + 32); }
      }
    }
    if (blockIdx.x < 128) { spin_until(&g_hcnt[0], 128u); spin_until(cnt + 1, 0x808u); mbar_arrive(b_acq); }
  }
}

__global__ void __launch_bounds__(384, 1)
fused_kernel(const __grid_constant__ CUtensorMap tmH, const __grid_constant__ CUtensorMap tmW, const __grid_constant__ CUtensorMap tmK,
            const __grid_constant__ CUtensorMap tmV, const __grid_constant__ CUtensorMap tmO, const __grid_constant__ CUtensorMap tmOl, const __grid_constant__ CUtensorMap tmWo,
            const __grid_constant__ CUtensorMap tmX, const __grid_constant__ CUtensorMap tmOut, uint32_t zero,
            const uint8_t* __restrict__ pf_wo, const bf16* __restrict__ kc, const bf16* __restrict__ vc,
            const bf16* __restrict__ x, const bf16* __restrict__ cvec, const bf16* __restrict__ w_mod, const bf16* __restrict__ w_r,
            const bf16* __restrict__ w_gate, const bf16* __restrict__ w_up, const bf16* __restrict__ w_down, bf16* __restrict__ out)
{
  extern __shared__ __align__(1024) uint8_t smem_raw[];
  const uint32_t sbase = smem_u32(smem_raw);
  const uint32_t bars = sbase + AT_SBAR;
  const uint32_t b_full = bars, b_empty = bars + 40;
  const uint32_t b_q0 = bars + 80, b_q1 = bars + 88;
  const uint32_t b_ob = bars + 96;
  const uint32_t b_ordy = bars + 104;
  const uint32_t b_pin = bars + 136;
  const uint32_t b_head = bars + 144;
  const uint32_t b_go = bars + 152;
  const uint32_t b_x = bars + 160;
  const int wg = __shfl_sync(0xffffffffu, threadIdx.x >> 7, 0);
  const bool single = blockIdx.x >= AT_NFULL;
  const int item0 = __shfl_sync(0xffffffffu, blockIdx.x < 128 ? (int)blockIdx.x : (int)blockIdx.x + 124, 0), n_items = __shfl_sync(0xffffffffu, single ? 1 : 2, 0);
  TL_START(3);
  if (threadIdx.x == 0) {
    if (sbase & 1023u) __trap();
    for (int i = 0; i < 5; i++) { mbar_init(b_full + 8 * i, 1); mbar_init(b_empty + 8 * i, 2); }
    mbar_init(b_q0, 1); mbar_init(b_q1, 8); mbar_init(b_ob, 1);
    for (int i = 0; i < 4; i++) mbar_init(b_ordy + 8 * i, 4);
    mbar_init(b_pin, 1); mbar_init(b_head, blockIdx.x < 128 ? 8 : 1); mbar_init(b_go, 1); mbar_init(b_x, 1);
    mbar_init(bars + 168, 1); mbar_init(bars + 176, 1); mbar_init(bars + 184, 8); mbar_init(bars + 192, 2);
    mbar_init(bars + 200, 8); mbar_init(bars + 208, 4); mbar_init(bars + 216, 1); mbar_init(bars + 264, 1); mbar_init(bars + 272, 1); mbar_init(bars + 280, 8); mbar_init(bars + 288, 1); mbar_init(bars + 296, 1); mbar_init(bars + 304, 8); mbar_init(bars + 312, 1); mbar_init(bars + 320, 1);
    fence_mbar_init();
  }

  if (wg == 0) {
    reg_dealloc<AT_PREG>();
    if (threadIdx.x < 32) { __syncwarp(); named_bar_arrive(6, 384); }
    if (threadIdx.x >= 64) {
      named_bar_sync(6, 384);
      if (blockIdx.x < 128 && threadIdx.x >= 96) {
        named_bar_sync(8, 288);
        if (threadIdx.x == 96) red_release_add(&g_hcnt[32 * (1 + (blockIdx.x >> 3)) + 1], 1u);
      }
      if (blockIdx.x < 128) {
        mbar_wait(MOD_AT, 0);
        mod_rest(sbase + OG_SCOL, b_q1, threadIdx.x - 64, cvec, w_mod, w_r);
      }
    } else if (threadIdx.x >= 32) {
      named_bar_sync(6, 384);
      store_warp(sbase, &tmO, item0, n_items);
      __syncwarp();
    } else {
     if (elect_one()) {
      const uint64_t pol = policy_evict_first();
      prefetch_tmap(&tmW); prefetch_tmap(&tmH); prefetch_tmap(&tmWo); prefetch_tmap(&tmOl);
      uint32_t slot = 0, ph = 1;
      if (ALIGN) { uint32_t sm; asm volatile("mov.u32 %0, %%smid;" : "=r"(sm)); g_smid[32 + blockIdx.x] = sm; }
      #pragma unroll 1
      for (int it = 0; it < n_items; it++) {
        const int item = item0 + it * 128, hp = item >> 4, qt = item & 15;
        const bool first = it == 0;
        #pragma unroll 1
        for (int j = 0; j < T_D / 64; j++) {
          const uint32_t sl = ring_slot(qp_pos(j, it)), fb = b_full + 8 * sl;
          mbar_wait(b_empty + 8 * sl, ring_par(qp_pos(j, it)) ^ ((j >> 2) & 1) ^ 1);
          mbar_expect_tx(fb, 49152);
          tma_load_3d_hint(sbase + sl * 32768, &tmW, j * 64, hp * 4, fb, pol);
          if (first && j < PRE_B) {
            if (j == PRE_B - 1) {
              spin_until(&g_hcnt[32 * (1 + qt)], 8u);
              TL_MARK2(16, true);
              fence_proxy_async_global();
              TL_MARK2(17, true);
              #pragma unroll 1
              for (int i = 0; i < PRE_B; i++) tma_load_2d(sbase + AT_SQ + i * 16384, &tmH, i * 64, qt * 128, b_full + 8 * i);
              mbar_arrive(b_go);
            }
          } else {
            if (first && j == 3) mbar_wait(b_head, 0);
            if (first && j == 4 * H_SPLIT) { spin_until(&g_hcnt[32 * (1 + qt) + 1], 8u); fence_proxy_async_global(); }
            if (!first && (j == 0 || j == 2)) mbar_wait(j ? b_q1 : b_q0, 0);
            tma_load_2d_hint(sbase + AT_SQ + (j & 3) * 16384, &tmH, j * 64, qt * 128, fb, first ? pol_normal() : pol);
          }
        }
        #pragma unroll 1
        for (int j = 0; j < 4 * AT_NBLK; j++) {
          const bool isv = (j > 0 && !(j & 1)) || j == 4 * AT_NBLK - 1;
          const int row = hp * 2 * T_SEQ + (isv ? (j - 1) >> 1 : (j + 1) >> 1) * 128;
          const uint32_t fb = b_full + 8 * slot;
          mbar_wait(b_empty + 8 * slot, ph);
          if (!first && j == 3) mbar_wait(b_ob, 0);
          if (j == 4 && it == n_items - 1) mbar_arrive(bars + 288);
          if (ALIGN && j == AL_P && it == 1) mbar_arrive(bars + 312);
          mbar_expect_tx(fb, 32768);
          tma_load_3d_hint(sbase + slot * 32768, isv ? &tmV : &tmK, row, 0, fb, pol);
          if (it == 1 && isv && j >= 2 * WO_LATE && j < 2 * WO_LATE + 32 && blockIdx.x < OG_NKB)
            l2_prefetch_bulk(pf_wo + (size_t)own_kb(blockIdx.x) * 131072 + ((j >> 1) - WO_LATE) * 8192, 8192);
          if (++slot == 5) { slot = 0; ph ^= 1; }
        }
      }
      if (__builtin_expect(single, 0)) {
        #pragma unroll 1
        for (int i = 0; i < 4; i++) spin_until(&g_hcnt[32 * (1 + 4 * i + (blockIdx.x & 3)) + 2], 0x800u);
        fence_proxy_async_global();
        const int nj = help_njobs() * OG_PRE;
        int ji = 0, job = help_job(0), kk = 0;
        #pragma unroll 1
        for (int j = 0; j < nj; j++) {
          const uint32_t sl = ring_slot(qp_pos(j, 1)), fb = b_full + 8 * sl;
          mbar_wait(b_empty + 8 * sl, ring_par(qp_pos(j, 1)) ^ ((j >> 2) & 1) ^ 1);
          mbar_expect_tx(fb, 49152);
          tma_load_3d_hint(sbase + sl * 32768, &tmWo, pre_kb(kk) * 64, (job & 3) * 4, fb, HPOL_B);
          tma_load_3d_hint(sbase + sl * 32768 + 16384, &tmWo, pre_kb(kk) * 64, (job & 3) * 4 + 2, fb, HPOL_B);
          if (j == 0 || j == 2) mbar_wait(j ? b_ob : b_q0, 0);
          tma_load_2d_hint(sbase + AT_SQ + (j & 3) * 16384, HMAP_A, pre_kb(kk) * 64, (job >> 2) * 128, fb, HPOL_A);
          if (++kk == OG_PRE) { kk = 0; job = help_job(++ji); }
        }
      }
      if (blockIdx.x < 128) {
        if (single) mbar_wait(b_x, 1);
        tail_producer(sbase, 0, pol, &tmOl, &tmWo, &tmX);
      }
     }
    }
    named_bar_sync(12 + (threadIdx.x >> 5), 32);
    if (blockIdx.x < 128) tail_exchange(sbase, &tmOut, w_down, w_r, out);
  } else {
    if (blockIdx.x < 128) head_phase(sbase + AT_SQ + 49152, sbase + 4 * 32768, b_x, b_go, b_head, threadIdx.x - 128, zero, x, cvec, w_mod);
    else { named_bar_sync(6, 384); if (threadIdx.x == 128) mbar_arrive(b_head); }
    TL_MARK2(0, threadIdx.x == 128);
    reg_alloc<AT_CREG>();
    const int cwg = wg - 1;
    const int tid = threadIdx.x & 127;
    const int warp = tid >> 5, lane = tid & 31;
    const uint32_t dbase = (sbase & 0x3FFFFu) >> 4;
    const uint32_t k_base = dbase + (1u << 16);
    const uint32_t v_base = dbase + (1024u << 16);
    const uint32_t w_base = dbase + (512u << 16);
    const uint32_t q_lo = dbase + ((AT_SQ + cwg * 8192) >> 4) + (1u << 16);
    const uint32_t frag = cwg * 8192 + (16 * warp + (lane & 7) + 8 * ((lane >> 3) & 1)) * 128;
    if (cwg == 1) named_bar_arrive(1, 256);
    bool raw = false;
    uint4 pre[8];
    #pragma unroll 1
    for (int it = 0; it < n_items; it++) {
      const bool more = it + 1 < n_items;
      constexpr int nkb = T_D / 64;
      const int ta = __shfl_sync(0xffffffffu, 4 * it, 0);
      float acc[128];
      {
        FS(2 * it, 0);
        #pragma unroll
        for (int i = 0; i < 128; i++) asm volatile("" : "=f"(acc[i]));
        {
          const uint32_t slot = ring_slot(ta), b_lo = w_base + slot * 2048;
          mbar_wait(b_full + 8 * slot, ring_par(ta));
          wgmma_fence();
          wgmma_m64n256k16_ss_tb<0, 0>(acc, q_lo, b_lo, 0);
          wgmma_m64n256k16_ss_tb<2, 128>(acc, q_lo, b_lo, 1);
          wgmma_m64n256k16_ss_tb<4, 256>(acc, q_lo, b_lo, 1);
          wgmma_m64n256k16_ss_tb<6, 384>(acc, q_lo, b_lo, 1);
          wgmma_commit();
        }
        #pragma unroll 1
        for (int j = NOZERO; j < nkb; j++) {
          const uint32_t slot = ring_slot(qp_pos(j, ta >> 2));
          mbar_wait(b_full + 8 * slot, ring_par(qp_pos(j, ta >> 2)) ^ ((j >> 2) & 1));
          if (QP_STAG > 0 && cwg == 1 && j == nkb - QP_STAG) named_bar_sync(7, 256);
          const uint32_t a_lo = q_lo + (j & 3) * 1024, b_lo = w_base + slot * 2048;
          wgmma_fence();
          wgmma_m64n256k16_ss_tb<0, 0>(acc, a_lo, b_lo, 1);
          wgmma_m64n256k16_ss_tb<2, 128>(acc, a_lo, b_lo, 1);
          wgmma_m64n256k16_ss_tb<4, 256>(acc, a_lo, b_lo, 1);
          wgmma_m64n256k16_ss_tb<6, 384>(acc, a_lo, b_lo, 1);
          wgmma_commit();
          if (QP_STAG > 0 && cwg == 0 && j == nkb - 1) named_bar_arrive(7, 256);
          if (j > 0) {
            wgmma_wait<1>();
            if (tid == 0) mbar_arrive(b_empty + 8 * ring_slot(qp_pos(j - 1, ta >> 2)));
          }
        }
        wgmma_wait<0>();
        fence_regs(acc);
        FS(2 * it, 1);
        TL_MARK2(29, threadIdx.x == 256 && it == 0);
        if (tid == 0) mbar_arrive(b_empty + 24);
      }
      float o[64], s[64];
      uint32_t p[32], q[32];
      #pragma unroll
      for (int i = 0; i < 32; i++) q[i] = pack_bf16(acc[2 * i] * AT_C, acc[2 * i + 1] * AT_C);
      zero_regs(s);
      const uint32_t sq = sbase + AT_SQ + cwg * 8192;
      const bool last_wg1 = cwg == 1 && !more;
      float mc0, mc1, al0 = 1.0f, al1 = 1.0f, l0 = 0.f, l1 = 0.f, lp0 = 0.f, lp1 = 0.f;
      bool redo0 = false;
      FS(2 * it, 2);
      mbar_wait(b_full + 8 * ring_slot(ta), ring_par(ta));
      named_bar_sync(1 + cwg, 256);
      FS(2 * it, 3);
      issue_qk(s, q, k_base + ring_slot(ta) * 2048);
      named_bar_arrive(1 + (cwg ^ 1), 256);
      bool ready = mbar_test(b_full + 8 * ring_slot(ta + 1), ring_par(ta + 1)) & mbar_test(b_full + 8 * ring_slot(ta + 2), ring_par(ta + 2));
      stage_q<16>(acc, AT_C, sbase + AT_SQ + frag, lane);
      wgmma_wait<0>();
      fence_regs(s);
      if (tid == 0) mbar_arrive(b_empty + 8 * ring_slot(ta));
      mc0 = 0.f; mc1 = 0.f;
      if (!raw) {
        raw = softmax_mode(s, mc0, mc1);
        if (__builtin_expect(!raw, 0)) softmax_sub(s, mc0, mc1);
      }
      softmax_exp<0, 64>(s);
      #pragma unroll
      for (int J = 0; J < 16; J += 2)
        stmatrix_x4(sbase + AT_SQ + frag + (J >> 3) * 16384 + ((((J & 7) + (lane >> 4)) ^ (lane & 7)) << 4), q[2 * J], q[2 * J + 1], q[2 * J + 2], q[2 * J + 3]);
      pack_p(p, s);
      zero_regs(o);
      FS(2 * it, 4);
      uint32_t ks = ring_slot(ta + 1), vs = ring_slot(ta + 2), kp = ring_par(ta + 1), vp = ring_par(ta + 2);
      auto finish_head = [&]() {
        FS(2 * it, 5);
        redo0 = finish_l(lp0, lp1);
        if (!redo0) {
          stage_o(o, lp0, lp1, sbase + AT_SQ + frag, lane);
          fence_proxy_async();
          __syncwarp();
          if (lane == 0) mbar_arrive(b_ordy + 8 * cwg);
        }
        FS(2 * it + 1, 4);
      };
      if (!ready) { mbar_wait(b_full + 8 * ks, kp); mbar_wait(b_full + 8 * vs, vp); }
      #pragma unroll 1
      for (int n = 1; n < 2 * AT_NBLK; n++) {
        named_bar_sync(1 + cwg, 256);
        issue_qk(s, q, k_base + ks * 2048);
        if (n == AT_NBLK + 1) finish_head();
        issue_pv(o, p, v_base + vs * 2048, (n & 15) != 1);
        if (!(last_wg1 && n == 2 * AT_NBLK - 1)) named_bar_arrive(1 + (cwg ^ 1), 256);
        wgmma_wait<1>();
        fence_regs(s);
        if (tid == 0) mbar_arrive(b_empty + 8 * ks);
        if (__builtin_expect(!raw || (n + 1) >> 1 == AT_NBLK / 2, 0)) {
          if (n == AT_NBLK - 1) {
            #pragma unroll
            for (int J = 0; J < 16; J += 2)
              ldmatrix_x4(sbase + AT_SQ + 32768 + frag + (J >> 3) * 16384 + ((((J & 7) + (lane >> 4)) ^ (lane & 7)) << 4), q[2 * J], q[2 * J + 1], q[2 * J + 2], q[2 * J + 3]);
          }
          if (!raw) {
            const float m0 = mc0, m1 = mc1;
            const bool ok = softmax_mode(s, mc0, mc1);
            if (n == AT_NBLK) raw = ok;
            else {
              mc0 = mc0 - AT_HEAD > m0 ? mc0 : m0; mc1 = mc1 - AT_HEAD > m1 ? mc1 : m1;
              al0 = ex2_approx(m0 - mc0); al1 = ex2_approx(m1 - mc1);
            }
            if (!raw) softmax_sub(s, mc0, mc1);
          }
        }
        softmax_exp<0, AT_SPLIT>(s);
        add_rowsum(p, l0, l1);
        if (tid == 0) {
          uint32_t dep = zero & __float_as_uint(l0) & __float_as_uint(l1);
          #pragma unroll
          for (int i = AT_SPLIT - AT_PIN - PINB; i < AT_SPLIT - PINB; i += 2) dep &= __float_as_uint(s[i]) & __float_as_uint(s[i + 1]);
          mbar_arrive(b_pin + dep);
        }
        wgmma_wait<0>();
        fence_regs(o);
        if (tid == 0) mbar_arrive(b_empty + 8 * vs);
        ks += 2; if (ks >= 5) { ks -= 5; kp ^= 1; }
        vs += 2; if (vs >= 5) { vs -= 5; vp ^= 1; }
        ready = mbar_test(b_full + 8 * ks, kp) & mbar_test(b_full + 8 * vs, vp);
        softmax_exp<AT_SPLIT, 64>(s);
        pack_p(p, s);
        if (n == AT_NBLK) { lp0 = l0; lp1 = l1; l0 = 0.f; l1 = 0.f; }
        if (__builtin_expect(!raw || !ready, 0)) {
        if (!raw && __any_sync(0xffffffffu, al0 != 1.0f || al1 != 1.0f)) {
          rescale_o(o, al0, al1);
          l0 *= al0; l1 *= al1;
          al0 = 1.0f; al1 = 1.0f;
        }
        if (!ready && n < 2 * AT_NBLK - 1) {
          mbar_wait(b_full + 8 * ks, kp);
          mbar_wait(b_full + 8 * vs, vp);
        }
        }
      }
      FS(2 * it + 1, 5);
      const uint32_t vl = ring_slot(ta + 63);
      vs = ring_slot(ta + 62);
      const uint32_t ob = more ? sbase + vs * 32768 : sbase + AT_SQ + 32768;
      if (redo0) {
        attn_rows_exact(sq, sq, 4 * ta, kc, vc);
        fence_proxy_async();
        __syncwarp();
        if (lane == 0) mbar_arrive(b_ordy + 8 * cwg);
      }
      mbar_wait(b_full + 8 * vl, ring_par(ta + 63));
      issue_pv(o, p, v_base + vl * 2048, 1);
      add_rowsum(p, l0, l1);
      const bool overflow = finish_l(l0, l1);
      if (!overflow && lane == 0) mbar_arrive(b_q1);
      #pragma unroll
      for (int i = 0; i < 8; i++) asm volatile("mov.b64 {%0, %1}, 0;\nmov.b64 {%2, %3}, 0;" : "=r"(pre[i].x), "=r"(pre[i].y), "=r"(pre[i].z), "=r"(pre[i].w));
      if (HOIST && !more && blockIdx.x < OG_MOE) {
        load_pre(pre, sbase, AT_SQ, threadIdx.x - 128);
        __syncwarp();
        if (lane == 0) mbar_arrive(bars + 304);
      }
      mbar_wait(b_empty + 8 * vs, ring_par(ta + 62));
      wgmma_wait<0>();
      fence_regs(o);
      if (tid == 0) mbar_arrive(b_empty + 8 * vl);
      FS(2 * it + 1, 6);
      if (overflow) {
        attn_rows_exact(sq + 32768, ob + cwg * 8192, 4 * ta + 1, kc, vc);
        __syncwarp();
        if (lane == 0) mbar_arrive(b_q1);
      } else stage_o(o, l0, l1, ob + frag, lane);
      fence_proxy_async();
      __syncwarp();
      if (lane == 0) mbar_arrive(b_ordy + 16 + 8 * cwg);
      if (redo0 || overflow) raw = false;
      named_bar_sync(3 + cwg, 128);
      FS(2 * it + 1, 7);
    }
    if (__builtin_expect(single, 0)) {
      float acc[128];
      uint32_t j = 0, pk[64];
      #pragma unroll
      for (int i = 0; i < 64; i++) asm volatile("" : "=f"(acc[2 * i]), "=f"(acc[2 * i + 1]), "=r"(pk[i]));
      uint4* dst = g_pre;
      int left = 0;
      auto put = [&](bool last) {
        #pragma unroll
        for (int i = 0; i < PUT_N; i++) dst[i * 256] = make_uint4(pk[4 * i], pk[4 * i + 1], pk[4 * i + 2], pk[4 * i + 3]);
        dst += PUT_N * 256;
        #pragma unroll
        for (int i = 0; i < 64 - 4 * PUT_N; i++) asm volatile("mov.b32 %0, %1;" : "=r"(pk[i]) : "r"(pk[i + 4 * PUT_N]));
        __syncwarp();
        if (last && lane == 0) mbar_arrive(bars + 280);
      };
      #pragma unroll 1
      for (int ji = 0; ji < help_njobs(); ji++) {
        #pragma unroll 1
        for (int kk = 0; kk < OG_PRE; kk++, j++) {
          const uint32_t slot = ring_slot(qp_pos(j, 1));
          mbar_wait(b_full + 8 * slot, ring_par(qp_pos(j, 1)) ^ ((j >> 2) & 1));
          if (H_STAG > 0 && cwg == 1 && kk == OG_PRE - H_STAG) named_bar_sync(7, 256);
          const uint32_t a_lo = q_lo + (j & 3) * 1024, b_lo = w_base + slot * 2048;
          wgmma_fence();
          wgmma_m64n256k16_ss_tb<0, 0>(acc, a_lo, b_lo, kk != 0);
          wgmma_m64n256k16_ss_tb<2, 128>(acc, a_lo, b_lo, 1);
          wgmma_m64n256k16_ss_tb<4, 256>(acc, a_lo, b_lo, 1);
          wgmma_m64n256k16_ss_tb<6, 384>(acc, a_lo, b_lo, 1);
          wgmma_commit();
          if (H_STAG > 0 && cwg == 0 && kk == OG_PRE - 1) named_bar_arrive(7, 256);
          wgmma_wait<1>();
          if (kk > 0 && tid == 0) mbar_arrive(b_empty + 8 * ring_slot(qp_pos(j - 1, 1)));
          #pragma unroll 1
          for (int i = ji == OG_JOBS ? 0 : 16 / PUT_N - 1; i < 16 / PUT_N && left > 0; i++) put(--left == 0);
        }
        wgmma_wait<0>();
        fence_regs(acc);
        if (tid == 0) mbar_arrive(b_empty + 8 * ring_slot(qp_pos(j - 1, 1)));
        #pragma unroll
        for (int i = 0; i < 64; i++) pk[i] = pack_bf16(acc[2 * i], acc[2 * i + 1]);
        left = 16 / PUT_N;
        if (ji == PRE_X) mbar_wait(bars + 296, 0);
        dst = g_pre + pre_loc(help_job(ji)) * 4096 + threadIdx.x - 128;
      }
      #pragma unroll
      for (int i = 0; i < 16; i++) dst[i * 256] = make_uint4(pk[4 * i], pk[4 * i + 1], pk[4 * i + 2], pk[4 * i + 3]);
      __syncwarp();
      if (lane == 0) mbar_arrive(bars + 280);
      named_bar_sync(5, 256);
      if (threadIdx.x == 128) {
        #pragma unroll 1
        for (int i = 0; i < 5; i++) {
          constexpr int n = OG_JOBS * OG_PRE;
          const int used = i == 3 ? 0 : (n + 3 - (i == 4 ? 3 : i)) / 4;
          if ((used ^ (i < 4)) & 1) {
            mbar_arrive(b_full + 8 * ring_slot(4 + i));
            mbar_arrive(b_empty + 8 * ring_slot(4 + i)); mbar_arrive(b_empty + 8 * ring_slot(4 + i));
          }
        }
        mbar_arrive(b_x);
      }
      named_bar_sync(5, 256);
      #pragma unroll
      for (int i = 0; i < 8; i++) pre[i] = make_uint4(0u, 0u, 0u, 0u);
    }
    TL_CLK(3, 1, threadIdx.x == 128);
    TL_CTA(1, threadIdx.x == 256);
    TL_END(3, tid == 0);
    TL_MARK2(19, tid == 0 && !single);
    if (blockIdx.x < 128) {
      if (!HOIST && blockIdx.x < OG_MOE) {
        load_pre(pre, sbase, AT_SQ, threadIdx.x - 128);
        __syncwarp();
        if (lane == 0) mbar_arrive(bars + 304);
      }
      tail_consumer(sbase, pre, cwg, w_gate, w_up);
    }
  }
}

typedef CUresult (*PFN_encodeTiled)(CUtensorMap*, CUtensorMapDataType, cuuint32_t, void*, const cuuint64_t*, const cuuint64_t*,
                                    const cuuint32_t*, const cuuint32_t*, CUtensorMapInterleave, CUtensorMapSwizzle,
                                    CUtensorMapL2promotion, CUtensorMapFloatOOBfill);

CUtensorMap make_map_2d(PFN_encodeTiled enc, const void* ptr, uint64_t inner, uint64_t outer, uint64_t stride_bytes, uint32_t box_inner, uint32_t box_outer) {
  CUtensorMap m;
  cuuint64_t gd[2] = {inner, outer}; cuuint64_t gs[1] = {stride_bytes};
  cuuint32_t bx[2] = {box_inner, box_outer}; cuuint32_t es[2] = {1, 1};
  enc(&m, CU_TENSOR_MAP_DATA_TYPE_BFLOAT16, 2, const_cast<void*>(ptr), gd, gs, bx, es, CU_TENSOR_MAP_INTERLEAVE_NONE,
      CU_TENSOR_MAP_SWIZZLE_128B, CU_TENSOR_MAP_L2_PROMOTION_L2_128B, CU_TENSOR_MAP_FLOAT_OOB_FILL_NONE);
  return m;
}

CUtensorMap make_map_3d(PFN_encodeTiled enc, const void* ptr, uint64_t cols, uint64_t rows, uint32_t box_rows, uint32_t chunks) {
  CUtensorMap m;
  cuuint64_t gd[3] = {64, rows, cols / 64}; cuuint64_t gs[2] = {cols * 2, 128};
  cuuint32_t bx[3] = {64, box_rows, chunks}; cuuint32_t es[3] = {1, 1, 1};
  enc(&m, CU_TENSOR_MAP_DATA_TYPE_BFLOAT16, 3, const_cast<void*>(ptr), gd, gs, bx, es, CU_TENSOR_MAP_INTERLEAVE_NONE,
      CU_TENSOR_MAP_SWIZZLE_128B, CU_TENSOR_MAP_L2_PROMOTION_L2_128B, CU_TENSOR_MAP_FLOAT_OOB_FILL_NONE);
  return m;
}

}

extern "C" void kernel_launch(void* const* d_in, const int* in_sizes, int n_in, void* d_out, int out_size) {
  const bf16* x      = (const bf16*)d_in[0];
  const bf16* kc     = (const bf16*)d_in[1];
  const bf16* vc     = (const bf16*)d_in[2];
  const bf16* wq     = (const bf16*)d_in[3];
  const bf16* wo     = (const bf16*)d_in[4];
  const bf16* w_r    = (const bf16*)d_in[6];
  const bf16* w_gate = (const bf16*)d_in[7];
  const bf16* w_up   = (const bf16*)d_in[8];
  const bf16* w_down = (const bf16*)d_in[9];
  const bf16* cvec   = (const bf16*)d_in[10];
  const bf16* w_mod  = (const bf16*)d_in[11];
  bf16* out = (bf16*)d_out;

  static PFN_encodeTiled enc = nullptr;
  static void *p_h = nullptr, *p_o = nullptr;
  if (!enc) {
    void* fn = nullptr; cudaDriverEntryPointQueryResult qres;
    cudaGetDriverEntryPoint("cuTensorMapEncodeTiled", &fn, cudaEnableDefault, &qres);
    enc = (PFN_encodeTiled)fn;
    cudaGetSymbolAddress(&p_h, g_pre);
    p_h = (uint4*)p_h + 16 * PRE_X * 2048;
    cudaGetSymbolAddress(&p_o, g_o);
    cudaFuncSetAttribute(fused_kernel, cudaFuncAttributeMaxDynamicSharedMemorySize, (int)AT_SMEM);
  }
  const CUtensorMap tm_h   = make_map_2d(enc, p_h, T_D, T_SEQ, T_D * 2, 64, 128);
  const CUtensorMap tm_wq  = W3D ? make_map_3d(enc, wq, T_DQKV, T_D, 64, 4) : make_map_2d(enc, wq, T_DQKV, T_D, T_DQKV * 2, 64, 64);
  const CUtensorMap tm_k   = KV3D ? make_map_3d(enc, kc, T_DH, (uint64_t)T_NH * T_SEQ, 128, 2) : make_map_2d(enc, kc, T_DH, (uint64_t)T_NH * T_SEQ, T_DH * 2, 64, 128);
  const CUtensorMap tm_v   = KV3D ? make_map_3d(enc, vc, T_DH, (uint64_t)T_NH * T_SEQ, 128, 2) : make_map_2d(enc, vc, T_DH, (uint64_t)T_NH * T_SEQ, T_DH * 2, 64, 128);
  const CUtensorMap tm_ost = make_map_2d(enc, p_o, T_DQKV, T_SEQ, T_DQKV * 2, 64, 64);
  const CUtensorMap tm_old = make_map_2d(enc, p_o, T_DQKV, T_SEQ, T_DQKV * 2, 64, 128);
  const CUtensorMap tm_wo  = make_map_3d(enc, wo, T_D, T_DQKV, 64, 2);
  const CUtensorMap tm_x   = make_map_3d(enc, x, T_D, T_SEQ, 128, 2);

  const CUtensorMap tm_out = make_map_2d(enc, out, T_D, T_SEQ, T_D * 2, 64, 128);

  fused_kernel<<<132, 384, AT_SMEM, cudaStreamPerThread>>>(tm_h, tm_wq, tm_k, tm_v, tm_ost, tm_old, tm_wo, tm_x, tm_out, 0u, (const uint8_t*)wo, kc, vc, x, cvec, w_mod,
             w_r, w_gate, w_up, w_down, out);
}
```

```cpp
#include <cuda_runtime.h>
#include <cuda_bf16.h>
#include <cuda.h>
#include <stdint.h>

namespace {

typedef __nv_bfloat16 bf16;

constexpr int T_SEQ = 2048, T_D = 1024, T_NH = 32, T_DH = 128, T_DQKV = 4096, T_F = 3584;

#define PRE_X 2
__device__ __align__(1024) uint4 g_pre[(16 * PRE_X + 128) * 2048];
#define g_h (reinterpret_cast<bf16*>(g_pre + 16 * PRE_X * 2048))
__device__ __align__(1024) bf16 g_o[T_SEQ * T_DQKV];
__device__ __align__(16) uint8_t g_col[8 * 1536];
__device__ __align__(16) float g_scal[64];
__device__ __align__(16) unsigned int g_hcnt[17 * 32];
__device__ unsigned int g_smid[160], g_tmax[128];
__device__ __align__(128) float g_modpart[4 * 2 * T_D];
struct __align__(2048) TailMail {
  float4 part1[T_SEQ * 8];
  uint32_t key[256];
  uint4 cand[16 * 2 * 2 * 128];
  uint32_t cnt[32];
  float ypart[(T_F / 32) * 2 * T_D];
};
__device__ TailMail g_mail;
#define g_part1 g_mail.part1
#define g_key g_mail.key
#define g_cand g_mail.cand
#define CNT_Y (g_mail.cnt)
#define g_ypart g_mail.ypart

__device__ __forceinline__ uint32_t smem_u32(const void* p) { return (uint32_t)__cvta_generic_to_shared(p); }
__device__ __forceinline__ void mbar_init(uint32_t bar, uint32_t cnt) { asm volatile("mbarrier.init.shared::cta.b64 [%0], %1;" :: "r"(bar), "r"(cnt)); }
__device__ __forceinline__ void mbar_expect_tx(uint32_t bar, uint32_t bytes) { asm volatile("mbarrier.arrive.expect_tx.shared::cta.b64 _, [%0], %1;" :: "r"(bar), "r"(bytes) : "memory"); }
__device__ __forceinline__ void mbar_arrive(uint32_t bar) { asm volatile("mbarrier.arrive.shared::cta.b64 _, [%0];" :: "r"(bar) : "memory"); }
__device__ __forceinline__ void mbar_wait(uint32_t bar, uint32_t parity) {
  asm volatile("{\n.reg .pred p;\nLAB_WAIT:\nmbarrier.try_wait.parity.shared::cta.b64 p, [%0], %1;\n@!p bra LAB_WAIT;\n}\n" :: "r"(bar), "r"(parity) : "memory");
}
__device__ __forceinline__ bool mbar_test(uint32_t bar, uint32_t parity) {
  uint32_t r; asm volatile("{\n.reg .pred p;\nmbarrier.test_wait.parity.shared::cta.b64 p, [%1], %2;\nselp.u32 %0, 1, 0, p;\n}\n" : "=r"(r) : "r"(bar), "r"(parity) : "memory");
  return r != 0;
}
__device__ __forceinline__ uint32_t clock_lo() { uint32_t c; asm volatile("mov.u32 %0, %%clock;" : "=r"(c)); return c; }
__device__ __forceinline__ void fence_mbar_init() { asm volatile("fence.mbarrier_init.release.cluster;" ::: "memory"); }
__device__ __forceinline__ void tma_load_2d(uint32_t dst, const CUtensorMap* map, int c0, int c1, uint32_t bar) {
  asm volatile("cp.async.bulk.tensor.2d.shared::cluster.global.mbarrier::complete_tx::bytes [%0], [%1, {%3, %4}], [%2];"
    :: "r"(dst), "l"(map), "r"(bar), "r"(c0), "r"(c1) : "memory");
}
__device__ __forceinline__ uint64_t policy_evict_first() {
  uint64_t p; asm volatile("createpolicy.fractional.L2::evict_first.b64 %0, 1.0;" : "=l"(p)); return p;
}
__device__ __forceinline__ void tma_load_2d_hint(uint32_t dst, const CUtensorMap* map, int c0, int c1, uint32_t bar, uint64_t pol) {
  asm volatile("cp.async.bulk.tensor.2d.shared::cluster.global.mbarrier::complete_tx::bytes.L2::cache_hint [%0], [%1, {%3, %4}], [%2], %5;"
    :: "r"(dst), "l"(map), "r"(bar), "r"(c0), "r"(c1), "l"(pol) : "memory");
}
__device__ __forceinline__ void tma_load_3d_hint(uint32_t dst, const CUtensorMap* map, int c1, int c2, uint32_t bar, uint64_t pol) {
  asm volatile("cp.async.bulk.tensor.3d.shared::cluster.global.mbarrier::complete_tx::bytes.L2::cache_hint [%0], [%1, {%3, %4, %5}], [%2], %6;"
    :: "r"(dst), "l"(map), "r"(bar), "n"(0), "r"(c1), "r"(c2), "l"(pol) : "memory");
}
__device__ __forceinline__ void tma_store_2d(const CUtensorMap* map, uint32_t src, int c0, int c1) {
  asm volatile("cp.async.bulk.tensor.2d.global.shared::cta.bulk_group [%0, {%2, %3}], [%1];" :: "l"(map), "r"(src), "r"(c0), "r"(c1) : "memory");
}
__device__ __forceinline__ void prefetch_tmap(const CUtensorMap* map) { asm volatile("prefetch.tensormap [%0];" :: "l"(map) : "memory"); }
__device__ __forceinline__ void l2_prefetch_bulk(const void* p, uint32_t bytes) {
  asm volatile("cp.async.bulk.prefetch.L2.global [%0], %1;" :: "l"(p), "r"(bytes) : "memory");
}
__device__ __forceinline__ void bulk_commit() { asm volatile("cp.async.bulk.commit_group;" ::: "memory"); }
template<int N> __device__ __forceinline__ void bulk_wait_read() { asm volatile("cp.async.bulk.wait_group.read %0;" :: "n"(N) : "memory"); }
template<int N> __device__ __forceinline__ void bulk_wait() { asm volatile("cp.async.bulk.wait_group %0;" :: "n"(N) : "memory"); }
__device__ __forceinline__ void named_bar_sync(int id, int nthreads) { asm volatile("bar.sync %0, %1;" :: "r"(id), "r"(nthreads) : "memory"); }
__device__ __forceinline__ void named_bar_arrive(int id, int nthreads) { asm volatile("bar.arrive %0, %1;" :: "r"(id), "r"(nthreads) : "memory"); }
__device__ __forceinline__ void wgmma_fence() { asm volatile("wgmma.fence.sync.aligned;" ::: "memory"); }
__device__ __forceinline__ void wgmma_commit() { asm volatile("wgmma.commit_group.sync.aligned;" ::: "memory"); }
template<int N> __device__ __forceinline__ void wgmma_wait() { asm volatile("wgmma.wait_group.sync.aligned %0;" :: "n"(N) : "memory"); }
template<int R> __device__ __forceinline__ void reg_alloc() { asm volatile("setmaxnreg.inc.sync.aligned.u32 %0;" :: "n"(R)); }
template<int R> __device__ __forceinline__ void reg_dealloc() { asm volatile("setmaxnreg.dec.sync.aligned.u32 %0;" :: "n"(R)); }
__device__ __forceinline__ bool elect_one() {
  uint32_t pred; asm volatile("{\n.reg .pred p;\nelect.sync _|p, 0xffffffff;\nselp.u32 %0, 1, 0, p;\n}\n" : "=r"(pred)); return pred != 0;
}
__device__ __forceinline__ uint32_t pack_bf16(float lo, float hi) {
  uint32_t r; asm("cvt.rn.bf16x2.f32 %0, %1, %2;" : "=r"(r) : "f"(hi), "f"(lo)); return r;
}
__device__ __forceinline__ void stmatrix_x4(uint32_t addr, uint32_t r0, uint32_t r1, uint32_t r2, uint32_t r3) {
  asm volatile("stmatrix.sync.aligned.m8n8.x4.shared.b16 [%0], {%1, %2, %3, %4};" :: "r"(addr), "r"(r0), "r"(r1), "r"(r2), "r"(r3) : "memory");
}
__device__ __forceinline__ void fence_proxy_async() { asm volatile("fence.proxy.async.shared::cta;" ::: "memory"); }
__device__ __forceinline__ float ex2_approx(float x) { float y; asm("ex2.approx.ftz.f32 %0, %1;" : "=f"(y) : "f"(x)); return y; }
template<int N> __device__ __forceinline__ void fence_regs(float (&r)[N]) {
  #pragma unroll
  for (int i = 0; i < N; i++) asm volatile("" : "+f"(r[i]) :: "memory");
}
template<int N> __device__ __forceinline__ void zero_regs(float (&r)[N]) {
  #pragma unroll
  for (int i = 0; i < N; i += 2) asm volatile("mov.b64 {%0, %1}, 0;" : "=f"(r[i]), "=f"(r[i + 1]));
}
__device__ __forceinline__ float rbf(float x) { return __uint_as_float(pack_bf16(0.f, x)); }
__device__ __forceinline__ float bflo(uint32_t v) { return __uint_as_float(v << 16); }
__device__ __forceinline__ float bfhi(uint32_t v) { return __uint_as_float(v & 0xffff0000u); }

#define TL_START(k) do {} while (0)
#define TL_END(k, cond) do {} while (0)
#define TL_CTA(i, cond) do {} while (0)
#define FS(slot, k) do {} while (0)
#define TL_MARK2(k, cond) do {} while (0)
#define TL_CLK(k, i, cond) do {} while (0)

template <int OFFA, int OFFB>
__device__ __forceinline__ void wgmma_m64n256k16_ss_tb(float (&d)[128], uint32_t a_lo, uint32_t b_lo, int scaleD) {
  asm volatile("{\n.reg .pred p;\n.reg .b32 ta, tb;\n.reg .b64 da, db;\nsetp.ne.b32 p, %130, 0;\n"
    "add.u32 ta, %128, %131;\nadd.u32 tb, %129, %132;\n"
    "mov.b64 da, {ta, 0x40000040};\nmov.b64 db, {tb, 0x40000040};\n"
    "wgmma.mma_async.sync.aligned.m64n256k16.f32.bf16.bf16 "
    "{%0, %1, %2, %3, %4, %5, %6, %7, %8, %9, %10, %11, %12, %13, %14, %15, %16, %17, %18, %19, %20, %21, %22, %23, %24, %25, %26, %27, %28, %29, %30, %31, %32, %33, %34, %35, %36, %37, %38, %39, %40, %41, %42, %43, %44, %45, %46, %47, %48, %49, %50, %51, %52, %53, %54, %55, %56, %57, %58, %59, %60, %61, %62, %63, %64, %65, %66, %67, %68, %69, %70, %71, %72, %73, %74, %75, %76, %77, %78, %79, %80, %81, %82, %83, %84, %85, %86, %87, %88, %89, %90, %91, %92, %93, %94, %95, %96, %97, %98, %99, %100, %101, %102, %103, %104, %105, %106, %107, %108, %109, %110, %111, %112, %113, %114, %115, %116, %117, %118, %119, %120, %121, %122, %123, %124, %125, %126, %127}, "
    "da, db, p, 1, 1, 0, 1;\n}\n"
    : "+f"(d[0]), "+f"(d[1]), "+f"(d[2]), "+f"(d[3]), "+f"(d[4]), "+f"(d[5]), "+f"(d[6]), "+f"(d[7]), "+f"(d[8]), "+f"(d[9]), "+f"(d[10]), "+f"(d[11]), "+f"(d[12]), "+f"(d[13]), "+f"(d[14]), "+f"(d[15]), "+f"(d[16]), "+f"(d[17]), "+f"(d[18]), "+f"(d[19]), "+f"(d[20]), "+f"(d[21]), "+f"(d[22]), "+f"(d[23]), "+f"(d[24]), "+f"(d[25]), "+f"(d[26]), "+f"(d[27]), "+f"(d[28]), "+f"(d[29]), "+f"(d[30]), "+f"(d[31]), "+f"(d[32]), "+f"(d[33]), "+f"(d[34]), "+f"(d[35]), "+f"(d[36]), "+f"(d[37]), "+f"(d[38]), "+f"(d[39]), "+f"(d[40]), "+f"(d[41]), "+f"(d[42]), "+f"(d[43]), "+f"(d[44]), "+f"(d[45]), "+f"(d[46]), "+f"(d[47]), "+f"(d[48]), "+f"(d[49]), "+f"(d[50]), "+f"(d[51]), "+f"(d[52]), "+f"(d[53]), "+f"(d[54]), "+f"(d[55]), "+f"(d[56]), "+f"(d[57]), "+f"(d[58]), "+f"(d[59]), "+f"(d[60]), "+f"(d[61]), "+f"(d[62]), "+f"(d[63]), "+f"(d[64]), "+f"(d[65]), "+f"(d[66]), "+f"(d[67]), "+f"(d[68]), "+f"(d[69]), "+f"(d[70]), "+f"(d[71]), "+f"(d[72]), "+f"(d[73]), "+f"(d[74]), "+f"(d[75]), "+f"(d[76]), "+f"(d[77]), "+f"(d[78]), "+f"(d[79]), "+f"(d[80]), "+f"(d[81]), "+f"(d[82]), "+f"(d[83]), "+f"(d[84]), "+f"(d[85]), "+f"(d[86]), "+f"(d[87]), "+f"(d[88]), "+f"(d[89]), "+f"(d[90]), "+f"(d[91]), "+f"(d[92]), "+f"(d[93]), "+f"(d[94]), "+f"(d[95]), "+f"(d[96]), "+f"(d[97]), "+f"(d[98]), "+f"(d[99]), "+f"(d[100]), "+f"(d[101]), "+f"(d[102]), "+f"(d[103]), "+f"(d[104]), "+f"(d[105]), "+f"(d[106]), "+f"(d[107]), "+f"(d[108]), "+f"(d[109]), "+f"(d[110]), "+f"(d[111]), "+f"(d[112]), "+f"(d[113]), "+f"(d[114]), "+f"(d[115]), "+f"(d[116]), "+f"(d[117]), "+f"(d[118]), "+f"(d[119]), "+f"(d[120]), "+f"(d[121]), "+f"(d[122]), "+f"(d[123]), "+f"(d[124]), "+f"(d[125]), "+f"(d[126]), "+f"(d[127])
    : "r"(a_lo), "r"(b_lo), "r"(scaleD), "n"(OFFA), "n"(OFFB));
}

template <int OFFA, int OFFB>
__device__ __forceinline__ void wgmma_m64n128k16_ss_tb(float (&d)[64], uint32_t a_lo, uint32_t b_lo, int scaleD) {
  asm volatile("{\n.reg .pred p;\n.reg .b32 ta, tb;\n.reg .b64 da, db;\nsetp.ne.b32 p, %66, 0;\n"
    "add.u32 ta, %64, %67;\nadd.u32 tb, %65, %68;\n"
    "mov.b64 da, {ta, 0x40000040};\nmov.b64 db, {tb, 0x40000040};\n"
    "wgmma.mma_async.sync.aligned.m64n128k16.f32.bf16.bf16 "
    "{%0, %1, %2, %3, %4, %5, %6, %7, %8, %9, %10, %11, %12, %13, %14, %15, %16, %17, %18, %19, %20, %21, %22, %23, %24, %25, %26, %27, %28, %29, %30, %31, %32, %33, %34, %35, %36, %37, %38, %39, %40, %41, %42, %43, %44, %45, %46, %47, %48, %49, %50, %51, %52, %53, %54, %55, %56, %57, %58, %59, %60, %61, %62, %63}, "
    "da, db, p, 1, 1, 0, 1;\n}\n"
    : "+f"(d[0]), "+f"(d[1]), "+f"(d[2]), "+f"(d[3]), "+f"(d[4]), "+f"(d[5]), "+f"(d[6]), "+f"(d[7]), "+f"(d[8]), "+f"(d[9]), "+f"(d[10]), "+f"(d[11]), "+f"(d[12]), "+f"(d[13]), "+f"(d[14]), "+f"(d[15]), "+f"(d[16]), "+f"(d[17]), "+f"(d[18]), "+f"(d[19]), "+f"(d[20]), "+f"(d[21]), "+f"(d[22]), "+f"(d[23]), "+f"(d[24]), "+f"(d[25]), "+f"(d[26]), "+f"(d[27]), "+f"(d[28]), "+f"(d[29]), "+f"(d[30]), "+f"(d[31]), "+f"(d[32]), "+f"(d[33]), "+f"(d[34]), "+f"(d[35]), "+f"(d[36]), "+f"(d[37]), "+f"(d[38]), "+f"(d[39]), "+f"(d[40]), "+f"(d[41]), "+f"(d[42]), "+f"(d[43]), "+f"(d[44]), "+f"(d[45]), "+f"(d[46]), "+f"(d[47]), "+f"(d[48]), "+f"(d[49]), "+f"(d[50]), "+f"(d[51]), "+f"(d[52]), "+f"(d[53]), "+f"(d[54]), "+f"(d[55]), "+f"(d[56]), "+f"(d[57]), "+f"(d[58]), "+f"(d[59]), "+f"(d[60]), "+f"(d[61]), "+f"(d[62]), "+f"(d[63])
    : "r"(a_lo), "r"(b_lo), "r"(scaleD), "n"(OFFA), "n"(OFFB));
}

template <int OFFB>
__device__ __forceinline__ void wgmma_m64n128k16_rs_tb(float (&d)[64], uint32_t a0, uint32_t a1, uint32_t a2, uint32_t a3, uint32_t b_lo, int scaleD) {
  asm volatile("{\n.reg .pred p;\n.reg .b32 tb;\n.reg .b64 db;\nsetp.ne.b32 p, %69, 0;\n"
    "add.u32 tb, %68, %70;\n"
    "mov.b64 db, {tb, 0x40000040};\n"
    "wgmma.mma_async.sync.aligned.m64n128k16.f32.bf16.bf16 "
    "{%0, %1, %2, %3, %4, %5, %6, %7, %8, %9, %10, %11, %12, %13, %14, %15, %16, %17, %18, %19, %20, %21, %22, %23, %24, %25, %26, %27, %28, %29, %30, %31, %32, %33, %34, %35, %36, %37, %38, %39, %40, %41, %42, %43, %44, %45, %46, %47, %48, %49, %50, %51, %52, %53, %54, %55, %56, %57, %58, %59, %60, %61, %62, %63}, "
    "{%64, %65, %66, %67}, db, p, 1, 1, 1;\n}\n"
    : "+f"(d[0]), "+f"(d[1]), "+f"(d[2]), "+f"(d[3]), "+f"(d[4]), "+f"(d[5]), "+f"(d[6]), "+f"(d[7]), "+f"(d[8]), "+f"(d[9]), "+f"(d[10]), "+f"(d[11]), "+f"(d[12]), "+f"(d[13]), "+f"(d[14]), "+f"(d[15]), "+f"(d[16]), "+f"(d[17]), "+f"(d[18]), "+f"(d[19]), "+f"(d[20]), "+f"(d[21]), "+f"(d[22]), "+f"(d[23]), "+f"(d[24]), "+f"(d[25]), "+f"(d[26]), "+f"(d[27]), "+f"(d[28]), "+f"(d[29]), "+f"(d[30]), "+f"(d[31]), "+f"(d[32]), "+f"(d[33]), "+f"(d[34]), "+f"(d[35]), "+f"(d[36]), "+f"(d[37]), "+f"(d[38]), "+f"(d[39]), "+f"(d[40]), "+f"(d[41]), "+f"(d[42]), "+f"(d[43]), "+f"(d[44]), "+f"(d[45]), "+f"(d[46]), "+f"(d[47]), "+f"(d[48]), "+f"(d[49]), "+f"(d[50]), "+f"(d[51]), "+f"(d[52]), "+f"(d[53]), "+f"(d[54]), "+f"(d[55]), "+f"(d[56]), "+f"(d[57]), "+f"(d[58]), "+f"(d[59]), "+f"(d[60]), "+f"(d[61]), "+f"(d[62]), "+f"(d[63])
    : "r"(a0), "r"(a1), "r"(a2), "r"(a3), "r"(b_lo), "r"(scaleD), "n"(OFFB));
}

template <int OFFB>
__device__ __forceinline__ void wgmma_m64n128k16_rs(float (&d)[64], uint32_t a0, uint32_t a1, uint32_t a2, uint32_t a3, uint32_t b_lo, int scaleD) {
  asm volatile("{\n.reg .pred p;\n.reg .b32 tb;\n.reg .b64 db;\nsetp.ne.b32 p, %69, 0;\n"
    "add.u32 tb, %68, %70;\n"
    "mov.b64 db, {tb, 0x40000040};\n"
    "wgmma.mma_async.sync.aligned.m64n128k16.f32.bf16.bf16 "
    "{%0, %1, %2, %3, %4, %5, %6, %7, %8, %9, %10, %11, %12, %13, %14, %15, %16, %17, %18, %19, %20, %21, %22, %23, %24, %25, %26, %27, %28, %29, %30, %31, %32, %33, %34, %35, %36, %37, %38, %39, %40, %41, %42, %43, %44, %45, %46, %47, %48, %49, %50, %51, %52, %53, %54, %55, %56, %57, %58, %59, %60, %61, %62, %63}, "
    "{%64, %65, %66, %67}, db, p, 1, 1, 0;\n}\n"
    : "+f"(d[0]), "+f"(d[1]), "+f"(d[2]), "+f"(d[3]), "+f"(d[4]), "+f"(d[5]), "+f"(d[6]), "+f"(d[7]), "+f"(d[8]), "+f"(d[9]), "+f"(d[10]), "+f"(d[11]), "+f"(d[12]), "+f"(d[13]), "+f"(d[14]), "+f"(d[15]), "+f"(d[16]), "+f"(d[17]), "+f"(d[18]), "+f"(d[19]), "+f"(d[20]), "+f"(d[21]), "+f"(d[22]), "+f"(d[23]), "+f"(d[24]), "+f"(d[25]), "+f"(d[26]), "+f"(d[27]), "+f"(d[28]), "+f"(d[29]), "+f"(d[30]), "+f"(d[31]), "+f"(d[32]), "+f"(d[33]), "+f"(d[34]), "+f"(d[35]), "+f"(d[36]), "+f"(d[37]), "+f"(d[38]), "+f"(d[39]), "+f"(d[40]), "+f"(d[41]), "+f"(d[42]), "+f"(d[43]), "+f"(d[44]), "+f"(d[45]), "+f"(d[46]), "+f"(d[47]), "+f"(d[48]), "+f"(d[49]), "+f"(d[50]), "+f"(d[51]), "+f"(d[52]), "+f"(d[53]), "+f"(d[54]), "+f"(d[55]), "+f"(d[56]), "+f"(d[57]), "+f"(d[58]), "+f"(d[59]), "+f"(d[60]), "+f"(d[61]), "+f"(d[62]), "+f"(d[63])
    : "r"(a0), "r"(a1), "r"(a2), "r"(a3), "r"(b_lo), "r"(scaleD), "n"(OFFB));
}

__device__ __forceinline__ uint4 ldg_nc_v4(const void* p) {
  uint4 v;
    asm volatile("{\n.reg .b64 pol;\ncreatepolicy.fractional.L2::evict_first.b64 pol, 1.0;\n"
                 "ld.global.nc.L1::no_allocate.L2::cache_hint.v4.u32 {%0, %1, %2, %3}, [%4], pol;\n}\n" : "=r"(v.x), "=r"(v.y), "=r"(v.z), "=r"(v.w) : "l"(p));
  return v;
}
__device__ __forceinline__ uint64_t pol_normal() {
  uint64_t p; asm volatile("createpolicy.fractional.L2::evict_normal.b64 %0, 1.0;" : "=l"(p)); return p;
}
__device__ __forceinline__ void unpack8(const uint4& u, float (&v)[8]) {
  v[0] = bflo(u.x); v[1] = bfhi(u.x); v[2] = bflo(u.y); v[3] = bfhi(u.y);
  v[4] = bflo(u.z); v[5] = bfhi(u.z); v[6] = bflo(u.w); v[7] = bfhi(u.w);
}
__device__ __forceinline__ void fma8(float (&acc)[8], float s, const uint4& w) {
  acc[0] = fmaf(s, bflo(w.x), acc[0]); acc[1] = fmaf(s, bfhi(w.x), acc[1]); acc[2] = fmaf(s, bflo(w.y), acc[2]); acc[3] = fmaf(s, bfhi(w.y), acc[3]);
  acc[4] = fmaf(s, bflo(w.z), acc[4]); acc[5] = fmaf(s, bfhi(w.z), acc[5]); acc[6] = fmaf(s, bflo(w.w), acc[6]); acc[7] = fmaf(s, bfhi(w.w), acc[7]);
}
__device__ __forceinline__ float rcp_approx(float x) { float y; asm("rcp.approx.ftz.f32 %0, %1;" : "=f"(y) : "f"(x)); return y; }
__device__ __forceinline__ float sigmoid_f(float v) { return rcp_approx(1.0f + ex2_approx(v * -1.4426950408889634f)); }
__device__ __forceinline__ float silu_bf(float v) { return rbf(v * sigmoid_f(v)); }
__device__ __forceinline__ uint32_t rank_key(float r, int idx) {
  const uint32_t b = __float_as_uint(r) >> 16;
  const uint32_t u = (r != r) ? 0u : ((b & 0x8000u) ? (~b & 0xffffu) : (b | 0x8000u));
  return (u << 16) | (0xffffu - (uint32_t)idx);
}
__device__ __forceinline__ void warp_top2(uint32_t& k1, uint32_t& k2) {
  const uint32_t m1 = __reduce_max_sync(0xffffffffu, k1);
  k2 = __reduce_max_sync(0xffffffffu, k1 == m1 ? k2 : k1);
  k1 = m1;
}
__device__ __forceinline__ uint32_t bmul2(uint32_t a, uint32_t b) { uint32_t r; asm("mul.rn.bf16x2 %0, %1, %2;" : "=r"(r) : "r"(a), "r"(b)); return r; }
__device__ __forceinline__ uint32_t badd2(uint32_t a, uint32_t b) { uint32_t r; asm("add.rn.bf16x2 %0, %1, %2;" : "=r"(r) : "r"(a), "r"(b)); return r; }
__device__ __forceinline__ uint32_t bsub2(uint32_t a, uint32_t b) { uint32_t r; asm("sub.rn.bf16x2 %0, %1, %2;" : "=r"(r) : "r"(a), "r"(b)); return r; }
__device__ __forceinline__ float sqrt_approx(float x) { float y; asm("sqrt.approx.f32 %0, %1;" : "=f"(y) : "f"(x)); return y; }
__device__ __forceinline__ uint32_t ln_norm2(uint32_t x1, uint32_t mb2, float inv) {
  const uint32_t d = bsub2(x1, mb2);
  return pack_bf16(bflo(d) * inv, bfhi(d) * inv);
}
__device__ __forceinline__ uint32_t ln_mod2(uint32_t x1, uint32_t mb2, float inv, uint32_t c1, uint32_t sb) { return badd2(bmul2(ln_norm2(x1, mb2, inv), c1), sb); }
__device__ __forceinline__ void ldmatrix_x4(uint32_t addr, uint32_t& r0, uint32_t& r1, uint32_t& r2, uint32_t& r3) {
  asm volatile("ldmatrix.sync.aligned.m8n8.x4.shared.b16 {%0, %1, %2, %3}, [%4];" : "=r"(r0), "=r"(r1), "=r"(r2), "=r"(r3) : "r"(addr) : "memory");
}
__device__ __forceinline__ uint4 ldg_stream_v4(const void* p, uint64_t pol) {
  uint4 v; asm volatile("ld.global.nc.L1::no_allocate.L2::cache_hint.L2::128B.v4.u32 {%0, %1, %2, %3}, [%4], %5;" : "=r"(v.x), "=r"(v.y), "=r"(v.z), "=r"(v.w) : "l"(p), "l"(pol)); return v;
}
__device__ __forceinline__ void bulk_load_hint(uint32_t dst, const void* src, uint32_t bytes, uint32_t bar, uint64_t pol) {
  asm volatile("cp.async.bulk.shared::cluster.global.mbarrier::complete_tx::bytes.L2::cache_hint [%0], [%1], %2, [%3], %4;"
    :: "r"(dst), "l"(src), "r"(bytes), "r"(bar), "l"(pol) : "memory");
}
__device__ __forceinline__ void red_release_add(unsigned int* p, unsigned int v) { asm volatile("red.release.gpu.global.add.u32 [%0], %1;" :: "l"(p), "r"(v) : "memory"); }
__device__ __forceinline__ unsigned int ld_acquire(const unsigned int* p) { unsigned int v; asm volatile("ld.acquire.gpu.global.u32 %0, [%1];" : "=r"(v) : "l"(p) : "memory"); return v; }
__device__ __forceinline__ void spin_until(const unsigned int* p, unsigned int target) {
  #pragma unroll 1
  for (unsigned int i = 0; i < (1u << 22); i++) { if (ld_acquire(p) >= target) return; }
}
__device__ __forceinline__ float lds_f32(uint32_t a) { float v; asm volatile("ld.shared.f32 %0, [%1];" : "=f"(v) : "r"(a) : "memory"); return v; }
__device__ __forceinline__ float2 lds_f32x2(uint32_t a) { float2 v; asm volatile("ld.shared.v2.f32 {%0, %1}, [%2];" : "=f"(v.x), "=f"(v.y) : "r"(a) : "memory"); return v; }
__device__ __forceinline__ uint2 lds_u32x2(uint32_t a) { uint2 v; asm volatile("ld.shared.v2.u32 {%0, %1}, [%2];" : "=r"(v.x), "=r"(v.y) : "r"(a) : "memory"); return v; }
__device__ __forceinline__ uint32_t lds_u32(uint32_t a) { uint32_t v; asm volatile("ld.shared.u32 %0, [%1];" : "=r"(v) : "r"(a) : "memory"); return v; }
__device__ __forceinline__ void sts_u32(uint32_t a, uint32_t v) { asm volatile("st.shared.u32 [%0], %1;" :: "r"(a), "r"(v) : "memory"); }
__device__ __forceinline__ void sts_u32x2(uint32_t a, uint32_t x, uint32_t y) { asm volatile("st.shared.v2.u32 [%0], {%1, %2};" :: "r"(a), "r"(x), "r"(y) : "memory"); }
__device__ __forceinline__ void sts_f32(uint32_t a, float v) { asm volatile("st.shared.f32 [%0], %1;" :: "r"(a), "f"(v) : "memory"); }
__device__ __forceinline__ void sts_f32x2(uint32_t a, float x, float y) { asm volatile("st.shared.v2.f32 [%0], {%1, %2};" :: "r"(a), "f"(x), "f"(y) : "memory"); }
__device__ __forceinline__ void sts_f32x4(uint32_t a, float x, float y, float z, float w) { asm volatile("st.shared.v4.f32 [%0], {%1, %2, %3, %4};" :: "r"(a), "f"(x), "f"(y), "f"(z), "f"(w) : "memory"); }

__device__ __forceinline__ uint4 lds_u32x4(uint32_t a) { uint4 v; asm volatile("ld.shared.v4.u32 {%0, %1, %2, %3}, [%4];" : "=r"(v.x), "=r"(v.y), "=r"(v.z), "=r"(v.w) : "r"(a) : "memory"); return v; }
__device__ __forceinline__ void sts_u32x4(uint32_t a, uint32_t x, uint32_t y, uint32_t z, uint32_t w) { asm volatile("st.shared.v4.u32 [%0], {%1, %2, %3, %4};" :: "r"(a), "r"(x), "r"(y), "r"(z), "r"(w) : "memory"); }
__device__ __forceinline__ void st_tagged(float* p, float v) {
  const uint32_t b = __float_as_uint(v);
  asm volatile("st.relaxed.gpu.global.u32 [%0], %1;" :: "l"(p), "r"(b == 0u ? 0x80000000u : b) : "memory");
}
__device__ __forceinline__ void st_tagged4(float* p, float x, float y, float z, float w) {
  const uint32_t a = __float_as_uint(x), b = __float_as_uint(y), c = __float_as_uint(z), d = __float_as_uint(w);
  asm volatile("st.relaxed.gpu.global.v4.u32 [%0], {%1, %2, %3, %4};" :: "l"(p), "r"(a == 0u ? 0x80000000u : a), "r"(b == 0u ? 0x80000000u : b),
               "r"(c == 0u ? 0x80000000u : c), "r"(d == 0u ? 0x80000000u : d) : "memory");
}
__device__ __forceinline__ void st_relaxed2(void* p, uint32_t a, uint32_t b) { asm volatile("st.relaxed.gpu.global.v2.u32 [%0], {%1, %2};" :: "l"(p), "r"(a), "r"(b) : "memory"); }
__device__ __forceinline__ float4 ld_tagged4(const float* p) {
  float4 v; asm volatile("ld.relaxed.gpu.global.v4.f32 {%0, %1, %2, %3}, [%4];" : "=f"(v.x), "=f"(v.y), "=f"(v.z), "=f"(v.w) : "l"(p) : "memory"); return v;
}
__device__ __forceinline__ bool tagged4(const float4& v) {
  return __float_as_uint(v.x) != 0u && __float_as_uint(v.y) != 0u && __float_as_uint(v.z) != 0u && __float_as_uint(v.w) != 0u;
}
__device__ __forceinline__ void hint_arrive(uint32_t* p) { asm volatile("red.relaxed.gpu.global.add.u32 [%0], 1;" :: "l"(p) : "memory"); }
__device__ __forceinline__ void hint_wait(const uint32_t* p, uint32_t target) {
  uint32_t v = 0u;
  #pragma unroll 1
  for (unsigned int i = 0; i < (1u << 22) && v < target; i++) asm volatile("ld.relaxed.gpu.global.u32 %0, [%1];" : "=r"(v) : "l"(p) : "memory");
}
__device__ __forceinline__ void fence_proxy_async_global() { asm volatile("fence.proxy.async.global;" ::: "memory"); }

constexpr int H_SPLIT = 1;
constexpr int PRE_B = 2;
__device__ __forceinline__ void load_parts(float4 (&pa)[4], float4 (&pb)[4], int t2) {
  #pragma unroll
  for (int k = 0; k < 4; k++) { pa[k] = ld_tagged4(g_modpart + k * 2 * T_D + t2 * 8); pb[k] = ld_tagged4(g_modpart + k * 2 * T_D + t2 * 8 + 4); }
}
__device__ __forceinline__ void finish_parts(float4 (&pa)[4], float4 (&pb)[4], int t2, uint32_t tab) {
  #pragma unroll 1
  for (unsigned int spin = 0; spin < (1u << 22); spin++) {
    bool ok = true;
    #pragma unroll
    for (int k = 0; k < 4; k++) ok &= tagged4(pa[k]) & tagged4(pb[k]);
    if (__all_sync(0xffffffffu, ok)) break;
    load_parts(pa, pb, t2);
  }
  #pragma unroll
  for (int k = 1; k < 4; k++) {
    pa[0].x += pa[k].x; pa[0].y += pa[k].y; pa[0].z += pa[k].z; pa[0].w += pa[k].w;
    pb[0].x += pb[k].x; pb[0].y += pb[k].y; pb[0].z += pb[k].z; pb[0].w += pb[k].w;
  }
  uint32_t m0 = pack_bf16(pa[0].x, pa[0].y), m1 = pack_bf16(pa[0].z, pa[0].w), m2 = pack_bf16(pb[0].x, pb[0].y), m3 = pack_bf16(pb[0].z, pb[0].w);
  if (t2 >= 128) { m0 = badd2(m0, 0x3F803F80u); m1 = badd2(m1, 0x3F803F80u); m2 = badd2(m2, 0x3F803F80u); m3 = badd2(m3, 0x3F803F80u); }
  sts_u32x4(tab + t2 * 16, m0, m1, m2, m3);
}
__device__ __forceinline__ void head_phase(uint32_t scr, uint32_t xs, uint32_t b_x, uint32_t b_go, uint32_t b_head, int t2, uint32_t zero, const bf16* __restrict__ x, const bf16* __restrict__ cvec, const bf16* __restrict__ w_mod) {
  const int lane = t2 & 31, w8 = t2 >> 5;
  const int cb = blockIdx.x & 31, ks = blockIdx.x >> 5;
  uint4 w[8], xv[2][4];
  const float cv = __bfloat162float(cvec[ks * 256 + t2]);
  #pragma unroll
  for (int i = 0; i < 8; i++) w[i] = ldg_nc_v4(w_mod + (size_t)(ks * 256 + (t2 >> 3) + 32 * i) * (6 * T_D) + cb * 64 + (t2 & 7) * 8);
  const int row0 = blockIdx.x * 16 + 2 * w8;
  sts_f32(scr + t2 * 4, silu_bf(cv));
  #pragma unroll 1
  for (uint32_t i = 0; i <= zero; i++) named_bar_sync(6, 384);
  TL_MARK2(1, t2 == 0);
  {
    float acc[8];
    #pragma unroll
    for (int j = 0; j < 8; j++) acc[j] = 0.f;
    #pragma unroll
    for (int i = 0; i < 8; i++) {
      fma8(acc, lds_f32(scr + ((t2 >> 3) + 32 * i) * 4), w[i]);
      if (i == 0 && t2 == 0) {
        mbar_expect_tx(b_x + (__float_as_uint(acc[0]) & zero), 32768);
        bulk_load_hint(xs, x + (size_t)blockIdx.x * 16 * T_D, 32768, b_x, policy_evict_first());
      }
    }
    #pragma unroll
    for (int j = 0; j < 4; j++) { const bool up = lane & 16; acc[j] = (up ? acc[4 + j] : acc[j]) + __shfl_xor_sync(0xffffffffu, up ? acc[j] : acc[4 + j], 16); }
    #pragma unroll
    for (int j = 0; j < 2; j++) { const bool up = lane & 8; acc[j] = (up ? acc[2 + j] : acc[j]) + __shfl_xor_sync(0xffffffffu, up ? acc[j] : acc[2 + j], 8); }
    sts_f32x2(scr + 1024 + w8 * 256 + (lane & 7) * 32 + (lane >> 3) * 8, acc[0], acc[1]);
  }
  named_bar_sync(5, 256);
  if (t2 < 64) {
    float sum = 0.f;
    #pragma unroll
    for (int i = 0; i < 8; i++) sum += lds_f32(scr + 1024 + i * 256 + t2 * 4);
    st_tagged(g_modpart + ks * 2 * T_D + cb * 64 + t2, sum);
    TL_MARK2(2, t2 == 0);
  }
  mbar_wait(b_x, 0);
  const bool first_cols = (__shfl_sync(0xffffffffu, w8, 0) & 3) == 0;
  float4 pa[4], pb[4];
  pa[0].x = 0.f;
  if (first_cols) load_parts(pa, pb, t2);
  #pragma unroll
  for (int r = 0; r < 2; r++)
    #pragma unroll
    for (int j = 0; j < 4; j++) xv[r][j] = lds_u32x4(xs + (2 * w8 + r) * 2048 + j * 512 + lane * 16);
  #pragma unroll
  for (int r = 0; r < 2; r++) {
    float v[4][8], sum = 0.f;
    #pragma unroll
    for (int j = 0; j < 4; j++) {
      unpack8(xv[r][j], v[j]);
      sum += ((v[j][0] + v[j][1]) + (v[j][2] + v[j][3])) + ((v[j][4] + v[j][5]) + (v[j][6] + v[j][7]));
    }
    #pragma unroll
    for (int o = 16; o > 0; o >>= 1) sum += __shfl_xor_sync(0xffffffffu, sum, o);
    const float mean = sum * (1.0f / T_D);
    float q = 0.f;
    #pragma unroll
    for (int j = 0; j < 4; j++)
      #pragma unroll
      for (int i = 0; i < 8; i++) { const float d = v[j][i] - mean; q = fmaf(d, d, q); }
    #pragma unroll
    for (int o = 16; o > 0; o >>= 1) q += __shfl_xor_sync(0xffffffffu, q, o);
    const uint32_t mb2 = pack_bf16(mean, mean);
    const float inv = rcp_approx(rbf(sqrt_approx(rbf(rbf(q * (1.0f / T_D)) + 1e-05f))));
    #pragma unroll
    for (int j = 0; j < 4; j++) {
      xv[r][j].x = ln_norm2(xv[r][j].x, mb2, inv); xv[r][j].y = ln_norm2(xv[r][j].y, mb2, inv);
      xv[r][j].z = ln_norm2(xv[r][j].z, mb2, inv); xv[r][j].w = ln_norm2(xv[r][j].w, mb2, inv);
    }
  }
  TL_MARK2(5, t2 == 0);
  #pragma unroll 1
  for (int ph = 0; ph < 2; ph++) {
    if (first_cols == (ph == 0)) finish_parts(pa, pb, t2, scr + 8192);
    named_bar_sync(5, 256);
    if (ph) break;
    TL_MARK2(7, t2 == 0);
    const uint4 sa = lds_u32x4(scr + 8192 + lane * 16), c1 = lds_u32x4(scr + 8192 + 2048 + lane * 16);
    #pragma unroll
    for (int r = 0; r < 2; r++)
      *reinterpret_cast<uint4*>(g_h + (size_t)(row0 + r) * T_D + lane * 8) = make_uint4(badd2(bmul2(xv[r][0].x, c1.x), sa.x), badd2(bmul2(xv[r][0].y, c1.y), sa.y),
                                                                                        badd2(bmul2(xv[r][0].z, c1.z), sa.z), badd2(bmul2(xv[r][0].w, c1.w), sa.w));
    named_bar_sync(5, 256);
    TL_MARK2(18, t2 == 0);
    if (t2 == 0) red_release_add(&g_hcnt[32 * (1 + (blockIdx.x >> 3))], 1u);
    TL_MARK2(11, t2 == 0);
  }
  TL_MARK2(6, t2 == 0);
  #pragma unroll
  for (int j = 1; j < 4; j++) {
    const uint4 sa = lds_u32x4(scr + 8192 + (j * 32 + lane) * 16), c1 = lds_u32x4(scr + 8192 + 2048 + (j * 32 + lane) * 16);
    #pragma unroll
    for (int r = 0; r < 2; r++) {
      xv[r][j].x = badd2(bmul2(xv[r][j].x, c1.x), sa.x); xv[r][j].y = badd2(bmul2(xv[r][j].y, c1.y), sa.y);
      xv[r][j].z = badd2(bmul2(xv[r][j].z, c1.z), sa.z); xv[r][j].w = badd2(bmul2(xv[r][j].w, c1.w), sa.w);
    }
  }
  __syncwarp();
  if (lane == 0) mbar_arrive(b_head + (xv[1][3].w & zero));
  mbar_wait(b_go, 0);
  #pragma unroll
  for (int j = 1; j < 4; j++)
    #pragma unroll
    for (int r = 0; r < 2; r++) *reinterpret_cast<uint4*>(g_h + (size_t)(row0 + r) * T_D + j * 256 + lane * 8) = xv[r][j];
  named_bar_arrive(8, 288);
}

#define MOD_AT (b_empty + 8)
#define MOD_PF 0
#define MOD_SPLIT 16
__device__ __forceinline__ void mod_rest(uint32_t scr, uint32_t b_go, int t, const bf16* __restrict__ cvec, const bf16* __restrict__ w_mod, const bf16* __restrict__ w_r) {
  const int lane = t & 31;
  #pragma unroll 1
  for (int i = t; i < T_D / 2; i += 64) {
    const uint32_t c2 = *reinterpret_cast<const uint32_t*>(cvec + 2 * i);
    sts_u32(scr + i * 4, pack_bf16(silu_bf(bflo(c2)), silu_bf(bfhi(c2))));
  }
  named_bar_sync(11, 64);
  const bf16* wp = w_mod + (size_t)(2 * (t >> 2)) * (6 * T_D) + 2 * T_D + blockIdx.x * 32 + (t & 3) * 8;
  float acc[8];
  #pragma unroll
  for (int i = 0; i < 8; i++) acc[i] = 0.f;
  #pragma unroll 1
  for (int i = 0; i < 32; i += 2) {
    if (i == MOD_SPLIT) mbar_wait(b_go, 0);
    const uint4 w0 = ldg_nc_v4(wp), w1 = ldg_nc_v4(wp + 6 * T_D), w2 = ldg_nc_v4(wp + 32 * 6 * T_D), w3 = ldg_nc_v4(wp + 33 * 6 * T_D);
    wp += 64 * 6 * T_D;
    const uint32_t s0 = lds_u32(scr + (i * 16 + (t >> 2)) * 4), s1 = lds_u32(scr + (i * 16 + 16 + (t >> 2)) * 4);
    fma8(acc, bflo(s0), w0); fma8(acc, bfhi(s0), w1); fma8(acc, bflo(s1), w2); fma8(acc, bfhi(s1), w3);
  }
  #pragma unroll
  for (int j = 0; j < 4; j++) { const bool up = lane & 16; acc[j] = (up ? acc[4 + j] : acc[j]) + __shfl_xor_sync(0xffffffffu, up ? acc[j] : acc[4 + j], 16); }
  #pragma unroll
  for (int j = 0; j < 2; j++) { const bool up = lane & 8; acc[j] = (up ? acc[2 + j] : acc[j]) + __shfl_xor_sync(0xffffffffu, up ? acc[j] : acc[2 + j], 8); }
  { const bool up = lane & 4; acc[0] = (up ? acc[1] : acc[0]) + __shfl_xor_sync(0xffffffffu, up ? acc[0] : acc[1], 4); }
  if (t >= 32) sts_f32(scr + 2048 + lane * 4, acc[0]);
  named_bar_sync(11, 64);
  if (__shfl_sync(0xffffffffu, t, 0) < 32) {
    const int kind = blockIdx.x >> 5;
    float v = rbf(acc[0] + lds_f32(scr + 2048 + lane * 4));
    const int col = (blockIdx.x & 31) * 32 + (lane & 3) * 8 + (lane >> 2);
    uint8_t* dst = g_col + (col >> 7) * 1536;
    if (kind == 2) v = rbf(1.0f + v);
    float vw = v * __bfloat162float(w_r[col]);
    if (kind == 2) {
      const int c = col & 127, i = (c & ~15) + ((c >> 1) & 3) * 4 + ((c >> 3) & 1) * 2 + (c & 1);
      reinterpret_cast<bf16*>(dst)[i] = __float2bfloat16_rn(vw);
      reinterpret_cast<bf16*>(dst)[128 + i] = __float2bfloat16_rn(vw - rbf(vw));
    }
    reinterpret_cast<bf16*>(dst + 512 + (kind & 1) * 512 + (kind >> 1) * 256)[col & 127] = __float2bfloat16_rn(v);
    #pragma unroll
    for (int o = 16; o > 0; o >>= 1) vw += __shfl_xor_sync(0xffffffffu, vw, o);
    if (lane == 0 && (kind == 1 || kind == 2)) g_scal[95 - blockIdx.x] = vw;
  }
  #pragma unroll 1
  for (int i = blockIdx.x * 64 + t; i < (int)(sizeof(g_mail) / 16); i += 128 * 64) reinterpret_cast<uint4*>(&g_mail)[i] = make_uint4(0u, 0u, 0u, 0u);
  named_bar_sync(11, 64);
  if (t == 0) red_release_add(&g_hcnt[0], 1u);
}

#define HPOL_A pol_normal()
#define HPOL_B pol_normal()
#define HMAP_A &tmOl
#define HMAP_B &tmWo
constexpr int AT_NBLK = T_SEQ / 128;
constexpr float AT_HEAD = 7.0f;
#define WO_LATE 12
constexpr int QP_STAG = 3;
constexpr int AT_SPLIT = 28, AT_PIN = 8, PINB = 4;
constexpr int AT_NFULL = 124;
constexpr int AT_PREG = 40, AT_CREG = 232;
constexpr uint32_t AT_SQ = 5 * 32768;
constexpr float AT_C = 0.08838834764831845f * 1.4426950408889634f;
constexpr float AT_RAW_LO = -16.0f, AT_RAW_HI = 24.0f;
constexpr float AT_RAW_SUM = 281474976710656.0f, AT_RAW_MIN = 9.094947017729282e-13f;
constexpr uint32_t AT_SBAR = AT_SQ + 65536 + 256;
constexpr uint32_t AT_SMEM = AT_SQ + 65536 + 3072;

__device__ __forceinline__ uint32_t ring_slot(uint32_t t) { return t - 5u * ((t * 205u) >> 10); }
__device__ __forceinline__ uint32_t qp_pos(uint32_t j, uint32_t it) { return 4u * it + (j & 3u) + ((j & 3u) == 3u ? it : 0u); }
__device__ __forceinline__ uint32_t ring_par(uint32_t t) { return ((t * 205u) >> 10) & 1u; }
__device__ __forceinline__ void softmax_rowmax(const float (&s)[64], float& mx0, float& mx1) {
  float a0 = fmaxf(s[0], s[1]), a1 = fmaxf(s[4], s[5]), a2 = fmaxf(s[8], s[9]), a3 = fmaxf(s[12], s[13]);
  float b0 = fmaxf(s[2], s[3]), b1 = fmaxf(s[6], s[7]), b2 = fmaxf(s[10], s[11]), b3 = fmaxf(s[14], s[15]);
  #pragma unroll
  for (int j = 4; j < 16; j += 4) {
    a0 = fmaxf(a0, fmaxf(s[4 * j + 0], s[4 * j + 1]));  b0 = fmaxf(b0, fmaxf(s[4 * j + 2], s[4 * j + 3]));
    a1 = fmaxf(a1, fmaxf(s[4 * j + 4], s[4 * j + 5]));  b1 = fmaxf(b1, fmaxf(s[4 * j + 6], s[4 * j + 7]));
    a2 = fmaxf(a2, fmaxf(s[4 * j + 8], s[4 * j + 9]));  b2 = fmaxf(b2, fmaxf(s[4 * j + 10], s[4 * j + 11]));
    a3 = fmaxf(a3, fmaxf(s[4 * j + 12], s[4 * j + 13])); b3 = fmaxf(b3, fmaxf(s[4 * j + 14], s[4 * j + 15]));
  }
  mx0 = fmaxf(fmaxf(a0, a1), fmaxf(a2, a3));
  mx1 = fmaxf(fmaxf(b0, b1), fmaxf(b2, b3));
  mx0 = fmaxf(mx0, __shfl_xor_sync(0xffffffffu, mx0, 1));
  mx1 = fmaxf(mx1, __shfl_xor_sync(0xffffffffu, mx1, 1));
  mx0 = fmaxf(mx0, __shfl_xor_sync(0xffffffffu, mx0, 2));
  mx1 = fmaxf(mx1, __shfl_xor_sync(0xffffffffu, mx1, 2));
}
__device__ __forceinline__ void softmax_sub(float (&s)[64], float mc0, float mc1) {
  #pragma unroll
  for (int j = 0; j < 16; j++) { s[4 * j] -= mc0; s[4 * j + 1] -= mc0; s[4 * j + 2] -= mc1; s[4 * j + 3] -= mc1; }
}
template <int LO, int HI>
__device__ __forceinline__ void softmax_exp(float (&s)[64]) {
  #pragma unroll
  for (int i = LO; i < HI; i++) s[i] = ex2_approx(s[i]);
}
__device__ __forceinline__ bool softmax_mode(const float (&s)[64], float& mc0, float& mc1) {
  softmax_rowmax(s, mc0, mc1);
  const bool raw = __all_sync(0xffffffffu, mc0 >= AT_RAW_LO && mc0 <= AT_RAW_HI && mc1 >= AT_RAW_LO && mc1 <= AT_RAW_HI);
  mc0 += AT_HEAD; mc1 += AT_HEAD;
  return raw;
}
__device__ __forceinline__ void rowsum_p(const uint32_t (&p)[32], uint32_t& t0, uint32_t& t1) {
  uint32_t a[16];
  #pragma unroll
  for (int i = 0; i < 8; i++) { a[2 * i] = badd2(p[4 * i], p[4 * i + 2]); a[2 * i + 1] = badd2(p[4 * i + 1], p[4 * i + 3]); }
  #pragma unroll
  for (int i = 0; i < 4; i++) { a[2 * i] = badd2(a[4 * i], a[4 * i + 2]); a[2 * i + 1] = badd2(a[4 * i + 1], a[4 * i + 3]); }
  t0 = badd2(badd2(a[0], a[2]), badd2(a[4], a[6]));
  t1 = badd2(badd2(a[1], a[3]), badd2(a[5], a[7]));
}
__device__ __forceinline__ void add_rowsum(const uint32_t (&p)[32], float& l0, float& l1) {
  uint32_t t0, t1;
  rowsum_p(p, t0, t1);
  l0 += bflo(t0) + bfhi(t0); l1 += bflo(t1) + bfhi(t1);
}
__device__ __forceinline__ void pack_p(uint32_t (&p)[32], const float (&s)[64]) {
  #pragma unroll
  for (int i = 0; i < 32; i++) p[i] = pack_bf16(s[2 * i], s[2 * i + 1]);
}
__device__ __noinline__ void attn_rows_exact(uint32_t sq, uint32_t so, int hsel, const bf16* __restrict__ kh, const bf16* __restrict__ vh) {
  const int warp = (threadIdx.x >> 5) & 3, lane = threadIdx.x & 31;
  const size_t hofs = (size_t)((blockIdx.x < 128 ? blockIdx.x >> 4 : 15) * 2 + hsel) * T_SEQ * T_DH;
  kh += hofs; vh += hofs;
  #pragma unroll 1
  for (int r = 16 * warp; r < 16 * warp + 16; r++) {
    const uint32_t ad = (lane >> 4) * 16384 + r * 128 + ((((lane & 15) >> 1) ^ (r & 7)) << 4) + (lane & 1) * 8;
    uint2 qv; asm volatile("ld.shared.v2.u32 {%0, %1}, [%2];" : "=r"(qv.x), "=r"(qv.y) : "r"(sq + ad) : "memory");
    const float q0 = bflo(qv.x), q1 = bfhi(qv.x), q2 = bflo(qv.y), q3 = bfhi(qv.y);
    float m = -INFINITY, l = 0.f, o0 = 0.f, o1 = 0.f, o2 = 0.f, o3 = 0.f;
    #pragma unroll 1
    for (int key = 0; key < T_SEQ; key++) {
      const uint2 kv = *reinterpret_cast<const uint2*>(kh + (size_t)key * T_DH + lane * 4);
      const uint2 vv = *reinterpret_cast<const uint2*>(vh + (size_t)key * T_DH + lane * 4);
      float sc = (q0 * bflo(kv.x) + q1 * bfhi(kv.x)) + (q2 * bflo(kv.y) + q3 * bfhi(kv.y));
      #pragma unroll
      for (int o = 16; o > 0; o >>= 1) sc += __shfl_xor_sync(0xffffffffu, sc, o);
      const float mn = fmaxf(m, sc);
      const float al = (m == mn) ? 1.0f : ex2_approx(m - mn), p = rbf(ex2_approx(sc - mn));
      m = mn;
      l = fmaf(l, al, p);
      o0 = fmaf(o0, al, p * bflo(vv.x)); o1 = fmaf(o1, al, p * bfhi(vv.x));
      o2 = fmaf(o2, al, p * bflo(vv.y)); o3 = fmaf(o3, al, p * bfhi(vv.y));
    }
    const float inv = rcp_approx(l);
    asm volatile("st.shared.v2.u32 [%0], {%1, %2};" :: "r"(so + ad), "r"(pack_bf16(o0 * inv, o1 * inv)), "r"(pack_bf16(o2 * inv, o3 * inv)) : "memory");
  }
}
__device__ __forceinline__ void issue_qk(float (&s)[64], const uint32_t (&q)[32], uint32_t k_lo) {
  wgmma_fence();
  wgmma_m64n128k16_rs<0>(s, q[0], q[1], q[2], q[3], k_lo, 0);
  wgmma_m64n128k16_rs<2>(s, q[4], q[5], q[6], q[7], k_lo, 1);
  wgmma_m64n128k16_rs<4>(s, q[8], q[9], q[10], q[11], k_lo, 1);
  wgmma_m64n128k16_rs<6>(s, q[12], q[13], q[14], q[15], k_lo, 1);
  wgmma_m64n128k16_rs<1024>(s, q[16], q[17], q[18], q[19], k_lo, 1);
  wgmma_m64n128k16_rs<1026>(s, q[20], q[21], q[22], q[23], k_lo, 1);
  wgmma_m64n128k16_rs<1028>(s, q[24], q[25], q[26], q[27], k_lo, 1);
  wgmma_m64n128k16_rs<1030>(s, q[28], q[29], q[30], q[31], k_lo, 1);
  wgmma_commit();
}
__device__ __forceinline__ void issue_pv(float (&o)[64], const uint32_t (&p)[32], uint32_t v_lo, int accumulate) {
  wgmma_fence();
  wgmma_m64n128k16_rs_tb<0>(o, p[0], p[1], p[2], p[3], v_lo, accumulate);
  wgmma_m64n128k16_rs_tb<128>(o, p[4], p[5], p[6], p[7], v_lo, 1);
  wgmma_m64n128k16_rs_tb<256>(o, p[8], p[9], p[10], p[11], v_lo, 1);
  wgmma_m64n128k16_rs_tb<384>(o, p[12], p[13], p[14], p[15], v_lo, 1);
  wgmma_m64n128k16_rs_tb<512>(o, p[16], p[17], p[18], p[19], v_lo, 1);
  wgmma_m64n128k16_rs_tb<640>(o, p[20], p[21], p[22], p[23], v_lo, 1);
  wgmma_m64n128k16_rs_tb<768>(o, p[24], p[25], p[26], p[27], v_lo, 1);
  wgmma_m64n128k16_rs_tb<896>(o, p[28], p[29], p[30], p[31], v_lo, 1);
  wgmma_commit();
}
__device__ __forceinline__ void block_end(uint32_t zero, uint32_t bar) {
  #pragma unroll 1
  for (uint32_t i = 0; i < zero; i++) mbar_arrive(bar);
}
__device__ __forceinline__ void rescale_o(float (&o)[64], float al0, float al1) {
  #pragma unroll
  for (int j = 0; j < 16; j++) { o[4 * j] *= al0; o[4 * j + 1] *= al0; o[4 * j + 2] *= al1; o[4 * j + 3] *= al1; }
}

__device__ __forceinline__ void stage_o(const float (&o)[64], float i0, float i1, uint32_t dst, int lane) {
  #pragma unroll
  for (int J = 0; J < 16; J += 2)
    stmatrix_x4(dst + (J >> 3) * 16384 + ((((J & 7) + (lane >> 4)) ^ (lane & 7)) << 4),
                pack_bf16(o[4 * J + 0] * i0, o[4 * J + 1] * i0), pack_bf16(o[4 * J + 2] * i1, o[4 * J + 3] * i1),
                pack_bf16(o[4 * J + 4] * i0, o[4 * J + 5] * i0), pack_bf16(o[4 * J + 6] * i1, o[4 * J + 7] * i1));
}
__device__ __forceinline__ bool finish_l(float& l0, float& l1) {
  l0 += __shfl_xor_sync(0xffffffffu, l0, 1); l1 += __shfl_xor_sync(0xffffffffu, l1, 1);
  l0 += __shfl_xor_sync(0xffffffffu, l0, 2); l1 += __shfl_xor_sync(0xffffffffu, l1, 2);
  const bool redo = __any_sync(0xffffffffu, !(l0 <= AT_RAW_SUM && l1 <= AT_RAW_SUM && l0 >= AT_RAW_MIN && l1 >= AT_RAW_MIN));
  l0 = rcp_approx(l0); l1 = rcp_approx(l1);
  return redo;
}
template <int J0>
__device__ __forceinline__ void stage_q(const float (&acc)[128], float c, uint32_t dst, int lane) {
  #pragma unroll
  for (int J = J0; J < J0 + 16; J += 2)
    stmatrix_x4(dst + (J >> 3) * 16384 + ((((J & 7) + (lane >> 4)) ^ (lane & 7)) << 4),
                pack_bf16(acc[4 * J + 0] * c, acc[4 * J + 1] * c), pack_bf16(acc[4 * J + 2] * c, acc[4 * J + 3] * c),
                pack_bf16(acc[4 * J + 4] * c, acc[4 * J + 5] * c), pack_bf16(acc[4 * J + 6] * c, acc[4 * J + 7] * c));
}
__device__ __forceinline__ void store_o(const CUtensorMap* tmO, uint32_t src, int head, int row) {
  tma_store_2d(tmO, src, head * T_DH, row);
  tma_store_2d(tmO, src + 16384, head * T_DH + 64, row);
  bulk_commit();
}
__device__ __forceinline__ void mma_bf16(float (&d)[4], uint32_t a0, uint32_t a1, uint32_t a2, uint32_t a3, uint32_t b0, uint32_t b1) {
  asm volatile("mma.sync.aligned.m16n8k16.row.col.f32.bf16.bf16.f32 {%0, %1, %2, %3}, {%4, %5, %6, %7}, {%8, %9}, {%0, %1, %2, %3};"
               : "+f"(d[0]), "+f"(d[1]), "+f"(d[2]), "+f"(d[3]) : "r"(a0), "r"(a1), "r"(a2), "r"(a3), "r"(b0), "r"(b1));
}
struct GemvSel { uint32_t lo0, hi0, lo1, hi1; };
__device__ __forceinline__ GemvSel gemv_sel(int lane) {
  const uint32_t lo = (lane & 8) ? 0x1044u : 0x4410u, hi = (lane & 8) ? 0x3244u : 0x4432u;
  GemvSel s; s.lo0 = (lane & 16) ? 0x4444u : lo; s.hi0 = (lane & 16) ? 0x4444u : hi; s.lo1 = (lane & 16) ? lo : 0x4444u; s.hi1 = (lane & 16) ? hi : 0x4444u;
  return s;
}
#define GEMV_B0(j, h, s) __byte_perm((j) < 2 ? (h).x : (h).y, 0u, ((j) & 1) ? (s).hi0 : (s).lo0)
#define GEMV_B1(j, h, s) __byte_perm((j) < 2 ? (h).x : (h).y, 0u, ((j) & 1) ? (s).hi1 : (s).lo1)
__device__ __forceinline__ float4 gemv_out(const float (&d)[4], int lane) {
  const bool tk = lane & 1;
  const float r0 = __shfl_xor_sync(0xffffffffu, tk ? d[0] : d[1], 1), r1 = __shfl_xor_sync(0xffffffffu, tk ? d[2] : d[3], 1);
  return tk ? make_float4(r0, d[1], r1, d[3]) : make_float4(d[0], r0, d[2], r1);
}
#define OG_NG 8
#define HOIST 1
#define PUT_N 2
#define H_STAG 2
#define NOZERO 1
#define PVPIN 0
#define QKPIN 0
#define ALIGN 1
#define AL_P 60
#define AL_SLEEP 1200
#define AL_MAX 800
#define AL_ADD 0
#define X_PF 0
#define POLL_NS 200
#define KV3D 1
#define W3D 1
#define OG_PRE 10
#define OG_JOBS 7
#define OG_GRP 7
#define LD_FIRST 1
#define LD_STAG (OG_GRP / 2)
constexpr int OG_ST = 5, OG_NKB = T_DQKV / 64 - OG_PRE, OG_MOE = T_F / 32;
__device__ __forceinline__ int pre_loc(int job) {
  const int step = ((job >> 4) << 2) + (job & 3);
  return (step < OG_JOBS ? 2 * step : step < 2 * OG_JOBS ? 2 * (step - OG_JOBS) + 1 : step) * 4 + ((job >> 2) & 3);
}
__device__ __forceinline__ int pre_kb(int i) { return (i >> 1) * 4 + (i & 1); }
__device__ __forceinline__ int own_kb(int i) { return i < (OG_PRE & ~1) ? pre_kb(i) + 2 : i + OG_PRE; }
constexpr int OG_POS = 8;
constexpr uint32_t OG_STAGE = 32768;
constexpr uint32_t OG_SCOL = AT_SBAR + 512;
constexpr uint32_t OG_SMISC = AT_SBAR + 2048;
constexpr int OG_XPOS = OG_POS + OG_NKB;
constexpr uint32_t OG_SWD = AT_SQ, OG_PSLOT = AT_SQ;
constexpr uint32_t OG_SWD1 = (OG_XPOS % OG_ST) * OG_STAGE;
constexpr uint32_t OG_XSLOT = AT_SQ + 32768;
constexpr uint32_t OG_OSLOT = ((OG_XPOS + 1) % OG_ST) * OG_STAGE;
constexpr uint32_t OG_SH2 = ((OG_XPOS + 2) % OG_ST) * OG_STAGE;
constexpr uint32_t OG_SRED = ((OG_XPOS + 3) % OG_ST) * OG_STAGE;
constexpr uint32_t OG_SSTAT = OG_SRED + 16384;
constexpr uint32_t OG_SGU = OG_SRED + 8192;
constexpr uint32_t OG_SFIN = OG_SGU + 256;
#define OGM 2
#define OG_MT(b) (((b) >> OGM) & 15)
#define OG_NT(b) (((b) & ((1 << OGM) - 1)) + (((b) >> (4 + OGM)) << OGM))
#define TAIL_SETUP \
  const uint32_t bar_full = sbase + AT_SBAR, bar_empty = bar_full + 40; \
  const uint32_t bar_wd = bar_full + 168, bar_col = bar_full + 176, bar_out = bar_full + 184, bar_end = bar_full + 192; \
  const uint32_t bar_key = bar_full + 200, bar_h2 = bar_full + 208, bar_sel = bar_full + 216; \
  const int mt = OG_MT(blockIdx.x), nt = OG_NT(blockIdx.x); \
  const int m0 = mt * 128, n0 = nt * 128; \
  const bool has_moe = (int)blockIdx.x < OG_MOE; \
  (void)bar_empty; (void)bar_wd; (void)bar_col; (void)bar_out; (void)bar_end; (void)bar_key; (void)bar_h2; (void)bar_sel; (void)m0; (void)n0; (void)has_moe;

__device__ __forceinline__ void tail_producer(uint32_t sbase, uint32_t ph, uint64_t pol, const CUtensorMap* tmA, const CUtensorMap* tmB, const CUtensorMap* tmX) {
  TAIL_SETUP
  uint32_t stage = OG_POS % OG_ST;
  int kb = 0;
  #pragma unroll 1
  for (int seg = 0; seg < 2; seg++) {
    mbar_wait(bar_full + 264, seg);
    fence_proxy_async_global();
    const int end = seg == 0 ? 32 - OG_PRE : OG_NKB;
    #pragma unroll 1
    for (; kb < end; kb++) {
      const uint32_t fb = bar_full + 8 * stage, sa = sbase + stage * OG_STAGE;
      const int k0 = own_kb(kb) * 64;
      mbar_wait(bar_empty + 8 * stage, ph);
      mbar_expect_tx(fb, OG_STAGE);
      tma_load_3d_hint(sa + 16384, tmB, k0, 2 * nt, fb, pol);
      tma_load_2d_hint(sa, tmA, k0, m0, fb, pol);
      if (++stage == OG_ST) { stage = 0; ph ^= 1; }
    }
  }
  if (has_moe) {
    mbar_wait(bar_empty + 8 * (OG_XPOS % OG_ST), ph);
    mbar_expect_tx(bar_wd, OG_STAGE);
    tma_load_3d_hint(sbase + OG_SWD1, tmX, blockIdx.x * 32, 8, bar_wd, pol);
  }
}

__device__ __forceinline__ uint32_t bfma2(uint32_t a, uint32_t b, uint32_t c) { uint32_t r; asm("fma.rn.bf16x2 %0, %1, %2, %3;" : "=r"(r) : "r"(a), "r"(b), "r"(c)); return r; }
__device__ __forceinline__ uint32_t out2(uint32_t x1, uint32_t mb2, uint32_t ih, uint32_t il, uint32_t c1, uint32_t sb, uint32_t gb) {
  const uint32_t d = bsub2(x1, mb2);
  const uint32_t h2 = badd2(bmul2(bfma2(d, ih, bmul2(d, il)), c1), sb);
  return badd2(x1, bmul2(gb, bfma2(h2, 0u, h2)));
}
#define OGTIME gtime()
#define PRE_N 1
#define PRE_PACE 150
#define X_PACE 200
#define WD_LATE 0
#define WD_PACE 300
__device__ __forceinline__ void tail_exchange(uint32_t sbase, const CUtensorMap* tmOut, const bf16* __restrict__ w_down, const bf16* __restrict__ w_r, const bf16* __restrict__ x, bf16* __restrict__ out) {
    TAIL_SETUP
    const int lane = threadIdx.x & 31, wi = __shfl_sync(0xffffffffu, threadIdx.x >> 5, 0);
    if (wi == 3) {
      mbar_wait(bar_full + 264, 0);
      if (blockIdx.x < AT_NFULL) {
        uint32_t a, b;
        asm volatile("ld.relaxed.gpu.global.u32 %0, [%1];" : "=r"(a) : "l"(g_smid + 32 + blockIdx.x - lane) : "memory");
        b = __shfl_down_sync(0xffffffffu, a, 1);
        unsigned int* tm = g_tmax + blockIdx.x - min((int)blockIdx.x, __ffs(__ballot_sync(0xffffffffu, b >= a)) - 1);
        mbar_wait(bar_full + 312, 0);
        if (lane == 0) {
          asm volatile("mov.u32 %0, %%globaltimer_lo;" : "=r"(a));
          asm volatile("red.relaxed.gpu.global.max.u32 [%0], %1;" :: "l"(tm), "r"(a) : "memory");
          __nanosleep(AL_SLEEP);
          asm volatile("ld.relaxed.gpu.global.u32 %0, [%1];" : "=r"(b) : "l"(tm) : "memory");
          b -= a;
          sts_u32(sbase + OG_SMISC + 32, (b < AL_MAX ? b * 13 / 8 : 0u) + AL_ADD);
          mbar_arrive(bar_full + 320);
        }
        named_bar_sync(15, 32);
      }
      mbar_wait(bar_full + 264, 1);
      float a = g_scal[lane], b = g_scal[32 + lane];
      #pragma unroll
      for (int i = 0; i < 3; i++) {
        const uint4 v = *reinterpret_cast<const uint4*>(g_col + nt * 1536 + i * 512 + lane * 16);
        sts_u32x4(sbase + OG_SCOL + i * 512 + lane * 16, v.x, v.y, v.z, v.w);
      }
      #pragma unroll
      for (int o = 16; o > 0; o >>= 1) { a += __shfl_xor_sync(0xffffffffu, a, o); b += __shfl_xor_sync(0xffffffffu, b, o); }
      if (lane == 0) sts_f32x2(sbase + OG_SMISC, a, b);
      const uint64_t pol = policy_evict_first();
      #pragma unroll 1
      for (int r = lane >> 4; r < 128; r += 4) {
        __nanosleep(X_PACE);
        #pragma unroll
        for (int j = 0; j < 4; j += 2)
          asm volatile("cp.async.cg.shared.global.L2::cache_hint [%0], [%1], 16, %2;" :: "r"(sbase + OG_XSLOT + (lane & 8) * 2048 + (r + j) * 128 + (((lane ^ (r + j)) & 7) << 4)),
                       "l"(x + (size_t)(m0 + r + j) * T_D + n0 + (lane & 15) * 8), "l"(pol) : "memory");
      }
      asm volatile("cp.async.wait_all;" ::: "memory");
      __syncwarp();
      if (lane == 0) mbar_arrive(bar_col);
    } else if (wi == 2) {
      if (elect_one()) {
        const uint32_t b_free = bar_full + (blockIdx.x < AT_NFULL ? 80 : 160);
        mbar_wait(b_free, 0); mbar_wait(b_free, 1);
        #pragma unroll 1
        for (unsigned int i = 0; i < (1u << 20) && ld_acquire(&g_hcnt[32 * (1 + mt) + 4 + (nt >> 1)]) == 0u; i++) __nanosleep(POLL_NS);
        TL_MARK2(23, true);
        fence_proxy_async_global();
        TL_MARK2(4, true);
        mbar_expect_tx(bar_full + 272, 32768);
        #pragma unroll 1
        for (int i = 0; i < PRE_N; i++) {
          bulk_load_hint(sbase + OG_PSLOT + i * (32768 / PRE_N), g_pre + pre_loc(mt * 4 + (nt >> 1)) * 4096 + (nt & 1) * 2048 + i * (2048 / PRE_N), 32768 / PRE_N,
                         bar_full + 272, policy_evict_first());
          if (PRE_N > 1) __nanosleep(PRE_PACE);
        }
      }
      named_bar_sync(14, 32);
      if (has_moe) {
        mbar_wait(bar_full + 96, 1); mbar_wait(bar_full + 304, 0);
        const uint64_t pol = policy_evict_first();
        #pragma unroll 1
        for (int r = 0; r < 32; r++) {
          __nanosleep(WD_PACE);
          #pragma unroll
          for (int j = 0; j < 2; j++)
            asm volatile("cp.async.cg.shared.global.L2::cache_hint [%0], [%1], 16, %2;" :: "r"(sbase + OG_SWD + (4 * j + (lane >> 3)) * 4096 + r * 128 + (((lane ^ r) & 7) << 4)),
                         "l"((const uint8_t*)w_down + (size_t)blockIdx.x * 65536 + r * 2048 + j * 512 + lane * 16), "l"(pol) : "memory");
        }
        asm volatile("cp.async.wait_all;" ::: "memory");
        __syncwarp();
        if (lane == 0) mbar_arrive(bar_wd);
      }
    }
    const uint4 wrv = ldg_nc_v4(w_r + threadIdx.x * 8);
    mbar_wait(bar_end, 0);
    TL_MARK2(22, lane == 0);
    if (wi == 0) {
      uint32_t k1 = 0u, k2 = 0u;
      #pragma unroll 1
      for (unsigned int spin = 0; spin < (1u << 22) && __any_sync(0xffffffffu, k1 == 0u); spin++) asm volatile("ld.relaxed.gpu.global.u32 %0, [%1];" : "=r"(k1) : "l"(g_key + lane) : "memory");
      TL_MARK2(28, lane == 0);
      warp_top2(k1, k2);
      if (lane == 0) {
        const uint32_t r1 = 0xffffu - (k1 & 0xffffu), r2 = 0xffffu - (k2 & 0xffffu);
        sts_u32x4(sbase + OG_SMISC + 64, r1, r2, (r1 >> 7) * 2, (r2 >> 7) * 2 + ((r1 >> 7) == (r2 >> 7)));
        mbar_arrive(bar_sel);
      }
    } else if (wi < 3) {
          mbar_wait(bar_key, 0);
          const uint4 kk = lds_u32x4(sbase + OG_SSTAT + 1024 + lane * 16);
          uint32_t k1 = max(kk.x, kk.y), k2 = min(kk.x, kk.y);
          k2 = max(max(k2, min(kk.z, kk.w)), min(k1, max(kk.z, kk.w))); k1 = max(k1, max(kk.z, kk.w));
          warp_top2(k1, k2);
          if (wi == 1) {
            if (lane == 0 && nt == (mt & 7)) st_relaxed2(g_key + mt * 2, k1, k2);
            TL_MARK2(27, lane == 0);
          } else {
            const uint32_t r = (~((lane & 16) ? k2 : k1)) & 127u, ch = lane & 15;
            const uint2 st = lds_u32x2(sbase + OG_SSTAT + r * 8);
            const uint4 xc = lds_u32x4(sbase + OG_XSLOT + (ch >> 3) * 16384 + r * 128 + (((ch ^ r) & 7) << 4));
            const uint4 c1 = lds_u32x4(sbase + OG_SCOL + 768 + ch * 16), sh = lds_u32x4(sbase + OG_SCOL + 1024 + ch * 16);
            const float inr = __uint_as_float(st.y);
            float* dst = reinterpret_cast<float*>(g_cand + (mt * 2 + (lane >> 4)) * 256 + nt * 16 + ch);
            st_tagged4(dst + 512, __uint_as_float(ln_mod2(xc.x, st.x, inr, c1.x, sh.x)), __uint_as_float(ln_mod2(xc.y, st.x, inr, c1.y, sh.y)),
                       __uint_as_float(ln_mod2(xc.z, st.x, inr, c1.z, sh.z)), __uint_as_float(ln_mod2(xc.w, st.x, inr, c1.w, sh.w)));
            st_tagged4(dst, __uint_as_float(xc.x), __uint_as_float(xc.y), __uint_as_float(xc.z), __uint_as_float(xc.w));
          }
    }
    mbar_wait(bar_sel, 0);
    const uint4 sel = lds_u32x4(sbase + OG_SMISC + 64);
    const int sel0 = (int)sel.x, sel1 = (int)sel.y;
    {
      const float* src0 = reinterpret_cast<const float*>(g_cand + sel.z * 256 + 128 + threadIdx.x);
      const float* src1 = reinterpret_cast<const float*>(g_cand + sel.w * 256 + 128 + threadIdx.x);
      float4 h0, h1;
      #pragma unroll 1
      for (unsigned int spin = 0; spin < (1u << 20); spin++) { h0 = ld_tagged4(src0); h1 = ld_tagged4(src1); if (__all_sync(0xffffffffu, tagged4(h0) & tagged4(h1))) break; }
      sts_f32x4(sbase + OG_SH2 + threadIdx.x * 16, h0.x, h0.y, h0.z, h0.w);
      sts_f32x4(sbase + OG_SH2 + 2048 + threadIdx.x * 16, h1.x, h1.y, h1.z, h1.w);
      __syncwarp();
      if (lane == 0) mbar_arrive(bar_h2);
      TL_MARK2(12, lane == 0);
      if (blockIdx.x >> 6) h0 = h1;
      float v[8], wr[8];
      unpack8(make_uint4(__float_as_uint(h0.x), __float_as_uint(h0.y), __float_as_uint(h0.z), __float_as_uint(h0.w)), v); unpack8(wrv, wr);
      float r = 0.f;
      #pragma unroll
      for (int i = 0; i < 8; i++) r = fmaf(v[i], wr[i], r);
      #pragma unroll
      for (int o = 16; o > 0; o >>= 1) r += __shfl_xor_sync(0xffffffffu, r, o);
      if (lane == 0) sts_f32(sbase + OG_SMISC + 192 + wi * 4, r);
    }
    mbar_wait(bar_out, 0);
    if ((sel0 >> 7) == mt || (sel1 >> 7) == mt) {
      #pragma unroll 2
      for (int i = 0; i < 16; i++) {
        const int r = i * 8 + (threadIdx.x >> 4), ch = threadIdx.x & 15;
        if (m0 + r != sel0 && m0 + r != sel1)
          *reinterpret_cast<uint4*>(out + (size_t)(m0 + r) * T_D + n0 + ch * 8) =
              lds_u32x4(sbase + OG_OSLOT + (ch >> 3) * 16384 + r * 128 + (((ch & 7) ^ (r & 7)) << 4));
      }
    } else if (threadIdx.x == 0) {
      tma_store_2d(tmOut, sbase + OG_OSLOT, n0, m0);
      tma_store_2d(tmOut, sbase + OG_OSLOT + 16384, n0 + 64, m0);
      bulk_commit();
    }
    if (blockIdx.x == 0 && threadIdx.x < 68) *reinterpret_cast<uint4*>(g_hcnt + 32 * (threadIdx.x >> 2) + 4 * (threadIdx.x & 3)) = make_uint4(0u, 0u, 0u, 0u);
    if (threadIdx.x < 64) g_modpart[blockIdx.x * 64 + threadIdx.x] = 0.f;
    if (ALIGN && threadIdx.x == 64) g_tmax[blockIdx.x] = 0u;
    {
      const int tk = blockIdx.x >> 6, c0 = (blockIdx.x & 63) * 16;
      const uint32_t gb2 = *reinterpret_cast<const uint32_t*>(g_col + (c0 >> 7) * 1536 + 512 + 768 + ((c0 & 127) + (threadIdx.x & 14)) * 2);
      const uint32_t* xp = reinterpret_cast<const uint32_t*>(g_cand + (tk ? sel.w : sel.z) * 256) + ((c0 + (threadIdx.x & 14)) >> 1);
      uint32_t x2 = 0u;
      #pragma unroll 1
      for (unsigned int spin = 0; spin < (1u << 20) && __any_sync(0xffffffffu, x2 == 0u); spin++) asm volatile("ld.relaxed.gpu.global.u32 %0, [%1];" : "=r"(x2) : "l"(xp) : "memory");
      const float* src = g_ypart + (size_t)((threadIdx.x >> 2) * 2 + tk) * T_D + c0 + (threadIdx.x & 3) * 4;
      const bool four = threadIdx.x < (OG_MOE - 96) * 4;
      if (threadIdx.x == 0) hint_wait(CNT_Y, (uint32_t)OG_MOE);
      named_bar_sync(10, 128);
      float4 p0, p1, p2, p3;
      #pragma unroll 1
      for (unsigned int spin = 0; spin < (1u << 20); spin++) {
        p0 = ld_tagged4(src); p1 = ld_tagged4(src + 64 * T_D); p2 = ld_tagged4(src + 128 * T_D); p3 = ld_tagged4(four ? src + 192 * T_D : src);
        if (__all_sync(0xffffffffu, tagged4(p0) & tagged4(p1) & tagged4(p2) & tagged4(p3))) break;
      }
      if (four) { p2.x += p3.x; p2.y += p3.y; p2.z += p3.z; p2.w += p3.w; }
      p0.x = (p0.x + p1.x) + p2.x; p0.y = (p0.y + p1.y) + p2.y; p0.z = (p0.z + p1.z) + p2.z; p0.w = (p0.w + p1.w) + p2.w;
      #pragma unroll
      for (int o = 4; o <= 16; o <<= 1) {
        p0.x += __shfl_xor_sync(0xffffffffu, p0.x, o); p0.y += __shfl_xor_sync(0xffffffffu, p0.y, o);
        p0.z += __shfl_xor_sync(0xffffffffu, p0.z, o); p0.w += __shfl_xor_sync(0xffffffffu, p0.w, o);
      }
      if (lane < 4) sts_f32x4(sbase + OG_SFIN + (threadIdx.x >> 5) * 64 + lane * 16, p0.x, p0.y, p0.z, p0.w);
      named_bar_sync(10, 128);
      TL_MARK2(21, threadIdx.x == 0);
      if (threadIdx.x < 16) {
        const uint32_t ya = sbase + OG_SFIN + threadIdx.x * 4, rp = sbase + OG_SMISC + 192;
        float y = (lds_f32(ya) + lds_f32(ya + 64)) + (lds_f32(ya + 128) + lds_f32(ya + 192));
        const float r = rbf((lds_f32(rp) + lds_f32(rp + 4)) + (lds_f32(rp + 8) + lds_f32(rp + 12)));
        const float rs = rbf(sigmoid_f(r));
        const uint32_t h2p = lds_u32(sbase + OG_SH2 + tk * 2048 + (c0 + (threadIdx.x & 14)) * 2);
        const float fh = (lane & 1) ? bfhi(h2p) : bflo(h2p);
        y = rbf(y);
        y = rbf(y * rs);
        const float upd = rbf(rbf(fh * 0.0f) + y);
        out[(size_t)(tk ? sel1 : sel0) * T_D + c0 + threadIdx.x] =
            __float2bfloat16_rn(((lane & 1) ? bfhi(x2) : bflo(x2)) + rbf(((lane & 1) ? bfhi(gb2) : bflo(gb2)) * rbf(fh + upd)));
      }
      if (threadIdx.x == 0) bulk_wait_read<0>();
    }
    TL_END(4, threadIdx.x == 0);
}

__device__ __forceinline__ void load_pre(uint4* pre, uint32_t sbase, uint32_t buf, int t2) {
  mbar_wait(sbase + AT_SBAR + 272, 0);
  #pragma unroll
  for (int i = 0; i < 8; i++) pre[i] = lds_u32x4(sbase + buf + i * 4096 + t2 * 16);
}
__device__ __forceinline__ void tail_consumer(uint32_t sbase, const uint4 (&pre)[8], int cwg, const bf16* __restrict__ w_gate, const bf16* __restrict__ w_up) {
    TAIL_SETUP
    const int tid = threadIdx.x & 127, t2 = threadIdx.x - 128;
    const int warp = tid >> 5, lane = tid & 31, w8 = t2 >> 5;
    const uint32_t dbase = (sbase & 0x3FFFFu) >> 4;
    const uint32_t a_base = dbase + ((cwg * 8192) >> 4) + (1u << 16);
    const uint32_t b_base = dbase + (16384 >> 4) + (512u << 16);
    TL_MARK2(25, threadIdx.x == 128);
    const uint64_t pol = policy_evict_first();
    const bf16* pw = ((lane & 16) ? w_up : w_gate) + (size_t)(w8 * 128 + (lane & 3) * 4) * T_F + (has_moe ? blockIdx.x : 0) * 32 + ((lane >> 2) & 3) * 8;
    uint4 wv[32];
    float acc[64];
    #pragma unroll
    for (int i = 0; i < 8; i++) {
      acc[8 * i] = bflo(pre[i].x); acc[8 * i + 1] = bfhi(pre[i].x); acc[8 * i + 2] = bflo(pre[i].y); acc[8 * i + 3] = bfhi(pre[i].y);
      acc[8 * i + 4] = bflo(pre[i].z); acc[8 * i + 5] = bfhi(pre[i].z); acc[8 * i + 6] = bflo(pre[i].w); acc[8 * i + 7] = bfhi(pre[i].w);
    }
    if (blockIdx.x < AT_NFULL) {
      const uint32_t c0 = clock_lo();
      mbar_wait(bar_full + 320, 0);
      const uint32_t d = lds_u32(sbase + OG_SMISC + 32);
      while (clock_lo() - c0 < d) {}
    }
    {
      uint32_t stage = OG_POS % OG_ST, phase = (OG_POS / OG_ST) & 1, prev = 12;
      int kb = 0;
      #pragma unroll
      for (int g = 0; g <= OG_NG; g++) {
        const int end = g == OG_NG ? OG_NKB : LD_FIRST + g * OG_GRP + LD_STAG * cwg;
        #pragma unroll 1
        do {
          mbar_wait(bar_full + 8 * stage, phase);
          const uint32_t a_lo = a_base + stage * (OG_STAGE >> 4), b_lo = b_base + stage * (OG_STAGE >> 4);
          wgmma_fence();
          wgmma_m64n128k16_ss_tb<0, 0>(acc, a_lo, b_lo, 1);
          wgmma_m64n128k16_ss_tb<2, 128>(acc, a_lo, b_lo, 1);
          wgmma_m64n128k16_ss_tb<4, 256>(acc, a_lo, b_lo, 1);
          wgmma_m64n128k16_ss_tb<6, 384>(acc, a_lo, b_lo, 1);
          wgmma_commit();
          wgmma_wait<1>();
          if (tid == 0) mbar_arrive(bar_empty + 8 * prev);
          prev = stage;
          if (++stage == OG_ST) { stage = 0; phase ^= 1; }
        } while (++kb < end);
        #pragma unroll
        for (int j = 4 * g; j < 4 * g + 4 && j < 32; j++) wv[j] = ldg_stream_v4(pw + (size_t)(16 * (j >> 2) + (j & 3)) * T_F, pol);
      }
    }
    mbar_wait(bar_col, 0);
    if (__builtin_expect(!has_moe, 0)) {
      load_pre(wv, sbase, AT_SQ, t2);
    }
    wgmma_wait<0>();
    fence_regs(acc);
    if (__builtin_expect(!has_moe, 0)) {
      #pragma unroll
      for (int i = 0; i < 8; i++) {
        acc[8 * i] += bflo(wv[i].x); acc[8 * i + 1] += bfhi(wv[i].x); acc[8 * i + 2] += bflo(wv[i].y); acc[8 * i + 3] += bfhi(wv[i].y);
        acc[8 * i + 4] += bflo(wv[i].z); acc[8 * i + 5] += bfhi(wv[i].z); acc[8 * i + 6] += bflo(wv[i].w); acc[8 * i + 7] += bfhi(wv[i].w);
      }
    }
    if (tid == 0) mbar_arrive(bar_end);
    TL_MARK2(9, lane == 0);
    const int q2 = 2 * (lane & 3);
    const uint32_t frag = (64 * cwg + 16 * warp + (lane & 7) + 8 * ((lane >> 3) & 1)) * 128;
    const int fsw = lane & 7, fhi = lane >> 4;
    {
      float dl[4] = {0.f, 0.f, 0.f, 0.f}, da[4] = {0.f, 0.f, 0.f, 0.f}, db[4] = {0.f, 0.f, 0.f, 0.f};
      const uint32_t tb = sbase + OG_SCOL + (lane & 8) * 32 + (lane & 3) * 8, g = lane >> 2;
      const uint32_t msk = (g == 1 || g == 2) ? 0xffffffffu : 0u, one = g == 0 ? 0x3F803F80u : 0u;
      #pragma unroll
      for (int J = 0; J < 16; J += 2) {
        const uint32_t ad = sbase + OG_XSLOT + (J >> 3) * 16384 + frag + ((((J & 7) + fhi) ^ fsw) << 4);
        uint32_t xr[4];
        ldmatrix_x4(ad, xr[0], xr[1], xr[2], xr[3]);
        const uint2 cw = lds_u32x2(tb + J * 16);
        #pragma unroll
        for (int h = 0; h < 2; h++) {
          const uint32_t ga = lds_u32(sbase + OG_SCOL + 512 + (8 * (J + h) + q2) * 2);
          xr[2 * h] = badd2(xr[2 * h], bmul2(ga, pack_bf16(acc[4 * (J + h)], acc[4 * (J + h) + 1])));
          xr[2 * h + 1] = badd2(xr[2 * h + 1], bmul2(ga, pack_bf16(acc[4 * (J + h) + 2], acc[4 * (J + h) + 3])));
        }
        stmatrix_x4(ad, xr[0], xr[1], xr[2], xr[3]);
        mma_bf16(dl, xr[0], xr[1], xr[2], xr[3], (cw.x & msk) | one, (cw.y & msk) | one);
        mma_bf16(da, xr[0], xr[1], xr[2], xr[3], xr[0], xr[2]);
        mma_bf16(db, xr[0], xr[1], xr[2], xr[3], xr[1], xr[3]);
      }
      {
        const int dsrc = (lane & ~3) + (g >> 1);
        const float qa = __shfl_sync(0xffffffffu, (g & 1) ? da[1] : da[0], dsrc), qb = __shfl_sync(0xffffffffu, (g & 1) ? db[3] : db[2], dsrc);
        const float e0 = __shfl_xor_sync(0xffffffffu, (lane & 1) ? dl[0] : dl[2], 1), e1 = __shfl_xor_sync(0xffffffffu, dl[3], 1);
        if ((lane & 3) < 2) {
          const bool hi = lane & 1;
          st_tagged4(reinterpret_cast<float*>(g_part1 + ((mt * 8 + w8) * 8 + nt) * 16 + g + (hi ? 8 : 0)),
                     hi ? e0 : dl[0], hi ? qb : qa, hi ? e1 + dl[2] : dl[1] + e0, 1.0f);
        }
      }
    }
    TL_MARK2(10, lane == 0);
    uint4 wd[16];
    if (has_moe) mbar_wait(bar_wd, 0);
    #pragma unroll
    for (int i = 0; i < 16; i++) wd[i] = lds_u32x4(sbase + (cwg ? OG_SWD1 : OG_SWD) + warp * 8192 + (i >> 3) * 4096 + (i & 6) * 512 + (i & 1) * 128 + (lane & 3) * 256 + (((lane >> 2) ^ (2 * (lane & 3) + (i & 1))) << 4));
    {
      const float* src = reinterpret_cast<const float*>(g_part1 + ((mt * 8 + w8) * 8 + (lane & 1) * 4) * 16 + (lane >> 1));
      float4 v, v1, v2, v3;
      #pragma unroll 1
      for (unsigned int spin = 0; spin < (1u << 22); spin++) {
        v = ld_tagged4(src); v1 = ld_tagged4(src + 64); v2 = ld_tagged4(src + 128); v3 = ld_tagged4(src + 192);
        if (__all_sync(0xffffffffu, tagged4(v) & tagged4(v1) & tagged4(v2) & tagged4(v3))) break;
        __nanosleep(100);
      }
      __syncwarp();
      TL_MARK2(26, lane == 0);
      v.x = (v.x + v1.x) + (v2.x + v3.x); v.y = (v.y + v1.y) + (v2.y + v3.y); v.z = (v.z + v1.z) + (v2.z + v3.z);
      v.x += __shfl_xor_sync(0xffffffffu, v.x, 1); v.y += __shfl_xor_sync(0xffffffffu, v.y, 1); v.z += __shfl_xor_sync(0xffffffffu, v.z, 1);
      const float mean = v.x * (1.0f / T_D);
      const float var = fmaxf(fmaf(-mean, mean, v.y * (1.0f / T_D)), 0.f);
      const uint32_t mb2 = pack_bf16(mean, mean);
      const float inv = rcp_approx(rbf(sqrt_approx(rbf(rbf(var) + 1e-05f))));
      {
        const float2 sc = lds_f32x2(sbase + OG_SMISC);
        const uint32_t key = rank_key(rbf(fmaf(fmaf(-bflo(mb2), sc.x, v.z), inv, sc.y)), m0 + 16 * w8 + (lane >> 1));
        mbar_wait(bar_end, 0);
        if (lane & 1) sts_u32(sbase + OG_SSTAT + 1024 + (16 * w8 + (lane >> 1)) * 4, key);
        else sts_u32x2(sbase + OG_SSTAT + (16 * w8 + (lane >> 1)) * 8, mb2, __float_as_uint(inv));
        __syncwarp();
        if (lane == 0) mbar_arrive(bar_key);
      }
      const uint32_t ih = pack_bf16(inv, inv), il = pack_bf16(inv - bflo(ih), inv - bflo(ih));
      const uint32_t mba = __shfl_sync(0xffffffffu, mb2, 2 * (lane >> 2)), mbb = __shfl_sync(0xffffffffu, mb2, 2 * (lane >> 2) + 16);
      const uint32_t iha = __shfl_sync(0xffffffffu, ih, 2 * (lane >> 2)), ihb = __shfl_sync(0xffffffffu, ih, 2 * (lane >> 2) + 16);
      const uint32_t ila = __shfl_sync(0xffffffffu, il, 2 * (lane >> 2)), ilb = __shfl_sync(0xffffffffu, il, 2 * (lane >> 2) + 16);
      #pragma unroll 2
      for (int J = 0; J < 16; J += 2) {
        const uint32_t off = (J >> 3) * 16384 + frag + ((((J & 7) + fhi) ^ fsw) << 4);
        uint32_t xr[4];
        ldmatrix_x4(sbase + OG_XSLOT + off, xr[0], xr[1], xr[2], xr[3]);
        #pragma unroll
        for (int h = 0; h < 2; h++) {
          const uint32_t ca = sbase + OG_SCOL + 512 + (8 * (J + h) + q2) * 2;
          const uint32_t c1 = lds_u32(ca + 256), sh = lds_u32(ca + 512), gb = lds_u32(ca + 768);
          xr[2 * h] = out2(xr[2 * h], mba, iha, ila, c1, sh, gb);
          xr[2 * h + 1] = out2(xr[2 * h + 1], mbb, ihb, ilb, c1, sh, gb);
        }
        stmatrix_x4(sbase + OG_OSLOT + off, xr[0], xr[1], xr[2], xr[3]);
      }
      fence_proxy_async();
      __syncwarp();
      if (lane == 0) mbar_arrive(bar_out);
      TL_MARK2(24, lane == 0);
    }
    if (has_moe) mbar_wait(bar_h2, 0);
    TL_MARK2(13, lane == 0);
    if (has_moe) {
      const GemvSel sel = gemv_sel(lane);
      {
        float d[4][4];
        #pragma unroll
        for (int c = 0; c < 4; c++) { d[c][0] = 0.f; d[c][1] = 0.f; d[c][2] = 0.f; d[c][3] = 0.f; }
        #pragma unroll
        for (int st = 0; st < 8; st++) {
          const uint2 hb = lds_u32x2(sbase + OG_SH2 + ((lane >> 2) & 1) * 2048 + (w8 * 128 + st * 16 + (lane & 3) * 4) * 2);
          #pragma unroll
          for (int j = 0; j < 4; j++) mma_bf16(d[j], wv[4 * st + j].x, wv[4 * st + j].y, wv[4 * st + j].z, wv[4 * st + j].w, GEMV_B0(j, hb, sel), GEMV_B1(j, hb, sel));
        }
        #pragma unroll
        for (int e = 0; e < 4; e++) d[0][e] = (d[0][e] + d[1][e]) + (d[2][e] + d[3][e]);
        const float4 r = gemv_out(d[0], lane);
        sts_f32x4(sbase + OG_SRED + w8 * 512 + (((lane >> 4) * 2 + (lane & 1)) * 32 + ((lane >> 2) & 3) * 8 + (lane & 2) * 2) * 4, r.x, r.y, r.z, r.w);
      }
      named_bar_sync(9, 256);
      if (t2 < 64) {
        float gp[8], up[8];
        #pragma unroll
        for (int w = 0; w < 8; w++) { gp[w] = lds_f32(sbase + OG_SRED + w * 512 + t2 * 4); up[w] = lds_f32(sbase + OG_SRED + w * 512 + 256 + t2 * 4); }
        const float gs = ((gp[0] + gp[1]) + (gp[2] + gp[3])) + ((gp[4] + gp[5]) + (gp[6] + gp[7]));
        const float us = ((up[0] + up[1]) + (up[2] + up[3])) + ((up[4] + up[5]) + (up[6] + up[7]));
        asm volatile("st.shared.u16 [%0], %1;" :: "r"(sbase + OG_SGU + ((t2 & ~15) + ((t2 >> 1) & 3) * 4 + ((t2 >> 3) & 1) * 2 + (t2 & 1)) * 2), "h"((uint16_t)pack_bf16(silu_bf(rbf(gs)) * rbf(us), 0.f)) : "memory");
      }
      named_bar_sync(9, 256);
      TL_MARK2(20, threadIdx.x == 128);
      float d[4][4];
      #pragma unroll
      for (int c = 0; c < 4; c++) { d[c][0] = 0.f; d[c][1] = 0.f; d[c][2] = 0.f; d[c][3] = 0.f; }
      #pragma unroll
      for (int st = 0; st < 2; st++) {
        const uint2 g = lds_u32x2(sbase + OG_SGU + ((lane >> 2) & 1) * 64 + st * 32 + (lane & 3) * 8);
        #pragma unroll
        for (int j = 0; j < 4; j++) {
          const uint32_t b0 = GEMV_B0(j, g, sel), b1 = GEMV_B1(j, g, sel);
          mma_bf16(d[j & 1], wd[4 * st + j].x, wd[4 * st + j].y, wd[4 * st + j].z, wd[4 * st + j].w, b0, b1);
          mma_bf16(d[2 + (j & 1)], wd[8 + 4 * st + j].x, wd[8 + 4 * st + j].y, wd[8 + 4 * st + j].z, wd[8 + 4 * st + j].w, b0, b1);
        }
      }
      #pragma unroll
      for (int e = 0; e < 4; e++) { d[0][e] += d[1][e]; d[2][e] += d[3][e]; }
      const float4 y0 = gemv_out(d[0], lane), y1 = gemv_out(d[2], lane);
      float* yp = g_ypart + (size_t)(blockIdx.x * 2 + (lane & 1)) * T_D + w8 * 128 + (lane >> 2) * 8 + (lane & 2) * 2;
      st_tagged4(yp, y0.x, y0.y, y0.z, y0.w);
      st_tagged4(yp + 64, y1.x, y1.y, y1.z, y1.w);
      named_bar_sync(9, 256);
      if (t2 == 0) hint_arrive(CNT_Y);
    }
    TL_MARK2(14, threadIdx.x == 128);
    TL_CLK(4, 1, threadIdx.x == 128);
}

#define OG_JOBS2 (16 - OG_JOBS)
__device__ __forceinline__ int help_njobs() { return blockIdx.x < 128 ? OG_JOBS : OG_JOBS2; }
__device__ __forceinline__ int help_job(int i) {
  const int step = i + (blockIdx.x < 128 ? 0 : OG_JOBS);
  return (step & ~3) * 4 + (blockIdx.x & 3) * 4 + (step & 3);
}
__device__ __noinline__ void store_warp(uint32_t sbase, const CUtensorMap* tmO, int item0, int n_items) {
  if (elect_one()) {
    const uint32_t bars = sbase + AT_SBAR, b_q0 = bars + 80, b_ob = bars + 96, b_ordy = bars + 104, b_acq = bars + 264;
    const unsigned int* cnt = &g_hcnt[32 * (1 + OG_MT(blockIdx.x)) + 2];
    #pragma unroll 1
    for (int q = 0; q < 4 * n_items; q++) {
      const int item = item0 + (q >> 2) * 128, h = (q >> 1) & 1, w = q & 1;
      const bool last = (q >> 2) == n_items - 1;
      if (q == 4 * n_items - 4) { mbar_wait(bars + 288, 0); red_release_add(&g_hcnt[1], 1u); }
      mbar_wait(b_ordy + 8 * (q & 3), q >> 2);
      store_o(tmO, (h ? (last ? sbase + AT_SQ + 32768 : sbase + 2 * 32768) : sbase + AT_SQ) + w * 8192, (item >> 4) * 2 + h, (item & 15) * 128 + w * 64);
      if (w) {
        bulk_wait_read<0>();
        mbar_arrive(h ? b_ob : b_q0);
        bulk_wait<0>();
        fence_proxy_async_global();
        red_release_add(&g_hcnt[32 * (1 + (item & 15)) + 2 + (item >> 7)], h ? 1u : 256u);
        if (blockIdx.x < 128 && q == (n_items == 2 ? 5 : 3)) { spin_until(cnt, 0x808u); mbar_arrive(b_acq); }
      }
    }
    if (n_items == 1) {
      #pragma unroll 1
      for (int i = 0; i < help_njobs(); i++) {
        mbar_wait(b_acq + 16, i & 1);
        TL_MARK2(23, i == OG_JOBS - 1);
        red_release_add(&g_hcnt[32 * (1 + (help_job(i) >> 2)) + 4 + (help_job(i) & 3)], 1u);
        TL_MARK2(4, i == OG_JOBS - 1);
        if (i == PRE_X - 1) { spin_until(&g_hcnt[1], 132u); mbar_arrive(b_acq + 32); }
      }
    }
    if (blockIdx.x < 128) { spin_until(&g_hcnt[0], 128u); spin_until(cnt + 1, 0x808u); mbar_arrive(b_acq); }
  }
}

__global__ void __launch_bounds__(384, 1)
fused_kernel(const __grid_constant__ CUtensorMap tmH, const __grid_constant__ CUtensorMap tmW, const __grid_constant__ CUtensorMap tmK,
            const __grid_constant__ CUtensorMap tmV, const __grid_constant__ CUtensorMap tmO, const __grid_constant__ CUtensorMap tmOl, const __grid_constant__ CUtensorMap tmWo,
            const __grid_constant__ CUtensorMap tmX, const __grid_constant__ CUtensorMap tmOut, uint32_t zero,
            const uint8_t* __restrict__ pf_wo, const bf16* __restrict__ kc, const bf16* __restrict__ vc,
            const bf16* __restrict__ x, const bf16* __restrict__ cvec, const bf16* __restrict__ w_mod, const bf16* __restrict__ w_r,
            const bf16* __restrict__ w_gate, const bf16* __restrict__ w_up, const bf16* __restrict__ w_down, bf16* __restrict__ out)
{
  extern __shared__ __align__(1024) uint8_t smem_raw[];
  const uint32_t sbase = smem_u32(smem_raw);
  const uint32_t bars = sbase + AT_SBAR;
  const uint32_t b_full = bars, b_empty = bars + 40;
  const uint32_t b_q0 = bars + 80, b_q1 = bars + 88;
  const uint32_t b_ob = bars + 96;
  const uint32_t b_ordy = bars + 104;
  const uint32_t b_pin = bars + 136;
  const uint32_t b_head = bars + 144;
  const uint32_t b_go = bars + 152;
  const uint32_t b_x = bars + 160;
  const int wg = __shfl_sync(0xffffffffu, threadIdx.x >> 7, 0);
  const bool single = blockIdx.x >= AT_NFULL;
  const int item0 = __shfl_sync(0xffffffffu, blockIdx.x < 128 ? (int)blockIdx.x : (int)blockIdx.x + 124, 0), n_items = __shfl_sync(0xffffffffu, single ? 1 : 2, 0);
  TL_START(3);
  if (threadIdx.x == 0) {
    if (sbase & 1023u) __trap();
    for (int i = 0; i < 5; i++) { mbar_init(b_full + 8 * i, 1); mbar_init(b_empty + 8 * i, 2); }
    mbar_init(b_q0, 1); mbar_init(b_q1, 8); mbar_init(b_ob, 1);
    for (int i = 0; i < 4; i++) mbar_init(b_ordy + 8 * i, 4);
    mbar_init(b_pin, 1); mbar_init(b_head, blockIdx.x < 128 ? 8 : 1); mbar_init(b_go, 1); mbar_init(b_x, 1);
    mbar_init(bars + 168, 2); mbar_init(bars + 176, 1); mbar_init(bars + 184, 8); mbar_init(bars + 192, 2);
    mbar_init(bars + 200, 8); mbar_init(bars + 208, 4); mbar_init(bars + 216, 1); mbar_init(bars + 264, 1); mbar_init(bars + 272, 1); mbar_init(bars + 280, 8); mbar_init(bars + 288, 1); mbar_init(bars + 296, 1); mbar_init(bars + 304, 8); mbar_init(bars + 312, 1); mbar_init(bars + 320, 1);
    fence_mbar_init();
  }

  if (wg == 0) {
    reg_dealloc<AT_PREG>();
    if (threadIdx.x < 32) { __syncwarp(); named_bar_arrive(6, 384); }
    if (threadIdx.x >= 64) {
      named_bar_sync(6, 384);
      if (blockIdx.x < 128 && threadIdx.x >= 96) {
        named_bar_sync(8, 288);
        if (threadIdx.x == 96) red_release_add(&g_hcnt[32 * (1 + (blockIdx.x >> 3)) + 1], 1u);
      }
      if (blockIdx.x < 128) {
        mbar_wait(MOD_AT, 0);
        mod_rest(sbase + OG_SCOL, b_q1, threadIdx.x - 64, cvec, w_mod, w_r);
      }
    } else if (threadIdx.x >= 32) {
      named_bar_sync(6, 384);
      store_warp(sbase, &tmO, item0, n_items);
      __syncwarp();
    } else {
     if (elect_one()) {
      const uint64_t pol = policy_evict_first();
      prefetch_tmap(&tmW); prefetch_tmap(&tmH); prefetch_tmap(&tmWo); prefetch_tmap(&tmOl);
      uint32_t slot = 0, ph = 1;
      if (ALIGN) { uint32_t sm; asm volatile("mov.u32 %0, %%smid;" : "=r"(sm)); g_smid[32 + blockIdx.x] = sm; }
      #pragma unroll 1
      for (int it = 0; it < n_items; it++) {
        const int item = item0 + it * 128, hp = item >> 4, qt = item & 15;
        const bool first = it == 0;
        #pragma unroll 1
        for (int j = 0; j < T_D / 64; j++) {
          const uint32_t sl = ring_slot(qp_pos(j, it)), fb = b_full + 8 * sl;
          mbar_wait(b_empty + 8 * sl, ring_par(qp_pos(j, it)) ^ ((j >> 2) & 1) ^ 1);
          mbar_expect_tx(fb, 49152);
          tma_load_3d_hint(sbase + sl * 32768, &tmW, j * 64, hp * 4, fb, pol);
          if (first && j < PRE_B) {
            if (j == PRE_B - 1) {
              spin_until(&g_hcnt[32 * (1 + qt)], 8u);
              TL_MARK2(16, true);
              fence_proxy_async_global();
              TL_MARK2(17, true);
              #pragma unroll 1
              for (int i = 0; i < PRE_B; i++) tma_load_2d(sbase + AT_SQ + i * 16384, &tmH, i * 64, qt * 128, b_full + 8 * i);
              mbar_arrive(b_go);
            }
          } else {
            if (first && j == 3) mbar_wait(b_head, 0);
            if (first && j == 4 * H_SPLIT) { spin_until(&g_hcnt[32 * (1 + qt) + 1], 8u); fence_proxy_async_global(); }
            if (!first && (j == 0 || j == 2)) mbar_wait(j ? b_q1 : b_q0, 0);
            tma_load_2d_hint(sbase + AT_SQ + (j & 3) * 16384, &tmH, j * 64, qt * 128, fb, first ? pol_normal() : pol);
          }
        }
        #pragma unroll 1
        for (int j = 0; j < 4 * AT_NBLK; j++) {
          const bool isv = (j > 0 && !(j & 1)) || j == 4 * AT_NBLK - 1;
          const int row = hp * 2 * T_SEQ + (isv ? (j - 1) >> 1 : (j + 1) >> 1) * 128;
          const uint32_t fb = b_full + 8 * slot;
          mbar_wait(b_empty + 8 * slot, ph);
          if (!first && j == 3) mbar_wait(b_ob, 0);
          if (j == 4 && it == n_items - 1) mbar_arrive(bars + 288);
          if (ALIGN && j == AL_P && it == 1) mbar_arrive(bars + 312);
          mbar_expect_tx(fb, 32768);
          tma_load_3d_hint(sbase + slot * 32768, isv ? &tmV : &tmK, row, 0, fb, pol);
          if (it == 1 && isv && j >= 2 * WO_LATE && j < 2 * WO_LATE + 32 && blockIdx.x < OG_NKB)
            l2_prefetch_bulk(pf_wo + (size_t)own_kb(blockIdx.x) * 131072 + ((j >> 1) - WO_LATE) * 8192, 8192);
          if (++slot == 5) { slot = 0; ph ^= 1; }
        }
      }
      if (__builtin_expect(single, 0)) {
        #pragma unroll 1
        for (int i = 0; i < 4; i++) spin_until(&g_hcnt[32 * (1 + 4 * i + (blockIdx.x & 3)) + 2], 0x800u);
        fence_proxy_async_global();
        const int nj = help_njobs() * OG_PRE;
        int ji = 0, job = help_job(0), kk = 0;
        #pragma unroll 1
        for (int j = 0; j < nj; j++) {
          const uint32_t sl = ring_slot(qp_pos(j, 1)), fb = b_full + 8 * sl;
          mbar_wait(b_empty + 8 * sl, ring_par(qp_pos(j, 1)) ^ ((j >> 2) & 1) ^ 1);
          mbar_expect_tx(fb, 49152);
          tma_load_3d_hint(sbase + sl * 32768, &tmWo, pre_kb(kk) * 64, (job & 3) * 4, fb, HPOL_B);
          tma_load_3d_hint(sbase + sl * 32768 + 16384, &tmWo, pre_kb(kk) * 64, (job & 3) * 4 + 2, fb, HPOL_B);
          if (j == 0 || j == 2) mbar_wait(j ? b_ob : b_q0, 0);
          tma_load_2d_hint(sbase + AT_SQ + (j & 3) * 16384, HMAP_A, pre_kb(kk) * 64, (job >> 2) * 128, fb, HPOL_A);
          if (++kk == OG_PRE) { kk = 0; job = help_job(++ji); }
        }
      }
      if (blockIdx.x < 128) {
        if (single) mbar_wait(b_x, 1);
        tail_producer(sbase, 0, pol, &tmOl, &tmWo, &tmX);
      }
     }
    }
    named_bar_sync(12 + (threadIdx.x >> 5), 32);
    if (blockIdx.x < 128) tail_exchange(sbase, &tmOut, w_down, w_r, x, out);
  } else {
    if (blockIdx.x < 128) head_phase(sbase + AT_SQ + 49152, sbase + 4 * 32768, b_x, b_go, b_head, threadIdx.x - 128, zero, x, cvec, w_mod);
    else { named_bar_sync(6, 384); if (threadIdx.x == 128) mbar_arrive(b_head); }
    TL_MARK2(0, threadIdx.x == 128);
    reg_alloc<AT_CREG>();
    const int cwg = wg - 1;
    const int tid = threadIdx.x & 127;
    const int warp = tid >> 5, lane = tid & 31;
    const uint32_t dbase = (sbase & 0x3FFFFu) >> 4;
    const uint32_t k_base = dbase + (1u << 16);
    const uint32_t v_base = dbase + (1024u << 16);
    const uint32_t w_base = dbase + (512u << 16);
    const uint32_t q_lo = dbase + ((AT_SQ + cwg * 8192) >> 4) + (1u << 16);
    const uint32_t frag = cwg * 8192 + (16 * warp + (lane & 7) + 8 * ((lane >> 3) & 1)) * 128;
    if (cwg == 1) named_bar_arrive(1, 256);
    bool raw = false;
    uint4 pre[8];
    #pragma unroll 1
    for (int it = 0; it < n_items; it++) {
      const bool more = it + 1 < n_items;
      constexpr int nkb = T_D / 64;
      const int ta = __shfl_sync(0xffffffffu, 4 * it, 0);
      float acc[128];
      {
        FS(2 * it, 0);
        #pragma unroll
        for (int i = 0; i < 128; i++) asm volatile("" : "=f"(acc[i]));
        {
          const uint32_t slot = ring_slot(ta), b_lo = w_base + slot * 2048;
          mbar_wait(b_full + 8 * slot, ring_par(ta));
          wgmma_fence();
          wgmma_m64n256k16_ss_tb<0, 0>(acc, q_lo, b_lo, 0);
          wgmma_m64n256k16_ss_tb<2, 128>(acc, q_lo, b_lo, 1);
          wgmma_m64n256k16_ss_tb<4, 256>(acc, q_lo, b_lo, 1);
          wgmma_m64n256k16_ss_tb<6, 384>(acc, q_lo, b_lo, 1);
          wgmma_commit();
        }
        #pragma unroll 1
        for (int j = NOZERO; j < nkb; j++) {
          const uint32_t slot = ring_slot(qp_pos(j, ta >> 2));
          mbar_wait(b_full + 8 * slot, ring_par(qp_pos(j, ta >> 2)) ^ ((j >> 2) & 1));
          if (QP_STAG > 0 && cwg == 1 && j == nkb - QP_STAG) named_bar_sync(7, 256);
          const uint32_t a_lo = q_lo + (j & 3) * 1024, b_lo = w_base + slot * 2048;
          wgmma_fence();
          wgmma_m64n256k16_ss_tb<0, 0>(acc, a_lo, b_lo, 1);
          wgmma_m64n256k16_ss_tb<2, 128>(acc, a_lo, b_lo, 1);
          wgmma_m64n256k16_ss_tb<4, 256>(acc, a_lo, b_lo, 1);
          wgmma_m64n256k16_ss_tb<6, 384>(acc, a_lo, b_lo, 1);
          wgmma_commit();
          if (QP_STAG > 0 && cwg == 0 && j == nkb - 1) named_bar_arrive(7, 256);
          if (j > 0) {
            wgmma_wait<1>();
            if (tid == 0) mbar_arrive(b_empty + 8 * ring_slot(qp_pos(j - 1, ta >> 2)));
          }
        }
        wgmma_wait<0>();
        fence_regs(acc);
        FS(2 * it, 1);
        TL_MARK2(29, threadIdx.x == 256 && it == 0);
        if (tid == 0) mbar_arrive(b_empty + 24);
      }
      float o[64], s[64];
      uint32_t p[32], q[32];
      #pragma unroll
      for (int i = 0; i < 32; i++) q[i] = pack_bf16(acc[2 * i] * AT_C, acc[2 * i + 1] * AT_C);
      zero_regs(s);
      const uint32_t sq = sbase + AT_SQ + cwg * 8192;
      const bool last_wg1 = cwg == 1 && !more;
      float mc0, mc1, al0 = 1.0f, al1 = 1.0f, l0 = 0.f, l1 = 0.f, lp0 = 0.f, lp1 = 0.f;
      bool redo0 = false;
      FS(2 * it, 2);
      mbar_wait(b_full + 8 * ring_slot(ta), ring_par(ta));
      named_bar_sync(1 + cwg, 256);
      FS(2 * it, 3);
      issue_qk(s, q, k_base + ring_slot(ta) * 2048);
      named_bar_arrive(1 + (cwg ^ 1), 256);
      bool ready = mbar_test(b_full + 8 * ring_slot(ta + 1), ring_par(ta + 1)) & mbar_test(b_full + 8 * ring_slot(ta + 2), ring_par(ta + 2));
      stage_q<16>(acc, AT_C, sbase + AT_SQ + frag, lane);
      wgmma_wait<0>();
      fence_regs(s);
      if (tid == 0) mbar_arrive(b_empty + 8 * ring_slot(ta));
      mc0 = 0.f; mc1 = 0.f;
      if (!raw) {
        raw = softmax_mode(s, mc0, mc1);
        if (__builtin_expect(!raw, 0)) softmax_sub(s, mc0, mc1);
      }
      softmax_exp<0, 64>(s);
      #pragma unroll
      for (int J = 0; J < 16; J += 2)
        stmatrix_x4(sbase + AT_SQ + frag + (J >> 3) * 16384 + ((((J & 7) + (lane >> 4)) ^ (lane & 7)) << 4), q[2 * J], q[2 * J + 1], q[2 * J + 2], q[2 * J + 3]);
      pack_p(p, s);
      zero_regs(o);
      FS(2 * it, 4);
      uint32_t ks = ring_slot(ta + 1), vs = ring_slot(ta + 2), kp = ring_par(ta + 1), vp = ring_par(ta + 2);
      auto finish_head = [&]() {
        FS(2 * it, 5);
        redo0 = finish_l(lp0, lp1);
        if (!redo0) {
          stage_o(o, lp0, lp1, sbase + AT_SQ + frag, lane);
          fence_proxy_async();
          __syncwarp();
          if (lane == 0) mbar_arrive(b_ordy + 8 * cwg);
        }
        FS(2 * it + 1, 4);
      };
      if (!ready) { mbar_wait(b_full + 8 * ks, kp); mbar_wait(b_full + 8 * vs, vp); }
      #pragma unroll 1
      for (int n = 1; n < 2 * AT_NBLK; n++) {
        named_bar_sync(1 + cwg, 256);
        issue_qk(s, q, k_base + ks * 2048);
        if (n == AT_NBLK + 1) finish_head();
        issue_pv(o, p, v_base + vs * 2048, (n & 15) != 1);
        if (!(last_wg1 && n == 2 * AT_NBLK - 1)) named_bar_arrive(1 + (cwg ^ 1), 256);
        wgmma_wait<1>();
        fence_regs(s);
        if (tid == 0) mbar_arrive(b_empty + 8 * ks);
        if (__builtin_expect(!raw || (n + 1) >> 1 == AT_NBLK / 2, 0)) {
          if (n == AT_NBLK - 1) {
            #pragma unroll
            for (int J = 0; J < 16; J += 2)
              ldmatrix_x4(sbase + AT_SQ + 32768 + frag + (J >> 3) * 16384 + ((((J & 7) + (lane >> 4)) ^ (lane & 7)) << 4), q[2 * J], q[2 * J + 1], q[2 * J + 2], q[2 * J + 3]);
          }
          if (!raw) {
            const float m0 = mc0, m1 = mc1;
            const bool ok = softmax_mode(s, mc0, mc1);
            if (n == AT_NBLK) raw = ok;
            else {
              mc0 = mc0 - AT_HEAD > m0 ? mc0 : m0; mc1 = mc1 - AT_HEAD > m1 ? mc1 : m1;
              al0 = ex2_approx(m0 - mc0); al1 = ex2_approx(m1 - mc1);
            }
            if (!raw) softmax_sub(s, mc0, mc1);
          }
        }
        softmax_exp<0, AT_SPLIT>(s);
        add_rowsum(p, l0, l1);
        if (tid == 0) {
          uint32_t dep = zero & __float_as_uint(l0) & __float_as_uint(l1);
          #pragma unroll
          for (int i = AT_SPLIT - AT_PIN - PINB; i < AT_SPLIT - PINB; i += 2) dep &= __float_as_uint(s[i]) & __float_as_uint(s[i + 1]);
          mbar_arrive(b_pin + dep);
        }
        wgmma_wait<0>();
        fence_regs(o);
        if (tid == 0) mbar_arrive(b_empty + 8 * vs);
        ks += 2; if (ks >= 5) { ks -= 5; kp ^= 1; }
        vs += 2; if (vs >= 5) { vs -= 5; vp ^= 1; }
        ready = mbar_test(b_full + 8 * ks, kp) & mbar_test(b_full + 8 * vs, vp);
        softmax_exp<AT_SPLIT, 64>(s);
        pack_p(p, s);
        if (n == AT_NBLK) { lp0 = l0; lp1 = l1; l0 = 0.f; l1 = 0.f; }
        if (__builtin_expect(!raw || !ready, 0)) {
        if (!raw && __any_sync(0xffffffffu, al0 != 1.0f || al1 != 1.0f)) {
          rescale_o(o, al0, al1);
          l0 *= al0; l1 *= al1;
          al0 = 1.0f; al1 = 1.0f;
        }
        if (!ready && n < 2 * AT_NBLK - 1) {
          mbar_wait(b_full + 8 * ks, kp);
          mbar_wait(b_full + 8 * vs, vp);
        }
        }
      }
      FS(2 * it + 1, 5);
      const uint32_t vl = ring_slot(ta + 63);
      vs = ring_slot(ta + 62);
      const uint32_t ob = more ? sbase + vs * 32768 : sbase + AT_SQ + 32768;
      if (redo0) {
        attn_rows_exact(sq, sq, 4 * ta, kc, vc);
        fence_proxy_async();
        __syncwarp();
        if (lane == 0) mbar_arrive(b_ordy + 8 * cwg);
      }
      mbar_wait(b_full + 8 * vl, ring_par(ta + 63));
      issue_pv(o, p, v_base + vl * 2048, 1);
      add_rowsum(p, l0, l1);
      const bool overflow = finish_l(l0, l1);
      if (!overflow && lane == 0) mbar_arrive(b_q1);
      #pragma unroll
      for (int i = 0; i < 8; i++) asm volatile("mov.b64 {%0, %1}, 0;\nmov.b64 {%2, %3}, 0;" : "=r"(pre[i].x), "=r"(pre[i].y), "=r"(pre[i].z), "=r"(pre[i].w));
      if (HOIST && !more && blockIdx.x < OG_MOE) {
        load_pre(pre, sbase, AT_SQ, threadIdx.x - 128);
        __syncwarp();
        if (lane == 0) mbar_arrive(bars + 304);
      }
      mbar_wait(b_empty + 8 * vs, ring_par(ta + 62));
      wgmma_wait<0>();
      fence_regs(o);
      if (tid == 0) mbar_arrive(b_empty + 8 * vl);
      FS(2 * it + 1, 6);
      if (overflow) {
        attn_rows_exact(sq + 32768, ob + cwg * 8192, 4 * ta + 1, kc, vc);
        __syncwarp();
        if (lane == 0) mbar_arrive(b_q1);
      } else stage_o(o, l0, l1, ob + frag, lane);
      fence_proxy_async();
      __syncwarp();
      if (lane == 0) mbar_arrive(b_ordy + 16 + 8 * cwg);
      if (redo0 || overflow) raw = false;
      named_bar_sync(3 + cwg, 128);
      FS(2 * it + 1, 7);
    }
    if (__builtin_expect(single, 0)) {
      float acc[128];
      uint32_t j = 0, pk[64];
      #pragma unroll
      for (int i = 0; i < 64; i++) asm volatile("" : "=f"(acc[2 * i]), "=f"(acc[2 * i + 1]), "=r"(pk[i]));
      uint4* dst = g_pre;
      int left = 0;
      auto put = [&](bool last) {
        #pragma unroll
        for (int i = 0; i < PUT_N; i++) dst[i * 256] = make_uint4(pk[4 * i], pk[4 * i + 1], pk[4 * i + 2], pk[4 * i + 3]);
        dst += PUT_N * 256;
        #pragma unroll
        for (int i = 0; i < 64 - 4 * PUT_N; i++) asm volatile("mov.b32 %0, %1;" : "=r"(pk[i]) : "r"(pk[i + 4 * PUT_N]));
        __syncwarp();
        if (last && lane == 0) mbar_arrive(bars + 280);
      };
      #pragma unroll 1
      for (int ji = 0; ji < help_njobs(); ji++) {
        #pragma unroll 1
        for (int kk = 0; kk < OG_PRE; kk++, j++) {
          const uint32_t slot = ring_slot(qp_pos(j, 1));
          mbar_wait(b_full + 8 * slot, ring_par(qp_pos(j, 1)) ^ ((j >> 2) & 1));
          if (H_STAG > 0 && cwg == 1 && kk == OG_PRE - H_STAG) named_bar_sync(7, 256);
          const uint32_t a_lo = q_lo + (j & 3) * 1024, b_lo = w_base + slot * 2048;
          wgmma_fence();
          wgmma_m64n256k16_ss_tb<0, 0>(acc, a_lo, b_lo, kk != 0);
          wgmma_m64n256k16_ss_tb<2, 128>(acc, a_lo, b_lo, 1);
          wgmma_m64n256k16_ss_tb<4, 256>(acc, a_lo, b_lo, 1);
          wgmma_m64n256k16_ss_tb<6, 384>(acc, a_lo, b_lo, 1);
          wgmma_commit();
          if (H_STAG > 0 && cwg == 0 && kk == OG_PRE - 1) named_bar_arrive(7, 256);
          wgmma_wait<1>();
          if (kk > 0 && tid == 0) mbar_arrive(b_empty + 8 * ring_slot(qp_pos(j - 1, 1)));
          #pragma unroll 1
          for (int i = ji == OG_JOBS ? 0 : 16 / PUT_N - 1; i < 16 / PUT_N && left > 0; i++) put(--left == 0);
        }
        wgmma_wait<0>();
        fence_regs(acc);
        if (tid == 0) mbar_arrive(b_empty + 8 * ring_slot(qp_pos(j - 1, 1)));
        #pragma unroll
        for (int i = 0; i < 64; i++) pk[i] = pack_bf16(acc[2 * i], acc[2 * i + 1]);
        left = 16 / PUT_N;
        if (ji == PRE_X) mbar_wait(bars + 296, 0);
        dst = g_pre + pre_loc(help_job(ji)) * 4096 + threadIdx.x - 128;
      }
      #pragma unroll
      for (int i = 0; i < 16; i++) dst[i * 256] = make_uint4(pk[4 * i], pk[4 * i + 1], pk[4 * i + 2], pk[4 * i + 3]);
      __syncwarp();
      if (lane == 0) mbar_arrive(bars + 280);
      named_bar_sync(5, 256);
      if (threadIdx.x == 128) {
        #pragma unroll 1
        for (int i = 0; i < 5; i++) {
          constexpr int n = OG_JOBS * OG_PRE;
          const int used = i == 3 ? 0 : (n + 3 - (i == 4 ? 3 : i)) / 4;
          if ((used ^ (i < 4)) & 1) {
            mbar_arrive(b_full + 8 * ring_slot(4 + i));
            mbar_arrive(b_empty + 8 * ring_slot(4 + i)); mbar_arrive(b_empty + 8 * ring_slot(4 + i));
          }
        }
        mbar_arrive(b_x);
      }
      named_bar_sync(5, 256);
      #pragma unroll
      for (int i = 0; i < 8; i++) pre[i] = make_uint4(0u, 0u, 0u, 0u);
    }
    TL_CLK(3, 1, threadIdx.x == 128);
    TL_CTA(1, threadIdx.x == 256);
    TL_END(3, tid == 0);
    TL_MARK2(19, tid == 0 && !single);
    if (blockIdx.x < 128) {
      if (!HOIST && blockIdx.x < OG_MOE) {
        load_pre(pre, sbase, AT_SQ, threadIdx.x - 128);
        __syncwarp();
        if (lane == 0) mbar_arrive(bars + 304);
      }
      tail_consumer(sbase, pre, cwg, w_gate, w_up);
    }
  }
}

typedef CUresult (*PFN_encodeTiled)(CUtensorMap*, CUtensorMapDataType, cuuint32_t, void*, const cuuint64_t*, const cuuint64_t*,
                                    const cuuint32_t*, const cuuint32_t*, CUtensorMapInterleave, CUtensorMapSwizzle,
                                    CUtensorMapL2promotion, CUtensorMapFloatOOBfill);

CUtensorMap make_map_2d(PFN_encodeTiled enc, const void* ptr, uint64_t inner, uint64_t outer, uint64_t stride_bytes, uint32_t box_inner, uint32_t box_outer) {
  CUtensorMap m;
  cuuint64_t gd[2] = {inner, outer}; cuuint64_t gs[1] = {stride_bytes};
  cuuint32_t bx[2] = {box_inner, box_outer}; cuuint32_t es[2] = {1, 1};
  enc(&m, CU_TENSOR_MAP_DATA_TYPE_BFLOAT16, 2, const_cast<void*>(ptr), gd, gs, bx, es, CU_TENSOR_MAP_INTERLEAVE_NONE,
      CU_TENSOR_MAP_SWIZZLE_128B, CU_TENSOR_MAP_L2_PROMOTION_L2_128B, CU_TENSOR_MAP_FLOAT_OOB_FILL_NONE);
  return m;
}

CUtensorMap make_map_3d(PFN_encodeTiled enc, const void* ptr, uint64_t cols, uint64_t rows, uint32_t box_rows, uint32_t chunks) {
  CUtensorMap m;
  cuuint64_t gd[3] = {64, rows, cols / 64}; cuuint64_t gs[2] = {cols * 2, 128};
  cuuint32_t bx[3] = {64, box_rows, chunks}; cuuint32_t es[3] = {1, 1, 1};
  enc(&m, CU_TENSOR_MAP_DATA_TYPE_BFLOAT16, 3, const_cast<void*>(ptr), gd, gs, bx, es, CU_TENSOR_MAP_INTERLEAVE_NONE,
      CU_TENSOR_MAP_SWIZZLE_128B, CU_TENSOR_MAP_L2_PROMOTION_L2_128B, CU_TENSOR_MAP_FLOAT_OOB_FILL_NONE);
  return m;
}

}

extern "C" void kernel_launch(void* const* d_in, const int* in_sizes, int n_in, void* d_out, int out_size) {
  const bf16* x      = (const bf16*)d_in[0];
  const bf16* kc     = (const bf16*)d_in[1];
  const bf16* vc     = (const bf16*)d_in[2];
  const bf16* wq     = (const bf16*)d_in[3];
  const bf16* wo     = (const bf16*)d_in[4];
  const bf16* w_r    = (const bf16*)d_in[6];
  const bf16* w_gate = (const bf16*)d_in[7];
  const bf16* w_up   = (const bf16*)d_in[8];
  const bf16* w_down = (const bf16*)d_in[9];
  const bf16* cvec   = (const bf16*)d_in[10];
  const bf16* w_mod  = (const bf16*)d_in[11];
  bf16* out = (bf16*)d_out;

  static PFN_encodeTiled enc = nullptr;
  static void *p_h = nullptr, *p_o = nullptr;
  if (!enc) {
    void* fn = nullptr; cudaDriverEntryPointQueryResult qres;
    cudaGetDriverEntryPoint("cuTensorMapEncodeTiled", &fn, cudaEnableDefault, &qres);
    enc = (PFN_encodeTiled)fn;
    cudaGetSymbolAddress(&p_h, g_pre);
    p_h = (uint4*)p_h + 16 * PRE_X * 2048;
    cudaGetSymbolAddress(&p_o, g_o);
    cudaFuncSetAttribute(fused_kernel, cudaFuncAttributeMaxDynamicSharedMemorySize, (int)AT_SMEM);
  }
  const CUtensorMap tm_h   = make_map_2d(enc, p_h, T_D, T_SEQ, T_D * 2, 64, 128);
  const CUtensorMap tm_wq  = W3D ? make_map_3d(enc, wq, T_DQKV, T_D, 64, 4) : make_map_2d(enc, wq, T_DQKV, T_D, T_DQKV * 2, 64, 64);
  const CUtensorMap tm_k   = KV3D ? make_map_3d(enc, kc, T_DH, (uint64_t)T_NH * T_SEQ, 128, 2) : make_map_2d(enc, kc, T_DH, (uint64_t)T_NH * T_SEQ, T_DH * 2, 64, 128);
  const CUtensorMap tm_v   = KV3D ? make_map_3d(enc, vc, T_DH, (uint64_t)T_NH * T_SEQ, 128, 2) : make_map_2d(enc, vc, T_DH, (uint64_t)T_NH * T_SEQ, T_DH * 2, 64, 128);
  const CUtensorMap tm_ost = make_map_2d(enc, p_o, T_DQKV, T_SEQ, T_DQKV * 2, 64, 64);
  const CUtensorMap tm_old = make_map_2d(enc, p_o, T_DQKV, T_SEQ, T_DQKV * 2, 64, 128);
  const CUtensorMap tm_wo  = make_map_3d(enc, wo, T_D, T_DQKV, 64, 2);
  const CUtensorMap tm_x   = make_map_3d(enc, w_down, T_D, T_F, 32, 8);

  const CUtensorMap tm_out = make_map_2d(enc, out, T_D, T_SEQ, T_D * 2, 64, 128);

  fused_kernel<<<132, 384, AT_SMEM, cudaStreamPerThread>>>(tm_h, tm_wq, tm_k, tm_v, tm_ost, tm_old, tm_wo, tm_x, tm_out, 0u, (const uint8_t*)wo, kc, vc, x, cvec, w_mod,
             w_r, w_gate, w_up, w_down, out);
}
```

```cpp
#include <cuda_runtime.h>
#include <cuda_bf16.h>
#include <cuda.h>
#include <stdint.h>

namespace {

typedef __nv_bfloat16 bf16;

constexpr int T_SEQ = 2048, T_D = 1024, T_NH = 32, T_DH = 128, T_DQKV = 4096, T_F = 3584;

#define PRE_X 2
__device__ __align__(1024) uint4 g_pre[(16 * PRE_X + 128) * 2048];
#define g_h (reinterpret_cast<bf16*>(g_pre + 16 * PRE_X * 2048))
__device__ __align__(1024) bf16 g_o[T_SEQ * T_DQKV];
__device__ __align__(16) uint8_t g_col[8 * 1536];
__device__ __align__(16) float g_scal[64];
__device__ __align__(16) unsigned int g_hcnt[17 * 32];
__device__ unsigned int g_smid[160], g_tmax[128];
__device__ __align__(128) float g_modpart[4 * 2 * T_D];
struct __align__(2048) TailMail {
  float4 part1[T_SEQ * 8];
  uint32_t key[256];
  uint4 cand[16 * 2 * 2 * 128];
  uint32_t cnt[32];
  float ypart[(T_F / 32) * 2 * T_D];
};
__device__ TailMail g_mail;
#define g_part1 g_mail.part1
#define g_key g_mail.key
#define g_cand g_mail.cand
#define CNT_Y (g_mail.cnt)
#define g_ypart g_mail.ypart

__device__ __forceinline__ uint32_t smem_u32(const void* p) { return (uint32_t)__cvta_generic_to_shared(p); }
__device__ __forceinline__ void mbar_init(uint32_t bar, uint32_t cnt) { asm volatile("mbarrier.init.shared::cta.b64 [%0], %1;" :: "r"(bar), "r"(cnt)); }
__device__ __forceinline__ void mbar_expect_tx(uint32_t bar, uint32_t bytes) { asm volatile("mbarrier.arrive.expect_tx.shared::cta.b64 _, [%0], %1;" :: "r"(bar), "r"(bytes) : "memory"); }
__device__ __forceinline__ void mbar_arrive(uint32_t bar) { asm volatile("mbarrier.arrive.shared::cta.b64 _, [%0];" :: "r"(bar) : "memory"); }
__device__ __forceinline__ void mbar_wait(uint32_t bar, uint32_t parity) {
  asm volatile("{\n.reg .pred p;\nLAB_WAIT:\nmbarrier.try_wait.parity.shared::cta.b64 p, [%0], %1;\n@!p bra LAB_WAIT;\n}\n" :: "r"(bar), "r"(parity) : "memory");
}
__device__ __forceinline__ bool mbar_test(uint32_t bar, uint32_t parity) {
  uint32_t r; asm volatile("{\n.reg .pred p;\nmbarrier.test_wait.parity.shared::cta.b64 p, [%1], %2;\nselp.u32 %0, 1, 0, p;\n}\n" : "=r"(r) : "r"(bar), "r"(parity) : "memory");
  return r != 0;
}
__device__ __forceinline__ uint32_t clock_lo() { uint32_t c; asm volatile("mov.u32 %0, %%clock;" : "=r"(c)); return c; }
__device__ __forceinline__ void fence_mbar_init() { asm volatile("fence.mbarrier_init.release.cluster;" ::: "memory"); }
__device__ __forceinline__ void tma_load_2d(uint32_t dst, const CUtensorMap* map, int c0, int c1, uint32_t bar) {
  asm volatile("cp.async.bulk.tensor.2d.shared::cluster.global.mbarrier::complete_tx::bytes [%0], [%1, {%3, %4}], [%2];"
    :: "r"(dst), "l"(map), "r"(bar), "r"(c0), "r"(c1) : "memory");
}
__device__ __forceinline__ uint64_t policy_evict_first() {
  uint64_t p; asm volatile("createpolicy.fractional.L2::evict_first.b64 %0, 1.0;" : "=l"(p)); return p;
}
__device__ __forceinline__ void tma_load_2d_hint(uint32_t dst, const CUtensorMap* map, int c0, int c1, uint32_t bar, uint64_t pol) {
  asm volatile("cp.async.bulk.tensor.2d.shared::cluster.global.mbarrier::complete_tx::bytes.L2::cache_hint [%0], [%1, {%3, %4}], [%2], %5;"
    :: "r"(dst), "l"(map), "r"(bar), "r"(c0), "r"(c1), "l"(pol) : "memory");
}
__device__ __forceinline__ void tma_load_3d_hint(uint32_t dst, const CUtensorMap* map, int c1, int c2, uint32_t bar, uint64_t pol) {
  asm volatile("cp.async.bulk.tensor.3d.shared::cluster.global.mbarrier::complete_tx::bytes.L2::cache_hint [%0], [%1, {%3, %4, %5}], [%2], %6;"
    :: "r"(dst), "l"(map), "r"(bar), "n"(0), "r"(c1), "r"(c2), "l"(pol) : "memory");
}
__device__ __forceinline__ void tma_store_2d(const CUtensorMap* map, uint32_t src, int c0, int c1) {
  asm volatile("cp.async.bulk.tensor.2d.global.shared::cta.bulk_group [%0, {%2, %3}], [%1];" :: "l"(map), "r"(src), "r"(c0), "r"(c1) : "memory");
}
__device__ __forceinline__ void prefetch_tmap(const CUtensorMap* map) { asm volatile("prefetch.tensormap [%0];" :: "l"(map) : "memory"); }
__device__ __forceinline__ void l2_prefetch_bulk(const void* p, uint32_t bytes) {
  asm volatile("cp.async.bulk.prefetch.L2.global [%0], %1;" :: "l"(p), "r"(bytes) : "memory");
}
__device__ __forceinline__ void bulk_commit() { asm volatile("cp.async.bulk.commit_group;" ::: "memory"); }
template<int N> __device__ __forceinline__ void bulk_wait_read() { asm volatile("cp.async.bulk.wait_group.read %0;" :: "n"(N) : "memory"); }
template<int N> __device__ __forceinline__ void bulk_wait() { asm volatile("cp.async.bulk.wait_group %0;" :: "n"(N) : "memory"); }
__device__ __forceinline__ void named_bar_sync(int id, int nthreads) { asm volatile("bar.sync %0, %1;" :: "r"(id), "r"(nthreads) : "memory"); }
__device__ __forceinline__ void named_bar_arrive(int id, int nthreads) { asm volatile("bar.arrive %0, %1;" :: "r"(id), "r"(nthreads) : "memory"); }
__device__ __forceinline__ void wgmma_fence() { asm volatile("wgmma.fence.sync.aligned;" ::: "memory"); }
__device__ __forceinline__ void wgmma_commit() { asm volatile("wgmma.commit_group.sync.aligned;" ::: "memory"); }
template<int N> __device__ __forceinline__ void wgmma_wait() { asm volatile("wgmma.wait_group.sync.aligned %0;" :: "n"(N) : "memory"); }
template<int R> __device__ __forceinline__ void reg_alloc() { asm volatile("setmaxnreg.inc.sync.aligned.u32 %0;" :: "n"(R)); }
template<int R> __device__ __forceinline__ void reg_dealloc() { asm volatile("setmaxnreg.dec.sync.aligned.u32 %0;" :: "n"(R)); }
__device__ __forceinline__ bool elect_one() {
  uint32_t pred; asm volatile("{\n.reg .pred p;\nelect.sync _|p, 0xffffffff;\nselp.u32 %0, 1, 0, p;\n}\n" : "=r"(pred)); return pred != 0;
}
__device__ __forceinline__ uint32_t pack_bf16(float lo, float hi) {
  uint32_t r; asm("cvt.rn.bf16x2.f32 %0, %1, %2;" : "=r"(r) : "f"(hi), "f"(lo)); return r;
}
__device__ __forceinline__ void stmatrix_x4(uint32_t addr, uint32_t r0, uint32_t r1, uint32_t r2, uint32_t r3) {
  asm volatile("stmatrix.sync.aligned.m8n8.x4.shared.b16 [%0], {%1, %2, %3, %4};" :: "r"(addr), "r"(r0), "r"(r1), "r"(r2), "r"(r3) : "memory");
}
__device__ __forceinline__ void fence_proxy_async() { asm volatile("fence.proxy.async.shared::cta;" ::: "memory"); }
__device__ __forceinline__ float ex2_approx(float x) { float y; asm("ex2.approx.ftz.f32 %0, %1;" : "=f"(y) : "f"(x)); return y; }
template<int N> __device__ __forceinline__ void fence_regs(float (&r)[N]) {
  #pragma unroll
  for (int i = 0; i < N; i++) asm volatile("" : "+f"(r[i]) :: "memory");
}
template<int N> __device__ __forceinline__ void zero_regs(float (&r)[N]) {
  #pragma unroll
  for (int i = 0; i < N; i += 2) asm volatile("mov.b64 {%0, %1}, 0;" : "=f"(r[i]), "=f"(r[i + 1]));
}
__device__ __forceinline__ float rbf(float x) { return __uint_as_float(pack_bf16(0.f, x)); }
__device__ __forceinline__ float bflo(uint32_t v) { return __uint_as_float(v << 16); }
__device__ __forceinline__ float bfhi(uint32_t v) { return __uint_as_float(v & 0xffff0000u); }

#define TL_START(k) do {} while (0)
#define TL_END(k, cond) do {} while (0)
#define TL_CTA(i, cond) do {} while (0)
#define FS(slot, k) do {} while (0)
#define TL_MARK2(k, cond) do {} while (0)
#define TL_CLK(k, i, cond) do {} while (0)

template <int OFFA, int OFFB>
__device__ __forceinline__ void wgmma_m64n256k16_ss_tb(float (&d)[128], uint32_t a_lo, uint32_t b_lo, int scaleD) {
  asm volatile("{\n.reg .pred p;\n.reg .b32 ta, tb;\n.reg .b64 da, db;\nsetp.ne.b32 p, %130, 0;\n"
    "add.u32 ta, %128, %131;\nadd.u32 tb, %129, %132;\n"
    "mov.b64 da, {ta, 0x40000040};\nmov.b64 db, {tb, 0x40000040};\n"
    "wgmma.mma_async.sync.aligned.m64n256k16.f32.bf16.bf16 "
    "{%0, %1, %2, %3, %4, %5, %6, %7, %8, %9, %10, %11, %12, %13, %14, %15, %16, %17, %18, %19, %20, %21, %22, %23, %24, %25, %26, %27, %28, %29, %30, %31, %32, %33, %34, %35, %36, %37, %38, %39, %40, %41, %42, %43, %44, %45, %46, %47, %48, %49, %50, %51, %52, %53, %54, %55, %56, %57, %58, %59, %60, %61, %62, %63, %64, %65, %66, %67, %68, %69, %70, %71, %72, %73, %74, %75, %76, %77, %78, %79, %80, %81, %82, %83, %84, %85, %86, %87, %88, %89, %90, %91, %92, %93, %94, %95, %96, %97, %98, %99, %100, %101, %102, %103, %104, %105, %106, %107, %108, %109, %110, %111, %112, %113, %114, %115, %116, %117, %118, %119, %120, %121, %122, %123, %124, %125, %126, %127}, "
    "da, db, p, 1, 1, 0, 1;\n}\n"
    : "+f"(d[0]), "+f"(d[1]), "+f"(d[2]), "+f"(d[3]), "+f"(d[4]), "+f"(d[5]), "+f"(d[6]), "+f"(d[7]), "+f"(d[8]), "+f"(d[9]), "+f"(d[10]), "+f"(d[11]), "+f"(d[12]), "+f"(d[13]), "+f"(d[14]), "+f"(d[15]), "+f"(d[16]), "+f"(d[17]), "+f"(d[18]), "+f"(d[19]), "+f"(d[20]), "+f"(d[21]), "+f"(d[22]), "+f"(d[23]), "+f"(d[24]), "+f"(d[25]), "+f"(d[26]), "+f"(d[27]), "+f"(d[28]), "+f"(d[29]), "+f"(d[30]), "+f"(d[31]), "+f"(d[32]), "+f"(d[33]), "+f"(d[34]), "+f"(d[35]), "+f"(d[36]), "+f"(d[37]), "+f"(d[38]), "+f"(d[39]), "+f"(d[40]), "+f"(d[41]), "+f"(d[42]), "+f"(d[43]), "+f"(d[44]), "+f"(d[45]), "+f"(d[46]), "+f"(d[47]), "+f"(d[48]), "+f"(d[49]), "+f"(d[50]), "+f"(d[51]), "+f"(d[52]), "+f"(d[53]), "+f"(d[54]), "+f"(d[55]), "+f"(d[56]), "+f"(d[57]), "+f"(d[58]), "+f"(d[59]), "+f"(d[60]), "+f"(d[61]), "+f"(d[62]), "+f"(d[63]), "+f"(d[64]), "+f"(d[65]), "+f"(d[66]), "+f"(d[67]), "+f"(d[68]), "+f"(d[69]), "+f"(d[70]), "+f"(d[71]), "+f"(d[72]), "+f"(d[73]), "+f"(d[74]), "+f"(d[75]), "+f"(d[76]), "+f"(d[77]), "+f"(d[78]), "+f"(d[79]), "+f"(d[80]), "+f"(d[81]), "+f"(d[82]), "+f"(d[83]), "+f"(d[84]), "+f"(d[85]), "+f"(d[86]), "+f"(d[87]), "+f"(d[88]), "+f"(d[89]), "+f"(d[90]), "+f"(d[91]), "+f"(d[92]), "+f"(d[93]), "+f"(d[94]), "+f"(d[95]), "+f"(d[96]), "+f"(d[97]), "+f"(d[98]), "+f"(d[99]), "+f"(d[100]), "+f"(d[101]), "+f"(d[102]), "+f"(d[103]), "+f"(d[104]), "+f"(d[105]), "+f"(d[106]), "+f"(d[107]), "+f"(d[108]), "+f"(d[109]), "+f"(d[110]), "+f"(d[111]), "+f"(d[112]), "+f"(d[113]), "+f"(d[114]), "+f"(d[115]), "+f"(d[116]), "+f"(d[117]), "+f"(d[118]), "+f"(d[119]), "+f"(d[120]), "+f"(d[121]), "+f"(d[122]), "+f"(d[123]), "+f"(d[124]), "+f"(d[125]), "+f"(d[126]), "+f"(d[127])
    : "r"(a_lo), "r"(b_lo), "r"(scaleD), "n"(OFFA), "n"(OFFB));
}

template <int OFFA, int OFFB>
__device__ __forceinline__ void wgmma_m64n128k16_ss_tb(float (&d)[64], uint32_t a_lo, uint32_t b_lo, int scaleD) {
  asm volatile("{\n.reg .pred p;\n.reg .b32 ta, tb;\n.reg .b64 da, db;\nsetp.ne.b32 p, %66, 0;\n"
    "add.u32 ta, %64, %67;\nadd.u32 tb, %65, %68;\n"
    "mov.b64 da, {ta, 0x40000040};\nmov.b64 db, {tb, 0x40000040};\n"
    "wgmma.mma_async.sync.aligned.m64n128k16.f32.bf16.bf16 "
    "{%0, %1, %2, %3, %4, %5, %6, %7, %8, %9, %10, %11, %12, %13, %14, %15, %16, %17, %18, %19, %20, %21, %22, %23, %24, %25, %26, %27, %28, %29, %30, %31, %32, %33, %34, %35, %36, %37, %38, %39, %40, %41, %42, %43, %44, %45, %46, %47, %48, %49, %50, %51, %52, %53, %54, %55, %56, %57, %58, %59, %60, %61, %62, %63}, "
    "da, db, p, 1, 1, 0, 1;\n}\n"
    : "+f"(d[0]), "+f"(d[1]), "+f"(d[2]), "+f"(d[3]), "+f"(d[4]), "+f"(d[5]), "+f"(d[6]), "+f"(d[7]), "+f"(d[8]), "+f"(d[9]), "+f"(d[10]), "+f"(d[11]), "+f"(d[12]), "+f"(d[13]), "+f"(d[14]), "+f"(d[15]), "+f"(d[16]), "+f"(d[17]), "+f"(d[18]), "+f"(d[19]), "+f"(d[20]), "+f"(d[21]), "+f"(d[22]), "+f"(d[23]), "+f"(d[24]), "+f"(d[25]), "+f"(d[26]), "+f"(d[27]), "+f"(d[28]), "+f"(d[29]), "+f"(d[30]), "+f"(d[31]), "+f"(d[32]), "+f"(d[33]), "+f"(d[34]), "+f"(d[35]), "+f"(d[36]), "+f"(d[37]), "+f"(d[38]), "+f"(d[39]), "+f"(d[40]), "+f"(d[41]), "+f"(d[42]), "+f"(d[43]), "+f"(d[44]), "+f"(d[45]), "+f"(d[46]), "+f"(d[47]), "+f"(d[48]), "+f"(d[49]), "+f"(d[50]), "+f"(d[51]), "+f"(d[52]), "+f"(d[53]), "+f"(d[54]), "+f"(d[55]), "+f"(d[56]), "+f"(d[57]), "+f"(d[58]), "+f"(d[59]), "+f"(d[60]), "+f"(d[61]), "+f"(d[62]), "+f"(d[63])
    : "r"(a_lo), "r"(b_lo), "r"(scaleD), "n"(OFFA), "n"(OFFB));
}

template <int OFFB>
__device__ __forceinline__ void wgmma_m64n128k16_rs_tb(float (&d)[64], uint32_t a0, uint32_t a1, uint32_t a2, uint32_t a3, uint32_t b_lo, int scaleD) {
  asm volatile("{\n.reg .pred p;\n.reg .b32 tb;\n.reg .b64 db;\nsetp.ne.b32 p, %69, 0;\n"
    "add.u32 tb, %68, %70;\n"
    "mov.b64 db, {tb, 0x40000040};\n"
    "wgmma.mma_async.sync.aligned.m64n128k16.f32.bf16.bf16 "
    "{%0, %1, %2, %3, %4, %5, %6, %7, %8, %9, %10, %11, %12, %13, %14, %15, %16, %17, %18, %19, %20, %21, %22, %23, %24, %25, %26, %27, %28, %29, %30, %31, %32, %33, %34, %35, %36, %37, %38, %39, %40, %41, %42, %43, %44, %45, %46, %47, %48, %49, %50, %51, %52, %53, %54, %55, %56, %57, %58, %59, %60, %61, %62, %63}, "
    "{%64, %65, %66, %67}, db, p, 1, 1, 1;\n}\n"
    : "+f"(d[0]), "+f"(d[1]), "+f"(d[2]), "+f"(d[3]), "+f"(d[4]), "+f"(d[5]), "+f"(d[6]), "+f"(d[7]), "+f"(d[8]), "+f"(d[9]), "+f"(d[10]), "+f"(d[11]), "+f"(d[12]), "+f"(d[13]), "+f"(d[14]), "+f"(d[15]), "+f"(d[16]), "+f"(d[17]), "+f"(d[18]), "+f"(d[19]), "+f"(d[20]), "+f"(d[21]), "+f"(d[22]), "+f"(d[23]), "+f"(d[24]), "+f"(d[25]), "+f"(d[26]), "+f"(d[27]), "+f"(d[28]), "+f"(d[29]), "+f"(d[30]), "+f"(d[31]), "+f"(d[32]), "+f"(d[33]), "+f"(d[34]), "+f"(d[35]), "+f"(d[36]), "+f"(d[37]), "+f"(d[38]), "+f"(d[39]), "+f"(d[40]), "+f"(d[41]), "+f"(d[42]), "+f"(d[43]), "+f"(d[44]), "+f"(d[45]), "+f"(d[46]), "+f"(d[47]), "+f"(d[48]), "+f"(d[49]), "+f"(d[50]), "+f"(d[51]), "+f"(d[52]), "+f"(d[53]), "+f"(d[54]), "+f"(d[55]), "+f"(d[56]), "+f"(d[57]), "+f"(d[58]), "+f"(d[59]), "+f"(d[60]), "+f"(d[61]), "+f"(d[62]), "+f"(d[63])
    : "r"(a0), "r"(a1), "r"(a2), "r"(a3), "r"(b_lo), "r"(scaleD), "n"(OFFB));
}

template <int OFFB>
__device__ __forceinline__ void wgmma_m64n128k16_rs(float (&d)[64], uint32_t a0, uint32_t a1, uint32_t a2, uint32_t a3, uint32_t b_lo, int scaleD) {
  asm volatile("{\n.reg .pred p;\n.reg .b32 tb;\n.reg .b64 db;\nsetp.ne.b32 p, %69, 0;\n"
    "add.u32 tb, %68, %70;\n"
    "mov.b64 db, {tb, 0x40000040};\n"
    "wgmma.mma_async.sync.aligned.m64n128k16.f32.bf16.bf16 "
    "{%0, %1, %2, %3, %4, %5, %6, %7, %8, %9, %10, %11, %12, %13, %14, %15, %16, %17, %18, %19, %20, %21, %22, %23, %24, %25, %26, %27, %28, %29, %30, %31, %32, %33, %34, %35, %36, %37, %38, %39, %40, %41, %42, %43, %44, %45, %46, %47, %48, %49, %50, %51, %52, %53, %54, %55, %56, %57, %58, %59, %60, %61, %62, %63}, "
    "{%64, %65, %66, %67}, db, p, 1, 1, 0;\n}\n"
    : "+f"(d[0]), "+f"(d[1]), "+f"(d[2]), "+f"(d[3]), "+f"(d[4]), "+f"(d[5]), "+f"(d[6]), "+f"(d[7]), "+f"(d[8]), "+f"(d[9]), "+f"(d[10]), "+f"(d[11]), "+f"(d[12]), "+f"(d[13]), "+f"(d[14]), "+f"(d[15]), "+f"(d[16]), "+f"(d[17]), "+f"(d[18]), "+f"(d[19]), "+f"(d[20]), "+f"(d[21]), "+f"(d[22]), "+f"(d[23]), "+f"(d[24]), "+f"(d[25]), "+f"(d[26]), "+f"(d[27]), "+f"(d[28]), "+f"(d[29]), "+f"(d[30]), "+f"(d[31]), "+f"(d[32]), "+f"(d[33]), "+f"(d[34]), "+f"(d[35]), "+f"(d[36]), "+f"(d[37]), "+f"(d[38]), "+f"(d[39]), "+f"(d[40]), "+f"(d[41]), "+f"(d[42]), "+f"(d[43]), "+f"(d[44]), "+f"(d[45]), "+f"(d[46]), "+f"(d[47]), "+f"(d[48]), "+f"(d[49]), "+f"(d[50]), "+f"(d[51]), "+f"(d[52]), "+f"(d[53]), "+f"(d[54]), "+f"(d[55]), "+f"(d[56]), "+f"(d[57]), "+f"(d[58]), "+f"(d[59]), "+f"(d[60]), "+f"(d[61]), "+f"(d[62]), "+f"(d[63])
    : "r"(a0), "r"(a1), "r"(a2), "r"(a3), "r"(b_lo), "r"(scaleD), "n"(OFFB));
}

__device__ __forceinline__ uint4 ldg_nc_v4(const void* p) {
  uint4 v;
    asm volatile("{\n.reg .b64 pol;\ncreatepolicy.fractional.L2::evict_first.b64 pol, 1.0;\n"
                 "ld.global.nc.L1::no_allocate.L2::cache_hint.v4.u32 {%0, %1, %2, %3}, [%4], pol;\n}\n" : "=r"(v.x), "=r"(v.y), "=r"(v.z), "=r"(v.w) : "l"(p));
  return v;
}
__device__ __forceinline__ uint64_t pol_normal() {
  uint64_t p; asm volatile("createpolicy.fractional.L2::evict_normal.b64 %0, 1.0;" : "=l"(p)); return p;
}
__device__ __forceinline__ void unpack8(const uint4& u, float (&v)[8]) {
  v[0] = bflo(u.x); v[1] = bfhi(u.x); v[2] = bflo(u.y); v[3] = bfhi(u.y);
  v[4] = bflo(u.z); v[5] = bfhi(u.z); v[6] = bflo(u.w); v[7] = bfhi(u.w);
}
__device__ __forceinline__ void fma8(float (&acc)[8], float s, const uint4& w) {
  acc[0] = fmaf(s, bflo(w.x), acc[0]); acc[1] = fmaf(s, bfhi(w.x), acc[1]); acc[2] = fmaf(s, bflo(w.y), acc[2]); acc[3] = fmaf(s, bfhi(w.y), acc[3]);
  acc[4] = fmaf(s, bflo(w.z), acc[4]); acc[5] = fmaf(s, bfhi(w.z), acc[5]); acc[6] = fmaf(s, bflo(w.w), acc[6]); acc[7] = fmaf(s, bfhi(w.w), acc[7]);
}
__device__ __forceinline__ float rcp_approx(float x) { float y; asm("rcp.approx.ftz.f32 %0, %1;" : "=f"(y) : "f"(x)); return y; }
__device__ __forceinline__ float sigmoid_f(float v) { return rcp_approx(1.0f + ex2_approx(v * -1.4426950408889634f)); }
__device__ __forceinline__ float silu_bf(float v) { return rbf(v * sigmoid_f(v)); }
__device__ __forceinline__ uint32_t rank_key(float r, int idx) {
  const uint32_t b = __float_as_uint(r) >> 16;
  const uint32_t u = (r != r) ? 0u : ((b & 0x8000u) ? (~b & 0xffffu) : (b | 0x8000u));
  return (u << 16) | (0xffffu - (uint32_t)idx);
}
__device__ __forceinline__ void warp_top2(uint32_t& k1, uint32_t& k2) {
  const uint32_t m1 = __reduce_max_sync(0xffffffffu, k1);
  k2 = __reduce_max_sync(0xffffffffu, k1 == m1 ? k2 : k1);
  k1 = m1;
}
__device__ __forceinline__ uint32_t bmul2(uint32_t a, uint32_t b) { uint32_t r; asm("mul.rn.bf16x2 %0, %1, %2;" : "=r"(r) : "r"(a), "r"(b)); return r; }
__device__ __forceinline__ uint32_t badd2(uint32_t a, uint32_t b) { uint32_t r; asm("add.rn.bf16x2 %0, %1, %2;" : "=r"(r) : "r"(a), "r"(b)); return r; }
__device__ __forceinline__ uint32_t bsub2(uint32_t a, uint32_t b) { uint32_t r; asm("sub.rn.bf16x2 %0, %1, %2;" : "=r"(r) : "r"(a), "r"(b)); return r; }
__device__ __forceinline__ float sqrt_approx(float x) { float y; asm("sqrt.approx.f32 %0, %1;" : "=f"(y) : "f"(x)); return y; }
__device__ __forceinline__ uint32_t ln_norm2(uint32_t x1, uint32_t mb2, float inv) {
  const uint32_t d = bsub2(x1, mb2);
  return pack_bf16(bflo(d) * inv, bfhi(d) * inv);
}
__device__ __forceinline__ uint32_t bfma2(uint32_t a, uint32_t b, uint32_t c) { uint32_t r; asm("fma.rn.bf16x2 %0, %1, %2, %3;" : "=r"(r) : "r"(a), "r"(b), "r"(c)); return r; }
__device__ __forceinline__ uint32_t ln_norm2b(uint32_t x1, uint32_t mb2, uint32_t ih, uint32_t il) {
  const uint32_t d = bsub2(x1, mb2);
  return bfma2(d, ih, bmul2(d, il));
}
__device__ __forceinline__ uint32_t ln_mod2(uint32_t x1, uint32_t mb2, float inv, uint32_t c1, uint32_t sb) { return badd2(bmul2(ln_norm2(x1, mb2, inv), c1), sb); }
__device__ __forceinline__ void ldmatrix_x4(uint32_t addr, uint32_t& r0, uint32_t& r1, uint32_t& r2, uint32_t& r3) {
  asm volatile("ldmatrix.sync.aligned.m8n8.x4.shared.b16 {%0, %1, %2, %3}, [%4];" : "=r"(r0), "=r"(r1), "=r"(r2), "=r"(r3) : "r"(addr) : "memory");
}
__device__ __forceinline__ uint4 ldg_stream_v4(const void* p, uint64_t pol) {
  uint4 v; asm volatile("ld.global.nc.L1::no_allocate.L2::cache_hint.L2::128B.v4.u32 {%0, %1, %2, %3}, [%4], %5;" : "=r"(v.x), "=r"(v.y), "=r"(v.z), "=r"(v.w) : "l"(p), "l"(pol)); return v;
}
__device__ __forceinline__ void bulk_load_hint(uint32_t dst, const void* src, uint32_t bytes, uint32_t bar, uint64_t pol) {
  asm volatile("cp.async.bulk.shared::cluster.global.mbarrier::complete_tx::bytes.L2::cache_hint [%0], [%1], %2, [%3], %4;"
    :: "r"(dst), "l"(src), "r"(bytes), "r"(bar), "l"(pol) : "memory");
}
__device__ __forceinline__ void red_release_add(unsigned int* p, unsigned int v) { asm volatile("red.release.gpu.global.add.u32 [%0], %1;" :: "l"(p), "r"(v) : "memory"); }
__device__ __forceinline__ unsigned int ld_acquire(const unsigned int* p) { unsigned int v; asm volatile("ld.acquire.gpu.global.u32 %0, [%1];" : "=r"(v) : "l"(p) : "memory"); return v; }
__device__ __forceinline__ void spin_until(const unsigned int* p, unsigned int target) {
  #pragma unroll 1
  for (unsigned int i = 0; i < (1u << 22); i++) { if (ld_acquire(p) >= target) return; }
}
__device__ __forceinline__ float lds_f32(uint32_t a) { float v; asm volatile("ld.shared.f32 %0, [%1];" : "=f"(v) : "r"(a) : "memory"); return v; }
__device__ __forceinline__ float2 lds_f32x2(uint32_t a) { float2 v; asm volatile("ld.shared.v2.f32 {%0, %1}, [%2];" : "=f"(v.x), "=f"(v.y) : "r"(a) : "memory"); return v; }
__device__ __forceinline__ uint2 lds_u32x2(uint32_t a) { uint2 v; asm volatile("ld.shared.v2.u32 {%0, %1}, [%2];" : "=r"(v.x), "=r"(v.y) : "r"(a) : "memory"); return v; }
__device__ __forceinline__ uint32_t lds_u32(uint32_t a) { uint32_t v; asm volatile("ld.shared.u32 %0, [%1];" : "=r"(v) : "r"(a) : "memory"); return v; }
__device__ __forceinline__ void sts_u32(uint32_t a, uint32_t v) { asm volatile("st.shared.u32 [%0], %1;" :: "r"(a), "r"(v) : "memory"); }
__device__ __forceinline__ void sts_u32x2(uint32_t a, uint32_t x, uint32_t y) { asm volatile("st.shared.v2.u32 [%0], {%1, %2};" :: "r"(a), "r"(x), "r"(y) : "memory"); }
__device__ __forceinline__ void sts_f32(uint32_t a, float v) { asm volatile("st.shared.f32 [%0], %1;" :: "r"(a), "f"(v) : "memory"); }
__device__ __forceinline__ void sts_f32x2(uint32_t a, float x, float y) { asm volatile("st.shared.v2.f32 [%0], {%1, %2};" :: "r"(a), "f"(x), "f"(y) : "memory"); }
__device__ __forceinline__ void sts_f32x4(uint32_t a, float x, float y, float z, float w) { asm volatile("st.shared.v4.f32 [%0], {%1, %2, %3, %4};" :: "r"(a), "f"(x), "f"(y), "f"(z), "f"(w) : "memory"); }

__device__ __forceinline__ uint4 lds_u32x4(uint32_t a) { uint4 v; asm volatile("ld.shared.v4.u32 {%0, %1, %2, %3}, [%4];" : "=r"(v.x), "=r"(v.y), "=r"(v.z), "=r"(v.w) : "r"(a) : "memory"); return v; }
__device__ __forceinline__ void sts_u32x4(uint32_t a, uint32_t x, uint32_t y, uint32_t z, uint32_t w) { asm volatile("st.shared.v4.u32 [%0], {%1, %2, %3, %4};" :: "r"(a), "r"(x), "r"(y), "r"(z), "r"(w) : "memory"); }
__device__ __forceinline__ void st_tagged(float* p, float v) {
  const uint32_t b = __float_as_uint(v);
  asm volatile("st.relaxed.gpu.global.u32 [%0], %1;" :: "l"(p), "r"(b == 0u ? 0x80000000u : b) : "memory");
}
__device__ __forceinline__ void st_tagged4(float* p, float x, float y, float z, float w) {
  const uint32_t a = __float_as_uint(x), b = __float_as_uint(y), c = __float_as_uint(z), d = __float_as_uint(w);
  asm volatile("st.relaxed.gpu.global.v4.u32 [%0], {%1, %2, %3, %4};" :: "l"(p), "r"(a == 0u ? 0x80000000u : a), "r"(b == 0u ? 0x80000000u : b),
               "r"(c == 0u ? 0x80000000u : c), "r"(d == 0u ? 0x80000000u : d) : "memory");
}
__device__ __forceinline__ void st_relaxed2(void* p, uint32_t a, uint32_t b) { asm volatile("st.relaxed.gpu.global.v2.u32 [%0], {%1, %2};" :: "l"(p), "r"(a), "r"(b) : "memory"); }
__device__ __forceinline__ float4 ld_tagged4(const float* p) {
  float4 v; asm volatile("ld.relaxed.gpu.global.v4.f32 {%0, %1, %2, %3}, [%4];" : "=f"(v.x), "=f"(v.y), "=f"(v.z), "=f"(v.w) : "l"(p) : "memory"); return v;
}
__device__ __forceinline__ bool tagged4(const float4& v) {
  return __float_as_uint(v.x) != 0u && __float_as_uint(v.y) != 0u && __float_as_uint(v.z) != 0u && __float_as_uint(v.w) != 0u;
}
__device__ __forceinline__ void hint_arrive(uint32_t* p) { asm volatile("red.relaxed.gpu.global.add.u32 [%0], 1;" :: "l"(p) : "memory"); }
__device__ __forceinline__ void hint_wait(const uint32_t* p, uint32_t target) {
  uint32_t v = 0u;
  #pragma unroll 1
  for (unsigned int i = 0; i < (1u << 22) && v < target; i++) asm volatile("ld.relaxed.gpu.global.u32 %0, [%1];" : "=r"(v) : "l"(p) : "memory");
}
__device__ __forceinline__ void fence_proxy_async_global() { asm volatile("fence.proxy.async.global;" ::: "memory"); }

constexpr int H_SPLIT = 1;
constexpr int PRE_B = 2;
__device__ __forceinline__ void load_parts(float4 (&pa)[4], float4 (&pb)[4], int t2) {
  #pragma unroll
  for (int k = 0; k < 4; k++) { pa[k] = ld_tagged4(g_modpart + k * 2 * T_D + t2 * 8); pb[k] = ld_tagged4(g_modpart + k * 2 * T_D + t2 * 8 + 4); }
}
__device__ __forceinline__ void finish_parts(float4 (&pa)[4], float4 (&pb)[4], int t2, uint32_t tab) {
  #pragma unroll 1
  for (unsigned int spin = 0; spin < (1u << 22); spin++) {
    bool ok = true;
    #pragma unroll
    for (int k = 0; k < 4; k++) ok &= tagged4(pa[k]) & tagged4(pb[k]);
    if (__all_sync(0xffffffffu, ok)) break;
    load_parts(pa, pb, t2);
  }
  #pragma unroll
  for (int k = 1; k < 4; k++) {
    pa[0].x += pa[k].x; pa[0].y += pa[k].y; pa[0].z += pa[k].z; pa[0].w += pa[k].w;
    pb[0].x += pb[k].x; pb[0].y += pb[k].y; pb[0].z += pb[k].z; pb[0].w += pb[k].w;
  }
  uint32_t m0 = pack_bf16(pa[0].x, pa[0].y), m1 = pack_bf16(pa[0].z, pa[0].w), m2 = pack_bf16(pb[0].x, pb[0].y), m3 = pack_bf16(pb[0].z, pb[0].w);
  if (t2 >= 128) { m0 = badd2(m0, 0x3F803F80u); m1 = badd2(m1, 0x3F803F80u); m2 = badd2(m2, 0x3F803F80u); m3 = badd2(m3, 0x3F803F80u); }
  sts_u32x4(tab + t2 * 16, m0, m1, m2, m3);
}
__device__ __forceinline__ void head_phase(uint32_t scr, uint32_t xs, uint32_t b_x, uint32_t b_go, uint32_t b_head, int t2, uint32_t zero, const bf16* __restrict__ x, const bf16* __restrict__ cvec, const bf16* __restrict__ w_mod) {
  const int lane = t2 & 31, w8 = t2 >> 5;
  const int cb = blockIdx.x & 31, ks = blockIdx.x >> 5;
  uint4 w[8], xv[2][4];
  const float cv = __bfloat162float(cvec[ks * 256 + t2]);
  #pragma unroll
  for (int i = 0; i < 8; i++) w[i] = ldg_nc_v4(w_mod + (size_t)(ks * 256 + (t2 >> 3) + 32 * i) * (6 * T_D) + cb * 64 + (t2 & 7) * 8);
  const int row0 = blockIdx.x * 16 + 2 * w8;
  sts_f32(scr + t2 * 4, silu_bf(cv));
  #pragma unroll 1
  for (uint32_t i = 0; i <= zero; i++) named_bar_sync(6, 384);
  TL_MARK2(1, t2 == 0);
  {
    float acc[8];
    #pragma unroll
    for (int j = 0; j < 8; j++) acc[j] = 0.f;
    #pragma unroll
    for (int i = 0; i < 8; i++) {
      fma8(acc, lds_f32(scr + ((t2 >> 3) + 32 * i) * 4), w[i]);
      if (i == 0 && t2 == 0) {
        mbar_expect_tx(b_x + (__float_as_uint(acc[0]) & zero), 32768);
        bulk_load_hint(xs, x + (size_t)blockIdx.x * 16 * T_D, 32768, b_x, policy_evict_first());
      }
    }
    #pragma unroll
    for (int j = 0; j < 4; j++) { const bool up = lane & 16; acc[j] = (up ? acc[4 + j] : acc[j]) + __shfl_xor_sync(0xffffffffu, up ? acc[j] : acc[4 + j], 16); }
    #pragma unroll
    for (int j = 0; j < 2; j++) { const bool up = lane & 8; acc[j] = (up ? acc[2 + j] : acc[j]) + __shfl_xor_sync(0xffffffffu, up ? acc[j] : acc[2 + j], 8); }
    sts_f32x2(scr + 1024 + w8 * 256 + (lane & 7) * 32 + (lane >> 3) * 8, acc[0], acc[1]);
  }
  named_bar_sync(5, 256);
  if (t2 < 64) {
    float sum = 0.f;
    #pragma unroll
    for (int i = 0; i < 8; i++) sum += lds_f32(scr + 1024 + i * 256 + t2 * 4);
    st_tagged(g_modpart + ks * 2 * T_D + cb * 64 + t2, sum);
    TL_MARK2(2, t2 == 0);
  }
  mbar_wait(b_x, 0);
  const bool first_cols = (__shfl_sync(0xffffffffu, w8, 0) & 3) == 0;
  float4 pa[4], pb[4];
  pa[0].x = 0.f;
  if (first_cols) load_parts(pa, pb, t2);
  #pragma unroll
  for (int r = 0; r < 2; r++)
    #pragma unroll
    for (int j = 0; j < 4; j++) xv[r][j] = lds_u32x4(xs + (2 * w8 + r) * 2048 + j * 512 + lane * 16);
  uint32_t mb2[2], ih[2], il[2];
  {
    float st[4] = {0.f, 0.f, 0.f, 0.f};
    #pragma unroll
    for (int r = 0; r < 2; r++)
      #pragma unroll
      for (int j = 0; j < 4; j++) {
        float v[8];
        unpack8(xv[r][j], v);
        st[2 * r] += ((v[0] + v[1]) + (v[2] + v[3])) + ((v[4] + v[5]) + (v[6] + v[7]));
        st[2 * r + 1] += fmaf(v[0], v[0], fmaf(v[1], v[1], fmaf(v[2], v[2], v[3] * v[3]))) + fmaf(v[4], v[4], fmaf(v[5], v[5], fmaf(v[6], v[6], v[7] * v[7])));
      }
    #pragma unroll
    for (int k = 0; k < 2; k++) { const bool up = lane & 16; st[k] = (up ? st[2 + k] : st[k]) + __shfl_xor_sync(0xffffffffu, up ? st[k] : st[2 + k], 16); }
    #pragma unroll
    for (int o = 8; o > 0; o >>= 1) { st[0] += __shfl_xor_sync(0xffffffffu, st[0], o); st[1] += __shfl_xor_sync(0xffffffffu, st[1], o); }
    const float mean = st[0] * (1.0f / T_D);
    const float inv = rcp_approx(rbf(sqrt_approx(rbf(rbf(fmaxf(fmaf(-mean, mean, st[1] * (1.0f / T_D)), 0.f)) + 1e-05f))));
    const uint32_t m = pack_bf16(mean, mean), h = pack_bf16(inv - rbf(inv), inv);
    #pragma unroll
    for (int r = 0; r < 2; r++) {
      mb2[r] = __shfl_sync(0xffffffffu, m, 16 * r);
      const uint32_t hr = __shfl_sync(0xffffffffu, h, 16 * r);
      ih[r] = __byte_perm(hr, hr, 0x3232); il[r] = __byte_perm(hr, hr, 0x1010);
    }
  }
  auto norm = [&](int j) {
    #pragma unroll
    for (int r = 0; r < 2; r++) {
      xv[r][j].x = ln_norm2b(xv[r][j].x, mb2[r], ih[r], il[r]); xv[r][j].y = ln_norm2b(xv[r][j].y, mb2[r], ih[r], il[r]);
      xv[r][j].z = ln_norm2b(xv[r][j].z, mb2[r], ih[r], il[r]); xv[r][j].w = ln_norm2b(xv[r][j].w, mb2[r], ih[r], il[r]);
    }
  };
  norm(0);
  TL_MARK2(5, t2 == 0);
  #pragma unroll 1
  for (int ph = 0; ph < 2; ph++) {
    if (first_cols == (ph == 0)) finish_parts(pa, pb, t2, scr + 8192);
    named_bar_sync(5, 256);
    if (ph) break;
    TL_MARK2(7, t2 == 0);
    const uint4 sa = lds_u32x4(scr + 8192 + lane * 16), c1 = lds_u32x4(scr + 8192 + 2048 + lane * 16);
    #pragma unroll
    for (int r = 0; r < 2; r++)
      *reinterpret_cast<uint4*>(g_h + (size_t)(row0 + r) * T_D + lane * 8) = make_uint4(badd2(bmul2(xv[r][0].x, c1.x), sa.x), badd2(bmul2(xv[r][0].y, c1.y), sa.y),
                                                                                        badd2(bmul2(xv[r][0].z, c1.z), sa.z), badd2(bmul2(xv[r][0].w, c1.w), sa.w));
    named_bar_sync(5, 256);
    TL_MARK2(18, t2 == 0);
    if (t2 == 0) red_release_add(&g_hcnt[32 * (1 + (blockIdx.x >> 3))], 1u);
    TL_MARK2(11, t2 == 0);
    norm(1); norm(2); norm(3);
  }
  TL_MARK2(6, t2 == 0);
  #pragma unroll
  for (int j = 1; j < 4; j++) {
    const uint4 sa = lds_u32x4(scr + 8192 + (j * 32 + lane) * 16), c1 = lds_u32x4(scr + 8192 + 2048 + (j * 32 + lane) * 16);
    #pragma unroll
    for (int r = 0; r < 2; r++) {
      xv[r][j].x = badd2(bmul2(xv[r][j].x, c1.x), sa.x); xv[r][j].y = badd2(bmul2(xv[r][j].y, c1.y), sa.y);
      xv[r][j].z = badd2(bmul2(xv[r][j].z, c1.z), sa.z); xv[r][j].w = badd2(bmul2(xv[r][j].w, c1.w), sa.w);
    }
  }
  __syncwarp();
  if (lane == 0) mbar_arrive(b_head + (xv[1][3].w & zero));
  mbar_wait(b_go, 0);
  #pragma unroll
  for (int j = 1; j < 4; j++)
    #pragma unroll
    for (int r = 0; r < 2; r++) *reinterpret_cast<uint4*>(g_h + (size_t)(row0 + r) * T_D + j * 256 + lane * 8) = xv[r][j];
  named_bar_arrive(8, 288);
}

#define MOD_AT (b_empty + 8)
#define MOD_PF 0
#define MOD_SPLIT 16
__device__ __forceinline__ void mod_rest(uint32_t scr, uint32_t b_go, int t, const bf16* __restrict__ cvec, const bf16* __restrict__ w_mod, const bf16* __restrict__ w_r) {
  const int lane = t & 31;
  #pragma unroll 1
  for (int i = t; i < T_D / 2; i += 64) {
    const uint32_t c2 = *reinterpret_cast<const uint32_t*>(cvec + 2 * i);
    sts_u32(scr + i * 4, pack_bf16(silu_bf(bflo(c2)), silu_bf(bfhi(c2))));
  }
  named_bar_sync(11, 64);
  const bf16* wp = w_mod + (size_t)(2 * (t >> 2)) * (6 * T_D) + 2 * T_D + blockIdx.x * 32 + (t & 3) * 8;
  float acc[8];
  #pragma unroll
  for (int i = 0; i < 8; i++) acc[i] = 0.f;
  #pragma unroll 1
  for (int i = 0; i < 32; i += 2) {
    if (i == MOD_SPLIT) mbar_wait(b_go, 0);
    const uint4 w0 = ldg_nc_v4(wp), w1 = ldg_nc_v4(wp + 6 * T_D), w2 = ldg_nc_v4(wp + 32 * 6 * T_D), w3 = ldg_nc_v4(wp + 33 * 6 * T_D);
    wp += 64 * 6 * T_D;
    const uint32_t s0 = lds_u32(scr + (i * 16 + (t >> 2)) * 4), s1 = lds_u32(scr + (i * 16 + 16 + (t >> 2)) * 4);
    fma8(acc, bflo(s0), w0); fma8(acc, bfhi(s0), w1); fma8(acc, bflo(s1), w2); fma8(acc, bfhi(s1), w3);
  }
  #pragma unroll
  for (int j = 0; j < 4; j++) { const bool up = lane & 16; acc[j] = (up ? acc[4 + j] : acc[j]) + __shfl_xor_sync(0xffffffffu, up ? acc[j] : acc[4 + j], 16); }
  #pragma unroll
  for (int j = 0; j < 2; j++) { const bool up = lane & 8; acc[j] = (up ? acc[2 + j] : acc[j]) + __shfl_xor_sync(0xffffffffu, up ? acc[j] : acc[2 + j], 8); }
  { const bool up = lane & 4; acc[0] = (up ? acc[1] : acc[0]) + __shfl_xor_sync(0xffffffffu, up ? acc[0] : acc[1], 4); }
  if (t >= 32) sts_f32(scr + 2048 + lane * 4, acc[0]);
  named_bar_sync(11, 64);
  if (__shfl_sync(0xffffffffu, t, 0) < 32) {
    const int kind = blockIdx.x >> 5;
    float v = rbf(acc[0] + lds_f32(scr + 2048 + lane * 4));
    const int col = (blockIdx.x & 31) * 32 + (lane & 3) * 8 + (lane >> 2);
    uint8_t* dst = g_col + (col >> 7) * 1536;
    if (kind == 2) v = rbf(1.0f + v);
    float vw = v * __bfloat162float(w_r[col]);
    if (kind == 2) {
      const int c = col & 127, i = (c & ~15) + ((c >> 1) & 3) * 4 + ((c >> 3) & 1) * 2 + (c & 1);
      reinterpret_cast<bf16*>(dst)[i] = __float2bfloat16_rn(vw);
      reinterpret_cast<bf16*>(dst)[128 + i] = __float2bfloat16_rn(vw - rbf(vw));
    }
    reinterpret_cast<bf16*>(dst + 512 + (kind & 1) * 512 + (kind >> 1) * 256)[col & 127] = __float2bfloat16_rn(v);
    #pragma unroll
    for (int o = 16; o > 0; o >>= 1) vw += __shfl_xor_sync(0xffffffffu, vw, o);
    if (lane == 0 && (kind == 1 || kind == 2)) g_scal[95 - blockIdx.x] = vw;
  }
  #pragma unroll 1
  for (int i = blockIdx.x * 64 + t; i < (int)(sizeof(g_mail) / 16); i += 128 * 64) reinterpret_cast<uint4*>(&g_mail)[i] = make_uint4(0u, 0u, 0u, 0u);
  named_bar_sync(11, 64);
  if (t == 0) red_release_add(&g_hcnt[0], 1u);
}

#define HPOL_A pol_normal()
#define HPOL_B pol_normal()
#define HMAP_A &tmOl
#define HMAP_B &tmWo
constexpr int AT_NBLK = T_SEQ / 128;
constexpr float AT_HEAD = 7.0f;
#define WO_LATE 12
constexpr int QP_STAG = 3;
constexpr int AT_SPLIT = 28, AT_PIN = 8, PINB = 4;
constexpr int AT_NFULL = 124;
constexpr int AT_PREG = 40, AT_CREG = 232;
constexpr uint32_t AT_SQ = 5 * 32768;
constexpr float AT_C = 0.08838834764831845f * 1.4426950408889634f;
constexpr float AT_RAW_LO = -16.0f, AT_RAW_HI = 24.0f;
constexpr float AT_RAW_SUM = 281474976710656.0f, AT_RAW_MIN = 9.094947017729282e-13f;
constexpr uint32_t AT_SBAR = AT_SQ + 65536 + 256;
constexpr uint32_t AT_SMEM = AT_SQ + 65536 + 3072;

__device__ __forceinline__ uint32_t ring_slot(uint32_t t) { return t - 5u * ((t * 205u) >> 10); }
__device__ __forceinline__ uint32_t qp_pos(uint32_t j, uint32_t it) { return 4u * it + (j & 3u) + ((j & 3u) == 3u ? it : 0u); }
__device__ __forceinline__ uint32_t ring_par(uint32_t t) { return ((t * 205u) >> 10) & 1u; }
__device__ __forceinline__ void softmax_rowmax(const float (&s)[64], float& mx0, float& mx1) {
  float a0 = fmaxf(s[0], s[1]), a1 = fmaxf(s[4], s[5]), a2 = fmaxf(s[8], s[9]), a3 = fmaxf(s[12], s[13]);
  float b0 = fmaxf(s[2], s[3]), b1 = fmaxf(s[6], s[7]), b2 = fmaxf(s[10], s[11]), b3 = fmaxf(s[14], s[15]);
  #pragma unroll
  for (int j = 4; j < 16; j += 4) {
    a0 = fmaxf(a0, fmaxf(s[4 * j + 0], s[4 * j + 1]));  b0 = fmaxf(b0, fmaxf(s[4 * j + 2], s[4 * j + 3]));
    a1 = fmaxf(a1, fmaxf(s[4 * j + 4], s[4 * j + 5]));  b1 = fmaxf(b1, fmaxf(s[4 * j + 6], s[4 * j + 7]));
    a2 = fmaxf(a2, fmaxf(s[4 * j + 8], s[4 * j + 9]));  b2 = fmaxf(b2, fmaxf(s[4 * j + 10], s[4 * j + 11]));
    a3 = fmaxf(a3, fmaxf(s[4 * j + 12], s[4 * j + 13])); b3 = fmaxf(b3, fmaxf(s[4 * j + 14], s[4 * j + 15]));
  }
  mx0 = fmaxf(fmaxf(a0, a1), fmaxf(a2, a3));
  mx1 = fmaxf(fmaxf(b0, b1), fmaxf(b2, b3));
  mx0 = fmaxf(mx0, __shfl_xor_sync(0xffffffffu, mx0, 1));
  mx1 = fmaxf(mx1, __shfl_xor_sync(0xffffffffu, mx1, 1));
  mx0 = fmaxf(mx0, __shfl_xor_sync(0xffffffffu, mx0, 2));
  mx1 = fmaxf(mx1, __shfl_xor_sync(0xffffffffu, mx1, 2));
}
__device__ __forceinline__ void softmax_sub(float (&s)[64], float mc0, float mc1) {
  #pragma unroll
  for (int j = 0; j < 16; j++) { s[4 * j] -= mc0; s[4 * j + 1] -= mc0; s[4 * j + 2] -= mc1; s[4 * j + 3] -= mc1; }
}
template <int LO, int HI>
__device__ __forceinline__ void softmax_exp(float (&s)[64]) {
  #pragma unroll
  for (int i = LO; i < HI; i++) s[i] = ex2_approx(s[i]);
}
__device__ __forceinline__ bool softmax_mode(const float (&s)[64], float& mc0, float& mc1) {
  softmax_rowmax(s, mc0, mc1);
  const bool raw = __all_sync(0xffffffffu, mc0 >= AT_RAW_LO && mc0 <= AT_RAW_HI && mc1 >= AT_RAW_LO && mc1 <= AT_RAW_HI);
  mc0 += AT_HEAD; mc1 += AT_HEAD;
  return raw;
}
__device__ __forceinline__ void rowsum_p(const uint32_t (&p)[32], uint32_t& t0, uint32_t& t1) {
  uint32_t a[16];
  #pragma unroll
  for (int i = 0; i < 8; i++) { a[2 * i] = badd2(p[4 * i], p[4 * i + 2]); a[2 * i + 1] = badd2(p[4 * i + 1], p[4 * i + 3]); }
  #pragma unroll
  for (int i = 0; i < 4; i++) { a[2 * i] = badd2(a[4 * i], a[4 * i + 2]); a[2 * i + 1] = badd2(a[4 * i + 1], a[4 * i + 3]); }
  t0 = badd2(badd2(a[0], a[2]), badd2(a[4], a[6]));
  t1 = badd2(badd2(a[1], a[3]), badd2(a[5], a[7]));
}
__device__ __forceinline__ void add_rowsum(const uint32_t (&p)[32], float& l0, float& l1) {
  uint32_t t0, t1;
  rowsum_p(p, t0, t1);
  l0 += bflo(t0) + bfhi(t0); l1 += bflo(t1) + bfhi(t1);
}
__device__ __forceinline__ void pack_p(uint32_t (&p)[32], const float (&s)[64]) {
  #pragma unroll
  for (int i = 0; i < 32; i++) p[i] = pack_bf16(s[2 * i], s[2 * i + 1]);
}
__device__ __noinline__ void attn_rows_exact(uint32_t sq, uint32_t so, int hsel, const bf16* __restrict__ kh, const bf16* __restrict__ vh) {
  const int warp = (threadIdx.x >> 5) & 3, lane = threadIdx.x & 31;
  const size_t hofs = (size_t)((blockIdx.x < 128 ? blockIdx.x >> 4 : 15) * 2 + hsel) * T_SEQ * T_DH;
  kh += hofs; vh += hofs;
  #pragma unroll 1
  for (int r = 16 * warp; r < 16 * warp + 16; r++) {
    const uint32_t ad = (lane >> 4) * 16384 + r * 128 + ((((lane & 15) >> 1) ^ (r & 7)) << 4) + (lane & 1) * 8;
    uint2 qv; asm volatile("ld.shared.v2.u32 {%0, %1}, [%2];" : "=r"(qv.x), "=r"(qv.y) : "r"(sq + ad) : "memory");
    const float q0 = bflo(qv.x), q1 = bfhi(qv.x), q2 = bflo(qv.y), q3 = bfhi(qv.y);
    float m = -INFINITY, l = 0.f, o0 = 0.f, o1 = 0.f, o2 = 0.f, o3 = 0.f;
    #pragma unroll 1
    for (int key = 0; key < T_SEQ; key++) {
      const uint2 kv = *reinterpret_cast<const uint2*>(kh + (size_t)key * T_DH + lane * 4);
      const uint2 vv = *reinterpret_cast<const uint2*>(vh + (size_t)key * T_DH + lane * 4);
      float sc = (q0 * bflo(kv.x) + q1 * bfhi(kv.x)) + (q2 * bflo(kv.y) + q3 * bfhi(kv.y));
      #pragma unroll
      for (int o = 16; o > 0; o >>= 1) sc += __shfl_xor_sync(0xffffffffu, sc, o);
      const float mn = fmaxf(m, sc);
      const float al = (m == mn) ? 1.0f : ex2_approx(m - mn), p = rbf(ex2_approx(sc - mn));
      m = mn;
      l = fmaf(l, al, p);
      o0 = fmaf(o0, al, p * bflo(vv.x)); o1 = fmaf(o1, al, p * bfhi(vv.x));
      o2 = fmaf(o2, al, p * bflo(vv.y)); o3 = fmaf(o3, al, p * bfhi(vv.y));
    }
    const float inv = rcp_approx(l);
    asm volatile("st.shared.v2.u32 [%0], {%1, %2};" :: "r"(so + ad), "r"(pack_bf16(o0 * inv, o1 * inv)), "r"(pack_bf16(o2 * inv, o3 * inv)) : "memory");
  }
}
__device__ __forceinline__ void issue_qk(float (&s)[64], const uint32_t (&q)[32], uint32_t k_lo) {
  wgmma_fence();
  wgmma_m64n128k16_rs<0>(s, q[0], q[1], q[2], q[3], k_lo, 0);
  wgmma_m64n128k16_rs<2>(s, q[4], q[5], q[6], q[7], k_lo, 1);
  wgmma_m64n128k16_rs<4>(s, q[8], q[9], q[10], q[11], k_lo, 1);
  wgmma_m64n128k16_rs<6>(s, q[12], q[13], q[14], q[15], k_lo, 1);
  wgmma_m64n128k16_rs<1024>(s, q[16], q[17], q[18], q[19], k_lo, 1);
  wgmma_m64n128k16_rs<1026>(s, q[20], q[21], q[22], q[23], k_lo, 1);
  wgmma_m64n128k16_rs<1028>(s, q[24], q[25], q[26], q[27], k_lo, 1);
  wgmma_m64n128k16_rs<1030>(s, q[28], q[29], q[30], q[31], k_lo, 1);
  wgmma_commit();
}
__device__ __forceinline__ void issue_pv(float (&o)[64], const uint32_t (&p)[32], uint32_t v_lo, int accumulate) {
  wgmma_fence();
  wgmma_m64n128k16_rs_tb<0>(o, p[0], p[1], p[2], p[3], v_lo, accumulate);
  wgmma_m64n128k16_rs_tb<128>(o, p[4], p[5], p[6], p[7], v_lo, 1);
  wgmma_m64n128k16_rs_tb<256>(o, p[8], p[9], p[10], p[11], v_lo, 1);
  wgmma_m64n128k16_rs_tb<384>(o, p[12], p[13], p[14], p[15], v_lo, 1);
  wgmma_m64n128k16_rs_tb<512>(o, p[16], p[17], p[18], p[19], v_lo, 1);
  wgmma_m64n128k16_rs_tb<640>(o, p[20], p[21], p[22], p[23], v_lo, 1);
  wgmma_m64n128k16_rs_tb<768>(o, p[24], p[25], p[26], p[27], v_lo, 1);
  wgmma_m64n128k16_rs_tb<896>(o, p[28], p[29], p[30], p[31], v_lo, 1);
  wgmma_commit();
}
__device__ __forceinline__ void block_end(uint32_t zero, uint32_t bar) {
  #pragma unroll 1
  for (uint32_t i = 0; i < zero; i++) mbar_arrive(bar);
}
__device__ __forceinline__ void rescale_o(float (&o)[64], float al0, float al1) {
  #pragma unroll
  for (int j = 0; j < 16; j++) { o[4 * j] *= al0; o[4 * j + 1] *= al0; o[4 * j + 2] *= al1; o[4 * j + 3] *= al1; }
}

__device__ __forceinline__ void stage_o(const float (&o)[64], float i0, float i1, uint32_t dst, int lane) {
  #pragma unroll
  for (int J = 0; J < 16; J += 2)
    stmatrix_x4(dst + (J >> 3) * 16384 + ((((J & 7) + (lane >> 4)) ^ (lane & 7)) << 4),
                pack_bf16(o[4 * J + 0] * i0, o[4 * J + 1] * i0), pack_bf16(o[4 * J + 2] * i1, o[4 * J + 3] * i1),
                pack_bf16(o[4 * J + 4] * i0, o[4 * J + 5] * i0), pack_bf16(o[4 * J + 6] * i1, o[4 * J + 7] * i1));
}
__device__ __forceinline__ bool finish_l(float& l0, float& l1) {
  l0 += __shfl_xor_sync(0xffffffffu, l0, 1); l1 += __shfl_xor_sync(0xffffffffu, l1, 1);
  l0 += __shfl_xor_sync(0xffffffffu, l0, 2); l1 += __shfl_xor_sync(0xffffffffu, l1, 2);
  const bool redo = __any_sync(0xffffffffu, !(l0 <= AT_RAW_SUM && l1 <= AT_RAW_SUM && l0 >= AT_RAW_MIN && l1 >= AT_RAW_MIN));
  l0 = rcp_approx(l0); l1 = rcp_approx(l1);
  return redo;
}
template <int J0>
__device__ __forceinline__ void stage_q(const float (&acc)[128], float c, uint32_t dst, int lane) {
  #pragma unroll
  for (int J = J0; J < J0 + 16; J += 2)
    stmatrix_x4(dst + (J >> 3) * 16384 + ((((J & 7) + (lane >> 4)) ^ (lane & 7)) << 4),
                pack_bf16(acc[4 * J + 0] * c, acc[4 * J + 1] * c), pack_bf16(acc[4 * J + 2] * c, acc[4 * J + 3] * c),
                pack_bf16(acc[4 * J + 4] * c, acc[4 * J + 5] * c), pack_bf16(acc[4 * J + 6] * c, acc[4 * J + 7] * c));
}
__device__ __forceinline__ void store_o(const CUtensorMap* tmO, uint32_t src, int head, int row) {
  tma_store_2d(tmO, src, head * T_DH, row);
  tma_store_2d(tmO, src + 16384, head * T_DH + 64, row);
  bulk_commit();
}
__device__ __forceinline__ void mma_bf16(float (&d)[4], uint32_t a0, uint32_t a1, uint32_t a2, uint32_t a3, uint32_t b0, uint32_t b1) {
  asm volatile("mma.sync.aligned.m16n8k16.row.col.f32.bf16.bf16.f32 {%0, %1, %2, %3}, {%4, %5, %6, %7}, {%8, %9}, {%0, %1, %2, %3};"
               : "+f"(d[0]), "+f"(d[1]), "+f"(d[2]), "+f"(d[3]) : "r"(a0), "r"(a1), "r"(a2), "r"(a3), "r"(b0), "r"(b1));
}
struct GemvSel { uint32_t lo0, hi0, lo1, hi1; };
__device__ __forceinline__ GemvSel gemv_sel(int lane) {
  const uint32_t lo = (lane & 8) ? 0x1044u : 0x4410u, hi = (lane & 8) ? 0x3244u : 0x4432u;
  GemvSel s; s.lo0 = (lane & 16) ? 0x4444u : lo; s.hi0 = (lane & 16) ? 0x4444u : hi; s.lo1 = (lane & 16) ? lo : 0x4444u; s.hi1 = (lane & 16) ? hi : 0x4444u;
  return s;
}
#define GEMV_B0(j, h, s) __byte_perm((j) < 2 ? (h).x : (h).y, 0u, ((j) & 1) ? (s).hi0 : (s).lo0)
#define GEMV_B1(j, h, s) __byte_perm((j) < 2 ? (h).x : (h).y, 0u, ((j) & 1) ? (s).hi1 : (s).lo1)
__device__ __forceinline__ float4 gemv_out(const float (&d)[4], int lane) {
  const bool tk = lane & 1;
  const float r0 = __shfl_xor_sync(0xffffffffu, tk ? d[0] : d[1], 1), r1 = __shfl_xor_sync(0xffffffffu, tk ? d[2] : d[3], 1);
  return tk ? make_float4(r0, d[1], r1, d[3]) : make_float4(d[0], r0, d[2], r1);
}
#define OG_NG 8
#define HOIST 1
#define PUT_N 2
#define H_STAG 2
#define NOZERO 1
#define PVPIN 0
#define QKPIN 0
#define ALIGN 1
#define AL_P 60
#define AL_SLEEP 1200
#define AL_MAX 800
#define AL_ADD 0
#define X_PF 0
#define POLL_NS 200
#define KV3D 1
#define W3D 1
#define OG_PRE 10
#define OG_JOBS 7
#define OG_GRP 7
#define LD_FIRST 1
#define LD_STAG (OG_GRP / 2)
constexpr int OG_ST = 5, OG_NKB = T_DQKV / 64 - OG_PRE, OG_MOE = T_F / 32;
__device__ __forceinline__ int pre_loc(int job) {
  const int step = ((job >> 4) << 2) + (job & 3);
  return (step < OG_JOBS ? 2 * step : step < 2 * OG_JOBS ? 2 * (step - OG_JOBS) + 1 : step) * 4 + ((job >> 2) & 3);
}
__device__ __forceinline__ int pre_kb(int i) { return (i >> 1) * 4 + (i & 1); }
__device__ __forceinline__ int own_kb(int i) { return i < (OG_PRE & ~1) ? pre_kb(i) + 2 : i + OG_PRE; }
constexpr int OG_POS = 8;
constexpr uint32_t OG_STAGE = 32768;
constexpr uint32_t OG_SCOL = AT_SBAR + 512;
constexpr uint32_t OG_SMISC = AT_SBAR + 2048;
constexpr int OG_XPOS = OG_POS + OG_NKB;
constexpr uint32_t OG_SWD = AT_SQ, OG_PSLOT = AT_SQ;
constexpr uint32_t OG_SWD1 = (OG_XPOS % OG_ST) * OG_STAGE;
constexpr uint32_t OG_XSLOT = AT_SQ + 32768;
constexpr uint32_t OG_OSLOT = ((OG_XPOS + 1) % OG_ST) * OG_STAGE;
constexpr uint32_t OG_SH2 = ((OG_XPOS + 2) % OG_ST) * OG_STAGE;
constexpr uint32_t OG_SRED = ((OG_XPOS + 3) % OG_ST) * OG_STAGE;
constexpr uint32_t OG_SSTAT = OG_SRED + 16384;
constexpr uint32_t OG_SGU = OG_SRED + 8192;
constexpr uint32_t OG_SFIN = OG_SGU + 256;
#define OGM 2
#define OG_MT(b) (((b) >> OGM) & 15)
#define OG_NT(b) (((b) & ((1 << OGM) - 1)) + (((b) >> (4 + OGM)) << OGM))
#define TAIL_SETUP \
  const uint32_t bar_full = sbase + AT_SBAR, bar_empty = bar_full + 40; \
  const uint32_t bar_wd = bar_full + 168, bar_col = bar_full + 176, bar_out = bar_full + 184, bar_end = bar_full + 192; \
  const uint32_t bar_key = bar_full + 200, bar_h2 = bar_full + 208, bar_sel = bar_full + 216; \
  const int mt = OG_MT(blockIdx.x), nt = OG_NT(blockIdx.x); \
  const int m0 = mt * 128, n0 = nt * 128; \
  const bool has_moe = (int)blockIdx.x < OG_MOE; \
  (void)bar_empty; (void)bar_wd; (void)bar_col; (void)bar_out; (void)bar_end; (void)bar_key; (void)bar_h2; (void)bar_sel; (void)m0; (void)n0; (void)has_moe;

__device__ __forceinline__ void tail_producer(uint32_t sbase, uint32_t ph, uint64_t pol, const CUtensorMap* tmA, const CUtensorMap* tmB, const CUtensorMap* tmX) {
  TAIL_SETUP
  uint32_t stage = OG_POS % OG_ST;
  int kb = 0;
  #pragma unroll 1
  for (int seg = 0; seg < 2; seg++) {
    mbar_wait(bar_full + 264, seg);
    fence_proxy_async_global();
    const int end = seg == 0 ? 32 - OG_PRE : OG_NKB;
    #pragma unroll 1
    for (; kb < end; kb++) {
      const uint32_t fb = bar_full + 8 * stage, sa = sbase + stage * OG_STAGE;
      const int k0 = own_kb(kb) * 64;
      mbar_wait(bar_empty + 8 * stage, ph);
      mbar_expect_tx(fb, OG_STAGE);
      tma_load_3d_hint(sa + 16384, tmB, k0, 2 * nt, fb, pol);
      tma_load_2d_hint(sa, tmA, k0, m0, fb, pol);
      if (++stage == OG_ST) { stage = 0; ph ^= 1; }
    }
  }
  if (has_moe) {
    mbar_wait(bar_empty + 8 * (OG_XPOS % OG_ST), ph);
    mbar_expect_tx(bar_wd, OG_STAGE);
    tma_load_3d_hint(sbase + OG_SWD1, tmX, blockIdx.x * 32, 8, bar_wd, pol);
  }
}

__device__ __forceinline__ uint32_t out2(uint32_t x1, uint32_t mb2, uint32_t ih, uint32_t il, uint32_t c1, uint32_t sb, uint32_t gb) {
  const uint32_t h2 = badd2(bmul2(ln_norm2b(x1, mb2, ih, il), c1), sb);
  return badd2(x1, bmul2(gb, bfma2(h2, 0u, h2)));
}
#define OGTIME gtime()
#define PRE_N 1
#define PRE_PACE 150
#define X_PACE 200
#define WD_LATE 0
#define WD_PACE 300
__device__ __forceinline__ void tail_exchange(uint32_t sbase, const CUtensorMap* tmOut, const bf16* __restrict__ w_down, const bf16* __restrict__ w_r, const bf16* __restrict__ x, bf16* __restrict__ out) {
    TAIL_SETUP
    const int lane = threadIdx.x & 31, wi = __shfl_sync(0xffffffffu, threadIdx.x >> 5, 0);
    if (wi == 3) {
      mbar_wait(bar_full + 264, 0);
      if (blockIdx.x < AT_NFULL) {
        uint32_t a, b;
        asm volatile("ld.relaxed.gpu.global.u32 %0, [%1];" : "=r"(a) : "l"(g_smid + 32 + blockIdx.x - lane) : "memory");
        b = __shfl_down_sync(0xffffffffu, a, 1);
        unsigned int* tm = g_tmax + blockIdx.x - min((int)blockIdx.x, __ffs(__ballot_sync(0xffffffffu, b >= a)) - 1);
        mbar_wait(bar_full + 312, 0);
        if (lane == 0) {
          asm volatile("mov.u32 %0, %%globaltimer_lo;" : "=r"(a));
          asm volatile("red.relaxed.gpu.global.max.u32 [%0], %1;" :: "l"(tm), "r"(a) : "memory");
          __nanosleep(AL_SLEEP);
          asm volatile("ld.relaxed.gpu.global.u32 %0, [%1];" : "=r"(b) : "l"(tm) : "memory");
          b -= a;
          sts_u32(sbase + OG_SMISC + 32, (b < AL_MAX ? b * 13 / 8 : 0u) + AL_ADD);
          mbar_arrive(bar_full + 320);
        }
        named_bar_sync(15, 32);
      }
      mbar_wait(bar_full + 264, 1);
      float a = g_scal[lane], b = g_scal[32 + lane];
      #pragma unroll
      for (int i = 0; i < 3; i++) {
        const uint4 v = *reinterpret_cast<const uint4*>(g_col + nt * 1536 + i * 512 + lane * 16);
        sts_u32x4(sbase + OG_SCOL + i * 512 + lane * 16, v.x, v.y, v.z, v.w);
      }
      #pragma unroll
      for (int o = 16; o > 0; o >>= 1) { a += __shfl_xor_sync(0xffffffffu, a, o); b += __shfl_xor_sync(0xffffffffu, b, o); }
      if (lane == 0) sts_f32x2(sbase + OG_SMISC, a, b);
      const uint64_t pol = policy_evict_first();
      #pragma unroll 1
      for (int r = lane >> 4; r < 128; r += 4) {
        __nanosleep(X_PACE);
        #pragma unroll
        for (int j = 0; j < 4; j += 2)
          asm volatile("cp.async.cg.shared.global.L2::cache_hint [%0], [%1], 16, %2;" :: "r"(sbase + OG_XSLOT + (lane & 8) * 2048 + (r + j) * 128 + (((lane ^ (r + j)) & 7) << 4)),
                       "l"(x + (size_t)(m0 + r + j) * T_D + n0 + (lane & 15) * 8), "l"(pol) : "memory");
      }
      asm volatile("cp.async.wait_all;" ::: "memory");
      __syncwarp();
      if (lane == 0) mbar_arrive(bar_col);
    } else if (wi == 2) {
      if (elect_one()) {
        const uint32_t b_free = bar_full + (blockIdx.x < AT_NFULL ? 80 : 160);
        mbar_wait(b_free, 0); mbar_wait(b_free, 1);
        #pragma unroll 1
        for (unsigned int i = 0; i < (1u << 20) && ld_acquire(&g_hcnt[32 * (1 + mt) + 4 + (nt >> 1)]) == 0u; i++) __nanosleep(POLL_NS);
        TL_MARK2(23, true);
        fence_proxy_async_global();
        TL_MARK2(4, true);
        mbar_expect_tx(bar_full + 272, 32768);
        #pragma unroll 1
        for (int i = 0; i < PRE_N; i++) {
          bulk_load_hint(sbase + OG_PSLOT + i * (32768 / PRE_N), g_pre + pre_loc(mt * 4 + (nt >> 1)) * 4096 + (nt & 1) * 2048 + i * (2048 / PRE_N), 32768 / PRE_N,
                         bar_full + 272, policy_evict_first());
          if (PRE_N > 1) __nanosleep(PRE_PACE);
        }
      }
      named_bar_sync(14, 32);
      if (has_moe) {
        mbar_wait(bar_full + 96, 1); mbar_wait(bar_full + 304, 0);
        const uint64_t pol = policy_evict_first();
        #pragma unroll 1
        for (int r = 0; r < 32; r++) {
          __nanosleep(WD_PACE);
          #pragma unroll
          for (int j = 0; j < 2; j++)
            asm volatile("cp.async.cg.shared.global.L2::cache_hint [%0], [%1], 16, %2;" :: "r"(sbase + OG_SWD + (4 * j + (lane >> 3)) * 4096 + r * 128 + (((lane ^ r) & 7) << 4)),
                         "l"((const uint8_t*)w_down + (size_t)blockIdx.x * 65536 + r * 2048 + j * 512 + lane * 16), "l"(pol) : "memory");
        }
        asm volatile("cp.async.wait_all;" ::: "memory");
        __syncwarp();
        if (lane == 0) mbar_arrive(bar_wd);
      }
    }
    const uint4 wrv = ldg_nc_v4(w_r + threadIdx.x * 8);
    mbar_wait(bar_end, 0);
    TL_MARK2(22, lane == 0);
    if (wi == 0) {
      uint32_t k1 = 0u, k2 = 0u;
      #pragma unroll 1
      for (unsigned int spin = 0; spin < (1u << 22) && __any_sync(0xffffffffu, k1 == 0u); spin++) asm volatile("ld.relaxed.gpu.global.u32 %0, [%1];" : "=r"(k1) : "l"(g_key + lane) : "memory");
      TL_MARK2(28, lane == 0);
      warp_top2(k1, k2);
      if (lane == 0) {
        const uint32_t r1 = 0xffffu - (k1 & 0xffffu), r2 = 0xffffu - (k2 & 0xffffu);
        sts_u32x4(sbase + OG_SMISC + 64, r1, r2, (r1 >> 7) * 2, (r2 >> 7) * 2 + ((r1 >> 7) == (r2 >> 7)));
        mbar_arrive(bar_sel);
      }
    } else if (wi < 3) {
          mbar_wait(bar_key, 0);
          const uint4 kk = lds_u32x4(sbase + OG_SSTAT + 1024 + lane * 16);
          uint32_t k1 = max(kk.x, kk.y), k2 = min(kk.x, kk.y);
          k2 = max(max(k2, min(kk.z, kk.w)), min(k1, max(kk.z, kk.w))); k1 = max(k1, max(kk.z, kk.w));
          warp_top2(k1, k2);
          if (wi == 1) {
            if (lane == 0 && nt == (mt & 7)) st_relaxed2(g_key + mt * 2, k1, k2);
            TL_MARK2(27, lane == 0);
          } else {
            const uint32_t r = (~((lane & 16) ? k2 : k1)) & 127u, ch = lane & 15;
            const uint2 st = lds_u32x2(sbase + OG_SSTAT + r * 8);
            const uint4 xc = lds_u32x4(sbase + OG_XSLOT + (ch >> 3) * 16384 + r * 128 + (((ch ^ r) & 7) << 4));
            const uint4 c1 = lds_u32x4(sbase + OG_SCOL + 768 + ch * 16), sh = lds_u32x4(sbase + OG_SCOL + 1024 + ch * 16);
            const float inr = __uint_as_float(st.y);
            float* dst = reinterpret_cast<float*>(g_cand + (mt * 2 + (lane >> 4)) * 256 + nt * 16 + ch);
            st_tagged4(dst + 512, __uint_as_float(ln_mod2(xc.x, st.x, inr, c1.x, sh.x)), __uint_as_float(ln_mod2(xc.y, st.x, inr, c1.y, sh.y)),
                       __uint_as_float(ln_mod2(xc.z, st.x, inr, c1.z, sh.z)), __uint_as_float(ln_mod2(xc.w, st.x, inr, c1.w, sh.w)));
            st_tagged4(dst, __uint_as_float(xc.x), __uint_as_float(xc.y), __uint_as_float(xc.z), __uint_as_float(xc.w));
          }
    }
    mbar_wait(bar_sel, 0);
    const uint4 sel = lds_u32x4(sbase + OG_SMISC + 64);
    const int sel0 = (int)sel.x, sel1 = (int)sel.y;
    {
      const float* src0 = reinterpret_cast<const float*>(g_cand + sel.z * 256 + 128 + threadIdx.x);
      const float* src1 = reinterpret_cast<const float*>(g_cand + sel.w * 256 + 128 + threadIdx.x);
      float4 h0, h1;
      #pragma unroll 1
      for (unsigned int spin = 0; spin < (1u << 20); spin++) { h0 = ld_tagged4(src0); h1 = ld_tagged4(src1); if (__all_sync(0xffffffffu, tagged4(h0) & tagged4(h1))) break; }
      sts_f32x4(sbase + OG_SH2 + threadIdx.x * 16, h0.x, h0.y, h0.z, h0.w);
      sts_f32x4(sbase + OG_SH2 + 2048 + threadIdx.x * 16, h1.x, h1.y, h1.z, h1.w);
      __syncwarp();
      if (lane == 0) mbar_arrive(bar_h2);
      TL_MARK2(12, lane == 0);
      if (blockIdx.x >> 6) h0 = h1;
      float v[8], wr[8];
      unpack8(make_uint4(__float_as_uint(h0.x), __float_as_uint(h0.y), __float_as_uint(h0.z), __float_as_uint(h0.w)), v); unpack8(wrv, wr);
      float r = 0.f;
      #pragma unroll
      for (int i = 0; i < 8; i++) r = fmaf(v[i], wr[i], r);
      #pragma unroll
      for (int o = 16; o > 0; o >>= 1) r += __shfl_xor_sync(0xffffffffu, r, o);
      if (lane == 0) sts_f32(sbase + OG_SMISC + 192 + wi * 4, r);
    }
    mbar_wait(bar_out, 0);
    if ((sel0 >> 7) == mt || (sel1 >> 7) == mt) {
      #pragma unroll 2
      for (int i = 0; i < 16; i++) {
        const int r = i * 8 + (threadIdx.x >> 4), ch = threadIdx.x & 15;
        if (m0 + r != sel0 && m0 + r != sel1)
          *reinterpret_cast<uint4*>(out + (size_t)(m0 + r) * T_D + n0 + ch * 8) =
              lds_u32x4(sbase + OG_OSLOT + (ch >> 3) * 16384 + r * 128 + (((ch & 7) ^ (r & 7)) << 4));
      }
    } else if (threadIdx.x == 0) {
      tma_store_2d(tmOut, sbase + OG_OSLOT, n0, m0);
      tma_store_2d(tmOut, sbase + OG_OSLOT + 16384, n0 + 64, m0);
      bulk_commit();
    }
    if (blockIdx.x == 0 && threadIdx.x < 68) *reinterpret_cast<uint4*>(g_hcnt + 32 * (threadIdx.x >> 2) + 4 * (threadIdx.x & 3)) = make_uint4(0u, 0u, 0u, 0u);
    if (threadIdx.x < 64) g_modpart[blockIdx.x * 64 + threadIdx.x] = 0.f;
    if (ALIGN && threadIdx.x == 64) g_tmax[blockIdx.x] = 0u;
    {
      const int tk = blockIdx.x >> 6, c0 = (blockIdx.x & 63) * 16;
      const uint32_t gb2 = *reinterpret_cast<const uint32_t*>(g_col + (c0 >> 7) * 1536 + 512 + 768 + ((c0 & 127) + (threadIdx.x & 14)) * 2);
      const uint32_t* xp = reinterpret_cast<const uint32_t*>(g_cand + (tk ? sel.w : sel.z) * 256) + ((c0 + (threadIdx.x & 14)) >> 1);
      uint32_t x2 = 0u;
      #pragma unroll 1
      for (unsigned int spin = 0; spin < (1u << 20) && __any_sync(0xffffffffu, x2 == 0u); spin++) asm volatile("ld.relaxed.gpu.global.u32 %0, [%1];" : "=r"(x2) : "l"(xp) : "memory");
      const float* src = g_ypart + (size_t)((threadIdx.x >> 2) * 2 + tk) * T_D + c0 + (threadIdx.x & 3) * 4;
      const bool four = threadIdx.x < (OG_MOE - 96) * 4;
      if (threadIdx.x == 0) hint_wait(CNT_Y, (uint32_t)OG_MOE);
      named_bar_sync(10, 128);
      float4 p0, p1, p2, p3;
      #pragma unroll 1
      for (unsigned int spin = 0; spin < (1u << 20); spin++) {
        p0 = ld_tagged4(src); p1 = ld_tagged4(src + 64 * T_D); p2 = ld_tagged4(src + 128 * T_D); p3 = ld_tagged4(four ? src + 192 * T_D : src);
        if (__all_sync(0xffffffffu, tagged4(p0) & tagged4(p1) & tagged4(p2) & tagged4(p3))) break;
      }
      if (four) { p2.x += p3.x; p2.y += p3.y; p2.z += p3.z; p2.w += p3.w; }
      p0.x = (p0.x + p1.x) + p2.x; p0.y = (p0.y + p1.y) + p2.y; p0.z = (p0.z + p1.z) + p2.z; p0.w = (p0.w + p1.w) + p2.w;
      #pragma unroll
      for (int o = 4; o <= 16; o <<= 1) {
        p0.x += __shfl_xor_sync(0xffffffffu, p0.x, o); p0.y += __shfl_xor_sync(0xffffffffu, p0.y, o);
        p0.z += __shfl_xor_sync(0xffffffffu, p0.z, o); p0.w += __shfl_xor_sync(0xffffffffu, p0.w, o);
      }
      if (lane < 4) sts_f32x4(sbase + OG_SFIN + (threadIdx.x >> 5) * 64 + lane * 16, p0.x, p0.y, p0.z, p0.w);
      named_bar_sync(10, 128);
      TL_MARK2(21, threadIdx.x == 0);
      if (threadIdx.x < 16) {
        const uint32_t ya = sbase + OG_SFIN + threadIdx.x * 4, rp = sbase + OG_SMISC + 192;
        float y = (lds_f32(ya) + lds_f32(ya + 64)) + (lds_f32(ya + 128) + lds_f32(ya + 192));
        const float r = rbf((lds_f32(rp) + lds_f32(rp + 4)) + (lds_f32(rp + 8) + lds_f32(rp + 12)));
        const float rs = rbf(sigmoid_f(r));
        const uint32_t h2p = lds_u32(sbase + OG_SH2 + tk * 2048 + (c0 + (threadIdx.x & 14)) * 2);
        const float fh = (lane & 1) ? bfhi(h2p) : bflo(h2p);
        y = rbf(y);
        y = rbf(y * rs);
        const float upd = rbf(rbf(fh * 0.0f) + y);
        out[(size_t)(tk ? sel1 : sel0) * T_D + c0 + threadIdx.x] =
            __float2bfloat16_rn(((lane & 1) ? bfhi(x2) : bflo(x2)) + rbf(((lane & 1) ? bfhi(gb2) : bflo(gb2)) * rbf(fh + upd)));
      }
      if (threadIdx.x == 0) bulk_wait_read<0>();
    }
    TL_END(4, threadIdx.x == 0);
}

__device__ __forceinline__ void load_pre(uint4* pre, uint32_t sbase, uint32_t buf, int t2) {
  mbar_wait(sbase + AT_SBAR + 272, 0);
  #pragma unroll
  for (int i = 0; i < 8; i++) pre[i] = lds_u32x4(sbase + buf + i * 4096 + t2 * 16);
}
__device__ __forceinline__ void tail_consumer(uint32_t sbase, const uint4 (&pre)[8], int cwg, const bf16* __restrict__ w_gate, const bf16* __restrict__ w_up) {
    TAIL_SETUP
    const int tid = threadIdx.x & 127, t2 = threadIdx.x - 128;
    const int warp = tid >> 5, lane = tid & 31, w8 = t2 >> 5;
    const uint32_t dbase = (sbase & 0x3FFFFu) >> 4;
    const uint32_t a_base = dbase + ((cwg * 8192) >> 4) + (1u << 16);
    const uint32_t b_base = dbase + (16384 >> 4) + (512u << 16);
    TL_MARK2(25, threadIdx.x == 128);
    const uint64_t pol = policy_evict_first();
    const bf16* pw = ((lane & 16) ? w_up : w_gate) + (size_t)(w8 * 128 + (lane & 3) * 4) * T_F + (has_moe ? blockIdx.x : 0) * 32 + ((lane >> 2) & 3) * 8;
    uint4 wv[32];
    float acc[64];
    #pragma unroll
    for (int i = 0; i < 8; i++) {
      acc[8 * i] = bflo(pre[i].x); acc[8 * i + 1] = bfhi(pre[i].x); acc[8 * i + 2] = bflo(pre[i].y); acc[8 * i + 3] = bfhi(pre[i].y);
      acc[8 * i + 4] = bflo(pre[i].z); acc[8 * i + 5] = bfhi(pre[i].z); acc[8 * i + 6] = bflo(pre[i].w); acc[8 * i + 7] = bfhi(pre[i].w);
    }
    if (blockIdx.x < AT_NFULL) {
      const uint32_t c0 = clock_lo();
      mbar_wait(bar_full + 320, 0);
      const uint32_t d = lds_u32(sbase + OG_SMISC + 32);
      while (clock_lo() - c0 < d) {}
    }
    {
      uint32_t stage = OG_POS % OG_ST, phase = (OG_POS / OG_ST) & 1, prev = 12;
      int kb = 0;
      #pragma unroll
      for (int g = 0; g <= OG_NG; g++) {
        const int end = g == OG_NG ? OG_NKB : LD_FIRST + g * OG_GRP + LD_STAG * cwg;
        #pragma unroll 1
        do {
          mbar_wait(bar_full + 8 * stage, phase);
          const uint32_t a_lo = a_base + stage * (OG_STAGE >> 4), b_lo = b_base + stage * (OG_STAGE >> 4);
          wgmma_fence();
          wgmma_m64n128k16_ss_tb<0, 0>(acc, a_lo, b_lo, 1);
          wgmma_m64n128k16_ss_tb<2, 128>(acc, a_lo, b_lo, 1);
          wgmma_m64n128k16_ss_tb<4, 256>(acc, a_lo, b_lo, 1);
          wgmma_m64n128k16_ss_tb<6, 384>(acc, a_lo, b_lo, 1);
          wgmma_commit();
          wgmma_wait<1>();
          if (tid == 0) mbar_arrive(bar_empty + 8 * prev);
          prev = stage;
          if (++stage == OG_ST) { stage = 0; phase ^= 1; }
        } while (++kb < end);
        #pragma unroll
        for (int j = 4 * g; j < 4 * g + 4 && j < 32; j++) wv[j] = ldg_stream_v4(pw + (size_t)(16 * (j >> 2) + (j & 3)) * T_F, pol);
      }
    }
    mbar_wait(bar_col, 0);
    if (__builtin_expect(!has_moe, 0)) {
      load_pre(wv, sbase, AT_SQ, t2);
    }
    wgmma_wait<0>();
    fence_regs(acc);
    if (__builtin_expect(!has_moe, 0)) {
      #pragma unroll
      for (int i = 0; i < 8; i++) {
        acc[8 * i] += bflo(wv[i].x); acc[8 * i + 1] += bfhi(wv[i].x); acc[8 * i + 2] += bflo(wv[i].y); acc[8 * i + 3] += bfhi(wv[i].y);
        acc[8 * i + 4] += bflo(wv[i].z); acc[8 * i + 5] += bfhi(wv[i].z); acc[8 * i + 6] += bflo(wv[i].w); acc[8 * i + 7] += bfhi(wv[i].w);
      }
    }
    if (tid == 0) mbar_arrive(bar_end);
    TL_MARK2(9, lane == 0);
    const int q2 = 2 * (lane & 3);
    const uint32_t frag = (64 * cwg + 16 * warp + (lane & 7) + 8 * ((lane >> 3) & 1)) * 128;
    const int fsw = lane & 7, fhi = lane >> 4;
    {
      float dl[4] = {0.f, 0.f, 0.f, 0.f}, da[4] = {0.f, 0.f, 0.f, 0.f}, db[4] = {0.f, 0.f, 0.f, 0.f};
      const uint32_t tb = sbase + OG_SCOL + (lane & 8) * 32 + (lane & 3) * 8, g = lane >> 2;
      const uint32_t msk = (g == 1 || g == 2) ? 0xffffffffu : 0u, one = g == 0 ? 0x3F803F80u : 0u;
      #pragma unroll
      for (int J = 0; J < 16; J += 2) {
        const uint32_t ad = sbase + OG_XSLOT + (J >> 3) * 16384 + frag + ((((J & 7) + fhi) ^ fsw) << 4);
        uint32_t xr[4];
        ldmatrix_x4(ad, xr[0], xr[1], xr[2], xr[3]);
        const uint2 cw = lds_u32x2(tb + J * 16);
        #pragma unroll
        for (int h = 0; h < 2; h++) {
          const uint32_t ga = lds_u32(sbase + OG_SCOL + 512 + (8 * (J + h) + q2) * 2);
          xr[2 * h] = badd2(xr[2 * h], bmul2(ga, pack_bf16(acc[4 * (J + h)], acc[4 * (J + h) + 1])));
          xr[2 * h + 1] = badd2(xr[2 * h + 1], bmul2(ga, pack_bf16(acc[4 * (J + h) + 2], acc[4 * (J + h) + 3])));
        }
        stmatrix_x4(ad, xr[0], xr[1], xr[2], xr[3]);
        mma_bf16(dl, xr[0], xr[1], xr[2], xr[3], (cw.x & msk) | one, (cw.y & msk) | one);
        mma_bf16(da, xr[0], xr[1], xr[2], xr[3], xr[0], xr[2]);
        mma_bf16(db, xr[0], xr[1], xr[2], xr[3], xr[1], xr[3]);
      }
      {
        const int dsrc = (lane & ~3) + (g >> 1);
        const float qa = __shfl_sync(0xffffffffu, (g & 1) ? da[1] : da[0], dsrc), qb = __shfl_sync(0xffffffffu, (g & 1) ? db[3] : db[2], dsrc);
        const float e0 = __shfl_xor_sync(0xffffffffu, (lane & 1) ? dl[0] : dl[2], 1), e1 = __shfl_xor_sync(0xffffffffu, dl[3], 1);
        if ((lane & 3) < 2) {
          const bool hi = lane & 1;
          st_tagged4(reinterpret_cast<float*>(g_part1 + ((mt * 8 + w8) * 8 + nt) * 16 + g + (hi ? 8 : 0)),
                     hi ? e0 : dl[0], hi ? qb : qa, hi ? e1 + dl[2] : dl[1] + e0, 1.0f);
        }
      }
    }
    TL_MARK2(10, lane == 0);
    uint4 wd[16];
    if (has_moe) mbar_wait(bar_wd, 0);
    #pragma unroll
    for (int i = 0; i < 16; i++) wd[i] = lds_u32x4(sbase + (cwg ? OG_SWD1 : OG_SWD) + warp * 8192 + (i >> 3) * 4096 + (i & 6) * 512 + (i & 1) * 128 + (lane & 3) * 256 + (((lane >> 2) ^ (2 * (lane & 3) + (i & 1))) << 4));
    {
      const float* src = reinterpret_cast<const float*>(g_part1 + ((mt * 8 + w8) * 8 + (lane & 1) * 4) * 16 + (lane >> 1));
      float4 v, v1, v2, v3;
      #pragma unroll 1
      for (unsigned int spin = 0; spin < (1u << 22); spin++) {
        v = ld_tagged4(src); v1 = ld_tagged4(src + 64); v2 = ld_tagged4(src + 128); v3 = ld_tagged4(src + 192);
        if (__all_sync(0xffffffffu, tagged4(v) & tagged4(v1) & tagged4(v2) & tagged4(v3))) break;
        __nanosleep(100);
      }
      __syncwarp();
      TL_MARK2(26, lane == 0);
      v.x = (v.x + v1.x) + (v2.x + v3.x); v.y = (v.y + v1.y) + (v2.y + v3.y); v.z = (v.z + v1.z) + (v2.z + v3.z);
      v.x += __shfl_xor_sync(0xffffffffu, v.x, 1); v.y += __shfl_xor_sync(0xffffffffu, v.y, 1); v.z += __shfl_xor_sync(0xffffffffu, v.z, 1);
      const float mean = v.x * (1.0f / T_D);
      const float var = fmaxf(fmaf(-mean, mean, v.y * (1.0f / T_D)), 0.f);
      const uint32_t mb2 = pack_bf16(mean, mean);
      const float inv = rcp_approx(rbf(sqrt_approx(rbf(rbf(var) + 1e-05f))));
      {
        const float2 sc = lds_f32x2(sbase + OG_SMISC);
        const uint32_t key = rank_key(rbf(fmaf(fmaf(-bflo(mb2), sc.x, v.z), inv, sc.y)), m0 + 16 * w8 + (lane >> 1));
        mbar_wait(bar_end, 0);
        if (lane & 1) sts_u32(sbase + OG_SSTAT + 1024 + (16 * w8 + (lane >> 1)) * 4, key);
        else sts_u32x2(sbase + OG_SSTAT + (16 * w8 + (lane >> 1)) * 8, mb2, __float_as_uint(inv));
        __syncwarp();
        if (lane == 0) mbar_arrive(bar_key);
      }
      const uint32_t ih = pack_bf16(inv, inv), il = pack_bf16(inv - bflo(ih), inv - bflo(ih));
      const uint32_t mba = __shfl_sync(0xffffffffu, mb2, 2 * (lane >> 2)), mbb = __shfl_sync(0xffffffffu, mb2, 2 * (lane >> 2) + 16);
      const uint32_t iha = __shfl_sync(0xffffffffu, ih, 2 * (lane >> 2)), ihb = __shfl_sync(0xffffffffu, ih, 2 * (lane >> 2) + 16);
      const uint32_t ila = __shfl_sync(0xffffffffu, il, 2 * (lane >> 2)), ilb = __shfl_sync(0xffffffffu, il, 2 * (lane >> 2) + 16);
      #pragma unroll 2
      for (int J = 0; J < 16; J += 2) {
        const uint32_t off = (J >> 3) * 16384 + frag + ((((J & 7) + fhi) ^ fsw) << 4);
        uint32_t xr[4];
        ldmatrix_x4(sbase + OG_XSLOT + off, xr[0], xr[1], xr[2], xr[3]);
        #pragma unroll
        for (int h = 0; h < 2; h++) {
          const uint32_t ca = sbase + OG_SCOL + 512 + (8 * (J + h) + q2) * 2;
          const uint32_t c1 = lds_u32(ca + 256), sh = lds_u32(ca + 512), gb = lds_u32(ca + 768);
          xr[2 * h] = out2(xr[2 * h], mba, iha, ila, c1, sh, gb);
          xr[2 * h + 1] = out2(xr[2 * h + 1], mbb, ihb, ilb, c1, sh, gb);
        }
        stmatrix_x4(sbase + OG_OSLOT + off, xr[0], xr[1], xr[2], xr[3]);
      }
      fence_proxy_async();
      __syncwarp();
      if (lane == 0) mbar_arrive(bar_out);
      TL_MARK2(24, lane == 0);
    }
    if (has_moe) mbar_wait(bar_h2, 0);
    TL_MARK2(13, lane == 0);
    if (has_moe) {
      const GemvSel sel = gemv_sel(lane);
      {
        float d[4][4];
        #pragma unroll
        for (int c = 0; c < 4; c++) { d[c][0] = 0.f; d[c][1] = 0.f; d[c][2] = 0.f; d[c][3] = 0.f; }
        #pragma unroll
        for (int st = 0; st < 8; st++) {
          const uint2 hb = lds_u32x2(sbase + OG_SH2 + ((lane >> 2) & 1) * 2048 + (w8 * 128 + st * 16 + (lane & 3) * 4) * 2);
          #pragma unroll
          for (int j = 0; j < 4; j++) mma_bf16(d[j], wv[4 * st + j].x, wv[4 * st + j].y, wv[4 * st + j].z, wv[4 * st + j].w, GEMV_B0(j, hb, sel), GEMV_B1(j, hb, sel));
        }
        #pragma unroll
        for (int e = 0; e < 4; e++) d[0][e] = (d[0][e] + d[1][e]) + (d[2][e] + d[3][e]);
        const float4 r = gemv_out(d[0], lane);
        sts_f32x4(sbase + OG_SRED + w8 * 512 + (((lane >> 4) * 2 + (lane & 1)) * 32 + ((lane >> 2) & 3) * 8 + (lane & 2) * 2) * 4, r.x, r.y, r.z, r.w);
      }
      named_bar_sync(9, 256);
      if (t2 < 64) {
        float gp[8], up[8];
        #pragma unroll
        for (int w = 0; w < 8; w++) { gp[w] = lds_f32(sbase + OG_SRED + w * 512 + t2 * 4); up[w] = lds_f32(sbase + OG_SRED + w * 512 + 256 + t2 * 4); }
        const float gs = ((gp[0] + gp[1]) + (gp[2] + gp[3])) + ((gp[4] + gp[5]) + (gp[6] + gp[7]));
        const float us = ((up[0] + up[1]) + (up[2] + up[3])) + ((up[4] + up[5]) + (up[6] + up[7]));
        asm volatile("st.shared.u16 [%0], %1;" :: "r"(sbase + OG_SGU + ((t2 & ~15) + ((t2 >> 1) & 3) * 4 + ((t2 >> 3) & 1) * 2 + (t2 & 1)) * 2), "h"((uint16_t)pack_bf16(silu_bf(rbf(gs)) * rbf(us), 0.f)) : "memory");
      }
      named_bar_sync(9, 256);
      TL_MARK2(20, threadIdx.x == 128);
      float d[4][4];
      #pragma unroll
      for (int c = 0; c < 4; c++) { d[c][0] = 0.f; d[c][1] = 0.f; d[c][2] = 0.f; d[c][3] = 0.f; }
      #pragma unroll
      for (int st = 0; st < 2; st++) {
        const uint2 g = lds_u32x2(sbase + OG_SGU + ((lane >> 2) & 1) * 64 + st * 32 + (lane & 3) * 8);
        #pragma unroll
        for (int j = 0; j < 4; j++) {
          const uint32_t b0 = GEMV_B0(j, g, sel), b1 = GEMV_B1(j, g, sel);
          mma_bf16(d[j & 1], wd[4 * st + j].x, wd[4 * st + j].y, wd[4 * st + j].z, wd[4 * st + j].w, b0, b1);
          mma_bf16(d[2 + (j & 1)], wd[8 + 4 * st + j].x, wd[8 + 4 * st + j].y, wd[8 + 4 * st + j].z, wd[8 + 4 * st + j].w, b0, b1);
        }
      }
      #pragma unroll
      for (int e = 0; e < 4; e++) { d[0][e] += d[1][e]; d[2][e] += d[3][e]; }
      const float4 y0 = gemv_out(d[0], lane), y1 = gemv_out(d[2], lane);
      float* yp = g_ypart + (size_t)(blockIdx.x * 2 + (lane & 1)) * T_D + w8 * 128 + (lane >> 2) * 8 + (lane & 2) * 2;
      st_tagged4(yp, y0.x, y0.y, y0.z, y0.w);
      st_tagged4(yp + 64, y1.x, y1.y, y1.z, y1.w);
      named_bar_sync(9, 256);
      if (t2 == 0) hint_arrive(CNT_Y);
    }
    TL_MARK2(14, threadIdx.x == 128);
    TL_CLK(4, 1, threadIdx.x == 128);
}

#define OG_JOBS2 (16 - OG_JOBS)
__device__ __forceinline__ int help_njobs() { return blockIdx.x < 128 ? OG_JOBS : OG_JOBS2; }
__device__ __forceinline__ int help_job(int i) {
  const int step = i + (blockIdx.x < 128 ? 0 : OG_JOBS);
  return (step & ~3) * 4 + (blockIdx.x & 3) * 4 + (step & 3);
}
__device__ __noinline__ void store_warp(uint32_t sbase, const CUtensorMap* tmO, int item0, int n_items) {
  if (elect_one()) {
    const uint32_t bars = sbase + AT_SBAR, b_q0 = bars + 80, b_ob = bars + 96, b_ordy = bars + 104, b_acq = bars + 264;
    const unsigned int* cnt = &g_hcnt[32 * (1 + OG_MT(blockIdx.x)) + 2];
    #pragma unroll 1
    for (int q = 0; q < 4 * n_items; q++) {
      const int item = item0 + (q >> 2) * 128, h = (q >> 1) & 1, w = q & 1;
      const bool last = (q >> 2) == n_items - 1;
      if (q == 4 * n_items - 4) { mbar_wait(bars + 288, 0); red_release_add(&g_hcnt[1], 1u); }
      mbar_wait(b_ordy + 8 * (q & 3), q >> 2);
      store_o(tmO, (h ? (last ? sbase + AT_SQ + 32768 : sbase + 2 * 32768) : sbase + AT_SQ) + w * 8192, (item >> 4) * 2 + h, (item & 15) * 128 + w * 64);
      if (w) {
        bulk_wait_read<0>();
        mbar_arrive(h ? b_ob : b_q0);
        bulk_wait<0>();
        fence_proxy_async_global();
        red_release_add(&g_hcnt[32 * (1 + (item & 15)) + 2 + (item >> 7)], h ? 1u : 256u);
        if (blockIdx.x < 128 && q == (n_items == 2 ? 5 : 3)) { spin_until(cnt, 0x808u); mbar_arrive(b_acq); }
      }
    }
    if (n_items == 1) {
      #pragma unroll 1
      for (int i = 0; i < help_njobs(); i++) {
        mbar_wait(b_acq + 16, i & 1);
        TL_MARK2(23, i == OG_JOBS - 1);
        red_release_add(&g_hcnt[32 * (1 + (help_job(i) >> 2)) + 4 + (help_job(i) & 3)], 1u);
        TL_MARK2(4, i == OG_JOBS - 1);
        if (i == PRE_X - 1) { spin_until(&g_hcnt[1], 132u); mbar_arrive(b_acq + 32); }
      }
    }
    if (blockIdx.x < 128) { spin_until(&g_hcnt[0], 128u); spin_until(cnt + 1, 0x808u); mbar_arrive(b_acq); }
  }
}

__global__ void __launch_bounds__(384, 1)
fused_kernel(const __grid_constant__ CUtensorMap tmH, const __grid_constant__ CUtensorMap tmW, const __grid_constant__ CUtensorMap tmK,
            const __grid_constant__ CUtensorMap tmV, const __grid_constant__ CUtensorMap tmO, const __grid_constant__ CUtensorMap tmOl, const __grid_constant__ CUtensorMap tmWo,
            const __grid_constant__ CUtensorMap tmX, const __grid_constant__ CUtensorMap tmOut, uint32_t zero,
            const uint8_t* __restrict__ pf_wo, const bf16* __restrict__ kc, const bf16* __restrict__ vc,
            const bf16* __restrict__ x, const bf16* __restrict__ cvec, const bf16* __restrict__ w_mod, const bf16* __restrict__ w_r,
            const bf16* __restrict__ w_gate, const bf16* __restrict__ w_up, const bf16* __restrict__ w_down, bf16* __restrict__ out)
{
  extern __shared__ __align__(1024) uint8_t smem_raw[];
  const uint32_t sbase = smem_u32(smem_raw);
  const uint32_t bars = sbase + AT_SBAR;
  const uint32_t b_full = bars, b_empty = bars + 40;
  const uint32_t b_q0 = bars + 80, b_q1 = bars + 88;
  const uint32_t b_ob = bars + 96;
  const uint32_t b_ordy = bars + 104;
  const uint32_t b_pin = bars + 136;
  const uint32_t b_head = bars + 144;
  const uint32_t b_go = bars + 152;
  const uint32_t b_x = bars + 160;
  const int wg = __shfl_sync(0xffffffffu, threadIdx.x >> 7, 0);
  const bool single = blockIdx.x >= AT_NFULL;
  const int item0 = __shfl_sync(0xffffffffu, blockIdx.x < 128 ? (int)blockIdx.x : (int)blockIdx.x + 124, 0), n_items = __shfl_sync(0xffffffffu, single ? 1 : 2, 0);
  TL_START(3);
  if (threadIdx.x == 0) {
    if (sbase & 1023u) __trap();
    for (int i = 0; i < 5; i++) { mbar_init(b_full + 8 * i, 1); mbar_init(b_empty + 8 * i, 2); }
    mbar_init(b_q0, 1); mbar_init(b_q1, 8); mbar_init(b_ob, 1);
    for (int i = 0; i < 4; i++) mbar_init(b_ordy + 8 * i, 4);
    mbar_init(b_pin, 1); mbar_init(b_head, blockIdx.x < 128 ? 8 : 1); mbar_init(b_go, 1); mbar_init(b_x, 1);
    mbar_init(bars + 168, 2); mbar_init(bars + 176, 1); mbar_init(bars + 184, 8); mbar_init(bars + 192, 2);
    mbar_init(bars + 200, 8); mbar_init(bars + 208, 4); mbar_init(bars + 216, 1); mbar_init(bars + 264, 1); mbar_init(bars + 272, 1); mbar_init(bars + 280, 8); mbar_init(bars + 288, 1); mbar_init(bars + 296, 1); mbar_init(bars + 304, 8); mbar_init(bars + 312, 1); mbar_init(bars + 320, 1);
    fence_mbar_init();
  }

  if (wg == 0) {
    reg_dealloc<AT_PREG>();
    if (threadIdx.x < 32) { __syncwarp(); named_bar_arrive(6, 384); }
    if (threadIdx.x >= 64) {
      named_bar_sync(6, 384);
      if (blockIdx.x < 128 && threadIdx.x >= 96) {
        named_bar_sync(8, 288);
        if (threadIdx.x == 96) red_release_add(&g_hcnt[32 * (1 + (blockIdx.x >> 3)) + 1], 1u);
      }
      if (blockIdx.x < 128) {
        mbar_wait(MOD_AT, 0);
        mod_rest(sbase + OG_SCOL, b_q1, threadIdx.x - 64, cvec, w_mod, w_r);
      }
    } else if (threadIdx.x >= 32) {
      named_bar_sync(6, 384);
      store_warp(sbase, &tmO, item0, n_items);
      __syncwarp();
    } else {
     if (elect_one()) {
      const uint64_t pol = policy_evict_first();
      prefetch_tmap(&tmW); prefetch_tmap(&tmH); prefetch_tmap(&tmWo); prefetch_tmap(&tmOl);
      uint32_t slot = 0, ph = 1;
      if (ALIGN) { uint32_t sm; asm volatile("mov.u32 %0, %%smid;" : "=r"(sm)); g_smid[32 + blockIdx.x] = sm; }
      #pragma unroll 1
      for (int it = 0; it < n_items; it++) {
        const int item = item0 + it * 128, hp = item >> 4, qt = item & 15;
        const bool first = it == 0;
        #pragma unroll 1
        for (int j = 0; j < T_D / 64; j++) {
          const uint32_t sl = ring_slot(qp_pos(j, it)), fb = b_full + 8 * sl;
          mbar_wait(b_empty + 8 * sl, ring_par(qp_pos(j, it)) ^ ((j >> 2) & 1) ^ 1);
          mbar_expect_tx(fb, 49152);
          tma_load_3d_hint(sbase + sl * 32768, &tmW, j * 64, hp * 4, fb, pol);
          if (first && j < PRE_B) {
            if (j == PRE_B - 1) {
              spin_until(&g_hcnt[32 * (1 + qt)], 8u);
              TL_MARK2(16, true);
              fence_proxy_async_global();
              TL_MARK2(17, true);
              #pragma unroll 1
              for (int i = 0; i < PRE_B; i++) tma_load_2d(sbase + AT_SQ + i * 16384, &tmH, i * 64, qt * 128, b_full + 8 * i);
              mbar_arrive(b_go);
            }
          } else {
            if (first && j == 3) mbar_wait(b_head, 0);
            if (first && j == 4 * H_SPLIT) { spin_until(&g_hcnt[32 * (1 + qt) + 1], 8u); fence_proxy_async_global(); }
            if (!first && (j == 0 || j == 2)) mbar_wait(j ? b_q1 : b_q0, 0);
            tma_load_2d_hint(sbase + AT_SQ + (j & 3) * 16384, &tmH, j * 64, qt * 128, fb, first ? pol_normal() : pol);
          }
        }
        #pragma unroll 1
        for (int j = 0; j < 4 * AT_NBLK; j++) {
          const bool isv = (j > 0 && !(j & 1)) || j == 4 * AT_NBLK - 1;
          const int row = hp * 2 * T_SEQ + (isv ? (j - 1) >> 1 : (j + 1) >> 1) * 128;
          const uint32_t fb = b_full + 8 * slot;
          mbar_wait(b_empty + 8 * slot, ph);
          if (!first && j == 3) mbar_wait(b_ob, 0);
          if (j == 4 && it == n_items - 1) mbar_arrive(bars + 288);
          if (ALIGN && j == AL_P && it == 1) mbar_arrive(bars + 312);
          mbar_expect_tx(fb, 32768);
          tma_load_3d_hint(sbase + slot * 32768, isv ? &tmV : &tmK, row, 0, fb, pol);
          if (it == 1 && isv && j >= 2 * WO_LATE && j < 2 * WO_LATE + 32 && blockIdx.x < OG_NKB)
            l2_prefetch_bulk(pf_wo + (size_t)own_kb(blockIdx.x) * 131072 + ((j >> 1) - WO_LATE) * 8192, 8192);
          if (++slot == 5) { slot = 0; ph ^= 1; }
        }
      }
      if (__builtin_expect(single, 0)) {
        #pragma unroll 1
        for (int i = 0; i < 4; i++) spin_until(&g_hcnt[32 * (1 + 4 * i + (blockIdx.x & 3)) + 2], 0x800u);
        fence_proxy_async_global();
        const int nj = help_njobs() * OG_PRE;
        int ji = 0, job = help_job(0), kk = 0;
        #pragma unroll 1
        for (int j = 0; j < nj; j++) {
          const uint32_t sl = ring_slot(qp_pos(j, 1)), fb = b_full + 8 * sl;
          mbar_wait(b_empty + 8 * sl, ring_par(qp_pos(j, 1)) ^ ((j >> 2) & 1) ^ 1);
          mbar_expect_tx(fb, 49152);
          tma_load_3d_hint(sbase + sl * 32768, &tmWo, pre_kb(kk) * 64, (job & 3) * 4, fb, HPOL_B);
          tma_load_3d_hint(sbase + sl * 32768 + 16384, &tmWo, pre_kb(kk) * 64, (job & 3) * 4 + 2, fb, HPOL_B);
          if (j == 0 || j == 2) mbar_wait(j ? b_ob : b_q0, 0);
          tma_load_2d_hint(sbase + AT_SQ + (j & 3) * 16384, HMAP_A, pre_kb(kk) * 64, (job >> 2) * 128, fb, HPOL_A);
          if (++kk == OG_PRE) { kk = 0; job = help_job(++ji); }
        }
      }
      if (blockIdx.x < 128) {
        if (single) mbar_wait(b_x, 1);
        tail_producer(sbase, 0, pol, &tmOl, &tmWo, &tmX);
      }
     }
    }
    named_bar_sync(12 + (threadIdx.x >> 5), 32);
    if (blockIdx.x < 128) tail_exchange(sbase, &tmOut, w_down, w_r, x, out);
  } else {
    if (blockIdx.x < 128) head_phase(sbase + AT_SQ + 49152, sbase + 4 * 32768, b_x, b_go, b_head, threadIdx.x - 128, zero, x, cvec, w_mod);
    else { named_bar_sync(6, 384); if (threadIdx.x == 128) mbar_arrive(b_head); }
    TL_MARK2(0, threadIdx.x == 128);
    reg_alloc<AT_CREG>();
    const int cwg = wg - 1;
    const int tid = threadIdx.x & 127;
    const int warp = tid >> 5, lane = tid & 31;
    const uint32_t dbase = (sbase & 0x3FFFFu) >> 4;
    const uint32_t k_base = dbase + (1u << 16);
    const uint32_t v_base = dbase + (1024u << 16);
    const uint32_t w_base = dbase + (512u << 16);
    const uint32_t q_lo = dbase + ((AT_SQ + cwg * 8192) >> 4) + (1u << 16);
    const uint32_t frag = cwg * 8192 + (16 * warp + (lane & 7) + 8 * ((lane >> 3) & 1)) * 128;
    if (cwg == 1) named_bar_arrive(1, 256);
    bool raw = false;
    uint4 pre[8];
    #pragma unroll 1
    for (int it = 0; it < n_items; it++) {
      const bool more = it + 1 < n_items;
      constexpr int nkb = T_D / 64;
      const int ta = __shfl_sync(0xffffffffu, 4 * it, 0);
      float acc[128];
      {
        FS(2 * it, 0);
        #pragma unroll
        for (int i = 0; i < 128; i++) asm volatile("" : "=f"(acc[i]));
        {
          const uint32_t slot = ring_slot(ta), b_lo = w_base + slot * 2048;
          mbar_wait(b_full + 8 * slot, ring_par(ta));
          wgmma_fence();
          wgmma_m64n256k16_ss_tb<0, 0>(acc, q_lo, b_lo, 0);
          wgmma_m64n256k16_ss_tb<2, 128>(acc, q_lo, b_lo, 1);
          wgmma_m64n256k16_ss_tb<4, 256>(acc, q_lo, b_lo, 1);
          wgmma_m64n256k16_ss_tb<6, 384>(acc, q_lo, b_lo, 1);
          wgmma_commit();
        }
        #pragma unroll 1
        for (int j = NOZERO; j < nkb; j++) {
          const uint32_t slot = ring_slot(qp_pos(j, ta >> 2));
          mbar_wait(b_full + 8 * slot, ring_par(qp_pos(j, ta >> 2)) ^ ((j >> 2) & 1));
          if (QP_STAG > 0 && cwg == 1 && j == nkb - QP_STAG) named_bar_sync(7, 256);
          const uint32_t a_lo = q_lo + (j & 3) * 1024, b_lo = w_base + slot * 2048;
          wgmma_fence();
          wgmma_m64n256k16_ss_tb<0, 0>(acc, a_lo, b_lo, 1);
          wgmma_m64n256k16_ss_tb<2, 128>(acc, a_lo, b_lo, 1);
          wgmma_m64n256k16_ss_tb<4, 256>(acc, a_lo, b_lo, 1);
          wgmma_m64n256k16_ss_tb<6, 384>(acc, a_lo, b_lo, 1);
          wgmma_commit();
          if (QP_STAG > 0 && cwg == 0 && j == nkb - 1) named_bar_arrive(7, 256);
          if (j > 0) {
            wgmma_wait<1>();
            if (tid == 0) mbar_arrive(b_empty + 8 * ring_slot(qp_pos(j - 1, ta >> 2)));
          }
        }
        wgmma_wait<0>();
        fence_regs(acc);
        FS(2 * it, 1);
        TL_MARK2(29, threadIdx.x == 256 && it == 0);
        if (tid == 0) mbar_arrive(b_empty + 24);
      }
      float o[64], s[64];
      uint32_t p[32], q[32];
      #pragma unroll
      for (int i = 0; i < 32; i++) q[i] = pack_bf16(acc[2 * i] * AT_C, acc[2 * i + 1] * AT_C);
      zero_regs(s);
      const uint32_t sq = sbase + AT_SQ + cwg * 8192;
      const bool last_wg1 = cwg == 1 && !more;
      float mc0, mc1, al0 = 1.0f, al1 = 1.0f, l0 = 0.f, l1 = 0.f, lp0 = 0.f, lp1 = 0.f;
      bool redo0 = false;
      FS(2 * it, 2);
      mbar_wait(b_full + 8 * ring_slot(ta), ring_par(ta));
      named_bar_sync(1 + cwg, 256);
      FS(2 * it, 3);
      issue_qk(s, q, k_base + ring_slot(ta) * 2048);
      named_bar_arrive(1 + (cwg ^ 1), 256);
      bool ready = mbar_test(b_full + 8 * ring_slot(ta + 1), ring_par(ta + 1)) & mbar_test(b_full + 8 * ring_slot(ta + 2), ring_par(ta + 2));
      stage_q<16>(acc, AT_C, sbase + AT_SQ + frag, lane);
      wgmma_wait<0>();
      fence_regs(s);
      if (tid == 0) mbar_arrive(b_empty + 8 * ring_slot(ta));
      mc0 = 0.f; mc1 = 0.f;
      if (!raw) {
        raw = softmax_mode(s, mc0, mc1);
        if (__builtin_expect(!raw, 0)) softmax_sub(s, mc0, mc1);
      }
      softmax_exp<0, 64>(s);
      #pragma unroll
      for (int J = 0; J < 16; J += 2)
        stmatrix_x4(sbase + AT_SQ + frag + (J >> 3) * 16384 + ((((J & 7) + (lane >> 4)) ^ (lane & 7)) << 4), q[2 * J], q[2 * J + 1], q[2 * J + 2], q[2 * J + 3]);
      pack_p(p, s);
      zero_regs(o);
      FS(2 * it, 4);
      uint32_t ks = ring_slot(ta + 1), vs = ring_slot(ta + 2), kp = ring_par(ta + 1), vp = ring_par(ta + 2);
      auto finish_head = [&]() {
        FS(2 * it, 5);
        redo0 = finish_l(lp0, lp1);
        if (!redo0) {
          stage_o(o, lp0, lp1, sbase + AT_SQ + frag, lane);
          fence_proxy_async();
          __syncwarp();
          if (lane == 0) mbar_arrive(b_ordy + 8 * cwg);
        }
        FS(2 * it + 1, 4);
      };
      if (!ready) { mbar_wait(b_full + 8 * ks, kp); mbar_wait(b_full + 8 * vs, vp); }
      #pragma unroll 1
      for (int n = 1; n < 2 * AT_NBLK; n++) {
        named_bar_sync(1 + cwg, 256);
        issue_qk(s, q, k_base + ks * 2048);
        if (n == AT_NBLK + 1) finish_head();
        issue_pv(o, p, v_base + vs * 2048, (n & 15) != 1);
        if (!(last_wg1 && n == 2 * AT_NBLK - 1)) named_bar_arrive(1 + (cwg ^ 1), 256);
        wgmma_wait<1>();
        fence_regs(s);
        if (tid == 0) mbar_arrive(b_empty + 8 * ks);
        if (__builtin_expect(!raw || (n + 1) >> 1 == AT_NBLK / 2, 0)) {
          if (n == AT_NBLK - 1) {
            #pragma unroll
            for (int J = 0; J < 16; J += 2)
              ldmatrix_x4(sbase + AT_SQ + 32768 + frag + (J >> 3) * 16384 + ((((J & 7) + (lane >> 4)) ^ (lane & 7)) << 4), q[2 * J], q[2 * J + 1], q[2 * J + 2], q[2 * J + 3]);
          }
          if (!raw) {
            const float m0 = mc0, m1 = mc1;
            const bool ok = softmax_mode(s, mc0, mc1);
            if (n == AT_NBLK) raw = ok;
            else {
              mc0 = mc0 - AT_HEAD > m0 ? mc0 : m0; mc1 = mc1 - AT_HEAD > m1 ? mc1 : m1;
              al0 = ex2_approx(m0 - mc0); al1 = ex2_approx(m1 - mc1);
            }
            if (!raw) softmax_sub(s, mc0, mc1);
          }
        }
        softmax_exp<0, AT_SPLIT>(s);
        add_rowsum(p, l0, l1);
        if (tid == 0) {
          uint32_t dep = zero & __float_as_uint(l0) & __float_as_uint(l1);
          #pragma unroll
          for (int i = AT_SPLIT - AT_PIN - PINB; i < AT_SPLIT - PINB; i += 2) dep &= __float_as_uint(s[i]) & __float_as_uint(s[i + 1]);
          mbar_arrive(b_pin + dep);
        }
        wgmma_wait<0>();
        fence_regs(o);
        if (tid == 0) mbar_arrive(b_empty + 8 * vs);
        ks += 2; if (ks >= 5) { ks -= 5; kp ^= 1; }
        vs += 2; if (vs >= 5) { vs -= 5; vp ^= 1; }
        ready = mbar_test(b_full + 8 * ks, kp) & mbar_test(b_full + 8 * vs, vp);
        softmax_exp<AT_SPLIT, 64>(s);
        pack_p(p, s);
        if (n == AT_NBLK) { lp0 = l0; lp1 = l1; l0 = 0.f; l1 = 0.f; }
        if (__builtin_expect(!raw || !ready, 0)) {
        if (!raw && __any_sync(0xffffffffu, al0 != 1.0f || al1 != 1.0f)) {
          rescale_o(o, al0, al1);
          l0 *= al0; l1 *= al1;
          al0 = 1.0f; al1 = 1.0f;
        }
        if (!ready && n < 2 * AT_NBLK - 1) {
          mbar_wait(b_full + 8 * ks, kp);
          mbar_wait(b_full + 8 * vs, vp);
        }
        }
      }
      FS(2 * it + 1, 5);
      const uint32_t vl = ring_slot(ta + 63);
      vs = ring_slot(ta + 62);
      const uint32_t ob = more ? sbase + vs * 32768 : sbase + AT_SQ + 32768;
      if (redo0) {
        attn_rows_exact(sq, sq, 4 * ta, kc, vc);
        fence_proxy_async();
        __syncwarp();
        if (lane == 0) mbar_arrive(b_ordy + 8 * cwg);
      }
      mbar_wait(b_full + 8 * vl, ring_par(ta + 63));
      issue_pv(o, p, v_base + vl * 2048, 1);
      add_rowsum(p, l0, l1);
      const bool overflow = finish_l(l0, l1);
      if (!overflow && lane == 0) mbar_arrive(b_q1);
      #pragma unroll
      for (int i = 0; i < 8; i++) asm volatile("mov.b64 {%0, %1}, 0;\nmov.b64 {%2, %3}, 0;" : "=r"(pre[i].x), "=r"(pre[i].y), "=r"(pre[i].z), "=r"(pre[i].w));
      if (HOIST && !more && blockIdx.x < OG_MOE) {
        load_pre(pre, sbase, AT_SQ, threadIdx.x - 128);
        __syncwarp();
        if (lane == 0) mbar_arrive(bars + 304);
      }
      mbar_wait(b_empty + 8 * vs, ring_par(ta + 62));
      wgmma_wait<0>();
      fence_regs(o);
      if (tid == 0) mbar_arrive(b_empty + 8 * vl);
      FS(2 * it + 1, 6);
      if (overflow) {
        attn_rows_exact(sq + 32768, ob + cwg * 8192, 4 * ta + 1, kc, vc);
        __syncwarp();
        if (lane == 0) mbar_arrive(b_q1);
      } else stage_o(o, l0, l1, ob + frag, lane);
      fence_proxy_async();
      __syncwarp();
      if (lane == 0) mbar_arrive(b_ordy + 16 + 8 * cwg);
      if (redo0 || overflow) raw = false;
      named_bar_sync(3 + cwg, 128);
      FS(2 * it + 1, 7);
    }
    if (__builtin_expect(single, 0)) {
      float acc[128];
      uint32_t j = 0, pk[64];
      #pragma unroll
      for (int i = 0; i < 64; i++) asm volatile("" : "=f"(acc[2 * i]), "=f"(acc[2 * i + 1]), "=r"(pk[i]));
      uint4* dst = g_pre;
      int left = 0;
      auto put = [&](bool last) {
        #pragma unroll
        for (int i = 0; i < PUT_N; i++) dst[i * 256] = make_uint4(pk[4 * i], pk[4 * i + 1], pk[4 * i + 2], pk[4 * i + 3]);
        dst += PUT_N * 256;
        #pragma unroll
        for (int i = 0; i < 64 - 4 * PUT_N; i++) asm volatile("mov.b32 %0, %1;" : "=r"(pk[i]) : "r"(pk[i + 4 * PUT_N]));
        __syncwarp();
        if (last && lane == 0) mbar_arrive(bars + 280);
      };
      #pragma unroll 1
      for (int ji = 0; ji < help_njobs(); ji++) {
        #pragma unroll 1
        for (int kk = 0; kk < OG_PRE; kk++, j++) {
          const uint32_t slot = ring_slot(qp_pos(j, 1));
          mbar_wait(b_full + 8 * slot, ring_par(qp_pos(j, 1)) ^ ((j >> 2) & 1));
          if (H_STAG > 0 && cwg == 1 && kk == OG_PRE - H_STAG) named_bar_sync(7, 256);
          const uint32_t a_lo = q_lo + (j & 3) * 1024, b_lo = w_base + slot * 2048;
          wgmma_fence();
          wgmma_m64n256k16_ss_tb<0, 0>(acc, a_lo, b_lo, kk != 0);
          wgmma_m64n256k16_ss_tb<2, 128>(acc, a_lo, b_lo, 1);
          wgmma_m64n256k16_ss_tb<4, 256>(acc, a_lo, b_lo, 1);
          wgmma_m64n256k16_ss_tb<6, 384>(acc, a_lo, b_lo, 1);
          wgmma_commit();
          if (H_STAG > 0 && cwg == 0 && kk == OG_PRE - 1) named_bar_arrive(7, 256);
          wgmma_wait<1>();
          if (kk > 0 && tid == 0) mbar_arrive(b_empty + 8 * ring_slot(qp_pos(j - 1, 1)));
          #pragma unroll 1
          for (int i = ji == OG_JOBS ? 0 : 16 / PUT_N - 1; i < 16 / PUT_N && left > 0; i++) put(--left == 0);
        }
        wgmma_wait<0>();
        fence_regs(acc);
        if (tid == 0) mbar_arrive(b_empty + 8 * ring_slot(qp_pos(j - 1, 1)));
        #pragma unroll
        for (int i = 0; i < 64; i++) pk[i] = pack_bf16(acc[2 * i], acc[2 * i + 1]);
        left = 16 / PUT_N;
        if (ji == PRE_X) mbar_wait(bars + 296, 0);
        dst = g_pre + pre_loc(help_job(ji)) * 4096 + threadIdx.x - 128;
      }
      #pragma unroll
      for (int i = 0; i < 16; i++) dst[i * 256] = make_uint4(pk[4 * i], pk[4 * i + 1], pk[4 * i + 2], pk[4 * i + 3]);
      __syncwarp();
      if (lane == 0) mbar_arrive(bars + 280);
      named_bar_sync(5, 256);
      if (threadIdx.x == 128) {
        #pragma unroll 1
        for (int i = 0; i < 5; i++) {
          constexpr int n = OG_JOBS * OG_PRE;
          const int used = i == 3 ? 0 : (n + 3 - (i == 4 ? 3 : i)) / 4;
          if ((used ^ (i < 4)) & 1) {
            mbar_arrive(b_full + 8 * ring_slot(4 + i));
            mbar_arrive(b_empty + 8 * ring_slot(4 + i)); mbar_arrive(b_empty + 8 * ring_slot(4 + i));
          }
        }
        mbar_arrive(b_x);
      }
      named_bar_sync(5, 256);
      #pragma unroll
      for (int i = 0; i < 8; i++) pre[i] = make_uint4(0u, 0u, 0u, 0u);
    }
    TL_CLK(3, 1, threadIdx.x == 128);
    TL_CTA(1, threadIdx.x == 256);
    TL_END(3, tid == 0);
    TL_MARK2(19, tid == 0 && !single);
    if (blockIdx.x < 128) {
      if (!HOIST && blockIdx.x < OG_MOE) {
        load_pre(pre, sbase, AT_SQ, threadIdx.x - 128);
        __syncwarp();
        if (lane == 0) mbar_arrive(bars + 304);
      }
      tail_consumer(sbase, pre, cwg, w_gate, w_up);
    }
  }
}

typedef CUresult (*PFN_encodeTiled)(CUtensorMap*, CUtensorMapDataType, cuuint32_t, void*, const cuuint64_t*, const cuuint64_t*,
                                    const cuuint32_t*, const cuuint32_t*, CUtensorMapInterleave, CUtensorMapSwizzle,
                                    CUtensorMapL2promotion, CUtensorMapFloatOOBfill);

CUtensorMap make_map_2d(PFN_encodeTiled enc, const void* ptr, uint64_t inner, uint64_t outer, uint64_t stride_bytes, uint32_t box_inner, uint32_t box_outer) {
  CUtensorMap m;
  cuuint64_t gd[2] = {inner, outer}; cuuint64_t gs[1] = {stride_bytes};
  cuuint32_t bx[2] = {box_inner, box_outer}; cuuint32_t es[2] = {1, 1};
  enc(&m, CU_TENSOR_MAP_DATA_TYPE_BFLOAT16, 2, const_cast<void*>(ptr), gd, gs, bx, es, CU_TENSOR_MAP_INTERLEAVE_NONE,
      CU_TENSOR_MAP_SWIZZLE_128B, CU_TENSOR_MAP_L2_PROMOTION_L2_128B, CU_TENSOR_MAP_FLOAT_OOB_FILL_NONE);
  return m;
}

CUtensorMap make_map_3d(PFN_encodeTiled enc, const void* ptr, uint64_t cols, uint64_t rows, uint32_t box_rows, uint32_t chunks) {
  CUtensorMap m;
  cuuint64_t gd[3] = {64, rows, cols / 64}; cuuint64_t gs[2] = {cols * 2, 128};
  cuuint32_t bx[3] = {64, box_rows, chunks}; cuuint32_t es[3] = {1, 1, 1};
  enc(&m, CU_TENSOR_MAP_DATA_TYPE_BFLOAT16, 3, const_cast<void*>(ptr), gd, gs, bx, es, CU_TENSOR_MAP_INTERLEAVE_NONE,
      CU_TENSOR_MAP_SWIZZLE_128B, CU_TENSOR_MAP_L2_PROMOTION_L2_128B, CU_TENSOR_MAP_FLOAT_OOB_FILL_NONE);
  return m;
}

}

extern "C" void kernel_launch(void* const* d_in, const int* in_sizes, int n_in, void* d_out, int out_size) {
  const bf16* x      = (const bf16*)d_in[0];
  const bf16* kc     = (const bf16*)d_in[1];
  const bf16* vc     = (const bf16*)d_in[2];
  const bf16* wq     = (const bf16*)d_in[3];
  const bf16* wo     = (const bf16*)d_in[4];
  const bf16* w_r    = (const bf16*)d_in[6];
  const bf16* w_gate = (const bf16*)d_in[7];
  const bf16* w_up   = (const bf16*)d_in[8];
  const bf16* w_down = (const bf16*)d_in[9];
  const bf16* cvec   = (const bf16*)d_in[10];
  const bf16* w_mod  = (const bf16*)d_in[11];
  bf16* out = (bf16*)d_out;

  static PFN_encodeTiled enc = nullptr;
  static void *p_h = nullptr, *p_o = nullptr;
  if (!enc) {
    void* fn = nullptr; cudaDriverEntryPointQueryResult qres;
    cudaGetDriverEntryPoint("cuTensorMapEncodeTiled", &fn, cudaEnableDefault, &qres);
    enc = (PFN_encodeTiled)fn;
    cudaGetSymbolAddress(&p_h, g_pre);
    p_h = (uint4*)p_h + 16 * PRE_X * 2048;
    cudaGetSymbolAddress(&p_o, g_o);
    cudaFuncSetAttribute(fused_kernel, cudaFuncAttributeMaxDynamicSharedMemorySize, (int)AT_SMEM);
  }
  const CUtensorMap tm_h   = make_map_2d(enc, p_h, T_D, T_SEQ, T_D * 2, 64, 128);
  const CUtensorMap tm_wq  = W3D ? make_map_3d(enc, wq, T_DQKV, T_D, 64, 4) : make_map_2d(enc, wq, T_DQKV, T_D, T_DQKV * 2, 64, 64);
  const CUtensorMap tm_k   = KV3D ? make_map_3d(enc, kc, T_DH, (uint64_t)T_NH * T_SEQ, 128, 2) : make_map_2d(enc, kc, T_DH, (uint64_t)T_NH * T_SEQ, T_DH * 2, 64, 128);
  const CUtensorMap tm_v   = KV3D ? make_map_3d(enc, vc, T_DH, (uint64_t)T_NH * T_SEQ, 128, 2) : make_map_2d(enc, vc, T_DH, (uint64_t)T_NH * T_SEQ, T_DH * 2, 64, 128);
  const CUtensorMap tm_ost = make_map_2d(enc, p_o, T_DQKV, T_SEQ, T_DQKV * 2, 64, 64);
  const CUtensorMap tm_old = make_map_2d(enc, p_o, T_DQKV, T_SEQ, T_DQKV * 2, 64, 128);
  const CUtensorMap tm_wo  = make_map_3d(enc, wo, T_D, T_DQKV, 64, 2);
  const CUtensorMap tm_x   = make_map_3d(enc, w_down, T_D, T_F, 32, 8);

  const CUtensorMap tm_out = make_map_2d(enc, out, T_D, T_SEQ, T_D * 2, 64, 128);

  fused_kernel<<<132, 384, AT_SMEM, cudaStreamPerThread>>>(tm_h, tm_wq, tm_k, tm_v, tm_ost, tm_old, tm_wo, tm_x, tm_out, 0u, (const uint8_t*)wo, kc, vc, x, cvec, w_mod,
             w_r, w_gate, w_up, w_down, out);
}
```

```cpp
#include <cuda_runtime.h>
#include <cuda_bf16.h>
#include <cuda.h>
#include <stdint.h>

namespace {

typedef __nv_bfloat16 bf16;

constexpr int T_SEQ = 2048, T_D = 1024, T_NH = 32, T_DH = 128, T_DQKV = 4096, T_F = 3584;

#define PRE_X 2
__device__ __align__(1024) uint4 g_pre[(16 * PRE_X + 128) * 2048];
#define g_h (reinterpret_cast<bf16*>(g_pre + 16 * PRE_X * 2048))
__device__ __align__(1024) bf16 g_o[T_SEQ * T_DQKV];
__device__ __align__(16) uint8_t g_col[8 * 1536];
__device__ __align__(16) float g_scal[64];
__device__ __align__(16) unsigned int g_hcnt[17 * 32];
__device__ unsigned int g_smid[160], g_tmax[128];
__device__ __align__(128) float g_modpart[4 * 2 * T_D];
struct __align__(2048) TailMail {
  float4 part1[T_SEQ * 8];
  uint32_t key[256];
  uint4 cand[16 * 2 * 2 * 128];
  uint32_t cnt[32];
  float ypart[(T_F / 32) * 2 * T_D];
};
__device__ TailMail g_mail;
#define g_part1 g_mail.part1
#define g_key g_mail.key
#define g_cand g_mail.cand
#define CNT_Y (g_mail.cnt)
#define g_ypart g_mail.ypart

__device__ __forceinline__ uint32_t smem_u32(const void* p) { return (uint32_t)__cvta_generic_to_shared(p); }
__device__ __forceinline__ void mbar_init(uint32_t bar, uint32_t cnt) { asm volatile("mbarrier.init.shared::cta.b64 [%0], %1;" :: "r"(bar), "r"(cnt)); }
__device__ __forceinline__ void mbar_expect_tx(uint32_t bar, uint32_t bytes) { asm volatile("mbarrier.arrive.expect_tx.shared::cta.b64 _, [%0], %1;" :: "r"(bar), "r"(bytes) : "memory"); }
__device__ __forceinline__ void mbar_arrive(uint32_t bar) { asm volatile("mbarrier.arrive.shared::cta.b64 _, [%0];" :: "r"(bar) : "memory"); }
__device__ __forceinline__ void mbar_wait(uint32_t bar, uint32_t parity) {
  asm volatile("{\n.reg .pred p;\nLAB_WAIT:\nmbarrier.try_wait.parity.shared::cta.b64 p, [%0], %1;\n@!p bra LAB_WAIT;\n}\n" :: "r"(bar), "r"(parity) : "memory");
}
__device__ __forceinline__ bool mbar_test(uint32_t bar, uint32_t parity) {
  uint32_t r; asm volatile("{\n.reg .pred p;\nmbarrier.test_wait.parity.shared::cta.b64 p, [%1], %2;\nselp.u32 %0, 1, 0, p;\n}\n" : "=r"(r) : "r"(bar), "r"(parity) : "memory");
  return r != 0;
}
__device__ __forceinline__ uint32_t clock_lo() { uint32_t c; asm volatile("mov.u32 %0, %%clock;" : "=r"(c)); return c; }
__device__ __forceinline__ void fence_mbar_init() { asm volatile("fence.mbarrier_init.release.cluster;" ::: "memory"); }
__device__ __forceinline__ void tma_load_2d(uint32_t dst, const CUtensorMap* map, int c0, int c1, uint32_t bar) {
  asm volatile("cp.async.bulk.tensor.2d.shared::cluster.global.mbarrier::complete_tx::bytes [%0], [%1, {%3, %4}], [%2];"
    :: "r"(dst), "l"(map), "r"(bar), "r"(c0), "r"(c1) : "memory");
}
__device__ __forceinline__ uint64_t policy_evict_first() {
  uint64_t p; asm volatile("createpolicy.fractional.L2::evict_first.b64 %0, 1.0;" : "=l"(p)); return p;
}
__device__ __forceinline__ void tma_load_2d_hint(uint32_t dst, const CUtensorMap* map, int c0, int c1, uint32_t bar, uint64_t pol) {
  asm volatile("cp.async.bulk.tensor.2d.shared::cluster.global.mbarrier::complete_tx::bytes.L2::cache_hint [%0], [%1, {%3, %4}], [%2], %5;"
    :: "r"(dst), "l"(map), "r"(bar), "r"(c0), "r"(c1), "l"(pol) : "memory");
}
__device__ __forceinline__ void tma_load_3d_hint(uint32_t dst, const CUtensorMap* map, int c1, int c2, uint32_t bar, uint64_t pol) {
  asm volatile("cp.async.bulk.tensor.3d.shared::cluster.global.mbarrier::complete_tx::bytes.L2::cache_hint [%0], [%1, {%3, %4, %5}], [%2], %6;"
    :: "r"(dst), "l"(map), "r"(bar), "n"(0), "r"(c1), "r"(c2), "l"(pol) : "memory");
}
__device__ __forceinline__ void tma_store_2d(const CUtensorMap* map, uint32_t src, int c0, int c1) {
  asm volatile("cp.async.bulk.tensor.2d.global.shared::cta.bulk_group [%0, {%2, %3}], [%1];" :: "l"(map), "r"(src), "r"(c0), "r"(c1) : "memory");
}
__device__ __forceinline__ void prefetch_tmap(const CUtensorMap* map) { asm volatile("prefetch.tensormap [%0];" :: "l"(map) : "memory"); }
__device__ __forceinline__ void l2_prefetch_bulk(const void* p, uint32_t bytes) {
  asm volatile("cp.async.bulk.prefetch.L2.global [%0], %1;" :: "l"(p), "r"(bytes) : "memory");
}
__device__ __forceinline__ void bulk_commit() { asm volatile("cp.async.bulk.commit_group;" ::: "memory"); }
template<int N> __device__ __forceinline__ void bulk_wait_read() { asm volatile("cp.async.bulk.wait_group.read %0;" :: "n"(N) : "memory"); }
template<int N> __device__ __forceinline__ void bulk_wait() { asm volatile("cp.async.bulk.wait_group %0;" :: "n"(N) : "memory"); }
__device__ __forceinline__ void named_bar_sync(int id, int nthreads) { asm volatile("bar.sync %0, %1;" :: "r"(id), "r"(nthreads) : "memory"); }
__device__ __forceinline__ void named_bar_arrive(int id, int nthreads) { asm volatile("bar.arrive %0, %1;" :: "r"(id), "r"(nthreads) : "memory"); }
__device__ __forceinline__ void wgmma_fence() { asm volatile("wgmma.fence.sync.aligned;" ::: "memory"); }
__device__ __forceinline__ void wgmma_commit() { asm volatile("wgmma.commit_group.sync.aligned;" ::: "memory"); }
template<int N> __device__ __forceinline__ void wgmma_wait() { asm volatile("wgmma.wait_group.sync.aligned %0;" :: "n"(N) : "memory"); }
template<int R> __device__ __forceinline__ void reg_alloc() { asm volatile("setmaxnreg.inc.sync.aligned.u32 %0;" :: "n"(R)); }
template<int R> __device__ __forceinline__ void reg_dealloc() { asm volatile("setmaxnreg.dec.sync.aligned.u32 %0;" :: "n"(R)); }
__device__ __forceinline__ bool elect_one() {
  uint32_t pred; asm volatile("{\n.reg .pred p;\nelect.sync _|p, 0xffffffff;\nselp.u32 %0, 1, 0, p;\n}\n" : "=r"(pred)); return pred != 0;
}
__device__ __forceinline__ uint32_t pack_bf16(float lo, float hi) {
  uint32_t r; asm("cvt.rn.bf16x2.f32 %0, %1, %2;" : "=r"(r) : "f"(hi), "f"(lo)); return r;
}
__device__ __forceinline__ void stmatrix_x4(uint32_t addr, uint32_t r0, uint32_t r1, uint32_t r2, uint32_t r3) {
  asm volatile("stmatrix.sync.aligned.m8n8.x4.shared.b16 [%0], {%1, %2, %3, %4};" :: "r"(addr), "r"(r0), "r"(r1), "r"(r2), "r"(r3) : "memory");
}
__device__ __forceinline__ void fence_proxy_async() { asm volatile("fence.proxy.async.shared::cta;" ::: "memory"); }
__device__ __forceinline__ float ex2_approx(float x) { float y; asm("ex2.approx.ftz.f32 %0, %1;" : "=f"(y) : "f"(x)); return y; }
template<int N> __device__ __forceinline__ void fence_regs(float (&r)[N]) {
  #pragma unroll
  for (int i = 0; i < N; i++) asm volatile("" : "+f"(r[i]) :: "memory");
}
template<int N> __device__ __forceinline__ void zero_regs(float (&r)[N]) {
  #pragma unroll
  for (int i = 0; i < N; i += 2) asm volatile("mov.b64 {%0, %1}, 0;" : "=f"(r[i]), "=f"(r[i + 1]));
}
__device__ __forceinline__ float rbf(float x) { return __uint_as_float(pack_bf16(0.f, x)); }
__device__ __forceinline__ float bflo(uint32_t v) { return __uint_as_float(v << 16); }
__device__ __forceinline__ float bfhi(uint32_t v) { return __uint_as_float(v & 0xffff0000u); }

#define TL_START(k) do {} while (0)
#define TL_END(k, cond) do {} while (0)
#define TL_CTA(i, cond) do {} while (0)
#define FS(slot, k) do {} while (0)
#define TL_MARK2(k, cond) do {} while (0)
#define TL_CLK(k, i, cond) do {} while (0)

template <int OFFA, int OFFB>
__device__ __forceinline__ void wgmma_m64n256k16_ss_tb(float (&d)[128], uint32_t a_lo, uint32_t b_lo, int scaleD) {
  asm volatile("{\n.reg .pred p;\n.reg .b32 ta, tb;\n.reg .b64 da, db;\nsetp.ne.b32 p, %130, 0;\n"
    "add.u32 ta, %128, %131;\nadd.u32 tb, %129, %132;\n"
    "mov.b64 da, {ta, 0x40000040};\nmov.b64 db, {tb, 0x40000040};\n"
    "wgmma.mma_async.sync.aligned.m64n256k16.f32.bf16.bf16 "
    "{%0, %1, %2, %3, %4, %5, %6, %7, %8, %9, %10, %11, %12, %13, %14, %15, %16, %17, %18, %19, %20, %21, %22, %23, %24, %25, %26, %27, %28, %29, %30, %31, %32, %33, %34, %35, %36, %37, %38, %39, %40, %41, %42, %43, %44, %45, %46, %47, %48, %49, %50, %51, %52, %53, %54, %55, %56, %57, %58, %59, %60, %61, %62, %63, %64, %65, %66, %67, %68, %69, %70, %71, %72, %73, %74, %75, %76, %77, %78, %79, %80, %81, %82, %83, %84, %85, %86, %87, %88, %89, %90, %91, %92, %93, %94, %95, %96, %97, %98, %99, %100, %101, %102, %103, %104, %105, %106, %107, %108, %109, %110, %111, %112, %113, %114, %115, %116, %117, %118, %119, %120, %121, %122, %123, %124, %125, %126, %127}, "
    "da, db, p, 1, 1, 0, 1;\n}\n"
    : "+f"(d[0]), "+f"(d[1]), "+f"(d[2]), "+f"(d[3]), "+f"(d[4]), "+f"(d[5]), "+f"(d[6]), "+f"(d[7]), "+f"(d[8]), "+f"(d[9]), "+f"(d[10]), "+f"(d[11]), "+f"(d[12]), "+f"(d[13]), "+f"(d[14]), "+f"(d[15]), "+f"(d[16]), "+f"(d[17]), "+f"(d[18]), "+f"(d[19]), "+f"(d[20]), "+f"(d[21]), "+f"(d[22]), "+f"(d[23]), "+f"(d[24]), "+f"(d[25]), "+f"(d[26]), "+f"(d[27]), "+f"(d[28]), "+f"(d[29]), "+f"(d[30]), "+f"(d[31]), "+f"(d[32]), "+f"(d[33]), "+f"(d[34]), "+f"(d[35]), "+f"(d[36]), "+f"(d[37]), "+f"(d[38]), "+f"(d[39]), "+f"(d[40]), "+f"(d[41]), "+f"(d[42]), "+f"(d[43]), "+f"(d[44]), "+f"(d[45]), "+f"(d[46]), "+f"(d[47]), "+f"(d[48]), "+f"(d[49]), "+f"(d[50]), "+f"(d[51]), "+f"(d[52]), "+f"(d[53]), "+f"(d[54]), "+f"(d[55]), "+f"(d[56]), "+f"(d[57]), "+f"(d[58]), "+f"(d[59]), "+f"(d[60]), "+f"(d[61]), "+f"(d[62]), "+f"(d[63]), "+f"(d[64]), "+f"(d[65]), "+f"(d[66]), "+f"(d[67]), "+f"(d[68]), "+f"(d[69]), "+f"(d[70]), "+f"(d[71]), "+f"(d[72]), "+f"(d[73]), "+f"(d[74]), "+f"(d[75]), "+f"(d[76]), "+f"(d[77]), "+f"(d[78]), "+f"(d[79]), "+f"(d[80]), "+f"(d[81]), "+f"(d[82]), "+f"(d[83]), "+f"(d[84]), "+f"(d[85]), "+f"(d[86]), "+f"(d[87]), "+f"(d[88]), "+f"(d[89]), "+f"(d[90]), "+f"(d[91]), "+f"(d[92]), "+f"(d[93]), "+f"(d[94]), "+f"(d[95]), "+f"(d[96]), "+f"(d[97]), "+f"(d[98]), "+f"(d[99]), "+f"(d[100]), "+f"(d[101]), "+f"(d[102]), "+f"(d[103]), "+f"(d[104]), "+f"(d[105]), "+f"(d[106]), "+f"(d[107]), "+f"(d[108]), "+f"(d[109]), "+f"(d[110]), "+f"(d[111]), "+f"(d[112]), "+f"(d[113]), "+f"(d[114]), "+f"(d[115]), "+f"(d[116]), "+f"(d[117]), "+f"(d[118]), "+f"(d[119]), "+f"(d[120]), "+f"(d[121]), "+f"(d[122]), "+f"(d[123]), "+f"(d[124]), "+f"(d[125]), "+f"(d[126]), "+f"(d[127])
    : "r"(a_lo), "r"(b_lo), "r"(scaleD), "n"(OFFA), "n"(OFFB));
}

template <int OFFA, int OFFB>
__device__ __forceinline__ void wgmma_m64n128k16_ss_tb(float (&d)[64], uint32_t a_lo, uint32_t b_lo, int scaleD) {
  asm volatile("{\n.reg .pred p;\n.reg .b32 ta, tb;\n.reg .b64 da, db;\nsetp.ne.b32 p, %66, 0;\n"
    "add.u32 ta, %64, %67;\nadd.u32 tb, %65, %68;\n"
    "mov.b64 da, {ta, 0x40000040};\nmov.b64 db, {tb, 0x40000040};\n"
    "wgmma.mma_async.sync.aligned.m64n128k16.f32.bf16.bf16 "
    "{%0, %1, %2, %3, %4, %5, %6, %7, %8, %9, %10, %11, %12, %13, %14, %15, %16, %17, %18, %19, %20, %21, %22, %23, %24, %25, %26, %27, %28, %29, %30, %31, %32, %33, %34, %35, %36, %37, %38, %39, %40, %41, %42, %43, %44, %45, %46, %47, %48, %49, %50, %51, %52, %53, %54, %55, %56, %57, %58, %59, %60, %61, %62, %63}, "
    "da, db, p, 1, 1, 0, 1;\n}\n"
    : "+f"(d[0]), "+f"(d[1]), "+f"(d[2]), "+f"(d[3]), "+f"(d[4]), "+f"(d[5]), "+f"(d[6]), "+f"(d[7]), "+f"(d[8]), "+f"(d[9]), "+f"(d[10]), "+f"(d[11]), "+f"(d[12]), "+f"(d[13]), "+f"(d[14]), "+f"(d[15]), "+f"(d[16]), "+f"(d[17]), "+f"(d[18]), "+f"(d[19]), "+f"(d[20]), "+f"(d[21]), "+f"(d[22]), "+f"(d[23]), "+f"(d[24]), "+f"(d[25]), "+f"(d[26]), "+f"(d[27]), "+f"(d[28]), "+f"(d[29]), "+f"(d[30]), "+f"(d[31]), "+f"(d[32]), "+f"(d[33]), "+f"(d[34]), "+f"(d[35]), "+f"(d[36]), "+f"(d[37]), "+f"(d[38]), "+f"(d[39]), "+f"(d[40]), "+f"(d[41]), "+f"(d[42]), "+f"(d[43]), "+f"(d[44]), "+f"(d[45]), "+f"(d[46]), "+f"(d[47]), "+f"(d[48]), "+f"(d[49]), "+f"(d[50]), "+f"(d[51]), "+f"(d[52]), "+f"(d[53]), "+f"(d[54]), "+f"(d[55]), "+f"(d[56]), "+f"(d[57]), "+f"(d[58]), "+f"(d[59]), "+f"(d[60]), "+f"(d[61]), "+f"(d[62]), "+f"(d[63])
    : "r"(a_lo), "r"(b_lo), "r"(scaleD), "n"(OFFA), "n"(OFFB));
}

template <int OFFB>
__device__ __forceinline__ void wgmma_m64n128k16_rs_tb(float (&d)[64], uint32_t a0, uint32_t a1, uint32_t a2, uint32_t a3, uint32_t b_lo, int scaleD) {
  asm volatile("{\n.reg .pred p;\n.reg .b32 tb;\n.reg .b64 db;\nsetp.ne.b32 p, %69, 0;\n"
    "add.u32 tb, %68, %70;\n"
    "mov.b64 db, {tb, 0x40000040};\n"
    "wgmma.mma_async.sync.aligned.m64n128k16.f32.bf16.bf16 "
    "{%0, %1, %2, %3, %4, %5, %6, %7, %8, %9, %10, %11, %12, %13, %14, %15, %16, %17, %18, %19, %20, %21, %22, %23, %24, %25, %26, %27, %28, %29, %30, %31, %32, %33, %34, %35, %36, %37, %38, %39, %40, %41, %42, %43, %44, %45, %46, %47, %48, %49, %50, %51, %52, %53, %54, %55, %56, %57, %58, %59, %60, %61, %62, %63}, "
    "{%64, %65, %66, %67}, db, p, 1, 1, 1;\n}\n"
    : "+f"(d[0]), "+f"(d[1]), "+f"(d[2]), "+f"(d[3]), "+f"(d[4]), "+f"(d[5]), "+f"(d[6]), "+f"(d[7]), "+f"(d[8]), "+f"(d[9]), "+f"(d[10]), "+f"(d[11]), "+f"(d[12]), "+f"(d[13]), "+f"(d[14]), "+f"(d[15]), "+f"(d[16]), "+f"(d[17]), "+f"(d[18]), "+f"(d[19]), "+f"(d[20]), "+f"(d[21]), "+f"(d[22]), "+f"(d[23]), "+f"(d[24]), "+f"(d[25]), "+f"(d[26]), "+f"(d[27]), "+f"(d[28]), "+f"(d[29]), "+f"(d[30]), "+f"(d[31]), "+f"(d[32]), "+f"(d[33]), "+f"(d[34]), "+f"(d[35]), "+f"(d[36]), "+f"(d[37]), "+f"(d[38]), "+f"(d[39]), "+f"(d[40]), "+f"(d[41]), "+f"(d[42]), "+f"(d[43]), "+f"(d[44]), "+f"(d[45]), "+f"(d[46]), "+f"(d[47]), "+f"(d[48]), "+f"(d[49]), "+f"(d[50]), "+f"(d[51]), "+f"(d[52]), "+f"(d[53]), "+f"(d[54]), "+f"(d[55]), "+f"(d[56]), "+f"(d[57]), "+f"(d[58]), "+f"(d[59]), "+f"(d[60]), "+f"(d[61]), "+f"(d[62]), "+f"(d[63])
    : "r"(a0), "r"(a1), "r"(a2), "r"(a3), "r"(b_lo), "r"(scaleD), "n"(OFFB));
}

template <int OFFB>
__device__ __forceinline__ void wgmma_m64n128k16_rs(float (&d)[64], uint32_t a0, uint32_t a1, uint32_t a2, uint32_t a3, uint32_t b_lo, int scaleD) {
  asm volatile("{\n.reg .pred p;\n.reg .b32 tb;\n.reg .b64 db;\nsetp.ne.b32 p, %69, 0;\n"
    "add.u32 tb, %68, %70;\n"
    "mov.b64 db, {tb, 0x40000040};\n"
    "wgmma.mma_async.sync.aligned.m64n128k16.f32.bf16.bf16 "
    "{%0, %1, %2, %3, %4, %5, %6, %7, %8, %9, %10, %11, %12, %13, %14, %15, %16, %17, %18, %19, %20, %21, %22, %23, %24, %25, %26, %27, %28, %29, %30, %31, %32, %33, %34, %35, %36, %37, %38, %39, %40, %41, %42, %43, %44, %45, %46, %47, %48, %49, %50, %51, %52, %53, %54, %55, %56, %57, %58, %59, %60, %61, %62, %63}, "
    "{%64, %65, %66, %67}, db, p, 1, 1, 0;\n}\n"
    : "+f"(d[0]), "+f"(d[1]), "+f"(d[2]), "+f"(d[3]), "+f"(d[4]), "+f"(d[5]), "+f"(d[6]), "+f"(d[7]), "+f"(d[8]), "+f"(d[9]), "+f"(d[10]), "+f"(d[11]), "+f"(d[12]), "+f"(d[13]), "+f"(d[14]), "+f"(d[15]), "+f"(d[16]), "+f"(d[17]), "+f"(d[18]), "+f"(d[19]), "+f"(d[20]), "+f"(d[21]), "+f"(d[22]), "+f"(d[23]), "+f"(d[24]), "+f"(d[25]), "+f"(d[26]), "+f"(d[27]), "+f"(d[28]), "+f"(d[29]), "+f"(d[30]), "+f"(d[31]), "+f"(d[32]), "+f"(d[33]), "+f"(d[34]), "+f"(d[35]), "+f"(d[36]), "+f"(d[37]), "+f"(d[38]), "+f"(d[39]), "+f"(d[40]), "+f"(d[41]), "+f"(d[42]), "+f"(d[43]), "+f"(d[44]), "+f"(d[45]), "+f"(d[46]), "+f"(d[47]), "+f"(d[48]), "+f"(d[49]), "+f"(d[50]), "+f"(d[51]), "+f"(d[52]), "+f"(d[53]), "+f"(d[54]), "+f"(d[55]), "+f"(d[56]), "+f"(d[57]), "+f"(d[58]), "+f"(d[59]), "+f"(d[60]), "+f"(d[61]), "+f"(d[62]), "+f"(d[63])
    : "r"(a0), "r"(a1), "r"(a2), "r"(a3), "r"(b_lo), "r"(scaleD), "n"(OFFB));
}

__device__ __forceinline__ uint4 ldg_nc_v4(const void* p) {
  uint4 v;
    asm volatile("{\n.reg .b64 pol;\ncreatepolicy.fractional.L2::evict_first.b64 pol, 1.0;\n"
                 "ld.global.nc.L1::no_allocate.L2::cache_hint.v4.u32 {%0, %1, %2, %3}, [%4], pol;\n}\n" : "=r"(v.x), "=r"(v.y), "=r"(v.z), "=r"(v.w) : "l"(p));
  return v;
}
__device__ __forceinline__ uint64_t pol_normal() {
  uint64_t p; asm volatile("createpolicy.fractional.L2::evict_normal.b64 %0, 1.0;" : "=l"(p)); return p;
}
__device__ __forceinline__ void unpack8(const uint4& u, float (&v)[8]) {
  v[0] = bflo(u.x); v[1] = bfhi(u.x); v[2] = bflo(u.y); v[3] = bfhi(u.y);
  v[4] = bflo(u.z); v[5] = bfhi(u.z); v[6] = bflo(u.w); v[7] = bfhi(u.w);
}
__device__ __forceinline__ void fma8(float (&acc)[8], float s, const uint4& w) {
  acc[0] = fmaf(s, bflo(w.x), acc[0]); acc[1] = fmaf(s, bfhi(w.x), acc[1]); acc[2] = fmaf(s, bflo(w.y), acc[2]); acc[3] = fmaf(s, bfhi(w.y), acc[3]);
  acc[4] = fmaf(s, bflo(w.z), acc[4]); acc[5] = fmaf(s, bfhi(w.z), acc[5]); acc[6] = fmaf(s, bflo(w.w), acc[6]); acc[7] = fmaf(s, bfhi(w.w), acc[7]);
}
__device__ __forceinline__ float rcp_approx(float x) { float y; asm("rcp.approx.ftz.f32 %0, %1;" : "=f"(y) : "f"(x)); return y; }
__device__ __forceinline__ float sigmoid_f(float v) { return rcp_approx(1.0f + ex2_approx(v * -1.4426950408889634f)); }
__device__ __forceinline__ float silu_bf(float v) { return rbf(v * sigmoid_f(v)); }
__device__ __forceinline__ uint32_t rank_key(float r, int idx) {
  const uint32_t b = __float_as_uint(r) >> 16;
  const uint32_t u = (r != r) ? 0u : ((b & 0x8000u) ? (~b & 0xffffu) : (b | 0x8000u));
  return (u << 16) | (0xffffu - (uint32_t)idx);
}
__device__ __forceinline__ void warp_top2(uint32_t& k1, uint32_t& k2) {
  const uint32_t m1 = __reduce_max_sync(0xffffffffu, k1);
  k2 = __reduce_max_sync(0xffffffffu, k1 == m1 ? k2 : k1);
  k1 = m1;
}
__device__ __forceinline__ uint32_t bmul2(uint32_t a, uint32_t b) { uint32_t r; asm("mul.rn.bf16x2 %0, %1, %2;" : "=r"(r) : "r"(a), "r"(b)); return r; }
__device__ __forceinline__ uint32_t badd2(uint32_t a, uint32_t b) { uint32_t r; asm("add.rn.bf16x2 %0, %1, %2;" : "=r"(r) : "r"(a), "r"(b)); return r; }
__device__ __forceinline__ uint32_t bsub2(uint32_t a, uint32_t b) { uint32_t r; asm("sub.rn.bf16x2 %0, %1, %2;" : "=r"(r) : "r"(a), "r"(b)); return r; }
__device__ __forceinline__ float sqrt_approx(float x) { float y; asm("sqrt.approx.f32 %0, %1;" : "=f"(y) : "f"(x)); return y; }
__device__ __forceinline__ uint32_t ln_norm2(uint32_t x1, uint32_t mb2, float inv) {
  const uint32_t d = bsub2(x1, mb2);
  return pack_bf16(bflo(d) * inv, bfhi(d) * inv);
}
__device__ __forceinline__ uint32_t bfma2(uint32_t a, uint32_t b, uint32_t c) { uint32_t r; asm("fma.rn.bf16x2 %0, %1, %2, %3;" : "=r"(r) : "r"(a), "r"(b), "r"(c)); return r; }
__device__ __forceinline__ uint32_t ln_norm2b(uint32_t x1, uint32_t mb2, uint32_t ih, uint32_t il) {
  const uint32_t d = bsub2(x1, mb2);
  return bfma2(d, ih, bmul2(d, il));
}
__device__ __forceinline__ uint32_t ln_mod2(uint32_t x1, uint32_t mb2, float inv, uint32_t c1, uint32_t sb) { return badd2(bmul2(ln_norm2(x1, mb2, inv), c1), sb); }
__device__ __forceinline__ void ldmatrix_x4(uint32_t addr, uint32_t& r0, uint32_t& r1, uint32_t& r2, uint32_t& r3) {
  asm volatile("ldmatrix.sync.aligned.m8n8.x4.shared.b16 {%0, %1, %2, %3}, [%4];" : "=r"(r0), "=r"(r1), "=r"(r2), "=r"(r3) : "r"(addr) : "memory");
}
__device__ __forceinline__ uint4 ldg_stream_v4(const void* p, uint64_t pol) {
  uint4 v; asm volatile("ld.global.nc.L1::no_allocate.L2::cache_hint.L2::128B.v4.u32 {%0, %1, %2, %3}, [%4], %5;" : "=r"(v.x), "=r"(v.y), "=r"(v.z), "=r"(v.w) : "l"(p), "l"(pol)); return v;
}
__device__ __forceinline__ void bulk_load_hint(uint32_t dst, const void* src, uint32_t bytes, uint32_t bar, uint64_t pol) {
  asm volatile("cp.async.bulk.shared::cluster.global.mbarrier::complete_tx::bytes.L2::cache_hint [%0], [%1], %2, [%3], %4;"
    :: "r"(dst), "l"(src), "r"(bytes), "r"(bar), "l"(pol) : "memory");
}
__device__ __forceinline__ void red_release_add(unsigned int* p, unsigned int v) { asm volatile("red.release.gpu.global.add.u32 [%0], %1;" :: "l"(p), "r"(v) : "memory"); }
__device__ __forceinline__ unsigned int ld_acquire(const unsigned int* p) { unsigned int v; asm volatile("ld.acquire.gpu.global.u32 %0, [%1];" : "=r"(v) : "l"(p) : "memory"); return v; }
__device__ __forceinline__ void spin_until(const unsigned int* p, unsigned int target) {
  #pragma unroll 1
  for (unsigned int i = 0; i < (1u << 22); i++) { if (ld_acquire(p) >= target) return; }
}
__device__ __forceinline__ float lds_f32(uint32_t a) { float v; asm volatile("ld.shared.f32 %0, [%1];" : "=f"(v) : "r"(a) : "memory"); return v; }
__device__ __forceinline__ float2 lds_f32x2(uint32_t a) { float2 v; asm volatile("ld.shared.v2.f32 {%0, %1}, [%2];" : "=f"(v.x), "=f"(v.y) : "r"(a) : "memory"); return v; }
__device__ __forceinline__ uint2 lds_u32x2(uint32_t a) { uint2 v; asm volatile("ld.shared.v2.u32 {%0, %1}, [%2];" : "=r"(v.x), "=r"(v.y) : "r"(a) : "memory"); return v; }
__device__ __forceinline__ uint32_t lds_u32(uint32_t a) { uint32_t v; asm volatile("ld.shared.u32 %0, [%1];" : "=r"(v) : "r"(a) : "memory"); return v; }
__device__ __forceinline__ void sts_u32(uint32_t a, uint32_t v) { asm volatile("st.shared.u32 [%0], %1;" :: "r"(a), "r"(v) : "memory"); }
__device__ __forceinline__ void sts_u32x2(uint32_t a, uint32_t x, uint32_t y) { asm volatile("st.shared.v2.u32 [%0], {%1, %2};" :: "r"(a), "r"(x), "r"(y) : "memory"); }
__device__ __forceinline__ void sts_f32(uint32_t a, float v) { asm volatile("st.shared.f32 [%0], %1;" :: "r"(a), "f"(v) : "memory"); }
__device__ __forceinline__ void sts_f32x2(uint32_t a, float x, float y) { asm volatile("st.shared.v2.f32 [%0], {%1, %2};" :: "r"(a), "f"(x), "f"(y) : "memory"); }
__device__ __forceinline__ void sts_f32x4(uint32_t a, float x, float y, float z, float w) { asm volatile("st.shared.v4.f32 [%0], {%1, %2, %3, %4};" :: "r"(a), "f"(x), "f"(y), "f"(z), "f"(w) : "memory"); }

__device__ __forceinline__ uint4 lds_u32x4(uint32_t a) { uint4 v; asm volatile("ld.shared.v4.u32 {%0, %1, %2, %3}, [%4];" : "=r"(v.x), "=r"(v.y), "=r"(v.z), "=r"(v.w) : "r"(a) : "memory"); return v; }
__device__ __forceinline__ void sts_u32x4(uint32_t a, uint32_t x, uint32_t y, uint32_t z, uint32_t w) { asm volatile("st.shared.v4.u32 [%0], {%1, %2, %3, %4};" :: "r"(a), "r"(x), "r"(y), "r"(z), "r"(w) : "memory"); }
__device__ __forceinline__ void st_tagged(float* p, float v) {
  const uint32_t b = __float_as_uint(v);
  asm volatile("st.relaxed.gpu.global.u32 [%0], %1;" :: "l"(p), "r"(b == 0u ? 0x80000000u : b) : "memory");
}
__device__ __forceinline__ void st_tagged4(float* p, float x, float y, float z, float w) {
  const uint32_t a = __float_as_uint(x), b = __float_as_uint(y), c = __float_as_uint(z), d = __float_as_uint(w);
  asm volatile("st.relaxed.gpu.global.v4.u32 [%0], {%1, %2, %3, %4};" :: "l"(p), "r"(a == 0u ? 0x80000000u : a), "r"(b == 0u ? 0x80000000u : b),
               "r"(c == 0u ? 0x80000000u : c), "r"(d == 0u ? 0x80000000u : d) : "memory");
}
__device__ __forceinline__ void st_relaxed2(void* p, uint32_t a, uint32_t b) { asm volatile("st.relaxed.gpu.global.v2.u32 [%0], {%1, %2};" :: "l"(p), "r"(a), "r"(b) : "memory"); }
__device__ __forceinline__ float4 ld_tagged4(const float* p) {
  float4 v; asm volatile("ld.relaxed.gpu.global.v4.f32 {%0, %1, %2, %3}, [%4];" : "=f"(v.x), "=f"(v.y), "=f"(v.z), "=f"(v.w) : "l"(p) : "memory"); return v;
}
__device__ __forceinline__ bool tagged4(const float4& v) {
  return __float_as_uint(v.x) != 0u && __float_as_uint(v.y) != 0u && __float_as_uint(v.z) != 0u && __float_as_uint(v.w) != 0u;
}
__device__ __forceinline__ void hint_arrive(uint32_t* p) { asm volatile("red.relaxed.gpu.global.add.u32 [%0], 1;" :: "l"(p) : "memory"); }
__device__ __forceinline__ void hint_wait(const uint32_t* p, uint32_t target) {
  uint32_t v = 0u;
  #pragma unroll 1
  for (unsigned int i = 0; i < (1u << 22) && v < target; i++) asm volatile("ld.relaxed.gpu.global.u32 %0, [%1];" : "=r"(v) : "l"(p) : "memory");
}
__device__ __forceinline__ void fence_proxy_async_global() { asm volatile("fence.proxy.async.global;" ::: "memory"); }

#define H_SPLIT 1
#define X_DLY 1000
#define W_TMA 1
#define W_DLY 1900
#define R_DLY 0
constexpr int PRE_B = 2;
#define H_P2 1
#define H_PREG 1
template <int J0, int J1>
__device__ __forceinline__ void load_parts(float2 (&pa)[J1 - J0][4], int t2) {
  #pragma unroll
  for (int j = J0; j < J1; j++)
    #pragma unroll
    for (int k = 0; k < 4; k++)
      asm volatile("ld.relaxed.gpu.global.v2.f32 {%0, %1}, [%2];" : "=f"(pa[j - J0][k].x), "=f"(pa[j - J0][k].y)
                   : "l"(g_modpart + k * 2 * T_D + (t2 >> 7) * T_D + j * 256 + (t2 & 127) * 2) : "memory");
}
template <int J0, int J1>
__device__ __forceinline__ void finish_parts(float2 (&pa)[J1 - J0][4], bool loaded, int t2, uint32_t tab) {
  #pragma unroll 1
  for (unsigned int spin = 0; spin < (1u << 22); spin++) {
    if (!loaded) load_parts<J0, J1>(pa, t2);
    loaded = false;
    bool ok = true;
    #pragma unroll
    for (int j = 0; j < J1 - J0; j++)
      #pragma unroll
      for (int k = 0; k < 4; k++) ok &= (__float_as_uint(pa[j][k].x) != 0u) & (__float_as_uint(pa[j][k].y) != 0u);
    if (__all_sync(0xffffffffu, ok)) break;
  }
  #pragma unroll
  for (int j = J0; j < J1; j++) {
    const float2* q = pa[j - J0];
    const uint32_t m = pack_bf16(((q[0].x + q[1].x) + q[2].x) + q[3].x, ((q[0].y + q[1].y) + q[2].y) + q[3].y);
    sts_u32(tab + (t2 >> 7) * 2048 + j * 512 + (t2 & 127) * 4, t2 >= 128 ? badd2(m, 0x3F803F80u) : m);
  }
}
__device__ __forceinline__ void head_phase(uint32_t scr, uint32_t xs, uint32_t b_x, uint32_t b_go, uint32_t b_head, int t2, uint32_t zero, const bf16* __restrict__ cvec, const bf16* __restrict__ w_mod) {
  const int lane = t2 & 31, w8 = t2 >> 5;
  const int cb = blockIdx.x & 31, ks = blockIdx.x >> 5;
  const bool early = (cb & 15) < 4 * H_SPLIT;
  const uint32_t ws = (xs - 32768 + (t2 >> 3) * 128 + (((t2 ^ (t2 >> 3)) & 7) << 4)) ^ zero;
  const float cv = __bfloat162float(cvec[ks * 256 + t2]);
  const bf16* wsrc = w_mod + (size_t)(ks * 256 + (t2 >> 3)) * (6 * T_D) + cb * 64 + (t2 & 7) * 8;
  auto fetch = [&]() {
    const uint64_t pol = policy_evict_first();
    #pragma unroll 2
    for (int i = 0; i < 8; i++)
      asm volatile("cp.async.cg.shared.global.L2::cache_hint [%0], [%1], 16, %2;" :: "r"(ws + i * 4096), "l"(wsrc + (size_t)i * 32 * 6 * T_D), "l"(pol) : "memory");
  };
  if (early) fetch();
  sts_f32(scr + t2 * 4, silu_bf(cv));
  named_bar_sync(6, 384);
  TL_MARK2(1, t2 == 0);
  uint4 xv[2][4];
  uint32_t mb2[2], ih[2], il[2];
  auto modulate = [&](int j) {
    const uint4 sa = lds_u32x4(scr + 8192 + j * 512 + lane * 16), c1 = lds_u32x4(scr + 8192 + 2048 + j * 512 + lane * 16);
    #pragma unroll
    for (int r = 0; r < 2; r++) {
      xv[r][j].x = badd2(bmul2(ln_norm2b(xv[r][j].x, mb2[r], ih[r], il[r]), c1.x), sa.x); xv[r][j].y = badd2(bmul2(ln_norm2b(xv[r][j].y, mb2[r], ih[r], il[r]), c1.y), sa.y);
      xv[r][j].z = badd2(bmul2(ln_norm2b(xv[r][j].z, mb2[r], ih[r], il[r]), c1.z), sa.z); xv[r][j].w = badd2(bmul2(ln_norm2b(xv[r][j].w, mb2[r], ih[r], il[r]), c1.w), sa.w);
    }
  };
  auto store = [&](int j) {
    #pragma unroll
    for (int r = 0; r < 2; r++) *reinterpret_cast<uint4*>(g_h + (size_t)(blockIdx.x * 16 + 2 * w8 + r) * T_D + j * 256 + lane * 8) = xv[r][j];
  };
  #pragma unroll 1
  for (int ph = 0; ph < 2; ph++) {
    if ((ph == 0) == early) {
      asm volatile("cp.async.wait_all;" ::: "memory");
      if (W_TMA && !early) mbar_wait(b_x + 168, 0);
      float acc[8];
      #pragma unroll
      for (int j = 0; j < 8; j++) acc[j] = 0.f;
      #pragma unroll
      for (int i = 0; i < 8; i++) fma8(acc, lds_f32(scr + ((t2 >> 3) + 32 * i) * 4), lds_u32x4(ws + i * 4096));
      #pragma unroll
      for (int j = 0; j < 4; j++) { const bool up = lane & 16; acc[j] = (up ? acc[4 + j] : acc[j]) + __shfl_xor_sync(0xffffffffu, up ? acc[j] : acc[4 + j], 16); }
      #pragma unroll
      for (int j = 0; j < 2; j++) { const bool up = lane & 8; acc[j] = (up ? acc[2 + j] : acc[j]) + __shfl_xor_sync(0xffffffffu, up ? acc[j] : acc[2 + j], 8); }
      sts_f32x2(scr + 1024 + w8 * 256 + (lane & 7) * 32 + (lane >> 3) * 8, acc[0], acc[1]);
      named_bar_sync(5, 256);
      if (t2 < 64) {
        float sum = 0.f;
        #pragma unroll
        for (int i = 0; i < 8; i++) sum += lds_f32(scr + 1024 + i * 256 + t2 * 4);
        st_tagged(g_modpart + ks * 2 * T_D + cb * 64 + t2, sum);
        TL_MARK2(early ? 2 : 6, t2 == 0);
      }
    } else {
      float2 pa[H_SPLIT][4];
      mbar_wait(b_x, 0);
      TL_MARK2(18, t2 == 0);
      if (H_PREG) load_parts<0, H_SPLIT>(pa, t2);
      if (!early && !W_TMA) fetch();
      #pragma unroll
      for (int r = 0; r < 2; r++)
        #pragma unroll
        for (int j = 0; j < 4; j++) xv[r][j] = lds_u32x4(xs + (2 * w8 + r) * 2048 + j * 512 + lane * 16);
  {
    float st[4] = {0.f, 0.f, 0.f, 0.f};
    #pragma unroll
    for (int r = 0; r < 2; r++)
      #pragma unroll
      for (int j = 0; j < 4; j++) {
        float v[8];
        unpack8(xv[r][j], v);
        st[2 * r] += ((v[0] + v[1]) + (v[2] + v[3])) + ((v[4] + v[5]) + (v[6] + v[7]));
        st[2 * r + 1] += fmaf(v[0], v[0], fmaf(v[1], v[1], fmaf(v[2], v[2], v[3] * v[3]))) + fmaf(v[4], v[4], fmaf(v[5], v[5], fmaf(v[6], v[6], v[7] * v[7])));
      }
    #pragma unroll
    for (int k = 0; k < 2; k++) { const bool up = lane & 16; st[k] = (up ? st[2 + k] : st[k]) + __shfl_xor_sync(0xffffffffu, up ? st[k] : st[2 + k], 16); }
    #pragma unroll
    for (int o = 8; o > 0; o >>= 1) { st[0] += __shfl_xor_sync(0xffffffffu, st[0], o); st[1] += __shfl_xor_sync(0xffffffffu, st[1], o); }
    const float mean = st[0] * (1.0f / T_D);
    const float inv = rcp_approx(rbf(sqrt_approx(rbf(rbf(fmaxf(fmaf(-mean, mean, st[1] * (1.0f / T_D)), 0.f)) + 1e-05f))));
    const uint32_t m = pack_bf16(mean, mean), h = pack_bf16(inv - rbf(inv), inv);
    #pragma unroll
    for (int r = 0; r < 2; r++) {
      mb2[r] = __shfl_sync(0xffffffffu, m, 16 * r);
      const uint32_t hr = __shfl_sync(0xffffffffu, h, 16 * r);
      ih[r] = __byte_perm(hr, hr, 0x3232); il[r] = __byte_perm(hr, hr, 0x1010);
    }
  }
      TL_MARK2(5, t2 == 0);
      finish_parts<0, H_SPLIT>(pa, H_PREG, t2, scr + 8192);
      named_bar_sync(5, 256);
      TL_MARK2(7, t2 == 0);
      #pragma unroll
      for (int j = 0; j < H_SPLIT; j++) { modulate(j); store(j); }
      named_bar_arrive(9, 288);
    }
  }
  if (R_DLY > 0) { const uint32_t c0 = clock_lo(); while (clock_lo() - c0 < R_DLY + 1) {} }
  float2 pb[4 - H_SPLIT][4];
  finish_parts<H_SPLIT, 4>(pb, false, t2, scr + 8192);
  named_bar_sync(5, 256);
  TL_MARK2(17, t2 == 0);
  #pragma unroll
  for (int j = H_SPLIT; j < 4; j++) modulate(j);
  __syncwarp();
  if (lane == 0) mbar_arrive(b_head + (xv[1][3].w & zero));
  mbar_wait(b_go, 0);
  #pragma unroll
  for (int j = H_SPLIT; j < 4; j++) store(j);
  named_bar_arrive(8, 288);
}

#define MOD_AT (b_empty + 8)
#define MOD_PF 0
#define MOD_SPLIT 16
__device__ __forceinline__ void mod_rest(uint32_t scr, uint32_t b_go, int t, const bf16* __restrict__ cvec, const bf16* __restrict__ w_mod, const bf16* __restrict__ w_r) {
  const int lane = t & 31;
  #pragma unroll 1
  for (int i = t; i < T_D / 2; i += 64) {
    const uint32_t c2 = *reinterpret_cast<const uint32_t*>(cvec + 2 * i);
    sts_u32(scr + i * 4, pack_bf16(silu_bf(bflo(c2)), silu_bf(bfhi(c2))));
  }
  named_bar_sync(11, 64);
  const bf16* wp = w_mod + (size_t)(2 * (t >> 2)) * (6 * T_D) + 2 * T_D + blockIdx.x * 32 + (t & 3) * 8;
  float acc[8];
  #pragma unroll
  for (int i = 0; i < 8; i++) acc[i] = 0.f;
  #pragma unroll 1
  for (int i = 0; i < 32; i += 2) {
    if (i == MOD_SPLIT) mbar_wait(b_go, 0);
    const uint4 w0 = ldg_nc_v4(wp), w1 = ldg_nc_v4(wp + 6 * T_D), w2 = ldg_nc_v4(wp + 32 * 6 * T_D), w3 = ldg_nc_v4(wp + 33 * 6 * T_D);
    wp += 64 * 6 * T_D;
    const uint32_t s0 = lds_u32(scr + (i * 16 + (t >> 2)) * 4), s1 = lds_u32(scr + (i * 16 + 16 + (t >> 2)) * 4);
    fma8(acc, bflo(s0), w0); fma8(acc, bfhi(s0), w1); fma8(acc, bflo(s1), w2); fma8(acc, bfhi(s1), w3);
  }
  #pragma unroll
  for (int j = 0; j < 4; j++) { const bool up = lane & 16; acc[j] = (up ? acc[4 + j] : acc[j]) + __shfl_xor_sync(0xffffffffu, up ? acc[j] : acc[4 + j], 16); }
  #pragma unroll
  for (int j = 0; j < 2; j++) { const bool up = lane & 8; acc[j] = (up ? acc[2 + j] : acc[j]) + __shfl_xor_sync(0xffffffffu, up ? acc[j] : acc[2 + j], 8); }
  { const bool up = lane & 4; acc[0] = (up ? acc[1] : acc[0]) + __shfl_xor_sync(0xffffffffu, up ? acc[0] : acc[1], 4); }
  if (t >= 32) sts_f32(scr + 2048 + lane * 4, acc[0]);
  named_bar_sync(11, 64);
  if (__shfl_sync(0xffffffffu, t, 0) < 32) {
    const int kind = blockIdx.x >> 5;
    float v = rbf(acc[0] + lds_f32(scr + 2048 + lane * 4));
    const int col = (blockIdx.x & 31) * 32 + (lane & 3) * 8 + (lane >> 2);
    uint8_t* dst = g_col + (col >> 7) * 1536;
    if (kind == 2) v = rbf(1.0f + v);
    float vw = v * __bfloat162float(w_r[col]);
    if (kind == 2) {
      const int c = col & 127, i = (c & ~15) + ((c >> 1) & 3) * 4 + ((c >> 3) & 1) * 2 + (c & 1);
      reinterpret_cast<bf16*>(dst)[i] = __float2bfloat16_rn(vw);
      reinterpret_cast<bf16*>(dst)[128 + i] = __float2bfloat16_rn(vw - rbf(vw));
    }
    reinterpret_cast<bf16*>(dst + 512 + (kind & 1) * 512 + (kind >> 1) * 256)[col & 127] = __float2bfloat16_rn(v);
    #pragma unroll
    for (int o = 16; o > 0; o >>= 1) vw += __shfl_xor_sync(0xffffffffu, vw, o);
    if (lane == 0 && (kind == 1 || kind == 2)) g_scal[95 - blockIdx.x] = vw;
  }
  #pragma unroll 1
  for (int i = blockIdx.x * 64 + t; i < (int)(sizeof(g_mail) / 16); i += 128 * 64) reinterpret_cast<uint4*>(&g_mail)[i] = make_uint4(0u, 0u, 0u, 0u);
  named_bar_sync(11, 64);
  if (t == 0) red_release_add(&g_hcnt[0], 1u);
}

#define HPOL_A pol_normal()
#define HPOL_B pol_normal()
#define HMAP_A &tmOl
#define HMAP_B &tmWo
constexpr int AT_NBLK = T_SEQ / 128;
constexpr float AT_HEAD = 7.0f;
#define WO_LATE 12
constexpr int QP_STAG = 3;
constexpr int AT_SPLIT = 28, AT_PIN = 8, PINB = 4;
constexpr int AT_NFULL = 124;
constexpr int AT_PREG = 40, AT_CREG = 232;
constexpr uint32_t AT_SQ = 5 * 32768;
constexpr float AT_C = 0.08838834764831845f * 1.4426950408889634f;
constexpr float AT_RAW_LO = -16.0f, AT_RAW_HI = 24.0f;
constexpr float AT_RAW_SUM = 281474976710656.0f, AT_RAW_MIN = 9.094947017729282e-13f;
constexpr uint32_t AT_SBAR = AT_SQ + 65536 + 256;
constexpr uint32_t AT_SMEM = AT_SQ + 65536 + 3072;

__device__ __forceinline__ uint32_t ring_slot(uint32_t t) { return t - 5u * ((t * 205u) >> 10); }
__device__ __forceinline__ uint32_t qp_pos(uint32_t j, uint32_t it) { return 4u * it + (j & 3u) + ((j & 3u) == 3u ? it : 0u); }
__device__ __forceinline__ uint32_t ring_par(uint32_t t) { return ((t * 205u) >> 10) & 1u; }
__device__ __forceinline__ void softmax_rowmax(const float (&s)[64], float& mx0, float& mx1) {
  float a0 = fmaxf(s[0], s[1]), a1 = fmaxf(s[4], s[5]), a2 = fmaxf(s[8], s[9]), a3 = fmaxf(s[12], s[13]);
  float b0 = fmaxf(s[2], s[3]), b1 = fmaxf(s[6], s[7]), b2 = fmaxf(s[10], s[11]), b3 = fmaxf(s[14], s[15]);
  #pragma unroll
  for (int j = 4; j < 16; j += 4) {
    a0 = fmaxf(a0, fmaxf(s[4 * j + 0], s[4 * j + 1]));  b0 = fmaxf(b0, fmaxf(s[4 * j + 2], s[4 * j + 3]));
    a1 = fmaxf(a1, fmaxf(s[4 * j + 4], s[4 * j + 5]));  b1 = fmaxf(b1, fmaxf(s[4 * j + 6], s[4 * j + 7]));
    a2 = fmaxf(a2, fmaxf(s[4 * j + 8], s[4 * j + 9]));  b2 = fmaxf(b2, fmaxf(s[4 * j + 10], s[4 * j + 11]));
    a3 = fmaxf(a3, fmaxf(s[4 * j + 12], s[4 * j + 13])); b3 = fmaxf(b3, fmaxf(s[4 * j + 14], s[4 * j + 15]));
  }
  mx0 = fmaxf(fmaxf(a0, a1), fmaxf(a2, a3));
  mx1 = fmaxf(fmaxf(b0, b1), fmaxf(b2, b3));
  mx0 = fmaxf(mx0, __shfl_xor_sync(0xffffffffu, mx0, 1));
  mx1 = fmaxf(mx1, __shfl_xor_sync(0xffffffffu, mx1, 1));
  mx0 = fmaxf(mx0, __shfl_xor_sync(0xffffffffu, mx0, 2));
  mx1 = fmaxf(mx1, __shfl_xor_sync(0xffffffffu, mx1, 2));
}
__device__ __forceinline__ void softmax_sub(float (&s)[64], float mc0, float mc1) {
  #pragma unroll
  for (int j = 0; j < 16; j++) { s[4 * j] -= mc0; s[4 * j + 1] -= mc0; s[4 * j + 2] -= mc1; s[4 * j + 3] -= mc1; }
}
template <int LO, int HI>
__device__ __forceinline__ void softmax_exp(float (&s)[64]) {
  #pragma unroll
  for (int i = LO; i < HI; i++) s[i] = ex2_approx(s[i]);
}
__device__ __forceinline__ bool softmax_mode(const float (&s)[64], float& mc0, float& mc1) {
  softmax_rowmax(s, mc0, mc1);
  const bool raw = __all_sync(0xffffffffu, mc0 >= AT_RAW_LO && mc0 <= AT_RAW_HI && mc1 >= AT_RAW_LO && mc1 <= AT_RAW_HI);
  mc0 += AT_HEAD; mc1 += AT_HEAD;
  return raw;
}
__device__ __forceinline__ void rowsum_p(const uint32_t (&p)[32], uint32_t& t0, uint32_t& t1) {
  uint32_t a[16];
  #pragma unroll
  for (int i = 0; i < 8; i++) { a[2 * i] = badd2(p[4 * i], p[4 * i + 2]); a[2 * i + 1] = badd2(p[4 * i + 1], p[4 * i + 3]); }
  #pragma unroll
  for (int i = 0; i < 4; i++) { a[2 * i] = badd2(a[4 * i], a[4 * i + 2]); a[2 * i + 1] = badd2(a[4 * i + 1], a[4 * i + 3]); }
  t0 = badd2(badd2(a[0], a[2]), badd2(a[4], a[6]));
  t1 = badd2(badd2(a[1], a[3]), badd2(a[5], a[7]));
}
__device__ __forceinline__ void add_rowsum(const uint32_t (&p)[32], float& l0, float& l1) {
  uint32_t t0, t1;
  rowsum_p(p, t0, t1);
  l0 += bflo(t0) + bfhi(t0); l1 += bflo(t1) + bfhi(t1);
}
__device__ __forceinline__ void pack_p(uint32_t (&p)[32], const float (&s)[64]) {
  #pragma unroll
  for (int i = 0; i < 32; i++) p[i] = pack_bf16(s[2 * i], s[2 * i + 1]);
}
__device__ __noinline__ void attn_rows_exact(uint32_t sq, uint32_t so, int hsel, const bf16* __restrict__ kh, const bf16* __restrict__ vh) {
  const int warp = (threadIdx.x >> 5) & 3, lane = threadIdx.x & 31;
  const size_t hofs = (size_t)((blockIdx.x < 128 ? blockIdx.x >> 4 : 15) * 2 + hsel) * T_SEQ * T_DH;
  kh += hofs; vh += hofs;
  #pragma unroll 1
  for (int r = 16 * warp; r < 16 * warp + 16; r++) {
    const uint32_t ad = (lane >> 4) * 16384 + r * 128 + ((((lane & 15) >> 1) ^ (r & 7)) << 4) + (lane & 1) * 8;
    uint2 qv; asm volatile("ld.shared.v2.u32 {%0, %1}, [%2];" : "=r"(qv.x), "=r"(qv.y) : "r"(sq + ad) : "memory");
    const float q0 = bflo(qv.x), q1 = bfhi(qv.x), q2 = bflo(qv.y), q3 = bfhi(qv.y);
    float m = -INFINITY, l = 0.f, o0 = 0.f, o1 = 0.f, o2 = 0.f, o3 = 0.f;
    #pragma unroll 1
    for (int key = 0; key < T_SEQ; key++) {
      const uint2 kv = *reinterpret_cast<const uint2*>(kh + (size_t)key * T_DH + lane * 4);
      const uint2 vv = *reinterpret_cast<const uint2*>(vh + (size_t)key * T_DH + lane * 4);
      float sc = (q0 * bflo(kv.x) + q1 * bfhi(kv.x)) + (q2 * bflo(kv.y) + q3 * bfhi(kv.y));
      #pragma unroll
      for (int o = 16; o > 0; o >>= 1) sc += __shfl_xor_sync(0xffffffffu, sc, o);
      const float mn = fmaxf(m, sc);
      const float al = (m == mn) ? 1.0f : ex2_approx(m - mn), p = rbf(ex2_approx(sc - mn));
      m = mn;
      l = fmaf(l, al, p);
      o0 = fmaf(o0, al, p * bflo(vv.x)); o1 = fmaf(o1, al, p * bfhi(vv.x));
      o2 = fmaf(o2, al, p * bflo(vv.y)); o3 = fmaf(o3, al, p * bfhi(vv.y));
    }
    const float inv = rcp_approx(l);
    asm volatile("st.shared.v2.u32 [%0], {%1, %2};" :: "r"(so + ad), "r"(pack_bf16(o0 * inv, o1 * inv)), "r"(pack_bf16(o2 * inv, o3 * inv)) : "memory");
  }
}
__device__ __forceinline__ void issue_qk(float (&s)[64], const uint32_t (&q)[32], uint32_t k_lo) {
  wgmma_fence();
  wgmma_m64n128k16_rs<0>(s, q[0], q[1], q[2], q[3], k_lo, 0);
  wgmma_m64n128k16_rs<2>(s, q[4], q[5], q[6], q[7], k_lo, 1);
  wgmma_m64n128k16_rs<4>(s, q[8], q[9], q[10], q[11], k_lo, 1);
  wgmma_m64n128k16_rs<6>(s, q[12], q[13], q[14], q[15], k_lo, 1);
  wgmma_m64n128k16_rs<1024>(s, q[16], q[17], q[18], q[19], k_lo, 1);
  wgmma_m64n128k16_rs<1026>(s, q[20], q[21], q[22], q[23], k_lo, 1);
  wgmma_m64n128k16_rs<1028>(s, q[24], q[25], q[26], q[27], k_lo, 1);
  wgmma_m64n128k16_rs<1030>(s, q[28], q[29], q[30], q[31], k_lo, 1);
  wgmma_commit();
}
__device__ __forceinline__ void issue_pv(float (&o)[64], const uint32_t (&p)[32], uint32_t v_lo, int accumulate) {
  wgmma_fence();
  wgmma_m64n128k16_rs_tb<0>(o, p[0], p[1], p[2], p[3], v_lo, accumulate);
  wgmma_m64n128k16_rs_tb<128>(o, p[4], p[5], p[6], p[7], v_lo, 1);
  wgmma_m64n128k16_rs_tb<256>(o, p[8], p[9], p[10], p[11], v_lo, 1);
  wgmma_m64n128k16_rs_tb<384>(o, p[12], p[13], p[14], p[15], v_lo, 1);
  wgmma_m64n128k16_rs_tb<512>(o, p[16], p[17], p[18], p[19], v_lo, 1);
  wgmma_m64n128k16_rs_tb<640>(o, p[20], p[21], p[22], p[23], v_lo, 1);
  wgmma_m64n128k16_rs_tb<768>(o, p[24], p[25], p[26], p[27], v_lo, 1);
  wgmma_m64n128k16_rs_tb<896>(o, p[28], p[29], p[30], p[31], v_lo, 1);
  wgmma_commit();
}
__device__ __forceinline__ void block_end(uint32_t zero, uint32_t bar) {
  #pragma unroll 1
  for (uint32_t i = 0; i < zero; i++) mbar_arrive(bar);
}
__device__ __forceinline__ void rescale_o(float (&o)[64], float al0, float al1) {
  #pragma unroll
  for (int j = 0; j < 16; j++) { o[4 * j] *= al0; o[4 * j + 1] *= al0; o[4 * j + 2] *= al1; o[4 * j + 3] *= al1; }
}

__device__ __forceinline__ void stage_o(const float (&o)[64], float i0, float i1, uint32_t dst, int lane) {
  #pragma unroll
  for (int J = 0; J < 16; J += 2)
    stmatrix_x4(dst + (J >> 3) * 16384 + ((((J & 7) + (lane >> 4)) ^ (lane & 7)) << 4),
                pack_bf16(o[4 * J + 0] * i0, o[4 * J + 1] * i0), pack_bf16(o[4 * J + 2] * i1, o[4 * J + 3] * i1),
                pack_bf16(o[4 * J + 4] * i0, o[4 * J + 5] * i0), pack_bf16(o[4 * J + 6] * i1, o[4 * J + 7] * i1));
}
__device__ __forceinline__ bool finish_l(float& l0, float& l1) {
  l0 += __shfl_xor_sync(0xffffffffu, l0, 1); l1 += __shfl_xor_sync(0xffffffffu, l1, 1);
  l0 += __shfl_xor_sync(0xffffffffu, l0, 2); l1 += __shfl_xor_sync(0xffffffffu, l1, 2);
  const bool redo = __any_sync(0xffffffffu, !(l0 <= AT_RAW_SUM && l1 <= AT_RAW_SUM && l0 >= AT_RAW_MIN && l1 >= AT_RAW_MIN));
  l0 = rcp_approx(l0); l1 = rcp_approx(l1);
  return redo;
}
template <int J0>
__device__ __forceinline__ void stage_q(const float (&acc)[128], float c, uint32_t dst, int lane) {
  #pragma unroll
  for (int J = J0; J < J0 + 16; J += 2)
    stmatrix_x4(dst + (J >> 3) * 16384 + ((((J & 7) + (lane >> 4)) ^ (lane & 7)) << 4),
                pack_bf16(acc[4 * J + 0] * c, acc[4 * J + 1] * c), pack_bf16(acc[4 * J + 2] * c, acc[4 * J + 3] * c),
                pack_bf16(acc[4 * J + 4] * c, acc[4 * J + 5] * c), pack_bf16(acc[4 * J + 6] * c, acc[4 * J + 7] * c));
}
__device__ __forceinline__ void store_o(const CUtensorMap* tmO, uint32_t src, int head, int row) {
  tma_store_2d(tmO, src, head * T_DH, row);
  tma_store_2d(tmO, src + 16384, head * T_DH + 64, row);
  bulk_commit();
}
__device__ __forceinline__ void mma_bf16(float (&d)[4], uint32_t a0, uint32_t a1, uint32_t a2, uint32_t a3, uint32_t b0, uint32_t b1) {
  asm volatile("mma.sync.aligned.m16n8k16.row.col.f32.bf16.bf16.f32 {%0, %1, %2, %3}, {%4, %5, %6, %7}, {%8, %9}, {%0, %1, %2, %3};"
               : "+f"(d[0]), "+f"(d[1]), "+f"(d[2]), "+f"(d[3]) : "r"(a0), "r"(a1), "r"(a2), "r"(a3), "r"(b0), "r"(b1));
}
struct GemvSel { uint32_t lo0, hi0, lo1, hi1; };
__device__ __forceinline__ GemvSel gemv_sel(int lane) {
  const uint32_t lo = (lane & 8) ? 0x1044u : 0x4410u, hi = (lane & 8) ? 0x3244u : 0x4432u;
  GemvSel s; s.lo0 = (lane & 16) ? 0x4444u : lo; s.hi0 = (lane & 16) ? 0x4444u : hi; s.lo1 = (lane & 16) ? lo : 0x4444u; s.hi1 = (lane & 16) ? hi : 0x4444u;
  return s;
}
#define GEMV_B0(j, h, s) __byte_perm((j) < 2 ? (h).x : (h).y, 0u, ((j) & 1) ? (s).hi0 : (s).lo0)
#define GEMV_B1(j, h, s) __byte_perm((j) < 2 ? (h).x : (h).y, 0u, ((j) & 1) ? (s).hi1 : (s).lo1)
__device__ __forceinline__ float4 gemv_out(const float (&d)[4], int lane) {
  const bool tk = lane & 1;
  const float r0 = __shfl_xor_sync(0xffffffffu, tk ? d[0] : d[1], 1), r1 = __shfl_xor_sync(0xffffffffu, tk ? d[2] : d[3], 1);
  return tk ? make_float4(r0, d[1], r1, d[3]) : make_float4(d[0], r0, d[2], r1);
}
#define OG_NG 8
#define HOIST 1
#define PUT_N 2
#define H_STAG 2
#define NOZERO 1
#define PVPIN 0
#define QKPIN 0
#define ALIGN 1
#define AL_P 60
#define AL_SLEEP 1200
#define AL_MAX 800
#define AL_ADD 0
#define X_PF 0
#define POLL_NS 200
#define KV3D 1
#define W3D 1
#define OG_PRE 10
#define OG_JOBS 7
#define OG_GRP 7
#define LD_FIRST 1
#define LD_STAG (OG_GRP / 2)
constexpr int OG_ST = 5, OG_NKB = T_DQKV / 64 - OG_PRE, OG_MOE = T_F / 32;
__device__ __forceinline__ int pre_loc(int job) {
  const int step = ((job >> 4) << 2) + (job & 3);
  return (step < OG_JOBS ? 2 * step : step < 2 * OG_JOBS ? 2 * (step - OG_JOBS) + 1 : step) * 4 + ((job >> 2) & 3);
}
__device__ __forceinline__ int pre_kb(int i) { return (i >> 1) * 4 + (i & 1); }
__device__ __forceinline__ int own_kb(int i) { return i < (OG_PRE & ~1) ? pre_kb(i) + 2 : i + OG_PRE; }
constexpr int OG_POS = 8;
constexpr uint32_t OG_STAGE = 32768;
constexpr uint32_t OG_SCOL = AT_SBAR + 512;
constexpr uint32_t OG_SMISC = AT_SBAR + 2048;
constexpr int OG_XPOS = OG_POS + OG_NKB;
constexpr uint32_t OG_SWD = AT_SQ, OG_PSLOT = AT_SQ;
constexpr uint32_t OG_SWD1 = (OG_XPOS % OG_ST) * OG_STAGE;
constexpr uint32_t OG_XSLOT = AT_SQ + 32768;
constexpr uint32_t OG_OSLOT = ((OG_XPOS + 1) % OG_ST) * OG_STAGE;
constexpr uint32_t OG_SH2 = ((OG_XPOS + 2) % OG_ST) * OG_STAGE;
constexpr uint32_t OG_SRED = ((OG_XPOS + 3) % OG_ST) * OG_STAGE;
constexpr uint32_t OG_SSTAT = OG_SRED + 16384;
constexpr uint32_t OG_SGU = OG_SRED + 8192;
constexpr uint32_t OG_SFIN = OG_SGU + 256;
#define OGM 2
#define OG_MT(b) (((b) >> OGM) & 15)
#define OG_NT(b) (((b) & ((1 << OGM) - 1)) + (((b) >> (4 + OGM)) << OGM))
#define TAIL_SETUP \
  const uint32_t bar_full = sbase + AT_SBAR, bar_empty = bar_full + 40; \
  const uint32_t bar_wd = bar_full + 168, bar_col = bar_full + 176, bar_out = bar_full + 184, bar_end = bar_full + 192; \
  const uint32_t bar_key = bar_full + 200, bar_h2 = bar_full + 208, bar_sel = bar_full + 216; \
  const int mt = OG_MT(blockIdx.x), nt = OG_NT(blockIdx.x); \
  const int m0 = mt * 128, n0 = nt * 128; \
  const bool has_moe = (int)blockIdx.x < OG_MOE; \
  (void)bar_empty; (void)bar_wd; (void)bar_col; (void)bar_out; (void)bar_end; (void)bar_key; (void)bar_h2; (void)bar_sel; (void)m0; (void)n0; (void)has_moe;

__device__ __forceinline__ void tail_producer(uint32_t sbase, uint32_t ph, uint64_t pol, const CUtensorMap* tmA, const CUtensorMap* tmB, const CUtensorMap* tmX) {
  TAIL_SETUP
  uint32_t stage = OG_POS % OG_ST;
  int kb = 0;
  #pragma unroll 1
  for (int seg = 0; seg < 2; seg++) {
    mbar_wait(bar_full + 264, seg);
    fence_proxy_async_global();
    const int end = seg == 0 ? 32 - OG_PRE : OG_NKB;
    #pragma unroll 1
    for (; kb < end; kb++) {
      const uint32_t fb = bar_full + 8 * stage, sa = sbase + stage * OG_STAGE;
      const int k0 = own_kb(kb) * 64;
      mbar_wait(bar_empty + 8 * stage, ph);
      mbar_expect_tx(fb, OG_STAGE);
      tma_load_3d_hint(sa + 16384, tmB, k0, 2 * nt, fb, pol);
      tma_load_2d_hint(sa, tmA, k0, m0, fb, pol);
      if (++stage == OG_ST) { stage = 0; ph ^= 1; }
    }
  }
  if (has_moe) {
    mbar_wait(bar_empty + 8 * (OG_XPOS % OG_ST), ph);
    mbar_expect_tx(bar_wd, OG_STAGE);
    tma_load_3d_hint(sbase + OG_SWD1, tmX, blockIdx.x * 32, 8, bar_wd, pol);
  }
}

__device__ __forceinline__ uint32_t out2(uint32_t x1, uint32_t mb2, uint32_t ih, uint32_t il, uint32_t c1, uint32_t sb, uint32_t gb) {
  const uint32_t h2 = badd2(bmul2(ln_norm2b(x1, mb2, ih, il), c1), sb);
  return badd2(x1, bmul2(gb, bfma2(h2, 0u, h2)));
}
#define OGTIME gtime()
#define PRE_N 1
#define PRE_PACE 150
#define X_PACE 200
#define WD_LATE 0
#define WD_PACE 300
__device__ __forceinline__ void tail_exchange(uint32_t sbase, const CUtensorMap* tmOut, const bf16* __restrict__ w_down, const bf16* __restrict__ w_r, const bf16* __restrict__ x, bf16* __restrict__ out) {
    TAIL_SETUP
    const int lane = threadIdx.x & 31, wi = __shfl_sync(0xffffffffu, threadIdx.x >> 5, 0);
    if (wi == 3) {
      mbar_wait(bar_full + 264, 0);
      if (blockIdx.x < AT_NFULL) {
        uint32_t a, b;
        asm volatile("ld.relaxed.gpu.global.u32 %0, [%1];" : "=r"(a) : "l"(g_smid + 32 + blockIdx.x - lane) : "memory");
        b = __shfl_down_sync(0xffffffffu, a, 1);
        unsigned int* tm = g_tmax + blockIdx.x - min((int)blockIdx.x, __ffs(__ballot_sync(0xffffffffu, b >= a)) - 1);
        mbar_wait(bar_full + 312, 0);
        if (lane == 0) {
          asm volatile("mov.u32 %0, %%globaltimer_lo;" : "=r"(a));
          asm volatile("red.relaxed.gpu.global.max.u32 [%0], %1;" :: "l"(tm), "r"(a) : "memory");
          __nanosleep(AL_SLEEP);
          asm volatile("ld.relaxed.gpu.global.u32 %0, [%1];" : "=r"(b) : "l"(tm) : "memory");
          b -= a;
          sts_u32(sbase + OG_SMISC + 32, (b < AL_MAX ? b * 13 / 8 : 0u) + AL_ADD);
          mbar_arrive(bar_full + 320);
        }
        named_bar_sync(15, 32);
      }
      mbar_wait(bar_full + 264, 1);
      float a = g_scal[lane], b = g_scal[32 + lane];
      #pragma unroll
      for (int i = 0; i < 3; i++) {
        const uint4 v = *reinterpret_cast<const uint4*>(g_col + nt * 1536 + i * 512 + lane * 16);
        sts_u32x4(sbase + OG_SCOL + i * 512 + lane * 16, v.x, v.y, v.z, v.w);
      }
      #pragma unroll
      for (int o = 16; o > 0; o >>= 1) { a += __shfl_xor_sync(0xffffffffu, a, o); b += __shfl_xor_sync(0xffffffffu, b, o); }
      if (lane == 0) sts_f32x2(sbase + OG_SMISC, a, b);
      const uint64_t pol = policy_evict_first();
      #pragma unroll 1
      for (int r = lane >> 4; r < 128; r += 4) {
        __nanosleep(X_PACE);
        #pragma unroll
        for (int j = 0; j < 4; j += 2)
          asm volatile("cp.async.cg.shared.global.L2::cache_hint [%0], [%1], 16, %2;" :: "r"(sbase + OG_XSLOT + (lane & 8) * 2048 + (r + j) * 128 + (((lane ^ (r + j)) & 7) << 4)),
                       "l"(x + (size_t)(m0 + r + j) * T_D + n0 + (lane & 15) * 8), "l"(pol) : "memory");
      }
      asm volatile("cp.async.wait_all;" ::: "memory");
      __syncwarp();
      if (lane == 0) mbar_arrive(bar_col);
    } else if (wi == 2) {
      if (elect_one()) {
        const uint32_t b_free = bar_full + (blockIdx.x < AT_NFULL ? 80 : 160);
        mbar_wait(b_free, 0); mbar_wait(b_free, 1);
        #pragma unroll 1
        for (unsigned int i = 0; i < (1u << 20) && ld_acquire(&g_hcnt[32 * (1 + mt) + 4 + (nt >> 1)]) == 0u; i++) __nanosleep(POLL_NS);
        TL_MARK2(23, true);
        fence_proxy_async_global();
        TL_MARK2(4, true);
        mbar_expect_tx(bar_full + 272, 32768);
        #pragma unroll 1
        for (int i = 0; i < PRE_N; i++) {
          bulk_load_hint(sbase + OG_PSLOT + i * (32768 / PRE_N), g_pre + pre_loc(mt * 4 + (nt >> 1)) * 4096 + (nt & 1) * 2048 + i * (2048 / PRE_N), 32768 / PRE_N,
                         bar_full + 272, policy_evict_first());
          if (PRE_N > 1) __nanosleep(PRE_PACE);
        }
      }
      named_bar_sync(14, 32);
      if (has_moe) {
        mbar_wait(bar_full + 96, 1); mbar_wait(bar_full + 304, 0);
        const uint64_t pol = policy_evict_first();
        #pragma unroll 1
        for (int r = 0; r < 32; r++) {
          __nanosleep(WD_PACE);
          #pragma unroll
          for (int j = 0; j < 2; j++)
            asm volatile("cp.async.cg.shared.global.L2::cache_hint [%0], [%1], 16, %2;" :: "r"(sbase + OG_SWD + (4 * j + (lane >> 3)) * 4096 + r * 128 + (((lane ^ r) & 7) << 4)),
                         "l"((const uint8_t*)w_down + (size_t)blockIdx.x * 65536 + r * 2048 + j * 512 + lane * 16), "l"(pol) : "memory");
        }
        asm volatile("cp.async.wait_all;" ::: "memory");
        __syncwarp();
        if (lane == 0) mbar_arrive(bar_wd);
      }
    }
    const uint4 wrv = ldg_nc_v4(w_r + threadIdx.x * 8);
    mbar_wait(bar_end, 0);
    TL_MARK2(22, lane == 0);
    if (wi == 0) {
      uint32_t k1 = 0u, k2 = 0u;
      #pragma unroll 1
      for (unsigned int spin = 0; spin < (1u << 22) && __any_sync(0xffffffffu, k1 == 0u); spin++) asm volatile("ld.relaxed.gpu.global.u32 %0, [%1];" : "=r"(k1) : "l"(g_key + lane) : "memory");
      TL_MARK2(28, lane == 0);
      warp_top2(k1, k2);
      if (lane == 0) {
        const uint32_t r1 = 0xffffu - (k1 & 0xffffu), r2 = 0xffffu - (k2 & 0xffffu);
        sts_u32x4(sbase + OG_SMISC + 64, r1, r2, (r1 >> 7) * 2, (r2 >> 7) * 2 + ((r1 >> 7) == (r2 >> 7)));
        mbar_arrive(bar_sel);
      }
    } else if (wi < 3) {
          mbar_wait(bar_key, 0);
          const uint4 kk = lds_u32x4(sbase + OG_SSTAT + 1024 + lane * 16);
          uint32_t k1 = max(kk.x, kk.y), k2 = min(kk.x, kk.y);
          k2 = max(max(k2, min(kk.z, kk.w)), min(k1, max(kk.z, kk.w))); k1 = max(k1, max(kk.z, kk.w));
          warp_top2(k1, k2);
          if (wi == 1) {
            if (lane == 0 && nt == (mt & 7)) st_relaxed2(g_key + mt * 2, k1, k2);
            TL_MARK2(27, lane == 0);
          } else {
            const uint32_t r = (~((lane & 16) ? k2 : k1)) & 127u, ch = lane & 15;
            const uint2 st = lds_u32x2(sbase + OG_SSTAT + r * 8);
            const uint4 xc = lds_u32x4(sbase + OG_XSLOT + (ch >> 3) * 16384 + r * 128 + (((ch ^ r) & 7) << 4));
            const uint4 c1 = lds_u32x4(sbase + OG_SCOL + 768 + ch * 16), sh = lds_u32x4(sbase + OG_SCOL + 1024 + ch * 16);
            const float inr = __uint_as_float(st.y);
            float* dst = reinterpret_cast<float*>(g_cand + (mt * 2 + (lane >> 4)) * 256 + nt * 16 + ch);
            st_tagged4(dst + 512, __uint_as_float(ln_mod2(xc.x, st.x, inr, c1.x, sh.x)), __uint_as_float(ln_mod2(xc.y, st.x, inr, c1.y, sh.y)),
                       __uint_as_float(ln_mod2(xc.z, st.x, inr, c1.z, sh.z)), __uint_as_float(ln_mod2(xc.w, st.x, inr, c1.w, sh.w)));
            st_tagged4(dst, __uint_as_float(xc.x), __uint_as_float(xc.y), __uint_as_float(xc.z), __uint_as_float(xc.w));
          }
    }
    mbar_wait(bar_sel, 0);
    const uint4 sel = lds_u32x4(sbase + OG_SMISC + 64);
    const int sel0 = (int)sel.x, sel1 = (int)sel.y;
    {
      const float* src0 = reinterpret_cast<const float*>(g_cand + sel.z * 256 + 128 + threadIdx.x);
      const float* src1 = reinterpret_cast<const float*>(g_cand + sel.w * 256 + 128 + threadIdx.x);
      float4 h0, h1;
      #pragma unroll 1
      for (unsigned int spin = 0; spin < (1u << 20); spin++) { h0 = ld_tagged4(src0); h1 = ld_tagged4(src1); if (__all_sync(0xffffffffu, tagged4(h0) & tagged4(h1))) break; }
      sts_f32x4(sbase + OG_SH2 + threadIdx.x * 16, h0.x, h0.y, h0.z, h0.w);
      sts_f32x4(sbase + OG_SH2 + 2048 + threadIdx.x * 16, h1.x, h1.y, h1.z, h1.w);
      __syncwarp();
      if (lane == 0) mbar_arrive(bar_h2);
      TL_MARK2(12, lane == 0);
      if (blockIdx.x >> 6) h0 = h1;
      float v[8], wr[8];
      unpack8(make_uint4(__float_as_uint(h0.x), __float_as_uint(h0.y), __float_as_uint(h0.z), __float_as_uint(h0.w)), v); unpack8(wrv, wr);
      float r = 0.f;
      #pragma unroll
      for (int i = 0; i < 8; i++) r = fmaf(v[i], wr[i], r);
      #pragma unroll
      for (int o = 16; o > 0; o >>= 1) r += __shfl_xor_sync(0xffffffffu, r, o);
      if (lane == 0) sts_f32(sbase + OG_SMISC + 192 + wi * 4, r);
    }
    mbar_wait(bar_out, 0);
    if ((sel0 >> 7) == mt || (sel1 >> 7) == mt) {
      #pragma unroll 2
      for (int i = 0; i < 16; i++) {
        const int r = i * 8 + (threadIdx.x >> 4), ch = threadIdx.x & 15;
        if (m0 + r != sel0 && m0 + r != sel1)
          *reinterpret_cast<uint4*>(out + (size_t)(m0 + r) * T_D + n0 + ch * 8) =
              lds_u32x4(sbase + OG_OSLOT + (ch >> 3) * 16384 + r * 128 + (((ch & 7) ^ (r & 7)) << 4));
      }
    } else if (threadIdx.x == 0) {
      tma_store_2d(tmOut, sbase + OG_OSLOT, n0, m0);
      tma_store_2d(tmOut, sbase + OG_OSLOT + 16384, n0 + 64, m0);
      bulk_commit();
    }
    if (blockIdx.x == 0 && threadIdx.x < 68) *reinterpret_cast<uint4*>(g_hcnt + 32 * (threadIdx.x >> 2) + 4 * (threadIdx.x & 3)) = make_uint4(0u, 0u, 0u, 0u);
    if (threadIdx.x < 64) g_modpart[blockIdx.x * 64 + threadIdx.x] = 0.f;
    if (ALIGN && threadIdx.x == 64) g_tmax[blockIdx.x] = 0u;
    {
      const int tk = blockIdx.x >> 6, c0 = (blockIdx.x & 63) * 16;
      const uint32_t gb2 = *reinterpret_cast<const uint32_t*>(g_col + (c0 >> 7) * 1536 + 512 + 768 + ((c0 & 127) + (threadIdx.x & 14)) * 2);
      const uint32_t* xp = reinterpret_cast<const uint32_t*>(g_cand + (tk ? sel.w : sel.z) * 256) + ((c0 + (threadIdx.x & 14)) >> 1);
      uint32_t x2 = 0u;
      #pragma unroll 1
      for (unsigned int spin = 0; spin < (1u << 20) && __any_sync(0xffffffffu, x2 == 0u); spin++) asm volatile("ld.relaxed.gpu.global.u32 %0, [%1];" : "=r"(x2) : "l"(xp) : "memory");
      const float* src = g_ypart + (size_t)((threadIdx.x >> 2) * 2 + tk) * T_D + c0 + (threadIdx.x & 3) * 4;
      const bool four = threadIdx.x < (OG_MOE - 96) * 4;
      if (threadIdx.x == 0) hint_wait(CNT_Y, (uint32_t)OG_MOE);
      named_bar_sync(10, 128);
      float4 p0, p1, p2, p3;
      #pragma unroll 1
      for (unsigned int spin = 0; spin < (1u << 20); spin++) {
        p0 = ld_tagged4(src); p1 = ld_tagged4(src + 64 * T_D); p2 = ld_tagged4(src + 128 * T_D); p3 = ld_tagged4(four ? src + 192 * T_D : src);
        if (__all_sync(0xffffffffu, tagged4(p0) & tagged4(p1) & tagged4(p2) & tagged4(p3))) break;
      }
      if (four) { p2.x += p3.x; p2.y += p3.y; p2.z += p3.z; p2.w += p3.w; }
      p0.x = (p0.x + p1.x) + p2.x; p0.y = (p0.y + p1.y) + p2.y; p0.z = (p0.z + p1.z) + p2.z; p0.w = (p0.w + p1.w) + p2.w;
      #pragma unroll
      for (int o = 4; o <= 16; o <<= 1) {
        p0.x += __shfl_xor_sync(0xffffffffu, p0.x, o); p0.y += __shfl_xor_sync(0xffffffffu, p0.y, o);
        p0.z += __shfl_xor_sync(0xffffffffu, p0.z, o); p0.w += __shfl_xor_sync(0xffffffffu, p0.w, o);
      }
      if (lane < 4) sts_f32x4(sbase + OG_SFIN + (threadIdx.x >> 5) * 64 + lane * 16, p0.x, p0.y, p0.z, p0.w);
      named_bar_sync(10, 128);
      TL_MARK2(21, threadIdx.x == 0);
      if (threadIdx.x < 16) {
        const uint32_t ya = sbase + OG_SFIN + threadIdx.x * 4, rp = sbase + OG_SMISC + 192;
        float y = (lds_f32(ya) + lds_f32(ya + 64)) + (lds_f32(ya + 128) + lds_f32(ya + 192));
        const float r = rbf((lds_f32(rp) + lds_f32(rp + 4)) + (lds_f32(rp + 8) + lds_f32(rp + 12)));
        const float rs = rbf(sigmoid_f(r));
        const uint32_t h2p = lds_u32(sbase + OG_SH2 + tk * 2048 + (c0 + (threadIdx.x & 14)) * 2);
        const float fh = (lane & 1) ? bfhi(h2p) : bflo(h2p);
        y = rbf(y);
        y = rbf(y * rs);
        const float upd = rbf(rbf(fh * 0.0f) + y);
        out[(size_t)(tk ? sel1 : sel0) * T_D + c0 + threadIdx.x] =
            __float2bfloat16_rn(((lane & 1) ? bfhi(x2) : bflo(x2)) + rbf(((lane & 1) ? bfhi(gb2) : bflo(gb2)) * rbf(fh + upd)));
      }
      if (threadIdx.x == 0) bulk_wait_read<0>();
    }
    TL_END(4, threadIdx.x == 0);
}

__device__ __forceinline__ void load_pre(uint4* pre, uint32_t sbase, uint32_t buf, int t2) {
  mbar_wait(sbase + AT_SBAR + 272, 0);
  #pragma unroll
  for (int i = 0; i < 8; i++) pre[i] = lds_u32x4(sbase + buf + i * 4096 + t2 * 16);
}
__device__ __forceinline__ void tail_consumer(uint32_t sbase, const uint4 (&pre)[8], int cwg, const bf16* __restrict__ w_gate, const bf16* __restrict__ w_up) {
    TAIL_SETUP
    const int tid = threadIdx.x & 127, t2 = threadIdx.x - 128;
    const int warp = tid >> 5, lane = tid & 31, w8 = t2 >> 5;
    const uint32_t dbase = (sbase & 0x3FFFFu) >> 4;
    const uint32_t a_base = dbase + ((cwg * 8192) >> 4) + (1u << 16);
    const uint32_t b_base = dbase + (16384 >> 4) + (512u << 16);
    TL_MARK2(25, threadIdx.x == 128);
    const uint64_t pol = policy_evict_first();
    const bf16* pw = ((lane & 16) ? w_up : w_gate) + (size_t)(w8 * 128 + (lane & 3) * 4) * T_F + (has_moe ? blockIdx.x : 0) * 32 + ((lane >> 2) & 3) * 8;
    uint4 wv[32];
    float acc[64];
    #pragma unroll
    for (int i = 0; i < 8; i++) {
      acc[8 * i] = bflo(pre[i].x); acc[8 * i + 1] = bfhi(pre[i].x); acc[8 * i + 2] = bflo(pre[i].y); acc[8 * i + 3] = bfhi(pre[i].y);
      acc[8 * i + 4] = bflo(pre[i].z); acc[8 * i + 5] = bfhi(pre[i].z); acc[8 * i + 6] = bflo(pre[i].w); acc[8 * i + 7] = bfhi(pre[i].w);
    }
    if (blockIdx.x < AT_NFULL) {
      const uint32_t c0 = clock_lo();
      mbar_wait(bar_full + 320, 0);
      const uint32_t d = lds_u32(sbase + OG_SMISC + 32);
      while (clock_lo() - c0 < d) {}
    }
    {
      uint32_t stage = OG_POS % OG_ST, phase = (OG_POS / OG_ST) & 1, prev = 12;
      int kb = 0;
      #pragma unroll
      for (int g = 0; g <= OG_NG; g++) {
        const int end = g == OG_NG ? OG_NKB : LD_FIRST + g * OG_GRP + LD_STAG * cwg;
        #pragma unroll 1
        do {
          mbar_wait(bar_full + 8 * stage, phase);
          const uint32_t a_lo = a_base + stage * (OG_STAGE >> 4), b_lo = b_base + stage * (OG_STAGE >> 4);
          wgmma_fence();
          wgmma_m64n128k16_ss_tb<0, 0>(acc, a_lo, b_lo, 1);
          wgmma_m64n128k16_ss_tb<2, 128>(acc, a_lo, b_lo, 1);
          wgmma_m64n128k16_ss_tb<4, 256>(acc, a_lo, b_lo, 1);
          wgmma_m64n128k16_ss_tb<6, 384>(acc, a_lo, b_lo, 1);
          wgmma_commit();
          wgmma_wait<1>();
          if (tid == 0) mbar_arrive(bar_empty + 8 * prev);
          prev = stage;
          if (++stage == OG_ST) { stage = 0; phase ^= 1; }
        } while (++kb < end);
        #pragma unroll
        for (int j = 4 * g; j < 4 * g + 4 && j < 32; j++) wv[j] = ldg_stream_v4(pw + (size_t)(16 * (j >> 2) + (j & 3)) * T_F, pol);
      }
    }
    mbar_wait(bar_col, 0);
    if (__builtin_expect(!has_moe, 0)) {
      load_pre(wv, sbase, AT_SQ, t2);
    }
    wgmma_wait<0>();
    fence_regs(acc);
    if (__builtin_expect(!has_moe, 0)) {
      #pragma unroll
      for (int i = 0; i < 8; i++) {
        acc[8 * i] += bflo(wv[i].x); acc[8 * i + 1] += bfhi(wv[i].x); acc[8 * i + 2] += bflo(wv[i].y); acc[8 * i + 3] += bfhi(wv[i].y);
        acc[8 * i + 4] += bflo(wv[i].z); acc[8 * i + 5] += bfhi(wv[i].z); acc[8 * i + 6] += bflo(wv[i].w); acc[8 * i + 7] += bfhi(wv[i].w);
      }
    }
    if (tid == 0) mbar_arrive(bar_end);
    TL_MARK2(9, lane == 0);
    const int q2 = 2 * (lane & 3);
    const uint32_t frag = (64 * cwg + 16 * warp + (lane & 7) + 8 * ((lane >> 3) & 1)) * 128;
    const int fsw = lane & 7, fhi = lane >> 4;
    {
      float dl[4] = {0.f, 0.f, 0.f, 0.f}, da[4] = {0.f, 0.f, 0.f, 0.f}, db[4] = {0.f, 0.f, 0.f, 0.f};
      const uint32_t tb = sbase + OG_SCOL + (lane & 8) * 32 + (lane & 3) * 8, g = lane >> 2;
      const uint32_t msk = (g == 1 || g == 2) ? 0xffffffffu : 0u, one = g == 0 ? 0x3F803F80u : 0u;
      #pragma unroll
      for (int J = 0; J < 16; J += 2) {
        const uint32_t ad = sbase + OG_XSLOT + (J >> 3) * 16384 + frag + ((((J & 7) + fhi) ^ fsw) << 4);
        uint32_t xr[4];
        ldmatrix_x4(ad, xr[0], xr[1], xr[2], xr[3]);
        const uint2 cw = lds_u32x2(tb + J * 16);
        #pragma unroll
        for (int h = 0; h < 2; h++) {
          const uint32_t ga = lds_u32(sbase + OG_SCOL + 512 + (8 * (J + h) + q2) * 2);
          xr[2 * h] = badd2(xr[2 * h], bmul2(ga, pack_bf16(acc[4 * (J + h)], acc[4 * (J + h) + 1])));
          xr[2 * h + 1] = badd2(xr[2 * h + 1], bmul2(ga, pack_bf16(acc[4 * (J + h) + 2], acc[4 * (J + h) + 3])));
        }
        stmatrix_x4(ad, xr[0], xr[1], xr[2], xr[3]);
        mma_bf16(dl, xr[0], xr[1], xr[2], xr[3], (cw.x & msk) | one, (cw.y & msk) | one);
        mma_bf16(da, xr[0], xr[1], xr[2], xr[3], xr[0], xr[2]);
        mma_bf16(db, xr[0], xr[1], xr[2], xr[3], xr[1], xr[3]);
      }
      {
        const int dsrc = (lane & ~3) + (g >> 1);
        const float qa = __shfl_sync(0xffffffffu, (g & 1) ? da[1] : da[0], dsrc), qb = __shfl_sync(0xffffffffu, (g & 1) ? db[3] : db[2], dsrc);
        const float e0 = __shfl_xor_sync(0xffffffffu, (lane & 1) ? dl[0] : dl[2], 1), e1 = __shfl_xor_sync(0xffffffffu, dl[3], 1);
        if ((lane & 3) < 2) {
          const bool hi = lane & 1;
          st_tagged4(reinterpret_cast<float*>(g_part1 + ((mt * 8 + w8) * 8 + nt) * 16 + g + (hi ? 8 : 0)),
                     hi ? e0 : dl[0], hi ? qb : qa, hi ? e1 + dl[2] : dl[1] + e0, 1.0f);
        }
      }
    }
    TL_MARK2(10, lane == 0);
    uint4 wd[16];
    if (has_moe) mbar_wait(bar_wd, 0);
    #pragma unroll
    for (int i = 0; i < 16; i++) wd[i] = lds_u32x4(sbase + (cwg ? OG_SWD1 : OG_SWD) + warp * 8192 + (i >> 3) * 4096 + (i & 6) * 512 + (i & 1) * 128 + (lane & 3) * 256 + (((lane >> 2) ^ (2 * (lane & 3) + (i & 1))) << 4));
    {
      const float* src = reinterpret_cast<const float*>(g_part1 + ((mt * 8 + w8) * 8 + (lane & 1) * 4) * 16 + (lane >> 1));
      float4 v, v1, v2, v3;
      #pragma unroll 1
      for (unsigned int spin = 0; spin < (1u << 22); spin++) {
        v = ld_tagged4(src); v1 = ld_tagged4(src + 64); v2 = ld_tagged4(src + 128); v3 = ld_tagged4(src + 192);
        if (__all_sync(0xffffffffu, tagged4(v) & tagged4(v1) & tagged4(v2) & tagged4(v3))) break;
        __nanosleep(100);
      }
      __syncwarp();
      TL_MARK2(26, lane == 0);
      v.x = (v.x + v1.x) + (v2.x + v3.x); v.y = (v.y + v1.y) + (v2.y + v3.y); v.z = (v.z + v1.z) + (v2.z + v3.z);
      v.x += __shfl_xor_sync(0xffffffffu, v.x, 1); v.y += __shfl_xor_sync(0xffffffffu, v.y, 1); v.z += __shfl_xor_sync(0xffffffffu, v.z, 1);
      const float mean = v.x * (1.0f / T_D);
      const float var = fmaxf(fmaf(-mean, mean, v.y * (1.0f / T_D)), 0.f);
      const uint32_t mb2 = pack_bf16(mean, mean);
      const float inv = rcp_approx(rbf(sqrt_approx(rbf(rbf(var) + 1e-05f))));
      {
        const float2 sc = lds_f32x2(sbase + OG_SMISC);
        const uint32_t key = rank_key(rbf(fmaf(fmaf(-bflo(mb2), sc.x, v.z), inv, sc.y)), m0 + 16 * w8 + (lane >> 1));
        mbar_wait(bar_end, 0);
        if (lane & 1) sts_u32(sbase + OG_SSTAT + 1024 + (16 * w8 + (lane >> 1)) * 4, key);
        else sts_u32x2(sbase + OG_SSTAT + (16 * w8 + (lane >> 1)) * 8, mb2, __float_as_uint(inv));
        __syncwarp();
        if (lane == 0) mbar_arrive(bar_key);
      }
      const uint32_t ih = pack_bf16(inv, inv), il = pack_bf16(inv - bflo(ih), inv - bflo(ih));
      const uint32_t mba = __shfl_sync(0xffffffffu, mb2, 2 * (lane >> 2)), mbb = __shfl_sync(0xffffffffu, mb2, 2 * (lane >> 2) + 16);
      const uint32_t iha = __shfl_sync(0xffffffffu, ih, 2 * (lane >> 2)), ihb = __shfl_sync(0xffffffffu, ih, 2 * (lane >> 2) + 16);
      const uint32_t ila = __shfl_sync(0xffffffffu, il, 2 * (lane >> 2)), ilb = __shfl_sync(0xffffffffu, il, 2 * (lane >> 2) + 16);
      #pragma unroll 2
      for (int J = 0; J < 16; J += 2) {
        const uint32_t off = (J >> 3) * 16384 + frag + ((((J & 7) + fhi) ^ fsw) << 4);
        uint32_t xr[4];
        ldmatrix_x4(sbase + OG_XSLOT + off, xr[0], xr[1], xr[2], xr[3]);
        #pragma unroll
        for (int h = 0; h < 2; h++) {
          const uint32_t ca = sbase + OG_SCOL + 512 + (8 * (J + h) + q2) * 2;
          const uint32_t c1 = lds_u32(ca + 256), sh = lds_u32(ca + 512), gb = lds_u32(ca + 768);
          xr[2 * h] = out2(xr[2 * h], mba, iha, ila, c1, sh, gb);
          xr[2 * h + 1] = out2(xr[2 * h + 1], mbb, ihb, ilb, c1, sh, gb);
        }
        stmatrix_x4(sbase + OG_OSLOT + off, xr[0], xr[1], xr[2], xr[3]);
      }
      fence_proxy_async();
      __syncwarp();
      if (lane == 0) mbar_arrive(bar_out);
      TL_MARK2(24, lane == 0);
    }
    if (has_moe) mbar_wait(bar_h2, 0);
    TL_MARK2(13, lane == 0);
    if (has_moe) {
      const GemvSel sel = gemv_sel(lane);
      {
        float d[4][4];
        #pragma unroll
        for (int c = 0; c < 4; c++) { d[c][0] = 0.f; d[c][1] = 0.f; d[c][2] = 0.f; d[c][3] = 0.f; }
        #pragma unroll
        for (int st = 0; st < 8; st++) {
          const uint2 hb = lds_u32x2(sbase + OG_SH2 + ((lane >> 2) & 1) * 2048 + (w8 * 128 + st * 16 + (lane & 3) * 4) * 2);
          #pragma unroll
          for (int j = 0; j < 4; j++) mma_bf16(d[j], wv[4 * st + j].x, wv[4 * st + j].y, wv[4 * st + j].z, wv[4 * st + j].w, GEMV_B0(j, hb, sel), GEMV_B1(j, hb, sel));
        }
        #pragma unroll
        for (int e = 0; e < 4; e++) d[0][e] = (d[0][e] + d[1][e]) + (d[2][e] + d[3][e]);
        const float4 r = gemv_out(d[0], lane);
        sts_f32x4(sbase + OG_SRED + w8 * 512 + (((lane >> 4) * 2 + (lane & 1)) * 32 + ((lane >> 2) & 3) * 8 + (lane & 2) * 2) * 4, r.x, r.y, r.z, r.w);
      }
      named_bar_sync(9, 256);
      if (t2 < 64) {
        float gp[8], up[8];
        #pragma unroll
        for (int w = 0; w < 8; w++) { gp[w] = lds_f32(sbase + OG_SRED + w * 512 + t2 * 4); up[w] = lds_f32(sbase + OG_SRED + w * 512 + 256 + t2 * 4); }
        const float gs = ((gp[0] + gp[1]) + (gp[2] + gp[3])) + ((gp[4] + gp[5]) + (gp[6] + gp[7]));
        const float us = ((up[0] + up[1]) + (up[2] + up[3])) + ((up[4] + up[5]) + (up[6] + up[7]));
        asm volatile("st.shared.u16 [%0], %1;" :: "r"(sbase + OG_SGU + ((t2 & ~15) + ((t2 >> 1) & 3) * 4 + ((t2 >> 3) & 1) * 2 + (t2 & 1)) * 2), "h"((uint16_t)pack_bf16(silu_bf(rbf(gs)) * rbf(us), 0.f)) : "memory");
      }
      named_bar_sync(9, 256);
      TL_MARK2(20, threadIdx.x == 128);
      float d[4][4];
      #pragma unroll
      for (int c = 0; c < 4; c++) { d[c][0] = 0.f; d[c][1] = 0.f; d[c][2] = 0.f; d[c][3] = 0.f; }
      #pragma unroll
      for (int st = 0; st < 2; st++) {
        const uint2 g = lds_u32x2(sbase + OG_SGU + ((lane >> 2) & 1) * 64 + st * 32 + (lane & 3) * 8);
        #pragma unroll
        for (int j = 0; j < 4; j++) {
          const uint32_t b0 = GEMV_B0(j, g, sel), b1 = GEMV_B1(j, g, sel);
          mma_bf16(d[j & 1], wd[4 * st + j].x, wd[4 * st + j].y, wd[4 * st + j].z, wd[4 * st + j].w, b0, b1);
          mma_bf16(d[2 + (j & 1)], wd[8 + 4 * st + j].x, wd[8 + 4 * st + j].y, wd[8 + 4 * st + j].z, wd[8 + 4 * st + j].w, b0, b1);
        }
      }
      #pragma unroll
      for (int e = 0; e < 4; e++) { d[0][e] += d[1][e]; d[2][e] += d[3][e]; }
      const float4 y0 = gemv_out(d[0], lane), y1 = gemv_out(d[2], lane);
      float* yp = g_ypart + (size_t)(blockIdx.x * 2 + (lane & 1)) * T_D + w8 * 128 + (lane >> 2) * 8 + (lane & 2) * 2;
      st_tagged4(yp, y0.x, y0.y, y0.z, y0.w);
      st_tagged4(yp + 64, y1.x, y1.y, y1.z, y1.w);
      named_bar_sync(9, 256);
      if (t2 == 0) hint_arrive(CNT_Y);
    }
    TL_MARK2(14, threadIdx.x == 128);
    TL_CLK(4, 1, threadIdx.x == 128);
}

#define OG_JOBS2 (16 - OG_JOBS)
__device__ __forceinline__ int help_njobs() { return blockIdx.x < 128 ? OG_JOBS : OG_JOBS2; }
__device__ __forceinline__ int help_job(int i) {
  const int step = i + (blockIdx.x < 128 ? 0 : OG_JOBS);
  return (step & ~3) * 4 + (blockIdx.x & 3) * 4 + (step & 3);
}
__device__ __noinline__ void store_warp(uint32_t sbase, const CUtensorMap* tmO, int item0, int n_items) {
  if (elect_one()) {
    const uint32_t bars = sbase + AT_SBAR, b_q0 = bars + 80, b_ob = bars + 96, b_ordy = bars + 104, b_acq = bars + 264;
    const unsigned int* cnt = &g_hcnt[32 * (1 + OG_MT(blockIdx.x)) + 2];
    #pragma unroll 1
    for (int q = 0; q < 4 * n_items; q++) {
      const int item = item0 + (q >> 2) * 128, h = (q >> 1) & 1, w = q & 1;
      const bool last = (q >> 2) == n_items - 1;
      if (q == 4 * n_items - 4) { mbar_wait(bars + 288, 0); red_release_add(&g_hcnt[1], 1u); }
      mbar_wait(b_ordy + 8 * (q & 3), q >> 2);
      store_o(tmO, (h ? (last ? sbase + AT_SQ + 32768 : sbase + 2 * 32768) : sbase + AT_SQ) + w * 8192, (item >> 4) * 2 + h, (item & 15) * 128 + w * 64);
      if (w) {
        bulk_wait_read<0>();
        mbar_arrive(h ? b_ob : b_q0);
        bulk_wait<0>();
        fence_proxy_async_global();
        red_release_add(&g_hcnt[32 * (1 + (item & 15)) + 2 + (item >> 7)], h ? 1u : 256u);
        if (blockIdx.x < 128 && q == (n_items == 2 ? 5 : 3)) { spin_until(cnt, 0x808u); mbar_arrive(b_acq); }
      }
    }
    if (n_items == 1) {
      #pragma unroll 1
      for (int i = 0; i < help_njobs(); i++) {
        mbar_wait(b_acq + 16, i & 1);
        TL_MARK2(23, i == OG_JOBS - 1);
        red_release_add(&g_hcnt[32 * (1 + (help_job(i) >> 2)) + 4 + (help_job(i) & 3)], 1u);
        TL_MARK2(4, i == OG_JOBS - 1);
        if (i == PRE_X - 1) { spin_until(&g_hcnt[1], 132u); mbar_arrive(b_acq + 32); }
      }
    }
    if (blockIdx.x < 128) { spin_until(&g_hcnt[0], 128u); spin_until(cnt + 1, 0x808u); mbar_arrive(b_acq); }
  }
}

__global__ void __launch_bounds__(384, 1)
fused_kernel(const __grid_constant__ CUtensorMap tmH, const __grid_constant__ CUtensorMap tmW, const __grid_constant__ CUtensorMap tmK,
            const __grid_constant__ CUtensorMap tmV, const __grid_constant__ CUtensorMap tmO, const __grid_constant__ CUtensorMap tmOl, const __grid_constant__ CUtensorMap tmWo,
            const __grid_constant__ CUtensorMap tmX, const __grid_constant__ CUtensorMap tmOut, const __grid_constant__ CUtensorMap tmM, uint32_t zero,
            const uint8_t* __restrict__ pf_wo, const bf16* __restrict__ kc, const bf16* __restrict__ vc,
            const bf16* __restrict__ x, const bf16* __restrict__ cvec, const bf16* __restrict__ w_mod, const bf16* __restrict__ w_r,
            const bf16* __restrict__ w_gate, const bf16* __restrict__ w_up, const bf16* __restrict__ w_down, bf16* __restrict__ out)
{
  extern __shared__ __align__(1024) uint8_t smem_raw[];
  const uint32_t sbase = smem_u32(smem_raw);
  const uint32_t bars = sbase + AT_SBAR;
  const uint32_t b_full = bars, b_empty = bars + 40;
  const uint32_t b_q0 = bars + 80, b_q1 = bars + 88;
  const uint32_t b_ob = bars + 96;
  const uint32_t b_ordy = bars + 104;
  const uint32_t b_pin = bars + 136;
  const uint32_t b_head = bars + 144;
  const uint32_t b_go = bars + 152;
  const uint32_t b_x = bars + 160;
  const int wg = __shfl_sync(0xffffffffu, threadIdx.x >> 7, 0);
  const bool single = blockIdx.x >= AT_NFULL;
  const int item0 = __shfl_sync(0xffffffffu, blockIdx.x < 128 ? (int)blockIdx.x : (int)blockIdx.x + 124, 0), n_items = __shfl_sync(0xffffffffu, single ? 1 : 2, 0);
  TL_START(3);
  if (threadIdx.x == 0) {
    if (sbase & 1023u) __trap();
    for (int i = 0; i < 5; i++) { mbar_init(b_full + 8 * i, 1); mbar_init(b_empty + 8 * i, 2); }
    mbar_init(b_q0, 1); mbar_init(b_q1, 8); mbar_init(b_ob, 1);
    for (int i = 0; i < 4; i++) mbar_init(b_ordy + 8 * i, 4);
    mbar_init(b_pin, 1); mbar_init(b_head, blockIdx.x < 128 ? 8 : 1); mbar_init(b_go, 1); mbar_init(b_x, 1);
    mbar_init(bars + 168, 2); mbar_init(bars + 176, 1); mbar_init(bars + 184, 8); mbar_init(bars + 192, 2);
    mbar_init(bars + 200, 8); mbar_init(bars + 208, 4); mbar_init(bars + 216, 1); mbar_init(bars + 264, 1); mbar_init(bars + 272, 1); mbar_init(bars + 280, 8); mbar_init(bars + 288, 1); mbar_init(bars + 296, 1); mbar_init(bars + 304, 8); mbar_init(bars + 312, 1); mbar_init(bars + 320, 1); mbar_init(bars + 328, 1);
    fence_mbar_init();
  }

  if (wg == 0) {
    reg_dealloc<AT_PREG>();
    if (threadIdx.x < 32) { __syncwarp(); named_bar_arrive(6, 384); }
    if (threadIdx.x >= 64) {
      named_bar_sync(6, 384);
      if (blockIdx.x < 128) {
        named_bar_sync(threadIdx.x >= 96 ? 8 : 9, 288);
        if ((threadIdx.x & 31) == 0) red_release_add(&g_hcnt[32 * (1 + (blockIdx.x >> 3)) + (threadIdx.x >= 96)], 1u);
        TL_MARK2(11, threadIdx.x == 64);
      }
      if (blockIdx.x < 128) {
        mbar_wait(MOD_AT, 0);
        mod_rest(sbase + OG_SCOL, b_q1, threadIdx.x - 64, cvec, w_mod, w_r);
      }
    } else if (threadIdx.x >= 32) {
      named_bar_sync(6, 384);
      store_warp(sbase, &tmO, item0, n_items);
      __syncwarp();
    } else {
     if (elect_one()) {
      const uint64_t pol = policy_evict_first();
      if (blockIdx.x < 128) {
        mbar_expect_tx(b_x, 32768);
        if (X_DLY) { const uint32_t c0 = clock_lo(); while (clock_lo() - c0 < X_DLY) {} }
        bulk_load_hint(sbase + 4 * 32768, x + (size_t)blockIdx.x * 16 * T_D, 32768, b_x, pol);
      }
      prefetch_tmap(&tmW); prefetch_tmap(&tmM); prefetch_tmap(&tmH); prefetch_tmap(&tmWo); prefetch_tmap(&tmOl);
      uint32_t slot = 0, ph = 1;
      if (ALIGN) { uint32_t sm; asm volatile("mov.u32 %0, %%smid;" : "=r"(sm)); g_smid[32 + blockIdx.x] = sm; }
      #pragma unroll 1
      for (int it = 0; it < n_items; it++) {
        const int item = item0 + it * 128, hp = item >> 4, qt = item & 15;
        const bool first = it == 0;
        #pragma unroll 1
        for (int j = 0; j < T_D / 64; j++) {
          const uint32_t sl = ring_slot(qp_pos(j, it)), fb = b_full + 8 * sl;
          mbar_wait(b_empty + 8 * sl, ring_par(qp_pos(j, it)) ^ ((j >> 2) & 1) ^ 1);
          if (first && j == 3) mbar_wait(b_head, 0);
          mbar_expect_tx(fb, 49152);
          tma_load_3d_hint(sbase + sl * 32768, &tmW, j * 64, hp * 4, fb, pol);
          if (first && j < PRE_B) {
            if (j == PRE_B - 1) {
              if (blockIdx.x < 128 && (blockIdx.x & 15) >= 4 * H_SPLIT) {
                const uint32_t c0 = clock_lo();
                mbar_expect_tx(bars + 328, 32768);
                while (clock_lo() - c0 < W_DLY) {}
                tma_load_2d_hint(sbase + 3 * 32768, &tmM, (blockIdx.x & 31) * 64, (blockIdx.x >> 5) * 256, bars + 328, pol);
              }
              spin_until(&g_hcnt[32 * (1 + qt)], 8u);
              TL_MARK2(16, true);
              fence_proxy_async_global();
              #pragma unroll 1
              for (int i = 0; i < PRE_B; i++) tma_load_2d(sbase + AT_SQ + i * 16384, &tmH, i * 64, qt * 128, b_full + 8 * i);
              mbar_arrive(b_go);
            }
          } else {
            if (first && j == 4 * H_SPLIT) { spin_until(&g_hcnt[32 * (1 + qt) + 1], 8u); fence_proxy_async_global(); }
            if (!first && (j == 0 || j == 2)) mbar_wait(j ? b_q1 : b_q0, 0);
            tma_load_2d_hint(sbase + AT_SQ + (j & 3) * 16384, &tmH, j * 64, qt * 128, fb, first ? pol_normal() : pol);
          }
        }
        #pragma unroll 1
        for (int j = 0; j < 4 * AT_NBLK; j++) {
          const bool isv = (j > 0 && !(j & 1)) || j == 4 * AT_NBLK - 1;
          const int row = hp * 2 * T_SEQ + (isv ? (j - 1) >> 1 : (j + 1) >> 1) * 128;
          const uint32_t fb = b_full + 8 * slot;
          mbar_wait(b_empty + 8 * slot, ph);
          if (!first && j == 3) mbar_wait(b_ob, 0);
          if (j == 4 && it == n_items - 1) mbar_arrive(bars + 288);
          if (ALIGN && j == AL_P && it == 1) mbar_arrive(bars + 312);
          mbar_expect_tx(fb, 32768);
          tma_load_3d_hint(sbase + slot * 32768, isv ? &tmV : &tmK, row, 0, fb, pol);
          if (it == 1 && isv && j >= 2 * WO_LATE && j < 2 * WO_LATE + 32 && blockIdx.x < OG_NKB)
            l2_prefetch_bulk(pf_wo + (size_t)own_kb(blockIdx.x) * 131072 + ((j >> 1) - WO_LATE) * 8192, 8192);
          if (++slot == 5) { slot = 0; ph ^= 1; }
        }
      }
      if (__builtin_expect(single, 0)) {
        #pragma unroll 1
        for (int i = 0; i < 4; i++) spin_until(&g_hcnt[32 * (1 + 4 * i + (blockIdx.x & 3)) + 2], 0x800u);
        fence_proxy_async_global();
        const int nj = help_njobs() * OG_PRE;
        int ji = 0, job = help_job(0), kk = 0;
        #pragma unroll 1
        for (int j = 0; j < nj; j++) {
          const uint32_t sl = ring_slot(qp_pos(j, 1)), fb = b_full + 8 * sl;
          mbar_wait(b_empty + 8 * sl, ring_par(qp_pos(j, 1)) ^ ((j >> 2) & 1) ^ 1);
          mbar_expect_tx(fb, 49152);
          tma_load_3d_hint(sbase + sl * 32768, &tmWo, pre_kb(kk) * 64, (job & 3) * 4, fb, HPOL_B);
          tma_load_3d_hint(sbase + sl * 32768 + 16384, &tmWo, pre_kb(kk) * 64, (job & 3) * 4 + 2, fb, HPOL_B);
          if (j == 0 || j == 2) mbar_wait(j ? b_ob : b_q0, 0);
          tma_load_2d_hint(sbase + AT_SQ + (j & 3) * 16384, HMAP_A, pre_kb(kk) * 64, (job >> 2) * 128, fb, HPOL_A);
          if (++kk == OG_PRE) { kk = 0; job = help_job(++ji); }
        }
      }
      if (blockIdx.x < 128) {
        if (single) mbar_wait(b_x, 1);
        tail_producer(sbase, 0, pol, &tmOl, &tmWo, &tmX);
      }
     }
    }
    named_bar_sync(12 + (threadIdx.x >> 5), 32);
    if (blockIdx.x < 128) tail_exchange(sbase, &tmOut, w_down, w_r, x, out);
  } else {
    if (blockIdx.x < 128) head_phase(sbase + AT_SQ + 49152, sbase + 4 * 32768, b_x, b_go, b_head, threadIdx.x - 128, zero, cvec, w_mod);
    else { named_bar_sync(6, 384); if (threadIdx.x == 128) mbar_arrive(b_head); }
    TL_MARK2(0, threadIdx.x == 128);
    reg_alloc<AT_CREG>();
    const int cwg = wg - 1;
    const int tid = threadIdx.x & 127;
    const int warp = tid >> 5, lane = tid & 31;
    const uint32_t dbase = (sbase & 0x3FFFFu) >> 4;
    const uint32_t k_base = dbase + (1u << 16);
    const uint32_t v_base = dbase + (1024u << 16);
    const uint32_t w_base = dbase + (512u << 16);
    const uint32_t q_lo = dbase + ((AT_SQ + cwg * 8192) >> 4) + (1u << 16);
    const uint32_t frag = cwg * 8192 + (16 * warp + (lane & 7) + 8 * ((lane >> 3) & 1)) * 128;
    if (cwg == 1) named_bar_arrive(1, 256);
    bool raw = false;
    uint4 pre[8];
    #pragma unroll 1
    for (int it = 0; it < n_items; it++) {
      const bool more = it + 1 < n_items;
      constexpr int nkb = T_D / 64;
      const int ta = __shfl_sync(0xffffffffu, 4 * it, 0);
      float acc[128];
      {
        FS(2 * it, 0);
        #pragma unroll
        for (int i = 0; i < 128; i++) asm volatile("" : "=f"(acc[i]));
        {
          const uint32_t slot = ring_slot(ta), b_lo = w_base + slot * 2048;
          mbar_wait(b_full + 8 * slot, ring_par(ta));
          wgmma_fence();
          wgmma_m64n256k16_ss_tb<0, 0>(acc, q_lo, b_lo, 0);
          wgmma_m64n256k16_ss_tb<2, 128>(acc, q_lo, b_lo, 1);
          wgmma_m64n256k16_ss_tb<4, 256>(acc, q_lo, b_lo, 1);
          wgmma_m64n256k16_ss_tb<6, 384>(acc, q_lo, b_lo, 1);
          wgmma_commit();
        }
        #pragma unroll 1
        for (int j = NOZERO; j < nkb; j++) {
          const uint32_t slot = ring_slot(qp_pos(j, ta >> 2));
          mbar_wait(b_full + 8 * slot, ring_par(qp_pos(j, ta >> 2)) ^ ((j >> 2) & 1));
          if (QP_STAG > 0 && cwg == 1 && j == nkb - QP_STAG) named_bar_sync(7, 256);
          const uint32_t a_lo = q_lo + (j & 3) * 1024, b_lo = w_base + slot * 2048;
          wgmma_fence();
          wgmma_m64n256k16_ss_tb<0, 0>(acc, a_lo, b_lo, 1);
          wgmma_m64n256k16_ss_tb<2, 128>(acc, a_lo, b_lo, 1);
          wgmma_m64n256k16_ss_tb<4, 256>(acc, a_lo, b_lo, 1);
          wgmma_m64n256k16_ss_tb<6, 384>(acc, a_lo, b_lo, 1);
          wgmma_commit();
          if (QP_STAG > 0 && cwg == 0 && j == nkb - 1) named_bar_arrive(7, 256);
          if (j > 0) {
            wgmma_wait<1>();
            if (tid == 0) mbar_arrive(b_empty + 8 * ring_slot(qp_pos(j - 1, ta >> 2)));
          }
        }
        wgmma_wait<0>();
        fence_regs(acc);
        FS(2 * it, 1);
        TL_MARK2(29, threadIdx.x == 256 && it == 0);
        if (tid == 0) mbar_arrive(b_empty + 24);
      }
      float o[64], s[64];
      uint32_t p[32], q[32];
      #pragma unroll
      for (int i = 0; i < 32; i++) q[i] = pack_bf16(acc[2 * i] * AT_C, acc[2 * i + 1] * AT_C);
      zero_regs(s);
      const uint32_t sq = sbase + AT_SQ + cwg * 8192;
      const bool last_wg1 = cwg == 1 && !more;
      float mc0, mc1, al0 = 1.0f, al1 = 1.0f, l0 = 0.f, l1 = 0.f, lp0 = 0.f, lp1 = 0.f;
      bool redo0 = false;
      FS(2 * it, 2);
      mbar_wait(b_full + 8 * ring_slot(ta), ring_par(ta));
      named_bar_sync(1 + cwg, 256);
      FS(2 * it, 3);
      issue_qk(s, q, k_base + ring_slot(ta) * 2048);
      named_bar_arrive(1 + (cwg ^ 1), 256);
      bool ready = mbar_test(b_full + 8 * ring_slot(ta + 1), ring_par(ta + 1)) & mbar_test(b_full + 8 * ring_slot(ta + 2), ring_par(ta + 2));
      stage_q<16>(acc, AT_C, sbase + AT_SQ + frag, lane);
      wgmma_wait<0>();
      fence_regs(s);
      if (tid == 0) mbar_arrive(b_empty + 8 * ring_slot(ta));
      mc0 = 0.f; mc1 = 0.f;
      if (!raw) {
        raw = softmax_mode(s, mc0, mc1);
        if (__builtin_expect(!raw, 0)) softmax_sub(s, mc0, mc1);
      }
      softmax_exp<0, 64>(s);
      #pragma unroll
      for (int J = 0; J < 16; J += 2)
        stmatrix_x4(sbase + AT_SQ + frag + (J >> 3) * 16384 + ((((J & 7) + (lane >> 4)) ^ (lane & 7)) << 4), q[2 * J], q[2 * J + 1], q[2 * J + 2], q[2 * J + 3]);
      pack_p(p, s);
      zero_regs(o);
      FS(2 * it, 4);
      uint32_t ks = ring_slot(ta + 1), vs = ring_slot(ta + 2), kp = ring_par(ta + 1), vp = ring_par(ta + 2);
      auto finish_head = [&]() {
        FS(2 * it, 5);
        redo0 = finish_l(lp0, lp1);
        if (!redo0) {
          stage_o(o, lp0, lp1, sbase + AT_SQ + frag, lane);
          fence_proxy_async();
          __syncwarp();
          if (lane == 0) mbar_arrive(b_ordy + 8 * cwg);
        }
        FS(2 * it + 1, 4);
      };
      if (!ready) { mbar_wait(b_full + 8 * ks, kp); mbar_wait(b_full + 8 * vs, vp); }
      #pragma unroll 1
      for (int n = 1; n < 2 * AT_NBLK; n++) {
        named_bar_sync(1 + cwg, 256);
        issue_qk(s, q, k_base + ks * 2048);
        if (n == AT_NBLK + 1) finish_head();
        issue_pv(o, p, v_base + vs * 2048, (n & 15) != 1);
        if (!(last_wg1 && n == 2 * AT_NBLK - 1)) named_bar_arrive(1 + (cwg ^ 1), 256);
        wgmma_wait<1>();
        fence_regs(s);
        if (tid == 0) mbar_arrive(b_empty + 8 * ks);
        if (__builtin_expect(!raw || (n + 1) >> 1 == AT_NBLK / 2, 0)) {
          if (n == AT_NBLK - 1) {
            #pragma unroll
            for (int J = 0; J < 16; J += 2)
              ldmatrix_x4(sbase + AT_SQ + 32768 + frag + (J >> 3) * 16384 + ((((J & 7) + (lane >> 4)) ^ (lane & 7)) << 4), q[2 * J], q[2 * J + 1], q[2 * J + 2], q[2 * J + 3]);
          }
          if (!raw) {
            const float m0 = mc0, m1 = mc1;
            const bool ok = softmax_mode(s, mc0, mc1);
            if (n == AT_NBLK) raw = ok;
            else {
              mc0 = mc0 - AT_HEAD > m0 ? mc0 : m0; mc1 = mc1 - AT_HEAD > m1 ? mc1 : m1;
              al0 = ex2_approx(m0 - mc0); al1 = ex2_approx(m1 - mc1);
            }
            if (!raw) softmax_sub(s, mc0, mc1);
          }
        }
        softmax_exp<0, AT_SPLIT>(s);
        add_rowsum(p, l0, l1);
        if (tid == 0) {
          uint32_t dep = zero & __float_as_uint(l0) & __float_as_uint(l1);
          #pragma unroll
          for (int i = AT_SPLIT - AT_PIN - PINB; i < AT_SPLIT - PINB; i += 2) dep &= __float_as_uint(s[i]) & __float_as_uint(s[i + 1]);
          mbar_arrive(b_pin + dep);
        }
        wgmma_wait<0>();
        fence_regs(o);
        if (tid == 0) mbar_arrive(b_empty + 8 * vs);
        ks += 2; if (ks >= 5) { ks -= 5; kp ^= 1; }
        vs += 2; if (vs >= 5) { vs -= 5; vp ^= 1; }
        ready = mbar_test(b_full + 8 * ks, kp) & mbar_test(b_full + 8 * vs, vp);
        softmax_exp<AT_SPLIT, 64>(s);
        pack_p(p, s);
        if (n == AT_NBLK) { lp0 = l0; lp1 = l1; l0 = 0.f; l1 = 0.f; }
        if (__builtin_expect(!raw || !ready, 0)) {
        if (!raw && __any_sync(0xffffffffu, al0 != 1.0f || al1 != 1.0f)) {
          rescale_o(o, al0, al1);
          l0 *= al0; l1 *= al1;
          al0 = 1.0f; al1 = 1.0f;
        }
        if (!ready && n < 2 * AT_NBLK - 1) {
          mbar_wait(b_full + 8 * ks, kp);
          mbar_wait(b_full + 8 * vs, vp);
        }
        }
      }
      FS(2 * it + 1, 5);
      const uint32_t vl = ring_slot(ta + 63);
      vs = ring_slot(ta + 62);
      const uint32_t ob = more ? sbase + vs * 32768 : sbase + AT_SQ + 32768;
      if (redo0) {
        attn_rows_exact(sq, sq, 4 * ta, kc, vc);
        fence_proxy_async();
        __syncwarp();
        if (lane == 0) mbar_arrive(b_ordy + 8 * cwg);
      }
      mbar_wait(b_full + 8 * vl, ring_par(ta + 63));
      issue_pv(o, p, v_base + vl * 2048, 1);
      add_rowsum(p, l0, l1);
      const bool overflow = finish_l(l0, l1);
      if (!overflow && lane == 0) mbar_arrive(b_q1);
      #pragma unroll
      for (int i = 0; i < 8; i++) asm volatile("mov.b64 {%0, %1}, 0;\nmov.b64 {%2, %3}, 0;" : "=r"(pre[i].x), "=r"(pre[i].y), "=r"(pre[i].z), "=r"(pre[i].w));
      if (HOIST && !more && blockIdx.x < OG_MOE) {
        load_pre(pre, sbase, AT_SQ, threadIdx.x - 128);
        __syncwarp();
        if (lane == 0) mbar_arrive(bars + 304);
      }
      mbar_wait(b_empty + 8 * vs, ring_par(ta + 62));
      wgmma_wait<0>();
      fence_regs(o);
      if (tid == 0) mbar_arrive(b_empty + 8 * vl);
      FS(2 * it + 1, 6);
      if (overflow) {
        attn_rows_exact(sq + 32768, ob + cwg * 8192, 4 * ta + 1, kc, vc);
        __syncwarp();
        if (lane == 0) mbar_arrive(b_q1);
      } else stage_o(o, l0, l1, ob + frag, lane);
      fence_proxy_async();
      __syncwarp();
      if (lane == 0) mbar_arrive(b_ordy + 16 + 8 * cwg);
      if (redo0 || overflow) raw = false;
      named_bar_sync(3 + cwg, 128);
      FS(2 * it + 1, 7);
    }
    if (__builtin_expect(single, 0)) {
      float acc[128];
      uint32_t j = 0, pk[64];
      #pragma unroll
      for (int i = 0; i < 64; i++) asm volatile("" : "=f"(acc[2 * i]), "=f"(acc[2 * i + 1]), "=r"(pk[i]));
      uint4* dst = g_pre;
      int left = 0;
      auto put = [&](bool last) {
        #pragma unroll
        for (int i = 0; i < PUT_N; i++) dst[i * 256] = make_uint4(pk[4 * i], pk[4 * i + 1], pk[4 * i + 2], pk[4 * i + 3]);
        dst += PUT_N * 256;
        #pragma unroll
        for (int i = 0; i < 64 - 4 * PUT_N; i++) asm volatile("mov.b32 %0, %1;" : "=r"(pk[i]) : "r"(pk[i + 4 * PUT_N]));
        __syncwarp();
        if (last && lane == 0) mbar_arrive(bars + 280);
      };
      #pragma unroll 1
      for (int ji = 0; ji < help_njobs(); ji++) {
        #pragma unroll 1
        for (int kk = 0; kk < OG_PRE; kk++, j++) {
          const uint32_t slot = ring_slot(qp_pos(j, 1));
          mbar_wait(b_full + 8 * slot, ring_par(qp_pos(j, 1)) ^ ((j >> 2) & 1));
          if (H_STAG > 0 && cwg == 1 && kk == OG_PRE - H_STAG) named_bar_sync(7, 256);
          const uint32_t a_lo = q_lo + (j & 3) * 1024, b_lo = w_base + slot * 2048;
          wgmma_fence();
          wgmma_m64n256k16_ss_tb<0, 0>(acc, a_lo, b_lo, kk != 0);
          wgmma_m64n256k16_ss_tb<2, 128>(acc, a_lo, b_lo, 1);
          wgmma_m64n256k16_ss_tb<4, 256>(acc, a_lo, b_lo, 1);
          wgmma_m64n256k16_ss_tb<6, 384>(acc, a_lo, b_lo, 1);
          wgmma_commit();
          if (H_STAG > 0 && cwg == 0 && kk == OG_PRE - 1) named_bar_arrive(7, 256);
          wgmma_wait<1>();
          if (kk > 0 && tid == 0) mbar_arrive(b_empty + 8 * ring_slot(qp_pos(j - 1, 1)));
          #pragma unroll 1
          for (int i = ji == OG_JOBS ? 0 : 16 / PUT_N - 1; i < 16 / PUT_N && left > 0; i++) put(--left == 0);
        }
        wgmma_wait<0>();
        fence_regs(acc);
        if (tid == 0) mbar_arrive(b_empty + 8 * ring_slot(qp_pos(j - 1, 1)));
        #pragma unroll
        for (int i = 0; i < 64; i++) pk[i] = pack_bf16(acc[2 * i], acc[2 * i + 1]);
        left = 16 / PUT_N;
        if (ji == PRE_X) mbar_wait(bars + 296, 0);
        dst = g_pre + pre_loc(help_job(ji)) * 4096 + threadIdx.x - 128;
      }
      #pragma unroll
      for (int i = 0; i < 16; i++) dst[i * 256] = make_uint4(pk[4 * i], pk[4 * i + 1], pk[4 * i + 2], pk[4 * i + 3]);
      __syncwarp();
      if (lane == 0) mbar_arrive(bars + 280);
      named_bar_sync(5, 256);
      if (threadIdx.x == 128) {
        #pragma unroll 1
        for (int i = 0; i < 5; i++) {
          constexpr int n = OG_JOBS * OG_PRE;
          const int used = i == 3 ? 0 : (n + 3 - (i == 4 ? 3 : i)) / 4;
          if ((used ^ (i < 4)) & 1) {
            mbar_arrive(b_full + 8 * ring_slot(4 + i));
            mbar_arrive(b_empty + 8 * ring_slot(4 + i)); mbar_arrive(b_empty + 8 * ring_slot(4 + i));
          }
        }
        mbar_arrive(b_x);
      }
      named_bar_sync(5, 256);
      #pragma unroll
      for (int i = 0; i < 8; i++) pre[i] = make_uint4(0u, 0u, 0u, 0u);
    }
    TL_CLK(3, 1, threadIdx.x == 128);
    TL_CTA(1, threadIdx.x == 256);
    TL_END(3, tid == 0);
    TL_MARK2(19, tid == 0 && !single);
    if (blockIdx.x < 128) {
      if (!HOIST && blockIdx.x < OG_MOE) {
        load_pre(pre, sbase, AT_SQ, threadIdx.x - 128);
        __syncwarp();
        if (lane == 0) mbar_arrive(bars + 304);
      }
      tail_consumer(sbase, pre, cwg, w_gate, w_up);
    }
  }
}

typedef CUresult (*PFN_encodeTiled)(CUtensorMap*, CUtensorMapDataType, cuuint32_t, void*, const cuuint64_t*, const cuuint64_t*,
                                    const cuuint32_t*, const cuuint32_t*, CUtensorMapInterleave, CUtensorMapSwizzle,
                                    CUtensorMapL2promotion, CUtensorMapFloatOOBfill);

CUtensorMap make_map_2d(PFN_encodeTiled enc, const void* ptr, uint64_t inner, uint64_t outer, uint64_t stride_bytes, uint32_t box_inner, uint32_t box_outer) {
  CUtensorMap m;
  cuuint64_t gd[2] = {inner, outer}; cuuint64_t gs[1] = {stride_bytes};
  cuuint32_t bx[2] = {box_inner, box_outer}; cuuint32_t es[2] = {1, 1};
  enc(&m, CU_TENSOR_MAP_DATA_TYPE_BFLOAT16, 2, const_cast<void*>(ptr), gd, gs, bx, es, CU_TENSOR_MAP_INTERLEAVE_NONE,
      CU_TENSOR_MAP_SWIZZLE_128B, CU_TENSOR_MAP_L2_PROMOTION_L2_128B, CU_TENSOR_MAP_FLOAT_OOB_FILL_NONE);
  return m;
}

CUtensorMap make_map_3d(PFN_encodeTiled enc, const void* ptr, uint64_t cols, uint64_t rows, uint32_t box_rows, uint32_t chunks) {
  CUtensorMap m;
  cuuint64_t gd[3] = {64, rows, cols / 64}; cuuint64_t gs[2] = {cols * 2, 128};
  cuuint32_t bx[3] = {64, box_rows, chunks}; cuuint32_t es[3] = {1, 1, 1};
  enc(&m, CU_TENSOR_MAP_DATA_TYPE_BFLOAT16, 3, const_cast<void*>(ptr), gd, gs, bx, es, CU_TENSOR_MAP_INTERLEAVE_NONE,
      CU_TENSOR_MAP_SWIZZLE_128B, CU_TENSOR_MAP_L2_PROMOTION_L2_128B, CU_TENSOR_MAP_FLOAT_OOB_FILL_NONE);
  return m;
}

}

extern "C" void kernel_launch(void* const* d_in, const int* in_sizes, int n_in, void* d_out, int out_size) {
  const bf16* x      = (const bf16*)d_in[0];
  const bf16* kc     = (const bf16*)d_in[1];
  const bf16* vc     = (const bf16*)d_in[2];
  const bf16* wq     = (const bf16*)d_in[3];
  const bf16* wo     = (const bf16*)d_in[4];
  const bf16* w_r    = (const bf16*)d_in[6];
  const bf16* w_gate = (const bf16*)d_in[7];
  const bf16* w_up   = (const bf16*)d_in[8];
  const bf16* w_down = (const bf16*)d_in[9];
  const bf16* cvec   = (const bf16*)d_in[10];
  const bf16* w_mod  = (const bf16*)d_in[11];
  bf16* out = (bf16*)d_out;

  static PFN_encodeTiled enc = nullptr;
  static void *p_h = nullptr, *p_o = nullptr;
  if (!enc) {
    void* fn = nullptr; cudaDriverEntryPointQueryResult qres;
    cudaGetDriverEntryPoint("cuTensorMapEncodeTiled", &fn, cudaEnableDefault, &qres);
    enc = (PFN_encodeTiled)fn;
    cudaGetSymbolAddress(&p_h, g_pre);
    p_h = (uint4*)p_h + 16 * PRE_X * 2048;
    cudaGetSymbolAddress(&p_o, g_o);
    cudaFuncSetAttribute(fused_kernel, cudaFuncAttributeMaxDynamicSharedMemorySize, (int)AT_SMEM);
  }
  const CUtensorMap tm_h   = make_map_2d(enc, p_h, T_D, T_SEQ, T_D * 2, 64, 128);
  const CUtensorMap tm_wq  = W3D ? make_map_3d(enc, wq, T_DQKV, T_D, 64, 4) : make_map_2d(enc, wq, T_DQKV, T_D, T_DQKV * 2, 64, 64);
  const CUtensorMap tm_k   = KV3D ? make_map_3d(enc, kc, T_DH, (uint64_t)T_NH * T_SEQ, 128, 2) : make_map_2d(enc, kc, T_DH, (uint64_t)T_NH * T_SEQ, T_DH * 2, 64, 128);
  const CUtensorMap tm_v   = KV3D ? make_map_3d(enc, vc, T_DH, (uint64_t)T_NH * T_SEQ, 128, 2) : make_map_2d(enc, vc, T_DH, (uint64_t)T_NH * T_SEQ, T_DH * 2, 64, 128);
  const CUtensorMap tm_ost = make_map_2d(enc, p_o, T_DQKV, T_SEQ, T_DQKV * 2, 64, 64);
  const CUtensorMap tm_old = make_map_2d(enc, p_o, T_DQKV, T_SEQ, T_DQKV * 2, 64, 128);
  const CUtensorMap tm_wo  = make_map_3d(enc, wo, T_D, T_DQKV, 64, 2);
  const CUtensorMap tm_x   = make_map_3d(enc, w_down, T_D, T_F, 32, 8);

  const CUtensorMap tm_m   = make_map_2d(enc, w_mod, 6 * T_D, T_D, 6 * T_D * 2, 64, 256);
  const CUtensorMap tm_out = make_map_2d(enc, out, T_D, T_SEQ, T_D * 2, 64, 128);

  fused_kernel<<<132, 384, AT_SMEM, cudaStreamPerThread>>>(tm_h, tm_wq, tm_k, tm_v, tm_ost, tm_old, tm_wo, tm_x, tm_out, tm_m, 0u, (const uint8_t*)wo, kc, vc, x, cvec, w_mod,
             w_r, w_gate, w_up, w_down, out);
}
```

```cpp
#include <cuda_runtime.h>
#include <cuda_bf16.h>
#include <cuda.h>
#include <stdint.h>

namespace {

typedef __nv_bfloat16 bf16;

constexpr int T_SEQ = 2048, T_D = 1024, T_NH = 32, T_DH = 128, T_DQKV = 4096, T_F = 3584;

#define PRE_X 2
__device__ __align__(1024) uint4 g_pre[(16 * PRE_X + 128) * 2048];
#define g_h (reinterpret_cast<bf16*>(g_pre + 16 * PRE_X * 2048))
__device__ __align__(1024) bf16 g_o[T_SEQ * T_DQKV];
__device__ __align__(16) uint8_t g_col[8 * 1536];
__device__ __align__(16) float g_scal[64];
__device__ __align__(16) unsigned int g_hcnt[17 * 32];
__device__ unsigned int g_smid[160], g_tmax[128];
__device__ __align__(128) float g_modpart[4 * 2 * T_D];
struct __align__(2048) TailMail {
  float4 part1[T_SEQ * 8];
  uint32_t key[256];
  uint4 cand[16 * 2 * 2 * 128];
  uint32_t cnt[32];
  float ypart[(T_F / 32) * 2 * T_D];
};
__device__ TailMail g_mail;
#define g_part1 g_mail.part1
#define g_key g_mail.key
#define g_cand g_mail.cand
#define CNT_Y (g_mail.cnt)
#define g_ypart g_mail.ypart

__device__ __forceinline__ uint32_t smem_u32(const void* p) { return (uint32_t)__cvta_generic_to_shared(p); }
__device__ __forceinline__ void mbar_init(uint32_t bar, uint32_t cnt) { asm volatile("mbarrier.init.shared::cta.b64 [%0], %1;" :: "r"(bar), "r"(cnt)); }
__device__ __forceinline__ void mbar_expect_tx(uint32_t bar, uint32_t bytes) { asm volatile("mbarrier.arrive.expect_tx.shared::cta.b64 _, [%0], %1;" :: "r"(bar), "r"(bytes) : "memory"); }
__device__ __forceinline__ void mbar_arrive(uint32_t bar) { asm volatile("mbarrier.arrive.shared::cta.b64 _, [%0];" :: "r"(bar) : "memory"); }
__device__ __forceinline__ void mbar_wait(uint32_t bar, uint32_t parity) {
  asm volatile("{\n.reg .pred p;\nLAB_WAIT:\nmbarrier.try_wait.parity.shared::cta.b64 p, [%0], %1;\n@!p bra LAB_WAIT;\n}\n" :: "r"(bar), "r"(parity) : "memory");
}
__device__ __forceinline__ bool mbar_test(uint32_t bar, uint32_t parity) {
  uint32_t r; asm volatile("{\n.reg .pred p;\nmbarrier.test_wait.parity.shared::cta.b64 p, [%1], %2;\nselp.u32 %0, 1, 0, p;\n}\n" : "=r"(r) : "r"(bar), "r"(parity) : "memory");
  return r != 0;
}
__device__ __forceinline__ uint32_t clock_lo() { uint32_t c; asm volatile("mov.u32 %0, %%clock;" : "=r"(c)); return c; }
__device__ __forceinline__ void fence_mbar_init() { asm volatile("fence.mbarrier_init.release.cluster;" ::: "memory"); }
__device__ __forceinline__ void tma_load_2d(uint32_t dst, const CUtensorMap* map, int c0, int c1, uint32_t bar) {
  asm volatile("cp.async.bulk.tensor.2d.shared::cluster.global.mbarrier::complete_tx::bytes [%0], [%1, {%3, %4}], [%2];"
    :: "r"(dst), "l"(map), "r"(bar), "r"(c0), "r"(c1) : "memory");
}
__device__ __forceinline__ uint64_t policy_evict_first() {
  uint64_t p; asm volatile("createpolicy.fractional.L2::evict_first.b64 %0, 1.0;" : "=l"(p)); return p;
}
__device__ __forceinline__ void tma_load_2d_hint(uint32_t dst, const CUtensorMap* map, int c0, int c1, uint32_t bar, uint64_t pol) {
  asm volatile("cp.async.bulk.tensor.2d.shared::cluster.global.mbarrier::complete_tx::bytes.L2::cache_hint [%0], [%1, {%3, %4}], [%2], %5;"
    :: "r"(dst), "l"(map), "r"(bar), "r"(c0), "r"(c1), "l"(pol) : "memory");
}
__device__ __forceinline__ void tma_load_3d_hint(uint32_t dst, const CUtensorMap* map, int c1, int c2, uint32_t bar, uint64_t pol) {
  asm volatile("cp.async.bulk.tensor.3d.shared::cluster.global.mbarrier::complete_tx::bytes.L2::cache_hint [%0], [%1, {%3, %4, %5}], [%2], %6;"
    :: "r"(dst), "l"(map), "r"(bar), "n"(0), "r"(c1), "r"(c2), "l"(pol) : "memory");
}
__device__ __forceinline__ void tma_store_2d(const CUtensorMap* map, uint32_t src, int c0, int c1) {
  asm volatile("cp.async.bulk.tensor.2d.global.shared::cta.bulk_group [%0, {%2, %3}], [%1];" :: "l"(map), "r"(src), "r"(c0), "r"(c1) : "memory");
}
__device__ __forceinline__ void prefetch_tmap(const CUtensorMap* map) { asm volatile("prefetch.tensormap [%0];" :: "l"(map) : "memory"); }
__device__ __forceinline__ void l2_prefetch_bulk(const void* p, uint32_t bytes) {
  asm volatile("cp.async.bulk.prefetch.L2.global [%0], %1;" :: "l"(p), "r"(bytes) : "memory");
}
__device__ __forceinline__ void bulk_commit() { asm volatile("cp.async.bulk.commit_group;" ::: "memory"); }
template<int N> __device__ __forceinline__ void bulk_wait_read() { asm volatile("cp.async.bulk.wait_group.read %0;" :: "n"(N) : "memory"); }
template<int N> __device__ __forceinline__ void bulk_wait() { asm volatile("cp.async.bulk.wait_group %0;" :: "n"(N) : "memory"); }
__device__ __forceinline__ void named_bar_sync(int id, int nthreads) { asm volatile("bar.sync %0, %1;" :: "r"(id), "r"(nthreads) : "memory"); }
__device__ __forceinline__ void named_bar_arrive(int id, int nthreads) { asm volatile("bar.arrive %0, %1;" :: "r"(id), "r"(nthreads) : "memory"); }
__device__ __forceinline__ void wgmma_fence() { asm volatile("wgmma.fence.sync.aligned;" ::: "memory"); }
__device__ __forceinline__ void wgmma_commit() { asm volatile("wgmma.commit_group.sync.aligned;" ::: "memory"); }
template<int N> __device__ __forceinline__ void wgmma_wait() { asm volatile("wgmma.wait_group.sync.aligned %0;" :: "n"(N) : "memory"); }
template<int R> __device__ __forceinline__ void reg_alloc() { asm volatile("setmaxnreg.inc.sync.aligned.u32 %0;" :: "n"(R)); }
template<int R> __device__ __forceinline__ void reg_dealloc() { asm volatile("setmaxnreg.dec.sync.aligned.u32 %0;" :: "n"(R)); }
__device__ __forceinline__ bool elect_one() {
  uint32_t pred; asm volatile("{\n.reg .pred p;\nelect.sync _|p, 0xffffffff;\nselp.u32 %0, 1, 0, p;\n}\n" : "=r"(pred)); return pred != 0;
}
__device__ __forceinline__ uint32_t pack_bf16(float lo, float hi) {
  uint32_t r; asm("cvt.rn.bf16x2.f32 %0, %1, %2;" : "=r"(r) : "f"(hi), "f"(lo)); return r;
}
__device__ __forceinline__ void stmatrix_x4(uint32_t addr, uint32_t r0, uint32_t r1, uint32_t r2, uint32_t r3) {
  asm volatile("stmatrix.sync.aligned.m8n8.x4.shared.b16 [%0], {%1, %2, %3, %4};" :: "r"(addr), "r"(r0), "r"(r1), "r"(r2), "r"(r3) : "memory");
}
__device__ __forceinline__ void fence_proxy_async() { asm volatile("fence.proxy.async.shared::cta;" ::: "memory"); }
__device__ __forceinline__ float ex2_approx(float x) { float y; asm("ex2.approx.ftz.f32 %0, %1;" : "=f"(y) : "f"(x)); return y; }
template<int N> __device__ __forceinline__ void fence_regs(float (&r)[N]) {
  #pragma unroll
  for (int i = 0; i < N; i++) asm volatile("" : "+f"(r[i]) :: "memory");
}
template<int N> __device__ __forceinline__ void zero_regs(float (&r)[N]) {
  #pragma unroll
  for (int i = 0; i < N; i += 2) asm volatile("mov.b64 {%0, %1}, 0;" : "=f"(r[i]), "=f"(r[i + 1]));
}
__device__ __forceinline__ float rbf(float x) { return __uint_as_float(pack_bf16(0.f, x)); }
__device__ __forceinline__ float bflo(uint32_t v) { return __uint_as_float(v << 16); }
__device__ __forceinline__ float bfhi(uint32_t v) { return __uint_as_float(v & 0xffff0000u); }

#define TL_START(k) do {} while (0)
#define TL_END(k, cond) do {} while (0)
#define TL_CTA(i, cond) do {} while (0)
#define FS(slot, k) do {} while (0)
#define TL_MARK2(k, cond) do {} while (0)
#define TL_CLK(k, i, cond) do {} while (0)

template <int OFFA, int OFFB>
__device__ __forceinline__ void wgmma_m64n256k16_ss_tb(float (&d)[128], uint32_t a_lo, uint32_t b_lo, int scaleD) {
  asm volatile("{\n.reg .pred p;\n.reg .b32 ta, tb;\n.reg .b64 da, db;\nsetp.ne.b32 p, %130, 0;\n"
    "add.u32 ta, %128, %131;\nadd.u32 tb, %129, %132;\n"
    "mov.b64 da, {ta, 0x40000040};\nmov.b64 db, {tb, 0x40000040};\n"
    "wgmma.mma_async.sync.aligned.m64n256k16.f32.bf16.bf16 "
    "{%0, %1, %2, %3, %4, %5, %6, %7, %8, %9, %10, %11, %12, %13, %14, %15, %16, %17, %18, %19, %20, %21, %22, %23, %24, %25, %26, %27, %28, %29, %30, %31, %32, %33, %34, %35, %36, %37, %38, %39, %40, %41, %42, %43, %44, %45, %46, %47, %48, %49, %50, %51, %52, %53, %54, %55, %56, %57, %58, %59, %60, %61, %62, %63, %64, %65, %66, %67, %68, %69, %70, %71, %72, %73, %74, %75, %76, %77, %78, %79, %80, %81, %82, %83, %84, %85, %86, %87, %88, %89, %90, %91, %92, %93, %94, %95, %96, %97, %98, %99, %100, %101, %102, %103, %104, %105, %106, %107, %108, %109, %110, %111, %112, %113, %114, %115, %116, %117, %118, %119, %120, %121, %122, %123, %124, %125, %126, %127}, "
    "da, db, p, 1, 1, 0, 1;\n}\n"
    : "+f"(d[0]), "+f"(d[1]), "+f"(d[2]), "+f"(d[3]), "+f"(d[4]), "+f"(d[5]), "+f"(d[6]), "+f"(d[7]), "+f"(d[8]), "+f"(d[9]), "+f"(d[10]), "+f"(d[11]), "+f"(d[12]), "+f"(d[13]), "+f"(d[14]), "+f"(d[15]), "+f"(d[16]), "+f"(d[17]), "+f"(d[18]), "+f"(d[19]), "+f"(d[20]), "+f"(d[21]), "+f"(d[22]), "+f"(d[23]), "+f"(d[24]), "+f"(d[25]), "+f"(d[26]), "+f"(d[27]), "+f"(d[28]), "+f"(d[29]), "+f"(d[30]), "+f"(d[31]), "+f"(d[32]), "+f"(d[33]), "+f"(d[34]), "+f"(d[35]), "+f"(d[36]), "+f"(d[37]), "+f"(d[38]), "+f"(d[39]), "+f"(d[40]), "+f"(d[41]), "+f"(d[42]), "+f"(d[43]), "+f"(d[44]), "+f"(d[45]), "+f"(d[46]), "+f"(d[47]), "+f"(d[48]), "+f"(d[49]), "+f"(d[50]), "+f"(d[51]), "+f"(d[52]), "+f"(d[53]), "+f"(d[54]), "+f"(d[55]), "+f"(d[56]), "+f"(d[57]), "+f"(d[58]), "+f"(d[59]), "+f"(d[60]), "+f"(d[61]), "+f"(d[62]), "+f"(d[63]), "+f"(d[64]), "+f"(d[65]), "+f"(d[66]), "+f"(d[67]), "+f"(d[68]), "+f"(d[69]), "+f"(d[70]), "+f"(d[71]), "+f"(d[72]), "+f"(d[73]), "+f"(d[74]), "+f"(d[75]), "+f"(d[76]), "+f"(d[77]), "+f"(d[78]), "+f"(d[79]), "+f"(d[80]), "+f"(d[81]), "+f"(d[82]), "+f"(d[83]), "+f"(d[84]), "+f"(d[85]), "+f"(d[86]), "+f"(d[87]), "+f"(d[88]), "+f"(d[89]), "+f"(d[90]), "+f"(d[91]), "+f"(d[92]), "+f"(d[93]), "+f"(d[94]), "+f"(d[95]), "+f"(d[96]), "+f"(d[97]), "+f"(d[98]), "+f"(d[99]), "+f"(d[100]), "+f"(d[101]), "+f"(d[102]), "+f"(d[103]), "+f"(d[104]), "+f"(d[105]), "+f"(d[106]), "+f"(d[107]), "+f"(d[108]), "+f"(d[109]), "+f"(d[110]), "+f"(d[111]), "+f"(d[112]), "+f"(d[113]), "+f"(d[114]), "+f"(d[115]), "+f"(d[116]), "+f"(d[117]), "+f"(d[118]), "+f"(d[119]), "+f"(d[120]), "+f"(d[121]), "+f"(d[122]), "+f"(d[123]), "+f"(d[124]), "+f"(d[125]), "+f"(d[126]), "+f"(d[127])
    : "r"(a_lo), "r"(b_lo), "r"(scaleD), "n"(OFFA), "n"(OFFB));
}

template <int OFFA, int OFFB>
__device__ __forceinline__ void wgmma_m64n128k16_ss_tb(float (&d)[64], uint32_t a_lo, uint32_t b_lo, int scaleD) {
  asm volatile("{\n.reg .pred p;\n.reg .b32 ta, tb;\n.reg .b64 da, db;\nsetp.ne.b32 p, %66, 0;\n"
    "add.u32 ta, %64, %67;\nadd.u32 tb, %65, %68;\n"
    "mov.b64 da, {ta, 0x40000040};\nmov.b64 db, {tb, 0x40000040};\n"
    "wgmma.mma_async.sync.aligned.m64n128k16.f32.bf16.bf16 "
    "{%0, %1, %2, %3, %4, %5, %6, %7, %8, %9, %10, %11, %12, %13, %14, %15, %16, %17, %18, %19, %20, %21, %22, %23, %24, %25, %26, %27, %28, %29, %30, %31, %32, %33, %34, %35, %36, %37, %38, %39, %40, %41, %42, %43, %44, %45, %46, %47, %48, %49, %50, %51, %52, %53, %54, %55, %56, %57, %58, %59, %60, %61, %62, %63}, "
    "da, db, p, 1, 1, 0, 1;\n}\n"
    : "+f"(d[0]), "+f"(d[1]), "+f"(d[2]), "+f"(d[3]), "+f"(d[4]), "+f"(d[5]), "+f"(d[6]), "+f"(d[7]), "+f"(d[8]), "+f"(d[9]), "+f"(d[10]), "+f"(d[11]), "+f"(d[12]), "+f"(d[13]), "+f"(d[14]), "+f"(d[15]), "+f"(d[16]), "+f"(d[17]), "+f"(d[18]), "+f"(d[19]), "+f"(d[20]), "+f"(d[21]), "+f"(d[22]), "+f"(d[23]), "+f"(d[24]), "+f"(d[25]), "+f"(d[26]), "+f"(d[27]), "+f"(d[28]), "+f"(d[29]), "+f"(d[30]), "+f"(d[31]), "+f"(d[32]), "+f"(d[33]), "+f"(d[34]), "+f"(d[35]), "+f"(d[36]), "+f"(d[37]), "+f"(d[38]), "+f"(d[39]), "+f"(d[40]), "+f"(d[41]), "+f"(d[42]), "+f"(d[43]), "+f"(d[44]), "+f"(d[45]), "+f"(d[46]), "+f"(d[47]), "+f"(d[48]), "+f"(d[49]), "+f"(d[50]), "+f"(d[51]), "+f"(d[52]), "+f"(d[53]), "+f"(d[54]), "+f"(d[55]), "+f"(d[56]), "+f"(d[57]), "+f"(d[58]), "+f"(d[59]), "+f"(d[60]), "+f"(d[61]), "+f"(d[62]), "+f"(d[63])
    : "r"(a_lo), "r"(b_lo), "r"(scaleD), "n"(OFFA), "n"(OFFB));
}

template <int OFFB>
__device__ __forceinline__ void wgmma_m64n128k16_rs_tb(float (&d)[64], uint32_t a0, uint32_t a1, uint32_t a2, uint32_t a3, uint32_t b_lo, int scaleD) {
  asm volatile("{\n.reg .pred p;\n.reg .b32 tb;\n.reg .b64 db;\nsetp.ne.b32 p, %69, 0;\n"
    "add.u32 tb, %68, %70;\n"
    "mov.b64 db, {tb, 0x40000040};\n"
    "wgmma.mma_async.sync.aligned.m64n128k16.f32.bf16.bf16 "
    "{%0, %1, %2, %3, %4, %5, %6, %7, %8, %9, %10, %11, %12, %13, %14, %15, %16, %17, %18, %19, %20, %21, %22, %23, %24, %25, %26, %27, %28, %29, %30, %31, %32, %33, %34, %35, %36, %37, %38, %39, %40, %41, %42, %43, %44, %45, %46, %47, %48, %49, %50, %51, %52, %53, %54, %55, %56, %57, %58, %59, %60, %61, %62, %63}, "
    "{%64, %65, %66, %67}, db, p, 1, 1, 1;\n}\n"
    : "+f"(d[0]), "+f"(d[1]), "+f"(d[2]), "+f"(d[3]), "+f"(d[4]), "+f"(d[5]), "+f"(d[6]), "+f"(d[7]), "+f"(d[8]), "+f"(d[9]), "+f"(d[10]), "+f"(d[11]), "+f"(d[12]), "+f"(d[13]), "+f"(d[14]), "+f"(d[15]), "+f"(d[16]), "+f"(d[17]), "+f"(d[18]), "+f"(d[19]), "+f"(d[20]), "+f"(d[21]), "+f"(d[22]), "+f"(d[23]), "+f"(d[24]), "+f"(d[25]), "+f"(d[26]), "+f"(d[27]), "+f"(d[28]), "+f"(d[29]), "+f"(d[30]), "+f"(d[31]), "+f"(d[32]), "+f"(d[33]), "+f"(d[34]), "+f"(d[35]), "+f"(d[36]), "+f"(d[37]), "+f"(d[38]), "+f"(d[39]), "+f"(d[40]), "+f"(d[41]), "+f"(d[42]), "+f"(d[43]), "+f"(d[44]), "+f"(d[45]), "+f"(d[46]), "+f"(d[47]), "+f"(d[48]), "+f"(d[49]), "+f"(d[50]), "+f"(d[51]), "+f"(d[52]), "+f"(d[53]), "+f"(d[54]), "+f"(d[55]), "+f"(d[56]), "+f"(d[57]), "+f"(d[58]), "+f"(d[59]), "+f"(d[60]), "+f"(d[61]), "+f"(d[62]), "+f"(d[63])
    : "r"(a0), "r"(a1), "r"(a2), "r"(a3), "r"(b_lo), "r"(scaleD), "n"(OFFB));
}

template <int OFFB>
__device__ __forceinline__ void wgmma_m64n128k16_rs(float (&d)[64], uint32_t a0, uint32_t a1, uint32_t a2, uint32_t a3, uint32_t b_lo, int scaleD) {
  asm volatile("{\n.reg .pred p;\n.reg .b32 tb;\n.reg .b64 db;\nsetp.ne.b32 p, %69, 0;\n"
    "add.u32 tb, %68, %70;\n"
    "mov.b64 db, {tb, 0x40000040};\n"
    "wgmma.mma_async.sync.aligned.m64n128k16.f32.bf16.bf16 "
    "{%0, %1, %2, %3, %4, %5, %6, %7, %8, %9, %10, %11, %12, %13, %14, %15, %16, %17, %18, %19, %20, %21, %22, %23, %24, %25, %26, %27, %28, %29, %30, %31, %32, %33, %34, %35, %36, %37, %38, %39, %40, %41, %42, %43, %44, %45, %46, %47, %48, %49, %50, %51, %52, %53, %54, %55, %56, %57, %58, %59, %60, %61, %62, %63}, "
    "{%64, %65, %66, %67}, db, p, 1, 1, 0;\n}\n"
    : "+f"(d[0]), "+f"(d[1]), "+f"(d[2]), "+f"(d[3]), "+f"(d[4]), "+f"(d[5]), "+f"(d[6]), "+f"(d[7]), "+f"(d[8]), "+f"(d[9]), "+f"(d[10]), "+f"(d[11]), "+f"(d[12]), "+f"(d[13]), "+f"(d[14]), "+f"(d[15]), "+f"(d[16]), "+f"(d[17]), "+f"(d[18]), "+f"(d[19]), "+f"(d[20]), "+f"(d[21]), "+f"(d[22]), "+f"(d[23]), "+f"(d[24]), "+f"(d[25]), "+f"(d[26]), "+f"(d[27]), "+f"(d[28]), "+f"(d[29]), "+f"(d[30]), "+f"(d[31]), "+f"(d[32]), "+f"(d[33]), "+f"(d[34]), "+f"(d[35]), "+f"(d[36]), "+f"(d[37]), "+f"(d[38]), "+f"(d[39]), "+f"(d[40]), "+f"(d[41]), "+f"(d[42]), "+f"(d[43]), "+f"(d[44]), "+f"(d[45]), "+f"(d[46]), "+f"(d[47]), "+f"(d[48]), "+f"(d[49]), "+f"(d[50]), "+f"(d[51]), "+f"(d[52]), "+f"(d[53]), "+f"(d[54]), "+f"(d[55]), "+f"(d[56]), "+f"(d[57]), "+f"(d[58]), "+f"(d[59]), "+f"(d[60]), "+f"(d[61]), "+f"(d[62]), "+f"(d[63])
    : "r"(a0), "r"(a1), "r"(a2), "r"(a3), "r"(b_lo), "r"(scaleD), "n"(OFFB));
}

__device__ __forceinline__ uint4 ldg_nc_v4(const void* p) {
  uint4 v;
    asm volatile("{\n.reg .b64 pol;\ncreatepolicy.fractional.L2::evict_first.b64 pol, 1.0;\n"
                 "ld.global.nc.L1::no_allocate.L2::cache_hint.v4.u32 {%0, %1, %2, %3}, [%4], pol;\n}\n" : "=r"(v.x), "=r"(v.y), "=r"(v.z), "=r"(v.w) : "l"(p));
  return v;
}
__device__ __forceinline__ uint64_t pol_normal() {
  uint64_t p; asm volatile("createpolicy.fractional.L2::evict_normal.b64 %0, 1.0;" : "=l"(p)); return p;
}
__device__ __forceinline__ void unpack8(const uint4& u, float (&v)[8]) {
  v[0] = bflo(u.x); v[1] = bfhi(u.x); v[2] = bflo(u.y); v[3] = bfhi(u.y);
  v[4] = bflo(u.z); v[5] = bfhi(u.z); v[6] = bflo(u.w); v[7] = bfhi(u.w);
}
__device__ __forceinline__ void fma8(float (&acc)[8], float s, const uint4& w) {
  acc[0] = fmaf(s, bflo(w.x), acc[0]); acc[1] = fmaf(s, bfhi(w.x), acc[1]); acc[2] = fmaf(s, bflo(w.y), acc[2]); acc[3] = fmaf(s, bfhi(w.y), acc[3]);
  acc[4] = fmaf(s, bflo(w.z), acc[4]); acc[5] = fmaf(s, bfhi(w.z), acc[5]); acc[6] = fmaf(s, bflo(w.w), acc[6]); acc[7] = fmaf(s, bfhi(w.w), acc[7]);
}
__device__ __forceinline__ float rcp_approx(float x) { float y; asm("rcp.approx.ftz.f32 %0, %1;" : "=f"(y) : "f"(x)); return y; }
__device__ __forceinline__ float sigmoid_f(float v) { return rcp_approx(1.0f + ex2_approx(v * -1.4426950408889634f)); }
__device__ __forceinline__ float silu_bf(float v) { return rbf(v * sigmoid_f(v)); }
__device__ __forceinline__ uint32_t rank_key(float r, int idx) {
  const uint32_t b = __float_as_uint(r) >> 16;
  const uint32_t u = (r != r) ? 0u : ((b & 0x8000u) ? (~b & 0xffffu) : (b | 0x8000u));
  return (u << 16) | (0xffffu - (uint32_t)idx);
}
__device__ __forceinline__ void warp_top2(uint32_t& k1, uint32_t& k2) {
  const uint32_t m1 = __reduce_max_sync(0xffffffffu, k1);
  k2 = __reduce_max_sync(0xffffffffu, k1 == m1 ? k2 : k1);
  k1 = m1;
}
__device__ __forceinline__ uint32_t bmul2(uint32_t a, uint32_t b) { uint32_t r; asm("mul.rn.bf16x2 %0, %1, %2;" : "=r"(r) : "r"(a), "r"(b)); return r; }
__device__ __forceinline__ uint32_t badd2(uint32_t a, uint32_t b) { uint32_t r; asm("add.rn.bf16x2 %0, %1, %2;" : "=r"(r) : "r"(a), "r"(b)); return r; }
__device__ __forceinline__ uint32_t bsub2(uint32_t a, uint32_t b) { uint32_t r; asm("sub.rn.bf16x2 %0, %1, %2;" : "=r"(r) : "r"(a), "r"(b)); return r; }
__device__ __forceinline__ float sqrt_approx(float x) { float y; asm("sqrt.approx.f32 %0, %1;" : "=f"(y) : "f"(x)); return y; }
__device__ __forceinline__ uint32_t ln_norm2(uint32_t x1, uint32_t mb2, float inv) {
  const uint32_t d = bsub2(x1, mb2);
  return pack_bf16(bflo(d) * inv, bfhi(d) * inv);
}
__device__ __forceinline__ uint32_t bfma2(uint32_t a, uint32_t b, uint32_t c) { uint32_t r; asm("fma.rn.bf16x2 %0, %1, %2, %3;" : "=r"(r) : "r"(a), "r"(b), "r"(c)); return r; }
__device__ __forceinline__ uint32_t ln_norm2b(uint32_t x1, uint32_t mb2, uint32_t ih, uint32_t il) {
  const uint32_t d = bsub2(x1, mb2);
  return bfma2(d, ih, bmul2(d, il));
}
__device__ __forceinline__ uint32_t ln_mod2(uint32_t x1, uint32_t mb2, float inv, uint32_t c1, uint32_t sb) { return badd2(bmul2(ln_norm2(x1, mb2, inv), c1), sb); }
__device__ __forceinline__ void ldmatrix_x4(uint32_t addr, uint32_t& r0, uint32_t& r1, uint32_t& r2, uint32_t& r3) {
  asm volatile("ldmatrix.sync.aligned.m8n8.x4.shared.b16 {%0, %1, %2, %3}, [%4];" : "=r"(r0), "=r"(r1), "=r"(r2), "=r"(r3) : "r"(addr) : "memory");
}
__device__ __forceinline__ uint4 ldg_stream_v4(const void* p, uint64_t pol) {
  uint4 v; asm volatile("ld.global.nc.L1::no_allocate.L2::cache_hint.L2::128B.v4.u32 {%0, %1, %2, %3}, [%4], %5;" : "=r"(v.x), "=r"(v.y), "=r"(v.z), "=r"(v.w) : "l"(p), "l"(pol)); return v;
}
__device__ __forceinline__ void bulk_load_hint(uint32_t dst, const void* src, uint32_t bytes, uint32_t bar, uint64_t pol) {
  asm volatile("cp.async.bulk.shared::cluster.global.mbarrier::complete_tx::bytes.L2::cache_hint [%0], [%1], %2, [%3], %4;"
    :: "r"(dst), "l"(src), "r"(bytes), "r"(bar), "l"(pol) : "memory");
}
__device__ __forceinline__ void red_release_add(unsigned int* p, unsigned int v) { asm volatile("red.release.gpu.global.add.u32 [%0], %1;" :: "l"(p), "r"(v) : "memory"); }
__device__ __forceinline__ unsigned int ld_acquire(const unsigned int* p) { unsigned int v; asm volatile("ld.acquire.gpu.global.u32 %0, [%1];" : "=r"(v) : "l"(p) : "memory"); return v; }
__device__ __forceinline__ void spin_until(const unsigned int* p, unsigned int target) {
  #pragma unroll 1
  for (unsigned int i = 0; i < (1u << 22); i++) { if (ld_acquire(p) >= target) return; }
}
__device__ __forceinline__ float lds_f32(uint32_t a) { float v; asm volatile("ld.shared.f32 %0, [%1];" : "=f"(v) : "r"(a) : "memory"); return v; }
__device__ __forceinline__ float2 lds_f32x2(uint32_t a) { float2 v; asm volatile("ld.shared.v2.f32 {%0, %1}, [%2];" : "=f"(v.x), "=f"(v.y) : "r"(a) : "memory"); return v; }
__device__ __forceinline__ uint2 lds_u32x2(uint32_t a) { uint2 v; asm volatile("ld.shared.v2.u32 {%0, %1}, [%2];" : "=r"(v.x), "=r"(v.y) : "r"(a) : "memory"); return v; }
__device__ __forceinline__ uint32_t lds_u32(uint32_t a) { uint32_t v; asm volatile("ld.shared.u32 %0, [%1];" : "=r"(v) : "r"(a) : "memory"); return v; }
__device__ __forceinline__ void sts_u32(uint32_t a, uint32_t v) { asm volatile("st.shared.u32 [%0], %1;" :: "r"(a), "r"(v) : "memory"); }
__device__ __forceinline__ void sts_u32x2(uint32_t a, uint32_t x, uint32_t y) { asm volatile("st.shared.v2.u32 [%0], {%1, %2};" :: "r"(a), "r"(x), "r"(y) : "memory"); }
__device__ __forceinline__ void sts_f32(uint32_t a, float v) { asm volatile("st.shared.f32 [%0], %1;" :: "r"(a), "f"(v) : "memory"); }
__device__ __forceinline__ void sts_f32x2(uint32_t a, float x, float y) { asm volatile("st.shared.v2.f32 [%0], {%1, %2};" :: "r"(a), "f"(x), "f"(y) : "memory"); }
__device__ __forceinline__ void sts_f32x4(uint32_t a, float x, float y, float z, float w) { asm volatile("st.shared.v4.f32 [%0], {%1, %2, %3, %4};" :: "r"(a), "f"(x), "f"(y), "f"(z), "f"(w) : "memory"); }

__device__ __forceinline__ uint4 lds_u32x4(uint32_t a) { uint4 v; asm volatile("ld.shared.v4.u32 {%0, %1, %2, %3}, [%4];" : "=r"(v.x), "=r"(v.y), "=r"(v.z), "=r"(v.w) : "r"(a) : "memory"); return v; }
__device__ __forceinline__ void sts_u32x4(uint32_t a, uint32_t x, uint32_t y, uint32_t z, uint32_t w) { asm volatile("st.shared.v4.u32 [%0], {%1, %2, %3, %4};" :: "r"(a), "r"(x), "r"(y), "r"(z), "r"(w) : "memory"); }
__device__ __forceinline__ void st_tagged(float* p, float v) {
  const uint32_t b = __float_as_uint(v);
  asm volatile("st.relaxed.gpu.global.u32 [%0], %1;" :: "l"(p), "r"(b == 0u ? 0x80000000u : b) : "memory");
}
__device__ __forceinline__ void st_tagged4(float* p, float x, float y, float z, float w) {
  const uint32_t a = __float_as_uint(x), b = __float_as_uint(y), c = __float_as_uint(z), d = __float_as_uint(w);
  asm volatile("st.relaxed.gpu.global.v4.u32 [%0], {%1, %2, %3, %4};" :: "l"(p), "r"(a == 0u ? 0x80000000u : a), "r"(b == 0u ? 0x80000000u : b),
               "r"(c == 0u ? 0x80000000u : c), "r"(d == 0u ? 0x80000000u : d) : "memory");
}
__device__ __forceinline__ void st_relaxed2(void* p, uint32_t a, uint32_t b) { asm volatile("st.relaxed.gpu.global.v2.u32 [%0], {%1, %2};" :: "l"(p), "r"(a), "r"(b) : "memory"); }
__device__ __forceinline__ float4 ld_tagged4(const float* p) {
  float4 v; asm volatile("ld.relaxed.gpu.global.v4.f32 {%0, %1, %2, %3}, [%4];" : "=f"(v.x), "=f"(v.y), "=f"(v.z), "=f"(v.w) : "l"(p) : "memory"); return v;
}
__device__ __forceinline__ bool tagged4(const float4& v) {
  return __float_as_uint(v.x) != 0u && __float_as_uint(v.y) != 0u && __float_as_uint(v.z) != 0u && __float_as_uint(v.w) != 0u;
}
__device__ __forceinline__ void hint_arrive(uint32_t* p) { asm volatile("red.relaxed.gpu.global.add.u32 [%0], 1;" :: "l"(p) : "memory"); }
__device__ __forceinline__ void hint_wait(const uint32_t* p, uint32_t target) {
  uint32_t v = 0u;
  #pragma unroll 1
  for (unsigned int i = 0; i < (1u << 22) && v < target; i++) asm volatile("ld.relaxed.gpu.global.u32 %0, [%1];" : "=r"(v) : "l"(p) : "memory");
}
__device__ __forceinline__ void fence_proxy_async_global() { asm volatile("fence.proxy.async.global;" ::: "memory"); }

#define H_SPLIT 1
#define X_DLY 1200
#define W_DLY 1900
#define W_FIRST 2200
#define PRE_B 2
#define H_PREG 1
template <int J0, int J1>
__device__ __forceinline__ void load_parts(float2 (&pa)[J1 - J0][4], int t2) {
  #pragma unroll
  for (int j = J0; j < J1; j++)
    #pragma unroll
    for (int k = 0; k < 4; k++)
      asm volatile("ld.relaxed.gpu.global.v2.f32 {%0, %1}, [%2];" : "=f"(pa[j - J0][k].x), "=f"(pa[j - J0][k].y)
                   : "l"(g_modpart + k * 2 * T_D + (t2 >> 7) * T_D + j * 256 + (t2 & 127) * 2) : "memory");
}
template <int J0, int J1>
__device__ __forceinline__ void finish_parts(float2 (&pa)[J1 - J0][4], bool loaded, int t2, uint32_t tab) {
  #pragma unroll 1
  for (unsigned int spin = 0; spin < (1u << 22); spin++) {
    if (!loaded) load_parts<J0, J1>(pa, t2);
    loaded = false;
    bool ok = true;
    #pragma unroll
    for (int j = 0; j < J1 - J0; j++)
      #pragma unroll
      for (int k = 0; k < 4; k++) ok &= (__float_as_uint(pa[j][k].x) != 0u) & (__float_as_uint(pa[j][k].y) != 0u);
    if (__all_sync(0xffffffffu, ok)) break;
  }
  #pragma unroll
  for (int j = J0; j < J1; j++) {
    const float2* q = pa[j - J0];
    const uint32_t m = pack_bf16(((q[0].x + q[1].x) + q[2].x) + q[3].x, ((q[0].y + q[1].y) + q[2].y) + q[3].y);
    sts_u32(tab + (t2 >> 7) * 2048 + j * 512 + (t2 & 127) * 4, t2 >= 128 ? badd2(m, 0x3F803F80u) : m);
  }
}
__device__ __forceinline__ void head_phase(uint32_t scr, uint32_t xs, uint32_t b_x, uint32_t b_go, uint32_t b_head, int t2, uint32_t zero, const bf16* __restrict__ cvec, const bf16* __restrict__ w_mod) {
  const int lane = t2 & 31, w8 = t2 >> 5;
  const int cb = blockIdx.x & 31, ks = blockIdx.x >> 5;
  const bool early = (cb & 15) < 4 * H_SPLIT;
  const uint32_t ws = (xs - 32768 + (t2 >> 3) * 128 + (((t2 ^ (t2 >> 3)) & 7) << 4)) ^ zero;
  const float cv = __bfloat162float(cvec[ks * 256 + t2]);
  const bf16* wsrc = w_mod + (size_t)(ks * 256 + (t2 >> 3)) * (6 * T_D) + cb * 64 + (t2 & 7) * 8;
  if (early) {
    const uint64_t pol = policy_evict_first();
    #pragma unroll 2
    for (int i = 0; i < 8; i++)
      asm volatile("cp.async.cg.shared.global.L2::cache_hint [%0], [%1], 16, %2;" :: "r"(ws + i * 4096), "l"(wsrc + (size_t)i * 32 * 6 * T_D), "l"(pol) : "memory");
  }
  sts_f32(scr + t2 * 4, silu_bf(cv));
  named_bar_sync(6, 384);
  TL_MARK2(1, t2 == 0);
  uint4 xv[2][4];
  uint32_t mb2[2], ih[2], il[2];
  auto norm = [&](int j) {
    #pragma unroll
    for (int r = 0; r < 2; r++) {
      xv[r][j].x = ln_norm2b(xv[r][j].x, mb2[r], ih[r], il[r]); xv[r][j].y = ln_norm2b(xv[r][j].y, mb2[r], ih[r], il[r]);
      xv[r][j].z = ln_norm2b(xv[r][j].z, mb2[r], ih[r], il[r]); xv[r][j].w = ln_norm2b(xv[r][j].w, mb2[r], ih[r], il[r]);
    }
  };
  auto modulate = [&](int j) {
    const uint4 sa = lds_u32x4(scr + 8192 + j * 512 + lane * 16), c1 = lds_u32x4(scr + 8192 + 2048 + j * 512 + lane * 16);
    #pragma unroll
    for (int r = 0; r < 2; r++) {
      xv[r][j].x = badd2(bmul2(xv[r][j].x, c1.x), sa.x); xv[r][j].y = badd2(bmul2(xv[r][j].y, c1.y), sa.y);
      xv[r][j].z = badd2(bmul2(xv[r][j].z, c1.z), sa.z); xv[r][j].w = badd2(bmul2(xv[r][j].w, c1.w), sa.w);
    }
  };
  auto store = [&](int j) {
    #pragma unroll
    for (int r = 0; r < 2; r++) *reinterpret_cast<uint4*>(g_h + (size_t)(blockIdx.x * 16 + 2 * w8 + r) * T_D + j * 256 + lane * 8) = xv[r][j];
  };
  #pragma unroll 1
  for (int ph = 0; ph < 2; ph++) {
    if ((ph == 0) == early) {
      asm volatile("cp.async.wait_all;" ::: "memory");
      if (!early) mbar_wait(b_x + 168, 0);
      float acc[8];
      #pragma unroll
      for (int j = 0; j < 8; j++) acc[j] = 0.f;
      #pragma unroll
      for (int i = 0; i < 8; i++) fma8(acc, lds_f32(scr + ((t2 >> 3) + 32 * i) * 4), lds_u32x4(ws + i * 4096));
      #pragma unroll
      for (int j = 0; j < 4; j++) { const bool up = lane & 16; acc[j] = (up ? acc[4 + j] : acc[j]) + __shfl_xor_sync(0xffffffffu, up ? acc[j] : acc[4 + j], 16); }
      #pragma unroll
      for (int j = 0; j < 2; j++) { const bool up = lane & 8; acc[j] = (up ? acc[2 + j] : acc[j]) + __shfl_xor_sync(0xffffffffu, up ? acc[j] : acc[2 + j], 8); }
      sts_f32x2(scr + 1024 + w8 * 256 + (lane & 7) * 32 + (lane >> 3) * 8, acc[0], acc[1]);
      named_bar_sync(5, 256);
      if (t2 < 64) {
        float sum = 0.f;
        #pragma unroll
        for (int i = 0; i < 8; i++) sum += lds_f32(scr + 1024 + i * 256 + t2 * 4);
        st_tagged(g_modpart + ks * 2 * T_D + cb * 64 + t2, sum);
        TL_MARK2(early ? 2 : 6, t2 == 0);
      }
    } else {
      float2 pa[H_SPLIT][4];
      mbar_wait(b_x, 0);
      TL_MARK2(18, t2 == 0);
      if (H_PREG) load_parts<0, H_SPLIT>(pa, t2);
      #pragma unroll
      for (int r = 0; r < 2; r++)
        #pragma unroll
        for (int j = 0; j < 4; j++) xv[r][j] = lds_u32x4(xs + (2 * w8 + r) * 2048 + j * 512 + lane * 16);
  {
    float st[4] = {0.f, 0.f, 0.f, 0.f};
    #pragma unroll
    for (int r = 0; r < 2; r++)
      #pragma unroll
      for (int j = 0; j < 4; j++) {
        float v[8];
        unpack8(xv[r][j], v);
        st[2 * r] += ((v[0] + v[1]) + (v[2] + v[3])) + ((v[4] + v[5]) + (v[6] + v[7]));
        st[2 * r + 1] += fmaf(v[0], v[0], fmaf(v[1], v[1], fmaf(v[2], v[2], v[3] * v[3]))) + fmaf(v[4], v[4], fmaf(v[5], v[5], fmaf(v[6], v[6], v[7] * v[7])));
      }
    #pragma unroll
    for (int k = 0; k < 2; k++) { const bool up = lane & 16; st[k] = (up ? st[2 + k] : st[k]) + __shfl_xor_sync(0xffffffffu, up ? st[k] : st[2 + k], 16); }
    #pragma unroll
    for (int o = 8; o > 0; o >>= 1) { st[0] += __shfl_xor_sync(0xffffffffu, st[0], o); st[1] += __shfl_xor_sync(0xffffffffu, st[1], o); }
    const float mean = st[0] * (1.0f / T_D);
    const float inv = rcp_approx(rbf(sqrt_approx(rbf(rbf(fmaxf(fmaf(-mean, mean, st[1] * (1.0f / T_D)), 0.f)) + 1e-05f))));
    const uint32_t m = pack_bf16(mean, mean), h = pack_bf16(inv - rbf(inv), inv);
    #pragma unroll
    for (int r = 0; r < 2; r++) {
      mb2[r] = __shfl_sync(0xffffffffu, m, 16 * r);
      const uint32_t hr = __shfl_sync(0xffffffffu, h, 16 * r);
      ih[r] = __byte_perm(hr, hr, 0x3232); il[r] = __byte_perm(hr, hr, 0x1010);
    }
  }
      #pragma unroll
      for (int j = 0; j < H_SPLIT; j++) norm(j);
      TL_MARK2(5, t2 == 0);
      finish_parts<0, H_SPLIT>(pa, H_PREG, t2, scr + 8192);
      named_bar_sync(5, 256);
      TL_MARK2(7, t2 == 0);
      #pragma unroll
      for (int j = 0; j < H_SPLIT; j++) { modulate(j); store(j); }
      named_bar_arrive(9, 288);
    }
  }
  #pragma unroll
  for (int j = H_SPLIT; j < 4; j++) norm(j);
  float2 pb[4 - H_SPLIT][4];
  finish_parts<H_SPLIT, 4>(pb, false, t2, scr + 8192);
  named_bar_sync(5, 256);
  TL_MARK2(17, t2 == 0);
  #pragma unroll
  for (int j = H_SPLIT; j < 4; j++) modulate(j);
  __syncwarp();
  if (lane == 0) mbar_arrive(b_head + (xv[1][3].w & zero));
  mbar_wait(b_go, 0);
  #pragma unroll
  for (int j = H_SPLIT; j < 4; j++) store(j);
  named_bar_arrive(8, 288);
}

#define MOD_AT (b_empty + 8)
#define MOD_PF 0
#define MOD_SPLIT 16
__device__ __forceinline__ void mod_rest(uint32_t scr, uint32_t b_go, int t, const bf16* __restrict__ cvec, const bf16* __restrict__ w_mod, const bf16* __restrict__ w_r) {
  const int lane = t & 31;
  #pragma unroll 1
  for (int i = t; i < T_D / 2; i += 64) {
    const uint32_t c2 = *reinterpret_cast<const uint32_t*>(cvec + 2 * i);
    sts_u32(scr + i * 4, pack_bf16(silu_bf(bflo(c2)), silu_bf(bfhi(c2))));
  }
  named_bar_sync(11, 64);
  const bf16* wp = w_mod + (size_t)(2 * (t >> 2)) * (6 * T_D) + 2 * T_D + blockIdx.x * 32 + (t & 3) * 8;
  float acc[8];
  #pragma unroll
  for (int i = 0; i < 8; i++) acc[i] = 0.f;
  #pragma unroll 1
  for (int i = 0; i < 32; i += 2) {
    if (i == MOD_SPLIT) mbar_wait(b_go, 0);
    const uint4 w0 = ldg_nc_v4(wp), w1 = ldg_nc_v4(wp + 6 * T_D), w2 = ldg_nc_v4(wp + 32 * 6 * T_D), w3 = ldg_nc_v4(wp + 33 * 6 * T_D);
    wp += 64 * 6 * T_D;
    const uint32_t s0 = lds_u32(scr + (i * 16 + (t >> 2)) * 4), s1 = lds_u32(scr + (i * 16 + 16 + (t >> 2)) * 4);
    fma8(acc, bflo(s0), w0); fma8(acc, bfhi(s0), w1); fma8(acc, bflo(s1), w2); fma8(acc, bfhi(s1), w3);
  }
  #pragma unroll
  for (int j = 0; j < 4; j++) { const bool up = lane & 16; acc[j] = (up ? acc[4 + j] : acc[j]) + __shfl_xor_sync(0xffffffffu, up ? acc[j] : acc[4 + j], 16); }
  #pragma unroll
  for (int j = 0; j < 2; j++) { const bool up = lane & 8; acc[j] = (up ? acc[2 + j] : acc[j]) + __shfl_xor_sync(0xffffffffu, up ? acc[j] : acc[2 + j], 8); }
  { const bool up = lane & 4; acc[0] = (up ? acc[1] : acc[0]) + __shfl_xor_sync(0xffffffffu, up ? acc[0] : acc[1], 4); }
  if (t >= 32) sts_f32(scr + 2048 + lane * 4, acc[0]);
  named_bar_sync(11, 64);
  if (__shfl_sync(0xffffffffu, t, 0) < 32) {
    const int kind = blockIdx.x >> 5;
    float v = rbf(acc[0] + lds_f32(scr + 2048 + lane * 4));
    const int col = (blockIdx.x & 31) * 32 + (lane & 3) * 8 + (lane >> 2);
    uint8_t* dst = g_col + (col >> 7) * 1536;
    if (kind == 2) v = rbf(1.0f + v);
    float vw = v * __bfloat162float(w_r[col]);
    if (kind == 2) {
      const int c = col & 127, i = (c & ~15) + ((c >> 1) & 3) * 4 + ((c >> 3) & 1) * 2 + (c & 1);
      reinterpret_cast<bf16*>(dst)[i] = __float2bfloat16_rn(vw);
      reinterpret_cast<bf16*>(dst)[128 + i] = __float2bfloat16_rn(vw - rbf(vw));
    }
    reinterpret_cast<bf16*>(dst + 512 + (kind & 1) * 512 + (kind >> 1) * 256)[col & 127] = __float2bfloat16_rn(v);
    #pragma unroll
    for (int o = 16; o > 0; o >>= 1) vw += __shfl_xor_sync(0xffffffffu, vw, o);
    if (lane == 0 && (kind == 1 || kind == 2)) g_scal[95 - blockIdx.x] = vw;
  }
  #pragma unroll 1
  for (int i = blockIdx.x * 64 + t; i < (int)(sizeof(g_mail) / 16); i += 128 * 64) reinterpret_cast<uint4*>(&g_mail)[i] = make_uint4(0u, 0u, 0u, 0u);
  named_bar_sync(11, 64);
  if (t == 0) red_release_add(&g_hcnt[0], 1u);
}

#define HPOL_A pol_normal()
#define HPOL_B pol_normal()
#define HMAP_A &tmOl
#define HMAP_B &tmWo
constexpr int AT_NBLK = T_SEQ / 128;
constexpr float AT_HEAD = 7.0f;
#define WO_LATE 12
constexpr int QP_STAG = 3;
constexpr int AT_SPLIT = 28, AT_PIN = 8, PINB = 4;
constexpr int AT_NFULL = 124;
constexpr int AT_PREG = 40, AT_CREG = 232;
constexpr uint32_t AT_SQ = 5 * 32768;
constexpr float AT_C = 0.08838834764831845f * 1.4426950408889634f;
constexpr float AT_RAW_LO = -16.0f, AT_RAW_HI = 24.0f;
constexpr float AT_RAW_SUM = 281474976710656.0f, AT_RAW_MIN = 9.094947017729282e-13f;
constexpr uint32_t AT_SBAR = AT_SQ + 65536 + 256;
constexpr uint32_t AT_SMEM = AT_SQ + 65536 + 3072;

__device__ __forceinline__ uint32_t ring_slot(uint32_t t) { return t - 5u * ((t * 205u) >> 10); }
__device__ __forceinline__ uint32_t qp_pos(uint32_t j, uint32_t it) { return 4u * it + (j & 3u) + ((j & 3u) == 3u ? it : 0u); }
__device__ __forceinline__ uint32_t ring_par(uint32_t t) { return ((t * 205u) >> 10) & 1u; }
__device__ __forceinline__ void softmax_rowmax(const float (&s)[64], float& mx0, float& mx1) {
  float a0 = fmaxf(s[0], s[1]), a1 = fmaxf(s[4], s[5]), a2 = fmaxf(s[8], s[9]), a3 = fmaxf(s[12], s[13]);
  float b0 = fmaxf(s[2], s[3]), b1 = fmaxf(s[6], s[7]), b2 = fmaxf(s[10], s[11]), b3 = fmaxf(s[14], s[15]);
  #pragma unroll
  for (int j = 4; j < 16; j += 4) {
    a0 = fmaxf(a0, fmaxf(s[4 * j + 0], s[4 * j + 1]));  b0 = fmaxf(b0, fmaxf(s[4 * j + 2], s[4 * j + 3]));
    a1 = fmaxf(a1, fmaxf(s[4 * j + 4], s[4 * j + 5]));  b1 = fmaxf(b1, fmaxf(s[4 * j + 6], s[4 * j + 7]));
    a2 = fmaxf(a2, fmaxf(s[4 * j + 8], s[4 * j + 9]));  b2 = fmaxf(b2, fmaxf(s[4 * j + 10], s[4 * j + 11]));
    a3 = fmaxf(a3, fmaxf(s[4 * j + 12], s[4 * j + 13])); b3 = fmaxf(b3, fmaxf(s[4 * j + 14], s[4 * j + 15]));
  }
  mx0 = fmaxf(fmaxf(a0, a1), fmaxf(a2, a3));
  mx1 = fmaxf(fmaxf(b0, b1), fmaxf(b2, b3));
  mx0 = fmaxf(mx0, __shfl_xor_sync(0xffffffffu, mx0, 1));
  mx1 = fmaxf(mx1, __shfl_xor_sync(0xffffffffu, mx1, 1));
  mx0 = fmaxf(mx0, __shfl_xor_sync(0xffffffffu, mx0, 2));
  mx1 = fmaxf(mx1, __shfl_xor_sync(0xffffffffu, mx1, 2));
}
__device__ __forceinline__ void softmax_sub(float (&s)[64], float mc0, float mc1) {
  #pragma unroll
  for (int j = 0; j < 16; j++) { s[4 * j] -= mc0; s[4 * j + 1] -= mc0; s[4 * j + 2] -= mc1; s[4 * j + 3] -= mc1; }
}
template <int LO, int HI>
__device__ __forceinline__ void softmax_exp(float (&s)[64]) {
  #pragma unroll
  for (int i = LO; i < HI; i++) s[i] = ex2_approx(s[i]);
}
__device__ __forceinline__ bool softmax_mode(const float (&s)[64], float& mc0, float& mc1) {
  softmax_rowmax(s, mc0, mc1);
  const bool raw = __all_sync(0xffffffffu, mc0 >= AT_RAW_LO && mc0 <= AT_RAW_HI && mc1 >= AT_RAW_LO && mc1 <= AT_RAW_HI);
  mc0 += AT_HEAD; mc1 += AT_HEAD;
  return raw;
}
__device__ __forceinline__ void rowsum_p(const uint32_t (&p)[32], uint32_t& t0, uint32_t& t1) {
  uint32_t a[16];
  #pragma unroll
  for (int i = 0; i < 8; i++) { a[2 * i] = badd2(p[4 * i], p[4 * i + 2]); a[2 * i + 1] = badd2(p[4 * i + 1], p[4 * i + 3]); }
  #pragma unroll
  for (int i = 0; i < 4; i++) { a[2 * i] = badd2(a[4 * i], a[4 * i + 2]); a[2 * i + 1] = badd2(a[4 * i + 1], a[4 * i + 3]); }
  t0 = badd2(badd2(a[0], a[2]), badd2(a[4], a[6]));
  t1 = badd2(badd2(a[1], a[3]), badd2(a[5], a[7]));
}
__device__ __forceinline__ void add_rowsum(const uint32_t (&p)[32], float& l0, float& l1) {
  uint32_t t0, t1;
  rowsum_p(p, t0, t1);
  l0 += bflo(t0) + bfhi(t0); l1 += bflo(t1) + bfhi(t1);
}
__device__ __forceinline__ void pack_p(uint32_t (&p)[32], const float (&s)[64]) {
  #pragma unroll
  for (int i = 0; i < 32; i++) p[i] = pack_bf16(s[2 * i], s[2 * i + 1]);
}
__device__ __noinline__ void attn_rows_exact(uint32_t sq, uint32_t so, int hsel, const bf16* __restrict__ kh, const bf16* __restrict__ vh) {
  const int warp = (threadIdx.x >> 5) & 3, lane = threadIdx.x & 31;
  const size_t hofs = (size_t)((blockIdx.x < 128 ? blockIdx.x >> 4 : 15) * 2 + hsel) * T_SEQ * T_DH;
  kh += hofs; vh += hofs;
  #pragma unroll 1
  for (int r = 16 * warp; r < 16 * warp + 16; r++) {
    const uint32_t ad = (lane >> 4) * 16384 + r * 128 + ((((lane & 15) >> 1) ^ (r & 7)) << 4) + (lane & 1) * 8;
    uint2 qv; asm volatile("ld.shared.v2.u32 {%0, %1}, [%2];" : "=r"(qv.x), "=r"(qv.y) : "r"(sq + ad) : "memory");
    const float q0 = bflo(qv.x), q1 = bfhi(qv.x), q2 = bflo(qv.y), q3 = bfhi(qv.y);
    float m = -INFINITY, l = 0.f, o0 = 0.f, o1 = 0.f, o2 = 0.f, o3 = 0.f;
    #pragma unroll 1
    for (int key = 0; key < T_SEQ; key++) {
      const uint2 kv = *reinterpret_cast<const uint2*>(kh + (size_t)key * T_DH + lane * 4);
      const uint2 vv = *reinterpret_cast<const uint2*>(vh + (size_t)key * T_DH + lane * 4);
      float sc = (q0 * bflo(kv.x) + q1 * bfhi(kv.x)) + (q2 * bflo(kv.y) + q3 * bfhi(kv.y));
      #pragma unroll
      for (int o = 16; o > 0; o >>= 1) sc += __shfl_xor_sync(0xffffffffu, sc, o);
      const float mn = fmaxf(m, sc);
      const float al = (m == mn) ? 1.0f : ex2_approx(m - mn), p = rbf(ex2_approx(sc - mn));
      m = mn;
      l = fmaf(l, al, p);
      o0 = fmaf(o0, al, p * bflo(vv.x)); o1 = fmaf(o1, al, p * bfhi(vv.x));
      o2 = fmaf(o2, al, p * bflo(vv.y)); o3 = fmaf(o3, al, p * bfhi(vv.y));
    }
    const float inv = rcp_approx(l);
    asm volatile("st.shared.v2.u32 [%0], {%1, %2};" :: "r"(so + ad), "r"(pack_bf16(o0 * inv, o1 * inv)), "r"(pack_bf16(o2 * inv, o3 * inv)) : "memory");
  }
}
__device__ __forceinline__ void issue_qk(float (&s)[64], const uint32_t (&q)[32], uint32_t k_lo) {
  wgmma_fence();
  wgmma_m64n128k16_rs<0>(s, q[0], q[1], q[2], q[3], k_lo, 0);
  wgmma_m64n128k16_rs<2>(s, q[4], q[5], q[6], q[7], k_lo, 1);
  wgmma_m64n128k16_rs<4>(s, q[8], q[9], q[10], q[11], k_lo, 1);
  wgmma_m64n128k16_rs<6>(s, q[12], q[13], q[14], q[15], k_lo, 1);
  wgmma_m64n128k16_rs<1024>(s, q[16], q[17], q[18], q[19], k_lo, 1);
  wgmma_m64n128k16_rs<1026>(s, q[20], q[21], q[22], q[23], k_lo, 1);
  wgmma_m64n128k16_rs<1028>(s, q[24], q[25], q[26], q[27], k_lo, 1);
  wgmma_m64n128k16_rs<1030>(s, q[28], q[29], q[30], q[31], k_lo, 1);
  wgmma_commit();
}
__device__ __forceinline__ void issue_pv(float (&o)[64], const uint32_t (&p)[32], uint32_t v_lo, int accumulate) {
  wgmma_fence();
  wgmma_m64n128k16_rs_tb<0>(o, p[0], p[1], p[2], p[3], v_lo, accumulate);
  wgmma_m64n128k16_rs_tb<128>(o, p[4], p[5], p[6], p[7], v_lo, 1);
  wgmma_m64n128k16_rs_tb<256>(o, p[8], p[9], p[10], p[11], v_lo, 1);
  wgmma_m64n128k16_rs_tb<384>(o, p[12], p[13], p[14], p[15], v_lo, 1);
  wgmma_m64n128k16_rs_tb<512>(o, p[16], p[17], p[18], p[19], v_lo, 1);
  wgmma_m64n128k16_rs_tb<640>(o, p[20], p[21], p[22], p[23], v_lo, 1);
  wgmma_m64n128k16_rs_tb<768>(o, p[24], p[25], p[26], p[27], v_lo, 1);
  wgmma_m64n128k16_rs_tb<896>(o, p[28], p[29], p[30], p[31], v_lo, 1);
  wgmma_commit();
}
__device__ __forceinline__ void block_end(uint32_t zero, uint32_t bar) {
  #pragma unroll 1
  for (uint32_t i = 0; i < zero; i++) mbar_arrive(bar);
}
__device__ __forceinline__ void rescale_o(float (&o)[64], float al0, float al1) {
  #pragma unroll
  for (int j = 0; j < 16; j++) { o[4 * j] *= al0; o[4 * j + 1] *= al0; o[4 * j + 2] *= al1; o[4 * j + 3] *= al1; }
}

__device__ __forceinline__ void stage_o(const float (&o)[64], float i0, float i1, uint32_t dst, int lane) {
  #pragma unroll
  for (int J = 0; J < 16; J += 2)
    stmatrix_x4(dst + (J >> 3) * 16384 + ((((J & 7) + (lane >> 4)) ^ (lane & 7)) << 4),
                pack_bf16(o[4 * J + 0] * i0, o[4 * J + 1] * i0), pack_bf16(o[4 * J + 2] * i1, o[4 * J + 3] * i1),
                pack_bf16(o[4 * J + 4] * i0, o[4 * J + 5] * i0), pack_bf16(o[4 * J + 6] * i1, o[4 * J + 7] * i1));
}
__device__ __forceinline__ bool finish_l(float& l0, float& l1) {
  l0 += __shfl_xor_sync(0xffffffffu, l0, 1); l1 += __shfl_xor_sync(0xffffffffu, l1, 1);
  l0 += __shfl_xor_sync(0xffffffffu, l0, 2); l1 += __shfl_xor_sync(0xffffffffu, l1, 2);
  const bool redo = __any_sync(0xffffffffu, !(l0 <= AT_RAW_SUM && l1 <= AT_RAW_SUM && l0 >= AT_RAW_MIN && l1 >= AT_RAW_MIN));
  l0 = rcp_approx(l0); l1 = rcp_approx(l1);
  return redo;
}
template <int J0>
__device__ __forceinline__ void stage_q(const float (&acc)[128], float c, uint32_t dst, int lane) {
  #pragma unroll
  for (int J = J0; J < J0 + 16; J += 2)
    stmatrix_x4(dst + (J >> 3) * 16384 + ((((J & 7) + (lane >> 4)) ^ (lane & 7)) << 4),
                pack_bf16(acc[4 * J + 0] * c, acc[4 * J + 1] * c), pack_bf16(acc[4 * J + 2] * c, acc[4 * J + 3] * c),
                pack_bf16(acc[4 * J + 4] * c, acc[4 * J + 5] * c), pack_bf16(acc[4 * J + 6] * c, acc[4 * J + 7] * c));
}
__device__ __forceinline__ void store_o(const CUtensorMap* tmO, uint32_t src, int head, int row) {
  tma_store_2d(tmO, src, head * T_DH, row);
  tma_store_2d(tmO, src + 16384, head * T_DH + 64, row);
  bulk_commit();
}
__device__ __forceinline__ void mma_bf16(float (&d)[4], uint32_t a0, uint32_t a1, uint32_t a2, uint32_t a3, uint32_t b0, uint32_t b1) {
  asm volatile("mma.sync.aligned.m16n8k16.row.col.f32.bf16.bf16.f32 {%0, %1, %2, %3}, {%4, %5, %6, %7}, {%8, %9}, {%0, %1, %2, %3};"
               : "+f"(d[0]), "+f"(d[1]), "+f"(d[2]), "+f"(d[3]) : "r"(a0), "r"(a1), "r"(a2), "r"(a3), "r"(b0), "r"(b1));
}
struct GemvSel { uint32_t lo0, hi0, lo1, hi1; };
__device__ __forceinline__ GemvSel gemv_sel(int lane) {
  const uint32_t lo = (lane & 8) ? 0x1044u : 0x4410u, hi = (lane & 8) ? 0x3244u : 0x4432u;
  GemvSel s; s.lo0 = (lane & 16) ? 0x4444u : lo; s.hi0 = (lane & 16) ? 0x4444u : hi; s.lo1 = (lane & 16) ? lo : 0x4444u; s.hi1 = (lane & 16) ? hi : 0x4444u;
  return s;
}
#define GEMV_B0(j, h, s) __byte_perm((j) < 2 ? (h).x : (h).y, 0u, ((j) & 1) ? (s).hi0 : (s).lo0)
#define GEMV_B1(j, h, s) __byte_perm((j) < 2 ? (h).x : (h).y, 0u, ((j) & 1) ? (s).hi1 : (s).lo1)
__device__ __forceinline__ float4 gemv_out(const float (&d)[4], int lane) {
  const bool tk = lane & 1;
  const float r0 = __shfl_xor_sync(0xffffffffu, tk ? d[0] : d[1], 1), r1 = __shfl_xor_sync(0xffffffffu, tk ? d[2] : d[3], 1);
  return tk ? make_float4(r0, d[1], r1, d[3]) : make_float4(d[0], r0, d[2], r1);
}
#define OG_NG 8
#define HOIST 1
#define PUT_N 2
#define H_STAG 2
#define NOZERO 1
#define PVPIN 0
#define QKPIN 0
#define ALIGN 1
#define AL_P 60
#define AL_SLEEP 1200
#define AL_MAX 800
#define AL_ADD 0
#define X_PF 0
#define POLL_NS 200
#define KV3D 1
#define W3D 1
#define OG_PRE 10
#define OG_JOBS 7
#define OG_GRP 7
#define LD_FIRST 1
#define LD_STAG (OG_GRP / 2)
constexpr int OG_ST = 5, OG_NKB = T_DQKV / 64 - OG_PRE, OG_MOE = T_F / 32;
__device__ __forceinline__ int pre_loc(int job) {
  const int step = ((job >> 4) << 2) + (job & 3);
  return (step < OG_JOBS ? 2 * step : step < 2 * OG_JOBS ? 2 * (step - OG_JOBS) + 1 : step) * 4 + ((job >> 2) & 3);
}
__device__ __forceinline__ int pre_kb(int i) { return (i >> 1) * 4 + (i & 1); }
__device__ __forceinline__ int own_kb(int i) { return i < (OG_PRE & ~1) ? pre_kb(i) + 2 : i + OG_PRE; }
constexpr int OG_POS = 8;
constexpr uint32_t OG_STAGE = 32768;
constexpr uint32_t OG_SCOL = AT_SBAR + 512;
constexpr uint32_t OG_SMISC = AT_SBAR + 2048;
constexpr int OG_XPOS = OG_POS + OG_NKB;
constexpr uint32_t OG_SWD = AT_SQ, OG_PSLOT = AT_SQ;
constexpr uint32_t OG_SWD1 = (OG_XPOS % OG_ST) * OG_STAGE;
constexpr uint32_t OG_XSLOT = AT_SQ + 32768;
constexpr uint32_t OG_OSLOT = ((OG_XPOS + 1) % OG_ST) * OG_STAGE;
constexpr uint32_t OG_SH2 = ((OG_XPOS + 2) % OG_ST) * OG_STAGE;
constexpr uint32_t OG_SRED = ((OG_XPOS + 3) % OG_ST) * OG_STAGE;
constexpr uint32_t OG_SSTAT = OG_SRED + 16384;
constexpr uint32_t OG_SGU = OG_SRED + 8192;
constexpr uint32_t OG_SFIN = OG_SGU + 256;
#define OGM 2
#define OG_MT(b) (((b) >> OGM) & 15)
#define OG_NT(b) (((b) & ((1 << OGM) - 1)) + (((b) >> (4 + OGM)) << OGM))
#define TAIL_SETUP \
  const uint32_t bar_full = sbase + AT_SBAR, bar_empty = bar_full + 40; \
  const uint32_t bar_wd = bar_full + 168, bar_col = bar_full + 176, bar_out = bar_full + 184, bar_end = bar_full + 192; \
  const uint32_t bar_key = bar_full + 200, bar_h2 = bar_full + 208, bar_sel = bar_full + 216; \
  const int mt = OG_MT(blockIdx.x), nt = OG_NT(blockIdx.x); \
  const int m0 = mt * 128, n0 = nt * 128; \
  const bool has_moe = (int)blockIdx.x < OG_MOE; \
  (void)bar_empty; (void)bar_wd; (void)bar_col; (void)bar_out; (void)bar_end; (void)bar_key; (void)bar_h2; (void)bar_sel; (void)m0; (void)n0; (void)has_moe;

__device__ __forceinline__ void tail_producer(uint32_t sbase, uint32_t ph, uint64_t pol, const CUtensorMap* tmA, const CUtensorMap* tmB, const CUtensorMap* tmX) {
  TAIL_SETUP
  uint32_t stage = OG_POS % OG_ST;
  int kb = 0;
  #pragma unroll 1
  for (int seg = 0; seg < 2; seg++) {
    mbar_wait(bar_full + 264, seg);
    fence_proxy_async_global();
    const int end = seg == 0 ? 32 - OG_PRE : OG_NKB;
    #pragma unroll 1
    for (; kb < end; kb++) {
      const uint32_t fb = bar_full + 8 * stage, sa = sbase + stage * OG_STAGE;
      const int k0 = own_kb(kb) * 64;
      mbar_wait(bar_empty + 8 * stage, ph);
      mbar_expect_tx(fb, OG_STAGE);
      tma_load_3d_hint(sa + 16384, tmB, k0, 2 * nt, fb, pol);
      tma_load_2d_hint(sa, tmA, k0, m0, fb, pol);
      if (++stage == OG_ST) { stage = 0; ph ^= 1; }
    }
  }
  if (has_moe) {
    mbar_wait(bar_empty + 8 * (OG_XPOS % OG_ST), ph);
    mbar_expect_tx(bar_wd, OG_STAGE);
    tma_load_3d_hint(sbase + OG_SWD1, tmX, blockIdx.x * 32, 8, bar_wd, pol);
  }
}

__device__ __forceinline__ uint32_t out2(uint32_t x1, uint32_t mb2, uint32_t ih, uint32_t il, uint32_t c1, uint32_t sb, uint32_t gb) {
  const uint32_t h2 = badd2(bmul2(ln_norm2b(x1, mb2, ih, il), c1), sb);
  return badd2(x1, bmul2(gb, bfma2(h2, 0u, h2)));
}
#define OGTIME gtime()
#define PRE_N 1
#define PRE_PACE 150
#define X_PACE 200
#define WD_LATE 0
#define WD_PACE 300
__device__ __forceinline__ void tail_exchange(uint32_t sbase, const CUtensorMap* tmOut, const bf16* __restrict__ w_down, const bf16* __restrict__ w_r, const bf16* __restrict__ x, bf16* __restrict__ out) {
    TAIL_SETUP
    const int lane = threadIdx.x & 31, wi = __shfl_sync(0xffffffffu, threadIdx.x >> 5, 0);
    if (wi == 3) {
      mbar_wait(bar_full + 264, 0);
      if (blockIdx.x < AT_NFULL) {
        uint32_t a, b;
        asm volatile("ld.relaxed.gpu.global.u32 %0, [%1];" : "=r"(a) : "l"(g_smid + 32 + blockIdx.x - lane) : "memory");
        b = __shfl_down_sync(0xffffffffu, a, 1);
        unsigned int* tm = g_tmax + blockIdx.x - min((int)blockIdx.x, __ffs(__ballot_sync(0xffffffffu, b >= a)) - 1);
        mbar_wait(bar_full + 312, 0);
        if (lane == 0) {
          asm volatile("mov.u32 %0, %%globaltimer_lo;" : "=r"(a));
          asm volatile("red.relaxed.gpu.global.max.u32 [%0], %1;" :: "l"(tm), "r"(a) : "memory");
          __nanosleep(AL_SLEEP);
          asm volatile("ld.relaxed.gpu.global.u32 %0, [%1];" : "=r"(b) : "l"(tm) : "memory");
          b -= a;
          sts_u32(sbase + OG_SMISC + 32, (b < AL_MAX ? b * 13 / 8 : 0u) + AL_ADD);
          mbar_arrive(bar_full + 320);
        }
        named_bar_sync(15, 32);
      }
      mbar_wait(bar_full + 264, 1);
      float a = g_scal[lane], b = g_scal[32 + lane];
      #pragma unroll
      for (int i = 0; i < 3; i++) {
        const uint4 v = *reinterpret_cast<const uint4*>(g_col + nt * 1536 + i * 512 + lane * 16);
        sts_u32x4(sbase + OG_SCOL + i * 512 + lane * 16, v.x, v.y, v.z, v.w);
      }
      #pragma unroll
      for (int o = 16; o > 0; o >>= 1) { a += __shfl_xor_sync(0xffffffffu, a, o); b += __shfl_xor_sync(0xffffffffu, b, o); }
      if (lane == 0) sts_f32x2(sbase + OG_SMISC, a, b);
      const uint64_t pol = policy_evict_first();
      #pragma unroll 1
      for (int r = lane >> 4; r < 128; r += 4) {
        __nanosleep(X_PACE);
        #pragma unroll
        for (int j = 0; j < 4; j += 2)
          asm volatile("cp.async.cg.shared.global.L2::cache_hint [%0], [%1], 16, %2;" :: "r"(sbase + OG_XSLOT + (lane & 8) * 2048 + (r + j) * 128 + (((lane ^ (r + j)) & 7) << 4)),
                       "l"(x + (size_t)(m0 + r + j) * T_D + n0 + (lane & 15) * 8), "l"(pol) : "memory");
      }
      asm volatile("cp.async.wait_all;" ::: "memory");
      __syncwarp();
      if (lane == 0) mbar_arrive(bar_col);
    } else if (wi == 2) {
      if (elect_one()) {
        const uint32_t b_free = bar_full + (blockIdx.x < AT_NFULL ? 80 : 160);
        mbar_wait(b_free, 0); mbar_wait(b_free, 1);
        #pragma unroll 1
        for (unsigned int i = 0; i < (1u << 20) && ld_acquire(&g_hcnt[32 * (1 + mt) + 4 + (nt >> 1)]) == 0u; i++) __nanosleep(POLL_NS);
        TL_MARK2(23, true);
        fence_proxy_async_global();
        TL_MARK2(4, true);
        mbar_expect_tx(bar_full + 272, 32768);
        #pragma unroll 1
        for (int i = 0; i < PRE_N; i++) {
          bulk_load_hint(sbase + OG_PSLOT + i * (32768 / PRE_N), g_pre + pre_loc(mt * 4 + (nt >> 1)) * 4096 + (nt & 1) * 2048 + i * (2048 / PRE_N), 32768 / PRE_N,
                         bar_full + 272, policy_evict_first());
          if (PRE_N > 1) __nanosleep(PRE_PACE);
        }
      }
      named_bar_sync(14, 32);
      if (has_moe) {
        mbar_wait(bar_full + 96, 1); mbar_wait(bar_full + 304, 0);
        const uint64_t pol = policy_evict_first();
        #pragma unroll 1
        for (int r = 0; r < 32; r++) {
          __nanosleep(WD_PACE);
          #pragma unroll
          for (int j = 0; j < 2; j++)
            asm volatile("cp.async.cg.shared.global.L2::cache_hint [%0], [%1], 16, %2;" :: "r"(sbase + OG_SWD + (4 * j + (lane >> 3)) * 4096 + r * 128 + (((lane ^ r) & 7) << 4)),
                         "l"((const uint8_t*)w_down + (size_t)blockIdx.x * 65536 + r * 2048 + j * 512 + lane * 16), "l"(pol) : "memory");
        }
        asm volatile("cp.async.wait_all;" ::: "memory");
        __syncwarp();
        if (lane == 0) mbar_arrive(bar_wd);
      }
    }
    const uint4 wrv = ldg_nc_v4(w_r + threadIdx.x * 8);
    mbar_wait(bar_end, 0);
    TL_MARK2(22, lane == 0);
    if (wi == 0) {
      uint32_t k1 = 0u, k2 = 0u;
      #pragma unroll 1
      for (unsigned int spin = 0; spin < (1u << 22) && __any_sync(0xffffffffu, k1 == 0u); spin++) asm volatile("ld.relaxed.gpu.global.u32 %0, [%1];" : "=r"(k1) : "l"(g_key + lane) : "memory");
      TL_MARK2(28, lane == 0);
      warp_top2(k1, k2);
      if (lane == 0) {
        const uint32_t r1 = 0xffffu - (k1 & 0xffffu), r2 = 0xffffu - (k2 & 0xffffu);
        sts_u32x4(sbase + OG_SMISC + 64, r1, r2, (r1 >> 7) * 2, (r2 >> 7) * 2 + ((r1 >> 7) == (r2 >> 7)));
        mbar_arrive(bar_sel);
      }
    } else if (wi < 3) {
          mbar_wait(bar_key, 0);
          const uint4 kk = lds_u32x4(sbase + OG_SSTAT + 1024 + lane * 16);
          uint32_t k1 = max(kk.x, kk.y), k2 = min(kk.x, kk.y);
          k2 = max(max(k2, min(kk.z, kk.w)), min(k1, max(kk.z, kk.w))); k1 = max(k1, max(kk.z, kk.w));
          warp_top2(k1, k2);
          if (wi == 1) {
            if (lane == 0 && nt == (mt & 7)) st_relaxed2(g_key + mt * 2, k1, k2);
            TL_MARK2(27, lane == 0);
          } else {
            const uint32_t r = (~((lane & 16) ? k2 : k1)) & 127u, ch = lane & 15;
            const uint2 st = lds_u32x2(sbase + OG_SSTAT + r * 8);
            const uint4 xc = lds_u32x4(sbase + OG_XSLOT + (ch >> 3) * 16384 + r * 128 + (((ch ^ r) & 7) << 4));
            const uint4 c1 = lds_u32x4(sbase + OG_SCOL + 768 + ch * 16), sh = lds_u32x4(sbase + OG_SCOL + 1024 + ch * 16);
            const float inr = __uint_as_float(st.y);
            float* dst = reinterpret_cast<float*>(g_cand + (mt * 2 + (lane >> 4)) * 256 + nt * 16 + ch);
            st_tagged4(dst + 512, __uint_as_float(ln_mod2(xc.x, st.x, inr, c1.x, sh.x)), __uint_as_float(ln_mod2(xc.y, st.x, inr, c1.y, sh.y)),
                       __uint_as_float(ln_mod2(xc.z, st.x, inr, c1.z, sh.z)), __uint_as_float(ln_mod2(xc.w, st.x, inr, c1.w, sh.w)));
            st_tagged4(dst, __uint_as_float(xc.x), __uint_as_float(xc.y), __uint_as_float(xc.z), __uint_as_float(xc.w));
          }
    }
    mbar_wait(bar_sel, 0);
    const uint4 sel = lds_u32x4(sbase + OG_SMISC + 64);
    const int sel0 = (int)sel.x, sel1 = (int)sel.y;
    {
      const float* src0 = reinterpret_cast<const float*>(g_cand + sel.z * 256 + 128 + threadIdx.x);
      const float* src1 = reinterpret_cast<const float*>(g_cand + sel.w * 256 + 128 + threadIdx.x);
      float4 h0, h1;
      #pragma unroll 1
      for (unsigned int spin = 0; spin < (1u << 20); spin++) { h0 = ld_tagged4(src0); h1 = ld_tagged4(src1); if (__all_sync(0xffffffffu, tagged4(h0) & tagged4(h1))) break; }
      sts_f32x4(sbase + OG_SH2 + threadIdx.x * 16, h0.x, h0.y, h0.z, h0.w);
      sts_f32x4(sbase + OG_SH2 + 2048 + threadIdx.x * 16, h1.x, h1.y, h1.z, h1.w);
      __syncwarp();
      if (lane == 0) mbar_arrive(bar_h2);
      TL_MARK2(12, lane == 0);
      if (blockIdx.x >> 6) h0 = h1;
      float v[8], wr[8];
      unpack8(make_uint4(__float_as_uint(h0.x), __float_as_uint(h0.y), __float_as_uint(h0.z), __float_as_uint(h0.w)), v); unpack8(wrv, wr);
      float r = 0.f;
      #pragma unroll
      for (int i = 0; i < 8; i++) r = fmaf(v[i], wr[i], r);
      #pragma unroll
      for (int o = 16; o > 0; o >>= 1) r += __shfl_xor_sync(0xffffffffu, r, o);
      if (lane == 0) sts_f32(sbase + OG_SMISC + 192 + wi * 4, r);
    }
    mbar_wait(bar_out, 0);
    if ((sel0 >> 7) == mt || (sel1 >> 7) == mt) {
      #pragma unroll 2
      for (int i = 0; i < 16; i++) {
        const int r = i * 8 + (threadIdx.x >> 4), ch = threadIdx.x & 15;
        if (m0 + r != sel0 && m0 + r != sel1)
          *reinterpret_cast<uint4*>(out + (size_t)(m0 + r) * T_D + n0 + ch * 8) =
              lds_u32x4(sbase + OG_OSLOT + (ch >> 3) * 16384 + r * 128 + (((ch & 7) ^ (r & 7)) << 4));
      }
    } else if (threadIdx.x == 0) {
      tma_store_2d(tmOut, sbase + OG_OSLOT, n0, m0);
      tma_store_2d(tmOut, sbase + OG_OSLOT + 16384, n0 + 64, m0);
      bulk_commit();
    }
    if (blockIdx.x == 0 && threadIdx.x < 68) *reinterpret_cast<uint4*>(g_hcnt + 32 * (threadIdx.x >> 2) + 4 * (threadIdx.x & 3)) = make_uint4(0u, 0u, 0u, 0u);
    if (threadIdx.x < 64) g_modpart[blockIdx.x * 64 + threadIdx.x] = 0.f;
    if (ALIGN && threadIdx.x == 64) g_tmax[blockIdx.x] = 0u;
    {
      const int tk = blockIdx.x >> 6, c0 = (blockIdx.x & 63) * 16;
      const uint32_t gb2 = *reinterpret_cast<const uint32_t*>(g_col + (c0 >> 7) * 1536 + 512 + 768 + ((c0 & 127) + (threadIdx.x & 14)) * 2);
      const uint32_t* xp = reinterpret_cast<const uint32_t*>(g_cand + (tk ? sel.w : sel.z) * 256) + ((c0 + (threadIdx.x & 14)) >> 1);
      uint32_t x2 = 0u;
      #pragma unroll 1
      for (unsigned int spin = 0; spin < (1u << 20) && __any_sync(0xffffffffu, x2 == 0u); spin++) asm volatile("ld.relaxed.gpu.global.u32 %0, [%1];" : "=r"(x2) : "l"(xp) : "memory");
      const float* src = g_ypart + (size_t)((threadIdx.x >> 2) * 2 + tk) * T_D + c0 + (threadIdx.x & 3) * 4;
      const bool four = threadIdx.x < (OG_MOE - 96) * 4;
      if (threadIdx.x == 0) hint_wait(CNT_Y, (uint32_t)OG_MOE);
      named_bar_sync(10, 128);
      float4 p0, p1, p2, p3;
      #pragma unroll 1
      for (unsigned int spin = 0; spin < (1u << 20); spin++) {
        p0 = ld_tagged4(src); p1 = ld_tagged4(src + 64 * T_D); p2 = ld_tagged4(src + 128 * T_D); p3 = ld_tagged4(four ? src + 192 * T_D : src);
        if (__all_sync(0xffffffffu, tagged4(p0) & tagged4(p1) & tagged4(p2) & tagged4(p3))) break;
      }
      if (four) { p2.x += p3.x; p2.y += p3.y; p2.z += p3.z; p2.w += p3.w; }
      p0.x = (p0.x + p1.x) + p2.x; p0.y = (p0.y + p1.y) + p2.y; p0.z = (p0.z + p1.z) + p2.z; p0.w = (p0.w + p1.w) + p2.w;
      #pragma unroll
      for (int o = 4; o <= 16; o <<= 1) {
        p0.x += __shfl_xor_sync(0xffffffffu, p0.x, o); p0.y += __shfl_xor_sync(0xffffffffu, p0.y, o);
        p0.z += __shfl_xor_sync(0xffffffffu, p0.z, o); p0.w += __shfl_xor_sync(0xffffffffu, p0.w, o);
      }
      if (lane < 4) sts_f32x4(sbase + OG_SFIN + (threadIdx.x >> 5) * 64 + lane * 16, p0.x, p0.y, p0.z, p0.w);
      named_bar_sync(10, 128);
      TL_MARK2(21, threadIdx.x == 0);
      if (threadIdx.x < 16) {
        const uint32_t ya = sbase + OG_SFIN + threadIdx.x * 4, rp = sbase + OG_SMISC + 192;
        float y = (lds_f32(ya) + lds_f32(ya + 64)) + (lds_f32(ya + 128) + lds_f32(ya + 192));
        const float r = rbf((lds_f32(rp) + lds_f32(rp + 4)) + (lds_f32(rp + 8) + lds_f32(rp + 12)));
        const float rs = rbf(sigmoid_f(r));
        const uint32_t h2p = lds_u32(sbase + OG_SH2 + tk * 2048 + (c0 + (threadIdx.x & 14)) * 2);
        const float fh = (lane & 1) ? bfhi(h2p) : bflo(h2p);
        y = rbf(y);
        y = rbf(y * rs);
        const float upd = rbf(rbf(fh * 0.0f) + y);
        out[(size_t)(tk ? sel1 : sel0) * T_D + c0 + threadIdx.x] =
            __float2bfloat16_rn(((lane & 1) ? bfhi(x2) : bflo(x2)) + rbf(((lane & 1) ? bfhi(gb2) : bflo(gb2)) * rbf(fh + upd)));
      }
      if (threadIdx.x == 0) bulk_wait_read<0>();
    }
    TL_END(4, threadIdx.x == 0);
}

__device__ __forceinline__ void load_pre(uint4* pre, uint32_t sbase, uint32_t buf, int t2) {
  mbar_wait(sbase + AT_SBAR + 272, 0);
  #pragma unroll
  for (int i = 0; i < 8; i++) pre[i] = lds_u32x4(sbase + buf + i * 4096 + t2 * 16);
}
__device__ __forceinline__ void tail_consumer(uint32_t sbase, const uint4 (&pre)[8], int cwg, const bf16* __restrict__ w_gate, const bf16* __restrict__ w_up) {
    TAIL_SETUP
    const int tid = threadIdx.x & 127, t2 = threadIdx.x - 128;
    const int warp = tid >> 5, lane = tid & 31, w8 = t2 >> 5;
    const uint32_t dbase = (sbase & 0x3FFFFu) >> 4;
    const uint32_t a_base = dbase + ((cwg * 8192) >> 4) + (1u << 16);
    const uint32_t b_base = dbase + (16384 >> 4) + (512u << 16);
    TL_MARK2(25, threadIdx.x == 128);
    const uint64_t pol = policy_evict_first();
    const bf16* pw = ((lane & 16) ? w_up : w_gate) + (size_t)(w8 * 128 + (lane & 3) * 4) * T_F + (has_moe ? blockIdx.x : 0) * 32 + ((lane >> 2) & 3) * 8;
    uint4 wv[32];
    float acc[64];
    #pragma unroll
    for (int i = 0; i < 8; i++) {
      acc[8 * i] = bflo(pre[i].x); acc[8 * i + 1] = bfhi(pre[i].x); acc[8 * i + 2] = bflo(pre[i].y); acc[8 * i + 3] = bfhi(pre[i].y);
      acc[8 * i + 4] = bflo(pre[i].z); acc[8 * i + 5] = bfhi(pre[i].z); acc[8 * i + 6] = bflo(pre[i].w); acc[8 * i + 7] = bfhi(pre[i].w);
    }
    if (blockIdx.x < AT_NFULL) {
      const uint32_t c0 = clock_lo();
      mbar_wait(bar_full + 320, 0);
      const uint32_t d = lds_u32(sbase + OG_SMISC + 32);
      while (clock_lo() - c0 < d) {}
    }
    {
      uint32_t stage = OG_POS % OG_ST, phase = (OG_POS / OG_ST) & 1, prev = 12;
      int kb = 0;
      #pragma unroll
      for (int g = 0; g <= OG_NG; g++) {
        const int end = g == OG_NG ? OG_NKB : LD_FIRST + g * OG_GRP + LD_STAG * cwg;
        #pragma unroll 1
        do {
          mbar_wait(bar_full + 8 * stage, phase);
          const uint32_t a_lo = a_base + stage * (OG_STAGE >> 4), b_lo = b_base + stage * (OG_STAGE >> 4);
          wgmma_fence();
          wgmma_m64n128k16_ss_tb<0, 0>(acc, a_lo, b_lo, 1);
          wgmma_m64n128k16_ss_tb<2, 128>(acc, a_lo, b_lo, 1);
          wgmma_m64n128k16_ss_tb<4, 256>(acc, a_lo, b_lo, 1);
          wgmma_m64n128k16_ss_tb<6, 384>(acc, a_lo, b_lo, 1);
          wgmma_commit();
          wgmma_wait<1>();
          if (tid == 0) mbar_arrive(bar_empty + 8 * prev);
          prev = stage;
          if (++stage == OG_ST) { stage = 0; phase ^= 1; }
        } while (++kb < end);
        #pragma unroll
        for (int j = 4 * g; j < 4 * g + 4 && j < 32; j++) wv[j] = ldg_stream_v4(pw + (size_t)(16 * (j >> 2) + (j & 3)) * T_F, pol);
      }
    }
    mbar_wait(bar_col, 0);
    if (__builtin_expect(!has_moe, 0)) {
      load_pre(wv, sbase, AT_SQ, t2);
    }
    wgmma_wait<0>();
    fence_regs(acc);
    if (__builtin_expect(!has_moe, 0)) {
      #pragma unroll
      for (int i = 0; i < 8; i++) {
        acc[8 * i] += bflo(wv[i].x); acc[8 * i + 1] += bfhi(wv[i].x); acc[8 * i + 2] += bflo(wv[i].y); acc[8 * i + 3] += bfhi(wv[i].y);
        acc[8 * i + 4] += bflo(wv[i].z); acc[8 * i + 5] += bfhi(wv[i].z); acc[8 * i + 6] += bflo(wv[i].w); acc[8 * i + 7] += bfhi(wv[i].w);
      }
    }
    if (tid == 0) mbar_arrive(bar_end);
    TL_MARK2(9, lane == 0);
    const int q2 = 2 * (lane & 3);
    const uint32_t frag = (64 * cwg + 16 * warp + (lane & 7) + 8 * ((lane >> 3) & 1)) * 128;
    const int fsw = lane & 7, fhi = lane >> 4;
    {
      float dl[4] = {0.f, 0.f, 0.f, 0.f}, da[4] = {0.f, 0.f, 0.f, 0.f}, db[4] = {0.f, 0.f, 0.f, 0.f};
      const uint32_t tb = sbase + OG_SCOL + (lane & 8) * 32 + (lane & 3) * 8, g = lane >> 2;
      const uint32_t msk = (g == 1 || g == 2) ? 0xffffffffu : 0u, one = g == 0 ? 0x3F803F80u : 0u;
      #pragma unroll
      for (int J = 0; J < 16; J += 2) {
        const uint32_t ad = sbase + OG_XSLOT + (J >> 3) * 16384 + frag + ((((J & 7) + fhi) ^ fsw) << 4);
        uint32_t xr[4];
        ldmatrix_x4(ad, xr[0], xr[1], xr[2], xr[3]);
        const uint2 cw = lds_u32x2(tb + J * 16);
        #pragma unroll
        for (int h = 0; h < 2; h++) {
          const uint32_t ga = lds_u32(sbase + OG_SCOL + 512 + (8 * (J + h) + q2) * 2);
          xr[2 * h] = badd2(xr[2 * h], bmul2(ga, pack_bf16(acc[4 * (J + h)], acc[4 * (J + h) + 1])));
          xr[2 * h + 1] = badd2(xr[2 * h + 1], bmul2(ga, pack_bf16(acc[4 * (J + h) + 2], acc[4 * (J + h) + 3])));
        }
        stmatrix_x4(ad, xr[0], xr[1], xr[2], xr[3]);
        mma_bf16(dl, xr[0], xr[1], xr[2], xr[3], (cw.x & msk) | one, (cw.y & msk) | one);
        mma_bf16(da, xr[0], xr[1], xr[2], xr[3], xr[0], xr[2]);
        mma_bf16(db, xr[0], xr[1], xr[2], xr[3], xr[1], xr[3]);
      }
      {
        const int dsrc = (lane & ~3) + (g >> 1);
        const float qa = __shfl_sync(0xffffffffu, (g & 1) ? da[1] : da[0], dsrc), qb = __shfl_sync(0xffffffffu, (g & 1) ? db[3] : db[2], dsrc);
        const float e0 = __shfl_xor_sync(0xffffffffu, (lane & 1) ? dl[0] : dl[2], 1), e1 = __shfl_xor_sync(0xffffffffu, dl[3], 1);
        if ((lane & 3) < 2) {
          const bool hi = lane & 1;
          st_tagged4(reinterpret_cast<float*>(g_part1 + ((mt * 8 + w8) * 8 + nt) * 16 + g + (hi ? 8 : 0)),
                     hi ? e0 : dl[0], hi ? qb : qa, hi ? e1 + dl[2] : dl[1] + e0, 1.0f);
        }
      }
    }
    TL_MARK2(10, lane == 0);
    uint4 wd[16];
    if (has_moe) mbar_wait(bar_wd, 0);
    #pragma unroll
    for (int i = 0; i < 16; i++) wd[i] = lds_u32x4(sbase + (cwg ? OG_SWD1 : OG_SWD) + warp * 8192 + (i >> 3) * 4096 + (i & 6) * 512 + (i & 1) * 128 + (lane & 3) * 256 + (((lane >> 2) ^ (2 * (lane & 3) + (i & 1))) << 4));
    {
      const float* src = reinterpret_cast<const float*>(g_part1 + ((mt * 8 + w8) * 8 + (lane & 1) * 4) * 16 + (lane >> 1));
      float4 v, v1, v2, v3;
      #pragma unroll 1
      for (unsigned int spin = 0; spin < (1u << 22); spin++) {
        v = ld_tagged4(src); v1 = ld_tagged4(src + 64); v2 = ld_tagged4(src + 128); v3 = ld_tagged4(src + 192);
        if (__all_sync(0xffffffffu, tagged4(v) & tagged4(v1) & tagged4(v2) & tagged4(v3))) break;
        __nanosleep(100);
      }
      __syncwarp();
      TL_MARK2(26, lane == 0);
      v.x = (v.x + v1.x) + (v2.x + v3.x); v.y = (v.y + v1.y) + (v2.y + v3.y); v.z = (v.z + v1.z) + (v2.z + v3.z);
      v.x += __shfl_xor_sync(0xffffffffu, v.x, 1); v.y += __shfl_xor_sync(0xffffffffu, v.y, 1); v.z += __shfl_xor_sync(0xffffffffu, v.z, 1);
      const float mean = v.x * (1.0f / T_D);
      const float var = fmaxf(fmaf(-mean, mean, v.y * (1.0f / T_D)), 0.f);
      const uint32_t mb2 = pack_bf16(mean, mean);
      const float inv = rcp_approx(rbf(sqrt_approx(rbf(rbf(var) + 1e-05f))));
      {
        const float2 sc = lds_f32x2(sbase + OG_SMISC);
        const uint32_t key = rank_key(rbf(fmaf(fmaf(-bflo(mb2), sc.x, v.z), inv, sc.y)), m0 + 16 * w8 + (lane >> 1));
        mbar_wait(bar_end, 0);
        if (lane & 1) sts_u32(sbase + OG_SSTAT + 1024 + (16 * w8 + (lane >> 1)) * 4, key);
        else sts_u32x2(sbase + OG_SSTAT + (16 * w8 + (lane >> 1)) * 8, mb2, __float_as_uint(inv));
        __syncwarp();
        if (lane == 0) mbar_arrive(bar_key);
      }
      const uint32_t ih = pack_bf16(inv, inv), il = pack_bf16(inv - bflo(ih), inv - bflo(ih));
      const uint32_t mba = __shfl_sync(0xffffffffu, mb2, 2 * (lane >> 2)), mbb = __shfl_sync(0xffffffffu, mb2, 2 * (lane >> 2) + 16);
      const uint32_t iha = __shfl_sync(0xffffffffu, ih, 2 * (lane >> 2)), ihb = __shfl_sync(0xffffffffu, ih, 2 * (lane >> 2) + 16);
      const uint32_t ila = __shfl_sync(0xffffffffu, il, 2 * (lane >> 2)), ilb = __shfl_sync(0xffffffffu, il, 2 * (lane >> 2) + 16);
      #pragma unroll 2
      for (int J = 0; J < 16; J += 2) {
        const uint32_t off = (J >> 3) * 16384 + frag + ((((J & 7) + fhi) ^ fsw) << 4);
        uint32_t xr[4];
        ldmatrix_x4(sbase + OG_XSLOT + off, xr[0], xr[1], xr[2], xr[3]);
        #pragma unroll
        for (int h = 0; h < 2; h++) {
          const uint32_t ca = sbase + OG_SCOL + 512 + (8 * (J + h) + q2) * 2;
          const uint32_t c1 = lds_u32(ca + 256), sh = lds_u32(ca + 512), gb = lds_u32(ca + 768);
          xr[2 * h] = out2(xr[2 * h], mba, iha, ila, c1, sh, gb);
          xr[2 * h + 1] = out2(xr[2 * h + 1], mbb, ihb, ilb, c1, sh, gb);
        }
        stmatrix_x4(sbase + OG_OSLOT + off, xr[0], xr[1], xr[2], xr[3]);
      }
      fence_proxy_async();
      __syncwarp();
      if (lane == 0) mbar_arrive(bar_out);
      TL_MARK2(24, lane == 0);
    }
    if (has_moe) mbar_wait(bar_h2, 0);
    TL_MARK2(13, lane == 0);
    if (has_moe) {
      const GemvSel sel = gemv_sel(lane);
      {
        float d[4][4];
        #pragma unroll
        for (int c = 0; c < 4; c++) { d[c][0] = 0.f; d[c][1] = 0.f; d[c][2] = 0.f; d[c][3] = 0.f; }
        #pragma unroll
        for (int st = 0; st < 8; st++) {
          const uint2 hb = lds_u32x2(sbase + OG_SH2 + ((lane >> 2) & 1) * 2048 + (w8 * 128 + st * 16 + (lane & 3) * 4) * 2);
          #pragma unroll
          for (int j = 0; j < 4; j++) mma_bf16(d[j], wv[4 * st + j].x, wv[4 * st + j].y, wv[4 * st + j].z, wv[4 * st + j].w, GEMV_B0(j, hb, sel), GEMV_B1(j, hb, sel));
        }
        #pragma unroll
        for (int e = 0; e < 4; e++) d[0][e] = (d[0][e] + d[1][e]) + (d[2][e] + d[3][e]);
        const float4 r = gemv_out(d[0], lane);
        sts_f32x4(sbase + OG_SRED + w8 * 512 + (((lane >> 4) * 2 + (lane & 1)) * 32 + ((lane >> 2) & 3) * 8 + (lane & 2) * 2) * 4, r.x, r.y, r.z, r.w);
      }
      named_bar_sync(9, 256);
      if (t2 < 64) {
        float gp[8], up[8];
        #pragma unroll
        for (int w = 0; w < 8; w++) { gp[w] = lds_f32(sbase + OG_SRED + w * 512 + t2 * 4); up[w] = lds_f32(sbase + OG_SRED + w * 512 + 256 + t2 * 4); }
        const float gs = ((gp[0] + gp[1]) + (gp[2] + gp[3])) + ((gp[4] + gp[5]) + (gp[6] + gp[7]));
        const float us = ((up[0] + up[1]) + (up[2] + up[3])) + ((up[4] + up[5]) + (up[6] + up[7]));
        asm volatile("st.shared.u16 [%0], %1;" :: "r"(sbase + OG_SGU + ((t2 & ~15) + ((t2 >> 1) & 3) * 4 + ((t2 >> 3) & 1) * 2 + (t2 & 1)) * 2), "h"((uint16_t)pack_bf16(silu_bf(rbf(gs)) * rbf(us), 0.f)) : "memory");
      }
      named_bar_sync(9, 256);
      TL_MARK2(20, threadIdx.x == 128);
      float d[4][4];
      #pragma unroll
      for (int c = 0; c < 4; c++) { d[c][0] = 0.f; d[c][1] = 0.f; d[c][2] = 0.f; d[c][3] = 0.f; }
      #pragma unroll
      for (int st = 0; st < 2; st++) {
        const uint2 g = lds_u32x2(sbase + OG_SGU + ((lane >> 2) & 1) * 64 + st * 32 + (lane & 3) * 8);
        #pragma unroll
        for (int j = 0; j < 4; j++) {
          const uint32_t b0 = GEMV_B0(j, g, sel), b1 = GEMV_B1(j, g, sel);
          mma_bf16(d[j & 1], wd[4 * st + j].x, wd[4 * st + j].y, wd[4 * st + j].z, wd[4 * st + j].w, b0, b1);
          mma_bf16(d[2 + (j & 1)], wd[8 + 4 * st + j].x, wd[8 + 4 * st + j].y, wd[8 + 4 * st + j].z, wd[8 + 4 * st + j].w, b0, b1);
        }
      }
      #pragma unroll
      for (int e = 0; e < 4; e++) { d[0][e] += d[1][e]; d[2][e] += d[3][e]; }
      const float4 y0 = gemv_out(d[0], lane), y1 = gemv_out(d[2], lane);
      float* yp = g_ypart + (size_t)(blockIdx.x * 2 + (lane & 1)) * T_D + w8 * 128 + (lane >> 2) * 8 + (lane & 2) * 2;
      st_tagged4(yp, y0.x, y0.y, y0.z, y0.w);
      st_tagged4(yp + 64, y1.x, y1.y, y1.z, y1.w);
      named_bar_sync(9, 256);
      if (t2 == 0) hint_arrive(CNT_Y);
    }
    TL_MARK2(14, threadIdx.x == 128);
    TL_CLK(4, 1, threadIdx.x == 128);
}

#define OG_JOBS2 (16 - OG_JOBS)
__device__ __forceinline__ int help_njobs() { return blockIdx.x < 128 ? OG_JOBS : OG_JOBS2; }
__device__ __forceinline__ int help_job(int i) {
  const int step = i + (blockIdx.x < 128 ? 0 : OG_JOBS);
  return (step & ~3) * 4 + (blockIdx.x & 3) * 4 + (step & 3);
}
__device__ __noinline__ void store_warp(uint32_t sbase, const CUtensorMap* tmO, int item0, int n_items) {
  if (elect_one()) {
    const uint32_t bars = sbase + AT_SBAR, b_q0 = bars + 80, b_ob = bars + 96, b_ordy = bars + 104, b_acq = bars + 264;
    const unsigned int* cnt = &g_hcnt[32 * (1 + OG_MT(blockIdx.x)) + 2];
    #pragma unroll 1
    for (int q = 0; q < 4 * n_items; q++) {
      const int item = item0 + (q >> 2) * 128, h = (q >> 1) & 1, w = q & 1;
      const bool last = (q >> 2) == n_items - 1;
      if (q == 4 * n_items - 4) { mbar_wait(bars + 288, 0); red_release_add(&g_hcnt[1], 1u); }
      mbar_wait(b_ordy + 8 * (q & 3), q >> 2);
      store_o(tmO, (h ? (last ? sbase + AT_SQ + 32768 : sbase + 2 * 32768) : sbase + AT_SQ) + w * 8192, (item >> 4) * 2 + h, (item & 15) * 128 + w * 64);
      if (w) {
        bulk_wait_read<0>();
        mbar_arrive(h ? b_ob : b_q0);
        bulk_wait<0>();
        fence_proxy_async_global();
        red_release_add(&g_hcnt[32 * (1 + (item & 15)) + 2 + (item >> 7)], h ? 1u : 256u);
        if (blockIdx.x < 128 && q == (n_items == 2 ? 5 : 3)) { spin_until(cnt, 0x808u); mbar_arrive(b_acq); }
      }
    }
    if (n_items == 1) {
      #pragma unroll 1
      for (int i = 0; i < help_njobs(); i++) {
        mbar_wait(b_acq + 16, i & 1);
        TL_MARK2(23, i == OG_JOBS - 1);
        red_release_add(&g_hcnt[32 * (1 + (help_job(i) >> 2)) + 4 + (help_job(i) & 3)], 1u);
        TL_MARK2(4, i == OG_JOBS - 1);
        if (i == PRE_X - 1) { spin_until(&g_hcnt[1], 132u); mbar_arrive(b_acq + 32); }
      }
    }
    if (blockIdx.x < 128) { spin_until(&g_hcnt[0], 128u); spin_until(cnt + 1, 0x808u); mbar_arrive(b_acq); }
  }
}

__global__ void __launch_bounds__(384, 1)
fused_kernel(const __grid_constant__ CUtensorMap tmH, const __grid_constant__ CUtensorMap tmW, const __grid_constant__ CUtensorMap tmK,
            const __grid_constant__ CUtensorMap tmV, const __grid_constant__ CUtensorMap tmO, const __grid_constant__ CUtensorMap tmOl, const __grid_constant__ CUtensorMap tmWo,
            const __grid_constant__ CUtensorMap tmX, const __grid_constant__ CUtensorMap tmOut, const __grid_constant__ CUtensorMap tmM, uint32_t zero,
            const uint8_t* __restrict__ pf_wo, const bf16* __restrict__ kc, const bf16* __restrict__ vc,
            const bf16* __restrict__ x, const bf16* __restrict__ cvec, const bf16* __restrict__ w_mod, const bf16* __restrict__ w_r,
            const bf16* __restrict__ w_gate, const bf16* __restrict__ w_up, const bf16* __restrict__ w_down, bf16* __restrict__ out)
{
  extern __shared__ __align__(1024) uint8_t smem_raw[];
  const uint32_t sbase = smem_u32(smem_raw);
  const uint32_t bars = sbase + AT_SBAR;
  const uint32_t b_full = bars, b_empty = bars + 40;
  const uint32_t b_q0 = bars + 80, b_q1 = bars + 88;
  const uint32_t b_ob = bars + 96;
  const uint32_t b_ordy = bars + 104;
  const uint32_t b_pin = bars + 136;
  const uint32_t b_head = bars + 144;
  const uint32_t b_go = bars + 152;
  const uint32_t b_x = bars + 160;
  const int wg = __shfl_sync(0xffffffffu, threadIdx.x >> 7, 0);
  const bool single = blockIdx.x >= AT_NFULL;
  const int item0 = __shfl_sync(0xffffffffu, blockIdx.x < 128 ? (int)blockIdx.x : (int)blockIdx.x + 124, 0), n_items = __shfl_sync(0xffffffffu, single ? 1 : 2, 0);
  TL_START(3);
  if (threadIdx.x == 0) {
    if (sbase & 1023u) __trap();
    for (int i = 0; i < 5; i++) { mbar_init(b_full + 8 * i, 1); mbar_init(b_empty + 8 * i, 2); }
    mbar_init(b_q0, 1); mbar_init(b_q1, 8); mbar_init(b_ob, 1);
    for (int i = 0; i < 4; i++) mbar_init(b_ordy + 8 * i, 4);
    mbar_init(b_pin, 1); mbar_init(b_head, blockIdx.x < 128 ? 8 : 1); mbar_init(b_go, 1); mbar_init(b_x, 1);
    mbar_init(bars + 168, 2); mbar_init(bars + 176, 1); mbar_init(bars + 184, 8); mbar_init(bars + 192, 2);
    mbar_init(bars + 200, 8); mbar_init(bars + 208, 4); mbar_init(bars + 216, 1); mbar_init(bars + 264, 1); mbar_init(bars + 272, 1); mbar_init(bars + 280, 8); mbar_init(bars + 288, 1); mbar_init(bars + 296, 1); mbar_init(bars + 304, 8); mbar_init(bars + 312, 1); mbar_init(bars + 320, 1); mbar_init(bars + 328, 1);
    fence_mbar_init();
  }

  if (wg == 0) {
    reg_dealloc<AT_PREG>();
    if (threadIdx.x < 32) { __syncwarp(); named_bar_arrive(6, 384); }
    if (threadIdx.x >= 64) {
      named_bar_sync(6, 384);
      if (blockIdx.x < 128) {
        named_bar_sync(threadIdx.x >= 96 ? 8 : 9, 288);
        if ((threadIdx.x & 31) == 0) red_release_add(&g_hcnt[32 * (1 + (blockIdx.x >> 3)) + (threadIdx.x >= 96)], 1u);
        TL_MARK2(11, threadIdx.x == 64);
      }
      if (blockIdx.x < 128) {
        mbar_wait(MOD_AT, 0);
        mod_rest(sbase + OG_SCOL, b_q1, threadIdx.x - 64, cvec, w_mod, w_r);
      }
    } else if (threadIdx.x >= 32) {
      named_bar_sync(6, 384);
      store_warp(sbase, &tmO, item0, n_items);
      __syncwarp();
    } else {
     if (elect_one()) {
      const uint64_t pol = policy_evict_first();
      if (blockIdx.x < 128) {
        mbar_expect_tx(b_x, 32768);
        if (X_DLY) { const uint32_t c0 = clock_lo(); while (clock_lo() - c0 < X_DLY) {} }
        bulk_load_hint(sbase + 4 * 32768, x + (size_t)blockIdx.x * 16 * T_D, 32768, b_x, pol);
      }
      prefetch_tmap(&tmW); prefetch_tmap(&tmM); prefetch_tmap(&tmH); prefetch_tmap(&tmWo); prefetch_tmap(&tmOl);
      {
        const uint32_t c0 = clock_lo();
        while (clock_lo() - c0 < W_DLY) {}
        if (blockIdx.x < 128 && (blockIdx.x & 15) >= 4 * H_SPLIT) {
          mbar_expect_tx(bars + 328, 32768);
          tma_load_2d_hint(sbase + 3 * 32768, &tmM, (blockIdx.x & 31) * 64, (blockIdx.x >> 5) * 256, bars + 328, pol);
        }
        while (clock_lo() - c0 < W_DLY + W_FIRST) {}
      }
      uint32_t slot = 0, ph = 1;
      if (ALIGN) { uint32_t sm; asm volatile("mov.u32 %0, %%smid;" : "=r"(sm)); g_smid[32 + blockIdx.x] = sm; }
      #pragma unroll 1
      for (int it = 0; it < n_items; it++) {
        const int item = item0 + it * 128, hp = item >> 4, qt = item & 15;
        const bool first = it == 0;
        #pragma unroll 1
        for (int j = 0; j < T_D / 64; j++) {
          const uint32_t sl = ring_slot(qp_pos(j, it)), fb = b_full + 8 * sl;
          mbar_wait(b_empty + 8 * sl, ring_par(qp_pos(j, it)) ^ ((j >> 2) & 1) ^ 1);
          if (first && j == 3) mbar_wait(b_head, 0);
          mbar_expect_tx(fb, 49152);
          tma_load_3d_hint(sbase + sl * 32768, &tmW, j * 64, hp * 4, fb, pol);
          if (first && j < PRE_B) {
            if (j == PRE_B - 1) {
              spin_until(&g_hcnt[32 * (1 + qt)], 8u);
              TL_MARK2(16, true);
              fence_proxy_async_global();
              #pragma unroll 1
              for (int i = 0; i < PRE_B; i++) tma_load_2d(sbase + AT_SQ + i * 16384, &tmH, i * 64, qt * 128, b_full + 8 * i);
              mbar_arrive(b_go);
            }
          } else {
            if (first && j == 4 * H_SPLIT) { spin_until(&g_hcnt[32 * (1 + qt) + 1], 8u); fence_proxy_async_global(); }
            if (!first && (j == 0 || j == 2)) mbar_wait(j ? b_q1 : b_q0, 0);
            tma_load_2d_hint(sbase + AT_SQ + (j & 3) * 16384, &tmH, j * 64, qt * 128, fb, first ? pol_normal() : pol);
          }
        }
        #pragma unroll 1
        for (int j = 0; j < 4 * AT_NBLK; j++) {
          const bool isv = (j > 0 && !(j & 1)) || j == 4 * AT_NBLK - 1;
          const int row = hp * 2 * T_SEQ + (isv ? (j - 1) >> 1 : (j + 1) >> 1) * 128;
          const uint32_t fb = b_full + 8 * slot;
          mbar_wait(b_empty + 8 * slot, ph);
          if (!first && j == 3) mbar_wait(b_ob, 0);
          if (j == 4 && it == n_items - 1) mbar_arrive(bars + 288);
          if (ALIGN && j == AL_P && it == 1) mbar_arrive(bars + 312);
          mbar_expect_tx(fb, 32768);
          tma_load_3d_hint(sbase + slot * 32768, isv ? &tmV : &tmK, row, 0, fb, pol);
          if (it == 1 && isv && j >= 2 * WO_LATE && j < 2 * WO_LATE + 32 && blockIdx.x < OG_NKB)
            l2_prefetch_bulk(pf_wo + (size_t)own_kb(blockIdx.x) * 131072 + ((j >> 1) - WO_LATE) * 8192, 8192);
          if (++slot == 5) { slot = 0; ph ^= 1; }
        }
      }
      if (__builtin_expect(single, 0)) {
        #pragma unroll 1
        for (int i = 0; i < 4; i++) spin_until(&g_hcnt[32 * (1 + 4 * i + (blockIdx.x & 3)) + 2], 0x800u);
        fence_proxy_async_global();
        const int nj = help_njobs() * OG_PRE;
        int ji = 0, job = help_job(0), kk = 0;
        #pragma unroll 1
        for (int j = 0; j < nj; j++) {
          const uint32_t sl = ring_slot(qp_pos(j, 1)), fb = b_full + 8 * sl;
          mbar_wait(b_empty + 8 * sl, ring_par(qp_pos(j, 1)) ^ ((j >> 2) & 1) ^ 1);
          mbar_expect_tx(fb, 49152);
          tma_load_3d_hint(sbase + sl * 32768, &tmWo, pre_kb(kk) * 64, (job & 3) * 4, fb, HPOL_B);
          tma_load_3d_hint(sbase + sl * 32768 + 16384, &tmWo, pre_kb(kk) * 64, (job & 3) * 4 + 2, fb, HPOL_B);
          if (j == 0 || j == 2) mbar_wait(j ? b_ob : b_q0, 0);
          tma_load_2d_hint(sbase + AT_SQ + (j & 3) * 16384, HMAP_A, pre_kb(kk) * 64, (job >> 2) * 128, fb, HPOL_A);
          if (++kk == OG_PRE) { kk = 0; job = help_job(++ji); }
        }
      }
      if (blockIdx.x < 128) {
        if (single) mbar_wait(b_x, 1);
        tail_producer(sbase, 0, pol, &tmOl, &tmWo, &tmX);
      }
     }
    }
    named_bar_sync(12 + (threadIdx.x >> 5), 32);
    if (blockIdx.x < 128) tail_exchange(sbase, &tmOut, w_down, w_r, x, out);
  } else {
    if (blockIdx.x < 128) head_phase(sbase + AT_SQ + 49152, sbase + 4 * 32768, b_x, b_go, b_head, threadIdx.x - 128, zero, cvec, w_mod);
    else { named_bar_sync(6, 384); if (threadIdx.x == 128) mbar_arrive(b_head); }
    TL_MARK2(0, threadIdx.x == 128);
    reg_alloc<AT_CREG>();
    const int cwg = wg - 1;
    const int tid = threadIdx.x & 127;
    const int warp = tid >> 5, lane = tid & 31;
    const uint32_t dbase = (sbase & 0x3FFFFu) >> 4;
    const uint32_t k_base = dbase + (1u << 16);
    const uint32_t v_base = dbase + (1024u << 16);
    const uint32_t w_base = dbase + (512u << 16);
    const uint32_t q_lo = dbase + ((AT_SQ + cwg * 8192) >> 4) + (1u << 16);
    const uint32_t frag = cwg * 8192 + (16 * warp + (lane & 7) + 8 * ((lane >> 3) & 1)) * 128;
    if (cwg == 1) named_bar_arrive(1, 256);
    bool raw = false;
    uint4 pre[8];
    #pragma unroll 1
    for (int it = 0; it < n_items; it++) {
      const bool more = it + 1 < n_items;
      constexpr int nkb = T_D / 64;
      const int ta = __shfl_sync(0xffffffffu, 4 * it, 0);
      float acc[128];
      {
        FS(2 * it, 0);
        #pragma unroll
        for (int i = 0; i < 128; i++) asm volatile("" : "=f"(acc[i]));
        {
          const uint32_t slot = ring_slot(ta), b_lo = w_base + slot * 2048;
          mbar_wait(b_full + 8 * slot, ring_par(ta));
          wgmma_fence();
          wgmma_m64n256k16_ss_tb<0, 0>(acc, q_lo, b_lo, 0);
          wgmma_m64n256k16_ss_tb<2, 128>(acc, q_lo, b_lo, 1);
          wgmma_m64n256k16_ss_tb<4, 256>(acc, q_lo, b_lo, 1);
          wgmma_m64n256k16_ss_tb<6, 384>(acc, q_lo, b_lo, 1);
          wgmma_commit();
        }
        #pragma unroll 1
        for (int j = NOZERO; j < nkb; j++) {
          const uint32_t slot = ring_slot(qp_pos(j, ta >> 2));
          mbar_wait(b_full + 8 * slot, ring_par(qp_pos(j, ta >> 2)) ^ ((j >> 2) & 1));
          if (QP_STAG > 0 && cwg == 1 && j == nkb - QP_STAG) named_bar_sync(7, 256);
          const uint32_t a_lo = q_lo + (j & 3) * 1024, b_lo = w_base + slot * 2048;
          wgmma_fence();
          wgmma_m64n256k16_ss_tb<0, 0>(acc, a_lo, b_lo, 1);
          wgmma_m64n256k16_ss_tb<2, 128>(acc, a_lo, b_lo, 1);
          wgmma_m64n256k16_ss_tb<4, 256>(acc, a_lo, b_lo, 1);
          wgmma_m64n256k16_ss_tb<6, 384>(acc, a_lo, b_lo, 1);
          wgmma_commit();
          if (QP_STAG > 0 && cwg == 0 && j == nkb - 1) named_bar_arrive(7, 256);
          if (j > 0) {
            wgmma_wait<1>();
            if (tid == 0) mbar_arrive(b_empty + 8 * ring_slot(qp_pos(j - 1, ta >> 2)));
          }
        }
        wgmma_wait<0>();
        fence_regs(acc);
        FS(2 * it, 1);
        TL_MARK2(29, threadIdx.x == 256 && it == 0);
        if (tid == 0) mbar_arrive(b_empty + 24);
      }
      float o[64], s[64];
      uint32_t p[32], q[32];
      #pragma unroll
      for (int i = 0; i < 32; i++) q[i] = pack_bf16(acc[2 * i] * AT_C, acc[2 * i + 1] * AT_C);
      zero_regs(s);
      const uint32_t sq = sbase + AT_SQ + cwg * 8192;
      const bool last_wg1 = cwg == 1 && !more;
      float mc0, mc1, al0 = 1.0f, al1 = 1.0f, l0 = 0.f, l1 = 0.f, lp0 = 0.f, lp1 = 0.f;
      bool redo0 = false;
      FS(2 * it, 2);
      mbar_wait(b_full + 8 * ring_slot(ta), ring_par(ta));
      named_bar_sync(1 + cwg, 256);
      FS(2 * it, 3);
      issue_qk(s, q, k_base + ring_slot(ta) * 2048);
      named_bar_arrive(1 + (cwg ^ 1), 256);
      bool ready = mbar_test(b_full + 8 * ring_slot(ta + 1), ring_par(ta + 1)) & mbar_test(b_full + 8 * ring_slot(ta + 2), ring_par(ta + 2));
      stage_q<16>(acc, AT_C, sbase + AT_SQ + frag, lane);
      wgmma_wait<0>();
      fence_regs(s);
      if (tid == 0) mbar_arrive(b_empty + 8 * ring_slot(ta));
      mc0 = 0.f; mc1 = 0.f;
      if (!raw) {
        raw = softmax_mode(s, mc0, mc1);
        if (__builtin_expect(!raw, 0)) softmax_sub(s, mc0, mc1);
      }
      softmax_exp<0, 64>(s);
      #pragma unroll
      for (int J = 0; J < 16; J += 2)
        stmatrix_x4(sbase + AT_SQ + frag + (J >> 3) * 16384 + ((((J & 7) + (lane >> 4)) ^ (lane & 7)) << 4), q[2 * J], q[2 * J + 1], q[2 * J + 2], q[2 * J + 3]);
      pack_p(p, s);
      zero_regs(o);
      FS(2 * it, 4);
      uint32_t ks = ring_slot(ta + 1), vs = ring_slot(ta + 2), kp = ring_par(ta + 1), vp = ring_par(ta + 2);
      auto finish_head = [&]() {
        FS(2 * it, 5);
        redo0 = finish_l(lp0, lp1);
        if (!redo0) {
          stage_o(o, lp0, lp1, sbase + AT_SQ + frag, lane);
          fence_proxy_async();
          __syncwarp();
          if (lane == 0) mbar_arrive(b_ordy + 8 * cwg);
        }
        FS(2 * it + 1, 4);
      };
      if (!ready) { mbar_wait(b_full + 8 * ks, kp); mbar_wait(b_full + 8 * vs, vp); }
      #pragma unroll 1
      for (int n = 1; n < 2 * AT_NBLK; n++) {
        named_bar_sync(1 + cwg, 256);
        issue_qk(s, q, k_base + ks * 2048);
        if (n == AT_NBLK + 1) finish_head();
        issue_pv(o, p, v_base + vs * 2048, (n & 15) != 1);
        if (!(last_wg1 && n == 2 * AT_NBLK - 1)) named_bar_arrive(1 + (cwg ^ 1), 256);
        wgmma_wait<1>();
        fence_regs(s);
        if (tid == 0) mbar_arrive(b_empty + 8 * ks);
        if (__builtin_expect(!raw || (n + 1) >> 1 == AT_NBLK / 2, 0)) {
          if (n == AT_NBLK - 1) {
            #pragma unroll
            for (int J = 0; J < 16; J += 2)
              ldmatrix_x4(sbase + AT_SQ + 32768 + frag + (J >> 3) * 16384 + ((((J & 7) + (lane >> 4)) ^ (lane & 7)) << 4), q[2 * J], q[2 * J + 1], q[2 * J + 2], q[2 * J + 3]);
          }
          if (!raw) {
            const float m0 = mc0, m1 = mc1;
            const bool ok = softmax_mode(s, mc0, mc1);
            if (n == AT_NBLK) raw = ok;
            else {
              mc0 = mc0 - AT_HEAD > m0 ? mc0 : m0; mc1 = mc1 - AT_HEAD > m1 ? mc1 : m1;
              al0 = ex2_approx(m0 - mc0); al1 = ex2_approx(m1 - mc1);
            }
            if (!raw) softmax_sub(s, mc0, mc1);
          }
        }
        softmax_exp<0, AT_SPLIT>(s);
        add_rowsum(p, l0, l1);
        if (tid == 0) {
          uint32_t dep = zero & __float_as_uint(l0) & __float_as_uint(l1);
          #pragma unroll
          for (int i = AT_SPLIT - AT_PIN - PINB; i < AT_SPLIT - PINB; i += 2) dep &= __float_as_uint(s[i]) & __float_as_uint(s[i + 1]);
          mbar_arrive(b_pin + dep);
        }
        wgmma_wait<0>();
        fence_regs(o);
        if (tid == 0) mbar_arrive(b_empty + 8 * vs);
        ks += 2; if (ks >= 5) { ks -= 5; kp ^= 1; }
        vs += 2; if (vs >= 5) { vs -= 5; vp ^= 1; }
        ready = mbar_test(b_full + 8 * ks, kp) & mbar_test(b_full + 8 * vs, vp);
        softmax_exp<AT_SPLIT, 64>(s);
        pack_p(p, s);
        if (n == AT_NBLK) { lp0 = l0; lp1 = l1; l0 = 0.f; l1 = 0.f; }
        if (__builtin_expect(!raw || !ready, 0)) {
        if (!raw && __any_sync(0xffffffffu, al0 != 1.0f || al1 != 1.0f)) {
          rescale_o(o, al0, al1);
          l0 *= al0; l1 *= al1;
          al0 = 1.0f; al1 = 1.0f;
        }
        if (!ready && n < 2 * AT_NBLK - 1) {
          mbar_wait(b_full + 8 * ks, kp);
          mbar_wait(b_full + 8 * vs, vp);
        }
        }
      }
      FS(2 * it + 1, 5);
      const uint32_t vl = ring_slot(ta + 63);
      vs = ring_slot(ta + 62);
      const uint32_t ob = more ? sbase + vs * 32768 : sbase + AT_SQ + 32768;
      if (redo0) {
        attn_rows_exact(sq, sq, 4 * ta, kc, vc);
        fence_proxy_async();
        __syncwarp();
        if (lane == 0) mbar_arrive(b_ordy + 8 * cwg);
      }
      mbar_wait(b_full + 8 * vl, ring_par(ta + 63));
      issue_pv(o, p, v_base + vl * 2048, 1);
      add_rowsum(p, l0, l1);
      const bool overflow = finish_l(l0, l1);
      if (!overflow && lane == 0) mbar_arrive(b_q1);
      #pragma unroll
      for (int i = 0; i < 8; i++) asm volatile("mov.b64 {%0, %1}, 0;\nmov.b64 {%2, %3}, 0;" : "=r"(pre[i].x), "=r"(pre[i].y), "=r"(pre[i].z), "=r"(pre[i].w));
      if (HOIST && !more && blockIdx.x < OG_MOE) {
        load_pre(pre, sbase, AT_SQ, threadIdx.x - 128);
        __syncwarp();
        if (lane == 0) mbar_arrive(bars + 304);
      }
      mbar_wait(b_empty + 8 * vs, ring_par(ta + 62));
      wgmma_wait<0>();
      fence_regs(o);
      if (tid == 0) mbar_arrive(b_empty + 8 * vl);
      FS(2 * it + 1, 6);
      if (overflow) {
        attn_rows_exact(sq + 32768, ob + cwg * 8192, 4 * ta + 1, kc, vc);
        __syncwarp();
        if (lane == 0) mbar_arrive(b_q1);
      } else stage_o(o, l0, l1, ob + frag, lane);
      fence_proxy_async();
      __syncwarp();
      if (lane == 0) mbar_arrive(b_ordy + 16 + 8 * cwg);
      if (redo0 || overflow) raw = false;
      named_bar_sync(3 + cwg, 128);
      FS(2 * it + 1, 7);
    }
    if (__builtin_expect(single, 0)) {
      float acc[128];
      uint32_t j = 0, pk[64];
      #pragma unroll
      for (int i = 0; i < 64; i++) asm volatile("" : "=f"(acc[2 * i]), "=f"(acc[2 * i + 1]), "=r"(pk[i]));
      uint4* dst = g_pre;
      int left = 0;
      auto put = [&](bool last) {
        #pragma unroll
        for (int i = 0; i < PUT_N; i++) dst[i * 256] = make_uint4(pk[4 * i], pk[4 * i + 1], pk[4 * i + 2], pk[4 * i + 3]);
        dst += PUT_N * 256;
        #pragma unroll
        for (int i = 0; i < 64 - 4 * PUT_N; i++) asm volatile("mov.b32 %0, %1;" : "=r"(pk[i]) : "r"(pk[i + 4 * PUT_N]));
        __syncwarp();
        if (last && lane == 0) mbar_arrive(bars + 280);
      };
      #pragma unroll 1
      for (int ji = 0; ji < help_njobs(); ji++) {
        #pragma unroll 1
        for (int kk = 0; kk < OG_PRE; kk++, j++) {
          const uint32_t slot = ring_slot(qp_pos(j, 1));
          mbar_wait(b_full + 8 * slot, ring_par(qp_pos(j, 1)) ^ ((j >> 2) & 1));
          if (H_STAG > 0 && cwg == 1 && kk == OG_PRE - H_STAG) named_bar_sync(7, 256);
          const uint32_t a_lo = q_lo + (j & 3) * 1024, b_lo = w_base + slot * 2048;
          wgmma_fence();
          wgmma_m64n256k16_ss_tb<0, 0>(acc, a_lo, b_lo, kk != 0);
          wgmma_m64n256k16_ss_tb<2, 128>(acc, a_lo, b_lo, 1);
          wgmma_m64n256k16_ss_tb<4, 256>(acc, a_lo, b_lo, 1);
          wgmma_m64n256k16_ss_tb<6, 384>(acc, a_lo, b_lo, 1);
          wgmma_commit();
          if (H_STAG > 0 && cwg == 0 && kk == OG_PRE - 1) named_bar_arrive(7, 256);
          wgmma_wait<1>();
          if (kk > 0 && tid == 0) mbar_arrive(b_empty + 8 * ring_slot(qp_pos(j - 1, 1)));
          #pragma unroll 1
          for (int i = ji == OG_JOBS ? 0 : 16 / PUT_N - 1; i < 16 / PUT_N && left > 0; i++) put(--left == 0);
        }
        wgmma_wait<0>();
        fence_regs(acc);
        if (tid == 0) mbar_arrive(b_empty + 8 * ring_slot(qp_pos(j - 1, 1)));
        #pragma unroll
        for (int i = 0; i < 64; i++) pk[i] = pack_bf16(acc[2 * i], acc[2 * i + 1]);
        left = 16 / PUT_N;
        if (ji == PRE_X) mbar_wait(bars + 296, 0);
        dst = g_pre + pre_loc(help_job(ji)) * 4096 + threadIdx.x - 128;
      }
      #pragma unroll
      for (int i = 0; i < 16; i++) dst[i * 256] = make_uint4(pk[4 * i], pk[4 * i + 1], pk[4 * i + 2], pk[4 * i + 3]);
      __syncwarp();
      if (lane == 0) mbar_arrive(bars + 280);
      named_bar_sync(5, 256);
      if (threadIdx.x == 128) {
        #pragma unroll 1
        for (int i = 0; i < 5; i++) {
          constexpr int n = OG_JOBS * OG_PRE;
          const int used = i == 3 ? 0 : (n + 3 - (i == 4 ? 3 : i)) / 4;
          if ((used ^ (i < 4)) & 1) {
            mbar_arrive(b_full + 8 * ring_slot(4 + i));
            mbar_arrive(b_empty + 8 * ring_slot(4 + i)); mbar_arrive(b_empty + 8 * ring_slot(4 + i));
          }
        }
        mbar_arrive(b_x);
      }
      named_bar_sync(5, 256);
      #pragma unroll
      for (int i = 0; i < 8; i++) pre[i] = make_uint4(0u, 0u, 0u, 0u);
    }
    TL_CLK(3, 1, threadIdx.x == 128);
    TL_CTA(1, threadIdx.x == 256);
    TL_END(3, tid == 0);
    TL_MARK2(19, tid == 0 && !single);
    if (blockIdx.x < 128) {
      if (!HOIST && blockIdx.x < OG_MOE) {
        load_pre(pre, sbase, AT_SQ, threadIdx.x - 128);
        __syncwarp();
        if (lane == 0) mbar_arrive(bars + 304);
      }
      tail_consumer(sbase, pre, cwg, w_gate, w_up);
    }
  }
}

typedef CUresult (*PFN_encodeTiled)(CUtensorMap*, CUtensorMapDataType, cuuint32_t, void*, const cuuint64_t*, const cuuint64_t*,
                                    const cuuint32_t*, const cuuint32_t*, CUtensorMapInterleave, CUtensorMapSwizzle,
                                    CUtensorMapL2promotion, CUtensorMapFloatOOBfill);

CUtensorMap make_map_2d(PFN_encodeTiled enc, const void* ptr, uint64_t inner, uint64_t outer, uint64_t stride_bytes, uint32_t box_inner, uint32_t box_outer) {
  CUtensorMap m;
  cuuint64_t gd[2] = {inner, outer}; cuuint64_t gs[1] = {stride_bytes};
  cuuint32_t bx[2] = {box_inner, box_outer}; cuuint32_t es[2] = {1, 1};
  enc(&m, CU_TENSOR_MAP_DATA_TYPE_BFLOAT16, 2, const_cast<void*>(ptr), gd, gs, bx, es, CU_TENSOR_MAP_INTERLEAVE_NONE,
      CU_TENSOR_MAP_SWIZZLE_128B, CU_TENSOR_MAP_L2_PROMOTION_L2_128B, CU_TENSOR_MAP_FLOAT_OOB_FILL_NONE);
  return m;
}

CUtensorMap make_map_3d(PFN_encodeTiled enc, const void* ptr, uint64_t cols, uint64_t rows, uint32_t box_rows, uint32_t chunks) {
  CUtensorMap m;
  cuuint64_t gd[3] = {64, rows, cols / 64}; cuuint64_t gs[2] = {cols * 2, 128};
  cuuint32_t bx[3] = {64, box_rows, chunks}; cuuint32_t es[3] = {1, 1, 1};
  enc(&m, CU_TENSOR_MAP_DATA_TYPE_BFLOAT16, 3, const_cast<void*>(ptr), gd, gs, bx, es, CU_TENSOR_MAP_INTERLEAVE_NONE,
      CU_TENSOR_MAP_SWIZZLE_128B, CU_TENSOR_MAP_L2_PROMOTION_L2_128B, CU_TENSOR_MAP_FLOAT_OOB_FILL_NONE);
  return m;
}

}

extern "C" void kernel_launch(void* const* d_in, const int* in_sizes, int n_in, void* d_out, int out_size) {
  const bf16* x      = (const bf16*)d_in[0];
  const bf16* kc     = (const bf16*)d_in[1];
  const bf16* vc     = (const bf16*)d_in[2];
  const bf16* wq     = (const bf16*)d_in[3];
  const bf16* wo     = (const bf16*)d_in[4];
  const bf16* w_r    = (const bf16*)d_in[6];
  const bf16* w_gate = (const bf16*)d_in[7];
  const bf16* w_up   = (const bf16*)d_in[8];
  const bf16* w_down = (const bf16*)d_in[9];
  const bf16* cvec   = (const bf16*)d_in[10];
  const bf16* w_mod  = (const bf16*)d_in[11];
  bf16* out = (bf16*)d_out;

  static PFN_encodeTiled enc = nullptr;
  static void *p_h = nullptr, *p_o = nullptr;
  if (!enc) {
    void* fn = nullptr; cudaDriverEntryPointQueryResult qres;
    cudaGetDriverEntryPoint("cuTensorMapEncodeTiled", &fn, cudaEnableDefault, &qres);
    enc = (PFN_encodeTiled)fn;
    cudaGetSymbolAddress(&p_h, g_pre);
    p_h = (uint4*)p_h + 16 * PRE_X * 2048;
    cudaGetSymbolAddress(&p_o, g_o);
    cudaFuncSetAttribute(fused_kernel, cudaFuncAttributeMaxDynamicSharedMemorySize, (int)AT_SMEM);
  }
  const CUtensorMap tm_h   = make_map_2d(enc, p_h, T_D, T_SEQ, T_D * 2, 64, 128);
  const CUtensorMap tm_wq  = W3D ? make_map_3d(enc, wq, T_DQKV, T_D, 64, 4) : make_map_2d(enc, wq, T_DQKV, T_D, T_DQKV * 2, 64, 64);
  const CUtensorMap tm_k   = KV3D ? make_map_3d(enc, kc, T_DH, (uint64_t)T_NH * T_SEQ, 128, 2) : make_map_2d(enc, kc, T_DH, (uint64_t)T_NH * T_SEQ, T_DH * 2, 64, 128);
  const CUtensorMap tm_v   = KV3D ? make_map_3d(enc, vc, T_DH, (uint64_t)T_NH * T_SEQ, 128, 2) : make_map_2d(enc, vc, T_DH, (uint64_t)T_NH * T_SEQ, T_DH * 2, 64, 128);
  const CUtensorMap tm_ost = make_map_2d(enc, p_o, T_DQKV, T_SEQ, T_DQKV * 2, 64, 64);
  const CUtensorMap tm_old = make_map_2d(enc, p_o, T_DQKV, T_SEQ, T_DQKV * 2, 64, 128);
  const CUtensorMap tm_wo  = make_map_3d(enc, wo, T_D, T_DQKV, 64, 2);
  const CUtensorMap tm_x   = make_map_3d(enc, w_down, T_D, T_F, 32, 8);

  const CUtensorMap tm_m   = make_map_2d(enc, w_mod, 6 * T_D, T_D, 6 * T_D * 2, 64, 256);
  const CUtensorMap tm_out = make_map_2d(enc, out, T_D, T_SEQ, T_D * 2, 64, 128);

  fused_kernel<<<132, 384, AT_SMEM, cudaStreamPerThread>>>(tm_h, tm_wq, tm_k, tm_v, tm_ost, tm_old, tm_wo, tm_x, tm_out, tm_m, 0u, (const uint8_t*)wo, kc, vc, x, cvec, w_mod,
             w_r, w_gate, w_up, w_down, out);
}
```

```cpp
#include <cuda_runtime.h>
#include <cuda_bf16.h>
#include <cuda.h>
#include <stdint.h>

namespace {

typedef __nv_bfloat16 bf16;

constexpr int T_SEQ = 2048, T_D = 1024, T_NH = 32, T_DH = 128, T_DQKV = 4096, T_F = 3584;

#define PRE_X 2
__device__ __align__(1024) uint4 g_pre[(16 * PRE_X + 128) * 2048];
#define g_h (reinterpret_cast<bf16*>(g_pre + 16 * PRE_X * 2048))
__device__ __align__(1024) bf16 g_o[T_SEQ * T_DQKV];
__device__ __align__(16) uint8_t g_col[8 * 1536];
__device__ __align__(16) float g_scal[64];
__device__ __align__(16) unsigned int g_hcnt[17 * 32];
__device__ unsigned int g_smid[160], g_tmax[128];
__device__ __align__(128) float g_modpart[4 * 2 * T_D];
struct __align__(2048) TailMail {
  float4 part1[T_SEQ * 8];
  uint32_t key[256];
  uint4 cand[16 * 2 * 2 * 128];
  uint32_t cnt[32];
  float ypart[(T_F / 32) * 2 * T_D];
};
__device__ TailMail g_mail;
#define g_part1 g_mail.part1
#define g_key g_mail.key
#define g_cand g_mail.cand
#define CNT_Y (g_mail.cnt)
#define g_ypart g_mail.ypart

__device__ __forceinline__ uint32_t smem_u32(const void* p) { return (uint32_t)__cvta_generic_to_shared(p); }
__device__ __forceinline__ void mbar_init(uint32_t bar, uint32_t cnt) { asm volatile("mbarrier.init.shared::cta.b64 [%0], %1;" :: "r"(bar), "r"(cnt)); }
__device__ __forceinline__ void mbar_expect_tx(uint32_t bar, uint32_t bytes) { asm volatile("mbarrier.arrive.expect_tx.shared::cta.b64 _, [%0], %1;" :: "r"(bar), "r"(bytes) : "memory"); }
__device__ __forceinline__ void mbar_arrive(uint32_t bar) { asm volatile("mbarrier.arrive.shared::cta.b64 _, [%0];" :: "r"(bar) : "memory"); }
__device__ __forceinline__ void mbar_wait(uint32_t bar, uint32_t parity) {
  asm volatile("{\n.reg .pred p;\nLAB_WAIT:\nmbarrier.try_wait.parity.shared::cta.b64 p, [%0], %1;\n@!p bra LAB_WAIT;\n}\n" :: "r"(bar), "r"(parity) : "memory");
}
__device__ __forceinline__ bool mbar_test(uint32_t bar, uint32_t parity) {
  uint32_t r; asm volatile("{\n.reg .pred p;\nmbarrier.test_wait.parity.shared::cta.b64 p, [%1], %2;\nselp.u32 %0, 1, 0, p;\n}\n" : "=r"(r) : "r"(bar), "r"(parity) : "memory");
  return r != 0;
}
__device__ __forceinline__ uint32_t clock_lo() { uint32_t c; asm volatile("mov.u32 %0, %%clock;" : "=r"(c)); return c; }
__device__ __forceinline__ void fence_mbar_init() { asm volatile("fence.mbarrier_init.release.cluster;" ::: "memory"); }
__device__ __forceinline__ void tma_load_2d(uint32_t dst, const CUtensorMap* map, int c0, int c1, uint32_t bar) {
  asm volatile("cp.async.bulk.tensor.2d.shared::cluster.global.mbarrier::complete_tx::bytes [%0], [%1, {%3, %4}], [%2];"
    :: "r"(dst), "l"(map), "r"(bar), "r"(c0), "r"(c1) : "memory");
}
__device__ __forceinline__ uint64_t policy_evict_first() {
  uint64_t p; asm volatile("createpolicy.fractional.L2::evict_first.b64 %0, 1.0;" : "=l"(p)); return p;
}
__device__ __forceinline__ void tma_load_2d_hint(uint32_t dst, const CUtensorMap* map, int c0, int c1, uint32_t bar, uint64_t pol) {
  asm volatile("cp.async.bulk.tensor.2d.shared::cluster.global.mbarrier::complete_tx::bytes.L2::cache_hint [%0], [%1, {%3, %4}], [%2], %5;"
    :: "r"(dst), "l"(map), "r"(bar), "r"(c0), "r"(c1), "l"(pol) : "memory");
}
__device__ __forceinline__ void tma_load_3d_hint(uint32_t dst, const CUtensorMap* map, int c1, int c2, uint32_t bar, uint64_t pol) {
  asm volatile("cp.async.bulk.tensor.3d.shared::cluster.global.mbarrier::complete_tx::bytes.L2::cache_hint [%0], [%1, {%3, %4, %5}], [%2], %6;"
    :: "r"(dst), "l"(map), "r"(bar), "n"(0), "r"(c1), "r"(c2), "l"(pol) : "memory");
}
__device__ __forceinline__ void tma_store_2d(const CUtensorMap* map, uint32_t src, int c0, int c1) {
  asm volatile("cp.async.bulk.tensor.2d.global.shared::cta.bulk_group [%0, {%2, %3}], [%1];" :: "l"(map), "r"(src), "r"(c0), "r"(c1) : "memory");
}
__device__ __forceinline__ void prefetch_tmap(const CUtensorMap* map) { asm volatile("prefetch.tensormap [%0];" :: "l"(map) : "memory"); }
__device__ __forceinline__ void l2_prefetch_bulk(const void* p, uint32_t bytes) {
  asm volatile("cp.async.bulk.prefetch.L2.global [%0], %1;" :: "l"(p), "r"(bytes) : "memory");
}
__device__ __forceinline__ void bulk_commit() { asm volatile("cp.async.bulk.commit_group;" ::: "memory"); }
template<int N> __device__ __forceinline__ void bulk_wait_read() { asm volatile("cp.async.bulk.wait_group.read %0;" :: "n"(N) : "memory"); }
template<int N> __device__ __forceinline__ void bulk_wait() { asm volatile("cp.async.bulk.wait_group %0;" :: "n"(N) : "memory"); }
__device__ __forceinline__ void named_bar_sync(int id, int nthreads) { asm volatile("bar.sync %0, %1;" :: "r"(id), "r"(nthreads) : "memory"); }
__device__ __forceinline__ void named_bar_arrive(int id, int nthreads) { asm volatile("bar.arrive %0, %1;" :: "r"(id), "r"(nthreads) : "memory"); }
__device__ __forceinline__ void wgmma_fence() { asm volatile("wgmma.fence.sync.aligned;" ::: "memory"); }
__device__ __forceinline__ void wgmma_commit() { asm volatile("wgmma.commit_group.sync.aligned;" ::: "memory"); }
template<int N> __device__ __forceinline__ void wgmma_wait() { asm volatile("wgmma.wait_group.sync.aligned %0;" :: "n"(N) : "memory"); }
template<int R> __device__ __forceinline__ void reg_alloc() { asm volatile("setmaxnreg.inc.sync.aligned.u32 %0;" :: "n"(R)); }
template<int R> __device__ __forceinline__ void reg_dealloc() { asm volatile("setmaxnreg.dec.sync.aligned.u32 %0;" :: "n"(R)); }
__device__ __forceinline__ bool elect_one() {
  uint32_t pred; asm volatile("{\n.reg .pred p;\nelect.sync _|p, 0xffffffff;\nselp.u32 %0, 1, 0, p;\n}\n" : "=r"(pred)); return pred != 0;
}
__device__ __forceinline__ uint32_t pack_bf16(float lo, float hi) {
  uint32_t r; asm("cvt.rn.bf16x2.f32 %0, %1, %2;" : "=r"(r) : "f"(hi), "f"(lo)); return r;
}
__device__ __forceinline__ void stmatrix_x4(uint32_t addr, uint32_t r0, uint32_t r1, uint32_t r2, uint32_t r3) {
  asm volatile("stmatrix.sync.aligned.m8n8.x4.shared.b16 [%0], {%1, %2, %3, %4};" :: "r"(addr), "r"(r0), "r"(r1), "r"(r2), "r"(r3) : "memory");
}
__device__ __forceinline__ void fence_proxy_async() { asm volatile("fence.proxy.async.shared::cta;" ::: "memory"); }
__device__ __forceinline__ float ex2_approx(float x) { float y; asm("ex2.approx.ftz.f32 %0, %1;" : "=f"(y) : "f"(x)); return y; }
template<int N> __device__ __forceinline__ void fence_regs(float (&r)[N]) {
  #pragma unroll
  for (int i = 0; i < N; i++) asm volatile("" : "+f"(r[i]) :: "memory");
}
template<int N> __device__ __forceinline__ void zero_regs(float (&r)[N]) {
  #pragma unroll
  for (int i = 0; i < N; i += 2) asm volatile("mov.b64 {%0, %1}, 0;" : "=f"(r[i]), "=f"(r[i + 1]));
}
__device__ __forceinline__ float rbf(float x) { return __uint_as_float(pack_bf16(0.f, x)); }
__device__ __forceinline__ float bflo(uint32_t v) { return __uint_as_float(v << 16); }
__device__ __forceinline__ float bfhi(uint32_t v) { return __uint_as_float(v & 0xffff0000u); }

#define TL_START(k) do {} while (0)
#define TL_END(k, cond) do {} while (0)
#define TL_CTA(i, cond) do {} while (0)
#define FS(slot, k) do {} while (0)
#define TL_MARK2(k, cond) do {} while (0)
#define TL_CLK(k, i, cond) do {} while (0)

template <int OFFA, int OFFB>
__device__ __forceinline__ void wgmma_m64n256k16_ss_tb(float (&d)[128], uint32_t a_lo, uint32_t b_lo, int scaleD) {
  asm volatile("{\n.reg .pred p;\n.reg .b32 ta, tb;\n.reg .b64 da, db;\nsetp.ne.b32 p, %130, 0;\n"
    "add.u32 ta, %128, %131;\nadd.u32 tb, %129, %132;\n"
    "mov.b64 da, {ta, 0x40000040};\nmov.b64 db, {tb, 0x40000040};\n"
    "wgmma.mma_async.sync.aligned.m64n256k16.f32.bf16.bf16 "
    "{%0, %1, %2, %3, %4, %5, %6, %7, %8, %9, %10, %11, %12, %13, %14, %15, %16, %17, %18, %19, %20, %21, %22, %23, %24, %25, %26, %27, %28, %29, %30, %31, %32, %33, %34, %35, %36, %37, %38, %39, %40, %41, %42, %43, %44, %45, %46, %47, %48, %49, %50, %51, %52, %53, %54, %55, %56, %57, %58, %59, %60, %61, %62, %63, %64, %65, %66, %67, %68, %69, %70, %71, %72, %73, %74, %75, %76, %77, %78, %79, %80, %81, %82, %83, %84, %85, %86, %87, %88, %89, %90, %91, %92, %93, %94, %95, %96, %97, %98, %99, %100, %101, %102, %103, %104, %105, %106, %107, %108, %109, %110, %111, %112, %113, %114, %115, %116, %117, %118, %119, %120, %121, %122, %123, %124, %125, %126, %127}, "
    "da, db, p, 1, 1, 0, 1;\n}\n"
    : "+f"(d[0]), "+f"(d[1]), "+f"(d[2]), "+f"(d[3]), "+f"(d[4]), "+f"(d[5]), "+f"(d[6]), "+f"(d[7]), "+f"(d[8]), "+f"(d[9]), "+f"(d[10]), "+f"(d[11]), "+f"(d[12]), "+f"(d[13]), "+f"(d[14]), "+f"(d[15]), "+f"(d[16]), "+f"(d[17]), "+f"(d[18]), "+f"(d[19]), "+f"(d[20]), "+f"(d[21]), "+f"(d[22]), "+f"(d[23]), "+f"(d[24]), "+f"(d[25]), "+f"(d[26]), "+f"(d[27]), "+f"(d[28]), "+f"(d[29]), "+f"(d[30]), "+f"(d[31]), "+f"(d[32]), "+f"(d[33]), "+f"(d[34]), "+f"(d[35]), "+f"(d[36]), "+f"(d[37]), "+f"(d[38]), "+f"(d[39]), "+f"(d[40]), "+f"(d[41]), "+f"(d[42]), "+f"(d[43]), "+f"(d[44]), "+f"(d[45]), "+f"(d[46]), "+f"(d[47]), "+f"(d[48]), "+f"(d[49]), "+f"(d[50]), "+f"(d[51]), "+f"(d[52]), "+f"(d[53]), "+f"(d[54]), "+f"(d[55]), "+f"(d[56]), "+f"(d[57]), "+f"(d[58]), "+f"(d[59]), "+f"(d[60]), "+f"(d[61]), "+f"(d[62]), "+f"(d[63]), "+f"(d[64]), "+f"(d[65]), "+f"(d[66]), "+f"(d[67]), "+f"(d[68]), "+f"(d[69]), "+f"(d[70]), "+f"(d[71]), "+f"(d[72]), "+f"(d[73]), "+f"(d[74]), "+f"(d[75]), "+f"(d[76]), "+f"(d[77]), "+f"(d[78]), "+f"(d[79]), "+f"(d[80]), "+f"(d[81]), "+f"(d[82]), "+f"(d[83]), "+f"(d[84]), "+f"(d[85]), "+f"(d[86]), "+f"(d[87]), "+f"(d[88]), "+f"(d[89]), "+f"(d[90]), "+f"(d[91]), "+f"(d[92]), "+f"(d[93]), "+f"(d[94]), "+f"(d[95]), "+f"(d[96]), "+f"(d[97]), "+f"(d[98]), "+f"(d[99]), "+f"(d[100]), "+f"(d[101]), "+f"(d[102]), "+f"(d[103]), "+f"(d[104]), "+f"(d[105]), "+f"(d[106]), "+f"(d[107]), "+f"(d[108]), "+f"(d[109]), "+f"(d[110]), "+f"(d[111]), "+f"(d[112]), "+f"(d[113]), "+f"(d[114]), "+f"(d[115]), "+f"(d[116]), "+f"(d[117]), "+f"(d[118]), "+f"(d[119]), "+f"(d[120]), "+f"(d[121]), "+f"(d[122]), "+f"(d[123]), "+f"(d[124]), "+f"(d[125]), "+f"(d[126]), "+f"(d[127])
    : "r"(a_lo), "r"(b_lo), "r"(scaleD), "n"(OFFA), "n"(OFFB));
}

template <int OFFA, int OFFB>
__device__ __forceinline__ void wgmma_m64n128k16_ss_tb(float (&d)[64], uint32_t a_lo, uint32_t b_lo, int scaleD) {
  asm volatile("{\n.reg .pred p;\n.reg .b32 ta, tb;\n.reg .b64 da, db;\nsetp.ne.b32 p, %66, 0;\n"
    "add.u32 ta, %64, %67;\nadd.u32 tb, %65, %68;\n"
    "mov.b64 da, {ta, 0x40000040};\nmov.b64 db, {tb, 0x40000040};\n"
    "wgmma.mma_async.sync.aligned.m64n128k16.f32.bf16.bf16 "
    "{%0, %1, %2, %3, %4, %5, %6, %7, %8, %9, %10, %11, %12, %13, %14, %15, %16, %17, %18, %19, %20, %21, %22, %23, %24, %25, %26, %27, %28, %29, %30, %31, %32, %33, %34, %35, %36, %37, %38, %39, %40, %41, %42, %43, %44, %45, %46, %47, %48, %49, %50, %51, %52, %53, %54, %55, %56, %57, %58, %59, %60, %61, %62, %63}, "
    "da, db, p, 1, 1, 0, 1;\n}\n"
    : "+f"(d[0]), "+f"(d[1]), "+f"(d[2]), "+f"(d[3]), "+f"(d[4]), "+f"(d[5]), "+f"(d[6]), "+f"(d[7]), "+f"(d[8]), "+f"(d[9]), "+f"(d[10]), "+f"(d[11]), "+f"(d[12]), "+f"(d[13]), "+f"(d[14]), "+f"(d[15]), "+f"(d[16]), "+f"(d[17]), "+f"(d[18]), "+f"(d[19]), "+f"(d[20]), "+f"(d[21]), "+f"(d[22]), "+f"(d[23]), "+f"(d[24]), "+f"(d[25]), "+f"(d[26]), "+f"(d[27]), "+f"(d[28]), "+f"(d[29]), "+f"(d[30]), "+f"(d[31]), "+f"(d[32]), "+f"(d[33]), "+f"(d[34]), "+f"(d[35]), "+f"(d[36]), "+f"(d[37]), "+f"(d[38]), "+f"(d[39]), "+f"(d[40]), "+f"(d[41]), "+f"(d[42]), "+f"(d[43]), "+f"(d[44]), "+f"(d[45]), "+f"(d[46]), "+f"(d[47]), "+f"(d[48]), "+f"(d[49]), "+f"(d[50]), "+f"(d[51]), "+f"(d[52]), "+f"(d[53]), "+f"(d[54]), "+f"(d[55]), "+f"(d[56]), "+f"(d[57]), "+f"(d[58]), "+f"(d[59]), "+f"(d[60]), "+f"(d[61]), "+f"(d[62]), "+f"(d[63])
    : "r"(a_lo), "r"(b_lo), "r"(scaleD), "n"(OFFA), "n"(OFFB));
}

template <int OFFB>
__device__ __forceinline__ void wgmma_m64n128k16_rs_tb(float (&d)[64], uint32_t a0, uint32_t a1, uint32_t a2, uint32_t a3, uint32_t b_lo, int scaleD) {
  asm volatile("{\n.reg .pred p;\n.reg .b32 tb;\n.reg .b64 db;\nsetp.ne.b32 p, %69, 0;\n"
    "add.u32 tb, %68, %70;\n"
    "mov.b64 db, {tb, 0x40000040};\n"
    "wgmma.mma_async.sync.aligned.m64n128k16.f32.bf16.bf16 "
    "{%0, %1, %2, %3, %4, %5, %6, %7, %8, %9, %10, %11, %12, %13, %14, %15, %16, %17, %18, %19, %20, %21, %22, %23, %24, %25, %26, %27, %28, %29, %30, %31, %32, %33, %34, %35, %36, %37, %38, %39, %40, %41, %42, %43, %44, %45, %46, %47, %48, %49, %50, %51, %52, %53, %54, %55, %56, %57, %58, %59, %60, %61, %62, %63}, "
    "{%64, %65, %66, %67}, db, p, 1, 1, 1;\n}\n"
    : "+f"(d[0]), "+f"(d[1]), "+f"(d[2]), "+f"(d[3]), "+f"(d[4]), "+f"(d[5]), "+f"(d[6]), "+f"(d[7]), "+f"(d[8]), "+f"(d[9]), "+f"(d[10]), "+f"(d[11]), "+f"(d[12]), "+f"(d[13]), "+f"(d[14]), "+f"(d[15]), "+f"(d[16]), "+f"(d[17]), "+f"(d[18]), "+f"(d[19]), "+f"(d[20]), "+f"(d[21]), "+f"(d[22]), "+f"(d[23]), "+f"(d[24]), "+f"(d[25]), "+f"(d[26]), "+f"(d[27]), "+f"(d[28]), "+f"(d[29]), "+f"(d[30]), "+f"(d[31]), "+f"(d[32]), "+f"(d[33]), "+f"(d[34]), "+f"(d[35]), "+f"(d[36]), "+f"(d[37]), "+f"(d[38]), "+f"(d[39]), "+f"(d[40]), "+f"(d[41]), "+f"(d[42]), "+f"(d[43]), "+f"(d[44]), "+f"(d[45]), "+f"(d[46]), "+f"(d[47]), "+f"(d[48]), "+f"(d[49]), "+f"(d[50]), "+f"(d[51]), "+f"(d[52]), "+f"(d[53]), "+f"(d[54]), "+f"(d[55]), "+f"(d[56]), "+f"(d[57]), "+f"(d[58]), "+f"(d[59]), "+f"(d[60]), "+f"(d[61]), "+f"(d[62]), "+f"(d[63])
    : "r"(a0), "r"(a1), "r"(a2), "r"(a3), "r"(b_lo), "r"(scaleD), "n"(OFFB));
}

template <int OFFB>
__device__ __forceinline__ void wgmma_m64n128k16_rs(float (&d)[64], uint32_t a0, uint32_t a1, uint32_t a2, uint32_t a3, uint32_t b_lo, int scaleD) {
  asm volatile("{\n.reg .pred p;\n.reg .b32 tb;\n.reg .b64 db;\nsetp.ne.b32 p, %69, 0;\n"
    "add.u32 tb, %68, %70;\n"
    "mov.b64 db, {tb, 0x40000040};\n"
    "wgmma.mma_async.sync.aligned.m64n128k16.f32.bf16.bf16 "
    "{%0, %1, %2, %3, %4, %5, %6, %7, %8, %9, %10, %11, %12, %13, %14, %15, %16, %17, %18, %19, %20, %21, %22, %23, %24, %25, %26, %27, %28, %29, %30, %31, %32, %33, %34, %35, %36, %37, %38, %39, %40, %41, %42, %43, %44, %45, %46, %47, %48, %49, %50, %51, %52, %53, %54, %55, %56, %57, %58, %59, %60, %61, %62, %63}, "
    "{%64, %65, %66, %67}, db, p, 1, 1, 0;\n}\n"
    : "+f"(d[0]), "+f"(d[1]), "+f"(d[2]), "+f"(d[3]), "+f"(d[4]), "+f"(d[5]), "+f"(d[6]), "+f"(d[7]), "+f"(d[8]), "+f"(d[9]), "+f"(d[10]), "+f"(d[11]), "+f"(d[12]), "+f"(d[13]), "+f"(d[14]), "+f"(d[15]), "+f"(d[16]), "+f"(d[17]), "+f"(d[18]), "+f"(d[19]), "+f"(d[20]), "+f"(d[21]), "+f"(d[22]), "+f"(d[23]), "+f"(d[24]), "+f"(d[25]), "+f"(d[26]), "+f"(d[27]), "+f"(d[28]), "+f"(d[29]), "+f"(d[30]), "+f"(d[31]), "+f"(d[32]), "+f"(d[33]), "+f"(d[34]), "+f"(d[35]), "+f"(d[36]), "+f"(d[37]), "+f"(d[38]), "+f"(d[39]), "+f"(d[40]), "+f"(d[41]), "+f"(d[42]), "+f"(d[43]), "+f"(d[44]), "+f"(d[45]), "+f"(d[46]), "+f"(d[47]), "+f"(d[48]), "+f"(d[49]), "+f"(d[50]), "+f"(d[51]), "+f"(d[52]), "+f"(d[53]), "+f"(d[54]), "+f"(d[55]), "+f"(d[56]), "+f"(d[57]), "+f"(d[58]), "+f"(d[59]), "+f"(d[60]), "+f"(d[61]), "+f"(d[62]), "+f"(d[63])
    : "r"(a0), "r"(a1), "r"(a2), "r"(a3), "r"(b_lo), "r"(scaleD), "n"(OFFB));
}

__device__ __forceinline__ uint4 ldg_nc_v4(const void* p) {
  uint4 v;
    asm volatile("{\n.reg .b64 pol;\ncreatepolicy.fractional.L2::evict_first.b64 pol, 1.0;\n"
                 "ld.global.nc.L1::no_allocate.L2::cache_hint.v4.u32 {%0, %1, %2, %3}, [%4], pol;\n}\n" : "=r"(v.x), "=r"(v.y), "=r"(v.z), "=r"(v.w) : "l"(p));
  return v;
}
__device__ __forceinline__ uint64_t pol_normal() {
  uint64_t p; asm volatile("createpolicy.fractional.L2::evict_normal.b64 %0, 1.0;" : "=l"(p)); return p;
}
__device__ __forceinline__ void unpack8(const uint4& u, float (&v)[8]) {
  v[0] = bflo(u.x); v[1] = bfhi(u.x); v[2] = bflo(u.y); v[3] = bfhi(u.y);
  v[4] = bflo(u.z); v[5] = bfhi(u.z); v[6] = bflo(u.w); v[7] = bfhi(u.w);
}
__device__ __forceinline__ void fma8(float (&acc)[8], float s, const uint4& w) {
  acc[0] = fmaf(s, bflo(w.x), acc[0]); acc[1] = fmaf(s, bfhi(w.x), acc[1]); acc[2] = fmaf(s, bflo(w.y), acc[2]); acc[3] = fmaf(s, bfhi(w.y), acc[3]);
  acc[4] = fmaf(s, bflo(w.z), acc[4]); acc[5] = fmaf(s, bfhi(w.z), acc[5]); acc[6] = fmaf(s, bflo(w.w), acc[6]); acc[7] = fmaf(s, bfhi(w.w), acc[7]);
}
__device__ __forceinline__ float rcp_approx(float x) { float y; asm("rcp.approx.ftz.f32 %0, %1;" : "=f"(y) : "f"(x)); return y; }
__device__ __forceinline__ float sigmoid_f(float v) { return rcp_approx(1.0f + ex2_approx(v * -1.4426950408889634f)); }
__device__ __forceinline__ float silu_bf(float v) { return rbf(v * sigmoid_f(v)); }
__device__ __forceinline__ uint32_t rank_key(float r, int idx) {
  const uint32_t b = __float_as_uint(r) >> 16;
  const uint32_t u = (r != r) ? 0u : ((b & 0x8000u) ? (~b & 0xffffu) : (b | 0x8000u));
  return (u << 16) | (0xffffu - (uint32_t)idx);
}
__device__ __forceinline__ void warp_top2(uint32_t& k1, uint32_t& k2) {
  const uint32_t m1 = __reduce_max_sync(0xffffffffu, k1);
  k2 = __reduce_max_sync(0xffffffffu, k1 == m1 ? k2 : k1);
  k1 = m1;
}
__device__ __forceinline__ uint32_t bmul2(uint32_t a, uint32_t b) { uint32_t r; asm("mul.rn.bf16x2 %0, %1, %2;" : "=r"(r) : "r"(a), "r"(b)); return r; }
__device__ __forceinline__ uint32_t badd2(uint32_t a, uint32_t b) { uint32_t r; asm("add.rn.bf16x2 %0, %1, %2;" : "=r"(r) : "r"(a), "r"(b)); return r; }
__device__ __forceinline__ uint32_t bsub2(uint32_t a, uint32_t b) { uint32_t r; asm("sub.rn.bf16x2 %0, %1, %2;" : "=r"(r) : "r"(a), "r"(b)); return r; }
__device__ __forceinline__ float sqrt_approx(float x) { float y; asm("sqrt.approx.f32 %0, %1;" : "=f"(y) : "f"(x)); return y; }
__device__ __forceinline__ uint32_t ln_norm2(uint32_t x1, uint32_t mb2, float inv) {
  const uint32_t d = bsub2(x1, mb2);
  return pack_bf16(bflo(d) * inv, bfhi(d) * inv);
}
__device__ __forceinline__ uint32_t bfma2(uint32_t a, uint32_t b, uint32_t c) { uint32_t r; asm("fma.rn.bf16x2 %0, %1, %2, %3;" : "=r"(r) : "r"(a), "r"(b), "r"(c)); return r; }
__device__ __forceinline__ uint32_t ln_norm2b(uint32_t x1, uint32_t mb2, uint32_t ih, uint32_t il) {
  const uint32_t d = bsub2(x1, mb2);
  return bfma2(d, ih, bmul2(d, il));
}
__device__ __forceinline__ uint32_t ln_mod2(uint32_t x1, uint32_t mb2, float inv, uint32_t c1, uint32_t sb) { return badd2(bmul2(ln_norm2(x1, mb2, inv), c1), sb); }
__device__ __forceinline__ void ldmatrix_x4(uint32_t addr, uint32_t& r0, uint32_t& r1, uint32_t& r2, uint32_t& r3) {
  asm volatile("ldmatrix.sync.aligned.m8n8.x4.shared.b16 {%0, %1, %2, %3}, [%4];" : "=r"(r0), "=r"(r1), "=r"(r2), "=r"(r3) : "r"(addr) : "memory");
}
__device__ __forceinline__ uint4 ldg_stream_v4(const void* p, uint64_t pol) {
  uint4 v; asm volatile("ld.global.nc.L1::no_allocate.L2::cache_hint.L2::128B.v4.u32 {%0, %1, %2, %3}, [%4], %5;" : "=r"(v.x), "=r"(v.y), "=r"(v.z), "=r"(v.w) : "l"(p), "l"(pol)); return v;
}
__device__ __forceinline__ void bulk_load_hint(uint32_t dst, const void* src, uint32_t bytes, uint32_t bar, uint64_t pol) {
  asm volatile("cp.async.bulk.shared::cluster.global.mbarrier::complete_tx::bytes.L2::cache_hint [%0], [%1], %2, [%3], %4;"
    :: "r"(dst), "l"(src), "r"(bytes), "r"(bar), "l"(pol) : "memory");
}
__device__ __forceinline__ void red_release_add(unsigned int* p, unsigned int v) { asm volatile("red.release.gpu.global.add.u32 [%0], %1;" :: "l"(p), "r"(v) : "memory"); }
__device__ __forceinline__ unsigned int ld_acquire(const unsigned int* p) { unsigned int v; asm volatile("ld.acquire.gpu.global.u32 %0, [%1];" : "=r"(v) : "l"(p) : "memory"); return v; }
__device__ __forceinline__ void spin_until(const unsigned int* p, unsigned int target) {
  #pragma unroll 1
  for (unsigned int i = 0; i < (1u << 22); i++) { if (ld_acquire(p) >= target) return; }
}
__device__ __forceinline__ float lds_f32(uint32_t a) { float v; asm volatile("ld.shared.f32 %0, [%1];" : "=f"(v) : "r"(a) : "memory"); return v; }
__device__ __forceinline__ float2 lds_f32x2(uint32_t a) { float2 v; asm volatile("ld.shared.v2.f32 {%0, %1}, [%2];" : "=f"(v.x), "=f"(v.y) : "r"(a) : "memory"); return v; }
__device__ __forceinline__ uint2 lds_u32x2(uint32_t a) { uint2 v; asm volatile("ld.shared.v2.u32 {%0, %1}, [%2];" : "=r"(v.x), "=r"(v.y) : "r"(a) : "memory"); return v; }
__device__ __forceinline__ uint32_t lds_u32(uint32_t a) { uint32_t v; asm volatile("ld.shared.u32 %0, [%1];" : "=r"(v) : "r"(a) : "memory"); return v; }
__device__ __forceinline__ void sts_u32(uint32_t a, uint32_t v) { asm volatile("st.shared.u32 [%0], %1;" :: "r"(a), "r"(v) : "memory"); }
__device__ __forceinline__ void sts_u32x2(uint32_t a, uint32_t x, uint32_t y) { asm volatile("st.shared.v2.u32 [%0], {%1, %2};" :: "r"(a), "r"(x), "r"(y) : "memory"); }
__device__ __forceinline__ void sts_f32(uint32_t a, float v) { asm volatile("st.shared.f32 [%0], %1;" :: "r"(a), "f"(v) : "memory"); }
__device__ __forceinline__ void sts_f32x2(uint32_t a, float x, float y) { asm volatile("st.shared.v2.f32 [%0], {%1, %2};" :: "r"(a), "f"(x), "f"(y) : "memory"); }
__device__ __forceinline__ void sts_f32x4(uint32_t a, float x, float y, float z, float w) { asm volatile("st.shared.v4.f32 [%0], {%1, %2, %3, %4};" :: "r"(a), "f"(x), "f"(y), "f"(z), "f"(w) : "memory"); }

__device__ __forceinline__ uint4 lds_u32x4(uint32_t a) { uint4 v; asm volatile("ld.shared.v4.u32 {%0, %1, %2, %3}, [%4];" : "=r"(v.x), "=r"(v.y), "=r"(v.z), "=r"(v.w) : "r"(a) : "memory"); return v; }
__device__ __forceinline__ void sts_u32x4(uint32_t a, uint32_t x, uint32_t y, uint32_t z, uint32_t w) { asm volatile("st.shared.v4.u32 [%0], {%1, %2, %3, %4};" :: "r"(a), "r"(x), "r"(y), "r"(z), "r"(w) : "memory"); }
__device__ __forceinline__ void st_tagged(float* p, float v) {
  const uint32_t b = __float_as_uint(v);
  asm volatile("st.relaxed.gpu.global.u32 [%0], %1;" :: "l"(p), "r"(b == 0u ? 0x80000000u : b) : "memory");
}
__device__ __forceinline__ void st_tagged4(float* p, float x, float y, float z, float w) {
  const uint32_t a = __float_as_uint(x), b = __float_as_uint(y), c = __float_as_uint(z), d = __float_as_uint(w);
  asm volatile("st.relaxed.gpu.global.v4.u32 [%0], {%1, %2, %3, %4};" :: "l"(p), "r"(a == 0u ? 0x80000000u : a), "r"(b == 0u ? 0x80000000u : b),
               "r"(c == 0u ? 0x80000000u : c), "r"(d == 0u ? 0x80000000u : d) : "memory");
}
__device__ __forceinline__ void st_relaxed2(void* p, uint32_t a, uint32_t b) { asm volatile("st.relaxed.gpu.global.v2.u32 [%0], {%1, %2};" :: "l"(p), "r"(a), "r"(b) : "memory"); }
__device__ __forceinline__ float4 ld_tagged4(const float* p) {
  float4 v; asm volatile("ld.relaxed.gpu.global.v4.f32 {%0, %1, %2, %3}, [%4];" : "=f"(v.x), "=f"(v.y), "=f"(v.z), "=f"(v.w) : "l"(p) : "memory"); return v;
}
__device__ __forceinline__ bool tagged4(const float4& v) {
  return __float_as_uint(v.x) != 0u && __float_as_uint(v.y) != 0u && __float_as_uint(v.z) != 0u && __float_as_uint(v.w) != 0u;
}
__device__ __forceinline__ void hint_arrive(uint32_t* p) { asm volatile("red.relaxed.gpu.global.add.u32 [%0], 1;" :: "l"(p) : "memory"); }
__device__ __forceinline__ void hint_wait(const uint32_t* p, uint32_t target) {
  uint32_t v = 0u;
  #pragma unroll 1
  for (unsigned int i = 0; i < (1u << 22) && v < target; i++) asm volatile("ld.relaxed.gpu.global.u32 %0, [%1];" : "=r"(v) : "l"(p) : "memory");
}
__device__ __forceinline__ void fence_proxy_async_global() { asm volatile("fence.proxy.async.global;" ::: "memory"); }

#define H_SPLIT 1
#define X_DLY 1200
#define W_DLY 1900
#define W_FIRST 2200
#define PRE_B 2
#define H_PREG 1
template <int J0, int J1>
__device__ __forceinline__ void load_parts(float2 (&pa)[J1 - J0][4], int t2) {
  #pragma unroll
  for (int j = J0; j < J1; j++)
    #pragma unroll
    for (int k = 0; k < 4; k++)
      asm volatile("ld.relaxed.gpu.global.v2.f32 {%0, %1}, [%2];" : "=f"(pa[j - J0][k].x), "=f"(pa[j - J0][k].y)
                   : "l"(g_modpart + k * 2 * T_D + (t2 >> 7) * T_D + j * 256 + (t2 & 127) * 2) : "memory");
}
template <int J0, int J1>
__device__ __forceinline__ void finish_parts(float2 (&pa)[J1 - J0][4], bool loaded, int t2, uint32_t tab) {
  #pragma unroll 1
  for (unsigned int spin = 0; spin < (1u << 22); spin++) {
    if (!loaded) load_parts<J0, J1>(pa, t2);
    loaded = false;
    bool ok = true;
    #pragma unroll
    for (int j = 0; j < J1 - J0; j++)
      #pragma unroll
      for (int k = 0; k < 4; k++) ok &= (__float_as_uint(pa[j][k].x) != 0u) & (__float_as_uint(pa[j][k].y) != 0u);
    if (__all_sync(0xffffffffu, ok)) break;
  }
  #pragma unroll
  for (int j = J0; j < J1; j++) {
    const float2* q = pa[j - J0];
    const uint32_t m = pack_bf16(((q[0].x + q[1].x) + q[2].x) + q[3].x, ((q[0].y + q[1].y) + q[2].y) + q[3].y);
    sts_u32(tab + (t2 >> 7) * 2048 + j * 512 + (t2 & 127) * 4, t2 >= 128 ? badd2(m, 0x3F803F80u) : m);
  }
}
__device__ __forceinline__ void head_phase(uint32_t scr, uint32_t xs, uint32_t b_x, uint32_t b_go, uint32_t b_head, int t2, uint32_t zero, const bf16* __restrict__ cvec, const bf16* __restrict__ w_mod) {
  const int lane = t2 & 31, w8 = t2 >> 5;
  const int cb = blockIdx.x & 31, ks = blockIdx.x >> 5;
  const bool early = (cb & 15) < 4 * H_SPLIT;
  const uint32_t ws = (xs - 32768 + (t2 >> 3) * 128 + (((t2 ^ (t2 >> 3)) & 7) << 4)) ^ zero;
  const float cv = __bfloat162float(cvec[ks * 256 + t2]);
  const bf16* wsrc = w_mod + (size_t)(ks * 256 + (t2 >> 3)) * (6 * T_D) + cb * 64 + (t2 & 7) * 8;
  if (early) {
    const uint64_t pol = policy_evict_first();
    #pragma unroll 2
    for (int i = 0; i < 8; i++)
      asm volatile("cp.async.cg.shared.global.L2::cache_hint [%0], [%1], 16, %2;" :: "r"(ws + i * 4096), "l"(wsrc + (size_t)i * 32 * 6 * T_D), "l"(pol) : "memory");
  }
  sts_f32(scr + t2 * 4, silu_bf(cv));
  named_bar_sync(6, 384);
  TL_MARK2(1, t2 == 0);
  uint4 xv[2][4];
  uint32_t mb2[2], ih[2], il[2];
  auto norm = [&](int j) {
    #pragma unroll
    for (int r = 0; r < 2; r++) {
      xv[r][j].x = ln_norm2b(xv[r][j].x, mb2[r], ih[r], il[r]); xv[r][j].y = ln_norm2b(xv[r][j].y, mb2[r], ih[r], il[r]);
      xv[r][j].z = ln_norm2b(xv[r][j].z, mb2[r], ih[r], il[r]); xv[r][j].w = ln_norm2b(xv[r][j].w, mb2[r], ih[r], il[r]);
    }
  };
  auto modulate = [&](int j) {
    const uint4 sa = lds_u32x4(scr + 8192 + j * 512 + lane * 16), c1 = lds_u32x4(scr + 8192 + 2048 + j * 512 + lane * 16);
    #pragma unroll
    for (int r = 0; r < 2; r++) {
      xv[r][j].x = badd2(bmul2(xv[r][j].x, c1.x), sa.x); xv[r][j].y = badd2(bmul2(xv[r][j].y, c1.y), sa.y);
      xv[r][j].z = badd2(bmul2(xv[r][j].z, c1.z), sa.z); xv[r][j].w = badd2(bmul2(xv[r][j].w, c1.w), sa.w);
    }
  };
  auto store = [&](int j) {
    #pragma unroll
    for (int r = 0; r < 2; r++) *reinterpret_cast<uint4*>(g_h + (size_t)(blockIdx.x * 16 + 2 * w8 + r) * T_D + j * 256 + lane * 8) = xv[r][j];
  };
  #pragma unroll 1
  for (int ph = 0; ph < 2; ph++) {
    if ((ph == 0) == early) {
      asm volatile("cp.async.wait_all;" ::: "memory");
      if (!early) mbar_wait(b_x + 168, 0);
      float acc[8];
      #pragma unroll
      for (int j = 0; j < 8; j++) acc[j] = 0.f;
      #pragma unroll
      for (int i = 0; i < 8; i++) fma8(acc, lds_f32(scr + ((t2 >> 3) + 32 * i) * 4), lds_u32x4(ws + i * 4096));
      #pragma unroll
      for (int j = 0; j < 4; j++) { const bool up = lane & 16; acc[j] = (up ? acc[4 + j] : acc[j]) + __shfl_xor_sync(0xffffffffu, up ? acc[j] : acc[4 + j], 16); }
      #pragma unroll
      for (int j = 0; j < 2; j++) { const bool up = lane & 8; acc[j] = (up ? acc[2 + j] : acc[j]) + __shfl_xor_sync(0xffffffffu, up ? acc[j] : acc[2 + j], 8); }
      sts_f32x2(scr + 1024 + w8 * 256 + (lane & 7) * 32 + (lane >> 3) * 8, acc[0], acc[1]);
      named_bar_sync(5, 256);
      if (t2 < 64) {
        float sum = 0.f;
        #pragma unroll
        for (int i = 0; i < 8; i++) sum += lds_f32(scr + 1024 + i * 256 + t2 * 4);
        st_tagged(g_modpart + ks * 2 * T_D + cb * 64 + t2, sum);
        TL_MARK2(early ? 2 : 6, t2 == 0);
      }
    } else {
      float2 pa[H_SPLIT][4];
      mbar_wait(b_x, 0);
      TL_MARK2(18, t2 == 0);
      if (H_PREG) load_parts<0, H_SPLIT>(pa, t2);
      #pragma unroll
      for (int r = 0; r < 2; r++)
        #pragma unroll
        for (int j = 0; j < 4; j++) xv[r][j] = lds_u32x4(xs + (2 * w8 + r) * 2048 + j * 512 + lane * 16);
  {
    float st[4] = {0.f, 0.f, 0.f, 0.f};
    #pragma unroll
    for (int r = 0; r < 2; r++)
      #pragma unroll
      for (int j = 0; j < 4; j++) {
        float v[8];
        unpack8(xv[r][j], v);
        st[2 * r] += ((v[0] + v[1]) + (v[2] + v[3])) + ((v[4] + v[5]) + (v[6] + v[7]));
        st[2 * r + 1] += fmaf(v[0], v[0], fmaf(v[1], v[1], fmaf(v[2], v[2], v[3] * v[3]))) + fmaf(v[4], v[4], fmaf(v[5], v[5], fmaf(v[6], v[6], v[7] * v[7])));
      }
    #pragma unroll
    for (int k = 0; k < 2; k++) { const bool up = lane & 16; st[k] = (up ? st[2 + k] : st[k]) + __shfl_xor_sync(0xffffffffu, up ? st[k] : st[2 + k], 16); }
    #pragma unroll
    for (int o = 8; o > 0; o >>= 1) { st[0] += __shfl_xor_sync(0xffffffffu, st[0], o); st[1] += __shfl_xor_sync(0xffffffffu, st[1], o); }
    const float mean = st[0] * (1.0f / T_D);
    const float inv = rcp_approx(rbf(sqrt_approx(rbf(rbf(fmaxf(fmaf(-mean, mean, st[1] * (1.0f / T_D)), 0.f)) + 1e-05f))));
    const uint32_t m = pack_bf16(mean, mean), h = pack_bf16(inv - rbf(inv), inv);
    #pragma unroll
    for (int r = 0; r < 2; r++) {
      mb2[r] = __shfl_sync(0xffffffffu, m, 16 * r);
      const uint32_t hr = __shfl_sync(0xffffffffu, h, 16 * r);
      ih[r] = __byte_perm(hr, hr, 0x3232); il[r] = __byte_perm(hr, hr, 0x1010);
    }
  }
      #pragma unroll
      for (int j = 0; j < H_SPLIT; j++) norm(j);
      TL_MARK2(5, t2 == 0);
      finish_parts<0, H_SPLIT>(pa, H_PREG, t2, scr + 8192);
      named_bar_sync(5, 256);
      TL_MARK2(7, t2 == 0);
      #pragma unroll
      for (int j = 0; j < H_SPLIT; j++) { modulate(j); store(j); }
      named_bar_arrive(9, 288);
    }
  }
  #pragma unroll
  for (int j = H_SPLIT; j < 4; j++) norm(j);
  float2 pb[4 - H_SPLIT][4];
  finish_parts<H_SPLIT, 4>(pb, false, t2, scr + 8192);
  named_bar_sync(5, 256);
  TL_MARK2(17, t2 == 0);
  #pragma unroll
  for (int j = H_SPLIT; j < 4; j++) modulate(j);
  __syncwarp();
  if (lane == 0) mbar_arrive(b_head + (xv[1][3].w & zero));
  mbar_wait(b_go, 0);
  #pragma unroll
  for (int j = H_SPLIT; j < 4; j++) store(j);
  named_bar_arrive(8, 288);
}

#define MOD_AT (b_empty + 8)
#define MOD_PF 0
#define MOD_SPLIT 16
__device__ __forceinline__ void mod_rest(uint32_t scr, uint32_t b_go, int t, const bf16* __restrict__ cvec, const bf16* __restrict__ w_mod, const bf16* __restrict__ w_r) {
  const int lane = t & 31;
  #pragma unroll 1
  for (int i = t; i < T_D / 2; i += 64) {
    const uint32_t c2 = *reinterpret_cast<const uint32_t*>(cvec + 2 * i);
    sts_u32(scr + i * 4, pack_bf16(silu_bf(bflo(c2)), silu_bf(bfhi(c2))));
  }
  named_bar_sync(11, 64);
  const bf16* wp = w_mod + (size_t)(2 * (t >> 2)) * (6 * T_D) + 2 * T_D + blockIdx.x * 32 + (t & 3) * 8;
  float acc[8];
  #pragma unroll
  for (int i = 0; i < 8; i++) acc[i] = 0.f;
  #pragma unroll 1
  for (int i = 0; i < 32; i += 2) {
    if (i == MOD_SPLIT) mbar_wait(b_go, 0);
    const uint4 w0 = ldg_nc_v4(wp), w1 = ldg_nc_v4(wp + 6 * T_D), w2 = ldg_nc_v4(wp + 32 * 6 * T_D), w3 = ldg_nc_v4(wp + 33 * 6 * T_D);
    wp += 64 * 6 * T_D;
    const uint32_t s0 = lds_u32(scr + (i * 16 + (t >> 2)) * 4), s1 = lds_u32(scr + (i * 16 + 16 + (t >> 2)) * 4);
    fma8(acc, bflo(s0), w0); fma8(acc, bfhi(s0), w1); fma8(acc, bflo(s1), w2); fma8(acc, bfhi(s1), w3);
  }
  #pragma unroll
  for (int j = 0; j < 4; j++) { const bool up = lane & 16; acc[j] = (up ? acc[4 + j] : acc[j]) + __shfl_xor_sync(0xffffffffu, up ? acc[j] : acc[4 + j], 16); }
  #pragma unroll
  for (int j = 0; j < 2; j++) { const bool up = lane & 8; acc[j] = (up ? acc[2 + j] : acc[j]) + __shfl_xor_sync(0xffffffffu, up ? acc[j] : acc[2 + j], 8); }
  { const bool up = lane & 4; acc[0] = (up ? acc[1] : acc[0]) + __shfl_xor_sync(0xffffffffu, up ? acc[0] : acc[1], 4); }
  if (t >= 32) sts_f32(scr + 2048 + lane * 4, acc[0]);
  named_bar_sync(11, 64);
  if (__shfl_sync(0xffffffffu, t, 0) < 32) {
    const int kind = blockIdx.x >> 5;
    float v = rbf(acc[0] + lds_f32(scr + 2048 + lane * 4));
    const int col = (blockIdx.x & 31) * 32 + (lane & 3) * 8 + (lane >> 2);
    uint8_t* dst = g_col + (col >> 7) * 1536;
    if (kind == 2) v = rbf(1.0f + v);
    float vw = v * __bfloat162float(w_r[col]);
    if (kind == 2) {
      const int c = col & 127, i = (c & ~15) + ((c >> 1) & 3) * 4 + ((c >> 3) & 1) * 2 + (c & 1);
      reinterpret_cast<bf16*>(dst)[i] = __float2bfloat16_rn(vw);
      reinterpret_cast<bf16*>(dst)[128 + i] = __float2bfloat16_rn(vw - rbf(vw));
    }
    reinterpret_cast<bf16*>(dst + 512 + (kind & 1) * 512 + (kind >> 1) * 256)[col & 127] = __float2bfloat16_rn(v);
    #pragma unroll
    for (int o = 16; o > 0; o >>= 1) vw += __shfl_xor_sync(0xffffffffu, vw, o);
    if (lane == 0 && (kind == 1 || kind == 2)) g_scal[95 - blockIdx.x] = vw;
  }
  #pragma unroll 1
  for (int i = blockIdx.x * 64 + t; i < (int)(sizeof(g_mail) / 16); i += 128 * 64) reinterpret_cast<uint4*>(&g_mail)[i] = make_uint4(0u, 0u, 0u, 0u);
  named_bar_sync(11, 64);
  if (t == 0) red_release_add(&g_hcnt[0], 1u);
}

#define HPOL_A pol_normal()
#define HPOL_B pol_normal()
#define HMAP_A &tmOl
#define HMAP_B &tmWo
constexpr int AT_NBLK = T_SEQ / 128;
constexpr float AT_HEAD = 7.0f;
#define WO_LATE 12
constexpr int QP_STAG = 3;
constexpr int AT_SPLIT = 28, AT_PIN = 8, PINB = 4;
constexpr int AT_NFULL = 124;
constexpr int AT_PREG = 40, AT_CREG = 232;
constexpr uint32_t AT_SQ = 5 * 32768;
constexpr float AT_C = 0.08838834764831845f * 1.4426950408889634f;
constexpr float AT_RAW_LO = -16.0f, AT_RAW_HI = 24.0f;
constexpr float AT_RAW_SUM = 281474976710656.0f, AT_RAW_MIN = 9.094947017729282e-13f;
constexpr uint32_t AT_SBAR = AT_SQ + 65536 + 256;
constexpr uint32_t AT_SMEM = AT_SQ + 65536 + 3072;

__device__ __forceinline__ uint32_t ring_slot(uint32_t t) { return t - 5u * ((t * 205u) >> 10); }
__device__ __forceinline__ uint32_t qp_pos(uint32_t j, uint32_t it) { return 4u * it + (j & 3u) + ((j & 3u) == 3u ? it : 0u); }
__device__ __forceinline__ uint32_t ring_par(uint32_t t) { return ((t * 205u) >> 10) & 1u; }
__device__ __forceinline__ void softmax_rowmax(const float (&s)[64], float& mx0, float& mx1) {
  float a0 = fmaxf(s[0], s[1]), a1 = fmaxf(s[4], s[5]), a2 = fmaxf(s[8], s[9]), a3 = fmaxf(s[12], s[13]);
  float b0 = fmaxf(s[2], s[3]), b1 = fmaxf(s[6], s[7]), b2 = fmaxf(s[10], s[11]), b3 = fmaxf(s[14], s[15]);
  #pragma unroll
  for (int j = 4; j < 16; j += 4) {
    a0 = fmaxf(a0, fmaxf(s[4 * j + 0], s[4 * j + 1]));  b0 = fmaxf(b0, fmaxf(s[4 * j + 2], s[4 * j + 3]));
    a1 = fmaxf(a1, fmaxf(s[4 * j + 4], s[4 * j + 5]));  b1 = fmaxf(b1, fmaxf(s[4 * j + 6], s[4 * j + 7]));
    a2 = fmaxf(a2, fmaxf(s[4 * j + 8], s[4 * j + 9]));  b2 = fmaxf(b2, fmaxf(s[4 * j + 10], s[4 * j + 11]));
    a3 = fmaxf(a3, fmaxf(s[4 * j + 12], s[4 * j + 13])); b3 = fmaxf(b3, fmaxf(s[4 * j + 14], s[4 * j + 15]));
  }
  mx0 = fmaxf(fmaxf(a0, a1), fmaxf(a2, a3));
  mx1 = fmaxf(fmaxf(b0, b1), fmaxf(b2, b3));
  mx0 = fmaxf(mx0, __shfl_xor_sync(0xffffffffu, mx0, 1));
  mx1 = fmaxf(mx1, __shfl_xor_sync(0xffffffffu, mx1, 1));
  mx0 = fmaxf(mx0, __shfl_xor_sync(0xffffffffu, mx0, 2));
  mx1 = fmaxf(mx1, __shfl_xor_sync(0xffffffffu, mx1, 2));
}
__device__ __forceinline__ void softmax_sub(float (&s)[64], float mc0, float mc1) {
  #pragma unroll
  for (int j = 0; j < 16; j++) { s[4 * j] -= mc0; s[4 * j + 1] -= mc0; s[4 * j + 2] -= mc1; s[4 * j + 3] -= mc1; }
}
template <int LO, int HI>
__device__ __forceinline__ void softmax_exp(float (&s)[64]) {
  #pragma unroll
  for (int i = LO; i < HI; i++) s[i] = ex2_approx(s[i]);
}
__device__ __forceinline__ bool softmax_mode(const float (&s)[64], float& mc0, float& mc1) {
  softmax_rowmax(s, mc0, mc1);
  const bool raw = __all_sync(0xffffffffu, mc0 >= AT_RAW_LO && mc0 <= AT_RAW_HI && mc1 >= AT_RAW_LO && mc1 <= AT_RAW_HI);
  mc0 += AT_HEAD; mc1 += AT_HEAD;
  return raw;
}
__device__ __forceinline__ void rowsum_p(const uint32_t (&p)[32], uint32_t& t0, uint32_t& t1) {
  uint32_t a[16];
  #pragma unroll
  for (int i = 0; i < 8; i++) { a[2 * i] = badd2(p[4 * i], p[4 * i + 2]); a[2 * i + 1] = badd2(p[4 * i + 1], p[4 * i + 3]); }
  #pragma unroll
  for (int i = 0; i < 4; i++) { a[2 * i] = badd2(a[4 * i], a[4 * i + 2]); a[2 * i + 1] = badd2(a[4 * i + 1], a[4 * i + 3]); }
  t0 = badd2(badd2(a[0], a[2]), badd2(a[4], a[6]));
  t1 = badd2(badd2(a[1], a[3]), badd2(a[5], a[7]));
}
__device__ __forceinline__ void add_rowsum(const uint32_t (&p)[32], float& l0, float& l1) {
  uint32_t t0, t1;
  rowsum_p(p, t0, t1);
  l0 += bflo(t0) + bfhi(t0); l1 += bflo(t1) + bfhi(t1);
}
__device__ __forceinline__ void pack_p(uint32_t (&p)[32], const float (&s)[64]) {
  #pragma unroll
  for (int i = 0; i < 32; i++) p[i] = pack_bf16(s[2 * i], s[2 * i + 1]);
}
__device__ __noinline__ void attn_rows_exact(uint32_t sq, uint32_t so, int hsel, const bf16* __restrict__ kh, const bf16* __restrict__ vh) {
  const int warp = (threadIdx.x >> 5) & 3, lane = threadIdx.x & 31;
  const size_t hofs = (size_t)((blockIdx.x < 128 ? blockIdx.x >> 4 : 15) * 2 + hsel) * T_SEQ * T_DH;
  kh += hofs; vh += hofs;
  #pragma unroll 1
  for (int r = 16 * warp; r < 16 * warp + 16; r++) {
    const uint32_t ad = (lane >> 4) * 16384 + r * 128 + ((((lane & 15) >> 1) ^ (r & 7)) << 4) + (lane & 1) * 8;
    uint2 qv; asm volatile("ld.shared.v2.u32 {%0, %1}, [%2];" : "=r"(qv.x), "=r"(qv.y) : "r"(sq + ad) : "memory");
    const float q0 = bflo(qv.x), q1 = bfhi(qv.x), q2 = bflo(qv.y), q3 = bfhi(qv.y);
    float m = -INFINITY, l = 0.f, o0 = 0.f, o1 = 0.f, o2 = 0.f, o3 = 0.f;
    #pragma unroll 1
    for (int key = 0; key < T_SEQ; key++) {
      const uint2 kv = *reinterpret_cast<const uint2*>(kh + (size_t)key * T_DH + lane * 4);
      const uint2 vv = *reinterpret_cast<const uint2*>(vh + (size_t)key * T_DH + lane * 4);
      float sc = (q0 * bflo(kv.x) + q1 * bfhi(kv.x)) + (q2 * bflo(kv.y) + q3 * bfhi(kv.y));
      #pragma unroll
      for (int o = 16; o > 0; o >>= 1) sc += __shfl_xor_sync(0xffffffffu, sc, o);
      const float mn = fmaxf(m, sc);
      const float al = (m == mn) ? 1.0f : ex2_approx(m - mn), p = rbf(ex2_approx(sc - mn));
      m = mn;
      l = fmaf(l, al, p);
      o0 = fmaf(o0, al, p * bflo(vv.x)); o1 = fmaf(o1, al, p * bfhi(vv.x));
      o2 = fmaf(o2, al, p * bflo(vv.y)); o3 = fmaf(o3, al, p * bfhi(vv.y));
    }
    const float inv = rcp_approx(l);
    asm volatile("st.shared.v2.u32 [%0], {%1, %2};" :: "r"(so + ad), "r"(pack_bf16(o0 * inv, o1 * inv)), "r"(pack_bf16(o2 * inv, o3 * inv)) : "memory");
  }
}
__device__ __forceinline__ void issue_qk(float (&s)[64], const uint32_t (&q)[32], uint32_t k_lo) {
  wgmma_fence();
  wgmma_m64n128k16_rs<0>(s, q[0], q[1], q[2], q[3], k_lo, 0);
  wgmma_m64n128k16_rs<2>(s, q[4], q[5], q[6], q[7], k_lo, 1);
  wgmma_m64n128k16_rs<4>(s, q[8], q[9], q[10], q[11], k_lo, 1);
  wgmma_m64n128k16_rs<6>(s, q[12], q[13], q[14], q[15], k_lo, 1);
  wgmma_m64n128k16_rs<1024>(s, q[16], q[17], q[18], q[19], k_lo, 1);
  wgmma_m64n128k16_rs<1026>(s, q[20], q[21], q[22], q[23], k_lo, 1);
  wgmma_m64n128k16_rs<1028>(s, q[24], q[25], q[26], q[27], k_lo, 1);
  wgmma_m64n128k16_rs<1030>(s, q[28], q[29], q[30], q[31], k_lo, 1);
  wgmma_commit();
}
__device__ __forceinline__ void issue_pv(float (&o)[64], const uint32_t (&p)[32], uint32_t v_lo, int accumulate) {
  wgmma_fence();
  wgmma_m64n128k16_rs_tb<0>(o, p[0], p[1], p[2], p[3], v_lo, accumulate);
  wgmma_m64n128k16_rs_tb<128>(o, p[4], p[5], p[6], p[7], v_lo, 1);
  wgmma_m64n128k16_rs_tb<256>(o, p[8], p[9], p[10], p[11], v_lo, 1);
  wgmma_m64n128k16_rs_tb<384>(o, p[12], p[13], p[14], p[15], v_lo, 1);
  wgmma_m64n128k16_rs_tb<512>(o, p[16], p[17], p[18], p[19], v_lo, 1);
  wgmma_m64n128k16_rs_tb<640>(o, p[20], p[21], p[22], p[23], v_lo, 1);
  wgmma_m64n128k16_rs_tb<768>(o, p[24], p[25], p[26], p[27], v_lo, 1);
  wgmma_m64n128k16_rs_tb<896>(o, p[28], p[29], p[30], p[31], v_lo, 1);
  wgmma_commit();
}
__device__ __forceinline__ void block_end(uint32_t zero, uint32_t bar) {
  #pragma unroll 1
  for (uint32_t i = 0; i < zero; i++) mbar_arrive(bar);
}
__device__ __forceinline__ void rescale_o(float (&o)[64], float al0, float al1) {
  #pragma unroll
  for (int j = 0; j < 16; j++) { o[4 * j] *= al0; o[4 * j + 1] *= al0; o[4 * j + 2] *= al1; o[4 * j + 3] *= al1; }
}

__device__ __forceinline__ void stage_o(const float (&o)[64], float i0, float i1, uint32_t dst, int lane) {
  #pragma unroll
  for (int J = 0; J < 16; J += 2)
    stmatrix_x4(dst + (J >> 3) * 16384 + ((((J & 7) + (lane >> 4)) ^ (lane & 7)) << 4),
                pack_bf16(o[4 * J + 0] * i0, o[4 * J + 1] * i0), pack_bf16(o[4 * J + 2] * i1, o[4 * J + 3] * i1),
                pack_bf16(o[4 * J + 4] * i0, o[4 * J + 5] * i0), pack_bf16(o[4 * J + 6] * i1, o[4 * J + 7] * i1));
}
__device__ __forceinline__ bool finish_l(float& l0, float& l1) {
  l0 += __shfl_xor_sync(0xffffffffu, l0, 1); l1 += __shfl_xor_sync(0xffffffffu, l1, 1);
  l0 += __shfl_xor_sync(0xffffffffu, l0, 2); l1 += __shfl_xor_sync(0xffffffffu, l1, 2);
  const bool redo = __any_sync(0xffffffffu, !(l0 <= AT_RAW_SUM && l1 <= AT_RAW_SUM && l0 >= AT_RAW_MIN && l1 >= AT_RAW_MIN));
  l0 = rcp_approx(l0); l1 = rcp_approx(l1);
  return redo;
}
template <int J0>
__device__ __forceinline__ void stage_q(const float (&acc)[128], float c, uint32_t dst, int lane) {
  #pragma unroll
  for (int J = J0; J < J0 + 16; J += 2)
    stmatrix_x4(dst + (J >> 3) * 16384 + ((((J & 7) + (lane >> 4)) ^ (lane & 7)) << 4),
                pack_bf16(acc[4 * J + 0] * c, acc[4 * J + 1] * c), pack_bf16(acc[4 * J + 2] * c, acc[4 * J + 3] * c),
                pack_bf16(acc[4 * J + 4] * c, acc[4 * J + 5] * c), pack_bf16(acc[4 * J + 6] * c, acc[4 * J + 7] * c));
}
__device__ __forceinline__ void store_o(const CUtensorMap* tmO, uint32_t src, int head, int row) {
  tma_store_2d(tmO, src, head * T_DH, row);
  tma_store_2d(tmO, src + 16384, head * T_DH + 64, row);
  bulk_commit();
}
__device__ __forceinline__ void mma_bf16(float (&d)[4], uint32_t a0, uint32_t a1, uint32_t a2, uint32_t a3, uint32_t b0, uint32_t b1) {
  asm volatile("mma.sync.aligned.m16n8k16.row.col.f32.bf16.bf16.f32 {%0, %1, %2, %3}, {%4, %5, %6, %7}, {%8, %9}, {%0, %1, %2, %3};"
               : "+f"(d[0]), "+f"(d[1]), "+f"(d[2]), "+f"(d[3]) : "r"(a0), "r"(a1), "r"(a2), "r"(a3), "r"(b0), "r"(b1));
}
struct GemvSel { uint32_t lo0, hi0, lo1, hi1; };
__device__ __forceinline__ GemvSel gemv_sel(int lane) {
  const uint32_t lo = (lane & 8) ? 0x1044u : 0x4410u, hi = (lane & 8) ? 0x3244u : 0x4432u;
  GemvSel s; s.lo0 = (lane & 16) ? 0x4444u : lo; s.hi0 = (lane & 16) ? 0x4444u : hi; s.lo1 = (lane & 16) ? lo : 0x4444u; s.hi1 = (lane & 16) ? hi : 0x4444u;
  return s;
}
#define GEMV_B0(j, h, s) __byte_perm((j) < 2 ? (h).x : (h).y, 0u, ((j) & 1) ? (s).hi0 : (s).lo0)
#define GEMV_B1(j, h, s) __byte_perm((j) < 2 ? (h).x : (h).y, 0u, ((j) & 1) ? (s).hi1 : (s).lo1)
__device__ __forceinline__ float4 gemv_out(const float (&d)[4], int lane) {
  const bool tk = lane & 1;
  const float r0 = __shfl_xor_sync(0xffffffffu, tk ? d[0] : d[1], 1), r1 = __shfl_xor_sync(0xffffffffu, tk ? d[2] : d[3], 1);
  return tk ? make_float4(r0, d[1], r1, d[3]) : make_float4(d[0], r0, d[2], r1);
}
#define OG_NG 8
#define HOIST 1
#define PUT_N 2
#define H_STAG 2
#define NOZERO 1
#define PVPIN 0
#define QKPIN 0
#define ALIGN 1
#define AL_P 60
#define AL_SLEEP 1200
#define AL_MAX 800
#define AL_ADD 0
#define X_PF 0
#define POLL_NS 200
#define KV3D 1
#define W3D 1
#define OG_PRE 10
#define OG_PRE2 14
#define SERP 1
#define OG_JOBS 7
#define OG_GRP 6
#define LD_FIRST 3
#define LD_STAG (OG_GRP / 2)
constexpr int OG_ST = 5, OG_NKB = T_DQKV / 64 - OG_PRE, OG_MOE = T_F / 32;
__device__ __forceinline__ int pre_loc(int job) {
  const int step = ((job >> 4) << 2) + (job & 3);
  return (step < OG_JOBS ? 2 * step : step < 2 * OG_JOBS ? 2 * (step - OG_JOBS) + 1 : step) * 4 + ((job >> 2) & 3);
}
__device__ __forceinline__ int pre_kb(int i) { return (i >> 1) * 4 + (i & 1); }
__device__ __forceinline__ int own_kb(int i) { return i < OG_PRE2 ? pre_kb(i) + 2 : i < 64 - OG_PRE2 ? i + OG_PRE2 : pre_kb(i - (64 - OG_PRE2 - OG_PRE)); }
constexpr int OG_POS = 8;
constexpr uint32_t OG_STAGE = 32768;
constexpr uint32_t OG_SCOL = AT_SBAR + 512;
constexpr uint32_t OG_SMISC = AT_SBAR + 2048;
constexpr int OG_XPOS = OG_POS + OG_NKB;
constexpr uint32_t OG_SWD = AT_SQ, OG_PSLOT = AT_SQ;
constexpr uint32_t OG_SWD1 = (OG_XPOS % OG_ST) * OG_STAGE;
constexpr uint32_t OG_XSLOT = AT_SQ + 32768;
constexpr uint32_t OG_OSLOT = ((OG_XPOS + 1) % OG_ST) * OG_STAGE;
constexpr uint32_t OG_SH2 = ((OG_XPOS + 2) % OG_ST) * OG_STAGE;
constexpr uint32_t OG_SRED = ((OG_XPOS + 3) % OG_ST) * OG_STAGE;
constexpr uint32_t OG_SSTAT = OG_SRED + 16384;
constexpr uint32_t OG_SGU = OG_SRED + 8192;
constexpr uint32_t OG_SFIN = OG_SGU + 256;
#define OGM 2
#define OG_MT(b) ((((b) >> OGM) & 15) ^ (SERP && ((b) & 64) ? 15 : 0))
#define OG_NT(b) (((b) & ((1 << OGM) - 1)) + (((b) >> (4 + OGM)) << OGM))
#define TAIL_SETUP \
  const uint32_t bar_full = sbase + AT_SBAR, bar_empty = bar_full + 40; \
  const uint32_t bar_wd = bar_full + 168, bar_col = bar_full + 176, bar_out = bar_full + 184, bar_end = bar_full + 192; \
  const uint32_t bar_key = bar_full + 200, bar_h2 = bar_full + 208, bar_sel = bar_full + 216; \
  const int mt = OG_MT(blockIdx.x), nt = OG_NT(blockIdx.x); \
  const int m0 = mt * 128, n0 = nt * 128; \
  const bool has_moe = (int)blockIdx.x < OG_MOE; \
  (void)bar_empty; (void)bar_wd; (void)bar_col; (void)bar_out; (void)bar_end; (void)bar_key; (void)bar_h2; (void)bar_sel; (void)m0; (void)n0; (void)has_moe;

__device__ __forceinline__ void tail_producer(uint32_t sbase, uint32_t ph, uint64_t pol, const CUtensorMap* tmA, const CUtensorMap* tmB, const CUtensorMap* tmX) {
  TAIL_SETUP
  uint32_t stage = OG_POS % OG_ST;
  int kb = 0;
  #pragma unroll 1
  for (int seg = 0; seg < 2; seg++) {
    mbar_wait(bar_full + 264, seg);
    fence_proxy_async_global();
    const int end = seg == 0 ? 32 - OG_PRE2 : has_moe ? OG_NKB : 64 - OG_PRE2;
    #pragma unroll 1
    for (; kb < end; kb++) {
      const uint32_t fb = bar_full + 8 * stage, sa = sbase + stage * OG_STAGE;
      const int k0 = own_kb(kb) * 64;
      mbar_wait(bar_empty + 8 * stage, ph);
      mbar_expect_tx(fb, OG_STAGE);
      tma_load_3d_hint(sa + 16384, tmB, k0, 2 * nt, fb, pol);
      tma_load_2d_hint(sa, tmA, k0, m0, fb, pol);
      if (++stage == OG_ST) { stage = 0; ph ^= 1; }
    }
  }
  if (has_moe) {
    mbar_wait(bar_empty + 8 * (OG_XPOS % OG_ST), ph);
    mbar_expect_tx(bar_wd, OG_STAGE);
    tma_load_3d_hint(sbase + OG_SWD1, tmX, blockIdx.x * 32, 8, bar_wd, pol);
  }
}

__device__ __forceinline__ uint32_t out2(uint32_t x1, uint32_t mb2, uint32_t ih, uint32_t il, uint32_t c1, uint32_t sb, uint32_t gb) {
  const uint32_t h2 = badd2(bmul2(ln_norm2b(x1, mb2, ih, il), c1), sb);
  return badd2(x1, bmul2(gb, bfma2(h2, 0u, h2)));
}
#define OGTIME gtime()
#define PRE_N 1
#define PRE_PACE 150
#define X_PACE 200
#define WD_LATE 0
#define WD_PACE 300
__device__ __forceinline__ void tail_exchange(uint32_t sbase, const CUtensorMap* tmOut, const bf16* __restrict__ w_down, const bf16* __restrict__ w_r, const bf16* __restrict__ x, bf16* __restrict__ out) {
    TAIL_SETUP
    const int lane = threadIdx.x & 31, wi = __shfl_sync(0xffffffffu, threadIdx.x >> 5, 0);
    if (wi == 3) {
      mbar_wait(bar_full + 264, 0);
      if (blockIdx.x < AT_NFULL) {
        uint32_t a, b;
        asm volatile("ld.relaxed.gpu.global.u32 %0, [%1];" : "=r"(a) : "l"(g_smid + 32 + blockIdx.x - lane) : "memory");
        b = __shfl_down_sync(0xffffffffu, a, 1);
        unsigned int* tm = g_tmax + blockIdx.x - min((int)blockIdx.x, __ffs(__ballot_sync(0xffffffffu, b >= a)) - 1);
        mbar_wait(bar_full + 312, 0);
        if (lane == 0) {
          asm volatile("mov.u32 %0, %%globaltimer_lo;" : "=r"(a));
          asm volatile("red.relaxed.gpu.global.max.u32 [%0], %1;" :: "l"(tm), "r"(a) : "memory");
          __nanosleep(AL_SLEEP);
          asm volatile("ld.relaxed.gpu.global.u32 %0, [%1];" : "=r"(b) : "l"(tm) : "memory");
          b -= a;
          sts_u32(sbase + OG_SMISC + 32, (b < AL_MAX ? b * 13 / 8 : 0u) + AL_ADD);
          mbar_arrive(bar_full + 320);
        }
        named_bar_sync(15, 32);
      }
      mbar_wait(bar_full + 264, 1);
      float a = g_scal[lane], b = g_scal[32 + lane];
      #pragma unroll
      for (int i = 0; i < 3; i++) {
        const uint4 v = *reinterpret_cast<const uint4*>(g_col + nt * 1536 + i * 512 + lane * 16);
        sts_u32x4(sbase + OG_SCOL + i * 512 + lane * 16, v.x, v.y, v.z, v.w);
      }
      #pragma unroll
      for (int o = 16; o > 0; o >>= 1) { a += __shfl_xor_sync(0xffffffffu, a, o); b += __shfl_xor_sync(0xffffffffu, b, o); }
      if (lane == 0) sts_f32x2(sbase + OG_SMISC, a, b);
      const uint64_t pol = policy_evict_first();
      #pragma unroll 1
      for (int r = lane >> 4; r < 128; r += 4) {
        __nanosleep(X_PACE);
        #pragma unroll
        for (int j = 0; j < 4; j += 2)
          asm volatile("cp.async.cg.shared.global.L2::cache_hint [%0], [%1], 16, %2;" :: "r"(sbase + OG_XSLOT + (lane & 8) * 2048 + (r + j) * 128 + (((lane ^ (r + j)) & 7) << 4)),
                       "l"(x + (size_t)(m0 + r + j) * T_D + n0 + (lane & 15) * 8), "l"(pol) : "memory");
      }
      asm volatile("cp.async.wait_all;" ::: "memory");
      __syncwarp();
      if (lane == 0) mbar_arrive(bar_col);
    } else if (wi == 2) {
      if (elect_one()) {
        const uint32_t b_free = bar_full + (blockIdx.x < AT_NFULL ? 80 : 160);
        mbar_wait(b_free, 0); mbar_wait(b_free, 1);
        #pragma unroll 1
        for (unsigned int i = 0; i < (1u << 20) && ld_acquire(&g_hcnt[8 * (4 + (blockIdx.x & 60)) + 4 + (nt >> 1)]) == 0u; i++) __nanosleep(POLL_NS);
        TL_MARK2(23, true);
        fence_proxy_async_global();
        TL_MARK2(4, true);
        mbar_expect_tx(bar_full + 272, 32768);
        #pragma unroll 1
        for (int i = 0; i < PRE_N; i++) {
          bulk_load_hint(sbase + OG_PSLOT + i * (32768 / PRE_N), g_pre + pre_loc((blockIdx.x & 60) + (nt >> 1)) * 4096 + (nt & 1) * 2048 + i * (2048 / PRE_N), 32768 / PRE_N,
                         bar_full + 272, policy_evict_first());
          if (PRE_N > 1) __nanosleep(PRE_PACE);
        }
      }
      named_bar_sync(14, 32);
      if (has_moe) {
        mbar_wait(bar_full + 96, 1); mbar_wait(bar_full + 304, 0);
        const uint64_t pol = policy_evict_first();
        #pragma unroll 1
        for (int r = 0; r < 32; r++) {
          __nanosleep(WD_PACE);
          #pragma unroll
          for (int j = 0; j < 2; j++)
            asm volatile("cp.async.cg.shared.global.L2::cache_hint [%0], [%1], 16, %2;" :: "r"(sbase + OG_SWD + (4 * j + (lane >> 3)) * 4096 + r * 128 + (((lane ^ r) & 7) << 4)),
                         "l"((const uint8_t*)w_down + (size_t)blockIdx.x * 65536 + r * 2048 + j * 512 + lane * 16), "l"(pol) : "memory");
        }
        asm volatile("cp.async.wait_all;" ::: "memory");
        __syncwarp();
        if (lane == 0) mbar_arrive(bar_wd);
      }
    }
    const uint4 wrv = ldg_nc_v4(w_r + threadIdx.x * 8);
    mbar_wait(bar_end, 0);
    TL_MARK2(22, lane == 0);
    if (wi == 0) {
      uint32_t k1 = 0u, k2 = 0u;
      #pragma unroll 1
      for (unsigned int spin = 0; spin < (1u << 22) && __any_sync(0xffffffffu, k1 == 0u); spin++) asm volatile("ld.relaxed.gpu.global.u32 %0, [%1];" : "=r"(k1) : "l"(g_key + lane) : "memory");
      TL_MARK2(28, lane == 0);
      warp_top2(k1, k2);
      if (lane == 0) {
        const uint32_t r1 = 0xffffu - (k1 & 0xffffu), r2 = 0xffffu - (k2 & 0xffffu);
        sts_u32x4(sbase + OG_SMISC + 64, r1, r2, (r1 >> 7) * 2, (r2 >> 7) * 2 + ((r1 >> 7) == (r2 >> 7)));
        mbar_arrive(bar_sel);
      }
    } else if (wi < 3) {
          mbar_wait(bar_key, 0);
          const uint4 kk = lds_u32x4(sbase + OG_SSTAT + 1024 + lane * 16);
          uint32_t k1 = max(kk.x, kk.y), k2 = min(kk.x, kk.y);
          k2 = max(max(k2, min(kk.z, kk.w)), min(k1, max(kk.z, kk.w))); k1 = max(k1, max(kk.z, kk.w));
          warp_top2(k1, k2);
          if (wi == 1) {
            if (lane == 0 && nt == (mt & 7)) st_relaxed2(g_key + mt * 2, k1, k2);
            TL_MARK2(27, lane == 0);
          } else {
            const uint32_t r = (~((lane & 16) ? k2 : k1)) & 127u, ch = lane & 15;
            const uint2 st = lds_u32x2(sbase + OG_SSTAT + r * 8);
            const uint4 xc = lds_u32x4(sbase + OG_XSLOT + (ch >> 3) * 16384 + r * 128 + (((ch ^ r) & 7) << 4));
            const uint4 c1 = lds_u32x4(sbase + OG_SCOL + 768 + ch * 16), sh = lds_u32x4(sbase + OG_SCOL + 1024 + ch * 16);
            const float inr = __uint_as_float(st.y);
            float* dst = reinterpret_cast<float*>(g_cand + (mt * 2 + (lane >> 4)) * 256 + nt * 16 + ch);
            st_tagged4(dst + 512, __uint_as_float(ln_mod2(xc.x, st.x, inr, c1.x, sh.x)), __uint_as_float(ln_mod2(xc.y, st.x, inr, c1.y, sh.y)),
                       __uint_as_float(ln_mod2(xc.z, st.x, inr, c1.z, sh.z)), __uint_as_float(ln_mod2(xc.w, st.x, inr, c1.w, sh.w)));
            st_tagged4(dst, __uint_as_float(xc.x), __uint_as_float(xc.y), __uint_as_float(xc.z), __uint_as_float(xc.w));
          }
    }
    mbar_wait(bar_sel, 0);
    const uint4 sel = lds_u32x4(sbase + OG_SMISC + 64);
    const int sel0 = (int)sel.x, sel1 = (int)sel.y;
    {
      const float* src0 = reinterpret_cast<const float*>(g_cand + sel.z * 256 + 128 + threadIdx.x);
      const float* src1 = reinterpret_cast<const float*>(g_cand + sel.w * 256 + 128 + threadIdx.x);
      float4 h0, h1;
      #pragma unroll 1
      for (unsigned int spin = 0; spin < (1u << 20); spin++) { h0 = ld_tagged4(src0); h1 = ld_tagged4(src1); if (__all_sync(0xffffffffu, tagged4(h0) & tagged4(h1))) break; }
      sts_f32x4(sbase + OG_SH2 + threadIdx.x * 16, h0.x, h0.y, h0.z, h0.w);
      sts_f32x4(sbase + OG_SH2 + 2048 + threadIdx.x * 16, h1.x, h1.y, h1.z, h1.w);
      __syncwarp();
      if (lane == 0) mbar_arrive(bar_h2);
      TL_MARK2(12, lane == 0);
      if (blockIdx.x >> 6) h0 = h1;
      float v[8], wr[8];
      unpack8(make_uint4(__float_as_uint(h0.x), __float_as_uint(h0.y), __float_as_uint(h0.z), __float_as_uint(h0.w)), v); unpack8(wrv, wr);
      float r = 0.f;
      #pragma unroll
      for (int i = 0; i < 8; i++) r = fmaf(v[i], wr[i], r);
      #pragma unroll
      for (int o = 16; o > 0; o >>= 1) r += __shfl_xor_sync(0xffffffffu, r, o);
      if (lane == 0) sts_f32(sbase + OG_SMISC + 192 + wi * 4, r);
    }
    mbar_wait(bar_out, 0);
    if ((sel0 >> 7) == mt || (sel1 >> 7) == mt) {
      #pragma unroll 2
      for (int i = 0; i < 16; i++) {
        const int r = i * 8 + (threadIdx.x >> 4), ch = threadIdx.x & 15;
        if (m0 + r != sel0 && m0 + r != sel1)
          *reinterpret_cast<uint4*>(out + (size_t)(m0 + r) * T_D + n0 + ch * 8) =
              lds_u32x4(sbase + OG_OSLOT + (ch >> 3) * 16384 + r * 128 + (((ch & 7) ^ (r & 7)) << 4));
      }
    } else if (threadIdx.x == 0) {
      tma_store_2d(tmOut, sbase + OG_OSLOT, n0, m0);
      tma_store_2d(tmOut, sbase + OG_OSLOT + 16384, n0 + 64, m0);
      bulk_commit();
    }
    if (blockIdx.x == 0 && threadIdx.x < 68) *reinterpret_cast<uint4*>(g_hcnt + 32 * (threadIdx.x >> 2) + 4 * (threadIdx.x & 3)) = make_uint4(0u, 0u, 0u, 0u);
    if (threadIdx.x < 64) g_modpart[blockIdx.x * 64 + threadIdx.x] = 0.f;
    if (ALIGN && threadIdx.x == 64) g_tmax[blockIdx.x] = 0u;
    {
      const int tk = blockIdx.x >> 6, c0 = (blockIdx.x & 63) * 16;
      const uint32_t gb2 = *reinterpret_cast<const uint32_t*>(g_col + (c0 >> 7) * 1536 + 512 + 768 + ((c0 & 127) + (threadIdx.x & 14)) * 2);
      const uint32_t* xp = reinterpret_cast<const uint32_t*>(g_cand + (tk ? sel.w : sel.z) * 256) + ((c0 + (threadIdx.x & 14)) >> 1);
      uint32_t x2 = 0u;
      #pragma unroll 1
      for (unsigned int spin = 0; spin < (1u << 20) && __any_sync(0xffffffffu, x2 == 0u); spin++) asm volatile("ld.relaxed.gpu.global.u32 %0, [%1];" : "=r"(x2) : "l"(xp) : "memory");
      const float* src = g_ypart + (size_t)((threadIdx.x >> 2) * 2 + tk) * T_D + c0 + (threadIdx.x & 3) * 4;
      const bool four = threadIdx.x < (OG_MOE - 96) * 4;
      if (threadIdx.x == 0) hint_wait(CNT_Y, (uint32_t)OG_MOE);
      named_bar_sync(10, 128);
      float4 p0, p1, p2, p3;
      #pragma unroll 1
      for (unsigned int spin = 0; spin < (1u << 20); spin++) {
        p0 = ld_tagged4(src); p1 = ld_tagged4(src + 64 * T_D); p2 = ld_tagged4(src + 128 * T_D); p3 = ld_tagged4(four ? src + 192 * T_D : src);
        if (__all_sync(0xffffffffu, tagged4(p0) & tagged4(p1) & tagged4(p2) & tagged4(p3))) break;
      }
      if (four) { p2.x += p3.x; p2.y += p3.y; p2.z += p3.z; p2.w += p3.w; }
      p0.x = (p0.x + p1.x) + p2.x; p0.y = (p0.y + p1.y) + p2.y; p0.z = (p0.z + p1.z) + p2.z; p0.w = (p0.w + p1.w) + p2.w;
      #pragma unroll
      for (int o = 4; o <= 16; o <<= 1) {
        p0.x += __shfl_xor_sync(0xffffffffu, p0.x, o); p0.y += __shfl_xor_sync(0xffffffffu, p0.y, o);
        p0.z += __shfl_xor_sync(0xffffffffu, p0.z, o); p0.w += __shfl_xor_sync(0xffffffffu, p0.w, o);
      }
      if (lane < 4) sts_f32x4(sbase + OG_SFIN + (threadIdx.x >> 5) * 64 + lane * 16, p0.x, p0.y, p0.z, p0.w);
      named_bar_sync(10, 128);
      TL_MARK2(21, threadIdx.x == 0);
      if (threadIdx.x < 16) {
        const uint32_t ya = sbase + OG_SFIN + threadIdx.x * 4, rp = sbase + OG_SMISC + 192;
        float y = (lds_f32(ya) + lds_f32(ya + 64)) + (lds_f32(ya + 128) + lds_f32(ya + 192));
        const float r = rbf((lds_f32(rp) + lds_f32(rp + 4)) + (lds_f32(rp + 8) + lds_f32(rp + 12)));
        const float rs = rbf(sigmoid_f(r));
        const uint32_t h2p = lds_u32(sbase + OG_SH2 + tk * 2048 + (c0 + (threadIdx.x & 14)) * 2);
        const float fh = (lane & 1) ? bfhi(h2p) : bflo(h2p);
        y = rbf(y);
        y = rbf(y * rs);
        const float upd = rbf(rbf(fh * 0.0f) + y);
        out[(size_t)(tk ? sel1 : sel0) * T_D + c0 + threadIdx.x] =
            __float2bfloat16_rn(((lane & 1) ? bfhi(x2) : bflo(x2)) + rbf(((lane & 1) ? bfhi(gb2) : bflo(gb2)) * rbf(fh + upd)));
      }
      if (threadIdx.x == 0) bulk_wait_read<0>();
    }
    TL_END(4, threadIdx.x == 0);
}

__device__ __forceinline__ void load_pre(uint4* pre, uint32_t sbase, uint32_t buf, int t2) {
  mbar_wait(sbase + AT_SBAR + 272, 0);
  #pragma unroll
  for (int i = 0; i < 8; i++) pre[i] = lds_u32x4(sbase + buf + i * 4096 + t2 * 16);
}
__device__ __forceinline__ void tail_consumer(uint32_t sbase, const uint4 (&pre)[8], int cwg, const bf16* __restrict__ w_gate, const bf16* __restrict__ w_up) {
    TAIL_SETUP
    const int tid = threadIdx.x & 127, t2 = threadIdx.x - 128;
    const int warp = tid >> 5, lane = tid & 31, w8 = t2 >> 5;
    const uint32_t dbase = (sbase & 0x3FFFFu) >> 4;
    const uint32_t a_base = dbase + ((cwg * 8192) >> 4) + (1u << 16);
    const uint32_t b_base = dbase + (16384 >> 4) + (512u << 16);
    TL_MARK2(25, threadIdx.x == 128);
    const uint64_t pol = policy_evict_first();
    const bf16* pw = ((lane & 16) ? w_up : w_gate) + (size_t)(w8 * 128 + (lane & 3) * 4) * T_F + (has_moe ? blockIdx.x : 0) * 32 + ((lane >> 2) & 3) * 8;
    uint4 wv[32];
    float acc[64];
    #pragma unroll
    for (int i = 0; i < 8; i++) {
      acc[8 * i] = bflo(pre[i].x); acc[8 * i + 1] = bfhi(pre[i].x); acc[8 * i + 2] = bflo(pre[i].y); acc[8 * i + 3] = bfhi(pre[i].y);
      acc[8 * i + 4] = bflo(pre[i].z); acc[8 * i + 5] = bfhi(pre[i].z); acc[8 * i + 6] = bflo(pre[i].w); acc[8 * i + 7] = bfhi(pre[i].w);
    }
    if (blockIdx.x < AT_NFULL) {
      const uint32_t c0 = clock_lo();
      mbar_wait(bar_full + 320, 0);
      const uint32_t d = lds_u32(sbase + OG_SMISC + 32);
      while (clock_lo() - c0 < d) {}
    }
    {
      uint32_t stage = OG_POS % OG_ST, phase = (OG_POS / OG_ST) & 1, prev = 12;
      int kb = 0;
      #pragma unroll
      for (int g = 0; g <= OG_NG; g++) {
        const int end = g == OG_NG ? (has_moe ? OG_NKB : 64 - OG_PRE2) : LD_FIRST + g * OG_GRP + LD_STAG * cwg;
        #pragma unroll 1
        do {
          mbar_wait(bar_full + 8 * stage, phase);
          const uint32_t a_lo = a_base + stage * (OG_STAGE >> 4), b_lo = b_base + stage * (OG_STAGE >> 4);
          wgmma_fence();
          wgmma_m64n128k16_ss_tb<0, 0>(acc, a_lo, b_lo, 1);
          wgmma_m64n128k16_ss_tb<2, 128>(acc, a_lo, b_lo, 1);
          wgmma_m64n128k16_ss_tb<4, 256>(acc, a_lo, b_lo, 1);
          wgmma_m64n128k16_ss_tb<6, 384>(acc, a_lo, b_lo, 1);
          wgmma_commit();
          wgmma_wait<1>();
          if (tid == 0) mbar_arrive(bar_empty + 8 * prev);
          prev = stage;
          if (++stage == OG_ST) { stage = 0; phase ^= 1; }
        } while (++kb < end);
        #pragma unroll
        for (int j = 4 * g; j < 4 * g + 4 && j < 32; j++) wv[j] = ldg_stream_v4(pw + (size_t)(16 * (j >> 2) + (j & 3)) * T_F, pol);
      }
    }
    mbar_wait(bar_col, 0);
    if (__builtin_expect(!has_moe, 0)) {
      load_pre(wv, sbase, AT_SQ, t2);
    }
    wgmma_wait<0>();
    fence_regs(acc);
    if (__builtin_expect(!has_moe, 0)) {
      #pragma unroll
      for (int i = 0; i < 8; i++) {
        acc[8 * i] += bflo(wv[i].x); acc[8 * i + 1] += bfhi(wv[i].x); acc[8 * i + 2] += bflo(wv[i].y); acc[8 * i + 3] += bfhi(wv[i].y);
        acc[8 * i + 4] += bflo(wv[i].z); acc[8 * i + 5] += bfhi(wv[i].z); acc[8 * i + 6] += bflo(wv[i].w); acc[8 * i + 7] += bfhi(wv[i].w);
      }
    }
    if (tid == 0) mbar_arrive(bar_end);
    TL_MARK2(9, lane == 0);
    const int q2 = 2 * (lane & 3);
    const uint32_t frag = (64 * cwg + 16 * warp + (lane & 7) + 8 * ((lane >> 3) & 1)) * 128;
    const int fsw = lane & 7, fhi = lane >> 4;
    {
      float dl[4] = {0.f, 0.f, 0.f, 0.f}, da[4] = {0.f, 0.f, 0.f, 0.f}, db[4] = {0.f, 0.f, 0.f, 0.f};
      const uint32_t tb = sbase + OG_SCOL + (lane & 8) * 32 + (lane & 3) * 8, g = lane >> 2;
      const uint32_t msk = (g == 1 || g == 2) ? 0xffffffffu : 0u, one = g == 0 ? 0x3F803F80u : 0u;
      #pragma unroll
      for (int J = 0; J < 16; J += 2) {
        const uint32_t ad = sbase + OG_XSLOT + (J >> 3) * 16384 + frag + ((((J & 7) + fhi) ^ fsw) << 4);
        uint32_t xr[4];
        ldmatrix_x4(ad, xr[0], xr[1], xr[2], xr[3]);
        const uint2 cw = lds_u32x2(tb + J * 16);
        #pragma unroll
        for (int h = 0; h < 2; h++) {
          const uint32_t ga = lds_u32(sbase + OG_SCOL + 512 + (8 * (J + h) + q2) * 2);
          xr[2 * h] = badd2(xr[2 * h], bmul2(ga, pack_bf16(acc[4 * (J + h)], acc[4 * (J + h) + 1])));
          xr[2 * h + 1] = badd2(xr[2 * h + 1], bmul2(ga, pack_bf16(acc[4 * (J + h) + 2], acc[4 * (J + h) + 3])));
        }
        stmatrix_x4(ad, xr[0], xr[1], xr[2], xr[3]);
        mma_bf16(dl, xr[0], xr[1], xr[2], xr[3], (cw.x & msk) | one, (cw.y & msk) | one);
        mma_bf16(da, xr[0], xr[1], xr[2], xr[3], xr[0], xr[2]);
        mma_bf16(db, xr[0], xr[1], xr[2], xr[3], xr[1], xr[3]);
      }
      {
        const int dsrc = (lane & ~3) + (g >> 1);
        const float qa = __shfl_sync(0xffffffffu, (g & 1) ? da[1] : da[0], dsrc), qb = __shfl_sync(0xffffffffu, (g & 1) ? db[3] : db[2], dsrc);
        const float e0 = __shfl_xor_sync(0xffffffffu, (lane & 1) ? dl[0] : dl[2], 1), e1 = __shfl_xor_sync(0xffffffffu, dl[3], 1);
        if ((lane & 3) < 2) {
          const bool hi = lane & 1;
          st_tagged4(reinterpret_cast<float*>(g_part1 + ((mt * 8 + w8) * 8 + nt) * 16 + g + (hi ? 8 : 0)),
                     hi ? e0 : dl[0], hi ? qb : qa, hi ? e1 + dl[2] : dl[1] + e0, 1.0f);
        }
      }
    }
    TL_MARK2(10, lane == 0);
    uint4 wd[16];
    if (has_moe) mbar_wait(bar_wd, 0);
    #pragma unroll
    for (int i = 0; i < 16; i++) wd[i] = lds_u32x4(sbase + (cwg ? OG_SWD1 : OG_SWD) + warp * 8192 + (i >> 3) * 4096 + (i & 6) * 512 + (i & 1) * 128 + (lane & 3) * 256 + (((lane >> 2) ^ (2 * (lane & 3) + (i & 1))) << 4));
    {
      const float* src = reinterpret_cast<const float*>(g_part1 + ((mt * 8 + w8) * 8 + (lane & 1) * 4) * 16 + (lane >> 1));
      float4 v, v1, v2, v3;
      #pragma unroll 1
      for (unsigned int spin = 0; spin < (1u << 22); spin++) {
        v = ld_tagged4(src); v1 = ld_tagged4(src + 64); v2 = ld_tagged4(src + 128); v3 = ld_tagged4(src + 192);
        if (__all_sync(0xffffffffu, tagged4(v) & tagged4(v1) & tagged4(v2) & tagged4(v3))) break;
        __nanosleep(100);
      }
      __syncwarp();
      TL_MARK2(26, lane == 0);
      v.x = (v.x + v1.x) + (v2.x + v3.x); v.y = (v.y + v1.y) + (v2.y + v3.y); v.z = (v.z + v1.z) + (v2.z + v3.z);
      v.x += __shfl_xor_sync(0xffffffffu, v.x, 1); v.y += __shfl_xor_sync(0xffffffffu, v.y, 1); v.z += __shfl_xor_sync(0xffffffffu, v.z, 1);
      const float mean = v.x * (1.0f / T_D);
      const float var = fmaxf(fmaf(-mean, mean, v.y * (1.0f / T_D)), 0.f);
      const uint32_t mb2 = pack_bf16(mean, mean);
      const float inv = rcp_approx(rbf(sqrt_approx(rbf(rbf(var) + 1e-05f))));
      {
        const float2 sc = lds_f32x2(sbase + OG_SMISC);
        const uint32_t key = rank_key(rbf(fmaf(fmaf(-bflo(mb2), sc.x, v.z), inv, sc.y)), m0 + 16 * w8 + (lane >> 1));
        mbar_wait(bar_end, 0);
        if (lane & 1) sts_u32(sbase + OG_SSTAT + 1024 + (16 * w8 + (lane >> 1)) * 4, key);
        else sts_u32x2(sbase + OG_SSTAT + (16 * w8 + (lane >> 1)) * 8, mb2, __float_as_uint(inv));
        __syncwarp();
        if (lane == 0) mbar_arrive(bar_key);
      }
      const uint32_t ih = pack_bf16(inv, inv), il = pack_bf16(inv - bflo(ih), inv - bflo(ih));
      const uint32_t mba = __shfl_sync(0xffffffffu, mb2, 2 * (lane >> 2)), mbb = __shfl_sync(0xffffffffu, mb2, 2 * (lane >> 2) + 16);
      const uint32_t iha = __shfl_sync(0xffffffffu, ih, 2 * (lane >> 2)), ihb = __shfl_sync(0xffffffffu, ih, 2 * (lane >> 2) + 16);
      const uint32_t ila = __shfl_sync(0xffffffffu, il, 2 * (lane >> 2)), ilb = __shfl_sync(0xffffffffu, il, 2 * (lane >> 2) + 16);
      #pragma unroll 2
      for (int J = 0; J < 16; J += 2) {
        const uint32_t off = (J >> 3) * 16384 + frag + ((((J & 7) + fhi) ^ fsw) << 4);
        uint32_t xr[4];
        ldmatrix_x4(sbase + OG_XSLOT + off, xr[0], xr[1], xr[2], xr[3]);
        #pragma unroll
        for (int h = 0; h < 2; h++) {
          const uint32_t ca = sbase + OG_SCOL + 512 + (8 * (J + h) + q2) * 2;
          const uint32_t c1 = lds_u32(ca + 256), sh = lds_u32(ca + 512), gb = lds_u32(ca + 768);
          xr[2 * h] = out2(xr[2 * h], mba, iha, ila, c1, sh, gb);
          xr[2 * h + 1] = out2(xr[2 * h + 1], mbb, ihb, ilb, c1, sh, gb);
        }
        stmatrix_x4(sbase + OG_OSLOT + off, xr[0], xr[1], xr[2], xr[3]);
      }
      fence_proxy_async();
      __syncwarp();
      if (lane == 0) mbar_arrive(bar_out);
      TL_MARK2(24, lane == 0);
    }
    if (has_moe) mbar_wait(bar_h2, 0);
    TL_MARK2(13, lane == 0);
    if (has_moe) {
      const GemvSel sel = gemv_sel(lane);
      {
        float d[4][4];
        #pragma unroll
        for (int c = 0; c < 4; c++) { d[c][0] = 0.f; d[c][1] = 0.f; d[c][2] = 0.f; d[c][3] = 0.f; }
        #pragma unroll
        for (int st = 0; st < 8; st++) {
          const uint2 hb = lds_u32x2(sbase + OG_SH2 + ((lane >> 2) & 1) * 2048 + (w8 * 128 + st * 16 + (lane & 3) * 4) * 2);
          #pragma unroll
          for (int j = 0; j < 4; j++) mma_bf16(d[j], wv[4 * st + j].x, wv[4 * st + j].y, wv[4 * st + j].z, wv[4 * st + j].w, GEMV_B0(j, hb, sel), GEMV_B1(j, hb, sel));
        }
        #pragma unroll
        for (int e = 0; e < 4; e++) d[0][e] = (d[0][e] + d[1][e]) + (d[2][e] + d[3][e]);
        const float4 r = gemv_out(d[0], lane);
        sts_f32x4(sbase + OG_SRED + w8 * 512 + (((lane >> 4) * 2 + (lane & 1)) * 32 + ((lane >> 2) & 3) * 8 + (lane & 2) * 2) * 4, r.x, r.y, r.z, r.w);
      }
      named_bar_sync(9, 256);
      if (t2 < 64) {
        float gp[8], up[8];
        #pragma unroll
        for (int w = 0; w < 8; w++) { gp[w] = lds_f32(sbase + OG_SRED + w * 512 + t2 * 4); up[w] = lds_f32(sbase + OG_SRED + w * 512 + 256 + t2 * 4); }
        const float gs = ((gp[0] + gp[1]) + (gp[2] + gp[3])) + ((gp[4] + gp[5]) + (gp[6] + gp[7]));
        const float us = ((up[0] + up[1]) + (up[2] + up[3])) + ((up[4] + up[5]) + (up[6] + up[7]));
        asm volatile("st.shared.u16 [%0], %1;" :: "r"(sbase + OG_SGU + ((t2 & ~15) + ((t2 >> 1) & 3) * 4 + ((t2 >> 3) & 1) * 2 + (t2 & 1)) * 2), "h"((uint16_t)pack_bf16(silu_bf(rbf(gs)) * rbf(us), 0.f)) : "memory");
      }
      named_bar_sync(9, 256);
      TL_MARK2(20, threadIdx.x == 128);
      float d[4][4];
      #pragma unroll
      for (int c = 0; c < 4; c++) { d[c][0] = 0.f; d[c][1] = 0.f; d[c][2] = 0.f; d[c][3] = 0.f; }
      #pragma unroll
      for (int st = 0; st < 2; st++) {
        const uint2 g = lds_u32x2(sbase + OG_SGU + ((lane >> 2) & 1) * 64 + st * 32 + (lane & 3) * 8);
        #pragma unroll
        for (int j = 0; j < 4; j++) {
          const uint32_t b0 = GEMV_B0(j, g, sel), b1 = GEMV_B1(j, g, sel);
          mma_bf16(d[j & 1], wd[4 * st + j].x, wd[4 * st + j].y, wd[4 * st + j].z, wd[4 * st + j].w, b0, b1);
          mma_bf16(d[2 + (j & 1)], wd[8 + 4 * st + j].x, wd[8 + 4 * st + j].y, wd[8 + 4 * st + j].z, wd[8 + 4 * st + j].w, b0, b1);
        }
      }
      #pragma unroll
      for (int e = 0; e < 4; e++) { d[0][e] += d[1][e]; d[2][e] += d[3][e]; }
      const float4 y0 = gemv_out(d[0], lane), y1 = gemv_out(d[2], lane);
      float* yp = g_ypart + (size_t)(blockIdx.x * 2 + (lane & 1)) * T_D + w8 * 128 + (lane >> 2) * 8 + (lane & 2) * 2;
      st_tagged4(yp, y0.x, y0.y, y0.z, y0.w);
      st_tagged4(yp + 64, y1.x, y1.y, y1.z, y1.w);
      named_bar_sync(9, 256);
      if (t2 == 0) hint_arrive(CNT_Y);
    }
    TL_MARK2(14, threadIdx.x == 128);
    TL_CLK(4, 1, threadIdx.x == 128);
}

#define OG_JOBS2 (16 - OG_JOBS)
__device__ __forceinline__ int help_njobs() { return blockIdx.x < 128 ? OG_JOBS : OG_JOBS2; }
__device__ __forceinline__ int help_job(int i) {
  const int step = i + (blockIdx.x < 128 ? 0 : OG_JOBS);
  return (step & ~3) * 4 + (blockIdx.x & 3) * 4 + (step & 3);
}
__device__ __noinline__ void store_warp(uint32_t sbase, const CUtensorMap* tmO, int item0, int n_items) {
  if (elect_one()) {
    const uint32_t bars = sbase + AT_SBAR, b_q0 = bars + 80, b_ob = bars + 96, b_ordy = bars + 104, b_acq = bars + 264;
    const unsigned int* cnt = &g_hcnt[32 * (1 + OG_MT(blockIdx.x)) + 2];
    #pragma unroll 1
    for (int q = 0; q < 4 * n_items; q++) {
      const int item = item0 + (q >> 2) * 128, h = (q >> 1) & 1, w = q & 1;
      const bool last = (q >> 2) == n_items - 1;
      if (q == 4 * n_items - 4) { mbar_wait(bars + 288, 0); red_release_add(&g_hcnt[1], 1u); }
      mbar_wait(b_ordy + 8 * (q & 3), q >> 2);
      store_o(tmO, (h ? (last ? sbase + AT_SQ + 32768 : sbase + 2 * 32768) : sbase + AT_SQ) + w * 8192, (item >> 4) * 2 + h, (item & 15) * 128 + w * 64);
      if (w) {
        bulk_wait_read<0>();
        mbar_arrive(h ? b_ob : b_q0);
        bulk_wait<0>();
        fence_proxy_async_global();
        asm volatile("fence.acq_rel.gpu;" ::: "memory");
        hint_arrive(&g_hcnt[32 * (1 + (item & 15)) + 2 + (item >> 7)]);
        if (!h && item < 128) hint_arrive(&g_hcnt[2]);
        if (blockIdx.x < 128 && q == (n_items == 2 ? 5 : 3)) { spin_until(cnt, 16u); mbar_arrive(b_acq); }
      }
    }
    if (n_items == 1) {
      #pragma unroll 1
      for (int i = 0; i < help_njobs(); i++) {
        mbar_wait(b_acq + 16, i & 1);
        TL_MARK2(23, i == OG_JOBS - 1);
        red_release_add(&g_hcnt[32 * (1 + (help_job(i) >> 2)) + 4 + (help_job(i) & 3)], 1u);
        TL_MARK2(4, i == OG_JOBS - 1);
        if (i == PRE_X - 1) { spin_until(&g_hcnt[1], 132u); mbar_arrive(b_acq + 32); }
      }
    }
    if (blockIdx.x < 128) { spin_until(&g_hcnt[0], 128u); spin_until(cnt + 1, 16u); mbar_arrive(b_acq); }
  }
}

__global__ void __launch_bounds__(384, 1)
fused_kernel(const __grid_constant__ CUtensorMap tmH, const __grid_constant__ CUtensorMap tmW, const __grid_constant__ CUtensorMap tmK,
            const __grid_constant__ CUtensorMap tmV, const __grid_constant__ CUtensorMap tmO, const __grid_constant__ CUtensorMap tmOl, const __grid_constant__ CUtensorMap tmWo,
            const __grid_constant__ CUtensorMap tmX, const __grid_constant__ CUtensorMap tmOut, const __grid_constant__ CUtensorMap tmM, uint32_t zero,
            const uint8_t* __restrict__ pf_wo, const bf16* __restrict__ kc, const bf16* __restrict__ vc,
            const bf16* __restrict__ x, const bf16* __restrict__ cvec, const bf16* __restrict__ w_mod, const bf16* __restrict__ w_r,
            const bf16* __restrict__ w_gate, const bf16* __restrict__ w_up, const bf16* __restrict__ w_down, bf16* __restrict__ out)
{
  extern __shared__ __align__(1024) uint8_t smem_raw[];
  const uint32_t sbase = smem_u32(smem_raw);
  const uint32_t bars = sbase + AT_SBAR;
  const uint32_t b_full = bars, b_empty = bars + 40;
  const uint32_t b_q0 = bars + 80, b_q1 = bars + 88;
  const uint32_t b_ob = bars + 96;
  const uint32_t b_ordy = bars + 104;
  const uint32_t b_pin = bars + 136;
  const uint32_t b_head = bars + 144;
  const uint32_t b_go = bars + 152;
  const uint32_t b_x = bars + 160;
  const int wg = __shfl_sync(0xffffffffu, threadIdx.x >> 7, 0);
  const bool single = blockIdx.x >= AT_NFULL;
  const int item0 = __shfl_sync(0xffffffffu, blockIdx.x < 128 ? (int)blockIdx.x : (int)blockIdx.x + 124, 0), n_items = __shfl_sync(0xffffffffu, single ? 1 : 2, 0);
  TL_START(3);
  if (threadIdx.x == 0) {
    if (sbase & 1023u) __trap();
    for (int i = 0; i < 5; i++) { mbar_init(b_full + 8 * i, 1); mbar_init(b_empty + 8 * i, 2); }
    mbar_init(b_q0, 1); mbar_init(b_q1, 8); mbar_init(b_ob, 1);
    for (int i = 0; i < 4; i++) mbar_init(b_ordy + 8 * i, 4);
    mbar_init(b_pin, 1); mbar_init(b_head, blockIdx.x < 128 ? 8 : 1); mbar_init(b_go, 1); mbar_init(b_x, 1);
    mbar_init(bars + 168, 2); mbar_init(bars + 176, 1); mbar_init(bars + 184, 8); mbar_init(bars + 192, 2);
    mbar_init(bars + 200, 8); mbar_init(bars + 208, 4); mbar_init(bars + 216, 1); mbar_init(bars + 264, 1); mbar_init(bars + 272, 1); mbar_init(bars + 280, 8); mbar_init(bars + 288, 1); mbar_init(bars + 296, 1); mbar_init(bars + 304, 8); mbar_init(bars + 312, 1); mbar_init(bars + 320, 1); mbar_init(bars + 328, 1);
    fence_mbar_init();
  }

  if (wg == 0) {
    reg_dealloc<AT_PREG>();
    if (threadIdx.x < 32) { __syncwarp(); named_bar_arrive(6, 384); }
    if (threadIdx.x >= 64) {
      named_bar_sync(6, 384);
      if (blockIdx.x < 128) {
        named_bar_sync(threadIdx.x >= 96 ? 8 : 9, 288);
        if ((threadIdx.x & 31) == 0) red_release_add(&g_hcnt[32 * (1 + (blockIdx.x >> 3)) + (threadIdx.x >= 96)], 1u);
        TL_MARK2(11, threadIdx.x == 64);
      }
      if (blockIdx.x < 128) {
        mbar_wait(MOD_AT, 0);
        mod_rest(sbase + OG_SCOL, b_q1, threadIdx.x - 64, cvec, w_mod, w_r);
      }
    } else if (threadIdx.x >= 32) {
      named_bar_sync(6, 384);
      store_warp(sbase, &tmO, item0, n_items);
      __syncwarp();
    } else {
     if (elect_one()) {
      const uint64_t pol = policy_evict_first();
      if (blockIdx.x < 128) {
        mbar_expect_tx(b_x, 32768);
        if (X_DLY) { const uint32_t c0 = clock_lo(); while (clock_lo() - c0 < X_DLY) {} }
        bulk_load_hint(sbase + 4 * 32768, x + (size_t)blockIdx.x * 16 * T_D, 32768, b_x, pol);
      }
      prefetch_tmap(&tmW); prefetch_tmap(&tmM); prefetch_tmap(&tmH); prefetch_tmap(&tmWo); prefetch_tmap(&tmOl);
      {
        const uint32_t c0 = clock_lo();
        while (clock_lo() - c0 < W_DLY) {}
        if (blockIdx.x < 128 && (blockIdx.x & 15) >= 4 * H_SPLIT) {
          mbar_expect_tx(bars + 328, 32768);
          tma_load_2d_hint(sbase + 3 * 32768, &tmM, (blockIdx.x & 31) * 64, (blockIdx.x >> 5) * 256, bars + 328, pol);
        }
        while (clock_lo() - c0 < W_DLY + W_FIRST) {}
      }
      uint32_t slot = 0, ph = 1;
      if (ALIGN) { uint32_t sm; asm volatile("mov.u32 %0, %%smid;" : "=r"(sm)); g_smid[32 + blockIdx.x] = sm; }
      #pragma unroll 1
      for (int it = 0; it < n_items; it++) {
        const int item = item0 + it * 128, hp = item >> 4, qt = item & 15;
        const bool first = it == 0;
        #pragma unroll 1
        for (int j = 0; j < T_D / 64; j++) {
          const uint32_t sl = ring_slot(qp_pos(j, it)), fb = b_full + 8 * sl;
          mbar_wait(b_empty + 8 * sl, ring_par(qp_pos(j, it)) ^ ((j >> 2) & 1) ^ 1);
          if (first && j == 3) mbar_wait(b_head, 0);
          mbar_expect_tx(fb, 49152);
          tma_load_3d_hint(sbase + sl * 32768, &tmW, j * 64, hp * 4, fb, pol);
          if (first && j < PRE_B) {
            if (j == PRE_B - 1) {
              spin_until(&g_hcnt[32 * (1 + qt)], 8u);
              TL_MARK2(16, true);
              fence_proxy_async_global();
              #pragma unroll 1
              for (int i = 0; i < PRE_B; i++) tma_load_2d(sbase + AT_SQ + i * 16384, &tmH, i * 64, qt * 128, b_full + 8 * i);
              mbar_arrive(b_go);
            }
          } else {
            if (first && j == 4 * H_SPLIT) { spin_until(&g_hcnt[32 * (1 + qt) + 1], 8u); fence_proxy_async_global(); }
            if (!first && (j == 0 || j == 2)) mbar_wait(j ? b_q1 : b_q0, 0);
            tma_load_2d_hint(sbase + AT_SQ + (j & 3) * 16384, &tmH, j * 64, qt * 128, fb, first ? pol_normal() : pol);
          }
        }
        #pragma unroll 1
        for (int j = 0; j < 4 * AT_NBLK; j++) {
          const bool isv = (j > 0 && !(j & 1)) || j == 4 * AT_NBLK - 1;
          const int row = hp * 2 * T_SEQ + (isv ? (j - 1) >> 1 : (j + 1) >> 1) * 128;
          const uint32_t fb = b_full + 8 * slot;
          mbar_wait(b_empty + 8 * slot, ph);
          if (!first && j == 3) mbar_wait(b_ob, 0);
          if (j == 4 && it == n_items - 1) mbar_arrive(bars + 288);
          if (ALIGN && j == AL_P && it == 1) mbar_arrive(bars + 312);
          mbar_expect_tx(fb, 32768);
          tma_load_3d_hint(sbase + slot * 32768, isv ? &tmV : &tmK, row, 0, fb, pol);
          if (it == 1 && isv && j >= 2 * WO_LATE && j < 2 * WO_LATE + 32 && blockIdx.x < OG_NKB)
            l2_prefetch_bulk(pf_wo + (size_t)own_kb(blockIdx.x) * 131072 + ((j >> 1) - WO_LATE) * 8192, 8192);
          if (++slot == 5) { slot = 0; ph ^= 1; }
        }
      }
      if (__builtin_expect(single, 0)) {
        spin_until(&g_hcnt[2], 128u);
        fence_proxy_async_global();
        const int nj = OG_JOBS * OG_PRE + (help_njobs() - OG_JOBS) * OG_PRE2;
        int ji = 0, job = help_job(0), kk = 0;
        #pragma unroll 1
        for (int j = 0; j < nj; j++) {
          const uint32_t sl = ring_slot(qp_pos(j, 1)), fb = b_full + 8 * sl;
          mbar_wait(b_empty + 8 * sl, ring_par(qp_pos(j, 1)) ^ ((j >> 2) & 1) ^ 1);
          mbar_expect_tx(fb, 49152);
          tma_load_3d_hint(sbase + sl * 32768, &tmWo, pre_kb(kk) * 64, (job & 3) * 4, fb, HPOL_B);
          tma_load_3d_hint(sbase + sl * 32768 + 16384, &tmWo, pre_kb(kk) * 64, (job & 3) * 4 + 2, fb, HPOL_B);
          if (j == 0 || j == 2) mbar_wait(j ? b_ob : b_q0, 0);
          tma_load_2d_hint(sbase + AT_SQ + (j & 3) * 16384, &tmOl, pre_kb(kk) * 64, OG_MT((job & 60) + (job & 2) * 32) * 128, fb, HPOL_A);
          if (++kk == (ji < OG_JOBS ? OG_PRE : OG_PRE2)) { kk = 0; job = help_job(++ji); }
        }
      }
      if (blockIdx.x < 128) {
        if (single) mbar_wait(b_x, 1);
        tail_producer(sbase, 0, pol, &tmOl, &tmWo, &tmX);
      }
     }
    }
    named_bar_sync(12 + (threadIdx.x >> 5), 32);
    if (blockIdx.x < 128) tail_exchange(sbase, &tmOut, w_down, w_r, x, out);
  } else {
    if (blockIdx.x < 128) head_phase(sbase + AT_SQ + 49152, sbase + 4 * 32768, b_x, b_go, b_head, threadIdx.x - 128, zero, cvec, w_mod);
    else { named_bar_sync(6, 384); if (threadIdx.x == 128) mbar_arrive(b_head); }
    TL_MARK2(0, threadIdx.x == 128);
    reg_alloc<AT_CREG>();
    const int cwg = wg - 1;
    const int tid = threadIdx.x & 127;
    const int warp = tid >> 5, lane = tid & 31;
    const uint32_t dbase = (sbase & 0x3FFFFu) >> 4;
    const uint32_t k_base = dbase + (1u << 16);
    const uint32_t v_base = dbase + (1024u << 16);
    const uint32_t w_base = dbase + (512u << 16);
    const uint32_t q_lo = dbase + ((AT_SQ + cwg * 8192) >> 4) + (1u << 16);
    const uint32_t frag = cwg * 8192 + (16 * warp + (lane & 7) + 8 * ((lane >> 3) & 1)) * 128;
    if (cwg == 1) named_bar_arrive(1, 256);
    bool raw = false;
    uint4 pre[8];
    #pragma unroll 1
    for (int it = 0; it < n_items; it++) {
      const bool more = it + 1 < n_items;
      constexpr int nkb = T_D / 64;
      const int ta = __shfl_sync(0xffffffffu, 4 * it, 0);
      float acc[128];
      {
        FS(2 * it, 0);
        #pragma unroll
        for (int i = 0; i < 128; i++) asm volatile("" : "=f"(acc[i]));
        {
          const uint32_t slot = ring_slot(ta), b_lo = w_base + slot * 2048;
          mbar_wait(b_full + 8 * slot, ring_par(ta));
          wgmma_fence();
          wgmma_m64n256k16_ss_tb<0, 0>(acc, q_lo, b_lo, 0);
          wgmma_m64n256k16_ss_tb<2, 128>(acc, q_lo, b_lo, 1);
          wgmma_m64n256k16_ss_tb<4, 256>(acc, q_lo, b_lo, 1);
          wgmma_m64n256k16_ss_tb<6, 384>(acc, q_lo, b_lo, 1);
          wgmma_commit();
        }
        #pragma unroll 1
        for (int j = NOZERO; j < nkb; j++) {
          const uint32_t slot = ring_slot(qp_pos(j, ta >> 2));
          mbar_wait(b_full + 8 * slot, ring_par(qp_pos(j, ta >> 2)) ^ ((j >> 2) & 1));
          if (QP_STAG > 0 && cwg == 1 && j == nkb - QP_STAG) named_bar_sync(7, 256);
          const uint32_t a_lo = q_lo + (j & 3) * 1024, b_lo = w_base + slot * 2048;
          wgmma_fence();
          wgmma_m64n256k16_ss_tb<0, 0>(acc, a_lo, b_lo, 1);
          wgmma_m64n256k16_ss_tb<2, 128>(acc, a_lo, b_lo, 1);
          wgmma_m64n256k16_ss_tb<4, 256>(acc, a_lo, b_lo, 1);
          wgmma_m64n256k16_ss_tb<6, 384>(acc, a_lo, b_lo, 1);
          wgmma_commit();
          if (QP_STAG > 0 && cwg == 0 && j == nkb - 1) named_bar_arrive(7, 256);
          if (j > 0) {
            wgmma_wait<1>();
            if (tid == 0) mbar_arrive(b_empty + 8 * ring_slot(qp_pos(j - 1, ta >> 2)));
          }
        }
        wgmma_wait<0>();
        fence_regs(acc);
        FS(2 * it, 1);
        TL_MARK2(29, threadIdx.x == 256 && it == 0);
        if (tid == 0) mbar_arrive(b_empty + 24);
      }
      float o[64], s[64];
      uint32_t p[32], q[32];
      #pragma unroll
      for (int i = 0; i < 32; i++) q[i] = pack_bf16(acc[2 * i] * AT_C, acc[2 * i + 1] * AT_C);
      zero_regs(s);
      const uint32_t sq = sbase + AT_SQ + cwg * 8192;
      const bool last_wg1 = cwg == 1 && !more;
      float mc0, mc1, al0 = 1.0f, al1 = 1.0f, l0 = 0.f, l1 = 0.f, lp0 = 0.f, lp1 = 0.f;
      bool redo0 = false;
      FS(2 * it, 2);
      mbar_wait(b_full + 8 * ring_slot(ta), ring_par(ta));
      named_bar_sync(1 + cwg, 256);
      FS(2 * it, 3);
      issue_qk(s, q, k_base + ring_slot(ta) * 2048);
      named_bar_arrive(1 + (cwg ^ 1), 256);
      bool ready = mbar_test(b_full + 8 * ring_slot(ta + 1), ring_par(ta + 1)) & mbar_test(b_full + 8 * ring_slot(ta + 2), ring_par(ta + 2));
      stage_q<16>(acc, AT_C, sbase + AT_SQ + frag, lane);
      wgmma_wait<0>();
      fence_regs(s);
      if (tid == 0) mbar_arrive(b_empty + 8 * ring_slot(ta));
      mc0 = 0.f; mc1 = 0.f;
      if (!raw) {
        raw = softmax_mode(s, mc0, mc1);
        if (__builtin_expect(!raw, 0)) softmax_sub(s, mc0, mc1);
      }
      softmax_exp<0, 64>(s);
      #pragma unroll
      for (int J = 0; J < 16; J += 2)
        stmatrix_x4(sbase + AT_SQ + frag + (J >> 3) * 16384 + ((((J & 7) + (lane >> 4)) ^ (lane & 7)) << 4), q[2 * J], q[2 * J + 1], q[2 * J + 2], q[2 * J + 3]);
      pack_p(p, s);
      zero_regs(o);
      FS(2 * it, 4);
      uint32_t ks = ring_slot(ta + 1), vs = ring_slot(ta + 2), kp = ring_par(ta + 1), vp = ring_par(ta + 2);
      auto finish_head = [&]() {
        FS(2 * it, 5);
        redo0 = finish_l(lp0, lp1);
        if (!redo0) {
          stage_o(o, lp0, lp1, sbase + AT_SQ + frag, lane);
          fence_proxy_async();
          __syncwarp();
          if (lane == 0) mbar_arrive(b_ordy + 8 * cwg);
        }
        FS(2 * it + 1, 4);
      };
      if (!ready) { mbar_wait(b_full + 8 * ks, kp); mbar_wait(b_full + 8 * vs, vp); }
      #pragma unroll 1
      for (int n = 1; n < 2 * AT_NBLK; n++) {
        named_bar_sync(1 + cwg, 256);
        issue_qk(s, q, k_base + ks * 2048);
        if (n == AT_NBLK + 1) finish_head();
        issue_pv(o, p, v_base + vs * 2048, (n & 15) != 1);
        if (!(last_wg1 && n == 2 * AT_NBLK - 1)) named_bar_arrive(1 + (cwg ^ 1), 256);
        wgmma_wait<1>();
        fence_regs(s);
        if (tid == 0) mbar_arrive(b_empty + 8 * ks);
        if (__builtin_expect(!raw || (n + 1) >> 1 == AT_NBLK / 2, 0)) {
          if (n == AT_NBLK - 1) {
            #pragma unroll
            for (int J = 0; J < 16; J += 2)
              ldmatrix_x4(sbase + AT_SQ + 32768 + frag + (J >> 3) * 16384 + ((((J & 7) + (lane >> 4)) ^ (lane & 7)) << 4), q[2 * J], q[2 * J + 1], q[2 * J + 2], q[2 * J + 3]);
          }
          if (!raw) {
            const float m0 = mc0, m1 = mc1;
            const bool ok = softmax_mode(s, mc0, mc1);
            if (n == AT_NBLK) raw = ok;
            else {
              mc0 = mc0 - AT_HEAD > m0 ? mc0 : m0; mc1 = mc1 - AT_HEAD > m1 ? mc1 : m1;
              al0 = ex2_approx(m0 - mc0); al1 = ex2_approx(m1 - mc1);
            }
            if (!raw) softmax_sub(s, mc0, mc1);
          }
        }
        softmax_exp<0, AT_SPLIT>(s);
        add_rowsum(p, l0, l1);
        if (tid == 0) {
          uint32_t dep = zero & __float_as_uint(l0) & __float_as_uint(l1);
          #pragma unroll
          for (int i = AT_SPLIT - AT_PIN - PINB; i < AT_SPLIT - PINB; i += 2) dep &= __float_as_uint(s[i]) & __float_as_uint(s[i + 1]);
          mbar_arrive(b_pin + dep);
        }
        wgmma_wait<0>();
        fence_regs(o);
        if (tid == 0) mbar_arrive(b_empty + 8 * vs);
        ks += 2; if (ks >= 5) { ks -= 5; kp ^= 1; }
        vs += 2; if (vs >= 5) { vs -= 5; vp ^= 1; }
        ready = mbar_test(b_full + 8 * ks, kp) & mbar_test(b_full + 8 * vs, vp);
        softmax_exp<AT_SPLIT, 64>(s);
        pack_p(p, s);
        if (n == AT_NBLK) { lp0 = l0; lp1 = l1; l0 = 0.f; l1 = 0.f; }
        if (__builtin_expect(!raw || !ready, 0)) {
        if (!raw && __any_sync(0xffffffffu, al0 != 1.0f || al1 != 1.0f)) {
          rescale_o(o, al0, al1);
          l0 *= al0; l1 *= al1;
          al0 = 1.0f; al1 = 1.0f;
        }
        if (!ready && n < 2 * AT_NBLK - 1) {
          mbar_wait(b_full + 8 * ks, kp);
          mbar_wait(b_full + 8 * vs, vp);
        }
        }
      }
      FS(2 * it + 1, 5);
      const uint32_t vl = ring_slot(ta + 63);
      vs = ring_slot(ta + 62);
      const uint32_t ob = more ? sbase + vs * 32768 : sbase + AT_SQ + 32768;
      if (redo0) {
        attn_rows_exact(sq, sq, 4 * ta, kc, vc);
        fence_proxy_async();
        __syncwarp();
        if (lane == 0) mbar_arrive(b_ordy + 8 * cwg);
      }
      mbar_wait(b_full + 8 * vl, ring_par(ta + 63));
      issue_pv(o, p, v_base + vl * 2048, 1);
      add_rowsum(p, l0, l1);
      const bool overflow = finish_l(l0, l1);
      if (!overflow && lane == 0) mbar_arrive(b_q1);
      #pragma unroll
      for (int i = 0; i < 8; i++) asm volatile("mov.b64 {%0, %1}, 0;\nmov.b64 {%2, %3}, 0;" : "=r"(pre[i].x), "=r"(pre[i].y), "=r"(pre[i].z), "=r"(pre[i].w));
      if (HOIST && !more && blockIdx.x < OG_MOE) {
        load_pre(pre, sbase, AT_SQ, threadIdx.x - 128);
        __syncwarp();
        if (lane == 0) mbar_arrive(bars + 304);
      }
      mbar_wait(b_empty + 8 * vs, ring_par(ta + 62));
      wgmma_wait<0>();
      fence_regs(o);
      if (tid == 0) mbar_arrive(b_empty + 8 * vl);
      FS(2 * it + 1, 6);
      if (overflow) {
        attn_rows_exact(sq + 32768, ob + cwg * 8192, 4 * ta + 1, kc, vc);
        __syncwarp();
        if (lane == 0) mbar_arrive(b_q1);
      } else stage_o(o, l0, l1, ob + frag, lane);
      fence_proxy_async();
      __syncwarp();
      if (lane == 0) mbar_arrive(b_ordy + 16 + 8 * cwg);
      if (redo0 || overflow) raw = false;
      named_bar_sync(3 + cwg, 128);
      FS(2 * it + 1, 7);
    }
    if (__builtin_expect(single, 0)) {
      float acc[128];
      uint32_t j = 0, pk[64];
      #pragma unroll
      for (int i = 0; i < 64; i++) asm volatile("" : "=f"(acc[2 * i]), "=f"(acc[2 * i + 1]), "=r"(pk[i]));
      uint4* dst = g_pre;
      int left = 0;
      auto put = [&](bool last) {
        #pragma unroll
        for (int i = 0; i < PUT_N; i++) dst[i * 256] = make_uint4(pk[4 * i], pk[4 * i + 1], pk[4 * i + 2], pk[4 * i + 3]);
        dst += PUT_N * 256;
        #pragma unroll
        for (int i = 0; i < 64 - 4 * PUT_N; i++) asm volatile("mov.b32 %0, %1;" : "=r"(pk[i]) : "r"(pk[i + 4 * PUT_N]));
        __syncwarp();
        if (last && lane == 0) mbar_arrive(bars + 280);
      };
      #pragma unroll 1
      for (int ji = 0; ji < help_njobs(); ji++) {
        const int nk = ji < OG_JOBS ? OG_PRE : OG_PRE2;
        #pragma unroll 1
        for (int kk = 0; kk < nk; kk++, j++) {
          const uint32_t slot = ring_slot(qp_pos(j, 1));
          mbar_wait(b_full + 8 * slot, ring_par(qp_pos(j, 1)) ^ ((j >> 2) & 1));
          if (H_STAG > 0 && cwg == 1 && kk == nk - H_STAG) named_bar_sync(7, 256);
          const uint32_t a_lo = q_lo + (j & 3) * 1024, b_lo = w_base + slot * 2048;
          wgmma_fence();
          wgmma_m64n256k16_ss_tb<0, 0>(acc, a_lo, b_lo, kk != 0);
          wgmma_m64n256k16_ss_tb<2, 128>(acc, a_lo, b_lo, 1);
          wgmma_m64n256k16_ss_tb<4, 256>(acc, a_lo, b_lo, 1);
          wgmma_m64n256k16_ss_tb<6, 384>(acc, a_lo, b_lo, 1);
          wgmma_commit();
          if (H_STAG > 0 && cwg == 0 && kk == nk - 1) named_bar_arrive(7, 256);
          wgmma_wait<1>();
          if (kk > 0 && tid == 0) mbar_arrive(b_empty + 8 * ring_slot(qp_pos(j - 1, 1)));
          #pragma unroll 1
          for (int i = ji == OG_JOBS ? 0 : 16 / PUT_N - 1; i < 16 / PUT_N && left > 0; i++) put(--left == 0);
        }
        wgmma_wait<0>();
        fence_regs(acc);
        if (tid == 0) mbar_arrive(b_empty + 8 * ring_slot(qp_pos(j - 1, 1)));
        #pragma unroll
        for (int i = 0; i < 64; i++) pk[i] = pack_bf16(acc[2 * i], acc[2 * i + 1]);
        left = 16 / PUT_N;
        if (ji == PRE_X) mbar_wait(bars + 296, 0);
        dst = g_pre + pre_loc(help_job(ji)) * 4096 + threadIdx.x - 128;
      }
      #pragma unroll
      for (int i = 0; i < 16; i++) dst[i * 256] = make_uint4(pk[4 * i], pk[4 * i + 1], pk[4 * i + 2], pk[4 * i + 3]);
      __syncwarp();
      if (lane == 0) mbar_arrive(bars + 280);
      named_bar_sync(5, 256);
      if (threadIdx.x == 128) {
        #pragma unroll 1
        for (int i = 0; i < 5; i++) {
          constexpr int n = OG_JOBS * OG_PRE;
          const int used = i == 3 ? 0 : (n + 3 - (i == 4 ? 3 : i)) / 4;
          if ((used ^ (i < 4)) & 1) {
            mbar_arrive(b_full + 8 * ring_slot(4 + i));
            mbar_arrive(b_empty + 8 * ring_slot(4 + i)); mbar_arrive(b_empty + 8 * ring_slot(4 + i));
          }
        }
        mbar_arrive(b_x);
      }
      named_bar_sync(5, 256);
      #pragma unroll
      for (int i = 0; i < 8; i++) pre[i] = make_uint4(0u, 0u, 0u, 0u);
    }
    TL_CLK(3, 1, threadIdx.x == 128);
    TL_CTA(1, threadIdx.x == 256);
    TL_END(3, tid == 0);
    TL_MARK2(19, tid == 0 && !single);
    if (blockIdx.x < 128) {
      if (!HOIST && blockIdx.x < OG_MOE) {
        load_pre(pre, sbase, AT_SQ, threadIdx.x - 128);
        __syncwarp();
        if (lane == 0) mbar_arrive(bars + 304);
      }
      tail_consumer(sbase, pre, cwg, w_gate, w_up);
    }
  }
}

typedef CUresult (*PFN_encodeTiled)(CUtensorMap*, CUtensorMapDataType, cuuint32_t, void*, const cuuint64_t*, const cuuint64_t*,
                                    const cuuint32_t*, const cuuint32_t*, CUtensorMapInterleave, CUtensorMapSwizzle,
                                    CUtensorMapL2promotion, CUtensorMapFloatOOBfill);

CUtensorMap make_map_2d(PFN_encodeTiled enc, const void* ptr, uint64_t inner, uint64_t outer, uint64_t stride_bytes, uint32_t box_inner, uint32_t box_outer) {
  CUtensorMap m;
  cuuint64_t gd[2] = {inner, outer}; cuuint64_t gs[1] = {stride_bytes};
  cuuint32_t bx[2] = {box_inner, box_outer}; cuuint32_t es[2] = {1, 1};
  enc(&m, CU_TENSOR_MAP_DATA_TYPE_BFLOAT16, 2, const_cast<void*>(ptr), gd, gs, bx, es, CU_TENSOR_MAP_INTERLEAVE_NONE,
      CU_TENSOR_MAP_SWIZZLE_128B, CU_TENSOR_MAP_L2_PROMOTION_L2_128B, CU_TENSOR_MAP_FLOAT_OOB_FILL_NONE);
  return m;
}

CUtensorMap make_map_3d(PFN_encodeTiled enc, const void* ptr, uint64_t cols, uint64_t rows, uint32_t box_rows, uint32_t chunks) {
  CUtensorMap m;
  cuuint64_t gd[3] = {64, rows, cols / 64}; cuuint64_t gs[2] = {cols * 2, 128};
  cuuint32_t bx[3] = {64, box_rows, chunks}; cuuint32_t es[3] = {1, 1, 1};
  enc(&m, CU_TENSOR_MAP_DATA_TYPE_BFLOAT16, 3, const_cast<void*>(ptr), gd, gs, bx, es, CU_TENSOR_MAP_INTERLEAVE_NONE,
      CU_TENSOR_MAP_SWIZZLE_128B, CU_TENSOR_MAP_L2_PROMOTION_L2_128B, CU_TENSOR_MAP_FLOAT_OOB_FILL_NONE);
  return m;
}

}

extern "C" void kernel_launch(void* const* d_in, const int* in_sizes, int n_in, void* d_out, int out_size) {
  const bf16* x      = (const bf16*)d_in[0];
  const bf16* kc     = (const bf16*)d_in[1];
  const bf16* vc     = (const bf16*)d_in[2];
  const bf16* wq     = (const bf16*)d_in[3];
  const bf16* wo     = (const bf16*)d_in[4];
  const bf16* w_r    = (const bf16*)d_in[6];
  const bf16* w_gate = (const bf16*)d_in[7];
  const bf16* w_up   = (const bf16*)d_in[8];
  const bf16* w_down = (const bf16*)d_in[9];
  const bf16* cvec   = (const bf16*)d_in[10];
  const bf16* w_mod  = (const bf16*)d_in[11];
  bf16* out = (bf16*)d_out;

  static PFN_encodeTiled enc = nullptr;
  static void *p_h = nullptr, *p_o = nullptr;
  if (!enc) {
    void* fn = nullptr; cudaDriverEntryPointQueryResult qres;
    cudaGetDriverEntryPoint("cuTensorMapEncodeTiled", &fn, cudaEnableDefault, &qres);
    enc = (PFN_encodeTiled)fn;
    cudaGetSymbolAddress(&p_h, g_pre);
    p_h = (uint4*)p_h + 16 * PRE_X * 2048;
    cudaGetSymbolAddress(&p_o, g_o);
    cudaFuncSetAttribute(fused_kernel, cudaFuncAttributeMaxDynamicSharedMemorySize, (int)AT_SMEM);
  }
  const CUtensorMap tm_h   = make_map_2d(enc, p_h, T_D, T_SEQ, T_D * 2, 64, 128);
  const CUtensorMap tm_wq  = W3D ? make_map_3d(enc, wq, T_DQKV, T_D, 64, 4) : make_map_2d(enc, wq, T_DQKV, T_D, T_DQKV * 2, 64, 64);
  const CUtensorMap tm_k   = KV3D ? make_map_3d(enc, kc, T_DH, (uint64_t)T_NH * T_SEQ, 128, 2) : make_map_2d(enc, kc, T_DH, (uint64_t)T_NH * T_SEQ, T_DH * 2, 64, 128);
  const CUtensorMap tm_v   = KV3D ? make_map_3d(enc, vc, T_DH, (uint64_t)T_NH * T_SEQ, 128, 2) : make_map_2d(enc, vc, T_DH, (uint64_t)T_NH * T_SEQ, T_DH * 2, 64, 128);
  const CUtensorMap tm_ost = make_map_2d(enc, p_o, T_DQKV, T_SEQ, T_DQKV * 2, 64, 64);
  const CUtensorMap tm_old = make_map_2d(enc, p_o, T_DQKV, T_SEQ, T_DQKV * 2, 64, 128);
  const CUtensorMap tm_wo  = make_map_3d(enc, wo, T_D, T_DQKV, 64, 2);
  const CUtensorMap tm_x   = make_map_3d(enc, w_down, T_D, T_F, 32, 8);

  const CUtensorMap tm_m   = make_map_2d(enc, w_mod, 6 * T_D, T_D, 6 * T_D * 2, 64, 256);
  const CUtensorMap tm_out = make_map_2d(enc, out, T_D, T_SEQ, T_D * 2, 64, 128);

  fused_kernel<<<132, 384, AT_SMEM, cudaStreamPerThread>>>(tm_h, tm_wq, tm_k, tm_v, tm_ost, tm_old, tm_wo, tm_x, tm_out, tm_m, 0u, (const uint8_t*)wo, kc, vc, x, cvec, w_mod,
             w_r, w_gate, w_up, w_down, out);
}
```

```cpp
#include <cuda_runtime.h>
#include <cuda_bf16.h>
#include <cuda.h>
#include <stdint.h>

namespace {

typedef __nv_bfloat16 bf16;

constexpr int T_SEQ = 2048, T_D = 1024, T_NH = 32, T_DH = 128, T_DQKV = 4096, T_F = 3584;

#define PRE_X 2
__device__ __align__(1024) uint4 g_pre[(16 * PRE_X + 128) * 2048];
#define g_h (reinterpret_cast<bf16*>(g_pre + 16 * PRE_X * 2048))
__device__ __align__(1024) bf16 g_o[T_SEQ * T_DQKV];
__device__ __align__(16) uint8_t g_col[8 * 1536];
__device__ __align__(16) float g_scal[64];
__device__ __align__(16) unsigned int g_hcnt[17 * 32];
__device__ unsigned int g_smid[168], g_tmax[128];
__device__ __align__(128) float g_modpart[4 * 2 * T_D];
struct __align__(2048) TailMail {
  float4 part1[T_SEQ * 8];
  uint32_t key[256];
  uint4 cand[16 * 2 * 2 * 128];
  uint32_t cnt[32];
  float ypart[(T_F / 32) * 2 * T_D];
};
__device__ TailMail g_mail;
#define g_part1 g_mail.part1
#define g_key g_mail.key
#define g_cand g_mail.cand
#define CNT_Y (g_mail.cnt)
#define g_ypart g_mail.ypart

__device__ __forceinline__ uint32_t smem_u32(const void* p) { return (uint32_t)__cvta_generic_to_shared(p); }
__device__ __forceinline__ void mbar_init(uint32_t bar, uint32_t cnt) { asm volatile("mbarrier.init.shared::cta.b64 [%0], %1;" :: "r"(bar), "r"(cnt)); }
__device__ __forceinline__ void mbar_expect_tx(uint32_t bar, uint32_t bytes) { asm volatile("mbarrier.arrive.expect_tx.shared::cta.b64 _, [%0], %1;" :: "r"(bar), "r"(bytes) : "memory"); }
__device__ __forceinline__ void mbar_arrive(uint32_t bar) { asm volatile("mbarrier.arrive.shared::cta.b64 _, [%0];" :: "r"(bar) : "memory"); }
__device__ __forceinline__ void mbar_wait(uint32_t bar, uint32_t parity) {
  asm volatile("{\n.reg .pred p;\nLAB_WAIT:\nmbarrier.try_wait.parity.shared::cta.b64 p, [%0], %1;\n@!p bra LAB_WAIT;\n}\n" :: "r"(bar), "r"(parity) : "memory");
}
__device__ __forceinline__ bool mbar_test(uint32_t bar, uint32_t parity) {
  uint32_t r; asm volatile("{\n.reg .pred p;\nmbarrier.test_wait.parity.shared::cta.b64 p, [%1], %2;\nselp.u32 %0, 1, 0, p;\n}\n" : "=r"(r) : "r"(bar), "r"(parity) : "memory");
  return r != 0;
}
__device__ __forceinline__ uint32_t clock_lo() { uint32_t c; asm volatile("mov.u32 %0, %%clock;" : "=r"(c)); return c; }
__device__ __forceinline__ void fence_mbar_init() { asm volatile("fence.mbarrier_init.release.cluster;" ::: "memory"); }
__device__ __forceinline__ void tma_load_2d(uint32_t dst, const CUtensorMap* map, int c0, int c1, uint32_t bar) {
  asm volatile("cp.async.bulk.tensor.2d.shared::cluster.global.mbarrier::complete_tx::bytes [%0], [%1, {%3, %4}], [%2];"
    :: "r"(dst), "l"(map), "r"(bar), "r"(c0), "r"(c1) : "memory");
}
__device__ __forceinline__ uint64_t policy_evict_first() {
  uint64_t p; asm volatile("createpolicy.fractional.L2::evict_first.b64 %0, 1.0;" : "=l"(p)); return p;
}
__device__ __forceinline__ void tma_load_2d_hint(uint32_t dst, const CUtensorMap* map, int c0, int c1, uint32_t bar, uint64_t pol) {
  asm volatile("cp.async.bulk.tensor.2d.shared::cluster.global.mbarrier::complete_tx::bytes.L2::cache_hint [%0], [%1, {%3, %4}], [%2], %5;"
    :: "r"(dst), "l"(map), "r"(bar), "r"(c0), "r"(c1), "l"(pol) : "memory");
}
__device__ __forceinline__ void tma_load_3d_hint(uint32_t dst, const CUtensorMap* map, int c1, int c2, uint32_t bar, uint64_t pol) {
  asm volatile("cp.async.bulk.tensor.3d.shared::cluster.global.mbarrier::complete_tx::bytes.L2::cache_hint [%0], [%1, {%3, %4, %5}], [%2], %6;"
    :: "r"(dst), "l"(map), "r"(bar), "n"(0), "r"(c1), "r"(c2), "l"(pol) : "memory");
}
__device__ __forceinline__ void tma_store_2d(const CUtensorMap* map, uint32_t src, int c0, int c1) {
  asm volatile("cp.async.bulk.tensor.2d.global.shared::cta.bulk_group [%0, {%2, %3}], [%1];" :: "l"(map), "r"(src), "r"(c0), "r"(c1) : "memory");
}
__device__ __forceinline__ void prefetch_tmap(const CUtensorMap* map) { asm volatile("prefetch.tensormap [%0];" :: "l"(map) : "memory"); }
__device__ __forceinline__ void l2_prefetch_bulk(const void* p, uint32_t bytes) {
  asm volatile("cp.async.bulk.prefetch.L2.global [%0], %1;" :: "l"(p), "r"(bytes) : "memory");
}
__device__ __forceinline__ void bulk_commit() { asm volatile("cp.async.bulk.commit_group;" ::: "memory"); }
template<int N> __device__ __forceinline__ void bulk_wait_read() { asm volatile("cp.async.bulk.wait_group.read %0;" :: "n"(N) : "memory"); }
template<int N> __device__ __forceinline__ void bulk_wait() { asm volatile("cp.async.bulk.wait_group %0;" :: "n"(N) : "memory"); }
__device__ __forceinline__ void named_bar_sync(int id, int nthreads) { asm volatile("bar.sync %0, %1;" :: "r"(id), "r"(nthreads) : "memory"); }
__device__ __forceinline__ void named_bar_arrive(int id, int nthreads) { asm volatile("bar.arrive %0, %1;" :: "r"(id), "r"(nthreads) : "memory"); }
__device__ __forceinline__ void wgmma_fence() { asm volatile("wgmma.fence.sync.aligned;" ::: "memory"); }
__device__ __forceinline__ void wgmma_commit() { asm volatile("wgmma.commit_group.sync.aligned;" ::: "memory"); }
template<int N> __device__ __forceinline__ void wgmma_wait() { asm volatile("wgmma.wait_group.sync.aligned %0;" :: "n"(N) : "memory"); }
template<int R> __device__ __forceinline__ void reg_alloc() { asm volatile("setmaxnreg.inc.sync.aligned.u32 %0;" :: "n"(R)); }
template<int R> __device__ __forceinline__ void reg_dealloc() { asm volatile("setmaxnreg.dec.sync.aligned.u32 %0;" :: "n"(R)); }
__device__ __forceinline__ bool elect_one() {
  uint32_t pred; asm volatile("{\n.reg .pred p;\nelect.sync _|p, 0xffffffff;\nselp.u32 %0, 1, 0, p;\n}\n" : "=r"(pred)); return pred != 0;
}
__device__ __forceinline__ uint32_t pack_bf16(float lo, float hi) {
  uint32_t r; asm("cvt.rn.bf16x2.f32 %0, %1, %2;" : "=r"(r) : "f"(hi), "f"(lo)); return r;
}
__device__ __forceinline__ void stmatrix_x4(uint32_t addr, uint32_t r0, uint32_t r1, uint32_t r2, uint32_t r3) {
  asm volatile("stmatrix.sync.aligned.m8n8.x4.shared.b16 [%0], {%1, %2, %3, %4};" :: "r"(addr), "r"(r0), "r"(r1), "r"(r2), "r"(r3) : "memory");
}
__device__ __forceinline__ void fence_proxy_async() { asm volatile("fence.proxy.async.shared::cta;" ::: "memory"); }
__device__ __forceinline__ float ex2_approx(float x) { float y; asm("ex2.approx.ftz.f32 %0, %1;" : "=f"(y) : "f"(x)); return y; }
template<int N> __device__ __forceinline__ void fence_regs(float (&r)[N]) {
  #pragma unroll
  for (int i = 0; i < N; i++) asm volatile("" : "+f"(r[i]) :: "memory");
}
template<int N> __device__ __forceinline__ void zero_regs(float (&r)[N]) {
  #pragma unroll
  for (int i = 0; i < N; i += 2) asm volatile("mov.b64 {%0, %1}, 0;" : "=f"(r[i]), "=f"(r[i + 1]));
}
__device__ __forceinline__ float rbf(float x) { return __uint_as_float(pack_bf16(0.f, x)); }
__device__ __forceinline__ float bflo(uint32_t v) { return __uint_as_float(v << 16); }
__device__ __forceinline__ float bfhi(uint32_t v) { return __uint_as_float(v & 0xffff0000u); }

#define TL_START(k) do {} while (0)
#define TL_END(k, cond) do {} while (0)
#define TL_CTA(i, cond) do {} while (0)
#define FS(slot, k) do {} while (0)
#define TL_MARK2(k, cond) do {} while (0)
#define TL_CLK(k, i, cond) do {} while (0)

template <int OFFA, int OFFB>
__device__ __forceinline__ void wgmma_m64n256k16_ss_tb(float (&d)[128], uint32_t a_lo, uint32_t b_lo, int scaleD) {
  asm volatile("{\n.reg .pred p;\n.reg .b32 ta, tb;\n.reg .b64 da, db;\nsetp.ne.b32 p, %130, 0;\n"
    "add.u32 ta, %128, %131;\nadd.u32 tb, %129, %132;\n"
    "mov.b64 da, {ta, 0x40000040};\nmov.b64 db, {tb, 0x40000040};\n"
    "wgmma.mma_async.sync.aligned.m64n256k16.f32.bf16.bf16 "
    "{%0, %1, %2, %3, %4, %5, %6, %7, %8, %9, %10, %11, %12, %13, %14, %15, %16, %17, %18, %19, %20, %21, %22, %23, %24, %25, %26, %27, %28, %29, %30, %31, %32, %33, %34, %35, %36, %37, %38, %39, %40, %41, %42, %43, %44, %45, %46, %47, %48, %49, %50, %51, %52, %53, %54, %55, %56, %57, %58, %59, %60, %61, %62, %63, %64, %65, %66, %67, %68, %69, %70, %71, %72, %73, %74, %75, %76, %77, %78, %79, %80, %81, %82, %83, %84, %85, %86, %87, %88, %89, %90, %91, %92, %93, %94, %95, %96, %97, %98, %99, %100, %101, %102, %103, %104, %105, %106, %107, %108, %109, %110, %111, %112, %113, %114, %115, %116, %117, %118, %119, %120, %121, %122, %123, %124, %125, %126, %127}, "
    "da, db, p, 1, 1, 0, 1;\n}\n"
    : "+f"(d[0]), "+f"(d[1]), "+f"(d[2]), "+f"(d[3]), "+f"(d[4]), "+f"(d[5]), "+f"(d[6]), "+f"(d[7]), "+f"(d[8]), "+f"(d[9]), "+f"(d[10]), "+f"(d[11]), "+f"(d[12]), "+f"(d[13]), "+f"(d[14]), "+f"(d[15]), "+f"(d[16]), "+f"(d[17]), "+f"(d[18]), "+f"(d[19]), "+f"(d[20]), "+f"(d[21]), "+f"(d[22]), "+f"(d[23]), "+f"(d[24]), "+f"(d[25]), "+f"(d[26]), "+f"(d[27]), "+f"(d[28]), "+f"(d[29]), "+f"(d[30]), "+f"(d[31]), "+f"(d[32]), "+f"(d[33]), "+f"(d[34]), "+f"(d[35]), "+f"(d[36]), "+f"(d[37]), "+f"(d[38]), "+f"(d[39]), "+f"(d[40]), "+f"(d[41]), "+f"(d[42]), "+f"(d[43]), "+f"(d[44]), "+f"(d[45]), "+f"(d[46]), "+f"(d[47]), "+f"(d[48]), "+f"(d[49]), "+f"(d[50]), "+f"(d[51]), "+f"(d[52]), "+f"(d[53]), "+f"(d[54]), "+f"(d[55]), "+f"(d[56]), "+f"(d[57]), "+f"(d[58]), "+f"(d[59]), "+f"(d[60]), "+f"(d[61]), "+f"(d[62]), "+f"(d[63]), "+f"(d[64]), "+f"(d[65]), "+f"(d[66]), "+f"(d[67]), "+f"(d[68]), "+f"(d[69]), "+f"(d[70]), "+f"(d[71]), "+f"(d[72]), "+f"(d[73]), "+f"(d[74]), "+f"(d[75]), "+f"(d[76]), "+f"(d[77]), "+f"(d[78]), "+f"(d[79]), "+f"(d[80]), "+f"(d[81]), "+f"(d[82]), "+f"(d[83]), "+f"(d[84]), "+f"(d[85]), "+f"(d[86]), "+f"(d[87]), "+f"(d[88]), "+f"(d[89]), "+f"(d[90]), "+f"(d[91]), "+f"(d[92]), "+f"(d[93]), "+f"(d[94]), "+f"(d[95]), "+f"(d[96]), "+f"(d[97]), "+f"(d[98]), "+f"(d[99]), "+f"(d[100]), "+f"(d[101]), "+f"(d[102]), "+f"(d[103]), "+f"(d[104]), "+f"(d[105]), "+f"(d[106]), "+f"(d[107]), "+f"(d[108]), "+f"(d[109]), "+f"(d[110]), "+f"(d[111]), "+f"(d[112]), "+f"(d[113]), "+f"(d[114]), "+f"(d[115]), "+f"(d[116]), "+f"(d[117]), "+f"(d[118]), "+f"(d[119]), "+f"(d[120]), "+f"(d[121]), "+f"(d[122]), "+f"(d[123]), "+f"(d[124]), "+f"(d[125]), "+f"(d[126]), "+f"(d[127])
    : "r"(a_lo), "r"(b_lo), "r"(scaleD), "n"(OFFA), "n"(OFFB));
}

template <int OFFA, int OFFB>
__device__ __forceinline__ void wgmma_m64n128k16_ss_tb(float (&d)[64], uint32_t a_lo, uint32_t b_lo, int scaleD) {
  asm volatile("{\n.reg .pred p;\n.reg .b32 ta, tb;\n.reg .b64 da, db;\nsetp.ne.b32 p, %66, 0;\n"
    "add.u32 ta, %64, %67;\nadd.u32 tb, %65, %68;\n"
    "mov.b64 da, {ta, 0x40000040};\nmov.b64 db, {tb, 0x40000040};\n"
    "wgmma.mma_async.sync.aligned.m64n128k16.f32.bf16.bf16 "
    "{%0, %1, %2, %3, %4, %5, %6, %7, %8, %9, %10, %11, %12, %13, %14, %15, %16, %17, %18, %19, %20, %21, %22, %23, %24, %25, %26, %27, %28, %29, %30, %31, %32, %33, %34, %35, %36, %37, %38, %39, %40, %41, %42, %43, %44, %45, %46, %47, %48, %49, %50, %51, %52, %53, %54, %55, %56, %57, %58, %59, %60, %61, %62, %63}, "
    "da, db, p, 1, 1, 0, 1;\n}\n"
    : "+f"(d[0]), "+f"(d[1]), "+f"(d[2]), "+f"(d[3]), "+f"(d[4]), "+f"(d[5]), "+f"(d[6]), "+f"(d[7]), "+f"(d[8]), "+f"(d[9]), "+f"(d[10]), "+f"(d[11]), "+f"(d[12]), "+f"(d[13]), "+f"(d[14]), "+f"(d[15]), "+f"(d[16]), "+f"(d[17]), "+f"(d[18]), "+f"(d[19]), "+f"(d[20]), "+f"(d[21]), "+f"(d[22]), "+f"(d[23]), "+f"(d[24]), "+f"(d[25]), "+f"(d[26]), "+f"(d[27]), "+f"(d[28]), "+f"(d[29]), "+f"(d[30]), "+f"(d[31]), "+f"(d[32]), "+f"(d[33]), "+f"(d[34]), "+f"(d[35]), "+f"(d[36]), "+f"(d[37]), "+f"(d[38]), "+f"(d[39]), "+f"(d[40]), "+f"(d[41]), "+f"(d[42]), "+f"(d[43]), "+f"(d[44]), "+f"(d[45]), "+f"(d[46]), "+f"(d[47]), "+f"(d[48]), "+f"(d[49]), "+f"(d[50]), "+f"(d[51]), "+f"(d[52]), "+f"(d[53]), "+f"(d[54]), "+f"(d[55]), "+f"(d[56]), "+f"(d[57]), "+f"(d[58]), "+f"(d[59]), "+f"(d[60]), "+f"(d[61]), "+f"(d[62]), "+f"(d[63])
    : "r"(a_lo), "r"(b_lo), "r"(scaleD), "n"(OFFA), "n"(OFFB));
}

template <int OFFB>
__device__ __forceinline__ void wgmma_m64n128k16_rs_tb(float (&d)[64], uint32_t a0, uint32_t a1, uint32_t a2, uint32_t a3, uint32_t b_lo, int scaleD) {
  asm volatile("{\n.reg .pred p;\n.reg .b32 tb;\n.reg .b64 db;\nsetp.ne.b32 p, %69, 0;\n"
    "add.u32 tb, %68, %70;\n"
    "mov.b64 db, {tb, 0x40000040};\n"
    "wgmma.mma_async.sync.aligned.m64n128k16.f32.bf16.bf16 "
    "{%0, %1, %2, %3, %4, %5, %6, %7, %8, %9, %10, %11, %12, %13, %14, %15, %16, %17, %18, %19, %20, %21, %22, %23, %24, %25, %26, %27, %28, %29, %30, %31, %32, %33, %34, %35, %36, %37, %38, %39, %40, %41, %42, %43, %44, %45, %46, %47, %48, %49, %50, %51, %52, %53, %54, %55, %56, %57, %58, %59, %60, %61, %62, %63}, "
    "{%64, %65, %66, %67}, db, p, 1, 1, 1;\n}\n"
    : "+f"(d[0]), "+f"(d[1]), "+f"(d[2]), "+f"(d[3]), "+f"(d[4]), "+f"(d[5]), "+f"(d[6]), "+f"(d[7]), "+f"(d[8]), "+f"(d[9]), "+f"(d[10]), "+f"(d[11]), "+f"(d[12]), "+f"(d[13]), "+f"(d[14]), "+f"(d[15]), "+f"(d[16]), "+f"(d[17]), "+f"(d[18]), "+f"(d[19]), "+f"(d[20]), "+f"(d[21]), "+f"(d[22]), "+f"(d[23]), "+f"(d[24]), "+f"(d[25]), "+f"(d[26]), "+f"(d[27]), "+f"(d[28]), "+f"(d[29]), "+f"(d[30]), "+f"(d[31]), "+f"(d[32]), "+f"(d[33]), "+f"(d[34]), "+f"(d[35]), "+f"(d[36]), "+f"(d[37]), "+f"(d[38]), "+f"(d[39]), "+f"(d[40]), "+f"(d[41]), "+f"(d[42]), "+f"(d[43]), "+f"(d[44]), "+f"(d[45]), "+f"(d[46]), "+f"(d[47]), "+f"(d[48]), "+f"(d[49]), "+f"(d[50]), "+f"(d[51]), "+f"(d[52]), "+f"(d[53]), "+f"(d[54]), "+f"(d[55]), "+f"(d[56]), "+f"(d[57]), "+f"(d[58]), "+f"(d[59]), "+f"(d[60]), "+f"(d[61]), "+f"(d[62]), "+f"(d[63])
    : "r"(a0), "r"(a1), "r"(a2), "r"(a3), "r"(b_lo), "r"(scaleD), "n"(OFFB));
}

template <int OFFB>
__device__ __forceinline__ void wgmma_m64n128k16_rs(float (&d)[64], uint32_t a0, uint32_t a1, uint32_t a2, uint32_t a3, uint32_t b_lo, int scaleD) {
  asm volatile("{\n.reg .pred p;\n.reg .b32 tb;\n.reg .b64 db;\nsetp.ne.b32 p, %69, 0;\n"
    "add.u32 tb, %68, %70;\n"
    "mov.b64 db, {tb, 0x40000040};\n"
    "wgmma.mma_async.sync.aligned.m64n128k16.f32.bf16.bf16 "
    "{%0, %1, %2, %3, %4, %5, %6, %7, %8, %9, %10, %11, %12, %13, %14, %15, %16, %17, %18, %19, %20, %21, %22, %23, %24, %25, %26, %27, %28, %29, %30, %31, %32, %33, %34, %35, %36, %37, %38, %39, %40, %41, %42, %43, %44, %45, %46, %47, %48, %49, %50, %51, %52, %53, %54, %55, %56, %57, %58, %59, %60, %61, %62, %63}, "
    "{%64, %65, %66, %67}, db, p, 1, 1, 0;\n}\n"
    : "+f"(d[0]), "+f"(d[1]), "+f"(d[2]), "+f"(d[3]), "+f"(d[4]), "+f"(d[5]), "+f"(d[6]), "+f"(d[7]), "+f"(d[8]), "+f"(d[9]), "+f"(d[10]), "+f"(d[11]), "+f"(d[12]), "+f"(d[13]), "+f"(d[14]), "+f"(d[15]), "+f"(d[16]), "+f"(d[17]), "+f"(d[18]), "+f"(d[19]), "+f"(d[20]), "+f"(d[21]), "+f"(d[22]), "+f"(d[23]), "+f"(d[24]), "+f"(d[25]), "+f"(d[26]), "+f"(d[27]), "+f"(d[28]), "+f"(d[29]), "+f"(d[30]), "+f"(d[31]), "+f"(d[32]), "+f"(d[33]), "+f"(d[34]), "+f"(d[35]), "+f"(d[36]), "+f"(d[37]), "+f"(d[38]), "+f"(d[39]), "+f"(d[40]), "+f"(d[41]), "+f"(d[42]), "+f"(d[43]), "+f"(d[44]), "+f"(d[45]), "+f"(d[46]), "+f"(d[47]), "+f"(d[48]), "+f"(d[49]), "+f"(d[50]), "+f"(d[51]), "+f"(d[52]), "+f"(d[53]), "+f"(d[54]), "+f"(d[55]), "+f"(d[56]), "+f"(d[57]), "+f"(d[58]), "+f"(d[59]), "+f"(d[60]), "+f"(d[61]), "+f"(d[62]), "+f"(d[63])
    : "r"(a0), "r"(a1), "r"(a2), "r"(a3), "r"(b_lo), "r"(scaleD), "n"(OFFB));
}

__device__ __forceinline__ uint4 ldg_nc_v4(const void* p) {
  uint4 v;
    asm volatile("{\n.reg .b64 pol;\ncreatepolicy.fractional.L2::evict_first.b64 pol, 1.0;\n"
                 "ld.global.nc.L1::no_allocate.L2::cache_hint.v4.u32 {%0, %1, %2, %3}, [%4], pol;\n}\n" : "=r"(v.x), "=r"(v.y), "=r"(v.z), "=r"(v.w) : "l"(p));
  return v;
}
__device__ __forceinline__ uint64_t pol_normal() {
  uint64_t p; asm volatile("createpolicy.fractional.L2::evict_normal.b64 %0, 1.0;" : "=l"(p)); return p;
}
__device__ __forceinline__ void unpack8(const uint4& u, float (&v)[8]) {
  v[0] = bflo(u.x); v[1] = bfhi(u.x); v[2] = bflo(u.y); v[3] = bfhi(u.y);
  v[4] = bflo(u.z); v[5] = bfhi(u.z); v[6] = bflo(u.w); v[7] = bfhi(u.w);
}
__device__ __forceinline__ void fma8(float (&acc)[8], float s, const uint4& w) {
  acc[0] = fmaf(s, bflo(w.x), acc[0]); acc[1] = fmaf(s, bfhi(w.x), acc[1]); acc[2] = fmaf(s, bflo(w.y), acc[2]); acc[3] = fmaf(s, bfhi(w.y), acc[3]);
  acc[4] = fmaf(s, bflo(w.z), acc[4]); acc[5] = fmaf(s, bfhi(w.z), acc[5]); acc[6] = fmaf(s, bflo(w.w), acc[6]); acc[7] = fmaf(s, bfhi(w.w), acc[7]);
}
__device__ __forceinline__ float rcp_approx(float x) { float y; asm("rcp.approx.ftz.f32 %0, %1;" : "=f"(y) : "f"(x)); return y; }
__device__ __forceinline__ float sigmoid_f(float v) { return rcp_approx(1.0f + ex2_approx(v * -1.4426950408889634f)); }
__device__ __forceinline__ float silu_bf(float v) { return rbf(v * sigmoid_f(v)); }
__device__ __forceinline__ uint32_t rank_key(float r, int idx) {
  const uint32_t b = __float_as_uint(r) >> 16;
  const uint32_t u = (r != r) ? 0u : ((b & 0x8000u) ? (~b & 0xffffu) : (b | 0x8000u));
  return (u << 16) | (0xffffu - (uint32_t)idx);
}
__device__ __forceinline__ void warp_top2(uint32_t& k1, uint32_t& k2) {
  const uint32_t m1 = __reduce_max_sync(0xffffffffu, k1);
  k2 = __reduce_max_sync(0xffffffffu, k1 == m1 ? k2 : k1);
  k1 = m1;
}
__device__ __forceinline__ uint32_t bmul2(uint32_t a, uint32_t b) { uint32_t r; asm("mul.rn.bf16x2 %0, %1, %2;" : "=r"(r) : "r"(a), "r"(b)); return r; }
__device__ __forceinline__ uint32_t badd2(uint32_t a, uint32_t b) { uint32_t r; asm("add.rn.bf16x2 %0, %1, %2;" : "=r"(r) : "r"(a), "r"(b)); return r; }
__device__ __forceinline__ uint32_t bsub2(uint32_t a, uint32_t b) { uint32_t r; asm("sub.rn.bf16x2 %0, %1, %2;" : "=r"(r) : "r"(a), "r"(b)); return r; }
__device__ __forceinline__ float sqrt_approx(float x) { float y; asm("sqrt.approx.f32 %0, %1;" : "=f"(y) : "f"(x)); return y; }
__device__ __forceinline__ uint32_t ln_norm2(uint32_t x1, uint32_t mb2, float inv) {
  const uint32_t d = bsub2(x1, mb2);
  return pack_bf16(bflo(d) * inv, bfhi(d) * inv);
}
__device__ __forceinline__ uint32_t bfma2(uint32_t a, uint32_t b, uint32_t c) { uint32_t r; asm("fma.rn.bf16x2 %0, %1, %2, %3;" : "=r"(r) : "r"(a), "r"(b), "r"(c)); return r; }
__device__ __forceinline__ uint32_t ln_norm2b(uint32_t x1, uint32_t mb2, uint32_t ih, uint32_t il) {
  const uint32_t d = bsub2(x1, mb2);
  return bfma2(d, ih, bmul2(d, il));
}
__device__ __forceinline__ uint32_t ln_mod2(uint32_t x1, uint32_t mb2, float inv, uint32_t c1, uint32_t sb) { return badd2(bmul2(ln_norm2(x1, mb2, inv), c1), sb); }
__device__ __forceinline__ void ldmatrix_x4(uint32_t addr, uint32_t& r0, uint32_t& r1, uint32_t& r2, uint32_t& r3) {
  asm volatile("ldmatrix.sync.aligned.m8n8.x4.shared.b16 {%0, %1, %2, %3}, [%4];" : "=r"(r0), "=r"(r1), "=r"(r2), "=r"(r3) : "r"(addr) : "memory");
}
__device__ __forceinline__ uint4 ldg_stream_v4(const void* p, uint64_t pol) {
  uint4 v; asm volatile("ld.global.nc.L1::no_allocate.L2::cache_hint.L2::128B.v4.u32 {%0, %1, %2, %3}, [%4], %5;" : "=r"(v.x), "=r"(v.y), "=r"(v.z), "=r"(v.w) : "l"(p), "l"(pol)); return v;
}
__device__ __forceinline__ void bulk_load_hint(uint32_t dst, const void* src, uint32_t bytes, uint32_t bar, uint64_t pol) {
  asm volatile("cp.async.bulk.shared::cluster.global.mbarrier::complete_tx::bytes.L2::cache_hint [%0], [%1], %2, [%3], %4;"
    :: "r"(dst), "l"(src), "r"(bytes), "r"(bar), "l"(pol) : "memory");
}
__device__ __forceinline__ void red_release_add(unsigned int* p, unsigned int v) { asm volatile("red.release.gpu.global.add.u32 [%0], %1;" :: "l"(p), "r"(v) : "memory"); }
__device__ __forceinline__ unsigned int ld_acquire(const unsigned int* p) { unsigned int v; asm volatile("ld.acquire.gpu.global.u32 %0, [%1];" : "=r"(v) : "l"(p) : "memory"); return v; }
__device__ __forceinline__ void spin_until(const unsigned int* p, unsigned int target) {
  #pragma unroll 1
  for (unsigned int i = 0; i < (1u << 22); i++) { if (ld_acquire(p) >= target) return; }
}
__device__ __forceinline__ float lds_f32(uint32_t a) { float v; asm volatile("ld.shared.f32 %0, [%1];" : "=f"(v) : "r"(a) : "memory"); return v; }
__device__ __forceinline__ float2 lds_f32x2(uint32_t a) { float2 v; asm volatile("ld.shared.v2.f32 {%0, %1}, [%2];" : "=f"(v.x), "=f"(v.y) : "r"(a) : "memory"); return v; }
__device__ __forceinline__ uint2 lds_u32x2(uint32_t a) { uint2 v; asm volatile("ld.shared.v2.u32 {%0, %1}, [%2];" : "=r"(v.x), "=r"(v.y) : "r"(a) : "memory"); return v; }
__device__ __forceinline__ uint32_t lds_u32(uint32_t a) { uint32_t v; asm volatile("ld.shared.u32 %0, [%1];" : "=r"(v) : "r"(a) : "memory"); return v; }
__device__ __forceinline__ void sts_u32(uint32_t a, uint32_t v) { asm volatile("st.shared.u32 [%0], %1;" :: "r"(a), "r"(v) : "memory"); }
__device__ __forceinline__ void sts_u32x2(uint32_t a, uint32_t x, uint32_t y) { asm volatile("st.shared.v2.u32 [%0], {%1, %2};" :: "r"(a), "r"(x), "r"(y) : "memory"); }
__device__ __forceinline__ void sts_f32(uint32_t a, float v) { asm volatile("st.shared.f32 [%0], %1;" :: "r"(a), "f"(v) : "memory"); }
__device__ __forceinline__ void sts_f32x2(uint32_t a, float x, float y) { asm volatile("st.shared.v2.f32 [%0], {%1, %2};" :: "r"(a), "f"(x), "f"(y) : "memory"); }
__device__ __forceinline__ void sts_f32x4(uint32_t a, float x, float y, float z, float w) { asm volatile("st.shared.v4.f32 [%0], {%1, %2, %3, %4};" :: "r"(a), "f"(x), "f"(y), "f"(z), "f"(w) : "memory"); }

__device__ __forceinline__ uint4 lds_u32x4(uint32_t a) { uint4 v; asm volatile("ld.shared.v4.u32 {%0, %1, %2, %3}, [%4];" : "=r"(v.x), "=r"(v.y), "=r"(v.z), "=r"(v.w) : "r"(a) : "memory"); return v; }
__device__ __forceinline__ void sts_u32x4(uint32_t a, uint32_t x, uint32_t y, uint32_t z, uint32_t w) { asm volatile("st.shared.v4.u32 [%0], {%1, %2, %3, %4};" :: "r"(a), "r"(x), "r"(y), "r"(z), "r"(w) : "memory"); }
__device__ __forceinline__ void st_tagged(float* p, float v) {
  const uint32_t b = __float_as_uint(v);
  asm volatile("st.relaxed.gpu.global.u32 [%0], %1;" :: "l"(p), "r"(b == 0u ? 0x80000000u : b) : "memory");
}
__device__ __forceinline__ void st_tagged4(float* p, float x, float y, float z, float w) {
  const uint32_t a = __float_as_uint(x), b = __float_as_uint(y), c = __float_as_uint(z), d = __float_as_uint(w);
  asm volatile("st.relaxed.gpu.global.v4.u32 [%0], {%1, %2, %3, %4};" :: "l"(p), "r"(a == 0u ? 0x80000000u : a), "r"(b == 0u ? 0x80000000u : b),
               "r"(c == 0u ? 0x80000000u : c), "r"(d == 0u ? 0x80000000u : d) : "memory");
}
__device__ __forceinline__ void st_relaxed2(void* p, uint32_t a, uint32_t b) { asm volatile("st.relaxed.gpu.global.v2.u32 [%0], {%1, %2};" :: "l"(p), "r"(a), "r"(b) : "memory"); }
__device__ __forceinline__ float4 ld_tagged4(const float* p) {
  float4 v; asm volatile("ld.relaxed.gpu.global.v4.f32 {%0, %1, %2, %3}, [%4];" : "=f"(v.x), "=f"(v.y), "=f"(v.z), "=f"(v.w) : "l"(p) : "memory"); return v;
}
__device__ __forceinline__ bool tagged4(const float4& v) {
  return __float_as_uint(v.x) != 0u && __float_as_uint(v.y) != 0u && __float_as_uint(v.z) != 0u && __float_as_uint(v.w) != 0u;
}
__device__ __forceinline__ void hint_arrive(uint32_t* p) { asm volatile("red.relaxed.gpu.global.add.u32 [%0], 1;" :: "l"(p) : "memory"); }
__device__ __forceinline__ void hint_wait(const uint32_t* p, uint32_t target) {
  uint32_t v = 0u;
  #pragma unroll 1
  for (unsigned int i = 0; i < (1u << 22) && v < target; i++) asm volatile("ld.relaxed.gpu.global.u32 %0, [%1];" : "=r"(v) : "l"(p) : "memory");
}
__device__ __forceinline__ void fence_proxy_async_global() { asm volatile("fence.proxy.async.global;" ::: "memory"); }

#define H_SPLIT 1
#define X_DLY 1200
#define W_DLY 1900
#define W_FIRST 2200
#define PRE_B 2
#define H_PREG 1
template <int J0, int J1>
__device__ __forceinline__ void load_parts(float2 (&pa)[J1 - J0][4], int t2) {
  #pragma unroll
  for (int j = J0; j < J1; j++)
    #pragma unroll
    for (int k = 0; k < 4; k++)
      asm volatile("ld.relaxed.gpu.global.v2.f32 {%0, %1}, [%2];" : "=f"(pa[j - J0][k].x), "=f"(pa[j - J0][k].y)
                   : "l"(g_modpart + k * 2 * T_D + (t2 >> 7) * T_D + j * 256 + (t2 & 127) * 2) : "memory");
}
template <int J0, int J1>
__device__ __forceinline__ void finish_parts(float2 (&pa)[J1 - J0][4], bool loaded, int t2, uint32_t tab) {
  #pragma unroll 1
  for (unsigned int spin = 0; spin < (1u << 22); spin++) {
    if (!loaded) load_parts<J0, J1>(pa, t2);
    loaded = false;
    bool ok = true;
    #pragma unroll
    for (int j = 0; j < J1 - J0; j++)
      #pragma unroll
      for (int k = 0; k < 4; k++) ok &= (__float_as_uint(pa[j][k].x) != 0u) & (__float_as_uint(pa[j][k].y) != 0u);
    if (__all_sync(0xffffffffu, ok)) break;
  }
  #pragma unroll
  for (int j = J0; j < J1; j++) {
    const float2* q = pa[j - J0];
    const uint32_t m = pack_bf16(((q[0].x + q[1].x) + q[2].x) + q[3].x, ((q[0].y + q[1].y) + q[2].y) + q[3].y);
    sts_u32(tab + (t2 >> 7) * 2048 + j * 512 + (t2 & 127) * 4, t2 >= 128 ? badd2(m, 0x3F803F80u) : m);
  }
}
__device__ __forceinline__ void head_phase(uint32_t scr, uint32_t xs, uint32_t b_x, uint32_t b_go, uint32_t b_head, int t2, uint32_t zero, const bf16* __restrict__ cvec, const bf16* __restrict__ w_mod) {
  const int lane = t2 & 31, w8 = t2 >> 5;
  const int cb = blockIdx.x & 31, ks = blockIdx.x >> 5;
  const bool early = (cb & 15) < 4 * H_SPLIT;
  const uint32_t ws = (xs - 32768 + (t2 >> 3) * 128 + (((t2 ^ (t2 >> 3)) & 7) << 4)) ^ zero;
  const float cv = __bfloat162float(cvec[ks * 256 + t2]);
  const bf16* wsrc = w_mod + (size_t)(ks * 256 + (t2 >> 3)) * (6 * T_D) + cb * 64 + (t2 & 7) * 8;
  if (early) {
    const uint64_t pol = policy_evict_first();
    #pragma unroll 2
    for (int i = 0; i < 8; i++)
      asm volatile("cp.async.cg.shared.global.L2::cache_hint [%0], [%1], 16, %2;" :: "r"(ws + i * 4096), "l"(wsrc + (size_t)i * 32 * 6 * T_D), "l"(pol) : "memory");
  }
  sts_f32(scr + t2 * 4, silu_bf(cv));
  named_bar_sync(6, 384);
  TL_MARK2(1, t2 == 0);
  uint4 xv[2][4];
  uint32_t mb2[2], ih[2], il[2];
  auto norm = [&](int j) {
    #pragma unroll
    for (int r = 0; r < 2; r++) {
      xv[r][j].x = ln_norm2b(xv[r][j].x, mb2[r], ih[r], il[r]); xv[r][j].y = ln_norm2b(xv[r][j].y, mb2[r], ih[r], il[r]);
      xv[r][j].z = ln_norm2b(xv[r][j].z, mb2[r], ih[r], il[r]); xv[r][j].w = ln_norm2b(xv[r][j].w, mb2[r], ih[r], il[r]);
    }
  };
  auto modulate = [&](int j) {
    const uint4 sa = lds_u32x4(scr + 8192 + j * 512 + lane * 16), c1 = lds_u32x4(scr + 8192 + 2048 + j * 512 + lane * 16);
    #pragma unroll
    for (int r = 0; r < 2; r++) {
      xv[r][j].x = badd2(bmul2(xv[r][j].x, c1.x), sa.x); xv[r][j].y = badd2(bmul2(xv[r][j].y, c1.y), sa.y);
      xv[r][j].z = badd2(bmul2(xv[r][j].z, c1.z), sa.z); xv[r][j].w = badd2(bmul2(xv[r][j].w, c1.w), sa.w);
    }
  };
  auto store = [&](int j) {
    #pragma unroll
    for (int r = 0; r < 2; r++) *reinterpret_cast<uint4*>(g_h + (size_t)(blockIdx.x * 16 + 2 * w8 + r) * T_D + j * 256 + lane * 8) = xv[r][j];
  };
  #pragma unroll 1
  for (int ph = 0; ph < 2; ph++) {
    if ((ph == 0) == early) {
      asm volatile("cp.async.wait_all;" ::: "memory");
      if (!early) mbar_wait(b_x + 168, 0);
      float acc[8];
      #pragma unroll
      for (int j = 0; j < 8; j++) acc[j] = 0.f;
      #pragma unroll
      for (int i = 0; i < 8; i++) fma8(acc, lds_f32(scr + ((t2 >> 3) + 32 * i) * 4), lds_u32x4(ws + i * 4096));
      #pragma unroll
      for (int j = 0; j < 4; j++) { const bool up = lane & 16; acc[j] = (up ? acc[4 + j] : acc[j]) + __shfl_xor_sync(0xffffffffu, up ? acc[j] : acc[4 + j], 16); }
      #pragma unroll
      for (int j = 0; j < 2; j++) { const bool up = lane & 8; acc[j] = (up ? acc[2 + j] : acc[j]) + __shfl_xor_sync(0xffffffffu, up ? acc[j] : acc[2 + j], 8); }
      sts_f32x2(scr + 1024 + w8 * 256 + (lane & 7) * 32 + (lane >> 3) * 8, acc[0], acc[1]);
      named_bar_sync(5, 256);
      if (t2 < 64) {
        float sum = 0.f;
        #pragma unroll
        for (int i = 0; i < 8; i++) sum += lds_f32(scr + 1024 + i * 256 + t2 * 4);
        st_tagged(g_modpart + ks * 2 * T_D + cb * 64 + t2, sum);
        TL_MARK2(early ? 2 : 6, t2 == 0);
      }
    } else {
      float2 pa[H_SPLIT][4];
      mbar_wait(b_x, 0);
      TL_MARK2(18, t2 == 0);
      if (H_PREG) load_parts<0, H_SPLIT>(pa, t2);
      #pragma unroll
      for (int r = 0; r < 2; r++)
        #pragma unroll
        for (int j = 0; j < 4; j++) xv[r][j] = lds_u32x4(xs + (2 * w8 + r) * 2048 + j * 512 + lane * 16);
  {
    float st[4] = {0.f, 0.f, 0.f, 0.f};
    #pragma unroll
    for (int r = 0; r < 2; r++)
      #pragma unroll
      for (int j = 0; j < 4; j++) {
        float v[8];
        unpack8(xv[r][j], v);
        st[2 * r] += ((v[0] + v[1]) + (v[2] + v[3])) + ((v[4] + v[5]) + (v[6] + v[7]));
        st[2 * r + 1] += fmaf(v[0], v[0], fmaf(v[1], v[1], fmaf(v[2], v[2], v[3] * v[3]))) + fmaf(v[4], v[4], fmaf(v[5], v[5], fmaf(v[6], v[6], v[7] * v[7])));
      }
    #pragma unroll
    for (int k = 0; k < 2; k++) { const bool up = lane & 16; st[k] = (up ? st[2 + k] : st[k]) + __shfl_xor_sync(0xffffffffu, up ? st[k] : st[2 + k], 16); }
    #pragma unroll
    for (int o = 8; o > 0; o >>= 1) { st[0] += __shfl_xor_sync(0xffffffffu, st[0], o); st[1] += __shfl_xor_sync(0xffffffffu, st[1], o); }
    const float mean = st[0] * (1.0f / T_D);
    const float inv = rcp_approx(rbf(sqrt_approx(rbf(rbf(fmaxf(fmaf(-mean, mean, st[1] * (1.0f / T_D)), 0.f)) + 1e-05f))));
    const uint32_t m = pack_bf16(mean, mean), h = pack_bf16(inv - rbf(inv), inv);
    #pragma unroll
    for (int r = 0; r < 2; r++) {
      mb2[r] = __shfl_sync(0xffffffffu, m, 16 * r);
      const uint32_t hr = __shfl_sync(0xffffffffu, h, 16 * r);
      ih[r] = __byte_perm(hr, hr, 0x3232); il[r] = __byte_perm(hr, hr, 0x1010);
    }
  }
      #pragma unroll
      for (int j = 0; j < H_SPLIT; j++) norm(j);
      TL_MARK2(5, t2 == 0);
      finish_parts<0, H_SPLIT>(pa, H_PREG, t2, scr + 8192);
      named_bar_sync(5, 256);
      TL_MARK2(7, t2 == 0);
      #pragma unroll
      for (int j = 0; j < H_SPLIT; j++) { modulate(j); store(j); }
      named_bar_arrive(9, 288);
    }
  }
  #pragma unroll
  for (int j = H_SPLIT; j < 4; j++) norm(j);
  float2 pb[4 - H_SPLIT][4];
  finish_parts<H_SPLIT, 4>(pb, false, t2, scr + 8192);
  named_bar_sync(5, 256);
  TL_MARK2(17, t2 == 0);
  #pragma unroll
  for (int j = H_SPLIT; j < 4; j++) modulate(j);
  __syncwarp();
  if (lane == 0) mbar_arrive(b_head + (xv[1][3].w & zero));
  mbar_wait(b_go, 0);
  #pragma unroll
  for (int j = H_SPLIT; j < 4; j++) store(j);
  named_bar_arrive(8, 288);
}

#define MOD_AT (b_empty + 8)
#define MOD_PF 0
#define MOD_SPLIT 16
__device__ __forceinline__ void mod_rest(uint32_t scr, uint32_t b_go, int t, const bf16* __restrict__ cvec, const bf16* __restrict__ w_mod, const bf16* __restrict__ w_r) {
  const int lane = t & 31;
  #pragma unroll 1
  for (int i = t; i < T_D / 2; i += 64) {
    const uint32_t c2 = *reinterpret_cast<const uint32_t*>(cvec + 2 * i);
    sts_u32(scr + i * 4, pack_bf16(silu_bf(bflo(c2)), silu_bf(bfhi(c2))));
  }
  named_bar_sync(11, 64);
  const bf16* wp = w_mod + (size_t)(2 * (t >> 2)) * (6 * T_D) + 2 * T_D + blockIdx.x * 32 + (t & 3) * 8;
  float acc[8];
  #pragma unroll
  for (int i = 0; i < 8; i++) acc[i] = 0.f;
  #pragma unroll 1
  for (int i = 0; i < 32; i += 2) {
    if (i == MOD_SPLIT) mbar_wait(b_go, 0);
    const uint4 w0 = ldg_nc_v4(wp), w1 = ldg_nc_v4(wp + 6 * T_D), w2 = ldg_nc_v4(wp + 32 * 6 * T_D), w3 = ldg_nc_v4(wp + 33 * 6 * T_D);
    wp += 64 * 6 * T_D;
    const uint32_t s0 = lds_u32(scr + (i * 16 + (t >> 2)) * 4), s1 = lds_u32(scr + (i * 16 + 16 + (t >> 2)) * 4);
    fma8(acc, bflo(s0), w0); fma8(acc, bfhi(s0), w1); fma8(acc, bflo(s1), w2); fma8(acc, bfhi(s1), w3);
  }
  #pragma unroll
  for (int j = 0; j < 4; j++) { const bool up = lane & 16; acc[j] = (up ? acc[4 + j] : acc[j]) + __shfl_xor_sync(0xffffffffu, up ? acc[j] : acc[4 + j], 16); }
  #pragma unroll
  for (int j = 0; j < 2; j++) { const bool up = lane & 8; acc[j] = (up ? acc[2 + j] : acc[j]) + __shfl_xor_sync(0xffffffffu, up ? acc[j] : acc[2 + j], 8); }
  { const bool up = lane & 4; acc[0] = (up ? acc[1] : acc[0]) + __shfl_xor_sync(0xffffffffu, up ? acc[0] : acc[1], 4); }
  if (t >= 32) sts_f32(scr + 2048 + lane * 4, acc[0]);
  named_bar_sync(11, 64);
  if (__shfl_sync(0xffffffffu, t, 0) < 32) {
    const int kind = blockIdx.x >> 5;
    float v = rbf(acc[0] + lds_f32(scr + 2048 + lane * 4));
    const int col = (blockIdx.x & 31) * 32 + (lane & 3) * 8 + (lane >> 2);
    uint8_t* dst = g_col + (col >> 7) * 1536;
    if (kind == 2) v = rbf(1.0f + v);
    float vw = v * __bfloat162float(w_r[col]);
    if (kind == 2) {
      const int c = col & 127, i = (c & ~15) + ((c >> 1) & 3) * 4 + ((c >> 3) & 1) * 2 + (c & 1);
      reinterpret_cast<bf16*>(dst)[i] = __float2bfloat16_rn(vw);
      reinterpret_cast<bf16*>(dst)[128 + i] = __float2bfloat16_rn(vw - rbf(vw));
    }
    reinterpret_cast<bf16*>(dst + 512 + (kind & 1) * 512 + (kind >> 1) * 256)[col & 127] = __float2bfloat16_rn(v);
    #pragma unroll
    for (int o = 16; o > 0; o >>= 1) vw += __shfl_xor_sync(0xffffffffu, vw, o);
    if (lane == 0 && (kind == 1 || kind == 2)) g_scal[95 - blockIdx.x] = vw;
  }
  #pragma unroll 1
  for (int i = blockIdx.x * 64 + t; i < (int)(sizeof(g_mail) / 16); i += 128 * 64) reinterpret_cast<uint4*>(&g_mail)[i] = make_uint4(0u, 0u, 0u, 0u);
  named_bar_sync(11, 64);
  if (t == 0) red_release_add(&g_hcnt[0], 1u);
}

#define HPOL_A pol
#define HPOL_B pol_normal()
#define HMAP_A &tmOl
#define HMAP_B &tmWo
constexpr int AT_NBLK = T_SEQ / 128;
constexpr float AT_HEAD = 7.0f;
#define WO_LATE 12
constexpr int QP_STAG = 3;
constexpr int AT_SPLIT = 28, AT_PIN = 8, PINB = 4;
constexpr int AT_NFULL = 124;
constexpr int AT_PREG = 40, AT_CREG = 232;
constexpr uint32_t AT_SQ = 5 * 32768;
constexpr float AT_C = 0.08838834764831845f * 1.4426950408889634f;
constexpr float AT_RAW_LO = -16.0f, AT_RAW_HI = 24.0f;
constexpr float AT_RAW_SUM = 281474976710656.0f, AT_RAW_MIN = 9.094947017729282e-13f;
constexpr uint32_t AT_SBAR = AT_SQ + 65536 + 256;
constexpr uint32_t AT_SMEM = AT_SQ + 65536 + 3072;

__device__ __forceinline__ uint32_t ring_slot(uint32_t t) { return t - 5u * ((t * 205u) >> 10); }
__device__ __forceinline__ uint32_t qp_pos(uint32_t j, uint32_t it) { return 4u * it + (j & 3u) + ((j & 3u) == 3u ? it : 0u); }
__device__ __forceinline__ uint32_t ring_par(uint32_t t) { return ((t * 205u) >> 10) & 1u; }
__device__ __forceinline__ void softmax_rowmax(const float (&s)[64], float& mx0, float& mx1) {
  float a0 = fmaxf(s[0], s[1]), a1 = fmaxf(s[4], s[5]), a2 = fmaxf(s[8], s[9]), a3 = fmaxf(s[12], s[13]);
  float b0 = fmaxf(s[2], s[3]), b1 = fmaxf(s[6], s[7]), b2 = fmaxf(s[10], s[11]), b3 = fmaxf(s[14], s[15]);
  #pragma unroll
  for (int j = 4; j < 16; j += 4) {
    a0 = fmaxf(a0, fmaxf(s[4 * j + 0], s[4 * j + 1]));  b0 = fmaxf(b0, fmaxf(s[4 * j + 2], s[4 * j + 3]));
    a1 = fmaxf(a1, fmaxf(s[4 * j + 4], s[4 * j + 5]));  b1 = fmaxf(b1, fmaxf(s[4 * j + 6], s[4 * j + 7]));
    a2 = fmaxf(a2, fmaxf(s[4 * j + 8], s[4 * j + 9]));  b2 = fmaxf(b2, fmaxf(s[4 * j + 10], s[4 * j + 11]));
    a3 = fmaxf(a3, fmaxf(s[4 * j + 12], s[4 * j + 13])); b3 = fmaxf(b3, fmaxf(s[4 * j + 14], s[4 * j + 15]));
  }
  mx0 = fmaxf(fmaxf(a0, a1), fmaxf(a2, a3));
  mx1 = fmaxf(fmaxf(b0, b1), fmaxf(b2, b3));
  mx0 = fmaxf(mx0, __shfl_xor_sync(0xffffffffu, mx0, 1));
  mx1 = fmaxf(mx1, __shfl_xor_sync(0xffffffffu, mx1, 1));
  mx0 = fmaxf(mx0, __shfl_xor_sync(0xffffffffu, mx0, 2));
  mx1 = fmaxf(mx1, __shfl_xor_sync(0xffffffffu, mx1, 2));
}
__device__ __forceinline__ void softmax_sub(float (&s)[64], float mc0, float mc1) {
  #pragma unroll
  for (int j = 0; j < 16; j++) { s[4 * j] -= mc0; s[4 * j + 1] -= mc0; s[4 * j + 2] -= mc1; s[4 * j + 3] -= mc1; }
}
template <int LO, int HI>
__device__ __forceinline__ void softmax_exp(float (&s)[64]) {
  #pragma unroll
  for (int i = LO; i < HI; i++) s[i] = ex2_approx(s[i]);
}
__device__ __forceinline__ bool softmax_mode(const float (&s)[64], float& mc0, float& mc1) {
  softmax_rowmax(s, mc0, mc1);
  const bool raw = __all_sync(0xffffffffu, mc0 >= AT_RAW_LO && mc0 <= AT_RAW_HI && mc1 >= AT_RAW_LO && mc1 <= AT_RAW_HI);
  mc0 += AT_HEAD; mc1 += AT_HEAD;
  return raw;
}
__device__ __forceinline__ void rowsum_p(const uint32_t (&p)[32], uint32_t& t0, uint32_t& t1) {
  uint32_t a[16];
  #pragma unroll
  for (int i = 0; i < 8; i++) { a[2 * i] = badd2(p[4 * i], p[4 * i + 2]); a[2 * i + 1] = badd2(p[4 * i + 1], p[4 * i + 3]); }
  #pragma unroll
  for (int i = 0; i < 4; i++) { a[2 * i] = badd2(a[4 * i], a[4 * i + 2]); a[2 * i + 1] = badd2(a[4 * i + 1], a[4 * i + 3]); }
  t0 = badd2(badd2(a[0], a[2]), badd2(a[4], a[6]));
  t1 = badd2(badd2(a[1], a[3]), badd2(a[5], a[7]));
}
__device__ __forceinline__ void add_rowsum(const uint32_t (&p)[32], float& l0, float& l1) {
  uint32_t t0, t1;
  rowsum_p(p, t0, t1);
  l0 += bflo(t0) + bfhi(t0); l1 += bflo(t1) + bfhi(t1);
}
__device__ __forceinline__ void pack_p(uint32_t (&p)[32], const float (&s)[64]) {
  #pragma unroll
  for (int i = 0; i < 32; i++) p[i] = pack_bf16(s[2 * i], s[2 * i + 1]);
}
__device__ __noinline__ void attn_rows_exact(uint32_t sq, uint32_t so, int hsel, const bf16* __restrict__ kh, const bf16* __restrict__ vh) {
  const int warp = (threadIdx.x >> 5) & 3, lane = threadIdx.x & 31;
  const size_t hofs = (size_t)((blockIdx.x < 128 ? blockIdx.x >> 4 : 15) * 2 + hsel) * T_SEQ * T_DH;
  kh += hofs; vh += hofs;
  #pragma unroll 1
  for (int r = 16 * warp; r < 16 * warp + 16; r++) {
    const uint32_t ad = (lane >> 4) * 16384 + r * 128 + ((((lane & 15) >> 1) ^ (r & 7)) << 4) + (lane & 1) * 8;
    uint2 qv; asm volatile("ld.shared.v2.u32 {%0, %1}, [%2];" : "=r"(qv.x), "=r"(qv.y) : "r"(sq + ad) : "memory");
    const float q0 = bflo(qv.x), q1 = bfhi(qv.x), q2 = bflo(qv.y), q3 = bfhi(qv.y);
    float m = -INFINITY, l = 0.f, o0 = 0.f, o1 = 0.f, o2 = 0.f, o3 = 0.f;
    #pragma unroll 1
    for (int key = 0; key < T_SEQ; key++) {
      const uint2 kv = *reinterpret_cast<const uint2*>(kh + (size_t)key * T_DH + lane * 4);
      const uint2 vv = *reinterpret_cast<const uint2*>(vh + (size_t)key * T_DH + lane * 4);
      float sc = (q0 * bflo(kv.x) + q1 * bfhi(kv.x)) + (q2 * bflo(kv.y) + q3 * bfhi(kv.y));
      #pragma unroll
      for (int o = 16; o > 0; o >>= 1) sc += __shfl_xor_sync(0xffffffffu, sc, o);
      const float mn = fmaxf(m, sc);
      const float al = (m == mn) ? 1.0f : ex2_approx(m - mn), p = rbf(ex2_approx(sc - mn));
      m = mn;
      l = fmaf(l, al, p);
      o0 = fmaf(o0, al, p * bflo(vv.x)); o1 = fmaf(o1, al, p * bfhi(vv.x));
      o2 = fmaf(o2, al, p * bflo(vv.y)); o3 = fmaf(o3, al, p * bfhi(vv.y));
    }
    const float inv = rcp_approx(l);
    asm volatile("st.shared.v2.u32 [%0], {%1, %2};" :: "r"(so + ad), "r"(pack_bf16(o0 * inv, o1 * inv)), "r"(pack_bf16(o2 * inv, o3 * inv)) : "memory");
  }
}
__device__ __forceinline__ void issue_qk(float (&s)[64], const uint32_t (&q)[32], uint32_t k_lo) {
  wgmma_fence();
  wgmma_m64n128k16_rs<0>(s, q[0], q[1], q[2], q[3], k_lo, 0);
  wgmma_m64n128k16_rs<2>(s, q[4], q[5], q[6], q[7], k_lo, 1);
  wgmma_m64n128k16_rs<4>(s, q[8], q[9], q[10], q[11], k_lo, 1);
  wgmma_m64n128k16_rs<6>(s, q[12], q[13], q[14], q[15], k_lo, 1);
  wgmma_m64n128k16_rs<1024>(s, q[16], q[17], q[18], q[19], k_lo, 1);
  wgmma_m64n128k16_rs<1026>(s, q[20], q[21], q[22], q[23], k_lo, 1);
  wgmma_m64n128k16_rs<1028>(s, q[24], q[25], q[26], q[27], k_lo, 1);
  wgmma_m64n128k16_rs<1030>(s, q[28], q[29], q[30], q[31], k_lo, 1);
  wgmma_commit();
}
__device__ __forceinline__ void issue_pv(float (&o)[64], const uint32_t (&p)[32], uint32_t v_lo, int accumulate) {
  wgmma_fence();
  wgmma_m64n128k16_rs_tb<0>(o, p[0], p[1], p[2], p[3], v_lo, accumulate);
  wgmma_m64n128k16_rs_tb<128>(o, p[4], p[5], p[6], p[7], v_lo, 1);
  wgmma_m64n128k16_rs_tb<256>(o, p[8], p[9], p[10], p[11], v_lo, 1);
  wgmma_m64n128k16_rs_tb<384>(o, p[12], p[13], p[14], p[15], v_lo, 1);
  wgmma_m64n128k16_rs_tb<512>(o, p[16], p[17], p[18], p[19], v_lo, 1);
  wgmma_m64n128k16_rs_tb<640>(o, p[20], p[21], p[22], p[23], v_lo, 1);
  wgmma_m64n128k16_rs_tb<768>(o, p[24], p[25], p[26], p[27], v_lo, 1);
  wgmma_m64n128k16_rs_tb<896>(o, p[28], p[29], p[30], p[31], v_lo, 1);
  wgmma_commit();
}
__device__ __forceinline__ void block_end(uint32_t zero, uint32_t bar) {
  #pragma unroll 1
  for (uint32_t i = 0; i < zero; i++) mbar_arrive(bar);
}
__device__ __forceinline__ void rescale_o(float (&o)[64], float al0, float al1) {
  #pragma unroll
  for (int j = 0; j < 16; j++) { o[4 * j] *= al0; o[4 * j + 1] *= al0; o[4 * j + 2] *= al1; o[4 * j + 3] *= al1; }
}

__device__ __forceinline__ void stage_o(const float (&o)[64], float i0, float i1, uint32_t dst, int lane) {
  #pragma unroll
  for (int J = 0; J < 16; J += 2)
    stmatrix_x4(dst + (J >> 3) * 16384 + ((((J & 7) + (lane >> 4)) ^ (lane & 7)) << 4),
                pack_bf16(o[4 * J + 0] * i0, o[4 * J + 1] * i0), pack_bf16(o[4 * J + 2] * i1, o[4 * J + 3] * i1),
                pack_bf16(o[4 * J + 4] * i0, o[4 * J + 5] * i0), pack_bf16(o[4 * J + 6] * i1, o[4 * J + 7] * i1));
}
__device__ __forceinline__ bool finish_l(float& l0, float& l1) {
  l0 += __shfl_xor_sync(0xffffffffu, l0, 1); l1 += __shfl_xor_sync(0xffffffffu, l1, 1);
  l0 += __shfl_xor_sync(0xffffffffu, l0, 2); l1 += __shfl_xor_sync(0xffffffffu, l1, 2);
  const bool redo = __any_sync(0xffffffffu, !(l0 <= AT_RAW_SUM && l1 <= AT_RAW_SUM && l0 >= AT_RAW_MIN && l1 >= AT_RAW_MIN));
  l0 = rcp_approx(l0); l1 = rcp_approx(l1);
  return redo;
}
template <int J0>
__device__ __forceinline__ void stage_q(const float (&acc)[128], float c, uint32_t dst, int lane) {
  #pragma unroll
  for (int J = J0; J < J0 + 16; J += 2)
    stmatrix_x4(dst + (J >> 3) * 16384 + ((((J & 7) + (lane >> 4)) ^ (lane & 7)) << 4),
                pack_bf16(acc[4 * J + 0] * c, acc[4 * J + 1] * c), pack_bf16(acc[4 * J + 2] * c, acc[4 * J + 3] * c),
                pack_bf16(acc[4 * J + 4] * c, acc[4 * J + 5] * c), pack_bf16(acc[4 * J + 6] * c, acc[4 * J + 7] * c));
}
__device__ __forceinline__ void store_o(const CUtensorMap* tmO, uint32_t src, int head, int row) {
  tma_store_2d(tmO, src, head * T_DH, row);
  tma_store_2d(tmO, src + 16384, head * T_DH + 64, row);
  bulk_commit();
}
__device__ __forceinline__ void mma_bf16(float (&d)[4], uint32_t a0, uint32_t a1, uint32_t a2, uint32_t a3, uint32_t b0, uint32_t b1) {
  asm volatile("mma.sync.aligned.m16n8k16.row.col.f32.bf16.bf16.f32 {%0, %1, %2, %3}, {%4, %5, %6, %7}, {%8, %9}, {%0, %1, %2, %3};"
               : "+f"(d[0]), "+f"(d[1]), "+f"(d[2]), "+f"(d[3]) : "r"(a0), "r"(a1), "r"(a2), "r"(a3), "r"(b0), "r"(b1));
}
struct GemvSel { uint32_t lo0, hi0, lo1, hi1; };
__device__ __forceinline__ GemvSel gemv_sel(int lane) {
  const uint32_t lo = (lane & 8) ? 0x1044u : 0x4410u, hi = (lane & 8) ? 0x3244u : 0x4432u;
  GemvSel s; s.lo0 = (lane & 16) ? 0x4444u : lo; s.hi0 = (lane & 16) ? 0x4444u : hi; s.lo1 = (lane & 16) ? lo : 0x4444u; s.hi1 = (lane & 16) ? hi : 0x4444u;
  return s;
}
#define GEMV_B0(j, h, s) __byte_perm((j) < 2 ? (h).x : (h).y, 0u, ((j) & 1) ? (s).hi0 : (s).lo0)
#define GEMV_B1(j, h, s) __byte_perm((j) < 2 ? (h).x : (h).y, 0u, ((j) & 1) ? (s).hi1 : (s).lo1)
__device__ __forceinline__ float4 gemv_out(const float (&d)[4], int lane) {
  const bool tk = lane & 1;
  const float r0 = __shfl_xor_sync(0xffffffffu, tk ? d[0] : d[1], 1), r1 = __shfl_xor_sync(0xffffffffu, tk ? d[2] : d[3], 1);
  return tk ? make_float4(r0, d[1], r1, d[3]) : make_float4(d[0], r0, d[2], r1);
}
#define OG_NG 8
#define HOIST 1
#define PUT_N 2
#define H_STAG 2
#define NOZERO 1
#define PVPIN 0
#define QKPIN 0
#define ALIGN 1
#define AL_P 60
#define AL_SLEEP 1200
#define AL_MAX 800
#define AL_ADD 0
#define X_PF 0
#define POLL_NS 200
#define KV3D 1
#define W3D 1
#define OG_PRE 10
#define OG_PRE2 12
#define SERP 1
#define OG_JOBS 7
#define OG_GRP 6
#define LD_FIRST 3
#define LD_STAG (OG_GRP / 2)
constexpr int OG_ST = 5, OG_NKB = T_DQKV / 64 - OG_PRE, OG_MOE = T_F / 32;
__device__ __forceinline__ int pre_kb(int i) { return (i >> 1) * 4 + (i & 1); }
__device__ __forceinline__ int own_kb(int i) { return i < OG_PRE2 ? pre_kb(i) + 2 : i < 64 - OG_PRE2 ? i + OG_PRE2 : pre_kb(i - (64 - OG_PRE2 - OG_PRE)); }
constexpr int OG_POS = 8;
constexpr uint32_t OG_STAGE = 32768;
constexpr uint32_t OG_SCOL = AT_SBAR + 512;
constexpr uint32_t OG_SMISC = AT_SBAR + 2048;
constexpr int OG_XPOS = OG_POS + OG_NKB;
constexpr uint32_t OG_SWD = AT_SQ, OG_PSLOT = AT_SQ;
constexpr uint32_t OG_SWD1 = (OG_XPOS % OG_ST) * OG_STAGE;
constexpr uint32_t OG_XSLOT = AT_SQ + 32768;
constexpr uint32_t OG_OSLOT = ((OG_XPOS + 1) % OG_ST) * OG_STAGE;
constexpr uint32_t OG_SH2 = ((OG_XPOS + 2) % OG_ST) * OG_STAGE;
constexpr uint32_t OG_SRED = ((OG_XPOS + 3) % OG_ST) * OG_STAGE;
constexpr uint32_t OG_SSTAT = OG_SRED + 16384;
constexpr uint32_t OG_SGU = OG_SRED + 8192;
constexpr uint32_t OG_SFIN = OG_SGU + 256;
#define OGM 2
#define OG_MT(b) ((((b) >> OGM) & 15) ^ (SERP && ((b) & 64) ? 15 : 0))
#define OG_NT(b) (((b) & ((1 << OGM) - 1)) + (((b) >> (4 + OGM)) << OGM))
#define TAIL_SETUP \
  const uint32_t bar_full = sbase + AT_SBAR, bar_empty = bar_full + 40; \
  const uint32_t bar_wd = bar_full + 168, bar_col = bar_full + 176, bar_out = bar_full + 184, bar_end = bar_full + 192; \
  const uint32_t bar_key = bar_full + 200, bar_h2 = bar_full + 208, bar_sel = bar_full + 216; \
  const int mt = OG_MT(blockIdx.x), nt = OG_NT(blockIdx.x); \
  const int m0 = mt * 128, n0 = nt * 128; \
  const bool has_moe = (int)blockIdx.x < OG_MOE; \
  (void)bar_empty; (void)bar_wd; (void)bar_col; (void)bar_out; (void)bar_end; (void)bar_key; (void)bar_h2; (void)bar_sel; (void)m0; (void)n0; (void)has_moe;

__device__ __forceinline__ void tail_producer(uint32_t sbase, uint32_t ph, uint64_t pol, const CUtensorMap* tmA, const CUtensorMap* tmB, const CUtensorMap* tmX) {
  TAIL_SETUP
  uint32_t stage = OG_POS % OG_ST;
  int kb = 0;
  #pragma unroll 1
  for (int seg = 0; seg < 2; seg++) {
    mbar_wait(bar_full + 264 + 80 * seg, 0);
    fence_proxy_async_global();
    const int end = seg == 0 ? 32 - OG_PRE2 : has_moe ? OG_NKB : 64 - OG_PRE2;
    #pragma unroll 1
    for (; kb < end; kb++) {
      const uint32_t fb = bar_full + 8 * stage, sa = sbase + stage * OG_STAGE;
      const int k0 = own_kb(kb) * 64;
      mbar_wait(bar_empty + 8 * stage, ph);
      mbar_expect_tx(fb, OG_STAGE);
      tma_load_3d_hint(sa + 16384, tmB, k0, 2 * nt, fb, pol);
      tma_load_2d_hint(sa, tmA, k0, m0, fb, pol);
      if (++stage == OG_ST) { stage = 0; ph ^= 1; }
    }
  }
  if (has_moe) {
    mbar_wait(bar_empty + 8 * (OG_XPOS % OG_ST), ph);
    mbar_expect_tx(bar_wd, OG_STAGE);
    tma_load_3d_hint(sbase + OG_SWD1, tmX, blockIdx.x * 32, 8, bar_wd, pol);
  }
}

__device__ __forceinline__ uint32_t out2(uint32_t x1, uint32_t mb2, uint32_t ih, uint32_t il, uint32_t c1, uint32_t sb, uint32_t gb) {
  const uint32_t h2 = badd2(bmul2(ln_norm2b(x1, mb2, ih, il), c1), sb);
  return badd2(x1, bmul2(gb, bfma2(h2, 0u, h2)));
}
#define OGTIME gtime()
#define PRE_N 1
#define PRE_PACE 150
#define X_PACE 200
#define WD_LATE 0
#define WD_PACE 300
__device__ __forceinline__ void tail_exchange(uint32_t sbase, const CUtensorMap* tmOut, const bf16* __restrict__ w_down, const bf16* __restrict__ w_r, const bf16* __restrict__ x, bf16* __restrict__ out) {
    TAIL_SETUP
    const int lane = threadIdx.x & 31, wi = __shfl_sync(0xffffffffu, threadIdx.x >> 5, 0);
    if (wi == 3) {
      if (blockIdx.x < AT_NFULL) {
        uint32_t a, b;
        asm volatile("ld.relaxed.gpu.global.u32 %0, [%1];" : "=r"(a) : "l"(g_smid + 32 + blockIdx.x - lane) : "memory");
        b = __shfl_down_sync(0xffffffffu, a, 1);
        unsigned int* tm = g_tmax + blockIdx.x - min((int)blockIdx.x, __ffs(__ballot_sync(0xffffffffu, b >= a)) - 1);
        mbar_wait(bar_full + 312, 0);
        if (lane == 0) {
          asm volatile("mov.u32 %0, %%globaltimer_lo;" : "=r"(a));
          asm volatile("red.relaxed.gpu.global.max.u32 [%0], %1;" :: "l"(tm), "r"(a) : "memory");
          __nanosleep(AL_SLEEP);
          asm volatile("ld.relaxed.gpu.global.u32 %0, [%1];" : "=r"(b) : "l"(tm) : "memory");
          b -= a;
          sts_u32(sbase + OG_SMISC + 32, (b < AL_MAX ? b * 13 / 8 : 0u) + AL_ADD);
          mbar_arrive(bar_full + 320);
        }
        named_bar_sync(15, 32);
      }
      mbar_wait(bar_full + 344, 0);
      float a = g_scal[lane], b = g_scal[32 + lane];
      #pragma unroll
      for (int i = 0; i < 3; i++) {
        const uint4 v = *reinterpret_cast<const uint4*>(g_col + nt * 1536 + i * 512 + lane * 16);
        sts_u32x4(sbase + OG_SCOL + i * 512 + lane * 16, v.x, v.y, v.z, v.w);
      }
      #pragma unroll
      for (int o = 16; o > 0; o >>= 1) { a += __shfl_xor_sync(0xffffffffu, a, o); b += __shfl_xor_sync(0xffffffffu, b, o); }
      if (lane == 0) sts_f32x2(sbase + OG_SMISC, a, b);
      const uint64_t pol = policy_evict_first();
      #pragma unroll 1
      for (int r = lane >> 4; r < 128; r += 4) {
        __nanosleep(X_PACE);
        #pragma unroll
        for (int j = 0; j < 4; j += 2)
          asm volatile("cp.async.cg.shared.global.L2::cache_hint [%0], [%1], 16, %2;" :: "r"(sbase + OG_XSLOT + (lane & 8) * 2048 + (r + j) * 128 + (((lane ^ (r + j)) & 7) << 4)),
                       "l"(x + (size_t)(m0 + r + j) * T_D + n0 + (lane & 15) * 8), "l"(pol) : "memory");
      }
      asm volatile("cp.async.wait_all;" ::: "memory");
      __syncwarp();
      if (lane == 0) mbar_arrive(bar_col);
    } else if (wi == 2) {
      if (elect_one()) {
        const uint32_t b_free = bar_full + (blockIdx.x < AT_NFULL ? 80 : 160);
        mbar_wait(b_free, 0); mbar_wait(b_free, 1);
        #pragma unroll 1
        for (unsigned int i = 0; i < (1u << 20) && ld_acquire(&g_hcnt[32 * (1 + (blockIdx.x >> 3)) + 4 + ((blockIdx.x >> 1) & 3)]) == 0u; i++) __nanosleep(POLL_NS);
        TL_MARK2(23, true);
        fence_proxy_async_global();
        TL_MARK2(4, true);
        mbar_expect_tx(bar_full + 272, 32768);
        #pragma unroll 1
        for (int i = 0; i < PRE_N; i++) {
          bulk_load_hint(sbase + OG_PSLOT + i * (32768 / PRE_N), g_pre + blockIdx.x * 2048 + i * (2048 / PRE_N), 32768 / PRE_N,
                         bar_full + 272, policy_evict_first());
          if (PRE_N > 1) __nanosleep(PRE_PACE);
        }
      }
      named_bar_sync(14, 32);
      if (has_moe) {
        mbar_wait(bar_full + 96, 1); mbar_wait(bar_full + 304, 0);
        const uint64_t pol = policy_evict_first();
        #pragma unroll 1
        for (int r = 0; r < 32; r++) {
          __nanosleep(WD_PACE);
          #pragma unroll
          for (int j = 0; j < 2; j++)
            asm volatile("cp.async.cg.shared.global.L2::cache_hint [%0], [%1], 16, %2;" :: "r"(sbase + OG_SWD + (4 * j + (lane >> 3)) * 4096 + r * 128 + (((lane ^ r) & 7) << 4)),
                         "l"((const uint8_t*)w_down + (size_t)blockIdx.x * 65536 + r * 2048 + j * 512 + lane * 16), "l"(pol) : "memory");
        }
        asm volatile("cp.async.wait_all;" ::: "memory");
        __syncwarp();
        if (lane == 0) mbar_arrive(bar_wd);
      }
    }
    const uint4 wrv = ldg_nc_v4(w_r + threadIdx.x * 8);
    mbar_wait(bar_end, 0);
    TL_MARK2(22, lane == 0);
    if (wi == 0) {
      uint32_t k1 = 0u, k2 = 0u;
      #pragma unroll 1
      for (unsigned int spin = 0; spin < (1u << 22) && __any_sync(0xffffffffu, k1 == 0u); spin++) asm volatile("ld.relaxed.gpu.global.u32 %0, [%1];" : "=r"(k1) : "l"(g_key + lane) : "memory");
      TL_MARK2(28, lane == 0);
      warp_top2(k1, k2);
      if (lane == 0) {
        const uint32_t r1 = 0xffffu - (k1 & 0xffffu), r2 = 0xffffu - (k2 & 0xffffu);
        sts_u32x4(sbase + OG_SMISC + 64, r1, r2, (r1 >> 7) * 2, (r2 >> 7) * 2 + ((r1 >> 7) == (r2 >> 7)));
        mbar_arrive(bar_sel);
      }
    } else if (wi < 3) {
          mbar_wait(bar_key, 0);
          const uint4 kk = lds_u32x4(sbase + OG_SSTAT + 1024 + lane * 16);
          uint32_t k1 = max(kk.x, kk.y), k2 = min(kk.x, kk.y);
          k2 = max(max(k2, min(kk.z, kk.w)), min(k1, max(kk.z, kk.w))); k1 = max(k1, max(kk.z, kk.w));
          warp_top2(k1, k2);
          if (wi == 1) {
            if (lane == 0 && nt == (mt & 7)) st_relaxed2(g_key + mt * 2, k1, k2);
            TL_MARK2(27, lane == 0);
          } else {
            const uint32_t r = (~((lane & 16) ? k2 : k1)) & 127u, ch = lane & 15;
            const uint2 st = lds_u32x2(sbase + OG_SSTAT + r * 8);
            const uint4 xc = lds_u32x4(sbase + OG_XSLOT + (ch >> 3) * 16384 + r * 128 + (((ch ^ r) & 7) << 4));
            const uint4 c1 = lds_u32x4(sbase + OG_SCOL + 768 + ch * 16), sh = lds_u32x4(sbase + OG_SCOL + 1024 + ch * 16);
            const float inr = __uint_as_float(st.y);
            float* dst = reinterpret_cast<float*>(g_cand + (mt * 2 + (lane >> 4)) * 256 + nt * 16 + ch);
            st_tagged4(dst + 512, __uint_as_float(ln_mod2(xc.x, st.x, inr, c1.x, sh.x)), __uint_as_float(ln_mod2(xc.y, st.x, inr, c1.y, sh.y)),
                       __uint_as_float(ln_mod2(xc.z, st.x, inr, c1.z, sh.z)), __uint_as_float(ln_mod2(xc.w, st.x, inr, c1.w, sh.w)));
            st_tagged4(dst, __uint_as_float(xc.x), __uint_as_float(xc.y), __uint_as_float(xc.z), __uint_as_float(xc.w));
          }
    }
    mbar_wait(bar_sel, 0);
    const uint4 sel = lds_u32x4(sbase + OG_SMISC + 64);
    const int sel0 = (int)sel.x, sel1 = (int)sel.y;
    {
      const float* src0 = reinterpret_cast<const float*>(g_cand + sel.z * 256 + 128 + threadIdx.x);
      const float* src1 = reinterpret_cast<const float*>(g_cand + sel.w * 256 + 128 + threadIdx.x);
      float4 h0, h1;
      #pragma unroll 1
      for (unsigned int spin = 0; spin < (1u << 20); spin++) { h0 = ld_tagged4(src0); h1 = ld_tagged4(src1); if (__all_sync(0xffffffffu, tagged4(h0) & tagged4(h1))) break; }
      sts_f32x4(sbase + OG_SH2 + threadIdx.x * 16, h0.x, h0.y, h0.z, h0.w);
      sts_f32x4(sbase + OG_SH2 + 2048 + threadIdx.x * 16, h1.x, h1.y, h1.z, h1.w);
      __syncwarp();
      if (lane == 0) mbar_arrive(bar_h2);
      TL_MARK2(12, lane == 0);
      if (blockIdx.x >> 6) h0 = h1;
      float v[8], wr[8];
      unpack8(make_uint4(__float_as_uint(h0.x), __float_as_uint(h0.y), __float_as_uint(h0.z), __float_as_uint(h0.w)), v); unpack8(wrv, wr);
      float r = 0.f;
      #pragma unroll
      for (int i = 0; i < 8; i++) r = fmaf(v[i], wr[i], r);
      #pragma unroll
      for (int o = 16; o > 0; o >>= 1) r += __shfl_xor_sync(0xffffffffu, r, o);
      if (lane == 0) sts_f32(sbase + OG_SMISC + 192 + wi * 4, r);
    }
    mbar_wait(bar_out, 0);
    if ((sel0 >> 7) == mt || (sel1 >> 7) == mt) {
      #pragma unroll 2
      for (int i = 0; i < 16; i++) {
        const int r = i * 8 + (threadIdx.x >> 4), ch = threadIdx.x & 15;
        if (m0 + r != sel0 && m0 + r != sel1)
          *reinterpret_cast<uint4*>(out + (size_t)(m0 + r) * T_D + n0 + ch * 8) =
              lds_u32x4(sbase + OG_OSLOT + (ch >> 3) * 16384 + r * 128 + (((ch & 7) ^ (r & 7)) << 4));
      }
    } else if (threadIdx.x == 0) {
      tma_store_2d(tmOut, sbase + OG_OSLOT, n0, m0);
      tma_store_2d(tmOut, sbase + OG_OSLOT + 16384, n0 + 64, m0);
      bulk_commit();
    }
    if (blockIdx.x == 0 && threadIdx.x < 68) *reinterpret_cast<uint4*>(g_hcnt + 32 * (threadIdx.x >> 2) + 4 * (threadIdx.x & 3)) = make_uint4(0u, 0u, 0u, 0u);
    if (threadIdx.x < 64) g_modpart[blockIdx.x * 64 + threadIdx.x] = 0.f;
    if (ALIGN && threadIdx.x == 64) g_tmax[blockIdx.x] = 0u;
    {
      const int tk = blockIdx.x >> 6, c0 = (blockIdx.x & 63) * 16;
      const uint32_t gb2 = *reinterpret_cast<const uint32_t*>(g_col + (c0 >> 7) * 1536 + 512 + 768 + ((c0 & 127) + (threadIdx.x & 14)) * 2);
      const uint32_t* xp = reinterpret_cast<const uint32_t*>(g_cand + (tk ? sel.w : sel.z) * 256) + ((c0 + (threadIdx.x & 14)) >> 1);
      uint32_t x2 = 0u;
      #pragma unroll 1
      for (unsigned int spin = 0; spin < (1u << 20) && __any_sync(0xffffffffu, x2 == 0u); spin++) asm volatile("ld.relaxed.gpu.global.u32 %0, [%1];" : "=r"(x2) : "l"(xp) : "memory");
      const float* src = g_ypart + (size_t)((threadIdx.x >> 2) * 2 + tk) * T_D + c0 + (threadIdx.x & 3) * 4;
      const bool four = threadIdx.x < (OG_MOE - 96) * 4;
      if (threadIdx.x == 0) hint_wait(CNT_Y, (uint32_t)OG_MOE);
      named_bar_sync(10, 128);
      float4 p0, p1, p2, p3;
      #pragma unroll 1
      for (unsigned int spin = 0; spin < (1u << 20); spin++) {
        p0 = ld_tagged4(src); p1 = ld_tagged4(src + 64 * T_D); p2 = ld_tagged4(src + 128 * T_D); p3 = ld_tagged4(four ? src + 192 * T_D : src);
        if (__all_sync(0xffffffffu, tagged4(p0) & tagged4(p1) & tagged4(p2) & tagged4(p3))) break;
      }
      if (four) { p2.x += p3.x; p2.y += p3.y; p2.z += p3.z; p2.w += p3.w; }
      p0.x = (p0.x + p1.x) + p2.x; p0.y = (p0.y + p1.y) + p2.y; p0.z = (p0.z + p1.z) + p2.z; p0.w = (p0.w + p1.w) + p2.w;
      #pragma unroll
      for (int o = 4; o <= 16; o <<= 1) {
        p0.x += __shfl_xor_sync(0xffffffffu, p0.x, o); p0.y += __shfl_xor_sync(0xffffffffu, p0.y, o);
        p0.z += __shfl_xor_sync(0xffffffffu, p0.z, o); p0.w += __shfl_xor_sync(0xffffffffu, p0.w, o);
      }
      if (lane < 4) sts_f32x4(sbase + OG_SFIN + (threadIdx.x >> 5) * 64 + lane * 16, p0.x, p0.y, p0.z, p0.w);
      named_bar_sync(10, 128);
      TL_MARK2(21, threadIdx.x == 0);
      if (threadIdx.x < 16) {
        const uint32_t ya = sbase + OG_SFIN + threadIdx.x * 4, rp = sbase + OG_SMISC + 192;
        float y = (lds_f32(ya) + lds_f32(ya + 64)) + (lds_f32(ya + 128) + lds_f32(ya + 192));
        const float r = rbf((lds_f32(rp) + lds_f32(rp + 4)) + (lds_f32(rp + 8) + lds_f32(rp + 12)));
        const float rs = rbf(sigmoid_f(r));
        const uint32_t h2p = lds_u32(sbase + OG_SH2 + tk * 2048 + (c0 + (threadIdx.x & 14)) * 2);
        const float fh = (lane & 1) ? bfhi(h2p) : bflo(h2p);
        y = rbf(y);
        y = rbf(y * rs);
        const float upd = rbf(rbf(fh * 0.0f) + y);
        out[(size_t)(tk ? sel1 : sel0) * T_D + c0 + threadIdx.x] =
            __float2bfloat16_rn(((lane & 1) ? bfhi(x2) : bflo(x2)) + rbf(((lane & 1) ? bfhi(gb2) : bflo(gb2)) * rbf(fh + upd)));
      }
      if (threadIdx.x == 0) bulk_wait_read<0>();
    }
    TL_END(4, threadIdx.x == 0);
}

__device__ __forceinline__ void load_pre(uint4* pre, uint32_t sbase, uint32_t buf, int t2) {
  mbar_wait(sbase + AT_SBAR + 272, 0);
  #pragma unroll
  for (int i = 0; i < 8; i++) pre[i] = lds_u32x4(sbase + buf + i * 4096 + t2 * 16);
}
__device__ __forceinline__ void tail_consumer(uint32_t sbase, const uint4 (&pre)[8], int cwg, const bf16* __restrict__ w_gate, const bf16* __restrict__ w_up) {
    TAIL_SETUP
    const int tid = threadIdx.x & 127, t2 = threadIdx.x - 128;
    const int warp = tid >> 5, lane = tid & 31, w8 = t2 >> 5;
    const uint32_t dbase = (sbase & 0x3FFFFu) >> 4;
    const uint32_t a_base = dbase + ((cwg * 8192) >> 4) + (1u << 16);
    const uint32_t b_base = dbase + (16384 >> 4) + (512u << 16);
    TL_MARK2(25, threadIdx.x == 128);
    const uint64_t pol = policy_evict_first();
    const bf16* pw = ((lane & 16) ? w_up : w_gate) + (size_t)(w8 * 128 + (lane & 3) * 4) * T_F + (has_moe ? blockIdx.x : 0) * 32 + ((lane >> 2) & 3) * 8;
    uint4 wv[32];
    float acc[64];
    #pragma unroll
    for (int i = 0; i < 8; i++) {
      acc[8 * i] = bflo(pre[i].x); acc[8 * i + 1] = bfhi(pre[i].x); acc[8 * i + 2] = bflo(pre[i].y); acc[8 * i + 3] = bfhi(pre[i].y);
      acc[8 * i + 4] = bflo(pre[i].z); acc[8 * i + 5] = bfhi(pre[i].z); acc[8 * i + 6] = bflo(pre[i].w); acc[8 * i + 7] = bfhi(pre[i].w);
    }
    if (blockIdx.x < AT_NFULL) {
      const uint32_t c0 = clock_lo();
      mbar_wait(bar_full + 320, 0);
      const uint32_t d = lds_u32(sbase + OG_SMISC + 32);
      while (clock_lo() - c0 < d) {}
    }
    {
      uint32_t stage = OG_POS % OG_ST, phase = (OG_POS / OG_ST) & 1, prev = 12;
      int kb = 0;
      #pragma unroll
      for (int g = 0; g <= OG_NG; g++) {
        const int end = g == OG_NG ? (has_moe ? OG_NKB : 64 - OG_PRE2) : LD_FIRST + g * OG_GRP + LD_STAG * cwg;
        #pragma unroll 1
        do {
          mbar_wait(bar_full + 8 * stage, phase);
          const uint32_t a_lo = a_base + stage * (OG_STAGE >> 4), b_lo = b_base + stage * (OG_STAGE >> 4);
          wgmma_fence();
          wgmma_m64n128k16_ss_tb<0, 0>(acc, a_lo, b_lo, 1);
          wgmma_m64n128k16_ss_tb<2, 128>(acc, a_lo, b_lo, 1);
          wgmma_m64n128k16_ss_tb<4, 256>(acc, a_lo, b_lo, 1);
          wgmma_m64n128k16_ss_tb<6, 384>(acc, a_lo, b_lo, 1);
          wgmma_commit();
          wgmma_wait<1>();
          if (tid == 0) mbar_arrive(bar_empty + 8 * prev);
          prev = stage;
          if (++stage == OG_ST) { stage = 0; phase ^= 1; }
        } while (++kb < end);
        #pragma unroll
        for (int j = 4 * g; j < 4 * g + 4 && j < 32; j++) wv[j] = ldg_stream_v4(pw + (size_t)(16 * (j >> 2) + (j & 3)) * T_F, pol);
      }
    }
    mbar_wait(bar_col, 0);
    if (__builtin_expect(!has_moe, 0)) {
      load_pre(wv, sbase, AT_SQ, t2);
    }
    wgmma_wait<0>();
    fence_regs(acc);
    if (__builtin_expect(!has_moe, 0)) {
      #pragma unroll
      for (int i = 0; i < 8; i++) {
        acc[8 * i] += bflo(wv[i].x); acc[8 * i + 1] += bfhi(wv[i].x); acc[8 * i + 2] += bflo(wv[i].y); acc[8 * i + 3] += bfhi(wv[i].y);
        acc[8 * i + 4] += bflo(wv[i].z); acc[8 * i + 5] += bfhi(wv[i].z); acc[8 * i + 6] += bflo(wv[i].w); acc[8 * i + 7] += bfhi(wv[i].w);
      }
    }
    if (tid == 0) mbar_arrive(bar_end);
    TL_MARK2(9, lane == 0);
    const int q2 = 2 * (lane & 3);
    const uint32_t frag = (64 * cwg + 16 * warp + (lane & 7) + 8 * ((lane >> 3) & 1)) * 128;
    const int fsw = lane & 7, fhi = lane >> 4;
    {
      float dl[4] = {0.f, 0.f, 0.f, 0.f}, da[4] = {0.f, 0.f, 0.f, 0.f}, db[4] = {0.f, 0.f, 0.f, 0.f};
      const uint32_t tb = sbase + OG_SCOL + (lane & 8) * 32 + (lane & 3) * 8, g = lane >> 2;
      const uint32_t msk = (g == 1 || g == 2) ? 0xffffffffu : 0u, one = g == 0 ? 0x3F803F80u : 0u;
      #pragma unroll
      for (int J = 0; J < 16; J += 2) {
        const uint32_t ad = sbase + OG_XSLOT + (J >> 3) * 16384 + frag + ((((J & 7) + fhi) ^ fsw) << 4);
        uint32_t xr[4];
        ldmatrix_x4(ad, xr[0], xr[1], xr[2], xr[3]);
        const uint2 cw = lds_u32x2(tb + J * 16);
        #pragma unroll
        for (int h = 0; h < 2; h++) {
          const uint32_t ga = lds_u32(sbase + OG_SCOL + 512 + (8 * (J + h) + q2) * 2);
          xr[2 * h] = badd2(xr[2 * h], bmul2(ga, pack_bf16(acc[4 * (J + h)], acc[4 * (J + h) + 1])));
          xr[2 * h + 1] = badd2(xr[2 * h + 1], bmul2(ga, pack_bf16(acc[4 * (J + h) + 2], acc[4 * (J + h) + 3])));
        }
        stmatrix_x4(ad, xr[0], xr[1], xr[2], xr[3]);
        mma_bf16(dl, xr[0], xr[1], xr[2], xr[3], (cw.x & msk) | one, (cw.y & msk) | one);
        mma_bf16(da, xr[0], xr[1], xr[2], xr[3], xr[0], xr[2]);
        mma_bf16(db, xr[0], xr[1], xr[2], xr[3], xr[1], xr[3]);
      }
      {
        const int dsrc = (lane & ~3) + (g >> 1);
        const float qa = __shfl_sync(0xffffffffu, (g & 1) ? da[1] : da[0], dsrc), qb = __shfl_sync(0xffffffffu, (g & 1) ? db[3] : db[2], dsrc);
        const float e0 = __shfl_xor_sync(0xffffffffu, (lane & 1) ? dl[0] : dl[2], 1), e1 = __shfl_xor_sync(0xffffffffu, dl[3], 1);
        if ((lane & 3) < 2) {
          const bool hi = lane & 1;
          st_tagged4(reinterpret_cast<float*>(g_part1 + ((mt * 8 + w8) * 8 + nt) * 16 + g + (hi ? 8 : 0)),
                     hi ? e0 : dl[0], hi ? qb : qa, hi ? e1 + dl[2] : dl[1] + e0, 1.0f);
        }
      }
    }
    TL_MARK2(10, lane == 0);
    uint4 wd[16];
    if (has_moe) mbar_wait(bar_wd, 0);
    #pragma unroll
    for (int i = 0; i < 16; i++) wd[i] = lds_u32x4(sbase + (cwg ? OG_SWD1 : OG_SWD) + warp * 8192 + (i >> 3) * 4096 + (i & 6) * 512 + (i & 1) * 128 + (lane & 3) * 256 + (((lane >> 2) ^ (2 * (lane & 3) + (i & 1))) << 4));
    {
      const float* src = reinterpret_cast<const float*>(g_part1 + ((mt * 8 + w8) * 8 + (lane & 1) * 4) * 16 + (lane >> 1));
      float4 v, v1, v2, v3;
      #pragma unroll 1
      for (unsigned int spin = 0; spin < (1u << 22); spin++) {
        v = ld_tagged4(src); v1 = ld_tagged4(src + 64); v2 = ld_tagged4(src + 128); v3 = ld_tagged4(src + 192);
        if (__all_sync(0xffffffffu, tagged4(v) & tagged4(v1) & tagged4(v2) & tagged4(v3))) break;
        __nanosleep(100);
      }
      __syncwarp();
      TL_MARK2(26, lane == 0);
      v.x = (v.x + v1.x) + (v2.x + v3.x); v.y = (v.y + v1.y) + (v2.y + v3.y); v.z = (v.z + v1.z) + (v2.z + v3.z);
      v.x += __shfl_xor_sync(0xffffffffu, v.x, 1); v.y += __shfl_xor_sync(0xffffffffu, v.y, 1); v.z += __shfl_xor_sync(0xffffffffu, v.z, 1);
      const float mean = v.x * (1.0f / T_D);
      const float var = fmaxf(fmaf(-mean, mean, v.y * (1.0f / T_D)), 0.f);
      const uint32_t mb2 = pack_bf16(mean, mean);
      const float inv = rcp_approx(rbf(sqrt_approx(rbf(rbf(var) + 1e-05f))));
      {
        const float2 sc = lds_f32x2(sbase + OG_SMISC);
        const uint32_t key = rank_key(rbf(fmaf(fmaf(-bflo(mb2), sc.x, v.z), inv, sc.y)), m0 + 16 * w8 + (lane >> 1));
        mbar_wait(bar_end, 0);
        if (lane & 1) sts_u32(sbase + OG_SSTAT + 1024 + (16 * w8 + (lane >> 1)) * 4, key);
        else sts_u32x2(sbase + OG_SSTAT + (16 * w8 + (lane >> 1)) * 8, mb2, __float_as_uint(inv));
        __syncwarp();
        if (lane == 0) mbar_arrive(bar_key);
      }
      const uint32_t ih = pack_bf16(inv, inv), il = pack_bf16(inv - bflo(ih), inv - bflo(ih));
      const uint32_t mba = __shfl_sync(0xffffffffu, mb2, 2 * (lane >> 2)), mbb = __shfl_sync(0xffffffffu, mb2, 2 * (lane >> 2) + 16);
      const uint32_t iha = __shfl_sync(0xffffffffu, ih, 2 * (lane >> 2)), ihb = __shfl_sync(0xffffffffu, ih, 2 * (lane >> 2) + 16);
      const uint32_t ila = __shfl_sync(0xffffffffu, il, 2 * (lane >> 2)), ilb = __shfl_sync(0xffffffffu, il, 2 * (lane >> 2) + 16);
      #pragma unroll 2
      for (int J = 0; J < 16; J += 2) {
        const uint32_t off = (J >> 3) * 16384 + frag + ((((J & 7) + fhi) ^ fsw) << 4);
        uint32_t xr[4];
        ldmatrix_x4(sbase + OG_XSLOT + off, xr[0], xr[1], xr[2], xr[3]);
        #pragma unroll
        for (int h = 0; h < 2; h++) {
          const uint32_t ca = sbase + OG_SCOL + 512 + (8 * (J + h) + q2) * 2;
          const uint32_t c1 = lds_u32(ca + 256), sh = lds_u32(ca + 512), gb = lds_u32(ca + 768);
          xr[2 * h] = out2(xr[2 * h], mba, iha, ila, c1, sh, gb);
          xr[2 * h + 1] = out2(xr[2 * h + 1], mbb, ihb, ilb, c1, sh, gb);
        }
        stmatrix_x4(sbase + OG_OSLOT + off, xr[0], xr[1], xr[2], xr[3]);
      }
      fence_proxy_async();
      __syncwarp();
      if (lane == 0) mbar_arrive(bar_out);
      TL_MARK2(24, lane == 0);
    }
    if (has_moe) mbar_wait(bar_h2, 0);
    TL_MARK2(13, lane == 0);
    if (has_moe) {
      const GemvSel sel = gemv_sel(lane);
      {
        float d[4][4];
        #pragma unroll
        for (int c = 0; c < 4; c++) { d[c][0] = 0.f; d[c][1] = 0.f; d[c][2] = 0.f; d[c][3] = 0.f; }
        #pragma unroll
        for (int st = 0; st < 8; st++) {
          const uint2 hb = lds_u32x2(sbase + OG_SH2 + ((lane >> 2) & 1) * 2048 + (w8 * 128 + st * 16 + (lane & 3) * 4) * 2);
          #pragma unroll
          for (int j = 0; j < 4; j++) mma_bf16(d[j], wv[4 * st + j].x, wv[4 * st + j].y, wv[4 * st + j].z, wv[4 * st + j].w, GEMV_B0(j, hb, sel), GEMV_B1(j, hb, sel));
        }
        #pragma unroll
        for (int e = 0; e < 4; e++) d[0][e] = (d[0][e] + d[1][e]) + (d[2][e] + d[3][e]);
        const float4 r = gemv_out(d[0], lane);
        sts_f32x4(sbase + OG_SRED + w8 * 512 + (((lane >> 4) * 2 + (lane & 1)) * 32 + ((lane >> 2) & 3) * 8 + (lane & 2) * 2) * 4, r.x, r.y, r.z, r.w);
      }
      named_bar_sync(9, 256);
      if (t2 < 64) {
        float gp[8], up[8];
        #pragma unroll
        for (int w = 0; w < 8; w++) { gp[w] = lds_f32(sbase + OG_SRED + w * 512 + t2 * 4); up[w] = lds_f32(sbase + OG_SRED + w * 512 + 256 + t2 * 4); }
        const float gs = ((gp[0] + gp[1]) + (gp[2] + gp[3])) + ((gp[4] + gp[5]) + (gp[6] + gp[7]));
        const float us = ((up[0] + up[1]) + (up[2] + up[3])) + ((up[4] + up[5]) + (up[6] + up[7]));
        asm volatile("st.shared.u16 [%0], %1;" :: "r"(sbase + OG_SGU + ((t2 & ~15) + ((t2 >> 1) & 3) * 4 + ((t2 >> 3) & 1) * 2 + (t2 & 1)) * 2), "h"((uint16_t)pack_bf16(silu_bf(rbf(gs)) * rbf(us), 0.f)) : "memory");
      }
      named_bar_sync(9, 256);
      TL_MARK2(20, threadIdx.x == 128);
      float d[4][4];
      #pragma unroll
      for (int c = 0; c < 4; c++) { d[c][0] = 0.f; d[c][1] = 0.f; d[c][2] = 0.f; d[c][3] = 0.f; }
      #pragma unroll
      for (int st = 0; st < 2; st++) {
        const uint2 g = lds_u32x2(sbase + OG_SGU + ((lane >> 2) & 1) * 64 + st * 32 + (lane & 3) * 8);
        #pragma unroll
        for (int j = 0; j < 4; j++) {
          const uint32_t b0 = GEMV_B0(j, g, sel), b1 = GEMV_B1(j, g, sel);
          mma_bf16(d[j & 1], wd[4 * st + j].x, wd[4 * st + j].y, wd[4 * st + j].z, wd[4 * st + j].w, b0, b1);
          mma_bf16(d[2 + (j & 1)], wd[8 + 4 * st + j].x, wd[8 + 4 * st + j].y, wd[8 + 4 * st + j].z, wd[8 + 4 * st + j].w, b0, b1);
        }
      }
      #pragma unroll
      for (int e = 0; e < 4; e++) { d[0][e] += d[1][e]; d[2][e] += d[3][e]; }
      const float4 y0 = gemv_out(d[0], lane), y1 = gemv_out(d[2], lane);
      float* yp = g_ypart + (size_t)(blockIdx.x * 2 + (lane & 1)) * T_D + w8 * 128 + (lane >> 2) * 8 + (lane & 2) * 2;
      st_tagged4(yp, y0.x, y0.y, y0.z, y0.w);
      st_tagged4(yp + 64, y1.x, y1.y, y1.z, y1.w);
      named_bar_sync(9, 256);
      if (t2 == 0) hint_arrive(CNT_Y);
    }
    TL_MARK2(14, threadIdx.x == 128);
    TL_CLK(4, 1, threadIdx.x == 128);
}

#define OG_JOBS2 (16 - OG_JOBS)
__device__ __forceinline__ int help_njobs() { return blockIdx.x < 128 ? OG_JOBS : OG_JOBS2; }
__device__ __forceinline__ int help_job(int i) { return (i < OG_JOBS ? 16 * i + (blockIdx.x >> 7) * 2 : 112 + (i - OG_JOBS) * 2) + (blockIdx.x & 3) * 4; }
__device__ __noinline__ void store_warp(uint32_t sbase, const CUtensorMap* tmO, int item0, int n_items) {
  if (elect_one()) {
    const uint32_t bars = sbase + AT_SBAR, b_q0 = bars + 80, b_ob = bars + 96, b_ordy = bars + 104, b_acq = bars + 264;
    const unsigned int* cnt = &g_hcnt[32 * (1 + OG_MT(blockIdx.x)) + 2];
    #pragma unroll 1
    for (int q = 0; q < 4 * n_items; q++) {
      const int item = item0 + (q >> 2) * 128, h = (q >> 1) & 1, w = q & 1;
      const bool last = (q >> 2) == n_items - 1;
      if (q == 4 * n_items - 4) { mbar_wait(bars + 288, 0); red_release_add(&g_hcnt[1], 1u); }
      mbar_wait(b_ordy + 8 * (q & 3), q >> 2);
      store_o(tmO, (h ? (last ? sbase + AT_SQ + 32768 : sbase + 2 * 32768) : sbase + AT_SQ) + w * 8192, (item >> 4) * 2 + h, (item & 15) * 128 + w * 64);
      if (w) {
        bulk_wait_read<0>();
        mbar_arrive(h ? b_ob : b_q0);
        bulk_wait<0>();
        fence_proxy_async_global();
        asm volatile("fence.acq_rel.gpu;" ::: "memory");
        hint_arrive(&g_hcnt[32 * (1 + (item & 15)) + 2 + (item >> 7)]);
        if (!h && item < 128) hint_arrive(&g_hcnt[2]);
        if (blockIdx.x < 128 && q == (n_items == 2 ? 5 : 3)) { spin_until(cnt, 16u); mbar_arrive(b_acq); }
      }
    }
    if (n_items == 1) {
      #pragma unroll 1
      for (int i = 0; i < help_njobs(); i++) {
        mbar_wait(b_acq + 16, i & 1);
        TL_MARK2(23, i == OG_JOBS - 1);
        red_release_add(&g_hcnt[32 * (1 + (help_job(i) >> 3)) + 4 + ((help_job(i) >> 1) & 3)], 1u);
        TL_MARK2(4, i == OG_JOBS - 1);
        if (i == PRE_X - 1) { spin_until(&g_hcnt[1], 132u); mbar_arrive(b_acq + 32); }
      }
    }
    if (blockIdx.x < 128) { spin_until(&g_hcnt[0], 128u); spin_until(cnt + 1, 16u); mbar_arrive(b_acq + 80); }
  }
}

__global__ void __launch_bounds__(384, 1)
fused_kernel(const __grid_constant__ CUtensorMap tmH, const __grid_constant__ CUtensorMap tmW, const __grid_constant__ CUtensorMap tmK,
            const __grid_constant__ CUtensorMap tmV, const __grid_constant__ CUtensorMap tmO, const __grid_constant__ CUtensorMap tmOl, const __grid_constant__ CUtensorMap tmWo,
            const __grid_constant__ CUtensorMap tmX, const __grid_constant__ CUtensorMap tmOut, const __grid_constant__ CUtensorMap tmM, uint32_t zero,
            const uint8_t* __restrict__ pf_wo, const bf16* __restrict__ kc, const bf16* __restrict__ vc,
            const bf16* __restrict__ x, const bf16* __restrict__ cvec, const bf16* __restrict__ w_mod, const bf16* __restrict__ w_r,
            const bf16* __restrict__ w_gate, const bf16* __restrict__ w_up, const bf16* __restrict__ w_down, bf16* __restrict__ out)
{
  extern __shared__ __align__(1024) uint8_t smem_raw[];
  const uint32_t sbase = smem_u32(smem_raw);
  const uint32_t bars = sbase + AT_SBAR;
  const uint32_t b_full = bars, b_empty = bars + 40;
  const uint32_t b_q0 = bars + 80, b_q1 = bars + 88;
  const uint32_t b_ob = bars + 96;
  const uint32_t b_ordy = bars + 104;
  const uint32_t b_pin = bars + 136;
  const uint32_t b_head = bars + 144;
  const uint32_t b_go = bars + 152;
  const uint32_t b_x = bars + 160;
  const int wg = __shfl_sync(0xffffffffu, threadIdx.x >> 7, 0);
  const bool single = blockIdx.x >= AT_NFULL;
  const int item0 = __shfl_sync(0xffffffffu, blockIdx.x < 128 ? (int)blockIdx.x : (int)blockIdx.x + 124, 0), n_items = __shfl_sync(0xffffffffu, single ? 1 : 2, 0);
  TL_START(3);
  if (threadIdx.x == 0) {
    if (sbase & 1023u) __trap();
    for (int i = 0; i < 5; i++) { mbar_init(b_full + 8 * i, 1); mbar_init(b_empty + 8 * i, 2); }
    mbar_init(b_q0, 1); mbar_init(b_q1, 8); mbar_init(b_ob, 1);
    for (int i = 0; i < 4; i++) mbar_init(b_ordy + 8 * i, 4);
    mbar_init(b_pin, 1); mbar_init(b_head, blockIdx.x < 128 ? 8 : 1); mbar_init(b_go, 1); mbar_init(b_x, 1);
    mbar_init(bars + 168, 2); mbar_init(bars + 176, 1); mbar_init(bars + 184, 8); mbar_init(bars + 192, 2);
    mbar_init(bars + 200, 8); mbar_init(bars + 208, 4); mbar_init(bars + 216, 1); mbar_init(bars + 264, 1); mbar_init(bars + 272, 1); mbar_init(bars + 280, 8); mbar_init(bars + 288, 1); mbar_init(bars + 296, 1); mbar_init(bars + 304, 8); mbar_init(bars + 312, 1); mbar_init(bars + 320, 1); mbar_init(bars + 328, 1); mbar_init(bars + 344, 1);
    fence_mbar_init();
  }

  if (wg == 0) {
    reg_dealloc<AT_PREG>();
    if (threadIdx.x < 32) { __syncwarp(); named_bar_arrive(6, 384); }
    if (threadIdx.x >= 64) {
      named_bar_sync(6, 384);
      if (blockIdx.x < 128) {
        named_bar_sync(threadIdx.x >= 96 ? 8 : 9, 288);
        if ((threadIdx.x & 31) == 0) red_release_add(&g_hcnt[32 * (1 + (blockIdx.x >> 3)) + (threadIdx.x >= 96)], 1u);
        TL_MARK2(11, threadIdx.x == 64);
      }
      if (blockIdx.x < 128) {
        mbar_wait(MOD_AT, 0);
        mod_rest(sbase + OG_SCOL, b_q1, threadIdx.x - 64, cvec, w_mod, w_r);
      }
    } else if (threadIdx.x >= 32) {
      named_bar_sync(6, 384);
      store_warp(sbase, &tmO, item0, n_items);
      __syncwarp();
    } else {
     if (elect_one()) {
      const uint64_t pol = policy_evict_first();
      if (blockIdx.x < 128) {
        mbar_expect_tx(b_x, 32768);
        if (X_DLY) { const uint32_t c0 = clock_lo(); while (clock_lo() - c0 < X_DLY) {} }
        bulk_load_hint(sbase + 4 * 32768, x + (size_t)blockIdx.x * 16 * T_D, 32768, b_x, pol);
      }
      prefetch_tmap(&tmW); prefetch_tmap(&tmM); prefetch_tmap(&tmH); prefetch_tmap(&tmWo); prefetch_tmap(&tmOl);
      {
        const uint32_t c0 = clock_lo();
        while (clock_lo() - c0 < W_DLY) {}
        if (blockIdx.x < 128 && (blockIdx.x & 15) >= 4 * H_SPLIT) {
          mbar_expect_tx(bars + 328, 32768);
          tma_load_2d_hint(sbase + 3 * 32768, &tmM, (blockIdx.x & 31) * 64, (blockIdx.x >> 5) * 256, bars + 328, pol);
        }
        while (clock_lo() - c0 < W_DLY + W_FIRST) {}
      }
      uint32_t slot = 0, ph = 1;
      if (ALIGN) { uint32_t sm; asm volatile("mov.u32 %0, %%smid;" : "=r"(sm)); g_smid[32 + blockIdx.x] = sm; }
      #pragma unroll 1
      for (int it = 0; it < n_items; it++) {
        const int item = item0 + it * 128, hp = item >> 4, qt = item & 15;
        const bool first = it == 0;
        #pragma unroll 1
        for (int j = 0; j < T_D / 64; j++) {
          const uint32_t sl = ring_slot(qp_pos(j, it)), fb = b_full + 8 * sl;
          mbar_wait(b_empty + 8 * sl, ring_par(qp_pos(j, it)) ^ ((j >> 2) & 1) ^ 1);
          if (first && j == 3) mbar_wait(b_head, 0);
          mbar_expect_tx(fb, 49152);
          tma_load_3d_hint(sbase + sl * 32768, &tmW, j * 64, hp * 4, fb, pol);
          if (first && j < PRE_B) {
            if (j == PRE_B - 1) {
              spin_until(&g_hcnt[32 * (1 + qt)], 8u);
              TL_MARK2(16, true);
              fence_proxy_async_global();
              #pragma unroll 1
              for (int i = 0; i < PRE_B; i++) tma_load_2d(sbase + AT_SQ + i * 16384, &tmH, i * 64, qt * 128, b_full + 8 * i);
              mbar_arrive(b_go);
            }
          } else {
            if (first && j == 4 * H_SPLIT) { spin_until(&g_hcnt[32 * (1 + qt) + 1], 8u); fence_proxy_async_global(); }
            if (!first && (j == 0 || j == 2)) mbar_wait(j ? b_q1 : b_q0, 0);
            tma_load_2d_hint(sbase + AT_SQ + (j & 3) * 16384, &tmH, j * 64, qt * 128, fb, first ? pol_normal() : pol);
          }
        }
        #pragma unroll 1
        for (int j = 0; j < 4 * AT_NBLK; j++) {
          const bool isv = (j > 0 && !(j & 1)) || j == 4 * AT_NBLK - 1;
          const int row = hp * 2 * T_SEQ + (isv ? (j - 1) >> 1 : (j + 1) >> 1) * 128;
          const uint32_t fb = b_full + 8 * slot;
          mbar_wait(b_empty + 8 * slot, ph);
          if (!first && j == 3) mbar_wait(b_ob, 0);
          if (j == 4 && it == n_items - 1) mbar_arrive(bars + 288);
          if (ALIGN && j == AL_P && it == 1) mbar_arrive(bars + 312);
          mbar_expect_tx(fb, 32768);
          tma_load_3d_hint(sbase + slot * 32768, isv ? &tmV : &tmK, row, 0, fb, pol);
          if (it == 1 && isv && j >= 2 * WO_LATE && j < 2 * WO_LATE + 32 && blockIdx.x < OG_NKB)
            l2_prefetch_bulk(pf_wo + (size_t)own_kb(blockIdx.x) * 131072 + ((j >> 1) - WO_LATE) * 8192, 8192);
          if (++slot == 5) { slot = 0; ph ^= 1; }
        }
      }
      if (__builtin_expect(single, 0)) {
        spin_until(&g_hcnt[2], 128u);
        fence_proxy_async_global();
        const int nj = OG_JOBS * OG_PRE + (help_njobs() - OG_JOBS) * OG_PRE2;
        int ji = 0, job = help_job(0), kk = 0;
        #pragma unroll 1
        for (int j = 0; j < nj; j++) {
          const uint32_t sl = ring_slot(qp_pos(j, 1)), fb = b_full + 8 * sl;
          mbar_wait(b_empty + 8 * sl, ring_par(qp_pos(j, 1)) ^ ((j >> 2) & 1) ^ 1);
          mbar_expect_tx(fb, 49152);
          tma_load_3d_hint(sbase + sl * 32768, &tmWo, pre_kb(kk) * 64, OG_NT(job) * 2, fb, HPOL_B);
          tma_load_3d_hint(sbase + sl * 32768 + 16384, &tmWo, pre_kb(kk) * 64, OG_NT(job) * 2 + 2, fb, HPOL_B);
          if (j == 0 || j == 2) mbar_wait(j ? b_ob : b_q0, 0);
          tma_load_2d_hint(sbase + AT_SQ + (j & 3) * 16384, &tmOl, pre_kb(kk) * 64, OG_MT(job) * 128, fb, HPOL_A);
          if (++kk == (ji < OG_JOBS ? OG_PRE : OG_PRE2)) { kk = 0; job = help_job(++ji); }
        }
      }
      if (blockIdx.x < 128) {
        if (single) mbar_wait(b_x, 1);
        tail_producer(sbase, 0, pol, &tmOl, &tmWo, &tmX);
      }
     }
    }
    named_bar_sync(12 + (threadIdx.x >> 5), 32);
    if (blockIdx.x < 128) tail_exchange(sbase, &tmOut, w_down, w_r, x, out);
  } else {
    if (blockIdx.x < 128) head_phase(sbase + AT_SQ + 49152, sbase + 4 * 32768, b_x, b_go, b_head, threadIdx.x - 128, zero, cvec, w_mod);
    else { named_bar_sync(6, 384); if (threadIdx.x == 128) mbar_arrive(b_head); }
    TL_MARK2(0, threadIdx.x == 128);
    reg_alloc<AT_CREG>();
    const int cwg = wg - 1;
    const int tid = threadIdx.x & 127;
    const int warp = tid >> 5, lane = tid & 31;
    const uint32_t dbase = (sbase & 0x3FFFFu) >> 4;
    const uint32_t k_base = dbase + (1u << 16);
    const uint32_t v_base = dbase + (1024u << 16);
    const uint32_t w_base = dbase + (512u << 16);
    const uint32_t q_lo = dbase + ((AT_SQ + cwg * 8192) >> 4) + (1u << 16);
    const uint32_t frag = cwg * 8192 + (16 * warp + (lane & 7) + 8 * ((lane >> 3) & 1)) * 128;
    if (cwg == 1) named_bar_arrive(1, 256);
    bool raw = false;
    uint4 pre[8];
    #pragma unroll 1
    for (int it = 0; it < n_items; it++) {
      const bool more = it + 1 < n_items;
      constexpr int nkb = T_D / 64;
      const int ta = __shfl_sync(0xffffffffu, 4 * it, 0);
      float acc[128];
      {
        FS(2 * it, 0);
        #pragma unroll
        for (int i = 0; i < 128; i++) asm volatile("" : "=f"(acc[i]));
        {
          const uint32_t slot = ring_slot(ta), b_lo = w_base + slot * 2048;
          mbar_wait(b_full + 8 * slot, ring_par(ta));
          wgmma_fence();
          wgmma_m64n256k16_ss_tb<0, 0>(acc, q_lo, b_lo, 0);
          wgmma_m64n256k16_ss_tb<2, 128>(acc, q_lo, b_lo, 1);
          wgmma_m64n256k16_ss_tb<4, 256>(acc, q_lo, b_lo, 1);
          wgmma_m64n256k16_ss_tb<6, 384>(acc, q_lo, b_lo, 1);
          wgmma_commit();
        }
        #pragma unroll 1
        for (int j = NOZERO; j < nkb; j++) {
          const uint32_t slot = ring_slot(qp_pos(j, ta >> 2));
          mbar_wait(b_full + 8 * slot, ring_par(qp_pos(j, ta >> 2)) ^ ((j >> 2) & 1));
          if (QP_STAG > 0 && cwg == 1 && j == nkb - QP_STAG) named_bar_sync(7, 256);
          const uint32_t a_lo = q_lo + (j & 3) * 1024, b_lo = w_base + slot * 2048;
          wgmma_fence();
          wgmma_m64n256k16_ss_tb<0, 0>(acc, a_lo, b_lo, 1);
          wgmma_m64n256k16_ss_tb<2, 128>(acc, a_lo, b_lo, 1);
          wgmma_m64n256k16_ss_tb<4, 256>(acc, a_lo, b_lo, 1);
          wgmma_m64n256k16_ss_tb<6, 384>(acc, a_lo, b_lo, 1);
          wgmma_commit();
          if (QP_STAG > 0 && cwg == 0 && j == nkb - 1) named_bar_arrive(7, 256);
          if (j > 0) {
            wgmma_wait<1>();
            if (tid == 0) mbar_arrive(b_empty + 8 * ring_slot(qp_pos(j - 1, ta >> 2)));
          }
        }
        wgmma_wait<0>();
        fence_regs(acc);
        FS(2 * it, 1);
        TL_MARK2(29, threadIdx.x == 256 && it == 0);
        if (tid == 0) mbar_arrive(b_empty + 24);
      }
      float o[64], s[64];
      uint32_t p[32], q[32];
      #pragma unroll
      for (int i = 0; i < 32; i++) q[i] = pack_bf16(acc[2 * i] * AT_C, acc[2 * i + 1] * AT_C);
      zero_regs(s);
      const uint32_t sq = sbase + AT_SQ + cwg * 8192;
      const bool last_wg1 = cwg == 1 && !more;
      float mc0, mc1, al0 = 1.0f, al1 = 1.0f, l0 = 0.f, l1 = 0.f, lp0 = 0.f, lp1 = 0.f;
      bool redo0 = false;
      FS(2 * it, 2);
      mbar_wait(b_full + 8 * ring_slot(ta), ring_par(ta));
      named_bar_sync(1 + cwg, 256);
      FS(2 * it, 3);
      issue_qk(s, q, k_base + ring_slot(ta) * 2048);
      named_bar_arrive(1 + (cwg ^ 1), 256);
      bool ready = mbar_test(b_full + 8 * ring_slot(ta + 1), ring_par(ta + 1)) & mbar_test(b_full + 8 * ring_slot(ta + 2), ring_par(ta + 2));
      stage_q<16>(acc, AT_C, sbase + AT_SQ + frag, lane);
      wgmma_wait<0>();
      fence_regs(s);
      if (tid == 0) mbar_arrive(b_empty + 8 * ring_slot(ta));
      mc0 = 0.f; mc1 = 0.f;
      if (!raw) {
        raw = softmax_mode(s, mc0, mc1);
        if (__builtin_expect(!raw, 0)) softmax_sub(s, mc0, mc1);
      }
      softmax_exp<0, 64>(s);
      #pragma unroll
      for (int J = 0; J < 16; J += 2)
        stmatrix_x4(sbase + AT_SQ + frag + (J >> 3) * 16384 + ((((J & 7) + (lane >> 4)) ^ (lane & 7)) << 4), q[2 * J], q[2 * J + 1], q[2 * J + 2], q[2 * J + 3]);
      pack_p(p, s);
      zero_regs(o);
      FS(2 * it, 4);
      uint32_t ks = ring_slot(ta + 1), vs = ring_slot(ta + 2), kp = ring_par(ta + 1), vp = ring_par(ta + 2);
      auto finish_head = [&]() {
        FS(2 * it, 5);
        redo0 = finish_l(lp0, lp1);
        if (!redo0) {
          stage_o(o, lp0, lp1, sbase + AT_SQ + frag, lane);
          fence_proxy_async();
          __syncwarp();
          if (lane == 0) mbar_arrive(b_ordy + 8 * cwg);
        }
        FS(2 * it + 1, 4);
      };
      if (!ready) { mbar_wait(b_full + 8 * ks, kp); mbar_wait(b_full + 8 * vs, vp); }
      #pragma unroll 1
      for (int n = 1; n < 2 * AT_NBLK; n++) {
        named_bar_sync(1 + cwg, 256);
        issue_qk(s, q, k_base + ks * 2048);
        if (n == AT_NBLK + 1) finish_head();
        issue_pv(o, p, v_base + vs * 2048, (n & 15) != 1);
        if (!(last_wg1 && n == 2 * AT_NBLK - 1)) named_bar_arrive(1 + (cwg ^ 1), 256);
        wgmma_wait<1>();
        fence_regs(s);
        if (tid == 0) mbar_arrive(b_empty + 8 * ks);
        if (__builtin_expect(!raw || (n + 1) >> 1 == AT_NBLK / 2, 0)) {
          if (n == AT_NBLK - 1) {
            #pragma unroll
            for (int J = 0; J < 16; J += 2)
              ldmatrix_x4(sbase + AT_SQ + 32768 + frag + (J >> 3) * 16384 + ((((J & 7) + (lane >> 4)) ^ (lane & 7)) << 4), q[2 * J], q[2 * J + 1], q[2 * J + 2], q[2 * J + 3]);
          }
          if (!raw) {
            const float m0 = mc0, m1 = mc1;
            const bool ok = softmax_mode(s, mc0, mc1);
            if (n == AT_NBLK) raw = ok;
            else {
              mc0 = mc0 - AT_HEAD > m0 ? mc0 : m0; mc1 = mc1 - AT_HEAD > m1 ? mc1 : m1;
              al0 = ex2_approx(m0 - mc0); al1 = ex2_approx(m1 - mc1);
            }
            if (!raw) softmax_sub(s, mc0, mc1);
          }
        }
        softmax_exp<0, AT_SPLIT>(s);
        add_rowsum(p, l0, l1);
        if (tid == 0) {
          uint32_t dep = zero & __float_as_uint(l0) & __float_as_uint(l1);
          #pragma unroll
          for (int i = AT_SPLIT - AT_PIN - PINB; i < AT_SPLIT - PINB; i += 2) dep &= __float_as_uint(s[i]) & __float_as_uint(s[i + 1]);
          mbar_arrive(b_pin + dep);
        }
        wgmma_wait<0>();
        fence_regs(o);
        if (tid == 0) mbar_arrive(b_empty + 8 * vs);
        ks += 2; if (ks >= 5) { ks -= 5; kp ^= 1; }
        vs += 2; if (vs >= 5) { vs -= 5; vp ^= 1; }
        ready = mbar_test(b_full + 8 * ks, kp) & mbar_test(b_full + 8 * vs, vp);
        softmax_exp<AT_SPLIT, 64>(s);
        pack_p(p, s);
        if (n == AT_NBLK) { lp0 = l0; lp1 = l1; l0 = 0.f; l1 = 0.f; }
        if (__builtin_expect(!raw || !ready, 0)) {
        if (!raw && __any_sync(0xffffffffu, al0 != 1.0f || al1 != 1.0f)) {
          rescale_o(o, al0, al1);
          l0 *= al0; l1 *= al1;
          al0 = 1.0f; al1 = 1.0f;
        }
        if (!ready && n < 2 * AT_NBLK - 1) {
          mbar_wait(b_full + 8 * ks, kp);
          mbar_wait(b_full + 8 * vs, vp);
        }
        }
      }
      FS(2 * it + 1, 5);
      const uint32_t vl = ring_slot(ta + 63);
      vs = ring_slot(ta + 62);
      const uint32_t ob = more ? sbase + vs * 32768 : sbase + AT_SQ + 32768;
      if (redo0) {
        attn_rows_exact(sq, sq, 4 * ta, kc, vc);
        fence_proxy_async();
        __syncwarp();
        if (lane == 0) mbar_arrive(b_ordy + 8 * cwg);
      }
      mbar_wait(b_full + 8 * vl, ring_par(ta + 63));
      issue_pv(o, p, v_base + vl * 2048, 1);
      add_rowsum(p, l0, l1);
      const bool overflow = finish_l(l0, l1);
      if (!overflow && lane == 0) mbar_arrive(b_q1);
      #pragma unroll
      for (int i = 0; i < 8; i++) asm volatile("mov.b64 {%0, %1}, 0;\nmov.b64 {%2, %3}, 0;" : "=r"(pre[i].x), "=r"(pre[i].y), "=r"(pre[i].z), "=r"(pre[i].w));
      if (HOIST && !more && blockIdx.x < OG_MOE) {
        load_pre(pre, sbase, AT_SQ, threadIdx.x - 128);
        __syncwarp();
        if (lane == 0) mbar_arrive(bars + 304);
      }
      mbar_wait(b_empty + 8 * vs, ring_par(ta + 62));
      wgmma_wait<0>();
      fence_regs(o);
      if (tid == 0) mbar_arrive(b_empty + 8 * vl);
      FS(2 * it + 1, 6);
      if (overflow) {
        attn_rows_exact(sq + 32768, ob + cwg * 8192, 4 * ta + 1, kc, vc);
        __syncwarp();
        if (lane == 0) mbar_arrive(b_q1);
      } else stage_o(o, l0, l1, ob + frag, lane);
      fence_proxy_async();
      __syncwarp();
      if (lane == 0) mbar_arrive(b_ordy + 16 + 8 * cwg);
      if (redo0 || overflow) raw = false;
      named_bar_sync(3 + cwg, 128);
      FS(2 * it + 1, 7);
    }
    if (__builtin_expect(single, 0)) {
      float acc[128];
      uint32_t j = 0, pk[64];
      #pragma unroll
      for (int i = 0; i < 64; i++) asm volatile("" : "=f"(acc[2 * i]), "=f"(acc[2 * i + 1]), "=r"(pk[i]));
      uint4* dst = g_pre;
      int left = 0;
      auto put = [&](bool last) {
        #pragma unroll
        for (int i = 0; i < PUT_N; i++) dst[i * 256] = make_uint4(pk[4 * i], pk[4 * i + 1], pk[4 * i + 2], pk[4 * i + 3]);
        dst += PUT_N * 256;
        #pragma unroll
        for (int i = 0; i < 64 - 4 * PUT_N; i++) asm volatile("mov.b32 %0, %1;" : "=r"(pk[i]) : "r"(pk[i + 4 * PUT_N]));
        __syncwarp();
        if (last && lane == 0) mbar_arrive(bars + 280);
      };
      #pragma unroll 1
      for (int ji = 0; ji < help_njobs(); ji++) {
        const int nk = ji < OG_JOBS ? OG_PRE : OG_PRE2;
        #pragma unroll 1
        for (int kk = 0; kk < nk; kk++, j++) {
          const uint32_t slot = ring_slot(qp_pos(j, 1));
          mbar_wait(b_full + 8 * slot, ring_par(qp_pos(j, 1)) ^ ((j >> 2) & 1));
          if (H_STAG > 0 && cwg == 1 && kk == nk - H_STAG) named_bar_sync(7, 256);
          const uint32_t a_lo = q_lo + (j & 3) * 1024, b_lo = w_base + slot * 2048;
          wgmma_fence();
          wgmma_m64n256k16_ss_tb<0, 0>(acc, a_lo, b_lo, kk != 0);
          wgmma_m64n256k16_ss_tb<2, 128>(acc, a_lo, b_lo, 1);
          wgmma_m64n256k16_ss_tb<4, 256>(acc, a_lo, b_lo, 1);
          wgmma_m64n256k16_ss_tb<6, 384>(acc, a_lo, b_lo, 1);
          wgmma_commit();
          if (H_STAG > 0 && cwg == 0 && kk == nk - 1) named_bar_arrive(7, 256);
          wgmma_wait<1>();
          if (kk > 0 && tid == 0) mbar_arrive(b_empty + 8 * ring_slot(qp_pos(j - 1, 1)));
          #pragma unroll 1
          for (int i = ji == OG_JOBS ? 0 : 16 / PUT_N - 1; i < 16 / PUT_N && left > 0; i++) put(--left == 0);
        }
        wgmma_wait<0>();
        fence_regs(acc);
        if (tid == 0) mbar_arrive(b_empty + 8 * ring_slot(qp_pos(j - 1, 1)));
        #pragma unroll
        for (int i = 0; i < 64; i++) pk[i] = pack_bf16(acc[2 * i], acc[2 * i + 1]);
        left = 16 / PUT_N;
        if (ji == PRE_X) mbar_wait(bars + 296, 0);
        dst = g_pre + help_job(ji) * 2048 + threadIdx.x - 128;
      }
      #pragma unroll
      for (int i = 0; i < 16; i++) dst[i * 256] = make_uint4(pk[4 * i], pk[4 * i + 1], pk[4 * i + 2], pk[4 * i + 3]);
      __syncwarp();
      if (lane == 0) mbar_arrive(bars + 280);
      named_bar_sync(5, 256);
      if (threadIdx.x == 128) {
        #pragma unroll 1
        for (int i = 0; i < 5; i++) {
          constexpr int n = OG_JOBS * OG_PRE;
          const int used = i == 3 ? 0 : (n + 3 - (i == 4 ? 3 : i)) / 4;
          if ((used ^ (i < 4)) & 1) {
            mbar_arrive(b_full + 8 * ring_slot(4 + i));
            mbar_arrive(b_empty + 8 * ring_slot(4 + i)); mbar_arrive(b_empty + 8 * ring_slot(4 + i));
          }
        }
        mbar_arrive(b_x);
      }
      named_bar_sync(5, 256);
      #pragma unroll
      for (int i = 0; i < 8; i++) pre[i] = make_uint4(0u, 0u, 0u, 0u);
    }
    TL_CLK(3, 1, threadIdx.x == 128);
    TL_CTA(1, threadIdx.x == 256);
    TL_END(3, tid == 0);
    TL_MARK2(19, tid == 0 && !single);
    if (blockIdx.x < 128) {
      if (!HOIST && blockIdx.x < OG_MOE) {
        load_pre(pre, sbase, AT_SQ, threadIdx.x - 128);
        __syncwarp();
        if (lane == 0) mbar_arrive(bars + 304);
      }
      tail_consumer(sbase, pre, cwg, w_gate, w_up);
    }
  }
}

typedef CUresult (*PFN_encodeTiled)(CUtensorMap*, CUtensorMapDataType, cuuint32_t, void*, const cuuint64_t*, const cuuint64_t*,
                                    const cuuint32_t*, const cuuint32_t*, CUtensorMapInterleave, CUtensorMapSwizzle,
                                    CUtensorMapL2promotion, CUtensorMapFloatOOBfill);

CUtensorMap make_map_2d(PFN_encodeTiled enc, const void* ptr, uint64_t inner, uint64_t outer, uint64_t stride_bytes, uint32_t box_inner, uint32_t box_outer) {
  CUtensorMap m;
  cuuint64_t gd[2] = {inner, outer}; cuuint64_t gs[1] = {stride_bytes};
  cuuint32_t bx[2] = {box_inner, box_outer}; cuuint32_t es[2] = {1, 1};
  enc(&m, CU_TENSOR_MAP_DATA_TYPE_BFLOAT16, 2, const_cast<void*>(ptr), gd, gs, bx, es, CU_TENSOR_MAP_INTERLEAVE_NONE,
      CU_TENSOR_MAP_SWIZZLE_128B, CU_TENSOR_MAP_L2_PROMOTION_L2_128B, CU_TENSOR_MAP_FLOAT_OOB_FILL_NONE);
  return m;
}

CUtensorMap make_map_3d(PFN_encodeTiled enc, const void* ptr, uint64_t cols, uint64_t rows, uint32_t box_rows, uint32_t chunks) {
  CUtensorMap m;
  cuuint64_t gd[3] = {64, rows, cols / 64}; cuuint64_t gs[2] = {cols * 2, 128};
  cuuint32_t bx[3] = {64, box_rows, chunks}; cuuint32_t es[3] = {1, 1, 1};
  enc(&m, CU_TENSOR_MAP_DATA_TYPE_BFLOAT16, 3, const_cast<void*>(ptr), gd, gs, bx, es, CU_TENSOR_MAP_INTERLEAVE_NONE,
      CU_TENSOR_MAP_SWIZZLE_128B, CU_TENSOR_MAP_L2_PROMOTION_L2_128B, CU_TENSOR_MAP_FLOAT_OOB_FILL_NONE);
  return m;
}

}

extern "C" void kernel_launch(void* const* d_in, const int* in_sizes, int n_in, void* d_out, int out_size) {
  const bf16* x      = (const bf16*)d_in[0];
  const bf16* kc     = (const bf16*)d_in[1];
  const bf16* vc     = (const bf16*)d_in[2];
  const bf16* wq     = (const bf16*)d_in[3];
  const bf16* wo     = (const bf16*)d_in[4];
  const bf16* w_r    = (const bf16*)d_in[6];
  const bf16* w_gate = (const bf16*)d_in[7];
  const bf16* w_up   = (const bf16*)d_in[8];
  const bf16* w_down = (const bf16*)d_in[9];
  const bf16* cvec   = (const bf16*)d_in[10];
  const bf16* w_mod  = (const bf16*)d_in[11];
  bf16* out = (bf16*)d_out;

  static PFN_encodeTiled enc = nullptr;
  static void *p_h = nullptr, *p_o = nullptr;
  if (!enc) {
    void* fn = nullptr; cudaDriverEntryPointQueryResult qres;
    cudaGetDriverEntryPoint("cuTensorMapEncodeTiled", &fn, cudaEnableDefault, &qres);
    enc = (PFN_encodeTiled)fn;
    cudaGetSymbolAddress(&p_h, g_pre);
    p_h = (uint4*)p_h + 16 * PRE_X * 2048;
    cudaGetSymbolAddress(&p_o, g_o);
    cudaFuncSetAttribute(fused_kernel, cudaFuncAttributeMaxDynamicSharedMemorySize, (int)AT_SMEM);
  }
  const CUtensorMap tm_h   = make_map_2d(enc, p_h, T_D, T_SEQ, T_D * 2, 64, 128);
  const CUtensorMap tm_wq  = W3D ? make_map_3d(enc, wq, T_DQKV, T_D, 64, 4) : make_map_2d(enc, wq, T_DQKV, T_D, T_DQKV * 2, 64, 64);
  const CUtensorMap tm_k   = KV3D ? make_map_3d(enc, kc, T_DH, (uint64_t)T_NH * T_SEQ, 128, 2) : make_map_2d(enc, kc, T_DH, (uint64_t)T_NH * T_SEQ, T_DH * 2, 64, 128);
  const CUtensorMap tm_v   = KV3D ? make_map_3d(enc, vc, T_DH, (uint64_t)T_NH * T_SEQ, 128, 2) : make_map_2d(enc, vc, T_DH, (uint64_t)T_NH * T_SEQ, T_DH * 2, 64, 128);
  const CUtensorMap tm_ost = make_map_2d(enc, p_o, T_DQKV, T_SEQ, T_DQKV * 2, 64, 64);
  const CUtensorMap tm_old = make_map_2d(enc, p_o, T_DQKV, T_SEQ, T_DQKV * 2, 64, 128);
  const CUtensorMap tm_wo  = make_map_3d(enc, wo, T_D, T_DQKV, 64, 2);
  const CUtensorMap tm_x   = make_map_3d(enc, w_down, T_D, T_F, 32, 8);

  const CUtensorMap tm_m   = make_map_2d(enc, w_mod, 6 * T_D, T_D, 6 * T_D * 2, 64, 256);
  const CUtensorMap tm_out = make_map_2d(enc, out, T_D, T_SEQ, T_D * 2, 64, 128);

  fused_kernel<<<132, 384, AT_SMEM, cudaStreamPerThread>>>(tm_h, tm_wq, tm_k, tm_v, tm_ost, tm_old, tm_wo, tm_x, tm_out, tm_m, 0u, (const uint8_t*)wo, kc, vc, x, cvec, w_mod,
             w_r, w_gate, w_up, w_down, out);
}
```

```cpp
#include <cuda_runtime.h>
#include <cuda_bf16.h>
#include <cuda.h>
#include <stdint.h>

namespace {

typedef __nv_bfloat16 bf16;

constexpr int T_SEQ = 2048, T_D = 1024, T_NH = 32, T_DH = 128, T_DQKV = 4096, T_F = 3584;

#define PRE_X 2
__device__ __align__(1024) uint4 g_pre[(16 * PRE_X + 128) * 2048];
#define g_h (reinterpret_cast<bf16*>(g_pre + 16 * PRE_X * 2048))
__device__ __align__(1024) bf16 g_o[T_SEQ * T_DQKV];
__device__ __align__(16) uint8_t g_col[8 * 1536];
__device__ __align__(16) float g_scal[64];
__device__ __align__(16) unsigned int g_hcnt[17 * 32];
__device__ unsigned int g_smid[168], g_tmax[128];
__device__ __align__(128) float g_modpart[4 * 2 * T_D];
struct __align__(2048) TailMail {
  float4 part1[T_SEQ * 8];
  uint32_t key[256];
  uint4 cand[16 * 2 * 2 * 128];
  uint32_t cnt[32];
  float ypart[(T_F / 32) * 2 * T_D];
};
__device__ TailMail g_mail;
#define g_part1 g_mail.part1
#define g_key g_mail.key
#define g_cand g_mail.cand
#define CNT_Y (g_mail.cnt)
#define g_ypart g_mail.ypart

__device__ __forceinline__ uint32_t smem_u32(const void* p) { return (uint32_t)__cvta_generic_to_shared(p); }
__device__ __forceinline__ void mbar_init(uint32_t bar, uint32_t cnt) { asm volatile("mbarrier.init.shared::cta.b64 [%0], %1;" :: "r"(bar), "r"(cnt)); }
__device__ __forceinline__ void mbar_expect_tx(uint32_t bar, uint32_t bytes) { asm volatile("mbarrier.arrive.expect_tx.shared::cta.b64 _, [%0], %1;" :: "r"(bar), "r"(bytes) : "memory"); }
__device__ __forceinline__ void mbar_arrive(uint32_t bar) { asm volatile("mbarrier.arrive.shared::cta.b64 _, [%0];" :: "r"(bar) : "memory"); }
__device__ __forceinline__ void mbar_wait(uint32_t bar, uint32_t parity) {
  asm volatile("{\n.reg .pred p;\nLAB_WAIT:\nmbarrier.try_wait.parity.shared::cta.b64 p, [%0], %1;\n@!p bra LAB_WAIT;\n}\n" :: "r"(bar), "r"(parity) : "memory");
}
__device__ __forceinline__ bool mbar_test(uint32_t bar, uint32_t parity) {
  uint32_t r; asm volatile("{\n.reg .pred p;\nmbarrier.test_wait.parity.shared::cta.b64 p, [%1], %2;\nselp.u32 %0, 1, 0, p;\n}\n" : "=r"(r) : "r"(bar), "r"(parity) : "memory");
  return r != 0;
}
__device__ __forceinline__ uint32_t clock_lo() { uint32_t c; asm volatile("mov.u32 %0, %%clock;" : "=r"(c)); return c; }
__device__ __forceinline__ void fence_mbar_init() { asm volatile("fence.mbarrier_init.release.cluster;" ::: "memory"); }
__device__ __forceinline__ void tma_load_2d(uint32_t dst, const CUtensorMap* map, int c0, int c1, uint32_t bar) {
  asm volatile("cp.async.bulk.tensor.2d.shared::cluster.global.mbarrier::complete_tx::bytes [%0], [%1, {%3, %4}], [%2];"
    :: "r"(dst), "l"(map), "r"(bar), "r"(c0), "r"(c1) : "memory");
}
__device__ __forceinline__ uint64_t policy_evict_first() {
  uint64_t p; asm volatile("createpolicy.fractional.L2::evict_first.b64 %0, 1.0;" : "=l"(p)); return p;
}
__device__ __forceinline__ void tma_load_2d_hint(uint32_t dst, const CUtensorMap* map, int c0, int c1, uint32_t bar, uint64_t pol) {
  asm volatile("cp.async.bulk.tensor.2d.shared::cluster.global.mbarrier::complete_tx::bytes.L2::cache_hint [%0], [%1, {%3, %4}], [%2], %5;"
    :: "r"(dst), "l"(map), "r"(bar), "r"(c0), "r"(c1), "l"(pol) : "memory");
}
__device__ __forceinline__ void tma_load_3d_hint(uint32_t dst, const CUtensorMap* map, int c1, int c2, uint32_t bar, uint64_t pol) {
  asm volatile("cp.async.bulk.tensor.3d.shared::cluster.global.mbarrier::complete_tx::bytes.L2::cache_hint [%0], [%1, {%3, %4, %5}], [%2], %6;"
    :: "r"(dst), "l"(map), "r"(bar), "n"(0), "r"(c1), "r"(c2), "l"(pol) : "memory");
}
__device__ __forceinline__ void tma_store_2d(const CUtensorMap* map, uint32_t src, int c0, int c1) {
  asm volatile("cp.async.bulk.tensor.2d.global.shared::cta.bulk_group [%0, {%2, %3}], [%1];" :: "l"(map), "r"(src), "r"(c0), "r"(c1) : "memory");
}
__device__ __forceinline__ void prefetch_tmap(const CUtensorMap* map) { asm volatile("prefetch.tensormap [%0];" :: "l"(map) : "memory"); }
__device__ __forceinline__ void l2_prefetch_bulk(const void* p, uint32_t bytes) {
  asm volatile("cp.async.bulk.prefetch.L2.global [%0], %1;" :: "l"(p), "r"(bytes) : "memory");
}
__device__ __forceinline__ void bulk_commit() { asm volatile("cp.async.bulk.commit_group;" ::: "memory"); }
template<int N> __device__ __forceinline__ void bulk_wait_read() { asm volatile("cp.async.bulk.wait_group.read %0;" :: "n"(N) : "memory"); }
template<int N> __device__ __forceinline__ void bulk_wait() { asm volatile("cp.async.bulk.wait_group %0;" :: "n"(N) : "memory"); }
__device__ __forceinline__ void named_bar_sync(int id, int nthreads) { asm volatile("bar.sync %0, %1;" :: "r"(id), "r"(nthreads) : "memory"); }
__device__ __forceinline__ void named_bar_arrive(int id, int nthreads) { asm volatile("bar.arrive %0, %1;" :: "r"(id), "r"(nthreads) : "memory"); }
__device__ __forceinline__ void wgmma_fence() { asm volatile("wgmma.fence.sync.aligned;" ::: "memory"); }
__device__ __forceinline__ void wgmma_commit() { asm volatile("wgmma.commit_group.sync.aligned;" ::: "memory"); }
template<int N> __device__ __forceinline__ void wgmma_wait() { asm volatile("wgmma.wait_group.sync.aligned %0;" :: "n"(N) : "memory"); }
template<int R> __device__ __forceinline__ void reg_alloc() { asm volatile("setmaxnreg.inc.sync.aligned.u32 %0;" :: "n"(R)); }
template<int R> __device__ __forceinline__ void reg_dealloc() { asm volatile("setmaxnreg.dec.sync.aligned.u32 %0;" :: "n"(R)); }
__device__ __forceinline__ bool elect_one() {
  uint32_t pred; asm volatile("{\n.reg .pred p;\nelect.sync _|p, 0xffffffff;\nselp.u32 %0, 1, 0, p;\n}\n" : "=r"(pred)); return pred != 0;
}
__device__ __forceinline__ uint32_t pack_bf16(float lo, float hi) {
  uint32_t r; asm("cvt.rn.bf16x2.f32 %0, %1, %2;" : "=r"(r) : "f"(hi), "f"(lo)); return r;
}
__device__ __forceinline__ void stmatrix_x4(uint32_t addr, uint32_t r0, uint32_t r1, uint32_t r2, uint32_t r3) {
  asm volatile("stmatrix.sync.aligned.m8n8.x4.shared.b16 [%0], {%1, %2, %3, %4};" :: "r"(addr), "r"(r0), "r"(r1), "r"(r2), "r"(r3) : "memory");
}
__device__ __forceinline__ void fence_proxy_async() { asm volatile("fence.proxy.async.shared::cta;" ::: "memory"); }
__device__ __forceinline__ float ex2_approx(float x) { float y; asm("ex2.approx.ftz.f32 %0, %1;" : "=f"(y) : "f"(x)); return y; }
template<int N> __device__ __forceinline__ void fence_regs(float (&r)[N]) {
  #pragma unroll
  for (int i = 0; i < N; i++) asm volatile("" : "+f"(r[i]) :: "memory");
}
template<int N> __device__ __forceinline__ void zero_regs(float (&r)[N]) {
  #pragma unroll
  for (int i = 0; i < N; i += 2) asm volatile("mov.b64 {%0, %1}, 0;" : "=f"(r[i]), "=f"(r[i + 1]));
}
__device__ __forceinline__ float rbf(float x) { return __uint_as_float(pack_bf16(0.f, x)); }
__device__ __forceinline__ float bflo(uint32_t v) { return __uint_as_float(v << 16); }
__device__ __forceinline__ float bfhi(uint32_t v) { return __uint_as_float(v & 0xffff0000u); }

#define TL_START(k) do {} while (0)
#define TL_END(k, cond) do {} while (0)
#define TL_CTA(i, cond) do {} while (0)
#define FS(slot, k) do {} while (0)
#define TL_MARK2(k, cond) do {} while (0)
#define TL_CLK(k, i, cond) do {} while (0)

template <int OFFA, int OFFB>
__device__ __forceinline__ void wgmma_m64n256k16_ss_tb(float (&d)[128], uint32_t a_lo, uint32_t b_lo, int scaleD) {
  asm volatile("{\n.reg .pred p;\n.reg .b32 ta, tb;\n.reg .b64 da, db;\nsetp.ne.b32 p, %130, 0;\n"
    "add.u32 ta, %128, %131;\nadd.u32 tb, %129, %132;\n"
    "mov.b64 da, {ta, 0x40000040};\nmov.b64 db, {tb, 0x40000040};\n"
    "wgmma.mma_async.sync.aligned.m64n256k16.f32.bf16.bf16 "
    "{%0, %1, %2, %3, %4, %5, %6, %7, %8, %9, %10, %11, %12, %13, %14, %15, %16, %17, %18, %19, %20, %21, %22, %23, %24, %25, %26, %27, %28, %29, %30, %31, %32, %33, %34, %35, %36, %37, %38, %39, %40, %41, %42, %43, %44, %45, %46, %47, %48, %49, %50, %51, %52, %53, %54, %55, %56, %57, %58, %59, %60, %61, %62, %63, %64, %65, %66, %67, %68, %69, %70, %71, %72, %73, %74, %75, %76, %77, %78, %79, %80, %81, %82, %83, %84, %85, %86, %87, %88, %89, %90, %91, %92, %93, %94, %95, %96, %97, %98, %99, %100, %101, %102, %103, %104, %105, %106, %107, %108, %109, %110, %111, %112, %113, %114, %115, %116, %117, %118, %119, %120, %121, %122, %123, %124, %125, %126, %127}, "
    "da, db, p, 1, 1, 0, 1;\n}\n"
    : "+f"(d[0]), "+f"(d[1]), "+f"(d[2]), "+f"(d[3]), "+f"(d[4]), "+f"(d[5]), "+f"(d[6]), "+f"(d[7]), "+f"(d[8]), "+f"(d[9]), "+f"(d[10]), "+f"(d[11]), "+f"(d[12]), "+f"(d[13]), "+f"(d[14]), "+f"(d[15]), "+f"(d[16]), "+f"(d[17]), "+f"(d[18]), "+f"(d[19]), "+f"(d[20]), "+f"(d[21]), "+f"(d[22]), "+f"(d[23]), "+f"(d[24]), "+f"(d[25]), "+f"(d[26]), "+f"(d[27]), "+f"(d[28]), "+f"(d[29]), "+f"(d[30]), "+f"(d[31]), "+f"(d[32]), "+f"(d[33]), "+f"(d[34]), "+f"(d[35]), "+f"(d[36]), "+f"(d[37]), "+f"(d[38]), "+f"(d[39]), "+f"(d[40]), "+f"(d[41]), "+f"(d[42]), "+f"(d[43]), "+f"(d[44]), "+f"(d[45]), "+f"(d[46]), "+f"(d[47]), "+f"(d[48]), "+f"(d[49]), "+f"(d[50]), "+f"(d[51]), "+f"(d[52]), "+f"(d[53]), "+f"(d[54]), "+f"(d[55]), "+f"(d[56]), "+f"(d[57]), "+f"(d[58]), "+f"(d[59]), "+f"(d[60]), "+f"(d[61]), "+f"(d[62]), "+f"(d[63]), "+f"(d[64]), "+f"(d[65]), "+f"(d[66]), "+f"(d[67]), "+f"(d[68]), "+f"(d[69]), "+f"(d[70]), "+f"(d[71]), "+f"(d[72]), "+f"(d[73]), "+f"(d[74]), "+f"(d[75]), "+f"(d[76]), "+f"(d[77]), "+f"(d[78]), "+f"(d[79]), "+f"(d[80]), "+f"(d[81]), "+f"(d[82]), "+f"(d[83]), "+f"(d[84]), "+f"(d[85]), "+f"(d[86]), "+f"(d[87]), "+f"(d[88]), "+f"(d[89]), "+f"(d[90]), "+f"(d[91]), "+f"(d[92]), "+f"(d[93]), "+f"(d[94]), "+f"(d[95]), "+f"(d[96]), "+f"(d[97]), "+f"(d[98]), "+f"(d[99]), "+f"(d[100]), "+f"(d[101]), "+f"(d[102]), "+f"(d[103]), "+f"(d[104]), "+f"(d[105]), "+f"(d[106]), "+f"(d[107]), "+f"(d[108]), "+f"(d[109]), "+f"(d[110]), "+f"(d[111]), "+f"(d[112]), "+f"(d[113]), "+f"(d[114]), "+f"(d[115]), "+f"(d[116]), "+f"(d[117]), "+f"(d[118]), "+f"(d[119]), "+f"(d[120]), "+f"(d[121]), "+f"(d[122]), "+f"(d[123]), "+f"(d[124]), "+f"(d[125]), "+f"(d[126]), "+f"(d[127])
    : "r"(a_lo), "r"(b_lo), "r"(scaleD), "n"(OFFA), "n"(OFFB));
}

template <int OFFA, int OFFB>
__device__ __forceinline__ void wgmma_m64n128k16_ss_tb(float (&d)[64], uint32_t a_lo, uint32_t b_lo, int scaleD) {
  asm volatile("{\n.reg .pred p;\n.reg .b32 ta, tb;\n.reg .b64 da, db;\nsetp.ne.b32 p, %66, 0;\n"
    "add.u32 ta, %64, %67;\nadd.u32 tb, %65, %68;\n"
    "mov.b64 da, {ta, 0x40000040};\nmov.b64 db, {tb, 0x40000040};\n"
    "wgmma.mma_async.sync.aligned.m64n128k16.f32.bf16.bf16 "
    "{%0, %1, %2, %3, %4, %5, %6, %7, %8, %9, %10, %11, %12, %13, %14, %15, %16, %17, %18, %19, %20, %21, %22, %23, %24, %25, %26, %27, %28, %29, %30, %31, %32, %33, %34, %35, %36, %37, %38, %39, %40, %41, %42, %43, %44, %45, %46, %47, %48, %49, %50, %51, %52, %53, %54, %55, %56, %57, %58, %59, %60, %61, %62, %63}, "
    "da, db, p, 1, 1, 0, 1;\n}\n"
    : "+f"(d[0]), "+f"(d[1]), "+f"(d[2]), "+f"(d[3]), "+f"(d[4]), "+f"(d[5]), "+f"(d[6]), "+f"(d[7]), "+f"(d[8]), "+f"(d[9]), "+f"(d[10]), "+f"(d[11]), "+f"(d[12]), "+f"(d[13]), "+f"(d[14]), "+f"(d[15]), "+f"(d[16]), "+f"(d[17]), "+f"(d[18]), "+f"(d[19]), "+f"(d[20]), "+f"(d[21]), "+f"(d[22]), "+f"(d[23]), "+f"(d[24]), "+f"(d[25]), "+f"(d[26]), "+f"(d[27]), "+f"(d[28]), "+f"(d[29]), "+f"(d[30]), "+f"(d[31]), "+f"(d[32]), "+f"(d[33]), "+f"(d[34]), "+f"(d[35]), "+f"(d[36]), "+f"(d[37]), "+f"(d[38]), "+f"(d[39]), "+f"(d[40]), "+f"(d[41]), "+f"(d[42]), "+f"(d[43]), "+f"(d[44]), "+f"(d[45]), "+f"(d[46]), "+f"(d[47]), "+f"(d[48]), "+f"(d[49]), "+f"(d[50]), "+f"(d[51]), "+f"(d[52]), "+f"(d[53]), "+f"(d[54]), "+f"(d[55]), "+f"(d[56]), "+f"(d[57]), "+f"(d[58]), "+f"(d[59]), "+f"(d[60]), "+f"(d[61]), "+f"(d[62]), "+f"(d[63])
    : "r"(a_lo), "r"(b_lo), "r"(scaleD), "n"(OFFA), "n"(OFFB));
}

template <int OFFB>
__device__ __forceinline__ void wgmma_m64n128k16_rs_tb(float (&d)[64], uint32_t a0, uint32_t a1, uint32_t a2, uint32_t a3, uint32_t b_lo, int scaleD) {
  asm volatile("{\n.reg .pred p;\n.reg .b32 tb;\n.reg .b64 db;\nsetp.ne.b32 p, %69, 0;\n"
    "add.u32 tb, %68, %70;\n"
    "mov.b64 db, {tb, 0x40000040};\n"
    "wgmma.mma_async.sync.aligned.m64n128k16.f32.bf16.bf16 "
    "{%0, %1, %2, %3, %4, %5, %6, %7, %8, %9, %10, %11, %12, %13, %14, %15, %16, %17, %18, %19, %20, %21, %22, %23, %24, %25, %26, %27, %28, %29, %30, %31, %32, %33, %34, %35, %36, %37, %38, %39, %40, %41, %42, %43, %44, %45, %46, %47, %48, %49, %50, %51, %52, %53, %54, %55, %56, %57, %58, %59, %60, %61, %62, %63}, "
    "{%64, %65, %66, %67}, db, p, 1, 1, 1;\n}\n"
    : "+f"(d[0]), "+f"(d[1]), "+f"(d[2]), "+f"(d[3]), "+f"(d[4]), "+f"(d[5]), "+f"(d[6]), "+f"(d[7]), "+f"(d[8]), "+f"(d[9]), "+f"(d[10]), "+f"(d[11]), "+f"(d[12]), "+f"(d[13]), "+f"(d[14]), "+f"(d[15]), "+f"(d[16]), "+f"(d[17]), "+f"(d[18]), "+f"(d[19]), "+f"(d[20]), "+f"(d[21]), "+f"(d[22]), "+f"(d[23]), "+f"(d[24]), "+f"(d[25]), "+f"(d[26]), "+f"(d[27]), "+f"(d[28]), "+f"(d[29]), "+f"(d[30]), "+f"(d[31]), "+f"(d[32]), "+f"(d[33]), "+f"(d[34]), "+f"(d[35]), "+f"(d[36]), "+f"(d[37]), "+f"(d[38]), "+f"(d[39]), "+f"(d[40]), "+f"(d[41]), "+f"(d[42]), "+f"(d[43]), "+f"(d[44]), "+f"(d[45]), "+f"(d[46]), "+f"(d[47]), "+f"(d[48]), "+f"(d[49]), "+f"(d[50]), "+f"(d[51]), "+f"(d[52]), "+f"(d[53]), "+f"(d[54]), "+f"(d[55]), "+f"(d[56]), "+f"(d[57]), "+f"(d[58]), "+f"(d[59]), "+f"(d[60]), "+f"(d[61]), "+f"(d[62]), "+f"(d[63])
    : "r"(a0), "r"(a1), "r"(a2), "r"(a3), "r"(b_lo), "r"(scaleD), "n"(OFFB));
}

template <int OFFB>
__device__ __forceinline__ void wgmma_m64n128k16_rs(float (&d)[64], uint32_t a0, uint32_t a1, uint32_t a2, uint32_t a3, uint32_t b_lo, int scaleD) {
  asm volatile("{\n.reg .pred p;\n.reg .b32 tb;\n.reg .b64 db;\nsetp.ne.b32 p, %69, 0;\n"
    "add.u32 tb, %68, %70;\n"
    "mov.b64 db, {tb, 0x40000040};\n"
    "wgmma.mma_async.sync.aligned.m64n128k16.f32.bf16.bf16 "
    "{%0, %1, %2, %3, %4, %5, %6, %7, %8, %9, %10, %11, %12, %13, %14, %15, %16, %17, %18, %19, %20, %21, %22, %23, %24, %25, %26, %27, %28, %29, %30, %31, %32, %33, %34, %35, %36, %37, %38, %39, %40, %41, %42, %43, %44, %45, %46, %47, %48, %49, %50, %51, %52, %53, %54, %55, %56, %57, %58, %59, %60, %61, %62, %63}, "
    "{%64, %65, %66, %67}, db, p, 1, 1, 0;\n}\n"
    : "+f"(d[0]), "+f"(d[1]), "+f"(d[2]), "+f"(d[3]), "+f"(d[4]), "+f"(d[5]), "+f"(d[6]), "+f"(d[7]), "+f"(d[8]), "+f"(d[9]), "+f"(d[10]), "+f"(d[11]), "+f"(d[12]), "+f"(d[13]), "+f"(d[14]), "+f"(d[15]), "+f"(d[16]), "+f"(d[17]), "+f"(d[18]), "+f"(d[19]), "+f"(d[20]), "+f"(d[21]), "+f"(d[22]), "+f"(d[23]), "+f"(d[24]), "+f"(d[25]), "+f"(d[26]), "+f"(d[27]), "+f"(d[28]), "+f"(d[29]), "+f"(d[30]), "+f"(d[31]), "+f"(d[32]), "+f"(d[33]), "+f"(d[34]), "+f"(d[35]), "+f"(d[36]), "+f"(d[37]), "+f"(d[38]), "+f"(d[39]), "+f"(d[40]), "+f"(d[41]), "+f"(d[42]), "+f"(d[43]), "+f"(d[44]), "+f"(d[45]), "+f"(d[46]), "+f"(d[47]), "+f"(d[48]), "+f"(d[49]), "+f"(d[50]), "+f"(d[51]), "+f"(d[52]), "+f"(d[53]), "+f"(d[54]), "+f"(d[55]), "+f"(d[56]), "+f"(d[57]), "+f"(d[58]), "+f"(d[59]), "+f"(d[60]), "+f"(d[61]), "+f"(d[62]), "+f"(d[63])
    : "r"(a0), "r"(a1), "r"(a2), "r"(a3), "r"(b_lo), "r"(scaleD), "n"(OFFB));
}

__device__ __forceinline__ uint4 ldg_nc_v4(const void* p) {
  uint4 v;
    asm volatile("{\n.reg .b64 pol;\ncreatepolicy.fractional.L2::evict_first.b64 pol, 1.0;\n"
                 "ld.global.nc.L1::no_allocate.L2::cache_hint.v4.u32 {%0, %1, %2, %3}, [%4], pol;\n}\n" : "=r"(v.x), "=r"(v.y), "=r"(v.z), "=r"(v.w) : "l"(p));
  return v;
}
__device__ __forceinline__ uint64_t pol_normal() {
  uint64_t p; asm volatile("createpolicy.fractional.L2::evict_normal.b64 %0, 1.0;" : "=l"(p)); return p;
}
__device__ __forceinline__ void unpack8(const uint4& u, float (&v)[8]) {
  v[0] = bflo(u.x); v[1] = bfhi(u.x); v[2] = bflo(u.y); v[3] = bfhi(u.y);
  v[4] = bflo(u.z); v[5] = bfhi(u.z); v[6] = bflo(u.w); v[7] = bfhi(u.w);
}
__device__ __forceinline__ void fma8(float (&acc)[8], float s, const uint4& w) {
  acc[0] = fmaf(s, bflo(w.x), acc[0]); acc[1] = fmaf(s, bfhi(w.x), acc[1]); acc[2] = fmaf(s, bflo(w.y), acc[2]); acc[3] = fmaf(s, bfhi(w.y), acc[3]);
  acc[4] = fmaf(s, bflo(w.z), acc[4]); acc[5] = fmaf(s, bfhi(w.z), acc[5]); acc[6] = fmaf(s, bflo(w.w), acc[6]); acc[7] = fmaf(s, bfhi(w.w), acc[7]);
}
__device__ __forceinline__ float rcp_approx(float x) { float y; asm("rcp.approx.ftz.f32 %0, %1;" : "=f"(y) : "f"(x)); return y; }
__device__ __forceinline__ float sigmoid_f(float v) { return rcp_approx(1.0f + ex2_approx(v * -1.4426950408889634f)); }
__device__ __forceinline__ float silu_bf(float v) { return rbf(v * sigmoid_f(v)); }
__device__ __forceinline__ uint32_t rank_key(float r, int idx) {
  const uint32_t b = __float_as_uint(r) >> 16;
  const uint32_t u = (r != r) ? 0u : ((b & 0x8000u) ? (~b & 0xffffu) : (b | 0x8000u));
  return (u << 16) | (0xffffu - (uint32_t)idx);
}
__device__ __forceinline__ void warp_top2(uint32_t& k1, uint32_t& k2) {
  const uint32_t m1 = __reduce_max_sync(0xffffffffu, k1);
  k2 = __reduce_max_sync(0xffffffffu, k1 == m1 ? k2 : k1);
  k1 = m1;
}
__device__ __forceinline__ uint32_t bmul2(uint32_t a, uint32_t b) { uint32_t r; asm("mul.rn.bf16x2 %0, %1, %2;" : "=r"(r) : "r"(a), "r"(b)); return r; }
__device__ __forceinline__ uint32_t badd2(uint32_t a, uint32_t b) { uint32_t r; asm("add.rn.bf16x2 %0, %1, %2;" : "=r"(r) : "r"(a), "r"(b)); return r; }
__device__ __forceinline__ uint32_t bsub2(uint32_t a, uint32_t b) { uint32_t r; asm("sub.rn.bf16x2 %0, %1, %2;" : "=r"(r) : "r"(a), "r"(b)); return r; }
__device__ __forceinline__ float sqrt_approx(float x) { float y; asm("sqrt.approx.f32 %0, %1;" : "=f"(y) : "f"(x)); return y; }
__device__ __forceinline__ uint32_t ln_norm2(uint32_t x1, uint32_t mb2, float inv) {
  const uint32_t d = bsub2(x1, mb2);
  return pack_bf16(bflo(d) * inv, bfhi(d) * inv);
}
__device__ __forceinline__ uint32_t bfma2(uint32_t a, uint32_t b, uint32_t c) { uint32_t r; asm("fma.rn.bf16x2 %0, %1, %2, %3;" : "=r"(r) : "r"(a), "r"(b), "r"(c)); return r; }
__device__ __forceinline__ uint32_t ln_norm2b(uint32_t x1, uint32_t mb2, uint32_t ih, uint32_t il) {
  const uint32_t d = bsub2(x1, mb2);
  return bfma2(d, ih, bmul2(d, il));
}
__device__ __forceinline__ uint32_t ln_mod2(uint32_t x1, uint32_t mb2, float inv, uint32_t c1, uint32_t sb) { return badd2(bmul2(ln_norm2(x1, mb2, inv), c1), sb); }
__device__ __forceinline__ void ldmatrix_x4(uint32_t addr, uint32_t& r0, uint32_t& r1, uint32_t& r2, uint32_t& r3) {
  asm volatile("ldmatrix.sync.aligned.m8n8.x4.shared.b16 {%0, %1, %2, %3}, [%4];" : "=r"(r0), "=r"(r1), "=r"(r2), "=r"(r3) : "r"(addr) : "memory");
}
__device__ __forceinline__ uint4 ldg_stream_v4(const void* p, uint64_t pol) {
  uint4 v; asm volatile("ld.global.nc.L1::no_allocate.L2::cache_hint.L2::128B.v4.u32 {%0, %1, %2, %3}, [%4], %5;" : "=r"(v.x), "=r"(v.y), "=r"(v.z), "=r"(v.w) : "l"(p), "l"(pol)); return v;
}
__device__ __forceinline__ void bulk_load_hint(uint32_t dst, const void* src, uint32_t bytes, uint32_t bar, uint64_t pol) {
  asm volatile("cp.async.bulk.shared::cluster.global.mbarrier::complete_tx::bytes.L2::cache_hint [%0], [%1], %2, [%3], %4;"
    :: "r"(dst), "l"(src), "r"(bytes), "r"(bar), "l"(pol) : "memory");
}
__device__ __forceinline__ void red_release_add(unsigned int* p, unsigned int v) { asm volatile("red.release.gpu.global.add.u32 [%0], %1;" :: "l"(p), "r"(v) : "memory"); }
__device__ __forceinline__ unsigned int ld_acquire(const unsigned int* p) { unsigned int v; asm volatile("ld.acquire.gpu.global.u32 %0, [%1];" : "=r"(v) : "l"(p) : "memory"); return v; }
__device__ __forceinline__ void spin_until(const unsigned int* p, unsigned int target) {
  #pragma unroll 1
  for (unsigned int i = 0; i < (1u << 22); i++) { if (ld_acquire(p) >= target) return; }
}
__device__ __forceinline__ float lds_f32(uint32_t a) { float v; asm volatile("ld.shared.f32 %0, [%1];" : "=f"(v) : "r"(a) : "memory"); return v; }
__device__ __forceinline__ float2 lds_f32x2(uint32_t a) { float2 v; asm volatile("ld.shared.v2.f32 {%0, %1}, [%2];" : "=f"(v.x), "=f"(v.y) : "r"(a) : "memory"); return v; }
__device__ __forceinline__ uint2 lds_u32x2(uint32_t a) { uint2 v; asm volatile("ld.shared.v2.u32 {%0, %1}, [%2];" : "=r"(v.x), "=r"(v.y) : "r"(a) : "memory"); return v; }
__device__ __forceinline__ uint32_t lds_u32(uint32_t a) { uint32_t v; asm volatile("ld.shared.u32 %0, [%1];" : "=r"(v) : "r"(a) : "memory"); return v; }
__device__ __forceinline__ void sts_u32(uint32_t a, uint32_t v) { asm volatile("st.shared.u32 [%0], %1;" :: "r"(a), "r"(v) : "memory"); }
__device__ __forceinline__ void sts_u32x2(uint32_t a, uint32_t x, uint32_t y) { asm volatile("st.shared.v2.u32 [%0], {%1, %2};" :: "r"(a), "r"(x), "r"(y) : "memory"); }
__device__ __forceinline__ void sts_f32(uint32_t a, float v) { asm volatile("st.shared.f32 [%0], %1;" :: "r"(a), "f"(v) : "memory"); }
__device__ __forceinline__ void sts_f32x2(uint32_t a, float x, float y) { asm volatile("st.shared.v2.f32 [%0], {%1, %2};" :: "r"(a), "f"(x), "f"(y) : "memory"); }
__device__ __forceinline__ void sts_f32x4(uint32_t a, float x, float y, float z, float w) { asm volatile("st.shared.v4.f32 [%0], {%1, %2, %3, %4};" :: "r"(a), "f"(x), "f"(y), "f"(z), "f"(w) : "memory"); }

__device__ __forceinline__ uint4 lds_u32x4(uint32_t a) { uint4 v; asm volatile("ld.shared.v4.u32 {%0, %1, %2, %3}, [%4];" : "=r"(v.x), "=r"(v.y), "=r"(v.z), "=r"(v.w) : "r"(a) : "memory"); return v; }
__device__ __forceinline__ void sts_u32x4(uint32_t a, uint32_t x, uint32_t y, uint32_t z, uint32_t w) { asm volatile("st.shared.v4.u32 [%0], {%1, %2, %3, %4};" :: "r"(a), "r"(x), "r"(y), "r"(z), "r"(w) : "memory"); }
__device__ __forceinline__ void st_tagged(float* p, float v) {
  const uint32_t b = __float_as_uint(v);
  asm volatile("st.relaxed.gpu.global.u32 [%0], %1;" :: "l"(p), "r"(b == 0u ? 0x80000000u : b) : "memory");
}
__device__ __forceinline__ void st_tagged4(float* p, float x, float y, float z, float w) {
  const uint32_t a = __float_as_uint(x), b = __float_as_uint(y), c = __float_as_uint(z), d = __float_as_uint(w);
  asm volatile("st.relaxed.gpu.global.v4.u32 [%0], {%1, %2, %3, %4};" :: "l"(p), "r"(a == 0u ? 0x80000000u : a), "r"(b == 0u ? 0x80000000u : b),
               "r"(c == 0u ? 0x80000000u : c), "r"(d == 0u ? 0x80000000u : d) : "memory");
}
__device__ __forceinline__ void st_relaxed2(void* p, uint32_t a, uint32_t b) { asm volatile("st.relaxed.gpu.global.v2.u32 [%0], {%1, %2};" :: "l"(p), "r"(a), "r"(b) : "memory"); }
__device__ __forceinline__ float4 ld_tagged4(const float* p) {
  float4 v; asm volatile("ld.relaxed.gpu.global.v4.f32 {%0, %1, %2, %3}, [%4];" : "=f"(v.x), "=f"(v.y), "=f"(v.z), "=f"(v.w) : "l"(p) : "memory"); return v;
}
__device__ __forceinline__ bool tagged4(const float4& v) {
  return __float_as_uint(v.x) != 0u && __float_as_uint(v.y) != 0u && __float_as_uint(v.z) != 0u && __float_as_uint(v.w) != 0u;
}
__device__ __forceinline__ void hint_arrive(uint32_t* p) { asm volatile("red.relaxed.gpu.global.add.u32 [%0], 1;" :: "l"(p) : "memory"); }
__device__ __forceinline__ void hint_wait(const uint32_t* p, uint32_t target) {
  uint32_t v = 0u;
  #pragma unroll 1
  for (unsigned int i = 0; i < (1u << 22) && v < target; i++) asm volatile("ld.relaxed.gpu.global.u32 %0, [%1];" : "=r"(v) : "l"(p) : "memory");
}
__device__ __forceinline__ void fence_proxy_async_global() { asm volatile("fence.proxy.async.global;" ::: "memory"); }

#define H_SPLIT 1
#define X_DLY 1200
#define W_DLY 1900
#define W_FIRST 2200
#define PRE_B 2
#define H_PREG 1
template <int J0, int J1>
__device__ __forceinline__ void load_parts(float2 (&pa)[J1 - J0][4], int t2) {
  #pragma unroll
  for (int j = J0; j < J1; j++)
    #pragma unroll
    for (int k = 0; k < 4; k++)
      asm volatile("ld.relaxed.gpu.global.v2.f32 {%0, %1}, [%2];" : "=f"(pa[j - J0][k].x), "=f"(pa[j - J0][k].y)
                   : "l"(g_modpart + k * 2 * T_D + (t2 >> 7) * T_D + j * 256 + (t2 & 127) * 2) : "memory");
}
template <int J0, int J1>
__device__ __forceinline__ void finish_parts(float2 (&pa)[J1 - J0][4], bool loaded, int t2, uint32_t tab) {
  #pragma unroll 1
  for (unsigned int spin = 0; spin < (1u << 22); spin++) {
    if (!loaded) load_parts<J0, J1>(pa, t2);
    loaded = false;
    bool ok = true;
    #pragma unroll
    for (int j = 0; j < J1 - J0; j++)
      #pragma unroll
      for (int k = 0; k < 4; k++) ok &= (__float_as_uint(pa[j][k].x) != 0u) & (__float_as_uint(pa[j][k].y) != 0u);
    if (__all_sync(0xffffffffu, ok)) break;
  }
  #pragma unroll
  for (int j = J0; j < J1; j++) {
    const float2* q = pa[j - J0];
    const uint32_t m = pack_bf16(((q[0].x + q[1].x) + q[2].x) + q[3].x, ((q[0].y + q[1].y) + q[2].y) + q[3].y);
    sts_u32(tab + (t2 >> 7) * 2048 + j * 512 + (t2 & 127) * 4, t2 >= 128 ? badd2(m, 0x3F803F80u) : m);
  }
}
__device__ __forceinline__ void head_phase(uint32_t scr, uint32_t xs, uint32_t b_x, uint32_t b_go, uint32_t b_head, int t2, uint32_t zero, const bf16* __restrict__ cvec, const bf16* __restrict__ w_mod) {
  const int lane = t2 & 31, w8 = t2 >> 5;
  const int cb = blockIdx.x & 31, ks = blockIdx.x >> 5;
  const bool early = (cb & 15) < 4 * H_SPLIT;
  const uint32_t ws = (xs - 32768 + (t2 >> 3) * 128 + (((t2 ^ (t2 >> 3)) & 7) << 4)) ^ zero;
  const float cv = __bfloat162float(cvec[ks * 256 + t2]);
  const bf16* wsrc = w_mod + (size_t)(ks * 256 + (t2 >> 3)) * (6 * T_D) + cb * 64 + (t2 & 7) * 8;
  if (early) {
    const uint64_t pol = policy_evict_first();
    #pragma unroll 2
    for (int i = 0; i < 8; i++)
      asm volatile("cp.async.cg.shared.global.L2::cache_hint [%0], [%1], 16, %2;" :: "r"(ws + i * 4096), "l"(wsrc + (size_t)i * 32 * 6 * T_D), "l"(pol) : "memory");
  }
  sts_f32(scr + t2 * 4, silu_bf(cv));
  named_bar_sync(6, 384);
  TL_MARK2(1, t2 == 0);
  uint4 xv[2][4];
  uint32_t mb2[2], ih[2], il[2];
  auto norm = [&](int j) {
    #pragma unroll
    for (int r = 0; r < 2; r++) {
      xv[r][j].x = ln_norm2b(xv[r][j].x, mb2[r], ih[r], il[r]); xv[r][j].y = ln_norm2b(xv[r][j].y, mb2[r], ih[r], il[r]);
      xv[r][j].z = ln_norm2b(xv[r][j].z, mb2[r], ih[r], il[r]); xv[r][j].w = ln_norm2b(xv[r][j].w, mb2[r], ih[r], il[r]);
    }
  };
  auto modulate = [&](int j) {
    const uint4 sa = lds_u32x4(scr + 8192 + j * 512 + lane * 16), c1 = lds_u32x4(scr + 8192 + 2048 + j * 512 + lane * 16);
    #pragma unroll
    for (int r = 0; r < 2; r++) {
      xv[r][j].x = badd2(bmul2(xv[r][j].x, c1.x), sa.x); xv[r][j].y = badd2(bmul2(xv[r][j].y, c1.y), sa.y);
      xv[r][j].z = badd2(bmul2(xv[r][j].z, c1.z), sa.z); xv[r][j].w = badd2(bmul2(xv[r][j].w, c1.w), sa.w);
    }
  };
  auto store = [&](int j) {
    #pragma unroll
    for (int r = 0; r < 2; r++) *reinterpret_cast<uint4*>(g_h + (size_t)(blockIdx.x * 16 + 2 * w8 + r) * T_D + j * 256 + lane * 8) = xv[r][j];
  };
  #pragma unroll 1
  for (int ph = 0; ph < 2; ph++) {
    if ((ph == 0) == early) {
      asm volatile("cp.async.wait_all;" ::: "memory");
      if (!early) mbar_wait(b_x + 168, 0);
      float acc[8];
      #pragma unroll
      for (int j = 0; j < 8; j++) acc[j] = 0.f;
      #pragma unroll
      for (int i = 0; i < 8; i++) fma8(acc, lds_f32(scr + ((t2 >> 3) + 32 * i) * 4), lds_u32x4(ws + i * 4096));
      #pragma unroll
      for (int j = 0; j < 4; j++) { const bool up = lane & 16; acc[j] = (up ? acc[4 + j] : acc[j]) + __shfl_xor_sync(0xffffffffu, up ? acc[j] : acc[4 + j], 16); }
      #pragma unroll
      for (int j = 0; j < 2; j++) { const bool up = lane & 8; acc[j] = (up ? acc[2 + j] : acc[j]) + __shfl_xor_sync(0xffffffffu, up ? acc[j] : acc[2 + j], 8); }
      sts_f32x2(scr + 1024 + w8 * 256 + (lane & 7) * 32 + (lane >> 3) * 8, acc[0], acc[1]);
      named_bar_sync(5, 256);
      if (t2 < 64) {
        float sum = 0.f;
        #pragma unroll
        for (int i = 0; i < 8; i++) sum += lds_f32(scr + 1024 + i * 256 + t2 * 4);
        st_tagged(g_modpart + ks * 2 * T_D + cb * 64 + t2, sum);
        TL_MARK2(early ? 2 : 6, t2 == 0);
      }
    } else {
      float2 pa[H_SPLIT][4];
      mbar_wait(b_x, 0);
      TL_MARK2(18, t2 == 0);
      if (H_PREG) load_parts<0, H_SPLIT>(pa, t2);
      #pragma unroll
      for (int r = 0; r < 2; r++)
        #pragma unroll
        for (int j = 0; j < 4; j++) xv[r][j] = lds_u32x4(xs + (2 * w8 + r) * 2048 + j * 512 + lane * 16);
  {
    float st[4] = {0.f, 0.f, 0.f, 0.f};
    #pragma unroll
    for (int r = 0; r < 2; r++)
      #pragma unroll
      for (int j = 0; j < 4; j++) {
        float v[8];
        unpack8(xv[r][j], v);
        st[2 * r] += ((v[0] + v[1]) + (v[2] + v[3])) + ((v[4] + v[5]) + (v[6] + v[7]));
        st[2 * r + 1] += fmaf(v[0], v[0], fmaf(v[1], v[1], fmaf(v[2], v[2], v[3] * v[3]))) + fmaf(v[4], v[4], fmaf(v[5], v[5], fmaf(v[6], v[6], v[7] * v[7])));
      }
    #pragma unroll
    for (int k = 0; k < 2; k++) { const bool up = lane & 16; st[k] = (up ? st[2 + k] : st[k]) + __shfl_xor_sync(0xffffffffu, up ? st[k] : st[2 + k], 16); }
    #pragma unroll
    for (int o = 8; o > 0; o >>= 1) { st[0] += __shfl_xor_sync(0xffffffffu, st[0], o); st[1] += __shfl_xor_sync(0xffffffffu, st[1], o); }
    const float mean = st[0] * (1.0f / T_D);
    const float inv = rcp_approx(rbf(sqrt_approx(rbf(rbf(fmaxf(fmaf(-mean, mean, st[1] * (1.0f / T_D)), 0.f)) + 1e-05f))));
    const uint32_t m = pack_bf16(mean, mean), h = pack_bf16(inv - rbf(inv), inv);
    #pragma unroll
    for (int r = 0; r < 2; r++) {
      mb2[r] = __shfl_sync(0xffffffffu, m, 16 * r);
      const uint32_t hr = __shfl_sync(0xffffffffu, h, 16 * r);
      ih[r] = __byte_perm(hr, hr, 0x3232); il[r] = __byte_perm(hr, hr, 0x1010);
    }
  }
      #pragma unroll
      for (int j = 0; j < H_SPLIT; j++) norm(j);
      TL_MARK2(5, t2 == 0);
      finish_parts<0, H_SPLIT>(pa, H_PREG, t2, scr + 8192);
      named_bar_sync(5, 256);
      TL_MARK2(7, t2 == 0);
      #pragma unroll
      for (int j = 0; j < H_SPLIT; j++) { modulate(j); store(j); }
      named_bar_arrive(9, 288);
    }
  }
  #pragma unroll
  for (int j = H_SPLIT; j < 4; j++) norm(j);
  float2 pb[4 - H_SPLIT][4];
  finish_parts<H_SPLIT, 4>(pb, false, t2, scr + 8192);
  named_bar_sync(5, 256);
  TL_MARK2(17, t2 == 0);
  #pragma unroll
  for (int j = H_SPLIT; j < 4; j++) modulate(j);
  __syncwarp();
  if (lane == 0) mbar_arrive(b_head + (xv[1][3].w & zero));
  mbar_wait(b_go, 0);
  #pragma unroll
  for (int j = H_SPLIT; j < 4; j++) store(j);
  named_bar_arrive(8, 288);
}

#define MOD_AT (b_empty + 8)
#define MOD_PF 0
#define MOD_SPLIT 16
__device__ __forceinline__ void mod_rest(uint32_t scr, uint32_t b_go, int t, const bf16* __restrict__ cvec, const bf16* __restrict__ w_mod, const bf16* __restrict__ w_r) {
  const int lane = t & 31;
  #pragma unroll 1
  for (int i = t; i < T_D / 2; i += 64) {
    const uint32_t c2 = *reinterpret_cast<const uint32_t*>(cvec + 2 * i);
    sts_u32(scr + i * 4, pack_bf16(silu_bf(bflo(c2)), silu_bf(bfhi(c2))));
  }
  named_bar_sync(11, 64);
  const bf16* wp = w_mod + (size_t)(2 * (t >> 2)) * (6 * T_D) + 2 * T_D + blockIdx.x * 32 + (t & 3) * 8;
  float acc[8];
  #pragma unroll
  for (int i = 0; i < 8; i++) acc[i] = 0.f;
  #pragma unroll 1
  for (int i = 0; i < 32; i += 2) {
    if (i == MOD_SPLIT) mbar_wait(b_go, 0);
    const uint4 w0 = ldg_nc_v4(wp), w1 = ldg_nc_v4(wp + 6 * T_D), w2 = ldg_nc_v4(wp + 32 * 6 * T_D), w3 = ldg_nc_v4(wp + 33 * 6 * T_D);
    wp += 64 * 6 * T_D;
    const uint32_t s0 = lds_u32(scr + (i * 16 + (t >> 2)) * 4), s1 = lds_u32(scr + (i * 16 + 16 + (t >> 2)) * 4);
    fma8(acc, bflo(s0), w0); fma8(acc, bfhi(s0), w1); fma8(acc, bflo(s1), w2); fma8(acc, bfhi(s1), w3);
  }
  #pragma unroll
  for (int j = 0; j < 4; j++) { const bool up = lane & 16; acc[j] = (up ? acc[4 + j] : acc[j]) + __shfl_xor_sync(0xffffffffu, up ? acc[j] : acc[4 + j], 16); }
  #pragma unroll
  for (int j = 0; j < 2; j++) { const bool up = lane & 8; acc[j] = (up ? acc[2 + j] : acc[j]) + __shfl_xor_sync(0xffffffffu, up ? acc[j] : acc[2 + j], 8); }
  { const bool up = lane & 4; acc[0] = (up ? acc[1] : acc[0]) + __shfl_xor_sync(0xffffffffu, up ? acc[0] : acc[1], 4); }
  if (t >= 32) sts_f32(scr + 2048 + lane * 4, acc[0]);
  named_bar_sync(11, 64);
  if (__shfl_sync(0xffffffffu, t, 0) < 32) {
    const int kind = blockIdx.x >> 5;
    float v = rbf(acc[0] + lds_f32(scr + 2048 + lane * 4));
    const int col = (blockIdx.x & 31) * 32 + (lane & 3) * 8 + (lane >> 2);
    uint8_t* dst = g_col + (col >> 7) * 1536;
    if (kind == 2) v = rbf(1.0f + v);
    float vw = v * __bfloat162float(w_r[col]);
    if (kind == 2) {
      const int c = col & 127, i = (c & ~15) + ((c >> 1) & 3) * 4 + ((c >> 3) & 1) * 2 + (c & 1);
      reinterpret_cast<bf16*>(dst)[i] = __float2bfloat16_rn(vw);
      reinterpret_cast<bf16*>(dst)[128 + i] = __float2bfloat16_rn(vw - rbf(vw));
    }
    reinterpret_cast<bf16*>(dst + 512 + (kind & 1) * 512 + (kind >> 1) * 256)[col & 127] = __float2bfloat16_rn(v);
    #pragma unroll
    for (int o = 16; o > 0; o >>= 1) vw += __shfl_xor_sync(0xffffffffu, vw, o);
    if (lane == 0 && (kind == 1 || kind == 2)) g_scal[95 - blockIdx.x] = vw;
  }
  #pragma unroll 1
  for (int i = blockIdx.x * 64 + t; i < (int)(sizeof(g_mail) / 16); i += 128 * 64) reinterpret_cast<uint4*>(&g_mail)[i] = make_uint4(0u, 0u, 0u, 0u);
  named_bar_sync(11, 64);
  if (t == 0) red_release_add(&g_hcnt[0], 1u);
}

#define HPOL_A pol
#define HPOL_B pol_normal()
#define HMAP_A &tmOl
#define HMAP_B &tmWo
constexpr int AT_NBLK = T_SEQ / 128;
constexpr float AT_HEAD = 7.0f;
#define WO_LATE 12
constexpr int QP_STAG = 3;
constexpr int AT_SPLIT = 28, AT_PIN = 8, PINB = 4;
constexpr int AT_NFULL = 124;
constexpr int AT_PREG = 40, AT_CREG = 232;
constexpr uint32_t AT_SQ = 5 * 32768;
constexpr float AT_C = 0.08838834764831845f * 1.4426950408889634f;
constexpr float AT_RAW_LO = -16.0f, AT_RAW_HI = 24.0f;
constexpr float AT_RAW_SUM = 281474976710656.0f, AT_RAW_MIN = 9.094947017729282e-13f;
constexpr uint32_t AT_SBAR = AT_SQ + 65536 + 256;
constexpr uint32_t AT_SMEM = AT_SQ + 65536 + 3072;

__device__ __forceinline__ uint32_t ring_slot(uint32_t t) { return t - 5u * ((t * 205u) >> 10); }
__device__ __forceinline__ uint32_t qp_pos(uint32_t j, uint32_t it) { return 4u * it + (j & 3u) + ((j & 3u) == 3u ? it : 0u); }
__device__ __forceinline__ uint32_t ring_par(uint32_t t) { return ((t * 205u) >> 10) & 1u; }
__device__ __forceinline__ void softmax_rowmax(const float (&s)[64], float& mx0, float& mx1) {
  float a0 = fmaxf(s[0], s[1]), a1 = fmaxf(s[4], s[5]), a2 = fmaxf(s[8], s[9]), a3 = fmaxf(s[12], s[13]);
  float b0 = fmaxf(s[2], s[3]), b1 = fmaxf(s[6], s[7]), b2 = fmaxf(s[10], s[11]), b3 = fmaxf(s[14], s[15]);
  #pragma unroll
  for (int j = 4; j < 16; j += 4) {
    a0 = fmaxf(a0, fmaxf(s[4 * j + 0], s[4 * j + 1]));  b0 = fmaxf(b0, fmaxf(s[4 * j + 2], s[4 * j + 3]));
    a1 = fmaxf(a1, fmaxf(s[4 * j + 4], s[4 * j + 5]));  b1 = fmaxf(b1, fmaxf(s[4 * j + 6], s[4 * j + 7]));
    a2 = fmaxf(a2, fmaxf(s[4 * j + 8], s[4 * j + 9]));  b2 = fmaxf(b2, fmaxf(s[4 * j + 10], s[4 * j + 11]));
    a3 = fmaxf(a3, fmaxf(s[4 * j + 12], s[4 * j + 13])); b3 = fmaxf(b3, fmaxf(s[4 * j + 14], s[4 * j + 15]));
  }
  mx0 = fmaxf(fmaxf(a0, a1), fmaxf(a2, a3));
  mx1 = fmaxf(fmaxf(b0, b1), fmaxf(b2, b3));
  mx0 = fmaxf(mx0, __shfl_xor_sync(0xffffffffu, mx0, 1));
  mx1 = fmaxf(mx1, __shfl_xor_sync(0xffffffffu, mx1, 1));
  mx0 = fmaxf(mx0, __shfl_xor_sync(0xffffffffu, mx0, 2));
  mx1 = fmaxf(mx1, __shfl_xor_sync(0xffffffffu, mx1, 2));
}
__device__ __forceinline__ void softmax_sub(float (&s)[64], float mc0, float mc1) {
  #pragma unroll
  for (int j = 0; j < 16; j++) { s[4 * j] -= mc0; s[4 * j + 1] -= mc0; s[4 * j + 2] -= mc1; s[4 * j + 3] -= mc1; }
}
template <int LO, int HI>
__device__ __forceinline__ void softmax_exp(float (&s)[64]) {
  #pragma unroll
  for (int i = LO; i < HI; i++) s[i] = ex2_approx(s[i]);
}
__device__ __forceinline__ bool softmax_mode(const float (&s)[64], float& mc0, float& mc1) {
  softmax_rowmax(s, mc0, mc1);
  const bool raw = __all_sync(0xffffffffu, mc0 >= AT_RAW_LO && mc0 <= AT_RAW_HI && mc1 >= AT_RAW_LO && mc1 <= AT_RAW_HI);
  mc0 += AT_HEAD; mc1 += AT_HEAD;
  return raw;
}
__device__ __forceinline__ void rowsum_p(const uint32_t (&p)[32], uint32_t& t0, uint32_t& t1) {
  uint32_t a[16];
  #pragma unroll
  for (int i = 0; i < 8; i++) { a[2 * i] = badd2(p[4 * i], p[4 * i + 2]); a[2 * i + 1] = badd2(p[4 * i + 1], p[4 * i + 3]); }
  #pragma unroll
  for (int i = 0; i < 4; i++) { a[2 * i] = badd2(a[4 * i], a[4 * i + 2]); a[2 * i + 1] = badd2(a[4 * i + 1], a[4 * i + 3]); }
  t0 = badd2(badd2(a[0], a[2]), badd2(a[4], a[6]));
  t1 = badd2(badd2(a[1], a[3]), badd2(a[5], a[7]));
}
__device__ __forceinline__ void add_rowsum(const uint32_t (&p)[32], float& l0, float& l1) {
  uint32_t t0, t1;
  rowsum_p(p, t0, t1);
  l0 += bflo(t0) + bfhi(t0); l1 += bflo(t1) + bfhi(t1);
}
__device__ __forceinline__ void pack_p(uint32_t (&p)[32], const float (&s)[64]) {
  #pragma unroll
  for (int i = 0; i < 32; i++) p[i] = pack_bf16(s[2 * i], s[2 * i + 1]);
}
__device__ __noinline__ void attn_rows_exact(uint32_t sq, uint32_t so, int hsel, const bf16* __restrict__ kh, const bf16* __restrict__ vh) {
  const int warp = (threadIdx.x >> 5) & 3, lane = threadIdx.x & 31;
  const size_t hofs = (size_t)((blockIdx.x < 128 ? blockIdx.x >> 4 : 15) * 2 + hsel) * T_SEQ * T_DH;
  kh += hofs; vh += hofs;
  #pragma unroll 1
  for (int r = 16 * warp; r < 16 * warp + 16; r++) {
    const uint32_t ad = (lane >> 4) * 16384 + r * 128 + ((((lane & 15) >> 1) ^ (r & 7)) << 4) + (lane & 1) * 8;
    uint2 qv; asm volatile("ld.shared.v2.u32 {%0, %1}, [%2];" : "=r"(qv.x), "=r"(qv.y) : "r"(sq + ad) : "memory");
    const float q0 = bflo(qv.x), q1 = bfhi(qv.x), q2 = bflo(qv.y), q3 = bfhi(qv.y);
    float m = -INFINITY, l = 0.f, o0 = 0.f, o1 = 0.f, o2 = 0.f, o3 = 0.f;
    #pragma unroll 1
    for (int key = 0; key < T_SEQ; key++) {
      const uint2 kv = *reinterpret_cast<const uint2*>(kh + (size_t)key * T_DH + lane * 4);
      const uint2 vv = *reinterpret_cast<const uint2*>(vh + (size_t)key * T_DH + lane * 4);
      float sc = (q0 * bflo(kv.x) + q1 * bfhi(kv.x)) + (q2 * bflo(kv.y) + q3 * bfhi(kv.y));
      #pragma unroll
      for (int o = 16; o > 0; o >>= 1) sc += __shfl_xor_sync(0xffffffffu, sc, o);
      const float mn = fmaxf(m, sc);
      const float al = (m == mn) ? 1.0f : ex2_approx(m - mn), p = rbf(ex2_approx(sc - mn));
      m = mn;
      l = fmaf(l, al, p);
      o0 = fmaf(o0, al, p * bflo(vv.x)); o1 = fmaf(o1, al, p * bfhi(vv.x));
      o2 = fmaf(o2, al, p * bflo(vv.y)); o3 = fmaf(o3, al, p * bfhi(vv.y));
    }
    const float inv = rcp_approx(l);
    asm volatile("st.shared.v2.u32 [%0], {%1, %2};" :: "r"(so + ad), "r"(pack_bf16(o0 * inv, o1 * inv)), "r"(pack_bf16(o2 * inv, o3 * inv)) : "memory");
  }
}
__device__ __forceinline__ void issue_qk(float (&s)[64], const uint32_t (&q)[32], uint32_t k_lo) {
  wgmma_fence();
  wgmma_m64n128k16_rs<0>(s, q[0], q[1], q[2], q[3], k_lo, 0);
  wgmma_m64n128k16_rs<2>(s, q[4], q[5], q[6], q[7], k_lo, 1);
  wgmma_m64n128k16_rs<4>(s, q[8], q[9], q[10], q[11], k_lo, 1);
  wgmma_m64n128k16_rs<6>(s, q[12], q[13], q[14], q[15], k_lo, 1);
  wgmma_m64n128k16_rs<1024>(s, q[16], q[17], q[18], q[19], k_lo, 1);
  wgmma_m64n128k16_rs<1026>(s, q[20], q[21], q[22], q[23], k_lo, 1);
  wgmma_m64n128k16_rs<1028>(s, q[24], q[25], q[26], q[27], k_lo, 1);
  wgmma_m64n128k16_rs<1030>(s, q[28], q[29], q[30], q[31], k_lo, 1);
  wgmma_commit();
}
__device__ __forceinline__ void issue_pv(float (&o)[64], const uint32_t (&p)[32], uint32_t v_lo, int accumulate) {
  wgmma_fence();
  wgmma_m64n128k16_rs_tb<0>(o, p[0], p[1], p[2], p[3], v_lo, accumulate);
  wgmma_m64n128k16_rs_tb<128>(o, p[4], p[5], p[6], p[7], v_lo, 1);
  wgmma_m64n128k16_rs_tb<256>(o, p[8], p[9], p[10], p[11], v_lo, 1);
  wgmma_m64n128k16_rs_tb<384>(o, p[12], p[13], p[14], p[15], v_lo, 1);
  wgmma_m64n128k16_rs_tb<512>(o, p[16], p[17], p[18], p[19], v_lo, 1);
  wgmma_m64n128k16_rs_tb<640>(o, p[20], p[21], p[22], p[23], v_lo, 1);
  wgmma_m64n128k16_rs_tb<768>(o, p[24], p[25], p[26], p[27], v_lo, 1);
  wgmma_m64n128k16_rs_tb<896>(o, p[28], p[29], p[30], p[31], v_lo, 1);
  wgmma_commit();
}
__device__ __forceinline__ void block_end(uint32_t zero, uint32_t bar) {
  #pragma unroll 1
  for (uint32_t i = 0; i < zero; i++) mbar_arrive(bar);
}
__device__ __forceinline__ void rescale_o(float (&o)[64], float al0, float al1) {
  #pragma unroll
  for (int j = 0; j < 16; j++) { o[4 * j] *= al0; o[4 * j + 1] *= al0; o[4 * j + 2] *= al1; o[4 * j + 3] *= al1; }
}

__device__ __forceinline__ void stage_o(const float (&o)[64], float i0, float i1, uint32_t dst, int lane) {
  #pragma unroll
  for (int J = 0; J < 16; J += 2)
    stmatrix_x4(dst + (J >> 3) * 16384 + ((((J & 7) + (lane >> 4)) ^ (lane & 7)) << 4),
                pack_bf16(o[4 * J + 0] * i0, o[4 * J + 1] * i0), pack_bf16(o[4 * J + 2] * i1, o[4 * J + 3] * i1),
                pack_bf16(o[4 * J + 4] * i0, o[4 * J + 5] * i0), pack_bf16(o[4 * J + 6] * i1, o[4 * J + 7] * i1));
}
__device__ __forceinline__ bool finish_l(float& l0, float& l1) {
  l0 += __shfl_xor_sync(0xffffffffu, l0, 1); l1 += __shfl_xor_sync(0xffffffffu, l1, 1);
  l0 += __shfl_xor_sync(0xffffffffu, l0, 2); l1 += __shfl_xor_sync(0xffffffffu, l1, 2);
  const bool redo = __any_sync(0xffffffffu, !(l0 <= AT_RAW_SUM && l1 <= AT_RAW_SUM && l0 >= AT_RAW_MIN && l1 >= AT_RAW_MIN));
  l0 = rcp_approx(l0); l1 = rcp_approx(l1);
  return redo;
}
template <int J0>
__device__ __forceinline__ void stage_q(const float (&acc)[128], float c, uint32_t dst, int lane) {
  #pragma unroll
  for (int J = J0; J < J0 + 16; J += 2)
    stmatrix_x4(dst + (J >> 3) * 16384 + ((((J & 7) + (lane >> 4)) ^ (lane & 7)) << 4),
                pack_bf16(acc[4 * J + 0] * c, acc[4 * J + 1] * c), pack_bf16(acc[4 * J + 2] * c, acc[4 * J + 3] * c),
                pack_bf16(acc[4 * J + 4] * c, acc[4 * J + 5] * c), pack_bf16(acc[4 * J + 6] * c, acc[4 * J + 7] * c));
}
__device__ __forceinline__ void store_o(const CUtensorMap* tmO, uint32_t src, int head, int row) {
  tma_store_2d(tmO, src, head * T_DH, row);
  tma_store_2d(tmO, src + 16384, head * T_DH + 64, row);
  bulk_commit();
}
__device__ __forceinline__ void mma_bf16(float (&d)[4], uint32_t a0, uint32_t a1, uint32_t a2, uint32_t a3, uint32_t b0, uint32_t b1) {
  asm volatile("mma.sync.aligned.m16n8k16.row.col.f32.bf16.bf16.f32 {%0, %1, %2, %3}, {%4, %5, %6, %7}, {%8, %9}, {%0, %1, %2, %3};"
               : "+f"(d[0]), "+f"(d[1]), "+f"(d[2]), "+f"(d[3]) : "r"(a0), "r"(a1), "r"(a2), "r"(a3), "r"(b0), "r"(b1));
}
struct GemvSel { uint32_t lo0, hi0, lo1, hi1; };
__device__ __forceinline__ GemvSel gemv_sel(int lane) {
  const uint32_t lo = (lane & 8) ? 0x1044u : 0x4410u, hi = (lane & 8) ? 0x3244u : 0x4432u;
  GemvSel s; s.lo0 = (lane & 16) ? 0x4444u : lo; s.hi0 = (lane & 16) ? 0x4444u : hi; s.lo1 = (lane & 16) ? lo : 0x4444u; s.hi1 = (lane & 16) ? hi : 0x4444u;
  return s;
}
#define GEMV_B0(j, h, s) __byte_perm((j) < 2 ? (h).x : (h).y, 0u, ((j) & 1) ? (s).hi0 : (s).lo0)
#define GEMV_B1(j, h, s) __byte_perm((j) < 2 ? (h).x : (h).y, 0u, ((j) & 1) ? (s).hi1 : (s).lo1)
__device__ __forceinline__ float4 gemv_out(const float (&d)[4], int lane) {
  const bool tk = lane & 1;
  const float r0 = __shfl_xor_sync(0xffffffffu, tk ? d[0] : d[1], 1), r1 = __shfl_xor_sync(0xffffffffu, tk ? d[2] : d[3], 1);
  return tk ? make_float4(r0, d[1], r1, d[3]) : make_float4(d[0], r0, d[2], r1);
}
#define OG_NG 8
#define PUT_N 2
#define H_STAG 2
#define NOZERO 1
#define PVPIN 0
#define QKPIN 0
#define ALIGN 1
#define AL_P 60
#define AL_SLEEP 1200
#define AL_MAX 800
#define AL_ADD 0
#define X_PF 0
#define POLL_NS 200
#define KV3D 1
#define W3D 1
#define OG_PRE 10
#define OG_PRE2 12
#define SERP 1
#define OG_JOBS 7
#define OG_GRP 6
#define LD_FIRST 3
#define LD_STAG (OG_GRP / 2)
constexpr int OG_ST = 5, OG_NKB = T_DQKV / 64 - OG_PRE, OG_MOE = T_F / 32;
__device__ __forceinline__ int pre_kb(int i) { return (i >> 1) * 4 + (i & 1); }
__device__ __forceinline__ int own_kb(int i) { return i < OG_PRE2 ? pre_kb(i) + 2 : i < 64 - OG_PRE2 ? i + OG_PRE2 : pre_kb(i - (64 - OG_PRE2 - OG_PRE)); }
constexpr int OG_POS = 8;
constexpr uint32_t OG_STAGE = 32768;
constexpr uint32_t OG_SCOL = AT_SBAR + 512;
constexpr uint32_t OG_SMISC = AT_SBAR + 2048;
constexpr int OG_XPOS = OG_POS + OG_NKB;
constexpr uint32_t OG_SWD = AT_SQ, OG_PSLOT = AT_SQ;
constexpr uint32_t OG_SWD1 = (OG_XPOS % OG_ST) * OG_STAGE;
constexpr uint32_t OG_XSLOT = AT_SQ + 32768;
constexpr uint32_t OG_OSLOT = ((OG_XPOS + 1) % OG_ST) * OG_STAGE;
constexpr uint32_t OG_SH2 = ((OG_XPOS + 2) % OG_ST) * OG_STAGE;
constexpr uint32_t OG_SRED = ((OG_XPOS + 3) % OG_ST) * OG_STAGE;
constexpr uint32_t OG_SSTAT = OG_SRED + 16384;
constexpr uint32_t OG_SGU = OG_SRED + 8192;
constexpr uint32_t OG_SFIN = OG_SGU + 256;
#define OGM 2
#define OG_MT(b) ((((b) >> OGM) & 15) ^ (SERP && ((b) & 64) ? 15 : 0))
#define OG_NT(b) (((b) & ((1 << OGM) - 1)) + (((b) >> (4 + OGM)) << OGM))
#define TAIL_SETUP \
  const uint32_t bar_full = sbase + AT_SBAR, bar_empty = bar_full + 40; \
  const uint32_t bar_wd = bar_full + 168, bar_col = bar_full + 176, bar_out = bar_full + 184, bar_end = bar_full + 192; \
  const uint32_t bar_key = bar_full + 200, bar_h2 = bar_full + 208, bar_sel = bar_full + 216; \
  const int mt = OG_MT(blockIdx.x), nt = OG_NT(blockIdx.x); \
  const int m0 = mt * 128, n0 = nt * 128; \
  const bool has_moe = (int)blockIdx.x < OG_MOE; \
  (void)bar_empty; (void)bar_wd; (void)bar_col; (void)bar_out; (void)bar_end; (void)bar_key; (void)bar_h2; (void)bar_sel; (void)m0; (void)n0; (void)has_moe;

__device__ __forceinline__ void tail_producer(uint32_t sbase, uint32_t ph, uint64_t pol, const CUtensorMap* tmA, const CUtensorMap* tmB, const CUtensorMap* tmX) {
  TAIL_SETUP
  uint32_t stage = OG_POS % OG_ST;
  int kb = 0;
  #pragma unroll 1
  for (int seg = 0; seg < 2; seg++) {
    mbar_wait(bar_full + 264 + 80 * seg, 0);
    fence_proxy_async_global();
    const int end = seg == 0 ? 32 - OG_PRE2 : has_moe ? OG_NKB : 64 - OG_PRE2;
    #pragma unroll 1
    for (; kb < end; kb++) {
      const uint32_t fb = bar_full + 8 * stage, sa = sbase + stage * OG_STAGE;
      const int k0 = own_kb(kb) * 64;
      mbar_wait(bar_empty + 8 * stage, ph);
      mbar_expect_tx(fb, OG_STAGE);
      tma_load_3d_hint(sa + 16384, tmB, k0, 2 * nt, fb, pol);
      tma_load_2d_hint(sa, tmA, k0, m0, fb, pol);
      if (++stage == OG_ST) { stage = 0; ph ^= 1; }
    }
  }
  if (has_moe) {
    mbar_wait(bar_empty + 8 * (OG_XPOS % OG_ST), ph);
    mbar_expect_tx(bar_wd, OG_STAGE);
    tma_load_3d_hint(sbase + OG_SWD1, tmX, blockIdx.x * 32, 8, bar_wd, pol);
  }
}

__device__ __forceinline__ uint32_t out2(uint32_t x1, uint32_t mb2, uint32_t ih, uint32_t il, uint32_t c1, uint32_t sb, uint32_t gb) {
  const uint32_t h2 = badd2(bmul2(ln_norm2b(x1, mb2, ih, il), c1), sb);
  return badd2(x1, bmul2(gb, bfma2(h2, 0u, h2)));
}
#define OGTIME gtime()
#define PRE_N 1
#define PRE_PACE 150
#define X_PACE 200
#define WD_LATE 0
#define WD_PACE 300
__device__ __forceinline__ void tail_exchange(uint32_t sbase, const CUtensorMap* tmOut, const bf16* __restrict__ w_down, const bf16* __restrict__ w_r, const bf16* __restrict__ x, bf16* __restrict__ out) {
    TAIL_SETUP
    const int lane = threadIdx.x & 31, wi = __shfl_sync(0xffffffffu, threadIdx.x >> 5, 0);
    if (wi == 3) {
      if (blockIdx.x < AT_NFULL) {
        uint32_t a, b;
        asm volatile("ld.relaxed.gpu.global.u32 %0, [%1];" : "=r"(a) : "l"(g_smid + 32 + blockIdx.x - lane) : "memory");
        b = __shfl_down_sync(0xffffffffu, a, 1);
        unsigned int* tm = g_tmax + blockIdx.x - min((int)blockIdx.x, __ffs(__ballot_sync(0xffffffffu, b >= a)) - 1);
        mbar_wait(bar_full + 312, 0);
        if (lane == 0) {
          asm volatile("mov.u32 %0, %%globaltimer_lo;" : "=r"(a));
          asm volatile("red.relaxed.gpu.global.max.u32 [%0], %1;" :: "l"(tm), "r"(a) : "memory");
          __nanosleep(AL_SLEEP);
          asm volatile("ld.relaxed.gpu.global.u32 %0, [%1];" : "=r"(b) : "l"(tm) : "memory");
          b -= a;
          sts_u32(sbase + OG_SMISC + 32, (b < AL_MAX ? b * 13 / 8 : 0u) + AL_ADD);
          mbar_arrive(bar_full + 320);
        }
        named_bar_sync(15, 32);
      }
      mbar_wait(bar_full + 344, 0);
      float a = g_scal[lane], b = g_scal[32 + lane];
      #pragma unroll
      for (int i = 0; i < 3; i++) {
        const uint4 v = *reinterpret_cast<const uint4*>(g_col + nt * 1536 + i * 512 + lane * 16);
        sts_u32x4(sbase + OG_SCOL + i * 512 + lane * 16, v.x, v.y, v.z, v.w);
      }
      #pragma unroll
      for (int o = 16; o > 0; o >>= 1) { a += __shfl_xor_sync(0xffffffffu, a, o); b += __shfl_xor_sync(0xffffffffu, b, o); }
      if (lane == 0) sts_f32x2(sbase + OG_SMISC, a, b);
      const uint64_t pol = policy_evict_first();
      #pragma unroll 1
      for (int r = lane >> 4; r < 128; r += 4) {
        __nanosleep(X_PACE);
        #pragma unroll
        for (int j = 0; j < 4; j += 2)
          asm volatile("cp.async.cg.shared.global.L2::cache_hint [%0], [%1], 16, %2;" :: "r"(sbase + OG_XSLOT + (lane & 8) * 2048 + (r + j) * 128 + (((lane ^ (r + j)) & 7) << 4)),
                       "l"(x + (size_t)(m0 + r + j) * T_D + n0 + (lane & 15) * 8), "l"(pol) : "memory");
      }
      asm volatile("cp.async.wait_all;" ::: "memory");
      __syncwarp();
      if (lane == 0) mbar_arrive(bar_col);
    } else if (wi == 2) {
      if (elect_one()) {
        const uint32_t b_free = bar_full + (blockIdx.x < AT_NFULL ? 80 : 160);
        mbar_wait(b_free, 0); mbar_wait(b_free, 1);
        #pragma unroll 1
        for (unsigned int i = 0; i < (1u << 20) && ld_acquire(&g_hcnt[32 * (1 + (blockIdx.x >> 3)) + 4 + ((blockIdx.x >> 1) & 3)]) == 0u; i++) __nanosleep(POLL_NS);
        TL_MARK2(23, true);
        fence_proxy_async_global();
        TL_MARK2(4, true);
        mbar_expect_tx(bar_full + 272, 32768);
        #pragma unroll 1
        for (int i = 0; i < PRE_N; i++) {
          bulk_load_hint(sbase + OG_PSLOT + i * (32768 / PRE_N), g_pre + blockIdx.x * 2048 + i * (2048 / PRE_N), 32768 / PRE_N,
                         bar_full + 272, policy_evict_first());
          if (PRE_N > 1) __nanosleep(PRE_PACE);
        }
      }
      named_bar_sync(14, 32);
      if (has_moe) {
        mbar_wait(bar_full + 96, 1); mbar_wait(bar_full + 304, 0);
        const uint64_t pol = policy_evict_first();
        #pragma unroll 1
        for (int r = 0; r < 32; r++) {
          __nanosleep(WD_PACE);
          #pragma unroll
          for (int j = 0; j < 2; j++)
            asm volatile("cp.async.cg.shared.global.L2::cache_hint [%0], [%1], 16, %2;" :: "r"(sbase + OG_SWD + (4 * j + (lane >> 3)) * 4096 + r * 128 + (((lane ^ r) & 7) << 4)),
                         "l"((const uint8_t*)w_down + (size_t)blockIdx.x * 65536 + r * 2048 + j * 512 + lane * 16), "l"(pol) : "memory");
        }
        asm volatile("cp.async.wait_all;" ::: "memory");
        __syncwarp();
        if (lane == 0) mbar_arrive(bar_wd);
      }
    }
    const uint4 wrv = ldg_nc_v4(w_r + threadIdx.x * 8);
    mbar_wait(bar_end, 0);
    TL_MARK2(22, lane == 0);
    if (wi == 0) {
      uint32_t k1 = 0u, k2 = 0u;
      #pragma unroll 1
      for (unsigned int spin = 0; spin < (1u << 22) && __any_sync(0xffffffffu, k1 == 0u); spin++) asm volatile("ld.relaxed.gpu.global.u32 %0, [%1];" : "=r"(k1) : "l"(g_key + lane) : "memory");
      TL_MARK2(28, lane == 0);
      warp_top2(k1, k2);
      if (lane == 0) {
        const uint32_t r1 = 0xffffu - (k1 & 0xffffu), r2 = 0xffffu - (k2 & 0xffffu);
        sts_u32x4(sbase + OG_SMISC + 64, r1, r2, (r1 >> 7) * 2, (r2 >> 7) * 2 + ((r1 >> 7) == (r2 >> 7)));
        mbar_arrive(bar_sel);
      }
    } else if (wi < 3) {
          mbar_wait(bar_key, 0);
          const uint4 kk = lds_u32x4(sbase + OG_SSTAT + 1024 + lane * 16);
          uint32_t k1 = max(kk.x, kk.y), k2 = min(kk.x, kk.y);
          k2 = max(max(k2, min(kk.z, kk.w)), min(k1, max(kk.z, kk.w))); k1 = max(k1, max(kk.z, kk.w));
          warp_top2(k1, k2);
          if (wi == 1) {
            if (lane == 0 && nt == (mt & 7)) st_relaxed2(g_key + mt * 2, k1, k2);
            TL_MARK2(27, lane == 0);
          } else {
            const uint32_t r = (~((lane & 16) ? k2 : k1)) & 127u, ch = lane & 15;
            const uint2 st = lds_u32x2(sbase + OG_SSTAT + r * 8);
            const uint4 xc = lds_u32x4(sbase + OG_XSLOT + (ch >> 3) * 16384 + r * 128 + (((ch ^ r) & 7) << 4));
            const uint4 c1 = lds_u32x4(sbase + OG_SCOL + 768 + ch * 16), sh = lds_u32x4(sbase + OG_SCOL + 1024 + ch * 16);
            const float inr = __uint_as_float(st.y);
            float* dst = reinterpret_cast<float*>(g_cand + (mt * 2 + (lane >> 4)) * 256 + nt * 16 + ch);
            st_tagged4(dst + 512, __uint_as_float(ln_mod2(xc.x, st.x, inr, c1.x, sh.x)), __uint_as_float(ln_mod2(xc.y, st.x, inr, c1.y, sh.y)),
                       __uint_as_float(ln_mod2(xc.z, st.x, inr, c1.z, sh.z)), __uint_as_float(ln_mod2(xc.w, st.x, inr, c1.w, sh.w)));
            st_tagged4(dst, __uint_as_float(xc.x), __uint_as_float(xc.y), __uint_as_float(xc.z), __uint_as_float(xc.w));
          }
    }
    mbar_wait(bar_sel, 0);
    const uint4 sel = lds_u32x4(sbase + OG_SMISC + 64);
    const int sel0 = (int)sel.x, sel1 = (int)sel.y;
    {
      const float* src0 = reinterpret_cast<const float*>(g_cand + sel.z * 256 + 128 + threadIdx.x);
      const float* src1 = reinterpret_cast<const float*>(g_cand + sel.w * 256 + 128 + threadIdx.x);
      float4 h0, h1;
      #pragma unroll 1
      for (unsigned int spin = 0; spin < (1u << 20); spin++) { h0 = ld_tagged4(src0); h1 = ld_tagged4(src1); if (__all_sync(0xffffffffu, tagged4(h0) & tagged4(h1))) break; }
      sts_f32x4(sbase + OG_SH2 + threadIdx.x * 16, h0.x, h0.y, h0.z, h0.w);
      sts_f32x4(sbase + OG_SH2 + 2048 + threadIdx.x * 16, h1.x, h1.y, h1.z, h1.w);
      __syncwarp();
      if (lane == 0) mbar_arrive(bar_h2);
      TL_MARK2(12, lane == 0);
      if (blockIdx.x >> 6) h0 = h1;
      float v[8], wr[8];
      unpack8(make_uint4(__float_as_uint(h0.x), __float_as_uint(h0.y), __float_as_uint(h0.z), __float_as_uint(h0.w)), v); unpack8(wrv, wr);
      float r = 0.f;
      #pragma unroll
      for (int i = 0; i < 8; i++) r = fmaf(v[i], wr[i], r);
      #pragma unroll
      for (int o = 16; o > 0; o >>= 1) r += __shfl_xor_sync(0xffffffffu, r, o);
      if (lane == 0) sts_f32(sbase + OG_SMISC + 192 + wi * 4, r);
    }
    mbar_wait(bar_out, 0);
    if ((sel0 >> 7) == mt || (sel1 >> 7) == mt) {
      #pragma unroll 2
      for (int i = 0; i < 16; i++) {
        const int r = i * 8 + (threadIdx.x >> 4), ch = threadIdx.x & 15;
        if (m0 + r != sel0 && m0 + r != sel1)
          *reinterpret_cast<uint4*>(out + (size_t)(m0 + r) * T_D + n0 + ch * 8) =
              lds_u32x4(sbase + OG_OSLOT + (ch >> 3) * 16384 + r * 128 + (((ch & 7) ^ (r & 7)) << 4));
      }
    } else if (threadIdx.x == 0) {
      tma_store_2d(tmOut, sbase + OG_OSLOT, n0, m0);
      tma_store_2d(tmOut, sbase + OG_OSLOT + 16384, n0 + 64, m0);
      bulk_commit();
    }
    if (blockIdx.x == 0 && threadIdx.x < 68) *reinterpret_cast<uint4*>(g_hcnt + 32 * (threadIdx.x >> 2) + 4 * (threadIdx.x & 3)) = make_uint4(0u, 0u, 0u, 0u);
    if (threadIdx.x < 64) g_modpart[blockIdx.x * 64 + threadIdx.x] = 0.f;
    if (ALIGN && threadIdx.x == 64) g_tmax[blockIdx.x] = 0u;
    {
      const int tk = blockIdx.x >> 6, c0 = (blockIdx.x & 63) * 16;
      const uint32_t gb2 = *reinterpret_cast<const uint32_t*>(g_col + (c0 >> 7) * 1536 + 512 + 768 + ((c0 & 127) + (threadIdx.x & 14)) * 2);
      const uint32_t* xp = reinterpret_cast<const uint32_t*>(g_cand + (tk ? sel.w : sel.z) * 256) + ((c0 + (threadIdx.x & 14)) >> 1);
      uint32_t x2 = 0u;
      #pragma unroll 1
      for (unsigned int spin = 0; spin < (1u << 20) && __any_sync(0xffffffffu, x2 == 0u); spin++) asm volatile("ld.relaxed.gpu.global.u32 %0, [%1];" : "=r"(x2) : "l"(xp) : "memory");
      const float* src = g_ypart + (size_t)((threadIdx.x >> 2) * 2 + tk) * T_D + c0 + (threadIdx.x & 3) * 4;
      const bool four = threadIdx.x < (OG_MOE - 96) * 4;
      if (threadIdx.x == 0) hint_wait(CNT_Y, (uint32_t)OG_MOE);
      named_bar_sync(10, 128);
      float4 p0, p1, p2, p3;
      #pragma unroll 1
      for (unsigned int spin = 0; spin < (1u << 20); spin++) {
        p0 = ld_tagged4(src); p1 = ld_tagged4(src + 64 * T_D); p2 = ld_tagged4(src + 128 * T_D); p3 = ld_tagged4(four ? src + 192 * T_D : src);
        if (__all_sync(0xffffffffu, tagged4(p0) & tagged4(p1) & tagged4(p2) & tagged4(p3))) break;
      }
      if (four) { p2.x += p3.x; p2.y += p3.y; p2.z += p3.z; p2.w += p3.w; }
      p0.x = (p0.x + p1.x) + p2.x; p0.y = (p0.y + p1.y) + p2.y; p0.z = (p0.z + p1.z) + p2.z; p0.w = (p0.w + p1.w) + p2.w;
      #pragma unroll
      for (int o = 4; o <= 16; o <<= 1) {
        p0.x += __shfl_xor_sync(0xffffffffu, p0.x, o); p0.y += __shfl_xor_sync(0xffffffffu, p0.y, o);
        p0.z += __shfl_xor_sync(0xffffffffu, p0.z, o); p0.w += __shfl_xor_sync(0xffffffffu, p0.w, o);
      }
      if (lane < 4) sts_f32x4(sbase + OG_SFIN + (threadIdx.x >> 5) * 64 + lane * 16, p0.x, p0.y, p0.z, p0.w);
      named_bar_sync(10, 128);
      TL_MARK2(21, threadIdx.x == 0);
      if (threadIdx.x < 16) {
        const uint32_t ya = sbase + OG_SFIN + threadIdx.x * 4, rp = sbase + OG_SMISC + 192;
        float y = (lds_f32(ya) + lds_f32(ya + 64)) + (lds_f32(ya + 128) + lds_f32(ya + 192));
        const float r = rbf((lds_f32(rp) + lds_f32(rp + 4)) + (lds_f32(rp + 8) + lds_f32(rp + 12)));
        const float rs = rbf(sigmoid_f(r));
        const uint32_t h2p = lds_u32(sbase + OG_SH2 + tk * 2048 + (c0 + (threadIdx.x & 14)) * 2);
        const float fh = (lane & 1) ? bfhi(h2p) : bflo(h2p);
        y = rbf(y);
        y = rbf(y * rs);
        const float upd = rbf(rbf(fh * 0.0f) + y);
        out[(size_t)(tk ? sel1 : sel0) * T_D + c0 + threadIdx.x] =
            __float2bfloat16_rn(((lane & 1) ? bfhi(x2) : bflo(x2)) + rbf(((lane & 1) ? bfhi(gb2) : bflo(gb2)) * rbf(fh + upd)));
      }
      if (threadIdx.x == 0) bulk_wait_read<0>();
    }
    TL_END(4, threadIdx.x == 0);
}

__device__ __forceinline__ void load_pre(uint4* pre, uint32_t sbase, uint32_t buf, int t2) {
  mbar_wait(sbase + AT_SBAR + 272, 0);
  #pragma unroll
  for (int i = 0; i < 8; i++) pre[i] = lds_u32x4(sbase + buf + i * 4096 + t2 * 16);
}
__device__ __forceinline__ void tail_consumer(uint32_t sbase, const uint4 (&pre)[8], int cwg, const bf16* __restrict__ w_gate, const bf16* __restrict__ w_up) {
    TAIL_SETUP
    const int tid = threadIdx.x & 127, t2 = threadIdx.x - 128;
    const int warp = tid >> 5, lane = tid & 31, w8 = t2 >> 5;
    const uint32_t dbase = (sbase & 0x3FFFFu) >> 4;
    const uint32_t a_base = dbase + ((cwg * 8192) >> 4) + (1u << 16);
    const uint32_t b_base = dbase + (16384 >> 4) + (512u << 16);
    TL_MARK2(25, threadIdx.x == 128);
    const uint64_t pol = policy_evict_first();
    const bf16* pw = ((lane & 16) ? w_up : w_gate) + (size_t)(w8 * 128 + (lane & 3) * 4) * T_F + (has_moe ? blockIdx.x : 0) * 32 + ((lane >> 2) & 3) * 8;
    uint4 wv[32];
    float acc[64];
    #pragma unroll
    for (int i = 0; i < 8; i++) {
      acc[8 * i] = bflo(pre[i].x); acc[8 * i + 1] = bfhi(pre[i].x); acc[8 * i + 2] = bflo(pre[i].y); acc[8 * i + 3] = bfhi(pre[i].y);
      acc[8 * i + 4] = bflo(pre[i].z); acc[8 * i + 5] = bfhi(pre[i].z); acc[8 * i + 6] = bflo(pre[i].w); acc[8 * i + 7] = bfhi(pre[i].w);
    }
    if (lane == 0) mbar_arrive(bar_full + 304);
    if (blockIdx.x < AT_NFULL) {
      const uint32_t c0 = clock_lo();
      mbar_wait(bar_full + 320, 0);
      const uint32_t d = lds_u32(sbase + OG_SMISC + 32);
      while (clock_lo() - c0 < d) {}
    }
    {
      uint32_t stage = OG_POS % OG_ST, phase = (OG_POS / OG_ST) & 1, prev = 12;
      int kb = 0;
      #pragma unroll
      for (int g = 0; g <= OG_NG; g++) {
        const int end = g == OG_NG ? (has_moe ? OG_NKB : 64 - OG_PRE2) : LD_FIRST + g * OG_GRP + LD_STAG * cwg;
        #pragma unroll 1
        do {
          mbar_wait(bar_full + 8 * stage, phase);
          const uint32_t a_lo = a_base + stage * (OG_STAGE >> 4), b_lo = b_base + stage * (OG_STAGE >> 4);
          wgmma_fence();
          wgmma_m64n128k16_ss_tb<0, 0>(acc, a_lo, b_lo, 1);
          wgmma_m64n128k16_ss_tb<2, 128>(acc, a_lo, b_lo, 1);
          wgmma_m64n128k16_ss_tb<4, 256>(acc, a_lo, b_lo, 1);
          wgmma_m64n128k16_ss_tb<6, 384>(acc, a_lo, b_lo, 1);
          wgmma_commit();
          wgmma_wait<1>();
          if (tid == 0) mbar_arrive(bar_empty + 8 * prev);
          prev = stage;
          if (++stage == OG_ST) { stage = 0; phase ^= 1; }
        } while (++kb < end);
        #pragma unroll
        for (int j = 4 * g; j < 4 * g + 4 && j < 32; j++) wv[j] = ldg_stream_v4(pw + (size_t)(16 * (j >> 2) + (j & 3)) * T_F, pol);
      }
    }
    mbar_wait(bar_col, 0);
    if (__builtin_expect(!has_moe, 0)) {
      load_pre(wv, sbase, AT_SQ, t2);
    }
    wgmma_wait<0>();
    fence_regs(acc);
    if (__builtin_expect(!has_moe, 0)) {
      #pragma unroll
      for (int i = 0; i < 8; i++) {
        acc[8 * i] += bflo(wv[i].x); acc[8 * i + 1] += bfhi(wv[i].x); acc[8 * i + 2] += bflo(wv[i].y); acc[8 * i + 3] += bfhi(wv[i].y);
        acc[8 * i + 4] += bflo(wv[i].z); acc[8 * i + 5] += bfhi(wv[i].z); acc[8 * i + 6] += bflo(wv[i].w); acc[8 * i + 7] += bfhi(wv[i].w);
      }
    }
    if (tid == 0) mbar_arrive(bar_end);
    TL_MARK2(9, lane == 0);
    const int q2 = 2 * (lane & 3);
    const uint32_t frag = (64 * cwg + 16 * warp + (lane & 7) + 8 * ((lane >> 3) & 1)) * 128;
    const int fsw = lane & 7, fhi = lane >> 4;
    {
      float dl[4] = {0.f, 0.f, 0.f, 0.f}, da[4] = {0.f, 0.f, 0.f, 0.f}, db[4] = {0.f, 0.f, 0.f, 0.f};
      const uint32_t tb = sbase + OG_SCOL + (lane & 8) * 32 + (lane & 3) * 8, g = lane >> 2;
      const uint32_t msk = (g == 1 || g == 2) ? 0xffffffffu : 0u, one = g == 0 ? 0x3F803F80u : 0u;
      #pragma unroll
      for (int J = 0; J < 16; J += 2) {
        const uint32_t ad = sbase + OG_XSLOT + (J >> 3) * 16384 + frag + ((((J & 7) + fhi) ^ fsw) << 4);
        uint32_t xr[4];
        ldmatrix_x4(ad, xr[0], xr[1], xr[2], xr[3]);
        const uint2 cw = lds_u32x2(tb + J * 16);
        #pragma unroll
        for (int h = 0; h < 2; h++) {
          const uint32_t ga = lds_u32(sbase + OG_SCOL + 512 + (8 * (J + h) + q2) * 2);
          xr[2 * h] = badd2(xr[2 * h], bmul2(ga, pack_bf16(acc[4 * (J + h)], acc[4 * (J + h) + 1])));
          xr[2 * h + 1] = badd2(xr[2 * h + 1], bmul2(ga, pack_bf16(acc[4 * (J + h) + 2], acc[4 * (J + h) + 3])));
        }
        stmatrix_x4(ad, xr[0], xr[1], xr[2], xr[3]);
        mma_bf16(dl, xr[0], xr[1], xr[2], xr[3], (cw.x & msk) | one, (cw.y & msk) | one);
        mma_bf16(da, xr[0], xr[1], xr[2], xr[3], xr[0], xr[2]);
        mma_bf16(db, xr[0], xr[1], xr[2], xr[3], xr[1], xr[3]);
      }
      {
        const int dsrc = (lane & ~3) + (g >> 1);
        const float qa = __shfl_sync(0xffffffffu, (g & 1) ? da[1] : da[0], dsrc), qb = __shfl_sync(0xffffffffu, (g & 1) ? db[3] : db[2], dsrc);
        const float e0 = __shfl_xor_sync(0xffffffffu, (lane & 1) ? dl[0] : dl[2], 1), e1 = __shfl_xor_sync(0xffffffffu, dl[3], 1);
        if ((lane & 3) < 2) {
          const bool hi = lane & 1;
          st_tagged4(reinterpret_cast<float*>(g_part1 + ((mt * 8 + w8) * 8 + nt) * 16 + g + (hi ? 8 : 0)),
                     hi ? e0 : dl[0], hi ? qb : qa, hi ? e1 + dl[2] : dl[1] + e0, 1.0f);
        }
      }
    }
    TL_MARK2(10, lane == 0);
    uint4 wd[16];
    if (has_moe) mbar_wait(bar_wd, 0);
    #pragma unroll
    for (int i = 0; i < 16; i++) wd[i] = lds_u32x4(sbase + (cwg ? OG_SWD1 : OG_SWD) + warp * 8192 + (i >> 3) * 4096 + (i & 6) * 512 + (i & 1) * 128 + (lane & 3) * 256 + (((lane >> 2) ^ (2 * (lane & 3) + (i & 1))) << 4));
    {
      const float* src = reinterpret_cast<const float*>(g_part1 + ((mt * 8 + w8) * 8 + (lane & 1) * 4) * 16 + (lane >> 1));
      float4 v, v1, v2, v3;
      #pragma unroll 1
      for (unsigned int spin = 0; spin < (1u << 22); spin++) {
        v = ld_tagged4(src); v1 = ld_tagged4(src + 64); v2 = ld_tagged4(src + 128); v3 = ld_tagged4(src + 192);
        if (__all_sync(0xffffffffu, tagged4(v) & tagged4(v1) & tagged4(v2) & tagged4(v3))) break;
        __nanosleep(100);
      }
      __syncwarp();
      TL_MARK2(26, lane == 0);
      v.x = (v.x + v1.x) + (v2.x + v3.x); v.y = (v.y + v1.y) + (v2.y + v3.y); v.z = (v.z + v1.z) + (v2.z + v3.z);
      v.x += __shfl_xor_sync(0xffffffffu, v.x, 1); v.y += __shfl_xor_sync(0xffffffffu, v.y, 1); v.z += __shfl_xor_sync(0xffffffffu, v.z, 1);
      const float mean = v.x * (1.0f / T_D);
      const float var = fmaxf(fmaf(-mean, mean, v.y * (1.0f / T_D)), 0.f);
      const uint32_t mb2 = pack_bf16(mean, mean);
      const float inv = rcp_approx(rbf(sqrt_approx(rbf(rbf(var) + 1e-05f))));
      {
        const float2 sc = lds_f32x2(sbase + OG_SMISC);
        const uint32_t key = rank_key(rbf(fmaf(fmaf(-bflo(mb2), sc.x, v.z), inv, sc.y)), m0 + 16 * w8 + (lane >> 1));
        mbar_wait(bar_end, 0);
        if (lane & 1) sts_u32(sbase + OG_SSTAT + 1024 + (16 * w8 + (lane >> 1)) * 4, key);
        else sts_u32x2(sbase + OG_SSTAT + (16 * w8 + (lane >> 1)) * 8, mb2, __float_as_uint(inv));
        __syncwarp();
        if (lane == 0) mbar_arrive(bar_key);
      }
      const uint32_t ih = pack_bf16(inv, inv), il = pack_bf16(inv - bflo(ih), inv - bflo(ih));
      const uint32_t mba = __shfl_sync(0xffffffffu, mb2, 2 * (lane >> 2)), mbb = __shfl_sync(0xffffffffu, mb2, 2 * (lane >> 2) + 16);
      const uint32_t iha = __shfl_sync(0xffffffffu, ih, 2 * (lane >> 2)), ihb = __shfl_sync(0xffffffffu, ih, 2 * (lane >> 2) + 16);
      const uint32_t ila = __shfl_sync(0xffffffffu, il, 2 * (lane >> 2)), ilb = __shfl_sync(0xffffffffu, il, 2 * (lane >> 2) + 16);
      #pragma unroll 2
      for (int J = 0; J < 16; J += 2) {
        const uint32_t off = (J >> 3) * 16384 + frag + ((((J & 7) + fhi) ^ fsw) << 4);
        uint32_t xr[4];
        ldmatrix_x4(sbase + OG_XSLOT + off, xr[0], xr[1], xr[2], xr[3]);
        #pragma unroll
        for (int h = 0; h < 2; h++) {
          const uint32_t ca = sbase + OG_SCOL + 512 + (8 * (J + h) + q2) * 2;
          const uint32_t c1 = lds_u32(ca + 256), sh = lds_u32(ca + 512), gb = lds_u32(ca + 768);
          xr[2 * h] = out2(xr[2 * h], mba, iha, ila, c1, sh, gb);
          xr[2 * h + 1] = out2(xr[2 * h + 1], mbb, ihb, ilb, c1, sh, gb);
        }
        stmatrix_x4(sbase + OG_OSLOT + off, xr[0], xr[1], xr[2], xr[3]);
      }
      fence_proxy_async();
      __syncwarp();
      if (lane == 0) mbar_arrive(bar_out);
      TL_MARK2(24, lane == 0);
    }
    if (has_moe) mbar_wait(bar_h2, 0);
    TL_MARK2(13, lane == 0);
    if (has_moe) {
      const GemvSel sel = gemv_sel(lane);
      {
        float d[4][4];
        #pragma unroll
        for (int c = 0; c < 4; c++) { d[c][0] = 0.f; d[c][1] = 0.f; d[c][2] = 0.f; d[c][3] = 0.f; }
        #pragma unroll
        for (int st = 0; st < 8; st++) {
          const uint2 hb = lds_u32x2(sbase + OG_SH2 + ((lane >> 2) & 1) * 2048 + (w8 * 128 + st * 16 + (lane & 3) * 4) * 2);
          #pragma unroll
          for (int j = 0; j < 4; j++) mma_bf16(d[j], wv[4 * st + j].x, wv[4 * st + j].y, wv[4 * st + j].z, wv[4 * st + j].w, GEMV_B0(j, hb, sel), GEMV_B1(j, hb, sel));
        }
        #pragma unroll
        for (int e = 0; e < 4; e++) d[0][e] = (d[0][e] + d[1][e]) + (d[2][e] + d[3][e]);
        const float4 r = gemv_out(d[0], lane);
        sts_f32x4(sbase + OG_SRED + w8 * 512 + (((lane >> 4) * 2 + (lane & 1)) * 32 + ((lane >> 2) & 3) * 8 + (lane & 2) * 2) * 4, r.x, r.y, r.z, r.w);
      }
      named_bar_sync(9, 256);
      if (t2 < 64) {
        float gp[8], up[8];
        #pragma unroll
        for (int w = 0; w < 8; w++) { gp[w] = lds_f32(sbase + OG_SRED + w * 512 + t2 * 4); up[w] = lds_f32(sbase + OG_SRED + w * 512 + 256 + t2 * 4); }
        const float gs = ((gp[0] + gp[1]) + (gp[2] + gp[3])) + ((gp[4] + gp[5]) + (gp[6] + gp[7]));
        const float us = ((up[0] + up[1]) + (up[2] + up[3])) + ((up[4] + up[5]) + (up[6] + up[7]));
        asm volatile("st.shared.u16 [%0], %1;" :: "r"(sbase + OG_SGU + ((t2 & ~15) + ((t2 >> 1) & 3) * 4 + ((t2 >> 3) & 1) * 2 + (t2 & 1)) * 2), "h"((uint16_t)pack_bf16(silu_bf(rbf(gs)) * rbf(us), 0.f)) : "memory");
      }
      named_bar_sync(9, 256);
      TL_MARK2(20, threadIdx.x == 128);
      float d[4][4];
      #pragma unroll
      for (int c = 0; c < 4; c++) { d[c][0] = 0.f; d[c][1] = 0.f; d[c][2] = 0.f; d[c][3] = 0.f; }
      #pragma unroll
      for (int st = 0; st < 2; st++) {
        const uint2 g = lds_u32x2(sbase + OG_SGU + ((lane >> 2) & 1) * 64 + st * 32 + (lane & 3) * 8);
        #pragma unroll
        for (int j = 0; j < 4; j++) {
          const uint32_t b0 = GEMV_B0(j, g, sel), b1 = GEMV_B1(j, g, sel);
          mma_bf16(d[j & 1], wd[4 * st + j].x, wd[4 * st + j].y, wd[4 * st + j].z, wd[4 * st + j].w, b0, b1);
          mma_bf16(d[2 + (j & 1)], wd[8 + 4 * st + j].x, wd[8 + 4 * st + j].y, wd[8 + 4 * st + j].z, wd[8 + 4 * st + j].w, b0, b1);
        }
      }
      #pragma unroll
      for (int e = 0; e < 4; e++) { d[0][e] += d[1][e]; d[2][e] += d[3][e]; }
      const float4 y0 = gemv_out(d[0], lane), y1 = gemv_out(d[2], lane);
      float* yp = g_ypart + (size_t)(blockIdx.x * 2 + (lane & 1)) * T_D + w8 * 128 + (lane >> 2) * 8 + (lane & 2) * 2;
      st_tagged4(yp, y0.x, y0.y, y0.z, y0.w);
      st_tagged4(yp + 64, y1.x, y1.y, y1.z, y1.w);
      named_bar_sync(9, 256);
      if (t2 == 0) hint_arrive(CNT_Y);
    }
    TL_MARK2(14, threadIdx.x == 128);
    TL_CLK(4, 1, threadIdx.x == 128);
}

#define OG_JOBS2 (16 - OG_JOBS)
__device__ __forceinline__ int help_njobs() { return blockIdx.x < 128 ? OG_JOBS : OG_JOBS2; }
__device__ __forceinline__ int help_job(int i) { return (i < OG_JOBS ? 16 * i + (blockIdx.x >> 7) * 2 : 112 + (i - OG_JOBS) * 2) + (blockIdx.x & 3) * 4; }
__device__ __noinline__ void store_warp(uint32_t sbase, const CUtensorMap* tmO, int item0, int n_items) {
  if (elect_one()) {
    const uint32_t bars = sbase + AT_SBAR, b_q0 = bars + 80, b_ob = bars + 96, b_ordy = bars + 104, b_acq = bars + 264;
    const unsigned int* cnt = &g_hcnt[32 * (1 + OG_MT(blockIdx.x)) + 2];
    #pragma unroll 1
    for (int q = 0; q < 4 * n_items; q++) {
      const int item = item0 + (q >> 2) * 128, h = (q >> 1) & 1, w = q & 1;
      const bool last = (q >> 2) == n_items - 1;
      if (q == 4 * n_items - 4) { mbar_wait(bars + 288, 0); red_release_add(&g_hcnt[1], 1u); }
      mbar_wait(b_ordy + 8 * (q & 3), q >> 2);
      store_o(tmO, (h ? (last ? sbase + AT_SQ + 32768 : sbase + 2 * 32768) : sbase + AT_SQ) + w * 8192, (item >> 4) * 2 + h, (item & 15) * 128 + w * 64);
      if (w) {
        bulk_wait_read<0>();
        mbar_arrive(h ? b_ob : b_q0);
        bulk_wait<0>();
        fence_proxy_async_global();
        asm volatile("fence.acq_rel.gpu;" ::: "memory");
        hint_arrive(&g_hcnt[32 * (1 + (item & 15)) + 2 + (item >> 7)]);
        if (!h && item < 128) hint_arrive(&g_hcnt[2]);
        if (q == 5) { spin_until(cnt, 16u); mbar_arrive(b_acq); }
      }
    }
    if (n_items == 1) {
      #pragma unroll 1
      for (int i = 0; i < help_njobs(); i++) {
        mbar_wait(b_acq + 16, i & 1);
        TL_MARK2(23, i == OG_JOBS - 1);
        red_release_add(&g_hcnt[32 * (1 + (help_job(i) >> 3)) + 4 + ((help_job(i) >> 1) & 3)], 1u);
        TL_MARK2(4, i == OG_JOBS - 1);
        if (i == PRE_X - 1) { spin_until(&g_hcnt[1], 132u); mbar_arrive(b_acq + 32); }
      }
    }
    if (blockIdx.x < 128) {
      if (n_items == 1) { spin_until(cnt, 16u); mbar_arrive(b_acq); }
      spin_until(&g_hcnt[0], 128u); spin_until(cnt + 1, 16u); mbar_arrive(b_acq + 80);
    }
  }
}

__global__ void __launch_bounds__(384, 1)
fused_kernel(const __grid_constant__ CUtensorMap tmH, const __grid_constant__ CUtensorMap tmW, const __grid_constant__ CUtensorMap tmK,
            const __grid_constant__ CUtensorMap tmV, const __grid_constant__ CUtensorMap tmO, const __grid_constant__ CUtensorMap tmOl, const __grid_constant__ CUtensorMap tmWo,
            const __grid_constant__ CUtensorMap tmX, const __grid_constant__ CUtensorMap tmOut, const __grid_constant__ CUtensorMap tmM, uint32_t zero,
            const uint8_t* __restrict__ pf_wo, const bf16* __restrict__ kc, const bf16* __restrict__ vc,
            const bf16* __restrict__ x, const bf16* __restrict__ cvec, const bf16* __restrict__ w_mod, const bf16* __restrict__ w_r,
            const bf16* __restrict__ w_gate, const bf16* __restrict__ w_up, const bf16* __restrict__ w_down, bf16* __restrict__ out)
{
  extern __shared__ __align__(1024) uint8_t smem_raw[];
  const uint32_t sbase = smem_u32(smem_raw);
  const uint32_t bars = sbase + AT_SBAR;
  const uint32_t b_full = bars, b_empty = bars + 40;
  const uint32_t b_q0 = bars + 80, b_q1 = bars + 88;
  const uint32_t b_ob = bars + 96;
  const uint32_t b_ordy = bars + 104;
  const uint32_t b_pin = bars + 136;
  const uint32_t b_head = bars + 144;
  const uint32_t b_go = bars + 152;
  const uint32_t b_x = bars + 160;
  const int wg = __shfl_sync(0xffffffffu, threadIdx.x >> 7, 0);
  const bool single = blockIdx.x >= AT_NFULL;
  const int item0 = __shfl_sync(0xffffffffu, blockIdx.x < 128 ? (int)blockIdx.x : (int)blockIdx.x + 124, 0), n_items = __shfl_sync(0xffffffffu, single ? 1 : 2, 0);
  TL_START(3);
  if (threadIdx.x == 0) {
    if (sbase & 1023u) __trap();
    for (int i = 0; i < 5; i++) { mbar_init(b_full + 8 * i, 1); mbar_init(b_empty + 8 * i, 2); }
    mbar_init(b_q0, 1); mbar_init(b_q1, 8); mbar_init(b_ob, 1);
    for (int i = 0; i < 4; i++) mbar_init(b_ordy + 8 * i, 4);
    mbar_init(b_pin, 1); mbar_init(b_head, blockIdx.x < 128 ? 8 : 1); mbar_init(b_go, 1); mbar_init(b_x, 1);
    mbar_init(bars + 168, 2); mbar_init(bars + 176, 1); mbar_init(bars + 184, 8); mbar_init(bars + 192, 2);
    mbar_init(bars + 200, 8); mbar_init(bars + 208, 4); mbar_init(bars + 216, 1); mbar_init(bars + 264, 1); mbar_init(bars + 272, 1); mbar_init(bars + 280, 8); mbar_init(bars + 288, 1); mbar_init(bars + 296, 1); mbar_init(bars + 304, 8); mbar_init(bars + 312, 1); mbar_init(bars + 320, 1); mbar_init(bars + 328, 1); mbar_init(bars + 344, 1);
    fence_mbar_init();
  }

  if (wg == 0) {
    reg_dealloc<AT_PREG>();
    if (threadIdx.x < 32) { __syncwarp(); named_bar_arrive(6, 384); }
    if (threadIdx.x >= 64) {
      named_bar_sync(6, 384);
      if (blockIdx.x < 128) {
        named_bar_sync(threadIdx.x >= 96 ? 8 : 9, 288);
        if ((threadIdx.x & 31) == 0) red_release_add(&g_hcnt[32 * (1 + (blockIdx.x >> 3)) + (threadIdx.x >= 96)], 1u);
        TL_MARK2(11, threadIdx.x == 64);
      }
      if (blockIdx.x < 128) {
        mbar_wait(MOD_AT, 0);
        mod_rest(sbase + OG_SCOL, b_q1, threadIdx.x - 64, cvec, w_mod, w_r);
      }
    } else if (threadIdx.x >= 32) {
      named_bar_sync(6, 384);
      store_warp(sbase, &tmO, item0, n_items);
      __syncwarp();
    } else {
     if (elect_one()) {
      const uint64_t pol = policy_evict_first();
      if (blockIdx.x < 128) {
        mbar_expect_tx(b_x, 32768);
        if (X_DLY) { const uint32_t c0 = clock_lo(); while (clock_lo() - c0 < X_DLY) {} }
        bulk_load_hint(sbase + 4 * 32768, x + (size_t)blockIdx.x * 16 * T_D, 32768, b_x, pol);
      }
      prefetch_tmap(&tmW); prefetch_tmap(&tmM); prefetch_tmap(&tmH); prefetch_tmap(&tmWo); prefetch_tmap(&tmOl);
      {
        const uint32_t c0 = clock_lo();
        while (clock_lo() - c0 < W_DLY) {}
        if (blockIdx.x < 128 && (blockIdx.x & 15) >= 4 * H_SPLIT) {
          mbar_expect_tx(bars + 328, 32768);
          tma_load_2d_hint(sbase + 3 * 32768, &tmM, (blockIdx.x & 31) * 64, (blockIdx.x >> 5) * 256, bars + 328, pol);
        }
        while (clock_lo() - c0 < W_DLY + W_FIRST) {}
      }
      uint32_t slot = 0, ph = 1;
      if (ALIGN) { uint32_t sm; asm volatile("mov.u32 %0, %%smid;" : "=r"(sm)); g_smid[32 + blockIdx.x] = sm; }
      #pragma unroll 1
      for (int it = 0; it < n_items; it++) {
        const int item = item0 + it * 128, hp = item >> 4, qt = item & 15;
        const bool first = it == 0;
        #pragma unroll 1
        for (int j = 0; j < T_D / 64; j++) {
          const uint32_t sl = ring_slot(qp_pos(j, it)), fb = b_full + 8 * sl;
          mbar_wait(b_empty + 8 * sl, ring_par(qp_pos(j, it)) ^ ((j >> 2) & 1) ^ 1);
          if (first && j == 3) mbar_wait(b_head, 0);
          mbar_expect_tx(fb, 49152);
          tma_load_3d_hint(sbase + sl * 32768, &tmW, j * 64, hp * 4, fb, pol);
          if (first && j < PRE_B) {
            if (j == PRE_B - 1) {
              spin_until(&g_hcnt[32 * (1 + qt)], 8u);
              TL_MARK2(16, true);
              fence_proxy_async_global();
              #pragma unroll 1
              for (int i = 0; i < PRE_B; i++) tma_load_2d(sbase + AT_SQ + i * 16384, &tmH, i * 64, qt * 128, b_full + 8 * i);
              mbar_arrive(b_go);
            }
          } else {
            if (first && j == 4 * H_SPLIT) { spin_until(&g_hcnt[32 * (1 + qt) + 1], 8u); fence_proxy_async_global(); }
            if (!first && (j == 0 || j == 2)) mbar_wait(j ? b_q1 : b_q0, 0);
            tma_load_2d_hint(sbase + AT_SQ + (j & 3) * 16384, &tmH, j * 64, qt * 128, fb, first ? pol_normal() : pol);
          }
        }
        #pragma unroll 1
        for (int j = 0; j < 4 * AT_NBLK; j++) {
          const bool isv = (j > 0 && !(j & 1)) || j == 4 * AT_NBLK - 1;
          const int row = hp * 2 * T_SEQ + (isv ? (j - 1) >> 1 : (j + 1) >> 1) * 128;
          const uint32_t fb = b_full + 8 * slot;
          mbar_wait(b_empty + 8 * slot, ph);
          if (!first && j == 3) mbar_wait(b_ob, 0);
          if (j == 4 && it == n_items - 1) mbar_arrive(bars + 288);
          if (ALIGN && j == AL_P && it == 1) mbar_arrive(bars + 312);
          mbar_expect_tx(fb, 32768);
          tma_load_3d_hint(sbase + slot * 32768, isv ? &tmV : &tmK, row, 0, fb, pol);
          if (it == 1 && isv && j >= 2 * WO_LATE && j < 2 * WO_LATE + 32 && blockIdx.x < OG_NKB)
            l2_prefetch_bulk(pf_wo + (size_t)own_kb(blockIdx.x) * 131072 + ((j >> 1) - WO_LATE) * 8192, 8192);
          if (++slot == 5) { slot = 0; ph ^= 1; }
        }
      }
      if (__builtin_expect(single, 0)) {
        spin_until(&g_hcnt[2], 128u);
        fence_proxy_async_global();
        const int nj = OG_JOBS * OG_PRE + (help_njobs() - OG_JOBS) * OG_PRE2;
        int ji = 0, job = help_job(0), kk = 0;
        #pragma unroll 1
        for (int j = 0; j < nj; j++) {
          const uint32_t sl = ring_slot(qp_pos(j, 1)), fb = b_full + 8 * sl;
          mbar_wait(b_empty + 8 * sl, ring_par(qp_pos(j, 1)) ^ ((j >> 2) & 1) ^ 1);
          mbar_expect_tx(fb, 49152);
          tma_load_3d_hint(sbase + sl * 32768, &tmWo, pre_kb(kk) * 64, OG_NT(job) * 2, fb, HPOL_B);
          tma_load_3d_hint(sbase + sl * 32768 + 16384, &tmWo, pre_kb(kk) * 64, OG_NT(job) * 2 + 2, fb, HPOL_B);
          if (j == 0 || j == 2) mbar_wait(j ? b_ob : b_q0, 0);
          tma_load_2d_hint(sbase + AT_SQ + (j & 3) * 16384, &tmOl, pre_kb(kk) * 64, OG_MT(job) * 128, fb, HPOL_A);
          if (++kk == (ji < OG_JOBS ? OG_PRE : OG_PRE2)) { kk = 0; job = help_job(++ji); }
        }
      }
      if (blockIdx.x < 128) {
        if (single) mbar_wait(b_x, 1);
        tail_producer(sbase, 0, pol, &tmOl, &tmWo, &tmX);
      }
     }
    }
    named_bar_sync(12 + (threadIdx.x >> 5), 32);
    if (blockIdx.x < 128) tail_exchange(sbase, &tmOut, w_down, w_r, x, out);
  } else {
    if (blockIdx.x < 128) head_phase(sbase + AT_SQ + 49152, sbase + 4 * 32768, b_x, b_go, b_head, threadIdx.x - 128, zero, cvec, w_mod);
    else { named_bar_sync(6, 384); if (threadIdx.x == 128) mbar_arrive(b_head); }
    TL_MARK2(0, threadIdx.x == 128);
    reg_alloc<AT_CREG>();
    const int cwg = wg - 1;
    const int tid = threadIdx.x & 127;
    const int warp = tid >> 5, lane = tid & 31;
    const uint32_t dbase = (sbase & 0x3FFFFu) >> 4;
    const uint32_t k_base = dbase + (1u << 16);
    const uint32_t v_base = dbase + (1024u << 16);
    const uint32_t w_base = dbase + (512u << 16);
    const uint32_t q_lo = dbase + ((AT_SQ + cwg * 8192) >> 4) + (1u << 16);
    const uint32_t frag = cwg * 8192 + (16 * warp + (lane & 7) + 8 * ((lane >> 3) & 1)) * 128;
    if (cwg == 1) named_bar_arrive(1, 256);
    bool raw = false;
    uint4 pre[8];
    #pragma unroll 1
    for (int it = 0; it < n_items; it++) {
      const bool more = it + 1 < n_items;
      constexpr int nkb = T_D / 64;
      const int ta = __shfl_sync(0xffffffffu, 4 * it, 0);
      float acc[128];
      {
        FS(2 * it, 0);
        #pragma unroll
        for (int i = 0; i < 128; i++) asm volatile("" : "=f"(acc[i]));
        {
          const uint32_t slot = ring_slot(ta), b_lo = w_base + slot * 2048;
          mbar_wait(b_full + 8 * slot, ring_par(ta));
          wgmma_fence();
          wgmma_m64n256k16_ss_tb<0, 0>(acc, q_lo, b_lo, 0);
          wgmma_m64n256k16_ss_tb<2, 128>(acc, q_lo, b_lo, 1);
          wgmma_m64n256k16_ss_tb<4, 256>(acc, q_lo, b_lo, 1);
          wgmma_m64n256k16_ss_tb<6, 384>(acc, q_lo, b_lo, 1);
          wgmma_commit();
        }
        #pragma unroll 1
        for (int j = NOZERO; j < nkb; j++) {
          const uint32_t slot = ring_slot(qp_pos(j, ta >> 2));
          mbar_wait(b_full + 8 * slot, ring_par(qp_pos(j, ta >> 2)) ^ ((j >> 2) & 1));
          if (QP_STAG > 0 && cwg == 1 && j == nkb - QP_STAG) named_bar_sync(7, 256);
          const uint32_t a_lo = q_lo + (j & 3) * 1024, b_lo = w_base + slot * 2048;
          wgmma_fence();
          wgmma_m64n256k16_ss_tb<0, 0>(acc, a_lo, b_lo, 1);
          wgmma_m64n256k16_ss_tb<2, 128>(acc, a_lo, b_lo, 1);
          wgmma_m64n256k16_ss_tb<4, 256>(acc, a_lo, b_lo, 1);
          wgmma_m64n256k16_ss_tb<6, 384>(acc, a_lo, b_lo, 1);
          wgmma_commit();
          if (QP_STAG > 0 && cwg == 0 && j == nkb - 1) named_bar_arrive(7, 256);
          if (j > 0) {
            wgmma_wait<1>();
            if (tid == 0) mbar_arrive(b_empty + 8 * ring_slot(qp_pos(j - 1, ta >> 2)));
          }
        }
        wgmma_wait<0>();
        fence_regs(acc);
        FS(2 * it, 1);
        TL_MARK2(29, threadIdx.x == 256 && it == 0);
        if (tid == 0) mbar_arrive(b_empty + 24);
      }
      float o[64], s[64];
      uint32_t p[32], q[32];
      #pragma unroll
      for (int i = 0; i < 32; i++) q[i] = pack_bf16(acc[2 * i] * AT_C, acc[2 * i + 1] * AT_C);
      zero_regs(s);
      const uint32_t sq = sbase + AT_SQ + cwg * 8192;
      const bool last_wg1 = cwg == 1 && !more;
      float mc0, mc1, al0 = 1.0f, al1 = 1.0f, l0 = 0.f, l1 = 0.f, lp0 = 0.f, lp1 = 0.f;
      bool redo0 = false;
      FS(2 * it, 2);
      mbar_wait(b_full + 8 * ring_slot(ta), ring_par(ta));
      named_bar_sync(1 + cwg, 256);
      FS(2 * it, 3);
      issue_qk(s, q, k_base + ring_slot(ta) * 2048);
      named_bar_arrive(1 + (cwg ^ 1), 256);
      bool ready = mbar_test(b_full + 8 * ring_slot(ta + 1), ring_par(ta + 1)) & mbar_test(b_full + 8 * ring_slot(ta + 2), ring_par(ta + 2));
      stage_q<16>(acc, AT_C, sbase + AT_SQ + frag, lane);
      wgmma_wait<0>();
      fence_regs(s);
      if (tid == 0) mbar_arrive(b_empty + 8 * ring_slot(ta));
      mc0 = 0.f; mc1 = 0.f;
      if (!raw) {
        raw = softmax_mode(s, mc0, mc1);
        if (__builtin_expect(!raw, 0)) softmax_sub(s, mc0, mc1);
      }
      softmax_exp<0, 64>(s);
      #pragma unroll
      for (int J = 0; J < 16; J += 2)
        stmatrix_x4(sbase + AT_SQ + frag + (J >> 3) * 16384 + ((((J & 7) + (lane >> 4)) ^ (lane & 7)) << 4), q[2 * J], q[2 * J + 1], q[2 * J + 2], q[2 * J + 3]);
      pack_p(p, s);
      zero_regs(o);
      FS(2 * it, 4);
      uint32_t ks = ring_slot(ta + 1), vs = ring_slot(ta + 2), kp = ring_par(ta + 1), vp = ring_par(ta + 2);
      auto finish_head = [&]() {
        FS(2 * it, 5);
        redo0 = finish_l(lp0, lp1);
        if (!redo0) {
          stage_o(o, lp0, lp1, sbase + AT_SQ + frag, lane);
          fence_proxy_async();
          __syncwarp();
          if (lane == 0) mbar_arrive(b_ordy + 8 * cwg);
        }
        FS(2 * it + 1, 4);
      };
      if (!ready) { mbar_wait(b_full + 8 * ks, kp); mbar_wait(b_full + 8 * vs, vp); }
      #pragma unroll 1
      for (int n = 1; n < 2 * AT_NBLK; n++) {
        named_bar_sync(1 + cwg, 256);
        issue_qk(s, q, k_base + ks * 2048);
        if (n == AT_NBLK + 1) finish_head();
        issue_pv(o, p, v_base + vs * 2048, (n & 15) != 1);
        if (!(last_wg1 && n == 2 * AT_NBLK - 1)) named_bar_arrive(1 + (cwg ^ 1), 256);
        wgmma_wait<1>();
        fence_regs(s);
        if (tid == 0) mbar_arrive(b_empty + 8 * ks);
        if (__builtin_expect(!raw || (n + 1) >> 1 == AT_NBLK / 2, 0)) {
          if (n == AT_NBLK - 1) {
            #pragma unroll
            for (int J = 0; J < 16; J += 2)
              ldmatrix_x4(sbase + AT_SQ + 32768 + frag + (J >> 3) * 16384 + ((((J & 7) + (lane >> 4)) ^ (lane & 7)) << 4), q[2 * J], q[2 * J + 1], q[2 * J + 2], q[2 * J + 3]);
          }
          if (!raw) {
            const float m0 = mc0, m1 = mc1;
            const bool ok = softmax_mode(s, mc0, mc1);
            if (n == AT_NBLK) raw = ok;
            else {
              mc0 = mc0 - AT_HEAD > m0 ? mc0 : m0; mc1 = mc1 - AT_HEAD > m1 ? mc1 : m1;
              al0 = ex2_approx(m0 - mc0); al1 = ex2_approx(m1 - mc1);
            }
            if (!raw) softmax_sub(s, mc0, mc1);
          }
        }
        softmax_exp<0, AT_SPLIT>(s);
        add_rowsum(p, l0, l1);
        if (tid == 0) {
          uint32_t dep = zero & __float_as_uint(l0) & __float_as_uint(l1);
          #pragma unroll
          for (int i = AT_SPLIT - AT_PIN - PINB; i < AT_SPLIT - PINB; i += 2) dep &= __float_as_uint(s[i]) & __float_as_uint(s[i + 1]);
          mbar_arrive(b_pin + dep);
        }
        wgmma_wait<0>();
        fence_regs(o);
        if (tid == 0) mbar_arrive(b_empty + 8 * vs);
        ks += 2; if (ks >= 5) { ks -= 5; kp ^= 1; }
        vs += 2; if (vs >= 5) { vs -= 5; vp ^= 1; }
        ready = mbar_test(b_full + 8 * ks, kp) & mbar_test(b_full + 8 * vs, vp);
        softmax_exp<AT_SPLIT, 64>(s);
        pack_p(p, s);
        if (n == AT_NBLK) { lp0 = l0; lp1 = l1; l0 = 0.f; l1 = 0.f; }
        if (__builtin_expect(!raw || !ready, 0)) {
        if (!raw && __any_sync(0xffffffffu, al0 != 1.0f || al1 != 1.0f)) {
          rescale_o(o, al0, al1);
          l0 *= al0; l1 *= al1;
          al0 = 1.0f; al1 = 1.0f;
        }
        if (!ready && n < 2 * AT_NBLK - 1) {
          mbar_wait(b_full + 8 * ks, kp);
          mbar_wait(b_full + 8 * vs, vp);
        }
        }
      }
      FS(2 * it + 1, 5);
      const uint32_t vl = ring_slot(ta + 63);
      vs = ring_slot(ta + 62);
      const uint32_t ob = more ? sbase + vs * 32768 : sbase + AT_SQ + 32768;
      mbar_wait(b_full + 8 * vl, ring_par(ta + 63));
      issue_pv(o, p, v_base + vl * 2048, 1);
      add_rowsum(p, l0, l1);
      const bool overflow = finish_l(l0, l1);
      if (!overflow && lane == 0) mbar_arrive(b_q1);
      #pragma unroll
      for (int i = 0; i < 8; i++) asm volatile("mov.b64 {%0, %1}, 0;\nmov.b64 {%2, %3}, 0;" : "=r"(pre[i].x), "=r"(pre[i].y), "=r"(pre[i].z), "=r"(pre[i].w));
      if (!redo0 && !more && blockIdx.x < OG_MOE) load_pre(pre, sbase, AT_SQ, threadIdx.x - 128);
      mbar_wait(b_empty + 8 * vs, ring_par(ta + 62));
      wgmma_wait<0>();
      fence_regs(o);
      if (tid == 0) mbar_arrive(b_empty + 8 * vl);
      FS(2 * it + 1, 6);
      if (overflow) {
        attn_rows_exact(sq + 32768, ob + cwg * 8192, 4 * ta + 1, kc, vc);
        __syncwarp();
        if (lane == 0) mbar_arrive(b_q1);
      } else stage_o(o, l0, l1, ob + frag, lane);
      if (redo0) attn_rows_exact(sq, sq, 4 * ta, kc, vc);
      fence_proxy_async();
      __syncwarp();
      if (lane == 0) {
        if (redo0) mbar_arrive(b_ordy + 8 * cwg);
        mbar_arrive(b_ordy + 16 + 8 * cwg);
      }
      if (redo0 && !more && blockIdx.x < OG_MOE) load_pre(pre, sbase, AT_SQ, threadIdx.x - 128);
      if (redo0 || overflow) raw = false;
      named_bar_sync(3 + cwg, 128);
      FS(2 * it + 1, 7);
    }
    if (__builtin_expect(single, 0)) {
      float acc[128];
      uint32_t j = 0, pk[64];
      #pragma unroll
      for (int i = 0; i < 64; i++) asm volatile("" : "=f"(acc[2 * i]), "=f"(acc[2 * i + 1]), "=r"(pk[i]));
      uint4* dst = g_pre;
      int left = 0;
      auto put = [&](bool last) {
        #pragma unroll
        for (int i = 0; i < PUT_N; i++) dst[i * 256] = make_uint4(pk[4 * i], pk[4 * i + 1], pk[4 * i + 2], pk[4 * i + 3]);
        dst += PUT_N * 256;
        #pragma unroll
        for (int i = 0; i < 64 - 4 * PUT_N; i++) asm volatile("mov.b32 %0, %1;" : "=r"(pk[i]) : "r"(pk[i + 4 * PUT_N]));
        __syncwarp();
        if (last && lane == 0) mbar_arrive(bars + 280);
      };
      #pragma unroll 1
      for (int ji = 0; ji < help_njobs(); ji++) {
        const int nk = ji < OG_JOBS ? OG_PRE : OG_PRE2;
        #pragma unroll 1
        for (int kk = 0; kk < nk; kk++, j++) {
          const uint32_t slot = ring_slot(qp_pos(j, 1));
          mbar_wait(b_full + 8 * slot, ring_par(qp_pos(j, 1)) ^ ((j >> 2) & 1));
          if (H_STAG > 0 && cwg == 1 && kk == nk - H_STAG) named_bar_sync(7, 256);
          const uint32_t a_lo = q_lo + (j & 3) * 1024, b_lo = w_base + slot * 2048;
          wgmma_fence();
          wgmma_m64n256k16_ss_tb<0, 0>(acc, a_lo, b_lo, kk != 0);
          wgmma_m64n256k16_ss_tb<2, 128>(acc, a_lo, b_lo, 1);
          wgmma_m64n256k16_ss_tb<4, 256>(acc, a_lo, b_lo, 1);
          wgmma_m64n256k16_ss_tb<6, 384>(acc, a_lo, b_lo, 1);
          wgmma_commit();
          if (H_STAG > 0 && cwg == 0 && kk == nk - 1) named_bar_arrive(7, 256);
          wgmma_wait<1>();
          if (kk > 0 && tid == 0) mbar_arrive(b_empty + 8 * ring_slot(qp_pos(j - 1, 1)));
          #pragma unroll 1
          for (int i = ji == OG_JOBS ? 0 : 16 / PUT_N - 1; i < 16 / PUT_N && left > 0; i++) put(--left == 0);
        }
        wgmma_wait<0>();
        fence_regs(acc);
        if (tid == 0) mbar_arrive(b_empty + 8 * ring_slot(qp_pos(j - 1, 1)));
        #pragma unroll
        for (int i = 0; i < 64; i++) pk[i] = pack_bf16(acc[2 * i], acc[2 * i + 1]);
        left = 16 / PUT_N;
        if (ji == PRE_X) mbar_wait(bars + 296, 0);
        dst = g_pre + help_job(ji) * 2048 + threadIdx.x - 128;
      }
      #pragma unroll
      for (int i = 0; i < 16; i++) dst[i * 256] = make_uint4(pk[4 * i], pk[4 * i + 1], pk[4 * i + 2], pk[4 * i + 3]);
      __syncwarp();
      if (lane == 0) mbar_arrive(bars + 280);
      named_bar_sync(5, 256);
      if (threadIdx.x == 128) {
        #pragma unroll 1
        for (int i = 0; i < 5; i++) {
          constexpr int n = OG_JOBS * OG_PRE;
          const int used = i == 3 ? 0 : (n + 3 - (i == 4 ? 3 : i)) / 4;
          if ((used ^ (i < 4)) & 1) {
            mbar_arrive(b_full + 8 * ring_slot(4 + i));
            mbar_arrive(b_empty + 8 * ring_slot(4 + i)); mbar_arrive(b_empty + 8 * ring_slot(4 + i));
          }
        }
        mbar_arrive(b_x);
      }
      named_bar_sync(5, 256);
      #pragma unroll
      for (int i = 0; i < 8; i++) pre[i] = make_uint4(0u, 0u, 0u, 0u);
    }
    TL_CLK(3, 1, threadIdx.x == 128);
    TL_CTA(1, threadIdx.x == 256);
    TL_END(3, tid == 0);
    TL_MARK2(19, tid == 0 && !single);
    if (blockIdx.x < 128) {
      tail_consumer(sbase, pre, cwg, w_gate, w_up);
    }
  }
}

typedef CUresult (*PFN_encodeTiled)(CUtensorMap*, CUtensorMapDataType, cuuint32_t, void*, const cuuint64_t*, const cuuint64_t*,
                                    const cuuint32_t*, const cuuint32_t*, CUtensorMapInterleave, CUtensorMapSwizzle,
                                    CUtensorMapL2promotion, CUtensorMapFloatOOBfill);

CUtensorMap make_map_2d(PFN_encodeTiled enc, const void* ptr, uint64_t inner, uint64_t outer, uint64_t stride_bytes, uint32_t box_inner, uint32_t box_outer) {
  CUtensorMap m;
  cuuint64_t gd[2] = {inner, outer}; cuuint64_t gs[1] = {stride_bytes};
  cuuint32_t bx[2] = {box_inner, box_outer}; cuuint32_t es[2] = {1, 1};
  enc(&m, CU_TENSOR_MAP_DATA_TYPE_BFLOAT16, 2, const_cast<void*>(ptr), gd, gs, bx, es, CU_TENSOR_MAP_INTERLEAVE_NONE,
      CU_TENSOR_MAP_SWIZZLE_128B, CU_TENSOR_MAP_L2_PROMOTION_L2_128B, CU_TENSOR_MAP_FLOAT_OOB_FILL_NONE);
  return m;
}

CUtensorMap make_map_3d(PFN_encodeTiled enc, const void* ptr, uint64_t cols, uint64_t rows, uint32_t box_rows, uint32_t chunks) {
  CUtensorMap m;
  cuuint64_t gd[3] = {64, rows, cols / 64}; cuuint64_t gs[2] = {cols * 2, 128};
  cuuint32_t bx[3] = {64, box_rows, chunks}; cuuint32_t es[3] = {1, 1, 1};
  enc(&m, CU_TENSOR_MAP_DATA_TYPE_BFLOAT16, 3, const_cast<void*>(ptr), gd, gs, bx, es, CU_TENSOR_MAP_INTERLEAVE_NONE,
      CU_TENSOR_MAP_SWIZZLE_128B, CU_TENSOR_MAP_L2_PROMOTION_L2_128B, CU_TENSOR_MAP_FLOAT_OOB_FILL_NONE);
  return m;
}

}

extern "C" void kernel_launch(void* const* d_in, const int* in_sizes, int n_in, void* d_out, int out_size) {
  const bf16* x      = (const bf16*)d_in[0];
  const bf16* kc     = (const bf16*)d_in[1];
  const bf16* vc     = (const bf16*)d_in[2];
  const bf16* wq     = (const bf16*)d_in[3];
  const bf16* wo     = (const bf16*)d_in[4];
  const bf16* w_r    = (const bf16*)d_in[6];
  const bf16* w_gate = (const bf16*)d_in[7];
  const bf16* w_up   = (const bf16*)d_in[8];
  const bf16* w_down = (const bf16*)d_in[9];
  const bf16* cvec   = (const bf16*)d_in[10];
  const bf16* w_mod  = (const bf16*)d_in[11];
  bf16* out = (bf16*)d_out;

  static PFN_encodeTiled enc = nullptr;
  static void *p_h = nullptr, *p_o = nullptr;
  if (!enc) {
    void* fn = nullptr; cudaDriverEntryPointQueryResult qres;
    cudaGetDriverEntryPoint("cuTensorMapEncodeTiled", &fn, cudaEnableDefault, &qres);
    enc = (PFN_encodeTiled)fn;
    cudaGetSymbolAddress(&p_h, g_pre);
    p_h = (uint4*)p_h + 16 * PRE_X * 2048;
    cudaGetSymbolAddress(&p_o, g_o);
    cudaFuncSetAttribute(fused_kernel, cudaFuncAttributeMaxDynamicSharedMemorySize, (int)AT_SMEM);
  }
  const CUtensorMap tm_h   = make_map_2d(enc, p_h, T_D, T_SEQ, T_D * 2, 64, 128);
  const CUtensorMap tm_wq  = W3D ? make_map_3d(enc, wq, T_DQKV, T_D, 64, 4) : make_map_2d(enc, wq, T_DQKV, T_D, T_DQKV * 2, 64, 64);
  const CUtensorMap tm_k   = KV3D ? make_map_3d(enc, kc, T_DH, (uint64_t)T_NH * T_SEQ, 128, 2) : make_map_2d(enc, kc, T_DH, (uint64_t)T_NH * T_SEQ, T_DH * 2, 64, 128);
  const CUtensorMap tm_v   = KV3D ? make_map_3d(enc, vc, T_DH, (uint64_t)T_NH * T_SEQ, 128, 2) : make_map_2d(enc, vc, T_DH, (uint64_t)T_NH * T_SEQ, T_DH * 2, 64, 128);
  const CUtensorMap tm_ost = make_map_2d(enc, p_o, T_DQKV, T_SEQ, T_DQKV * 2, 64, 64);
  const CUtensorMap tm_old = make_map_2d(enc, p_o, T_DQKV, T_SEQ, T_DQKV * 2, 64, 128);
  const CUtensorMap tm_wo  = make_map_3d(enc, wo, T_D, T_DQKV, 64, 2);
  const CUtensorMap tm_x   = make_map_3d(enc, w_down, T_D, T_F, 32, 8);

  const CUtensorMap tm_m   = make_map_2d(enc, w_mod, 6 * T_D, T_D, 6 * T_D * 2, 64, 256);
  const CUtensorMap tm_out = make_map_2d(enc, out, T_D, T_SEQ, T_D * 2, 64, 128);

  fused_kernel<<<132, 384, AT_SMEM, cudaStreamPerThread>>>(tm_h, tm_wq, tm_k, tm_v, tm_ost, tm_old, tm_wo, tm_x, tm_out, tm_m, 0u, (const uint8_t*)wo, kc, vc, x, cvec, w_mod,
             w_r, w_gate, w_up, w_down, out);
}
```

```cpp
#include <cuda_runtime.h>
#include <cuda_bf16.h>
#include <cuda.h>
#include <stdint.h>

namespace {

typedef __nv_bfloat16 bf16;

constexpr int T_SEQ = 2048, T_D = 1024, T_NH = 32, T_DH = 128, T_DQKV = 4096, T_F = 3584;

#define PRE_X 2
__device__ __align__(1024) uint4 g_pre[(16 * PRE_X + 128) * 2048];
#define g_h (reinterpret_cast<bf16*>(g_pre + 16 * PRE_X * 2048))
__device__ __align__(1024) bf16 g_o[T_SEQ * T_DQKV];
__device__ __align__(16) uint8_t g_col[8 * 1536];
__device__ __align__(16) float g_scal[64];
__device__ __align__(16) unsigned int g_hcnt[17 * 32];
__device__ unsigned int g_smid[168], g_tmax[128];
__device__ __align__(128) float g_modpart[4 * 2 * T_D];
struct __align__(2048) TailMail {
  float4 part1[T_SEQ * 8];
  uint32_t key[256];
  uint4 cand[16 * 2 * 2 * 128];
  uint32_t cnt[32];
  float ypart[(T_F / 32) * 2 * T_D];
};
__device__ TailMail g_mail;
#define g_part1 g_mail.part1
#define g_key g_mail.key
#define g_cand g_mail.cand
#define CNT_Y (g_mail.cnt)
#define g_ypart g_mail.ypart

__device__ __forceinline__ uint32_t smem_u32(const void* p) { return (uint32_t)__cvta_generic_to_shared(p); }
__device__ __forceinline__ void mbar_init(uint32_t bar, uint32_t cnt) { asm volatile("mbarrier.init.shared::cta.b64 [%0], %1;" :: "r"(bar), "r"(cnt)); }
__device__ __forceinline__ void mbar_expect_tx(uint32_t bar, uint32_t bytes) { asm volatile("mbarrier.arrive.expect_tx.shared::cta.b64 _, [%0], %1;" :: "r"(bar), "r"(bytes) : "memory"); }
__device__ __forceinline__ void mbar_arrive(uint32_t bar) { asm volatile("mbarrier.arrive.shared::cta.b64 _, [%0];" :: "r"(bar) : "memory"); }
__device__ __forceinline__ void mbar_wait(uint32_t bar, uint32_t parity) {
  asm volatile("{\n.reg .pred p;\nLAB_WAIT:\nmbarrier.try_wait.parity.shared::cta.b64 p, [%0], %1;\n@!p bra LAB_WAIT;\n}\n" :: "r"(bar), "r"(parity) : "memory");
}
__device__ __forceinline__ bool mbar_test(uint32_t bar, uint32_t parity) {
  uint32_t r; asm volatile("{\n.reg .pred p;\nmbarrier.test_wait.parity.shared::cta.b64 p, [%1], %2;\nselp.u32 %0, 1, 0, p;\n}\n" : "=r"(r) : "r"(bar), "r"(parity) : "memory");
  return r != 0;
}
__device__ __forceinline__ uint32_t clock_lo() { uint32_t c; asm volatile("mov.u32 %0, %%clock;" : "=r"(c)); return c; }
__device__ __forceinline__ void fence_mbar_init() { asm volatile("fence.mbarrier_init.release.cluster;" ::: "memory"); }
__device__ __forceinline__ void tma_load_2d(uint32_t dst, const CUtensorMap* map, int c0, int c1, uint32_t bar) {
  asm volatile("cp.async.bulk.tensor.2d.shared::cluster.global.mbarrier::complete_tx::bytes [%0], [%1, {%3, %4}], [%2];"
    :: "r"(dst), "l"(map), "r"(bar), "r"(c0), "r"(c1) : "memory");
}
__device__ __forceinline__ uint64_t policy_evict_first() {
  uint64_t p; asm volatile("createpolicy.fractional.L2::evict_first.b64 %0, 1.0;" : "=l"(p)); return p;
}
__device__ __forceinline__ void tma_load_2d_hint(uint32_t dst, const CUtensorMap* map, int c0, int c1, uint32_t bar, uint64_t pol) {
  asm volatile("cp.async.bulk.tensor.2d.shared::cluster.global.mbarrier::complete_tx::bytes.L2::cache_hint [%0], [%1, {%3, %4}], [%2], %5;"
    :: "r"(dst), "l"(map), "r"(bar), "r"(c0), "r"(c1), "l"(pol) : "memory");
}
__device__ __forceinline__ void tma_load_3d_hint(uint32_t dst, const CUtensorMap* map, int c1, int c2, uint32_t bar, uint64_t pol) {
  asm volatile("cp.async.bulk.tensor.3d.shared::cluster.global.mbarrier::complete_tx::bytes.L2::cache_hint [%0], [%1, {%3, %4, %5}], [%2], %6;"
    :: "r"(dst), "l"(map), "r"(bar), "n"(0), "r"(c1), "r"(c2), "l"(pol) : "memory");
}
__device__ __forceinline__ void tma_store_2d(const CUtensorMap* map, uint32_t src, int c0, int c1) {
  asm volatile("cp.async.bulk.tensor.2d.global.shared::cta.bulk_group [%0, {%2, %3}], [%1];" :: "l"(map), "r"(src), "r"(c0), "r"(c1) : "memory");
}
__device__ __forceinline__ void prefetch_tmap(const CUtensorMap* map) { asm volatile("prefetch.tensormap [%0];" :: "l"(map) : "memory"); }
__device__ __forceinline__ void l2_prefetch_bulk(const void* p, uint32_t bytes) {
  asm volatile("cp.async.bulk.prefetch.L2.global [%0], %1;" :: "l"(p), "r"(bytes) : "memory");
}
__device__ __forceinline__ void bulk_commit() { asm volatile("cp.async.bulk.commit_group;" ::: "memory"); }
template<int N> __device__ __forceinline__ void bulk_wait_read() { asm volatile("cp.async.bulk.wait_group.read %0;" :: "n"(N) : "memory"); }
template<int N> __device__ __forceinline__ void bulk_wait() { asm volatile("cp.async.bulk.wait_group %0;" :: "n"(N) : "memory"); }
__device__ __forceinline__ void named_bar_sync(int id, int nthreads) { asm volatile("bar.sync %0, %1;" :: "r"(id), "r"(nthreads) : "memory"); }
__device__ __forceinline__ void named_bar_arrive(int id, int nthreads) { asm volatile("bar.arrive %0, %1;" :: "r"(id), "r"(nthreads) : "memory"); }
__device__ __forceinline__ void wgmma_fence() { asm volatile("wgmma.fence.sync.aligned;" ::: "memory"); }
__device__ __forceinline__ void wgmma_commit() { asm volatile("wgmma.commit_group.sync.aligned;" ::: "memory"); }
template<int N> __device__ __forceinline__ void wgmma_wait() { asm volatile("wgmma.wait_group.sync.aligned %0;" :: "n"(N) : "memory"); }
template<int R> __device__ __forceinline__ void reg_alloc() { asm volatile("setmaxnreg.inc.sync.aligned.u32 %0;" :: "n"(R)); }
template<int R> __device__ __forceinline__ void reg_dealloc() { asm volatile("setmaxnreg.dec.sync.aligned.u32 %0;" :: "n"(R)); }
__device__ __forceinline__ bool elect_one() {
  uint32_t pred; asm volatile("{\n.reg .pred p;\nelect.sync _|p, 0xffffffff;\nselp.u32 %0, 1, 0, p;\n}\n" : "=r"(pred)); return pred != 0;
}
__device__ __forceinline__ uint32_t pack_bf16(float lo, float hi) {
  uint32_t r; asm("cvt.rn.bf16x2.f32 %0, %1, %2;" : "=r"(r) : "f"(hi), "f"(lo)); return r;
}
__device__ __forceinline__ void stmatrix_x4(uint32_t addr, uint32_t r0, uint32_t r1, uint32_t r2, uint32_t r3) {
  asm volatile("stmatrix.sync.aligned.m8n8.x4.shared.b16 [%0], {%1, %2, %3, %4};" :: "r"(addr), "r"(r0), "r"(r1), "r"(r2), "r"(r3) : "memory");
}
__device__ __forceinline__ void fence_proxy_async() { asm volatile("fence.proxy.async.shared::cta;" ::: "memory"); }
__device__ __forceinline__ float ex2_approx(float x) { float y; asm("ex2.approx.ftz.f32 %0, %1;" : "=f"(y) : "f"(x)); return y; }
template<int N> __device__ __forceinline__ void fence_regs(float (&r)[N]) {
  #pragma unroll
  for (int i = 0; i < N; i++) asm volatile("" : "+f"(r[i]) :: "memory");
}
template<int N> __device__ __forceinline__ void zero_regs(float (&r)[N]) {
  #pragma unroll
  for (int i = 0; i < N; i += 2) asm volatile("mov.b64 {%0, %1}, 0;" : "=f"(r[i]), "=f"(r[i + 1]));
}
__device__ __forceinline__ float rbf(float x) { return __uint_as_float(pack_bf16(0.f, x)); }
__device__ __forceinline__ float bflo(uint32_t v) { return __uint_as_float(v << 16); }
__device__ __forceinline__ float bfhi(uint32_t v) { return __uint_as_float(v & 0xffff0000u); }

#define XT(i) do {} while (0)
#define TL_START(k) do {} while (0)
#define TL_END(k, cond) do {} while (0)
#define TL_CTA(i, cond) do {} while (0)
#define FS(slot, k) do {} while (0)
#define TL_MARK2(k, cond) do {} while (0)
#define TL_CLK(k, i, cond) do {} while (0)

template <int OFFA, int OFFB>
__device__ __forceinline__ void wgmma_m64n256k16_ss_tb(float (&d)[128], uint32_t a_lo, uint32_t b_lo, int scaleD) {
  asm volatile("{\n.reg .pred p;\n.reg .b32 ta, tb;\n.reg .b64 da, db;\nsetp.ne.b32 p, %130, 0;\n"
    "add.u32 ta, %128, %131;\nadd.u32 tb, %129, %132;\n"
    "mov.b64 da, {ta, 0x40000040};\nmov.b64 db, {tb, 0x40000040};\n"
    "wgmma.mma_async.sync.aligned.m64n256k16.f32.bf16.bf16 "
    "{%0, %1, %2, %3, %4, %5, %6, %7, %8, %9, %10, %11, %12, %13, %14, %15, %16, %17, %18, %19, %20, %21, %22, %23, %24, %25, %26, %27, %28, %29, %30, %31, %32, %33, %34, %35, %36, %37, %38, %39, %40, %41, %42, %43, %44, %45, %46, %47, %48, %49, %50, %51, %52, %53, %54, %55, %56, %57, %58, %59, %60, %61, %62, %63, %64, %65, %66, %67, %68, %69, %70, %71, %72, %73, %74, %75, %76, %77, %78, %79, %80, %81, %82, %83, %84, %85, %86, %87, %88, %89, %90, %91, %92, %93, %94, %95, %96, %97, %98, %99, %100, %101, %102, %103, %104, %105, %106, %107, %108, %109, %110, %111, %112, %113, %114, %115, %116, %117, %118, %119, %120, %121, %122, %123, %124, %125, %126, %127}, "
    "da, db, p, 1, 1, 0, 1;\n}\n"
    : "+f"(d[0]), "+f"(d[1]), "+f"(d[2]), "+f"(d[3]), "+f"(d[4]), "+f"(d[5]), "+f"(d[6]), "+f"(d[7]), "+f"(d[8]), "+f"(d[9]), "+f"(d[10]), "+f"(d[11]), "+f"(d[12]), "+f"(d[13]), "+f"(d[14]), "+f"(d[15]), "+f"(d[16]), "+f"(d[17]), "+f"(d[18]), "+f"(d[19]), "+f"(d[20]), "+f"(d[21]), "+f"(d[22]), "+f"(d[23]), "+f"(d[24]), "+f"(d[25]), "+f"(d[26]), "+f"(d[27]), "+f"(d[28]), "+f"(d[29]), "+f"(d[30]), "+f"(d[31]), "+f"(d[32]), "+f"(d[33]), "+f"(d[34]), "+f"(d[35]), "+f"(d[36]), "+f"(d[37]), "+f"(d[38]), "+f"(d[39]), "+f"(d[40]), "+f"(d[41]), "+f"(d[42]), "+f"(d[43]), "+f"(d[44]), "+f"(d[45]), "+f"(d[46]), "+f"(d[47]), "+f"(d[48]), "+f"(d[49]), "+f"(d[50]), "+f"(d[51]), "+f"(d[52]), "+f"(d[53]), "+f"(d[54]), "+f"(d[55]), "+f"(d[56]), "+f"(d[57]), "+f"(d[58]), "+f"(d[59]), "+f"(d[60]), "+f"(d[61]), "+f"(d[62]), "+f"(d[63]), "+f"(d[64]), "+f"(d[65]), "+f"(d[66]), "+f"(d[67]), "+f"(d[68]), "+f"(d[69]), "+f"(d[70]), "+f"(d[71]), "+f"(d[72]), "+f"(d[73]), "+f"(d[74]), "+f"(d[75]), "+f"(d[76]), "+f"(d[77]), "+f"(d[78]), "+f"(d[79]), "+f"(d[80]), "+f"(d[81]), "+f"(d[82]), "+f"(d[83]), "+f"(d[84]), "+f"(d[85]), "+f"(d[86]), "+f"(d[87]), "+f"(d[88]), "+f"(d[89]), "+f"(d[90]), "+f"(d[91]), "+f"(d[92]), "+f"(d[93]), "+f"(d[94]), "+f"(d[95]), "+f"(d[96]), "+f"(d[97]), "+f"(d[98]), "+f"(d[99]), "+f"(d[100]), "+f"(d[101]), "+f"(d[102]), "+f"(d[103]), "+f"(d[104]), "+f"(d[105]), "+f"(d[106]), "+f"(d[107]), "+f"(d[108]), "+f"(d[109]), "+f"(d[110]), "+f"(d[111]), "+f"(d[112]), "+f"(d[113]), "+f"(d[114]), "+f"(d[115]), "+f"(d[116]), "+f"(d[117]), "+f"(d[118]), "+f"(d[119]), "+f"(d[120]), "+f"(d[121]), "+f"(d[122]), "+f"(d[123]), "+f"(d[124]), "+f"(d[125]), "+f"(d[126]), "+f"(d[127])
    : "r"(a_lo), "r"(b_lo), "r"(scaleD), "n"(OFFA), "n"(OFFB));
}

template <int OFFA, int OFFB>
__device__ __forceinline__ void wgmma_m64n128k16_ss_tb(float (&d)[64], uint32_t a_lo, uint32_t b_lo, int scaleD) {
  asm volatile("{\n.reg .pred p;\n.reg .b32 ta, tb;\n.reg .b64 da, db;\nsetp.ne.b32 p, %66, 0;\n"
    "add.u32 ta, %64, %67;\nadd.u32 tb, %65, %68;\n"
    "mov.b64 da, {ta, 0x40000040};\nmov.b64 db, {tb, 0x40000040};\n"
    "wgmma.mma_async.sync.aligned.m64n128k16.f32.bf16.bf16 "
    "{%0, %1, %2, %3, %4, %5, %6, %7, %8, %9, %10, %11, %12, %13, %14, %15, %16, %17, %18, %19, %20, %21, %22, %23, %24, %25, %26, %27, %28, %29, %30, %31, %32, %33, %34, %35, %36, %37, %38, %39, %40, %41, %42, %43, %44, %45, %46, %47, %48, %49, %50, %51, %52, %53, %54, %55, %56, %57, %58, %59, %60, %61, %62, %63}, "
    "da, db, p, 1, 1, 0, 1;\n}\n"
    : "+f"(d[0]), "+f"(d[1]), "+f"(d[2]), "+f"(d[3]), "+f"(d[4]), "+f"(d[5]), "+f"(d[6]), "+f"(d[7]), "+f"(d[8]), "+f"(d[9]), "+f"(d[10]), "+f"(d[11]), "+f"(d[12]), "+f"(d[13]), "+f"(d[14]), "+f"(d[15]), "+f"(d[16]), "+f"(d[17]), "+f"(d[18]), "+f"(d[19]), "+f"(d[20]), "+f"(d[21]), "+f"(d[22]), "+f"(d[23]), "+f"(d[24]), "+f"(d[25]), "+f"(d[26]), "+f"(d[27]), "+f"(d[28]), "+f"(d[29]), "+f"(d[30]), "+f"(d[31]), "+f"(d[32]), "+f"(d[33]), "+f"(d[34]), "+f"(d[35]), "+f"(d[36]), "+f"(d[37]), "+f"(d[38]), "+f"(d[39]), "+f"(d[40]), "+f"(d[41]), "+f"(d[42]), "+f"(d[43]), "+f"(d[44]), "+f"(d[45]), "+f"(d[46]), "+f"(d[47]), "+f"(d[48]), "+f"(d[49]), "+f"(d[50]), "+f"(d[51]), "+f"(d[52]), "+f"(d[53]), "+f"(d[54]), "+f"(d[55]), "+f"(d[56]), "+f"(d[57]), "+f"(d[58]), "+f"(d[59]), "+f"(d[60]), "+f"(d[61]), "+f"(d[62]), "+f"(d[63])
    : "r"(a_lo), "r"(b_lo), "r"(scaleD), "n"(OFFA), "n"(OFFB));
}

template <int OFFB>
__device__ __forceinline__ void wgmma_m64n128k16_rs_tb(float (&d)[64], uint32_t a0, uint32_t a1, uint32_t a2, uint32_t a3, uint32_t b_lo, int scaleD) {
  asm volatile("{\n.reg .pred p;\n.reg .b32 tb;\n.reg .b64 db;\nsetp.ne.b32 p, %69, 0;\n"
    "add.u32 tb, %68, %70;\n"
    "mov.b64 db, {tb, 0x40000040};\n"
    "wgmma.mma_async.sync.aligned.m64n128k16.f32.bf16.bf16 "
    "{%0, %1, %2, %3, %4, %5, %6, %7, %8, %9, %10, %11, %12, %13, %14, %15, %16, %17, %18, %19, %20, %21, %22, %23, %24, %25, %26, %27, %28, %29, %30, %31, %32, %33, %34, %35, %36, %37, %38, %39, %40, %41, %42, %43, %44, %45, %46, %47, %48, %49, %50, %51, %52, %53, %54, %55, %56, %57, %58, %59, %60, %61, %62, %63}, "
    "{%64, %65, %66, %67}, db, p, 1, 1, 1;\n}\n"
    : "+f"(d[0]), "+f"(d[1]), "+f"(d[2]), "+f"(d[3]), "+f"(d[4]), "+f"(d[5]), "+f"(d[6]), "+f"(d[7]), "+f"(d[8]), "+f"(d[9]), "+f"(d[10]), "+f"(d[11]), "+f"(d[12]), "+f"(d[13]), "+f"(d[14]), "+f"(d[15]), "+f"(d[16]), "+f"(d[17]), "+f"(d[18]), "+f"(d[19]), "+f"(d[20]), "+f"(d[21]), "+f"(d[22]), "+f"(d[23]), "+f"(d[24]), "+f"(d[25]), "+f"(d[26]), "+f"(d[27]), "+f"(d[28]), "+f"(d[29]), "+f"(d[30]), "+f"(d[31]), "+f"(d[32]), "+f"(d[33]), "+f"(d[34]), "+f"(d[35]), "+f"(d[36]), "+f"(d[37]), "+f"(d[38]), "+f"(d[39]), "+f"(d[40]), "+f"(d[41]), "+f"(d[42]), "+f"(d[43]), "+f"(d[44]), "+f"(d[45]), "+f"(d[46]), "+f"(d[47]), "+f"(d[48]), "+f"(d[49]), "+f"(d[50]), "+f"(d[51]), "+f"(d[52]), "+f"(d[53]), "+f"(d[54]), "+f"(d[55]), "+f"(d[56]), "+f"(d[57]), "+f"(d[58]), "+f"(d[59]), "+f"(d[60]), "+f"(d[61]), "+f"(d[62]), "+f"(d[63])
    : "r"(a0), "r"(a1), "r"(a2), "r"(a3), "r"(b_lo), "r"(scaleD), "n"(OFFB));
}

template <int OFFB>
__device__ __forceinline__ void wgmma_m64n128k16_rs(float (&d)[64], uint32_t a0, uint32_t a1, uint32_t a2, uint32_t a3, uint32_t b_lo, int scaleD) {
  asm volatile("{\n.reg .pred p;\n.reg .b32 tb;\n.reg .b64 db;\nsetp.ne.b32 p, %69, 0;\n"
    "add.u32 tb, %68, %70;\n"
    "mov.b64 db, {tb, 0x40000040};\n"
    "wgmma.mma_async.sync.aligned.m64n128k16.f32.bf16.bf16 "
    "{%0, %1, %2, %3, %4, %5, %6, %7, %8, %9, %10, %11, %12, %13, %14, %15, %16, %17, %18, %19, %20, %21, %22, %23, %24, %25, %26, %27, %28, %29, %30, %31, %32, %33, %34, %35, %36, %37, %38, %39, %40, %41, %42, %43, %44, %45, %46, %47, %48, %49, %50, %51, %52, %53, %54, %55, %56, %57, %58, %59, %60, %61, %62, %63}, "
    "{%64, %65, %66, %67}, db, p, 1, 1, 0;\n}\n"
    : "+f"(d[0]), "+f"(d[1]), "+f"(d[2]), "+f"(d[3]), "+f"(d[4]), "+f"(d[5]), "+f"(d[6]), "+f"(d[7]), "+f"(d[8]), "+f"(d[9]), "+f"(d[10]), "+f"(d[11]), "+f"(d[12]), "+f"(d[13]), "+f"(d[14]), "+f"(d[15]), "+f"(d[16]), "+f"(d[17]), "+f"(d[18]), "+f"(d[19]), "+f"(d[20]), "+f"(d[21]), "+f"(d[22]), "+f"(d[23]), "+f"(d[24]), "+f"(d[25]), "+f"(d[26]), "+f"(d[27]), "+f"(d[28]), "+f"(d[29]), "+f"(d[30]), "+f"(d[31]), "+f"(d[32]), "+f"(d[33]), "+f"(d[34]), "+f"(d[35]), "+f"(d[36]), "+f"(d[37]), "+f"(d[38]), "+f"(d[39]), "+f"(d[40]), "+f"(d[41]), "+f"(d[42]), "+f"(d[43]), "+f"(d[44]), "+f"(d[45]), "+f"(d[46]), "+f"(d[47]), "+f"(d[48]), "+f"(d[49]), "+f"(d[50]), "+f"(d[51]), "+f"(d[52]), "+f"(d[53]), "+f"(d[54]), "+f"(d[55]), "+f"(d[56]), "+f"(d[57]), "+f"(d[58]), "+f"(d[59]), "+f"(d[60]), "+f"(d[61]), "+f"(d[62]), "+f"(d[63])
    : "r"(a0), "r"(a1), "r"(a2), "r"(a3), "r"(b_lo), "r"(scaleD), "n"(OFFB));
}

__device__ __forceinline__ uint4 ldg_nc_v4(const void* p) {
  uint4 v;
    asm volatile("{\n.reg .b64 pol;\ncreatepolicy.fractional.L2::evict_first.b64 pol, 1.0;\n"
                 "ld.global.nc.L1::no_allocate.L2::cache_hint.v4.u32 {%0, %1, %2, %3}, [%4], pol;\n}\n" : "=r"(v.x), "=r"(v.y), "=r"(v.z), "=r"(v.w) : "l"(p));
  return v;
}
__device__ __forceinline__ uint64_t pol_normal() {
  uint64_t p; asm volatile("createpolicy.fractional.L2::evict_normal.b64 %0, 1.0;" : "=l"(p)); return p;
}
__device__ __forceinline__ void unpack8(const uint4& u, float (&v)[8]) {
  v[0] = bflo(u.x); v[1] = bfhi(u.x); v[2] = bflo(u.y); v[3] = bfhi(u.y);
  v[4] = bflo(u.z); v[5] = bfhi(u.z); v[6] = bflo(u.w); v[7] = bfhi(u.w);
}
__device__ __forceinline__ void fma8(float (&acc)[8], float s, const uint4& w) {
  acc[0] = fmaf(s, bflo(w.x), acc[0]); acc[1] = fmaf(s, bfhi(w.x), acc[1]); acc[2] = fmaf(s, bflo(w.y), acc[2]); acc[3] = fmaf(s, bfhi(w.y), acc[3]);
  acc[4] = fmaf(s, bflo(w.z), acc[4]); acc[5] = fmaf(s, bfhi(w.z), acc[5]); acc[6] = fmaf(s, bflo(w.w), acc[6]); acc[7] = fmaf(s, bfhi(w.w), acc[7]);
}
__device__ __forceinline__ float rcp_approx(float x) { float y; asm("rcp.approx.ftz.f32 %0, %1;" : "=f"(y) : "f"(x)); return y; }
__device__ __forceinline__ float sigmoid_f(float v) { return rcp_approx(1.0f + ex2_approx(v * -1.4426950408889634f)); }
__device__ __forceinline__ float silu_bf(float v) { return rbf(v * sigmoid_f(v)); }
__device__ __forceinline__ uint32_t rank_key(float r, int idx) {
  const uint32_t b = __float_as_uint(r) >> 16;
  const uint32_t u = (r != r) ? 0u : ((b & 0x8000u) ? (~b & 0xffffu) : (b | 0x8000u));
  return (u << 16) | (0xffffu - (uint32_t)idx);
}
__device__ __forceinline__ void warp_top2(uint32_t& k1, uint32_t& k2) {
  const uint32_t m1 = __reduce_max_sync(0xffffffffu, k1);
  k2 = __reduce_max_sync(0xffffffffu, k1 == m1 ? k2 : k1);
  k1 = m1;
}
__device__ __forceinline__ uint32_t bmul2(uint32_t a, uint32_t b) { uint32_t r; asm("mul.rn.bf16x2 %0, %1, %2;" : "=r"(r) : "r"(a), "r"(b)); return r; }
__device__ __forceinline__ uint32_t badd2(uint32_t a, uint32_t b) { uint32_t r; asm("add.rn.bf16x2 %0, %1, %2;" : "=r"(r) : "r"(a), "r"(b)); return r; }
__device__ __forceinline__ uint32_t bsub2(uint32_t a, uint32_t b) { uint32_t r; asm("sub.rn.bf16x2 %0, %1, %2;" : "=r"(r) : "r"(a), "r"(b)); return r; }
__device__ __forceinline__ float sqrt_approx(float x) { float y; asm("sqrt.approx.f32 %0, %1;" : "=f"(y) : "f"(x)); return y; }
__device__ __forceinline__ uint32_t ln_norm2(uint32_t x1, uint32_t mb2, float inv) {
  const uint32_t d = bsub2(x1, mb2);
  return pack_bf16(bflo(d) * inv, bfhi(d) * inv);
}
__device__ __forceinline__ uint32_t bfma2(uint32_t a, uint32_t b, uint32_t c) { uint32_t r; asm("fma.rn.bf16x2 %0, %1, %2, %3;" : "=r"(r) : "r"(a), "r"(b), "r"(c)); return r; }
__device__ __forceinline__ uint32_t ln_norm2b(uint32_t x1, uint32_t mb2, uint32_t ih, uint32_t il) {
  const uint32_t d = bsub2(x1, mb2);
  return bfma2(d, ih, bmul2(d, il));
}
__device__ __forceinline__ uint32_t ln_mod2(uint32_t x1, uint32_t mb2, float inv, uint32_t c1, uint32_t sb) { return badd2(bmul2(ln_norm2(x1, mb2, inv), c1), sb); }
__device__ __forceinline__ void ldmatrix_x4(uint32_t addr, uint32_t& r0, uint32_t& r1, uint32_t& r2, uint32_t& r3) {
  asm volatile("ldmatrix.sync.aligned.m8n8.x4.shared.b16 {%0, %1, %2, %3}, [%4];" : "=r"(r0), "=r"(r1), "=r"(r2), "=r"(r3) : "r"(addr) : "memory");
}
__device__ __forceinline__ uint4 ldg_stream_v4(const void* p, uint64_t pol) {
  uint4 v; asm volatile("ld.global.nc.L1::no_allocate.L2::cache_hint.L2::128B.v4.u32 {%0, %1, %2, %3}, [%4], %5;" : "=r"(v.x), "=r"(v.y), "=r"(v.z), "=r"(v.w) : "l"(p), "l"(pol)); return v;
}
__device__ __forceinline__ void bulk_load_hint(uint32_t dst, const void* src, uint32_t bytes, uint32_t bar, uint64_t pol) {
  asm volatile("cp.async.bulk.shared::cluster.global.mbarrier::complete_tx::bytes.L2::cache_hint [%0], [%1], %2, [%3], %4;"
    :: "r"(dst), "l"(src), "r"(bytes), "r"(bar), "l"(pol) : "memory");
}
__device__ __forceinline__ void red_release_add(unsigned int* p, unsigned int v) { asm volatile("red.release.gpu.global.add.u32 [%0], %1;" :: "l"(p), "r"(v) : "memory"); }
__device__ __forceinline__ unsigned int ld_acquire(const unsigned int* p) { unsigned int v; asm volatile("ld.acquire.gpu.global.u32 %0, [%1];" : "=r"(v) : "l"(p) : "memory"); return v; }
__device__ __forceinline__ void spin_until(const unsigned int* p, unsigned int target) {
  #pragma unroll 1
  for (unsigned int i = 0; i < (1u << 22); i++) { if (ld_acquire(p) >= target) return; }
}
__device__ __forceinline__ float lds_f32(uint32_t a) { float v; asm volatile("ld.shared.f32 %0, [%1];" : "=f"(v) : "r"(a) : "memory"); return v; }
__device__ __forceinline__ float2 lds_f32x2(uint32_t a) { float2 v; asm volatile("ld.shared.v2.f32 {%0, %1}, [%2];" : "=f"(v.x), "=f"(v.y) : "r"(a) : "memory"); return v; }
__device__ __forceinline__ uint2 lds_u32x2(uint32_t a) { uint2 v; asm volatile("ld.shared.v2.u32 {%0, %1}, [%2];" : "=r"(v.x), "=r"(v.y) : "r"(a) : "memory"); return v; }
__device__ __forceinline__ uint32_t lds_u32(uint32_t a) { uint32_t v; asm volatile("ld.shared.u32 %0, [%1];" : "=r"(v) : "r"(a) : "memory"); return v; }
__device__ __forceinline__ void sts_u32(uint32_t a, uint32_t v) { asm volatile("st.shared.u32 [%0], %1;" :: "r"(a), "r"(v) : "memory"); }
__device__ __forceinline__ void sts_u32x2(uint32_t a, uint32_t x, uint32_t y) { asm volatile("st.shared.v2.u32 [%0], {%1, %2};" :: "r"(a), "r"(x), "r"(y) : "memory"); }
__device__ __forceinline__ void sts_f32(uint32_t a, float v) { asm volatile("st.shared.f32 [%0], %1;" :: "r"(a), "f"(v) : "memory"); }
__device__ __forceinline__ void sts_f32x2(uint32_t a, float x, float y) { asm volatile("st.shared.v2.f32 [%0], {%1, %2};" :: "r"(a), "f"(x), "f"(y) : "memory"); }
__device__ __forceinline__ void sts_f32x4(uint32_t a, float x, float y, float z, float w) { asm volatile("st.shared.v4.f32 [%0], {%1, %2, %3, %4};" :: "r"(a), "f"(x), "f"(y), "f"(z), "f"(w) : "memory"); }

__device__ __forceinline__ uint4 lds_u32x4(uint32_t a) { uint4 v; asm volatile("ld.shared.v4.u32 {%0, %1, %2, %3}, [%4];" : "=r"(v.x), "=r"(v.y), "=r"(v.z), "=r"(v.w) : "r"(a) : "memory"); return v; }
__device__ __forceinline__ void sts_u32x4(uint32_t a, uint32_t x, uint32_t y, uint32_t z, uint32_t w) { asm volatile("st.shared.v4.u32 [%0], {%1, %2, %3, %4};" :: "r"(a), "r"(x), "r"(y), "r"(z), "r"(w) : "memory"); }
__device__ __forceinline__ void st_tagged(float* p, float v) {
  const uint32_t b = __float_as_uint(v);
  asm volatile("st.relaxed.gpu.global.u32 [%0], %1;" :: "l"(p), "r"(b == 0u ? 0x80000000u : b) : "memory");
}
__device__ __forceinline__ void st_tagged4(float* p, float x, float y, float z, float w) {
  const uint32_t a = __float_as_uint(x), b = __float_as_uint(y), c = __float_as_uint(z), d = __float_as_uint(w);
  asm volatile("st.relaxed.gpu.global.v4.u32 [%0], {%1, %2, %3, %4};" :: "l"(p), "r"(a == 0u ? 0x80000000u : a), "r"(b == 0u ? 0x80000000u : b),
               "r"(c == 0u ? 0x80000000u : c), "r"(d == 0u ? 0x80000000u : d) : "memory");
}
__device__ __forceinline__ void st_relaxed2(void* p, uint32_t a, uint32_t b) { asm volatile("st.relaxed.gpu.global.v2.u32 [%0], {%1, %2};" :: "l"(p), "r"(a), "r"(b) : "memory"); }
__device__ __forceinline__ float4 ld_tagged4(const float* p) {
  float4 v; asm volatile("ld.relaxed.gpu.global.v4.f32 {%0, %1, %2, %3}, [%4];" : "=f"(v.x), "=f"(v.y), "=f"(v.z), "=f"(v.w) : "l"(p) : "memory"); return v;
}
__device__ __forceinline__ bool tagged4(const float4& v) {
  return __float_as_uint(v.x) != 0u && __float_as_uint(v.y) != 0u && __float_as_uint(v.z) != 0u && __float_as_uint(v.w) != 0u;
}
__device__ __forceinline__ void hint_arrive(uint32_t* p) { asm volatile("red.relaxed.gpu.global.add.u32 [%0], 1;" :: "l"(p) : "memory"); }
__device__ __forceinline__ void hint_wait(const uint32_t* p, uint32_t target) {
  uint32_t v = 0u;
  #pragma unroll 1
  for (unsigned int i = 0; i < (1u << 22) && v < target; i++) asm volatile("ld.relaxed.gpu.global.u32 %0, [%1];" : "=r"(v) : "l"(p) : "memory");
}
__device__ __forceinline__ void fence_proxy_async_global() { asm volatile("fence.proxy.async.global;" ::: "memory"); }

#define H_SPLIT 1
#define X_DLY 1200
#define W_DLY 1900
#define W_FIRST 2200
#define PRE_B 2
#define H_PREG 1
template <int J0, int J1>
__device__ __forceinline__ void load_parts(float2 (&pa)[J1 - J0][4], int t2) {
  #pragma unroll
  for (int j = J0; j < J1; j++)
    #pragma unroll
    for (int k = 0; k < 4; k++)
      asm volatile("ld.relaxed.gpu.global.v2.f32 {%0, %1}, [%2];" : "=f"(pa[j - J0][k].x), "=f"(pa[j - J0][k].y)
                   : "l"(g_modpart + k * 2 * T_D + (t2 >> 7) * T_D + j * 256 + (t2 & 127) * 2) : "memory");
}
template <int J0, int J1>
__device__ __forceinline__ void finish_parts(float2 (&pa)[J1 - J0][4], bool loaded, int t2, uint32_t tab) {
  #pragma unroll 1
  for (unsigned int spin = 0; spin < (1u << 22); spin++) {
    if (!loaded) load_parts<J0, J1>(pa, t2);
    loaded = false;
    bool ok = true;
    #pragma unroll
    for (int j = 0; j < J1 - J0; j++)
      #pragma unroll
      for (int k = 0; k < 4; k++) ok &= (__float_as_uint(pa[j][k].x) != 0u) & (__float_as_uint(pa[j][k].y) != 0u);
    if (__all_sync(0xffffffffu, ok)) break;
  }
  #pragma unroll
  for (int j = J0; j < J1; j++) {
    const float2* q = pa[j - J0];
    const uint32_t m = pack_bf16(((q[0].x + q[1].x) + q[2].x) + q[3].x, ((q[0].y + q[1].y) + q[2].y) + q[3].y);
    sts_u32(tab + (t2 >> 7) * 2048 + j * 512 + (t2 & 127) * 4, t2 >= 128 ? badd2(m, 0x3F803F80u) : m);
  }
}
__device__ __forceinline__ void head_phase(uint32_t scr, uint32_t xs, uint32_t b_x, uint32_t b_go, uint32_t b_head, int t2, uint32_t zero, const bf16* __restrict__ cvec, const bf16* __restrict__ w_mod) {
  const int lane = t2 & 31, w8 = t2 >> 5;
  const int cb = blockIdx.x & 31, ks = blockIdx.x >> 5;
  const bool early = (cb & 15) < 4 * H_SPLIT;
  const uint32_t ws = (xs - 32768 + (t2 >> 3) * 128 + (((t2 ^ (t2 >> 3)) & 7) << 4)) ^ zero;
  const float cv = __bfloat162float(cvec[ks * 256 + t2]);
  const bf16* wsrc = w_mod + (size_t)(ks * 256 + (t2 >> 3)) * (6 * T_D) + cb * 64 + (t2 & 7) * 8;
  if (early) {
    const uint64_t pol = policy_evict_first();
    #pragma unroll 2
    for (int i = 0; i < 8; i++)
      asm volatile("cp.async.cg.shared.global.L2::cache_hint [%0], [%1], 16, %2;" :: "r"(ws + i * 4096), "l"(wsrc + (size_t)i * 32 * 6 * T_D), "l"(pol) : "memory");
  }
  sts_f32(scr + t2 * 4, silu_bf(cv));
  named_bar_sync(6, 384);
  TL_MARK2(1, t2 == 0);
  uint4 xv[2][4];
  uint32_t mb2[2], ih[2], il[2];
  auto norm = [&](int j) {
    #pragma unroll
    for (int r = 0; r < 2; r++) {
      xv[r][j].x = ln_norm2b(xv[r][j].x, mb2[r], ih[r], il[r]); xv[r][j].y = ln_norm2b(xv[r][j].y, mb2[r], ih[r], il[r]);
      xv[r][j].z = ln_norm2b(xv[r][j].z, mb2[r], ih[r], il[r]); xv[r][j].w = ln_norm2b(xv[r][j].w, mb2[r], ih[r], il[r]);
    }
  };
  auto modulate = [&](int j) {
    const uint4 sa = lds_u32x4(scr + 8192 + j * 512 + lane * 16), c1 = lds_u32x4(scr + 8192 + 2048 + j * 512 + lane * 16);
    #pragma unroll
    for (int r = 0; r < 2; r++) {
      xv[r][j].x = badd2(bmul2(xv[r][j].x, c1.x), sa.x); xv[r][j].y = badd2(bmul2(xv[r][j].y, c1.y), sa.y);
      xv[r][j].z = badd2(bmul2(xv[r][j].z, c1.z), sa.z); xv[r][j].w = badd2(bmul2(xv[r][j].w, c1.w), sa.w);
    }
  };
  auto store = [&](int j) {
    #pragma unroll
    for (int r = 0; r < 2; r++) *reinterpret_cast<uint4*>(g_h + (size_t)(blockIdx.x * 16 + 2 * w8 + r) * T_D + j * 256 + lane * 8) = xv[r][j];
  };
  #pragma unroll 1
  for (int ph = 0; ph < 2; ph++) {
    if ((ph == 0) == early) {
      asm volatile("cp.async.wait_all;" ::: "memory");
      if (!early) mbar_wait(b_x + 168, 0);
      float acc[8];
      #pragma unroll
      for (int j = 0; j < 8; j++) acc[j] = 0.f;
      #pragma unroll
      for (int i = 0; i < 8; i++) fma8(acc, lds_f32(scr + ((t2 >> 3) + 32 * i) * 4), lds_u32x4(ws + i * 4096));
      #pragma unroll
      for (int j = 0; j < 4; j++) { const bool up = lane & 16; acc[j] = (up ? acc[4 + j] : acc[j]) + __shfl_xor_sync(0xffffffffu, up ? acc[j] : acc[4 + j], 16); }
      #pragma unroll
      for (int j = 0; j < 2; j++) { const bool up = lane & 8; acc[j] = (up ? acc[2 + j] : acc[j]) + __shfl_xor_sync(0xffffffffu, up ? acc[j] : acc[2 + j], 8); }
      sts_f32x2(scr + 1024 + w8 * 256 + (lane & 7) * 32 + (lane >> 3) * 8, acc[0], acc[1]);
      named_bar_sync(5, 256);
      if (t2 < 64) {
        float sum = 0.f;
        #pragma unroll
        for (int i = 0; i < 8; i++) sum += lds_f32(scr + 1024 + i * 256 + t2 * 4);
        st_tagged(g_modpart + ks * 2 * T_D + cb * 64 + t2, sum);
        TL_MARK2(early ? 2 : 6, t2 == 0);
      }
    } else {
      float2 pa[H_SPLIT][4];
      mbar_wait(b_x, 0);
      TL_MARK2(18, t2 == 0);
      if (H_PREG) load_parts<0, H_SPLIT>(pa, t2);
      #pragma unroll
      for (int r = 0; r < 2; r++)
        #pragma unroll
        for (int j = 0; j < 4; j++) xv[r][j] = lds_u32x4(xs + (2 * w8 + r) * 2048 + j * 512 + lane * 16);
  {
    float st[4] = {0.f, 0.f, 0.f, 0.f};
    #pragma unroll
    for (int r = 0; r < 2; r++)
      #pragma unroll
      for (int j = 0; j < 4; j++) {
        float v[8];
        unpack8(xv[r][j], v);
        st[2 * r] += ((v[0] + v[1]) + (v[2] + v[3])) + ((v[4] + v[5]) + (v[6] + v[7]));
        st[2 * r + 1] += fmaf(v[0], v[0], fmaf(v[1], v[1], fmaf(v[2], v[2], v[3] * v[3]))) + fmaf(v[4], v[4], fmaf(v[5], v[5], fmaf(v[6], v[6], v[7] * v[7])));
      }
    #pragma unroll
    for (int k = 0; k < 2; k++) { const bool up = lane & 16; st[k] = (up ? st[2 + k] : st[k]) + __shfl_xor_sync(0xffffffffu, up ? st[k] : st[2 + k], 16); }
    #pragma unroll
    for (int o = 8; o > 0; o >>= 1) { st[0] += __shfl_xor_sync(0xffffffffu, st[0], o); st[1] += __shfl_xor_sync(0xffffffffu, st[1], o); }
    const float mean = st[0] * (1.0f / T_D);
    const float inv = rcp_approx(rbf(sqrt_approx(rbf(rbf(fmaxf(fmaf(-mean, mean, st[1] * (1.0f / T_D)), 0.f)) + 1e-05f))));
    const uint32_t m = pack_bf16(mean, mean), h = pack_bf16(inv - rbf(inv), inv);
    #pragma unroll
    for (int r = 0; r < 2; r++) {
      mb2[r] = __shfl_sync(0xffffffffu, m, 16 * r);
      const uint32_t hr = __shfl_sync(0xffffffffu, h, 16 * r);
      ih[r] = __byte_perm(hr, hr, 0x3232); il[r] = __byte_perm(hr, hr, 0x1010);
    }
  }
      #pragma unroll
      for (int j = 0; j < H_SPLIT; j++) norm(j);
      TL_MARK2(5, t2 == 0);
      finish_parts<0, H_SPLIT>(pa, H_PREG, t2, scr + 8192);
      named_bar_sync(5, 256);
      TL_MARK2(7, t2 == 0);
      #pragma unroll
      for (int j = 0; j < H_SPLIT; j++) { modulate(j); store(j); }
      named_bar_arrive(9, 288);
    }
  }
  #pragma unroll
  for (int j = H_SPLIT; j < 4; j++) norm(j);
  float2 pb[4 - H_SPLIT][4];
  finish_parts<H_SPLIT, 4>(pb, false, t2, scr + 8192);
  named_bar_sync(5, 256);
  TL_MARK2(17, t2 == 0);
  #pragma unroll
  for (int j = H_SPLIT; j < 4; j++) modulate(j);
  __syncwarp();
  if (lane == 0) mbar_arrive(b_head + (xv[1][3].w & zero));
  mbar_wait(b_go, 0);
  #pragma unroll
  for (int j = H_SPLIT; j < 4; j++) store(j);
  named_bar_arrive(8, 288);
}

#define MOD_AT (b_empty + 8)
#define MOD_PF 0
#define MOD_SPLIT 16
__device__ __forceinline__ void mod_rest(uint32_t scr, uint32_t b_go, int t, const bf16* __restrict__ cvec, const bf16* __restrict__ w_mod, const bf16* __restrict__ w_r) {
  const int lane = t & 31;
  #pragma unroll 1
  for (int i = t; i < T_D / 2; i += 64) {
    const uint32_t c2 = *reinterpret_cast<const uint32_t*>(cvec + 2 * i);
    sts_u32(scr + i * 4, pack_bf16(silu_bf(bflo(c2)), silu_bf(bfhi(c2))));
  }
  named_bar_sync(11, 64);
  const bf16* wp = w_mod + (size_t)(2 * (t >> 2)) * (6 * T_D) + 2 * T_D + blockIdx.x * 32 + (t & 3) * 8;
  float acc[8];
  #pragma unroll
  for (int i = 0; i < 8; i++) acc[i] = 0.f;
  #pragma unroll 1
  for (int i = 0; i < 32; i += 2) {
    if (i == MOD_SPLIT) mbar_wait(b_go, 0);
    const uint4 w0 = ldg_nc_v4(wp), w1 = ldg_nc_v4(wp + 6 * T_D), w2 = ldg_nc_v4(wp + 32 * 6 * T_D), w3 = ldg_nc_v4(wp + 33 * 6 * T_D);
    wp += 64 * 6 * T_D;
    const uint32_t s0 = lds_u32(scr + (i * 16 + (t >> 2)) * 4), s1 = lds_u32(scr + (i * 16 + 16 + (t >> 2)) * 4);
    fma8(acc, bflo(s0), w0); fma8(acc, bfhi(s0), w1); fma8(acc, bflo(s1), w2); fma8(acc, bfhi(s1), w3);
  }
  #pragma unroll
  for (int j = 0; j < 4; j++) { const bool up = lane & 16; acc[j] = (up ? acc[4 + j] : acc[j]) + __shfl_xor_sync(0xffffffffu, up ? acc[j] : acc[4 + j], 16); }
  #pragma unroll
  for (int j = 0; j < 2; j++) { const bool up = lane & 8; acc[j] = (up ? acc[2 + j] : acc[j]) + __shfl_xor_sync(0xffffffffu, up ? acc[j] : acc[2 + j], 8); }
  { const bool up = lane & 4; acc[0] = (up ? acc[1] : acc[0]) + __shfl_xor_sync(0xffffffffu, up ? acc[0] : acc[1], 4); }
  if (t >= 32) sts_f32(scr + 2048 + lane * 4, acc[0]);
  named_bar_sync(11, 64);
  if (__shfl_sync(0xffffffffu, t, 0) < 32) {
    const int kind = blockIdx.x >> 5;
    float v = rbf(acc[0] + lds_f32(scr + 2048 + lane * 4));
    const int col = (blockIdx.x & 31) * 32 + (lane & 3) * 8 + (lane >> 2);
    uint8_t* dst = g_col + (col >> 7) * 1536;
    if (kind == 2) v = rbf(1.0f + v);
    float vw = v * __bfloat162float(w_r[col]);
    if (kind == 2) {
      const int c = col & 127, i = (c & ~15) + ((c >> 1) & 3) * 4 + ((c >> 3) & 1) * 2 + (c & 1);
      reinterpret_cast<bf16*>(dst)[i] = __float2bfloat16_rn(vw);
      reinterpret_cast<bf16*>(dst)[128 + i] = __float2bfloat16_rn(vw - rbf(vw));
    }
    reinterpret_cast<bf16*>(dst + 512 + (kind & 1) * 512 + (kind >> 1) * 256)[col & 127] = __float2bfloat16_rn(v);
    #pragma unroll
    for (int o = 16; o > 0; o >>= 1) vw += __shfl_xor_sync(0xffffffffu, vw, o);
    if (lane == 0 && (kind == 1 || kind == 2)) g_scal[95 - blockIdx.x] = vw;
  }
  #pragma unroll 1
  for (int i = blockIdx.x * 64 + t; i < (int)(sizeof(g_mail) / 16); i += 128 * 64) reinterpret_cast<uint4*>(&g_mail)[i] = make_uint4(0u, 0u, 0u, 0u);
  named_bar_sync(11, 64);
  if (t == 0) red_release_add(&g_hcnt[0], 1u);
}

#define HPOL_A pol
#define HPOL_B pol_normal()
#define HMAP_A &tmOl
#define HMAP_B &tmWo
constexpr int AT_NBLK = T_SEQ / 128;
constexpr float AT_HEAD = 7.0f;
#define WO_LATE 12
#define QP_STAG 3
#define AT_SPLIT 28
#define AT_PIN 12
#define PINB 4
constexpr int AT_NFULL = 124;
constexpr int AT_PREG = 40, AT_CREG = 232;
constexpr uint32_t AT_SQ = 5 * 32768;
constexpr float AT_C = 0.08838834764831845f * 1.4426950408889634f;
constexpr float AT_RAW_LO = -16.0f, AT_RAW_HI = 24.0f;
constexpr float AT_RAW_SUM = 281474976710656.0f, AT_RAW_MIN = 9.094947017729282e-13f;
constexpr uint32_t AT_SBAR = AT_SQ + 65536 + 256;
constexpr uint32_t AT_SMEM = AT_SQ + 65536 + 3072;

__device__ __forceinline__ uint32_t ring_slot(uint32_t t) { return t - 5u * ((t * 205u) >> 10); }
__device__ __forceinline__ uint32_t qp_pos(uint32_t j, uint32_t it) { return 4u * it + (j & 3u) + ((j & 3u) == 3u ? it : 0u); }
__device__ __forceinline__ uint32_t ring_par(uint32_t t) { return ((t * 205u) >> 10) & 1u; }
__device__ __forceinline__ void softmax_rowmax(const float (&s)[64], float& mx0, float& mx1) {
  float a0 = fmaxf(s[0], s[1]), a1 = fmaxf(s[4], s[5]), a2 = fmaxf(s[8], s[9]), a3 = fmaxf(s[12], s[13]);
  float b0 = fmaxf(s[2], s[3]), b1 = fmaxf(s[6], s[7]), b2 = fmaxf(s[10], s[11]), b3 = fmaxf(s[14], s[15]);
  #pragma unroll
  for (int j = 4; j < 16; j += 4) {
    a0 = fmaxf(a0, fmaxf(s[4 * j + 0], s[4 * j + 1]));  b0 = fmaxf(b0, fmaxf(s[4 * j + 2], s[4 * j + 3]));
    a1 = fmaxf(a1, fmaxf(s[4 * j + 4], s[4 * j + 5]));  b1 = fmaxf(b1, fmaxf(s[4 * j + 6], s[4 * j + 7]));
    a2 = fmaxf(a2, fmaxf(s[4 * j + 8], s[4 * j + 9]));  b2 = fmaxf(b2, fmaxf(s[4 * j + 10], s[4 * j + 11]));
    a3 = fmaxf(a3, fmaxf(s[4 * j + 12], s[4 * j + 13])); b3 = fmaxf(b3, fmaxf(s[4 * j + 14], s[4 * j + 15]));
  }
  mx0 = fmaxf(fmaxf(a0, a1), fmaxf(a2, a3));
  mx1 = fmaxf(fmaxf(b0, b1), fmaxf(b2, b3));
  mx0 = fmaxf(mx0, __shfl_xor_sync(0xffffffffu, mx0, 1));
  mx1 = fmaxf(mx1, __shfl_xor_sync(0xffffffffu, mx1, 1));
  mx0 = fmaxf(mx0, __shfl_xor_sync(0xffffffffu, mx0, 2));
  mx1 = fmaxf(mx1, __shfl_xor_sync(0xffffffffu, mx1, 2));
}
__device__ __forceinline__ void softmax_sub(float (&s)[64], float mc0, float mc1) {
  #pragma unroll
  for (int j = 0; j < 16; j++) { s[4 * j] -= mc0; s[4 * j + 1] -= mc0; s[4 * j + 2] -= mc1; s[4 * j + 3] -= mc1; }
}
template <int LO, int HI>
__device__ __forceinline__ void softmax_exp(float (&s)[64]) {
  #pragma unroll
  for (int i = LO; i < HI; i++) s[i] = ex2_approx(s[i]);
}
__device__ __forceinline__ bool softmax_mode(const float (&s)[64], float& mc0, float& mc1) {
  softmax_rowmax(s, mc0, mc1);
  const bool raw = __all_sync(0xffffffffu, mc0 >= AT_RAW_LO && mc0 <= AT_RAW_HI && mc1 >= AT_RAW_LO && mc1 <= AT_RAW_HI);
  mc0 += AT_HEAD; mc1 += AT_HEAD;
  return raw;
}
__device__ __forceinline__ void rowsum_p(const uint32_t (&p)[32], uint32_t& t0, uint32_t& t1) {
  uint32_t a[16];
  #pragma unroll
  for (int i = 0; i < 8; i++) { a[2 * i] = badd2(p[4 * i], p[4 * i + 2]); a[2 * i + 1] = badd2(p[4 * i + 1], p[4 * i + 3]); }
  #pragma unroll
  for (int i = 0; i < 4; i++) { a[2 * i] = badd2(a[4 * i], a[4 * i + 2]); a[2 * i + 1] = badd2(a[4 * i + 1], a[4 * i + 3]); }
  t0 = badd2(badd2(a[0], a[2]), badd2(a[4], a[6]));
  t1 = badd2(badd2(a[1], a[3]), badd2(a[5], a[7]));
}
__device__ __forceinline__ void add_rowsum(const uint32_t (&p)[32], float& l0, float& l1) {
  uint32_t t0, t1;
  rowsum_p(p, t0, t1);
  l0 += bflo(t0) + bfhi(t0); l1 += bflo(t1) + bfhi(t1);
}
__device__ __forceinline__ void pack_p(uint32_t (&p)[32], const float (&s)[64]) {
  #pragma unroll
  for (int i = 0; i < 32; i++) p[i] = pack_bf16(s[2 * i], s[2 * i + 1]);
}
__device__ __noinline__ void attn_rows_exact(uint32_t sq, uint32_t so, int hsel, const bf16* __restrict__ kh, const bf16* __restrict__ vh) {
  const int warp = (threadIdx.x >> 5) & 3, lane = threadIdx.x & 31;
  const size_t hofs = (size_t)((blockIdx.x < 128 ? blockIdx.x >> 4 : 15) * 2 + hsel) * T_SEQ * T_DH;
  kh += hofs; vh += hofs;
  #pragma unroll 1
  for (int r = 16 * warp; r < 16 * warp + 16; r++) {
    const uint32_t ad = (lane >> 4) * 16384 + r * 128 + ((((lane & 15) >> 1) ^ (r & 7)) << 4) + (lane & 1) * 8;
    uint2 qv; asm volatile("ld.shared.v2.u32 {%0, %1}, [%2];" : "=r"(qv.x), "=r"(qv.y) : "r"(sq + ad) : "memory");
    const float q0 = bflo(qv.x), q1 = bfhi(qv.x), q2 = bflo(qv.y), q3 = bfhi(qv.y);
    float m = -INFINITY, l = 0.f, o0 = 0.f, o1 = 0.f, o2 = 0.f, o3 = 0.f;
    #pragma unroll 1
    for (int key = 0; key < T_SEQ; key++) {
      const uint2 kv = *reinterpret_cast<const uint2*>(kh + (size_t)key * T_DH + lane * 4);
      const uint2 vv = *reinterpret_cast<const uint2*>(vh + (size_t)key * T_DH + lane * 4);
      float sc = (q0 * bflo(kv.x) + q1 * bfhi(kv.x)) + (q2 * bflo(kv.y) + q3 * bfhi(kv.y));
      #pragma unroll
      for (int o = 16; o > 0; o >>= 1) sc += __shfl_xor_sync(0xffffffffu, sc, o);
      const float mn = fmaxf(m, sc);
      const float al = (m == mn) ? 1.0f : ex2_approx(m - mn), p = rbf(ex2_approx(sc - mn));
      m = mn;
      l = fmaf(l, al, p);
      o0 = fmaf(o0, al, p * bflo(vv.x)); o1 = fmaf(o1, al, p * bfhi(vv.x));
      o2 = fmaf(o2, al, p * bflo(vv.y)); o3 = fmaf(o3, al, p * bfhi(vv.y));
    }
    const float inv = rcp_approx(l);
    asm volatile("st.shared.v2.u32 [%0], {%1, %2};" :: "r"(so + ad), "r"(pack_bf16(o0 * inv, o1 * inv)), "r"(pack_bf16(o2 * inv, o3 * inv)) : "memory");
  }
}
__device__ __forceinline__ void issue_qk(float (&s)[64], const uint32_t (&q)[32], uint32_t k_lo) {
  wgmma_fence();
  wgmma_m64n128k16_rs<0>(s, q[0], q[1], q[2], q[3], k_lo, 0);
  wgmma_m64n128k16_rs<2>(s, q[4], q[5], q[6], q[7], k_lo, 1);
  wgmma_m64n128k16_rs<4>(s, q[8], q[9], q[10], q[11], k_lo, 1);
  wgmma_m64n128k16_rs<6>(s, q[12], q[13], q[14], q[15], k_lo, 1);
  wgmma_m64n128k16_rs<1024>(s, q[16], q[17], q[18], q[19], k_lo, 1);
  wgmma_m64n128k16_rs<1026>(s, q[20], q[21], q[22], q[23], k_lo, 1);
  wgmma_m64n128k16_rs<1028>(s, q[24], q[25], q[26], q[27], k_lo, 1);
  wgmma_m64n128k16_rs<1030>(s, q[28], q[29], q[30], q[31], k_lo, 1);
  wgmma_commit();
}
__device__ __forceinline__ void issue_pv(float (&o)[64], const uint32_t (&p)[32], uint32_t v_lo, int accumulate) {
  wgmma_fence();
  wgmma_m64n128k16_rs_tb<0>(o, p[0], p[1], p[2], p[3], v_lo, accumulate);
  wgmma_m64n128k16_rs_tb<128>(o, p[4], p[5], p[6], p[7], v_lo, 1);
  wgmma_m64n128k16_rs_tb<256>(o, p[8], p[9], p[10], p[11], v_lo, 1);
  wgmma_m64n128k16_rs_tb<384>(o, p[12], p[13], p[14], p[15], v_lo, 1);
  wgmma_m64n128k16_rs_tb<512>(o, p[16], p[17], p[18], p[19], v_lo, 1);
  wgmma_m64n128k16_rs_tb<640>(o, p[20], p[21], p[22], p[23], v_lo, 1);
  wgmma_m64n128k16_rs_tb<768>(o, p[24], p[25], p[26], p[27], v_lo, 1);
  wgmma_m64n128k16_rs_tb<896>(o, p[28], p[29], p[30], p[31], v_lo, 1);
  wgmma_commit();
}
__device__ __forceinline__ void block_end(uint32_t zero, uint32_t bar) {
  #pragma unroll 1
  for (uint32_t i = 0; i < zero; i++) mbar_arrive(bar);
}
__device__ __forceinline__ void rescale_o(float (&o)[64], float al0, float al1) {
  #pragma unroll
  for (int j = 0; j < 16; j++) { o[4 * j] *= al0; o[4 * j + 1] *= al0; o[4 * j + 2] *= al1; o[4 * j + 3] *= al1; }
}

__device__ __forceinline__ void stage_o(const float (&o)[64], float i0, float i1, uint32_t dst, int lane) {
  #pragma unroll
  for (int J = 0; J < 16; J += 2)
    stmatrix_x4(dst + (J >> 3) * 16384 + ((((J & 7) + (lane >> 4)) ^ (lane & 7)) << 4),
                pack_bf16(o[4 * J + 0] * i0, o[4 * J + 1] * i0), pack_bf16(o[4 * J + 2] * i1, o[4 * J + 3] * i1),
                pack_bf16(o[4 * J + 4] * i0, o[4 * J + 5] * i0), pack_bf16(o[4 * J + 6] * i1, o[4 * J + 7] * i1));
}
__device__ __forceinline__ bool finish_l(float& l0, float& l1) {
  l0 += __shfl_xor_sync(0xffffffffu, l0, 1); l1 += __shfl_xor_sync(0xffffffffu, l1, 1);
  l0 += __shfl_xor_sync(0xffffffffu, l0, 2); l1 += __shfl_xor_sync(0xffffffffu, l1, 2);
  const bool redo = __any_sync(0xffffffffu, !(l0 <= AT_RAW_SUM && l1 <= AT_RAW_SUM && l0 >= AT_RAW_MIN && l1 >= AT_RAW_MIN));
  l0 = rcp_approx(l0); l1 = rcp_approx(l1);
  return redo;
}
template <int J0>
__device__ __forceinline__ void stage_q(const float (&acc)[128], float c, uint32_t dst, int lane) {
  #pragma unroll
  for (int J = J0; J < J0 + 16; J += 2)
    stmatrix_x4(dst + (J >> 3) * 16384 + ((((J & 7) + (lane >> 4)) ^ (lane & 7)) << 4),
                pack_bf16(acc[4 * J + 0] * c, acc[4 * J + 1] * c), pack_bf16(acc[4 * J + 2] * c, acc[4 * J + 3] * c),
                pack_bf16(acc[4 * J + 4] * c, acc[4 * J + 5] * c), pack_bf16(acc[4 * J + 6] * c, acc[4 * J + 7] * c));
}
__device__ __forceinline__ void store_o(const CUtensorMap* tmO, uint32_t src, int head, int row) {
  tma_store_2d(tmO, src, head * T_DH, row);
  tma_store_2d(tmO, src + 16384, head * T_DH + 64, row);
  bulk_commit();
}
__device__ __forceinline__ void mma_bf16(float (&d)[4], uint32_t a0, uint32_t a1, uint32_t a2, uint32_t a3, uint32_t b0, uint32_t b1) {
  asm volatile("mma.sync.aligned.m16n8k16.row.col.f32.bf16.bf16.f32 {%0, %1, %2, %3}, {%4, %5, %6, %7}, {%8, %9}, {%0, %1, %2, %3};"
               : "+f"(d[0]), "+f"(d[1]), "+f"(d[2]), "+f"(d[3]) : "r"(a0), "r"(a1), "r"(a2), "r"(a3), "r"(b0), "r"(b1));
}
struct GemvSel { uint32_t lo0, hi0, lo1, hi1; };
__device__ __forceinline__ GemvSel gemv_sel(int lane) {
  const uint32_t lo = (lane & 8) ? 0x1044u : 0x4410u, hi = (lane & 8) ? 0x3244u : 0x4432u;
  GemvSel s; s.lo0 = (lane & 16) ? 0x4444u : lo; s.hi0 = (lane & 16) ? 0x4444u : hi; s.lo1 = (lane & 16) ? lo : 0x4444u; s.hi1 = (lane & 16) ? hi : 0x4444u;
  return s;
}
#define GEMV_B0(j, h, s) __byte_perm((j) < 2 ? (h).x : (h).y, 0u, ((j) & 1) ? (s).hi0 : (s).lo0)
#define GEMV_B1(j, h, s) __byte_perm((j) < 2 ? (h).x : (h).y, 0u, ((j) & 1) ? (s).hi1 : (s).lo1)
__device__ __forceinline__ float4 gemv_out(const float (&d)[4], int lane) {
  const bool tk = lane & 1;
  const float r0 = __shfl_xor_sync(0xffffffffu, tk ? d[0] : d[1], 1), r1 = __shfl_xor_sync(0xffffffffu, tk ? d[2] : d[3], 1);
  return tk ? make_float4(r0, d[1], r1, d[3]) : make_float4(d[0], r0, d[2], r1);
}
#define OG_NG 8
#define PUT_N 2
#define H_STAG 2
#define NOZERO 1
#define PVPIN 1
#define QKPIN 0
#define ALIGN 1
#define AL_P 60
#define AL_SLEEP 1200
#define AL_MAX 800
#define AL_ADD 0
#define X_PF 0
#define POLL_NS 200
#define KV3D 1
#define W3D 1
#define ARV_IMM 1
#define ZS 1
#define OG_PRE 10
#define OG_PRE2 12
#define SERP 1
#define OG_JOBS 7
#define OG_GRP 6
#define LD_FIRST 3
#define LD_STAG (OG_GRP / 2)
constexpr int OG_ST = 5, OG_NKB = T_DQKV / 64 - OG_PRE, OG_MOE = T_F / 32;
__device__ __forceinline__ int pre_kb(int i) { return (i >> 1) * 4 + (i & 1); }
__device__ __forceinline__ int own_kb(int i) { return i < OG_PRE2 ? pre_kb(i) + 2 : i < 64 - OG_PRE2 ? i + OG_PRE2 : pre_kb(i - (64 - OG_PRE2 - OG_PRE)); }
constexpr int OG_POS = 8;
constexpr uint32_t OG_STAGE = 32768;
constexpr uint32_t OG_SCOL = AT_SBAR + 512;
constexpr uint32_t OG_SMISC = AT_SBAR + 2048;
constexpr int OG_XPOS = OG_POS + OG_NKB;
constexpr uint32_t OG_SWD = AT_SQ, OG_PSLOT = AT_SQ;
constexpr uint32_t OG_SWD1 = (OG_XPOS % OG_ST) * OG_STAGE;
constexpr uint32_t OG_XSLOT = AT_SQ + 32768;
constexpr uint32_t OG_OSLOT = ((OG_XPOS + 1) % OG_ST) * OG_STAGE;
constexpr uint32_t OG_SH2 = ((OG_XPOS + 2) % OG_ST) * OG_STAGE;
constexpr uint32_t OG_SRED = ((OG_XPOS + 3) % OG_ST) * OG_STAGE;
constexpr uint32_t OG_SSTAT = OG_SRED + 16384;
constexpr uint32_t OG_SGU = OG_SRED + 8192;
constexpr uint32_t OG_SFIN = OG_SGU + 256;
#define OGM 2
#define OG_MT(b) ((((b) >> OGM) & 15) ^ (SERP && ((b) & 64) ? 15 : 0))
#define OG_NT(b) (((b) & ((1 << OGM) - 1)) + (((b) >> (4 + OGM)) << OGM))
#define TAIL_SETUP \
  const uint32_t bar_full = sbase + AT_SBAR, bar_empty = bar_full + 40; \
  const uint32_t bar_wd = bar_full + 168, bar_col = bar_full + 176, bar_out = bar_full + 184, bar_end = bar_full + 192; \
  const uint32_t bar_key = bar_full + 200, bar_h2 = bar_full + 208, bar_sel = bar_full + 216; \
  const int mt = OG_MT(blockIdx.x), nt = OG_NT(blockIdx.x); \
  const int m0 = mt * 128, n0 = nt * 128; \
  const bool has_moe = (int)blockIdx.x < OG_MOE; \
  (void)bar_empty; (void)bar_wd; (void)bar_col; (void)bar_out; (void)bar_end; (void)bar_key; (void)bar_h2; (void)bar_sel; (void)m0; (void)n0; (void)has_moe;

__device__ __forceinline__ void tail_producer(uint32_t sbase, uint32_t ph, uint64_t pol, const CUtensorMap* tmA, const CUtensorMap* tmB, const CUtensorMap* tmX) {
  TAIL_SETUP
  uint32_t stage = OG_POS % OG_ST;
  int kb = 0;
  #pragma unroll 1
  for (int seg = 0; seg < 2; seg++) {
    mbar_wait(bar_full + 264 + 80 * seg, 0);
    fence_proxy_async_global();
    const int end = seg == 0 ? 32 - OG_PRE2 : has_moe ? OG_NKB : 64 - OG_PRE2;
    #pragma unroll 1
    for (; kb < end; kb++) {
      const uint32_t fb = bar_full + 8 * stage, sa = sbase + stage * OG_STAGE;
      const int k0 = own_kb(kb) * 64;
      mbar_wait(bar_empty + 8 * stage, ph);
      mbar_expect_tx(fb, OG_STAGE);
      tma_load_3d_hint(sa + 16384, tmB, k0, 2 * nt, fb, pol);
      tma_load_2d_hint(sa, tmA, k0, m0, fb, pol);
      if (++stage == OG_ST) { stage = 0; ph ^= 1; }
    }
  }
  if (has_moe) {
    mbar_wait(bar_empty + 8 * (OG_XPOS % OG_ST), ph);
    mbar_expect_tx(bar_wd, OG_STAGE);
    tma_load_3d_hint(sbase + OG_SWD1, tmX, blockIdx.x * 32, 8, bar_wd, pol);
  }
}

__device__ __forceinline__ uint32_t out2(uint32_t x1, uint32_t mb2, uint32_t ih, uint32_t il, uint32_t c1, uint32_t sb, uint32_t gb) {
  const uint32_t h2 = badd2(bmul2(ln_norm2b(x1, mb2, ih, il), c1), sb);
  return badd2(x1, bmul2(gb, bfma2(h2, 0u, h2)));
}
#define OGTIME gtime()
#define PRE_N 1
#define PRE_PACE 150
#define X_PACE 200
#define WD_LATE 0
#define WD_PACE 300
__device__ __forceinline__ void tail_exchange(uint32_t sbase, const CUtensorMap* tmOut, const bf16* __restrict__ w_down, const bf16* __restrict__ w_r, const bf16* __restrict__ x, bf16* __restrict__ out) {
    TAIL_SETUP
    const int lane = threadIdx.x & 31, wi = __shfl_sync(0xffffffffu, threadIdx.x >> 5, 0);
    if (wi == 3) {
      if (blockIdx.x < AT_NFULL) {
        uint32_t a, b;
        asm volatile("ld.relaxed.gpu.global.u32 %0, [%1];" : "=r"(a) : "l"(g_smid + 32 + blockIdx.x - lane) : "memory");
        b = __shfl_down_sync(0xffffffffu, a, 1);
        unsigned int* tm = g_tmax + blockIdx.x - min((int)blockIdx.x, __ffs(__ballot_sync(0xffffffffu, b >= a)) - 1);
        mbar_wait(bar_full + 312, 0);
        if (lane == 0) {
          asm volatile("mov.u32 %0, %%globaltimer_lo;" : "=r"(a));
          asm volatile("red.relaxed.gpu.global.max.u32 [%0], %1;" :: "l"(tm), "r"(a) : "memory");
          __nanosleep(AL_SLEEP);
          asm volatile("ld.relaxed.gpu.global.u32 %0, [%1];" : "=r"(b) : "l"(tm) : "memory");
          b -= a;
          sts_u32(sbase + OG_SMISC + 32, (b < AL_MAX ? b * 13 / 8 : 0u) + AL_ADD);
          mbar_arrive(bar_full + 320);
        }
        named_bar_sync(15, 32);
      }
      mbar_wait(bar_full + 344, 0);
      float a = g_scal[lane], b = g_scal[32 + lane];
      #pragma unroll
      for (int i = 0; i < 3; i++) {
        const uint4 v = *reinterpret_cast<const uint4*>(g_col + nt * 1536 + i * 512 + lane * 16);
        sts_u32x4(sbase + OG_SCOL + i * 512 + lane * 16, v.x, v.y, v.z, v.w);
      }
      #pragma unroll
      for (int o = 16; o > 0; o >>= 1) { a += __shfl_xor_sync(0xffffffffu, a, o); b += __shfl_xor_sync(0xffffffffu, b, o); }
      if (lane == 0) sts_f32x2(sbase + OG_SMISC, a, b);
      const uint64_t pol = policy_evict_first();
      #pragma unroll 1
      for (int r = lane >> 4; r < 128; r += 4) {
        __nanosleep(X_PACE);
        #pragma unroll
        for (int j = 0; j < 4; j += 2)
          asm volatile("cp.async.cg.shared.global.L2::cache_hint [%0], [%1], 16, %2;" :: "r"(sbase + OG_XSLOT + (lane & 8) * 2048 + (r + j) * 128 + (((lane ^ (r + j)) & 7) << 4)),
                       "l"(x + (size_t)(m0 + r + j) * T_D + n0 + (lane & 15) * 8), "l"(pol) : "memory");
      }
      asm volatile("cp.async.wait_all;" ::: "memory");
      __syncwarp();
      if (lane == 0) mbar_arrive(bar_col);
    } else if (wi == 2) {
      if (elect_one()) {
        const uint32_t b_free = bar_full + (blockIdx.x < AT_NFULL ? 80 : 160);
        mbar_wait(b_free, 0); mbar_wait(b_free, 1);
        #pragma unroll 1
        for (unsigned int i = 0; i < (1u << 20) && ld_acquire(&g_hcnt[32 * (1 + (blockIdx.x >> 3)) + 4 + ((blockIdx.x >> 1) & 3)]) == 0u; i++) __nanosleep(POLL_NS);
        TL_MARK2(23, true);
        fence_proxy_async_global();
        TL_MARK2(4, true);
        mbar_expect_tx(bar_full + 272, 32768);
        #pragma unroll 1
        for (int i = 0; i < PRE_N; i++) {
          bulk_load_hint(sbase + OG_PSLOT + i * (32768 / PRE_N), g_pre + blockIdx.x * 2048 + i * (2048 / PRE_N), 32768 / PRE_N,
                         bar_full + 272, policy_evict_first());
          if (PRE_N > 1) __nanosleep(PRE_PACE);
        }
      }
      named_bar_sync(14, 32);
      if (has_moe) {
        mbar_wait(bar_full + 96, 1); mbar_wait(bar_full + 304, 0);
        const uint64_t pol = policy_evict_first();
        #pragma unroll 1
        for (int r = 0; r < 32; r++) {
          __nanosleep(WD_PACE);
          #pragma unroll
          for (int j = 0; j < 2; j++)
            asm volatile("cp.async.cg.shared.global.L2::cache_hint [%0], [%1], 16, %2;" :: "r"(sbase + OG_SWD + (4 * j + (lane >> 3)) * 4096 + r * 128 + (((lane ^ r) & 7) << 4)),
                         "l"((const uint8_t*)w_down + (size_t)blockIdx.x * 65536 + r * 2048 + j * 512 + lane * 16), "l"(pol) : "memory");
        }
        asm volatile("cp.async.wait_all;" ::: "memory");
        __syncwarp();
        if (lane == 0) mbar_arrive(bar_wd);
      }
    }
    const uint4 wrv = ldg_nc_v4(w_r + threadIdx.x * 8);
    mbar_wait(bar_end, 0);
    if (threadIdx.x == 96) XT(10);
    TL_MARK2(22, lane == 0);
    if (wi == 0) {
      uint32_t k1 = 0u, k2 = 0u;
      #pragma unroll 1
      for (unsigned int spin = 0; spin < (1u << 22) && __any_sync(0xffffffffu, k1 == 0u); spin++) asm volatile("ld.relaxed.gpu.global.u32 %0, [%1];" : "=r"(k1) : "l"(g_key + lane) : "memory");
      TL_MARK2(28, lane == 0);
      warp_top2(k1, k2);
      if (lane == 0) {
        const uint32_t r1 = 0xffffu - (k1 & 0xffffu), r2 = 0xffffu - (k2 & 0xffffu);
        sts_u32x4(sbase + OG_SMISC + 64, r1, r2, (r1 >> 7) * 2, (r2 >> 7) * 2 + ((r1 >> 7) == (r2 >> 7)));
        mbar_arrive(bar_sel);
      }
    } else if (wi < 3) {
          mbar_wait(bar_key, 0);
          const uint4 kk = lds_u32x4(sbase + OG_SSTAT + 1024 + lane * 16);
          uint32_t k1 = max(kk.x, kk.y), k2 = min(kk.x, kk.y);
          k2 = max(max(k2, min(kk.z, kk.w)), min(k1, max(kk.z, kk.w))); k1 = max(k1, max(kk.z, kk.w));
          warp_top2(k1, k2);
          if (wi == 1) {
            if (lane == 0 && nt == (mt & 7)) st_relaxed2(g_key + mt * 2, k1, k2);
            TL_MARK2(27, lane == 0);
          } else {
            const uint32_t r = (~((lane & 16) ? k2 : k1)) & 127u, ch = lane & 15;
            const uint2 st = lds_u32x2(sbase + OG_SSTAT + r * 8);
            const uint4 xc = lds_u32x4(sbase + OG_XSLOT + (ch >> 3) * 16384 + r * 128 + (((ch ^ r) & 7) << 4));
            const uint4 c1 = lds_u32x4(sbase + OG_SCOL + 768 + ch * 16), sh = lds_u32x4(sbase + OG_SCOL + 1024 + ch * 16);
            const float inr = __uint_as_float(st.y);
            float* dst = reinterpret_cast<float*>(g_cand + (mt * 2 + (lane >> 4)) * 256 + nt * 16 + ch);
            st_tagged4(dst + 512, __uint_as_float(ln_mod2(xc.x, st.x, inr, c1.x, sh.x)), __uint_as_float(ln_mod2(xc.y, st.x, inr, c1.y, sh.y)),
                       __uint_as_float(ln_mod2(xc.z, st.x, inr, c1.z, sh.z)), __uint_as_float(ln_mod2(xc.w, st.x, inr, c1.w, sh.w)));
            st_tagged4(dst, __uint_as_float(xc.x), __uint_as_float(xc.y), __uint_as_float(xc.z), __uint_as_float(xc.w));
          }
    }
    mbar_wait(bar_sel, 0);
    const uint4 sel = lds_u32x4(sbase + OG_SMISC + 64);
    const int sel0 = (int)sel.x, sel1 = (int)sel.y;
    {
      const float* src0 = reinterpret_cast<const float*>(g_cand + sel.z * 256 + 128 + threadIdx.x);
      const float* src1 = reinterpret_cast<const float*>(g_cand + sel.w * 256 + 128 + threadIdx.x);
      float4 h0, h1;
      #pragma unroll 1
      for (unsigned int spin = 0; spin < (1u << 20); spin++) { h0 = ld_tagged4(src0); h1 = ld_tagged4(src1); if (__all_sync(0xffffffffu, tagged4(h0) & tagged4(h1))) break; }
      sts_f32x4(sbase + OG_SH2 + threadIdx.x * 16, h0.x, h0.y, h0.z, h0.w);
      sts_f32x4(sbase + OG_SH2 + 2048 + threadIdx.x * 16, h1.x, h1.y, h1.z, h1.w);
      __syncwarp();
      if (lane == 0) mbar_arrive(bar_h2);
      TL_MARK2(12, lane == 0);
      if (blockIdx.x >> 6) h0 = h1;
      float v[8], wr[8];
      unpack8(make_uint4(__float_as_uint(h0.x), __float_as_uint(h0.y), __float_as_uint(h0.z), __float_as_uint(h0.w)), v); unpack8(wrv, wr);
      float r = 0.f;
      #pragma unroll
      for (int i = 0; i < 8; i++) r = fmaf(v[i], wr[i], r);
      #pragma unroll
      for (int o = 16; o > 0; o >>= 1) r += __shfl_xor_sync(0xffffffffu, r, o);
      if (lane == 0) sts_f32(sbase + OG_SMISC + 192 + wi * 4, r);
    }
    mbar_wait(bar_out, 0);
    if ((sel0 >> 7) == mt || (sel1 >> 7) == mt) {
      #pragma unroll 2
      for (int i = 0; i < 16; i++) {
        const int r = i * 8 + (threadIdx.x >> 4), ch = threadIdx.x & 15;
        if (m0 + r != sel0 && m0 + r != sel1)
          *reinterpret_cast<uint4*>(out + (size_t)(m0 + r) * T_D + n0 + ch * 8) =
              lds_u32x4(sbase + OG_OSLOT + (ch >> 3) * 16384 + r * 128 + (((ch & 7) ^ (r & 7)) << 4));
      }
    } else if (threadIdx.x == 0) {
      tma_store_2d(tmOut, sbase + OG_OSLOT, n0, m0);
      tma_store_2d(tmOut, sbase + OG_OSLOT + 16384, n0 + 64, m0);
      bulk_commit();
    }
    if (blockIdx.x == 0 && threadIdx.x < 68) *reinterpret_cast<uint4*>(g_hcnt + 32 * (threadIdx.x >> 2) + 4 * (threadIdx.x & 3)) = make_uint4(0u, 0u, 0u, 0u);
    if (threadIdx.x < 64) g_modpart[blockIdx.x * 64 + threadIdx.x] = 0.f;
    if (ALIGN && threadIdx.x == 64) g_tmax[blockIdx.x] = 0u;
    {
      const int tk = blockIdx.x >> 6, c0 = (blockIdx.x & 63) * 16;
      const uint32_t gb2 = *reinterpret_cast<const uint32_t*>(g_col + (c0 >> 7) * 1536 + 512 + 768 + ((c0 & 127) + (threadIdx.x & 14)) * 2);
      const uint32_t* xp = reinterpret_cast<const uint32_t*>(g_cand + (tk ? sel.w : sel.z) * 256) + ((c0 + (threadIdx.x & 14)) >> 1);
      uint32_t x2 = 0u;
      #pragma unroll 1
      for (unsigned int spin = 0; spin < (1u << 20) && __any_sync(0xffffffffu, x2 == 0u); spin++) asm volatile("ld.relaxed.gpu.global.u32 %0, [%1];" : "=r"(x2) : "l"(xp) : "memory");
      const float* src = g_ypart + (size_t)((threadIdx.x >> 2) * 2 + tk) * T_D + c0 + (threadIdx.x & 3) * 4;
      const bool four = threadIdx.x < (OG_MOE - 96) * 4;
      if (threadIdx.x == 0) hint_wait(CNT_Y, (uint32_t)OG_MOE);
      named_bar_sync(10, 128);
      float4 p0, p1, p2, p3;
      #pragma unroll 1
      for (unsigned int spin = 0; spin < (1u << 20); spin++) {
        p0 = ld_tagged4(src); p1 = ld_tagged4(src + 64 * T_D); p2 = ld_tagged4(src + 128 * T_D); p3 = ld_tagged4(four ? src + 192 * T_D : src);
        if (__all_sync(0xffffffffu, tagged4(p0) & tagged4(p1) & tagged4(p2) & tagged4(p3))) break;
      }
      if (four) { p2.x += p3.x; p2.y += p3.y; p2.z += p3.z; p2.w += p3.w; }
      p0.x = (p0.x + p1.x) + p2.x; p0.y = (p0.y + p1.y) + p2.y; p0.z = (p0.z + p1.z) + p2.z; p0.w = (p0.w + p1.w) + p2.w;
      #pragma unroll
      for (int o = 4; o <= 16; o <<= 1) {
        p0.x += __shfl_xor_sync(0xffffffffu, p0.x, o); p0.y += __shfl_xor_sync(0xffffffffu, p0.y, o);
        p0.z += __shfl_xor_sync(0xffffffffu, p0.z, o); p0.w += __shfl_xor_sync(0xffffffffu, p0.w, o);
      }
      if (lane < 4) sts_f32x4(sbase + OG_SFIN + (threadIdx.x >> 5) * 64 + lane * 16, p0.x, p0.y, p0.z, p0.w);
      named_bar_sync(10, 128);
      TL_MARK2(21, threadIdx.x == 0);
      if (threadIdx.x < 16) {
        const uint32_t ya = sbase + OG_SFIN + threadIdx.x * 4, rp = sbase + OG_SMISC + 192;
        float y = (lds_f32(ya) + lds_f32(ya + 64)) + (lds_f32(ya + 128) + lds_f32(ya + 192));
        const float r = rbf((lds_f32(rp) + lds_f32(rp + 4)) + (lds_f32(rp + 8) + lds_f32(rp + 12)));
        const float rs = rbf(sigmoid_f(r));
        const uint32_t h2p = lds_u32(sbase + OG_SH2 + tk * 2048 + (c0 + (threadIdx.x & 14)) * 2);
        const float fh = (lane & 1) ? bfhi(h2p) : bflo(h2p);
        y = rbf(y);
        y = rbf(y * rs);
        const float upd = rbf(rbf(fh * 0.0f) + y);
        out[(size_t)(tk ? sel1 : sel0) * T_D + c0 + threadIdx.x] =
            __float2bfloat16_rn(((lane & 1) ? bfhi(x2) : bflo(x2)) + rbf(((lane & 1) ? bfhi(gb2) : bflo(gb2)) * rbf(fh + upd)));
      }
      if (threadIdx.x == 0) bulk_wait_read<0>();
    }
    if (threadIdx.x == 0) XT(11);
    TL_END(4, threadIdx.x == 0);
}

__device__ __forceinline__ void load_pre(uint4* pre, uint32_t sbase, uint32_t buf, int t2) {
  mbar_wait(sbase + AT_SBAR + 272, 0);
  #pragma unroll
  for (int i = 0; i < 8; i++) pre[i] = lds_u32x4(sbase + buf + i * 4096 + t2 * 16);
}
__device__ __forceinline__ void tail_consumer(uint32_t sbase, const uint4 (&pre)[8], int cwg, const bf16* __restrict__ w_gate, const bf16* __restrict__ w_up) {
    TAIL_SETUP
    const int tid = threadIdx.x & 127, t2 = threadIdx.x - 128;
    const int warp = tid >> 5, lane = tid & 31, w8 = t2 >> 5;
    const uint32_t dbase = (sbase & 0x3FFFFu) >> 4;
    const uint32_t a_base = dbase + ((cwg * 8192) >> 4) + (1u << 16);
    const uint32_t b_base = dbase + (16384 >> 4) + (512u << 16);
    TL_MARK2(25, threadIdx.x == 128);
    const uint64_t pol = policy_evict_first();
    const bf16* pw = ((lane & 16) ? w_up : w_gate) + (size_t)(w8 * 128 + (lane & 3) * 4) * T_F + (has_moe ? blockIdx.x : 0) * 32 + ((lane >> 2) & 3) * 8;
    uint4 wv[32];
    float acc[64];
    #pragma unroll
    for (int i = 0; i < 8; i++) {
      acc[8 * i] = bflo(pre[i].x); acc[8 * i + 1] = bfhi(pre[i].x); acc[8 * i + 2] = bflo(pre[i].y); acc[8 * i + 3] = bfhi(pre[i].y);
      acc[8 * i + 4] = bflo(pre[i].z); acc[8 * i + 5] = bfhi(pre[i].z); acc[8 * i + 6] = bflo(pre[i].w); acc[8 * i + 7] = bfhi(pre[i].w);
    }
    if (lane == 0) mbar_arrive(bar_full + 304);
    if (blockIdx.x < AT_NFULL) {
      const uint32_t c0 = clock_lo();
      mbar_wait(bar_full + 320, 0);
      const uint32_t d = lds_u32(sbase + OG_SMISC + 32);
      while (clock_lo() - c0 < d) {}
    }
    {
      uint32_t stage = OG_POS % OG_ST, phase = (OG_POS / OG_ST) & 1, prev = 12;
      int kb = 0;
      #pragma unroll
      for (int g = 0; g <= OG_NG; g++) {
        const int end = g == OG_NG ? (has_moe ? OG_NKB : 64 - OG_PRE2) : LD_FIRST + g * OG_GRP + LD_STAG * cwg;
        #pragma unroll 1
        do {
          mbar_wait(bar_full + 8 * stage, phase);
          const uint32_t a_lo = a_base + stage * (OG_STAGE >> 4), b_lo = b_base + stage * (OG_STAGE >> 4);
          wgmma_fence();
          wgmma_m64n128k16_ss_tb<0, 0>(acc, a_lo, b_lo, 1);
          wgmma_m64n128k16_ss_tb<2, 128>(acc, a_lo, b_lo, 1);
          wgmma_m64n128k16_ss_tb<4, 256>(acc, a_lo, b_lo, 1);
          wgmma_m64n128k16_ss_tb<6, 384>(acc, a_lo, b_lo, 1);
          wgmma_commit();
          wgmma_wait<1>();
          if (tid == 0) mbar_arrive(bar_empty + 8 * prev);
          prev = stage;
          if (++stage == OG_ST) { stage = 0; phase ^= 1; }
        } while (++kb < end);
        #pragma unroll
        for (int j = 4 * g; j < 4 * g + 4 && j < 32; j++) wv[j] = ldg_stream_v4(pw + (size_t)(16 * (j >> 2) + (j & 3)) * T_F, pol);
      }
    }
    mbar_wait(bar_col, 0);
    if (__builtin_expect(!has_moe, 0)) {
      load_pre(wv, sbase, AT_SQ, t2);
    }
    wgmma_wait<0>();
    fence_regs(acc);
    if (__builtin_expect(!has_moe, 0)) {
      #pragma unroll
      for (int i = 0; i < 8; i++) {
        acc[8 * i] += bflo(wv[i].x); acc[8 * i + 1] += bfhi(wv[i].x); acc[8 * i + 2] += bflo(wv[i].y); acc[8 * i + 3] += bfhi(wv[i].y);
        acc[8 * i + 4] += bflo(wv[i].z); acc[8 * i + 5] += bfhi(wv[i].z); acc[8 * i + 6] += bflo(wv[i].w); acc[8 * i + 7] += bfhi(wv[i].w);
      }
    }
    if (tid == 0) mbar_arrive(bar_end);
    TL_MARK2(9, lane == 0);
    const int q2 = 2 * (lane & 3);
    const uint32_t frag = (64 * cwg + 16 * warp + (lane & 7) + 8 * ((lane >> 3) & 1)) * 128;
    const int fsw = lane & 7, fhi = lane >> 4;
    {
      float dl[4] = {0.f, 0.f, 0.f, 0.f}, da[4] = {0.f, 0.f, 0.f, 0.f}, db[4] = {0.f, 0.f, 0.f, 0.f};
      const uint32_t tb = sbase + OG_SCOL + (lane & 8) * 32 + (lane & 3) * 8, g = lane >> 2;
      const uint32_t msk = (g == 1 || g == 2) ? 0xffffffffu : 0u, one = g == 0 ? 0x3F803F80u : 0u;
      #pragma unroll
      for (int J = 0; J < 16; J += 2) {
        const uint32_t ad = sbase + OG_XSLOT + (J >> 3) * 16384 + frag + ((((J & 7) + fhi) ^ fsw) << 4);
        uint32_t xr[4];
        ldmatrix_x4(ad, xr[0], xr[1], xr[2], xr[3]);
        const uint2 cw = lds_u32x2(tb + J * 16);
        #pragma unroll
        for (int h = 0; h < 2; h++) {
          const uint32_t ga = lds_u32(sbase + OG_SCOL + 512 + (8 * (J + h) + q2) * 2);
          xr[2 * h] = badd2(xr[2 * h], bmul2(ga, pack_bf16(acc[4 * (J + h)], acc[4 * (J + h) + 1])));
          xr[2 * h + 1] = badd2(xr[2 * h + 1], bmul2(ga, pack_bf16(acc[4 * (J + h) + 2], acc[4 * (J + h) + 3])));
        }
        stmatrix_x4(ad, xr[0], xr[1], xr[2], xr[3]);
        mma_bf16(dl, xr[0], xr[1], xr[2], xr[3], (cw.x & msk) | one, (cw.y & msk) | one);
        mma_bf16(da, xr[0], xr[1], xr[2], xr[3], xr[0], xr[2]);
        mma_bf16(db, xr[0], xr[1], xr[2], xr[3], xr[1], xr[3]);
      }
      {
        const int dsrc = (lane & ~3) + (g >> 1);
        const float qa = __shfl_sync(0xffffffffu, (g & 1) ? da[1] : da[0], dsrc), qb = __shfl_sync(0xffffffffu, (g & 1) ? db[3] : db[2], dsrc);
        const float e0 = __shfl_xor_sync(0xffffffffu, (lane & 1) ? dl[0] : dl[2], 1), e1 = __shfl_xor_sync(0xffffffffu, dl[3], 1);
        if ((lane & 3) < 2) {
          const bool hi = lane & 1;
          st_tagged4(reinterpret_cast<float*>(g_part1 + ((mt * 8 + w8) * 8 + nt) * 16 + g + (hi ? 8 : 0)),
                     hi ? e0 : dl[0], hi ? qb : qa, hi ? e1 + dl[2] : dl[1] + e0, 1.0f);
        }
      }
    }
    TL_MARK2(10, lane == 0);
    uint4 wd[16];
    if (has_moe) mbar_wait(bar_wd, 0);
    #pragma unroll
    for (int i = 0; i < 16; i++) wd[i] = lds_u32x4(sbase + (cwg ? OG_SWD1 : OG_SWD) + warp * 8192 + (i >> 3) * 4096 + (i & 6) * 512 + (i & 1) * 128 + (lane & 3) * 256 + (((lane >> 2) ^ (2 * (lane & 3) + (i & 1))) << 4));
    {
      const float* src = reinterpret_cast<const float*>(g_part1 + ((mt * 8 + w8) * 8 + (lane & 1) * 4) * 16 + (lane >> 1));
      float4 v, v1, v2, v3;
      #pragma unroll 1
      for (unsigned int spin = 0; spin < (1u << 22); spin++) {
        v = ld_tagged4(src); v1 = ld_tagged4(src + 64); v2 = ld_tagged4(src + 128); v3 = ld_tagged4(src + 192);
        if (__all_sync(0xffffffffu, tagged4(v) & tagged4(v1) & tagged4(v2) & tagged4(v3))) break;
        __nanosleep(100);
      }
      __syncwarp();
      TL_MARK2(26, lane == 0);
      v.x = (v.x + v1.x) + (v2.x + v3.x); v.y = (v.y + v1.y) + (v2.y + v3.y); v.z = (v.z + v1.z) + (v2.z + v3.z);
      v.x += __shfl_xor_sync(0xffffffffu, v.x, 1); v.y += __shfl_xor_sync(0xffffffffu, v.y, 1); v.z += __shfl_xor_sync(0xffffffffu, v.z, 1);
      const float mean = v.x * (1.0f / T_D);
      const float var = fmaxf(fmaf(-mean, mean, v.y * (1.0f / T_D)), 0.f);
      const uint32_t mb2 = pack_bf16(mean, mean);
      const float inv = rcp_approx(rbf(sqrt_approx(rbf(rbf(var) + 1e-05f))));
      {
        const float2 sc = lds_f32x2(sbase + OG_SMISC);
        const uint32_t key = rank_key(rbf(fmaf(fmaf(-bflo(mb2), sc.x, v.z), inv, sc.y)), m0 + 16 * w8 + (lane >> 1));
        mbar_wait(bar_end, 0);
        if (lane & 1) sts_u32(sbase + OG_SSTAT + 1024 + (16 * w8 + (lane >> 1)) * 4, key);
        else sts_u32x2(sbase + OG_SSTAT + (16 * w8 + (lane >> 1)) * 8, mb2, __float_as_uint(inv));
        __syncwarp();
        if (lane == 0) mbar_arrive(bar_key);
      }
      const uint32_t ih = pack_bf16(inv, inv), il = pack_bf16(inv - bflo(ih), inv - bflo(ih));
      const uint32_t mba = __shfl_sync(0xffffffffu, mb2, 2 * (lane >> 2)), mbb = __shfl_sync(0xffffffffu, mb2, 2 * (lane >> 2) + 16);
      const uint32_t iha = __shfl_sync(0xffffffffu, ih, 2 * (lane >> 2)), ihb = __shfl_sync(0xffffffffu, ih, 2 * (lane >> 2) + 16);
      const uint32_t ila = __shfl_sync(0xffffffffu, il, 2 * (lane >> 2)), ilb = __shfl_sync(0xffffffffu, il, 2 * (lane >> 2) + 16);
      #pragma unroll 2
      for (int J = 0; J < 16; J += 2) {
        const uint32_t off = (J >> 3) * 16384 + frag + ((((J & 7) + fhi) ^ fsw) << 4);
        uint32_t xr[4];
        ldmatrix_x4(sbase + OG_XSLOT + off, xr[0], xr[1], xr[2], xr[3]);
        #pragma unroll
        for (int h = 0; h < 2; h++) {
          const uint32_t ca = sbase + OG_SCOL + 512 + (8 * (J + h) + q2) * 2;
          const uint32_t c1 = lds_u32(ca + 256), sh = lds_u32(ca + 512), gb = lds_u32(ca + 768);
          xr[2 * h] = out2(xr[2 * h], mba, iha, ila, c1, sh, gb);
          xr[2 * h + 1] = out2(xr[2 * h + 1], mbb, ihb, ilb, c1, sh, gb);
        }
        stmatrix_x4(sbase + OG_OSLOT + off, xr[0], xr[1], xr[2], xr[3]);
      }
      fence_proxy_async();
      __syncwarp();
      if (lane == 0) mbar_arrive(bar_out);
      TL_MARK2(24, lane == 0);
    }
    if (has_moe) mbar_wait(bar_h2, 0);
    TL_MARK2(13, lane == 0);
    if (has_moe) {
      const GemvSel sel = gemv_sel(lane);
      {
        float d[4][4];
        #pragma unroll
        for (int c = 0; c < 4; c++) { d[c][0] = 0.f; d[c][1] = 0.f; d[c][2] = 0.f; d[c][3] = 0.f; }
        #pragma unroll
        for (int st = 0; st < 8; st++) {
          const uint2 hb = lds_u32x2(sbase + OG_SH2 + ((lane >> 2) & 1) * 2048 + (w8 * 128 + st * 16 + (lane & 3) * 4) * 2);
          #pragma unroll
          for (int j = 0; j < 4; j++) mma_bf16(d[j], wv[4 * st + j].x, wv[4 * st + j].y, wv[4 * st + j].z, wv[4 * st + j].w, GEMV_B0(j, hb, sel), GEMV_B1(j, hb, sel));
        }
        #pragma unroll
        for (int e = 0; e < 4; e++) d[0][e] = (d[0][e] + d[1][e]) + (d[2][e] + d[3][e]);
        const float4 r = gemv_out(d[0], lane);
        sts_f32x4(sbase + OG_SRED + w8 * 512 + (((lane >> 4) * 2 + (lane & 1)) * 32 + ((lane >> 2) & 3) * 8 + (lane & 2) * 2) * 4, r.x, r.y, r.z, r.w);
      }
      named_bar_sync(9, 256);
      if (t2 < 64) {
        float gp[8], up[8];
        #pragma unroll
        for (int w = 0; w < 8; w++) { gp[w] = lds_f32(sbase + OG_SRED + w * 512 + t2 * 4); up[w] = lds_f32(sbase + OG_SRED + w * 512 + 256 + t2 * 4); }
        const float gs = ((gp[0] + gp[1]) + (gp[2] + gp[3])) + ((gp[4] + gp[5]) + (gp[6] + gp[7]));
        const float us = ((up[0] + up[1]) + (up[2] + up[3])) + ((up[4] + up[5]) + (up[6] + up[7]));
        asm volatile("st.shared.u16 [%0], %1;" :: "r"(sbase + OG_SGU + ((t2 & ~15) + ((t2 >> 1) & 3) * 4 + ((t2 >> 3) & 1) * 2 + (t2 & 1)) * 2), "h"((uint16_t)pack_bf16(silu_bf(rbf(gs)) * rbf(us), 0.f)) : "memory");
      }
      named_bar_sync(9, 256);
      TL_MARK2(20, threadIdx.x == 128);
      float d[4][4];
      #pragma unroll
      for (int c = 0; c < 4; c++) { d[c][0] = 0.f; d[c][1] = 0.f; d[c][2] = 0.f; d[c][3] = 0.f; }
      #pragma unroll
      for (int st = 0; st < 2; st++) {
        const uint2 g = lds_u32x2(sbase + OG_SGU + ((lane >> 2) & 1) * 64 + st * 32 + (lane & 3) * 8);
        #pragma unroll
        for (int j = 0; j < 4; j++) {
          const uint32_t b0 = GEMV_B0(j, g, sel), b1 = GEMV_B1(j, g, sel);
          mma_bf16(d[j & 1], wd[4 * st + j].x, wd[4 * st + j].y, wd[4 * st + j].z, wd[4 * st + j].w, b0, b1);
          mma_bf16(d[2 + (j & 1)], wd[8 + 4 * st + j].x, wd[8 + 4 * st + j].y, wd[8 + 4 * st + j].z, wd[8 + 4 * st + j].w, b0, b1);
        }
      }
      #pragma unroll
      for (int e = 0; e < 4; e++) { d[0][e] += d[1][e]; d[2][e] += d[3][e]; }
      const float4 y0 = gemv_out(d[0], lane), y1 = gemv_out(d[2], lane);
      float* yp = g_ypart + (size_t)(blockIdx.x * 2 + (lane & 1)) * T_D + w8 * 128 + (lane >> 2) * 8 + (lane & 2) * 2;
      st_tagged4(yp, y0.x, y0.y, y0.z, y0.w);
      st_tagged4(yp + 64, y1.x, y1.y, y1.z, y1.w);
      named_bar_sync(9, 256);
      if (t2 == 0) hint_arrive(CNT_Y);
    }
    TL_MARK2(14, threadIdx.x == 128);
    TL_CLK(4, 1, threadIdx.x == 128);
}

#define OG_JOBS2 (16 - OG_JOBS)
__device__ __forceinline__ int help_njobs() { return blockIdx.x < 128 ? OG_JOBS : OG_JOBS2; }
__device__ __forceinline__ int help_job(int i) { return (i < OG_JOBS ? 16 * i + (blockIdx.x >> 7) * 2 : 112 + (i - OG_JOBS) * 2) + (blockIdx.x & 3) * 4; }
__device__ __noinline__ void store_warp(uint32_t sbase, const CUtensorMap* tmO, int item0, int n_items) {
  if (elect_one()) {
    const uint32_t bars = sbase + AT_SBAR, b_q0 = bars + 80, b_ob = bars + 96, b_ordy = bars + 104, b_acq = bars + 264;
    const unsigned int* cnt = &g_hcnt[32 * (1 + OG_MT(blockIdx.x)) + 2];
    #pragma unroll 1
    for (int q = 0; q < 4 * n_items; q++) {
      const int item = item0 + (q >> 2) * 128, h = (q >> 1) & 1, w = q & 1;
      const bool last = (q >> 2) == n_items - 1;
      if (q == 4 * n_items - 4) { mbar_wait(bars + 288, 0); red_release_add(&g_hcnt[1], 1u); }
      mbar_wait(b_ordy + 8 * (q & 3), q >> 2);
      store_o(tmO, (h ? (last ? sbase + AT_SQ + 32768 : sbase + 2 * 32768) : sbase + AT_SQ) + w * 8192, (item >> 4) * 2 + h, (item & 15) * 128 + w * 64);
      if (w) {
        bulk_wait_read<0>();
        mbar_arrive(h ? b_ob : b_q0);
        bulk_wait<0>();
        fence_proxy_async_global();
        asm volatile("fence.acq_rel.gpu;" ::: "memory");
        hint_arrive(&g_hcnt[32 * (1 + (item & 15)) + 2 + (item >> 7)]);
        if (!h && item < 128) hint_arrive(&g_hcnt[2]);
        if (q == 5) { spin_until(cnt, 16u); mbar_arrive(b_acq); }
      }
    }
    if (n_items == 1) {
      #pragma unroll 1
      for (int i = 0; i < help_njobs(); i++) {
        mbar_wait(b_acq + 16, i & 1);
        TL_MARK2(23, i == OG_JOBS - 1);
        red_release_add(&g_hcnt[32 * (1 + (help_job(i) >> 3)) + 4 + ((help_job(i) >> 1) & 3)], 1u);
        TL_MARK2(4, i == OG_JOBS - 1);
        if (i == PRE_X - 1) { spin_until(&g_hcnt[1], 132u); mbar_arrive(b_acq + 32); }
      }
    }
    if (blockIdx.x < 128) {
      if (n_items == 1) { spin_until(cnt, 16u); mbar_arrive(b_acq); }
      spin_until(&g_hcnt[0], 128u); spin_until(cnt + 1, 16u); mbar_arrive(b_acq + 80);
    }
  }
}

__global__ void __launch_bounds__(384, 1)
fused_kernel(const __grid_constant__ CUtensorMap tmH, const __grid_constant__ CUtensorMap tmW, const __grid_constant__ CUtensorMap tmK,
            const __grid_constant__ CUtensorMap tmV, const __grid_constant__ CUtensorMap tmO, const __grid_constant__ CUtensorMap tmOl, const __grid_constant__ CUtensorMap tmWo,
            const __grid_constant__ CUtensorMap tmX, const __grid_constant__ CUtensorMap tmOut, const __grid_constant__ CUtensorMap tmM, uint32_t zero,
            const uint8_t* __restrict__ pf_wo, const bf16* __restrict__ kc, const bf16* __restrict__ vc,
            const bf16* __restrict__ x, const bf16* __restrict__ cvec, const bf16* __restrict__ w_mod, const bf16* __restrict__ w_r,
            const bf16* __restrict__ w_gate, const bf16* __restrict__ w_up, const bf16* __restrict__ w_down, bf16* __restrict__ out)
{
  extern __shared__ __align__(1024) uint8_t smem_raw[];
  const uint32_t sbase = smem_u32(smem_raw);
  const uint32_t bars = sbase + AT_SBAR;
  const uint32_t b_full = bars, b_empty = bars + 40;
  const uint32_t b_q0 = bars + 80, b_q1 = bars + 88;
  const uint32_t b_ob = bars + 96;
  const uint32_t b_ordy = bars + 104;
  const uint32_t b_pin = bars + 136;
  const uint32_t b_head = bars + 144;
  const uint32_t b_go = bars + 152;
  const uint32_t b_x = bars + 160;
  const int wg = __shfl_sync(0xffffffffu, threadIdx.x >> 7, 0);
  const bool single = blockIdx.x >= AT_NFULL;
  const int item0 = __shfl_sync(0xffffffffu, blockIdx.x < 128 ? (int)blockIdx.x : (int)blockIdx.x + 124, 0), n_items = __shfl_sync(0xffffffffu, single ? 1 : 2, 0);
  TL_START(3);
  if (threadIdx.x == 0) {
    if (sbase & 1023u) __trap();
    for (int i = 0; i < 5; i++) { mbar_init(b_full + 8 * i, 1); mbar_init(b_empty + 8 * i, 2); }
    mbar_init(b_q0, 1); mbar_init(b_q1, 8); mbar_init(b_ob, 1);
    for (int i = 0; i < 4; i++) mbar_init(b_ordy + 8 * i, 4);
    mbar_init(b_pin, 1); mbar_init(b_head, blockIdx.x < 128 ? 8 : 1); mbar_init(b_go, 1); mbar_init(b_x, 1);
    mbar_init(bars + 168, 2); mbar_init(bars + 176, 1); mbar_init(bars + 184, 8); mbar_init(bars + 192, 2);
    mbar_init(bars + 200, 8); mbar_init(bars + 208, 4); mbar_init(bars + 216, 1); mbar_init(bars + 264, 1); mbar_init(bars + 272, 1); mbar_init(bars + 280, 8); mbar_init(bars + 288, 1); mbar_init(bars + 296, 1); mbar_init(bars + 304, 8); mbar_init(bars + 312, 1); mbar_init(bars + 320, 1); mbar_init(bars + 328, 1); mbar_init(bars + 344, 1);
    fence_mbar_init();
  }

  if (wg == 0) {
    reg_dealloc<AT_PREG>();
    if (threadIdx.x < 32) { __syncwarp(); named_bar_arrive(6, 384); }
    if (threadIdx.x >= 64) {
      named_bar_sync(6, 384);
      if (blockIdx.x < 128) {
        named_bar_sync(threadIdx.x >= 96 ? 8 : 9, 288);
        if ((threadIdx.x & 31) == 0) red_release_add(&g_hcnt[32 * (1 + (blockIdx.x >> 3)) + (threadIdx.x >= 96)], 1u);
        TL_MARK2(11, threadIdx.x == 64);
      }
      if (blockIdx.x < 128) {
        mbar_wait(MOD_AT, 0);
        mod_rest(sbase + OG_SCOL, b_q1, threadIdx.x - 64, cvec, w_mod, w_r);
      }
    } else if (threadIdx.x >= 32) {
      named_bar_sync(6, 384);
      store_warp(sbase, &tmO, item0, n_items);
      __syncwarp();
    } else {
     if (elect_one()) {
      const uint64_t pol = policy_evict_first();
      if (blockIdx.x < 128) {
        mbar_expect_tx(b_x, 32768);
        if (X_DLY) { const uint32_t c0 = clock_lo(); while (clock_lo() - c0 < X_DLY) {} }
        bulk_load_hint(sbase + 4 * 32768, x + (size_t)blockIdx.x * 16 * T_D, 32768, b_x, pol);
      }
      prefetch_tmap(&tmW); prefetch_tmap(&tmM); prefetch_tmap(&tmH); prefetch_tmap(&tmWo); prefetch_tmap(&tmOl);
      {
        const uint32_t c0 = clock_lo();
        while (clock_lo() - c0 < W_DLY) {}
        if (blockIdx.x < 128 && (blockIdx.x & 15) >= 4 * H_SPLIT) {
          mbar_expect_tx(bars + 328, 32768);
          tma_load_2d_hint(sbase + 3 * 32768, &tmM, (blockIdx.x & 31) * 64, (blockIdx.x >> 5) * 256, bars + 328, pol);
        }
        while (clock_lo() - c0 < W_DLY + W_FIRST) {}
      }
      uint32_t slot = 0, ph = 1;
      if (ALIGN) { uint32_t sm; asm volatile("mov.u32 %0, %%smid;" : "=r"(sm)); g_smid[32 + blockIdx.x] = sm; }
      #pragma unroll 1
      for (int it = 0; it < n_items; it++) {
        const int item = item0 + it * 128, hp = item >> 4, qt = item & 15;
        const bool first = it == 0;
        #pragma unroll 1
        for (int j = 0; j < T_D / 64; j++) {
          const uint32_t sl = ring_slot(qp_pos(j, it)), fb = b_full + 8 * sl;
          mbar_wait(b_empty + 8 * sl, ring_par(qp_pos(j, it)) ^ ((j >> 2) & 1) ^ 1);
          if (first && j == 3) mbar_wait(b_head, 0);
          mbar_expect_tx(fb, 49152);
          tma_load_3d_hint(sbase + sl * 32768, &tmW, j * 64, hp * 4, fb, pol);
          if (first && j < PRE_B) {
            if (j == PRE_B - 1) {
              spin_until(&g_hcnt[32 * (1 + qt)], 8u);
              TL_MARK2(16, true);
              fence_proxy_async_global();
              #pragma unroll 1
              for (int i = 0; i < PRE_B; i++) tma_load_2d(sbase + AT_SQ + i * 16384, &tmH, i * 64, qt * 128, b_full + 8 * i);
              mbar_arrive(b_go);
            }
          } else {
            if (first && j == 4 * H_SPLIT) { spin_until(&g_hcnt[32 * (1 + qt) + 1], 8u); fence_proxy_async_global(); }
            if (!first && (j == 0 || j == 2)) mbar_wait(j ? b_q1 : b_q0, 0);
            tma_load_2d_hint(sbase + AT_SQ + (j & 3) * 16384, &tmH, j * 64, qt * 128, fb, first ? pol_normal() : pol);
          }
        }
        #pragma unroll 1
        for (int j = 0; j < 4 * AT_NBLK; j++) {
          const bool isv = (j > 0 && !(j & 1)) || j == 4 * AT_NBLK - 1;
          const int row = hp * 2 * T_SEQ + (isv ? (j - 1) >> 1 : (j + 1) >> 1) * 128;
          const uint32_t fb = b_full + 8 * slot;
          mbar_wait(b_empty + 8 * slot, ph);
          if (!first && j == 3) mbar_wait(b_ob, 0);
          if (j == 4 && it == n_items - 1) mbar_arrive(bars + 288);
          if (ALIGN && j == AL_P && it == 1) mbar_arrive(bars + 312);
          mbar_expect_tx(fb, 32768);
          tma_load_3d_hint(sbase + slot * 32768, isv ? &tmV : &tmK, row, 0, fb, pol);
          if (it == 1 && isv && j >= 2 * WO_LATE && j < 2 * WO_LATE + 32 && blockIdx.x < OG_NKB)
            l2_prefetch_bulk(pf_wo + (size_t)own_kb(blockIdx.x) * 131072 + ((j >> 1) - WO_LATE) * 8192, 8192);
          if (++slot == 5) { slot = 0; ph ^= 1; }
        }
      }
      if (__builtin_expect(single, 0)) {
        spin_until(&g_hcnt[2], 128u);
        fence_proxy_async_global();
        const int nj = OG_JOBS * OG_PRE + (help_njobs() - OG_JOBS) * OG_PRE2;
        int ji = 0, job = help_job(0), kk = 0;
        #pragma unroll 1
        for (int j = 0; j < nj; j++) {
          const uint32_t sl = ring_slot(qp_pos(j, 1)), fb = b_full + 8 * sl;
          mbar_wait(b_empty + 8 * sl, ring_par(qp_pos(j, 1)) ^ ((j >> 2) & 1) ^ 1);
          mbar_expect_tx(fb, 49152);
          tma_load_3d_hint(sbase + sl * 32768, &tmWo, pre_kb(kk) * 64, OG_NT(job) * 2, fb, HPOL_B);
          tma_load_3d_hint(sbase + sl * 32768 + 16384, &tmWo, pre_kb(kk) * 64, OG_NT(job) * 2 + 2, fb, HPOL_B);
          if (j == 0 || j == 2) mbar_wait(j ? b_ob : b_q0, 0);
          tma_load_2d_hint(sbase + AT_SQ + (j & 3) * 16384, &tmOl, pre_kb(kk) * 64, OG_MT(job) * 128, fb, HPOL_A);
          if (++kk == (ji < OG_JOBS ? OG_PRE : OG_PRE2)) { kk = 0; job = help_job(++ji); }
        }
      }
      if (blockIdx.x < 128) {
        if (single) mbar_wait(b_x, 1);
        tail_producer(sbase, 0, pol, &tmOl, &tmWo, &tmX);
      }
     }
    }
    named_bar_sync(12 + (threadIdx.x >> 5), 32);
    if (blockIdx.x < 128) tail_exchange(sbase, &tmOut, w_down, w_r, x, out);
  } else {
    if (blockIdx.x < 128) head_phase(sbase + AT_SQ + 49152, sbase + 4 * 32768, b_x, b_go, b_head, threadIdx.x - 128, zero, cvec, w_mod);
    else { named_bar_sync(6, 384); if (threadIdx.x == 128) mbar_arrive(b_head); }
    TL_MARK2(0, threadIdx.x == 128);
    reg_alloc<AT_CREG>();
    const int cwg = wg - 1;
    const int tid = threadIdx.x & 127;
    const int warp = tid >> 5, lane = tid & 31;
    const uint32_t dbase = (sbase & 0x3FFFFu) >> 4;
    const uint32_t k_base = dbase + (1u << 16);
    const uint32_t v_base = dbase + (1024u << 16);
    const uint32_t w_base = dbase + (512u << 16);
    const uint32_t q_lo = dbase + ((AT_SQ + cwg * 8192) >> 4) + (1u << 16);
    const uint32_t frag = cwg * 8192 + (16 * warp + (lane & 7) + 8 * ((lane >> 3) & 1)) * 128;
    if (cwg == 1) named_bar_arrive(1, 256);
    bool raw = false;
    uint4 pre[8];
    #pragma unroll 1
    for (int it = 0; it < n_items; it++) {
      const bool more = it + 1 < n_items;
      constexpr int nkb = T_D / 64;
      const int ta = __shfl_sync(0xffffffffu, 4 * it, 0);
      float acc[128];
      {
        FS(2 * it, 0);
        #pragma unroll
        for (int i = 0; i < 128; i++) asm volatile("" : "=f"(acc[i]));
        {
          const uint32_t slot = ring_slot(ta), b_lo = w_base + slot * 2048;
          mbar_wait(b_full + 8 * slot, ring_par(ta));
          wgmma_fence();
          wgmma_m64n256k16_ss_tb<0, 0>(acc, q_lo, b_lo, 0);
          wgmma_m64n256k16_ss_tb<2, 128>(acc, q_lo, b_lo, 1);
          wgmma_m64n256k16_ss_tb<4, 256>(acc, q_lo, b_lo, 1);
          wgmma_m64n256k16_ss_tb<6, 384>(acc, q_lo, b_lo, 1);
          wgmma_commit();
        }
        #pragma unroll 1
        for (int j = NOZERO; j < nkb; j++) {
          const uint32_t slot = ring_slot(qp_pos(j, ta >> 2));
          mbar_wait(b_full + 8 * slot, ring_par(qp_pos(j, ta >> 2)) ^ ((j >> 2) & 1));
          if (QP_STAG > 0 && cwg == 1 && j == nkb - QP_STAG) named_bar_sync(7, 256);
          const uint32_t a_lo = q_lo + (j & 3) * 1024, b_lo = w_base + slot * 2048;
          wgmma_fence();
          wgmma_m64n256k16_ss_tb<0, 0>(acc, a_lo, b_lo, 1);
          wgmma_m64n256k16_ss_tb<2, 128>(acc, a_lo, b_lo, 1);
          wgmma_m64n256k16_ss_tb<4, 256>(acc, a_lo, b_lo, 1);
          wgmma_m64n256k16_ss_tb<6, 384>(acc, a_lo, b_lo, 1);
          wgmma_commit();
          if (QP_STAG > 0 && cwg == 0 && j == nkb - 1) named_bar_arrive(7, 256);
          if (j > 0) {
            wgmma_wait<1>();
            if (tid == 0) mbar_arrive(b_empty + 8 * ring_slot(qp_pos(j - 1, ta >> 2)));
          }
        }
        wgmma_wait<0>();
        fence_regs(acc);
        FS(2 * it, 1);
        TL_MARK2(29, threadIdx.x == 256 && it == 0);
        if (tid == 0) mbar_arrive(b_empty + 24);
      }
      float o[64], s[64];
      uint32_t p[32], q[32];
      #pragma unroll
      for (int i = 0; i < 32; i++) q[i] = pack_bf16(acc[2 * i] * AT_C, acc[2 * i + 1] * AT_C);
      zero_regs(s);
      const uint32_t sq = sbase + AT_SQ + cwg * 8192;
      const bool last_wg1 = cwg == 1 && !more;
      float mc0, mc1, al0 = 1.0f, al1 = 1.0f, l0 = 0.f, l1 = 0.f, lp0 = 0.f, lp1 = 0.f;
      bool redo0 = false;
      FS(2 * it, 2);
      mbar_wait(b_full + 8 * ring_slot(ta), ring_par(ta));
      named_bar_sync(1 + cwg, 256);
      FS(2 * it, 3);
      issue_qk(s, q, k_base + ring_slot(ta) * 2048);
      named_bar_arrive(1 + (cwg ^ 1), 256);
      bool ready = mbar_test(b_full + 8 * ring_slot(ta + 1), ring_par(ta + 1)) & mbar_test(b_full + 8 * ring_slot(ta + 2), ring_par(ta + 2));
      stage_q<16>(acc, AT_C, sbase + AT_SQ + frag, lane);
      wgmma_wait<0>();
      fence_regs(s);
      if (tid == 0) mbar_arrive(b_empty + 8 * ring_slot(ta));
      mc0 = 0.f; mc1 = 0.f;
      if (!raw) {
        raw = softmax_mode(s, mc0, mc1);
        if (__builtin_expect(!raw, 0)) softmax_sub(s, mc0, mc1);
      }
      softmax_exp<0, 64>(s);
      #pragma unroll
      for (int J = 0; J < 16; J += 2)
        stmatrix_x4(sbase + AT_SQ + frag + (J >> 3) * 16384 + ((((J & 7) + (lane >> 4)) ^ (lane & 7)) << 4), q[2 * J], q[2 * J + 1], q[2 * J + 2], q[2 * J + 3]);
      pack_p(p, s);
      zero_regs(o);
      FS(2 * it, 4);
      uint32_t ks = ring_slot(ta + 1), vs = ring_slot(ta + 2), kp = ring_par(ta + 1), vp = ring_par(ta + 2);
      auto finish_head = [&]() {
        FS(2 * it, 5);
        redo0 = finish_l(lp0, lp1);
        if (!redo0) stage_o(o, lp0, lp1, sbase + AT_SQ + frag, lane);
        FS(2 * it + 1, 4);
      };
      if (!ready) { mbar_wait(b_full + 8 * ks, kp); mbar_wait(b_full + 8 * vs, vp); }
      #pragma unroll 1
      for (int n = 1; n < 2 * AT_NBLK; n++) {
        named_bar_sync(1 + cwg, 256);
        issue_qk(s, q, k_base + ks * 2048);
        if (n == AT_NBLK + 1) finish_head();
        issue_pv(o, p, v_base + vs * 2048, (n & 15) != 1);
        asm volatile("{\n.reg .pred p;\nsetp.ne.u32 p, %0, 0;\n@p bar.arrive 1, 256;\n@!p bar.arrive 2, 256;\n}\n" :: "r"(cwg) : "memory");
        wgmma_wait<1>();
        fence_regs(s);
        if (tid == 0) mbar_arrive(b_empty + 8 * ks);
        if (__builtin_expect(!raw || (uint32_t)(n - (AT_NBLK - 1)) <= 2u, 0)) {
          if (n == AT_NBLK + 1 && !redo0) {
            fence_proxy_async();
            __syncwarp();
            if (lane == 0) mbar_arrive(b_ordy + 8 * cwg);
          }
          if (n == AT_NBLK - 1) {
            #pragma unroll
            for (int J = 0; J < 16; J += 2)
              ldmatrix_x4(sbase + AT_SQ + 32768 + frag + (J >> 3) * 16384 + ((((J & 7) + (lane >> 4)) ^ (lane & 7)) << 4), q[2 * J], q[2 * J + 1], q[2 * J + 2], q[2 * J + 3]);
          }
          if (!raw) {
            const float m0 = mc0, m1 = mc1;
            const bool ok = softmax_mode(s, mc0, mc1);
            if (n == AT_NBLK) raw = ok;
            else {
              mc0 = mc0 - AT_HEAD > m0 ? mc0 : m0; mc1 = mc1 - AT_HEAD > m1 ? mc1 : m1;
              al0 = ex2_approx(m0 - mc0); al1 = ex2_approx(m1 - mc1);
            }
            if (!raw) softmax_sub(s, mc0, mc1);
          }
        }
        softmax_exp<0, AT_SPLIT>(s);
        add_rowsum(p, l0, l1);
        if (tid == 0) {
          uint32_t dep = zero & __float_as_uint(l0) & __float_as_uint(l1);
          #pragma unroll
          for (int i = AT_SPLIT - AT_PIN - PINB; i < AT_SPLIT - PINB; i += 2) dep &= __float_as_uint(s[i]) & __float_as_uint(s[i + 1]);
          mbar_arrive(b_pin + dep);
        }
        wgmma_wait<0>();
        fence_regs(o);
        if (tid == 0) mbar_arrive(b_empty + 8 * vs);
        ks += 2; if (ks >= 5) { ks -= 5; kp ^= 1; }
        vs += 2; if (vs >= 5) { vs -= 5; vp ^= 1; }
        ready = mbar_test(b_full + 8 * ks, kp) & mbar_test(b_full + 8 * vs, vp);
        softmax_exp<AT_SPLIT, 64>(s);
        pack_p(p, s);
        if (n == AT_NBLK) { lp0 = l0; lp1 = l1; l0 = 0.f; l1 = 0.f; }
        if (__builtin_expect(!raw || !ready, 0)) {
        if (!raw && __any_sync(0xffffffffu, al0 != 1.0f || al1 != 1.0f)) {
          rescale_o(o, al0, al1);
          l0 *= al0; l1 *= al1;
          al0 = 1.0f; al1 = 1.0f;
        }
        if (!ready && n < 2 * AT_NBLK - 1) {
          mbar_wait(b_full + 8 * ks, kp);
          mbar_wait(b_full + 8 * vs, vp);
        }
        }
      }
      FS(2 * it + 1, 5);
      const uint32_t vl = ring_slot(ta + 63);
      vs = ring_slot(ta + 62);
      const uint32_t ob = more ? sbase + vs * 32768 : sbase + AT_SQ + 32768;
      mbar_wait(b_full + 8 * vl, ring_par(ta + 63));
      issue_pv(o, p, v_base + vl * 2048, 1);
      block_end(zero, b_pin);
      add_rowsum(p, l0, l1);
      const bool overflow = finish_l(l0, l1);
      if (!overflow && lane == 0) mbar_arrive(b_q1);
      #pragma unroll
      for (int i = 0; i < 8; i++) asm volatile("mov.b64 {%0, %1}, 0;\nmov.b64 {%2, %3}, 0;" : "=r"(pre[i].x), "=r"(pre[i].y), "=r"(pre[i].z), "=r"(pre[i].w));
      const bool want_pre = !more && blockIdx.x < OG_MOE, got_pre = want_pre && __all_sync(0xffffffffu, mbar_test(bars + 272, 0));
      if (got_pre) load_pre(pre, sbase, AT_SQ, threadIdx.x - 128);
      mbar_wait(b_empty + 8 * vs, ring_par(ta + 62));
      wgmma_wait<0>();
      fence_regs(o);
      if (tid == 0) mbar_arrive(b_empty + 8 * vl);
      FS(2 * it + 1, 6);
      if (overflow) {
        attn_rows_exact(sq + 32768, ob + cwg * 8192, 4 * ta + 1, kc, vc);
        __syncwarp();
        if (lane == 0) mbar_arrive(b_q1);
      } else stage_o(o, l0, l1, ob + frag, lane);
      if (redo0) attn_rows_exact(sq, sq, 4 * ta, kc, vc);
      fence_proxy_async();
      __syncwarp();
      if (lane == 0) {
        if (redo0) mbar_arrive(b_ordy + 8 * cwg);
        mbar_arrive(b_ordy + 16 + 8 * cwg);
      }
      if (want_pre && !got_pre) load_pre(pre, sbase, AT_SQ, threadIdx.x - 128);
      if (redo0 || overflow) raw = false;
      named_bar_sync(3 + cwg, 128);
      FS(2 * it + 1, 7);
    }
    if (ARV_IMM && cwg == 0) named_bar_arrive(1, 256);
    if (__builtin_expect(single, 0)) {
      float acc[128];
      uint32_t j = 0, pk[64];
      #pragma unroll
      for (int i = 0; i < 64; i++) asm volatile("" : "=f"(acc[2 * i]), "=f"(acc[2 * i + 1]), "=r"(pk[i]));
      uint4* dst = g_pre;
      int left = 0;
      auto put = [&](bool last) {
        #pragma unroll
        for (int i = 0; i < PUT_N; i++) dst[i * 256] = make_uint4(pk[4 * i], pk[4 * i + 1], pk[4 * i + 2], pk[4 * i + 3]);
        dst += PUT_N * 256;
        #pragma unroll
        for (int i = 0; i < 64 - 4 * PUT_N; i++) asm volatile("mov.b32 %0, %1;" : "=r"(pk[i]) : "r"(pk[i + 4 * PUT_N]));
        __syncwarp();
        if (last && lane == 0) mbar_arrive(bars + 280);
      };
      #pragma unroll 1
      for (int ji = 0; ji < help_njobs(); ji++) {
        const int nk = ji < OG_JOBS ? OG_PRE : OG_PRE2;
        #pragma unroll 1
        for (int kk = 0; kk < nk; kk++, j++) {
          const uint32_t slot = ring_slot(qp_pos(j, 1));
          mbar_wait(b_full + 8 * slot, ring_par(qp_pos(j, 1)) ^ ((j >> 2) & 1));
          if (H_STAG > 0 && cwg == 1 && kk == nk - H_STAG) named_bar_sync(7, 256);
          const uint32_t a_lo = q_lo + (j & 3) * 1024, b_lo = w_base + slot * 2048;
          wgmma_fence();
          wgmma_m64n256k16_ss_tb<0, 0>(acc, a_lo, b_lo, kk != 0);
          wgmma_m64n256k16_ss_tb<2, 128>(acc, a_lo, b_lo, 1);
          wgmma_m64n256k16_ss_tb<4, 256>(acc, a_lo, b_lo, 1);
          wgmma_m64n256k16_ss_tb<6, 384>(acc, a_lo, b_lo, 1);
          wgmma_commit();
          if (H_STAG > 0 && cwg == 0 && kk == nk - 1) named_bar_arrive(7, 256);
          wgmma_wait<1>();
          if (kk > 0 && tid == 0) mbar_arrive(b_empty + 8 * ring_slot(qp_pos(j - 1, 1)));
          #pragma unroll 1
          for (int i = ji == OG_JOBS ? 0 : 16 / PUT_N - 1; i < 16 / PUT_N && left > 0; i++) put(--left == 0);
        }
        wgmma_wait<0>();
        fence_regs(acc);
        if (tid == 0) mbar_arrive(b_empty + 8 * ring_slot(qp_pos(j - 1, 1)));
        #pragma unroll
        for (int i = 0; i < 64; i++) pk[i] = pack_bf16(acc[2 * i], acc[2 * i + 1]);
        left = 16 / PUT_N;
        if (ji == PRE_X) mbar_wait(bars + 296, 0);
        dst = g_pre + help_job(ji) * 2048 + threadIdx.x - 128;
      }
      #pragma unroll
      for (int i = 0; i < 16; i++) dst[i * 256] = make_uint4(pk[4 * i], pk[4 * i + 1], pk[4 * i + 2], pk[4 * i + 3]);
      __syncwarp();
      if (lane == 0) mbar_arrive(bars + 280);
      named_bar_sync(5, 256);
      if (threadIdx.x == 128) {
        #pragma unroll 1
        for (int i = 0; i < 5; i++) {
          constexpr int n = OG_JOBS * OG_PRE;
          const int used = i == 3 ? 0 : (n + 3 - (i == 4 ? 3 : i)) / 4;
          if ((used ^ (i < 4)) & 1) {
            mbar_arrive(b_full + 8 * ring_slot(4 + i));
            mbar_arrive(b_empty + 8 * ring_slot(4 + i)); mbar_arrive(b_empty + 8 * ring_slot(4 + i));
          }
        }
        mbar_arrive(b_x);
      }
      named_bar_sync(5, 256);
      #pragma unroll
      for (int i = 0; i < 8; i++) pre[i] = make_uint4(0u, 0u, 0u, 0u);
    }
    TL_CLK(3, 1, threadIdx.x == 128);
    TL_CTA(1, threadIdx.x == 256);
    TL_END(3, tid == 0);
    TL_MARK2(19, tid == 0 && !single);
    if (blockIdx.x < 128) {
      tail_consumer(sbase, pre, cwg, w_gate, w_up);
    }
  }
}

typedef CUresult (*PFN_encodeTiled)(CUtensorMap*, CUtensorMapDataType, cuuint32_t, void*, const cuuint64_t*, const cuuint64_t*,
                                    const cuuint32_t*, const cuuint32_t*, CUtensorMapInterleave, CUtensorMapSwizzle,
                                    CUtensorMapL2promotion, CUtensorMapFloatOOBfill);

CUtensorMap make_map_2d(PFN_encodeTiled enc, const void* ptr, uint64_t inner, uint64_t outer, uint64_t stride_bytes, uint32_t box_inner, uint32_t box_outer) {
  CUtensorMap m;
  cuuint64_t gd[2] = {inner, outer}; cuuint64_t gs[1] = {stride_bytes};
  cuuint32_t bx[2] = {box_inner, box_outer}; cuuint32_t es[2] = {1, 1};
  enc(&m, CU_TENSOR_MAP_DATA_TYPE_BFLOAT16, 2, const_cast<void*>(ptr), gd, gs, bx, es, CU_TENSOR_MAP_INTERLEAVE_NONE,
      CU_TENSOR_MAP_SWIZZLE_128B, CU_TENSOR_MAP_L2_PROMOTION_L2_128B, CU_TENSOR_MAP_FLOAT_OOB_FILL_NONE);
  return m;
}

CUtensorMap make_map_3d(PFN_encodeTiled enc, const void* ptr, uint64_t cols, uint64_t rows, uint32_t box_rows, uint32_t chunks) {
  CUtensorMap m;
  cuuint64_t gd[3] = {64, rows, cols / 64}; cuuint64_t gs[2] = {cols * 2, 128};
  cuuint32_t bx[3] = {64, box_rows, chunks}; cuuint32_t es[3] = {1, 1, 1};
  enc(&m, CU_TENSOR_MAP_DATA_TYPE_BFLOAT16, 3, const_cast<void*>(ptr), gd, gs, bx, es, CU_TENSOR_MAP_INTERLEAVE_NONE,
      CU_TENSOR_MAP_SWIZZLE_128B, CU_TENSOR_MAP_L2_PROMOTION_L2_128B, CU_TENSOR_MAP_FLOAT_OOB_FILL_NONE);
  return m;
}

}

extern "C" void kernel_launch(void* const* d_in, const int* in_sizes, int n_in, void* d_out, int out_size) {
  const bf16* x      = (const bf16*)d_in[0];
  const bf16* kc     = (const bf16*)d_in[1];
  const bf16* vc     = (const bf16*)d_in[2];
  const bf16* wq     = (const bf16*)d_in[3];
  const bf16* wo     = (const bf16*)d_in[4];
  const bf16* w_r    = (const bf16*)d_in[6];
  const bf16* w_gate = (const bf16*)d_in[7];
  const bf16* w_up   = (const bf16*)d_in[8];
  const bf16* w_down = (const bf16*)d_in[9];
  const bf16* cvec   = (const bf16*)d_in[10];
  const bf16* w_mod  = (const bf16*)d_in[11];
  bf16* out = (bf16*)d_out;

  static PFN_encodeTiled enc = nullptr;
  static void *p_h = nullptr, *p_o = nullptr;
  if (!enc) {
    void* fn = nullptr; cudaDriverEntryPointQueryResult qres;
    cudaGetDriverEntryPoint("cuTensorMapEncodeTiled", &fn, cudaEnableDefault, &qres);
    enc = (PFN_encodeTiled)fn;
    cudaGetSymbolAddress(&p_h, g_pre);
    p_h = (uint4*)p_h + 16 * PRE_X * 2048;
    cudaGetSymbolAddress(&p_o, g_o);
    cudaFuncSetAttribute(fused_kernel, cudaFuncAttributeMaxDynamicSharedMemorySize, (int)AT_SMEM);
  }
  const CUtensorMap tm_h   = make_map_2d(enc, p_h, T_D, T_SEQ, T_D * 2, 64, 128);
  const CUtensorMap tm_wq  = W3D ? make_map_3d(enc, wq, T_DQKV, T_D, 64, 4) : make_map_2d(enc, wq, T_DQKV, T_D, T_DQKV * 2, 64, 64);
  const CUtensorMap tm_k   = KV3D ? make_map_3d(enc, kc, T_DH, (uint64_t)T_NH * T_SEQ, 128, 2) : make_map_2d(enc, kc, T_DH, (uint64_t)T_NH * T_SEQ, T_DH * 2, 64, 128);
  const CUtensorMap tm_v   = KV3D ? make_map_3d(enc, vc, T_DH, (uint64_t)T_NH * T_SEQ, 128, 2) : make_map_2d(enc, vc, T_DH, (uint64_t)T_NH * T_SEQ, T_DH * 2, 64, 128);
  const CUtensorMap tm_ost = make_map_2d(enc, p_o, T_DQKV, T_SEQ, T_DQKV * 2, 64, 64);
  const CUtensorMap tm_old = make_map_2d(enc, p_o, T_DQKV, T_SEQ, T_DQKV * 2, 64, 128);
  const CUtensorMap tm_wo  = make_map_3d(enc, wo, T_D, T_DQKV, 64, 2);
  const CUtensorMap tm_x   = make_map_3d(enc, w_down, T_D, T_F, 32, 8);

  const CUtensorMap tm_m   = make_map_2d(enc, w_mod, 6 * T_D, T_D, 6 * T_D * 2, 64, 256);
  const CUtensorMap tm_out = make_map_2d(enc, out, T_D, T_SEQ, T_D * 2, 64, 128);

  fused_kernel<<<132, 384, AT_SMEM, cudaStreamPerThread>>>(tm_h, tm_wq, tm_k, tm_v, tm_ost, tm_old, tm_wo, tm_x, tm_out, tm_m, 0u, (const uint8_t*)wo, kc, vc, x, cvec, w_mod,
             w_r, w_gate, w_up, w_down, out);
}
```

```cpp
#include <cuda_runtime.h>
#include <cuda_bf16.h>
#include <cuda.h>
#include <stdint.h>

namespace {

typedef __nv_bfloat16 bf16;

constexpr int T_SEQ = 2048, T_D = 1024, T_NH = 32, T_DH = 128, T_DQKV = 4096, T_F = 3584;

#define PRE_X 2
__device__ __align__(1024) uint4 g_pre[(16 * PRE_X + 128) * 2048];
#define g_h (reinterpret_cast<bf16*>(g_pre + 16 * PRE_X * 2048))
__device__ __align__(1024) bf16 g_o[T_SEQ * T_DQKV];
__device__ __align__(16) uint8_t g_col[8 * 1536];
__device__ __align__(16) float g_scal[64];
__device__ __align__(16) unsigned int g_hcnt[17 * 32];
__device__ unsigned int g_smid[168], g_tmax[128];
__device__ __align__(128) float g_modpart[4 * 2 * T_D];
struct __align__(2048) TailMail {
  float4 part1[T_SEQ * 8];
  uint32_t key[256];
  uint4 cand[16 * 2 * 2 * 128];
  uint32_t cnt[32];
  float ypart[(T_F / 32) * 2 * T_D];
};
__device__ TailMail g_mail;
#define g_part1 g_mail.part1
#define g_key g_mail.key
#define g_cand g_mail.cand
#define CNT_Y (g_mail.cnt)
#define g_ypart g_mail.ypart

__device__ __forceinline__ uint32_t smem_u32(const void* p) { return (uint32_t)__cvta_generic_to_shared(p); }
__device__ __forceinline__ void mbar_init(uint32_t bar, uint32_t cnt) { asm volatile("mbarrier.init.shared::cta.b64 [%0], %1;" :: "r"(bar), "r"(cnt)); }
__device__ __forceinline__ void mbar_expect_tx(uint32_t bar, uint32_t bytes) { asm volatile("mbarrier.arrive.expect_tx.shared::cta.b64 _, [%0], %1;" :: "r"(bar), "r"(bytes) : "memory"); }
__device__ __forceinline__ void mbar_arrive(uint32_t bar) { asm volatile("mbarrier.arrive.shared::cta.b64 _, [%0];" :: "r"(bar) : "memory"); }
__device__ __forceinline__ void mbar_wait(uint32_t bar, uint32_t parity) {
  asm volatile("{\n.reg .pred p;\nLAB_WAIT:\nmbarrier.try_wait.parity.shared::cta.b64 p, [%0], %1;\n@!p bra LAB_WAIT;\n}\n" :: "r"(bar), "r"(parity) : "memory");
}
__device__ __forceinline__ bool mbar_test(uint32_t bar, uint32_t parity) {
  uint32_t r; asm volatile("{\n.reg .pred p;\nmbarrier.test_wait.parity.shared::cta.b64 p, [%1], %2;\nselp.u32 %0, 1, 0, p;\n}\n" : "=r"(r) : "r"(bar), "r"(parity) : "memory");
  return r != 0;
}
__device__ __forceinline__ uint32_t clock_lo() { uint32_t c; asm volatile("mov.u32 %0, %%clock;" : "=r"(c)); return c; }
__device__ __forceinline__ void fence_mbar_init() { asm volatile("fence.mbarrier_init.release.cluster;" ::: "memory"); }
__device__ __forceinline__ void tma_load_2d(uint32_t dst, const CUtensorMap* map, int c0, int c1, uint32_t bar) {
  asm volatile("cp.async.bulk.tensor.2d.shared::cluster.global.mbarrier::complete_tx::bytes [%0], [%1, {%3, %4}], [%2];"
    :: "r"(dst), "l"(map), "r"(bar), "r"(c0), "r"(c1) : "memory");
}
__device__ __forceinline__ uint64_t policy_evict_first() {
  uint64_t p; asm volatile("createpolicy.fractional.L2::evict_first.b64 %0, 1.0;" : "=l"(p)); return p;
}
__device__ __forceinline__ void tma_load_2d_hint(uint32_t dst, const CUtensorMap* map, int c0, int c1, uint32_t bar, uint64_t pol) {
  asm volatile("cp.async.bulk.tensor.2d.shared::cluster.global.mbarrier::complete_tx::bytes.L2::cache_hint [%0], [%1, {%3, %4}], [%2], %5;"
    :: "r"(dst), "l"(map), "r"(bar), "r"(c0), "r"(c1), "l"(pol) : "memory");
}
__device__ __forceinline__ void tma_load_3d_hint(uint32_t dst, const CUtensorMap* map, int c1, int c2, uint32_t bar, uint64_t pol) {
  asm volatile("cp.async.bulk.tensor.3d.shared::cluster.global.mbarrier::complete_tx::bytes.L2::cache_hint [%0], [%1, {%3, %4, %5}], [%2], %6;"
    :: "r"(dst), "l"(map), "r"(bar), "n"(0), "r"(c1), "r"(c2), "l"(pol) : "memory");
}
__device__ __forceinline__ void tma_store_2d(const CUtensorMap* map, uint32_t src, int c0, int c1) {
  asm volatile("cp.async.bulk.tensor.2d.global.shared::cta.bulk_group [%0, {%2, %3}], [%1];" :: "l"(map), "r"(src), "r"(c0), "r"(c1) : "memory");
}
__device__ __forceinline__ void prefetch_tmap(const CUtensorMap* map) { asm volatile("prefetch.tensormap [%0];" :: "l"(map) : "memory"); }
__device__ __forceinline__ void l2_prefetch_bulk(const void* p, uint32_t bytes) {
  asm volatile("cp.async.bulk.prefetch.L2.global [%0], %1;" :: "l"(p), "r"(bytes) : "memory");
}
__device__ __forceinline__ void bulk_commit() { asm volatile("cp.async.bulk.commit_group;" ::: "memory"); }
template<int N> __device__ __forceinline__ void bulk_wait_read() { asm volatile("cp.async.bulk.wait_group.read %0;" :: "n"(N) : "memory"); }
template<int N> __device__ __forceinline__ void bulk_wait() { asm volatile("cp.async.bulk.wait_group %0;" :: "n"(N) : "memory"); }
__device__ __forceinline__ void named_bar_sync(int id, int nthreads) { asm volatile("bar.sync %0, %1;" :: "r"(id), "r"(nthreads) : "memory"); }
__device__ __forceinline__ void named_bar_arrive(int id, int nthreads) { asm volatile("bar.arrive %0, %1;" :: "r"(id), "r"(nthreads) : "memory"); }
__device__ __forceinline__ void wgmma_fence() { asm volatile("wgmma.fence.sync.aligned;" ::: "memory"); }
__device__ __forceinline__ void wgmma_commit() { asm volatile("wgmma.commit_group.sync.aligned;" ::: "memory"); }
template<int N> __device__ __forceinline__ void wgmma_wait() { asm volatile("wgmma.wait_group.sync.aligned %0;" :: "n"(N) : "memory"); }
template<int R> __device__ __forceinline__ void reg_alloc() { asm volatile("setmaxnreg.inc.sync.aligned.u32 %0;" :: "n"(R)); }
template<int R> __device__ __forceinline__ void reg_dealloc() { asm volatile("setmaxnreg.dec.sync.aligned.u32 %0;" :: "n"(R)); }
__device__ __forceinline__ bool elect_one() {
  uint32_t pred; asm volatile("{\n.reg .pred p;\nelect.sync _|p, 0xffffffff;\nselp.u32 %0, 1, 0, p;\n}\n" : "=r"(pred)); return pred != 0;
}
__device__ __forceinline__ uint32_t pack_bf16(float lo, float hi) {
  uint32_t r; asm("cvt.rn.bf16x2.f32 %0, %1, %2;" : "=r"(r) : "f"(hi), "f"(lo)); return r;
}
__device__ __forceinline__ void stmatrix_x4(uint32_t addr, uint32_t r0, uint32_t r1, uint32_t r2, uint32_t r3) {
  asm volatile("stmatrix.sync.aligned.m8n8.x4.shared.b16 [%0], {%1, %2, %3, %4};" :: "r"(addr), "r"(r0), "r"(r1), "r"(r2), "r"(r3) : "memory");
}
__device__ __forceinline__ void fence_proxy_async() { asm volatile("fence.proxy.async.shared::cta;" ::: "memory"); }
__device__ __forceinline__ float ex2_approx(float x) { float y; asm("ex2.approx.ftz.f32 %0, %1;" : "=f"(y) : "f"(x)); return y; }
template<int N> __device__ __forceinline__ void fence_regs(float (&r)[N]) {
  #pragma unroll
  for (int i = 0; i < N; i++) asm volatile("" : "+f"(r[i]) :: "memory");
}
template<int N> __device__ __forceinline__ void zero_regs(float (&r)[N]) {
  #pragma unroll
  for (int i = 0; i < N; i += 2) asm volatile("mov.b64 {%0, %1}, 0;" : "=f"(r[i]), "=f"(r[i + 1]));
}
__device__ __forceinline__ float rbf(float x) { return __uint_as_float(pack_bf16(0.f, x)); }
__device__ __forceinline__ float bflo(uint32_t v) { return __uint_as_float(v << 16); }
__device__ __forceinline__ float bfhi(uint32_t v) { return __uint_as_float(v & 0xffff0000u); }

#define XT(i) do {} while (0)
#define TL_START(k) do {} while (0)
#define TL_END(k, cond) do {} while (0)
#define TL_CTA(i, cond) do {} while (0)
#define FS(slot, k) do {} while (0)
#define TL_MARK2(k, cond) do {} while (0)
#define TL_CLK(k, i, cond) do {} while (0)

template <int OFFA, int OFFB>
__device__ __forceinline__ void wgmma_m64n256k16_ss_tb(float (&d)[128], uint32_t a_lo, uint32_t b_lo, int scaleD) {
  asm volatile("{\n.reg .pred p;\n.reg .b32 ta, tb;\n.reg .b64 da, db;\nsetp.ne.b32 p, %130, 0;\n"
    "add.u32 ta, %128, %131;\nadd.u32 tb, %129, %132;\n"
    "mov.b64 da, {ta, 0x40000040};\nmov.b64 db, {tb, 0x40000040};\n"
    "wgmma.mma_async.sync.aligned.m64n256k16.f32.bf16.bf16 "
    "{%0, %1, %2, %3, %4, %5, %6, %7, %8, %9, %10, %11, %12, %13, %14, %15, %16, %17, %18, %19, %20, %21, %22, %23, %24, %25, %26, %27, %28, %29, %30, %31, %32, %33, %34, %35, %36, %37, %38, %39, %40, %41, %42, %43, %44, %45, %46, %47, %48, %49, %50, %51, %52, %53, %54, %55, %56, %57, %58, %59, %60, %61, %62, %63, %64, %65, %66, %67, %68, %69, %70, %71, %72, %73, %74, %75, %76, %77, %78, %79, %80, %81, %82, %83, %84, %85, %86, %87, %88, %89, %90, %91, %92, %93, %94, %95, %96, %97, %98, %99, %100, %101, %102, %103, %104, %105, %106, %107, %108, %109, %110, %111, %112, %113, %114, %115, %116, %117, %118, %119, %120, %121, %122, %123, %124, %125, %126, %127}, "
    "da, db, p, 1, 1, 0, 1;\n}\n"
    : "+f"(d[0]), "+f"(d[1]), "+f"(d[2]), "+f"(d[3]), "+f"(d[4]), "+f"(d[5]), "+f"(d[6]), "+f"(d[7]), "+f"(d[8]), "+f"(d[9]), "+f"(d[10]), "+f"(d[11]), "+f"(d[12]), "+f"(d[13]), "+f"(d[14]), "+f"(d[15]), "+f"(d[16]), "+f"(d[17]), "+f"(d[18]), "+f"(d[19]), "+f"(d[20]), "+f"(d[21]), "+f"(d[22]), "+f"(d[23]), "+f"(d[24]), "+f"(d[25]), "+f"(d[26]), "+f"(d[27]), "+f"(d[28]), "+f"(d[29]), "+f"(d[30]), "+f"(d[31]), "+f"(d[32]), "+f"(d[33]), "+f"(d[34]), "+f"(d[35]), "+f"(d[36]), "+f"(d[37]), "+f"(d[38]), "+f"(d[39]), "+f"(d[40]), "+f"(d[41]), "+f"(d[42]), "+f"(d[43]), "+f"(d[44]), "+f"(d[45]), "+f"(d[46]), "+f"(d[47]), "+f"(d[48]), "+f"(d[49]), "+f"(d[50]), "+f"(d[51]), "+f"(d[52]), "+f"(d[53]), "+f"(d[54]), "+f"(d[55]), "+f"(d[56]), "+f"(d[57]), "+f"(d[58]), "+f"(d[59]), "+f"(d[60]), "+f"(d[61]), "+f"(d[62]), "+f"(d[63]), "+f"(d[64]), "+f"(d[65]), "+f"(d[66]), "+f"(d[67]), "+f"(d[68]), "+f"(d[69]), "+f"(d[70]), "+f"(d[71]), "+f"(d[72]), "+f"(d[73]), "+f"(d[74]), "+f"(d[75]), "+f"(d[76]), "+f"(d[77]), "+f"(d[78]), "+f"(d[79]), "+f"(d[80]), "+f"(d[81]), "+f"(d[82]), "+f"(d[83]), "+f"(d[84]), "+f"(d[85]), "+f"(d[86]), "+f"(d[87]), "+f"(d[88]), "+f"(d[89]), "+f"(d[90]), "+f"(d[91]), "+f"(d[92]), "+f"(d[93]), "+f"(d[94]), "+f"(d[95]), "+f"(d[96]), "+f"(d[97]), "+f"(d[98]), "+f"(d[99]), "+f"(d[100]), "+f"(d[101]), "+f"(d[102]), "+f"(d[103]), "+f"(d[104]), "+f"(d[105]), "+f"(d[106]), "+f"(d[107]), "+f"(d[108]), "+f"(d[109]), "+f"(d[110]), "+f"(d[111]), "+f"(d[112]), "+f"(d[113]), "+f"(d[114]), "+f"(d[115]), "+f"(d[116]), "+f"(d[117]), "+f"(d[118]), "+f"(d[119]), "+f"(d[120]), "+f"(d[121]), "+f"(d[122]), "+f"(d[123]), "+f"(d[124]), "+f"(d[125]), "+f"(d[126]), "+f"(d[127])
    : "r"(a_lo), "r"(b_lo), "r"(scaleD), "n"(OFFA), "n"(OFFB));
}

template <int OFFA, int OFFB>
__device__ __forceinline__ void wgmma_m64n128k16_ss_tb(float (&d)[64], uint32_t a_lo, uint32_t b_lo, int scaleD) {
  asm volatile("{\n.reg .pred p;\n.reg .b32 ta, tb;\n.reg .b64 da, db;\nsetp.ne.b32 p, %66, 0;\n"
    "add.u32 ta, %64, %67;\nadd.u32 tb, %65, %68;\n"
    "mov.b64 da, {ta, 0x40000040};\nmov.b64 db, {tb, 0x40000040};\n"
    "wgmma.mma_async.sync.aligned.m64n128k16.f32.bf16.bf16 "
    "{%0, %1, %2, %3, %4, %5, %6, %7, %8, %9, %10, %11, %12, %13, %14, %15, %16, %17, %18, %19, %20, %21, %22, %23, %24, %25, %26, %27, %28, %29, %30, %31, %32, %33, %34, %35, %36, %37, %38, %39, %40, %41, %42, %43, %44, %45, %46, %47, %48, %49, %50, %51, %52, %53, %54, %55, %56, %57, %58, %59, %60, %61, %62, %63}, "
    "da, db, p, 1, 1, 0, 1;\n}\n"
    : "+f"(d[0]), "+f"(d[1]), "+f"(d[2]), "+f"(d[3]), "+f"(d[4]), "+f"(d[5]), "+f"(d[6]), "+f"(d[7]), "+f"(d[8]), "+f"(d[9]), "+f"(d[10]), "+f"(d[11]), "+f"(d[12]), "+f"(d[13]), "+f"(d[14]), "+f"(d[15]), "+f"(d[16]), "+f"(d[17]), "+f"(d[18]), "+f"(d[19]), "+f"(d[20]), "+f"(d[21]), "+f"(d[22]), "+f"(d[23]), "+f"(d[24]), "+f"(d[25]), "+f"(d[26]), "+f"(d[27]), "+f"(d[28]), "+f"(d[29]), "+f"(d[30]), "+f"(d[31]), "+f"(d[32]), "+f"(d[33]), "+f"(d[34]), "+f"(d[35]), "+f"(d[36]), "+f"(d[37]), "+f"(d[38]), "+f"(d[39]), "+f"(d[40]), "+f"(d[41]), "+f"(d[42]), "+f"(d[43]), "+f"(d[44]), "+f"(d[45]), "+f"(d[46]), "+f"(d[47]), "+f"(d[48]), "+f"(d[49]), "+f"(d[50]), "+f"(d[51]), "+f"(d[52]), "+f"(d[53]), "+f"(d[54]), "+f"(d[55]), "+f"(d[56]), "+f"(d[57]), "+f"(d[58]), "+f"(d[59]), "+f"(d[60]), "+f"(d[61]), "+f"(d[62]), "+f"(d[63])
    : "r"(a_lo), "r"(b_lo), "r"(scaleD), "n"(OFFA), "n"(OFFB));
}

template <int OFFB>
__device__ __forceinline__ void wgmma_m64n128k16_rs_tb(float (&d)[64], uint32_t a0, uint32_t a1, uint32_t a2, uint32_t a3, uint32_t b_lo, int scaleD) {
  asm volatile("{\n.reg .pred p;\n.reg .b32 tb;\n.reg .b64 db;\nsetp.ne.b32 p, %69, 0;\n"
    "add.u32 tb, %68, %70;\n"
    "mov.b64 db, {tb, 0x40000040};\n"
    "wgmma.mma_async.sync.aligned.m64n128k16.f32.bf16.bf16 "
    "{%0, %1, %2, %3, %4, %5, %6, %7, %8, %9, %10, %11, %12, %13, %14, %15, %16, %17, %18, %19, %20, %21, %22, %23, %24, %25, %26, %27, %28, %29, %30, %31, %32, %33, %34, %35, %36, %37, %38, %39, %40, %41, %42, %43, %44, %45, %46, %47, %48, %49, %50, %51, %52, %53, %54, %55, %56, %57, %58, %59, %60, %61, %62, %63}, "
    "{%64, %65, %66, %67}, db, p, 1, 1, 1;\n}\n"
    : "+f"(d[0]), "+f"(d[1]), "+f"(d[2]), "+f"(d[3]), "+f"(d[4]), "+f"(d[5]), "+f"(d[6]), "+f"(d[7]), "+f"(d[8]), "+f"(d[9]), "+f"(d[10]), "+f"(d[11]), "+f"(d[12]), "+f"(d[13]), "+f"(d[14]), "+f"(d[15]), "+f"(d[16]), "+f"(d[17]), "+f"(d[18]), "+f"(d[19]), "+f"(d[20]), "+f"(d[21]), "+f"(d[22]), "+f"(d[23]), "+f"(d[24]), "+f"(d[25]), "+f"(d[26]), "+f"(d[27]), "+f"(d[28]), "+f"(d[29]), "+f"(d[30]), "+f"(d[31]), "+f"(d[32]), "+f"(d[33]), "+f"(d[34]), "+f"(d[35]), "+f"(d[36]), "+f"(d[37]), "+f"(d[38]), "+f"(d[39]), "+f"(d[40]), "+f"(d[41]), "+f"(d[42]), "+f"(d[43]), "+f"(d[44]), "+f"(d[45]), "+f"(d[46]), "+f"(d[47]), "+f"(d[48]), "+f"(d[49]), "+f"(d[50]), "+f"(d[51]), "+f"(d[52]), "+f"(d[53]), "+f"(d[54]), "+f"(d[55]), "+f"(d[56]), "+f"(d[57]), "+f"(d[58]), "+f"(d[59]), "+f"(d[60]), "+f"(d[61]), "+f"(d[62]), "+f"(d[63])
    : "r"(a0), "r"(a1), "r"(a2), "r"(a3), "r"(b_lo), "r"(scaleD), "n"(OFFB));
}

template <int OFFB>
__device__ __forceinline__ void wgmma_m64n128k16_rs(float (&d)[64], uint32_t a0, uint32_t a1, uint32_t a2, uint32_t a3, uint32_t b_lo, int scaleD) {
  asm volatile("{\n.reg .pred p;\n.reg .b32 tb;\n.reg .b64 db;\nsetp.ne.b32 p, %69, 0;\n"
    "add.u32 tb, %68, %70;\n"
    "mov.b64 db, {tb, 0x40000040};\n"
    "wgmma.mma_async.sync.aligned.m64n128k16.f32.bf16.bf16 "
    "{%0, %1, %2, %3, %4, %5, %6, %7, %8, %9, %10, %11, %12, %13, %14, %15, %16, %17, %18, %19, %20, %21, %22, %23, %24, %25, %26, %27, %28, %29, %30, %31, %32, %33, %34, %35, %36, %37, %38, %39, %40, %41, %42, %43, %44, %45, %46, %47, %48, %49, %50, %51, %52, %53, %54, %55, %56, %57, %58, %59, %60, %61, %62, %63}, "
    "{%64, %65, %66, %67}, db, p, 1, 1, 0;\n}\n"
    : "+f"(d[0]), "+f"(d[1]), "+f"(d[2]), "+f"(d[3]), "+f"(d[4]), "+f"(d[5]), "+f"(d[6]), "+f"(d[7]), "+f"(d[8]), "+f"(d[9]), "+f"(d[10]), "+f"(d[11]), "+f"(d[12]), "+f"(d[13]), "+f"(d[14]), "+f"(d[15]), "+f"(d[16]), "+f"(d[17]), "+f"(d[18]), "+f"(d[19]), "+f"(d[20]), "+f"(d[21]), "+f"(d[22]), "+f"(d[23]), "+f"(d[24]), "+f"(d[25]), "+f"(d[26]), "+f"(d[27]), "+f"(d[28]), "+f"(d[29]), "+f"(d[30]), "+f"(d[31]), "+f"(d[32]), "+f"(d[33]), "+f"(d[34]), "+f"(d[35]), "+f"(d[36]), "+f"(d[37]), "+f"(d[38]), "+f"(d[39]), "+f"(d[40]), "+f"(d[41]), "+f"(d[42]), "+f"(d[43]), "+f"(d[44]), "+f"(d[45]), "+f"(d[46]), "+f"(d[47]), "+f"(d[48]), "+f"(d[49]), "+f"(d[50]), "+f"(d[51]), "+f"(d[52]), "+f"(d[53]), "+f"(d[54]), "+f"(d[55]), "+f"(d[56]), "+f"(d[57]), "+f"(d[58]), "+f"(d[59]), "+f"(d[60]), "+f"(d[61]), "+f"(d[62]), "+f"(d[63])
    : "r"(a0), "r"(a1), "r"(a2), "r"(a3), "r"(b_lo), "r"(scaleD), "n"(OFFB));
}

__device__ __forceinline__ uint4 ldg_nc_v4(const void* p) {
  uint4 v;
    asm volatile("{\n.reg .b64 pol;\ncreatepolicy.fractional.L2::evict_first.b64 pol, 1.0;\n"
                 "ld.global.nc.L1::no_allocate.L2::cache_hint.v4.u32 {%0, %1, %2, %3}, [%4], pol;\n}\n" : "=r"(v.x), "=r"(v.y), "=r"(v.z), "=r"(v.w) : "l"(p));
  return v;
}
__device__ __forceinline__ uint64_t pol_normal() {
  uint64_t p; asm volatile("createpolicy.fractional.L2::evict_normal.b64 %0, 1.0;" : "=l"(p)); return p;
}
__device__ __forceinline__ void unpack8(const uint4& u, float (&v)[8]) {
  v[0] = bflo(u.x); v[1] = bfhi(u.x); v[2] = bflo(u.y); v[3] = bfhi(u.y);
  v[4] = bflo(u.z); v[5] = bfhi(u.z); v[6] = bflo(u.w); v[7] = bfhi(u.w);
}
__device__ __forceinline__ void fma8(float (&acc)[8], float s, const uint4& w) {
  acc[0] = fmaf(s, bflo(w.x), acc[0]); acc[1] = fmaf(s, bfhi(w.x), acc[1]); acc[2] = fmaf(s, bflo(w.y), acc[2]); acc[3] = fmaf(s, bfhi(w.y), acc[3]);
  acc[4] = fmaf(s, bflo(w.z), acc[4]); acc[5] = fmaf(s, bfhi(w.z), acc[5]); acc[6] = fmaf(s, bflo(w.w), acc[6]); acc[7] = fmaf(s, bfhi(w.w), acc[7]);
}
__device__ __forceinline__ float rcp_approx(float x) { float y; asm("rcp.approx.ftz.f32 %0, %1;" : "=f"(y) : "f"(x)); return y; }
__device__ __forceinline__ float sigmoid_f(float v) { return rcp_approx(1.0f + ex2_approx(v * -1.4426950408889634f)); }
__device__ __forceinline__ float silu_bf(float v) { return rbf(v * sigmoid_f(v)); }
__device__ __forceinline__ uint32_t rank_key(float r, int idx) {
  const uint32_t b = __float_as_uint(r) >> 16;
  const uint32_t u = (r != r) ? 0u : ((b & 0x8000u) ? (~b & 0xffffu) : (b | 0x8000u));
  return (u << 16) | (0xffffu - (uint32_t)idx);
}
__device__ __forceinline__ void warp_top2(uint32_t& k1, uint32_t& k2) {
  const uint32_t m1 = __reduce_max_sync(0xffffffffu, k1);
  k2 = __reduce_max_sync(0xffffffffu, k1 == m1 ? k2 : k1);
  k1 = m1;
}
__device__ __forceinline__ uint32_t bmul2(uint32_t a, uint32_t b) { uint32_t r; asm("mul.rn.bf16x2 %0, %1, %2;" : "=r"(r) : "r"(a), "r"(b)); return r; }
__device__ __forceinline__ uint32_t badd2(uint32_t a, uint32_t b) { uint32_t r; asm("add.rn.bf16x2 %0, %1, %2;" : "=r"(r) : "r"(a), "r"(b)); return r; }
__device__ __forceinline__ uint32_t bsub2(uint32_t a, uint32_t b) { uint32_t r; asm("sub.rn.bf16x2 %0, %1, %2;" : "=r"(r) : "r"(a), "r"(b)); return r; }
__device__ __forceinline__ float sqrt_approx(float x) { float y; asm("sqrt.approx.f32 %0, %1;" : "=f"(y) : "f"(x)); return y; }
__device__ __forceinline__ uint32_t ln_norm2(uint32_t x1, uint32_t mb2, float inv) {
  const uint32_t d = bsub2(x1, mb2);
  return pack_bf16(bflo(d) * inv, bfhi(d) * inv);
}
__device__ __forceinline__ uint32_t bfma2(uint32_t a, uint32_t b, uint32_t c) { uint32_t r; asm("fma.rn.bf16x2 %0, %1, %2, %3;" : "=r"(r) : "r"(a), "r"(b), "r"(c)); return r; }
__device__ __forceinline__ uint32_t ln_norm2b(uint32_t x1, uint32_t mb2, uint32_t ih, uint32_t il) {
  const uint32_t d = bsub2(x1, mb2);
  return bfma2(d, ih, bmul2(d, il));
}
__device__ __forceinline__ uint32_t ln_mod2(uint32_t x1, uint32_t mb2, float inv, uint32_t c1, uint32_t sb) { return badd2(bmul2(ln_norm2(x1, mb2, inv), c1), sb); }
__device__ __forceinline__ void ldmatrix_x4(uint32_t addr, uint32_t& r0, uint32_t& r1, uint32_t& r2, uint32_t& r3) {
  asm volatile("ldmatrix.sync.aligned.m8n8.x4.shared.b16 {%0, %1, %2, %3}, [%4];" : "=r"(r0), "=r"(r1), "=r"(r2), "=r"(r3) : "r"(addr) : "memory");
}
__device__ __forceinline__ uint4 ldg_stream_v4(const void* p, uint64_t pol) {
  uint4 v; asm volatile("ld.global.nc.L1::no_allocate.L2::cache_hint.L2::128B.v4.u32 {%0, %1, %2, %3}, [%4], %5;" : "=r"(v.x), "=r"(v.y), "=r"(v.z), "=r"(v.w) : "l"(p), "l"(pol)); return v;
}
__device__ __forceinline__ void bulk_load_hint(uint32_t dst, const void* src, uint32_t bytes, uint32_t bar, uint64_t pol) {
  asm volatile("cp.async.bulk.shared::cluster.global.mbarrier::complete_tx::bytes.L2::cache_hint [%0], [%1], %2, [%3], %4;"
    :: "r"(dst), "l"(src), "r"(bytes), "r"(bar), "l"(pol) : "memory");
}
__device__ __forceinline__ void red_release_add(unsigned int* p, unsigned int v) { asm volatile("red.release.gpu.global.add.u32 [%0], %1;" :: "l"(p), "r"(v) : "memory"); }
__device__ __forceinline__ unsigned int ld_acquire(const unsigned int* p) { unsigned int v; asm volatile("ld.acquire.gpu.global.u32 %0, [%1];" : "=r"(v) : "l"(p) : "memory"); return v; }
__device__ __forceinline__ void spin_until(const unsigned int* p, unsigned int target) {
  #pragma unroll 1
  for (unsigned int i = 0; i < (1u << 22); i++) { if (ld_acquire(p) >= target) return; }
}
__device__ __forceinline__ float lds_f32(uint32_t a) { float v; asm volatile("ld.shared.f32 %0, [%1];" : "=f"(v) : "r"(a) : "memory"); return v; }
__device__ __forceinline__ float2 lds_f32x2(uint32_t a) { float2 v; asm volatile("ld.shared.v2.f32 {%0, %1}, [%2];" : "=f"(v.x), "=f"(v.y) : "r"(a) : "memory"); return v; }
__device__ __forceinline__ uint2 lds_u32x2(uint32_t a) { uint2 v; asm volatile("ld.shared.v2.u32 {%0, %1}, [%2];" : "=r"(v.x), "=r"(v.y) : "r"(a) : "memory"); return v; }
__device__ __forceinline__ uint32_t lds_u32(uint32_t a) { uint32_t v; asm volatile("ld.shared.u32 %0, [%1];" : "=r"(v) : "r"(a) : "memory"); return v; }
__device__ __forceinline__ void sts_u32(uint32_t a, uint32_t v) { asm volatile("st.shared.u32 [%0], %1;" :: "r"(a), "r"(v) : "memory"); }
__device__ __forceinline__ void sts_u32x2(uint32_t a, uint32_t x, uint32_t y) { asm volatile("st.shared.v2.u32 [%0], {%1, %2};" :: "r"(a), "r"(x), "r"(y) : "memory"); }
__device__ __forceinline__ void sts_f32(uint32_t a, float v) { asm volatile("st.shared.f32 [%0], %1;" :: "r"(a), "f"(v) : "memory"); }
__device__ __forceinline__ void sts_f32x2(uint32_t a, float x, float y) { asm volatile("st.shared.v2.f32 [%0], {%1, %2};" :: "r"(a), "f"(x), "f"(y) : "memory"); }
__device__ __forceinline__ void sts_f32x4(uint32_t a, float x, float y, float z, float w) { asm volatile("st.shared.v4.f32 [%0], {%1, %2, %3, %4};" :: "r"(a), "f"(x), "f"(y), "f"(z), "f"(w) : "memory"); }

__device__ __forceinline__ uint4 lds_u32x4(uint32_t a) { uint4 v; asm volatile("ld.shared.v4.u32 {%0, %1, %2, %3}, [%4];" : "=r"(v.x), "=r"(v.y), "=r"(v.z), "=r"(v.w) : "r"(a) : "memory"); return v; }
__device__ __forceinline__ void sts_u32x4(uint32_t a, uint32_t x, uint32_t y, uint32_t z, uint32_t w) { asm volatile("st.shared.v4.u32 [%0], {%1, %2, %3, %4};" :: "r"(a), "r"(x), "r"(y), "r"(z), "r"(w) : "memory"); }
__device__ __forceinline__ void st_tagged(float* p, float v) {
  const uint32_t b = __float_as_uint(v);
  asm volatile("st.relaxed.gpu.global.u32 [%0], %1;" :: "l"(p), "r"(b == 0u ? 0x80000000u : b) : "memory");
}
__device__ __forceinline__ void st_tagged4(float* p, float x, float y, float z, float w) {
  const uint32_t a = __float_as_uint(x), b = __float_as_uint(y), c = __float_as_uint(z), d = __float_as_uint(w);
  asm volatile("st.relaxed.gpu.global.v4.u32 [%0], {%1, %2, %3, %4};" :: "l"(p), "r"(a == 0u ? 0x80000000u : a), "r"(b == 0u ? 0x80000000u : b),
               "r"(c == 0u ? 0x80000000u : c), "r"(d == 0u ? 0x80000000u : d) : "memory");
}
__device__ __forceinline__ void st_relaxed2(void* p, uint32_t a, uint32_t b) { asm volatile("st.relaxed.gpu.global.v2.u32 [%0], {%1, %2};" :: "l"(p), "r"(a), "r"(b) : "memory"); }
__device__ __forceinline__ float4 ld_tagged4(const float* p) {
  float4 v; asm volatile("ld.relaxed.gpu.global.v4.f32 {%0, %1, %2, %3}, [%4];" : "=f"(v.x), "=f"(v.y), "=f"(v.z), "=f"(v.w) : "l"(p) : "memory"); return v;
}
__device__ __forceinline__ bool tagged4(const float4& v) {
  return __float_as_uint(v.x) != 0u && __float_as_uint(v.y) != 0u && __float_as_uint(v.z) != 0u && __float_as_uint(v.w) != 0u;
}
__device__ __forceinline__ void hint_arrive(uint32_t* p) { asm volatile("red.relaxed.gpu.global.add.u32 [%0], 1;" :: "l"(p) : "memory"); }
__device__ __forceinline__ void hint_wait(const uint32_t* p, uint32_t target) {
  uint32_t v = 0u;
  #pragma unroll 1
  for (unsigned int i = 0; i < (1u << 22) && v < target; i++) asm volatile("ld.relaxed.gpu.global.u32 %0, [%1];" : "=r"(v) : "l"(p) : "memory");
}
__device__ __forceinline__ void fence_proxy_async_global() { asm volatile("fence.proxy.async.global;" ::: "memory"); }

#define H_SPLIT 1
#define X_DLY 1200
#define W_DLY 1900
#define W_FIRST 2200
#define PRE_B 2
#define H_PREG 1
template <int J0, int J1>
__device__ __forceinline__ void load_parts(float2 (&pa)[J1 - J0][4], int t2) {
  #pragma unroll
  for (int j = J0; j < J1; j++)
    #pragma unroll
    for (int k = 0; k < 4; k++)
      asm volatile("ld.relaxed.gpu.global.v2.f32 {%0, %1}, [%2];" : "=f"(pa[j - J0][k].x), "=f"(pa[j - J0][k].y)
                   : "l"(g_modpart + k * 2 * T_D + (t2 >> 7) * T_D + j * 256 + (t2 & 127) * 2) : "memory");
}
template <int J0, int J1>
__device__ __forceinline__ void finish_parts(float2 (&pa)[J1 - J0][4], bool loaded, int t2, uint32_t tab) {
  #pragma unroll 1
  for (unsigned int spin = 0; spin < (1u << 22); spin++) {
    if (!loaded) load_parts<J0, J1>(pa, t2);
    loaded = false;
    bool ok = true;
    #pragma unroll
    for (int j = 0; j < J1 - J0; j++)
      #pragma unroll
      for (int k = 0; k < 4; k++) ok &= (__float_as_uint(pa[j][k].x) != 0u) & (__float_as_uint(pa[j][k].y) != 0u);
    if (__all_sync(0xffffffffu, ok)) break;
  }
  #pragma unroll
  for (int j = J0; j < J1; j++) {
    const float2* q = pa[j - J0];
    const uint32_t m = pack_bf16(((q[0].x + q[1].x) + q[2].x) + q[3].x, ((q[0].y + q[1].y) + q[2].y) + q[3].y);
    sts_u32(tab + (t2 >> 7) * 2048 + j * 512 + (t2 & 127) * 4, t2 >= 128 ? badd2(m, 0x3F803F80u) : m);
  }
}
__device__ __forceinline__ void head_phase(uint32_t scr, uint32_t xs, uint32_t b_x, uint32_t b_go, uint32_t b_head, int t2, uint32_t zero, const bf16* __restrict__ cvec, const bf16* __restrict__ w_mod) {
  const int lane = t2 & 31, w8 = t2 >> 5;
  const int cb = blockIdx.x & 31, ks = blockIdx.x >> 5;
  const bool early = (cb & 15) < 4 * H_SPLIT;
  const uint32_t ws = (xs - 32768 + (t2 >> 3) * 128 + (((t2 ^ (t2 >> 3)) & 7) << 4)) ^ zero;
  const float cv = __bfloat162float(cvec[ks * 256 + t2]);
  const bf16* wsrc = w_mod + (size_t)(ks * 256 + (t2 >> 3)) * (6 * T_D) + cb * 64 + (t2 & 7) * 8;
  if (early) {
    const uint64_t pol = policy_evict_first();
    #pragma unroll 2
    for (int i = 0; i < 8; i++)
      asm volatile("cp.async.cg.shared.global.L2::cache_hint [%0], [%1], 16, %2;" :: "r"(ws + i * 4096), "l"(wsrc + (size_t)i * 32 * 6 * T_D), "l"(pol) : "memory");
  }
  sts_f32(scr + t2 * 4, silu_bf(cv));
  named_bar_sync(6, 384);
  TL_MARK2(1, t2 == 0);
  uint4 xv[2][4];
  uint32_t mb2[2], ih[2], il[2];
  auto norm = [&](int j) {
    #pragma unroll
    for (int r = 0; r < 2; r++) {
      xv[r][j].x = ln_norm2b(xv[r][j].x, mb2[r], ih[r], il[r]); xv[r][j].y = ln_norm2b(xv[r][j].y, mb2[r], ih[r], il[r]);
      xv[r][j].z = ln_norm2b(xv[r][j].z, mb2[r], ih[r], il[r]); xv[r][j].w = ln_norm2b(xv[r][j].w, mb2[r], ih[r], il[r]);
    }
  };
  auto modulate = [&](int j) {
    const uint4 sa = lds_u32x4(scr + 8192 + j * 512 + lane * 16), c1 = lds_u32x4(scr + 8192 + 2048 + j * 512 + lane * 16);
    #pragma unroll
    for (int r = 0; r < 2; r++) {
      xv[r][j].x = badd2(bmul2(xv[r][j].x, c1.x), sa.x); xv[r][j].y = badd2(bmul2(xv[r][j].y, c1.y), sa.y);
      xv[r][j].z = badd2(bmul2(xv[r][j].z, c1.z), sa.z); xv[r][j].w = badd2(bmul2(xv[r][j].w, c1.w), sa.w);
    }
  };
  auto store = [&](int j) {
    #pragma unroll
    for (int r = 0; r < 2; r++) *reinterpret_cast<uint4*>(g_h + (size_t)(blockIdx.x * 16 + 2 * w8 + r) * T_D + j * 256 + lane * 8) = xv[r][j];
  };
  #pragma unroll 1
  for (int ph = 0; ph < 2; ph++) {
    if ((ph == 0) == early) {
      asm volatile("cp.async.wait_all;" ::: "memory");
      if (!early) mbar_wait(b_x + 168, 0);
      float acc[8];
      #pragma unroll
      for (int j = 0; j < 8; j++) acc[j] = 0.f;
      #pragma unroll
      for (int i = 0; i < 8; i++) fma8(acc, lds_f32(scr + ((t2 >> 3) + 32 * i) * 4), lds_u32x4(ws + i * 4096));
      #pragma unroll
      for (int j = 0; j < 4; j++) { const bool up = lane & 16; acc[j] = (up ? acc[4 + j] : acc[j]) + __shfl_xor_sync(0xffffffffu, up ? acc[j] : acc[4 + j], 16); }
      #pragma unroll
      for (int j = 0; j < 2; j++) { const bool up = lane & 8; acc[j] = (up ? acc[2 + j] : acc[j]) + __shfl_xor_sync(0xffffffffu, up ? acc[j] : acc[2 + j], 8); }
      sts_f32x2(scr + 1024 + w8 * 256 + (lane & 7) * 32 + (lane >> 3) * 8, acc[0], acc[1]);
      named_bar_sync(5, 256);
      if (t2 < 64) {
        float sum = 0.f;
        #pragma unroll
        for (int i = 0; i < 8; i++) sum += lds_f32(scr + 1024 + i * 256 + t2 * 4);
        st_tagged(g_modpart + ks * 2 * T_D + cb * 64 + t2, sum);
        TL_MARK2(early ? 2 : 6, t2 == 0);
      }
    } else {
      float2 pa[H_SPLIT][4];
      mbar_wait(b_x, 0);
      TL_MARK2(18, t2 == 0);
      if (H_PREG) load_parts<0, H_SPLIT>(pa, t2);
      #pragma unroll
      for (int r = 0; r < 2; r++)
        #pragma unroll
        for (int j = 0; j < 4; j++) xv[r][j] = lds_u32x4(xs + (2 * w8 + r) * 2048 + j * 512 + lane * 16);
  {
    float st[4] = {0.f, 0.f, 0.f, 0.f};
    #pragma unroll
    for (int r = 0; r < 2; r++)
      #pragma unroll
      for (int j = 0; j < 4; j++) {
        float v[8];
        unpack8(xv[r][j], v);
        st[2 * r] += ((v[0] + v[1]) + (v[2] + v[3])) + ((v[4] + v[5]) + (v[6] + v[7]));
        st[2 * r + 1] += fmaf(v[0], v[0], fmaf(v[1], v[1], fmaf(v[2], v[2], v[3] * v[3]))) + fmaf(v[4], v[4], fmaf(v[5], v[5], fmaf(v[6], v[6], v[7] * v[7])));
      }
    #pragma unroll
    for (int k = 0; k < 2; k++) { const bool up = lane & 16; st[k] = (up ? st[2 + k] : st[k]) + __shfl_xor_sync(0xffffffffu, up ? st[k] : st[2 + k], 16); }
    #pragma unroll
    for (int o = 8; o > 0; o >>= 1) { st[0] += __shfl_xor_sync(0xffffffffu, st[0], o); st[1] += __shfl_xor_sync(0xffffffffu, st[1], o); }
    const float mean = st[0] * (1.0f / T_D);
    const float inv = rcp_approx(rbf(sqrt_approx(rbf(rbf(fmaxf(fmaf(-mean, mean, st[1] * (1.0f / T_D)), 0.f)) + 1e-05f))));
    const uint32_t m = pack_bf16(mean, mean), h = pack_bf16(inv - rbf(inv), inv);
    #pragma unroll
    for (int r = 0; r < 2; r++) {
      mb2[r] = __shfl_sync(0xffffffffu, m, 16 * r);
      const uint32_t hr = __shfl_sync(0xffffffffu, h, 16 * r);
      ih[r] = __byte_perm(hr, hr, 0x3232); il[r] = __byte_perm(hr, hr, 0x1010);
    }
  }
      #pragma unroll
      for (int j = 0; j < H_SPLIT; j++) norm(j);
      TL_MARK2(5, t2 == 0);
      finish_parts<0, H_SPLIT>(pa, H_PREG, t2, scr + 8192);
      named_bar_sync(5, 256);
      TL_MARK2(7, t2 == 0);
      #pragma unroll
      for (int j = 0; j < H_SPLIT; j++) { modulate(j); store(j); }
      named_bar_arrive(9, 288);
    }
  }
  #pragma unroll
  for (int j = H_SPLIT; j < 4; j++) norm(j);
  float2 pb[4 - H_SPLIT][4];
  finish_parts<H_SPLIT, 4>(pb, false, t2, scr + 8192);
  named_bar_sync(5, 256);
  TL_MARK2(17, t2 == 0);
  #pragma unroll
  for (int j = H_SPLIT; j < 4; j++) modulate(j);
  __syncwarp();
  if (lane == 0) mbar_arrive(b_head + (xv[1][3].w & zero));
  mbar_wait(b_go, 0);
  #pragma unroll
  for (int j = H_SPLIT; j < 4; j++) store(j);
  named_bar_arrive(8, 288);
}

#define MOD_AT (b_empty + 8)
#define MOD_PF 0
#define MOD_SPLIT 16
__device__ __forceinline__ void mod_rest(uint32_t scr, uint32_t b_go, int t, const bf16* __restrict__ cvec, const bf16* __restrict__ w_mod, const bf16* __restrict__ w_r) {
  const int lane = t & 31;
  #pragma unroll 1
  for (int i = t; i < T_D / 2; i += 64) {
    const uint32_t c2 = *reinterpret_cast<const uint32_t*>(cvec + 2 * i);
    sts_u32(scr + i * 4, pack_bf16(silu_bf(bflo(c2)), silu_bf(bfhi(c2))));
  }
  named_bar_sync(11, 64);
  const bf16* wp = w_mod + (size_t)(2 * (t >> 2)) * (6 * T_D) + 2 * T_D + blockIdx.x * 32 + (t & 3) * 8;
  float acc[8];
  #pragma unroll
  for (int i = 0; i < 8; i++) acc[i] = 0.f;
  #pragma unroll 1
  for (int i = 0; i < 32; i += 2) {
    if (i == MOD_SPLIT) mbar_wait(b_go, 0);
    const uint4 w0 = ldg_nc_v4(wp), w1 = ldg_nc_v4(wp + 6 * T_D), w2 = ldg_nc_v4(wp + 32 * 6 * T_D), w3 = ldg_nc_v4(wp + 33 * 6 * T_D);
    wp += 64 * 6 * T_D;
    const uint32_t s0 = lds_u32(scr + (i * 16 + (t >> 2)) * 4), s1 = lds_u32(scr + (i * 16 + 16 + (t >> 2)) * 4);
    fma8(acc, bflo(s0), w0); fma8(acc, bfhi(s0), w1); fma8(acc, bflo(s1), w2); fma8(acc, bfhi(s1), w3);
  }
  #pragma unroll
  for (int j = 0; j < 4; j++) { const bool up = lane & 16; acc[j] = (up ? acc[4 + j] : acc[j]) + __shfl_xor_sync(0xffffffffu, up ? acc[j] : acc[4 + j], 16); }
  #pragma unroll
  for (int j = 0; j < 2; j++) { const bool up = lane & 8; acc[j] = (up ? acc[2 + j] : acc[j]) + __shfl_xor_sync(0xffffffffu, up ? acc[j] : acc[2 + j], 8); }
  { const bool up = lane & 4; acc[0] = (up ? acc[1] : acc[0]) + __shfl_xor_sync(0xffffffffu, up ? acc[0] : acc[1], 4); }
  if (t >= 32) sts_f32(scr + 2048 + lane * 4, acc[0]);
  named_bar_sync(11, 64);
  if (__shfl_sync(0xffffffffu, t, 0) < 32) {
    const int kind = blockIdx.x >> 5;
    float v = rbf(acc[0] + lds_f32(scr + 2048 + lane * 4));
    const int col = (blockIdx.x & 31) * 32 + (lane & 3) * 8 + (lane >> 2);
    uint8_t* dst = g_col + (col >> 7) * 1536;
    if (kind == 2) v = rbf(1.0f + v);
    float vw = v * __bfloat162float(w_r[col]);
    if (kind == 2) {
      const int c = col & 127, i = (c & ~15) + ((c >> 1) & 3) * 4 + ((c >> 3) & 1) * 2 + (c & 1);
      reinterpret_cast<bf16*>(dst)[i] = __float2bfloat16_rn(vw);
      reinterpret_cast<bf16*>(dst)[128 + i] = __float2bfloat16_rn(vw - rbf(vw));
    }
    reinterpret_cast<bf16*>(dst + 512 + (kind & 1) * 512 + (kind >> 1) * 256)[col & 127] = __float2bfloat16_rn(v);
    #pragma unroll
    for (int o = 16; o > 0; o >>= 1) vw += __shfl_xor_sync(0xffffffffu, vw, o);
    if (lane == 0 && (kind == 1 || kind == 2)) g_scal[95 - blockIdx.x] = vw;
  }
  #pragma unroll 1
  for (int i = blockIdx.x * 64 + t; i < (int)(sizeof(g_mail) / 16); i += 128 * 64) reinterpret_cast<uint4*>(&g_mail)[i] = make_uint4(0u, 0u, 0u, 0u);
  named_bar_sync(11, 64);
  if (t == 0) red_release_add(&g_hcnt[0], 1u);
}

#define HPOL_A pol
#define HPOL_B pol_normal()
#define HMAP_A &tmOl
#define HMAP_B &tmWo
constexpr int AT_NBLK = T_SEQ / 128;
constexpr float AT_HEAD = 7.0f;
#define WO_LATE 12
#define QP_STAG 3
#define AT_SPLIT 28
#define AT_PIN 12
#define PINB 4
constexpr int AT_NFULL = 124;
constexpr int AT_PREG = 40, AT_CREG = 232;
constexpr uint32_t AT_SQ = 5 * 32768;
constexpr float AT_C = 0.08838834764831845f * 1.4426950408889634f;
constexpr float AT_RAW_LO = -16.0f, AT_RAW_HI = 24.0f;
constexpr float AT_RAW_SUM = 281474976710656.0f, AT_RAW_MIN = 9.094947017729282e-13f;
constexpr uint32_t AT_SBAR = AT_SQ + 65536 + 256;
constexpr uint32_t AT_SMEM = AT_SQ + 65536 + 3072;

__device__ __forceinline__ uint32_t ring_slot(uint32_t t) { return t - 5u * ((t * 205u) >> 10); }
__device__ __forceinline__ uint32_t qp_pos(uint32_t j, uint32_t it) { return 4u * it + (j & 3u) + ((j & 3u) == 3u ? it : 0u); }
__device__ __forceinline__ uint32_t ring_par(uint32_t t) { return ((t * 205u) >> 10) & 1u; }
__device__ __forceinline__ void softmax_rowmax(const float (&s)[64], float& mx0, float& mx1) {
  float a0 = fmaxf(s[0], s[1]), a1 = fmaxf(s[4], s[5]), a2 = fmaxf(s[8], s[9]), a3 = fmaxf(s[12], s[13]);
  float b0 = fmaxf(s[2], s[3]), b1 = fmaxf(s[6], s[7]), b2 = fmaxf(s[10], s[11]), b3 = fmaxf(s[14], s[15]);
  #pragma unroll
  for (int j = 4; j < 16; j += 4) {
    a0 = fmaxf(a0, fmaxf(s[4 * j + 0], s[4 * j + 1]));  b0 = fmaxf(b0, fmaxf(s[4 * j + 2], s[4 * j + 3]));
    a1 = fmaxf(a1, fmaxf(s[4 * j + 4], s[4 * j + 5]));  b1 = fmaxf(b1, fmaxf(s[4 * j + 6], s[4 * j + 7]));
    a2 = fmaxf(a2, fmaxf(s[4 * j + 8], s[4 * j + 9]));  b2 = fmaxf(b2, fmaxf(s[4 * j + 10], s[4 * j + 11]));
    a3 = fmaxf(a3, fmaxf(s[4 * j + 12], s[4 * j + 13])); b3 = fmaxf(b3, fmaxf(s[4 * j + 14], s[4 * j + 15]));
  }
  mx0 = fmaxf(fmaxf(a0, a1), fmaxf(a2, a3));
  mx1 = fmaxf(fmaxf(b0, b1), fmaxf(b2, b3));
  mx0 = fmaxf(mx0, __shfl_xor_sync(0xffffffffu, mx0, 1));
  mx1 = fmaxf(mx1, __shfl_xor_sync(0xffffffffu, mx1, 1));
  mx0 = fmaxf(mx0, __shfl_xor_sync(0xffffffffu, mx0, 2));
  mx1 = fmaxf(mx1, __shfl_xor_sync(0xffffffffu, mx1, 2));
}
__device__ __forceinline__ void softmax_sub(float (&s)[64], float mc0, float mc1) {
  #pragma unroll
  for (int j = 0; j < 16; j++) { s[4 * j] -= mc0; s[4 * j + 1] -= mc0; s[4 * j + 2] -= mc1; s[4 * j + 3] -= mc1; }
}
template <int LO, int HI>
__device__ __forceinline__ void softmax_exp(float (&s)[64]) {
  #pragma unroll
  for (int i = LO; i < HI; i++) s[i] = ex2_approx(s[i]);
}
__device__ __forceinline__ bool softmax_mode(const float (&s)[64], float& mc0, float& mc1) {
  softmax_rowmax(s, mc0, mc1);
  const bool raw = __all_sync(0xffffffffu, mc0 >= AT_RAW_LO && mc0 <= AT_RAW_HI && mc1 >= AT_RAW_LO && mc1 <= AT_RAW_HI);
  mc0 += AT_HEAD; mc1 += AT_HEAD;
  return raw;
}
__device__ __forceinline__ void rowsum_p(const uint32_t (&p)[32], uint32_t& t0, uint32_t& t1) {
  uint32_t a[16];
  #pragma unroll
  for (int i = 0; i < 8; i++) { a[2 * i] = badd2(p[4 * i], p[4 * i + 2]); a[2 * i + 1] = badd2(p[4 * i + 1], p[4 * i + 3]); }
  #pragma unroll
  for (int i = 0; i < 4; i++) { a[2 * i] = badd2(a[4 * i], a[4 * i + 2]); a[2 * i + 1] = badd2(a[4 * i + 1], a[4 * i + 3]); }
  t0 = badd2(badd2(a[0], a[2]), badd2(a[4], a[6]));
  t1 = badd2(badd2(a[1], a[3]), badd2(a[5], a[7]));
}
__device__ __forceinline__ void add_rowsum(const uint32_t (&p)[32], float& l0, float& l1) {
  uint32_t t0, t1;
  rowsum_p(p, t0, t1);
  l0 += bflo(t0) + bfhi(t0); l1 += bflo(t1) + bfhi(t1);
}
__device__ __forceinline__ void pack_p(uint32_t (&p)[32], const float (&s)[64]) {
  #pragma unroll
  for (int i = 0; i < 32; i++) p[i] = pack_bf16(s[2 * i], s[2 * i + 1]);
}
__device__ __noinline__ void attn_rows_exact(uint32_t sq, uint32_t so, int hsel, const bf16* __restrict__ kh, const bf16* __restrict__ vh) {
  const int warp = (threadIdx.x >> 5) & 3, lane = threadIdx.x & 31;
  const size_t hofs = (size_t)((blockIdx.x < 128 ? blockIdx.x >> 4 : 15) * 2 + hsel) * T_SEQ * T_DH;
  kh += hofs; vh += hofs;
  #pragma unroll 1
  for (int r = 16 * warp; r < 16 * warp + 16; r++) {
    const uint32_t ad = (lane >> 4) * 16384 + r * 128 + ((((lane & 15) >> 1) ^ (r & 7)) << 4) + (lane & 1) * 8;
    uint2 qv; asm volatile("ld.shared.v2.u32 {%0, %1}, [%2];" : "=r"(qv.x), "=r"(qv.y) : "r"(sq + ad) : "memory");
    const float q0 = bflo(qv.x), q1 = bfhi(qv.x), q2 = bflo(qv.y), q3 = bfhi(qv.y);
    float m = -INFINITY, l = 0.f, o0 = 0.f, o1 = 0.f, o2 = 0.f, o3 = 0.f;
    #pragma unroll 1
    for (int key = 0; key < T_SEQ; key++) {
      const uint2 kv = *reinterpret_cast<const uint2*>(kh + (size_t)key * T_DH + lane * 4);
      const uint2 vv = *reinterpret_cast<const uint2*>(vh + (size_t)key * T_DH + lane * 4);
      float sc = (q0 * bflo(kv.x) + q1 * bfhi(kv.x)) + (q2 * bflo(kv.y) + q3 * bfhi(kv.y));
      #pragma unroll
      for (int o = 16; o > 0; o >>= 1) sc += __shfl_xor_sync(0xffffffffu, sc, o);
      const float mn = fmaxf(m, sc);
      const float al = (m == mn) ? 1.0f : ex2_approx(m - mn), p = rbf(ex2_approx(sc - mn));
      m = mn;
      l = fmaf(l, al, p);
      o0 = fmaf(o0, al, p * bflo(vv.x)); o1 = fmaf(o1, al, p * bfhi(vv.x));
      o2 = fmaf(o2, al, p * bflo(vv.y)); o3 = fmaf(o3, al, p * bfhi(vv.y));
    }
    const float inv = rcp_approx(l);
    asm volatile("st.shared.v2.u32 [%0], {%1, %2};" :: "r"(so + ad), "r"(pack_bf16(o0 * inv, o1 * inv)), "r"(pack_bf16(o2 * inv, o3 * inv)) : "memory");
  }
}
__device__ __forceinline__ void issue_qk(float (&s)[64], const uint32_t (&q)[32], uint32_t k_lo) {
  wgmma_fence();
  wgmma_m64n128k16_rs<0>(s, q[0], q[1], q[2], q[3], k_lo, 0);
  wgmma_m64n128k16_rs<2>(s, q[4], q[5], q[6], q[7], k_lo, 1);
  wgmma_m64n128k16_rs<4>(s, q[8], q[9], q[10], q[11], k_lo, 1);
  wgmma_m64n128k16_rs<6>(s, q[12], q[13], q[14], q[15], k_lo, 1);
  wgmma_m64n128k16_rs<1024>(s, q[16], q[17], q[18], q[19], k_lo, 1);
  wgmma_m64n128k16_rs<1026>(s, q[20], q[21], q[22], q[23], k_lo, 1);
  wgmma_m64n128k16_rs<1028>(s, q[24], q[25], q[26], q[27], k_lo, 1);
  wgmma_m64n128k16_rs<1030>(s, q[28], q[29], q[30], q[31], k_lo, 1);
  wgmma_commit();
}
__device__ __forceinline__ void issue_pv(float (&o)[64], const uint32_t (&p)[32], uint32_t v_lo, int accumulate) {
  wgmma_fence();
  wgmma_m64n128k16_rs_tb<0>(o, p[0], p[1], p[2], p[3], v_lo, accumulate);
  wgmma_m64n128k16_rs_tb<128>(o, p[4], p[5], p[6], p[7], v_lo, 1);
  wgmma_m64n128k16_rs_tb<256>(o, p[8], p[9], p[10], p[11], v_lo, 1);
  wgmma_m64n128k16_rs_tb<384>(o, p[12], p[13], p[14], p[15], v_lo, 1);
  wgmma_m64n128k16_rs_tb<512>(o, p[16], p[17], p[18], p[19], v_lo, 1);
  wgmma_m64n128k16_rs_tb<640>(o, p[20], p[21], p[22], p[23], v_lo, 1);
  wgmma_m64n128k16_rs_tb<768>(o, p[24], p[25], p[26], p[27], v_lo, 1);
  wgmma_m64n128k16_rs_tb<896>(o, p[28], p[29], p[30], p[31], v_lo, 1);
  wgmma_commit();
}
__device__ __forceinline__ void block_end(uint32_t zero, uint32_t bar) {
  #pragma unroll 1
  for (uint32_t i = 0; i < zero; i++) mbar_arrive(bar);
}
__device__ __forceinline__ void rescale_o(float (&o)[64], float al0, float al1) {
  #pragma unroll
  for (int j = 0; j < 16; j++) { o[4 * j] *= al0; o[4 * j + 1] *= al0; o[4 * j + 2] *= al1; o[4 * j + 3] *= al1; }
}

__device__ __forceinline__ void stage_o(const float (&o)[64], float i0, float i1, uint32_t dst, int lane) {
  #pragma unroll
  for (int J = 0; J < 16; J += 2)
    stmatrix_x4(dst + (J >> 3) * 16384 + ((((J & 7) + (lane >> 4)) ^ (lane & 7)) << 4),
                pack_bf16(o[4 * J + 0] * i0, o[4 * J + 1] * i0), pack_bf16(o[4 * J + 2] * i1, o[4 * J + 3] * i1),
                pack_bf16(o[4 * J + 4] * i0, o[4 * J + 5] * i0), pack_bf16(o[4 * J + 6] * i1, o[4 * J + 7] * i1));
}
__device__ __forceinline__ bool finish_l(float& l0, float& l1) {
  l0 += __shfl_xor_sync(0xffffffffu, l0, 1); l1 += __shfl_xor_sync(0xffffffffu, l1, 1);
  l0 += __shfl_xor_sync(0xffffffffu, l0, 2); l1 += __shfl_xor_sync(0xffffffffu, l1, 2);
  const bool redo = __any_sync(0xffffffffu, !(l0 <= AT_RAW_SUM && l1 <= AT_RAW_SUM && l0 >= AT_RAW_MIN && l1 >= AT_RAW_MIN));
  l0 = rcp_approx(l0); l1 = rcp_approx(l1);
  return redo;
}
template <int J0>
__device__ __forceinline__ void stage_q(const float (&acc)[128], float c, uint32_t dst, int lane) {
  #pragma unroll
  for (int J = J0; J < J0 + 16; J += 2)
    stmatrix_x4(dst + (J >> 3) * 16384 + ((((J & 7) + (lane >> 4)) ^ (lane & 7)) << 4),
                pack_bf16(acc[4 * J + 0] * c, acc[4 * J + 1] * c), pack_bf16(acc[4 * J + 2] * c, acc[4 * J + 3] * c),
                pack_bf16(acc[4 * J + 4] * c, acc[4 * J + 5] * c), pack_bf16(acc[4 * J + 6] * c, acc[4 * J + 7] * c));
}
__device__ __forceinline__ void store_o(const CUtensorMap* tmO, uint32_t src, int head, int row) {
  tma_store_2d(tmO, src, head * T_DH, row);
  tma_store_2d(tmO, src + 16384, head * T_DH + 64, row);
  bulk_commit();
}
__device__ __forceinline__ void mma_bf16(float (&d)[4], uint32_t a0, uint32_t a1, uint32_t a2, uint32_t a3, uint32_t b0, uint32_t b1) {
  asm volatile("mma.sync.aligned.m16n8k16.row.col.f32.bf16.bf16.f32 {%0, %1, %2, %3}, {%4, %5, %6, %7}, {%8, %9}, {%0, %1, %2, %3};"
               : "+f"(d[0]), "+f"(d[1]), "+f"(d[2]), "+f"(d[3]) : "r"(a0), "r"(a1), "r"(a2), "r"(a3), "r"(b0), "r"(b1));
}
struct GemvSel { uint32_t lo0, hi0, lo1, hi1; };
__device__ __forceinline__ GemvSel gemv_sel(int lane) {
  const uint32_t lo = (lane & 8) ? 0x1044u : 0x4410u, hi = (lane & 8) ? 0x3244u : 0x4432u;
  GemvSel s; s.lo0 = (lane & 16) ? 0x4444u : lo; s.hi0 = (lane & 16) ? 0x4444u : hi; s.lo1 = (lane & 16) ? lo : 0x4444u; s.hi1 = (lane & 16) ? hi : 0x4444u;
  return s;
}
#define GEMV_B0(j, h, s) __byte_perm((j) < 2 ? (h).x : (h).y, 0u, ((j) & 1) ? (s).hi0 : (s).lo0)
#define GEMV_B1(j, h, s) __byte_perm((j) < 2 ? (h).x : (h).y, 0u, ((j) & 1) ? (s).hi1 : (s).lo1)
__device__ __forceinline__ float4 gemv_out(const float (&d)[4], int lane) {
  const bool tk = lane & 1;
  const float r0 = __shfl_xor_sync(0xffffffffu, tk ? d[0] : d[1], 1), r1 = __shfl_xor_sync(0xffffffffu, tk ? d[2] : d[3], 1);
  return tk ? make_float4(r0, d[1], r1, d[3]) : make_float4(d[0], r0, d[2], r1);
}
#define OG_NG 8
#define PUT_N 2
#define H_STAG 2
#define NOZERO 1
#define PVPIN 1
#define QKPIN 0
#define ALIGN 1
#define AL_P 60
#define AL_SLEEP 1200
#define AL_MAX 800
#define AL_ADD 0
#define X_PF 0
#define POLL_NS 200
#define KV3D 1
#define W3D 1
#define ARV_IMM 1
#define ZS 1
#define OG_PRE 10
#define OG_PRE2 12
#define SERP 1
#define OG_JOBS 7
#define OG_GRP 6
#define LD_FIRST 3
#define LD_STAG (OG_GRP / 2)
constexpr int OG_ST = 5, OG_NKB = T_DQKV / 64 - OG_PRE, OG_MOE = T_F / 32;
__device__ __forceinline__ int pre_kb(int i) { return (i >> 1) * 4 + (i & 1); }
__device__ __forceinline__ int own_kb(int i) { return i < OG_PRE2 ? pre_kb(i) + 2 : i < 64 - OG_PRE2 ? i + OG_PRE2 : pre_kb(i - (64 - OG_PRE2 - OG_PRE)); }
constexpr int OG_POS = 8;
constexpr uint32_t OG_STAGE = 32768;
constexpr uint32_t OG_SCOL = AT_SBAR + 512;
constexpr uint32_t OG_SMISC = AT_SBAR + 2048;
constexpr int OG_XPOS = OG_POS + OG_NKB;
constexpr uint32_t OG_SWD = AT_SQ, OG_PSLOT = AT_SQ;
constexpr uint32_t OG_SWD1 = (OG_XPOS % OG_ST) * OG_STAGE;
constexpr uint32_t OG_XSLOT = AT_SQ + 32768;
constexpr uint32_t OG_OSLOT = ((OG_XPOS + 1) % OG_ST) * OG_STAGE;
constexpr uint32_t OG_SH2 = ((OG_XPOS + 2) % OG_ST) * OG_STAGE;
constexpr uint32_t OG_SRED = ((OG_XPOS + 3) % OG_ST) * OG_STAGE;
constexpr uint32_t OG_SSTAT = OG_SRED + 16384;
constexpr uint32_t OG_SGU = OG_SRED + 8192;
constexpr uint32_t OG_SFIN = OG_SGU + 256;
#define OGM 2
#define OG_MT(b) ((((b) >> OGM) & 15) ^ (SERP && ((b) & 64) ? 15 : 0))
#define OG_NT(b) (((b) & ((1 << OGM) - 1)) + (((b) >> (4 + OGM)) << OGM))
#define TAIL_SETUP \
  const uint32_t bar_full = sbase + AT_SBAR, bar_empty = bar_full + 40; \
  const uint32_t bar_wd = bar_full + 168, bar_col = bar_full + 176, bar_out = bar_full + 184, bar_end = bar_full + 192; \
  const uint32_t bar_key = bar_full + 200, bar_h2 = bar_full + 208, bar_sel = bar_full + 216; \
  const int mt = OG_MT(blockIdx.x), nt = OG_NT(blockIdx.x); \
  const int m0 = mt * 128, n0 = nt * 128; \
  const bool has_moe = (int)blockIdx.x < OG_MOE; \
  (void)bar_empty; (void)bar_wd; (void)bar_col; (void)bar_out; (void)bar_end; (void)bar_key; (void)bar_h2; (void)bar_sel; (void)m0; (void)n0; (void)has_moe;

__device__ __forceinline__ void tail_producer(uint32_t sbase, uint32_t ph, uint64_t pol, const CUtensorMap* tmA, const CUtensorMap* tmB, const CUtensorMap* tmX) {
  TAIL_SETUP
  uint32_t stage = OG_POS % OG_ST;
  int kb = 0;
  #pragma unroll 1
  for (int seg = 0; seg < 2; seg++) {
    mbar_wait(bar_full + 264 + 80 * seg, 0);
    fence_proxy_async_global();
    const int end = seg == 0 ? 32 - OG_PRE2 : has_moe ? OG_NKB : 64 - OG_PRE2;
    #pragma unroll 1
    for (; kb < end; kb++) {
      const uint32_t fb = bar_full + 8 * stage, sa = sbase + stage * OG_STAGE;
      const int k0 = own_kb(kb) * 64;
      mbar_wait(bar_empty + 8 * stage, ph);
      mbar_expect_tx(fb, OG_STAGE);
      tma_load_3d_hint(sa + 16384, tmB, k0, 2 * nt, fb, pol);
      tma_load_2d_hint(sa, tmA, k0, m0, fb, pol);
      if (++stage == OG_ST) { stage = 0; ph ^= 1; }
    }
  }
  if (has_moe) {
    mbar_wait(bar_empty + 8 * (OG_XPOS % OG_ST), ph);
    mbar_expect_tx(bar_wd, OG_STAGE);
    tma_load_3d_hint(sbase + OG_SWD1, tmX, blockIdx.x * 32, 8, bar_wd, pol);
  }
}

__device__ __forceinline__ uint32_t out2(uint32_t x1, uint32_t mb2, uint32_t ih, uint32_t il, uint32_t c1, uint32_t sb, uint32_t gb) {
  const uint32_t h2 = badd2(bmul2(ln_norm2b(x1, mb2, ih, il), c1), sb);
  return badd2(x1, bmul2(gb, bfma2(h2, 0u, h2)));
}
#define OGTIME gtime()
#define PRE_N 1
#define PRE_PACE 150
#define X_PACE 200
#define WD_LATE 0
#define Y_SLACK 80
#define WD_PACE 300
__device__ __forceinline__ void tail_exchange(uint32_t sbase, const bf16* __restrict__ w_down, const bf16* __restrict__ w_r, const bf16* __restrict__ x, bf16* __restrict__ out) {
    TAIL_SETUP
    const int lane = threadIdx.x & 31, wi = __shfl_sync(0xffffffffu, threadIdx.x >> 5, 0);
    if (wi == 3) {
      if (blockIdx.x < AT_NFULL) {
        uint32_t a, b;
        asm volatile("ld.relaxed.gpu.global.u32 %0, [%1];" : "=r"(a) : "l"(g_smid + 32 + blockIdx.x - lane) : "memory");
        b = __shfl_down_sync(0xffffffffu, a, 1);
        unsigned int* tm = g_tmax + blockIdx.x - min((int)blockIdx.x, __ffs(__ballot_sync(0xffffffffu, b >= a)) - 1);
        mbar_wait(bar_full + 312, 0);
        if (lane == 0) {
          asm volatile("mov.u32 %0, %%globaltimer_lo;" : "=r"(a));
          asm volatile("red.relaxed.gpu.global.max.u32 [%0], %1;" :: "l"(tm), "r"(a) : "memory");
          __nanosleep(AL_SLEEP);
          asm volatile("ld.relaxed.gpu.global.u32 %0, [%1];" : "=r"(b) : "l"(tm) : "memory");
          b -= a;
          sts_u32(sbase + OG_SMISC + 32, (b < AL_MAX ? b * 13 / 8 : 0u) + AL_ADD);
          mbar_arrive(bar_full + 320);
        }
        named_bar_sync(15, 32);
      }
      mbar_wait(bar_full + 344, 0);
      float a = g_scal[lane], b = g_scal[32 + lane];
      #pragma unroll
      for (int i = 0; i < 3; i++) {
        const uint4 v = *reinterpret_cast<const uint4*>(g_col + nt * 1536 + i * 512 + lane * 16);
        sts_u32x4(sbase + OG_SCOL + i * 512 + lane * 16, v.x, v.y, v.z, v.w);
      }
      #pragma unroll
      for (int o = 16; o > 0; o >>= 1) { a += __shfl_xor_sync(0xffffffffu, a, o); b += __shfl_xor_sync(0xffffffffu, b, o); }
      if (lane == 0) sts_f32x2(sbase + OG_SMISC, a, b);
      const uint64_t pol = policy_evict_first();
      #pragma unroll 1
      for (int r = lane >> 4; r < 128; r += 4) {
        __nanosleep(X_PACE);
        #pragma unroll
        for (int j = 0; j < 4; j += 2)
          asm volatile("cp.async.cg.shared.global.L2::cache_hint [%0], [%1], 16, %2;" :: "r"(sbase + OG_XSLOT + (lane & 8) * 2048 + (r + j) * 128 + (((lane ^ (r + j)) & 7) << 4)),
                       "l"(x + (size_t)(m0 + r + j) * T_D + n0 + (lane & 15) * 8), "l"(pol) : "memory");
      }
      asm volatile("cp.async.wait_all;" ::: "memory");
      __syncwarp();
      if (lane == 0) mbar_arrive(bar_col);
    } else if (wi == 2) {
      if (elect_one()) {
        const uint32_t b_free = bar_full + (blockIdx.x < AT_NFULL ? 80 : 160);
        mbar_wait(b_free, 0); mbar_wait(b_free, 1);
        #pragma unroll 1
        for (unsigned int i = 0; i < (1u << 20) && ld_acquire(&g_hcnt[32 * (1 + (blockIdx.x >> 3)) + 4 + ((blockIdx.x >> 1) & 3)]) == 0u; i++) __nanosleep(POLL_NS);
        TL_MARK2(23, true);
        fence_proxy_async_global();
        TL_MARK2(4, true);
        mbar_expect_tx(bar_full + 272, 32768);
        #pragma unroll 1
        for (int i = 0; i < PRE_N; i++) {
          bulk_load_hint(sbase + OG_PSLOT + i * (32768 / PRE_N), g_pre + blockIdx.x * 2048 + i * (2048 / PRE_N), 32768 / PRE_N,
                         bar_full + 272, policy_evict_first());
          if (PRE_N > 1) __nanosleep(PRE_PACE);
        }
      }
      named_bar_sync(14, 32);
      if (has_moe) {
        mbar_wait(bar_full + 96, 1); mbar_wait(bar_full + 304, 0);
        const uint64_t pol = policy_evict_first();
        #pragma unroll 1
        for (int r = 0; r < 32; r++) {
          __nanosleep(WD_PACE);
          #pragma unroll
          for (int j = 0; j < 2; j++)
            asm volatile("cp.async.cg.shared.global.L2::cache_hint [%0], [%1], 16, %2;" :: "r"(sbase + OG_SWD + (4 * j + (lane >> 3)) * 4096 + r * 128 + (((lane ^ r) & 7) << 4)),
                         "l"((const uint8_t*)w_down + (size_t)blockIdx.x * 65536 + r * 2048 + j * 512 + lane * 16), "l"(pol) : "memory");
        }
        asm volatile("cp.async.wait_all;" ::: "memory");
        __syncwarp();
        if (lane == 0) mbar_arrive(bar_wd);
      }
    }
    const uint4 wrv = ldg_nc_v4(w_r + threadIdx.x * 8);
    mbar_wait(bar_end, 0);
    if (threadIdx.x == 96) XT(10);
    TL_MARK2(22, lane == 0);
    if (wi == 0) {
      uint32_t k1 = 0u, k2 = 0u;
      #pragma unroll 1
      for (unsigned int spin = 0; spin < (1u << 22) && __any_sync(0xffffffffu, k1 == 0u); spin++) asm volatile("ld.relaxed.gpu.global.u32 %0, [%1];" : "=r"(k1) : "l"(g_key + lane) : "memory");
      TL_MARK2(28, lane == 0);
      warp_top2(k1, k2);
      if (lane == 0) {
        const uint32_t r1 = 0xffffu - (k1 & 0xffffu), r2 = 0xffffu - (k2 & 0xffffu);
        sts_u32x4(sbase + OG_SMISC + 64, r1, r2, (r1 >> 7) * 2, (r2 >> 7) * 2 + ((r1 >> 7) == (r2 >> 7)));
        mbar_arrive(bar_sel);
      }
    } else if (wi < 3) {
          mbar_wait(bar_key, 0);
          const uint4 kk = lds_u32x4(sbase + OG_SSTAT + 1024 + lane * 16);
          uint32_t k1 = max(kk.x, kk.y), k2 = min(kk.x, kk.y);
          k2 = max(max(k2, min(kk.z, kk.w)), min(k1, max(kk.z, kk.w))); k1 = max(k1, max(kk.z, kk.w));
          warp_top2(k1, k2);
          if (wi == 1) {
            if (lane == 0) {
              if (nt == (mt & 7)) st_relaxed2(g_key + mt * 2, k1, k2);
              sts_u32x2(sbase + OG_SMISC + 96, (~k1 >> 4) & 7u, (~k2 >> 4) & 7u);
              mbar_arrive(bar_full + 352);
            }
            TL_MARK2(27, lane == 0);
          } else {
            const uint32_t r = (~((lane & 16) ? k2 : k1)) & 127u, ch = lane & 15;
            const uint2 st = lds_u32x2(sbase + OG_SSTAT + r * 8);
            const uint4 xc = lds_u32x4(sbase + OG_XSLOT + (ch >> 3) * 16384 + r * 128 + (((ch ^ r) & 7) << 4));
            const uint4 c1 = lds_u32x4(sbase + OG_SCOL + 768 + ch * 16), sh = lds_u32x4(sbase + OG_SCOL + 1024 + ch * 16);
            const float inr = __uint_as_float(st.y);
            float* dst = reinterpret_cast<float*>(g_cand + (mt * 2 + (lane >> 4)) * 256 + nt * 16 + ch);
            st_tagged4(dst + 512, __uint_as_float(ln_mod2(xc.x, st.x, inr, c1.x, sh.x)), __uint_as_float(ln_mod2(xc.y, st.x, inr, c1.y, sh.y)),
                       __uint_as_float(ln_mod2(xc.z, st.x, inr, c1.z, sh.z)), __uint_as_float(ln_mod2(xc.w, st.x, inr, c1.w, sh.w)));
            st_tagged4(dst, __uint_as_float(xc.x), __uint_as_float(xc.y), __uint_as_float(xc.z), __uint_as_float(xc.w));
          }
    }
    mbar_wait(bar_sel, 0);
    const uint4 sel = lds_u32x4(sbase + OG_SMISC + 64);
    const int sel0 = (int)sel.x, sel1 = (int)sel.y;
    {
      const float* src0 = reinterpret_cast<const float*>(g_cand + sel.z * 256 + 128 + threadIdx.x);
      const float* src1 = reinterpret_cast<const float*>(g_cand + sel.w * 256 + 128 + threadIdx.x);
      float4 h0, h1;
      #pragma unroll 1
      for (unsigned int spin = 0; spin < (1u << 20); spin++) { h0 = ld_tagged4(src0); h1 = ld_tagged4(src1); if (__all_sync(0xffffffffu, tagged4(h0) & tagged4(h1))) break; }
      sts_f32x4(sbase + OG_SH2 + threadIdx.x * 16, h0.x, h0.y, h0.z, h0.w);
      sts_f32x4(sbase + OG_SH2 + 2048 + threadIdx.x * 16, h1.x, h1.y, h1.z, h1.w);
      __syncwarp();
      if (lane == 0) mbar_arrive(bar_h2);
      TL_MARK2(12, lane == 0);
      if (blockIdx.x >> 6) h0 = h1;
      float v[8], wr[8];
      unpack8(make_uint4(__float_as_uint(h0.x), __float_as_uint(h0.y), __float_as_uint(h0.z), __float_as_uint(h0.w)), v); unpack8(wrv, wr);
      float r = 0.f;
      #pragma unroll
      for (int i = 0; i < 8; i++) r = fmaf(v[i], wr[i], r);
      #pragma unroll
      for (int o = 16; o > 0; o >>= 1) r += __shfl_xor_sync(0xffffffffu, r, o);
      if (lane == 0) sts_f32(sbase + OG_SMISC + 192 + wi * 4, r);
    }
    mbar_wait(bar_out, 0);
    {
      const uint2 cg = lds_u32x2(sbase + OG_SMISC + 96);
      #pragma unroll
      for (int i = 0; i < 4; i++) {
        const int r = (i < 2 ? cg.x : cg.y) * 16 + (i & 1) * 8 + (threadIdx.x >> 4), ch = threadIdx.x & 15;
        if (m0 + r != sel0 && m0 + r != sel1)
          *reinterpret_cast<uint4*>(out + (size_t)(m0 + r) * T_D + n0 + ch * 8) =
              lds_u32x4(sbase + OG_OSLOT + (ch >> 3) * 16384 + r * 128 + (((ch & 7) ^ (r & 7)) << 4));
      }
    }
    if (blockIdx.x == 0 && threadIdx.x < 68) *reinterpret_cast<uint4*>(g_hcnt + 32 * (threadIdx.x >> 2) + 4 * (threadIdx.x & 3)) = make_uint4(0u, 0u, 0u, 0u);
    if (threadIdx.x < 64) g_modpart[blockIdx.x * 64 + threadIdx.x] = 0.f;
    if (ALIGN && threadIdx.x == 64) g_tmax[blockIdx.x] = 0u;
    {
      const int tk = blockIdx.x >> 6, c0 = (blockIdx.x & 63) * 16;
      const uint32_t gb2 = *reinterpret_cast<const uint32_t*>(g_col + (c0 >> 7) * 1536 + 512 + 768 + ((c0 & 127) + (threadIdx.x & 14)) * 2);
      const uint32_t* xp = reinterpret_cast<const uint32_t*>(g_cand + (tk ? sel.w : sel.z) * 256) + ((c0 + (threadIdx.x & 14)) >> 1);
      uint32_t x2 = 0u;
      #pragma unroll 1
      for (unsigned int spin = 0; spin < (1u << 20) && __any_sync(0xffffffffu, x2 == 0u); spin++) asm volatile("ld.relaxed.gpu.global.u32 %0, [%1];" : "=r"(x2) : "l"(xp) : "memory");
      const float* src = g_ypart + (size_t)((threadIdx.x >> 2) * 2 + tk) * T_D + c0 + (threadIdx.x & 3) * 4;
      const bool four = threadIdx.x < (OG_MOE - 96) * 4;
      if (threadIdx.x == 0) hint_wait(CNT_Y, (uint32_t)(OG_MOE - Y_SLACK));
      named_bar_sync(10, 128);
      float4 p0, p1, p2, p3;
      #pragma unroll 1
      for (unsigned int spin = 0; spin < (1u << 20); spin++) {
        p0 = ld_tagged4(src); p1 = ld_tagged4(src + 64 * T_D); p2 = ld_tagged4(src + 128 * T_D); p3 = ld_tagged4(four ? src + 192 * T_D : src);
        if (__all_sync(0xffffffffu, tagged4(p0) & tagged4(p1) & tagged4(p2) & tagged4(p3))) break;
      }
      if (four) { p2.x += p3.x; p2.y += p3.y; p2.z += p3.z; p2.w += p3.w; }
      p0.x = (p0.x + p1.x) + p2.x; p0.y = (p0.y + p1.y) + p2.y; p0.z = (p0.z + p1.z) + p2.z; p0.w = (p0.w + p1.w) + p2.w;
      #pragma unroll
      for (int o = 4; o <= 16; o <<= 1) {
        p0.x += __shfl_xor_sync(0xffffffffu, p0.x, o); p0.y += __shfl_xor_sync(0xffffffffu, p0.y, o);
        p0.z += __shfl_xor_sync(0xffffffffu, p0.z, o); p0.w += __shfl_xor_sync(0xffffffffu, p0.w, o);
      }
      if (lane < 4) sts_f32x4(sbase + OG_SFIN + (threadIdx.x >> 5) * 64 + lane * 16, p0.x, p0.y, p0.z, p0.w);
      named_bar_sync(10, 128);
      TL_MARK2(21, threadIdx.x == 0);
      if (threadIdx.x < 16) {
        const uint32_t ya = sbase + OG_SFIN + threadIdx.x * 4, rp = sbase + OG_SMISC + 192;
        float y = (lds_f32(ya) + lds_f32(ya + 64)) + (lds_f32(ya + 128) + lds_f32(ya + 192));
        const float r = rbf((lds_f32(rp) + lds_f32(rp + 4)) + (lds_f32(rp + 8) + lds_f32(rp + 12)));
        const float rs = rbf(sigmoid_f(r));
        const uint32_t h2p = lds_u32(sbase + OG_SH2 + tk * 2048 + (c0 + (threadIdx.x & 14)) * 2);
        const float fh = (lane & 1) ? bfhi(h2p) : bflo(h2p);
        y = rbf(y);
        y = rbf(y * rs);
        const float upd = rbf(rbf(fh * 0.0f) + y);
        out[(size_t)(tk ? sel1 : sel0) * T_D + c0 + threadIdx.x] =
            __float2bfloat16_rn(((lane & 1) ? bfhi(x2) : bflo(x2)) + rbf(((lane & 1) ? bfhi(gb2) : bflo(gb2)) * rbf(fh + upd)));
      }
    }
    if (threadIdx.x == 0) XT(11);
    TL_END(4, threadIdx.x == 0);
}

__device__ __forceinline__ void load_pre(uint4* pre, uint32_t sbase, uint32_t buf, int t2) {
  mbar_wait(sbase + AT_SBAR + 272, 0);
  #pragma unroll
  for (int i = 0; i < 8; i++) pre[i] = lds_u32x4(sbase + buf + i * 4096 + t2 * 16);
}
__device__ __forceinline__ void tail_consumer(uint32_t sbase, const CUtensorMap* tmOut, const uint4 (&pre)[8], int cwg, const bf16* __restrict__ w_gate, const bf16* __restrict__ w_up) {
    TAIL_SETUP
    const int tid = threadIdx.x & 127, t2 = threadIdx.x - 128;
    const int warp = tid >> 5, lane = tid & 31, w8 = t2 >> 5;
    const uint32_t dbase = (sbase & 0x3FFFFu) >> 4;
    const uint32_t a_base = dbase + ((cwg * 8192) >> 4) + (1u << 16);
    const uint32_t b_base = dbase + (16384 >> 4) + (512u << 16);
    TL_MARK2(25, threadIdx.x == 128);
    const uint64_t pol = policy_evict_first();
    const bf16* pw = ((lane & 16) ? w_up : w_gate) + (size_t)(w8 * 128 + (lane & 3) * 4) * T_F + (has_moe ? blockIdx.x : 0) * 32 + ((lane >> 2) & 3) * 8;
    uint4 wv[32];
    float acc[64];
    #pragma unroll
    for (int i = 0; i < 8; i++) {
      acc[8 * i] = bflo(pre[i].x); acc[8 * i + 1] = bfhi(pre[i].x); acc[8 * i + 2] = bflo(pre[i].y); acc[8 * i + 3] = bfhi(pre[i].y);
      acc[8 * i + 4] = bflo(pre[i].z); acc[8 * i + 5] = bfhi(pre[i].z); acc[8 * i + 6] = bflo(pre[i].w); acc[8 * i + 7] = bfhi(pre[i].w);
    }
    if (lane == 0) mbar_arrive(bar_full + 304);
    if (blockIdx.x < AT_NFULL) {
      const uint32_t c0 = clock_lo();
      mbar_wait(bar_full + 320, 0);
      const uint32_t d = lds_u32(sbase + OG_SMISC + 32);
      while (clock_lo() - c0 < d) {}
    }
    {
      uint32_t stage = OG_POS % OG_ST, phase = (OG_POS / OG_ST) & 1, prev = 12;
      int kb = 0;
      #pragma unroll
      for (int g = 0; g <= OG_NG; g++) {
        const int end = g == OG_NG ? (has_moe ? OG_NKB : 64 - OG_PRE2) : LD_FIRST + g * OG_GRP + LD_STAG * cwg;
        #pragma unroll 1
        do {
          mbar_wait(bar_full + 8 * stage, phase);
          const uint32_t a_lo = a_base + stage * (OG_STAGE >> 4), b_lo = b_base + stage * (OG_STAGE >> 4);
          wgmma_fence();
          wgmma_m64n128k16_ss_tb<0, 0>(acc, a_lo, b_lo, 1);
          wgmma_m64n128k16_ss_tb<2, 128>(acc, a_lo, b_lo, 1);
          wgmma_m64n128k16_ss_tb<4, 256>(acc, a_lo, b_lo, 1);
          wgmma_m64n128k16_ss_tb<6, 384>(acc, a_lo, b_lo, 1);
          wgmma_commit();
          wgmma_wait<1>();
          if (tid == 0) mbar_arrive(bar_empty + 8 * prev);
          prev = stage;
          if (++stage == OG_ST) { stage = 0; phase ^= 1; }
        } while (++kb < end);
        #pragma unroll
        for (int j = 4 * g; j < 4 * g + 4 && j < 32; j++) wv[j] = ldg_stream_v4(pw + (size_t)(16 * (j >> 2) + (j & 3)) * T_F, pol);
      }
    }
    mbar_wait(bar_col, 0);
    if (__builtin_expect(!has_moe, 0)) {
      load_pre(wv, sbase, AT_SQ, t2);
    }
    wgmma_wait<0>();
    fence_regs(acc);
    if (__builtin_expect(!has_moe, 0)) {
      #pragma unroll
      for (int i = 0; i < 8; i++) {
        acc[8 * i] += bflo(wv[i].x); acc[8 * i + 1] += bfhi(wv[i].x); acc[8 * i + 2] += bflo(wv[i].y); acc[8 * i + 3] += bfhi(wv[i].y);
        acc[8 * i + 4] += bflo(wv[i].z); acc[8 * i + 5] += bfhi(wv[i].z); acc[8 * i + 6] += bflo(wv[i].w); acc[8 * i + 7] += bfhi(wv[i].w);
      }
    }
    if (tid == 0) mbar_arrive(bar_end);
    TL_MARK2(9, lane == 0);
    const int q2 = 2 * (lane & 3);
    const uint32_t frag = (64 * cwg + 16 * warp + (lane & 7) + 8 * ((lane >> 3) & 1)) * 128;
    const int fsw = lane & 7, fhi = lane >> 4;
    {
      float dl[4] = {0.f, 0.f, 0.f, 0.f}, da[4] = {0.f, 0.f, 0.f, 0.f}, db[4] = {0.f, 0.f, 0.f, 0.f};
      const uint32_t tb = sbase + OG_SCOL + (lane & 8) * 32 + (lane & 3) * 8, g = lane >> 2;
      const uint32_t msk = (g == 1 || g == 2) ? 0xffffffffu : 0u, one = g == 0 ? 0x3F803F80u : 0u;
      #pragma unroll
      for (int J = 0; J < 16; J += 2) {
        const uint32_t ad = sbase + OG_XSLOT + (J >> 3) * 16384 + frag + ((((J & 7) + fhi) ^ fsw) << 4);
        uint32_t xr[4];
        ldmatrix_x4(ad, xr[0], xr[1], xr[2], xr[3]);
        const uint2 cw = lds_u32x2(tb + J * 16);
        #pragma unroll
        for (int h = 0; h < 2; h++) {
          const uint32_t ga = lds_u32(sbase + OG_SCOL + 512 + (8 * (J + h) + q2) * 2);
          xr[2 * h] = badd2(xr[2 * h], bmul2(ga, pack_bf16(acc[4 * (J + h)], acc[4 * (J + h) + 1])));
          xr[2 * h + 1] = badd2(xr[2 * h + 1], bmul2(ga, pack_bf16(acc[4 * (J + h) + 2], acc[4 * (J + h) + 3])));
        }
        stmatrix_x4(ad, xr[0], xr[1], xr[2], xr[3]);
        mma_bf16(dl, xr[0], xr[1], xr[2], xr[3], (cw.x & msk) | one, (cw.y & msk) | one);
        mma_bf16(da, xr[0], xr[1], xr[2], xr[3], xr[0], xr[2]);
        mma_bf16(db, xr[0], xr[1], xr[2], xr[3], xr[1], xr[3]);
      }
      {
        const int dsrc = (lane & ~3) + (g >> 1);
        const float qa = __shfl_sync(0xffffffffu, (g & 1) ? da[1] : da[0], dsrc), qb = __shfl_sync(0xffffffffu, (g & 1) ? db[3] : db[2], dsrc);
        const float e0 = __shfl_xor_sync(0xffffffffu, (lane & 1) ? dl[0] : dl[2], 1), e1 = __shfl_xor_sync(0xffffffffu, dl[3], 1);
        if ((lane & 3) < 2) {
          const bool hi = lane & 1;
          st_tagged4(reinterpret_cast<float*>(g_part1 + ((mt * 8 + w8) * 8 + nt) * 16 + g + (hi ? 8 : 0)),
                     hi ? e0 : dl[0], hi ? qb : qa, hi ? e1 + dl[2] : dl[1] + e0, 1.0f);
        }
      }
    }
    TL_MARK2(10, lane == 0);
    uint4 wd[16];
    if (has_moe) mbar_wait(bar_wd, 0);
    #pragma unroll
    for (int i = 0; i < 16; i++) wd[i] = lds_u32x4(sbase + (cwg ? OG_SWD1 : OG_SWD) + warp * 8192 + (i >> 3) * 4096 + (i & 6) * 512 + (i & 1) * 128 + (lane & 3) * 256 + (((lane >> 2) ^ (2 * (lane & 3) + (i & 1))) << 4));
    {
      const float* src = reinterpret_cast<const float*>(g_part1 + ((mt * 8 + w8) * 8 + (lane & 1) * 4) * 16 + (lane >> 1));
      float4 v, v1, v2, v3;
      #pragma unroll 1
      for (unsigned int spin = 0; spin < (1u << 22); spin++) {
        v = ld_tagged4(src); v1 = ld_tagged4(src + 64); v2 = ld_tagged4(src + 128); v3 = ld_tagged4(src + 192);
        if (__all_sync(0xffffffffu, tagged4(v) & tagged4(v1) & tagged4(v2) & tagged4(v3))) break;
        __nanosleep(100);
      }
      __syncwarp();
      TL_MARK2(26, lane == 0);
      v.x = (v.x + v1.x) + (v2.x + v3.x); v.y = (v.y + v1.y) + (v2.y + v3.y); v.z = (v.z + v1.z) + (v2.z + v3.z);
      v.x += __shfl_xor_sync(0xffffffffu, v.x, 1); v.y += __shfl_xor_sync(0xffffffffu, v.y, 1); v.z += __shfl_xor_sync(0xffffffffu, v.z, 1);
      const float mean = v.x * (1.0f / T_D);
      const float var = fmaxf(fmaf(-mean, mean, v.y * (1.0f / T_D)), 0.f);
      const uint32_t mb2 = pack_bf16(mean, mean);
      const float inv = rcp_approx(rbf(sqrt_approx(rbf(rbf(var) + 1e-05f))));
      {
        const float2 sc = lds_f32x2(sbase + OG_SMISC);
        const uint32_t key = rank_key(rbf(fmaf(fmaf(-bflo(mb2), sc.x, v.z), inv, sc.y)), m0 + 16 * w8 + (lane >> 1));
        mbar_wait(bar_end, 0);
        if (lane & 1) sts_u32(sbase + OG_SSTAT + 1024 + (16 * w8 + (lane >> 1)) * 4, key);
        else sts_u32x2(sbase + OG_SSTAT + (16 * w8 + (lane >> 1)) * 8, mb2, __float_as_uint(inv));
        __syncwarp();
        if (lane == 0) mbar_arrive(bar_key);
      }
      const uint32_t ih = pack_bf16(inv, inv), il = pack_bf16(inv - bflo(ih), inv - bflo(ih));
      const uint32_t mba = __shfl_sync(0xffffffffu, mb2, 2 * (lane >> 2)), mbb = __shfl_sync(0xffffffffu, mb2, 2 * (lane >> 2) + 16);
      const uint32_t iha = __shfl_sync(0xffffffffu, ih, 2 * (lane >> 2)), ihb = __shfl_sync(0xffffffffu, ih, 2 * (lane >> 2) + 16);
      const uint32_t ila = __shfl_sync(0xffffffffu, il, 2 * (lane >> 2)), ilb = __shfl_sync(0xffffffffu, il, 2 * (lane >> 2) + 16);
      #pragma unroll 2
      for (int J = 0; J < 16; J += 2) {
        const uint32_t off = (J >> 3) * 16384 + frag + ((((J & 7) + fhi) ^ fsw) << 4);
        uint32_t xr[4];
        ldmatrix_x4(sbase + OG_XSLOT + off, xr[0], xr[1], xr[2], xr[3]);
        #pragma unroll
        for (int h = 0; h < 2; h++) {
          const uint32_t ca = sbase + OG_SCOL + 512 + (8 * (J + h) + q2) * 2;
          const uint32_t c1 = lds_u32(ca + 256), sh = lds_u32(ca + 512), gb = lds_u32(ca + 768);
          xr[2 * h] = out2(xr[2 * h], mba, iha, ila, c1, sh, gb);
          xr[2 * h + 1] = out2(xr[2 * h + 1], mbb, ihb, ilb, c1, sh, gb);
        }
        stmatrix_x4(sbase + OG_OSLOT + off, xr[0], xr[1], xr[2], xr[3]);
      }
      fence_proxy_async();
      mbar_wait(bar_full + 352, 0);
      const uint2 cg = lds_u32x2(sbase + OG_SMISC + 96);
      __syncwarp();
      if (elect_one()) {
        mbar_arrive(bar_out);
        if (cg.x != w8 && cg.y != w8) {
          asm volatile("cp.async.bulk.tensor.2d.global.shared::cta.bulk_group [%0, {%2, %3}], [%1];" :: "l"(tmOut), "r"(sbase + OG_OSLOT + w8 * 2048), "r"(n0), "r"(m0 + 16 * w8) : "memory");
          asm volatile("cp.async.bulk.tensor.2d.global.shared::cta.bulk_group [%0, {%2, %3}], [%1];" :: "l"(tmOut), "r"(sbase + OG_OSLOT + 16384 + w8 * 2048), "r"(n0 + 64), "r"(m0 + 16 * w8) : "memory");
          bulk_commit();
        }
      }
      TL_MARK2(24, lane == 0);
    }
    if (has_moe) mbar_wait(bar_h2, 0);
    TL_MARK2(13, lane == 0);
    if (has_moe) {
      const GemvSel sel = gemv_sel(lane);
      {
        float d[4][4];
        #pragma unroll
        for (int c = 0; c < 4; c++) { d[c][0] = 0.f; d[c][1] = 0.f; d[c][2] = 0.f; d[c][3] = 0.f; }
        #pragma unroll
        for (int st = 0; st < 8; st++) {
          const uint2 hb = lds_u32x2(sbase + OG_SH2 + ((lane >> 2) & 1) * 2048 + (w8 * 128 + st * 16 + (lane & 3) * 4) * 2);
          #pragma unroll
          for (int j = 0; j < 4; j++) mma_bf16(d[j], wv[4 * st + j].x, wv[4 * st + j].y, wv[4 * st + j].z, wv[4 * st + j].w, GEMV_B0(j, hb, sel), GEMV_B1(j, hb, sel));
        }
        #pragma unroll
        for (int e = 0; e < 4; e++) d[0][e] = (d[0][e] + d[1][e]) + (d[2][e] + d[3][e]);
        const float4 r = gemv_out(d[0], lane);
        sts_f32x4(sbase + OG_SRED + w8 * 512 + (((lane >> 4) * 2 + (lane & 1)) * 32 + ((lane >> 2) & 3) * 8 + (lane & 2) * 2) * 4, r.x, r.y, r.z, r.w);
      }
      named_bar_sync(9, 256);
      if (t2 < 64) {
        float gp[8], up[8];
        #pragma unroll
        for (int w = 0; w < 8; w++) { gp[w] = lds_f32(sbase + OG_SRED + w * 512 + t2 * 4); up[w] = lds_f32(sbase + OG_SRED + w * 512 + 256 + t2 * 4); }
        const float gs = ((gp[0] + gp[1]) + (gp[2] + gp[3])) + ((gp[4] + gp[5]) + (gp[6] + gp[7]));
        const float us = ((up[0] + up[1]) + (up[2] + up[3])) + ((up[4] + up[5]) + (up[6] + up[7]));
        asm volatile("st.shared.u16 [%0], %1;" :: "r"(sbase + OG_SGU + ((t2 & ~15) + ((t2 >> 1) & 3) * 4 + ((t2 >> 3) & 1) * 2 + (t2 & 1)) * 2), "h"((uint16_t)pack_bf16(silu_bf(rbf(gs)) * rbf(us), 0.f)) : "memory");
      }
      named_bar_sync(9, 256);
      TL_MARK2(20, threadIdx.x == 128);
      float d[4][4];
      #pragma unroll
      for (int c = 0; c < 4; c++) { d[c][0] = 0.f; d[c][1] = 0.f; d[c][2] = 0.f; d[c][3] = 0.f; }
      #pragma unroll
      for (int st = 0; st < 2; st++) {
        const uint2 g = lds_u32x2(sbase + OG_SGU + ((lane >> 2) & 1) * 64 + st * 32 + (lane & 3) * 8);
        #pragma unroll
        for (int j = 0; j < 4; j++) {
          const uint32_t b0 = GEMV_B0(j, g, sel), b1 = GEMV_B1(j, g, sel);
          mma_bf16(d[j & 1], wd[4 * st + j].x, wd[4 * st + j].y, wd[4 * st + j].z, wd[4 * st + j].w, b0, b1);
          mma_bf16(d[2 + (j & 1)], wd[8 + 4 * st + j].x, wd[8 + 4 * st + j].y, wd[8 + 4 * st + j].z, wd[8 + 4 * st + j].w, b0, b1);
        }
      }
      #pragma unroll
      for (int e = 0; e < 4; e++) { d[0][e] += d[1][e]; d[2][e] += d[3][e]; }
      const float4 y0 = gemv_out(d[0], lane), y1 = gemv_out(d[2], lane);
      float* yp = g_ypart + (size_t)(blockIdx.x * 2 + (lane & 1)) * T_D + w8 * 128 + (lane >> 2) * 8 + (lane & 2) * 2;
      st_tagged4(yp, y0.x, y0.y, y0.z, y0.w);
      st_tagged4(yp + 64, y1.x, y1.y, y1.z, y1.w);
      named_bar_sync(9, 256);
      if (t2 == 0) hint_arrive(CNT_Y);
    }
    bulk_wait_read<0>();
    TL_MARK2(14, threadIdx.x == 128);
    TL_CLK(4, 1, threadIdx.x == 128);
}

#define OG_JOBS2 (16 - OG_JOBS)
__device__ __forceinline__ int help_njobs() { return blockIdx.x < 128 ? OG_JOBS : OG_JOBS2; }
__device__ __forceinline__ int help_job(int i) { return (i < OG_JOBS ? 16 * i + (blockIdx.x >> 7) * 2 : 112 + (i - OG_JOBS) * 2) + (blockIdx.x & 3) * 4; }
__device__ __noinline__ void store_warp(uint32_t sbase, const CUtensorMap* tmO, int item0, int n_items) {
  if (elect_one()) {
    const uint32_t bars = sbase + AT_SBAR, b_q0 = bars + 80, b_ob = bars + 96, b_ordy = bars + 104, b_acq = bars + 264;
    const unsigned int* cnt = &g_hcnt[32 * (1 + OG_MT(blockIdx.x)) + 2];
    #pragma unroll 1
    for (int q = 0; q < 4 * n_items; q++) {
      const int item = item0 + (q >> 2) * 128, h = (q >> 1) & 1, w = q & 1;
      const bool last = (q >> 2) == n_items - 1;
      if (q == 4 * n_items - 4) { mbar_wait(bars + 288, 0); red_release_add(&g_hcnt[1], 1u); }
      mbar_wait(b_ordy + 8 * (q & 3), q >> 2);
      store_o(tmO, (h ? (last ? sbase + AT_SQ + 32768 : sbase + 2 * 32768) : sbase + AT_SQ) + w * 8192, (item >> 4) * 2 + h, (item & 15) * 128 + w * 64);
      if (w) {
        bulk_wait_read<0>();
        mbar_arrive(h ? b_ob : b_q0);
        bulk_wait<0>();
        fence_proxy_async_global();
        asm volatile("fence.acq_rel.gpu;" ::: "memory");
        hint_arrive(&g_hcnt[32 * (1 + (item & 15)) + 2 + (item >> 7)]);
        if (!h && item < 128) hint_arrive(&g_hcnt[2]);
        if (q == 5) { spin_until(cnt, 16u); mbar_arrive(b_acq); }
      }
    }
    if (n_items == 1) {
      #pragma unroll 1
      for (int i = 0; i < help_njobs(); i++) {
        mbar_wait(b_acq + 16, i & 1);
        TL_MARK2(23, i == OG_JOBS - 1);
        red_release_add(&g_hcnt[32 * (1 + (help_job(i) >> 3)) + 4 + ((help_job(i) >> 1) & 3)], 1u);
        TL_MARK2(4, i == OG_JOBS - 1);
        if (i == PRE_X - 1) { spin_until(&g_hcnt[1], 132u); mbar_arrive(b_acq + 32); }
      }
    }
    if (blockIdx.x < 128) {
      if (n_items == 1) { spin_until(cnt, 16u); mbar_arrive(b_acq); }
      spin_until(&g_hcnt[0], 128u); spin_until(cnt + 1, 16u); mbar_arrive(b_acq + 80);
    }
  }
}

__global__ void __launch_bounds__(384, 1)
fused_kernel(const __grid_constant__ CUtensorMap tmH, const __grid_constant__ CUtensorMap tmW, const __grid_constant__ CUtensorMap tmK,
            const __grid_constant__ CUtensorMap tmV, const __grid_constant__ CUtensorMap tmO, const __grid_constant__ CUtensorMap tmOl, const __grid_constant__ CUtensorMap tmWo,
            const __grid_constant__ CUtensorMap tmX, const __grid_constant__ CUtensorMap tmOut, const __grid_constant__ CUtensorMap tmM, uint32_t zero,
            const uint8_t* __restrict__ pf_wo, const bf16* __restrict__ kc, const bf16* __restrict__ vc,
            const bf16* __restrict__ x, const bf16* __restrict__ cvec, const bf16* __restrict__ w_mod, const bf16* __restrict__ w_r,
            const bf16* __restrict__ w_gate, const bf16* __restrict__ w_up, const bf16* __restrict__ w_down, bf16* __restrict__ out)
{
  extern __shared__ __align__(1024) uint8_t smem_raw[];
  const uint32_t sbase = smem_u32(smem_raw);
  const uint32_t bars = sbase + AT_SBAR;
  const uint32_t b_full = bars, b_empty = bars + 40;
  const uint32_t b_q0 = bars + 80, b_q1 = bars + 88;
  const uint32_t b_ob = bars + 96;
  const uint32_t b_ordy = bars + 104;
  const uint32_t b_pin = bars + 136;
  const uint32_t b_head = bars + 144;
  const uint32_t b_go = bars + 152;
  const uint32_t b_x = bars + 160;
  const int wg = __shfl_sync(0xffffffffu, threadIdx.x >> 7, 0);
  const bool single = blockIdx.x >= AT_NFULL;
  const int item0 = __shfl_sync(0xffffffffu, blockIdx.x < 128 ? (int)blockIdx.x : (int)blockIdx.x + 124, 0), n_items = __shfl_sync(0xffffffffu, single ? 1 : 2, 0);
  TL_START(3);
  if (threadIdx.x == 0) {
    if (sbase & 1023u) __trap();
    for (int i = 0; i < 5; i++) { mbar_init(b_full + 8 * i, 1); mbar_init(b_empty + 8 * i, 2); }
    mbar_init(b_q0, 1); mbar_init(b_q1, 8); mbar_init(b_ob, 1);
    for (int i = 0; i < 4; i++) mbar_init(b_ordy + 8 * i, 4);
    mbar_init(b_pin, 1); mbar_init(b_head, blockIdx.x < 128 ? 8 : 1); mbar_init(b_go, 1); mbar_init(b_x, 1);
    mbar_init(bars + 168, 2); mbar_init(bars + 176, 1); mbar_init(bars + 184, 8); mbar_init(bars + 192, 2);
    mbar_init(bars + 200, 8); mbar_init(bars + 208, 4); mbar_init(bars + 216, 1); mbar_init(bars + 264, 1); mbar_init(bars + 272, 1); mbar_init(bars + 280, 8); mbar_init(bars + 288, 1); mbar_init(bars + 296, 1); mbar_init(bars + 304, 8); mbar_init(bars + 312, 1); mbar_init(bars + 320, 1); mbar_init(bars + 328, 1); mbar_init(bars + 344, 1); mbar_init(bars + 352, 1);
    fence_mbar_init();
  }

  if (wg == 0) {
    reg_dealloc<AT_PREG>();
    if (threadIdx.x < 32) { __syncwarp(); named_bar_arrive(6, 384); }
    if (threadIdx.x >= 64) {
      named_bar_sync(6, 384);
      if (blockIdx.x < 128) {
        named_bar_sync(threadIdx.x >= 96 ? 8 : 9, 288);
        if ((threadIdx.x & 31) == 0) red_release_add(&g_hcnt[32 * (1 + (blockIdx.x >> 3)) + (threadIdx.x >= 96)], 1u);
        TL_MARK2(11, threadIdx.x == 64);
      }
      if (blockIdx.x < 128) {
        mbar_wait(MOD_AT, 0);
        mod_rest(sbase + OG_SCOL, b_q1, threadIdx.x - 64, cvec, w_mod, w_r);
      }
    } else if (threadIdx.x >= 32) {
      named_bar_sync(6, 384);
      store_warp(sbase, &tmO, item0, n_items);
      __syncwarp();
    } else {
     if (elect_one()) {
      const uint64_t pol = policy_evict_first();
      if (blockIdx.x < 128) {
        mbar_expect_tx(b_x, 32768);
        if (X_DLY) { const uint32_t c0 = clock_lo(); while (clock_lo() - c0 < X_DLY) {} }
        bulk_load_hint(sbase + 4 * 32768, x + (size_t)blockIdx.x * 16 * T_D, 32768, b_x, pol);
      }
      prefetch_tmap(&tmW); prefetch_tmap(&tmM); prefetch_tmap(&tmH); prefetch_tmap(&tmWo); prefetch_tmap(&tmOl);
      {
        const uint32_t c0 = clock_lo();
        while (clock_lo() - c0 < W_DLY) {}
        if (blockIdx.x < 128 && (blockIdx.x & 15) >= 4 * H_SPLIT) {
          mbar_expect_tx(bars + 328, 32768);
          tma_load_2d_hint(sbase + 3 * 32768, &tmM, (blockIdx.x & 31) * 64, (blockIdx.x >> 5) * 256, bars + 328, pol);
        }
        while (clock_lo() - c0 < W_DLY + W_FIRST) {}
      }
      uint32_t slot = 0, ph = 1;
      if (ALIGN) { uint32_t sm; asm volatile("mov.u32 %0, %%smid;" : "=r"(sm)); g_smid[32 + blockIdx.x] = sm; }
      #pragma unroll 1
      for (int it = 0; it < n_items; it++) {
        const int item = item0 + it * 128, hp = item >> 4, qt = item & 15;
        const bool first = it == 0;
        #pragma unroll 1
        for (int j = 0; j < T_D / 64; j++) {
          const uint32_t sl = ring_slot(qp_pos(j, it)), fb = b_full + 8 * sl;
          mbar_wait(b_empty + 8 * sl, ring_par(qp_pos(j, it)) ^ ((j >> 2) & 1) ^ 1);
          if (first && j == 3) mbar_wait(b_head, 0);
          mbar_expect_tx(fb, 49152);
          tma_load_3d_hint(sbase + sl * 32768, &tmW, j * 64, hp * 4, fb, pol);
          if (first && j < PRE_B) {
            if (j == PRE_B - 1) {
              spin_until(&g_hcnt[32 * (1 + qt)], 8u);
              TL_MARK2(16, true);
              fence_proxy_async_global();
              #pragma unroll 1
              for (int i = 0; i < PRE_B; i++) tma_load_2d(sbase + AT_SQ + i * 16384, &tmH, i * 64, qt * 128, b_full + 8 * i);
              mbar_arrive(b_go);
            }
          } else {
            if (first && j == 4 * H_SPLIT) { spin_until(&g_hcnt[32 * (1 + qt) + 1], 8u); fence_proxy_async_global(); }
            if (!first && (j == 0 || j == 2)) mbar_wait(j ? b_q1 : b_q0, 0);
            tma_load_2d_hint(sbase + AT_SQ + (j & 3) * 16384, &tmH, j * 64, qt * 128, fb, first ? pol_normal() : pol);
          }
        }
        #pragma unroll 1
        for (int j = 0; j < 4 * AT_NBLK; j++) {
          const bool isv = (j > 0 && !(j & 1)) || j == 4 * AT_NBLK - 1;
          const int row = hp * 2 * T_SEQ + (isv ? (j - 1) >> 1 : (j + 1) >> 1) * 128;
          const uint32_t fb = b_full + 8 * slot;
          mbar_wait(b_empty + 8 * slot, ph);
          if (!first && j == 3) mbar_wait(b_ob, 0);
          if (j == 4 && it == n_items - 1) mbar_arrive(bars + 288);
          if (ALIGN && j == AL_P && it == 1) mbar_arrive(bars + 312);
          mbar_expect_tx(fb, 32768);
          tma_load_3d_hint(sbase + slot * 32768, isv ? &tmV : &tmK, row, 0, fb, pol);
          if (it == 1 && isv && j >= 2 * WO_LATE && j < 2 * WO_LATE + 32 && blockIdx.x < OG_NKB)
            l2_prefetch_bulk(pf_wo + (size_t)own_kb(blockIdx.x) * 131072 + ((j >> 1) - WO_LATE) * 8192, 8192);
          if (++slot == 5) { slot = 0; ph ^= 1; }
        }
      }
      if (__builtin_expect(single, 0)) {
        spin_until(&g_hcnt[2], 128u);
        fence_proxy_async_global();
        const int nj = OG_JOBS * OG_PRE + (help_njobs() - OG_JOBS) * OG_PRE2;
        int ji = 0, job = help_job(0), kk = 0;
        #pragma unroll 1
        for (int j = 0; j < nj; j++) {
          const uint32_t sl = ring_slot(qp_pos(j, 1)), fb = b_full + 8 * sl;
          mbar_wait(b_empty + 8 * sl, ring_par(qp_pos(j, 1)) ^ ((j >> 2) & 1) ^ 1);
          mbar_expect_tx(fb, 49152);
          tma_load_3d_hint(sbase + sl * 32768, &tmWo, pre_kb(kk) * 64, OG_NT(job) * 2, fb, HPOL_B);
          tma_load_3d_hint(sbase + sl * 32768 + 16384, &tmWo, pre_kb(kk) * 64, OG_NT(job) * 2 + 2, fb, HPOL_B);
          if (j == 0 || j == 2) mbar_wait(j ? b_ob : b_q0, 0);
          tma_load_2d_hint(sbase + AT_SQ + (j & 3) * 16384, &tmOl, pre_kb(kk) * 64, OG_MT(job) * 128, fb, HPOL_A);
          if (++kk == (ji < OG_JOBS ? OG_PRE : OG_PRE2)) { kk = 0; job = help_job(++ji); }
        }
      }
      if (blockIdx.x < 128) {
        if (single) mbar_wait(b_x, 1);
        tail_producer(sbase, 0, pol, &tmOl, &tmWo, &tmX);
      }
     }
    }
    named_bar_sync(12 + (threadIdx.x >> 5), 32);
    if (blockIdx.x < 128) tail_exchange(sbase, w_down, w_r, x, out);
  } else {
    if (blockIdx.x < 128) head_phase(sbase + AT_SQ + 49152, sbase + 4 * 32768, b_x, b_go, b_head, threadIdx.x - 128, zero, cvec, w_mod);
    else { named_bar_sync(6, 384); if (threadIdx.x == 128) mbar_arrive(b_head); }
    TL_MARK2(0, threadIdx.x == 128);
    reg_alloc<AT_CREG>();
    const int cwg = wg - 1;
    const int tid = threadIdx.x & 127;
    const int warp = tid >> 5, lane = tid & 31;
    const uint32_t dbase = (sbase & 0x3FFFFu) >> 4;
    const uint32_t k_base = dbase + (1u << 16);
    const uint32_t v_base = dbase + (1024u << 16);
    const uint32_t w_base = dbase + (512u << 16);
    const uint32_t q_lo = dbase + ((AT_SQ + cwg * 8192) >> 4) + (1u << 16);
    const uint32_t frag = cwg * 8192 + (16 * warp + (lane & 7) + 8 * ((lane >> 3) & 1)) * 128;
    if (cwg == 1) named_bar_arrive(1, 256);
    bool raw = false;
    uint4 pre[8];
    #pragma unroll 1
    for (int it = 0; it < n_items; it++) {
      const bool more = it + 1 < n_items;
      constexpr int nkb = T_D / 64;
      const int ta = __shfl_sync(0xffffffffu, 4 * it, 0);
      float acc[128];
      {
        FS(2 * it, 0);
        #pragma unroll
        for (int i = 0; i < 128; i++) asm volatile("" : "=f"(acc[i]));
        {
          const uint32_t slot = ring_slot(ta), b_lo = w_base + slot * 2048;
          mbar_wait(b_full + 8 * slot, ring_par(ta));
          wgmma_fence();
          wgmma_m64n256k16_ss_tb<0, 0>(acc, q_lo, b_lo, 0);
          wgmma_m64n256k16_ss_tb<2, 128>(acc, q_lo, b_lo, 1);
          wgmma_m64n256k16_ss_tb<4, 256>(acc, q_lo, b_lo, 1);
          wgmma_m64n256k16_ss_tb<6, 384>(acc, q_lo, b_lo, 1);
          wgmma_commit();
        }
        #pragma unroll 1
        for (int j = NOZERO; j < nkb; j++) {
          const uint32_t slot = ring_slot(qp_pos(j, ta >> 2));
          mbar_wait(b_full + 8 * slot, ring_par(qp_pos(j, ta >> 2)) ^ ((j >> 2) & 1));
          if (QP_STAG > 0 && cwg == 1 && j == nkb - QP_STAG) named_bar_sync(7, 256);
          const uint32_t a_lo = q_lo + (j & 3) * 1024, b_lo = w_base + slot * 2048;
          wgmma_fence();
          wgmma_m64n256k16_ss_tb<0, 0>(acc, a_lo, b_lo, 1);
          wgmma_m64n256k16_ss_tb<2, 128>(acc, a_lo, b_lo, 1);
          wgmma_m64n256k16_ss_tb<4, 256>(acc, a_lo, b_lo, 1);
          wgmma_m64n256k16_ss_tb<6, 384>(acc, a_lo, b_lo, 1);
          wgmma_commit();
          if (QP_STAG > 0 && cwg == 0 && j == nkb - 1) named_bar_arrive(7, 256);
          if (j > 0) {
            wgmma_wait<1>();
            if (tid == 0) mbar_arrive(b_empty + 8 * ring_slot(qp_pos(j - 1, ta >> 2)));
          }
        }
        wgmma_wait<0>();
        fence_regs(acc);
        FS(2 * it, 1);
        TL_MARK2(29, threadIdx.x == 256 && it == 0);
        if (tid == 0) mbar_arrive(b_empty + 24);
      }
      float o[64], s[64];
      uint32_t p[32], q[32];
      #pragma unroll
      for (int i = 0; i < 32; i++) q[i] = pack_bf16(acc[2 * i] * AT_C, acc[2 * i + 1] * AT_C);
      zero_regs(s);
      const uint32_t sq = sbase + AT_SQ + cwg * 8192;
      const bool last_wg1 = cwg == 1 && !more;
      float mc0, mc1, al0 = 1.0f, al1 = 1.0f, l0 = 0.f, l1 = 0.f, lp0 = 0.f, lp1 = 0.f;
      bool redo0 = false;
      FS(2 * it, 2);
      mbar_wait(b_full + 8 * ring_slot(ta), ring_par(ta));
      named_bar_sync(1 + cwg, 256);
      FS(2 * it, 3);
      issue_qk(s, q, k_base + ring_slot(ta) * 2048);
      named_bar_arrive(1 + (cwg ^ 1), 256);
      bool ready = mbar_test(b_full + 8 * ring_slot(ta + 1), ring_par(ta + 1)) & mbar_test(b_full + 8 * ring_slot(ta + 2), ring_par(ta + 2));
      stage_q<16>(acc, AT_C, sbase + AT_SQ + frag, lane);
      wgmma_wait<0>();
      fence_regs(s);
      if (tid == 0) mbar_arrive(b_empty + 8 * ring_slot(ta));
      mc0 = 0.f; mc1 = 0.f;
      if (!raw) {
        raw = softmax_mode(s, mc0, mc1);
        if (__builtin_expect(!raw, 0)) softmax_sub(s, mc0, mc1);
      }
      softmax_exp<0, 64>(s);
      #pragma unroll
      for (int J = 0; J < 16; J += 2)
        stmatrix_x4(sbase + AT_SQ + frag + (J >> 3) * 16384 + ((((J & 7) + (lane >> 4)) ^ (lane & 7)) << 4), q[2 * J], q[2 * J + 1], q[2 * J + 2], q[2 * J + 3]);
      pack_p(p, s);
      zero_regs(o);
      FS(2 * it, 4);
      uint32_t ks = ring_slot(ta + 1), vs = ring_slot(ta + 2), kp = ring_par(ta + 1), vp = ring_par(ta + 2);
      auto finish_head = [&]() {
        FS(2 * it, 5);
        redo0 = finish_l(lp0, lp1);
        if (!redo0) stage_o(o, lp0, lp1, sbase + AT_SQ + frag, lane);
        FS(2 * it + 1, 4);
      };
      if (!ready) { mbar_wait(b_full + 8 * ks, kp); mbar_wait(b_full + 8 * vs, vp); }
      #pragma unroll 1
      for (int n = 1; n < 2 * AT_NBLK; n++) {
        named_bar_sync(1 + cwg, 256);
        issue_qk(s, q, k_base + ks * 2048);
        if (n == AT_NBLK + 1) finish_head();
        issue_pv(o, p, v_base + vs * 2048, (n & 15) != 1);
        asm volatile("{\n.reg .pred p;\nsetp.ne.u32 p, %0, 0;\n@p bar.arrive 1, 256;\n@!p bar.arrive 2, 256;\n}\n" :: "r"(cwg) : "memory");
        wgmma_wait<1>();
        fence_regs(s);
        if (tid == 0) mbar_arrive(b_empty + 8 * ks);
        if (__builtin_expect(!raw || (uint32_t)(n - (AT_NBLK - 1)) <= 2u, 0)) {
          if (n == AT_NBLK + 1 && !redo0) {
            fence_proxy_async();
            __syncwarp();
            if (lane == 0) mbar_arrive(b_ordy + 8 * cwg);
          }
          if (n == AT_NBLK - 1) {
            #pragma unroll
            for (int J = 0; J < 16; J += 2)
              ldmatrix_x4(sbase + AT_SQ + 32768 + frag + (J >> 3) * 16384 + ((((J & 7) + (lane >> 4)) ^ (lane & 7)) << 4), q[2 * J], q[2 * J + 1], q[2 * J + 2], q[2 * J + 3]);
          }
          if (!raw) {
            const float m0 = mc0, m1 = mc1;
            const bool ok = softmax_mode(s, mc0, mc1);
            if (n == AT_NBLK) raw = ok;
            else {
              mc0 = mc0 - AT_HEAD > m0 ? mc0 : m0; mc1 = mc1 - AT_HEAD > m1 ? mc1 : m1;
              al0 = ex2_approx(m0 - mc0); al1 = ex2_approx(m1 - mc1);
            }
            if (!raw) softmax_sub(s, mc0, mc1);
          }
        }
        softmax_exp<0, AT_SPLIT>(s);
        add_rowsum(p, l0, l1);
        if (tid == 0) {
          uint32_t dep = zero & __float_as_uint(l0) & __float_as_uint(l1);
          #pragma unroll
          for (int i = AT_SPLIT - AT_PIN - PINB; i < AT_SPLIT - PINB; i += 2) dep &= __float_as_uint(s[i]) & __float_as_uint(s[i + 1]);
          mbar_arrive(b_pin + dep);
        }
        wgmma_wait<0>();
        fence_regs(o);
        if (tid == 0) mbar_arrive(b_empty + 8 * vs);
        ks += 2; if (ks >= 5) { ks -= 5; kp ^= 1; }
        vs += 2; if (vs >= 5) { vs -= 5; vp ^= 1; }
        ready = mbar_test(b_full + 8 * ks, kp) & mbar_test(b_full + 8 * vs, vp);
        softmax_exp<AT_SPLIT, 64>(s);
        pack_p(p, s);
        if (n == AT_NBLK) { lp0 = l0; lp1 = l1; l0 = 0.f; l1 = 0.f; }
        if (__builtin_expect(!raw || !ready, 0)) {
        if (!raw && __any_sync(0xffffffffu, al0 != 1.0f || al1 != 1.0f)) {
          rescale_o(o, al0, al1);
          l0 *= al0; l1 *= al1;
          al0 = 1.0f; al1 = 1.0f;
        }
        if (!ready && n < 2 * AT_NBLK - 1) {
          mbar_wait(b_full + 8 * ks, kp);
          mbar_wait(b_full + 8 * vs, vp);
        }
        }
      }
      FS(2 * it + 1, 5);
      const uint32_t vl = ring_slot(ta + 63);
      vs = ring_slot(ta + 62);
      const uint32_t ob = more ? sbase + vs * 32768 : sbase + AT_SQ + 32768;
      mbar_wait(b_full + 8 * vl, ring_par(ta + 63));
      issue_pv(o, p, v_base + vl * 2048, 1);
      block_end(zero, b_pin);
      add_rowsum(p, l0, l1);
      const bool overflow = finish_l(l0, l1);
      if (!overflow && lane == 0) mbar_arrive(b_q1);
      #pragma unroll
      for (int i = 0; i < 8; i++) asm volatile("mov.b64 {%0, %1}, 0;\nmov.b64 {%2, %3}, 0;" : "=r"(pre[i].x), "=r"(pre[i].y), "=r"(pre[i].z), "=r"(pre[i].w));
      const bool want_pre = !more && blockIdx.x < OG_MOE, got_pre = want_pre && __all_sync(0xffffffffu, mbar_test(bars + 272, 0));
      if (got_pre) load_pre(pre, sbase, AT_SQ, threadIdx.x - 128);
      mbar_wait(b_empty + 8 * vs, ring_par(ta + 62));
      wgmma_wait<0>();
      fence_regs(o);
      if (tid == 0) mbar_arrive(b_empty + 8 * vl);
      FS(2 * it + 1, 6);
      if (overflow) {
        attn_rows_exact(sq + 32768, ob + cwg * 8192, 4 * ta + 1, kc, vc);
        __syncwarp();
        if (lane == 0) mbar_arrive(b_q1);
      } else stage_o(o, l0, l1, ob + frag, lane);
      if (redo0) attn_rows_exact(sq, sq, 4 * ta, kc, vc);
      fence_proxy_async();
      __syncwarp();
      if (lane == 0) {
        if (redo0) mbar_arrive(b_ordy + 8 * cwg);
        mbar_arrive(b_ordy + 16 + 8 * cwg);
      }
      if (want_pre && !got_pre) load_pre(pre, sbase, AT_SQ, threadIdx.x - 128);
      if (redo0 || overflow) raw = false;
      named_bar_sync(3 + cwg, 128);
      FS(2 * it + 1, 7);
    }
    if (ARV_IMM && cwg == 0) named_bar_arrive(1, 256);
    if (__builtin_expect(single, 0)) {
      float acc[128];
      uint32_t j = 0, pk[64];
      #pragma unroll
      for (int i = 0; i < 64; i++) asm volatile("" : "=f"(acc[2 * i]), "=f"(acc[2 * i + 1]), "=r"(pk[i]));
      uint4* dst = g_pre;
      int left = 0;
      auto put = [&](bool last) {
        #pragma unroll
        for (int i = 0; i < PUT_N; i++) dst[i * 256] = make_uint4(pk[4 * i], pk[4 * i + 1], pk[4 * i + 2], pk[4 * i + 3]);
        dst += PUT_N * 256;
        #pragma unroll
        for (int i = 0; i < 64 - 4 * PUT_N; i++) asm volatile("mov.b32 %0, %1;" : "=r"(pk[i]) : "r"(pk[i + 4 * PUT_N]));
        __syncwarp();
        if (last && lane == 0) mbar_arrive(bars + 280);
      };
      #pragma unroll 1
      for (int ji = 0; ji < help_njobs(); ji++) {
        const int nk = ji < OG_JOBS ? OG_PRE : OG_PRE2;
        #pragma unroll 1
        for (int kk = 0; kk < nk; kk++, j++) {
          const uint32_t slot = ring_slot(qp_pos(j, 1));
          mbar_wait(b_full + 8 * slot, ring_par(qp_pos(j, 1)) ^ ((j >> 2) & 1));
          if (H_STAG > 0 && cwg == 1 && kk == nk - H_STAG) named_bar_sync(7, 256);
          const uint32_t a_lo = q_lo + (j & 3) * 1024, b_lo = w_base + slot * 2048;
          wgmma_fence();
          wgmma_m64n256k16_ss_tb<0, 0>(acc, a_lo, b_lo, kk != 0);
          wgmma_m64n256k16_ss_tb<2, 128>(acc, a_lo, b_lo, 1);
          wgmma_m64n256k16_ss_tb<4, 256>(acc, a_lo, b_lo, 1);
          wgmma_m64n256k16_ss_tb<6, 384>(acc, a_lo, b_lo, 1);
          wgmma_commit();
          if (H_STAG > 0 && cwg == 0 && kk == nk - 1) named_bar_arrive(7, 256);
          wgmma_wait<1>();
          if (kk > 0 && tid == 0) mbar_arrive(b_empty + 8 * ring_slot(qp_pos(j - 1, 1)));
          #pragma unroll 1
          for (int i = ji == OG_JOBS ? 0 : 16 / PUT_N - 1; i < 16 / PUT_N && left > 0; i++) put(--left == 0);
        }
        wgmma_wait<0>();
        fence_regs(acc);
        if (tid == 0) mbar_arrive(b_empty + 8 * ring_slot(qp_pos(j - 1, 1)));
        #pragma unroll
        for (int i = 0; i < 64; i++) pk[i] = pack_bf16(acc[2 * i], acc[2 * i + 1]);
        left = 16 / PUT_N;
        if (ji == PRE_X) mbar_wait(bars + 296, 0);
        dst = g_pre + help_job(ji) * 2048 + threadIdx.x - 128;
      }
      #pragma unroll
      for (int i = 0; i < 16; i++) dst[i * 256] = make_uint4(pk[4 * i], pk[4 * i + 1], pk[4 * i + 2], pk[4 * i + 3]);
      __syncwarp();
      if (lane == 0) mbar_arrive(bars + 280);
      named_bar_sync(5, 256);
      if (threadIdx.x == 128) {
        #pragma unroll 1
        for (int i = 0; i < 5; i++) {
          constexpr int n = OG_JOBS * OG_PRE;
          const int used = i == 3 ? 0 : (n + 3 - (i == 4 ? 3 : i)) / 4;
          if ((used ^ (i < 4)) & 1) {
            mbar_arrive(b_full + 8 * ring_slot(4 + i));
            mbar_arrive(b_empty + 8 * ring_slot(4 + i)); mbar_arrive(b_empty + 8 * ring_slot(4 + i));
          }
        }
        mbar_arrive(b_x);
      }
      named_bar_sync(5, 256);
      #pragma unroll
      for (int i = 0; i < 8; i++) pre[i] = make_uint4(0u, 0u, 0u, 0u);
    }
    TL_CLK(3, 1, threadIdx.x == 128);
    TL_CTA(1, threadIdx.x == 256);
    TL_END(3, tid == 0);
    TL_MARK2(19, tid == 0 && !single);
    if (blockIdx.x < 128) {
      tail_consumer(sbase, &tmOut, pre, cwg, w_gate, w_up);
    }
  }
}

typedef CUresult (*PFN_encodeTiled)(CUtensorMap*, CUtensorMapDataType, cuuint32_t, void*, const cuuint64_t*, const cuuint64_t*,
                                    const cuuint32_t*, const cuuint32_t*, CUtensorMapInterleave, CUtensorMapSwizzle,
                                    CUtensorMapL2promotion, CUtensorMapFloatOOBfill);

CUtensorMap make_map_2d(PFN_encodeTiled enc, const void* ptr, uint64_t inner, uint64_t outer, uint64_t stride_bytes, uint32_t box_inner, uint32_t box_outer) {
  CUtensorMap m;
  cuuint64_t gd[2] = {inner, outer}; cuuint64_t gs[1] = {stride_bytes};
  cuuint32_t bx[2] = {box_inner, box_outer}; cuuint32_t es[2] = {1, 1};
  enc(&m, CU_TENSOR_MAP_DATA_TYPE_BFLOAT16, 2, const_cast<void*>(ptr), gd, gs, bx, es, CU_TENSOR_MAP_INTERLEAVE_NONE,
      CU_TENSOR_MAP_SWIZZLE_128B, CU_TENSOR_MAP_L2_PROMOTION_L2_128B, CU_TENSOR_MAP_FLOAT_OOB_FILL_NONE);
  return m;
}

CUtensorMap make_map_3d(PFN_encodeTiled enc, const void* ptr, uint64_t cols, uint64_t rows, uint32_t box_rows, uint32_t chunks) {
  CUtensorMap m;
  cuuint64_t gd[3] = {64, rows, cols / 64}; cuuint64_t gs[2] = {cols * 2, 128};
  cuuint32_t bx[3] = {64, box_rows, chunks}; cuuint32_t es[3] = {1, 1, 1};
  enc(&m, CU_TENSOR_MAP_DATA_TYPE_BFLOAT16, 3, const_cast<void*>(ptr), gd, gs, bx, es, CU_TENSOR_MAP_INTERLEAVE_NONE,
      CU_TENSOR_MAP_SWIZZLE_128B, CU_TENSOR_MAP_L2_PROMOTION_L2_128B, CU_TENSOR_MAP_FLOAT_OOB_FILL_NONE);
  return m;
}

}

extern "C" void kernel_launch(void* const* d_in, const int* in_sizes, int n_in, void* d_out, int out_size) {
  const bf16* x      = (const bf16*)d_in[0];
  const bf16* kc     = (const bf16*)d_in[1];
  const bf16* vc     = (const bf16*)d_in[2];
  const bf16* wq     = (const bf16*)d_in[3];
  const bf16* wo     = (const bf16*)d_in[4];
  const bf16* w_r    = (const bf16*)d_in[6];
  const bf16* w_gate = (const bf16*)d_in[7];
  const bf16* w_up   = (const bf16*)d_in[8];
  const bf16* w_down = (const bf16*)d_in[9];
  const bf16* cvec   = (const bf16*)d_in[10];
  const bf16* w_mod  = (const bf16*)d_in[11];
  bf16* out = (bf16*)d_out;

  static PFN_encodeTiled enc = nullptr;
  static void *p_h = nullptr, *p_o = nullptr;
  if (!enc) {
    void* fn = nullptr; cudaDriverEntryPointQueryResult qres;
    cudaGetDriverEntryPoint("cuTensorMapEncodeTiled", &fn, cudaEnableDefault, &qres);
    enc = (PFN_encodeTiled)fn;
    cudaGetSymbolAddress(&p_h, g_pre);
    p_h = (uint4*)p_h + 16 * PRE_X * 2048;
    cudaGetSymbolAddress(&p_o, g_o);
    cudaFuncSetAttribute(fused_kernel, cudaFuncAttributeMaxDynamicSharedMemorySize, (int)AT_SMEM);
  }
  const CUtensorMap tm_h   = make_map_2d(enc, p_h, T_D, T_SEQ, T_D * 2, 64, 128);
  const CUtensorMap tm_wq  = W3D ? make_map_3d(enc, wq, T_DQKV, T_D, 64, 4) : make_map_2d(enc, wq, T_DQKV, T_D, T_DQKV * 2, 64, 64);
  const CUtensorMap tm_k   = KV3D ? make_map_3d(enc, kc, T_DH, (uint64_t)T_NH * T_SEQ, 128, 2) : make_map_2d(enc, kc, T_DH, (uint64_t)T_NH * T_SEQ, T_DH * 2, 64, 128);
  const CUtensorMap tm_v   = KV3D ? make_map_3d(enc, vc, T_DH, (uint64_t)T_NH * T_SEQ, 128, 2) : make_map_2d(enc, vc, T_DH, (uint64_t)T_NH * T_SEQ, T_DH * 2, 64, 128);
  const CUtensorMap tm_ost = make_map_2d(enc, p_o, T_DQKV, T_SEQ, T_DQKV * 2, 64, 64);
  const CUtensorMap tm_old = make_map_2d(enc, p_o, T_DQKV, T_SEQ, T_DQKV * 2, 64, 128);
  const CUtensorMap tm_wo  = make_map_3d(enc, wo, T_D, T_DQKV, 64, 2);
  const CUtensorMap tm_x   = make_map_3d(enc, w_down, T_D, T_F, 32, 8);

  const CUtensorMap tm_m   = make_map_2d(enc, w_mod, 6 * T_D, T_D, 6 * T_D * 2, 64, 256);
  const CUtensorMap tm_out = make_map_2d(enc, out, T_D, T_SEQ, T_D * 2, 64, 16);

  fused_kernel<<<132, 384, AT_SMEM, cudaStreamPerThread>>>(tm_h, tm_wq, tm_k, tm_v, tm_ost, tm_old, tm_wo, tm_x, tm_out, tm_m, 0u, (const uint8_t*)wo, kc, vc, x, cvec, w_mod,
             w_r, w_gate, w_up, w_down, out);
}
```

```cpp
#include <cuda_runtime.h>
#include <cuda_bf16.h>
#include <cuda.h>
#include <stdint.h>

namespace {

typedef __nv_bfloat16 bf16;

constexpr int T_SEQ = 2048, T_D = 1024, T_NH = 32, T_DH = 128, T_DQKV = 4096, T_F = 3584;

#define PRE_X 2
__device__ __align__(1024) uint4 g_pre[(16 * PRE_X + 128) * 2048];
#define g_h (reinterpret_cast<bf16*>(g_pre + 16 * PRE_X * 2048))
__device__ __align__(1024) bf16 g_o[T_SEQ * T_DQKV];
__device__ __align__(16) uint8_t g_col[8 * 1536];
__device__ __align__(16) float g_scal[64];
__device__ __align__(16) unsigned int g_hcnt[17 * 32];
__device__ unsigned int g_smid[168], g_tmax[128];
__device__ __align__(128) float g_modpart[4 * 2 * T_D];
struct __align__(2048) TailMail {
  float4 part1[T_SEQ * 8];
  uint32_t key[256];
  uint4 cand[16 * 2 * 2 * 128];
  uint32_t cnt[32];
  float ypart[(T_F / 32) * 2 * T_D];
};
__device__ TailMail g_mail;
#define g_part1 g_mail.part1
#define g_key g_mail.key
#define g_cand g_mail.cand
#define CNT_Y (g_mail.cnt)
#define g_ypart g_mail.ypart

__device__ __forceinline__ uint32_t smem_u32(const void* p) { return (uint32_t)__cvta_generic_to_shared(p); }
__device__ __forceinline__ void mbar_init(uint32_t bar, uint32_t cnt) { asm volatile("mbarrier.init.shared::cta.b64 [%0], %1;" :: "r"(bar), "r"(cnt)); }
__device__ __forceinline__ void mbar_expect_tx(uint32_t bar, uint32_t bytes) { asm volatile("mbarrier.arrive.expect_tx.shared::cta.b64 _, [%0], %1;" :: "r"(bar), "r"(bytes) : "memory"); }
__device__ __forceinline__ void mbar_arrive(uint32_t bar) { asm volatile("mbarrier.arrive.shared::cta.b64 _, [%0];" :: "r"(bar) : "memory"); }
__device__ __forceinline__ void mbar_wait(uint32_t bar, uint32_t parity) {
  asm volatile("{\n.reg .pred p;\nLAB_WAIT:\nmbarrier.try_wait.parity.shared::cta.b64 p, [%0], %1;\n@!p bra LAB_WAIT;\n}\n" :: "r"(bar), "r"(parity) : "memory");
}
__device__ __forceinline__ bool mbar_test(uint32_t bar, uint32_t parity) {
  uint32_t r; asm volatile("{\n.reg .pred p;\nmbarrier.test_wait.parity.shared::cta.b64 p, [%1], %2;\nselp.u32 %0, 1, 0, p;\n}\n" : "=r"(r) : "r"(bar), "r"(parity) : "memory");
  return r != 0;
}
__device__ __forceinline__ uint32_t clock_lo() { uint32_t c; asm volatile("mov.u32 %0, %%clock;" : "=r"(c)); return c; }
__device__ __forceinline__ void fence_mbar_init() { asm volatile("fence.mbarrier_init.release.cluster;" ::: "memory"); }
__device__ __forceinline__ void tma_load_2d(uint32_t dst, const CUtensorMap* map, int c0, int c1, uint32_t bar) {
  asm volatile("cp.async.bulk.tensor.2d.shared::cluster.global.mbarrier::complete_tx::bytes [%0], [%1, {%3, %4}], [%2];"
    :: "r"(dst), "l"(map), "r"(bar), "r"(c0), "r"(c1) : "memory");
}
__device__ __forceinline__ uint64_t policy_evict_first() {
  uint64_t p; asm volatile("createpolicy.fractional.L2::evict_first.b64 %0, 1.0;" : "=l"(p)); return p;
}
__device__ __forceinline__ void tma_load_2d_hint(uint32_t dst, const CUtensorMap* map, int c0, int c1, uint32_t bar, uint64_t pol) {
  asm volatile("cp.async.bulk.tensor.2d.shared::cluster.global.mbarrier::complete_tx::bytes.L2::cache_hint [%0], [%1, {%3, %4}], [%2], %5;"
    :: "r"(dst), "l"(map), "r"(bar), "r"(c0), "r"(c1), "l"(pol) : "memory");
}
__device__ __forceinline__ void tma_load_3d_hint(uint32_t dst, const CUtensorMap* map, int c1, int c2, uint32_t bar, uint64_t pol) {
  asm volatile("cp.async.bulk.tensor.3d.shared::cluster.global.mbarrier::complete_tx::bytes.L2::cache_hint [%0], [%1, {%3, %4, %5}], [%2], %6;"
    :: "r"(dst), "l"(map), "r"(bar), "n"(0), "r"(c1), "r"(c2), "l"(pol) : "memory");
}
__device__ __forceinline__ void tma_store_2d(const CUtensorMap* map, uint32_t src, int c0, int c1) {
  asm volatile("cp.async.bulk.tensor.2d.global.shared::cta.bulk_group [%0, {%2, %3}], [%1];" :: "l"(map), "r"(src), "r"(c0), "r"(c1) : "memory");
}
__device__ __forceinline__ void prefetch_tmap(const CUtensorMap* map) { asm volatile("prefetch.tensormap [%0];" :: "l"(map) : "memory"); }
__device__ __forceinline__ void l2_prefetch_bulk(const void* p, uint32_t bytes) {
  asm volatile("cp.async.bulk.prefetch.L2.global [%0], %1;" :: "l"(p), "r"(bytes) : "memory");
}
__device__ __forceinline__ void bulk_commit() { asm volatile("cp.async.bulk.commit_group;" ::: "memory"); }
template<int N> __device__ __forceinline__ void bulk_wait_read() { asm volatile("cp.async.bulk.wait_group.read %0;" :: "n"(N) : "memory"); }
template<int N> __device__ __forceinline__ void bulk_wait() { asm volatile("cp.async.bulk.wait_group %0;" :: "n"(N) : "memory"); }
__device__ __forceinline__ void named_bar_sync(int id, int nthreads) { asm volatile("bar.sync %0, %1;" :: "r"(id), "r"(nthreads) : "memory"); }
__device__ __forceinline__ void named_bar_arrive(int id, int nthreads) { asm volatile("bar.arrive %0, %1;" :: "r"(id), "r"(nthreads) : "memory"); }
__device__ __forceinline__ void wgmma_fence() { asm volatile("wgmma.fence.sync.aligned;" ::: "memory"); }
__device__ __forceinline__ void wgmma_commit() { asm volatile("wgmma.commit_group.sync.aligned;" ::: "memory"); }
template<int N> __device__ __forceinline__ void wgmma_wait() { asm volatile("wgmma.wait_group.sync.aligned %0;" :: "n"(N) : "memory"); }
template<int R> __device__ __forceinline__ void reg_alloc() { asm volatile("setmaxnreg.inc.sync.aligned.u32 %0;" :: "n"(R)); }
template<int R> __device__ __forceinline__ void reg_dealloc() { asm volatile("setmaxnreg.dec.sync.aligned.u32 %0;" :: "n"(R)); }
__device__ __forceinline__ bool elect_one() {
  uint32_t pred; asm volatile("{\n.reg .pred p;\nelect.sync _|p, 0xffffffff;\nselp.u32 %0, 1, 0, p;\n}\n" : "=r"(pred)); return pred != 0;
}
__device__ __forceinline__ uint32_t pack_bf16(float lo, float hi) {
  uint32_t r; asm("cvt.rn.bf16x2.f32 %0, %1, %2;" : "=r"(r) : "f"(hi), "f"(lo)); return r;
}
__device__ __forceinline__ void stmatrix_x4(uint32_t addr, uint32_t r0, uint32_t r1, uint32_t r2, uint32_t r3) {
  asm volatile("stmatrix.sync.aligned.m8n8.x4.shared.b16 [%0], {%1, %2, %3, %4};" :: "r"(addr), "r"(r0), "r"(r1), "r"(r2), "r"(r3) : "memory");
}
__device__ __forceinline__ void fence_proxy_async() { asm volatile("fence.proxy.async.shared::cta;" ::: "memory"); }
__device__ __forceinline__ float ex2_approx(float x) { float y; asm("ex2.approx.ftz.f32 %0, %1;" : "=f"(y) : "f"(x)); return y; }
template<int N> __device__ __forceinline__ void fence_regs(float (&r)[N]) {
  #pragma unroll
  for (int i = 0; i < N; i++) asm volatile("" : "+f"(r[i]) :: "memory");
}
template<int N> __device__ __forceinline__ void zero_regs(float (&r)[N]) {
  #pragma unroll
  for (int i = 0; i < N; i += 2) asm volatile("mov.b64 {%0, %1}, 0;" : "=f"(r[i]), "=f"(r[i + 1]));
}
__device__ __forceinline__ float rbf(float x) { return __uint_as_float(pack_bf16(0.f, x)); }
__device__ __forceinline__ float bflo(uint32_t v) { return __uint_as_float(v << 16); }
__device__ __forceinline__ float bfhi(uint32_t v) { return __uint_as_float(v & 0xffff0000u); }

#define XT(i) do {} while (0)
#define TL_START(k) do {} while (0)
#define TL_END(k, cond) do {} while (0)
#define TL_CTA(i, cond) do {} while (0)
#define FS(slot, k) do {} while (0)
#define TL_MARK2(k, cond) do {} while (0)
#define TL_CLK(k, i, cond) do {} while (0)

template <int OFFA, int OFFB>
__device__ __forceinline__ void wgmma_m64n256k16_ss_tb(float (&d)[128], uint32_t a_lo, uint32_t b_lo, int scaleD) {
  asm volatile("{\n.reg .pred p;\n.reg .b32 ta, tb;\n.reg .b64 da, db;\nsetp.ne.b32 p, %130, 0;\n"
    "add.u32 ta, %128, %131;\nadd.u32 tb, %129, %132;\n"
    "mov.b64 da, {ta, 0x40000040};\nmov.b64 db, {tb, 0x40000040};\n"
    "wgmma.mma_async.sync.aligned.m64n256k16.f32.bf16.bf16 "
    "{%0, %1, %2, %3, %4, %5, %6, %7, %8, %9, %10, %11, %12, %13, %14, %15, %16, %17, %18, %19, %20, %21, %22, %23, %24, %25, %26, %27, %28, %29, %30, %31, %32, %33, %34, %35, %36, %37, %38, %39, %40, %41, %42, %43, %44, %45, %46, %47, %48, %49, %50, %51, %52, %53, %54, %55, %56, %57, %58, %59, %60, %61, %62, %63, %64, %65, %66, %67, %68, %69, %70, %71, %72, %73, %74, %75, %76, %77, %78, %79, %80, %81, %82, %83, %84, %85, %86, %87, %88, %89, %90, %91, %92, %93, %94, %95, %96, %97, %98, %99, %100, %101, %102, %103, %104, %105, %106, %107, %108, %109, %110, %111, %112, %113, %114, %115, %116, %117, %118, %119, %120, %121, %122, %123, %124, %125, %126, %127}, "
    "da, db, p, 1, 1, 0, 1;\n}\n"
    : "+f"(d[0]), "+f"(d[1]), "+f"(d[2]), "+f"(d[3]), "+f"(d[4]), "+f"(d[5]), "+f"(d[6]), "+f"(d[7]), "+f"(d[8]), "+f"(d[9]), "+f"(d[10]), "+f"(d[11]), "+f"(d[12]), "+f"(d[13]), "+f"(d[14]), "+f"(d[15]), "+f"(d[16]), "+f"(d[17]), "+f"(d[18]), "+f"(d[19]), "+f"(d[20]), "+f"(d[21]), "+f"(d[22]), "+f"(d[23]), "+f"(d[24]), "+f"(d[25]), "+f"(d[26]), "+f"(d[27]), "+f"(d[28]), "+f"(d[29]), "+f"(d[30]), "+f"(d[31]), "+f"(d[32]), "+f"(d[33]), "+f"(d[34]), "+f"(d[35]), "+f"(d[36]), "+f"(d[37]), "+f"(d[38]), "+f"(d[39]), "+f"(d[40]), "+f"(d[41]), "+f"(d[42]), "+f"(d[43]), "+f"(d[44]), "+f"(d[45]), "+f"(d[46]), "+f"(d[47]), "+f"(d[48]), "+f"(d[49]), "+f"(d[50]), "+f"(d[51]), "+f"(d[52]), "+f"(d[53]), "+f"(d[54]), "+f"(d[55]), "+f"(d[56]), "+f"(d[57]), "+f"(d[58]), "+f"(d[59]), "+f"(d[60]), "+f"(d[61]), "+f"(d[62]), "+f"(d[63]), "+f"(d[64]), "+f"(d[65]), "+f"(d[66]), "+f"(d[67]), "+f"(d[68]), "+f"(d[69]), "+f"(d[70]), "+f"(d[71]), "+f"(d[72]), "+f"(d[73]), "+f"(d[74]), "+f"(d[75]), "+f"(d[76]), "+f"(d[77]), "+f"(d[78]), "+f"(d[79]), "+f"(d[80]), "+f"(d[81]), "+f"(d[82]), "+f"(d[83]), "+f"(d[84]), "+f"(d[85]), "+f"(d[86]), "+f"(d[87]), "+f"(d[88]), "+f"(d[89]), "+f"(d[90]), "+f"(d[91]), "+f"(d[92]), "+f"(d[93]), "+f"(d[94]), "+f"(d[95]), "+f"(d[96]), "+f"(d[97]), "+f"(d[98]), "+f"(d[99]), "+f"(d[100]), "+f"(d[101]), "+f"(d[102]), "+f"(d[103]), "+f"(d[104]), "+f"(d[105]), "+f"(d[106]), "+f"(d[107]), "+f"(d[108]), "+f"(d[109]), "+f"(d[110]), "+f"(d[111]), "+f"(d[112]), "+f"(d[113]), "+f"(d[114]), "+f"(d[115]), "+f"(d[116]), "+f"(d[117]), "+f"(d[118]), "+f"(d[119]), "+f"(d[120]), "+f"(d[121]), "+f"(d[122]), "+f"(d[123]), "+f"(d[124]), "+f"(d[125]), "+f"(d[126]), "+f"(d[127])
    : "r"(a_lo), "r"(b_lo), "r"(scaleD), "n"(OFFA), "n"(OFFB));
}

template <int OFFA, int OFFB>
__device__ __forceinline__ void wgmma_m64n128k16_ss_tb(float (&d)[64], uint32_t a_lo, uint32_t b_lo, int scaleD) {
  asm volatile("{\n.reg .pred p;\n.reg .b32 ta, tb;\n.reg .b64 da, db;\nsetp.ne.b32 p, %66, 0;\n"
    "add.u32 ta, %64, %67;\nadd.u32 tb, %65, %68;\n"
    "mov.b64 da, {ta, 0x40000040};\nmov.b64 db, {tb, 0x40000040};\n"
    "wgmma.mma_async.sync.aligned.m64n128k16.f32.bf16.bf16 "
    "{%0, %1, %2, %3, %4, %5, %6, %7, %8, %9, %10, %11, %12, %13, %14, %15, %16, %17, %18, %19, %20, %21, %22, %23, %24, %25, %26, %27, %28, %29, %30, %31, %32, %33, %34, %35, %36, %37, %38, %39, %40, %41, %42, %43, %44, %45, %46, %47, %48, %49, %50, %51, %52, %53, %54, %55, %56, %57, %58, %59, %60, %61, %62, %63}, "
    "da, db, p, 1, 1, 0, 1;\n}\n"
    : "+f"(d[0]), "+f"(d[1]), "+f"(d[2]), "+f"(d[3]), "+f"(d[4]), "+f"(d[5]), "+f"(d[6]), "+f"(d[7]), "+f"(d[8]), "+f"(d[9]), "+f"(d[10]), "+f"(d[11]), "+f"(d[12]), "+f"(d[13]), "+f"(d[14]), "+f"(d[15]), "+f"(d[16]), "+f"(d[17]), "+f"(d[18]), "+f"(d[19]), "+f"(d[20]), "+f"(d[21]), "+f"(d[22]), "+f"(d[23]), "+f"(d[24]), "+f"(d[25]), "+f"(d[26]), "+f"(d[27]), "+f"(d[28]), "+f"(d[29]), "+f"(d[30]), "+f"(d[31]), "+f"(d[32]), "+f"(d[33]), "+f"(d[34]), "+f"(d[35]), "+f"(d[36]), "+f"(d[37]), "+f"(d[38]), "+f"(d[39]), "+f"(d[40]), "+f"(d[41]), "+f"(d[42]), "+f"(d[43]), "+f"(d[44]), "+f"(d[45]), "+f"(d[46]), "+f"(d[47]), "+f"(d[48]), "+f"(d[49]), "+f"(d[50]), "+f"(d[51]), "+f"(d[52]), "+f"(d[53]), "+f"(d[54]), "+f"(d[55]), "+f"(d[56]), "+f"(d[57]), "+f"(d[58]), "+f"(d[59]), "+f"(d[60]), "+f"(d[61]), "+f"(d[62]), "+f"(d[63])
    : "r"(a_lo), "r"(b_lo), "r"(scaleD), "n"(OFFA), "n"(OFFB));
}

template <int OFFB>
__device__ __forceinline__ void wgmma_m64n128k16_rs_tb(float (&d)[64], uint32_t a0, uint32_t a1, uint32_t a2, uint32_t a3, uint32_t b_lo, int scaleD) {
  asm volatile("{\n.reg .pred p;\n.reg .b32 tb;\n.reg .b64 db;\nsetp.ne.b32 p, %69, 0;\n"
    "add.u32 tb, %68, %70;\n"
    "mov.b64 db, {tb, 0x40000040};\n"
    "wgmma.mma_async.sync.aligned.m64n128k16.f32.bf16.bf16 "
    "{%0, %1, %2, %3, %4, %5, %6, %7, %8, %9, %10, %11, %12, %13, %14, %15, %16, %17, %18, %19, %20, %21, %22, %23, %24, %25, %26, %27, %28, %29, %30, %31, %32, %33, %34, %35, %36, %37, %38, %39, %40, %41, %42, %43, %44, %45, %46, %47, %48, %49, %50, %51, %52, %53, %54, %55, %56, %57, %58, %59, %60, %61, %62, %63}, "
    "{%64, %65, %66, %67}, db, p, 1, 1, 1;\n}\n"
    : "+f"(d[0]), "+f"(d[1]), "+f"(d[2]), "+f"(d[3]), "+f"(d[4]), "+f"(d[5]), "+f"(d[6]), "+f"(d[7]), "+f"(d[8]), "+f"(d[9]), "+f"(d[10]), "+f"(d[11]), "+f"(d[12]), "+f"(d[13]), "+f"(d[14]), "+f"(d[15]), "+f"(d[16]), "+f"(d[17]), "+f"(d[18]), "+f"(d[19]), "+f"(d[20]), "+f"(d[21]), "+f"(d[22]), "+f"(d[23]), "+f"(d[24]), "+f"(d[25]), "+f"(d[26]), "+f"(d[27]), "+f"(d[28]), "+f"(d[29]), "+f"(d[30]), "+f"(d[31]), "+f"(d[32]), "+f"(d[33]), "+f"(d[34]), "+f"(d[35]), "+f"(d[36]), "+f"(d[37]), "+f"(d[38]), "+f"(d[39]), "+f"(d[40]), "+f"(d[41]), "+f"(d[42]), "+f"(d[43]), "+f"(d[44]), "+f"(d[45]), "+f"(d[46]), "+f"(d[47]), "+f"(d[48]), "+f"(d[49]), "+f"(d[50]), "+f"(d[51]), "+f"(d[52]), "+f"(d[53]), "+f"(d[54]), "+f"(d[55]), "+f"(d[56]), "+f"(d[57]), "+f"(d[58]), "+f"(d[59]), "+f"(d[60]), "+f"(d[61]), "+f"(d[62]), "+f"(d[63])
    : "r"(a0), "r"(a1), "r"(a2), "r"(a3), "r"(b_lo), "r"(scaleD), "n"(OFFB));
}

template <int OFFB>
__device__ __forceinline__ void wgmma_m64n128k16_rs(float (&d)[64], uint32_t a0, uint32_t a1, uint32_t a2, uint32_t a3, uint32_t b_lo, int scaleD) {
  asm volatile("{\n.reg .pred p;\n.reg .b32 tb;\n.reg .b64 db;\nsetp.ne.b32 p, %69, 0;\n"
    "add.u32 tb, %68, %70;\n"
    "mov.b64 db, {tb, 0x40000040};\n"
    "wgmma.mma_async.sync.aligned.m64n128k16.f32.bf16.bf16 "
    "{%0, %1, %2, %3, %4, %5, %6, %7, %8, %9, %10, %11, %12, %13, %14, %15, %16, %17, %18, %19, %20, %21, %22, %23, %24, %25, %26, %27, %28, %29, %30, %31, %32, %33, %34, %35, %36, %37, %38, %39, %40, %41, %42, %43, %44, %45, %46, %47, %48, %49, %50, %51, %52, %53, %54, %55, %56, %57, %58, %59, %60, %61, %62, %63}, "
    "{%64, %65, %66, %67}, db, p, 1, 1, 0;\n}\n"
    : "+f"(d[0]), "+f"(d[1]), "+f"(d[2]), "+f"(d[3]), "+f"(d[4]), "+f"(d[5]), "+f"(d[6]), "+f"(d[7]), "+f"(d[8]), "+f"(d[9]), "+f"(d[10]), "+f"(d[11]), "+f"(d[12]), "+f"(d[13]), "+f"(d[14]), "+f"(d[15]), "+f"(d[16]), "+f"(d[17]), "+f"(d[18]), "+f"(d[19]), "+f"(d[20]), "+f"(d[21]), "+f"(d[22]), "+f"(d[23]), "+f"(d[24]), "+f"(d[25]), "+f"(d[26]), "+f"(d[27]), "+f"(d[28]), "+f"(d[29]), "+f"(d[30]), "+f"(d[31]), "+f"(d[32]), "+f"(d[33]), "+f"(d[34]), "+f"(d[35]), "+f"(d[36]), "+f"(d[37]), "+f"(d[38]), "+f"(d[39]), "+f"(d[40]), "+f"(d[41]), "+f"(d[42]), "+f"(d[43]), "+f"(d[44]), "+f"(d[45]), "+f"(d[46]), "+f"(d[47]), "+f"(d[48]), "+f"(d[49]), "+f"(d[50]), "+f"(d[51]), "+f"(d[52]), "+f"(d[53]), "+f"(d[54]), "+f"(d[55]), "+f"(d[56]), "+f"(d[57]), "+f"(d[58]), "+f"(d[59]), "+f"(d[60]), "+f"(d[61]), "+f"(d[62]), "+f"(d[63])
    : "r"(a0), "r"(a1), "r"(a2), "r"(a3), "r"(b_lo), "r"(scaleD), "n"(OFFB));
}

__device__ __forceinline__ uint4 ldg_nc_v4(const void* p) {
  uint4 v;
    asm volatile("{\n.reg .b64 pol;\ncreatepolicy.fractional.L2::evict_first.b64 pol, 1.0;\n"
                 "ld.global.nc.L1::no_allocate.L2::cache_hint.v4.u32 {%0, %1, %2, %3}, [%4], pol;\n}\n" : "=r"(v.x), "=r"(v.y), "=r"(v.z), "=r"(v.w) : "l"(p));
  return v;
}
__device__ __forceinline__ uint64_t pol_normal() {
  uint64_t p; asm volatile("createpolicy.fractional.L2::evict_normal.b64 %0, 1.0;" : "=l"(p)); return p;
}
__device__ __forceinline__ void unpack8(const uint4& u, float (&v)[8]) {
  v[0] = bflo(u.x); v[1] = bfhi(u.x); v[2] = bflo(u.y); v[3] = bfhi(u.y);
  v[4] = bflo(u.z); v[5] = bfhi(u.z); v[6] = bflo(u.w); v[7] = bfhi(u.w);
}
__device__ __forceinline__ void fma8(float (&acc)[8], float s, const uint4& w) {
  acc[0] = fmaf(s, bflo(w.x), acc[0]); acc[1] = fmaf(s, bfhi(w.x), acc[1]); acc[2] = fmaf(s, bflo(w.y), acc[2]); acc[3] = fmaf(s, bfhi(w.y), acc[3]);
  acc[4] = fmaf(s, bflo(w.z), acc[4]); acc[5] = fmaf(s, bfhi(w.z), acc[5]); acc[6] = fmaf(s, bflo(w.w), acc[6]); acc[7] = fmaf(s, bfhi(w.w), acc[7]);
}
__device__ __forceinline__ float rcp_approx(float x) { float y; asm("rcp.approx.ftz.f32 %0, %1;" : "=f"(y) : "f"(x)); return y; }
__device__ __forceinline__ float sigmoid_f(float v) { return rcp_approx(1.0f + ex2_approx(v * -1.4426950408889634f)); }
__device__ __forceinline__ float silu_bf(float v) { return rbf(v * sigmoid_f(v)); }
__device__ __forceinline__ uint32_t rank_key(float r, int idx) {
  const uint32_t b = __float_as_uint(r) >> 16;
  const uint32_t u = (r != r) ? 0u : ((b & 0x8000u) ? (~b & 0xffffu) : (b | 0x8000u));
  return (u << 16) | (0xffffu - (uint32_t)idx);
}
__device__ __forceinline__ void warp_top2(uint32_t& k1, uint32_t& k2) {
  const uint32_t m1 = __reduce_max_sync(0xffffffffu, k1);
  k2 = __reduce_max_sync(0xffffffffu, k1 == m1 ? k2 : k1);
  k1 = m1;
}
__device__ __forceinline__ uint32_t bmul2(uint32_t a, uint32_t b) { uint32_t r; asm("mul.rn.bf16x2 %0, %1, %2;" : "=r"(r) : "r"(a), "r"(b)); return r; }
__device__ __forceinline__ uint32_t badd2(uint32_t a, uint32_t b) { uint32_t r; asm("add.rn.bf16x2 %0, %1, %2;" : "=r"(r) : "r"(a), "r"(b)); return r; }
__device__ __forceinline__ uint32_t bsub2(uint32_t a, uint32_t b) { uint32_t r; asm("sub.rn.bf16x2 %0, %1, %2;" : "=r"(r) : "r"(a), "r"(b)); return r; }
__device__ __forceinline__ float sqrt_approx(float x) { float y; asm("sqrt.approx.f32 %0, %1;" : "=f"(y) : "f"(x)); return y; }
__device__ __forceinline__ uint32_t ln_norm2(uint32_t x1, uint32_t mb2, float inv) {
  const uint32_t d = bsub2(x1, mb2);
  return pack_bf16(bflo(d) * inv, bfhi(d) * inv);
}
__device__ __forceinline__ uint32_t bfma2(uint32_t a, uint32_t b, uint32_t c) { uint32_t r; asm("fma.rn.bf16x2 %0, %1, %2, %3;" : "=r"(r) : "r"(a), "r"(b), "r"(c)); return r; }
__device__ __forceinline__ uint32_t ln_norm2b(uint32_t x1, uint32_t mb2, uint32_t ih, uint32_t il) {
  const uint32_t d = bsub2(x1, mb2);
  return bfma2(d, ih, bmul2(d, il));
}
__device__ __forceinline__ uint32_t ln_mod2(uint32_t x1, uint32_t mb2, float inv, uint32_t c1, uint32_t sb) { return badd2(bmul2(ln_norm2(x1, mb2, inv), c1), sb); }
__device__ __forceinline__ void ldmatrix_x4(uint32_t addr, uint32_t& r0, uint32_t& r1, uint32_t& r2, uint32_t& r3) {
  asm volatile("ldmatrix.sync.aligned.m8n8.x4.shared.b16 {%0, %1, %2, %3}, [%4];" : "=r"(r0), "=r"(r1), "=r"(r2), "=r"(r3) : "r"(addr) : "memory");
}
__device__ __forceinline__ uint4 ldg_stream_v4(const void* p, uint64_t pol) {
  uint4 v; asm volatile("ld.global.nc.L1::no_allocate.L2::cache_hint.L2::128B.v4.u32 {%0, %1, %2, %3}, [%4], %5;" : "=r"(v.x), "=r"(v.y), "=r"(v.z), "=r"(v.w) : "l"(p), "l"(pol)); return v;
}
__device__ __forceinline__ void bulk_load_hint(uint32_t dst, const void* src, uint32_t bytes, uint32_t bar, uint64_t pol) {
  asm volatile("cp.async.bulk.shared::cluster.global.mbarrier::complete_tx::bytes.L2::cache_hint [%0], [%1], %2, [%3], %4;"
    :: "r"(dst), "l"(src), "r"(bytes), "r"(bar), "l"(pol) : "memory");
}
__device__ __forceinline__ void red_release_add(unsigned int* p, unsigned int v) { asm volatile("red.release.gpu.global.add.u32 [%0], %1;" :: "l"(p), "r"(v) : "memory"); }
__device__ __forceinline__ unsigned int ld_acquire(const unsigned int* p) { unsigned int v; asm volatile("ld.acquire.gpu.global.u32 %0, [%1];" : "=r"(v) : "l"(p) : "memory"); return v; }
__device__ __forceinline__ void spin_until(const unsigned int* p, unsigned int target) {
  #pragma unroll 1
  for (unsigned int i = 0; i < (1u << 22); i++) { if (ld_acquire(p) >= target) return; }
}
__device__ __forceinline__ float lds_f32(uint32_t a) { float v; asm volatile("ld.shared.f32 %0, [%1];" : "=f"(v) : "r"(a) : "memory"); return v; }
__device__ __forceinline__ float2 lds_f32x2(uint32_t a) { float2 v; asm volatile("ld.shared.v2.f32 {%0, %1}, [%2];" : "=f"(v.x), "=f"(v.y) : "r"(a) : "memory"); return v; }
__device__ __forceinline__ uint2 lds_u32x2(uint32_t a) { uint2 v; asm volatile("ld.shared.v2.u32 {%0, %1}, [%2];" : "=r"(v.x), "=r"(v.y) : "r"(a) : "memory"); return v; }
__device__ __forceinline__ uint32_t lds_u32(uint32_t a) { uint32_t v; asm volatile("ld.shared.u32 %0, [%1];" : "=r"(v) : "r"(a) : "memory"); return v; }
__device__ __forceinline__ void sts_u32(uint32_t a, uint32_t v) { asm volatile("st.shared.u32 [%0], %1;" :: "r"(a), "r"(v) : "memory"); }
__device__ __forceinline__ void sts_u32x2(uint32_t a, uint32_t x, uint32_t y) { asm volatile("st.shared.v2.u32 [%0], {%1, %2};" :: "r"(a), "r"(x), "r"(y) : "memory"); }
__device__ __forceinline__ void sts_f32(uint32_t a, float v) { asm volatile("st.shared.f32 [%0], %1;" :: "r"(a), "f"(v) : "memory"); }
__device__ __forceinline__ void sts_f32x2(uint32_t a, float x, float y) { asm volatile("st.shared.v2.f32 [%0], {%1, %2};" :: "r"(a), "f"(x), "f"(y) : "memory"); }
__device__ __forceinline__ void sts_f32x4(uint32_t a, float x, float y, float z, float w) { asm volatile("st.shared.v4.f32 [%0], {%1, %2, %3, %4};" :: "r"(a), "f"(x), "f"(y), "f"(z), "f"(w) : "memory"); }

__device__ __forceinline__ uint4 lds_u32x4(uint32_t a) { uint4 v; asm volatile("ld.shared.v4.u32 {%0, %1, %2, %3}, [%4];" : "=r"(v.x), "=r"(v.y), "=r"(v.z), "=r"(v.w) : "r"(a) : "memory"); return v; }
__device__ __forceinline__ void sts_u32x4(uint32_t a, uint32_t x, uint32_t y, uint32_t z, uint32_t w) { asm volatile("st.shared.v4.u32 [%0], {%1, %2, %3, %4};" :: "r"(a), "r"(x), "r"(y), "r"(z), "r"(w) : "memory"); }
__device__ __forceinline__ void st_tagged(float* p, float v) {
  const uint32_t b = __float_as_uint(v);
  asm volatile("st.relaxed.gpu.global.u32 [%0], %1;" :: "l"(p), "r"(b == 0u ? 0x80000000u : b) : "memory");
}
__device__ __forceinline__ void st_tagged4(float* p, float x, float y, float z, float w) {
  const uint32_t a = __float_as_uint(x), b = __float_as_uint(y), c = __float_as_uint(z), d = __float_as_uint(w);
  asm volatile("st.relaxed.gpu.global.v4.u32 [%0], {%1, %2, %3, %4};" :: "l"(p), "r"(a == 0u ? 0x80000000u : a), "r"(b == 0u ? 0x80000000u : b),
               "r"(c == 0u ? 0x80000000u : c), "r"(d == 0u ? 0x80000000u : d) : "memory");
}
__device__ __forceinline__ void st_relaxed2(void* p, uint32_t a, uint32_t b) { asm volatile("st.relaxed.gpu.global.v2.u32 [%0], {%1, %2};" :: "l"(p), "r"(a), "r"(b) : "memory"); }
__device__ __forceinline__ float4 ld_tagged4(const float* p) {
  float4 v; asm volatile("ld.relaxed.gpu.global.v4.f32 {%0, %1, %2, %3}, [%4];" : "=f"(v.x), "=f"(v.y), "=f"(v.z), "=f"(v.w) : "l"(p) : "memory"); return v;
}
__device__ __forceinline__ bool tagged4(const float4& v) {
  return __float_as_uint(v.x) != 0u && __float_as_uint(v.y) != 0u && __float_as_uint(v.z) != 0u && __float_as_uint(v.w) != 0u;
}
__device__ __forceinline__ void hint_arrive(uint32_t* p) { asm volatile("red.relaxed.gpu.global.add.u32 [%0], 1;" :: "l"(p) : "memory"); }
__device__ __forceinline__ void hint_wait(const uint32_t* p, uint32_t target) {
  uint32_t v = 0u;
  #pragma unroll 1
  for (unsigned int i = 0; i < (1u << 22) && v < target; i++) asm volatile("ld.relaxed.gpu.global.u32 %0, [%1];" : "=r"(v) : "l"(p) : "memory");
}
__device__ __forceinline__ void fence_proxy_async_global() { asm volatile("fence.proxy.async.global;" ::: "memory"); }

#define H_SPLIT 1
#define X_DLY 1200
#define W_DLY 1900
#define W_FIRST 2200
#define PRE_B 2
#define H_PREG 1
template <int J0, int J1>
__device__ __forceinline__ void load_parts(float2 (&pa)[J1 - J0][4], int t2) {
  #pragma unroll
  for (int j = J0; j < J1; j++)
    #pragma unroll
    for (int k = 0; k < 4; k++)
      asm volatile("ld.relaxed.gpu.global.v2.f32 {%0, %1}, [%2];" : "=f"(pa[j - J0][k].x), "=f"(pa[j - J0][k].y)
                   : "l"(g_modpart + k * 2 * T_D + (t2 >> 7) * T_D + j * 256 + (t2 & 127) * 2) : "memory");
}
template <int J0, int J1>
__device__ __forceinline__ void finish_parts(float2 (&pa)[J1 - J0][4], bool loaded, int t2, uint32_t tab) {
  #pragma unroll 1
  for (unsigned int spin = 0; spin < (1u << 22); spin++) {
    if (!loaded) load_parts<J0, J1>(pa, t2);
    loaded = false;
    bool ok = true;
    #pragma unroll
    for (int j = 0; j < J1 - J0; j++)
      #pragma unroll
      for (int k = 0; k < 4; k++) ok &= (__float_as_uint(pa[j][k].x) != 0u) & (__float_as_uint(pa[j][k].y) != 0u);
    if (__all_sync(0xffffffffu, ok)) break;
  }
  #pragma unroll
  for (int j = J0; j < J1; j++) {
    const float2* q = pa[j - J0];
    const uint32_t m = pack_bf16(((q[0].x + q[1].x) + q[2].x) + q[3].x, ((q[0].y + q[1].y) + q[2].y) + q[3].y);
    sts_u32(tab + (t2 >> 7) * 2048 + j * 512 + (t2 & 127) * 4, t2 >= 128 ? badd2(m, 0x3F803F80u) : m);
  }
}
__device__ __forceinline__ void head_phase(uint32_t scr, uint32_t xs, uint32_t b_x, uint32_t b_go, uint32_t b_head, int t2, uint32_t zero, const bf16* __restrict__ cvec, const bf16* __restrict__ w_mod) {
  const int lane = t2 & 31, w8 = t2 >> 5;
  const int cb = blockIdx.x & 31, ks = blockIdx.x >> 5;
  const bool early = (cb & 15) < 4 * H_SPLIT;
  const uint32_t ws = (xs - 32768 + (t2 >> 3) * 128 + (((t2 ^ (t2 >> 3)) & 7) << 4)) ^ zero;
  const float cv = __bfloat162float(cvec[ks * 256 + t2]);
  const bf16* wsrc = w_mod + (size_t)(ks * 256 + (t2 >> 3)) * (6 * T_D) + cb * 64 + (t2 & 7) * 8;
  if (early) {
    const uint64_t pol = policy_evict_first();
    #pragma unroll 2
    for (int i = 0; i < 8; i++)
      asm volatile("cp.async.cg.shared.global.L2::cache_hint [%0], [%1], 16, %2;" :: "r"(ws + i * 4096), "l"(wsrc + (size_t)i * 32 * 6 * T_D), "l"(pol) : "memory");
  }
  sts_f32(scr + t2 * 4, silu_bf(cv));
  named_bar_sync(6, 384);
  TL_MARK2(1, t2 == 0);
  uint4 xv[2][4];
  uint32_t mb2[2], ih[2], il[2];
  auto norm = [&](int j) {
    #pragma unroll
    for (int r = 0; r < 2; r++) {
      xv[r][j].x = ln_norm2b(xv[r][j].x, mb2[r], ih[r], il[r]); xv[r][j].y = ln_norm2b(xv[r][j].y, mb2[r], ih[r], il[r]);
      xv[r][j].z = ln_norm2b(xv[r][j].z, mb2[r], ih[r], il[r]); xv[r][j].w = ln_norm2b(xv[r][j].w, mb2[r], ih[r], il[r]);
    }
  };
  auto modulate = [&](int j) {
    const uint4 sa = lds_u32x4(scr + 8192 + j * 512 + lane * 16), c1 = lds_u32x4(scr + 8192 + 2048 + j * 512 + lane * 16);
    #pragma unroll
    for (int r = 0; r < 2; r++) {
      xv[r][j].x = badd2(bmul2(xv[r][j].x, c1.x), sa.x); xv[r][j].y = badd2(bmul2(xv[r][j].y, c1.y), sa.y);
      xv[r][j].z = badd2(bmul2(xv[r][j].z, c1.z), sa.z); xv[r][j].w = badd2(bmul2(xv[r][j].w, c1.w), sa.w);
    }
  };
  auto store = [&](int j) {
    #pragma unroll
    for (int r = 0; r < 2; r++) *reinterpret_cast<uint4*>(g_h + (size_t)(blockIdx.x * 16 + 2 * w8 + r) * T_D + j * 256 + lane * 8) = xv[r][j];
  };
  #pragma unroll 1
  for (int ph = 0; ph < 2; ph++) {
    if ((ph == 0) == early) {
      asm volatile("cp.async.wait_all;" ::: "memory");
      if (!early) mbar_wait(b_x + 168, 0);
      float acc[8];
      #pragma unroll
      for (int j = 0; j < 8; j++) acc[j] = 0.f;
      #pragma unroll
      for (int i = 0; i < 8; i++) fma8(acc, lds_f32(scr + ((t2 >> 3) + 32 * i) * 4), lds_u32x4(ws + i * 4096));
      #pragma unroll
      for (int j = 0; j < 4; j++) { const bool up = lane & 16; acc[j] = (up ? acc[4 + j] : acc[j]) + __shfl_xor_sync(0xffffffffu, up ? acc[j] : acc[4 + j], 16); }
      #pragma unroll
      for (int j = 0; j < 2; j++) { const bool up = lane & 8; acc[j] = (up ? acc[2 + j] : acc[j]) + __shfl_xor_sync(0xffffffffu, up ? acc[j] : acc[2 + j], 8); }
      sts_f32x2(scr + 1024 + w8 * 256 + (lane & 7) * 32 + (lane >> 3) * 8, acc[0], acc[1]);
      named_bar_sync(5, 256);
      if (t2 < 64) {
        float sum = 0.f;
        #pragma unroll
        for (int i = 0; i < 8; i++) sum += lds_f32(scr + 1024 + i * 256 + t2 * 4);
        st_tagged(g_modpart + ks * 2 * T_D + cb * 64 + t2, sum);
        TL_MARK2(early ? 2 : 6, t2 == 0);
      }
    } else {
      float2 pa[H_SPLIT][4];
      mbar_wait(b_x, 0);
      TL_MARK2(18, t2 == 0);
      if (H_PREG) load_parts<0, H_SPLIT>(pa, t2);
      #pragma unroll
      for (int r = 0; r < 2; r++)
        #pragma unroll
        for (int j = 0; j < 4; j++) xv[r][j] = lds_u32x4(xs + (2 * w8 + r) * 2048 + j * 512 + lane * 16);
  {
    float st[4] = {0.f, 0.f, 0.f, 0.f};
    #pragma unroll
    for (int r = 0; r < 2; r++)
      #pragma unroll
      for (int j = 0; j < 4; j++) {
        float v[8];
        unpack8(xv[r][j], v);
        st[2 * r] += ((v[0] + v[1]) + (v[2] + v[3])) + ((v[4] + v[5]) + (v[6] + v[7]));
        st[2 * r + 1] += fmaf(v[0], v[0], fmaf(v[1], v[1], fmaf(v[2], v[2], v[3] * v[3]))) + fmaf(v[4], v[4], fmaf(v[5], v[5], fmaf(v[6], v[6], v[7] * v[7])));
      }
    #pragma unroll
    for (int k = 0; k < 2; k++) { const bool up = lane & 16; st[k] = (up ? st[2 + k] : st[k]) + __shfl_xor_sync(0xffffffffu, up ? st[k] : st[2 + k], 16); }
    #pragma unroll
    for (int o = 8; o > 0; o >>= 1) { st[0] += __shfl_xor_sync(0xffffffffu, st[0], o); st[1] += __shfl_xor_sync(0xffffffffu, st[1], o); }
    const float mean = st[0] * (1.0f / T_D);
    const float inv = rcp_approx(rbf(sqrt_approx(rbf(rbf(fmaxf(fmaf(-mean, mean, st[1] * (1.0f / T_D)), 0.f)) + 1e-05f))));
    const uint32_t m = pack_bf16(mean, mean), h = pack_bf16(inv - rbf(inv), inv);
    #pragma unroll
    for (int r = 0; r < 2; r++) {
      mb2[r] = __shfl_sync(0xffffffffu, m, 16 * r);
      const uint32_t hr = __shfl_sync(0xffffffffu, h, 16 * r);
      ih[r] = __byte_perm(hr, hr, 0x3232); il[r] = __byte_perm(hr, hr, 0x1010);
    }
  }
      #pragma unroll
      for (int j = 0; j < H_SPLIT; j++) norm(j);
      TL_MARK2(5, t2 == 0);
      finish_parts<0, H_SPLIT>(pa, H_PREG, t2, scr + 8192);
      named_bar_sync(5, 256);
      TL_MARK2(7, t2 == 0);
      #pragma unroll
      for (int j = 0; j < H_SPLIT; j++) { modulate(j); store(j); }
      named_bar_arrive(9, 288);
    }
  }
  #pragma unroll
  for (int j = H_SPLIT; j < 4; j++) norm(j);
  float2 pb[4 - H_SPLIT][4];
  finish_parts<H_SPLIT, 4>(pb, false, t2, scr + 8192);
  named_bar_sync(5, 256);
  TL_MARK2(17, t2 == 0);
  #pragma unroll
  for (int j = H_SPLIT; j < 4; j++) modulate(j);
  __syncwarp();
  if (lane == 0) mbar_arrive(b_head + (xv[1][3].w & zero));
  mbar_wait(b_go, 0);
  #pragma unroll
  for (int j = H_SPLIT; j < 4; j++) store(j);
  named_bar_arrive(8, 288);
}

#define MOD_AT (b_empty + 8)
#define MOD_PF 0
#define MOD_SPLIT 16
__device__ __forceinline__ void mod_rest(uint32_t scr, uint32_t b_go, int t, const bf16* __restrict__ cvec, const bf16* __restrict__ w_mod, const bf16* __restrict__ w_r) {
  const int lane = t & 31;
  #pragma unroll 1
  for (int i = t; i < T_D / 2; i += 64) {
    const uint32_t c2 = *reinterpret_cast<const uint32_t*>(cvec + 2 * i);
    sts_u32(scr + i * 4, pack_bf16(silu_bf(bflo(c2)), silu_bf(bfhi(c2))));
  }
  named_bar_sync(11, 64);
  const bf16* wp = w_mod + (size_t)(2 * (t >> 2)) * (6 * T_D) + 2 * T_D + blockIdx.x * 32 + (t & 3) * 8;
  float acc[8];
  #pragma unroll
  for (int i = 0; i < 8; i++) acc[i] = 0.f;
  #pragma unroll 1
  for (int i = 0; i < 32; i += 2) {
    if (i == MOD_SPLIT) mbar_wait(b_go, 0);
    const uint4 w0 = ldg_nc_v4(wp), w1 = ldg_nc_v4(wp + 6 * T_D), w2 = ldg_nc_v4(wp + 32 * 6 * T_D), w3 = ldg_nc_v4(wp + 33 * 6 * T_D);
    wp += 64 * 6 * T_D;
    const uint32_t s0 = lds_u32(scr + (i * 16 + (t >> 2)) * 4), s1 = lds_u32(scr + (i * 16 + 16 + (t >> 2)) * 4);
    fma8(acc, bflo(s0), w0); fma8(acc, bfhi(s0), w1); fma8(acc, bflo(s1), w2); fma8(acc, bfhi(s1), w3);
  }
  #pragma unroll
  for (int j = 0; j < 4; j++) { const bool up = lane & 16; acc[j] = (up ? acc[4 + j] : acc[j]) + __shfl_xor_sync(0xffffffffu, up ? acc[j] : acc[4 + j], 16); }
  #pragma unroll
  for (int j = 0; j < 2; j++) { const bool up = lane & 8; acc[j] = (up ? acc[2 + j] : acc[j]) + __shfl_xor_sync(0xffffffffu, up ? acc[j] : acc[2 + j], 8); }
  { const bool up = lane & 4; acc[0] = (up ? acc[1] : acc[0]) + __shfl_xor_sync(0xffffffffu, up ? acc[0] : acc[1], 4); }
  if (t >= 32) sts_f32(scr + 2048 + lane * 4, acc[0]);
  named_bar_sync(11, 64);
  if (__shfl_sync(0xffffffffu, t, 0) < 32) {
    const int kind = blockIdx.x >> 5;
    float v = rbf(acc[0] + lds_f32(scr + 2048 + lane * 4));
    const int col = (blockIdx.x & 31) * 32 + (lane & 3) * 8 + (lane >> 2);
    uint8_t* dst = g_col + (col >> 7) * 1536;
    if (kind == 2) v = rbf(1.0f + v);
    float vw = v * __bfloat162float(w_r[col]);
    if (kind == 2) {
      const int c = col & 127, i = (c & ~15) + ((c >> 1) & 3) * 4 + ((c >> 3) & 1) * 2 + (c & 1);
      reinterpret_cast<bf16*>(dst)[i] = __float2bfloat16_rn(vw);
      reinterpret_cast<bf16*>(dst)[128 + i] = __float2bfloat16_rn(vw - rbf(vw));
    }
    reinterpret_cast<bf16*>(dst + 512 + (kind & 1) * 512 + (kind >> 1) * 256)[col & 127] = __float2bfloat16_rn(v);
    #pragma unroll
    for (int o = 16; o > 0; o >>= 1) vw += __shfl_xor_sync(0xffffffffu, vw, o);
    if (lane == 0 && (kind == 1 || kind == 2)) g_scal[95 - blockIdx.x] = vw;
  }
  #pragma unroll 1
  for (int i = blockIdx.x * 64 + t; i < (int)(sizeof(g_mail) / 16); i += 128 * 64) reinterpret_cast<uint4*>(&g_mail)[i] = make_uint4(0u, 0u, 0u, 0u);
  named_bar_sync(11, 64);
  if (t == 0) red_release_add(&g_hcnt[0], 1u);
}

#define HPOL_A pol
#define HPOL_B pol_normal()
#define HMAP_A &tmOl
#define HMAP_B &tmWo
constexpr int AT_NBLK = T_SEQ / 128;
constexpr float AT_HEAD = 7.0f;
#define WO_LATE 12
#define QP_STAG 3
#define AT_SPLIT 28
#define AT_PIN 12
#define PINB 4
constexpr int AT_NFULL = 124;
constexpr int AT_PREG = 40, AT_CREG = 232;
constexpr uint32_t AT_SQ = 5 * 32768;
constexpr float AT_C = 0.08838834764831845f * 1.4426950408889634f;
constexpr float AT_RAW_LO = -16.0f, AT_RAW_HI = 24.0f;
constexpr float AT_RAW_SUM = 281474976710656.0f, AT_RAW_MIN = 9.094947017729282e-13f;
constexpr uint32_t AT_SBAR = AT_SQ + 65536 + 256;
constexpr uint32_t AT_SMEM = AT_SQ + 65536 + 3072;

__device__ __forceinline__ uint32_t ring_slot(uint32_t t) { return t - 5u * ((t * 205u) >> 10); }
__device__ __forceinline__ uint32_t qp_pos(uint32_t j, uint32_t it) { return 4u * it + (j & 3u) + ((j & 3u) == 3u ? it : 0u); }
__device__ __forceinline__ uint32_t ring_par(uint32_t t) { return ((t * 205u) >> 10) & 1u; }
__device__ __forceinline__ void softmax_rowmax(const float (&s)[64], float& mx0, float& mx1) {
  float a0 = fmaxf(s[0], s[1]), a1 = fmaxf(s[4], s[5]), a2 = fmaxf(s[8], s[9]), a3 = fmaxf(s[12], s[13]);
  float b0 = fmaxf(s[2], s[3]), b1 = fmaxf(s[6], s[7]), b2 = fmaxf(s[10], s[11]), b3 = fmaxf(s[14], s[15]);
  #pragma unroll
  for (int j = 4; j < 16; j += 4) {
    a0 = fmaxf(a0, fmaxf(s[4 * j + 0], s[4 * j + 1]));  b0 = fmaxf(b0, fmaxf(s[4 * j + 2], s[4 * j + 3]));
    a1 = fmaxf(a1, fmaxf(s[4 * j + 4], s[4 * j + 5]));  b1 = fmaxf(b1, fmaxf(s[4 * j + 6], s[4 * j + 7]));
    a2 = fmaxf(a2, fmaxf(s[4 * j + 8], s[4 * j + 9]));  b2 = fmaxf(b2, fmaxf(s[4 * j + 10], s[4 * j + 11]));
    a3 = fmaxf(a3, fmaxf(s[4 * j + 12], s[4 * j + 13])); b3 = fmaxf(b3, fmaxf(s[4 * j + 14], s[4 * j + 15]));
  }
  mx0 = fmaxf(fmaxf(a0, a1), fmaxf(a2, a3));
  mx1 = fmaxf(fmaxf(b0, b1), fmaxf(b2, b3));
  mx0 = fmaxf(mx0, __shfl_xor_sync(0xffffffffu, mx0, 1));
  mx1 = fmaxf(mx1, __shfl_xor_sync(0xffffffffu, mx1, 1));
  mx0 = fmaxf(mx0, __shfl_xor_sync(0xffffffffu, mx0, 2));
  mx1 = fmaxf(mx1, __shfl_xor_sync(0xffffffffu, mx1, 2));
}
__device__ __forceinline__ void softmax_sub(float (&s)[64], float mc0, float mc1) {
  #pragma unroll
  for (int j = 0; j < 16; j++) { s[4 * j] -= mc0; s[4 * j + 1] -= mc0; s[4 * j + 2] -= mc1; s[4 * j + 3] -= mc1; }
}
template <int LO, int HI>
__device__ __forceinline__ void softmax_exp(float (&s)[64]) {
  #pragma unroll
  for (int i = LO; i < HI; i++) s[i] = ex2_approx(s[i]);
}
__device__ __forceinline__ bool softmax_mode(const float (&s)[64], float& mc0, float& mc1) {
  softmax_rowmax(s, mc0, mc1);
  const bool raw = __all_sync(0xffffffffu, mc0 >= AT_RAW_LO && mc0 <= AT_RAW_HI && mc1 >= AT_RAW_LO && mc1 <= AT_RAW_HI);
  mc0 += AT_HEAD; mc1 += AT_HEAD;
  return raw;
}
__device__ __forceinline__ void rowsum_p(const uint32_t (&p)[32], uint32_t& t0, uint32_t& t1) {
  uint32_t a[16];
  #pragma unroll
  for (int i = 0; i < 8; i++) { a[2 * i] = badd2(p[4 * i], p[4 * i + 2]); a[2 * i + 1] = badd2(p[4 * i + 1], p[4 * i + 3]); }
  #pragma unroll
  for (int i = 0; i < 4; i++) { a[2 * i] = badd2(a[4 * i], a[4 * i + 2]); a[2 * i + 1] = badd2(a[4 * i + 1], a[4 * i + 3]); }
  t0 = badd2(badd2(a[0], a[2]), badd2(a[4], a[6]));
  t1 = badd2(badd2(a[1], a[3]), badd2(a[5], a[7]));
}
__device__ __forceinline__ void add_rowsum(const uint32_t (&p)[32], float& l0, float& l1) {
  uint32_t t0, t1;
  rowsum_p(p, t0, t1);
  l0 += bflo(t0) + bfhi(t0); l1 += bflo(t1) + bfhi(t1);
}
__device__ __forceinline__ void pack_p(uint32_t (&p)[32], const float (&s)[64]) {
  #pragma unroll
  for (int i = 0; i < 32; i++) p[i] = pack_bf16(s[2 * i], s[2 * i + 1]);
}
__device__ __noinline__ void attn_rows_exact(uint32_t sq, uint32_t so, int hsel, const bf16* __restrict__ kh, const bf16* __restrict__ vh) {
  const int warp = (threadIdx.x >> 5) & 3, lane = threadIdx.x & 31;
  const size_t hofs = (size_t)((blockIdx.x < 128 ? blockIdx.x >> 4 : 15) * 2 + hsel) * T_SEQ * T_DH;
  kh += hofs; vh += hofs;
  #pragma unroll 1
  for (int r = 16 * warp; r < 16 * warp + 16; r++) {
    const uint32_t ad = (lane >> 4) * 16384 + r * 128 + ((((lane & 15) >> 1) ^ (r & 7)) << 4) + (lane & 1) * 8;
    uint2 qv; asm volatile("ld.shared.v2.u32 {%0, %1}, [%2];" : "=r"(qv.x), "=r"(qv.y) : "r"(sq + ad) : "memory");
    const float q0 = bflo(qv.x), q1 = bfhi(qv.x), q2 = bflo(qv.y), q3 = bfhi(qv.y);
    float m = -INFINITY, l = 0.f, o0 = 0.f, o1 = 0.f, o2 = 0.f, o3 = 0.f;
    #pragma unroll 1
    for (int key = 0; key < T_SEQ; key++) {
      const uint2 kv = *reinterpret_cast<const uint2*>(kh + (size_t)key * T_DH + lane * 4);
      const uint2 vv = *reinterpret_cast<const uint2*>(vh + (size_t)key * T_DH + lane * 4);
      float sc = (q0 * bflo(kv.x) + q1 * bfhi(kv.x)) + (q2 * bflo(kv.y) + q3 * bfhi(kv.y));
      #pragma unroll
      for (int o = 16; o > 0; o >>= 1) sc += __shfl_xor_sync(0xffffffffu, sc, o);
      const float mn = fmaxf(m, sc);
      const float al = (m == mn) ? 1.0f : ex2_approx(m - mn), p = rbf(ex2_approx(sc - mn));
      m = mn;
      l = fmaf(l, al, p);
      o0 = fmaf(o0, al, p * bflo(vv.x)); o1 = fmaf(o1, al, p * bfhi(vv.x));
      o2 = fmaf(o2, al, p * bflo(vv.y)); o3 = fmaf(o3, al, p * bfhi(vv.y));
    }
    const float inv = rcp_approx(l);
    asm volatile("st.shared.v2.u32 [%0], {%1, %2};" :: "r"(so + ad), "r"(pack_bf16(o0 * inv, o1 * inv)), "r"(pack_bf16(o2 * inv, o3 * inv)) : "memory");
  }
}
__device__ __forceinline__ void issue_qk(float (&s)[64], const uint32_t (&q)[32], uint32_t k_lo) {
  wgmma_fence();
  wgmma_m64n128k16_rs<0>(s, q[0], q[1], q[2], q[3], k_lo, 0);
  wgmma_m64n128k16_rs<2>(s, q[4], q[5], q[6], q[7], k_lo, 1);
  wgmma_m64n128k16_rs<4>(s, q[8], q[9], q[10], q[11], k_lo, 1);
  wgmma_m64n128k16_rs<6>(s, q[12], q[13], q[14], q[15], k_lo, 1);
  wgmma_m64n128k16_rs<1024>(s, q[16], q[17], q[18], q[19], k_lo, 1);
  wgmma_m64n128k16_rs<1026>(s, q[20], q[21], q[22], q[23], k_lo, 1);
  wgmma_m64n128k16_rs<1028>(s, q[24], q[25], q[26], q[27], k_lo, 1);
  wgmma_m64n128k16_rs<1030>(s, q[28], q[29], q[30], q[31], k_lo, 1);
  wgmma_commit();
}
__device__ __forceinline__ void issue_pv(float (&o)[64], const uint32_t (&p)[32], uint32_t v_lo, int accumulate) {
  wgmma_fence();
  wgmma_m64n128k16_rs_tb<0>(o, p[0], p[1], p[2], p[3], v_lo, accumulate);
  wgmma_m64n128k16_rs_tb<128>(o, p[4], p[5], p[6], p[7], v_lo, 1);
  wgmma_m64n128k16_rs_tb<256>(o, p[8], p[9], p[10], p[11], v_lo, 1);
  wgmma_m64n128k16_rs_tb<384>(o, p[12], p[13], p[14], p[15], v_lo, 1);
  wgmma_m64n128k16_rs_tb<512>(o, p[16], p[17], p[18], p[19], v_lo, 1);
  wgmma_m64n128k16_rs_tb<640>(o, p[20], p[21], p[22], p[23], v_lo, 1);
  wgmma_m64n128k16_rs_tb<768>(o, p[24], p[25], p[26], p[27], v_lo, 1);
  wgmma_m64n128k16_rs_tb<896>(o, p[28], p[29], p[30], p[31], v_lo, 1);
  wgmma_commit();
}
__device__ __forceinline__ void block_end(uint32_t zero, uint32_t bar) {
  #pragma unroll 1
  for (uint32_t i = 0; i < zero; i++) mbar_arrive(bar);
}
__device__ __forceinline__ void rescale_o(float (&o)[64], float al0, float al1) {
  #pragma unroll
  for (int j = 0; j < 16; j++) { o[4 * j] *= al0; o[4 * j + 1] *= al0; o[4 * j + 2] *= al1; o[4 * j + 3] *= al1; }
}

__device__ __forceinline__ void stage_o(const float (&o)[64], float i0, float i1, uint32_t dst, int lane) {
  #pragma unroll
  for (int J = 0; J < 16; J += 2)
    stmatrix_x4(dst + (J >> 3) * 16384 + ((((J & 7) + (lane >> 4)) ^ (lane & 7)) << 4),
                pack_bf16(o[4 * J + 0] * i0, o[4 * J + 1] * i0), pack_bf16(o[4 * J + 2] * i1, o[4 * J + 3] * i1),
                pack_bf16(o[4 * J + 4] * i0, o[4 * J + 5] * i0), pack_bf16(o[4 * J + 6] * i1, o[4 * J + 7] * i1));
}
__device__ __forceinline__ bool finish_l(float& l0, float& l1) {
  l0 += __shfl_xor_sync(0xffffffffu, l0, 1); l1 += __shfl_xor_sync(0xffffffffu, l1, 1);
  l0 += __shfl_xor_sync(0xffffffffu, l0, 2); l1 += __shfl_xor_sync(0xffffffffu, l1, 2);
  const bool redo = __any_sync(0xffffffffu, !(l0 <= AT_RAW_SUM && l1 <= AT_RAW_SUM && l0 >= AT_RAW_MIN && l1 >= AT_RAW_MIN));
  l0 = rcp_approx(l0); l1 = rcp_approx(l1);
  return redo;
}
template <int J0>
__device__ __forceinline__ void stage_q(const float (&acc)[128], float c, uint32_t dst, int lane) {
  #pragma unroll
  for (int J = J0; J < J0 + 16; J += 2)
    stmatrix_x4(dst + (J >> 3) * 16384 + ((((J & 7) + (lane >> 4)) ^ (lane & 7)) << 4),
                pack_bf16(acc[4 * J + 0] * c, acc[4 * J + 1] * c), pack_bf16(acc[4 * J + 2] * c, acc[4 * J + 3] * c),
                pack_bf16(acc[4 * J + 4] * c, acc[4 * J + 5] * c), pack_bf16(acc[4 * J + 6] * c, acc[4 * J + 7] * c));
}
__device__ __forceinline__ void store_o(const CUtensorMap* tmO, uint32_t src, int head, int row) {
  tma_store_2d(tmO, src, head * T_DH, row);
  tma_store_2d(tmO, src + 16384, head * T_DH + 64, row);
  bulk_commit();
}
__device__ __forceinline__ void mma_bf16(float (&d)[4], uint32_t a0, uint32_t a1, uint32_t a2, uint32_t a3, uint32_t b0, uint32_t b1) {
  asm volatile("mma.sync.aligned.m16n8k16.row.col.f32.bf16.bf16.f32 {%0, %1, %2, %3}, {%4, %5, %6, %7}, {%8, %9}, {%0, %1, %2, %3};"
               : "+f"(d[0]), "+f"(d[1]), "+f"(d[2]), "+f"(d[3]) : "r"(a0), "r"(a1), "r"(a2), "r"(a3), "r"(b0), "r"(b1));
}
struct GemvSel { uint32_t lo0, hi0, lo1, hi1; };
__device__ __forceinline__ GemvSel gemv_sel(int lane) {
  const uint32_t lo = (lane & 8) ? 0x1044u : 0x4410u, hi = (lane & 8) ? 0x3244u : 0x4432u;
  GemvSel s; s.lo0 = (lane & 16) ? 0x4444u : lo; s.hi0 = (lane & 16) ? 0x4444u : hi; s.lo1 = (lane & 16) ? lo : 0x4444u; s.hi1 = (lane & 16) ? hi : 0x4444u;
  return s;
}
#define GEMV_B0(j, h, s) __byte_perm((j) < 2 ? (h).x : (h).y, 0u, ((j) & 1) ? (s).hi0 : (s).lo0)
#define GEMV_B1(j, h, s) __byte_perm((j) < 2 ? (h).x : (h).y, 0u, ((j) & 1) ? (s).hi1 : (s).lo1)
__device__ __forceinline__ float4 gemv_out(const float (&d)[4], int lane) {
  const bool tk = lane & 1;
  const float r0 = __shfl_xor_sync(0xffffffffu, tk ? d[0] : d[1], 1), r1 = __shfl_xor_sync(0xffffffffu, tk ? d[2] : d[3], 1);
  return tk ? make_float4(r0, d[1], r1, d[3]) : make_float4(d[0], r0, d[2], r1);
}
#define OG_NG 8
#define PUT_N 2
#define H_STAG 2
#define NOZERO 1
#define PVPIN 1
#define QKPIN 0
#define ALIGN 1
#define AL_P 60
#define AL_SLEEP 1200
#define AL_MAX 800
#define AL_ADD 0
#define X_PF 0
#define POLL_NS 200
#define KV3D 1
#define W3D 1
#define ARV_IMM 1
#define ZS 1
#define OG_PRE 10
#define OG_PRE2 12
#define SERP 1
#define OG_JOBS 7
#define OG_GRP 6
#define LD_FIRST 3
#define LD_STAG (OG_GRP / 2)
constexpr int OG_ST = 5, OG_NKB = T_DQKV / 64 - OG_PRE, OG_MOE = T_F / 32;
__device__ __forceinline__ int pre_kb(int i) { return (i >> 1) * 4 + (i & 1); }
__device__ __forceinline__ int own_kb(int i) { return i < OG_PRE2 ? pre_kb(i) + 2 : i < 64 - OG_PRE2 ? i + OG_PRE2 : pre_kb(i - (64 - OG_PRE2 - OG_PRE)); }
constexpr int OG_POS = 8;
constexpr uint32_t OG_STAGE = 32768;
constexpr uint32_t OG_SCOL = AT_SBAR + 512;
constexpr uint32_t OG_SMISC = AT_SBAR + 2048;
constexpr int OG_XPOS = OG_POS + OG_NKB;
constexpr uint32_t OG_SWD = AT_SQ, OG_PSLOT = AT_SQ;
constexpr uint32_t OG_SWD1 = (OG_XPOS % OG_ST) * OG_STAGE;
constexpr uint32_t OG_XSLOT = AT_SQ + 32768;
constexpr uint32_t OG_OSLOT = ((OG_XPOS + 1) % OG_ST) * OG_STAGE;
constexpr uint32_t OG_SH2 = ((OG_XPOS + 2) % OG_ST) * OG_STAGE;
constexpr uint32_t OG_SRED = ((OG_XPOS + 3) % OG_ST) * OG_STAGE;
constexpr uint32_t OG_SSTAT = OG_SRED + 16384;
constexpr uint32_t OG_SGU = OG_SRED + 8192;
constexpr uint32_t OG_SFIN = OG_SGU + 256;
#define OGM 2
#define OG_MT(b) ((((b) >> OGM) & 15) ^ (SERP && ((b) & 64) ? 15 : 0))
#define OG_NT(b) (((b) & ((1 << OGM) - 1)) + (((b) >> (4 + OGM)) << OGM))
#define TAIL_SETUP \
  const uint32_t bar_full = sbase + AT_SBAR, bar_empty = bar_full + 40; \
  const uint32_t bar_wd = bar_full + 168, bar_col = bar_full + 176, bar_out = bar_full + 184, bar_end = bar_full + 192; \
  const uint32_t bar_key = bar_full + 200, bar_h2 = bar_full + 208, bar_sel = bar_full + 216; \
  const int mt = OG_MT(blockIdx.x), nt = OG_NT(blockIdx.x); \
  const int m0 = mt * 128, n0 = nt * 128; \
  const bool has_moe = (int)blockIdx.x < OG_MOE; \
  (void)bar_empty; (void)bar_wd; (void)bar_col; (void)bar_out; (void)bar_end; (void)bar_key; (void)bar_h2; (void)bar_sel; (void)m0; (void)n0; (void)has_moe;

__device__ __forceinline__ void tail_producer(uint32_t sbase, uint32_t ph, uint64_t pol, const CUtensorMap* tmA, const CUtensorMap* tmB, const CUtensorMap* tmX) {
  TAIL_SETUP
  uint32_t stage = OG_POS % OG_ST;
  int kb = 0;
  #pragma unroll 1
  for (int seg = 0; seg < 2; seg++) {
    mbar_wait(bar_full + 264 + 80 * seg, 0);
    fence_proxy_async_global();
    const int end = seg == 0 ? 32 - OG_PRE2 : has_moe ? OG_NKB : 64 - OG_PRE2;
    #pragma unroll 1
    for (; kb < end; kb++) {
      const uint32_t fb = bar_full + 8 * stage, sa = sbase + stage * OG_STAGE;
      const int k0 = own_kb(kb) * 64;
      mbar_wait(bar_empty + 8 * stage, ph);
      mbar_expect_tx(fb, OG_STAGE);
      tma_load_3d_hint(sa + 16384, tmB, k0, 2 * nt, fb, pol);
      tma_load_2d_hint(sa, tmA, k0, m0, fb, pol);
      if (++stage == OG_ST) { stage = 0; ph ^= 1; }
    }
  }
  if (has_moe) {
    mbar_wait(bar_empty + 8 * (OG_XPOS % OG_ST), ph);
    mbar_expect_tx(bar_wd, OG_STAGE);
    tma_load_3d_hint(sbase + OG_SWD1, tmX, blockIdx.x * 32, 8, bar_wd, pol);
  }
}

__device__ __forceinline__ uint32_t out2(uint32_t x1, uint32_t mb2, uint32_t ih, uint32_t il, uint32_t c1, uint32_t sb, uint32_t gb) {
  const uint32_t h2 = badd2(bmul2(ln_norm2b(x1, mb2, ih, il), c1), sb);
  return badd2(x1, bmul2(gb, bfma2(h2, 0u, h2)));
}
#define OGTIME gtime()
#define PRE_N 1
#define PRE_PACE 150
#define X_PACE 200
#define WD_LATE 0
#define Y_SLACK 96
#define OG_STAG 3
#define WD_PACE 300
__device__ __forceinline__ void tail_exchange(uint32_t sbase, const bf16* __restrict__ w_down, const bf16* __restrict__ w_r, const bf16* __restrict__ x, bf16* __restrict__ out) {
    TAIL_SETUP
    const int lane = threadIdx.x & 31, wi = __shfl_sync(0xffffffffu, threadIdx.x >> 5, 0);
    if (wi == 3) {
      if (blockIdx.x < AT_NFULL) {
        uint32_t a, b;
        asm volatile("ld.relaxed.gpu.global.u32 %0, [%1];" : "=r"(a) : "l"(g_smid + 32 + blockIdx.x - lane) : "memory");
        b = __shfl_down_sync(0xffffffffu, a, 1);
        unsigned int* tm = g_tmax + blockIdx.x - min((int)blockIdx.x, __ffs(__ballot_sync(0xffffffffu, b >= a)) - 1);
        mbar_wait(bar_full + 312, 0);
        if (lane == 0) {
          asm volatile("mov.u32 %0, %%globaltimer_lo;" : "=r"(a));
          asm volatile("red.relaxed.gpu.global.max.u32 [%0], %1;" :: "l"(tm), "r"(a) : "memory");
          __nanosleep(AL_SLEEP);
          asm volatile("ld.relaxed.gpu.global.u32 %0, [%1];" : "=r"(b) : "l"(tm) : "memory");
          b -= a;
          sts_u32(sbase + OG_SMISC + 32, (b < AL_MAX ? b * 13 / 8 : 0u) + AL_ADD);
          mbar_arrive(bar_full + 320);
        }
        named_bar_sync(15, 32);
      }
      mbar_wait(bar_full + 344, 0);
      float a = g_scal[lane], b = g_scal[32 + lane];
      #pragma unroll
      for (int i = 0; i < 3; i++) {
        const uint4 v = *reinterpret_cast<const uint4*>(g_col + nt * 1536 + i * 512 + lane * 16);
        sts_u32x4(sbase + OG_SCOL + i * 512 + lane * 16, v.x, v.y, v.z, v.w);
      }
      #pragma unroll
      for (int o = 16; o > 0; o >>= 1) { a += __shfl_xor_sync(0xffffffffu, a, o); b += __shfl_xor_sync(0xffffffffu, b, o); }
      if (lane == 0) sts_f32x2(sbase + OG_SMISC, a, b);
      const uint64_t pol = policy_evict_first();
      #pragma unroll 1
      for (int r = lane >> 4; r < 128; r += 4) {
        __nanosleep(X_PACE);
        #pragma unroll
        for (int j = 0; j < 4; j += 2)
          asm volatile("cp.async.cg.shared.global.L2::cache_hint [%0], [%1], 16, %2;" :: "r"(sbase + OG_XSLOT + (lane & 8) * 2048 + (r + j) * 128 + (((lane ^ (r + j)) & 7) << 4)),
                       "l"(x + (size_t)(m0 + r + j) * T_D + n0 + (lane & 15) * 8), "l"(pol) : "memory");
      }
      asm volatile("cp.async.wait_all;" ::: "memory");
      __syncwarp();
      if (lane == 0) mbar_arrive(bar_col);
    } else if (wi == 2) {
      if (elect_one()) {
        const uint32_t b_free = bar_full + (blockIdx.x < AT_NFULL ? 80 : 160);
        mbar_wait(b_free, 0); mbar_wait(b_free, 1);
        #pragma unroll 1
        for (unsigned int i = 0; i < (1u << 20) && ld_acquire(&g_hcnt[32 * (1 + (blockIdx.x >> 3)) + 4 + ((blockIdx.x >> 1) & 3)]) == 0u; i++) __nanosleep(POLL_NS);
        TL_MARK2(23, true);
        fence_proxy_async_global();
        TL_MARK2(4, true);
        mbar_expect_tx(bar_full + 272, 32768);
        #pragma unroll 1
        for (int i = 0; i < PRE_N; i++) {
          bulk_load_hint(sbase + OG_PSLOT + i * (32768 / PRE_N), g_pre + blockIdx.x * 2048 + i * (2048 / PRE_N), 32768 / PRE_N,
                         bar_full + 272, policy_evict_first());
          if (PRE_N > 1) __nanosleep(PRE_PACE);
        }
      }
      named_bar_sync(14, 32);
      if (has_moe) {
        mbar_wait(bar_full + 96, 1); mbar_wait(bar_full + 304, 0);
        const uint64_t pol = policy_evict_first();
        #pragma unroll 1
        for (int r = 0; r < 32; r++) {
          __nanosleep(WD_PACE);
          #pragma unroll
          for (int j = 0; j < 2; j++)
            asm volatile("cp.async.cg.shared.global.L2::cache_hint [%0], [%1], 16, %2;" :: "r"(sbase + OG_SWD + (4 * j + (lane >> 3)) * 4096 + r * 128 + (((lane ^ r) & 7) << 4)),
                         "l"((const uint8_t*)w_down + (size_t)blockIdx.x * 65536 + r * 2048 + j * 512 + lane * 16), "l"(pol) : "memory");
        }
        asm volatile("cp.async.wait_all;" ::: "memory");
        __syncwarp();
        if (lane == 0) mbar_arrive(bar_wd);
      }
    }
    const uint4 wrv = ldg_nc_v4(w_r + threadIdx.x * 8);
    mbar_wait(bar_end, 0);
    if (threadIdx.x == 96) XT(10);
    TL_MARK2(22, lane == 0);
    if (wi == 0) {
      uint32_t k1 = 0u, k2 = 0u;
      #pragma unroll 1
      for (unsigned int spin = 0; spin < (1u << 22) && __any_sync(0xffffffffu, k1 == 0u); spin++) asm volatile("ld.relaxed.gpu.global.u32 %0, [%1];" : "=r"(k1) : "l"(g_key + lane) : "memory");
      TL_MARK2(28, lane == 0);
      warp_top2(k1, k2);
      if (lane == 0) {
        const uint32_t r1 = 0xffffu - (k1 & 0xffffu), r2 = 0xffffu - (k2 & 0xffffu);
        sts_u32x4(sbase + OG_SMISC + 64, r1, r2, (r1 >> 7) * 2, (r2 >> 7) * 2 + ((r1 >> 7) == (r2 >> 7)));
        mbar_arrive(bar_sel);
      }
    } else if (wi < 3) {
          mbar_wait(bar_key, 0);
          const uint4 kk = lds_u32x4(sbase + OG_SSTAT + 1024 + lane * 16);
          uint32_t k1 = max(kk.x, kk.y), k2 = min(kk.x, kk.y);
          k2 = max(max(k2, min(kk.z, kk.w)), min(k1, max(kk.z, kk.w))); k1 = max(k1, max(kk.z, kk.w));
          warp_top2(k1, k2);
          if (wi == 1) {
            if (lane == 0) {
              if (nt == (mt & 7)) st_relaxed2(g_key + mt * 2, k1, k2);
              sts_u32x2(sbase + OG_SMISC + 96, (~k1 >> 4) & 7u, (~k2 >> 4) & 7u);
              mbar_arrive(bar_full + 352);
            }
            TL_MARK2(27, lane == 0);
          } else {
            const uint32_t r = (~((lane & 16) ? k2 : k1)) & 127u, ch = lane & 15;
            const uint2 st = lds_u32x2(sbase + OG_SSTAT + r * 8);
            const uint4 xc = lds_u32x4(sbase + OG_XSLOT + (ch >> 3) * 16384 + r * 128 + (((ch ^ r) & 7) << 4));
            const uint4 c1 = lds_u32x4(sbase + OG_SCOL + 768 + ch * 16), sh = lds_u32x4(sbase + OG_SCOL + 1024 + ch * 16);
            const float inr = __uint_as_float(st.y);
            float* dst = reinterpret_cast<float*>(g_cand + (mt * 2 + (lane >> 4)) * 256 + nt * 16 + ch);
            st_tagged4(dst + 512, __uint_as_float(ln_mod2(xc.x, st.x, inr, c1.x, sh.x)), __uint_as_float(ln_mod2(xc.y, st.x, inr, c1.y, sh.y)),
                       __uint_as_float(ln_mod2(xc.z, st.x, inr, c1.z, sh.z)), __uint_as_float(ln_mod2(xc.w, st.x, inr, c1.w, sh.w)));
            st_tagged4(dst, __uint_as_float(xc.x), __uint_as_float(xc.y), __uint_as_float(xc.z), __uint_as_float(xc.w));
          }
    }
    mbar_wait(bar_sel, 0);
    const uint4 sel = lds_u32x4(sbase + OG_SMISC + 64);
    const int sel0 = (int)sel.x, sel1 = (int)sel.y;
    {
      const float* src0 = reinterpret_cast<const float*>(g_cand + sel.z * 256 + 128 + threadIdx.x);
      const float* src1 = reinterpret_cast<const float*>(g_cand + sel.w * 256 + 128 + threadIdx.x);
      float4 h0, h1;
      #pragma unroll 1
      for (unsigned int spin = 0; spin < (1u << 20); spin++) { h0 = ld_tagged4(src0); h1 = ld_tagged4(src1); if (__all_sync(0xffffffffu, tagged4(h0) & tagged4(h1))) break; }
      sts_f32x4(sbase + OG_SH2 + threadIdx.x * 16, h0.x, h0.y, h0.z, h0.w);
      sts_f32x4(sbase + OG_SH2 + 2048 + threadIdx.x * 16, h1.x, h1.y, h1.z, h1.w);
      __syncwarp();
      if (lane == 0) mbar_arrive(bar_h2);
      TL_MARK2(12, lane == 0);
      if (blockIdx.x >> 6) h0 = h1;
      float v[8], wr[8];
      unpack8(make_uint4(__float_as_uint(h0.x), __float_as_uint(h0.y), __float_as_uint(h0.z), __float_as_uint(h0.w)), v); unpack8(wrv, wr);
      float r = 0.f;
      #pragma unroll
      for (int i = 0; i < 8; i++) r = fmaf(v[i], wr[i], r);
      #pragma unroll
      for (int o = 16; o > 0; o >>= 1) r += __shfl_xor_sync(0xffffffffu, r, o);
      if (lane == 0) sts_f32(sbase + OG_SMISC + 192 + wi * 4, r);
    }
    mbar_wait(bar_out, 0);
    {
      const uint2 cg = lds_u32x2(sbase + OG_SMISC + 96);
      #pragma unroll
      for (int i = 0; i < 4; i++) {
        const int r = (i < 2 ? cg.x : cg.y) * 16 + (i & 1) * 8 + (threadIdx.x >> 4), ch = threadIdx.x & 15;
        if (m0 + r != sel0 && m0 + r != sel1)
          *reinterpret_cast<uint4*>(out + (size_t)(m0 + r) * T_D + n0 + ch * 8) =
              lds_u32x4(sbase + OG_OSLOT + (ch >> 3) * 16384 + r * 128 + (((ch & 7) ^ (r & 7)) << 4));
      }
    }
    if (blockIdx.x == 0 && threadIdx.x < 68) *reinterpret_cast<uint4*>(g_hcnt + 32 * (threadIdx.x >> 2) + 4 * (threadIdx.x & 3)) = make_uint4(0u, 0u, 0u, 0u);
    if (threadIdx.x < 64) g_modpart[blockIdx.x * 64 + threadIdx.x] = 0.f;
    if (ALIGN && threadIdx.x == 64) g_tmax[blockIdx.x] = 0u;
    {
      const int tk = blockIdx.x >> 6, c0 = (blockIdx.x & 63) * 16;
      const uint32_t gb2 = *reinterpret_cast<const uint32_t*>(g_col + (c0 >> 7) * 1536 + 512 + 768 + ((c0 & 127) + (threadIdx.x & 14)) * 2);
      const uint32_t* xp = reinterpret_cast<const uint32_t*>(g_cand + (tk ? sel.w : sel.z) * 256) + ((c0 + (threadIdx.x & 14)) >> 1);
      uint32_t x2 = 0u;
      #pragma unroll 1
      for (unsigned int spin = 0; spin < (1u << 20) && __any_sync(0xffffffffu, x2 == 0u); spin++) asm volatile("ld.relaxed.gpu.global.u32 %0, [%1];" : "=r"(x2) : "l"(xp) : "memory");
      const float* src = g_ypart + (size_t)((threadIdx.x >> 2) * 2 + tk) * T_D + c0 + (threadIdx.x & 3) * 4;
      const bool four = threadIdx.x < (OG_MOE - 96) * 4;
      if (threadIdx.x == 0) hint_wait(CNT_Y, (uint32_t)(OG_MOE - Y_SLACK));
      named_bar_sync(10, 128);
      float4 p0, p1, p2, p3;
      #pragma unroll 1
      for (unsigned int spin = 0; spin < (1u << 20); spin++) {
        p0 = ld_tagged4(src); p1 = ld_tagged4(src + 64 * T_D); p2 = ld_tagged4(src + 128 * T_D); p3 = ld_tagged4(four ? src + 192 * T_D : src);
        if (__all_sync(0xffffffffu, tagged4(p0) & tagged4(p1) & tagged4(p2) & tagged4(p3))) break;
      }
      if (four) { p2.x += p3.x; p2.y += p3.y; p2.z += p3.z; p2.w += p3.w; }
      p0.x = (p0.x + p1.x) + p2.x; p0.y = (p0.y + p1.y) + p2.y; p0.z = (p0.z + p1.z) + p2.z; p0.w = (p0.w + p1.w) + p2.w;
      #pragma unroll
      for (int o = 4; o <= 16; o <<= 1) {
        p0.x += __shfl_xor_sync(0xffffffffu, p0.x, o); p0.y += __shfl_xor_sync(0xffffffffu, p0.y, o);
        p0.z += __shfl_xor_sync(0xffffffffu, p0.z, o); p0.w += __shfl_xor_sync(0xffffffffu, p0.w, o);
      }
      if (lane < 4) sts_f32x4(sbase + OG_SFIN + (threadIdx.x >> 5) * 64 + lane * 16, p0.x, p0.y, p0.z, p0.w);
      named_bar_sync(10, 128);
      TL_MARK2(21, threadIdx.x == 0);
      if (threadIdx.x < 16) {
        const uint32_t ya = sbase + OG_SFIN + threadIdx.x * 4, rp = sbase + OG_SMISC + 192;
        float y = (lds_f32(ya) + lds_f32(ya + 64)) + (lds_f32(ya + 128) + lds_f32(ya + 192));
        const float r = rbf((lds_f32(rp) + lds_f32(rp + 4)) + (lds_f32(rp + 8) + lds_f32(rp + 12)));
        const float rs = rbf(sigmoid_f(r));
        const uint32_t h2p = lds_u32(sbase + OG_SH2 + tk * 2048 + (c0 + (threadIdx.x & 14)) * 2);
        const float fh = (lane & 1) ? bfhi(h2p) : bflo(h2p);
        y = rbf(y);
        y = rbf(y * rs);
        const float upd = rbf(rbf(fh * 0.0f) + y);
        out[(size_t)(tk ? sel1 : sel0) * T_D + c0 + threadIdx.x] =
            __float2bfloat16_rn(((lane & 1) ? bfhi(x2) : bflo(x2)) + rbf(((lane & 1) ? bfhi(gb2) : bflo(gb2)) * rbf(fh + upd)));
      }
    }
    if (threadIdx.x == 0) XT(11);
    TL_END(4, threadIdx.x == 0);
}

__device__ __forceinline__ void load_pre(uint4* pre, uint32_t sbase, uint32_t buf, int t2) {
  mbar_wait(sbase + AT_SBAR + 272, 0);
  #pragma unroll
  for (int i = 0; i < 8; i++) pre[i] = lds_u32x4(sbase + buf + i * 4096 + t2 * 16);
}
__device__ __forceinline__ void tail_consumer(uint32_t sbase, const CUtensorMap* tmOut, const uint4 (&pre)[8], int cwg, const bf16* __restrict__ w_gate, const bf16* __restrict__ w_up) {
    TAIL_SETUP
    const int tid = threadIdx.x & 127, t2 = threadIdx.x - 128;
    const int warp = tid >> 5, lane = tid & 31, w8 = t2 >> 5;
    const uint32_t dbase = (sbase & 0x3FFFFu) >> 4;
    const uint32_t a_base = dbase + ((cwg * 8192) >> 4) + (1u << 16);
    const uint32_t b_base = dbase + (16384 >> 4) + (512u << 16);
    TL_MARK2(25, threadIdx.x == 128);
    const uint64_t pol = policy_evict_first();
    const bf16* pw = ((lane & 16) ? w_up : w_gate) + (size_t)(w8 * 128 + (lane & 3) * 4) * T_F + (has_moe ? blockIdx.x : 0) * 32 + ((lane >> 2) & 3) * 8;
    uint4 wv[32];
    float acc[64];
    #pragma unroll
    for (int i = 0; i < 8; i++) {
      acc[8 * i] = bflo(pre[i].x); acc[8 * i + 1] = bfhi(pre[i].x); acc[8 * i + 2] = bflo(pre[i].y); acc[8 * i + 3] = bfhi(pre[i].y);
      acc[8 * i + 4] = bflo(pre[i].z); acc[8 * i + 5] = bfhi(pre[i].z); acc[8 * i + 6] = bflo(pre[i].w); acc[8 * i + 7] = bfhi(pre[i].w);
    }
    if (lane == 0) mbar_arrive(bar_full + 304);
    if (blockIdx.x < AT_NFULL) {
      const uint32_t c0 = clock_lo();
      mbar_wait(bar_full + 320, 0);
      const uint32_t d = lds_u32(sbase + OG_SMISC + 32);
      while (clock_lo() - c0 < d) {}
    }
    {
      uint32_t stage = OG_POS % OG_ST, phase = (OG_POS / OG_ST) & 1, prev = 12;
      int kb = 0;
      #pragma unroll
      for (int g = 0; g <= OG_NG; g++) {
        const int end = g == OG_NG ? (has_moe ? OG_NKB : 64 - OG_PRE2) : LD_FIRST + g * OG_GRP + LD_STAG * cwg;
        #pragma unroll 1
        do {
          mbar_wait(bar_full + 8 * stage, phase);
          if (OG_STAG > 0 && g == OG_NG && cwg == 1 && kb == end - OG_STAG) named_bar_sync(7, 256);
          const uint32_t a_lo = a_base + stage * (OG_STAGE >> 4), b_lo = b_base + stage * (OG_STAGE >> 4);
          wgmma_fence();
          wgmma_m64n128k16_ss_tb<0, 0>(acc, a_lo, b_lo, 1);
          wgmma_m64n128k16_ss_tb<2, 128>(acc, a_lo, b_lo, 1);
          wgmma_m64n128k16_ss_tb<4, 256>(acc, a_lo, b_lo, 1);
          wgmma_m64n128k16_ss_tb<6, 384>(acc, a_lo, b_lo, 1);
          wgmma_commit();
          if (OG_STAG > 0 && g == OG_NG && cwg == 0 && kb == end - 1) named_bar_arrive(7, 256);
          wgmma_wait<1>();
          if (tid == 0) mbar_arrive(bar_empty + 8 * prev);
          prev = stage;
          if (++stage == OG_ST) { stage = 0; phase ^= 1; }
        } while (++kb < end);
        #pragma unroll
        for (int j = 4 * g; j < 4 * g + 4 && j < 32; j++) wv[j] = ldg_stream_v4(pw + (size_t)(16 * (j >> 2) + (j & 3)) * T_F, pol);
      }
    }
    mbar_wait(bar_col, 0);
    if (__builtin_expect(!has_moe, 0)) {
      load_pre(wv, sbase, AT_SQ, t2);
    }
    wgmma_wait<0>();
    fence_regs(acc);
    if (__builtin_expect(!has_moe, 0)) {
      #pragma unroll
      for (int i = 0; i < 8; i++) {
        acc[8 * i] += bflo(wv[i].x); acc[8 * i + 1] += bfhi(wv[i].x); acc[8 * i + 2] += bflo(wv[i].y); acc[8 * i + 3] += bfhi(wv[i].y);
        acc[8 * i + 4] += bflo(wv[i].z); acc[8 * i + 5] += bfhi(wv[i].z); acc[8 * i + 6] += bflo(wv[i].w); acc[8 * i + 7] += bfhi(wv[i].w);
      }
    }
    if (tid == 0) mbar_arrive(bar_end);
    TL_MARK2(9, lane == 0);
    const int q2 = 2 * (lane & 3);
    const uint32_t frag = (64 * cwg + 16 * warp + (lane & 7) + 8 * ((lane >> 3) & 1)) * 128;
    const int fsw = lane & 7, fhi = lane >> 4;
    {
      float dl[4] = {0.f, 0.f, 0.f, 0.f}, da[4] = {0.f, 0.f, 0.f, 0.f}, db[4] = {0.f, 0.f, 0.f, 0.f};
      const uint32_t tb = sbase + OG_SCOL + (lane & 8) * 32 + (lane & 3) * 8, g = lane >> 2;
      const uint32_t msk = (g == 1 || g == 2) ? 0xffffffffu : 0u, one = g == 0 ? 0x3F803F80u : 0u;
      #pragma unroll
      for (int J = 0; J < 16; J += 2) {
        const uint32_t ad = sbase + OG_XSLOT + (J >> 3) * 16384 + frag + ((((J & 7) + fhi) ^ fsw) << 4);
        uint32_t xr[4];
        ldmatrix_x4(ad, xr[0], xr[1], xr[2], xr[3]);
        const uint2 cw = lds_u32x2(tb + J * 16);
        #pragma unroll
        for (int h = 0; h < 2; h++) {
          const uint32_t ga = lds_u32(sbase + OG_SCOL + 512 + (8 * (J + h) + q2) * 2);
          xr[2 * h] = badd2(xr[2 * h], bmul2(ga, pack_bf16(acc[4 * (J + h)], acc[4 * (J + h) + 1])));
          xr[2 * h + 1] = badd2(xr[2 * h + 1], bmul2(ga, pack_bf16(acc[4 * (J + h) + 2], acc[4 * (J + h) + 3])));
        }
        stmatrix_x4(ad, xr[0], xr[1], xr[2], xr[3]);
        mma_bf16(dl, xr[0], xr[1], xr[2], xr[3], (cw.x & msk) | one, (cw.y & msk) | one);
        mma_bf16(da, xr[0], xr[1], xr[2], xr[3], xr[0], xr[2]);
        mma_bf16(db, xr[0], xr[1], xr[2], xr[3], xr[1], xr[3]);
      }
      {
        const int dsrc = (lane & ~3) + (g >> 1);
        const float qa = __shfl_sync(0xffffffffu, (g & 1) ? da[1] : da[0], dsrc), qb = __shfl_sync(0xffffffffu, (g & 1) ? db[3] : db[2], dsrc);
        const float e0 = __shfl_xor_sync(0xffffffffu, (lane & 1) ? dl[0] : dl[2], 1), e1 = __shfl_xor_sync(0xffffffffu, dl[3], 1);
        if ((lane & 3) < 2) {
          const bool hi = lane & 1;
          st_tagged4(reinterpret_cast<float*>(g_part1 + ((mt * 8 + w8) * 8 + nt) * 16 + g + (hi ? 8 : 0)),
                     hi ? e0 : dl[0], hi ? qb : qa, hi ? e1 + dl[2] : dl[1] + e0, 1.0f);
        }
      }
    }
    TL_MARK2(10, lane == 0);
    uint4 wd[16];
    if (has_moe) mbar_wait(bar_wd, 0);
    #pragma unroll
    for (int i = 0; i < 16; i++) wd[i] = lds_u32x4(sbase + (cwg ? OG_SWD1 : OG_SWD) + warp * 8192 + (i >> 3) * 4096 + (i & 6) * 512 + (i & 1) * 128 + (lane & 3) * 256 + (((lane >> 2) ^ (2 * (lane & 3) + (i & 1))) << 4));
    {
      const float* src = reinterpret_cast<const float*>(g_part1 + ((mt * 8 + w8) * 8 + (lane & 1) * 4) * 16 + (lane >> 1));
      float4 v, v1, v2, v3;
      #pragma unroll 1
      for (unsigned int spin = 0; spin < (1u << 22); spin++) {
        v = ld_tagged4(src); v1 = ld_tagged4(src + 64); v2 = ld_tagged4(src + 128); v3 = ld_tagged4(src + 192);
        if (__all_sync(0xffffffffu, tagged4(v) & tagged4(v1) & tagged4(v2) & tagged4(v3))) break;
        __nanosleep(100);
      }
      __syncwarp();
      TL_MARK2(26, lane == 0);
      v.x = (v.x + v1.x) + (v2.x + v3.x); v.y = (v.y + v1.y) + (v2.y + v3.y); v.z = (v.z + v1.z) + (v2.z + v3.z);
      v.x += __shfl_xor_sync(0xffffffffu, v.x, 1); v.y += __shfl_xor_sync(0xffffffffu, v.y, 1); v.z += __shfl_xor_sync(0xffffffffu, v.z, 1);
      const float mean = v.x * (1.0f / T_D);
      const float var = fmaxf(fmaf(-mean, mean, v.y * (1.0f / T_D)), 0.f);
      const uint32_t mb2 = pack_bf16(mean, mean);
      const float inv = rcp_approx(rbf(sqrt_approx(rbf(rbf(var) + 1e-05f))));
      {
        const float2 sc = lds_f32x2(sbase + OG_SMISC);
        const uint32_t key = rank_key(rbf(fmaf(fmaf(-bflo(mb2), sc.x, v.z), inv, sc.y)), m0 + 16 * w8 + (lane >> 1));
        mbar_wait(bar_end, 0);
        if (lane & 1) sts_u32(sbase + OG_SSTAT + 1024 + (16 * w8 + (lane >> 1)) * 4, key);
        else sts_u32x2(sbase + OG_SSTAT + (16 * w8 + (lane >> 1)) * 8, mb2, __float_as_uint(inv));
        __syncwarp();
        if (lane == 0) mbar_arrive(bar_key);
      }
      const uint32_t ih = pack_bf16(inv, inv), il = pack_bf16(inv - bflo(ih), inv - bflo(ih));
      const uint32_t mba = __shfl_sync(0xffffffffu, mb2, 2 * (lane >> 2)), mbb = __shfl_sync(0xffffffffu, mb2, 2 * (lane >> 2) + 16);
      const uint32_t iha = __shfl_sync(0xffffffffu, ih, 2 * (lane >> 2)), ihb = __shfl_sync(0xffffffffu, ih, 2 * (lane >> 2) + 16);
      const uint32_t ila = __shfl_sync(0xffffffffu, il, 2 * (lane >> 2)), ilb = __shfl_sync(0xffffffffu, il, 2 * (lane >> 2) + 16);
      #pragma unroll 2
      for (int J = 0; J < 16; J += 2) {
        const uint32_t off = (J >> 3) * 16384 + frag + ((((J & 7) + fhi) ^ fsw) << 4);
        uint32_t xr[4];
        ldmatrix_x4(sbase + OG_XSLOT + off, xr[0], xr[1], xr[2], xr[3]);
        #pragma unroll
        for (int h = 0; h < 2; h++) {
          const uint32_t ca = sbase + OG_SCOL + 512 + (8 * (J + h) + q2) * 2;
          const uint32_t c1 = lds_u32(ca + 256), sh = lds_u32(ca + 512), gb = lds_u32(ca + 768);
          xr[2 * h] = out2(xr[2 * h], mba, iha, ila, c1, sh, gb);
          xr[2 * h + 1] = out2(xr[2 * h + 1], mbb, ihb, ilb, c1, sh, gb);
        }
        stmatrix_x4(sbase + OG_OSLOT + off, xr[0], xr[1], xr[2], xr[3]);
      }
      fence_proxy_async();
      mbar_wait(bar_full + 352, 0);
      const uint2 cg = lds_u32x2(sbase + OG_SMISC + 96);
      __syncwarp();
      if (elect_one()) {
        mbar_arrive(bar_out);
        if (cg.x != w8 && cg.y != w8) {
          asm volatile("cp.async.bulk.tensor.2d.global.shared::cta.bulk_group [%0, {%2, %3}], [%1];" :: "l"(tmOut), "r"(sbase + OG_OSLOT + w8 * 2048), "r"(n0), "r"(m0 + 16 * w8) : "memory");
          asm volatile("cp.async.bulk.tensor.2d.global.shared::cta.bulk_group [%0, {%2, %3}], [%1];" :: "l"(tmOut), "r"(sbase + OG_OSLOT + 16384 + w8 * 2048), "r"(n0 + 64), "r"(m0 + 16 * w8) : "memory");
          bulk_commit();
        }
      }
      TL_MARK2(24, lane == 0);
    }
    if (has_moe) mbar_wait(bar_h2, 0);
    TL_MARK2(13, lane == 0);
    if (has_moe) {
      const GemvSel sel = gemv_sel(lane);
      {
        float d[4][4];
        #pragma unroll
        for (int c = 0; c < 4; c++) { d[c][0] = 0.f; d[c][1] = 0.f; d[c][2] = 0.f; d[c][3] = 0.f; }
        #pragma unroll
        for (int st = 0; st < 8; st++) {
          const uint2 hb = lds_u32x2(sbase + OG_SH2 + ((lane >> 2) & 1) * 2048 + (w8 * 128 + st * 16 + (lane & 3) * 4) * 2);
          #pragma unroll
          for (int j = 0; j < 4; j++) mma_bf16(d[j], wv[4 * st + j].x, wv[4 * st + j].y, wv[4 * st + j].z, wv[4 * st + j].w, GEMV_B0(j, hb, sel), GEMV_B1(j, hb, sel));
        }
        #pragma unroll
        for (int e = 0; e < 4; e++) d[0][e] = (d[0][e] + d[1][e]) + (d[2][e] + d[3][e]);
        const float4 r = gemv_out(d[0], lane);
        sts_f32x4(sbase + OG_SRED + w8 * 512 + (((lane >> 4) * 2 + (lane & 1)) * 32 + ((lane >> 2) & 3) * 8 + (lane & 2) * 2) * 4, r.x, r.y, r.z, r.w);
      }
      named_bar_sync(9, 256);
      if (t2 < 64) {
        float gp[8], up[8];
        #pragma unroll
        for (int w = 0; w < 8; w++) { gp[w] = lds_f32(sbase + OG_SRED + w * 512 + t2 * 4); up[w] = lds_f32(sbase + OG_SRED + w * 512 + 256 + t2 * 4); }
        const float gs = ((gp[0] + gp[1]) + (gp[2] + gp[3])) + ((gp[4] + gp[5]) + (gp[6] + gp[7]));
        const float us = ((up[0] + up[1]) + (up[2] + up[3])) + ((up[4] + up[5]) + (up[6] + up[7]));
        asm volatile("st.shared.u16 [%0], %1;" :: "r"(sbase + OG_SGU + ((t2 & ~15) + ((t2 >> 1) & 3) * 4 + ((t2 >> 3) & 1) * 2 + (t2 & 1)) * 2), "h"((uint16_t)pack_bf16(silu_bf(rbf(gs)) * rbf(us), 0.f)) : "memory");
      }
      named_bar_sync(9, 256);
      TL_MARK2(20, threadIdx.x == 128);
      float d[4][4];
      #pragma unroll
      for (int c = 0; c < 4; c++) { d[c][0] = 0.f; d[c][1] = 0.f; d[c][2] = 0.f; d[c][3] = 0.f; }
      #pragma unroll
      for (int st = 0; st < 2; st++) {
        const uint2 g = lds_u32x2(sbase + OG_SGU + ((lane >> 2) & 1) * 64 + st * 32 + (lane & 3) * 8);
        #pragma unroll
        for (int j = 0; j < 4; j++) {
          const uint32_t b0 = GEMV_B0(j, g, sel), b1 = GEMV_B1(j, g, sel);
          mma_bf16(d[j & 1], wd[4 * st + j].x, wd[4 * st + j].y, wd[4 * st + j].z, wd[4 * st + j].w, b0, b1);
          mma_bf16(d[2 + (j & 1)], wd[8 + 4 * st + j].x, wd[8 + 4 * st + j].y, wd[8 + 4 * st + j].z, wd[8 + 4 * st + j].w, b0, b1);
        }
      }
      #pragma unroll
      for (int e = 0; e < 4; e++) { d[0][e] += d[1][e]; d[2][e] += d[3][e]; }
      const float4 y0 = gemv_out(d[0], lane), y1 = gemv_out(d[2], lane);
      float* yp = g_ypart + (size_t)(blockIdx.x * 2 + (lane & 1)) * T_D + w8 * 128 + (lane >> 2) * 8 + (lane & 2) * 2;
      st_tagged4(yp, y0.x, y0.y, y0.z, y0.w);
      st_tagged4(yp + 64, y1.x, y1.y, y1.z, y1.w);
      named_bar_sync(9, 256);
      if (t2 == 0) hint_arrive(CNT_Y);
    }
    bulk_wait_read<0>();
    TL_MARK2(14, threadIdx.x == 128);
    TL_CLK(4, 1, threadIdx.x == 128);
}

#define OG_JOBS2 (16 - OG_JOBS)
__device__ __forceinline__ int help_njobs() { return blockIdx.x < 128 ? OG_JOBS : OG_JOBS2; }
__device__ __forceinline__ int help_job(int i) { return (i < OG_JOBS ? 16 * i + (blockIdx.x >> 7) * 2 : 112 + (i - OG_JOBS) * 2) + (blockIdx.x & 3) * 4; }
__device__ __noinline__ void store_warp(uint32_t sbase, const CUtensorMap* tmO, int item0, int n_items) {
  if (elect_one()) {
    const uint32_t bars = sbase + AT_SBAR, b_q0 = bars + 80, b_ob = bars + 96, b_ordy = bars + 104, b_acq = bars + 264;
    const unsigned int* cnt = &g_hcnt[32 * (1 + OG_MT(blockIdx.x)) + 2];
    #pragma unroll 1
    for (int q = 0; q < 4 * n_items; q++) {
      const int item = item0 + (q >> 2) * 128, h = (q >> 1) & 1, w = q & 1;
      const bool last = (q >> 2) == n_items - 1;
      if (q == 4 * n_items - 4) { mbar_wait(bars + 288, 0); red_release_add(&g_hcnt[1], 1u); }
      mbar_wait(b_ordy + 8 * (q & 3), q >> 2);
      store_o(tmO, (h ? (last ? sbase + AT_SQ + 32768 : sbase + 2 * 32768) : sbase + AT_SQ) + w * 8192, (item >> 4) * 2 + h, (item & 15) * 128 + w * 64);
      if (w) {
        bulk_wait_read<0>();
        mbar_arrive(h ? b_ob : b_q0);
        bulk_wait<0>();
        fence_proxy_async_global();
        asm volatile("fence.acq_rel.gpu;" ::: "memory");
        hint_arrive(&g_hcnt[32 * (1 + (item & 15)) + 2 + (item >> 7)]);
        if (!h && item < 128) hint_arrive(&g_hcnt[2]);
        if (q == 5) { spin_until(cnt, 16u); mbar_arrive(b_acq); }
      }
    }
    if (n_items == 1) {
      #pragma unroll 1
      for (int i = 0; i < help_njobs(); i++) {
        mbar_wait(b_acq + 16, i & 1);
        TL_MARK2(23, i == OG_JOBS - 1);
        red_release_add(&g_hcnt[32 * (1 + (help_job(i) >> 3)) + 4 + ((help_job(i) >> 1) & 3)], 1u);
        TL_MARK2(4, i == OG_JOBS - 1);
        if (i == PRE_X - 1) { spin_until(&g_hcnt[1], 132u); mbar_arrive(b_acq + 32); }
      }
    }
    if (blockIdx.x < 128) {
      if (n_items == 1) { spin_until(cnt, 16u); mbar_arrive(b_acq); }
      spin_until(&g_hcnt[0], 128u); spin_until(cnt + 1, 16u); mbar_arrive(b_acq + 80);
    }
  }
}

__global__ void __launch_bounds__(384, 1)
fused_kernel(const __grid_constant__ CUtensorMap tmH, const __grid_constant__ CUtensorMap tmW, const __grid_constant__ CUtensorMap tmK,
            const __grid_constant__ CUtensorMap tmV, const __grid_constant__ CUtensorMap tmO, const __grid_constant__ CUtensorMap tmOl, const __grid_constant__ CUtensorMap tmWo,
            const __grid_constant__ CUtensorMap tmX, const __grid_constant__ CUtensorMap tmOut, const __grid_constant__ CUtensorMap tmM, uint32_t zero,
            const uint8_t* __restrict__ pf_wo, const bf16* __restrict__ kc, const bf16* __restrict__ vc,
            const bf16* __restrict__ x, const bf16* __restrict__ cvec, const bf16* __restrict__ w_mod, const bf16* __restrict__ w_r,
            const bf16* __restrict__ w_gate, const bf16* __restrict__ w_up, const bf16* __restrict__ w_down, bf16* __restrict__ out)
{
  extern __shared__ __align__(1024) uint8_t smem_raw[];
  const uint32_t sbase = smem_u32(smem_raw);
  const uint32_t bars = sbase + AT_SBAR;
  const uint32_t b_full = bars, b_empty = bars + 40;
  const uint32_t b_q0 = bars + 80, b_q1 = bars + 88;
  const uint32_t b_ob = bars + 96;
  const uint32_t b_ordy = bars + 104;
  const uint32_t b_pin = bars + 136;
  const uint32_t b_head = bars + 144;
  const uint32_t b_go = bars + 152;
  const uint32_t b_x = bars + 160;
  const int wg = __shfl_sync(0xffffffffu, threadIdx.x >> 7, 0);
  const bool single = blockIdx.x >= AT_NFULL;
  const int item0 = __shfl_sync(0xffffffffu, blockIdx.x < 128 ? (int)blockIdx.x : (int)blockIdx.x + 124, 0), n_items = __shfl_sync(0xffffffffu, single ? 1 : 2, 0);
  TL_START(3);
  if (threadIdx.x == 0) {
    if (sbase & 1023u) __trap();
    for (int i = 0; i < 5; i++) { mbar_init(b_full + 8 * i, 1); mbar_init(b_empty + 8 * i, 2); }
    mbar_init(b_q0, 1); mbar_init(b_q1, 8); mbar_init(b_ob, 1);
    for (int i = 0; i < 4; i++) mbar_init(b_ordy + 8 * i, 4);
    mbar_init(b_pin, 1); mbar_init(b_head, blockIdx.x < 128 ? 8 : 1); mbar_init(b_go, 1); mbar_init(b_x, 1);
    mbar_init(bars + 168, 2); mbar_init(bars + 176, 1); mbar_init(bars + 184, 8); mbar_init(bars + 192, 2);
    mbar_init(bars + 200, 8); mbar_init(bars + 208, 4); mbar_init(bars + 216, 1); mbar_init(bars + 264, 1); mbar_init(bars + 272, 1); mbar_init(bars + 280, 8); mbar_init(bars + 288, 1); mbar_init(bars + 296, 1); mbar_init(bars + 304, 8); mbar_init(bars + 312, 1); mbar_init(bars + 320, 1); mbar_init(bars + 328, 1); mbar_init(bars + 344, 1); mbar_init(bars + 352, 1);
    fence_mbar_init();
  }

  if (wg == 0) {
    reg_dealloc<AT_PREG>();
    if (threadIdx.x < 32) { __syncwarp(); named_bar_arrive(6, 384); }
    if (threadIdx.x >= 64) {
      named_bar_sync(6, 384);
      if (blockIdx.x < 128) {
        named_bar_sync(threadIdx.x >= 96 ? 8 : 9, 288);
        if ((threadIdx.x & 31) == 0) red_release_add(&g_hcnt[32 * (1 + (blockIdx.x >> 3)) + (threadIdx.x >= 96)], 1u);
        TL_MARK2(11, threadIdx.x == 64);
      }
      if (blockIdx.x < 128) {
        mbar_wait(MOD_AT, 0);
        mod_rest(sbase + OG_SCOL, b_q1, threadIdx.x - 64, cvec, w_mod, w_r);
      }
    } else if (threadIdx.x >= 32) {
      named_bar_sync(6, 384);
      store_warp(sbase, &tmO, item0, n_items);
      __syncwarp();
    } else {
     if (elect_one()) {
      const uint64_t pol = policy_evict_first();
      if (blockIdx.x < 128) {
        mbar_expect_tx(b_x, 32768);
        if (X_DLY) { const uint32_t c0 = clock_lo(); while (clock_lo() - c0 < X_DLY) {} }
        bulk_load_hint(sbase + 4 * 32768, x + (size_t)blockIdx.x * 16 * T_D, 32768, b_x, pol);
      }
      prefetch_tmap(&tmW); prefetch_tmap(&tmM); prefetch_tmap(&tmH); prefetch_tmap(&tmWo); prefetch_tmap(&tmOl);
      {
        const uint32_t c0 = clock_lo();
        while (clock_lo() - c0 < W_DLY) {}
        if (blockIdx.x < 128 && (blockIdx.x & 15) >= 4 * H_SPLIT) {
          mbar_expect_tx(bars + 328, 32768);
          tma_load_2d_hint(sbase + 3 * 32768, &tmM, (blockIdx.x & 31) * 64, (blockIdx.x >> 5) * 256, bars + 328, pol);
        }
        while (clock_lo() - c0 < W_DLY + W_FIRST) {}
      }
      uint32_t slot = 0, ph = 1;
      if (ALIGN) { uint32_t sm; asm volatile("mov.u32 %0, %%smid;" : "=r"(sm)); g_smid[32 + blockIdx.x] = sm; }
      #pragma unroll 1
      for (int it = 0; it < n_items; it++) {
        const int item = item0 + it * 128, hp = item >> 4, qt = item & 15;
        const bool first = it == 0;
        #pragma unroll 1
        for (int j = 0; j < T_D / 64; j++) {
          const uint32_t sl = ring_slot(qp_pos(j, it)), fb = b_full + 8 * sl;
          mbar_wait(b_empty + 8 * sl, ring_par(qp_pos(j, it)) ^ ((j >> 2) & 1) ^ 1);
          if (first && j == 3) mbar_wait(b_head, 0);
          mbar_expect_tx(fb, 49152);
          tma_load_3d_hint(sbase + sl * 32768, &tmW, j * 64, hp * 4, fb, pol);
          if (first && j < PRE_B) {
            if (j == PRE_B - 1) {
              spin_until(&g_hcnt[32 * (1 + qt)], 8u);
              TL_MARK2(16, true);
              fence_proxy_async_global();
              #pragma unroll 1
              for (int i = 0; i < PRE_B; i++) tma_load_2d(sbase + AT_SQ + i * 16384, &tmH, i * 64, qt * 128, b_full + 8 * i);
              mbar_arrive(b_go);
            }
          } else {
            if (first && j == 4 * H_SPLIT) { spin_until(&g_hcnt[32 * (1 + qt) + 1], 8u); fence_proxy_async_global(); }
            if (!first && (j == 0 || j == 2)) mbar_wait(j ? b_q1 : b_q0, 0);
            tma_load_2d_hint(sbase + AT_SQ + (j & 3) * 16384, &tmH, j * 64, qt * 128, fb, first ? pol_normal() : pol);
          }
        }
        #pragma unroll 1
        for (int j = 0; j < 4 * AT_NBLK; j++) {
          const bool isv = (j > 0 && !(j & 1)) || j == 4 * AT_NBLK - 1;
          const int row = hp * 2 * T_SEQ + (isv ? (j - 1) >> 1 : (j + 1) >> 1) * 128;
          const uint32_t fb = b_full + 8 * slot;
          mbar_wait(b_empty + 8 * slot, ph);
          if (!first && j == 3) mbar_wait(b_ob, 0);
          if (j == 4 && it == n_items - 1) mbar_arrive(bars + 288);
          if (ALIGN && j == AL_P && it == 1) mbar_arrive(bars + 312);
          mbar_expect_tx(fb, 32768);
          tma_load_3d_hint(sbase + slot * 32768, isv ? &tmV : &tmK, row, 0, fb, pol);
          if (it == 1 && isv && j >= 2 * WO_LATE && j < 2 * WO_LATE + 32 && blockIdx.x < OG_NKB)
            l2_prefetch_bulk(pf_wo + (size_t)own_kb(blockIdx.x) * 131072 + ((j >> 1) - WO_LATE) * 8192, 8192);
          if (++slot == 5) { slot = 0; ph ^= 1; }
        }
      }
      if (__builtin_expect(single, 0)) {
        spin_until(&g_hcnt[2], 128u);
        fence_proxy_async_global();
        const int nj = OG_JOBS * OG_PRE + (help_njobs() - OG_JOBS) * OG_PRE2;
        int ji = 0, job = help_job(0), kk = 0;
        #pragma unroll 1
        for (int j = 0; j < nj; j++) {
          const uint32_t sl = ring_slot(qp_pos(j, 1)), fb = b_full + 8 * sl;
          mbar_wait(b_empty + 8 * sl, ring_par(qp_pos(j, 1)) ^ ((j >> 2) & 1) ^ 1);
          mbar_expect_tx(fb, 49152);
          tma_load_3d_hint(sbase + sl * 32768, &tmWo, pre_kb(kk) * 64, OG_NT(job) * 2, fb, HPOL_B);
          tma_load_3d_hint(sbase + sl * 32768 + 16384, &tmWo, pre_kb(kk) * 64, OG_NT(job) * 2 + 2, fb, HPOL_B);
          if (j == 0 || j == 2) mbar_wait(j ? b_ob : b_q0, 0);
          tma_load_2d_hint(sbase + AT_SQ + (j & 3) * 16384, &tmOl, pre_kb(kk) * 64, OG_MT(job) * 128, fb, HPOL_A);
          if (++kk == (ji < OG_JOBS ? OG_PRE : OG_PRE2)) { kk = 0; job = help_job(++ji); }
        }
      }
      if (blockIdx.x < 128) {
        if (single) mbar_wait(b_x, 1);
        tail_producer(sbase, 0, pol, &tmOl, &tmWo, &tmX);
      }
     }
    }
    named_bar_sync(12 + (threadIdx.x >> 5), 32);
    if (blockIdx.x < 128) tail_exchange(sbase, w_down, w_r, x, out);
  } else {
    if (blockIdx.x < 128) head_phase(sbase + AT_SQ + 49152, sbase + 4 * 32768, b_x, b_go, b_head, threadIdx.x - 128, zero, cvec, w_mod);
    else { named_bar_sync(6, 384); if (threadIdx.x == 128) mbar_arrive(b_head); }
    TL_MARK2(0, threadIdx.x == 128);
    reg_alloc<AT_CREG>();
    const int cwg = wg - 1;
    const int tid = threadIdx.x & 127;
    const int warp = tid >> 5, lane = tid & 31;
    const uint32_t dbase = (sbase & 0x3FFFFu) >> 4;
    const uint32_t k_base = dbase + (1u << 16);
    const uint32_t v_base = dbase + (1024u << 16);
    const uint32_t w_base = dbase + (512u << 16);
    const uint32_t q_lo = dbase + ((AT_SQ + cwg * 8192) >> 4) + (1u << 16);
    const uint32_t frag = cwg * 8192 + (16 * warp + (lane & 7) + 8 * ((lane >> 3) & 1)) * 128;
    if (cwg == 1) named_bar_arrive(1, 256);
    bool raw = false;
    uint4 pre[8];
    #pragma unroll 1
    for (int it = 0; it < n_items; it++) {
      const bool more = it + 1 < n_items;
      constexpr int nkb = T_D / 64;
      const int ta = __shfl_sync(0xffffffffu, 4 * it, 0);
      float acc[128];
      {
        FS(2 * it, 0);
        #pragma unroll
        for (int i = 0; i < 128; i++) asm volatile("" : "=f"(acc[i]));
        {
          const uint32_t slot = ring_slot(ta), b_lo = w_base + slot * 2048;
          mbar_wait(b_full + 8 * slot, ring_par(ta));
          wgmma_fence();
          wgmma_m64n256k16_ss_tb<0, 0>(acc, q_lo, b_lo, 0);
          wgmma_m64n256k16_ss_tb<2, 128>(acc, q_lo, b_lo, 1);
          wgmma_m64n256k16_ss_tb<4, 256>(acc, q_lo, b_lo, 1);
          wgmma_m64n256k16_ss_tb<6, 384>(acc, q_lo, b_lo, 1);
          wgmma_commit();
        }
        #pragma unroll 1
        for (int j = NOZERO; j < nkb; j++) {
          const uint32_t slot = ring_slot(qp_pos(j, ta >> 2));
          mbar_wait(b_full + 8 * slot, ring_par(qp_pos(j, ta >> 2)) ^ ((j >> 2) & 1));
          if (QP_STAG > 0 && cwg == 1 && j == nkb - QP_STAG) named_bar_sync(7, 256);
          const uint32_t a_lo = q_lo + (j & 3) * 1024, b_lo = w_base + slot * 2048;
          wgmma_fence();
          wgmma_m64n256k16_ss_tb<0, 0>(acc, a_lo, b_lo, 1);
          wgmma_m64n256k16_ss_tb<2, 128>(acc, a_lo, b_lo, 1);
          wgmma_m64n256k16_ss_tb<4, 256>(acc, a_lo, b_lo, 1);
          wgmma_m64n256k16_ss_tb<6, 384>(acc, a_lo, b_lo, 1);
          wgmma_commit();
          if (QP_STAG > 0 && cwg == 0 && j == nkb - 1) named_bar_arrive(7, 256);
          if (j > 0) {
            wgmma_wait<1>();
            if (tid == 0) mbar_arrive(b_empty + 8 * ring_slot(qp_pos(j - 1, ta >> 2)));
          }
        }
        wgmma_wait<0>();
        fence_regs(acc);
        FS(2 * it, 1);
        TL_MARK2(29, threadIdx.x == 256 && it == 0);
        if (tid == 0) mbar_arrive(b_empty + 24);
      }
      float o[64], s[64];
      uint32_t p[32], q[32];
      #pragma unroll
      for (int i = 0; i < 32; i++) q[i] = pack_bf16(acc[2 * i] * AT_C, acc[2 * i + 1] * AT_C);
      zero_regs(s);
      const uint32_t sq = sbase + AT_SQ + cwg * 8192;
      const bool last_wg1 = cwg == 1 && !more;
      float mc0, mc1, al0 = 1.0f, al1 = 1.0f, l0 = 0.f, l1 = 0.f, lp0 = 0.f, lp1 = 0.f;
      bool redo0 = false;
      FS(2 * it, 2);
      mbar_wait(b_full + 8 * ring_slot(ta), ring_par(ta));
      named_bar_sync(1 + cwg, 256);
      FS(2 * it, 3);
      issue_qk(s, q, k_base + ring_slot(ta) * 2048);
      named_bar_arrive(1 + (cwg ^ 1), 256);
      bool ready = mbar_test(b_full + 8 * ring_slot(ta + 1), ring_par(ta + 1)) & mbar_test(b_full + 8 * ring_slot(ta + 2), ring_par(ta + 2));
      stage_q<16>(acc, AT_C, sbase + AT_SQ + frag, lane);
      wgmma_wait<0>();
      fence_regs(s);
      if (tid == 0) mbar_arrive(b_empty + 8 * ring_slot(ta));
      mc0 = 0.f; mc1 = 0.f;
      if (!raw) {
        raw = softmax_mode(s, mc0, mc1);
        if (__builtin_expect(!raw, 0)) softmax_sub(s, mc0, mc1);
      }
      softmax_exp<0, 64>(s);
      #pragma unroll
      for (int J = 0; J < 16; J += 2)
        stmatrix_x4(sbase + AT_SQ + frag + (J >> 3) * 16384 + ((((J & 7) + (lane >> 4)) ^ (lane & 7)) << 4), q[2 * J], q[2 * J + 1], q[2 * J + 2], q[2 * J + 3]);
      pack_p(p, s);
      zero_regs(o);
      FS(2 * it, 4);
      uint32_t ks = ring_slot(ta + 1), vs = ring_slot(ta + 2), kp = ring_par(ta + 1), vp = ring_par(ta + 2);
      auto finish_head = [&]() {
        FS(2 * it, 5);
        redo0 = finish_l(lp0, lp1);
        if (!redo0) stage_o(o, lp0, lp1, sbase + AT_SQ + frag, lane);
        FS(2 * it + 1, 4);
      };
      if (!ready) { mbar_wait(b_full + 8 * ks, kp); mbar_wait(b_full + 8 * vs, vp); }
      #pragma unroll 1
      for (int n = 1; n < 2 * AT_NBLK; n++) {
        named_bar_sync(1 + cwg, 256);
        issue_qk(s, q, k_base + ks * 2048);
        if (n == AT_NBLK + 1) finish_head();
        issue_pv(o, p, v_base + vs * 2048, (n & 15) != 1);
        asm volatile("{\n.reg .pred p;\nsetp.ne.u32 p, %0, 0;\n@p bar.arrive 1, 256;\n@!p bar.arrive 2, 256;\n}\n" :: "r"(cwg) : "memory");
        wgmma_wait<1>();
        fence_regs(s);
        if (tid == 0) mbar_arrive(b_empty + 8 * ks);
        if (__builtin_expect(!raw || (uint32_t)(n - (AT_NBLK - 1)) <= 2u, 0)) {
          if (n == AT_NBLK + 1 && !redo0) {
            fence_proxy_async();
            __syncwarp();
            if (lane == 0) mbar_arrive(b_ordy + 8 * cwg);
          }
          if (n == AT_NBLK - 1) {
            #pragma unroll
            for (int J = 0; J < 16; J += 2)
              ldmatrix_x4(sbase + AT_SQ + 32768 + frag + (J >> 3) * 16384 + ((((J & 7) + (lane >> 4)) ^ (lane & 7)) << 4), q[2 * J], q[2 * J + 1], q[2 * J + 2], q[2 * J + 3]);
          }
          if (!raw) {
            const float m0 = mc0, m1 = mc1;
            const bool ok = softmax_mode(s, mc0, mc1);
            if (n == AT_NBLK) raw = ok;
            else {
              mc0 = mc0 - AT_HEAD > m0 ? mc0 : m0; mc1 = mc1 - AT_HEAD > m1 ? mc1 : m1;
              al0 = ex2_approx(m0 - mc0); al1 = ex2_approx(m1 - mc1);
            }
            if (!raw) softmax_sub(s, mc0, mc1);
          }
        }
        softmax_exp<0, AT_SPLIT>(s);
        add_rowsum(p, l0, l1);
        if (tid == 0) {
          uint32_t dep = zero & __float_as_uint(l0) & __float_as_uint(l1);
          #pragma unroll
          for (int i = AT_SPLIT - AT_PIN - PINB; i < AT_SPLIT - PINB; i += 2) dep &= __float_as_uint(s[i]) & __float_as_uint(s[i + 1]);
          mbar_arrive(b_pin + dep);
        }
        wgmma_wait<0>();
        fence_regs(o);
        if (tid == 0) mbar_arrive(b_empty + 8 * vs);
        ks += 2; if (ks >= 5) { ks -= 5; kp ^= 1; }
        vs += 2; if (vs >= 5) { vs -= 5; vp ^= 1; }
        ready = mbar_test(b_full + 8 * ks, kp) & mbar_test(b_full + 8 * vs, vp);
        softmax_exp<AT_SPLIT, 64>(s);
        pack_p(p, s);
        if (n == AT_NBLK) { lp0 = l0; lp1 = l1; l0 = 0.f; l1 = 0.f; }
        if (__builtin_expect(!raw || !ready, 0)) {
        if (!raw && __any_sync(0xffffffffu, al0 != 1.0f || al1 != 1.0f)) {
          rescale_o(o, al0, al1);
          l0 *= al0; l1 *= al1;
          al0 = 1.0f; al1 = 1.0f;
        }
        if (!ready && n < 2 * AT_NBLK - 1) {
          mbar_wait(b_full + 8 * ks, kp);
          mbar_wait(b_full + 8 * vs, vp);
        }
        }
      }
      FS(2 * it + 1, 5);
      const uint32_t vl = ring_slot(ta + 63);
      vs = ring_slot(ta + 62);
      const uint32_t ob = more ? sbase + vs * 32768 : sbase + AT_SQ + 32768;
      mbar_wait(b_full + 8 * vl, ring_par(ta + 63));
      issue_pv(o, p, v_base + vl * 2048, 1);
      block_end(zero, b_pin);
      add_rowsum(p, l0, l1);
      const bool overflow = finish_l(l0, l1);
      if (!overflow && lane == 0) mbar_arrive(b_q1);
      #pragma unroll
      for (int i = 0; i < 8; i++) asm volatile("mov.b64 {%0, %1}, 0;\nmov.b64 {%2, %3}, 0;" : "=r"(pre[i].x), "=r"(pre[i].y), "=r"(pre[i].z), "=r"(pre[i].w));
      const bool want_pre = !more && blockIdx.x < OG_MOE, got_pre = want_pre && __all_sync(0xffffffffu, mbar_test(bars + 272, 0));
      if (got_pre) load_pre(pre, sbase, AT_SQ, threadIdx.x - 128);
      mbar_wait(b_empty + 8 * vs, ring_par(ta + 62));
      wgmma_wait<0>();
      fence_regs(o);
      if (tid == 0) mbar_arrive(b_empty + 8 * vl);
      FS(2 * it + 1, 6);
      if (overflow) {
        attn_rows_exact(sq + 32768, ob + cwg * 8192, 4 * ta + 1, kc, vc);
        __syncwarp();
        if (lane == 0) mbar_arrive(b_q1);
      } else stage_o(o, l0, l1, ob + frag, lane);
      if (redo0) attn_rows_exact(sq, sq, 4 * ta, kc, vc);
      fence_proxy_async();
      __syncwarp();
      if (lane == 0) {
        if (redo0) mbar_arrive(b_ordy + 8 * cwg);
        mbar_arrive(b_ordy + 16 + 8 * cwg);
      }
      if (want_pre && !got_pre) load_pre(pre, sbase, AT_SQ, threadIdx.x - 128);
      if (redo0 || overflow) raw = false;
      named_bar_sync(3 + cwg, 128);
      FS(2 * it + 1, 7);
    }
    if (ARV_IMM && cwg == 0) named_bar_arrive(1, 256);
    if (__builtin_expect(single, 0)) {
      float acc[128];
      uint32_t j = 0, pk[64];
      #pragma unroll
      for (int i = 0; i < 64; i++) asm volatile("" : "=f"(acc[2 * i]), "=f"(acc[2 * i + 1]), "=r"(pk[i]));
      uint4* dst = g_pre;
      int left = 0;
      auto put = [&](bool last) {
        #pragma unroll
        for (int i = 0; i < PUT_N; i++) dst[i * 256] = make_uint4(pk[4 * i], pk[4 * i + 1], pk[4 * i + 2], pk[4 * i + 3]);
        dst += PUT_N * 256;
        #pragma unroll
        for (int i = 0; i < 64 - 4 * PUT_N; i++) asm volatile("mov.b32 %0, %1;" : "=r"(pk[i]) : "r"(pk[i + 4 * PUT_N]));
        __syncwarp();
        if (last && lane == 0) mbar_arrive(bars + 280);
      };
      #pragma unroll 1
      for (int ji = 0; ji < help_njobs(); ji++) {
        const int nk = ji < OG_JOBS ? OG_PRE : OG_PRE2;
        #pragma unroll 1
        for (int kk = 0; kk < nk; kk++, j++) {
          const uint32_t slot = ring_slot(qp_pos(j, 1));
          mbar_wait(b_full + 8 * slot, ring_par(qp_pos(j, 1)) ^ ((j >> 2) & 1));
          if (H_STAG > 0 && cwg == 1 && kk == nk - H_STAG) named_bar_sync(7, 256);
          const uint32_t a_lo = q_lo + (j & 3) * 1024, b_lo = w_base + slot * 2048;
          wgmma_fence();
          wgmma_m64n256k16_ss_tb<0, 0>(acc, a_lo, b_lo, kk != 0);
          wgmma_m64n256k16_ss_tb<2, 128>(acc, a_lo, b_lo, 1);
          wgmma_m64n256k16_ss_tb<4, 256>(acc, a_lo, b_lo, 1);
          wgmma_m64n256k16_ss_tb<6, 384>(acc, a_lo, b_lo, 1);
          wgmma_commit();
          if (H_STAG > 0 && cwg == 0 && kk == nk - 1) named_bar_arrive(7, 256);
          wgmma_wait<1>();
          if (kk > 0 && tid == 0) mbar_arrive(b_empty + 8 * ring_slot(qp_pos(j - 1, 1)));
          #pragma unroll 1
          for (int i = ji == OG_JOBS ? 0 : 16 / PUT_N - 1; i < 16 / PUT_N && left > 0; i++) put(--left == 0);
        }
        wgmma_wait<0>();
        fence_regs(acc);
        if (tid == 0) mbar_arrive(b_empty + 8 * ring_slot(qp_pos(j - 1, 1)));
        #pragma unroll
        for (int i = 0; i < 64; i++) pk[i] = pack_bf16(acc[2 * i], acc[2 * i + 1]);
        left = 16 / PUT_N;
        if (ji == PRE_X) mbar_wait(bars + 296, 0);
        dst = g_pre + help_job(ji) * 2048 + threadIdx.x - 128;
      }
      #pragma unroll
      for (int i = 0; i < 16; i++) dst[i * 256] = make_uint4(pk[4 * i], pk[4 * i + 1], pk[4 * i + 2], pk[4 * i + 3]);
      __syncwarp();
      if (lane == 0) mbar_arrive(bars + 280);
      named_bar_sync(5, 256);
      if (threadIdx.x == 128) {
        #pragma unroll 1
        for (int i = 0; i < 5; i++) {
          constexpr int n = OG_JOBS * OG_PRE;
          const int used = i == 3 ? 0 : (n + 3 - (i == 4 ? 3 : i)) / 4;
          if ((used ^ (i < 4)) & 1) {
            mbar_arrive(b_full + 8 * ring_slot(4 + i));
            mbar_arrive(b_empty + 8 * ring_slot(4 + i)); mbar_arrive(b_empty + 8 * ring_slot(4 + i));
          }
        }
        mbar_arrive(b_x);
      }
      named_bar_sync(5, 256);
      #pragma unroll
      for (int i = 0; i < 8; i++) pre[i] = make_uint4(0u, 0u, 0u, 0u);
    }
    TL_CLK(3, 1, threadIdx.x == 128);
    TL_CTA(1, threadIdx.x == 256);
    TL_END(3, tid == 0);
    TL_MARK2(19, tid == 0 && !single);
    if (blockIdx.x < 128) {
      tail_consumer(sbase, &tmOut, pre, cwg, w_gate, w_up);
    }
  }
}

typedef CUresult (*PFN_encodeTiled)(CUtensorMap*, CUtensorMapDataType, cuuint32_t, void*, const cuuint64_t*, const cuuint64_t*,
                                    const cuuint32_t*, const cuuint32_t*, CUtensorMapInterleave, CUtensorMapSwizzle,
                                    CUtensorMapL2promotion, CUtensorMapFloatOOBfill);

CUtensorMap make_map_2d(PFN_encodeTiled enc, const void* ptr, uint64_t inner, uint64_t outer, uint64_t stride_bytes, uint32_t box_inner, uint32_t box_outer) {
  CUtensorMap m;
  cuuint64_t gd[2] = {inner, outer}; cuuint64_t gs[1] = {stride_bytes};
  cuuint32_t bx[2] = {box_inner, box_outer}; cuuint32_t es[2] = {1, 1};
  enc(&m, CU_TENSOR_MAP_DATA_TYPE_BFLOAT16, 2, const_cast<void*>(ptr), gd, gs, bx, es, CU_TENSOR_MAP_INTERLEAVE_NONE,
      CU_TENSOR_MAP_SWIZZLE_128B, CU_TENSOR_MAP_L2_PROMOTION_L2_128B, CU_TENSOR_MAP_FLOAT_OOB_FILL_NONE);
  return m;
}

CUtensorMap make_map_3d(PFN_encodeTiled enc, const void* ptr, uint64_t cols, uint64_t rows, uint32_t box_rows, uint32_t chunks) {
  CUtensorMap m;
  cuuint64_t gd[3] = {64, rows, cols / 64}; cuuint64_t gs[2] = {cols * 2, 128};
  cuuint32_t bx[3] = {64, box_rows, chunks}; cuuint32_t es[3] = {1, 1, 1};
  enc(&m, CU_TENSOR_MAP_DATA_TYPE_BFLOAT16, 3, const_cast<void*>(ptr), gd, gs, bx, es, CU_TENSOR_MAP_INTERLEAVE_NONE,
      CU_TENSOR_MAP_SWIZZLE_128B, CU_TENSOR_MAP_L2_PROMOTION_L2_128B, CU_TENSOR_MAP_FLOAT_OOB_FILL_NONE);
  return m;
}

}

extern "C" void kernel_launch(void* const* d_in, const int* in_sizes, int n_in, void* d_out, int out_size) {
  const bf16* x      = (const bf16*)d_in[0];
  const bf16* kc     = (const bf16*)d_in[1];
  const bf16* vc     = (const bf16*)d_in[2];
  const bf16* wq     = (const bf16*)d_in[3];
  const bf16* wo     = (const bf16*)d_in[4];
  const bf16* w_r    = (const bf16*)d_in[6];
  const bf16* w_gate = (const bf16*)d_in[7];
  const bf16* w_up   = (const bf16*)d_in[8];
  const bf16* w_down = (const bf16*)d_in[9];
  const bf16* cvec   = (const bf16*)d_in[10];
  const bf16* w_mod  = (const bf16*)d_in[11];
  bf16* out = (bf16*)d_out;

  static PFN_encodeTiled enc = nullptr;
  static void *p_h = nullptr, *p_o = nullptr;
  if (!enc) {
    void* fn = nullptr; cudaDriverEntryPointQueryResult qres;
    cudaGetDriverEntryPoint("cuTensorMapEncodeTiled", &fn, cudaEnableDefault, &qres);
    enc = (PFN_encodeTiled)fn;
    cudaGetSymbolAddress(&p_h, g_pre);
    p_h = (uint4*)p_h + 16 * PRE_X * 2048;
    cudaGetSymbolAddress(&p_o, g_o);
    cudaFuncSetAttribute(fused_kernel, cudaFuncAttributeMaxDynamicSharedMemorySize, (int)AT_SMEM);
  }
  const CUtensorMap tm_h   = make_map_2d(enc, p_h, T_D, T_SEQ, T_D * 2, 64, 128);
  const CUtensorMap tm_wq  = W3D ? make_map_3d(enc, wq, T_DQKV, T_D, 64, 4) : make_map_2d(enc, wq, T_DQKV, T_D, T_DQKV * 2, 64, 64);
  const CUtensorMap tm_k   = KV3D ? make_map_3d(enc, kc, T_DH, (uint64_t)T_NH * T_SEQ, 128, 2) : make_map_2d(enc, kc, T_DH, (uint64_t)T_NH * T_SEQ, T_DH * 2, 64, 128);
  const CUtensorMap tm_v   = KV3D ? make_map_3d(enc, vc, T_DH, (uint64_t)T_NH * T_SEQ, 128, 2) : make_map_2d(enc, vc, T_DH, (uint64_t)T_NH * T_SEQ, T_DH * 2, 64, 128);
  const CUtensorMap tm_ost = make_map_2d(enc, p_o, T_DQKV, T_SEQ, T_DQKV * 2, 64, 64);
  const CUtensorMap tm_old = make_map_2d(enc, p_o, T_DQKV, T_SEQ, T_DQKV * 2, 64, 128);
  const CUtensorMap tm_wo  = make_map_3d(enc, wo, T_D, T_DQKV, 64, 2);
  const CUtensorMap tm_x   = make_map_3d(enc, w_down, T_D, T_F, 32, 8);

  const CUtensorMap tm_m   = make_map_2d(enc, w_mod, 6 * T_D, T_D, 6 * T_D * 2, 64, 256);
  const CUtensorMap tm_out = make_map_2d(enc, out, T_D, T_SEQ, T_D * 2, 64, 16);

  fused_kernel<<<132, 384, AT_SMEM, cudaStreamPerThread>>>(tm_h, tm_wq, tm_k, tm_v, tm_ost, tm_old, tm_wo, tm_x, tm_out, tm_m, 0u, (const uint8_t*)wo, kc, vc, x, cvec, w_mod,
             w_r, w_gate, w_up, w_down, out);
}
```

```cpp
#include <cuda_runtime.h>
#include <cuda_bf16.h>
#include <cuda.h>
#include <stdint.h>

namespace {

typedef __nv_bfloat16 bf16;

constexpr int T_SEQ = 2048, T_D = 1024, T_NH = 32, T_DH = 128, T_DQKV = 4096, T_F = 3584;

#define PRE_X 2
__device__ __align__(1024) uint4 g_pre[(16 * PRE_X + 128) * 2048];
#define g_h (reinterpret_cast<bf16*>(g_pre + 16 * PRE_X * 2048))
__device__ __align__(1024) bf16 g_o[T_SEQ * T_DQKV];
__device__ __align__(16) uint8_t g_col[8 * 1536];
__device__ __align__(16) float g_scal[64];
__device__ __align__(16) unsigned int g_hcnt[17 * 32];
__device__ unsigned int g_smid[168], g_tmax[128];
__device__ __align__(128) float g_modpart[4 * 2 * T_D];
struct __align__(2048) TailMail {
  float4 part1[T_SEQ * 8];
  uint32_t key[256];
  uint4 cand[16 * 2 * 2 * 128];
  uint32_t cnt[32];
  float ypart[(T_F / 32) * 2 * T_D];
};
__device__ TailMail g_mail;
#define g_part1 g_mail.part1
#define g_key g_mail.key
#define g_cand g_mail.cand
#define CNT_Y (g_mail.cnt)
#define g_ypart g_mail.ypart

__device__ __forceinline__ uint32_t smem_u32(const void* p) { return (uint32_t)__cvta_generic_to_shared(p); }
__device__ __forceinline__ void mbar_init(uint32_t bar, uint32_t cnt) { asm volatile("mbarrier.init.shared::cta.b64 [%0], %1;" :: "r"(bar), "r"(cnt)); }
__device__ __forceinline__ void mbar_expect_tx(uint32_t bar, uint32_t bytes) { asm volatile("mbarrier.arrive.expect_tx.shared::cta.b64 _, [%0], %1;" :: "r"(bar), "r"(bytes) : "memory"); }
__device__ __forceinline__ void mbar_arrive(uint32_t bar) { asm volatile("mbarrier.arrive.shared::cta.b64 _, [%0];" :: "r"(bar) : "memory"); }
__device__ __forceinline__ void mbar_wait(uint32_t bar, uint32_t parity) {
  asm volatile("{\n.reg .pred p;\nLAB_WAIT:\nmbarrier.try_wait.parity.shared::cta.b64 p, [%0], %1;\n@!p bra LAB_WAIT;\n}\n" :: "r"(bar), "r"(parity) : "memory");
}
__device__ __forceinline__ bool mbar_test(uint32_t bar, uint32_t parity) {
  uint32_t r; asm volatile("{\n.reg .pred p;\nmbarrier.test_wait.parity.shared::cta.b64 p, [%1], %2;\nselp.u32 %0, 1, 0, p;\n}\n" : "=r"(r) : "r"(bar), "r"(parity) : "memory");
  return r != 0;
}
__device__ __forceinline__ uint32_t clock_lo() { uint32_t c; asm volatile("mov.u32 %0, %%clock;" : "=r"(c)); return c; }
__device__ __forceinline__ void fence_mbar_init() { asm volatile("fence.mbarrier_init.release.cluster;" ::: "memory"); }
__device__ __forceinline__ void tma_load_2d(uint32_t dst, const CUtensorMap* map, int c0, int c1, uint32_t bar) {
  asm volatile("cp.async.bulk.tensor.2d.shared::cluster.global.mbarrier::complete_tx::bytes [%0], [%1, {%3, %4}], [%2];"
    :: "r"(dst), "l"(map), "r"(bar), "r"(c0), "r"(c1) : "memory");
}
__device__ __forceinline__ uint64_t policy_evict_first() {
  uint64_t p; asm volatile("createpolicy.fractional.L2::evict_first.b64 %0, 1.0;" : "=l"(p)); return p;
}
__device__ __forceinline__ void tma_load_2d_hint(uint32_t dst, const CUtensorMap* map, int c0, int c1, uint32_t bar, uint64_t pol) {
  asm volatile("cp.async.bulk.tensor.2d.shared::cluster.global.mbarrier::complete_tx::bytes.L2::cache_hint [%0], [%1, {%3, %4}], [%2], %5;"
    :: "r"(dst), "l"(map), "r"(bar), "r"(c0), "r"(c1), "l"(pol) : "memory");
}
__device__ __forceinline__ void tma_load_3d_hint(uint32_t dst, const CUtensorMap* map, int c1, int c2, uint32_t bar, uint64_t pol) {
  asm volatile("cp.async.bulk.tensor.3d.shared::cluster.global.mbarrier::complete_tx::bytes.L2::cache_hint [%0], [%1, {%3, %4, %5}], [%2], %6;"
    :: "r"(dst), "l"(map), "r"(bar), "n"(0), "r"(c1), "r"(c2), "l"(pol) : "memory");
}
__device__ __forceinline__ void tma_store_2d(const CUtensorMap* map, uint32_t src, int c0, int c1) {
  asm volatile("cp.async.bulk.tensor.2d.global.shared::cta.bulk_group [%0, {%2, %3}], [%1];" :: "l"(map), "r"(src), "r"(c0), "r"(c1) : "memory");
}
__device__ __forceinline__ void prefetch_tmap(const CUtensorMap* map) { asm volatile("prefetch.tensormap [%0];" :: "l"(map) : "memory"); }
__device__ __forceinline__ void l2_prefetch_bulk(const void* p, uint32_t bytes) {
  asm volatile("cp.async.bulk.prefetch.L2.global [%0], %1;" :: "l"(p), "r"(bytes) : "memory");
}
__device__ __forceinline__ void bulk_commit() { asm volatile("cp.async.bulk.commit_group;" ::: "memory"); }
template<int N> __device__ __forceinline__ void bulk_wait_read() { asm volatile("cp.async.bulk.wait_group.read %0;" :: "n"(N) : "memory"); }
template<int N> __device__ __forceinline__ void bulk_wait() { asm volatile("cp.async.bulk.wait_group %0;" :: "n"(N) : "memory"); }
__device__ __forceinline__ void named_bar_sync(int id, int nthreads) { asm volatile("bar.sync %0, %1;" :: "r"(id), "r"(nthreads) : "memory"); }
__device__ __forceinline__ void named_bar_arrive(int id, int nthreads) { asm volatile("bar.arrive %0, %1;" :: "r"(id), "r"(nthreads) : "memory"); }
__device__ __forceinline__ void pass_turn(int cwg) {
  asm volatile("{\n.reg .pred p;\nsetp.ne.u32 p, %0, 0;\n@p bar.arrive 1, 256;\n@!p bar.arrive 2, 256;\n}\n" :: "r"(cwg) : "memory");
}
__device__ __forceinline__ void wgmma_fence() { asm volatile("wgmma.fence.sync.aligned;" ::: "memory"); }
__device__ __forceinline__ void wgmma_commit() { asm volatile("wgmma.commit_group.sync.aligned;" ::: "memory"); }
template<int N> __device__ __forceinline__ void wgmma_wait() { asm volatile("wgmma.wait_group.sync.aligned %0;" :: "n"(N) : "memory"); }
template<int R> __device__ __forceinline__ void reg_alloc() { asm volatile("setmaxnreg.inc.sync.aligned.u32 %0;" :: "n"(R)); }
template<int R> __device__ __forceinline__ void reg_dealloc() { asm volatile("setmaxnreg.dec.sync.aligned.u32 %0;" :: "n"(R)); }
__device__ __forceinline__ bool elect_one() {
  uint32_t pred; asm volatile("{\n.reg .pred p;\nelect.sync _|p, 0xffffffff;\nselp.u32 %0, 1, 0, p;\n}\n" : "=r"(pred)); return pred != 0;
}
__device__ __forceinline__ uint32_t pack_bf16(float lo, float hi) {
  uint32_t r; asm("cvt.rn.bf16x2.f32 %0, %1, %2;" : "=r"(r) : "f"(hi), "f"(lo)); return r;
}
__device__ __forceinline__ void stmatrix_x4(uint32_t addr, uint32_t r0, uint32_t r1, uint32_t r2, uint32_t r3) {
  asm volatile("stmatrix.sync.aligned.m8n8.x4.shared.b16 [%0], {%1, %2, %3, %4};" :: "r"(addr), "r"(r0), "r"(r1), "r"(r2), "r"(r3) : "memory");
}
__device__ __forceinline__ void fence_proxy_async() { asm volatile("fence.proxy.async.shared::cta;" ::: "memory"); }
__device__ __forceinline__ float ex2_approx(float x) { float y; asm("ex2.approx.ftz.f32 %0, %1;" : "=f"(y) : "f"(x)); return y; }
template<int N> __device__ __forceinline__ void fence_regs(float (&r)[N]) {
  #pragma unroll
  for (int i = 0; i < N; i++) asm volatile("" : "+f"(r[i]) :: "memory");
}
template<int N> __device__ __forceinline__ void zero_regs(float (&r)[N]) {
  #pragma unroll
  for (int i = 0; i < N; i += 2) asm volatile("mov.b64 {%0, %1}, 0;" : "=f"(r[i]), "=f"(r[i + 1]));
}
__device__ __forceinline__ float rbf(float x) { return __uint_as_float(pack_bf16(0.f, x)); }
__device__ __forceinline__ float bflo(uint32_t v) { return __uint_as_float(v << 16); }
__device__ __forceinline__ float bfhi(uint32_t v) { return __uint_as_float(v & 0xffff0000u); }

#define XT(i) do {} while (0)
#define TL_START(k) do {} while (0)
#define TL_END(k, cond) do {} while (0)
#define TL_CTA(i, cond) do {} while (0)
#define FS(slot, k) do {} while (0)
#define TL_MARK2(k, cond) do {} while (0)
#define TL_CLK(k, i, cond) do {} while (0)

template <int OFFA, int OFFB>
__device__ __forceinline__ void wgmma_m64n256k16_ss_tb(float (&d)[128], uint32_t a_lo, uint32_t b_lo, int scaleD) {
  asm volatile("{\n.reg .pred p;\n.reg .b32 ta, tb;\n.reg .b64 da, db;\nsetp.ne.b32 p, %130, 0;\n"
    "add.u32 ta, %128, %131;\nadd.u32 tb, %129, %132;\n"
    "mov.b64 da, {ta, 0x40000040};\nmov.b64 db, {tb, 0x40000040};\n"
    "wgmma.mma_async.sync.aligned.m64n256k16.f32.bf16.bf16 "
    "{%0, %1, %2, %3, %4, %5, %6, %7, %8, %9, %10, %11, %12, %13, %14, %15, %16, %17, %18, %19, %20, %21, %22, %23, %24, %25, %26, %27, %28, %29, %30, %31, %32, %33, %34, %35, %36, %37, %38, %39, %40, %41, %42, %43, %44, %45, %46, %47, %48, %49, %50, %51, %52, %53, %54, %55, %56, %57, %58, %59, %60, %61, %62, %63, %64, %65, %66, %67, %68, %69, %70, %71, %72, %73, %74, %75, %76, %77, %78, %79, %80, %81, %82, %83, %84, %85, %86, %87, %88, %89, %90, %91, %92, %93, %94, %95, %96, %97, %98, %99, %100, %101, %102, %103, %104, %105, %106, %107, %108, %109, %110, %111, %112, %113, %114, %115, %116, %117, %118, %119, %120, %121, %122, %123, %124, %125, %126, %127}, "
    "da, db, p, 1, 1, 0, 1;\n}\n"
    : "+f"(d[0]), "+f"(d[1]), "+f"(d[2]), "+f"(d[3]), "+f"(d[4]), "+f"(d[5]), "+f"(d[6]), "+f"(d[7]), "+f"(d[8]), "+f"(d[9]), "+f"(d[10]), "+f"(d[11]), "+f"(d[12]), "+f"(d[13]), "+f"(d[14]), "+f"(d[15]), "+f"(d[16]), "+f"(d[17]), "+f"(d[18]), "+f"(d[19]), "+f"(d[20]), "+f"(d[21]), "+f"(d[22]), "+f"(d[23]), "+f"(d[24]), "+f"(d[25]), "+f"(d[26]), "+f"(d[27]), "+f"(d[28]), "+f"(d[29]), "+f"(d[30]), "+f"(d[31]), "+f"(d[32]), "+f"(d[33]), "+f"(d[34]), "+f"(d[35]), "+f"(d[36]), "+f"(d[37]), "+f"(d[38]), "+f"(d[39]), "+f"(d[40]), "+f"(d[41]), "+f"(d[42]), "+f"(d[43]), "+f"(d[44]), "+f"(d[45]), "+f"(d[46]), "+f"(d[47]), "+f"(d[48]), "+f"(d[49]), "+f"(d[50]), "+f"(d[51]), "+f"(d[52]), "+f"(d[53]), "+f"(d[54]), "+f"(d[55]), "+f"(d[56]), "+f"(d[57]), "+f"(d[58]), "+f"(d[59]), "+f"(d[60]), "+f"(d[61]), "+f"(d[62]), "+f"(d[63]), "+f"(d[64]), "+f"(d[65]), "+f"(d[66]), "+f"(d[67]), "+f"(d[68]), "+f"(d[69]), "+f"(d[70]), "+f"(d[71]), "+f"(d[72]), "+f"(d[73]), "+f"(d[74]), "+f"(d[75]), "+f"(d[76]), "+f"(d[77]), "+f"(d[78]), "+f"(d[79]), "+f"(d[80]), "+f"(d[81]), "+f"(d[82]), "+f"(d[83]), "+f"(d[84]), "+f"(d[85]), "+f"(d[86]), "+f"(d[87]), "+f"(d[88]), "+f"(d[89]), "+f"(d[90]), "+f"(d[91]), "+f"(d[92]), "+f"(d[93]), "+f"(d[94]), "+f"(d[95]), "+f"(d[96]), "+f"(d[97]), "+f"(d[98]), "+f"(d[99]), "+f"(d[100]), "+f"(d[101]), "+f"(d[102]), "+f"(d[103]), "+f"(d[104]), "+f"(d[105]), "+f"(d[106]), "+f"(d[107]), "+f"(d[108]), "+f"(d[109]), "+f"(d[110]), "+f"(d[111]), "+f"(d[112]), "+f"(d[113]), "+f"(d[114]), "+f"(d[115]), "+f"(d[116]), "+f"(d[117]), "+f"(d[118]), "+f"(d[119]), "+f"(d[120]), "+f"(d[121]), "+f"(d[122]), "+f"(d[123]), "+f"(d[124]), "+f"(d[125]), "+f"(d[126]), "+f"(d[127])
    : "r"(a_lo), "r"(b_lo), "r"(scaleD), "n"(OFFA), "n"(OFFB));
}

template <int OFFA, int OFFB>
__device__ __forceinline__ void wgmma_m64n128k16_ss_tb(float (&d)[64], uint32_t a_lo, uint32_t b_lo, int scaleD) {
  asm volatile("{\n.reg .pred p;\n.reg .b32 ta, tb;\n.reg .b64 da, db;\nsetp.ne.b32 p, %66, 0;\n"
    "add.u32 ta, %64, %67;\nadd.u32 tb, %65, %68;\n"
    "mov.b64 da, {ta, 0x40000040};\nmov.b64 db, {tb, 0x40000040};\n"
    "wgmma.mma_async.sync.aligned.m64n128k16.f32.bf16.bf16 "
    "{%0, %1, %2, %3, %4, %5, %6, %7, %8, %9, %10, %11, %12, %13, %14, %15, %16, %17, %18, %19, %20, %21, %22, %23, %24, %25, %26, %27, %28, %29, %30, %31, %32, %33, %34, %35, %36, %37, %38, %39, %40, %41, %42, %43, %44, %45, %46, %47, %48, %49, %50, %51, %52, %53, %54, %55, %56, %57, %58, %59, %60, %61, %62, %63}, "
    "da, db, p, 1, 1, 0, 1;\n}\n"
    : "+f"(d[0]), "+f"(d[1]), "+f"(d[2]), "+f"(d[3]), "+f"(d[4]), "+f"(d[5]), "+f"(d[6]), "+f"(d[7]), "+f"(d[8]), "+f"(d[9]), "+f"(d[10]), "+f"(d[11]), "+f"(d[12]), "+f"(d[13]), "+f"(d[14]), "+f"(d[15]), "+f"(d[16]), "+f"(d[17]), "+f"(d[18]), "+f"(d[19]), "+f"(d[20]), "+f"(d[21]), "+f"(d[22]), "+f"(d[23]), "+f"(d[24]), "+f"(d[25]), "+f"(d[26]), "+f"(d[27]), "+f"(d[28]), "+f"(d[29]), "+f"(d[30]), "+f"(d[31]), "+f"(d[32]), "+f"(d[33]), "+f"(d[34]), "+f"(d[35]), "+f"(d[36]), "+f"(d[37]), "+f"(d[38]), "+f"(d[39]), "+f"(d[40]), "+f"(d[41]), "+f"(d[42]), "+f"(d[43]), "+f"(d[44]), "+f"(d[45]), "+f"(d[46]), "+f"(d[47]), "+f"(d[48]), "+f"(d[49]), "+f"(d[50]), "+f"(d[51]), "+f"(d[52]), "+f"(d[53]), "+f"(d[54]), "+f"(d[55]), "+f"(d[56]), "+f"(d[57]), "+f"(d[58]), "+f"(d[59]), "+f"(d[60]), "+f"(d[61]), "+f"(d[62]), "+f"(d[63])
    : "r"(a_lo), "r"(b_lo), "r"(scaleD), "n"(OFFA), "n"(OFFB));
}

template <int OFFB>
__device__ __forceinline__ void wgmma_m64n128k16_rs_tb(float (&d)[64], uint32_t a0, uint32_t a1, uint32_t a2, uint32_t a3, uint32_t b_lo, int scaleD) {
  asm volatile("{\n.reg .pred p;\n.reg .b32 tb;\n.reg .b64 db;\nsetp.ne.b32 p, %69, 0;\n"
    "add.u32 tb, %68, %70;\n"
    "mov.b64 db, {tb, 0x40000040};\n"
    "wgmma.mma_async.sync.aligned.m64n128k16.f32.bf16.bf16 "
    "{%0, %1, %2, %3, %4, %5, %6, %7, %8, %9, %10, %11, %12, %13, %14, %15, %16, %17, %18, %19, %20, %21, %22, %23, %24, %25, %26, %27, %28, %29, %30, %31, %32, %33, %34, %35, %36, %37, %38, %39, %40, %41, %42, %43, %44, %45, %46, %47, %48, %49, %50, %51, %52, %53, %54, %55, %56, %57, %58, %59, %60, %61, %62, %63}, "
    "{%64, %65, %66, %67}, db, p, 1, 1, 1;\n}\n"
    : "+f"(d[0]), "+f"(d[1]), "+f"(d[2]), "+f"(d[3]), "+f"(d[4]), "+f"(d[5]), "+f"(d[6]), "+f"(d[7]), "+f"(d[8]), "+f"(d[9]), "+f"(d[10]), "+f"(d[11]), "+f"(d[12]), "+f"(d[13]), "+f"(d[14]), "+f"(d[15]), "+f"(d[16]), "+f"(d[17]), "+f"(d[18]), "+f"(d[19]), "+f"(d[20]), "+f"(d[21]), "+f"(d[22]), "+f"(d[23]), "+f"(d[24]), "+f"(d[25]), "+f"(d[26]), "+f"(d[27]), "+f"(d[28]), "+f"(d[29]), "+f"(d[30]), "+f"(d[31]), "+f"(d[32]), "+f"(d[33]), "+f"(d[34]), "+f"(d[35]), "+f"(d[36]), "+f"(d[37]), "+f"(d[38]), "+f"(d[39]), "+f"(d[40]), "+f"(d[41]), "+f"(d[42]), "+f"(d[43]), "+f"(d[44]), "+f"(d[45]), "+f"(d[46]), "+f"(d[47]), "+f"(d[48]), "+f"(d[49]), "+f"(d[50]), "+f"(d[51]), "+f"(d[52]), "+f"(d[53]), "+f"(d[54]), "+f"(d[55]), "+f"(d[56]), "+f"(d[57]), "+f"(d[58]), "+f"(d[59]), "+f"(d[60]), "+f"(d[61]), "+f"(d[62]), "+f"(d[63])
    : "r"(a0), "r"(a1), "r"(a2), "r"(a3), "r"(b_lo), "r"(scaleD), "n"(OFFB));
}

template <int OFFB>
__device__ __forceinline__ void wgmma_m64n128k16_rs(float (&d)[64], uint32_t a0, uint32_t a1, uint32_t a2, uint32_t a3, uint32_t b_lo, int scaleD) {
  asm volatile("{\n.reg .pred p;\n.reg .b32 tb;\n.reg .b64 db;\nsetp.ne.b32 p, %69, 0;\n"
    "add.u32 tb, %68, %70;\n"
    "mov.b64 db, {tb, 0x40000040};\n"
    "wgmma.mma_async.sync.aligned.m64n128k16.f32.bf16.bf16 "
    "{%0, %1, %2, %3, %4, %5, %6, %7, %8, %9, %10, %11, %12, %13, %14, %15, %16, %17, %18, %19, %20, %21, %22, %23, %24, %25, %26, %27, %28, %29, %30, %31, %32, %33, %34, %35, %36, %37, %38, %39, %40, %41, %42, %43, %44, %45, %46, %47, %48, %49, %50, %51, %52, %53, %54, %55, %56, %57, %58, %59, %60, %61, %62, %63}, "
    "{%64, %65, %66, %67}, db, p, 1, 1, 0;\n}\n"
    : "+f"(d[0]), "+f"(d[1]), "+f"(d[2]), "+f"(d[3]), "+f"(d[4]), "+f"(d[5]), "+f"(d[6]), "+f"(d[7]), "+f"(d[8]), "+f"(d[9]), "+f"(d[10]), "+f"(d[11]), "+f"(d[12]), "+f"(d[13]), "+f"(d[14]), "+f"(d[15]), "+f"(d[16]), "+f"(d[17]), "+f"(d[18]), "+f"(d[19]), "+f"(d[20]), "+f"(d[21]), "+f"(d[22]), "+f"(d[23]), "+f"(d[24]), "+f"(d[25]), "+f"(d[26]), "+f"(d[27]), "+f"(d[28]), "+f"(d[29]), "+f"(d[30]), "+f"(d[31]), "+f"(d[32]), "+f"(d[33]), "+f"(d[34]), "+f"(d[35]), "+f"(d[36]), "+f"(d[37]), "+f"(d[38]), "+f"(d[39]), "+f"(d[40]), "+f"(d[41]), "+f"(d[42]), "+f"(d[43]), "+f"(d[44]), "+f"(d[45]), "+f"(d[46]), "+f"(d[47]), "+f"(d[48]), "+f"(d[49]), "+f"(d[50]), "+f"(d[51]), "+f"(d[52]), "+f"(d[53]), "+f"(d[54]), "+f"(d[55]), "+f"(d[56]), "+f"(d[57]), "+f"(d[58]), "+f"(d[59]), "+f"(d[60]), "+f"(d[61]), "+f"(d[62]), "+f"(d[63])
    : "r"(a0), "r"(a1), "r"(a2), "r"(a3), "r"(b_lo), "r"(scaleD), "n"(OFFB));
}

__device__ __forceinline__ uint4 ldg_nc_v4(const void* p) {
  uint4 v;
    asm volatile("{\n.reg .b64 pol;\ncreatepolicy.fractional.L2::evict_first.b64 pol, 1.0;\n"
                 "ld.global.nc.L1::no_allocate.L2::cache_hint.v4.u32 {%0, %1, %2, %3}, [%4], pol;\n}\n" : "=r"(v.x), "=r"(v.y), "=r"(v.z), "=r"(v.w) : "l"(p));
  return v;
}
__device__ __forceinline__ uint64_t pol_normal() {
  uint64_t p; asm volatile("createpolicy.fractional.L2::evict_normal.b64 %0, 1.0;" : "=l"(p)); return p;
}
__device__ __forceinline__ void unpack8(const uint4& u, float (&v)[8]) {
  v[0] = bflo(u.x); v[1] = bfhi(u.x); v[2] = bflo(u.y); v[3] = bfhi(u.y);
  v[4] = bflo(u.z); v[5] = bfhi(u.z); v[6] = bflo(u.w); v[7] = bfhi(u.w);
}
__device__ __forceinline__ void fma8(float (&acc)[8], float s, const uint4& w) {
  acc[0] = fmaf(s, bflo(w.x), acc[0]); acc[1] = fmaf(s, bfhi(w.x), acc[1]); acc[2] = fmaf(s, bflo(w.y), acc[2]); acc[3] = fmaf(s, bfhi(w.y), acc[3]);
  acc[4] = fmaf(s, bflo(w.z), acc[4]); acc[5] = fmaf(s, bfhi(w.z), acc[5]); acc[6] = fmaf(s, bflo(w.w), acc[6]); acc[7] = fmaf(s, bfhi(w.w), acc[7]);
}
__device__ __forceinline__ float rcp_approx(float x) { float y; asm("rcp.approx.ftz.f32 %0, %1;" : "=f"(y) : "f"(x)); return y; }
__device__ __forceinline__ float sigmoid_f(float v) { return rcp_approx(1.0f + ex2_approx(v * -1.4426950408889634f)); }
__device__ __forceinline__ float silu_bf(float v) { return rbf(v * sigmoid_f(v)); }
__device__ __forceinline__ uint32_t rank_key(float r, int idx) {
  const uint32_t b = __float_as_uint(r) >> 16;
  const uint32_t u = (r != r) ? 0u : ((b & 0x8000u) ? (~b & 0xffffu) : (b | 0x8000u));
  return (u << 16) | (0xffffu - (uint32_t)idx);
}
__device__ __forceinline__ void warp_top2(uint32_t& k1, uint32_t& k2) {
  const uint32_t m1 = __reduce_max_sync(0xffffffffu, k1);
  k2 = __reduce_max_sync(0xffffffffu, k1 == m1 ? k2 : k1);
  k1 = m1;
}
__device__ __forceinline__ uint32_t bmul2(uint32_t a, uint32_t b) { uint32_t r; asm("mul.rn.bf16x2 %0, %1, %2;" : "=r"(r) : "r"(a), "r"(b)); return r; }
__device__ __forceinline__ uint32_t badd2(uint32_t a, uint32_t b) { uint32_t r; asm("add.rn.bf16x2 %0, %1, %2;" : "=r"(r) : "r"(a), "r"(b)); return r; }
__device__ __forceinline__ uint32_t bsub2(uint32_t a, uint32_t b) { uint32_t r; asm("sub.rn.bf16x2 %0, %1, %2;" : "=r"(r) : "r"(a), "r"(b)); return r; }
__device__ __forceinline__ float sqrt_approx(float x) { float y; asm("sqrt.approx.f32 %0, %1;" : "=f"(y) : "f"(x)); return y; }
__device__ __forceinline__ uint32_t ln_norm2(uint32_t x1, uint32_t mb2, float inv) {
  const uint32_t d = bsub2(x1, mb2);
  return pack_bf16(bflo(d) * inv, bfhi(d) * inv);
}
__device__ __forceinline__ uint32_t bfma2(uint32_t a, uint32_t b, uint32_t c) { uint32_t r; asm("fma.rn.bf16x2 %0, %1, %2, %3;" : "=r"(r) : "r"(a), "r"(b), "r"(c)); return r; }
__device__ __forceinline__ uint32_t ln_norm2b(uint32_t x1, uint32_t mb2, uint32_t ih, uint32_t il) {
  const uint32_t d = bsub2(x1, mb2);
  return bfma2(d, ih, bmul2(d, il));
}
__device__ __forceinline__ uint32_t ln_mod2(uint32_t x1, uint32_t mb2, float inv, uint32_t c1, uint32_t sb) { return badd2(bmul2(ln_norm2(x1, mb2, inv), c1), sb); }
__device__ __forceinline__ void ldmatrix_x4(uint32_t addr, uint32_t& r0, uint32_t& r1, uint32_t& r2, uint32_t& r3) {
  asm volatile("ldmatrix.sync.aligned.m8n8.x4.shared.b16 {%0, %1, %2, %3}, [%4];" : "=r"(r0), "=r"(r1), "=r"(r2), "=r"(r3) : "r"(addr) : "memory");
}
__device__ __forceinline__ uint4 ldg_stream_v4(const void* p, uint64_t pol) {
  uint4 v; asm volatile("ld.global.nc.L1::no_allocate.L2::cache_hint.L2::128B.v4.u32 {%0, %1, %2, %3}, [%4], %5;" : "=r"(v.x), "=r"(v.y), "=r"(v.z), "=r"(v.w) : "l"(p), "l"(pol)); return v;
}
__device__ __forceinline__ void bulk_load_hint(uint32_t dst, const void* src, uint32_t bytes, uint32_t bar, uint64_t pol) {
  asm volatile("cp.async.bulk.shared::cluster.global.mbarrier::complete_tx::bytes.L2::cache_hint [%0], [%1], %2, [%3], %4;"
    :: "r"(dst), "l"(src), "r"(bytes), "r"(bar), "l"(pol) : "memory");
}
__device__ __forceinline__ void red_release_add(unsigned int* p, unsigned int v) { asm volatile("red.release.gpu.global.add.u32 [%0], %1;" :: "l"(p), "r"(v) : "memory"); }
__device__ __forceinline__ unsigned int ld_acquire(const unsigned int* p) { unsigned int v; asm volatile("ld.acquire.gpu.global.u32 %0, [%1];" : "=r"(v) : "l"(p) : "memory"); return v; }
__device__ __forceinline__ void spin_until(const unsigned int* p, unsigned int target) {
  #pragma unroll 1
  for (unsigned int i = 0; i < (1u << 22); i++) { if (ld_acquire(p) >= target) return; }
}
__device__ __forceinline__ float lds_f32(uint32_t a) { float v; asm volatile("ld.shared.f32 %0, [%1];" : "=f"(v) : "r"(a) : "memory"); return v; }
__device__ __forceinline__ float2 lds_f32x2(uint32_t a) { float2 v; asm volatile("ld.shared.v2.f32 {%0, %1}, [%2];" : "=f"(v.x), "=f"(v.y) : "r"(a) : "memory"); return v; }
__device__ __forceinline__ uint2 lds_u32x2(uint32_t a) { uint2 v; asm volatile("ld.shared.v2.u32 {%0, %1}, [%2];" : "=r"(v.x), "=r"(v.y) : "r"(a) : "memory"); return v; }
__device__ __forceinline__ uint32_t lds_u32(uint32_t a) { uint32_t v; asm volatile("ld.shared.u32 %0, [%1];" : "=r"(v) : "r"(a) : "memory"); return v; }
__device__ __forceinline__ void sts_u32(uint32_t a, uint32_t v) { asm volatile("st.shared.u32 [%0], %1;" :: "r"(a), "r"(v) : "memory"); }
__device__ __forceinline__ void sts_u32x2(uint32_t a, uint32_t x, uint32_t y) { asm volatile("st.shared.v2.u32 [%0], {%1, %2};" :: "r"(a), "r"(x), "r"(y) : "memory"); }
__device__ __forceinline__ void sts_f32(uint32_t a, float v) { asm volatile("st.shared.f32 [%0], %1;" :: "r"(a), "f"(v) : "memory"); }
__device__ __forceinline__ void sts_f32x2(uint32_t a, float x, float y) { asm volatile("st.shared.v2.f32 [%0], {%1, %2};" :: "r"(a), "f"(x), "f"(y) : "memory"); }
__device__ __forceinline__ void sts_f32x4(uint32_t a, float x, float y, float z, float w) { asm volatile("st.shared.v4.f32 [%0], {%1, %2, %3, %4};" :: "r"(a), "f"(x), "f"(y), "f"(z), "f"(w) : "memory"); }

__device__ __forceinline__ uint4 lds_u32x4(uint32_t a) { uint4 v; asm volatile("ld.shared.v4.u32 {%0, %1, %2, %3}, [%4];" : "=r"(v.x), "=r"(v.y), "=r"(v.z), "=r"(v.w) : "r"(a) : "memory"); return v; }
__device__ __forceinline__ void sts_u32x4(uint32_t a, uint32_t x, uint32_t y, uint32_t z, uint32_t w) { asm volatile("st.shared.v4.u32 [%0], {%1, %2, %3, %4};" :: "r"(a), "r"(x), "r"(y), "r"(z), "r"(w) : "memory"); }
__device__ __forceinline__ void st_tagged(float* p, float v) {
  const uint32_t b = __float_as_uint(v);
  asm volatile("st.relaxed.gpu.global.u32 [%0], %1;" :: "l"(p), "r"(b == 0u ? 0x80000000u : b) : "memory");
}
__device__ __forceinline__ void st_tagged4(float* p, float x, float y, float z, float w) {
  const uint32_t a = __float_as_uint(x), b = __float_as_uint(y), c = __float_as_uint(z), d = __float_as_uint(w);
  asm volatile("st.relaxed.gpu.global.v4.u32 [%0], {%1, %2, %3, %4};" :: "l"(p), "r"(a == 0u ? 0x80000000u : a), "r"(b == 0u ? 0x80000000u : b),
               "r"(c == 0u ? 0x80000000u : c), "r"(d == 0u ? 0x80000000u : d) : "memory");
}
__device__ __forceinline__ void st_relaxed2(void* p, uint32_t a, uint32_t b) { asm volatile("st.relaxed.gpu.global.v2.u32 [%0], {%1, %2};" :: "l"(p), "r"(a), "r"(b) : "memory"); }
__device__ __forceinline__ float4 ld_tagged4(const float* p) {
  float4 v; asm volatile("ld.relaxed.gpu.global.v4.f32 {%0, %1, %2, %3}, [%4];" : "=f"(v.x), "=f"(v.y), "=f"(v.z), "=f"(v.w) : "l"(p) : "memory"); return v;
}
__device__ __forceinline__ bool tagged4(const float4& v) {
  return __float_as_uint(v.x) != 0u && __float_as_uint(v.y) != 0u && __float_as_uint(v.z) != 0u && __float_as_uint(v.w) != 0u;
}
__device__ __forceinline__ void hint_arrive(uint32_t* p) { asm volatile("red.relaxed.gpu.global.add.u32 [%0], 1;" :: "l"(p) : "memory"); }
__device__ __forceinline__ void hint_wait(const uint32_t* p, uint32_t target) {
  uint32_t v = 0u;
  #pragma unroll 1
  for (unsigned int i = 0; i < (1u << 22) && v < target; i++) asm volatile("ld.relaxed.gpu.global.u32 %0, [%1];" : "=r"(v) : "l"(p) : "memory");
}
__device__ __forceinline__ void fence_proxy_async_global() { asm volatile("fence.proxy.async.global;" ::: "memory"); }

#define H_SPLIT 1
#define X_DLY 1200
#define W_DLY 1900
#define W_FIRST 2200
#define PRE_B 2
template <int J0, int J1>
__device__ __forceinline__ void load_parts(float2 (&pa)[J1 - J0][4], int t2) {
  #pragma unroll
  for (int j = J0; j < J1; j++)
    #pragma unroll
    for (int k = 0; k < 4; k++)
      asm volatile("ld.relaxed.gpu.global.v2.f32 {%0, %1}, [%2];" : "=f"(pa[j - J0][k].x), "=f"(pa[j - J0][k].y)
                   : "l"(g_modpart + k * 2 * T_D + (t2 >> 7) * T_D + j * 256 + (t2 & 127) * 2) : "memory");
}
template <int J0, int J1>
__device__ __forceinline__ void finish_parts(float2 (&pa)[J1 - J0][4], bool loaded, int t2, uint32_t tab) {
  #pragma unroll 1
  for (unsigned int spin = 0; spin < (1u << 22); spin++) {
    if (!loaded) load_parts<J0, J1>(pa, t2);
    loaded = false;
    bool ok = true;
    #pragma unroll
    for (int j = 0; j < J1 - J0; j++)
      #pragma unroll
      for (int k = 0; k < 4; k++) ok &= (__float_as_uint(pa[j][k].x) != 0u) & (__float_as_uint(pa[j][k].y) != 0u);
    if (__all_sync(0xffffffffu, ok)) break;
  }
  #pragma unroll
  for (int j = J0; j < J1; j++) {
    const float2* q = pa[j - J0];
    const uint32_t m = pack_bf16(((q[0].x + q[1].x) + q[2].x) + q[3].x, ((q[0].y + q[1].y) + q[2].y) + q[3].y);
    sts_u32(tab + (t2 >> 7) * 2048 + j * 512 + (t2 & 127) * 4, t2 >= 128 ? badd2(m, 0x3F803F80u) : m);
  }
}
__device__ __forceinline__ void head_phase(uint32_t scr, uint32_t xs, uint32_t b_x, uint32_t b_go, uint32_t b_head, int t2, uint32_t zero, const bf16* __restrict__ cvec, const bf16* __restrict__ w_mod) {
  const int lane = t2 & 31, w8 = t2 >> 5;
  const int cb = blockIdx.x & 31, ks = blockIdx.x >> 5;
  const bool early = (cb & 15) < 4 * H_SPLIT;
  const uint32_t ws = (xs - 32768 + (t2 >> 3) * 128 + (((t2 ^ (t2 >> 3)) & 7) << 4)) ^ zero;
  const float cv = __bfloat162float(cvec[ks * 256 + t2]);
  const bf16* wsrc = w_mod + (size_t)(ks * 256 + (t2 >> 3)) * (6 * T_D) + cb * 64 + (t2 & 7) * 8;
  if (early) {
    const uint64_t pol = policy_evict_first();
    #pragma unroll 2
    for (int i = 0; i < 8; i++)
      asm volatile("cp.async.cg.shared.global.L2::cache_hint [%0], [%1], 16, %2;" :: "r"(ws + i * 4096), "l"(wsrc + (size_t)i * 32 * 6 * T_D), "l"(pol) : "memory");
  }
  sts_f32(scr + t2 * 4, silu_bf(cv));
  named_bar_sync(6, 384);
  TL_MARK2(1, t2 == 0);
  uint4 xv[2][4];
  uint32_t mb2[2], ih[2], il[2];
  auto norm = [&](int j) {
    #pragma unroll
    for (int r = 0; r < 2; r++) {
      xv[r][j].x = ln_norm2b(xv[r][j].x, mb2[r], ih[r], il[r]); xv[r][j].y = ln_norm2b(xv[r][j].y, mb2[r], ih[r], il[r]);
      xv[r][j].z = ln_norm2b(xv[r][j].z, mb2[r], ih[r], il[r]); xv[r][j].w = ln_norm2b(xv[r][j].w, mb2[r], ih[r], il[r]);
    }
  };
  auto modulate = [&](int j) {
    const uint4 sa = lds_u32x4(scr + 8192 + j * 512 + lane * 16), c1 = lds_u32x4(scr + 8192 + 2048 + j * 512 + lane * 16);
    #pragma unroll
    for (int r = 0; r < 2; r++) {
      xv[r][j].x = badd2(bmul2(xv[r][j].x, c1.x), sa.x); xv[r][j].y = badd2(bmul2(xv[r][j].y, c1.y), sa.y);
      xv[r][j].z = badd2(bmul2(xv[r][j].z, c1.z), sa.z); xv[r][j].w = badd2(bmul2(xv[r][j].w, c1.w), sa.w);
    }
  };
  auto store = [&](int j) {
    #pragma unroll
    for (int r = 0; r < 2; r++) *reinterpret_cast<uint4*>(g_h + (size_t)(blockIdx.x * 16 + 2 * w8 + r) * T_D + j * 256 + lane * 8) = xv[r][j];
  };
  #pragma unroll 1
  for (int ph = 0; ph < 2; ph++) {
    if ((ph == 0) == early) {
      asm volatile("cp.async.wait_all;" ::: "memory");
      if (!early) mbar_wait(b_x + 168, 0);
      float acc[8];
      #pragma unroll
      for (int j = 0; j < 8; j++) acc[j] = 0.f;
      #pragma unroll
      for (int i = 0; i < 8; i++) fma8(acc, lds_f32(scr + ((t2 >> 3) + 32 * i) * 4), lds_u32x4(ws + i * 4096));
      #pragma unroll
      for (int j = 0; j < 4; j++) { const bool up = lane & 16; acc[j] = (up ? acc[4 + j] : acc[j]) + __shfl_xor_sync(0xffffffffu, up ? acc[j] : acc[4 + j], 16); }
      #pragma unroll
      for (int j = 0; j < 2; j++) { const bool up = lane & 8; acc[j] = (up ? acc[2 + j] : acc[j]) + __shfl_xor_sync(0xffffffffu, up ? acc[j] : acc[2 + j], 8); }
      sts_f32x2(scr + 1024 + w8 * 256 + (lane & 7) * 32 + (lane >> 3) * 8, acc[0], acc[1]);
      named_bar_sync(5, 256);
      if (t2 < 64) {
        float sum = 0.f;
        #pragma unroll
        for (int i = 0; i < 8; i++) sum += lds_f32(scr + 1024 + i * 256 + t2 * 4);
        st_tagged(g_modpart + ks * 2 * T_D + cb * 64 + t2, sum);
        TL_MARK2(early ? 2 : 6, t2 == 0);
      }
    } else {
      float2 pa[H_SPLIT][4];
      mbar_wait(b_x, 0);
      TL_MARK2(18, t2 == 0);
      load_parts<0, H_SPLIT>(pa, t2);
      #pragma unroll
      for (int r = 0; r < 2; r++)
        #pragma unroll
        for (int j = 0; j < 4; j++) xv[r][j] = lds_u32x4(xs + (2 * w8 + r) * 2048 + j * 512 + lane * 16);
  {
    float st[4] = {0.f, 0.f, 0.f, 0.f};
    #pragma unroll
    for (int r = 0; r < 2; r++)
      #pragma unroll
      for (int j = 0; j < 4; j++) {
        float v[8];
        unpack8(xv[r][j], v);
        st[2 * r] += ((v[0] + v[1]) + (v[2] + v[3])) + ((v[4] + v[5]) + (v[6] + v[7]));
        st[2 * r + 1] += fmaf(v[0], v[0], fmaf(v[1], v[1], fmaf(v[2], v[2], v[3] * v[3]))) + fmaf(v[4], v[4], fmaf(v[5], v[5], fmaf(v[6], v[6], v[7] * v[7])));
      }
    #pragma unroll
    for (int k = 0; k < 2; k++) { const bool up = lane & 16; st[k] = (up ? st[2 + k] : st[k]) + __shfl_xor_sync(0xffffffffu, up ? st[k] : st[2 + k], 16); }
    #pragma unroll
    for (int o = 8; o > 0; o >>= 1) { st[0] += __shfl_xor_sync(0xffffffffu, st[0], o); st[1] += __shfl_xor_sync(0xffffffffu, st[1], o); }
    const float mean = st[0] * (1.0f / T_D);
    const float inv = rcp_approx(rbf(sqrt_approx(rbf(rbf(fmaxf(fmaf(-mean, mean, st[1] * (1.0f / T_D)), 0.f)) + 1e-05f))));
    const uint32_t m = pack_bf16(mean, mean), h = pack_bf16(inv - rbf(inv), inv);
    #pragma unroll
    for (int r = 0; r < 2; r++) {
      mb2[r] = __shfl_sync(0xffffffffu, m, 16 * r);
      const uint32_t hr = __shfl_sync(0xffffffffu, h, 16 * r);
      ih[r] = __byte_perm(hr, hr, 0x3232); il[r] = __byte_perm(hr, hr, 0x1010);
    }
  }
      #pragma unroll
      for (int j = 0; j < H_SPLIT; j++) norm(j);
      TL_MARK2(5, t2 == 0);
      finish_parts<0, H_SPLIT>(pa, true, t2, scr + 8192);
      named_bar_sync(5, 256);
      TL_MARK2(7, t2 == 0);
      #pragma unroll
      for (int j = 0; j < H_SPLIT; j++) { modulate(j); store(j); }
      named_bar_arrive(9, 288);
    }
  }
  #pragma unroll
  for (int j = H_SPLIT; j < 4; j++) norm(j);
  float2 pb[4 - H_SPLIT][4];
  finish_parts<H_SPLIT, 4>(pb, false, t2, scr + 8192);
  named_bar_sync(5, 256);
  TL_MARK2(17, t2 == 0);
  #pragma unroll
  for (int j = H_SPLIT; j < 4; j++) modulate(j);
  __syncwarp();
  if (lane == 0) mbar_arrive(b_head + (xv[1][3].w & zero));
  mbar_wait(b_go, 0);
  #pragma unroll
  for (int j = H_SPLIT; j < 4; j++) store(j);
  named_bar_arrive(8, 288);
}

#define MOD_AT (b_empty + 8)
#define MOD_SPLIT 16
__device__ __forceinline__ void mod_rest(uint32_t scr, uint32_t b_go, int t, const bf16* __restrict__ cvec, const bf16* __restrict__ w_mod, const bf16* __restrict__ w_r) {
  const int lane = t & 31;
  #pragma unroll 1
  for (int i = t; i < T_D / 2; i += 64) {
    const uint32_t c2 = *reinterpret_cast<const uint32_t*>(cvec + 2 * i);
    sts_u32(scr + i * 4, pack_bf16(silu_bf(bflo(c2)), silu_bf(bfhi(c2))));
  }
  named_bar_sync(11, 64);
  const bf16* wp = w_mod + (size_t)(2 * (t >> 2)) * (6 * T_D) + 2 * T_D + blockIdx.x * 32 + (t & 3) * 8;
  float acc[8];
  #pragma unroll
  for (int i = 0; i < 8; i++) acc[i] = 0.f;
  #pragma unroll 1
  for (int i = 0; i < 32; i += 2) {
    if (i == MOD_SPLIT) mbar_wait(b_go, 0);
    const uint4 w0 = ldg_nc_v4(wp), w1 = ldg_nc_v4(wp + 6 * T_D), w2 = ldg_nc_v4(wp + 32 * 6 * T_D), w3 = ldg_nc_v4(wp + 33 * 6 * T_D);
    wp += 64 * 6 * T_D;
    const uint32_t s0 = lds_u32(scr + (i * 16 + (t >> 2)) * 4), s1 = lds_u32(scr + (i * 16 + 16 + (t >> 2)) * 4);
    fma8(acc, bflo(s0), w0); fma8(acc, bfhi(s0), w1); fma8(acc, bflo(s1), w2); fma8(acc, bfhi(s1), w3);
  }
  #pragma unroll
  for (int j = 0; j < 4; j++) { const bool up = lane & 16; acc[j] = (up ? acc[4 + j] : acc[j]) + __shfl_xor_sync(0xffffffffu, up ? acc[j] : acc[4 + j], 16); }
  #pragma unroll
  for (int j = 0; j < 2; j++) { const bool up = lane & 8; acc[j] = (up ? acc[2 + j] : acc[j]) + __shfl_xor_sync(0xffffffffu, up ? acc[j] : acc[2 + j], 8); }
  { const bool up = lane & 4; acc[0] = (up ? acc[1] : acc[0]) + __shfl_xor_sync(0xffffffffu, up ? acc[0] : acc[1], 4); }
  if (t >= 32) sts_f32(scr + 2048 + lane * 4, acc[0]);
  named_bar_sync(11, 64);
  if (__shfl_sync(0xffffffffu, t, 0) < 32) {
    const int kind = blockIdx.x >> 5;
    float v = rbf(acc[0] + lds_f32(scr + 2048 + lane * 4));
    const int col = (blockIdx.x & 31) * 32 + (lane & 3) * 8 + (lane >> 2);
    uint8_t* dst = g_col + (col >> 7) * 1536;
    if (kind == 2) v = rbf(1.0f + v);
    float vw = v * __bfloat162float(w_r[col]);
    if (kind == 2) {
      const int c = col & 127, i = (c & ~15) + ((c >> 1) & 3) * 4 + ((c >> 3) & 1) * 2 + (c & 1);
      reinterpret_cast<bf16*>(dst)[i] = __float2bfloat16_rn(vw);
      reinterpret_cast<bf16*>(dst)[128 + i] = __float2bfloat16_rn(vw - rbf(vw));
    }
    reinterpret_cast<bf16*>(dst + 512 + (kind & 1) * 512 + (kind >> 1) * 256)[col & 127] = __float2bfloat16_rn(v);
    #pragma unroll
    for (int o = 16; o > 0; o >>= 1) vw += __shfl_xor_sync(0xffffffffu, vw, o);
    if (lane == 0 && (kind == 1 || kind == 2)) g_scal[95 - blockIdx.x] = vw;
  }
  #pragma unroll 1
  for (int i = blockIdx.x * 64 + t; i < (int)(sizeof(g_mail) / 16); i += 128 * 64) reinterpret_cast<uint4*>(&g_mail)[i] = make_uint4(0u, 0u, 0u, 0u);
  named_bar_sync(11, 64);
  if (t == 0) red_release_add(&g_hcnt[0], 1u);
}

constexpr int AT_NBLK = T_SEQ / 128;
constexpr float AT_HEAD = 7.0f;
#define WO_LATE 12
#define QP_STAG 3
#define AT_SPLIT 28
#define AT_PIN 12
#define PINB 4
constexpr int AT_NFULL = 124;
constexpr int AT_PREG = 40, AT_CREG = 232;
constexpr uint32_t AT_SQ = 5 * 32768;
constexpr float AT_C = 0.08838834764831845f * 1.4426950408889634f;
constexpr float AT_RAW_LO = -16.0f, AT_RAW_HI = 24.0f;
constexpr float AT_RAW_SUM = 281474976710656.0f, AT_RAW_MIN = 9.094947017729282e-13f;
constexpr uint32_t AT_SBAR = AT_SQ + 65536 + 256;
constexpr uint32_t AT_SMEM = AT_SQ + 65536 + 3072;

__device__ __forceinline__ uint32_t ring_slot(uint32_t t) { return t - 5u * ((t * 205u) >> 10); }
__device__ __forceinline__ uint32_t qp_pos(uint32_t j, uint32_t it) { return 4u * it + (j & 3u) + ((j & 3u) == 3u ? it : 0u); }
__device__ __forceinline__ uint32_t ring_par(uint32_t t) { return ((t * 205u) >> 10) & 1u; }
__device__ __forceinline__ void softmax_rowmax(const float (&s)[64], float& mx0, float& mx1) {
  float a0 = fmaxf(s[0], s[1]), a1 = fmaxf(s[4], s[5]), a2 = fmaxf(s[8], s[9]), a3 = fmaxf(s[12], s[13]);
  float b0 = fmaxf(s[2], s[3]), b1 = fmaxf(s[6], s[7]), b2 = fmaxf(s[10], s[11]), b3 = fmaxf(s[14], s[15]);
  #pragma unroll
  for (int j = 4; j < 16; j += 4) {
    a0 = fmaxf(a0, fmaxf(s[4 * j + 0], s[4 * j + 1]));  b0 = fmaxf(b0, fmaxf(s[4 * j + 2], s[4 * j + 3]));
    a1 = fmaxf(a1, fmaxf(s[4 * j + 4], s[4 * j + 5]));  b1 = fmaxf(b1, fmaxf(s[4 * j + 6], s[4 * j + 7]));
    a2 = fmaxf(a2, fmaxf(s[4 * j + 8], s[4 * j + 9]));  b2 = fmaxf(b2, fmaxf(s[4 * j + 10], s[4 * j + 11]));
    a3 = fmaxf(a3, fmaxf(s[4 * j + 12], s[4 * j + 13])); b3 = fmaxf(b3, fmaxf(s[4 * j + 14], s[4 * j + 15]));
  }
  mx0 = fmaxf(fmaxf(a0, a1), fmaxf(a2, a3));
  mx1 = fmaxf(fmaxf(b0, b1), fmaxf(b2, b3));
  mx0 = fmaxf(mx0, __shfl_xor_sync(0xffffffffu, mx0, 1));
  mx1 = fmaxf(mx1, __shfl_xor_sync(0xffffffffu, mx1, 1));
  mx0 = fmaxf(mx0, __shfl_xor_sync(0xffffffffu, mx0, 2));
  mx1 = fmaxf(mx1, __shfl_xor_sync(0xffffffffu, mx1, 2));
}
__device__ __forceinline__ void softmax_sub(float (&s)[64], float mc0, float mc1) {
  #pragma unroll
  for (int j = 0; j < 16; j++) { s[4 * j] -= mc0; s[4 * j + 1] -= mc0; s[4 * j + 2] -= mc1; s[4 * j + 3] -= mc1; }
}
template <int LO, int HI>
__device__ __forceinline__ void softmax_exp(float (&s)[64]) {
  #pragma unroll
  for (int i = LO; i < HI; i++) s[i] = ex2_approx(s[i]);
}
__device__ __forceinline__ bool softmax_mode(const float (&s)[64], float& mc0, float& mc1) {
  softmax_rowmax(s, mc0, mc1);
  const bool raw = __all_sync(0xffffffffu, mc0 >= AT_RAW_LO && mc0 <= AT_RAW_HI && mc1 >= AT_RAW_LO && mc1 <= AT_RAW_HI);
  mc0 += AT_HEAD; mc1 += AT_HEAD;
  return raw;
}
__device__ __forceinline__ void rowsum_p(const uint32_t (&p)[32], uint32_t& t0, uint32_t& t1) {
  uint32_t a[16];
  #pragma unroll
  for (int i = 0; i < 8; i++) { a[2 * i] = badd2(p[4 * i], p[4 * i + 2]); a[2 * i + 1] = badd2(p[4 * i + 1], p[4 * i + 3]); }
  #pragma unroll
  for (int i = 0; i < 4; i++) { a[2 * i] = badd2(a[4 * i], a[4 * i + 2]); a[2 * i + 1] = badd2(a[4 * i + 1], a[4 * i + 3]); }
  t0 = badd2(badd2(a[0], a[2]), badd2(a[4], a[6]));
  t1 = badd2(badd2(a[1], a[3]), badd2(a[5], a[7]));
}
__device__ __forceinline__ void add_rowsum(const uint32_t (&p)[32], float& l0, float& l1) {
  uint32_t t0, t1;
  rowsum_p(p, t0, t1);
  l0 += bflo(t0) + bfhi(t0); l1 += bflo(t1) + bfhi(t1);
}
__device__ __forceinline__ void pack_p(uint32_t (&p)[32], const float (&s)[64]) {
  #pragma unroll
  for (int i = 0; i < 32; i++) p[i] = pack_bf16(s[2 * i], s[2 * i + 1]);
}
__device__ __noinline__ void attn_rows_exact(uint32_t sq, uint32_t so, int hsel, const bf16* __restrict__ kh, const bf16* __restrict__ vh) {
  const int warp = (threadIdx.x >> 5) & 3, lane = threadIdx.x & 31;
  const size_t hofs = (size_t)((blockIdx.x < 128 ? blockIdx.x >> 4 : 15) * 2 + hsel) * T_SEQ * T_DH;
  kh += hofs; vh += hofs;
  #pragma unroll 1
  for (int r = 16 * warp; r < 16 * warp + 16; r++) {
    const uint32_t ad = (lane >> 4) * 16384 + r * 128 + ((((lane & 15) >> 1) ^ (r & 7)) << 4) + (lane & 1) * 8;
    uint2 qv; asm volatile("ld.shared.v2.u32 {%0, %1}, [%2];" : "=r"(qv.x), "=r"(qv.y) : "r"(sq + ad) : "memory");
    const float q0 = bflo(qv.x), q1 = bfhi(qv.x), q2 = bflo(qv.y), q3 = bfhi(qv.y);
    float m = -INFINITY, l = 0.f, o0 = 0.f, o1 = 0.f, o2 = 0.f, o3 = 0.f;
    #pragma unroll 1
    for (int key = 0; key < T_SEQ; key++) {
      const uint2 kv = *reinterpret_cast<const uint2*>(kh + (size_t)key * T_DH + lane * 4);
      const uint2 vv = *reinterpret_cast<const uint2*>(vh + (size_t)key * T_DH + lane * 4);
      float sc = (q0 * bflo(kv.x) + q1 * bfhi(kv.x)) + (q2 * bflo(kv.y) + q3 * bfhi(kv.y));
      #pragma unroll
      for (int o = 16; o > 0; o >>= 1) sc += __shfl_xor_sync(0xffffffffu, sc, o);
      const float mn = fmaxf(m, sc);
      const float al = (m == mn) ? 1.0f : ex2_approx(m - mn), p = rbf(ex2_approx(sc - mn));
      m = mn;
      l = fmaf(l, al, p);
      o0 = fmaf(o0, al, p * bflo(vv.x)); o1 = fmaf(o1, al, p * bfhi(vv.x));
      o2 = fmaf(o2, al, p * bflo(vv.y)); o3 = fmaf(o3, al, p * bfhi(vv.y));
    }
    const float inv = rcp_approx(l);
    asm volatile("st.shared.v2.u32 [%0], {%1, %2};" :: "r"(so + ad), "r"(pack_bf16(o0 * inv, o1 * inv)), "r"(pack_bf16(o2 * inv, o3 * inv)) : "memory");
  }
}
__device__ __forceinline__ void issue_qk(float (&s)[64], const uint32_t (&q)[32], uint32_t k_lo) {
  wgmma_fence();
  wgmma_m64n128k16_rs<0>(s, q[0], q[1], q[2], q[3], k_lo, 0);
  wgmma_m64n128k16_rs<2>(s, q[4], q[5], q[6], q[7], k_lo, 1);
  wgmma_m64n128k16_rs<4>(s, q[8], q[9], q[10], q[11], k_lo, 1);
  wgmma_m64n128k16_rs<6>(s, q[12], q[13], q[14], q[15], k_lo, 1);
  wgmma_m64n128k16_rs<1024>(s, q[16], q[17], q[18], q[19], k_lo, 1);
  wgmma_m64n128k16_rs<1026>(s, q[20], q[21], q[22], q[23], k_lo, 1);
  wgmma_m64n128k16_rs<1028>(s, q[24], q[25], q[26], q[27], k_lo, 1);
  wgmma_m64n128k16_rs<1030>(s, q[28], q[29], q[30], q[31], k_lo, 1);
  wgmma_commit();
}
__device__ __forceinline__ void issue_pv(float (&o)[64], const uint32_t (&p)[32], uint32_t v_lo, int accumulate) {
  wgmma_fence();
  wgmma_m64n128k16_rs_tb<0>(o, p[0], p[1], p[2], p[3], v_lo, accumulate);
  wgmma_m64n128k16_rs_tb<128>(o, p[4], p[5], p[6], p[7], v_lo, 1);
  wgmma_m64n128k16_rs_tb<256>(o, p[8], p[9], p[10], p[11], v_lo, 1);
  wgmma_m64n128k16_rs_tb<384>(o, p[12], p[13], p[14], p[15], v_lo, 1);
  wgmma_m64n128k16_rs_tb<512>(o, p[16], p[17], p[18], p[19], v_lo, 1);
  wgmma_m64n128k16_rs_tb<640>(o, p[20], p[21], p[22], p[23], v_lo, 1);
  wgmma_m64n128k16_rs_tb<768>(o, p[24], p[25], p[26], p[27], v_lo, 1);
  wgmma_m64n128k16_rs_tb<896>(o, p[28], p[29], p[30], p[31], v_lo, 1);
  wgmma_commit();
}
__device__ __forceinline__ void block_end(uint32_t zero, uint32_t bar) {
  #pragma unroll 1
  for (uint32_t i = 0; i < zero; i++) mbar_arrive(bar);
}
__device__ __forceinline__ void rescale_o(float (&o)[64], float al0, float al1) {
  #pragma unroll
  for (int j = 0; j < 16; j++) { o[4 * j] *= al0; o[4 * j + 1] *= al0; o[4 * j + 2] *= al1; o[4 * j + 3] *= al1; }
}

__device__ __forceinline__ void stage_o(const float (&o)[64], float i0, float i1, uint32_t dst, int lane) {
  #pragma unroll
  for (int J = 0; J < 16; J += 2)
    stmatrix_x4(dst + (J >> 3) * 16384 + ((((J & 7) + (lane >> 4)) ^ (lane & 7)) << 4),
                pack_bf16(o[4 * J + 0] * i0, o[4 * J + 1] * i0), pack_bf16(o[4 * J + 2] * i1, o[4 * J + 3] * i1),
                pack_bf16(o[4 * J + 4] * i0, o[4 * J + 5] * i0), pack_bf16(o[4 * J + 6] * i1, o[4 * J + 7] * i1));
}
__device__ __forceinline__ bool finish_l(float& l0, float& l1) {
  l0 += __shfl_xor_sync(0xffffffffu, l0, 1); l1 += __shfl_xor_sync(0xffffffffu, l1, 1);
  l0 += __shfl_xor_sync(0xffffffffu, l0, 2); l1 += __shfl_xor_sync(0xffffffffu, l1, 2);
  const bool redo = __any_sync(0xffffffffu, !(l0 <= AT_RAW_SUM && l1 <= AT_RAW_SUM && l0 >= AT_RAW_MIN && l1 >= AT_RAW_MIN));
  l0 = rcp_approx(l0); l1 = rcp_approx(l1);
  return redo;
}
template <int J0>
__device__ __forceinline__ void stage_q(const float (&acc)[128], float c, uint32_t dst, int lane) {
  #pragma unroll
  for (int J = J0; J < J0 + 16; J += 2)
    stmatrix_x4(dst + (J >> 3) * 16384 + ((((J & 7) + (lane >> 4)) ^ (lane & 7)) << 4),
                pack_bf16(acc[4 * J + 0] * c, acc[4 * J + 1] * c), pack_bf16(acc[4 * J + 2] * c, acc[4 * J + 3] * c),
                pack_bf16(acc[4 * J + 4] * c, acc[4 * J + 5] * c), pack_bf16(acc[4 * J + 6] * c, acc[4 * J + 7] * c));
}
__device__ __forceinline__ void store_o(const CUtensorMap* tmO, uint32_t src, int head, int row) {
  tma_store_2d(tmO, src, head * T_DH, row);
  tma_store_2d(tmO, src + 16384, head * T_DH + 64, row);
  bulk_commit();
}
__device__ __forceinline__ void mma_bf16(float (&d)[4], uint32_t a0, uint32_t a1, uint32_t a2, uint32_t a3, uint32_t b0, uint32_t b1) {
  asm volatile("mma.sync.aligned.m16n8k16.row.col.f32.bf16.bf16.f32 {%0, %1, %2, %3}, {%4, %5, %6, %7}, {%8, %9}, {%0, %1, %2, %3};"
               : "+f"(d[0]), "+f"(d[1]), "+f"(d[2]), "+f"(d[3]) : "r"(a0), "r"(a1), "r"(a2), "r"(a3), "r"(b0), "r"(b1));
}
struct GemvSel { uint32_t lo0, hi0, lo1, hi1; };
__device__ __forceinline__ GemvSel gemv_sel(int lane) {
  const uint32_t lo = (lane & 8) ? 0x1044u : 0x4410u, hi = (lane & 8) ? 0x3244u : 0x4432u;
  GemvSel s; s.lo0 = (lane & 16) ? 0x4444u : lo; s.hi0 = (lane & 16) ? 0x4444u : hi; s.lo1 = (lane & 16) ? lo : 0x4444u; s.hi1 = (lane & 16) ? hi : 0x4444u;
  return s;
}
#define GEMV_B0(j, h, s) __byte_perm((j) < 2 ? (h).x : (h).y, 0u, ((j) & 1) ? (s).hi0 : (s).lo0)
#define GEMV_B1(j, h, s) __byte_perm((j) < 2 ? (h).x : (h).y, 0u, ((j) & 1) ? (s).hi1 : (s).lo1)
__device__ __forceinline__ float4 gemv_out(const float (&d)[4], int lane) {
  const bool tk = lane & 1;
  const float r0 = __shfl_xor_sync(0xffffffffu, tk ? d[0] : d[1], 1), r1 = __shfl_xor_sync(0xffffffffu, tk ? d[2] : d[3], 1);
  return tk ? make_float4(r0, d[1], r1, d[3]) : make_float4(d[0], r0, d[2], r1);
}
#define OG_NG 8
#define PUT_N 2
#define H_STAG 2
#define AL_P 60
#define AL_SLEEP 1200
#define AL_MAX 800
#define POLL_NS 200
#define OG_PRE 10
#define OG_PRE2 12
#define OG_JOBS 7
#define OG_GRP 6
#define LD_FIRST 3
#define LD_STAG (OG_GRP / 2)
constexpr int OG_ST = 5, OG_NKB = T_DQKV / 64 - OG_PRE, OG_MOE = T_F / 32;
__device__ __forceinline__ int pre_kb(int i) { return (i >> 1) * 4 + (i & 1); }
__device__ __forceinline__ int own_kb(int i) { return i < OG_PRE2 ? pre_kb(i) + 2 : i < 64 - OG_PRE2 ? i + OG_PRE2 : pre_kb(i - (64 - OG_PRE2 - OG_PRE)); }
constexpr int OG_POS = 8;
constexpr uint32_t OG_STAGE = 32768;
constexpr uint32_t OG_SCOL = AT_SBAR + 512;
constexpr uint32_t OG_SMISC = AT_SBAR + 2048;
constexpr int OG_XPOS = OG_POS + OG_NKB;
constexpr uint32_t OG_SWD = AT_SQ, OG_PSLOT = AT_SQ;
constexpr uint32_t OG_SWD1 = (OG_XPOS % OG_ST) * OG_STAGE;
constexpr uint32_t OG_XSLOT = AT_SQ + 32768;
constexpr uint32_t OG_OSLOT = ((OG_XPOS + 1) % OG_ST) * OG_STAGE;
constexpr uint32_t OG_SH2 = ((OG_XPOS + 2) % OG_ST) * OG_STAGE;
constexpr uint32_t OG_SRED = ((OG_XPOS + 3) % OG_ST) * OG_STAGE;
constexpr uint32_t OG_SSTAT = OG_SRED + 16384;
constexpr uint32_t OG_SGU = OG_SRED + 8192;
constexpr uint32_t OG_SFIN = OG_SGU + 256;
#define OGM 2
#define OG_MT(b) ((((b) >> OGM) & 15) ^ (((b) & 64) ? 15 : 0))
#define OG_NT(b) (((b) & ((1 << OGM) - 1)) + (((b) >> (4 + OGM)) << OGM))
#define TAIL_SETUP \
  const uint32_t bar_full = sbase + AT_SBAR, bar_empty = bar_full + 40; \
  const uint32_t bar_wd = bar_full + 168, bar_col = bar_full + 176, bar_out = bar_full + 184, bar_end = bar_full + 192; \
  const uint32_t bar_key = bar_full + 200, bar_h2 = bar_full + 208, bar_sel = bar_full + 216; \
  const int mt = OG_MT(blockIdx.x), nt = OG_NT(blockIdx.x); \
  const int m0 = mt * 128, n0 = nt * 128; \
  const bool has_moe = (int)blockIdx.x < OG_MOE; \
  (void)bar_empty; (void)bar_wd; (void)bar_col; (void)bar_out; (void)bar_end; (void)bar_key; (void)bar_h2; (void)bar_sel; (void)m0; (void)n0; (void)has_moe;

__device__ __forceinline__ void tail_producer(uint32_t sbase, uint32_t ph, uint64_t pol, const CUtensorMap* tmA, const CUtensorMap* tmB, const CUtensorMap* tmD) {
  TAIL_SETUP
  uint32_t stage = OG_POS % OG_ST;
  int kb = 0;
  #pragma unroll 1
  for (int seg = 0; seg < 2; seg++) {
    mbar_wait(bar_full + 264 + 80 * seg, 0);
    fence_proxy_async_global();
    const int end = seg == 0 ? 32 - OG_PRE2 : has_moe ? OG_NKB : 64 - OG_PRE2;
    #pragma unroll 1
    for (; kb < end; kb++) {
      const uint32_t fb = bar_full + 8 * stage, sa = sbase + stage * OG_STAGE;
      const int k0 = own_kb(kb) * 64;
      mbar_wait(bar_empty + 8 * stage, ph);
      mbar_expect_tx(fb, OG_STAGE);
      tma_load_3d_hint(sa + 16384, tmB, k0, 2 * nt, fb, pol);
      tma_load_2d_hint(sa, tmA, k0, m0, fb, pol);
      if (++stage == OG_ST) { stage = 0; ph ^= 1; }
    }
  }
  if (has_moe) {
    mbar_wait(bar_empty + 8 * (OG_XPOS % OG_ST), ph);
    mbar_expect_tx(bar_wd, OG_STAGE);
    tma_load_3d_hint(sbase + OG_SWD1, tmD, blockIdx.x * 32, 8, bar_wd, pol);
  }
}

__device__ __forceinline__ uint32_t out2(uint32_t x1, uint32_t mb2, uint32_t ih, uint32_t il, uint32_t c1, uint32_t sb, uint32_t gb) {
  const uint32_t h2 = badd2(bmul2(ln_norm2b(x1, mb2, ih, il), c1), sb);
  return badd2(x1, bmul2(gb, bfma2(h2, 0u, h2)));
}
#define OGTIME gtime()
#define X_PACE 200
#define Y_SLACK 96
#define OG_STAG 3
#define WD_PACE 300
__device__ __forceinline__ void tail_exchange(uint32_t sbase, const bf16* __restrict__ w_down, const bf16* __restrict__ w_r, const bf16* __restrict__ x, bf16* __restrict__ out) {
    TAIL_SETUP
    const int lane = threadIdx.x & 31, wi = __shfl_sync(0xffffffffu, threadIdx.x >> 5, 0);
    if (wi == 3) {
      if (blockIdx.x < AT_NFULL) {
        uint32_t a, b;
        asm volatile("ld.relaxed.gpu.global.u32 %0, [%1];" : "=r"(a) : "l"(g_smid + 32 + blockIdx.x - lane) : "memory");
        b = __shfl_down_sync(0xffffffffu, a, 1);
        unsigned int* tm = g_tmax + blockIdx.x - min((int)blockIdx.x, __ffs(__ballot_sync(0xffffffffu, b >= a)) - 1);
        mbar_wait(bar_full + 312, 0);
        if (lane == 0) {
          asm volatile("mov.u32 %0, %%globaltimer_lo;" : "=r"(a));
          asm volatile("red.relaxed.gpu.global.max.u32 [%0], %1;" :: "l"(tm), "r"(a) : "memory");
          __nanosleep(AL_SLEEP);
          asm volatile("ld.relaxed.gpu.global.u32 %0, [%1];" : "=r"(b) : "l"(tm) : "memory");
          b -= a;
          sts_u32(sbase + OG_SMISC + 32, (b < AL_MAX ? b * 13 / 8 : 0u));
          mbar_arrive(bar_full + 320);
        }
        named_bar_sync(15, 32);
      }
      mbar_wait(bar_full + 344, 0);
      float a = g_scal[lane], b = g_scal[32 + lane];
      #pragma unroll
      for (int i = 0; i < 3; i++) {
        const uint4 v = *reinterpret_cast<const uint4*>(g_col + nt * 1536 + i * 512 + lane * 16);
        sts_u32x4(sbase + OG_SCOL + i * 512 + lane * 16, v.x, v.y, v.z, v.w);
      }
      #pragma unroll
      for (int o = 16; o > 0; o >>= 1) { a += __shfl_xor_sync(0xffffffffu, a, o); b += __shfl_xor_sync(0xffffffffu, b, o); }
      if (lane == 0) sts_f32x2(sbase + OG_SMISC, a, b);
      const uint64_t pol = policy_evict_first();
      #pragma unroll 1
      for (int r = lane >> 4; r < 128; r += 4) {
        __nanosleep(X_PACE);
        #pragma unroll
        for (int j = 0; j < 4; j += 2)
          asm volatile("cp.async.cg.shared.global.L2::cache_hint [%0], [%1], 16, %2;" :: "r"(sbase + OG_XSLOT + (lane & 8) * 2048 + (r + j) * 128 + (((lane ^ (r + j)) & 7) << 4)),
                       "l"(x + (size_t)(m0 + r + j) * T_D + n0 + (lane & 15) * 8), "l"(pol) : "memory");
      }
      asm volatile("cp.async.wait_all;" ::: "memory");
      __syncwarp();
      if (lane == 0) mbar_arrive(bar_col);
    } else if (wi == 2) {
      if (elect_one()) {
        const uint32_t b_free = bar_full + (blockIdx.x < AT_NFULL ? 80 : 160);
        mbar_wait(b_free, 0); mbar_wait(b_free, 1);
        #pragma unroll 1
        for (unsigned int i = 0; i < (1u << 20) && ld_acquire(&g_hcnt[32 * (1 + (blockIdx.x >> 3)) + 4 + ((blockIdx.x >> 1) & 3)]) == 0u; i++) __nanosleep(POLL_NS);
        TL_MARK2(23, true);
        fence_proxy_async_global();
        TL_MARK2(4, true);
        mbar_expect_tx(bar_full + 272, 32768);
        bulk_load_hint(sbase + OG_PSLOT, g_pre + blockIdx.x * 2048, 32768, bar_full + 272, policy_evict_first());
      }
      named_bar_sync(14, 32);
      if (has_moe) {
        mbar_wait(bar_full + 96, 1); mbar_wait(bar_full + 304, 0);
        const uint64_t pol = policy_evict_first();
        #pragma unroll 1
        for (int r = 0; r < 32; r++) {
          __nanosleep(WD_PACE);
          #pragma unroll
          for (int j = 0; j < 2; j++)
            asm volatile("cp.async.cg.shared.global.L2::cache_hint [%0], [%1], 16, %2;" :: "r"(sbase + OG_SWD + (4 * j + (lane >> 3)) * 4096 + r * 128 + (((lane ^ r) & 7) << 4)),
                         "l"((const uint8_t*)w_down + (size_t)blockIdx.x * 65536 + r * 2048 + j * 512 + lane * 16), "l"(pol) : "memory");
        }
        asm volatile("cp.async.wait_all;" ::: "memory");
        __syncwarp();
        if (lane == 0) mbar_arrive(bar_wd);
      }
    }
    const uint4 wrv = ldg_nc_v4(w_r + threadIdx.x * 8);
    mbar_wait(bar_end, 0);
    if (threadIdx.x == 96) XT(10);
    TL_MARK2(22, lane == 0);
    if (wi == 0) {
      uint32_t k1 = 0u, k2 = 0u;
      #pragma unroll 1
      for (unsigned int spin = 0; spin < (1u << 22) && __any_sync(0xffffffffu, k1 == 0u); spin++) asm volatile("ld.relaxed.gpu.global.u32 %0, [%1];" : "=r"(k1) : "l"(g_key + lane) : "memory");
      TL_MARK2(28, lane == 0);
      warp_top2(k1, k2);
      if (lane == 0) {
        const uint32_t r1 = 0xffffu - (k1 & 0xffffu), r2 = 0xffffu - (k2 & 0xffffu);
        sts_u32x4(sbase + OG_SMISC + 64, r1, r2, (r1 >> 7) * 2, (r2 >> 7) * 2 + ((r1 >> 7) == (r2 >> 7)));
        mbar_arrive(bar_sel);
      }
    } else if (wi < 3) {
          mbar_wait(bar_key, 0);
          const uint4 kk = lds_u32x4(sbase + OG_SSTAT + 1024 + lane * 16);
          uint32_t k1 = max(kk.x, kk.y), k2 = min(kk.x, kk.y);
          k2 = max(max(k2, min(kk.z, kk.w)), min(k1, max(kk.z, kk.w))); k1 = max(k1, max(kk.z, kk.w));
          warp_top2(k1, k2);
          if (wi == 1) {
            if (lane == 0) {
              if (nt == (mt & 7)) st_relaxed2(g_key + mt * 2, k1, k2);
              sts_u32x2(sbase + OG_SMISC + 96, (~k1 >> 4) & 7u, (~k2 >> 4) & 7u);
              mbar_arrive(bar_full + 352);
            }
            TL_MARK2(27, lane == 0);
          } else {
            const uint32_t r = (~((lane & 16) ? k2 : k1)) & 127u, ch = lane & 15;
            const uint2 st = lds_u32x2(sbase + OG_SSTAT + r * 8);
            const uint4 xc = lds_u32x4(sbase + OG_XSLOT + (ch >> 3) * 16384 + r * 128 + (((ch ^ r) & 7) << 4));
            const uint4 c1 = lds_u32x4(sbase + OG_SCOL + 768 + ch * 16), sh = lds_u32x4(sbase + OG_SCOL + 1024 + ch * 16);
            const float inr = __uint_as_float(st.y);
            float* dst = reinterpret_cast<float*>(g_cand + (mt * 2 + (lane >> 4)) * 256 + nt * 16 + ch);
            st_tagged4(dst + 512, __uint_as_float(ln_mod2(xc.x, st.x, inr, c1.x, sh.x)), __uint_as_float(ln_mod2(xc.y, st.x, inr, c1.y, sh.y)),
                       __uint_as_float(ln_mod2(xc.z, st.x, inr, c1.z, sh.z)), __uint_as_float(ln_mod2(xc.w, st.x, inr, c1.w, sh.w)));
            st_tagged4(dst, __uint_as_float(xc.x), __uint_as_float(xc.y), __uint_as_float(xc.z), __uint_as_float(xc.w));
          }
    }
    mbar_wait(bar_sel, 0);
    const uint4 sel = lds_u32x4(sbase + OG_SMISC + 64);
    const int sel0 = (int)sel.x, sel1 = (int)sel.y;
    {
      const float* src0 = reinterpret_cast<const float*>(g_cand + sel.z * 256 + 128 + threadIdx.x);
      const float* src1 = reinterpret_cast<const float*>(g_cand + sel.w * 256 + 128 + threadIdx.x);
      float4 h0, h1;
      #pragma unroll 1
      for (unsigned int spin = 0; spin < (1u << 20); spin++) { h0 = ld_tagged4(src0); h1 = ld_tagged4(src1); if (__all_sync(0xffffffffu, tagged4(h0) & tagged4(h1))) break; }
      sts_f32x4(sbase + OG_SH2 + threadIdx.x * 16, h0.x, h0.y, h0.z, h0.w);
      sts_f32x4(sbase + OG_SH2 + 2048 + threadIdx.x * 16, h1.x, h1.y, h1.z, h1.w);
      __syncwarp();
      if (lane == 0) mbar_arrive(bar_h2);
      TL_MARK2(12, lane == 0);
      if (blockIdx.x >> 6) h0 = h1;
      float v[8], wr[8];
      unpack8(make_uint4(__float_as_uint(h0.x), __float_as_uint(h0.y), __float_as_uint(h0.z), __float_as_uint(h0.w)), v); unpack8(wrv, wr);
      float r = 0.f;
      #pragma unroll
      for (int i = 0; i < 8; i++) r = fmaf(v[i], wr[i], r);
      #pragma unroll
      for (int o = 16; o > 0; o >>= 1) r += __shfl_xor_sync(0xffffffffu, r, o);
      if (lane == 0) sts_f32(sbase + OG_SMISC + 192 + wi * 4, r);
    }
    mbar_wait(bar_out, 0);
    {
      const uint2 cg = lds_u32x2(sbase + OG_SMISC + 96);
      #pragma unroll
      for (int i = 0; i < 4; i++) {
        const int r = (i < 2 ? cg.x : cg.y) * 16 + (i & 1) * 8 + (threadIdx.x >> 4), ch = threadIdx.x & 15;
        if (m0 + r != sel0 && m0 + r != sel1)
          *reinterpret_cast<uint4*>(out + (size_t)(m0 + r) * T_D + n0 + ch * 8) =
              lds_u32x4(sbase + OG_OSLOT + (ch >> 3) * 16384 + r * 128 + (((ch & 7) ^ (r & 7)) << 4));
      }
    }
    if (blockIdx.x == 0 && threadIdx.x < 68) *reinterpret_cast<uint4*>(g_hcnt + 32 * (threadIdx.x >> 2) + 4 * (threadIdx.x & 3)) = make_uint4(0u, 0u, 0u, 0u);
    if (threadIdx.x < 64) g_modpart[blockIdx.x * 64 + threadIdx.x] = 0.f;
    if (threadIdx.x == 64) g_tmax[blockIdx.x] = 0u;
    {
      const int tk = blockIdx.x >> 6, c0 = (blockIdx.x & 63) * 16;
      const uint32_t gb2 = *reinterpret_cast<const uint32_t*>(g_col + (c0 >> 7) * 1536 + 512 + 768 + ((c0 & 127) + (threadIdx.x & 14)) * 2);
      const uint32_t* xp = reinterpret_cast<const uint32_t*>(g_cand + (tk ? sel.w : sel.z) * 256) + ((c0 + (threadIdx.x & 14)) >> 1);
      uint32_t x2 = 0u;
      #pragma unroll 1
      for (unsigned int spin = 0; spin < (1u << 20) && __any_sync(0xffffffffu, x2 == 0u); spin++) asm volatile("ld.relaxed.gpu.global.u32 %0, [%1];" : "=r"(x2) : "l"(xp) : "memory");
      const float* src = g_ypart + (size_t)((threadIdx.x >> 2) * 2 + tk) * T_D + c0 + (threadIdx.x & 3) * 4;
      const bool four = threadIdx.x < (OG_MOE - 96) * 4;
      if (threadIdx.x == 0) hint_wait(CNT_Y, (uint32_t)(OG_MOE - Y_SLACK));
      named_bar_sync(10, 128);
      float4 p0, p1, p2, p3;
      #pragma unroll 1
      for (unsigned int spin = 0; spin < (1u << 20); spin++) {
        p0 = ld_tagged4(src); p1 = ld_tagged4(src + 64 * T_D); p2 = ld_tagged4(src + 128 * T_D); p3 = ld_tagged4(four ? src + 192 * T_D : src);
        if (__all_sync(0xffffffffu, tagged4(p0) & tagged4(p1) & tagged4(p2) & tagged4(p3))) break;
      }
      if (four) { p2.x += p3.x; p2.y += p3.y; p2.z += p3.z; p2.w += p3.w; }
      p0.x = (p0.x + p1.x) + p2.x; p0.y = (p0.y + p1.y) + p2.y; p0.z = (p0.z + p1.z) + p2.z; p0.w = (p0.w + p1.w) + p2.w;
      #pragma unroll
      for (int o = 4; o <= 16; o <<= 1) {
        p0.x += __shfl_xor_sync(0xffffffffu, p0.x, o); p0.y += __shfl_xor_sync(0xffffffffu, p0.y, o);
        p0.z += __shfl_xor_sync(0xffffffffu, p0.z, o); p0.w += __shfl_xor_sync(0xffffffffu, p0.w, o);
      }
      if (lane < 4) sts_f32x4(sbase + OG_SFIN + (threadIdx.x >> 5) * 64 + lane * 16, p0.x, p0.y, p0.z, p0.w);
      named_bar_sync(10, 128);
      TL_MARK2(21, threadIdx.x == 0);
      if (threadIdx.x < 16) {
        const uint32_t ya = sbase + OG_SFIN + threadIdx.x * 4, rp = sbase + OG_SMISC + 192;
        float y = (lds_f32(ya) + lds_f32(ya + 64)) + (lds_f32(ya + 128) + lds_f32(ya + 192));
        const float r = rbf((lds_f32(rp) + lds_f32(rp + 4)) + (lds_f32(rp + 8) + lds_f32(rp + 12)));
        const float rs = rbf(sigmoid_f(r));
        const uint32_t h2p = lds_u32(sbase + OG_SH2 + tk * 2048 + (c0 + (threadIdx.x & 14)) * 2);
        const float fh = (lane & 1) ? bfhi(h2p) : bflo(h2p);
        y = rbf(y);
        y = rbf(y * rs);
        const float upd = rbf(rbf(fh * 0.0f) + y);
        out[(size_t)(tk ? sel1 : sel0) * T_D + c0 + threadIdx.x] =
            __float2bfloat16_rn(((lane & 1) ? bfhi(x2) : bflo(x2)) + rbf(((lane & 1) ? bfhi(gb2) : bflo(gb2)) * rbf(fh + upd)));
      }
    }
    if (threadIdx.x == 0) XT(11);
    TL_END(4, threadIdx.x == 0);
}

__device__ __forceinline__ void load_pre(uint4* pre, uint32_t sbase, uint32_t buf, int t2) {
  mbar_wait(sbase + AT_SBAR + 272, 0);
  #pragma unroll
  for (int i = 0; i < 8; i++) pre[i] = lds_u32x4(sbase + buf + i * 4096 + t2 * 16);
}
__device__ __forceinline__ void tail_consumer(uint32_t sbase, const CUtensorMap* tmOut, const uint4 (&pre)[8], int cwg, const bf16* __restrict__ w_gate, const bf16* __restrict__ w_up) {
    TAIL_SETUP
    const int tid = threadIdx.x & 127, t2 = threadIdx.x - 128;
    const int warp = tid >> 5, lane = tid & 31, w8 = t2 >> 5;
    const uint32_t dbase = (sbase & 0x3FFFFu) >> 4;
    const uint32_t a_base = dbase + ((cwg * 8192) >> 4) + (1u << 16);
    const uint32_t b_base = dbase + (16384 >> 4) + (512u << 16);
    TL_MARK2(25, threadIdx.x == 128);
    const uint64_t pol = policy_evict_first();
    const bf16* pw = ((lane & 16) ? w_up : w_gate) + (size_t)(w8 * 128 + (lane & 3) * 4) * T_F + (has_moe ? blockIdx.x : 0) * 32 + ((lane >> 2) & 3) * 8;
    uint4 wv[32];
    float acc[64];
    #pragma unroll
    for (int i = 0; i < 8; i++) {
      acc[8 * i] = bflo(pre[i].x); acc[8 * i + 1] = bfhi(pre[i].x); acc[8 * i + 2] = bflo(pre[i].y); acc[8 * i + 3] = bfhi(pre[i].y);
      acc[8 * i + 4] = bflo(pre[i].z); acc[8 * i + 5] = bfhi(pre[i].z); acc[8 * i + 6] = bflo(pre[i].w); acc[8 * i + 7] = bfhi(pre[i].w);
    }
    if (lane == 0) mbar_arrive(bar_full + 304);
    if (blockIdx.x < AT_NFULL) {
      const uint32_t c0 = clock_lo();
      mbar_wait(bar_full + 320, 0);
      const uint32_t d = lds_u32(sbase + OG_SMISC + 32);
      while (clock_lo() - c0 < d) {}
    }
    {
      uint32_t stage = OG_POS % OG_ST, phase = (OG_POS / OG_ST) & 1, prev = 12;
      int kb = 0;
      #pragma unroll
      for (int g = 0; g <= OG_NG; g++) {
        const int end = g == OG_NG ? (has_moe ? OG_NKB : 64 - OG_PRE2) : LD_FIRST + g * OG_GRP + LD_STAG * cwg;
        #pragma unroll 1
        do {
          mbar_wait(bar_full + 8 * stage, phase);
          if (OG_STAG > 0 && g == OG_NG && cwg == 1 && kb == end - OG_STAG) named_bar_sync(7, 256);
          const uint32_t a_lo = a_base + stage * (OG_STAGE >> 4), b_lo = b_base + stage * (OG_STAGE >> 4);
          wgmma_fence();
          wgmma_m64n128k16_ss_tb<0, 0>(acc, a_lo, b_lo, 1);
          wgmma_m64n128k16_ss_tb<2, 128>(acc, a_lo, b_lo, 1);
          wgmma_m64n128k16_ss_tb<4, 256>(acc, a_lo, b_lo, 1);
          wgmma_m64n128k16_ss_tb<6, 384>(acc, a_lo, b_lo, 1);
          wgmma_commit();
          if (OG_STAG > 0 && g == OG_NG && cwg == 0 && kb == end - 1) named_bar_arrive(7, 256);
          wgmma_wait<1>();
          if (tid == 0) mbar_arrive(bar_empty + 8 * prev);
          prev = stage;
          if (++stage == OG_ST) { stage = 0; phase ^= 1; }
        } while (++kb < end);
        #pragma unroll
        for (int j = 4 * g; j < 4 * g + 4 && j < 32; j++) wv[j] = ldg_stream_v4(pw + (size_t)(16 * (j >> 2) + (j & 3)) * T_F, pol);
      }
    }
    mbar_wait(bar_col, 0);
    if (__builtin_expect(!has_moe, 0)) {
      load_pre(wv, sbase, AT_SQ, t2);
    }
    wgmma_wait<0>();
    fence_regs(acc);
    if (__builtin_expect(!has_moe, 0)) {
      #pragma unroll
      for (int i = 0; i < 8; i++) {
        acc[8 * i] += bflo(wv[i].x); acc[8 * i + 1] += bfhi(wv[i].x); acc[8 * i + 2] += bflo(wv[i].y); acc[8 * i + 3] += bfhi(wv[i].y);
        acc[8 * i + 4] += bflo(wv[i].z); acc[8 * i + 5] += bfhi(wv[i].z); acc[8 * i + 6] += bflo(wv[i].w); acc[8 * i + 7] += bfhi(wv[i].w);
      }
    }
    if (tid == 0) mbar_arrive(bar_end);
    TL_MARK2(9, lane == 0);
    const int q2 = 2 * (lane & 3);
    const uint32_t frag = (64 * cwg + 16 * warp + (lane & 7) + 8 * ((lane >> 3) & 1)) * 128;
    const int fsw = lane & 7, fhi = lane >> 4;
    {
      float dl[4] = {0.f, 0.f, 0.f, 0.f}, da[4] = {0.f, 0.f, 0.f, 0.f}, db[4] = {0.f, 0.f, 0.f, 0.f};
      const uint32_t tb = sbase + OG_SCOL + (lane & 8) * 32 + (lane & 3) * 8, g = lane >> 2;
      const uint32_t msk = (g == 1 || g == 2) ? 0xffffffffu : 0u, one = g == 0 ? 0x3F803F80u : 0u;
      #pragma unroll
      for (int J = 0; J < 16; J += 2) {
        const uint32_t ad = sbase + OG_XSLOT + (J >> 3) * 16384 + frag + ((((J & 7) + fhi) ^ fsw) << 4);
        uint32_t xr[4];
        ldmatrix_x4(ad, xr[0], xr[1], xr[2], xr[3]);
        const uint2 cw = lds_u32x2(tb + J * 16);
        #pragma unroll
        for (int h = 0; h < 2; h++) {
          const uint32_t ga = lds_u32(sbase + OG_SCOL + 512 + (8 * (J + h) + q2) * 2);
          xr[2 * h] = badd2(xr[2 * h], bmul2(ga, pack_bf16(acc[4 * (J + h)], acc[4 * (J + h) + 1])));
          xr[2 * h + 1] = badd2(xr[2 * h + 1], bmul2(ga, pack_bf16(acc[4 * (J + h) + 2], acc[4 * (J + h) + 3])));
        }
        stmatrix_x4(ad, xr[0], xr[1], xr[2], xr[3]);
        mma_bf16(dl, xr[0], xr[1], xr[2], xr[3], (cw.x & msk) | one, (cw.y & msk) | one);
        mma_bf16(da, xr[0], xr[1], xr[2], xr[3], xr[0], xr[2]);
        mma_bf16(db, xr[0], xr[1], xr[2], xr[3], xr[1], xr[3]);
      }
      {
        const int dsrc = (lane & ~3) + (g >> 1);
        const float qa = __shfl_sync(0xffffffffu, (g & 1) ? da[1] : da[0], dsrc), qb = __shfl_sync(0xffffffffu, (g & 1) ? db[3] : db[2], dsrc);
        const float e0 = __shfl_xor_sync(0xffffffffu, (lane & 1) ? dl[0] : dl[2], 1), e1 = __shfl_xor_sync(0xffffffffu, dl[3], 1);
        if ((lane & 3) < 2) {
          const bool hi = lane & 1;
          st_tagged4(reinterpret_cast<float*>(g_part1 + ((mt * 8 + w8) * 8 + nt) * 16 + g + (hi ? 8 : 0)),
                     hi ? e0 : dl[0], hi ? qb : qa, hi ? e1 + dl[2] : dl[1] + e0, 1.0f);
        }
      }
    }
    TL_MARK2(10, lane == 0);
    uint4 wd[16];
    if (has_moe) mbar_wait(bar_wd, 0);
    #pragma unroll
    for (int i = 0; i < 16; i++) wd[i] = lds_u32x4(sbase + (cwg ? OG_SWD1 : OG_SWD) + warp * 8192 + (i >> 3) * 4096 + (i & 6) * 512 + (i & 1) * 128 + (lane & 3) * 256 + (((lane >> 2) ^ (2 * (lane & 3) + (i & 1))) << 4));
    {
      const float* src = reinterpret_cast<const float*>(g_part1 + ((mt * 8 + w8) * 8 + (lane & 1) * 4) * 16 + (lane >> 1));
      float4 v, v1, v2, v3;
      #pragma unroll 1
      for (unsigned int spin = 0; spin < (1u << 22); spin++) {
        v = ld_tagged4(src); v1 = ld_tagged4(src + 64); v2 = ld_tagged4(src + 128); v3 = ld_tagged4(src + 192);
        if (__all_sync(0xffffffffu, tagged4(v) & tagged4(v1) & tagged4(v2) & tagged4(v3))) break;
        __nanosleep(100);
      }
      __syncwarp();
      TL_MARK2(26, lane == 0);
      v.x = (v.x + v1.x) + (v2.x + v3.x); v.y = (v.y + v1.y) + (v2.y + v3.y); v.z = (v.z + v1.z) + (v2.z + v3.z);
      v.x += __shfl_xor_sync(0xffffffffu, v.x, 1); v.y += __shfl_xor_sync(0xffffffffu, v.y, 1); v.z += __shfl_xor_sync(0xffffffffu, v.z, 1);
      const float mean = v.x * (1.0f / T_D);
      const float var = fmaxf(fmaf(-mean, mean, v.y * (1.0f / T_D)), 0.f);
      const uint32_t mb2 = pack_bf16(mean, mean);
      const float inv = rcp_approx(rbf(sqrt_approx(rbf(rbf(var) + 1e-05f))));
      {
        const float2 sc = lds_f32x2(sbase + OG_SMISC);
        const uint32_t key = rank_key(rbf(fmaf(fmaf(-bflo(mb2), sc.x, v.z), inv, sc.y)), m0 + 16 * w8 + (lane >> 1));
        mbar_wait(bar_end, 0);
        if (lane & 1) sts_u32(sbase + OG_SSTAT + 1024 + (16 * w8 + (lane >> 1)) * 4, key);
        else sts_u32x2(sbase + OG_SSTAT + (16 * w8 + (lane >> 1)) * 8, mb2, __float_as_uint(inv));
        __syncwarp();
        if (lane == 0) mbar_arrive(bar_key);
      }
      const uint32_t ih = pack_bf16(inv, inv), il = pack_bf16(inv - bflo(ih), inv - bflo(ih));
      const uint32_t mba = __shfl_sync(0xffffffffu, mb2, 2 * (lane >> 2)), mbb = __shfl_sync(0xffffffffu, mb2, 2 * (lane >> 2) + 16);
      const uint32_t iha = __shfl_sync(0xffffffffu, ih, 2 * (lane >> 2)), ihb = __shfl_sync(0xffffffffu, ih, 2 * (lane >> 2) + 16);
      const uint32_t ila = __shfl_sync(0xffffffffu, il, 2 * (lane >> 2)), ilb = __shfl_sync(0xffffffffu, il, 2 * (lane >> 2) + 16);
      #pragma unroll 2
      for (int J = 0; J < 16; J += 2) {
        const uint32_t off = (J >> 3) * 16384 + frag + ((((J & 7) + fhi) ^ fsw) << 4);
        uint32_t xr[4];
        ldmatrix_x4(sbase + OG_XSLOT + off, xr[0], xr[1], xr[2], xr[3]);
        #pragma unroll
        for (int h = 0; h < 2; h++) {
          const uint32_t ca = sbase + OG_SCOL + 512 + (8 * (J + h) + q2) * 2;
          const uint32_t c1 = lds_u32(ca + 256), sh = lds_u32(ca + 512), gb = lds_u32(ca + 768);
          xr[2 * h] = out2(xr[2 * h], mba, iha, ila, c1, sh, gb);
          xr[2 * h + 1] = out2(xr[2 * h + 1], mbb, ihb, ilb, c1, sh, gb);
        }
        stmatrix_x4(sbase + OG_OSLOT + off, xr[0], xr[1], xr[2], xr[3]);
      }
      fence_proxy_async();
      mbar_wait(bar_full + 352, 0);
      const uint2 cg = lds_u32x2(sbase + OG_SMISC + 96);
      __syncwarp();
      if (elect_one()) {
        mbar_arrive(bar_out);
        if (cg.x != w8 && cg.y != w8) {
          asm volatile("cp.async.bulk.tensor.2d.global.shared::cta.bulk_group [%0, {%2, %3}], [%1];" :: "l"(tmOut), "r"(sbase + OG_OSLOT + w8 * 2048), "r"(n0), "r"(m0 + 16 * w8) : "memory");
          asm volatile("cp.async.bulk.tensor.2d.global.shared::cta.bulk_group [%0, {%2, %3}], [%1];" :: "l"(tmOut), "r"(sbase + OG_OSLOT + 16384 + w8 * 2048), "r"(n0 + 64), "r"(m0 + 16 * w8) : "memory");
          bulk_commit();
        }
      }
      TL_MARK2(24, lane == 0);
    }
    if (has_moe) mbar_wait(bar_h2, 0);
    TL_MARK2(13, lane == 0);
    if (has_moe) {
      const GemvSel sel = gemv_sel(lane);
      {
        float d[4][4];
        #pragma unroll
        for (int c = 0; c < 4; c++) { d[c][0] = 0.f; d[c][1] = 0.f; d[c][2] = 0.f; d[c][3] = 0.f; }
        #pragma unroll
        for (int st = 0; st < 8; st++) {
          const uint2 hb = lds_u32x2(sbase + OG_SH2 + ((lane >> 2) & 1) * 2048 + (w8 * 128 + st * 16 + (lane & 3) * 4) * 2);
          #pragma unroll
          for (int j = 0; j < 4; j++) mma_bf16(d[j], wv[4 * st + j].x, wv[4 * st + j].y, wv[4 * st + j].z, wv[4 * st + j].w, GEMV_B0(j, hb, sel), GEMV_B1(j, hb, sel));
        }
        #pragma unroll
        for (int e = 0; e < 4; e++) d[0][e] = (d[0][e] + d[1][e]) + (d[2][e] + d[3][e]);
        const float4 r = gemv_out(d[0], lane);
        sts_f32x4(sbase + OG_SRED + w8 * 512 + (((lane >> 4) * 2 + (lane & 1)) * 32 + ((lane >> 2) & 3) * 8 + (lane & 2) * 2) * 4, r.x, r.y, r.z, r.w);
      }
      named_bar_sync(9, 256);
      if (t2 < 64) {
        float gp[8], up[8];
        #pragma unroll
        for (int w = 0; w < 8; w++) { gp[w] = lds_f32(sbase + OG_SRED + w * 512 + t2 * 4); up[w] = lds_f32(sbase + OG_SRED + w * 512 + 256 + t2 * 4); }
        const float gs = ((gp[0] + gp[1]) + (gp[2] + gp[3])) + ((gp[4] + gp[5]) + (gp[6] + gp[7]));
        const float us = ((up[0] + up[1]) + (up[2] + up[3])) + ((up[4] + up[5]) + (up[6] + up[7]));
        asm volatile("st.shared.u16 [%0], %1;" :: "r"(sbase + OG_SGU + ((t2 & ~15) + ((t2 >> 1) & 3) * 4 + ((t2 >> 3) & 1) * 2 + (t2 & 1)) * 2), "h"((uint16_t)pack_bf16(silu_bf(rbf(gs)) * rbf(us), 0.f)) : "memory");
      }
      named_bar_sync(9, 256);
      TL_MARK2(20, threadIdx.x == 128);
      float d[4][4];
      #pragma unroll
      for (int c = 0; c < 4; c++) { d[c][0] = 0.f; d[c][1] = 0.f; d[c][2] = 0.f; d[c][3] = 0.f; }
      #pragma unroll
      for (int st = 0; st < 2; st++) {
        const uint2 g = lds_u32x2(sbase + OG_SGU + ((lane >> 2) & 1) * 64 + st * 32 + (lane & 3) * 8);
        #pragma unroll
        for (int j = 0; j < 4; j++) {
          const uint32_t b0 = GEMV_B0(j, g, sel), b1 = GEMV_B1(j, g, sel);
          mma_bf16(d[j & 1], wd[4 * st + j].x, wd[4 * st + j].y, wd[4 * st + j].z, wd[4 * st + j].w, b0, b1);
          mma_bf16(d[2 + (j & 1)], wd[8 + 4 * st + j].x, wd[8 + 4 * st + j].y, wd[8 + 4 * st + j].z, wd[8 + 4 * st + j].w, b0, b1);
        }
      }
      #pragma unroll
      for (int e = 0; e < 4; e++) { d[0][e] += d[1][e]; d[2][e] += d[3][e]; }
      const float4 y0 = gemv_out(d[0], lane), y1 = gemv_out(d[2], lane);
      float* yp = g_ypart + (size_t)(blockIdx.x * 2 + (lane & 1)) * T_D + w8 * 128 + (lane >> 2) * 8 + (lane & 2) * 2;
      st_tagged4(yp, y0.x, y0.y, y0.z, y0.w);
      st_tagged4(yp + 64, y1.x, y1.y, y1.z, y1.w);
      named_bar_sync(9, 256);
      if (t2 == 0) hint_arrive(CNT_Y);
    }
    bulk_wait_read<0>();
    TL_MARK2(14, threadIdx.x == 128);
    TL_CLK(4, 1, threadIdx.x == 128);
}

__device__ __forceinline__ int help_njobs() { return blockIdx.x < 128 ? OG_JOBS : 16 - OG_JOBS; }
__device__ __forceinline__ int help_job(int i) { return (i < OG_JOBS ? 16 * i + (blockIdx.x >> 7) * 2 : 112 + (i - OG_JOBS) * 2) + (blockIdx.x & 3) * 4; }
__device__ __noinline__ void store_warp(uint32_t sbase, const CUtensorMap* tmO, int item0, int n_items) {
  if (elect_one()) {
    const uint32_t bars = sbase + AT_SBAR, b_q0 = bars + 80, b_ob = bars + 96, b_ordy = bars + 104, b_acq = bars + 264;
    const unsigned int* cnt = &g_hcnt[32 * (1 + OG_MT(blockIdx.x)) + 2];
    #pragma unroll 1
    for (int q = 0; q < 4 * n_items; q++) {
      const int item = item0 + (q >> 2) * 128, h = (q >> 1) & 1, w = q & 1;
      const bool last = (q >> 2) == n_items - 1;
      if (q == 4 * n_items - 4) { mbar_wait(bars + 288, 0); red_release_add(&g_hcnt[1], 1u); }
      mbar_wait(b_ordy + 8 * (q & 3), q >> 2);
      store_o(tmO, (h ? (last ? sbase + AT_SQ + 32768 : sbase + 2 * 32768) : sbase + AT_SQ) + w * 8192, (item >> 4) * 2 + h, (item & 15) * 128 + w * 64);
      if (w) {
        bulk_wait_read<0>();
        mbar_arrive(h ? b_ob : b_q0);
        bulk_wait<0>();
        fence_proxy_async_global();
        asm volatile("fence.acq_rel.gpu;" ::: "memory");
        hint_arrive(&g_hcnt[32 * (1 + (item & 15)) + 2 + (item >> 7)]);
        if (!h && item < 128) hint_arrive(&g_hcnt[2]);
        if (q == 5) { spin_until(cnt, 16u); mbar_arrive(b_acq); }
      }
    }
    if (n_items == 1) {
      #pragma unroll 1
      for (int i = 0; i < help_njobs(); i++) {
        mbar_wait(b_acq + 16, i & 1);
        TL_MARK2(23, i == OG_JOBS - 1);
        red_release_add(&g_hcnt[32 * (1 + (help_job(i) >> 3)) + 4 + ((help_job(i) >> 1) & 3)], 1u);
        TL_MARK2(4, i == OG_JOBS - 1);
        if (i == PRE_X - 1) { spin_until(&g_hcnt[1], 132u); mbar_arrive(b_acq + 32); }
      }
    }
    if (blockIdx.x < 128) {
      if (n_items == 1) { spin_until(cnt, 16u); mbar_arrive(b_acq); }
      spin_until(&g_hcnt[0], 128u); spin_until(cnt + 1, 16u); mbar_arrive(b_acq + 80);
    }
  }
}

__global__ void __launch_bounds__(384, 1)
fused_kernel(const __grid_constant__ CUtensorMap tmH, const __grid_constant__ CUtensorMap tmW, const __grid_constant__ CUtensorMap tmK,
            const __grid_constant__ CUtensorMap tmV, const __grid_constant__ CUtensorMap tmO, const __grid_constant__ CUtensorMap tmOl, const __grid_constant__ CUtensorMap tmWo,
            const __grid_constant__ CUtensorMap tmD, const __grid_constant__ CUtensorMap tmOut, const __grid_constant__ CUtensorMap tmM, uint32_t zero,
            const uint8_t* __restrict__ pf_wo, const bf16* __restrict__ kc, const bf16* __restrict__ vc,
            const bf16* __restrict__ x, const bf16* __restrict__ cvec, const bf16* __restrict__ w_mod, const bf16* __restrict__ w_r,
            const bf16* __restrict__ w_gate, const bf16* __restrict__ w_up, const bf16* __restrict__ w_down, bf16* __restrict__ out)
{
  extern __shared__ __align__(1024) uint8_t smem_raw[];
  const uint32_t sbase = smem_u32(smem_raw);
  const uint32_t bars = sbase + AT_SBAR;
  const uint32_t b_full = bars, b_empty = bars + 40;
  const uint32_t b_q0 = bars + 80, b_q1 = bars + 88;
  const uint32_t b_ob = bars + 96;
  const uint32_t b_ordy = bars + 104;
  const uint32_t b_pin = bars + 136;
  const uint32_t b_head = bars + 144;
  const uint32_t b_go = bars + 152;
  const uint32_t b_x = bars + 160;
  const int wg = __shfl_sync(0xffffffffu, threadIdx.x >> 7, 0);
  const bool single = blockIdx.x >= AT_NFULL;
  const int item0 = __shfl_sync(0xffffffffu, blockIdx.x < 128 ? (int)blockIdx.x : (int)blockIdx.x + 124, 0), n_items = __shfl_sync(0xffffffffu, single ? 1 : 2, 0);
  TL_START(3);
  if (threadIdx.x == 0) {
    if (sbase & 1023u) __trap();
    for (int i = 0; i < 5; i++) { mbar_init(b_full + 8 * i, 1); mbar_init(b_empty + 8 * i, 2); }
    mbar_init(b_q0, 1); mbar_init(b_q1, 8); mbar_init(b_ob, 1);
    for (int i = 0; i < 4; i++) mbar_init(b_ordy + 8 * i, 4);
    mbar_init(b_pin, 1); mbar_init(b_head, blockIdx.x < 128 ? 8 : 1); mbar_init(b_go, 1); mbar_init(b_x, 1);
    mbar_init(bars + 168, 2); mbar_init(bars + 176, 1); mbar_init(bars + 184, 8); mbar_init(bars + 192, 2);
    mbar_init(bars + 200, 8); mbar_init(bars + 208, 4); mbar_init(bars + 216, 1); mbar_init(bars + 264, 1); mbar_init(bars + 272, 1); mbar_init(bars + 280, 8); mbar_init(bars + 288, 1); mbar_init(bars + 296, 1); mbar_init(bars + 304, 8); mbar_init(bars + 312, 1); mbar_init(bars + 320, 1); mbar_init(bars + 328, 1); mbar_init(bars + 344, 1); mbar_init(bars + 352, 1);
    fence_mbar_init();
  }

  if (wg == 0) {
    reg_dealloc<AT_PREG>();
    if (threadIdx.x < 32) { __syncwarp(); named_bar_arrive(6, 384); }
    if (threadIdx.x >= 64) {
      named_bar_sync(6, 384);
      if (blockIdx.x < 128) {
        named_bar_sync(threadIdx.x >= 96 ? 8 : 9, 288);
        if ((threadIdx.x & 31) == 0) red_release_add(&g_hcnt[32 * (1 + (blockIdx.x >> 3)) + (threadIdx.x >= 96)], 1u);
        TL_MARK2(11, threadIdx.x == 64);
      }
      if (blockIdx.x < 128) {
        mbar_wait(MOD_AT, 0);
        mod_rest(sbase + OG_SCOL, b_q1, threadIdx.x - 64, cvec, w_mod, w_r);
      }
    } else if (threadIdx.x >= 32) {
      named_bar_sync(6, 384);
      store_warp(sbase, &tmO, item0, n_items);
      __syncwarp();
    } else {
     if (elect_one()) {
      const uint64_t pol = policy_evict_first();
      if (blockIdx.x < 128) {
        mbar_expect_tx(b_x, 32768);
        if (X_DLY) { const uint32_t c0 = clock_lo(); while (clock_lo() - c0 < X_DLY) {} }
        bulk_load_hint(sbase + 4 * 32768, x + (size_t)blockIdx.x * 16 * T_D, 32768, b_x, pol);
      }
      prefetch_tmap(&tmW); prefetch_tmap(&tmM); prefetch_tmap(&tmH); prefetch_tmap(&tmWo); prefetch_tmap(&tmOl);
      {
        const uint32_t c0 = clock_lo();
        while (clock_lo() - c0 < W_DLY) {}
        if (blockIdx.x < 128 && (blockIdx.x & 15) >= 4 * H_SPLIT) {
          mbar_expect_tx(bars + 328, 32768);
          tma_load_2d_hint(sbase + 3 * 32768, &tmM, (blockIdx.x & 31) * 64, (blockIdx.x >> 5) * 256, bars + 328, pol);
        }
        while (clock_lo() - c0 < W_DLY + W_FIRST) {}
      }
      uint32_t slot = 0, ph = 1;
      { uint32_t sm; asm volatile("mov.u32 %0, %%smid;" : "=r"(sm)); g_smid[32 + blockIdx.x] = sm; }
      #pragma unroll 1
      for (int it = 0; it < n_items; it++) {
        const int item = item0 + it * 128, hp = item >> 4, qt = item & 15;
        const bool first = it == 0;
        #pragma unroll 1
        for (int j = 0; j < T_D / 64; j++) {
          const uint32_t sl = ring_slot(qp_pos(j, it)), fb = b_full + 8 * sl;
          mbar_wait(b_empty + 8 * sl, ring_par(qp_pos(j, it)) ^ ((j >> 2) & 1) ^ 1);
          if (first && j == 3) mbar_wait(b_head, 0);
          mbar_expect_tx(fb, 49152);
          tma_load_3d_hint(sbase + sl * 32768, &tmW, j * 64, hp * 4, fb, pol);
          if (first && j < PRE_B) {
            if (j == PRE_B - 1) {
              spin_until(&g_hcnt[32 * (1 + qt)], 8u);
              TL_MARK2(16, true);
              fence_proxy_async_global();
              #pragma unroll 1
              for (int i = 0; i < PRE_B; i++) tma_load_2d(sbase + AT_SQ + i * 16384, &tmH, i * 64, qt * 128, b_full + 8 * i);
              mbar_arrive(b_go);
            }
          } else {
            if (first && j == 4 * H_SPLIT) { spin_until(&g_hcnt[32 * (1 + qt) + 1], 8u); fence_proxy_async_global(); }
            if (!first && (j == 0 || j == 2)) mbar_wait(j ? b_q1 : b_q0, 0);
            tma_load_2d_hint(sbase + AT_SQ + (j & 3) * 16384, &tmH, j * 64, qt * 128, fb, first ? pol_normal() : pol);
          }
        }
        #pragma unroll 1
        for (int j = 0; j < 4 * AT_NBLK; j++) {
          const bool isv = (j > 0 && !(j & 1)) || j == 4 * AT_NBLK - 1;
          const int row = hp * 2 * T_SEQ + (isv ? (j - 1) >> 1 : (j + 1) >> 1) * 128;
          const uint32_t fb = b_full + 8 * slot;
          mbar_wait(b_empty + 8 * slot, ph);
          if (!first && j == 3) mbar_wait(b_ob, 0);
          if (j == 4 && it == n_items - 1) mbar_arrive(bars + 288);
          if (j == AL_P && it == 1) mbar_arrive(bars + 312);
          mbar_expect_tx(fb, 32768);
          tma_load_3d_hint(sbase + slot * 32768, isv ? &tmV : &tmK, row, 0, fb, pol);
          if (it == 1 && isv && j >= 2 * WO_LATE && j < 2 * WO_LATE + 32 && blockIdx.x < OG_NKB)
            l2_prefetch_bulk(pf_wo + (size_t)own_kb(blockIdx.x) * 131072 + ((j >> 1) - WO_LATE) * 8192, 8192);
          if (++slot == 5) { slot = 0; ph ^= 1; }
        }
      }
      if (__builtin_expect(single, 0)) {
        spin_until(&g_hcnt[2], 128u);
        fence_proxy_async_global();
        const int nj = OG_JOBS * OG_PRE + (help_njobs() - OG_JOBS) * OG_PRE2;
        int ji = 0, job = help_job(0), kk = 0;
        #pragma unroll 1
        for (int j = 0; j < nj; j++) {
          const uint32_t sl = ring_slot(qp_pos(j, 1)), fb = b_full + 8 * sl;
          mbar_wait(b_empty + 8 * sl, ring_par(qp_pos(j, 1)) ^ ((j >> 2) & 1) ^ 1);
          mbar_expect_tx(fb, 49152);
          tma_load_3d_hint(sbase + sl * 32768, &tmWo, pre_kb(kk) * 64, OG_NT(job) * 2, fb, pol_normal());
          tma_load_3d_hint(sbase + sl * 32768 + 16384, &tmWo, pre_kb(kk) * 64, OG_NT(job) * 2 + 2, fb, pol_normal());
          if (j == 0 || j == 2) mbar_wait(j ? b_ob : b_q0, 0);
          tma_load_2d_hint(sbase + AT_SQ + (j & 3) * 16384, &tmOl, pre_kb(kk) * 64, OG_MT(job) * 128, fb, pol);
          if (++kk == (ji < OG_JOBS ? OG_PRE : OG_PRE2)) { kk = 0; job = help_job(++ji); }
        }
      }
      if (blockIdx.x < 128) {
        if (single) mbar_wait(b_x, 1);
        tail_producer(sbase, 0, pol, &tmOl, &tmWo, &tmD);
      }
     }
    }
    named_bar_sync(12 + (threadIdx.x >> 5), 32);
    if (blockIdx.x < 128) tail_exchange(sbase, w_down, w_r, x, out);
  } else {
    if (blockIdx.x < 128) head_phase(sbase + AT_SQ + 49152, sbase + 4 * 32768, b_x, b_go, b_head, threadIdx.x - 128, zero, cvec, w_mod);
    else { named_bar_sync(6, 384); if (threadIdx.x == 128) mbar_arrive(b_head); }
    TL_MARK2(0, threadIdx.x == 128);
    reg_alloc<AT_CREG>();
    const int cwg = wg - 1;
    const int tid = threadIdx.x & 127;
    const int warp = tid >> 5, lane = tid & 31;
    const uint32_t dbase = (sbase & 0x3FFFFu) >> 4;
    const uint32_t k_base = dbase + (1u << 16);
    const uint32_t v_base = dbase + (1024u << 16);
    const uint32_t w_base = dbase + (512u << 16);
    const uint32_t q_lo = dbase + ((AT_SQ + cwg * 8192) >> 4) + (1u << 16);
    const uint32_t frag = cwg * 8192 + (16 * warp + (lane & 7) + 8 * ((lane >> 3) & 1)) * 128;
    if (cwg == 1) named_bar_arrive(1, 256);
    bool raw = false;
    uint4 pre[8];
    #pragma unroll 1
    for (int it = 0; it < n_items; it++) {
      const bool more = it + 1 < n_items;
      constexpr int nkb = T_D / 64;
      const int ta = __shfl_sync(0xffffffffu, 4 * it, 0);
      float acc[128];
      {
        FS(2 * it, 0);
        #pragma unroll
        for (int i = 0; i < 128; i++) asm volatile("" : "=f"(acc[i]));
        {
          const uint32_t slot = ring_slot(ta), b_lo = w_base + slot * 2048;
          mbar_wait(b_full + 8 * slot, ring_par(ta));
          wgmma_fence();
          wgmma_m64n256k16_ss_tb<0, 0>(acc, q_lo, b_lo, 0);
          wgmma_m64n256k16_ss_tb<2, 128>(acc, q_lo, b_lo, 1);
          wgmma_m64n256k16_ss_tb<4, 256>(acc, q_lo, b_lo, 1);
          wgmma_m64n256k16_ss_tb<6, 384>(acc, q_lo, b_lo, 1);
          wgmma_commit();
        }
        #pragma unroll 1
        for (int j = 1; j < nkb; j++) {
          const uint32_t slot = ring_slot(qp_pos(j, ta >> 2));
          mbar_wait(b_full + 8 * slot, ring_par(qp_pos(j, ta >> 2)) ^ ((j >> 2) & 1));
          if (QP_STAG > 0 && cwg == 1 && j == nkb - QP_STAG) named_bar_sync(7, 256);
          const uint32_t a_lo = q_lo + (j & 3) * 1024, b_lo = w_base + slot * 2048;
          wgmma_fence();
          wgmma_m64n256k16_ss_tb<0, 0>(acc, a_lo, b_lo, 1);
          wgmma_m64n256k16_ss_tb<2, 128>(acc, a_lo, b_lo, 1);
          wgmma_m64n256k16_ss_tb<4, 256>(acc, a_lo, b_lo, 1);
          wgmma_m64n256k16_ss_tb<6, 384>(acc, a_lo, b_lo, 1);
          wgmma_commit();
          if (QP_STAG > 0 && cwg == 0 && j == nkb - 1) named_bar_arrive(7, 256);
          if (j > 0) {
            wgmma_wait<1>();
            if (tid == 0) mbar_arrive(b_empty + 8 * ring_slot(qp_pos(j - 1, ta >> 2)));
          }
        }
        wgmma_wait<0>();
        fence_regs(acc);
        FS(2 * it, 1);
        TL_MARK2(29, threadIdx.x == 256 && it == 0);
        if (tid == 0) mbar_arrive(b_empty + 24);
      }
      float o[64], s[64];
      uint32_t p[32], q[32];
      #pragma unroll
      for (int i = 0; i < 32; i++) q[i] = pack_bf16(acc[2 * i] * AT_C, acc[2 * i + 1] * AT_C);
      zero_regs(s);
      const uint32_t sq = sbase + AT_SQ + cwg * 8192;
      float mc0, mc1, al0 = 1.0f, al1 = 1.0f, l0 = 0.f, l1 = 0.f, lp0 = 0.f, lp1 = 0.f;
      bool redo0 = false;
      FS(2 * it, 2);
      mbar_wait(b_full + 8 * ring_slot(ta), ring_par(ta));
      named_bar_sync(1 + cwg, 256);
      FS(2 * it, 3);
      issue_qk(s, q, k_base + ring_slot(ta) * 2048);
      pass_turn(cwg);
      bool ready = mbar_test(b_full + 8 * ring_slot(ta + 1), ring_par(ta + 1)) & mbar_test(b_full + 8 * ring_slot(ta + 2), ring_par(ta + 2));
      stage_q<16>(acc, AT_C, sbase + AT_SQ + frag, lane);
      wgmma_wait<0>();
      fence_regs(s);
      if (tid == 0) mbar_arrive(b_empty + 8 * ring_slot(ta));
      mc0 = 0.f; mc1 = 0.f;
      if (!raw) {
        raw = softmax_mode(s, mc0, mc1);
        if (__builtin_expect(!raw, 0)) softmax_sub(s, mc0, mc1);
      }
      softmax_exp<0, 64>(s);
      #pragma unroll
      for (int J = 0; J < 16; J += 2)
        stmatrix_x4(sbase + AT_SQ + frag + (J >> 3) * 16384 + ((((J & 7) + (lane >> 4)) ^ (lane & 7)) << 4), q[2 * J], q[2 * J + 1], q[2 * J + 2], q[2 * J + 3]);
      pack_p(p, s);
      zero_regs(o);
      FS(2 * it, 4);
      uint32_t ks = ring_slot(ta + 1), vs = ring_slot(ta + 2), kp = ring_par(ta + 1), vp = ring_par(ta + 2);
      auto finish_head = [&]() {
        FS(2 * it, 5);
        redo0 = finish_l(lp0, lp1);
        if (!redo0) stage_o(o, lp0, lp1, sbase + AT_SQ + frag, lane);
        FS(2 * it + 1, 4);
      };
      if (!ready) { mbar_wait(b_full + 8 * ks, kp); mbar_wait(b_full + 8 * vs, vp); }
      #pragma unroll 1
      for (int n = 1; n < 2 * AT_NBLK; n++) {
        named_bar_sync(1 + cwg, 256);
        issue_qk(s, q, k_base + ks * 2048);
        if (n == AT_NBLK + 1) finish_head();
        issue_pv(o, p, v_base + vs * 2048, (n & 15) != 1);
        pass_turn(cwg);
        wgmma_wait<1>();
        fence_regs(s);
        if (tid == 0) mbar_arrive(b_empty + 8 * ks);
        if (__builtin_expect(!raw || (uint32_t)(n - (AT_NBLK - 1)) <= 2u, 0)) {
          if (n == AT_NBLK + 1 && !redo0) {
            fence_proxy_async();
            __syncwarp();
            if (lane == 0) mbar_arrive(b_ordy + 8 * cwg);
          }
          if (n == AT_NBLK - 1) {
            #pragma unroll
            for (int J = 0; J < 16; J += 2)
              ldmatrix_x4(sbase + AT_SQ + 32768 + frag + (J >> 3) * 16384 + ((((J & 7) + (lane >> 4)) ^ (lane & 7)) << 4), q[2 * J], q[2 * J + 1], q[2 * J + 2], q[2 * J + 3]);
          }
          if (!raw) {
            const float m0 = mc0, m1 = mc1;
            const bool ok = softmax_mode(s, mc0, mc1);
            if (n == AT_NBLK) raw = ok;
            else {
              mc0 = mc0 - AT_HEAD > m0 ? mc0 : m0; mc1 = mc1 - AT_HEAD > m1 ? mc1 : m1;
              al0 = ex2_approx(m0 - mc0); al1 = ex2_approx(m1 - mc1);
            }
            if (!raw) softmax_sub(s, mc0, mc1);
          }
        }
        softmax_exp<0, AT_SPLIT>(s);
        add_rowsum(p, l0, l1);
        if (tid == 0) {
          uint32_t dep = zero & __float_as_uint(l0) & __float_as_uint(l1);
          #pragma unroll
          for (int i = AT_SPLIT - AT_PIN - PINB; i < AT_SPLIT - PINB; i += 2) dep &= __float_as_uint(s[i]) & __float_as_uint(s[i + 1]);
          mbar_arrive(b_pin + dep);
        }
        wgmma_wait<0>();
        fence_regs(o);
        if (tid == 0) mbar_arrive(b_empty + 8 * vs);
        ks += 2; if (ks >= 5) { ks -= 5; kp ^= 1; }
        vs += 2; if (vs >= 5) { vs -= 5; vp ^= 1; }
        ready = mbar_test(b_full + 8 * ks, kp) & mbar_test(b_full + 8 * vs, vp);
        softmax_exp<AT_SPLIT, 64>(s);
        pack_p(p, s);
        if (n == AT_NBLK) { lp0 = l0; lp1 = l1; l0 = 0.f; l1 = 0.f; }
        if (__builtin_expect(!raw || !ready, 0)) {
        if (!raw && __any_sync(0xffffffffu, al0 != 1.0f || al1 != 1.0f)) {
          rescale_o(o, al0, al1);
          l0 *= al0; l1 *= al1;
          al0 = 1.0f; al1 = 1.0f;
        }
        if (!ready && n < 2 * AT_NBLK - 1) {
          mbar_wait(b_full + 8 * ks, kp);
          mbar_wait(b_full + 8 * vs, vp);
        }
        }
      }
      FS(2 * it + 1, 5);
      const uint32_t vl = ring_slot(ta + 63);
      vs = ring_slot(ta + 62);
      const uint32_t ob = more ? sbase + vs * 32768 : sbase + AT_SQ + 32768;
      mbar_wait(b_full + 8 * vl, ring_par(ta + 63));
      issue_pv(o, p, v_base + vl * 2048, 1);
      block_end(zero, b_pin);
      add_rowsum(p, l0, l1);
      const bool overflow = finish_l(l0, l1);
      if (!overflow && lane == 0) mbar_arrive(b_q1);
      #pragma unroll
      for (int i = 0; i < 8; i++) asm volatile("mov.b64 {%0, %1}, 0;\nmov.b64 {%2, %3}, 0;" : "=r"(pre[i].x), "=r"(pre[i].y), "=r"(pre[i].z), "=r"(pre[i].w));
      const bool want_pre = !more && blockIdx.x < OG_MOE, got_pre = want_pre && __all_sync(0xffffffffu, mbar_test(bars + 272, 0));
      if (got_pre) load_pre(pre, sbase, AT_SQ, threadIdx.x - 128);
      mbar_wait(b_empty + 8 * vs, ring_par(ta + 62));
      wgmma_wait<0>();
      fence_regs(o);
      if (tid == 0) mbar_arrive(b_empty + 8 * vl);
      FS(2 * it + 1, 6);
      if (overflow) {
        attn_rows_exact(sq + 32768, ob + cwg * 8192, 4 * ta + 1, kc, vc);
        __syncwarp();
        if (lane == 0) mbar_arrive(b_q1);
      } else stage_o(o, l0, l1, ob + frag, lane);
      if (redo0) attn_rows_exact(sq, sq, 4 * ta, kc, vc);
      fence_proxy_async();
      __syncwarp();
      if (lane == 0) {
        if (redo0) mbar_arrive(b_ordy + 8 * cwg);
        mbar_arrive(b_ordy + 16 + 8 * cwg);
      }
      if (want_pre && !got_pre) load_pre(pre, sbase, AT_SQ, threadIdx.x - 128);
      if (redo0 || overflow) raw = false;
      named_bar_sync(3 + cwg, 128);
      FS(2 * it + 1, 7);
    }
    if (cwg == 0) named_bar_arrive(1, 256);
    if (__builtin_expect(single, 0)) {
      float acc[128];
      uint32_t j = 0, pk[64];
      #pragma unroll
      for (int i = 0; i < 64; i++) asm volatile("" : "=f"(acc[2 * i]), "=f"(acc[2 * i + 1]), "=r"(pk[i]));
      uint4* dst = g_pre;
      int left = 0;
      auto put = [&](bool last) {
        #pragma unroll
        for (int i = 0; i < PUT_N; i++) dst[i * 256] = make_uint4(pk[4 * i], pk[4 * i + 1], pk[4 * i + 2], pk[4 * i + 3]);
        dst += PUT_N * 256;
        #pragma unroll
        for (int i = 0; i < 64 - 4 * PUT_N; i++) asm volatile("mov.b32 %0, %1;" : "=r"(pk[i]) : "r"(pk[i + 4 * PUT_N]));
        __syncwarp();
        if (last && lane == 0) mbar_arrive(bars + 280);
      };
      #pragma unroll 1
      for (int ji = 0; ji < help_njobs(); ji++) {
        const int nk = ji < OG_JOBS ? OG_PRE : OG_PRE2;
        #pragma unroll 1
        for (int kk = 0; kk < nk; kk++, j++) {
          const uint32_t slot = ring_slot(qp_pos(j, 1));
          mbar_wait(b_full + 8 * slot, ring_par(qp_pos(j, 1)) ^ ((j >> 2) & 1));
          if (H_STAG > 0 && cwg == 1 && kk == nk - H_STAG) named_bar_sync(7, 256);
          const uint32_t a_lo = q_lo + (j & 3) * 1024, b_lo = w_base + slot * 2048;
          wgmma_fence();
          wgmma_m64n256k16_ss_tb<0, 0>(acc, a_lo, b_lo, kk != 0);
          wgmma_m64n256k16_ss_tb<2, 128>(acc, a_lo, b_lo, 1);
          wgmma_m64n256k16_ss_tb<4, 256>(acc, a_lo, b_lo, 1);
          wgmma_m64n256k16_ss_tb<6, 384>(acc, a_lo, b_lo, 1);
          wgmma_commit();
          if (H_STAG > 0 && cwg == 0 && kk == nk - 1) named_bar_arrive(7, 256);
          wgmma_wait<1>();
          if (kk > 0 && tid == 0) mbar_arrive(b_empty + 8 * ring_slot(qp_pos(j - 1, 1)));
          #pragma unroll 1
          for (int i = ji == OG_JOBS ? 0 : 16 / PUT_N - 1; i < 16 / PUT_N && left > 0; i++) put(--left == 0);
        }
        wgmma_wait<0>();
        fence_regs(acc);
        if (tid == 0) mbar_arrive(b_empty + 8 * ring_slot(qp_pos(j - 1, 1)));
        #pragma unroll
        for (int i = 0; i < 64; i++) pk[i] = pack_bf16(acc[2 * i], acc[2 * i + 1]);
        left = 16 / PUT_N;
        if (ji == PRE_X) mbar_wait(bars + 296, 0);
        dst = g_pre + help_job(ji) * 2048 + threadIdx.x - 128;
      }
      #pragma unroll
      for (int i = 0; i < 16; i++) dst[i * 256] = make_uint4(pk[4 * i], pk[4 * i + 1], pk[4 * i + 2], pk[4 * i + 3]);
      __syncwarp();
      if (lane == 0) mbar_arrive(bars + 280);
      named_bar_sync(5, 256);
      if (threadIdx.x == 128) {
        #pragma unroll 1
        for (int i = 0; i < 5; i++) {
          constexpr int n = OG_JOBS * OG_PRE;
          const int used = i == 3 ? 0 : (n + 3 - (i == 4 ? 3 : i)) / 4;
          if ((used ^ (i < 4)) & 1) {
            mbar_arrive(b_full + 8 * ring_slot(4 + i));
            mbar_arrive(b_empty + 8 * ring_slot(4 + i)); mbar_arrive(b_empty + 8 * ring_slot(4 + i));
          }
        }
        mbar_arrive(b_x);
      }
      named_bar_sync(5, 256);
      #pragma unroll
      for (int i = 0; i < 8; i++) pre[i] = make_uint4(0u, 0u, 0u, 0u);
    }
    TL_CLK(3, 1, threadIdx.x == 128);
    TL_CTA(1, threadIdx.x == 256);
    TL_END(3, tid == 0);
    TL_MARK2(19, tid == 0 && !single);
    if (blockIdx.x < 128) {
      tail_consumer(sbase, &tmOut, pre, cwg, w_gate, w_up);
    }
  }
}

typedef CUresult (*PFN_encodeTiled)(CUtensorMap*, CUtensorMapDataType, cuuint32_t, void*, const cuuint64_t*, const cuuint64_t*,
                                    const cuuint32_t*, const cuuint32_t*, CUtensorMapInterleave, CUtensorMapSwizzle,
                                    CUtensorMapL2promotion, CUtensorMapFloatOOBfill);

CUtensorMap make_map_2d(PFN_encodeTiled enc, const void* ptr, uint64_t inner, uint64_t outer, uint64_t stride_bytes, uint32_t box_inner, uint32_t box_outer) {
  CUtensorMap m;
  cuuint64_t gd[2] = {inner, outer}; cuuint64_t gs[1] = {stride_bytes};
  cuuint32_t bx[2] = {box_inner, box_outer}; cuuint32_t es[2] = {1, 1};
  enc(&m, CU_TENSOR_MAP_DATA_TYPE_BFLOAT16, 2, const_cast<void*>(ptr), gd, gs, bx, es, CU_TENSOR_MAP_INTERLEAVE_NONE,
      CU_TENSOR_MAP_SWIZZLE_128B, CU_TENSOR_MAP_L2_PROMOTION_L2_128B, CU_TENSOR_MAP_FLOAT_OOB_FILL_NONE);
  return m;
}

CUtensorMap make_map_3d(PFN_encodeTiled enc, const void* ptr, uint64_t cols, uint64_t rows, uint32_t box_rows, uint32_t chunks) {
  CUtensorMap m;
  cuuint64_t gd[3] = {64, rows, cols / 64}; cuuint64_t gs[2] = {cols * 2, 128};
  cuuint32_t bx[3] = {64, box_rows, chunks}; cuuint32_t es[3] = {1, 1, 1};
  enc(&m, CU_TENSOR_MAP_DATA_TYPE_BFLOAT16, 3, const_cast<void*>(ptr), gd, gs, bx, es, CU_TENSOR_MAP_INTERLEAVE_NONE,
      CU_TENSOR_MAP_SWIZZLE_128B, CU_TENSOR_MAP_L2_PROMOTION_L2_128B, CU_TENSOR_MAP_FLOAT_OOB_FILL_NONE);
  return m;
}

}

extern "C" void kernel_launch(void* const* d_in, const int* in_sizes, int n_in, void* d_out, int out_size) {
  const bf16* x      = (const bf16*)d_in[0];
  const bf16* kc     = (const bf16*)d_in[1];
  const bf16* vc     = (const bf16*)d_in[2];
  const bf16* wq     = (const bf16*)d_in[3];
  const bf16* wo     = (const bf16*)d_in[4];
  const bf16* w_r    = (const bf16*)d_in[6];
  const bf16* w_gate = (const bf16*)d_in[7];
  const bf16* w_up   = (const bf16*)d_in[8];
  const bf16* w_down = (const bf16*)d_in[9];
  const bf16* cvec   = (const bf16*)d_in[10];
  const bf16* w_mod  = (const bf16*)d_in[11];
  bf16* out = (bf16*)d_out;

  static PFN_encodeTiled enc = nullptr;
  static void *p_h = nullptr, *p_o = nullptr;
  if (!enc) {
    void* fn = nullptr; cudaDriverEntryPointQueryResult qres;
    cudaGetDriverEntryPoint("cuTensorMapEncodeTiled", &fn, cudaEnableDefault, &qres);
    enc = (PFN_encodeTiled)fn;
    cudaGetSymbolAddress(&p_h, g_pre);
    p_h = (uint4*)p_h + 16 * PRE_X * 2048;
    cudaGetSymbolAddress(&p_o, g_o);
    cudaFuncSetAttribute(fused_kernel, cudaFuncAttributeMaxDynamicSharedMemorySize, (int)AT_SMEM);
  }
  const CUtensorMap tm_h   = make_map_2d(enc, p_h, T_D, T_SEQ, T_D * 2, 64, 128);
  const CUtensorMap tm_wq  = make_map_3d(enc, wq, T_DQKV, T_D, 64, 4);
  const CUtensorMap tm_k   = make_map_3d(enc, kc, T_DH, (uint64_t)T_NH * T_SEQ, 128, 2);
  const CUtensorMap tm_v   = make_map_3d(enc, vc, T_DH, (uint64_t)T_NH * T_SEQ, 128, 2);
  const CUtensorMap tm_ost = make_map_2d(enc, p_o, T_DQKV, T_SEQ, T_DQKV * 2, 64, 64);
  const CUtensorMap tm_old = make_map_2d(enc, p_o, T_DQKV, T_SEQ, T_DQKV * 2, 64, 128);
  const CUtensorMap tm_wo  = make_map_3d(enc, wo, T_D, T_DQKV, 64, 2);
  const CUtensorMap tm_d   = make_map_3d(enc, w_down, T_D, T_F, 32, 8);

  const CUtensorMap tm_m   = make_map_2d(enc, w_mod, 6 * T_D, T_D, 6 * T_D * 2, 64, 256);
  const CUtensorMap tm_out = make_map_2d(enc, out, T_D, T_SEQ, T_D * 2, 64, 16);

  fused_kernel<<<132, 384, AT_SMEM, cudaStreamPerThread>>>(tm_h, tm_wq, tm_k, tm_v, tm_ost, tm_old, tm_wo, tm_d, tm_out, tm_m, 0u, (const uint8_t*)wo, kc, vc, x, cvec, w_mod,
             w_r, w_gate, w_up, w_down, out);
}
```

```cpp
#include <cuda_runtime.h>
#include <cuda_bf16.h>
#include <cuda.h>
#include <stdint.h>

namespace {

typedef __nv_bfloat16 bf16;

constexpr int T_SEQ = 2048, T_D = 1024, T_NH = 32, T_DH = 128, T_DQKV = 4096, T_F = 3584;

#define PRE_X 2
__device__ __align__(1024) uint4 g_pre[(16 * PRE_X + 128) * 2048];
#define g_h (reinterpret_cast<bf16*>(g_pre + 16 * PRE_X * 2048))
__device__ __align__(1024) bf16 g_o[T_SEQ * T_DQKV];
__device__ __align__(16) uint8_t g_col[8 * 1536];
__device__ __align__(16) float g_scal[64];
__device__ __align__(16) unsigned int g_hcnt[17 * 32];
__device__ unsigned int g_smid[168], g_tmax[128];
__device__ __align__(128) float g_modpart[4 * 2 * T_D];
struct __align__(2048) TailMail {
  float4 part1[T_SEQ * 8];
  uint32_t key[256];
  uint4 cand[16 * 2 * 2 * 128];
  uint32_t cnt[32];
  float ypart[(T_F / 32) * 2 * T_D];
};
__device__ TailMail g_mail;
#define g_part1 g_mail.part1
#define g_key g_mail.key
#define g_cand g_mail.cand
#define CNT_Y (g_mail.cnt)
#define g_ypart g_mail.ypart

__device__ __forceinline__ uint32_t smem_u32(const void* p) { return (uint32_t)__cvta_generic_to_shared(p); }
__device__ __forceinline__ void mbar_init(uint32_t bar, uint32_t cnt) { asm volatile("mbarrier.init.shared::cta.b64 [%0], %1;" :: "r"(bar), "r"(cnt)); }
__device__ __forceinline__ void mbar_expect_tx(uint32_t bar, uint32_t bytes) { asm volatile("mbarrier.arrive.expect_tx.shared::cta.b64 _, [%0], %1;" :: "r"(bar), "r"(bytes) : "memory"); }
__device__ __forceinline__ void mbar_arrive(uint32_t bar) { asm volatile("mbarrier.arrive.shared::cta.b64 _, [%0];" :: "r"(bar) : "memory"); }
__device__ __forceinline__ void mbar_wait(uint32_t bar, uint32_t parity) {
  asm volatile("{\n.reg .pred p;\nLAB_WAIT:\nmbarrier.try_wait.parity.shared::cta.b64 p, [%0], %1;\n@!p bra LAB_WAIT;\n}\n" :: "r"(bar), "r"(parity) : "memory");
}
__device__ __forceinline__ bool mbar_test(uint32_t bar, uint32_t parity) {
  uint32_t r; asm volatile("{\n.reg .pred p;\nmbarrier.test_wait.parity.shared::cta.b64 p, [%1], %2;\nselp.u32 %0, 1, 0, p;\n}\n" : "=r"(r) : "r"(bar), "r"(parity) : "memory");
  return r != 0;
}
__device__ __forceinline__ uint32_t clock_lo() { uint32_t c; asm volatile("mov.u32 %0, %%clock;" : "=r"(c)); return c; }
__device__ __forceinline__ void fence_mbar_init() { asm volatile("fence.mbarrier_init.release.cluster;" ::: "memory"); }
__device__ __forceinline__ void tma_load_2d(uint32_t dst, const CUtensorMap* map, int c0, int c1, uint32_t bar) {
  asm volatile("cp.async.bulk.tensor.2d.shared::cluster.global.mbarrier::complete_tx::bytes [%0], [%1, {%3, %4}], [%2];"
    :: "r"(dst), "l"(map), "r"(bar), "r"(c0), "r"(c1) : "memory");
}
__device__ __forceinline__ uint64_t policy_evict_first() {
  uint64_t p; asm volatile("createpolicy.fractional.L2::evict_first.b64 %0, 1.0;" : "=l"(p)); return p;
}
__device__ __forceinline__ void tma_load_2d_hint(uint32_t dst, const CUtensorMap* map, int c0, int c1, uint32_t bar, uint64_t pol) {
  asm volatile("cp.async.bulk.tensor.2d.shared::cluster.global.mbarrier::complete_tx::bytes.L2::cache_hint [%0], [%1, {%3, %4}], [%2], %5;"
    :: "r"(dst), "l"(map), "r"(bar), "r"(c0), "r"(c1), "l"(pol) : "memory");
}
__device__ __forceinline__ void tma_load_3d_hint(uint32_t dst, const CUtensorMap* map, int c1, int c2, uint32_t bar, uint64_t pol) {
  asm volatile("cp.async.bulk.tensor.3d.shared::cluster.global.mbarrier::complete_tx::bytes.L2::cache_hint [%0], [%1, {%3, %4, %5}], [%2], %6;"
    :: "r"(dst), "l"(map), "r"(bar), "n"(0), "r"(c1), "r"(c2), "l"(pol) : "memory");
}
__device__ __forceinline__ void tma_store_2d(const CUtensorMap* map, uint32_t src, int c0, int c1) {
  asm volatile("cp.async.bulk.tensor.2d.global.shared::cta.bulk_group [%0, {%2, %3}], [%1];" :: "l"(map), "r"(src), "r"(c0), "r"(c1) : "memory");
}
__device__ __forceinline__ void prefetch_tmap(const CUtensorMap* map) { asm volatile("prefetch.tensormap [%0];" :: "l"(map) : "memory"); }
__device__ __forceinline__ void l2_prefetch_bulk(const void* p, uint32_t bytes) {
  asm volatile("cp.async.bulk.prefetch.L2.global [%0], %1;" :: "l"(p), "r"(bytes) : "memory");
}
__device__ __forceinline__ void bulk_commit() { asm volatile("cp.async.bulk.commit_group;" ::: "memory"); }
template<int N> __device__ __forceinline__ void bulk_wait_read() { asm volatile("cp.async.bulk.wait_group.read %0;" :: "n"(N) : "memory"); }
template<int N> __device__ __forceinline__ void bulk_wait() { asm volatile("cp.async.bulk.wait_group %0;" :: "n"(N) : "memory"); }
__device__ __forceinline__ void named_bar_sync(int id, int nthreads) { asm volatile("bar.sync %0, %1;" :: "r"(id), "r"(nthreads) : "memory"); }
__device__ __forceinline__ void named_bar_arrive(int id, int nthreads) { asm volatile("bar.arrive %0, %1;" :: "r"(id), "r"(nthreads) : "memory"); }
__device__ __forceinline__ void pass_turn(int cwg) {
  asm volatile("{\n.reg .pred p;\nsetp.ne.u32 p, %0, 0;\n@p bar.arrive 1, 256;\n@!p bar.arrive 2, 256;\n}\n" :: "r"(cwg) : "memory");
}
__device__ __forceinline__ void wgmma_fence() { asm volatile("wgmma.fence.sync.aligned;" ::: "memory"); }
__device__ __forceinline__ void wgmma_commit() { asm volatile("wgmma.commit_group.sync.aligned;" ::: "memory"); }
template<int N> __device__ __forceinline__ void wgmma_wait() { asm volatile("wgmma.wait_group.sync.aligned %0;" :: "n"(N) : "memory"); }
template<int R> __device__ __forceinline__ void reg_alloc() { asm volatile("setmaxnreg.inc.sync.aligned.u32 %0;" :: "n"(R)); }
template<int R> __device__ __forceinline__ void reg_dealloc() { asm volatile("setmaxnreg.dec.sync.aligned.u32 %0;" :: "n"(R)); }
__device__ __forceinline__ bool elect_one() {
  uint32_t pred; asm volatile("{\n.reg .pred p;\nelect.sync _|p, 0xffffffff;\nselp.u32 %0, 1, 0, p;\n}\n" : "=r"(pred)); return pred != 0;
}
__device__ __forceinline__ uint32_t pack_bf16(float lo, float hi) {
  uint32_t r; asm("cvt.rn.bf16x2.f32 %0, %1, %2;" : "=r"(r) : "f"(hi), "f"(lo)); return r;
}
__device__ __forceinline__ void stmatrix_x4(uint32_t addr, uint32_t r0, uint32_t r1, uint32_t r2, uint32_t r3) {
  asm volatile("stmatrix.sync.aligned.m8n8.x4.shared.b16 [%0], {%1, %2, %3, %4};" :: "r"(addr), "r"(r0), "r"(r1), "r"(r2), "r"(r3) : "memory");
}
__device__ __forceinline__ void fence_proxy_async() { asm volatile("fence.proxy.async.shared::cta;" ::: "memory"); }
__device__ __forceinline__ float ex2_approx(float x) { float y; asm("ex2.approx.ftz.f32 %0, %1;" : "=f"(y) : "f"(x)); return y; }
template<int N> __device__ __forceinline__ void fence_regs(float (&r)[N]) {
  #pragma unroll
  for (int i = 0; i < N; i++) asm volatile("" : "+f"(r[i]) :: "memory");
}
template<int N> __device__ __forceinline__ void zero_regs(float (&r)[N]) {
  #pragma unroll
  for (int i = 0; i < N; i += 2) asm volatile("mov.b64 {%0, %1}, 0;" : "=f"(r[i]), "=f"(r[i + 1]));
}
__device__ __forceinline__ float rbf(float x) { return __uint_as_float(pack_bf16(0.f, x)); }
__device__ __forceinline__ float bflo(uint32_t v) { return __uint_as_float(v << 16); }
__device__ __forceinline__ float bfhi(uint32_t v) { return __uint_as_float(v & 0xffff0000u); }

#define XT(i) do {} while (0)
#define TL_START(k) do {} while (0)
#define TL_END(k, cond) do {} while (0)
#define TL_CTA(i, cond) do {} while (0)
#define FS(slot, k) do {} while (0)
#define TL_MARK2(k, cond) do {} while (0)
#define TL_CLK(k, i, cond) do {} while (0)

template <int OFFA, int OFFB>
__device__ __forceinline__ void wgmma_m64n256k16_ss_tb(float (&d)[128], uint32_t a_lo, uint32_t b_lo, int scaleD) {
  asm volatile("{\n.reg .pred p;\n.reg .b32 ta, tb;\n.reg .b64 da, db;\nsetp.ne.b32 p, %130, 0;\n"
    "add.u32 ta, %128, %131;\nadd.u32 tb, %129, %132;\n"
    "mov.b64 da, {ta, 0x40000040};\nmov.b64 db, {tb, 0x40000040};\n"
    "wgmma.mma_async.sync.aligned.m64n256k16.f32.bf16.bf16 "
    "{%0, %1, %2, %3, %4, %5, %6, %7, %8, %9, %10, %11, %12, %13, %14, %15, %16, %17, %18, %19, %20, %21, %22, %23, %24, %25, %26, %27, %28, %29, %30, %31, %32, %33, %34, %35, %36, %37, %38, %39, %40, %41, %42, %43, %44, %45, %46, %47, %48, %49, %50, %51, %52, %53, %54, %55, %56, %57, %58, %59, %60, %61, %62, %63, %64, %65, %66, %67, %68, %69, %70, %71, %72, %73, %74, %75, %76, %77, %78, %79, %80, %81, %82, %83, %84, %85, %86, %87, %88, %89, %90, %91, %92, %93, %94, %95, %96, %97, %98, %99, %100, %101, %102, %103, %104, %105, %106, %107, %108, %109, %110, %111, %112, %113, %114, %115, %116, %117, %118, %119, %120, %121, %122, %123, %124, %125, %126, %127}, "
    "da, db, p, 1, 1, 0, 1;\n}\n"
    : "+f"(d[0]), "+f"(d[1]), "+f"(d[2]), "+f"(d[3]), "+f"(d[4]), "+f"(d[5]), "+f"(d[6]), "+f"(d[7]), "+f"(d[8]), "+f"(d[9]), "+f"(d[10]), "+f"(d[11]), "+f"(d[12]), "+f"(d[13]), "+f"(d[14]), "+f"(d[15]), "+f"(d[16]), "+f"(d[17]), "+f"(d[18]), "+f"(d[19]), "+f"(d[20]), "+f"(d[21]), "+f"(d[22]), "+f"(d[23]), "+f"(d[24]), "+f"(d[25]), "+f"(d[26]), "+f"(d[27]), "+f"(d[28]), "+f"(d[29]), "+f"(d[30]), "+f"(d[31]), "+f"(d[32]), "+f"(d[33]), "+f"(d[34]), "+f"(d[35]), "+f"(d[36]), "+f"(d[37]), "+f"(d[38]), "+f"(d[39]), "+f"(d[40]), "+f"(d[41]), "+f"(d[42]), "+f"(d[43]), "+f"(d[44]), "+f"(d[45]), "+f"(d[46]), "+f"(d[47]), "+f"(d[48]), "+f"(d[49]), "+f"(d[50]), "+f"(d[51]), "+f"(d[52]), "+f"(d[53]), "+f"(d[54]), "+f"(d[55]), "+f"(d[56]), "+f"(d[57]), "+f"(d[58]), "+f"(d[59]), "+f"(d[60]), "+f"(d[61]), "+f"(d[62]), "+f"(d[63]), "+f"(d[64]), "+f"(d[65]), "+f"(d[66]), "+f"(d[67]), "+f"(d[68]), "+f"(d[69]), "+f"(d[70]), "+f"(d[71]), "+f"(d[72]), "+f"(d[73]), "+f"(d[74]), "+f"(d[75]), "+f"(d[76]), "+f"(d[77]), "+f"(d[78]), "+f"(d[79]), "+f"(d[80]), "+f"(d[81]), "+f"(d[82]), "+f"(d[83]), "+f"(d[84]), "+f"(d[85]), "+f"(d[86]), "+f"(d[87]), "+f"(d[88]), "+f"(d[89]), "+f"(d[90]), "+f"(d[91]), "+f"(d[92]), "+f"(d[93]), "+f"(d[94]), "+f"(d[95]), "+f"(d[96]), "+f"(d[97]), "+f"(d[98]), "+f"(d[99]), "+f"(d[100]), "+f"(d[101]), "+f"(d[102]), "+f"(d[103]), "+f"(d[104]), "+f"(d[105]), "+f"(d[106]), "+f"(d[107]), "+f"(d[108]), "+f"(d[109]), "+f"(d[110]), "+f"(d[111]), "+f"(d[112]), "+f"(d[113]), "+f"(d[114]), "+f"(d[115]), "+f"(d[116]), "+f"(d[117]), "+f"(d[118]), "+f"(d[119]), "+f"(d[120]), "+f"(d[121]), "+f"(d[122]), "+f"(d[123]), "+f"(d[124]), "+f"(d[125]), "+f"(d[126]), "+f"(d[127])
    : "r"(a_lo), "r"(b_lo), "r"(scaleD), "n"(OFFA), "n"(OFFB));
}

template <int OFFA, int OFFB>
__device__ __forceinline__ void wgmma_m64n128k16_ss_tb(float (&d)[64], uint32_t a_lo, uint32_t b_lo, int scaleD) {
  asm volatile("{\n.reg .pred p;\n.reg .b32 ta, tb;\n.reg .b64 da, db;\nsetp.ne.b32 p, %66, 0;\n"
    "add.u32 ta, %64, %67;\nadd.u32 tb, %65, %68;\n"
    "mov.b64 da, {ta, 0x40000040};\nmov.b64 db, {tb, 0x40000040};\n"
    "wgmma.mma_async.sync.aligned.m64n128k16.f32.bf16.bf16 "
    "{%0, %1, %2, %3, %4, %5, %6, %7, %8, %9, %10, %11, %12, %13, %14, %15, %16, %17, %18, %19, %20, %21, %22, %23, %24, %25, %26, %27, %28, %29, %30, %31, %32, %33, %34, %35, %36, %37, %38, %39, %40, %41, %42, %43, %44, %45, %46, %47, %48, %49, %50, %51, %52, %53, %54, %55, %56, %57, %58, %59, %60, %61, %62, %63}, "
    "da, db, p, 1, 1, 0, 1;\n}\n"
    : "+f"(d[0]), "+f"(d[1]), "+f"(d[2]), "+f"(d[3]), "+f"(d[4]), "+f"(d[5]), "+f"(d[6]), "+f"(d[7]), "+f"(d[8]), "+f"(d[9]), "+f"(d[10]), "+f"(d[11]), "+f"(d[12]), "+f"(d[13]), "+f"(d[14]), "+f"(d[15]), "+f"(d[16]), "+f"(d[17]), "+f"(d[18]), "+f"(d[19]), "+f"(d[20]), "+f"(d[21]), "+f"(d[22]), "+f"(d[23]), "+f"(d[24]), "+f"(d[25]), "+f"(d[26]), "+f"(d[27]), "+f"(d[28]), "+f"(d[29]), "+f"(d[30]), "+f"(d[31]), "+f"(d[32]), "+f"(d[33]), "+f"(d[34]), "+f"(d[35]), "+f"(d[36]), "+f"(d[37]), "+f"(d[38]), "+f"(d[39]), "+f"(d[40]), "+f"(d[41]), "+f"(d[42]), "+f"(d[43]), "+f"(d[44]), "+f"(d[45]), "+f"(d[46]), "+f"(d[47]), "+f"(d[48]), "+f"(d[49]), "+f"(d[50]), "+f"(d[51]), "+f"(d[52]), "+f"(d[53]), "+f"(d[54]), "+f"(d[55]), "+f"(d[56]), "+f"(d[57]), "+f"(d[58]), "+f"(d[59]), "+f"(d[60]), "+f"(d[61]), "+f"(d[62]), "+f"(d[63])
    : "r"(a_lo), "r"(b_lo), "r"(scaleD), "n"(OFFA), "n"(OFFB));
}

template <int OFFB>
__device__ __forceinline__ void wgmma_m64n128k16_rs_tb(float (&d)[64], uint32_t a0, uint32_t a1, uint32_t a2, uint32_t a3, uint32_t b_lo, int scaleD) {
  asm volatile("{\n.reg .pred p;\n.reg .b32 tb;\n.reg .b64 db;\nsetp.ne.b32 p, %69, 0;\n"
    "add.u32 tb, %68, %70;\n"
    "mov.b64 db, {tb, 0x40000040};\n"
    "wgmma.mma_async.sync.aligned.m64n128k16.f32.bf16.bf16 "
    "{%0, %1, %2, %3, %4, %5, %6, %7, %8, %9, %10, %11, %12, %13, %14, %15, %16, %17, %18, %19, %20, %21, %22, %23, %24, %25, %26, %27, %28, %29, %30, %31, %32, %33, %34, %35, %36, %37, %38, %39, %40, %41, %42, %43, %44, %45, %46, %47, %48, %49, %50, %51, %52, %53, %54, %55, %56, %57, %58, %59, %60, %61, %62, %63}, "
    "{%64, %65, %66, %67}, db, p, 1, 1, 1;\n}\n"
    : "+f"(d[0]), "+f"(d[1]), "+f"(d[2]), "+f"(d[3]), "+f"(d[4]), "+f"(d[5]), "+f"(d[6]), "+f"(d[7]), "+f"(d[8]), "+f"(d[9]), "+f"(d[10]), "+f"(d[11]), "+f"(d[12]), "+f"(d[13]), "+f"(d[14]), "+f"(d[15]), "+f"(d[16]), "+f"(d[17]), "+f"(d[18]), "+f"(d[19]), "+f"(d[20]), "+f"(d[21]), "+f"(d[22]), "+f"(d[23]), "+f"(d[24]), "+f"(d[25]), "+f"(d[26]), "+f"(d[27]), "+f"(d[28]), "+f"(d[29]), "+f"(d[30]), "+f"(d[31]), "+f"(d[32]), "+f"(d[33]), "+f"(d[34]), "+f"(d[35]), "+f"(d[36]), "+f"(d[37]), "+f"(d[38]), "+f"(d[39]), "+f"(d[40]), "+f"(d[41]), "+f"(d[42]), "+f"(d[43]), "+f"(d[44]), "+f"(d[45]), "+f"(d[46]), "+f"(d[47]), "+f"(d[48]), "+f"(d[49]), "+f"(d[50]), "+f"(d[51]), "+f"(d[52]), "+f"(d[53]), "+f"(d[54]), "+f"(d[55]), "+f"(d[56]), "+f"(d[57]), "+f"(d[58]), "+f"(d[59]), "+f"(d[60]), "+f"(d[61]), "+f"(d[62]), "+f"(d[63])
    : "r"(a0), "r"(a1), "r"(a2), "r"(a3), "r"(b_lo), "r"(scaleD), "n"(OFFB));
}

template <int OFFB>
__device__ __forceinline__ void wgmma_m64n128k16_rs(float (&d)[64], uint32_t a0, uint32_t a1, uint32_t a2, uint32_t a3, uint32_t b_lo, int scaleD) {
  asm volatile("{\n.reg .pred p;\n.reg .b32 tb;\n.reg .b64 db;\nsetp.ne.b32 p, %69, 0;\n"
    "add.u32 tb, %68, %70;\n"
    "mov.b64 db, {tb, 0x40000040};\n"
    "wgmma.mma_async.sync.aligned.m64n128k16.f32.bf16.bf16 "
    "{%0, %1, %2, %3, %4, %5, %6, %7, %8, %9, %10, %11, %12, %13, %14, %15, %16, %17, %18, %19, %20, %21, %22, %23, %24, %25, %26, %27, %28, %29, %30, %31, %32, %33, %34, %35, %36, %37, %38, %39, %40, %41, %42, %43, %44, %45, %46, %47, %48, %49, %50, %51, %52, %53, %54, %55, %56, %57, %58, %59, %60, %61, %62, %63}, "
    "{%64, %65, %66, %67}, db, p, 1, 1, 0;\n}\n"
    : "+f"(d[0]), "+f"(d[1]), "+f"(d[2]), "+f"(d[3]), "+f"(d[4]), "+f"(d[5]), "+f"(d[6]), "+f"(d[7]), "+f"(d[8]), "+f"(d[9]), "+f"(d[10]), "+f"(d[11]), "+f"(d[12]), "+f"(d[13]), "+f"(d[14]), "+f"(d[15]), "+f"(d[16]), "+f"(d[17]), "+f"(d[18]), "+f"(d[19]), "+f"(d[20]), "+f"(d[21]), "+f"(d[22]), "+f"(d[23]), "+f"(d[24]), "+f"(d[25]), "+f"(d[26]), "+f"(d[27]), "+f"(d[28]), "+f"(d[29]), "+f"(d[30]), "+f"(d[31]), "+f"(d[32]), "+f"(d[33]), "+f"(d[34]), "+f"(d[35]), "+f"(d[36]), "+f"(d[37]), "+f"(d[38]), "+f"(d[39]), "+f"(d[40]), "+f"(d[41]), "+f"(d[42]), "+f"(d[43]), "+f"(d[44]), "+f"(d[45]), "+f"(d[46]), "+f"(d[47]), "+f"(d[48]), "+f"(d[49]), "+f"(d[50]), "+f"(d[51]), "+f"(d[52]), "+f"(d[53]), "+f"(d[54]), "+f"(d[55]), "+f"(d[56]), "+f"(d[57]), "+f"(d[58]), "+f"(d[59]), "+f"(d[60]), "+f"(d[61]), "+f"(d[62]), "+f"(d[63])
    : "r"(a0), "r"(a1), "r"(a2), "r"(a3), "r"(b_lo), "r"(scaleD), "n"(OFFB));
}

__device__ __forceinline__ uint4 ldg_nc_v4(const void* p) {
  uint4 v;
    asm volatile("{\n.reg .b64 pol;\ncreatepolicy.fractional.L2::evict_first.b64 pol, 1.0;\n"
                 "ld.global.nc.L1::no_allocate.L2::cache_hint.v4.u32 {%0, %1, %2, %3}, [%4], pol;\n}\n" : "=r"(v.x), "=r"(v.y), "=r"(v.z), "=r"(v.w) : "l"(p));
  return v;
}
__device__ __forceinline__ uint64_t pol_normal() {
  uint64_t p; asm volatile("createpolicy.fractional.L2::evict_normal.b64 %0, 1.0;" : "=l"(p)); return p;
}
__device__ __forceinline__ void unpack8(const uint4& u, float (&v)[8]) {
  v[0] = bflo(u.x); v[1] = bfhi(u.x); v[2] = bflo(u.y); v[3] = bfhi(u.y);
  v[4] = bflo(u.z); v[5] = bfhi(u.z); v[6] = bflo(u.w); v[7] = bfhi(u.w);
}
__device__ __forceinline__ void fma8(float (&acc)[8], float s, const uint4& w) {
  acc[0] = fmaf(s, bflo(w.x), acc[0]); acc[1] = fmaf(s, bfhi(w.x), acc[1]); acc[2] = fmaf(s, bflo(w.y), acc[2]); acc[3] = fmaf(s, bfhi(w.y), acc[3]);
  acc[4] = fmaf(s, bflo(w.z), acc[4]); acc[5] = fmaf(s, bfhi(w.z), acc[5]); acc[6] = fmaf(s, bflo(w.w), acc[6]); acc[7] = fmaf(s, bfhi(w.w), acc[7]);
}
__device__ __forceinline__ float rcp_approx(float x) { float y; asm("rcp.approx.ftz.f32 %0, %1;" : "=f"(y) : "f"(x)); return y; }
__device__ __forceinline__ float sigmoid_f(float v) { return rcp_approx(1.0f + ex2_approx(v * -1.4426950408889634f)); }
__device__ __forceinline__ float silu_bf(float v) { return rbf(v * sigmoid_f(v)); }
__device__ __forceinline__ uint32_t rank_key(float r, int idx) {
  const uint32_t b = __float_as_uint(r) >> 16;
  const uint32_t u = (r != r) ? 0u : ((b & 0x8000u) ? (~b & 0xffffu) : (b | 0x8000u));
  return (u << 16) | (0xffffu - (uint32_t)idx);
}
__device__ __forceinline__ void warp_top2(uint32_t& k1, uint32_t& k2) {
  const uint32_t m1 = __reduce_max_sync(0xffffffffu, k1);
  k2 = __reduce_max_sync(0xffffffffu, k1 == m1 ? k2 : k1);
  k1 = m1;
}
__device__ __forceinline__ uint32_t bmul2(uint32_t a, uint32_t b) { uint32_t r; asm("mul.rn.bf16x2 %0, %1, %2;" : "=r"(r) : "r"(a), "r"(b)); return r; }
__device__ __forceinline__ uint32_t badd2(uint32_t a, uint32_t b) { uint32_t r; asm("add.rn.bf16x2 %0, %1, %2;" : "=r"(r) : "r"(a), "r"(b)); return r; }
__device__ __forceinline__ uint32_t bsub2(uint32_t a, uint32_t b) { uint32_t r; asm("sub.rn.bf16x2 %0, %1, %2;" : "=r"(r) : "r"(a), "r"(b)); return r; }
__device__ __forceinline__ float sqrt_approx(float x) { float y; asm("sqrt.approx.f32 %0, %1;" : "=f"(y) : "f"(x)); return y; }
__device__ __forceinline__ uint32_t ln_norm2(uint32_t x1, uint32_t mb2, float inv) {
  const uint32_t d = bsub2(x1, mb2);
  return pack_bf16(bflo(d) * inv, bfhi(d) * inv);
}
__device__ __forceinline__ uint32_t bfma2(uint32_t a, uint32_t b, uint32_t c) { uint32_t r; asm("fma.rn.bf16x2 %0, %1, %2, %3;" : "=r"(r) : "r"(a), "r"(b), "r"(c)); return r; }
__device__ __forceinline__ uint32_t ln_norm2b(uint32_t x1, uint32_t mb2, uint32_t ih, uint32_t il) {
  const uint32_t d = bsub2(x1, mb2);
  return bfma2(d, ih, bmul2(d, il));
}
__device__ __forceinline__ uint32_t ln_mod2(uint32_t x1, uint32_t mb2, float inv, uint32_t c1, uint32_t sb) { return badd2(bmul2(ln_norm2(x1, mb2, inv), c1), sb); }
__device__ __forceinline__ void ldmatrix_x4(uint32_t addr, uint32_t& r0, uint32_t& r1, uint32_t& r2, uint32_t& r3) {
  asm volatile("ldmatrix.sync.aligned.m8n8.x4.shared.b16 {%0, %1, %2, %3}, [%4];" : "=r"(r0), "=r"(r1), "=r"(r2), "=r"(r3) : "r"(addr) : "memory");
}
__device__ __forceinline__ uint4 ldg_stream_v4(const void* p, uint64_t pol) {
  uint4 v; asm volatile("ld.global.nc.L1::no_allocate.L2::cache_hint.L2::128B.v4.u32 {%0, %1, %2, %3}, [%4], %5;" : "=r"(v.x), "=r"(v.y), "=r"(v.z), "=r"(v.w) : "l"(p), "l"(pol)); return v;
}
__device__ __forceinline__ void bulk_load_hint(uint32_t dst, const void* src, uint32_t bytes, uint32_t bar, uint64_t pol) {
  asm volatile("cp.async.bulk.shared::cluster.global.mbarrier::complete_tx::bytes.L2::cache_hint [%0], [%1], %2, [%3], %4;"
    :: "r"(dst), "l"(src), "r"(bytes), "r"(bar), "l"(pol) : "memory");
}
__device__ __forceinline__ void red_release_add(unsigned int* p, unsigned int v) { asm volatile("red.release.gpu.global.add.u32 [%0], %1;" :: "l"(p), "r"(v) : "memory"); }
__device__ __forceinline__ unsigned int ld_acquire(const unsigned int* p) { unsigned int v; asm volatile("ld.acquire.gpu.global.u32 %0, [%1];" : "=r"(v) : "l"(p) : "memory"); return v; }
__device__ __forceinline__ void spin_until(const unsigned int* p, unsigned int target) {
  #pragma unroll 1
  for (unsigned int i = 0; i < (1u << 22); i++) { if (ld_acquire(p) >= target) return; }
}
__device__ __forceinline__ float lds_f32(uint32_t a) { float v; asm volatile("ld.shared.f32 %0, [%1];" : "=f"(v) : "r"(a) : "memory"); return v; }
__device__ __forceinline__ float2 lds_f32x2(uint32_t a) { float2 v; asm volatile("ld.shared.v2.f32 {%0, %1}, [%2];" : "=f"(v.x), "=f"(v.y) : "r"(a) : "memory"); return v; }
__device__ __forceinline__ uint2 lds_u32x2(uint32_t a) { uint2 v; asm volatile("ld.shared.v2.u32 {%0, %1}, [%2];" : "=r"(v.x), "=r"(v.y) : "r"(a) : "memory"); return v; }
__device__ __forceinline__ uint32_t lds_u32(uint32_t a) { uint32_t v; asm volatile("ld.shared.u32 %0, [%1];" : "=r"(v) : "r"(a) : "memory"); return v; }
__device__ __forceinline__ void sts_u32(uint32_t a, uint32_t v) { asm volatile("st.shared.u32 [%0], %1;" :: "r"(a), "r"(v) : "memory"); }
__device__ __forceinline__ void sts_u32x2(uint32_t a, uint32_t x, uint32_t y) { asm volatile("st.shared.v2.u32 [%0], {%1, %2};" :: "r"(a), "r"(x), "r"(y) : "memory"); }
__device__ __forceinline__ void sts_f32(uint32_t a, float v) { asm volatile("st.shared.f32 [%0], %1;" :: "r"(a), "f"(v) : "memory"); }
__device__ __forceinline__ void sts_f32x2(uint32_t a, float x, float y) { asm volatile("st.shared.v2.f32 [%0], {%1, %2};" :: "r"(a), "f"(x), "f"(y) : "memory"); }
__device__ __forceinline__ void sts_f32x4(uint32_t a, float x, float y, float z, float w) { asm volatile("st.shared.v4.f32 [%0], {%1, %2, %3, %4};" :: "r"(a), "f"(x), "f"(y), "f"(z), "f"(w) : "memory"); }

__device__ __forceinline__ uint4 lds_u32x4(uint32_t a) { uint4 v; asm volatile("ld.shared.v4.u32 {%0, %1, %2, %3}, [%4];" : "=r"(v.x), "=r"(v.y), "=r"(v.z), "=r"(v.w) : "r"(a) : "memory"); return v; }
__device__ __forceinline__ void sts_u32x4(uint32_t a, uint32_t x, uint32_t y, uint32_t z, uint32_t w) { asm volatile("st.shared.v4.u32 [%0], {%1, %2, %3, %4};" :: "r"(a), "r"(x), "r"(y), "r"(z), "r"(w) : "memory"); }
__device__ __forceinline__ void st_tagged(float* p, float v) {
  const uint32_t b = __float_as_uint(v);
  asm volatile("st.relaxed.gpu.global.u32 [%0], %1;" :: "l"(p), "r"(b == 0u ? 0x80000000u : b) : "memory");
}
__device__ __forceinline__ void st_tagged4(float* p, float x, float y, float z, float w) {
  const uint32_t a = __float_as_uint(x), b = __float_as_uint(y), c = __float_as_uint(z), d = __float_as_uint(w);
  asm volatile("st.relaxed.gpu.global.v4.u32 [%0], {%1, %2, %3, %4};" :: "l"(p), "r"(a == 0u ? 0x80000000u : a), "r"(b == 0u ? 0x80000000u : b),
               "r"(c == 0u ? 0x80000000u : c), "r"(d == 0u ? 0x80000000u : d) : "memory");
}
__device__ __forceinline__ void st_relaxed2(void* p, uint32_t a, uint32_t b) { asm volatile("st.relaxed.gpu.global.v2.u32 [%0], {%1, %2};" :: "l"(p), "r"(a), "r"(b) : "memory"); }
__device__ __forceinline__ float4 ld_tagged4(const float* p) {
  float4 v; asm volatile("ld.relaxed.gpu.global.v4.f32 {%0, %1, %2, %3}, [%4];" : "=f"(v.x), "=f"(v.y), "=f"(v.z), "=f"(v.w) : "l"(p) : "memory"); return v;
}
__device__ __forceinline__ bool tagged4(const float4& v) {
  return __float_as_uint(v.x) != 0u && __float_as_uint(v.y) != 0u && __float_as_uint(v.z) != 0u && __float_as_uint(v.w) != 0u;
}
__device__ __forceinline__ void hint_arrive(uint32_t* p) { asm volatile("red.relaxed.gpu.global.add.u32 [%0], 1;" :: "l"(p) : "memory"); }
__device__ __forceinline__ void hint_wait(const uint32_t* p, uint32_t target) {
  uint32_t v = 0u;
  #pragma unroll 1
  for (unsigned int i = 0; i < (1u << 22) && v < target; i++) asm volatile("ld.relaxed.gpu.global.u32 %0, [%1];" : "=r"(v) : "l"(p) : "memory");
}
__device__ __forceinline__ void fence_proxy_async_global() { asm volatile("fence.proxy.async.global;" ::: "memory"); }

#define H_SPLIT 1
#define X_DLY 1200
#define W_DLY 1900
#define W_FIRST 2200
#define PRE_B 2
template <int J0, int J1>
__device__ __forceinline__ void load_parts(float2 (&pa)[J1 - J0][4], int t2) {
  #pragma unroll
  for (int j = J0; j < J1; j++)
    #pragma unroll
    for (int k = 0; k < 4; k++)
      asm volatile("ld.relaxed.gpu.global.v2.f32 {%0, %1}, [%2];" : "=f"(pa[j - J0][k].x), "=f"(pa[j - J0][k].y)
                   : "l"(g_modpart + k * 2 * T_D + (t2 >> 7) * T_D + j * 256 + (t2 & 127) * 2) : "memory");
}
template <int J0, int J1>
__device__ __forceinline__ void finish_parts(float2 (&pa)[J1 - J0][4], bool loaded, int t2, uint32_t tab) {
  #pragma unroll 1
  for (unsigned int spin = 0; spin < (1u << 22); spin++) {
    if (!loaded) load_parts<J0, J1>(pa, t2);
    loaded = false;
    bool ok = true;
    #pragma unroll
    for (int j = 0; j < J1 - J0; j++)
      #pragma unroll
      for (int k = 0; k < 4; k++) ok &= (__float_as_uint(pa[j][k].x) != 0u) & (__float_as_uint(pa[j][k].y) != 0u);
    if (__all_sync(0xffffffffu, ok)) break;
  }
  #pragma unroll
  for (int j = J0; j < J1; j++) {
    const float2* q = pa[j - J0];
    const uint32_t m = pack_bf16(((q[0].x + q[1].x) + q[2].x) + q[3].x, ((q[0].y + q[1].y) + q[2].y) + q[3].y);
    sts_u32(tab + (t2 >> 7) * 2048 + j * 512 + (t2 & 127) * 4, t2 >= 128 ? badd2(m, 0x3F803F80u) : m);
  }
}
__device__ __forceinline__ void head_phase(uint32_t bid, uint32_t scr, uint32_t xs, uint32_t b_x, uint32_t b_go, uint32_t b_head, int t2, uint32_t zero, const bf16* __restrict__ cvec, const bf16* __restrict__ w_mod) {
  const int lane = t2 & 31, w8 = t2 >> 5;
  const int cb = bid & 31, ks = bid >> 5;
  const bool early = (cb & 15) < 4 * H_SPLIT;
  const uint32_t ws = (xs - 32768 + (t2 >> 3) * 128 + (((t2 ^ (t2 >> 3)) & 7) << 4)) ^ zero;
  const float cv = __bfloat162float(cvec[ks * 256 + t2]);
  const bf16* wsrc = w_mod + (size_t)(ks * 256 + (t2 >> 3)) * (6 * T_D) + cb * 64 + (t2 & 7) * 8;
  if (early) {
    const uint64_t pol = policy_evict_first();
    #pragma unroll 2
    for (int i = 0; i < 8; i++)
      asm volatile("cp.async.cg.shared.global.L2::cache_hint [%0], [%1], 16, %2;" :: "r"(ws + i * 4096), "l"(wsrc + (size_t)i * 32 * 6 * T_D), "l"(pol) : "memory");
  }
  sts_f32(scr + t2 * 4, silu_bf(cv));
  named_bar_sync(6, 384);
  TL_MARK2(1, t2 == 0);
  uint4 xv[2][4];
  uint32_t mb2[2], ih[2], il[2];
  auto norm = [&](int j) {
    #pragma unroll
    for (int r = 0; r < 2; r++) {
      xv[r][j].x = ln_norm2b(xv[r][j].x, mb2[r], ih[r], il[r]); xv[r][j].y = ln_norm2b(xv[r][j].y, mb2[r], ih[r], il[r]);
      xv[r][j].z = ln_norm2b(xv[r][j].z, mb2[r], ih[r], il[r]); xv[r][j].w = ln_norm2b(xv[r][j].w, mb2[r], ih[r], il[r]);
    }
  };
  auto modulate = [&](int j) {
    const uint4 sa = lds_u32x4(scr + 8192 + j * 512 + lane * 16), c1 = lds_u32x4(scr + 8192 + 2048 + j * 512 + lane * 16);
    #pragma unroll
    for (int r = 0; r < 2; r++) {
      xv[r][j].x = badd2(bmul2(xv[r][j].x, c1.x), sa.x); xv[r][j].y = badd2(bmul2(xv[r][j].y, c1.y), sa.y);
      xv[r][j].z = badd2(bmul2(xv[r][j].z, c1.z), sa.z); xv[r][j].w = badd2(bmul2(xv[r][j].w, c1.w), sa.w);
    }
  };
  auto store = [&](int j) {
    #pragma unroll
    for (int r = 0; r < 2; r++) *reinterpret_cast<uint4*>(g_h + (size_t)(bid * 16 + 2 * w8 + r) * T_D + j * 256 + lane * 8) = xv[r][j];
  };
  #pragma unroll 1
  for (int ph = 0; ph < 2; ph++) {
    if ((ph == 0) == early) {
      asm volatile("cp.async.wait_all;" ::: "memory");
      if (!early) mbar_wait(b_x + 168, 0);
      float acc[8];
      #pragma unroll
      for (int j = 0; j < 8; j++) acc[j] = 0.f;
      #pragma unroll
      for (int i = 0; i < 8; i++) fma8(acc, lds_f32(scr + ((t2 >> 3) + 32 * i) * 4), lds_u32x4(ws + i * 4096));
      #pragma unroll
      for (int j = 0; j < 4; j++) { const bool up = lane & 16; acc[j] = (up ? acc[4 + j] : acc[j]) + __shfl_xor_sync(0xffffffffu, up ? acc[j] : acc[4 + j], 16); }
      #pragma unroll
      for (int j = 0; j < 2; j++) { const bool up = lane & 8; acc[j] = (up ? acc[2 + j] : acc[j]) + __shfl_xor_sync(0xffffffffu, up ? acc[j] : acc[2 + j], 8); }
      sts_f32x2(scr + 1024 + w8 * 256 + (lane & 7) * 32 + (lane >> 3) * 8, acc[0], acc[1]);
      named_bar_sync(5, 256);
      if (t2 < 64) {
        float sum = 0.f;
        #pragma unroll
        for (int i = 0; i < 8; i++) sum += lds_f32(scr + 1024 + i * 256 + t2 * 4);
        st_tagged(g_modpart + ks * 2 * T_D + cb * 64 + t2, sum);
        TL_MARK2(early ? 2 : 6, t2 == 0);
      }
    } else {
      float2 pa[H_SPLIT][4];
      mbar_wait(b_x, 0);
      TL_MARK2(18, t2 == 0);
      load_parts<0, H_SPLIT>(pa, t2);
      #pragma unroll
      for (int r = 0; r < 2; r++)
        #pragma unroll
        for (int j = 0; j < 4; j++) xv[r][j] = lds_u32x4(xs + (2 * w8 + r) * 2048 + j * 512 + lane * 16);
  {
    float st[4] = {0.f, 0.f, 0.f, 0.f};
    #pragma unroll
    for (int r = 0; r < 2; r++)
      #pragma unroll
      for (int j = 0; j < 4; j++) {
        float v[8];
        unpack8(xv[r][j], v);
        st[2 * r] += ((v[0] + v[1]) + (v[2] + v[3])) + ((v[4] + v[5]) + (v[6] + v[7]));
        st[2 * r + 1] += fmaf(v[0], v[0], fmaf(v[1], v[1], fmaf(v[2], v[2], v[3] * v[3]))) + fmaf(v[4], v[4], fmaf(v[5], v[5], fmaf(v[6], v[6], v[7] * v[7])));
      }
    #pragma unroll
    for (int k = 0; k < 2; k++) { const bool up = lane & 16; st[k] = (up ? st[2 + k] : st[k]) + __shfl_xor_sync(0xffffffffu, up ? st[k] : st[2 + k], 16); }
    #pragma unroll
    for (int o = 8; o > 0; o >>= 1) { st[0] += __shfl_xor_sync(0xffffffffu, st[0], o); st[1] += __shfl_xor_sync(0xffffffffu, st[1], o); }
    const float mean = st[0] * (1.0f / T_D);
    const float inv = rcp_approx(rbf(sqrt_approx(rbf(rbf(fmaxf(fmaf(-mean, mean, st[1] * (1.0f / T_D)), 0.f)) + 1e-05f))));
    const uint32_t m = pack_bf16(mean, mean), h = pack_bf16(inv - rbf(inv), inv);
    #pragma unroll
    for (int r = 0; r < 2; r++) {
      mb2[r] = __shfl_sync(0xffffffffu, m, 16 * r);
      const uint32_t hr = __shfl_sync(0xffffffffu, h, 16 * r);
      ih[r] = __byte_perm(hr, hr, 0x3232); il[r] = __byte_perm(hr, hr, 0x1010);
    }
  }
      #pragma unroll
      for (int j = 0; j < H_SPLIT; j++) norm(j);
      TL_MARK2(5, t2 == 0);
      finish_parts<0, H_SPLIT>(pa, true, t2, scr + 8192);
      named_bar_sync(5, 256);
      TL_MARK2(7, t2 == 0);
      #pragma unroll
      for (int j = 0; j < H_SPLIT; j++) { modulate(j); store(j); }
      named_bar_arrive(9, 288);
    }
  }
  #pragma unroll
  for (int j = H_SPLIT; j < 4; j++) norm(j);
  float2 pb[4 - H_SPLIT][4];
  finish_parts<H_SPLIT, 4>(pb, false, t2, scr + 8192);
  named_bar_sync(5, 256);
  TL_MARK2(17, t2 == 0);
  #pragma unroll
  for (int j = H_SPLIT; j < 4; j++) modulate(j);
  __syncwarp();
  if (lane == 0) mbar_arrive(b_head + (xv[1][3].w & zero));
  mbar_wait(b_go, 0);
  #pragma unroll
  for (int j = H_SPLIT; j < 4; j++) store(j);
  named_bar_arrive(8, 288);
}

#define MOD_AT (b_empty + 8)
#define MOD_SPLIT 16
__device__ __forceinline__ void mod_rest(uint32_t bid, uint32_t scr, uint32_t b_go, int t, const bf16* __restrict__ cvec, const bf16* __restrict__ w_mod, const bf16* __restrict__ w_r) {
  const int lane = t & 31;
  #pragma unroll 1
  for (int i = t; i < T_D / 2; i += 64) {
    const uint32_t c2 = *reinterpret_cast<const uint32_t*>(cvec + 2 * i);
    sts_u32(scr + i * 4, pack_bf16(silu_bf(bflo(c2)), silu_bf(bfhi(c2))));
  }
  named_bar_sync(11, 64);
  const bf16* wp = w_mod + (size_t)(2 * (t >> 2)) * (6 * T_D) + 2 * T_D + bid * 32 + (t & 3) * 8;
  float acc[8];
  #pragma unroll
  for (int i = 0; i < 8; i++) acc[i] = 0.f;
  #pragma unroll 1
  for (int i = 0; i < 32; i += 2) {
    if (i == MOD_SPLIT) mbar_wait(b_go, 0);
    const uint4 w0 = ldg_nc_v4(wp), w1 = ldg_nc_v4(wp + 6 * T_D), w2 = ldg_nc_v4(wp + 32 * 6 * T_D), w3 = ldg_nc_v4(wp + 33 * 6 * T_D);
    wp += 64 * 6 * T_D;
    const uint32_t s0 = lds_u32(scr + (i * 16 + (t >> 2)) * 4), s1 = lds_u32(scr + (i * 16 + 16 + (t >> 2)) * 4);
    fma8(acc, bflo(s0), w0); fma8(acc, bfhi(s0), w1); fma8(acc, bflo(s1), w2); fma8(acc, bfhi(s1), w3);
  }
  #pragma unroll
  for (int j = 0; j < 4; j++) { const bool up = lane & 16; acc[j] = (up ? acc[4 + j] : acc[j]) + __shfl_xor_sync(0xffffffffu, up ? acc[j] : acc[4 + j], 16); }
  #pragma unroll
  for (int j = 0; j < 2; j++) { const bool up = lane & 8; acc[j] = (up ? acc[2 + j] : acc[j]) + __shfl_xor_sync(0xffffffffu, up ? acc[j] : acc[2 + j], 8); }
  { const bool up = lane & 4; acc[0] = (up ? acc[1] : acc[0]) + __shfl_xor_sync(0xffffffffu, up ? acc[0] : acc[1], 4); }
  if (t >= 32) sts_f32(scr + 2048 + lane * 4, acc[0]);
  named_bar_sync(11, 64);
  if (__shfl_sync(0xffffffffu, t, 0) < 32) {
    const int kind = bid >> 5;
    float v = rbf(acc[0] + lds_f32(scr + 2048 + lane * 4));
    const int col = (bid & 31) * 32 + (lane & 3) * 8 + (lane >> 2);
    uint8_t* dst = g_col + (col >> 7) * 1536;
    if (kind == 2) v = rbf(1.0f + v);
    float vw = v * __bfloat162float(w_r[col]);
    if (kind == 2) {
      const int c = col & 127, i = (c & ~15) + ((c >> 1) & 3) * 4 + ((c >> 3) & 1) * 2 + (c & 1);
      reinterpret_cast<bf16*>(dst)[i] = __float2bfloat16_rn(vw);
      reinterpret_cast<bf16*>(dst)[128 + i] = __float2bfloat16_rn(vw - rbf(vw));
    }
    reinterpret_cast<bf16*>(dst + 512 + (kind & 1) * 512 + (kind >> 1) * 256)[col & 127] = __float2bfloat16_rn(v);
    #pragma unroll
    for (int o = 16; o > 0; o >>= 1) vw += __shfl_xor_sync(0xffffffffu, vw, o);
    if (lane == 0 && (kind == 1 || kind == 2)) g_scal[95 - bid] = vw;
  }
  #pragma unroll 1
  for (int i = bid * 64 + t; i < (int)(sizeof(g_mail) / 16); i += 128 * 64) reinterpret_cast<uint4*>(&g_mail)[i] = make_uint4(0u, 0u, 0u, 0u);
  named_bar_sync(11, 64);
  if (t == 0) red_release_add(&g_hcnt[0], 1u);
}

constexpr int AT_NBLK = T_SEQ / 128;
constexpr float AT_HEAD = 7.0f;
#define WO_LATE 12
#define QP_STAG 3
#define AT_SPLIT 28
#define AT_PIN 12
#define PINB 4
constexpr int AT_NFULL = 124;
constexpr int AT_PREG = 40, AT_CREG = 232;
constexpr uint32_t AT_SQ = 5 * 32768;
constexpr float AT_C = 0.08838834764831845f * 1.4426950408889634f;
constexpr float AT_RAW_LO = -16.0f, AT_RAW_HI = 24.0f;
constexpr float AT_RAW_SUM = 281474976710656.0f, AT_RAW_MIN = 9.094947017729282e-13f;
constexpr uint32_t AT_SBAR = AT_SQ + 65536 + 256;
constexpr uint32_t AT_SMEM = AT_SQ + 65536 + 3072;

__device__ __forceinline__ uint32_t ring_slot(uint32_t t) { return t - 5u * ((t * 205u) >> 10); }
__device__ __forceinline__ uint32_t qp_pos(uint32_t j, uint32_t it) { return 4u * it + (j & 3u) + ((j & 3u) == 3u ? it : 0u); }
__device__ __forceinline__ uint32_t ring_par(uint32_t t) { return ((t * 205u) >> 10) & 1u; }
__device__ __forceinline__ void softmax_rowmax(const float (&s)[64], float& mx0, float& mx1) {
  float a0 = fmaxf(s[0], s[1]), a1 = fmaxf(s[4], s[5]), a2 = fmaxf(s[8], s[9]), a3 = fmaxf(s[12], s[13]);
  float b0 = fmaxf(s[2], s[3]), b1 = fmaxf(s[6], s[7]), b2 = fmaxf(s[10], s[11]), b3 = fmaxf(s[14], s[15]);
  #pragma unroll
  for (int j = 4; j < 16; j += 4) {
    a0 = fmaxf(a0, fmaxf(s[4 * j + 0], s[4 * j + 1]));  b0 = fmaxf(b0, fmaxf(s[4 * j + 2], s[4 * j + 3]));
    a1 = fmaxf(a1, fmaxf(s[4 * j + 4], s[4 * j + 5]));  b1 = fmaxf(b1, fmaxf(s[4 * j + 6], s[4 * j + 7]));
    a2 = fmaxf(a2, fmaxf(s[4 * j + 8], s[4 * j + 9]));  b2 = fmaxf(b2, fmaxf(s[4 * j + 10], s[4 * j + 11]));
    a3 = fmaxf(a3, fmaxf(s[4 * j + 12], s[4 * j + 13])); b3 = fmaxf(b3, fmaxf(s[4 * j + 14], s[4 * j + 15]));
  }
  mx0 = fmaxf(fmaxf(a0, a1), fmaxf(a2, a3));
  mx1 = fmaxf(fmaxf(b0, b1), fmaxf(b2, b3));
  mx0 = fmaxf(mx0, __shfl_xor_sync(0xffffffffu, mx0, 1));
  mx1 = fmaxf(mx1, __shfl_xor_sync(0xffffffffu, mx1, 1));
  mx0 = fmaxf(mx0, __shfl_xor_sync(0xffffffffu, mx0, 2));
  mx1 = fmaxf(mx1, __shfl_xor_sync(0xffffffffu, mx1, 2));
}
__device__ __forceinline__ void softmax_sub(float (&s)[64], float mc0, float mc1) {
  #pragma unroll
  for (int j = 0; j < 16; j++) { s[4 * j] -= mc0; s[4 * j + 1] -= mc0; s[4 * j + 2] -= mc1; s[4 * j + 3] -= mc1; }
}
template <int LO, int HI>
__device__ __forceinline__ void softmax_exp(float (&s)[64]) {
  #pragma unroll
  for (int i = LO; i < HI; i++) s[i] = ex2_approx(s[i]);
}
__device__ __forceinline__ bool softmax_mode(const float (&s)[64], float& mc0, float& mc1) {
  softmax_rowmax(s, mc0, mc1);
  const bool raw = __all_sync(0xffffffffu, mc0 >= AT_RAW_LO && mc0 <= AT_RAW_HI && mc1 >= AT_RAW_LO && mc1 <= AT_RAW_HI);
  mc0 += AT_HEAD; mc1 += AT_HEAD;
  return raw;
}
__device__ __forceinline__ void rowsum_p(const uint32_t (&p)[32], uint32_t& t0, uint32_t& t1) {
  uint32_t a[16];
  #pragma unroll
  for (int i = 0; i < 8; i++) { a[2 * i] = badd2(p[4 * i], p[4 * i + 2]); a[2 * i + 1] = badd2(p[4 * i + 1], p[4 * i + 3]); }
  #pragma unroll
  for (int i = 0; i < 4; i++) { a[2 * i] = badd2(a[4 * i], a[4 * i + 2]); a[2 * i + 1] = badd2(a[4 * i + 1], a[4 * i + 3]); }
  t0 = badd2(badd2(a[0], a[2]), badd2(a[4], a[6]));
  t1 = badd2(badd2(a[1], a[3]), badd2(a[5], a[7]));
}
__device__ __forceinline__ void add_rowsum(const uint32_t (&p)[32], float& l0, float& l1) {
  uint32_t t0, t1;
  rowsum_p(p, t0, t1);
  l0 += bflo(t0) + bfhi(t0); l1 += bflo(t1) + bfhi(t1);
}
__device__ __forceinline__ void pack_p(uint32_t (&p)[32], const float (&s)[64]) {
  #pragma unroll
  for (int i = 0; i < 32; i++) p[i] = pack_bf16(s[2 * i], s[2 * i + 1]);
}
__device__ __noinline__ void attn_rows_exact(uint32_t bid, uint32_t sq, uint32_t so, int hsel, const bf16* __restrict__ kh, const bf16* __restrict__ vh) {
  const int warp = (threadIdx.x >> 5) & 3, lane = threadIdx.x & 31;
  const size_t hofs = (size_t)((bid < 128 ? bid >> 4 : 15) * 2 + hsel) * T_SEQ * T_DH;
  kh += hofs; vh += hofs;
  #pragma unroll 1
  for (int r = 16 * warp; r < 16 * warp + 16; r++) {
    const uint32_t ad = (lane >> 4) * 16384 + r * 128 + ((((lane & 15) >> 1) ^ (r & 7)) << 4) + (lane & 1) * 8;
    uint2 qv; asm volatile("ld.shared.v2.u32 {%0, %1}, [%2];" : "=r"(qv.x), "=r"(qv.y) : "r"(sq + ad) : "memory");
    const float q0 = bflo(qv.x), q1 = bfhi(qv.x), q2 = bflo(qv.y), q3 = bfhi(qv.y);
    float m = -INFINITY, l = 0.f, o0 = 0.f, o1 = 0.f, o2 = 0.f, o3 = 0.f;
    #pragma unroll 1
    for (int key = 0; key < T_SEQ; key++) {
      const uint2 kv = *reinterpret_cast<const uint2*>(kh + (size_t)key * T_DH + lane * 4);
      const uint2 vv = *reinterpret_cast<const uint2*>(vh + (size_t)key * T_DH + lane * 4);
      float sc = (q0 * bflo(kv.x) + q1 * bfhi(kv.x)) + (q2 * bflo(kv.y) + q3 * bfhi(kv.y));
      #pragma unroll
      for (int o = 16; o > 0; o >>= 1) sc += __shfl_xor_sync(0xffffffffu, sc, o);
      const float mn = fmaxf(m, sc);
      const float al = (m == mn) ? 1.0f : ex2_approx(m - mn), p = rbf(ex2_approx(sc - mn));
      m = mn;
      l = fmaf(l, al, p);
      o0 = fmaf(o0, al, p * bflo(vv.x)); o1 = fmaf(o1, al, p * bfhi(vv.x));
      o2 = fmaf(o2, al, p * bflo(vv.y)); o3 = fmaf(o3, al, p * bfhi(vv.y));
    }
    const float inv = rcp_approx(l);
    asm volatile("st.shared.v2.u32 [%0], {%1, %2};" :: "r"(so + ad), "r"(pack_bf16(o0 * inv, o1 * inv)), "r"(pack_bf16(o2 * inv, o3 * inv)) : "memory");
  }
}
__device__ __forceinline__ void issue_qk(float (&s)[64], const uint32_t (&q)[32], uint32_t k_lo) {
  wgmma_fence();
  wgmma_m64n128k16_rs<0>(s, q[0], q[1], q[2], q[3], k_lo, 0);
  wgmma_m64n128k16_rs<2>(s, q[4], q[5], q[6], q[7], k_lo, 1);
  wgmma_m64n128k16_rs<4>(s, q[8], q[9], q[10], q[11], k_lo, 1);
  wgmma_m64n128k16_rs<6>(s, q[12], q[13], q[14], q[15], k_lo, 1);
  wgmma_m64n128k16_rs<1024>(s, q[16], q[17], q[18], q[19], k_lo, 1);
  wgmma_m64n128k16_rs<1026>(s, q[20], q[21], q[22], q[23], k_lo, 1);
  wgmma_m64n128k16_rs<1028>(s, q[24], q[25], q[26], q[27], k_lo, 1);
  wgmma_m64n128k16_rs<1030>(s, q[28], q[29], q[30], q[31], k_lo, 1);
  wgmma_commit();
}
__device__ __forceinline__ void issue_pv(float (&o)[64], const uint32_t (&p)[32], uint32_t v_lo, int accumulate) {
  wgmma_fence();
  wgmma_m64n128k16_rs_tb<0>(o, p[0], p[1], p[2], p[3], v_lo, accumulate);
  wgmma_m64n128k16_rs_tb<128>(o, p[4], p[5], p[6], p[7], v_lo, 1);
  wgmma_m64n128k16_rs_tb<256>(o, p[8], p[9], p[10], p[11], v_lo, 1);
  wgmma_m64n128k16_rs_tb<384>(o, p[12], p[13], p[14], p[15], v_lo, 1);
  wgmma_m64n128k16_rs_tb<512>(o, p[16], p[17], p[18], p[19], v_lo, 1);
  wgmma_m64n128k16_rs_tb<640>(o, p[20], p[21], p[22], p[23], v_lo, 1);
  wgmma_m64n128k16_rs_tb<768>(o, p[24], p[25], p[26], p[27], v_lo, 1);
  wgmma_m64n128k16_rs_tb<896>(o, p[28], p[29], p[30], p[31], v_lo, 1);
  wgmma_commit();
}
__device__ __forceinline__ void block_end(uint32_t zero, uint32_t bar) {
  #pragma unroll 1
  for (uint32_t i = 0; i < zero; i++) mbar_arrive(bar);
}
__device__ __forceinline__ void rescale_o(float (&o)[64], float al0, float al1) {
  #pragma unroll
  for (int j = 0; j < 16; j++) { o[4 * j] *= al0; o[4 * j + 1] *= al0; o[4 * j + 2] *= al1; o[4 * j + 3] *= al1; }
}

__device__ __forceinline__ void stage_o(const float (&o)[64], float i0, float i1, uint32_t dst, int lane) {
  #pragma unroll
  for (int J = 0; J < 16; J += 2)
    stmatrix_x4(dst + (J >> 3) * 16384 + ((((J & 7) + (lane >> 4)) ^ (lane & 7)) << 4),
                pack_bf16(o[4 * J + 0] * i0, o[4 * J + 1] * i0), pack_bf16(o[4 * J + 2] * i1, o[4 * J + 3] * i1),
                pack_bf16(o[4 * J + 4] * i0, o[4 * J + 5] * i0), pack_bf16(o[4 * J + 6] * i1, o[4 * J + 7] * i1));
}
__device__ __forceinline__ bool finish_l(float& l0, float& l1) {
  l0 += __shfl_xor_sync(0xffffffffu, l0, 1); l1 += __shfl_xor_sync(0xffffffffu, l1, 1);
  l0 += __shfl_xor_sync(0xffffffffu, l0, 2); l1 += __shfl_xor_sync(0xffffffffu, l1, 2);
  const bool redo = __any_sync(0xffffffffu, !(l0 <= AT_RAW_SUM && l1 <= AT_RAW_SUM && l0 >= AT_RAW_MIN && l1 >= AT_RAW_MIN));
  l0 = rcp_approx(l0); l1 = rcp_approx(l1);
  return redo;
}
template <int J0>
__device__ __forceinline__ void stage_q(const float (&acc)[128], float c, uint32_t dst, int lane) {
  #pragma unroll
  for (int J = J0; J < J0 + 16; J += 2)
    stmatrix_x4(dst + (J >> 3) * 16384 + ((((J & 7) + (lane >> 4)) ^ (lane & 7)) << 4),
                pack_bf16(acc[4 * J + 0] * c, acc[4 * J + 1] * c), pack_bf16(acc[4 * J + 2] * c, acc[4 * J + 3] * c),
                pack_bf16(acc[4 * J + 4] * c, acc[4 * J + 5] * c), pack_bf16(acc[4 * J + 6] * c, acc[4 * J + 7] * c));
}
__device__ __forceinline__ void store_o(const CUtensorMap* tmO, uint32_t src, int head, int row) {
  tma_store_2d(tmO, src, head * T_DH, row);
  tma_store_2d(tmO, src + 16384, head * T_DH + 64, row);
  bulk_commit();
}
__device__ __forceinline__ void mma_bf16(float (&d)[4], uint32_t a0, uint32_t a1, uint32_t a2, uint32_t a3, uint32_t b0, uint32_t b1) {
  asm volatile("mma.sync.aligned.m16n8k16.row.col.f32.bf16.bf16.f32 {%0, %1, %2, %3}, {%4, %5, %6, %7}, {%8, %9}, {%0, %1, %2, %3};"
               : "+f"(d[0]), "+f"(d[1]), "+f"(d[2]), "+f"(d[3]) : "r"(a0), "r"(a1), "r"(a2), "r"(a3), "r"(b0), "r"(b1));
}
struct GemvSel { uint32_t lo0, hi0, lo1, hi1; };
__device__ __forceinline__ GemvSel gemv_sel(int lane) {
  const uint32_t lo = (lane & 8) ? 0x1044u : 0x4410u, hi = (lane & 8) ? 0x3244u : 0x4432u;
  GemvSel s; s.lo0 = (lane & 16) ? 0x4444u : lo; s.hi0 = (lane & 16) ? 0x4444u : hi; s.lo1 = (lane & 16) ? lo : 0x4444u; s.hi1 = (lane & 16) ? hi : 0x4444u;
  return s;
}
#define GEMV_B0(j, h, s) __byte_perm((j) < 2 ? (h).x : (h).y, 0u, ((j) & 1) ? (s).hi0 : (s).lo0)
#define GEMV_B1(j, h, s) __byte_perm((j) < 2 ? (h).x : (h).y, 0u, ((j) & 1) ? (s).hi1 : (s).lo1)
__device__ __forceinline__ float4 gemv_out(const float (&d)[4], int lane) {
  const bool tk = lane & 1;
  const float r0 = __shfl_xor_sync(0xffffffffu, tk ? d[0] : d[1], 1), r1 = __shfl_xor_sync(0xffffffffu, tk ? d[2] : d[3], 1);
  return tk ? make_float4(r0, d[1], r1, d[3]) : make_float4(d[0], r0, d[2], r1);
}
#define OG_NG 8
#define PUT_N 2
#define H_STAG 2
#define AL_P 60
#define AL_SLEEP 1200
#define AL_MAX 800
#define POLL_NS 200
#define OG_PRE 10
#define OG_PRE2 12
#define OG_JOBS 7
#define OG_GRP 6
#define LD_FIRST 3
#define LD_STAG (OG_GRP / 2)
constexpr int OG_ST = 5, OG_NKB = T_DQKV / 64 - OG_PRE, OG_MOE = T_F / 32;
__device__ __forceinline__ int pre_kb(int i) { return (i >> 1) * 4 + (i & 1); }
__device__ __forceinline__ int own_kb(int i) { return i < OG_PRE2 ? pre_kb(i) + 2 : i < 64 - OG_PRE2 ? i + OG_PRE2 : pre_kb(i - (64 - OG_PRE2 - OG_PRE)); }
constexpr int OG_POS = 8;
constexpr uint32_t OG_STAGE = 32768;
constexpr uint32_t OG_SCOL = AT_SBAR + 512;
constexpr uint32_t OG_SMISC = AT_SBAR + 2048;
constexpr int OG_XPOS = OG_POS + OG_NKB;
constexpr uint32_t OG_SWD = AT_SQ, OG_PSLOT = AT_SQ;
constexpr uint32_t OG_SWD1 = (OG_XPOS % OG_ST) * OG_STAGE;
constexpr uint32_t OG_XSLOT = AT_SQ + 32768;
constexpr uint32_t OG_OSLOT = ((OG_XPOS + 1) % OG_ST) * OG_STAGE;
constexpr uint32_t OG_SH2 = ((OG_XPOS + 2) % OG_ST) * OG_STAGE;
constexpr uint32_t OG_SRED = ((OG_XPOS + 3) % OG_ST) * OG_STAGE;
constexpr uint32_t OG_SSTAT = OG_SRED + 16384;
constexpr uint32_t OG_SGU = OG_SRED + 8192;
constexpr uint32_t OG_SFIN = OG_SGU + 256;
#define OGM 2
#define OG_MT(b) ((((b) >> OGM) & 15) ^ (((b) & 64) ? 15 : 0))
#define OG_NT(b) (((b) & ((1 << OGM) - 1)) + (((b) >> (4 + OGM)) << OGM))
#define TAIL_SETUP \
  const uint32_t bar_full = sbase + AT_SBAR, bar_empty = bar_full + 40; \
  const uint32_t bar_wd = bar_full + 168, bar_col = bar_full + 176, bar_out = bar_full + 184, bar_end = bar_full + 192; \
  const uint32_t bar_key = bar_full + 200, bar_h2 = bar_full + 208, bar_sel = bar_full + 216; \
  const int mt = OG_MT(bid), nt = OG_NT(bid); \
  const int m0 = mt * 128, n0 = nt * 128; \
  const bool has_moe = (int)bid < OG_MOE; \
  (void)bar_empty; (void)bar_wd; (void)bar_col; (void)bar_out; (void)bar_end; (void)bar_key; (void)bar_h2; (void)bar_sel; (void)m0; (void)n0; (void)has_moe;

__device__ __forceinline__ void tail_producer(uint32_t bid, uint32_t sbase, uint32_t ph, uint64_t pol, const CUtensorMap* tmA, const CUtensorMap* tmB, const CUtensorMap* tmD) {
  TAIL_SETUP
  uint32_t stage = OG_POS % OG_ST;
  int kb = 0;
  #pragma unroll 1
  for (int seg = 0; seg < 2; seg++) {
    mbar_wait(bar_full + 264 + 80 * seg, 0);
    fence_proxy_async_global();
    const int end = seg == 0 ? 32 - OG_PRE2 : has_moe ? OG_NKB : 64 - OG_PRE2;
    #pragma unroll 1
    for (; kb < end; kb++) {
      const uint32_t fb = bar_full + 8 * stage, sa = sbase + stage * OG_STAGE;
      const int k0 = own_kb(kb) * 64;
      mbar_wait(bar_empty + 8 * stage, ph);
      mbar_expect_tx(fb, OG_STAGE);
      tma_load_3d_hint(sa + 16384, tmB, k0, 2 * nt, fb, pol);
      tma_load_2d_hint(sa, tmA, k0, m0, fb, pol);
      if (++stage == OG_ST) { stage = 0; ph ^= 1; }
    }
  }
  if (has_moe) {
    mbar_wait(bar_empty + 8 * (OG_XPOS % OG_ST), ph);
    mbar_expect_tx(bar_wd, OG_STAGE);
    tma_load_3d_hint(sbase + OG_SWD1, tmD, bid * 32, 8, bar_wd, pol);
  }
}

__device__ __forceinline__ uint32_t out2(uint32_t x1, uint32_t mb2, uint32_t ih, uint32_t il, uint32_t c1, uint32_t sb, uint32_t gb) {
  const uint32_t h2 = badd2(bmul2(ln_norm2b(x1, mb2, ih, il), c1), sb);
  return badd2(x1, bmul2(gb, bfma2(h2, 0u, h2)));
}
#define OGTIME gtime()
#define X_PACE 200
#define Y_SLACK 96
#define OG_STAG 3
#define WD_PACE 300
__device__ __forceinline__ void tail_exchange(uint32_t bid, uint32_t sbase, const bf16* __restrict__ w_down, const bf16* __restrict__ w_r, const bf16* __restrict__ x, bf16* __restrict__ out) {
    TAIL_SETUP
    const int lane = threadIdx.x & 31, wi = __shfl_sync(0xffffffffu, threadIdx.x >> 5, 0);
    if (wi == 3) {
      if (bid < AT_NFULL) {
        uint32_t a, b;
        asm volatile("ld.relaxed.gpu.global.u32 %0, [%1];" : "=r"(a) : "l"(g_smid + 32 + bid - lane) : "memory");
        b = __shfl_down_sync(0xffffffffu, a, 1);
        unsigned int* tm = g_tmax + bid - min((int)bid, __ffs(__ballot_sync(0xffffffffu, b >= a)) - 1);
        mbar_wait(bar_full + 312, 0);
        if (lane == 0) {
          asm volatile("mov.u32 %0, %%globaltimer_lo;" : "=r"(a));
          asm volatile("red.relaxed.gpu.global.max.u32 [%0], %1;" :: "l"(tm), "r"(a) : "memory");
          __nanosleep(AL_SLEEP);
          asm volatile("ld.relaxed.gpu.global.u32 %0, [%1];" : "=r"(b) : "l"(tm) : "memory");
          b -= a;
          sts_u32(sbase + OG_SMISC + 32, (b < AL_MAX ? b * 13 / 8 : 0u));
          mbar_arrive(bar_full + 320);
        }
        named_bar_sync(15, 32);
      }
      mbar_wait(bar_full + 344, 0);
      float a = g_scal[lane], b = g_scal[32 + lane];
      #pragma unroll
      for (int i = 0; i < 3; i++) {
        const uint4 v = *reinterpret_cast<const uint4*>(g_col + nt * 1536 + i * 512 + lane * 16);
        sts_u32x4(sbase + OG_SCOL + i * 512 + lane * 16, v.x, v.y, v.z, v.w);
      }
      #pragma unroll
      for (int o = 16; o > 0; o >>= 1) { a += __shfl_xor_sync(0xffffffffu, a, o); b += __shfl_xor_sync(0xffffffffu, b, o); }
      if (lane == 0) sts_f32x2(sbase + OG_SMISC, a, b);
      const uint64_t pol = policy_evict_first();
      #pragma unroll 1
      for (int r = lane >> 4; r < 128; r += 4) {
        __nanosleep(X_PACE);
        #pragma unroll
        for (int j = 0; j < 4; j += 2)
          asm volatile("cp.async.cg.shared.global.L2::cache_hint [%0], [%1], 16, %2;" :: "r"(sbase + OG_XSLOT + (lane & 8) * 2048 + (r + j) * 128 + (((lane ^ (r + j)) & 7) << 4)),
                       "l"(x + (size_t)(m0 + r + j) * T_D + n0 + (lane & 15) * 8), "l"(pol) : "memory");
      }
      asm volatile("cp.async.wait_all;" ::: "memory");
      __syncwarp();
      if (lane == 0) mbar_arrive(bar_col);
    } else if (wi == 2) {
      if (elect_one()) {
        const uint32_t b_free = bar_full + (bid < AT_NFULL ? 80 : 160);
        mbar_wait(b_free, 0); mbar_wait(b_free, 1);
        #pragma unroll 1
        for (unsigned int i = 0; i < (1u << 20) && ld_acquire(&g_hcnt[32 * (1 + (bid >> 3)) + 4 + ((bid >> 1) & 3)]) == 0u; i++) __nanosleep(POLL_NS);
        TL_MARK2(23, true);
        fence_proxy_async_global();
        TL_MARK2(4, true);
        mbar_expect_tx(bar_full + 272, 32768);
        bulk_load_hint(sbase + OG_PSLOT, g_pre + bid * 2048, 32768, bar_full + 272, policy_evict_first());
      }
      named_bar_sync(14, 32);
      if (has_moe) {
        mbar_wait(bar_full + 96, 1); mbar_wait(bar_full + 304, 0);
        const uint64_t pol = policy_evict_first();
        #pragma unroll 1
        for (int r = 0; r < 32; r++) {
          __nanosleep(WD_PACE);
          #pragma unroll
          for (int j = 0; j < 2; j++)
            asm volatile("cp.async.cg.shared.global.L2::cache_hint [%0], [%1], 16, %2;" :: "r"(sbase + OG_SWD + (4 * j + (lane >> 3)) * 4096 + r * 128 + (((lane ^ r) & 7) << 4)),
                         "l"((const uint8_t*)w_down + (size_t)bid * 65536 + r * 2048 + j * 512 + lane * 16), "l"(pol) : "memory");
        }
        asm volatile("cp.async.wait_all;" ::: "memory");
        __syncwarp();
        if (lane == 0) mbar_arrive(bar_wd);
      }
    }
    const uint4 wrv = ldg_nc_v4(w_r + threadIdx.x * 8);
    mbar_wait(bar_end, 0);
    if (threadIdx.x == 96) XT(10);
    TL_MARK2(22, lane == 0);
    if (wi == 0) {
      uint32_t k1 = 0u, k2 = 0u;
      #pragma unroll 1
      for (unsigned int spin = 0; spin < (1u << 22) && __any_sync(0xffffffffu, k1 == 0u); spin++) asm volatile("ld.relaxed.gpu.global.u32 %0, [%1];" : "=r"(k1) : "l"(g_key + lane) : "memory");
      TL_MARK2(28, lane == 0);
      warp_top2(k1, k2);
      if (lane == 0) {
        const uint32_t r1 = 0xffffu - (k1 & 0xffffu), r2 = 0xffffu - (k2 & 0xffffu);
        sts_u32x4(sbase + OG_SMISC + 64, r1, r2, (r1 >> 7) * 2, (r2 >> 7) * 2 + ((r1 >> 7) == (r2 >> 7)));
        mbar_arrive(bar_sel);
      }
    } else if (wi < 3) {
          mbar_wait(bar_key, 0);
          const uint4 kk = lds_u32x4(sbase + OG_SSTAT + 1024 + lane * 16);
          uint32_t k1 = max(kk.x, kk.y), k2 = min(kk.x, kk.y);
          k2 = max(max(k2, min(kk.z, kk.w)), min(k1, max(kk.z, kk.w))); k1 = max(k1, max(kk.z, kk.w));
          warp_top2(k1, k2);
          if (wi == 1) {
            if (lane == 0) {
              if (nt == (mt & 7)) st_relaxed2(g_key + mt * 2, k1, k2);
              sts_u32x2(sbase + OG_SMISC + 96, (~k1 >> 4) & 7u, (~k2 >> 4) & 7u);
              mbar_arrive(bar_full + 352);
            }
            TL_MARK2(27, lane == 0);
          } else {
            const uint32_t r = (~((lane & 16) ? k2 : k1)) & 127u, ch = lane & 15;
            const uint2 st = lds_u32x2(sbase + OG_SSTAT + r * 8);
            const uint4 xc = lds_u32x4(sbase + OG_XSLOT + (ch >> 3) * 16384 + r * 128 + (((ch ^ r) & 7) << 4));
            const uint4 c1 = lds_u32x4(sbase + OG_SCOL + 768 + ch * 16), sh = lds_u32x4(sbase + OG_SCOL + 1024 + ch * 16);
            const float inr = __uint_as_float(st.y);
            float* dst = reinterpret_cast<float*>(g_cand + (mt * 2 + (lane >> 4)) * 256 + nt * 16 + ch);
            st_tagged4(dst + 512, __uint_as_float(ln_mod2(xc.x, st.x, inr, c1.x, sh.x)), __uint_as_float(ln_mod2(xc.y, st.x, inr, c1.y, sh.y)),
                       __uint_as_float(ln_mod2(xc.z, st.x, inr, c1.z, sh.z)), __uint_as_float(ln_mod2(xc.w, st.x, inr, c1.w, sh.w)));
            st_tagged4(dst, __uint_as_float(xc.x), __uint_as_float(xc.y), __uint_as_float(xc.z), __uint_as_float(xc.w));
          }
    }
    mbar_wait(bar_sel, 0);
    const uint4 sel = lds_u32x4(sbase + OG_SMISC + 64);
    const int sel0 = (int)sel.x, sel1 = (int)sel.y;
    {
      const float* src0 = reinterpret_cast<const float*>(g_cand + sel.z * 256 + 128 + threadIdx.x);
      const float* src1 = reinterpret_cast<const float*>(g_cand + sel.w * 256 + 128 + threadIdx.x);
      float4 h0, h1;
      #pragma unroll 1
      for (unsigned int spin = 0; spin < (1u << 20); spin++) { h0 = ld_tagged4(src0); h1 = ld_tagged4(src1); if (__all_sync(0xffffffffu, tagged4(h0) & tagged4(h1))) break; }
      sts_f32x4(sbase + OG_SH2 + threadIdx.x * 16, h0.x, h0.y, h0.z, h0.w);
      sts_f32x4(sbase + OG_SH2 + 2048 + threadIdx.x * 16, h1.x, h1.y, h1.z, h1.w);
      __syncwarp();
      if (lane == 0) mbar_arrive(bar_h2);
      TL_MARK2(12, lane == 0);
      if (bid >> 6) h0 = h1;
      float v[8], wr[8];
      unpack8(make_uint4(__float_as_uint(h0.x), __float_as_uint(h0.y), __float_as_uint(h0.z), __float_as_uint(h0.w)), v); unpack8(wrv, wr);
      float r = 0.f;
      #pragma unroll
      for (int i = 0; i < 8; i++) r = fmaf(v[i], wr[i], r);
      #pragma unroll
      for (int o = 16; o > 0; o >>= 1) r += __shfl_xor_sync(0xffffffffu, r, o);
      if (lane == 0) sts_f32(sbase + OG_SMISC + 192 + wi * 4, r);
    }
    mbar_wait(bar_out, 0);
    {
      const uint2 cg = lds_u32x2(sbase + OG_SMISC + 96);
      #pragma unroll
      for (int i = 0; i < 4; i++) {
        const int r = (i < 2 ? cg.x : cg.y) * 16 + (i & 1) * 8 + (threadIdx.x >> 4), ch = threadIdx.x & 15;
        if (m0 + r != sel0 && m0 + r != sel1)
          *reinterpret_cast<uint4*>(out + (size_t)(m0 + r) * T_D + n0 + ch * 8) =
              lds_u32x4(sbase + OG_OSLOT + (ch >> 3) * 16384 + r * 128 + (((ch & 7) ^ (r & 7)) << 4));
      }
    }
    if (bid == 0 && threadIdx.x < 68) *reinterpret_cast<uint4*>(g_hcnt + 32 * (threadIdx.x >> 2) + 4 * (threadIdx.x & 3)) = make_uint4(0u, 0u, 0u, 0u);
    if (threadIdx.x < 64) g_modpart[bid * 64 + threadIdx.x] = 0.f;
    if (threadIdx.x == 64) g_tmax[bid] = 0u;
    {
      const int tk = bid >> 6, c0 = (bid & 63) * 16;
      const uint32_t gb2 = *reinterpret_cast<const uint32_t*>(g_col + (c0 >> 7) * 1536 + 512 + 768 + ((c0 & 127) + (threadIdx.x & 14)) * 2);
      const uint32_t* xp = reinterpret_cast<const uint32_t*>(g_cand + (tk ? sel.w : sel.z) * 256) + ((c0 + (threadIdx.x & 14)) >> 1);
      uint32_t x2 = 0u;
      #pragma unroll 1
      for (unsigned int spin = 0; spin < (1u << 20) && __any_sync(0xffffffffu, x2 == 0u); spin++) asm volatile("ld.relaxed.gpu.global.u32 %0, [%1];" : "=r"(x2) : "l"(xp) : "memory");
      const float* src = g_ypart + (size_t)((threadIdx.x >> 2) * 2 + tk) * T_D + c0 + (threadIdx.x & 3) * 4;
      const bool four = threadIdx.x < (OG_MOE - 96) * 4;
      if (threadIdx.x == 0) hint_wait(CNT_Y, (uint32_t)(OG_MOE - Y_SLACK));
      named_bar_sync(10, 128);
      float4 p0, p1, p2, p3;
      #pragma unroll 1
      for (unsigned int spin = 0; spin < (1u << 20); spin++) {
        p0 = ld_tagged4(src); p1 = ld_tagged4(src + 64 * T_D); p2 = ld_tagged4(src + 128 * T_D); p3 = ld_tagged4(four ? src + 192 * T_D : src);
        if (__all_sync(0xffffffffu, tagged4(p0) & tagged4(p1) & tagged4(p2) & tagged4(p3))) break;
      }
      if (four) { p2.x += p3.x; p2.y += p3.y; p2.z += p3.z; p2.w += p3.w; }
      p0.x = (p0.x + p1.x) + p2.x; p0.y = (p0.y + p1.y) + p2.y; p0.z = (p0.z + p1.z) + p2.z; p0.w = (p0.w + p1.w) + p2.w;
      #pragma unroll
      for (int o = 4; o <= 16; o <<= 1) {
        p0.x += __shfl_xor_sync(0xffffffffu, p0.x, o); p0.y += __shfl_xor_sync(0xffffffffu, p0.y, o);
        p0.z += __shfl_xor_sync(0xffffffffu, p0.z, o); p0.w += __shfl_xor_sync(0xffffffffu, p0.w, o);
      }
      if (lane < 4) sts_f32x4(sbase + OG_SFIN + (threadIdx.x >> 5) * 64 + lane * 16, p0.x, p0.y, p0.z, p0.w);
      named_bar_sync(10, 128);
      TL_MARK2(21, threadIdx.x == 0);
      if (threadIdx.x < 16) {
        const uint32_t ya = sbase + OG_SFIN + threadIdx.x * 4, rp = sbase + OG_SMISC + 192;
        float y = (lds_f32(ya) + lds_f32(ya + 64)) + (lds_f32(ya + 128) + lds_f32(ya + 192));
        const float r = rbf((lds_f32(rp) + lds_f32(rp + 4)) + (lds_f32(rp + 8) + lds_f32(rp + 12)));
        const float rs = rbf(sigmoid_f(r));
        const uint32_t h2p = lds_u32(sbase + OG_SH2 + tk * 2048 + (c0 + (threadIdx.x & 14)) * 2);
        const float fh = (lane & 1) ? bfhi(h2p) : bflo(h2p);
        y = rbf(y);
        y = rbf(y * rs);
        const float upd = rbf(rbf(fh * 0.0f) + y);
        out[(size_t)(tk ? sel1 : sel0) * T_D + c0 + threadIdx.x] =
            __float2bfloat16_rn(((lane & 1) ? bfhi(x2) : bflo(x2)) + rbf(((lane & 1) ? bfhi(gb2) : bflo(gb2)) * rbf(fh + upd)));
      }
    }
    if (threadIdx.x == 0) XT(11);
    TL_END(4, threadIdx.x == 0);
}

__device__ __forceinline__ void load_pre(uint4* pre, uint32_t sbase, uint32_t buf, int t2) {
  mbar_wait(sbase + AT_SBAR + 272, 0);
  #pragma unroll
  for (int i = 0; i < 8; i++) pre[i] = lds_u32x4(sbase + buf + i * 4096 + t2 * 16);
}
__device__ __forceinline__ void tail_consumer(uint32_t bid, uint32_t sbase, const CUtensorMap* tmOut, const uint4 (&pre)[8], int cwg, const bf16* __restrict__ w_gate, const bf16* __restrict__ w_up) {
    TAIL_SETUP
    const int tid = threadIdx.x & 127, t2 = threadIdx.x - 128;
    const int warp = tid >> 5, lane = tid & 31, w8 = t2 >> 5;
    const uint32_t dbase = (sbase & 0x3FFFFu) >> 4;
    const uint32_t a_base = dbase + ((cwg * 8192) >> 4) + (1u << 16);
    const uint32_t b_base = dbase + (16384 >> 4) + (512u << 16);
    TL_MARK2(25, threadIdx.x == 128);
    const uint64_t pol = policy_evict_first();
    const bf16* pw = ((lane & 16) ? w_up : w_gate) + (size_t)(w8 * 128 + (lane & 3) * 4) * T_F + (has_moe ? bid : 0) * 32 + ((lane >> 2) & 3) * 8;
    uint4 wv[32];
    float acc[64];
    #pragma unroll
    for (int i = 0; i < 8; i++) {
      acc[8 * i] = bflo(pre[i].x); acc[8 * i + 1] = bfhi(pre[i].x); acc[8 * i + 2] = bflo(pre[i].y); acc[8 * i + 3] = bfhi(pre[i].y);
      acc[8 * i + 4] = bflo(pre[i].z); acc[8 * i + 5] = bfhi(pre[i].z); acc[8 * i + 6] = bflo(pre[i].w); acc[8 * i + 7] = bfhi(pre[i].w);
    }
    if (lane == 0) mbar_arrive(bar_full + 304);
    if (bid < AT_NFULL) {
      const uint32_t c0 = clock_lo();
      mbar_wait(bar_full + 320, 0);
      const uint32_t d = lds_u32(sbase + OG_SMISC + 32);
      while (clock_lo() - c0 < d) {}
    }
    {
      uint32_t stage = OG_POS % OG_ST, phase = (OG_POS / OG_ST) & 1, prev = 12;
      int kb = 0;
      #pragma unroll
      for (int g = 0; g <= OG_NG; g++) {
        const int end = g == OG_NG ? (has_moe ? OG_NKB : 64 - OG_PRE2) : LD_FIRST + g * OG_GRP + LD_STAG * cwg;
        #pragma unroll 1
        do {
          mbar_wait(bar_full + 8 * stage, phase);
          if (OG_STAG > 0 && g == OG_NG && cwg == 1 && kb == end - OG_STAG) named_bar_sync(7, 256);
          const uint32_t a_lo = a_base + stage * (OG_STAGE >> 4), b_lo = b_base + stage * (OG_STAGE >> 4);
          wgmma_fence();
          wgmma_m64n128k16_ss_tb<0, 0>(acc, a_lo, b_lo, 1);
          wgmma_m64n128k16_ss_tb<2, 128>(acc, a_lo, b_lo, 1);
          wgmma_m64n128k16_ss_tb<4, 256>(acc, a_lo, b_lo, 1);
          wgmma_m64n128k16_ss_tb<6, 384>(acc, a_lo, b_lo, 1);
          wgmma_commit();
          if (OG_STAG > 0 && g == OG_NG && cwg == 0 && kb == end - 1) named_bar_arrive(7, 256);
          wgmma_wait<1>();
          if (tid == 0) mbar_arrive(bar_empty + 8 * prev);
          prev = stage;
          if (++stage == OG_ST) { stage = 0; phase ^= 1; }
        } while (++kb < end);
        #pragma unroll
        for (int j = 4 * g; j < 4 * g + 4 && j < 32; j++) wv[j] = ldg_stream_v4(pw + (size_t)(16 * (j >> 2) + (j & 3)) * T_F, pol);
      }
    }
    mbar_wait(bar_col, 0);
    if (__builtin_expect(!has_moe, 0)) {
      load_pre(wv, sbase, AT_SQ, t2);
    }
    wgmma_wait<0>();
    fence_regs(acc);
    if (__builtin_expect(!has_moe, 0)) {
      #pragma unroll
      for (int i = 0; i < 8; i++) {
        acc[8 * i] += bflo(wv[i].x); acc[8 * i + 1] += bfhi(wv[i].x); acc[8 * i + 2] += bflo(wv[i].y); acc[8 * i + 3] += bfhi(wv[i].y);
        acc[8 * i + 4] += bflo(wv[i].z); acc[8 * i + 5] += bfhi(wv[i].z); acc[8 * i + 6] += bflo(wv[i].w); acc[8 * i + 7] += bfhi(wv[i].w);
      }
    }
    if (tid == 0) mbar_arrive(bar_end);
    TL_MARK2(9, lane == 0);
    const int q2 = 2 * (lane & 3);
    const uint32_t frag = (64 * cwg + 16 * warp + (lane & 7) + 8 * ((lane >> 3) & 1)) * 128;
    const int fsw = lane & 7, fhi = lane >> 4;
    {
      float dl[4] = {0.f, 0.f, 0.f, 0.f}, da[4] = {0.f, 0.f, 0.f, 0.f}, db[4] = {0.f, 0.f, 0.f, 0.f};
      const uint32_t tb = sbase + OG_SCOL + (lane & 8) * 32 + (lane & 3) * 8, g = lane >> 2;
      const uint32_t msk = (g == 1 || g == 2) ? 0xffffffffu : 0u, one = g == 0 ? 0x3F803F80u : 0u;
      #pragma unroll
      for (int J = 0; J < 16; J += 2) {
        const uint32_t ad = sbase + OG_XSLOT + (J >> 3) * 16384 + frag + ((((J & 7) + fhi) ^ fsw) << 4);
        uint32_t xr[4];
        ldmatrix_x4(ad, xr[0], xr[1], xr[2], xr[3]);
        const uint2 cw = lds_u32x2(tb + J * 16);
        #pragma unroll
        for (int h = 0; h < 2; h++) {
          const uint32_t ga = lds_u32(sbase + OG_SCOL + 512 + (8 * (J + h) + q2) * 2);
          xr[2 * h] = badd2(xr[2 * h], bmul2(ga, pack_bf16(acc[4 * (J + h)], acc[4 * (J + h) + 1])));
          xr[2 * h + 1] = badd2(xr[2 * h + 1], bmul2(ga, pack_bf16(acc[4 * (J + h) + 2], acc[4 * (J + h) + 3])));
        }
        stmatrix_x4(ad, xr[0], xr[1], xr[2], xr[3]);
        mma_bf16(dl, xr[0], xr[1], xr[2], xr[3], (cw.x & msk) | one, (cw.y & msk) | one);
        mma_bf16(da, xr[0], xr[1], xr[2], xr[3], xr[0], xr[2]);
        mma_bf16(db, xr[0], xr[1], xr[2], xr[3], xr[1], xr[3]);
      }
      {
        const int dsrc = (lane & ~3) + (g >> 1);
        const float qa = __shfl_sync(0xffffffffu, (g & 1) ? da[1] : da[0], dsrc), qb = __shfl_sync(0xffffffffu, (g & 1) ? db[3] : db[2], dsrc);
        const float e0 = __shfl_xor_sync(0xffffffffu, (lane & 1) ? dl[0] : dl[2], 1), e1 = __shfl_xor_sync(0xffffffffu, dl[3], 1);
        if ((lane & 3) < 2) {
          const bool hi = lane & 1;
          st_tagged4(reinterpret_cast<float*>(g_part1 + ((mt * 8 + w8) * 8 + nt) * 16 + g + (hi ? 8 : 0)),
                     hi ? e0 : dl[0], hi ? qb : qa, hi ? e1 + dl[2] : dl[1] + e0, 1.0f);
        }
      }
    }
    TL_MARK2(10, lane == 0);
    uint4 wd[16];
    if (has_moe) mbar_wait(bar_wd, 0);
    #pragma unroll
    for (int i = 0; i < 16; i++) wd[i] = lds_u32x4(sbase + (cwg ? OG_SWD1 : OG_SWD) + warp * 8192 + (i >> 3) * 4096 + (i & 6) * 512 + (i & 1) * 128 + (lane & 3) * 256 + (((lane >> 2) ^ (2 * (lane & 3) + (i & 1))) << 4));
    {
      const float* src = reinterpret_cast<const float*>(g_part1 + ((mt * 8 + w8) * 8 + (lane & 1) * 4) * 16 + (lane >> 1));
      float4 v, v1, v2, v3;
      #pragma unroll 1
      for (unsigned int spin = 0; spin < (1u << 22); spin++) {
        v = ld_tagged4(src); v1 = ld_tagged4(src + 64); v2 = ld_tagged4(src + 128); v3 = ld_tagged4(src + 192);
        if (__all_sync(0xffffffffu, tagged4(v) & tagged4(v1) & tagged4(v2) & tagged4(v3))) break;
        __nanosleep(100);
      }
      __syncwarp();
      TL_MARK2(26, lane == 0);
      v.x = (v.x + v1.x) + (v2.x + v3.x); v.y = (v.y + v1.y) + (v2.y + v3.y); v.z = (v.z + v1.z) + (v2.z + v3.z);
      v.x += __shfl_xor_sync(0xffffffffu, v.x, 1); v.y += __shfl_xor_sync(0xffffffffu, v.y, 1); v.z += __shfl_xor_sync(0xffffffffu, v.z, 1);
      const float mean = v.x * (1.0f / T_D);
      const float var = fmaxf(fmaf(-mean, mean, v.y * (1.0f / T_D)), 0.f);
      const uint32_t mb2 = pack_bf16(mean, mean);
      const float inv = rcp_approx(rbf(sqrt_approx(rbf(rbf(var) + 1e-05f))));
      {
        const float2 sc = lds_f32x2(sbase + OG_SMISC);
        const uint32_t key = rank_key(rbf(fmaf(fmaf(-bflo(mb2), sc.x, v.z), inv, sc.y)), m0 + 16 * w8 + (lane >> 1));
        mbar_wait(bar_end, 0);
        if (lane & 1) sts_u32(sbase + OG_SSTAT + 1024 + (16 * w8 + (lane >> 1)) * 4, key);
        else sts_u32x2(sbase + OG_SSTAT + (16 * w8 + (lane >> 1)) * 8, mb2, __float_as_uint(inv));
        __syncwarp();
        if (lane == 0) mbar_arrive(bar_key);
      }
      const uint32_t ih = pack_bf16(inv, inv), il = pack_bf16(inv - bflo(ih), inv - bflo(ih));
      const uint32_t mba = __shfl_sync(0xffffffffu, mb2, 2 * (lane >> 2)), mbb = __shfl_sync(0xffffffffu, mb2, 2 * (lane >> 2) + 16);
      const uint32_t iha = __shfl_sync(0xffffffffu, ih, 2 * (lane >> 2)), ihb = __shfl_sync(0xffffffffu, ih, 2 * (lane >> 2) + 16);
      const uint32_t ila = __shfl_sync(0xffffffffu, il, 2 * (lane >> 2)), ilb = __shfl_sync(0xffffffffu, il, 2 * (lane >> 2) + 16);
      #pragma unroll 2
      for (int J = 0; J < 16; J += 2) {
        const uint32_t off = (J >> 3) * 16384 + frag + ((((J & 7) + fhi) ^ fsw) << 4);
        uint32_t xr[4];
        ldmatrix_x4(sbase + OG_XSLOT + off, xr[0], xr[1], xr[2], xr[3]);
        #pragma unroll
        for (int h = 0; h < 2; h++) {
          const uint32_t ca = sbase + OG_SCOL + 512 + (8 * (J + h) + q2) * 2;
          const uint32_t c1 = lds_u32(ca + 256), sh = lds_u32(ca + 512), gb = lds_u32(ca + 768);
          xr[2 * h] = out2(xr[2 * h], mba, iha, ila, c1, sh, gb);
          xr[2 * h + 1] = out2(xr[2 * h + 1], mbb, ihb, ilb, c1, sh, gb);
        }
        stmatrix_x4(sbase + OG_OSLOT + off, xr[0], xr[1], xr[2], xr[3]);
      }
      fence_proxy_async();
      mbar_wait(bar_full + 352, 0);
      const uint2 cg = lds_u32x2(sbase + OG_SMISC + 96);
      __syncwarp();
      if (elect_one()) {
        mbar_arrive(bar_out);
        if (cg.x != w8 && cg.y != w8) {
          asm volatile("cp.async.bulk.tensor.2d.global.shared::cta.bulk_group [%0, {%2, %3}], [%1];" :: "l"(tmOut), "r"(sbase + OG_OSLOT + w8 * 2048), "r"(n0), "r"(m0 + 16 * w8) : "memory");
          asm volatile("cp.async.bulk.tensor.2d.global.shared::cta.bulk_group [%0, {%2, %3}], [%1];" :: "l"(tmOut), "r"(sbase + OG_OSLOT + 16384 + w8 * 2048), "r"(n0 + 64), "r"(m0 + 16 * w8) : "memory");
          bulk_commit();
        }
      }
      TL_MARK2(24, lane == 0);
    }
    if (has_moe) mbar_wait(bar_h2, 0);
    TL_MARK2(13, lane == 0);
    if (has_moe) {
      const GemvSel sel = gemv_sel(lane);
      {
        float d[4][4];
        #pragma unroll
        for (int c = 0; c < 4; c++) { d[c][0] = 0.f; d[c][1] = 0.f; d[c][2] = 0.f; d[c][3] = 0.f; }
        #pragma unroll
        for (int st = 0; st < 8; st++) {
          const uint2 hb = lds_u32x2(sbase + OG_SH2 + ((lane >> 2) & 1) * 2048 + (w8 * 128 + st * 16 + (lane & 3) * 4) * 2);
          #pragma unroll
          for (int j = 0; j < 4; j++) mma_bf16(d[j], wv[4 * st + j].x, wv[4 * st + j].y, wv[4 * st + j].z, wv[4 * st + j].w, GEMV_B0(j, hb, sel), GEMV_B1(j, hb, sel));
        }
        #pragma unroll
        for (int e = 0; e < 4; e++) d[0][e] = (d[0][e] + d[1][e]) + (d[2][e] + d[3][e]);
        const float4 r = gemv_out(d[0], lane);
        sts_f32x4(sbase + OG_SRED + w8 * 512 + (((lane >> 4) * 2 + (lane & 1)) * 32 + ((lane >> 2) & 3) * 8 + (lane & 2) * 2) * 4, r.x, r.y, r.z, r.w);
      }
      named_bar_sync(9, 256);
      if (t2 < 64) {
        float gp[8], up[8];
        #pragma unroll
        for (int w = 0; w < 8; w++) { gp[w] = lds_f32(sbase + OG_SRED + w * 512 + t2 * 4); up[w] = lds_f32(sbase + OG_SRED + w * 512 + 256 + t2 * 4); }
        const float gs = ((gp[0] + gp[1]) + (gp[2] + gp[3])) + ((gp[4] + gp[5]) + (gp[6] + gp[7]));
        const float us = ((up[0] + up[1]) + (up[2] + up[3])) + ((up[4] + up[5]) + (up[6] + up[7]));
        asm volatile("st.shared.u16 [%0], %1;" :: "r"(sbase + OG_SGU + ((t2 & ~15) + ((t2 >> 1) & 3) * 4 + ((t2 >> 3) & 1) * 2 + (t2 & 1)) * 2), "h"((uint16_t)pack_bf16(silu_bf(rbf(gs)) * rbf(us), 0.f)) : "memory");
      }
      named_bar_sync(9, 256);
      TL_MARK2(20, threadIdx.x == 128);
      float d[4][4];
      #pragma unroll
      for (int c = 0; c < 4; c++) { d[c][0] = 0.f; d[c][1] = 0.f; d[c][2] = 0.f; d[c][3] = 0.f; }
      #pragma unroll
      for (int st = 0; st < 2; st++) {
        const uint2 g = lds_u32x2(sbase + OG_SGU + ((lane >> 2) & 1) * 64 + st * 32 + (lane & 3) * 8);
        #pragma unroll
        for (int j = 0; j < 4; j++) {
          const uint32_t b0 = GEMV_B0(j, g, sel), b1 = GEMV_B1(j, g, sel);
          mma_bf16(d[j & 1], wd[4 * st + j].x, wd[4 * st + j].y, wd[4 * st + j].z, wd[4 * st + j].w, b0, b1);
          mma_bf16(d[2 + (j & 1)], wd[8 + 4 * st + j].x, wd[8 + 4 * st + j].y, wd[8 + 4 * st + j].z, wd[8 + 4 * st + j].w, b0, b1);
        }
      }
      #pragma unroll
      for (int e = 0; e < 4; e++) { d[0][e] += d[1][e]; d[2][e] += d[3][e]; }
      const float4 y0 = gemv_out(d[0], lane), y1 = gemv_out(d[2], lane);
      float* yp = g_ypart + (size_t)(bid * 2 + (lane & 1)) * T_D + w8 * 128 + (lane >> 2) * 8 + (lane & 2) * 2;
      st_tagged4(yp, y0.x, y0.y, y0.z, y0.w);
      st_tagged4(yp + 64, y1.x, y1.y, y1.z, y1.w);
      named_bar_sync(9, 256);
      if (t2 == 0) hint_arrive(CNT_Y);
    }
    bulk_wait_read<0>();
    TL_MARK2(14, threadIdx.x == 128);
    TL_CLK(4, 1, threadIdx.x == 128);
}

__device__ __forceinline__ int help_njobs(uint32_t bid) { return bid < 128 ? OG_JOBS : 16 - OG_JOBS; }
__device__ __forceinline__ int help_job(uint32_t bid, int i) { return (i < OG_JOBS ? 16 * i + (bid >> 7) * 2 : 112 + (i - OG_JOBS) * 2) + (bid & 3) * 4; }
__device__ __noinline__ void store_warp(uint32_t bid, uint32_t sbase, const CUtensorMap* tmO, int item0, int n_items) {
  if (elect_one()) {
    const uint32_t bars = sbase + AT_SBAR, b_q0 = bars + 80, b_ob = bars + 96, b_ordy = bars + 104, b_acq = bars + 264;
    const unsigned int* cnt = &g_hcnt[32 * (1 + OG_MT(bid)) + 2];
    #pragma unroll 1
    for (int q = 0; q < 4 * n_items; q++) {
      const int item = item0 + (q >> 2) * 128, h = (q >> 1) & 1, w = q & 1;
      const bool last = (q >> 2) == n_items - 1;
      if (q == 4 * n_items - 4) { mbar_wait(bars + 288, 0); red_release_add(&g_hcnt[1], 1u); }
      mbar_wait(b_ordy + 8 * (q & 3), q >> 2);
      store_o(tmO, (h ? (last ? sbase + AT_SQ + 32768 : sbase + 2 * 32768) : sbase + AT_SQ) + w * 8192, (item >> 4) * 2 + h, (item & 15) * 128 + w * 64);
      if (w) {
        bulk_wait_read<0>();
        mbar_arrive(h ? b_ob : b_q0);
        bulk_wait<0>();
        fence_proxy_async_global();
        asm volatile("fence.acq_rel.gpu;" ::: "memory");
        hint_arrive(&g_hcnt[32 * (1 + (item & 15)) + 2 + (item >> 7)]);
        if (!h && item < 128) hint_arrive(&g_hcnt[2]);
        if (q == 5) { spin_until(cnt, 16u); mbar_arrive(b_acq); }
      }
    }
    if (n_items == 1) {
      #pragma unroll 1
      for (int i = 0; i < help_njobs(bid); i++) {
        mbar_wait(b_acq + 16, i & 1);
        TL_MARK2(23, i == OG_JOBS - 1);
        red_release_add(&g_hcnt[32 * (1 + (help_job(bid, i) >> 3)) + 4 + ((help_job(bid, i) >> 1) & 3)], 1u);
        TL_MARK2(4, i == OG_JOBS - 1);
        if (i == PRE_X - 1) { spin_until(&g_hcnt[1], 132u); mbar_arrive(b_acq + 32); }
      }
    }
    if (bid < 128) {
      if (n_items == 1) { spin_until(cnt, 16u); mbar_arrive(b_acq); }
      spin_until(&g_hcnt[0], 128u); spin_until(cnt + 1, 16u); mbar_arrive(b_acq + 80);
    }
  }
}

struct Roles { uint8_t of_sm[132]; };
#define GMAP 1
__global__ void __launch_bounds__(384, 1)
fused_kernel(const __grid_constant__ CUtensorMap tmH, const __grid_constant__ CUtensorMap tmW, const __grid_constant__ CUtensorMap tmK,
            const __grid_constant__ CUtensorMap tmV, const __grid_constant__ CUtensorMap tmO, const __grid_constant__ CUtensorMap tmOl, const __grid_constant__ CUtensorMap tmWo,
            const __grid_constant__ CUtensorMap tmD, const __grid_constant__ CUtensorMap tmOut, const __grid_constant__ CUtensorMap tmM, const __grid_constant__ Roles roles, uint32_t zero,
            const uint8_t* __restrict__ pf_wo, const bf16* __restrict__ kc, const bf16* __restrict__ vc,
            const bf16* __restrict__ x, const bf16* __restrict__ cvec, const bf16* __restrict__ w_mod, const bf16* __restrict__ w_r,
            const bf16* __restrict__ w_gate, const bf16* __restrict__ w_up, const bf16* __restrict__ w_down, bf16* __restrict__ out)
{
  uint32_t bid;
  asm volatile("mov.u32 %0, %%smid;" : "=r"(bid));
  bid = __shfl_sync(0xffffffffu, GMAP ? (uint32_t)roles.of_sm[bid] : blockIdx.x, 0);
  extern __shared__ __align__(1024) uint8_t smem_raw[];
  const uint32_t sbase = smem_u32(smem_raw);
  const uint32_t bars = sbase + AT_SBAR;
  const uint32_t b_full = bars, b_empty = bars + 40;
  const uint32_t b_q0 = bars + 80, b_q1 = bars + 88;
  const uint32_t b_ob = bars + 96;
  const uint32_t b_ordy = bars + 104;
  const uint32_t b_pin = bars + 136;
  const uint32_t b_head = bars + 144;
  const uint32_t b_go = bars + 152;
  const uint32_t b_x = bars + 160;
  const int wg = __shfl_sync(0xffffffffu, threadIdx.x >> 7, 0);
  const bool single = bid >= AT_NFULL;
  const int item0 = __shfl_sync(0xffffffffu, bid < 128 ? (int)bid : (int)bid + 124, 0), n_items = __shfl_sync(0xffffffffu, single ? 1 : 2, 0);
  TL_START(3);
  if (threadIdx.x == 0) {
    if (sbase & 1023u) __trap();
    for (int i = 0; i < 5; i++) { mbar_init(b_full + 8 * i, 1); mbar_init(b_empty + 8 * i, 2); }
    mbar_init(b_q0, 1); mbar_init(b_q1, 8); mbar_init(b_ob, 1);
    for (int i = 0; i < 4; i++) mbar_init(b_ordy + 8 * i, 4);
    mbar_init(b_pin, 1); mbar_init(b_head, bid < 128 ? 8 : 1); mbar_init(b_go, 1); mbar_init(b_x, 1);
    mbar_init(bars + 168, 2); mbar_init(bars + 176, 1); mbar_init(bars + 184, 8); mbar_init(bars + 192, 2);
    mbar_init(bars + 200, 8); mbar_init(bars + 208, 4); mbar_init(bars + 216, 1); mbar_init(bars + 264, 1); mbar_init(bars + 272, 1); mbar_init(bars + 280, 8); mbar_init(bars + 288, 1); mbar_init(bars + 296, 1); mbar_init(bars + 304, 8); mbar_init(bars + 312, 1); mbar_init(bars + 320, 1); mbar_init(bars + 328, 1); mbar_init(bars + 344, 1); mbar_init(bars + 352, 1);
    sts_u32(bars + 400, bid);
    fence_mbar_init();
  }

  if (wg == 0) {
    reg_dealloc<AT_PREG>();
    if (threadIdx.x < 32) { __syncwarp(); named_bar_arrive(6, 384); }
    if (threadIdx.x >= 64) {
      named_bar_sync(6, 384);
      if (bid < 128) {
        named_bar_sync(threadIdx.x >= 96 ? 8 : 9, 288);
        if ((threadIdx.x & 31) == 0) red_release_add(&g_hcnt[32 * (1 + (bid >> 3)) + (threadIdx.x >= 96)], 1u);
        TL_MARK2(11, threadIdx.x == 64);
      }
      if (bid < 128) {
        mbar_wait(MOD_AT, 0);
        mod_rest(bid, sbase + OG_SCOL, b_q1, threadIdx.x - 64, cvec, w_mod, w_r);
      }
    } else if (threadIdx.x >= 32) {
      named_bar_sync(6, 384);
      store_warp(bid, sbase, &tmO, item0, n_items);
      __syncwarp();
    } else {
     if (elect_one()) {
      const uint64_t pol = policy_evict_first();
      if (bid < 128) {
        mbar_expect_tx(b_x, 32768);
        if (X_DLY) { const uint32_t c0 = clock_lo(); while (clock_lo() - c0 < X_DLY) {} }
        bulk_load_hint(sbase + 4 * 32768, x + (size_t)bid * 16 * T_D, 32768, b_x, pol);
      }
      prefetch_tmap(&tmW); prefetch_tmap(&tmM); prefetch_tmap(&tmH); prefetch_tmap(&tmWo); prefetch_tmap(&tmOl);
      {
        const uint32_t c0 = clock_lo();
        while (clock_lo() - c0 < W_DLY) {}
        if (bid < 128 && (bid & 15) >= 4 * H_SPLIT) {
          mbar_expect_tx(bars + 328, 32768);
          tma_load_2d_hint(sbase + 3 * 32768, &tmM, (bid & 31) * 64, (bid >> 5) * 256, bars + 328, pol);
        }
        while (clock_lo() - c0 < W_DLY + W_FIRST) {}
      }
      uint32_t slot = 0, ph = 1;
      { uint32_t sm; asm volatile("mov.u32 %0, %%smid;" : "=r"(sm)); g_smid[32 + bid] = sm; }
      #pragma unroll 1
      for (int it = 0; it < n_items; it++) {
        const int item = item0 + it * 128, hp = item >> 4, qt = item & 15;
        const bool first = it == 0;
        #pragma unroll 1
        for (int j = 0; j < T_D / 64; j++) {
          const uint32_t sl = ring_slot(qp_pos(j, it)), fb = b_full + 8 * sl;
          mbar_wait(b_empty + 8 * sl, ring_par(qp_pos(j, it)) ^ ((j >> 2) & 1) ^ 1);
          if (first && j == 3) mbar_wait(b_head, 0);
          mbar_expect_tx(fb, 49152);
          tma_load_3d_hint(sbase + sl * 32768, &tmW, j * 64, hp * 4, fb, pol);
          if (first && j < PRE_B) {
            if (j == PRE_B - 1) {
              spin_until(&g_hcnt[32 * (1 + qt)], 8u);
              TL_MARK2(16, true);
              fence_proxy_async_global();
              #pragma unroll 1
              for (int i = 0; i < PRE_B; i++) tma_load_2d(sbase + AT_SQ + i * 16384, &tmH, i * 64, qt * 128, b_full + 8 * i);
              mbar_arrive(b_go);
            }
          } else {
            if (first && j == 4 * H_SPLIT) { spin_until(&g_hcnt[32 * (1 + qt) + 1], 8u); fence_proxy_async_global(); }
            if (!first && (j == 0 || j == 2)) mbar_wait(j ? b_q1 : b_q0, 0);
            tma_load_2d_hint(sbase + AT_SQ + (j & 3) * 16384, &tmH, j * 64, qt * 128, fb, first ? pol_normal() : pol);
          }
        }
        #pragma unroll 1
        for (int j = 0; j < 4 * AT_NBLK; j++) {
          const bool isv = (j > 0 && !(j & 1)) || j == 4 * AT_NBLK - 1;
          const int row = hp * 2 * T_SEQ + (isv ? (j - 1) >> 1 : (j + 1) >> 1) * 128;
          const uint32_t fb = b_full + 8 * slot;
          mbar_wait(b_empty + 8 * slot, ph);
          if (!first && j == 3) mbar_wait(b_ob, 0);
          if (j == 4 && it == n_items - 1) mbar_arrive(bars + 288);
          if (j == AL_P && it == 1) mbar_arrive(bars + 312);
          mbar_expect_tx(fb, 32768);
          tma_load_3d_hint(sbase + slot * 32768, isv ? &tmV : &tmK, row, 0, fb, pol);
          if (it == 1 && isv && j >= 2 * WO_LATE && j < 2 * WO_LATE + 32 && bid < OG_NKB)
            l2_prefetch_bulk(pf_wo + (size_t)own_kb(bid) * 131072 + ((j >> 1) - WO_LATE) * 8192, 8192);
          if (++slot == 5) { slot = 0; ph ^= 1; }
        }
      }
      if (__builtin_expect(single, 0)) {
        spin_until(&g_hcnt[2], 128u);
        fence_proxy_async_global();
        const int nj = OG_JOBS * OG_PRE + (help_njobs(bid) - OG_JOBS) * OG_PRE2;
        int ji = 0, job = help_job(bid, 0), kk = 0;
        #pragma unroll 1
        for (int j = 0; j < nj; j++) {
          const uint32_t sl = ring_slot(qp_pos(j, 1)), fb = b_full + 8 * sl;
          mbar_wait(b_empty + 8 * sl, ring_par(qp_pos(j, 1)) ^ ((j >> 2) & 1) ^ 1);
          mbar_expect_tx(fb, 49152);
          tma_load_3d_hint(sbase + sl * 32768, &tmWo, pre_kb(kk) * 64, OG_NT(job) * 2, fb, pol_normal());
          tma_load_3d_hint(sbase + sl * 32768 + 16384, &tmWo, pre_kb(kk) * 64, OG_NT(job) * 2 + 2, fb, pol_normal());
          if (j == 0 || j == 2) mbar_wait(j ? b_ob : b_q0, 0);
          tma_load_2d_hint(sbase + AT_SQ + (j & 3) * 16384, &tmOl, pre_kb(kk) * 64, OG_MT(job) * 128, fb, pol);
          if (++kk == (ji < OG_JOBS ? OG_PRE : OG_PRE2)) { kk = 0; job = help_job(bid, ++ji); }
        }
      }
      if (bid < 128) {
        if (single) mbar_wait(b_x, 1);
        tail_producer(bid, sbase, 0, pol, &tmOl, &tmWo, &tmD);
      }
     }
    }
    named_bar_sync(12 + (threadIdx.x >> 5), 32);
    if (bid < 128) tail_exchange(bid, sbase, w_down, w_r, x, out);
  } else {
    if (bid < 128) head_phase(bid, sbase + AT_SQ + 49152, sbase + 4 * 32768, b_x, b_go, b_head, threadIdx.x - 128, zero, cvec, w_mod);
    else { named_bar_sync(6, 384); if (threadIdx.x == 128) mbar_arrive(b_head); }
    TL_MARK2(0, threadIdx.x == 128);
    reg_alloc<AT_CREG>();
    const int cwg = wg - 1;
    const int tid = threadIdx.x & 127;
    const int warp = tid >> 5, lane = tid & 31;
    const uint32_t dbase = (sbase & 0x3FFFFu) >> 4;
    const uint32_t k_base = dbase + (1u << 16);
    const uint32_t v_base = dbase + (1024u << 16);
    const uint32_t w_base = dbase + (512u << 16);
    const uint32_t q_lo = dbase + ((AT_SQ + cwg * 8192) >> 4) + (1u << 16);
    const uint32_t frag = cwg * 8192 + (16 * warp + (lane & 7) + 8 * ((lane >> 3) & 1)) * 128;
    if (cwg == 1) named_bar_arrive(1, 256);
    bool raw = false;
    uint4 pre[8];
    #pragma unroll 1
    for (int it = 0; it < n_items; it++) {
      const bool more = it + 1 < n_items;
      constexpr int nkb = T_D / 64;
      const int ta = __shfl_sync(0xffffffffu, 4 * it, 0);
      float acc[128];
      {
        FS(2 * it, 0);
        #pragma unroll
        for (int i = 0; i < 128; i++) asm volatile("" : "=f"(acc[i]));
        {
          const uint32_t slot = ring_slot(ta), b_lo = w_base + slot * 2048;
          mbar_wait(b_full + 8 * slot, ring_par(ta));
          wgmma_fence();
          wgmma_m64n256k16_ss_tb<0, 0>(acc, q_lo, b_lo, 0);
          wgmma_m64n256k16_ss_tb<2, 128>(acc, q_lo, b_lo, 1);
          wgmma_m64n256k16_ss_tb<4, 256>(acc, q_lo, b_lo, 1);
          wgmma_m64n256k16_ss_tb<6, 384>(acc, q_lo, b_lo, 1);
          wgmma_commit();
        }
        #pragma unroll 1
        for (int j = 1; j < nkb; j++) {
          const uint32_t slot = ring_slot(qp_pos(j, ta >> 2));
          mbar_wait(b_full + 8 * slot, ring_par(qp_pos(j, ta >> 2)) ^ ((j >> 2) & 1));
          if (QP_STAG > 0 && cwg == 1 && j == nkb - QP_STAG) named_bar_sync(7, 256);
          const uint32_t a_lo = q_lo + (j & 3) * 1024, b_lo = w_base + slot * 2048;
          wgmma_fence();
          wgmma_m64n256k16_ss_tb<0, 0>(acc, a_lo, b_lo, 1);
          wgmma_m64n256k16_ss_tb<2, 128>(acc, a_lo, b_lo, 1);
          wgmma_m64n256k16_ss_tb<4, 256>(acc, a_lo, b_lo, 1);
          wgmma_m64n256k16_ss_tb<6, 384>(acc, a_lo, b_lo, 1);
          wgmma_commit();
          if (QP_STAG > 0 && cwg == 0 && j == nkb - 1) named_bar_arrive(7, 256);
          if (j > 0) {
            wgmma_wait<1>();
            if (tid == 0) mbar_arrive(b_empty + 8 * ring_slot(qp_pos(j - 1, ta >> 2)));
          }
        }
        wgmma_wait<0>();
        fence_regs(acc);
        FS(2 * it, 1);
        TL_MARK2(29, threadIdx.x == 256 && it == 0);
        if (tid == 0) mbar_arrive(b_empty + 24);
      }
      float o[64], s[64];
      uint32_t p[32], q[32];
      #pragma unroll
      for (int i = 0; i < 32; i++) q[i] = pack_bf16(acc[2 * i] * AT_C, acc[2 * i + 1] * AT_C);
      zero_regs(s);
      const uint32_t sq = sbase + AT_SQ + cwg * 8192;
      float mc0, mc1, al0 = 1.0f, al1 = 1.0f, l0 = 0.f, l1 = 0.f, lp0 = 0.f, lp1 = 0.f;
      bool redo0 = false;
      FS(2 * it, 2);
      mbar_wait(b_full + 8 * ring_slot(ta), ring_par(ta));
      named_bar_sync(1 + cwg, 256);
      FS(2 * it, 3);
      issue_qk(s, q, k_base + ring_slot(ta) * 2048);
      pass_turn(cwg);
      bool ready = mbar_test(b_full + 8 * ring_slot(ta + 1), ring_par(ta + 1)) & mbar_test(b_full + 8 * ring_slot(ta + 2), ring_par(ta + 2));
      stage_q<16>(acc, AT_C, sbase + AT_SQ + frag, lane);
      wgmma_wait<0>();
      fence_regs(s);
      if (tid == 0) mbar_arrive(b_empty + 8 * ring_slot(ta));
      mc0 = 0.f; mc1 = 0.f;
      if (!raw) {
        raw = softmax_mode(s, mc0, mc1);
        if (__builtin_expect(!raw, 0)) softmax_sub(s, mc0, mc1);
      }
      softmax_exp<0, 64>(s);
      #pragma unroll
      for (int J = 0; J < 16; J += 2)
        stmatrix_x4(sbase + AT_SQ + frag + (J >> 3) * 16384 + ((((J & 7) + (lane >> 4)) ^ (lane & 7)) << 4), q[2 * J], q[2 * J + 1], q[2 * J + 2], q[2 * J + 3]);
      pack_p(p, s);
      zero_regs(o);
      FS(2 * it, 4);
      uint32_t ks = ring_slot(ta + 1), vs = ring_slot(ta + 2), kp = ring_par(ta + 1), vp = ring_par(ta + 2);
      auto finish_head = [&]() {
        FS(2 * it, 5);
        redo0 = finish_l(lp0, lp1);
        if (!redo0) stage_o(o, lp0, lp1, sbase + AT_SQ + frag, lane);
        FS(2 * it + 1, 4);
      };
      if (!ready) { mbar_wait(b_full + 8 * ks, kp); mbar_wait(b_full + 8 * vs, vp); }
      #pragma unroll 1
      for (int n = 1; n < 2 * AT_NBLK; n++) {
        named_bar_sync(1 + cwg, 256);
        issue_qk(s, q, k_base + ks * 2048);
        if (n == AT_NBLK + 1) finish_head();
        issue_pv(o, p, v_base + vs * 2048, (n & 15) != 1);
        pass_turn(cwg);
        wgmma_wait<1>();
        fence_regs(s);
        if (tid == 0) mbar_arrive(b_empty + 8 * ks);
        if (__builtin_expect(!raw || (uint32_t)(n - (AT_NBLK - 1)) <= 2u, 0)) {
          if (n == AT_NBLK + 1 && !redo0) {
            fence_proxy_async();
            __syncwarp();
            if (lane == 0) mbar_arrive(b_ordy + 8 * cwg);
          }
          if (n == AT_NBLK - 1) {
            #pragma unroll
            for (int J = 0; J < 16; J += 2)
              ldmatrix_x4(sbase + AT_SQ + 32768 + frag + (J >> 3) * 16384 + ((((J & 7) + (lane >> 4)) ^ (lane & 7)) << 4), q[2 * J], q[2 * J + 1], q[2 * J + 2], q[2 * J + 3]);
          }
          if (!raw) {
            const float m0 = mc0, m1 = mc1;
            const bool ok = softmax_mode(s, mc0, mc1);
            if (n == AT_NBLK) raw = ok;
            else {
              mc0 = mc0 - AT_HEAD > m0 ? mc0 : m0; mc1 = mc1 - AT_HEAD > m1 ? mc1 : m1;
              al0 = ex2_approx(m0 - mc0); al1 = ex2_approx(m1 - mc1);
            }
            if (!raw) softmax_sub(s, mc0, mc1);
          }
        }
        softmax_exp<0, AT_SPLIT>(s);
        add_rowsum(p, l0, l1);
        if (tid == 0) {
          uint32_t dep = zero & __float_as_uint(l0) & __float_as_uint(l1);
          #pragma unroll
          for (int i = AT_SPLIT - AT_PIN - PINB; i < AT_SPLIT - PINB; i += 2) dep &= __float_as_uint(s[i]) & __float_as_uint(s[i + 1]);
          mbar_arrive(b_pin + dep);
        }
        wgmma_wait<0>();
        fence_regs(o);
        if (tid == 0) mbar_arrive(b_empty + 8 * vs);
        ks += 2; if (ks >= 5) { ks -= 5; kp ^= 1; }
        vs += 2; if (vs >= 5) { vs -= 5; vp ^= 1; }
        ready = mbar_test(b_full + 8 * ks, kp) & mbar_test(b_full + 8 * vs, vp);
        softmax_exp<AT_SPLIT, 64>(s);
        pack_p(p, s);
        if (n == AT_NBLK) { lp0 = l0; lp1 = l1; l0 = 0.f; l1 = 0.f; }
        if (__builtin_expect(!raw || !ready, 0)) {
        if (!raw && __any_sync(0xffffffffu, al0 != 1.0f || al1 != 1.0f)) {
          rescale_o(o, al0, al1);
          l0 *= al0; l1 *= al1;
          al0 = 1.0f; al1 = 1.0f;
        }
        if (!ready && n < 2 * AT_NBLK - 1) {
          mbar_wait(b_full + 8 * ks, kp);
          mbar_wait(b_full + 8 * vs, vp);
        }
        }
      }
      FS(2 * it + 1, 5);
      const uint32_t vl = ring_slot(ta + 63);
      vs = ring_slot(ta + 62);
      const uint32_t ob = more ? sbase + vs * 32768 : sbase + AT_SQ + 32768;
      mbar_wait(b_full + 8 * vl, ring_par(ta + 63));
      issue_pv(o, p, v_base + vl * 2048, 1);
      block_end(zero, b_pin);
      add_rowsum(p, l0, l1);
      const bool overflow = finish_l(l0, l1);
      if (!overflow && lane == 0) mbar_arrive(b_q1);
      #pragma unroll
      for (int i = 0; i < 8; i++) asm volatile("mov.b64 {%0, %1}, 0;\nmov.b64 {%2, %3}, 0;" : "=r"(pre[i].x), "=r"(pre[i].y), "=r"(pre[i].z), "=r"(pre[i].w));
      const bool want_pre = !more && bid < OG_MOE, got_pre = want_pre && __all_sync(0xffffffffu, mbar_test(bars + 272, 0));
      if (got_pre) load_pre(pre, sbase, AT_SQ, threadIdx.x - 128);
      mbar_wait(b_empty + 8 * vs, ring_par(ta + 62));
      wgmma_wait<0>();
      fence_regs(o);
      if (tid == 0) mbar_arrive(b_empty + 8 * vl);
      FS(2 * it + 1, 6);
      if (overflow) {
        attn_rows_exact(lds_u32(bars + 400), sq + 32768, ob + cwg * 8192, 4 * ta + 1, kc, vc);
        __syncwarp();
        if (lane == 0) mbar_arrive(b_q1);
      } else stage_o(o, l0, l1, ob + frag, lane);
      if (redo0) attn_rows_exact(lds_u32(bars + 400), sq, sq, 4 * ta, kc, vc);
      fence_proxy_async();
      __syncwarp();
      if (lane == 0) {
        if (redo0) mbar_arrive(b_ordy + 8 * cwg);
        mbar_arrive(b_ordy + 16 + 8 * cwg);
      }
      if (want_pre && !got_pre) load_pre(pre, sbase, AT_SQ, threadIdx.x - 128);
      if (redo0 || overflow) raw = false;
      named_bar_sync(3 + cwg, 128);
      FS(2 * it + 1, 7);
    }
    if (cwg == 0) named_bar_arrive(1, 256);
    if (__builtin_expect(single, 0)) {
      float acc[128];
      uint32_t j = 0, pk[64];
      #pragma unroll
      for (int i = 0; i < 64; i++) asm volatile("" : "=f"(acc[2 * i]), "=f"(acc[2 * i + 1]), "=r"(pk[i]));
      uint4* dst = g_pre;
      int left = 0;
      auto put = [&](bool last) {
        #pragma unroll
        for (int i = 0; i < PUT_N; i++) dst[i * 256] = make_uint4(pk[4 * i], pk[4 * i + 1], pk[4 * i + 2], pk[4 * i + 3]);
        dst += PUT_N * 256;
        #pragma unroll
        for (int i = 0; i < 64 - 4 * PUT_N; i++) asm volatile("mov.b32 %0, %1;" : "=r"(pk[i]) : "r"(pk[i + 4 * PUT_N]));
        __syncwarp();
        if (last && lane == 0) mbar_arrive(bars + 280);
      };
      #pragma unroll 1
      for (int ji = 0; ji < help_njobs(bid); ji++) {
        const int nk = ji < OG_JOBS ? OG_PRE : OG_PRE2;
        #pragma unroll 1
        for (int kk = 0; kk < nk; kk++, j++) {
          const uint32_t slot = ring_slot(qp_pos(j, 1));
          mbar_wait(b_full + 8 * slot, ring_par(qp_pos(j, 1)) ^ ((j >> 2) & 1));
          if (H_STAG > 0 && cwg == 1 && kk == nk - H_STAG) named_bar_sync(7, 256);
          const uint32_t a_lo = q_lo + (j & 3) * 1024, b_lo = w_base + slot * 2048;
          wgmma_fence();
          wgmma_m64n256k16_ss_tb<0, 0>(acc, a_lo, b_lo, kk != 0);
          wgmma_m64n256k16_ss_tb<2, 128>(acc, a_lo, b_lo, 1);
          wgmma_m64n256k16_ss_tb<4, 256>(acc, a_lo, b_lo, 1);
          wgmma_m64n256k16_ss_tb<6, 384>(acc, a_lo, b_lo, 1);
          wgmma_commit();
          if (H_STAG > 0 && cwg == 0 && kk == nk - 1) named_bar_arrive(7, 256);
          wgmma_wait<1>();
          if (kk > 0 && tid == 0) mbar_arrive(b_empty + 8 * ring_slot(qp_pos(j - 1, 1)));
          #pragma unroll 1
          for (int i = ji == OG_JOBS ? 0 : 16 / PUT_N - 1; i < 16 / PUT_N && left > 0; i++) put(--left == 0);
        }
        wgmma_wait<0>();
        fence_regs(acc);
        if (tid == 0) mbar_arrive(b_empty + 8 * ring_slot(qp_pos(j - 1, 1)));
        #pragma unroll
        for (int i = 0; i < 64; i++) pk[i] = pack_bf16(acc[2 * i], acc[2 * i + 1]);
        left = 16 / PUT_N;
        if (ji == PRE_X) mbar_wait(bars + 296, 0);
        dst = g_pre + help_job(bid, ji) * 2048 + threadIdx.x - 128;
      }
      #pragma unroll
      for (int i = 0; i < 16; i++) dst[i * 256] = make_uint4(pk[4 * i], pk[4 * i + 1], pk[4 * i + 2], pk[4 * i + 3]);
      __syncwarp();
      if (lane == 0) mbar_arrive(bars + 280);
      named_bar_sync(5, 256);
      if (threadIdx.x == 128) {
        #pragma unroll 1
        for (int i = 0; i < 5; i++) {
          constexpr int n = OG_JOBS * OG_PRE;
          const int used = i == 3 ? 0 : (n + 3 - (i == 4 ? 3 : i)) / 4;
          if ((used ^ (i < 4)) & 1) {
            mbar_arrive(b_full + 8 * ring_slot(4 + i));
            mbar_arrive(b_empty + 8 * ring_slot(4 + i)); mbar_arrive(b_empty + 8 * ring_slot(4 + i));
          }
        }
        mbar_arrive(b_x);
      }
      named_bar_sync(5, 256);
      #pragma unroll
      for (int i = 0; i < 8; i++) pre[i] = make_uint4(0u, 0u, 0u, 0u);
    }
    TL_CLK(3, 1, threadIdx.x == 128);
    TL_CTA(1, threadIdx.x == 256);
    TL_END(3, tid == 0);
    TL_MARK2(19, tid == 0 && !single);
    if (bid < 128) {
      tail_consumer(bid, sbase, &tmOut, pre, cwg, w_gate, w_up);
    }
  }
}

typedef CUresult (*PFN_encodeTiled)(CUtensorMap*, CUtensorMapDataType, cuuint32_t, void*, const cuuint64_t*, const cuuint64_t*,
                                    const cuuint32_t*, const cuuint32_t*, CUtensorMapInterleave, CUtensorMapSwizzle,
                                    CUtensorMapL2promotion, CUtensorMapFloatOOBfill);

CUtensorMap make_map_2d(PFN_encodeTiled enc, const void* ptr, uint64_t inner, uint64_t outer, uint64_t stride_bytes, uint32_t box_inner, uint32_t box_outer) {
  CUtensorMap m;
  cuuint64_t gd[2] = {inner, outer}; cuuint64_t gs[1] = {stride_bytes};
  cuuint32_t bx[2] = {box_inner, box_outer}; cuuint32_t es[2] = {1, 1};
  enc(&m, CU_TENSOR_MAP_DATA_TYPE_BFLOAT16, 2, const_cast<void*>(ptr), gd, gs, bx, es, CU_TENSOR_MAP_INTERLEAVE_NONE,
      CU_TENSOR_MAP_SWIZZLE_128B, CU_TENSOR_MAP_L2_PROMOTION_L2_128B, CU_TENSOR_MAP_FLOAT_OOB_FILL_NONE);
  return m;
}

CUtensorMap make_map_3d(PFN_encodeTiled enc, const void* ptr, uint64_t cols, uint64_t rows, uint32_t box_rows, uint32_t chunks) {
  CUtensorMap m;
  cuuint64_t gd[3] = {64, rows, cols / 64}; cuuint64_t gs[2] = {cols * 2, 128};
  cuuint32_t bx[3] = {64, box_rows, chunks}; cuuint32_t es[3] = {1, 1, 1};
  enc(&m, CU_TENSOR_MAP_DATA_TYPE_BFLOAT16, 3, const_cast<void*>(ptr), gd, gs, bx, es, CU_TENSOR_MAP_INTERLEAVE_NONE,
      CU_TENSOR_MAP_SWIZZLE_128B, CU_TENSOR_MAP_L2_PROMOTION_L2_128B, CU_TENSOR_MAP_FLOAT_OOB_FILL_NONE);
  return m;
}

}

extern "C" void kernel_launch(void* const* d_in, const int* in_sizes, int n_in, void* d_out, int out_size) {
  const bf16* x      = (const bf16*)d_in[0];
  const bf16* kc     = (const bf16*)d_in[1];
  const bf16* vc     = (const bf16*)d_in[2];
  const bf16* wq     = (const bf16*)d_in[3];
  const bf16* wo     = (const bf16*)d_in[4];
  const bf16* w_r    = (const bf16*)d_in[6];
  const bf16* w_gate = (const bf16*)d_in[7];
  const bf16* w_up   = (const bf16*)d_in[8];
  const bf16* w_down = (const bf16*)d_in[9];
  const bf16* cvec   = (const bf16*)d_in[10];
  const bf16* w_mod  = (const bf16*)d_in[11];
  bf16* out = (bf16*)d_out;

  static PFN_encodeTiled enc = nullptr;
  static void *p_h = nullptr, *p_o = nullptr;
  if (!enc) {
    void* fn = nullptr; cudaDriverEntryPointQueryResult qres;
    cudaGetDriverEntryPoint("cuTensorMapEncodeTiled", &fn, cudaEnableDefault, &qres);
    enc = (PFN_encodeTiled)fn;
    cudaGetSymbolAddress(&p_h, g_pre);
    p_h = (uint4*)p_h + 16 * PRE_X * 2048;
    cudaGetSymbolAddress(&p_o, g_o);
    cudaFuncSetAttribute(fused_kernel, cudaFuncAttributeMaxDynamicSharedMemorySize, (int)AT_SMEM);
  }
  const CUtensorMap tm_h   = make_map_2d(enc, p_h, T_D, T_SEQ, T_D * 2, 64, 128);
  const CUtensorMap tm_wq  = make_map_3d(enc, wq, T_DQKV, T_D, 64, 4);
  const CUtensorMap tm_k   = make_map_3d(enc, kc, T_DH, (uint64_t)T_NH * T_SEQ, 128, 2);
  const CUtensorMap tm_v   = make_map_3d(enc, vc, T_DH, (uint64_t)T_NH * T_SEQ, 128, 2);
  const CUtensorMap tm_ost = make_map_2d(enc, p_o, T_DQKV, T_SEQ, T_DQKV * 2, 64, 64);
  const CUtensorMap tm_old = make_map_2d(enc, p_o, T_DQKV, T_SEQ, T_DQKV * 2, 64, 128);
  const CUtensorMap tm_wo  = make_map_3d(enc, wo, T_D, T_DQKV, 64, 2);
  const CUtensorMap tm_d   = make_map_3d(enc, w_down, T_D, T_F, 32, 8);

  const CUtensorMap tm_m   = make_map_2d(enc, w_mod, 6 * T_D, T_D, 6 * T_D * 2, 64, 256);
  const CUtensorMap tm_out = make_map_2d(enc, out, T_D, T_SEQ, T_D * 2, 64, 16);

  Roles roles;
  for (int sm = 0; sm < 132; sm++) {
    const int t = sm >> 1;
    roles.of_sm[sm] = (uint8_t)((t < 32 ? (t & 7) * 16 + (t >> 3) * 2 : t < 60 ? (1 + (t - 32) % 7) * 16 + (4 + (t - 32) / 7) * 2 : t < 62 ? 128 + (t - 60) * 2 : (t - 58) * 2) + (sm & 1));
  }
  fused_kernel<<<132, 384, AT_SMEM, cudaStreamPerThread>>>(tm_h, tm_wq, tm_k, tm_v, tm_ost, tm_old, tm_wo, tm_d, tm_out, tm_m, roles, 0u, (const uint8_t*)wo, kc, vc, x, cvec, w_mod,
             w_r, w_gate, w_up, w_down, out);
}
```

```cpp
#include <cuda_runtime.h>
#include <cuda_bf16.h>
#include <cuda.h>
#include <stdint.h>

namespace {

typedef __nv_bfloat16 bf16;

constexpr int T_SEQ = 2048, T_D = 1024, T_NH = 32, T_DH = 128, T_DQKV = 4096, T_F = 3584;

#define PRE_X 2
__device__ __align__(1024) uint4 g_pre[(16 * PRE_X + 128) * 2048];
#define g_h (reinterpret_cast<bf16*>(g_pre + 16 * PRE_X * 2048))
__device__ __align__(1024) bf16 g_o[T_SEQ * T_DQKV];
__device__ __align__(16) uint8_t g_col[8 * 1536];
__device__ __align__(16) float g_scal[64];
__device__ __align__(16) unsigned int g_hcnt[17 * 32];
__device__ __align__(128) float g_modpart[4 * 2 * T_D];
struct __align__(2048) TailMail {
  float4 part1[T_SEQ * 8];
  uint32_t key[256];
  uint4 cand[16 * 2 * 2 * 128];
  uint32_t cnt[32];
  float ypart[(T_F / 32) * 2 * T_D];
};
__device__ TailMail g_mail;
#define g_part1 g_mail.part1
#define g_key g_mail.key
#define g_cand g_mail.cand
#define CNT_Y (g_mail.cnt)
#define g_ypart g_mail.ypart

__device__ __forceinline__ uint32_t smem_u32(const void* p) { return (uint32_t)__cvta_generic_to_shared(p); }
__device__ __forceinline__ void mbar_init(uint32_t bar, uint32_t cnt) { asm volatile("mbarrier.init.shared::cta.b64 [%0], %1;" :: "r"(bar), "r"(cnt)); }
__device__ __forceinline__ void mbar_expect_tx(uint32_t bar, uint32_t bytes) { asm volatile("mbarrier.arrive.expect_tx.shared::cta.b64 _, [%0], %1;" :: "r"(bar), "r"(bytes) : "memory"); }
__device__ __forceinline__ void mbar_arrive(uint32_t bar) { asm volatile("mbarrier.arrive.shared::cta.b64 _, [%0];" :: "r"(bar) : "memory"); }
__device__ __forceinline__ void mbar_wait(uint32_t bar, uint32_t parity) {
  asm volatile("{\n.reg .pred p;\nLAB_WAIT:\nmbarrier.try_wait.parity.shared::cta.b64 p, [%0], %1;\n@!p bra LAB_WAIT;\n}\n" :: "r"(bar), "r"(parity) : "memory");
}
__device__ __forceinline__ bool mbar_test(uint32_t bar, uint32_t parity) {
  uint32_t r; asm volatile("{\n.reg .pred p;\nmbarrier.test_wait.parity.shared::cta.b64 p, [%1], %2;\nselp.u32 %0, 1, 0, p;\n}\n" : "=r"(r) : "r"(bar), "r"(parity) : "memory");
  return r != 0;
}
__device__ __forceinline__ uint32_t clock_lo() { uint32_t c; asm volatile("mov.u32 %0, %%clock;" : "=r"(c)); return c; }
__device__ __forceinline__ void fence_mbar_init() { asm volatile("fence.mbarrier_init.release.cluster;" ::: "memory"); }
__device__ __forceinline__ void tma_load_2d(uint32_t dst, const CUtensorMap* map, int c0, int c1, uint32_t bar) {
  asm volatile("cp.async.bulk.tensor.2d.shared::cluster.global.mbarrier::complete_tx::bytes [%0], [%1, {%3, %4}], [%2];"
    :: "r"(dst), "l"(map), "r"(bar), "r"(c0), "r"(c1) : "memory");
}
__device__ __forceinline__ uint64_t policy_evict_first() {
  uint64_t p; asm volatile("createpolicy.fractional.L2::evict_first.b64 %0, 1.0;" : "=l"(p)); return p;
}
__device__ __forceinline__ void tma_load_2d_hint(uint32_t dst, const CUtensorMap* map, int c0, int c1, uint32_t bar, uint64_t pol) {
  asm volatile("cp.async.bulk.tensor.2d.shared::cluster.global.mbarrier::complete_tx::bytes.L2::cache_hint [%0], [%1, {%3, %4}], [%2], %5;"
    :: "r"(dst), "l"(map), "r"(bar), "r"(c0), "r"(c1), "l"(pol) : "memory");
}
__device__ __forceinline__ void tma_load_3d_hint(uint32_t dst, const CUtensorMap* map, int c1, int c2, uint32_t bar, uint64_t pol) {
  asm volatile("cp.async.bulk.tensor.3d.shared::cluster.global.mbarrier::complete_tx::bytes.L2::cache_hint [%0], [%1, {%3, %4, %5}], [%2], %6;"
    :: "r"(dst), "l"(map), "r"(bar), "n"(0), "r"(c1), "r"(c2), "l"(pol) : "memory");
}
__device__ __forceinline__ void tma_store_2d(const CUtensorMap* map, uint32_t src, int c0, int c1) {
  asm volatile("cp.async.bulk.tensor.2d.global.shared::cta.bulk_group [%0, {%2, %3}], [%1];" :: "l"(map), "r"(src), "r"(c0), "r"(c1) : "memory");
}
__device__ __forceinline__ void prefetch_tmap(const CUtensorMap* map) { asm volatile("prefetch.tensormap [%0];" :: "l"(map) : "memory"); }
__device__ __forceinline__ void l2_prefetch_bulk(const void* p, uint32_t bytes) {
  asm volatile("cp.async.bulk.prefetch.L2.global [%0], %1;" :: "l"(p), "r"(bytes) : "memory");
}
__device__ __forceinline__ void bulk_commit() { asm volatile("cp.async.bulk.commit_group;" ::: "memory"); }
template<int N> __device__ __forceinline__ void bulk_wait_read() { asm volatile("cp.async.bulk.wait_group.read %0;" :: "n"(N) : "memory"); }
template<int N> __device__ __forceinline__ void bulk_wait() { asm volatile("cp.async.bulk.wait_group %0;" :: "n"(N) : "memory"); }
__device__ __forceinline__ void named_bar_sync(int id, int nthreads) { asm volatile("bar.sync %0, %1;" :: "r"(id), "r"(nthreads) : "memory"); }
__device__ __forceinline__ void named_bar_arrive(int id, int nthreads) { asm volatile("bar.arrive %0, %1;" :: "r"(id), "r"(nthreads) : "memory"); }
__device__ __forceinline__ void pass_turn(int cwg) {
  asm volatile("{\n.reg .pred p;\nsetp.ne.u32 p, %0, 0;\n@p bar.arrive 1, 256;\n@!p bar.arrive 2, 256;\n}\n" :: "r"(cwg) : "memory");
}
__device__ __forceinline__ void wgmma_fence() { asm volatile("wgmma.fence.sync.aligned;" ::: "memory"); }
__device__ __forceinline__ void wgmma_commit() { asm volatile("wgmma.commit_group.sync.aligned;" ::: "memory"); }
template<int N> __device__ __forceinline__ void wgmma_wait() { asm volatile("wgmma.wait_group.sync.aligned %0;" :: "n"(N) : "memory"); }
template<int R> __device__ __forceinline__ void reg_alloc() { asm volatile("setmaxnreg.inc.sync.aligned.u32 %0;" :: "n"(R)); }
template<int R> __device__ __forceinline__ void reg_dealloc() { asm volatile("setmaxnreg.dec.sync.aligned.u32 %0;" :: "n"(R)); }
__device__ __forceinline__ bool elect_one() {
  uint32_t pred; asm volatile("{\n.reg .pred p;\nelect.sync _|p, 0xffffffff;\nselp.u32 %0, 1, 0, p;\n}\n" : "=r"(pred)); return pred != 0;
}
__device__ __forceinline__ uint32_t pack_bf16(float lo, float hi) {
  uint32_t r; asm("cvt.rn.bf16x2.f32 %0, %1, %2;" : "=r"(r) : "f"(hi), "f"(lo)); return r;
}
__device__ __forceinline__ void stmatrix_x4(uint32_t addr, uint32_t r0, uint32_t r1, uint32_t r2, uint32_t r3) {
  asm volatile("stmatrix.sync.aligned.m8n8.x4.shared.b16 [%0], {%1, %2, %3, %4};" :: "r"(addr), "r"(r0), "r"(r1), "r"(r2), "r"(r3) : "memory");
}
__device__ __forceinline__ void fence_proxy_async() { asm volatile("fence.proxy.async.shared::cta;" ::: "memory"); }
__device__ __forceinline__ float ex2_approx(float x) { float y; asm("ex2.approx.ftz.f32 %0, %1;" : "=f"(y) : "f"(x)); return y; }
template<int N> __device__ __forceinline__ void fence_regs(float (&r)[N]) {
  #pragma unroll
  for (int i = 0; i < N; i++) asm volatile("" : "+f"(r[i]) :: "memory");
}
template<int N> __device__ __forceinline__ void zero_regs(float (&r)[N]) {
  #pragma unroll
  for (int i = 0; i < N; i += 2) asm volatile("mov.b64 {%0, %1}, 0;" : "=f"(r[i]), "=f"(r[i + 1]));
}
__device__ __forceinline__ float rbf(float x) { return __uint_as_float(pack_bf16(0.f, x)); }
__device__ __forceinline__ float bflo(uint32_t v) { return __uint_as_float(v << 16); }
__device__ __forceinline__ float bfhi(uint32_t v) { return __uint_as_float(v & 0xffff0000u); }

#define XT(i) do {} while (0)
#define TL_START(k) do {} while (0)
#define TL_END(k, cond) do {} while (0)
#define TL_CTA(i, cond) do {} while (0)
#define FS(slot, k) do {} while (0)
#define TL_MARK2(k, cond) do {} while (0)
#define TL_CLK(k, i, cond) do {} while (0)

template <int OFFA, int OFFB>
__device__ __forceinline__ void wgmma_m64n256k16_ss_tb(float (&d)[128], uint32_t a_lo, uint32_t b_lo, int scaleD) {
  asm volatile("{\n.reg .pred p;\n.reg .b32 ta, tb;\n.reg .b64 da, db;\nsetp.ne.b32 p, %130, 0;\n"
    "add.u32 ta, %128, %131;\nadd.u32 tb, %129, %132;\n"
    "mov.b64 da, {ta, 0x40000040};\nmov.b64 db, {tb, 0x40000040};\n"
    "wgmma.mma_async.sync.aligned.m64n256k16.f32.bf16.bf16 "
    "{%0, %1, %2, %3, %4, %5, %6, %7, %8, %9, %10, %11, %12, %13, %14, %15, %16, %17, %18, %19, %20, %21, %22, %23, %24, %25, %26, %27, %28, %29, %30, %31, %32, %33, %34, %35, %36, %37, %38, %39, %40, %41, %42, %43, %44, %45, %46, %47, %48, %49, %50, %51, %52, %53, %54, %55, %56, %57, %58, %59, %60, %61, %62, %63, %64, %65, %66, %67, %68, %69, %70, %71, %72, %73, %74, %75, %76, %77, %78, %79, %80, %81, %82, %83, %84, %85, %86, %87, %88, %89, %90, %91, %92, %93, %94, %95, %96, %97, %98, %99, %100, %101, %102, %103, %104, %105, %106, %107, %108, %109, %110, %111, %112, %113, %114, %115, %116, %117, %118, %119, %120, %121, %122, %123, %124, %125, %126, %127}, "
    "da, db, p, 1, 1, 0, 1;\n}\n"
    : "+f"(d[0]), "+f"(d[1]), "+f"(d[2]), "+f"(d[3]), "+f"(d[4]), "+f"(d[5]), "+f"(d[6]), "+f"(d[7]), "+f"(d[8]), "+f"(d[9]), "+f"(d[10]), "+f"(d[11]), "+f"(d[12]), "+f"(d[13]), "+f"(d[14]), "+f"(d[15]), "+f"(d[16]), "+f"(d[17]), "+f"(d[18]), "+f"(d[19]), "+f"(d[20]), "+f"(d[21]), "+f"(d[22]), "+f"(d[23]), "+f"(d[24]), "+f"(d[25]), "+f"(d[26]), "+f"(d[27]), "+f"(d[28]), "+f"(d[29]), "+f"(d[30]), "+f"(d[31]), "+f"(d[32]), "+f"(d[33]), "+f"(d[34]), "+f"(d[35]), "+f"(d[36]), "+f"(d[37]), "+f"(d[38]), "+f"(d[39]), "+f"(d[40]), "+f"(d[41]), "+f"(d[42]), "+f"(d[43]), "+f"(d[44]), "+f"(d[45]), "+f"(d[46]), "+f"(d[47]), "+f"(d[48]), "+f"(d[49]), "+f"(d[50]), "+f"(d[51]), "+f"(d[52]), "+f"(d[53]), "+f"(d[54]), "+f"(d[55]), "+f"(d[56]), "+f"(d[57]), "+f"(d[58]), "+f"(d[59]), "+f"(d[60]), "+f"(d[61]), "+f"(d[62]), "+f"(d[63]), "+f"(d[64]), "+f"(d[65]), "+f"(d[66]), "+f"(d[67]), "+f"(d[68]), "+f"(d[69]), "+f"(d[70]), "+f"(d[71]), "+f"(d[72]), "+f"(d[73]), "+f"(d[74]), "+f"(d[75]), "+f"(d[76]), "+f"(d[77]), "+f"(d[78]), "+f"(d[79]), "+f"(d[80]), "+f"(d[81]), "+f"(d[82]), "+f"(d[83]), "+f"(d[84]), "+f"(d[85]), "+f"(d[86]), "+f"(d[87]), "+f"(d[88]), "+f"(d[89]), "+f"(d[90]), "+f"(d[91]), "+f"(d[92]), "+f"(d[93]), "+f"(d[94]), "+f"(d[95]), "+f"(d[96]), "+f"(d[97]), "+f"(d[98]), "+f"(d[99]), "+f"(d[100]), "+f"(d[101]), "+f"(d[102]), "+f"(d[103]), "+f"(d[104]), "+f"(d[105]), "+f"(d[106]), "+f"(d[107]), "+f"(d[108]), "+f"(d[109]), "+f"(d[110]), "+f"(d[111]), "+f"(d[112]), "+f"(d[113]), "+f"(d[114]), "+f"(d[115]), "+f"(d[116]), "+f"(d[117]), "+f"(d[118]), "+f"(d[119]), "+f"(d[120]), "+f"(d[121]), "+f"(d[122]), "+f"(d[123]), "+f"(d[124]), "+f"(d[125]), "+f"(d[126]), "+f"(d[127])
    : "r"(a_lo), "r"(b_lo), "r"(scaleD), "n"(OFFA), "n"(OFFB));
}

template <int OFFA, int OFFB>
__device__ __forceinline__ void wgmma_m64n128k16_ss_tb(float (&d)[64], uint32_t a_lo, uint32_t b_lo, int scaleD) {
  asm volatile("{\n.reg .pred p;\n.reg .b32 ta, tb;\n.reg .b64 da, db;\nsetp.ne.b32 p, %66, 0;\n"
    "add.u32 ta, %64, %67;\nadd.u32 tb, %65, %68;\n"
    "mov.b64 da, {ta, 0x40000040};\nmov.b64 db, {tb, 0x40000040};\n"
    "wgmma.mma_async.sync.aligned.m64n128k16.f32.bf16.bf16 "
    "{%0, %1, %2, %3, %4, %5, %6, %7, %8, %9, %10, %11, %12, %13, %14, %15, %16, %17, %18, %19, %20, %21, %22, %23, %24, %25, %26, %27, %28, %29, %30, %31, %32, %33, %34, %35, %36, %37, %38, %39, %40, %41, %42, %43, %44, %45, %46, %47, %48, %49, %50, %51, %52, %53, %54, %55, %56, %57, %58, %59, %60, %61, %62, %63}, "
    "da, db, p, 1, 1, 0, 1;\n}\n"
    : "+f"(d[0]), "+f"(d[1]), "+f"(d[2]), "+f"(d[3]), "+f"(d[4]), "+f"(d[5]), "+f"(d[6]), "+f"(d[7]), "+f"(d[8]), "+f"(d[9]), "+f"(d[10]), "+f"(d[11]), "+f"(d[12]), "+f"(d[13]), "+f"(d[14]), "+f"(d[15]), "+f"(d[16]), "+f"(d[17]), "+f"(d[18]), "+f"(d[19]), "+f"(d[20]), "+f"(d[21]), "+f"(d[22]), "+f"(d[23]), "+f"(d[24]), "+f"(d[25]), "+f"(d[26]), "+f"(d[27]), "+f"(d[28]), "+f"(d[29]), "+f"(d[30]), "+f"(d[31]), "+f"(d[32]), "+f"(d[33]), "+f"(d[34]), "+f"(d[35]), "+f"(d[36]), "+f"(d[37]), "+f"(d[38]), "+f"(d[39]), "+f"(d[40]), "+f"(d[41]), "+f"(d[42]), "+f"(d[43]), "+f"(d[44]), "+f"(d[45]), "+f"(d[46]), "+f"(d[47]), "+f"(d[48]), "+f"(d[49]), "+f"(d[50]), "+f"(d[51]), "+f"(d[52]), "+f"(d[53]), "+f"(d[54]), "+f"(d[55]), "+f"(d[56]), "+f"(d[57]), "+f"(d[58]), "+f"(d[59]), "+f"(d[60]), "+f"(d[61]), "+f"(d[62]), "+f"(d[63])
    : "r"(a_lo), "r"(b_lo), "r"(scaleD), "n"(OFFA), "n"(OFFB));
}

template <int OFFB>
__device__ __forceinline__ void wgmma_m64n128k16_rs_tb(float (&d)[64], uint32_t a0, uint32_t a1, uint32_t a2, uint32_t a3, uint32_t b_lo, int scaleD) {
  asm volatile("{\n.reg .pred p;\n.reg .b32 tb;\n.reg .b64 db;\nsetp.ne.b32 p, %69, 0;\n"
    "add.u32 tb, %68, %70;\n"
    "mov.b64 db, {tb, 0x40000040};\n"
    "wgmma.mma_async.sync.aligned.m64n128k16.f32.bf16.bf16 "
    "{%0, %1, %2, %3, %4, %5, %6, %7, %8, %9, %10, %11, %12, %13, %14, %15, %16, %17, %18, %19, %20, %21, %22, %23, %24, %25, %26, %27, %28, %29, %30, %31, %32, %33, %34, %35, %36, %37, %38, %39, %40, %41, %42, %43, %44, %45, %46, %47, %48, %49, %50, %51, %52, %53, %54, %55, %56, %57, %58, %59, %60, %61, %62, %63}, "
    "{%64, %65, %66, %67}, db, p, 1, 1, 1;\n}\n"
    : "+f"(d[0]), "+f"(d[1]), "+f"(d[2]), "+f"(d[3]), "+f"(d[4]), "+f"(d[5]), "+f"(d[6]), "+f"(d[7]), "+f"(d[8]), "+f"(d[9]), "+f"(d[10]), "+f"(d[11]), "+f"(d[12]), "+f"(d[13]), "+f"(d[14]), "+f"(d[15]), "+f"(d[16]), "+f"(d[17]), "+f"(d[18]), "+f"(d[19]), "+f"(d[20]), "+f"(d[21]), "+f"(d[22]), "+f"(d[23]), "+f"(d[24]), "+f"(d[25]), "+f"(d[26]), "+f"(d[27]), "+f"(d[28]), "+f"(d[29]), "+f"(d[30]), "+f"(d[31]), "+f"(d[32]), "+f"(d[33]), "+f"(d[34]), "+f"(d[35]), "+f"(d[36]), "+f"(d[37]), "+f"(d[38]), "+f"(d[39]), "+f"(d[40]), "+f"(d[41]), "+f"(d[42]), "+f"(d[43]), "+f"(d[44]), "+f"(d[45]), "+f"(d[46]), "+f"(d[47]), "+f"(d[48]), "+f"(d[49]), "+f"(d[50]), "+f"(d[51]), "+f"(d[52]), "+f"(d[53]), "+f"(d[54]), "+f"(d[55]), "+f"(d[56]), "+f"(d[57]), "+f"(d[58]), "+f"(d[59]), "+f"(d[60]), "+f"(d[61]), "+f"(d[62]), "+f"(d[63])
    : "r"(a0), "r"(a1), "r"(a2), "r"(a3), "r"(b_lo), "r"(scaleD), "n"(OFFB));
}

template <int OFFB>
__device__ __forceinline__ void wgmma_m64n128k16_rs(float (&d)[64], uint32_t a0, uint32_t a1, uint32_t a2, uint32_t a3, uint32_t b_lo, int scaleD) {
  asm volatile("{\n.reg .pred p;\n.reg .b32 tb;\n.reg .b64 db;\nsetp.ne.b32 p, %69, 0;\n"
    "add.u32 tb, %68, %70;\n"
    "mov.b64 db, {tb, 0x40000040};\n"
    "wgmma.mma_async.sync.aligned.m64n128k16.f32.bf16.bf16 "
    "{%0, %1, %2, %3, %4, %5, %6, %7, %8, %9, %10, %11, %12, %13, %14, %15, %16, %17, %18, %19, %20, %21, %22, %23, %24, %25, %26, %27, %28, %29, %30, %31, %32, %33, %34, %35, %36, %37, %38, %39, %40, %41, %42, %43, %44, %45, %46, %47, %48, %49, %50, %51, %52, %53, %54, %55, %56, %57, %58, %59, %60, %61, %62, %63}, "
    "{%64, %65, %66, %67}, db, p, 1, 1, 0;\n}\n"
    : "+f"(d[0]), "+f"(d[1]), "+f"(d[2]), "+f"(d[3]), "+f"(d[4]), "+f"(d[5]), "+f"(d[6]), "+f"(d[7]), "+f"(d[8]), "+f"(d[9]), "+f"(d[10]), "+f"(d[11]), "+f"(d[12]), "+f"(d[13]), "+f"(d[14]), "+f"(d[15]), "+f"(d[16]), "+f"(d[17]), "+f"(d[18]), "+f"(d[19]), "+f"(d[20]), "+f"(d[21]), "+f"(d[22]), "+f"(d[23]), "+f"(d[24]), "+f"(d[25]), "+f"(d[26]), "+f"(d[27]), "+f"(d[28]), "+f"(d[29]), "+f"(d[30]), "+f"(d[31]), "+f"(d[32]), "+f"(d[33]), "+f"(d[34]), "+f"(d[35]), "+f"(d[36]), "+f"(d[37]), "+f"(d[38]), "+f"(d[39]), "+f"(d[40]), "+f"(d[41]), "+f"(d[42]), "+f"(d[43]), "+f"(d[44]), "+f"(d[45]), "+f"(d[46]), "+f"(d[47]), "+f"(d[48]), "+f"(d[49]), "+f"(d[50]), "+f"(d[51]), "+f"(d[52]), "+f"(d[53]), "+f"(d[54]), "+f"(d[55]), "+f"(d[56]), "+f"(d[57]), "+f"(d[58]), "+f"(d[59]), "+f"(d[60]), "+f"(d[61]), "+f"(d[62]), "+f"(d[63])
    : "r"(a0), "r"(a1), "r"(a2), "r"(a3), "r"(b_lo), "r"(scaleD), "n"(OFFB));
}

__device__ __forceinline__ uint4 ldg_nc_v4(const void* p) {
  uint4 v;
    asm volatile("{\n.reg .b64 pol;\ncreatepolicy.fractional.L2::evict_first.b64 pol, 1.0;\n"
                 "ld.global.nc.L1::no_allocate.L2::cache_hint.v4.u32 {%0, %1, %2, %3}, [%4], pol;\n}\n" : "=r"(v.x), "=r"(v.y), "=r"(v.z), "=r"(v.w) : "l"(p));
  return v;
}
__device__ __forceinline__ uint64_t pol_normal() {
  uint64_t p; asm volatile("createpolicy.fractional.L2::evict_normal.b64 %0, 1.0;" : "=l"(p)); return p;
}
__device__ __forceinline__ void unpack8(const uint4& u, float (&v)[8]) {
  v[0] = bflo(u.x); v[1] = bfhi(u.x); v[2] = bflo(u.y); v[3] = bfhi(u.y);
  v[4] = bflo(u.z); v[5] = bfhi(u.z); v[6] = bflo(u.w); v[7] = bfhi(u.w);
}
__device__ __forceinline__ void fma8(float (&acc)[8], float s, const uint4& w) {
  acc[0] = fmaf(s, bflo(w.x), acc[0]); acc[1] = fmaf(s, bfhi(w.x), acc[1]); acc[2] = fmaf(s, bflo(w.y), acc[2]); acc[3] = fmaf(s, bfhi(w.y), acc[3]);
  acc[4] = fmaf(s, bflo(w.z), acc[4]); acc[5] = fmaf(s, bfhi(w.z), acc[5]); acc[6] = fmaf(s, bflo(w.w), acc[6]); acc[7] = fmaf(s, bfhi(w.w), acc[7]);
}
__device__ __forceinline__ float rcp_approx(float x) { float y; asm("rcp.approx.ftz.f32 %0, %1;" : "=f"(y) : "f"(x)); return y; }
__device__ __forceinline__ float sigmoid_f(float v) { return rcp_approx(1.0f + ex2_approx(v * -1.4426950408889634f)); }
__device__ __forceinline__ float silu_bf(float v) { return rbf(v * sigmoid_f(v)); }
__device__ __forceinline__ uint32_t rank_key(float r, int idx) {
  const uint32_t b = __float_as_uint(r) >> 16;
  const uint32_t u = (r != r) ? 0u : ((b & 0x8000u) ? (~b & 0xffffu) : (b | 0x8000u));
  return (u << 16) | (0xffffu - (uint32_t)idx);
}
__device__ __forceinline__ void warp_top2(uint32_t& k1, uint32_t& k2) {
  const uint32_t m1 = __reduce_max_sync(0xffffffffu, k1);
  k2 = __reduce_max_sync(0xffffffffu, k1 == m1 ? k2 : k1);
  k1 = m1;
}
__device__ __forceinline__ uint32_t bmul2(uint32_t a, uint32_t b) { uint32_t r; asm("mul.rn.bf16x2 %0, %1, %2;" : "=r"(r) : "r"(a), "r"(b)); return r; }
__device__ __forceinline__ uint32_t badd2(uint32_t a, uint32_t b) { uint32_t r; asm("add.rn.bf16x2 %0, %1, %2;" : "=r"(r) : "r"(a), "r"(b)); return r; }
__device__ __forceinline__ uint32_t bsub2(uint32_t a, uint32_t b) { uint32_t r; asm("sub.rn.bf16x2 %0, %1, %2;" : "=r"(r) : "r"(a), "r"(b)); return r; }
__device__ __forceinline__ float sqrt_approx(float x) { float y; asm("sqrt.approx.f32 %0, %1;" : "=f"(y) : "f"(x)); return y; }
__device__ __forceinline__ uint32_t ln_norm2(uint32_t x1, uint32_t mb2, float inv) {
  const uint32_t d = bsub2(x1, mb2);
  return pack_bf16(bflo(d) * inv, bfhi(d) * inv);
}
__device__ __forceinline__ uint32_t bfma2(uint32_t a, uint32_t b, uint32_t c) { uint32_t r; asm("fma.rn.bf16x2 %0, %1, %2, %3;" : "=r"(r) : "r"(a), "r"(b), "r"(c)); return r; }
__device__ __forceinline__ uint32_t ln_norm2b(uint32_t x1, uint32_t mb2, uint32_t ih, uint32_t il) {
  const uint32_t d = bsub2(x1, mb2);
  return bfma2(d, ih, bmul2(d, il));
}
__device__ __forceinline__ uint32_t ln_mod2(uint32_t x1, uint32_t mb2, float inv, uint32_t c1, uint32_t sb) { return badd2(bmul2(ln_norm2(x1, mb2, inv), c1), sb); }
__device__ __forceinline__ void ldmatrix_x4(uint32_t addr, uint32_t& r0, uint32_t& r1, uint32_t& r2, uint32_t& r3) {
  asm volatile("ldmatrix.sync.aligned.m8n8.x4.shared.b16 {%0, %1, %2, %3}, [%4];" : "=r"(r0), "=r"(r1), "=r"(r2), "=r"(r3) : "r"(addr) : "memory");
}
__device__ __forceinline__ uint4 ldg_stream_v4(const void* p, uint64_t pol) {
  uint4 v; asm volatile("ld.global.nc.L1::no_allocate.L2::cache_hint.L2::128B.v4.u32 {%0, %1, %2, %3}, [%4], %5;" : "=r"(v.x), "=r"(v.y), "=r"(v.z), "=r"(v.w) : "l"(p), "l"(pol)); return v;
}
__device__ __forceinline__ void bulk_load_hint(uint32_t dst, const void* src, uint32_t bytes, uint32_t bar, uint64_t pol) {
  asm volatile("cp.async.bulk.shared::cluster.global.mbarrier::complete_tx::bytes.L2::cache_hint [%0], [%1], %2, [%3], %4;"
    :: "r"(dst), "l"(src), "r"(bytes), "r"(bar), "l"(pol) : "memory");
}
__device__ __forceinline__ void red_release_add(unsigned int* p, unsigned int v) { asm volatile("red.release.gpu.global.add.u32 [%0], %1;" :: "l"(p), "r"(v) : "memory"); }
__device__ __forceinline__ unsigned int ld_acquire(const unsigned int* p) { unsigned int v; asm volatile("ld.acquire.gpu.global.u32 %0, [%1];" : "=r"(v) : "l"(p) : "memory"); return v; }
__device__ __forceinline__ void spin_until(const unsigned int* p, unsigned int target) {
  #pragma unroll 1
  for (unsigned int i = 0; i < (1u << 22); i++) { if (ld_acquire(p) >= target) return; }
}
__device__ __forceinline__ float lds_f32(uint32_t a) { float v; asm volatile("ld.shared.f32 %0, [%1];" : "=f"(v) : "r"(a) : "memory"); return v; }
__device__ __forceinline__ float2 lds_f32x2(uint32_t a) { float2 v; asm volatile("ld.shared.v2.f32 {%0, %1}, [%2];" : "=f"(v.x), "=f"(v.y) : "r"(a) : "memory"); return v; }
__device__ __forceinline__ uint2 lds_u32x2(uint32_t a) { uint2 v; asm volatile("ld.shared.v2.u32 {%0, %1}, [%2];" : "=r"(v.x), "=r"(v.y) : "r"(a) : "memory"); return v; }
__device__ __forceinline__ uint32_t lds_u32(uint32_t a) { uint32_t v; asm volatile("ld.shared.u32 %0, [%1];" : "=r"(v) : "r"(a) : "memory"); return v; }
__device__ __forceinline__ void sts_u32(uint32_t a, uint32_t v) { asm volatile("st.shared.u32 [%0], %1;" :: "r"(a), "r"(v) : "memory"); }
__device__ __forceinline__ void sts_u32x2(uint32_t a, uint32_t x, uint32_t y) { asm volatile("st.shared.v2.u32 [%0], {%1, %2};" :: "r"(a), "r"(x), "r"(y) : "memory"); }
__device__ __forceinline__ void sts_f32(uint32_t a, float v) { asm volatile("st.shared.f32 [%0], %1;" :: "r"(a), "f"(v) : "memory"); }
__device__ __forceinline__ void sts_f32x2(uint32_t a, float x, float y) { asm volatile("st.shared.v2.f32 [%0], {%1, %2};" :: "r"(a), "f"(x), "f"(y) : "memory"); }
__device__ __forceinline__ void sts_f32x4(uint32_t a, float x, float y, float z, float w) { asm volatile("st.shared.v4.f32 [%0], {%1, %2, %3, %4};" :: "r"(a), "f"(x), "f"(y), "f"(z), "f"(w) : "memory"); }

__device__ __forceinline__ uint4 lds_u32x4(uint32_t a) { uint4 v; asm volatile("ld.shared.v4.u32 {%0, %1, %2, %3}, [%4];" : "=r"(v.x), "=r"(v.y), "=r"(v.z), "=r"(v.w) : "r"(a) : "memory"); return v; }
__device__ __forceinline__ void sts_u32x4(uint32_t a, uint32_t x, uint32_t y, uint32_t z, uint32_t w) { asm volatile("st.shared.v4.u32 [%0], {%1, %2, %3, %4};" :: "r"(a), "r"(x), "r"(y), "r"(z), "r"(w) : "memory"); }
__device__ __forceinline__ void st_tagged(float* p, float v) {
  const uint32_t b = __float_as_uint(v);
  asm volatile("st.relaxed.gpu.global.u32 [%0], %1;" :: "l"(p), "r"(b == 0u ? 0x80000000u : b) : "memory");
}
__device__ __forceinline__ void st_tagged4(float* p, float x, float y, float z, float w) {
  const uint32_t a = __float_as_uint(x), b = __float_as_uint(y), c = __float_as_uint(z), d = __float_as_uint(w);
  asm volatile("st.relaxed.gpu.global.v4.u32 [%0], {%1, %2, %3, %4};" :: "l"(p), "r"(a == 0u ? 0x80000000u : a), "r"(b == 0u ? 0x80000000u : b),
               "r"(c == 0u ? 0x80000000u : c), "r"(d == 0u ? 0x80000000u : d) : "memory");
}
__device__ __forceinline__ void st_relaxed2(void* p, uint32_t a, uint32_t b) { asm volatile("st.relaxed.gpu.global.v2.u32 [%0], {%1, %2};" :: "l"(p), "r"(a), "r"(b) : "memory"); }
__device__ __forceinline__ float4 ld_tagged4(const float* p) {
  float4 v; asm volatile("ld.relaxed.gpu.global.v4.f32 {%0, %1, %2, %3}, [%4];" : "=f"(v.x), "=f"(v.y), "=f"(v.z), "=f"(v.w) : "l"(p) : "memory"); return v;
}
__device__ __forceinline__ bool tagged4(const float4& v) {
  return __float_as_uint(v.x) != 0u && __float_as_uint(v.y) != 0u && __float_as_uint(v.z) != 0u && __float_as_uint(v.w) != 0u;
}
__device__ __forceinline__ void hint_arrive(uint32_t* p) { asm volatile("red.relaxed.gpu.global.add.u32 [%0], 1;" :: "l"(p) : "memory"); }
__device__ __forceinline__ void hint_wait(const uint32_t* p, uint32_t target) {
  uint32_t v = 0u;
  #pragma unroll 1
  for (unsigned int i = 0; i < (1u << 22) && v < target; i++) asm volatile("ld.relaxed.gpu.global.u32 %0, [%1];" : "=r"(v) : "l"(p) : "memory");
}
__device__ __forceinline__ void fence_proxy_async_global() { asm volatile("fence.proxy.async.global;" ::: "memory"); }

#define H_SPLIT 1
#define X_DLY 1200
#define W_DLY 1900
#define W_FIRST 2200
#define PRE_B 2
template <int J0, int J1>
__device__ __forceinline__ void load_parts(float2 (&pa)[J1 - J0][4], int t2) {
  #pragma unroll
  for (int j = J0; j < J1; j++)
    #pragma unroll
    for (int k = 0; k < 4; k++)
      asm volatile("ld.relaxed.gpu.global.v2.f32 {%0, %1}, [%2];" : "=f"(pa[j - J0][k].x), "=f"(pa[j - J0][k].y)
                   : "l"(g_modpart + k * 2 * T_D + (t2 >> 7) * T_D + j * 256 + (t2 & 127) * 2) : "memory");
}
template <int J0, int J1>
__device__ __forceinline__ void finish_parts(float2 (&pa)[J1 - J0][4], bool loaded, int t2, uint32_t tab) {
  #pragma unroll 1
  for (unsigned int spin = 0; spin < (1u << 22); spin++) {
    if (!loaded) load_parts<J0, J1>(pa, t2);
    loaded = false;
    bool ok = true;
    #pragma unroll
    for (int j = 0; j < J1 - J0; j++)
      #pragma unroll
      for (int k = 0; k < 4; k++) ok &= (__float_as_uint(pa[j][k].x) != 0u) & (__float_as_uint(pa[j][k].y) != 0u);
    if (__all_sync(0xffffffffu, ok)) break;
  }
  #pragma unroll
  for (int j = J0; j < J1; j++) {
    const float2* q = pa[j - J0];
    const uint32_t m = pack_bf16(((q[0].x + q[1].x) + q[2].x) + q[3].x, ((q[0].y + q[1].y) + q[2].y) + q[3].y);
    sts_u32(tab + (t2 >> 7) * 2048 + j * 512 + (t2 & 127) * 4, t2 >= 128 ? badd2(m, 0x3F803F80u) : m);
  }
}
__device__ __forceinline__ void head_phase(uint32_t bid, uint32_t scr, uint32_t xs, uint32_t b_x, uint32_t b_go, uint32_t b_head, int t2, uint32_t zero, const bf16* __restrict__ cvec, const bf16* __restrict__ w_mod) {
  const int lane = t2 & 31, w8 = t2 >> 5;
  const int cb = bid & 31, ks = bid >> 5;
  const bool early = (cb & 15) < 4 * H_SPLIT;
  const uint32_t ws = (xs - 32768 + (t2 >> 3) * 128 + (((t2 ^ (t2 >> 3)) & 7) << 4)) ^ zero;
  const float cv = __bfloat162float(cvec[ks * 256 + t2]);
  const bf16* wsrc = w_mod + (size_t)(ks * 256 + (t2 >> 3)) * (6 * T_D) + cb * 64 + (t2 & 7) * 8;
  if (early) {
    const uint64_t pol = policy_evict_first();
    #pragma unroll 2
    for (int i = 0; i < 8; i++)
      asm volatile("cp.async.cg.shared.global.L2::cache_hint [%0], [%1], 16, %2;" :: "r"(ws + i * 4096), "l"(wsrc + (size_t)i * 32 * 6 * T_D), "l"(pol) : "memory");
  }
  sts_f32(scr + t2 * 4, silu_bf(cv));
  named_bar_sync(6, 384);
  TL_MARK2(1, t2 == 0);
  uint4 xv[2][4];
  uint32_t mb2[2], ih[2], il[2];
  auto norm = [&](int j) {
    #pragma unroll
    for (int r = 0; r < 2; r++) {
      xv[r][j].x = ln_norm2b(xv[r][j].x, mb2[r], ih[r], il[r]); xv[r][j].y = ln_norm2b(xv[r][j].y, mb2[r], ih[r], il[r]);
      xv[r][j].z = ln_norm2b(xv[r][j].z, mb2[r], ih[r], il[r]); xv[r][j].w = ln_norm2b(xv[r][j].w, mb2[r], ih[r], il[r]);
    }
  };
  auto modulate = [&](int j) {
    const uint4 sa = lds_u32x4(scr + 8192 + j * 512 + lane * 16), c1 = lds_u32x4(scr + 8192 + 2048 + j * 512 + lane * 16);
    #pragma unroll
    for (int r = 0; r < 2; r++) {
      xv[r][j].x = badd2(bmul2(xv[r][j].x, c1.x), sa.x); xv[r][j].y = badd2(bmul2(xv[r][j].y, c1.y), sa.y);
      xv[r][j].z = badd2(bmul2(xv[r][j].z, c1.z), sa.z); xv[r][j].w = badd2(bmul2(xv[r][j].w, c1.w), sa.w);
    }
  };
  auto store = [&](int j) {
    #pragma unroll
    for (int r = 0; r < 2; r++) *reinterpret_cast<uint4*>(g_h + (size_t)(bid * 16 + 2 * w8 + r) * T_D + j * 256 + lane * 8) = xv[r][j];
  };
  #pragma unroll 1
  for (int ph = 0; ph < 2; ph++) {
    if ((ph == 0) == early) {
      asm volatile("cp.async.wait_all;" ::: "memory");
      if (!early) mbar_wait(b_x + 168, 0);
      float acc[8];
      #pragma unroll
      for (int j = 0; j < 8; j++) acc[j] = 0.f;
      #pragma unroll
      for (int i = 0; i < 8; i++) fma8(acc, lds_f32(scr + ((t2 >> 3) + 32 * i) * 4), lds_u32x4(ws + i * 4096));
      #pragma unroll
      for (int j = 0; j < 4; j++) { const bool up = lane & 16; acc[j] = (up ? acc[4 + j] : acc[j]) + __shfl_xor_sync(0xffffffffu, up ? acc[j] : acc[4 + j], 16); }
      #pragma unroll
      for (int j = 0; j < 2; j++) { const bool up = lane & 8; acc[j] = (up ? acc[2 + j] : acc[j]) + __shfl_xor_sync(0xffffffffu, up ? acc[j] : acc[2 + j], 8); }
      sts_f32x2(scr + 1024 + w8 * 256 + (lane & 7) * 32 + (lane >> 3) * 8, acc[0], acc[1]);
      named_bar_sync(5, 256);
      if (t2 < 64) {
        float sum = 0.f;
        #pragma unroll
        for (int i = 0; i < 8; i++) sum += lds_f32(scr + 1024 + i * 256 + t2 * 4);
        st_tagged(g_modpart + ks * 2 * T_D + cb * 64 + t2, sum);
        TL_MARK2(early ? 2 : 6, t2 == 0);
      }
    } else {
      float2 pa[H_SPLIT][4];
      mbar_wait(b_x, 0);
      TL_MARK2(18, t2 == 0);
      load_parts<0, H_SPLIT>(pa, t2);
      #pragma unroll
      for (int r = 0; r < 2; r++)
        #pragma unroll
        for (int j = 0; j < 4; j++) xv[r][j] = lds_u32x4(xs + (2 * w8 + r) * 2048 + j * 512 + lane * 16);
  {
    float st[4] = {0.f, 0.f, 0.f, 0.f};
    #pragma unroll
    for (int r = 0; r < 2; r++)
      #pragma unroll
      for (int j = 0; j < 4; j++) {
        float v[8];
        unpack8(xv[r][j], v);
        st[2 * r] += ((v[0] + v[1]) + (v[2] + v[3])) + ((v[4] + v[5]) + (v[6] + v[7]));
        st[2 * r + 1] += fmaf(v[0], v[0], fmaf(v[1], v[1], fmaf(v[2], v[2], v[3] * v[3]))) + fmaf(v[4], v[4], fmaf(v[5], v[5], fmaf(v[6], v[6], v[7] * v[7])));
      }
    #pragma unroll
    for (int k = 0; k < 2; k++) { const bool up = lane & 16; st[k] = (up ? st[2 + k] : st[k]) + __shfl_xor_sync(0xffffffffu, up ? st[k] : st[2 + k], 16); }
    #pragma unroll
    for (int o = 8; o > 0; o >>= 1) { st[0] += __shfl_xor_sync(0xffffffffu, st[0], o); st[1] += __shfl_xor_sync(0xffffffffu, st[1], o); }
    const float mean = st[0] * (1.0f / T_D);
    const float inv = rcp_approx(rbf(sqrt_approx(rbf(rbf(fmaxf(fmaf(-mean, mean, st[1] * (1.0f / T_D)), 0.f)) + 1e-05f))));
    const uint32_t m = pack_bf16(mean, mean), h = pack_bf16(inv - rbf(inv), inv);
    #pragma unroll
    for (int r = 0; r < 2; r++) {
      mb2[r] = __shfl_sync(0xffffffffu, m, 16 * r);
      const uint32_t hr = __shfl_sync(0xffffffffu, h, 16 * r);
      ih[r] = __byte_perm(hr, hr, 0x3232); il[r] = __byte_perm(hr, hr, 0x1010);
    }
  }
      #pragma unroll
      for (int j = 0; j < H_SPLIT; j++) norm(j);
      TL_MARK2(5, t2 == 0);
      finish_parts<0, H_SPLIT>(pa, true, t2, scr + 8192);
      named_bar_sync(5, 256);
      TL_MARK2(7, t2 == 0);
      #pragma unroll
      for (int j = 0; j < H_SPLIT; j++) { modulate(j); store(j); }
      named_bar_arrive(9, 288);
    }
  }
  #pragma unroll
  for (int j = H_SPLIT; j < 4; j++) norm(j);
  float2 pb[4 - H_SPLIT][4];
  finish_parts<H_SPLIT, 4>(pb, false, t2, scr + 8192);
  named_bar_sync(5, 256);
  TL_MARK2(17, t2 == 0);
  #pragma unroll
  for (int j = H_SPLIT; j < 4; j++) modulate(j);
  __syncwarp();
  if (lane == 0) mbar_arrive(b_head + (xv[1][3].w & zero));
  mbar_wait(b_go, 0);
  #pragma unroll
  for (int j = H_SPLIT; j < 4; j++) store(j);
  named_bar_arrive(8, 288);
}

#define MOD_AT (b_empty + 8)
#define MOD_SPLIT 16
__device__ __forceinline__ void mod_rest(uint32_t bid, uint32_t scr, uint32_t b_go, int t, const bf16* __restrict__ cvec, const bf16* __restrict__ w_mod, const bf16* __restrict__ w_r) {
  const int lane = t & 31;
  #pragma unroll 1
  for (int i = t; i < T_D / 2; i += 64) {
    const uint32_t c2 = *reinterpret_cast<const uint32_t*>(cvec + 2 * i);
    sts_u32(scr + i * 4, pack_bf16(silu_bf(bflo(c2)), silu_bf(bfhi(c2))));
  }
  named_bar_sync(11, 64);
  const bf16* wp = w_mod + (size_t)(2 * (t >> 2)) * (6 * T_D) + 2 * T_D + bid * 32 + (t & 3) * 8;
  float acc[8];
  #pragma unroll
  for (int i = 0; i < 8; i++) acc[i] = 0.f;
  #pragma unroll 1
  for (int i = 0; i < 32; i += 2) {
    if (i == MOD_SPLIT) mbar_wait(b_go, 0);
    const uint4 w0 = ldg_nc_v4(wp), w1 = ldg_nc_v4(wp + 6 * T_D), w2 = ldg_nc_v4(wp + 32 * 6 * T_D), w3 = ldg_nc_v4(wp + 33 * 6 * T_D);
    wp += 64 * 6 * T_D;
    const uint32_t s0 = lds_u32(scr + (i * 16 + (t >> 2)) * 4), s1 = lds_u32(scr + (i * 16 + 16 + (t >> 2)) * 4);
    fma8(acc, bflo(s0), w0); fma8(acc, bfhi(s0), w1); fma8(acc, bflo(s1), w2); fma8(acc, bfhi(s1), w3);
  }
  #pragma unroll
  for (int j = 0; j < 4; j++) { const bool up = lane & 16; acc[j] = (up ? acc[4 + j] : acc[j]) + __shfl_xor_sync(0xffffffffu, up ? acc[j] : acc[4 + j], 16); }
  #pragma unroll
  for (int j = 0; j < 2; j++) { const bool up = lane & 8; acc[j] = (up ? acc[2 + j] : acc[j]) + __shfl_xor_sync(0xffffffffu, up ? acc[j] : acc[2 + j], 8); }
  { const bool up = lane & 4; acc[0] = (up ? acc[1] : acc[0]) + __shfl_xor_sync(0xffffffffu, up ? acc[0] : acc[1], 4); }
  if (t >= 32) sts_f32(scr + 2048 + lane * 4, acc[0]);
  named_bar_sync(11, 64);
  if (__shfl_sync(0xffffffffu, t, 0) < 32) {
    const int kind = bid >> 5;
    float v = rbf(acc[0] + lds_f32(scr + 2048 + lane * 4));
    const int col = (bid & 31) * 32 + (lane & 3) * 8 + (lane >> 2);
    uint8_t* dst = g_col + (col >> 7) * 1536;
    if (kind == 2) v = rbf(1.0f + v);
    float vw = v * __bfloat162float(w_r[col]);
    if (kind == 2) {
      const int c = col & 127, i = (c & ~15) + ((c >> 1) & 3) * 4 + ((c >> 3) & 1) * 2 + (c & 1);
      reinterpret_cast<bf16*>(dst)[i] = __float2bfloat16_rn(vw);
      reinterpret_cast<bf16*>(dst)[128 + i] = __float2bfloat16_rn(vw - rbf(vw));
    }
    reinterpret_cast<bf16*>(dst + 512 + (kind & 1) * 512 + (kind >> 1) * 256)[col & 127] = __float2bfloat16_rn(v);
    #pragma unroll
    for (int o = 16; o > 0; o >>= 1) vw += __shfl_xor_sync(0xffffffffu, vw, o);
    if (lane == 0 && (kind == 1 || kind == 2)) g_scal[95 - bid] = vw;
  }
  #pragma unroll 1
  for (int i = bid * 64 + t; i < (int)(sizeof(g_mail) / 16); i += 128 * 64) reinterpret_cast<uint4*>(&g_mail)[i] = make_uint4(0u, 0u, 0u, 0u);
  named_bar_sync(11, 64);
  if (t == 0) red_release_add(&g_hcnt[0], 1u);
}

constexpr int AT_NBLK = T_SEQ / 128;
constexpr float AT_HEAD = 7.0f;
#define WO_LATE 12
#define QP_STAG 3
#define AT_SPLIT 28
#define AT_PIN 12
#define PINB 4
constexpr int AT_NFULL = 124;
constexpr int AT_PREG = 40, AT_CREG = 232;
constexpr uint32_t AT_SQ = 5 * 32768;
constexpr float AT_C = 0.08838834764831845f * 1.4426950408889634f;
constexpr float AT_RAW_LO = -16.0f, AT_RAW_HI = 24.0f;
constexpr float AT_RAW_SUM = 281474976710656.0f, AT_RAW_MIN = 9.094947017729282e-13f;
constexpr uint32_t AT_SBAR = AT_SQ + 65536 + 256;
constexpr uint32_t AT_SMEM = AT_SQ + 65536 + 3072;

__device__ __forceinline__ uint32_t ring_slot(uint32_t t) { return t - 5u * ((t * 205u) >> 10); }
__device__ __forceinline__ uint32_t qp_pos(uint32_t j, uint32_t it) { return 4u * it + (j & 3u) + ((j & 3u) == 3u ? it : 0u); }
__device__ __forceinline__ uint32_t ring_par(uint32_t t) { return ((t * 205u) >> 10) & 1u; }
__device__ __forceinline__ void softmax_rowmax(const float (&s)[64], float& mx0, float& mx1) {
  float a0 = fmaxf(s[0], s[1]), a1 = fmaxf(s[4], s[5]), a2 = fmaxf(s[8], s[9]), a3 = fmaxf(s[12], s[13]);
  float b0 = fmaxf(s[2], s[3]), b1 = fmaxf(s[6], s[7]), b2 = fmaxf(s[10], s[11]), b3 = fmaxf(s[14], s[15]);
  #pragma unroll
  for (int j = 4; j < 16; j += 4) {
    a0 = fmaxf(a0, fmaxf(s[4 * j + 0], s[4 * j + 1]));  b0 = fmaxf(b0, fmaxf(s[4 * j + 2], s[4 * j + 3]));
    a1 = fmaxf(a1, fmaxf(s[4 * j + 4], s[4 * j + 5]));  b1 = fmaxf(b1, fmaxf(s[4 * j + 6], s[4 * j + 7]));
    a2 = fmaxf(a2, fmaxf(s[4 * j + 8], s[4 * j + 9]));  b2 = fmaxf(b2, fmaxf(s[4 * j + 10], s[4 * j + 11]));
    a3 = fmaxf(a3, fmaxf(s[4 * j + 12], s[4 * j + 13])); b3 = fmaxf(b3, fmaxf(s[4 * j + 14], s[4 * j + 15]));
  }
  mx0 = fmaxf(fmaxf(a0, a1), fmaxf(a2, a3));
  mx1 = fmaxf(fmaxf(b0, b1), fmaxf(b2, b3));
  mx0 = fmaxf(mx0, __shfl_xor_sync(0xffffffffu, mx0, 1));
  mx1 = fmaxf(mx1, __shfl_xor_sync(0xffffffffu, mx1, 1));
  mx0 = fmaxf(mx0, __shfl_xor_sync(0xffffffffu, mx0, 2));
  mx1 = fmaxf(mx1, __shfl_xor_sync(0xffffffffu, mx1, 2));
}
__device__ __forceinline__ void softmax_sub(float (&s)[64], float mc0, float mc1) {
  #pragma unroll
  for (int j = 0; j < 16; j++) { s[4 * j] -= mc0; s[4 * j + 1] -= mc0; s[4 * j + 2] -= mc1; s[4 * j + 3] -= mc1; }
}
template <int LO, int HI>
__device__ __forceinline__ void softmax_exp(float (&s)[64]) {
  #pragma unroll
  for (int i = LO; i < HI; i++) s[i] = ex2_approx(s[i]);
}
__device__ __forceinline__ bool softmax_mode(const float (&s)[64], float& mc0, float& mc1) {
  softmax_rowmax(s, mc0, mc1);
  const bool raw = __all_sync(0xffffffffu, mc0 >= AT_RAW_LO && mc0 <= AT_RAW_HI && mc1 >= AT_RAW_LO && mc1 <= AT_RAW_HI);
  mc0 += AT_HEAD; mc1 += AT_HEAD;
  return raw;
}
__device__ __forceinline__ void rowsum_p(const uint32_t (&p)[32], uint32_t& t0, uint32_t& t1) {
  uint32_t a[16];
  #pragma unroll
  for (int i = 0; i < 8; i++) { a[2 * i] = badd2(p[4 * i], p[4 * i + 2]); a[2 * i + 1] = badd2(p[4 * i + 1], p[4 * i + 3]); }
  #pragma unroll
  for (int i = 0; i < 4; i++) { a[2 * i] = badd2(a[4 * i], a[4 * i + 2]); a[2 * i + 1] = badd2(a[4 * i + 1], a[4 * i + 3]); }
  t0 = badd2(badd2(a[0], a[2]), badd2(a[4], a[6]));
  t1 = badd2(badd2(a[1], a[3]), badd2(a[5], a[7]));
}
__device__ __forceinline__ void add_rowsum(const uint32_t (&p)[32], float& l0, float& l1) {
  uint32_t t0, t1;
  rowsum_p(p, t0, t1);
  l0 += bflo(t0) + bfhi(t0); l1 += bflo(t1) + bfhi(t1);
}
__device__ __forceinline__ void pack_p(uint32_t (&p)[32], const float (&s)[64]) {
  #pragma unroll
  for (int i = 0; i < 32; i++) p[i] = pack_bf16(s[2 * i], s[2 * i + 1]);
}
__device__ __noinline__ void attn_rows_exact(uint32_t bid, uint32_t sq, uint32_t so, int hsel, const bf16* __restrict__ kh, const bf16* __restrict__ vh) {
  const int warp = (threadIdx.x >> 5) & 3, lane = threadIdx.x & 31;
  const size_t hofs = (size_t)((bid < 128 ? bid >> 4 : 15) * 2 + hsel) * T_SEQ * T_DH;
  kh += hofs; vh += hofs;
  #pragma unroll 1
  for (int r = 16 * warp; r < 16 * warp + 16; r++) {
    const uint32_t ad = (lane >> 4) * 16384 + r * 128 + ((((lane & 15) >> 1) ^ (r & 7)) << 4) + (lane & 1) * 8;
    uint2 qv; asm volatile("ld.shared.v2.u32 {%0, %1}, [%2];" : "=r"(qv.x), "=r"(qv.y) : "r"(sq + ad) : "memory");
    const float q0 = bflo(qv.x), q1 = bfhi(qv.x), q2 = bflo(qv.y), q3 = bfhi(qv.y);
    float m = -INFINITY, l = 0.f, o0 = 0.f, o1 = 0.f, o2 = 0.f, o3 = 0.f;
    #pragma unroll 1
    for (int key = 0; key < T_SEQ; key++) {
      const uint2 kv = *reinterpret_cast<const uint2*>(kh + (size_t)key * T_DH + lane * 4);
      const uint2 vv = *reinterpret_cast<const uint2*>(vh + (size_t)key * T_DH + lane * 4);
      float sc = (q0 * bflo(kv.x) + q1 * bfhi(kv.x)) + (q2 * bflo(kv.y) + q3 * bfhi(kv.y));
      #pragma unroll
      for (int o = 16; o > 0; o >>= 1) sc += __shfl_xor_sync(0xffffffffu, sc, o);
      const float mn = fmaxf(m, sc);
      const float al = (m == mn) ? 1.0f : ex2_approx(m - mn), p = rbf(ex2_approx(sc - mn));
      m = mn;
      l = fmaf(l, al, p);
      o0 = fmaf(o0, al, p * bflo(vv.x)); o1 = fmaf(o1, al, p * bfhi(vv.x));
      o2 = fmaf(o2, al, p * bflo(vv.y)); o3 = fmaf(o3, al, p * bfhi(vv.y));
    }
    const float inv = rcp_approx(l);
    asm volatile("st.shared.v2.u32 [%0], {%1, %2};" :: "r"(so + ad), "r"(pack_bf16(o0 * inv, o1 * inv)), "r"(pack_bf16(o2 * inv, o3 * inv)) : "memory");
  }
}
__device__ __forceinline__ void issue_qk(float (&s)[64], const uint32_t (&q)[32], uint32_t k_lo) {
  wgmma_fence();
  wgmma_m64n128k16_rs<0>(s, q[0], q[1], q[2], q[3], k_lo, 0);
  wgmma_m64n128k16_rs<2>(s, q[4], q[5], q[6], q[7], k_lo, 1);
  wgmma_m64n128k16_rs<4>(s, q[8], q[9], q[10], q[11], k_lo, 1);
  wgmma_m64n128k16_rs<6>(s, q[12], q[13], q[14], q[15], k_lo, 1);
  wgmma_m64n128k16_rs<1024>(s, q[16], q[17], q[18], q[19], k_lo, 1);
  wgmma_m64n128k16_rs<1026>(s, q[20], q[21], q[22], q[23], k_lo, 1);
  wgmma_m64n128k16_rs<1028>(s, q[24], q[25], q[26], q[27], k_lo, 1);
  wgmma_m64n128k16_rs<1030>(s, q[28], q[29], q[30], q[31], k_lo, 1);
  wgmma_commit();
}
__device__ __forceinline__ void issue_pv(float (&o)[64], const uint32_t (&p)[32], uint32_t v_lo, int accumulate) {
  wgmma_fence();
  wgmma_m64n128k16_rs_tb<0>(o, p[0], p[1], p[2], p[3], v_lo, accumulate);
  wgmma_m64n128k16_rs_tb<128>(o, p[4], p[5], p[6], p[7], v_lo, 1);
  wgmma_m64n128k16_rs_tb<256>(o, p[8], p[9], p[10], p[11], v_lo, 1);
  wgmma_m64n128k16_rs_tb<384>(o, p[12], p[13], p[14], p[15], v_lo, 1);
  wgmma_m64n128k16_rs_tb<512>(o, p[16], p[17], p[18], p[19], v_lo, 1);
  wgmma_m64n128k16_rs_tb<640>(o, p[20], p[21], p[22], p[23], v_lo, 1);
  wgmma_m64n128k16_rs_tb<768>(o, p[24], p[25], p[26], p[27], v_lo, 1);
  wgmma_m64n128k16_rs_tb<896>(o, p[28], p[29], p[30], p[31], v_lo, 1);
  wgmma_commit();
}
__device__ __forceinline__ void block_end(uint32_t zero, uint32_t bar) {
  #pragma unroll 1
  for (uint32_t i = 0; i < zero; i++) mbar_arrive(bar);
}
__device__ __forceinline__ void rescale_o(float (&o)[64], float al0, float al1) {
  #pragma unroll
  for (int j = 0; j < 16; j++) { o[4 * j] *= al0; o[4 * j + 1] *= al0; o[4 * j + 2] *= al1; o[4 * j + 3] *= al1; }
}

__device__ __forceinline__ void stage_o(const float (&o)[64], float i0, float i1, uint32_t dst, int lane) {
  #pragma unroll
  for (int J = 0; J < 16; J += 2)
    stmatrix_x4(dst + (J >> 3) * 16384 + ((((J & 7) + (lane >> 4)) ^ (lane & 7)) << 4),
                pack_bf16(o[4 * J + 0] * i0, o[4 * J + 1] * i0), pack_bf16(o[4 * J + 2] * i1, o[4 * J + 3] * i1),
                pack_bf16(o[4 * J + 4] * i0, o[4 * J + 5] * i0), pack_bf16(o[4 * J + 6] * i1, o[4 * J + 7] * i1));
}
__device__ __forceinline__ bool finish_l(float& l0, float& l1) {
  l0 += __shfl_xor_sync(0xffffffffu, l0, 1); l1 += __shfl_xor_sync(0xffffffffu, l1, 1);
  l0 += __shfl_xor_sync(0xffffffffu, l0, 2); l1 += __shfl_xor_sync(0xffffffffu, l1, 2);
  const bool redo = __any_sync(0xffffffffu, !(l0 <= AT_RAW_SUM && l1 <= AT_RAW_SUM && l0 >= AT_RAW_MIN && l1 >= AT_RAW_MIN));
  l0 = rcp_approx(l0); l1 = rcp_approx(l1);
  return redo;
}
template <int J0>
__device__ __forceinline__ void stage_q(const float (&acc)[128], float c, uint32_t dst, int lane) {
  #pragma unroll
  for (int J = J0; J < J0 + 16; J += 2)
    stmatrix_x4(dst + (J >> 3) * 16384 + ((((J & 7) + (lane >> 4)) ^ (lane & 7)) << 4),
                pack_bf16(acc[4 * J + 0] * c, acc[4 * J + 1] * c), pack_bf16(acc[4 * J + 2] * c, acc[4 * J + 3] * c),
                pack_bf16(acc[4 * J + 4] * c, acc[4 * J + 5] * c), pack_bf16(acc[4 * J + 6] * c, acc[4 * J + 7] * c));
}
__device__ __forceinline__ void store_o(const CUtensorMap* tmO, uint32_t src, int head, int row) {
  tma_store_2d(tmO, src, head * T_DH, row);
  tma_store_2d(tmO, src + 16384, head * T_DH + 64, row);
  bulk_commit();
}
__device__ __forceinline__ void mma_bf16(float (&d)[4], uint32_t a0, uint32_t a1, uint32_t a2, uint32_t a3, uint32_t b0, uint32_t b1) {
  asm volatile("mma.sync.aligned.m16n8k16.row.col.f32.bf16.bf16.f32 {%0, %1, %2, %3}, {%4, %5, %6, %7}, {%8, %9}, {%0, %1, %2, %3};"
               : "+f"(d[0]), "+f"(d[1]), "+f"(d[2]), "+f"(d[3]) : "r"(a0), "r"(a1), "r"(a2), "r"(a3), "r"(b0), "r"(b1));
}
struct GemvSel { uint32_t lo0, hi0, lo1, hi1; };
__device__ __forceinline__ GemvSel gemv_sel(int lane) {
  const uint32_t lo = (lane & 8) ? 0x1044u : 0x4410u, hi = (lane & 8) ? 0x3244u : 0x4432u;
  GemvSel s; s.lo0 = (lane & 16) ? 0x4444u : lo; s.hi0 = (lane & 16) ? 0x4444u : hi; s.lo1 = (lane & 16) ? lo : 0x4444u; s.hi1 = (lane & 16) ? hi : 0x4444u;
  return s;
}
#define GEMV_B0(j, h, s) __byte_perm((j) < 2 ? (h).x : (h).y, 0u, ((j) & 1) ? (s).hi0 : (s).lo0)
#define GEMV_B1(j, h, s) __byte_perm((j) < 2 ? (h).x : (h).y, 0u, ((j) & 1) ? (s).hi1 : (s).lo1)
__device__ __forceinline__ float4 gemv_out(const float (&d)[4], int lane) {
  const bool tk = lane & 1;
  const float r0 = __shfl_xor_sync(0xffffffffu, tk ? d[0] : d[1], 1), r1 = __shfl_xor_sync(0xffffffffu, tk ? d[2] : d[3], 1);
  return tk ? make_float4(r0, d[1], r1, d[3]) : make_float4(d[0], r0, d[2], r1);
}
#define OG_NG 8
#define PUT_N 2
#define H_STAG 2
#define AL_P 60
#define AL_SLEEP 1200
#define AL_MAX 800
#define POLL_NS 200
#define OG_PROF 0xCCCAAA88u
#define RK_P 24
#define RANK 1
__host__ __device__ constexpr int og_pre(int tile) { return (OG_PROF >> ((tile >> 4) * 4)) & 15; }
constexpr int OG_PRE2 = og_pre(127), OG_HSUM = og_pre(0) + og_pre(16) + og_pre(32) + og_pre(48) + og_pre(64) + og_pre(80) + og_pre(96);
#define OG_JOBS 7
#define OG_GRP 6
#define LD_FIRST 3
#define LD_STAG (OG_GRP / 2)
constexpr int OG_ST = 5, OG_NKB = T_DQKV / 64 - og_pre(0), OG_MOE = T_F / 32;
__device__ __forceinline__ int pre_kb(int i) { return (i >> 1) * 4 + (i & 1); }
__device__ __forceinline__ int own_kb(int i) { return i < OG_PRE2 ? pre_kb(i) + 2 : i < 64 - OG_PRE2 ? i + OG_PRE2 : pre_kb(63 - i); }
constexpr int OG_POS = 8;
constexpr uint32_t OG_STAGE = 32768;
constexpr uint32_t OG_SCOL = AT_SBAR + 512;
constexpr uint32_t OG_SMISC = AT_SBAR + 2048;
constexpr uint32_t OG_SWD = AT_SQ, OG_PSLOT = AT_SQ;
constexpr uint32_t OG_XSLOT = AT_SQ + 32768;
constexpr uint32_t OG_OSLOT = 1 * OG_STAGE;
constexpr uint32_t OG_SRED = 3 * OG_STAGE;
constexpr uint32_t OG_SH2 = OG_SRED + 24576;
constexpr uint32_t OG_SSTAT = OG_SRED + 16384;
constexpr uint32_t OG_SGU = OG_SRED + 8192;
constexpr uint32_t OG_SFIN = OG_SGU + 256;
#define OGM 2
#define OG_MT(b) ((((b) >> OGM) & 15) ^ (((b) & 64) ? 15 : 0))
#define OG_NT(b) (((b) & ((1 << OGM) - 1)) + (((b) >> (4 + OGM)) << OGM))
__device__ __forceinline__ int tail_tile(uint32_t sbase) { mbar_wait(sbase + AT_SBAR + 336, 0); return (int)lds_u32(sbase + AT_SBAR + 408); }
#define TAIL_SETUP \
  const uint32_t bar_full = sbase + AT_SBAR, bar_empty = bar_full + 40; \
  const uint32_t bar_wd = bar_full + 168, bar_col = bar_full + 176, bar_out = bar_full + 184, bar_end = bar_full + 192; \
  const uint32_t bar_key = bar_full + 200, bar_h2 = bar_full + 208, bar_sel = bar_full + 216; \
  const int mt = OG_MT(tb), nt = OG_NT(tb); \
  const int m0 = mt * 128, n0 = nt * 128; \
  const bool has_moe = (int)bid < OG_MOE; \
  (void)bar_empty; (void)bar_wd; (void)bar_col; (void)bar_out; (void)bar_end; (void)bar_key; (void)bar_h2; (void)bar_sel; (void)m0; (void)n0; (void)has_moe;

__device__ __forceinline__ void tail_producer(uint32_t bid, uint32_t sbase, uint32_t ph, uint64_t pol, const CUtensorMap* tmA, const CUtensorMap* tmB, const CUtensorMap* tmD) {
  const int tb = tail_tile(sbase);
  TAIL_SETUP
  uint32_t stage = OG_POS % OG_ST;
  int kb = 0;
  #pragma unroll 1
  for (int seg = 0; seg < 2; seg++) {
    mbar_wait(bar_full + 264 + 80 * seg, 0);
    fence_proxy_async_global();
    const int end = seg == 0 ? 32 - OG_PRE2 : 64 - og_pre(tb);
    #pragma unroll 1
    for (; kb < end; kb++) {
      const uint32_t fb = bar_full + 8 * stage, sa = sbase + stage * OG_STAGE;
      const int k0 = own_kb(kb) * 64;
      mbar_wait(bar_empty + 8 * stage, ph);
      mbar_expect_tx(fb, OG_STAGE);
      tma_load_3d_hint(sa + 16384, tmB, k0, 2 * nt, fb, pol);
      tma_load_2d_hint(sa, tmA, k0, m0, fb, pol);
      if (++stage == OG_ST) { stage = 0; ph ^= 1; }
    }
  }
  if (has_moe) {
    mbar_wait(bar_empty + 8 * stage, ph);
    mbar_expect_tx(bar_wd, OG_STAGE);
    tma_load_3d_hint(sbase + stage * OG_STAGE, tmD, bid * 32, 8, bar_wd, pol);
  }
}

__device__ __forceinline__ uint32_t out2(uint32_t x1, uint32_t mb2, uint32_t ih, uint32_t il, uint32_t c1, uint32_t sb, uint32_t gb) {
  const uint32_t h2 = badd2(bmul2(ln_norm2b(x1, mb2, ih, il), c1), sb);
  return badd2(x1, bmul2(gb, bfma2(h2, 0u, h2)));
}
#define OGTIME gtime()
#define X_PACE 200
#define Y_SLACK 96
#define OG_STAG 3
#define WD_PACE 300
__device__ __forceinline__ void tail_exchange(uint32_t bid, uint32_t sbase, const bf16* __restrict__ w_down, const bf16* __restrict__ w_r, const bf16* __restrict__ x, bf16* __restrict__ out) {
    const int lane = threadIdx.x & 31, wi = __shfl_sync(0xffffffffu, threadIdx.x >> 5, 0);
    if (wi == 3) {
      uint32_t a = bid, b = 0u;
      if (bid < AT_NFULL) mbar_wait(sbase + AT_SBAR + 312, 0);
      if (bid < OG_MOE) {
        asm volatile("mov.u32 %0, %%globaltimer_lo;" : "=r"(a));
        if (lane == 0 && (bid & 15) == 0) asm volatile("st.relaxed.gpu.global.u32 [%0], %1;" :: "l"(g_hcnt + 8 + (bid >> 4)), "r"((a & ~15u) | 8u | (bid >> 4)) : "memory");
        #pragma unroll 1
        for (unsigned int spin = 0; spin < (1u << 22) && __any_sync(0xffffffffu, b == 0u); spin++) {
          __nanosleep(200);
          asm volatile("ld.relaxed.gpu.global.u32 %0, [%1];" : "=r"(b) : "l"(g_hcnt + 8 + min(lane, 6)) : "memory");
        }
        a = RANK ? __popc(__ballot_sync(0xffffffffu, b < __shfl_sync(0xffffffffu, b, bid >> 4)) & 127u) * 16 + (bid & 15) : bid;
      }
      if (lane == 0) {
        sts_u32(sbase + AT_SBAR + 408, a);
        mbar_arrive(sbase + AT_SBAR + 336);
        b = 0u;
        if (bid < AT_NFULL) {
          unsigned int* tm = g_hcnt + 32 * (1 + (bid >> 4)) + 8;
          mbar_wait(sbase + AT_SBAR + 312, 1);
          asm volatile("mov.u32 %0, %%globaltimer_lo;" : "=r"(a));
          asm volatile("red.relaxed.gpu.global.max.u32 [%0], %1;" :: "l"(tm), "r"(a) : "memory");
          __nanosleep(AL_SLEEP);
          asm volatile("ld.relaxed.gpu.global.u32 %0, [%1];" : "=r"(b) : "l"(tm) : "memory");
          b -= a;
        }
        sts_u32(sbase + AT_SBAR + 412, b < AL_MAX ? b * 13 / 8 : 0u);
        mbar_arrive(sbase + AT_SBAR + 320);
      }
      named_bar_sync(15, 32);
    }
    const int tb = __shfl_sync(0xffffffffu, tail_tile(sbase), 0);
    TAIL_SETUP
    if (wi == 3) {
      mbar_wait(bar_full + 344, 0);
      float a = g_scal[lane], b = g_scal[32 + lane];
      #pragma unroll
      for (int i = 0; i < 3; i++) {
        const uint4 v = *reinterpret_cast<const uint4*>(g_col + nt * 1536 + i * 512 + lane * 16);
        sts_u32x4(sbase + OG_SCOL + i * 512 + lane * 16, v.x, v.y, v.z, v.w);
      }
      #pragma unroll
      for (int o = 16; o > 0; o >>= 1) { a += __shfl_xor_sync(0xffffffffu, a, o); b += __shfl_xor_sync(0xffffffffu, b, o); }
      if (lane == 0) sts_f32x2(sbase + OG_SMISC, a, b);
      const uint64_t pol = policy_evict_first();
      #pragma unroll 1
      for (int r = lane >> 4; r < 128; r += 4) {
        __nanosleep(X_PACE);
        #pragma unroll
        for (int j = 0; j < 4; j += 2)
          asm volatile("cp.async.cg.shared.global.L2::cache_hint [%0], [%1], 16, %2;" :: "r"(sbase + OG_XSLOT + (lane & 8) * 2048 + (r + j) * 128 + (((lane ^ (r + j)) & 7) << 4)),
                       "l"(x + (size_t)(m0 + r + j) * T_D + n0 + (lane & 15) * 8), "l"(pol) : "memory");
      }
      asm volatile("cp.async.wait_all;" ::: "memory");
      __syncwarp();
      if (lane == 0) mbar_arrive(bar_col);
    } else if (wi == 2) {
      if (elect_one()) {
        const uint32_t b_free = bar_full + (bid < AT_NFULL ? 80 : 160);
        mbar_wait(b_free, 1);
        #pragma unroll 1
        for (unsigned int i = 0; i < (1u << 20) && ld_acquire(&g_hcnt[32 * (1 + (tb >> 3)) + 4 + ((tb >> 1) & 3)]) == 0u; i++) __nanosleep(POLL_NS);
        TL_MARK2(23, true);
        fence_proxy_async_global();
        TL_MARK2(4, true);
        mbar_expect_tx(bar_full + 272, 32768);
        bulk_load_hint(sbase + OG_PSLOT, g_pre + tb * 2048, 32768, bar_full + 272, policy_evict_first());
      }
      named_bar_sync(14, 32);
      if (has_moe) {
        mbar_wait(bar_full + 96, 1); mbar_wait(bar_full + 304, 0);
        const uint64_t pol = policy_evict_first();
        #pragma unroll 1
        for (int r = 0; r < 32; r++) {
          __nanosleep(WD_PACE);
          #pragma unroll
          for (int j = 0; j < 2; j++)
            asm volatile("cp.async.cg.shared.global.L2::cache_hint [%0], [%1], 16, %2;" :: "r"(sbase + OG_SWD + (4 * j + (lane >> 3)) * 4096 + r * 128 + (((lane ^ r) & 7) << 4)),
                         "l"((const uint8_t*)w_down + (size_t)bid * 65536 + r * 2048 + j * 512 + lane * 16), "l"(pol) : "memory");
        }
        asm volatile("cp.async.wait_all;" ::: "memory");
        __syncwarp();
        if (lane == 0) mbar_arrive(bar_wd);
      }
    }
    const uint4 wrv = ldg_nc_v4(w_r + threadIdx.x * 8);
    mbar_wait(bar_end, 0);
    if (threadIdx.x == 96) XT(10);
    TL_MARK2(22, lane == 0);
    if (wi == 0) {
      uint32_t k1 = 0u, k2 = 0u;
      #pragma unroll 1
      for (unsigned int spin = 0; spin < (1u << 22) && __any_sync(0xffffffffu, k1 == 0u); spin++) asm volatile("ld.relaxed.gpu.global.u32 %0, [%1];" : "=r"(k1) : "l"(g_key + lane) : "memory");
      TL_MARK2(28, lane == 0);
      warp_top2(k1, k2);
      if (lane == 0) {
        const uint32_t r1 = 0xffffu - (k1 & 0xffffu), r2 = 0xffffu - (k2 & 0xffffu);
        sts_u32x4(sbase + OG_SMISC + 64, r1, r2, (r1 >> 7) * 2, (r2 >> 7) * 2 + ((r1 >> 7) == (r2 >> 7)));
        mbar_arrive(bar_sel);
      }
    } else if (wi < 3) {
          mbar_wait(bar_key, 0);
          const uint4 kk = lds_u32x4(sbase + OG_SSTAT + 1024 + lane * 16);
          uint32_t k1 = max(kk.x, kk.y), k2 = min(kk.x, kk.y);
          k2 = max(max(k2, min(kk.z, kk.w)), min(k1, max(kk.z, kk.w))); k1 = max(k1, max(kk.z, kk.w));
          warp_top2(k1, k2);
          if (wi == 1) {
            if (lane == 0) {
              if (nt == (mt & 7)) st_relaxed2(g_key + mt * 2, k1, k2);
              sts_u32x2(sbase + OG_SMISC + 96, (~k1 >> 4) & 7u, (~k2 >> 4) & 7u);
              mbar_arrive(bar_full + 352);
            }
            TL_MARK2(27, lane == 0);
          } else {
            const uint32_t r = (~((lane & 16) ? k2 : k1)) & 127u, ch = lane & 15;
            const uint2 st = lds_u32x2(sbase + OG_SSTAT + r * 8);
            const uint4 xc = lds_u32x4(sbase + OG_XSLOT + (ch >> 3) * 16384 + r * 128 + (((ch ^ r) & 7) << 4));
            const uint4 c1 = lds_u32x4(sbase + OG_SCOL + 768 + ch * 16), sh = lds_u32x4(sbase + OG_SCOL + 1024 + ch * 16);
            const float inr = __uint_as_float(st.y);
            float* dst = reinterpret_cast<float*>(g_cand + (mt * 2 + (lane >> 4)) * 256 + nt * 16 + ch);
            st_tagged4(dst + 512, __uint_as_float(ln_mod2(xc.x, st.x, inr, c1.x, sh.x)), __uint_as_float(ln_mod2(xc.y, st.x, inr, c1.y, sh.y)),
                       __uint_as_float(ln_mod2(xc.z, st.x, inr, c1.z, sh.z)), __uint_as_float(ln_mod2(xc.w, st.x, inr, c1.w, sh.w)));
            st_tagged4(dst, __uint_as_float(xc.x), __uint_as_float(xc.y), __uint_as_float(xc.z), __uint_as_float(xc.w));
          }
    }
    mbar_wait(bar_sel, 0);
    const uint4 sel = lds_u32x4(sbase + OG_SMISC + 64);
    const int sel0 = (int)sel.x, sel1 = (int)sel.y;
    {
      const float* src0 = reinterpret_cast<const float*>(g_cand + sel.z * 256 + 128 + threadIdx.x);
      const float* src1 = reinterpret_cast<const float*>(g_cand + sel.w * 256 + 128 + threadIdx.x);
      float4 h0, h1;
      #pragma unroll 1
      for (unsigned int spin = 0; spin < (1u << 20); spin++) { h0 = ld_tagged4(src0); h1 = ld_tagged4(src1); if (__all_sync(0xffffffffu, tagged4(h0) & tagged4(h1))) break; }
      sts_f32x4(sbase + OG_SH2 + threadIdx.x * 16, h0.x, h0.y, h0.z, h0.w);
      sts_f32x4(sbase + OG_SH2 + 2048 + threadIdx.x * 16, h1.x, h1.y, h1.z, h1.w);
      __syncwarp();
      if (lane == 0) mbar_arrive(bar_h2);
      TL_MARK2(12, lane == 0);
      if (bid >> 6) h0 = h1;
      float v[8], wr[8];
      unpack8(make_uint4(__float_as_uint(h0.x), __float_as_uint(h0.y), __float_as_uint(h0.z), __float_as_uint(h0.w)), v); unpack8(wrv, wr);
      float r = 0.f;
      #pragma unroll
      for (int i = 0; i < 8; i++) r = fmaf(v[i], wr[i], r);
      #pragma unroll
      for (int o = 16; o > 0; o >>= 1) r += __shfl_xor_sync(0xffffffffu, r, o);
      if (lane == 0) sts_f32(sbase + OG_SMISC + 192 + wi * 4, r);
    }
    mbar_wait(bar_out, 0);
    {
      const uint2 cg = lds_u32x2(sbase + OG_SMISC + 96);
      #pragma unroll
      for (int i = 0; i < 4; i++) {
        const int r = (i < 2 ? cg.x : cg.y) * 16 + (i & 1) * 8 + (threadIdx.x >> 4), ch = threadIdx.x & 15;
        if (m0 + r != sel0 && m0 + r != sel1)
          *reinterpret_cast<uint4*>(out + (size_t)(m0 + r) * T_D + n0 + ch * 8) =
              lds_u32x4(sbase + OG_OSLOT + (ch >> 3) * 16384 + r * 128 + (((ch & 7) ^ (r & 7)) << 4));
      }
    }
    if (bid == 0 && threadIdx.x < 68) *reinterpret_cast<uint4*>(g_hcnt + 32 * (threadIdx.x >> 2) + 4 * (threadIdx.x & 3)) = make_uint4(0u, 0u, 0u, 0u);
    if (threadIdx.x < 64) g_modpart[bid * 64 + threadIdx.x] = 0.f;
    {
      const int tk = bid >> 6, c0 = (bid & 63) * 16;
      const uint32_t gb2 = *reinterpret_cast<const uint32_t*>(g_col + (c0 >> 7) * 1536 + 512 + 768 + ((c0 & 127) + (threadIdx.x & 14)) * 2);
      const uint32_t* xp = reinterpret_cast<const uint32_t*>(g_cand + (tk ? sel.w : sel.z) * 256) + ((c0 + (threadIdx.x & 14)) >> 1);
      uint32_t x2 = 0u;
      #pragma unroll 1
      for (unsigned int spin = 0; spin < (1u << 20) && __any_sync(0xffffffffu, x2 == 0u); spin++) asm volatile("ld.relaxed.gpu.global.u32 %0, [%1];" : "=r"(x2) : "l"(xp) : "memory");
      const float* src = g_ypart + (size_t)((threadIdx.x >> 2) * 2 + tk) * T_D + c0 + (threadIdx.x & 3) * 4;
      const bool four = threadIdx.x < (OG_MOE - 96) * 4;
      if (threadIdx.x == 0) hint_wait(CNT_Y, (uint32_t)(OG_MOE - Y_SLACK));
      named_bar_sync(10, 128);
      float4 p0, p1, p2, p3;
      #pragma unroll 1
      for (unsigned int spin = 0; spin < (1u << 20); spin++) {
        p0 = ld_tagged4(src); p1 = ld_tagged4(src + 64 * T_D); p2 = ld_tagged4(src + 128 * T_D); p3 = ld_tagged4(four ? src + 192 * T_D : src);
        if (__all_sync(0xffffffffu, tagged4(p0) & tagged4(p1) & tagged4(p2) & tagged4(p3))) break;
      }
      if (four) { p2.x += p3.x; p2.y += p3.y; p2.z += p3.z; p2.w += p3.w; }
      p0.x = (p0.x + p1.x) + p2.x; p0.y = (p0.y + p1.y) + p2.y; p0.z = (p0.z + p1.z) + p2.z; p0.w = (p0.w + p1.w) + p2.w;
      #pragma unroll
      for (int o = 4; o <= 16; o <<= 1) {
        p0.x += __shfl_xor_sync(0xffffffffu, p0.x, o); p0.y += __shfl_xor_sync(0xffffffffu, p0.y, o);
        p0.z += __shfl_xor_sync(0xffffffffu, p0.z, o); p0.w += __shfl_xor_sync(0xffffffffu, p0.w, o);
      }
      if (lane < 4) sts_f32x4(sbase + OG_SFIN + (threadIdx.x >> 5) * 64 + lane * 16, p0.x, p0.y, p0.z, p0.w);
      named_bar_sync(10, 128);
      TL_MARK2(21, threadIdx.x == 0);
      if (threadIdx.x < 16) {
        const uint32_t ya = sbase + OG_SFIN + threadIdx.x * 4, rp = sbase + OG_SMISC + 192;
        float y = (lds_f32(ya) + lds_f32(ya + 64)) + (lds_f32(ya + 128) + lds_f32(ya + 192));
        const float r = rbf((lds_f32(rp) + lds_f32(rp + 4)) + (lds_f32(rp + 8) + lds_f32(rp + 12)));
        const float rs = rbf(sigmoid_f(r));
        const uint32_t h2p = lds_u32(sbase + OG_SH2 + tk * 2048 + (c0 + (threadIdx.x & 14)) * 2);
        const float fh = (lane & 1) ? bfhi(h2p) : bflo(h2p);
        y = rbf(y);
        y = rbf(y * rs);
        const float upd = rbf(rbf(fh * 0.0f) + y);
        out[(size_t)(tk ? sel1 : sel0) * T_D + c0 + threadIdx.x] =
            __float2bfloat16_rn(((lane & 1) ? bfhi(x2) : bflo(x2)) + rbf(((lane & 1) ? bfhi(gb2) : bflo(gb2)) * rbf(fh + upd)));
      }
    }
    if (threadIdx.x == 0) XT(11);
    TL_END(4, threadIdx.x == 0);
}

__device__ __forceinline__ void load_pre(uint4* pre, uint32_t sbase, uint32_t buf, int t2) {
  mbar_wait(sbase + AT_SBAR + 272, 0);
  #pragma unroll
  for (int i = 0; i < 8; i++) pre[i] = lds_u32x4(sbase + buf + i * 4096 + t2 * 16);
}
__device__ __forceinline__ void tail_consumer(uint32_t bid, uint32_t sbase, const CUtensorMap* tmOut, const uint4 (&pre)[8], int cwg, const bf16* __restrict__ w_gate, const bf16* __restrict__ w_up) {
    const uint32_t c0 = clock_lo();
    mbar_wait(sbase + AT_SBAR + 320, 0);
    const uint2 td = lds_u32x2(sbase + AT_SBAR + 408);
    const int tb = __shfl_sync(0xffffffffu, (int)td.x, 0);
    TAIL_SETUP
    const int tid = threadIdx.x & 127, t2 = threadIdx.x - 128;
    const int warp = tid >> 5, lane = tid & 31, w8 = t2 >> 5;
    const uint32_t dbase = (sbase & 0x3FFFFu) >> 4;
    const uint32_t a_base = dbase + ((cwg * 8192) >> 4) + (1u << 16);
    const uint32_t b_base = dbase + (16384 >> 4) + (512u << 16);
    TL_MARK2(25, threadIdx.x == 128);
    const uint64_t pol = policy_evict_first();
    const bf16* pw = ((lane & 16) ? w_up : w_gate) + (size_t)(w8 * 128 + (lane & 3) * 4) * T_F + (has_moe ? bid : 0) * 32 + ((lane >> 2) & 3) * 8;
    uint4 wv[32];
    float acc[64];
    #pragma unroll
    for (int i = 0; i < 8; i++) {
      acc[8 * i] = bflo(pre[i].x); acc[8 * i + 1] = bfhi(pre[i].x); acc[8 * i + 2] = bflo(pre[i].y); acc[8 * i + 3] = bfhi(pre[i].y);
      acc[8 * i + 4] = bflo(pre[i].z); acc[8 * i + 5] = bfhi(pre[i].z); acc[8 * i + 6] = bflo(pre[i].w); acc[8 * i + 7] = bfhi(pre[i].w);
    }
    if (lane == 0) mbar_arrive(bar_full + 304);
    while (__any_sync(0xffffffffu, clock_lo() - c0 < td.y)) {}
    uint32_t stage = OG_POS % OG_ST;
    {
      uint32_t phase = (OG_POS / OG_ST) & 1, prev = 12;
      int kb = 0;
      #pragma unroll
      for (int g = 0; g <= OG_NG; g++) {
        const int end = g == OG_NG ? 64 - og_pre(tb) : LD_FIRST + g * OG_GRP + LD_STAG * cwg;
        #pragma unroll 1
        do {
          mbar_wait(bar_full + 8 * stage, phase);
          if (OG_STAG > 0 && g == OG_NG && cwg == 1 && kb == end - OG_STAG) named_bar_sync(7, 256);
          const uint32_t a_lo = a_base + stage * (OG_STAGE >> 4), b_lo = b_base + stage * (OG_STAGE >> 4);
          wgmma_fence();
          wgmma_m64n128k16_ss_tb<0, 0>(acc, a_lo, b_lo, 1);
          wgmma_m64n128k16_ss_tb<2, 128>(acc, a_lo, b_lo, 1);
          wgmma_m64n128k16_ss_tb<4, 256>(acc, a_lo, b_lo, 1);
          wgmma_m64n128k16_ss_tb<6, 384>(acc, a_lo, b_lo, 1);
          wgmma_commit();
          if (OG_STAG > 0 && g == OG_NG && cwg == 0 && kb == end - 1) named_bar_arrive(7, 256);
          wgmma_wait<1>();
          if (tid == 0) mbar_arrive(bar_empty + 8 * prev);
          prev = stage;
          if (++stage == OG_ST) { stage = 0; phase ^= 1; }
        } while (++kb < end);
        #pragma unroll
        for (int j = 4 * g; j < 4 * g + 4 && j < 32; j++) wv[j] = ldg_stream_v4(pw + (size_t)(16 * (j >> 2) + (j & 3)) * T_F, pol);
      }
    }
    mbar_wait(bar_col, 0);
    if (__builtin_expect(!has_moe, 0)) {
      load_pre(wv, sbase, AT_SQ, t2);
    }
    wgmma_wait<0>();
    fence_regs(acc);
    if (__builtin_expect(!has_moe, 0)) {
      #pragma unroll
      for (int i = 0; i < 8; i++) {
        acc[8 * i] += bflo(wv[i].x); acc[8 * i + 1] += bfhi(wv[i].x); acc[8 * i + 2] += bflo(wv[i].y); acc[8 * i + 3] += bfhi(wv[i].y);
        acc[8 * i + 4] += bflo(wv[i].z); acc[8 * i + 5] += bfhi(wv[i].z); acc[8 * i + 6] += bflo(wv[i].w); acc[8 * i + 7] += bfhi(wv[i].w);
      }
    }
    if (tid == 0) mbar_arrive(bar_end);
    TL_MARK2(9, lane == 0);
    const int q2 = 2 * (lane & 3);
    const uint32_t frag = (64 * cwg + 16 * warp + (lane & 7) + 8 * ((lane >> 3) & 1)) * 128;
    const int fsw = lane & 7, fhi = lane >> 4;
    {
      float dl[4] = {0.f, 0.f, 0.f, 0.f}, da[4] = {0.f, 0.f, 0.f, 0.f}, db[4] = {0.f, 0.f, 0.f, 0.f};
      const uint32_t tb = sbase + OG_SCOL + (lane & 8) * 32 + (lane & 3) * 8, g = lane >> 2;
      const uint32_t msk = (g == 1 || g == 2) ? 0xffffffffu : 0u, one = g == 0 ? 0x3F803F80u : 0u;
      #pragma unroll
      for (int J = 0; J < 16; J += 2) {
        const uint32_t ad = sbase + OG_XSLOT + (J >> 3) * 16384 + frag + ((((J & 7) + fhi) ^ fsw) << 4);
        uint32_t xr[4];
        ldmatrix_x4(ad, xr[0], xr[1], xr[2], xr[3]);
        const uint2 cw = lds_u32x2(tb + J * 16);
        #pragma unroll
        for (int h = 0; h < 2; h++) {
          const uint32_t ga = lds_u32(sbase + OG_SCOL + 512 + (8 * (J + h) + q2) * 2);
          xr[2 * h] = badd2(xr[2 * h], bmul2(ga, pack_bf16(acc[4 * (J + h)], acc[4 * (J + h) + 1])));
          xr[2 * h + 1] = badd2(xr[2 * h + 1], bmul2(ga, pack_bf16(acc[4 * (J + h) + 2], acc[4 * (J + h) + 3])));
        }
        stmatrix_x4(ad, xr[0], xr[1], xr[2], xr[3]);
        mma_bf16(dl, xr[0], xr[1], xr[2], xr[3], (cw.x & msk) | one, (cw.y & msk) | one);
        mma_bf16(da, xr[0], xr[1], xr[2], xr[3], xr[0], xr[2]);
        mma_bf16(db, xr[0], xr[1], xr[2], xr[3], xr[1], xr[3]);
      }
      {
        const int dsrc = (lane & ~3) + (g >> 1);
        const float qa = __shfl_sync(0xffffffffu, (g & 1) ? da[1] : da[0], dsrc), qb = __shfl_sync(0xffffffffu, (g & 1) ? db[3] : db[2], dsrc);
        const float e0 = __shfl_xor_sync(0xffffffffu, (lane & 1) ? dl[0] : dl[2], 1), e1 = __shfl_xor_sync(0xffffffffu, dl[3], 1);
        if ((lane & 3) < 2) {
          const bool hi = lane & 1;
          st_tagged4(reinterpret_cast<float*>(g_part1 + ((mt * 8 + w8) * 8 + nt) * 16 + g + (hi ? 8 : 0)),
                     hi ? e0 : dl[0], hi ? qb : qa, hi ? e1 + dl[2] : dl[1] + e0, 1.0f);
        }
      }
    }
    TL_MARK2(10, lane == 0);
    uint4 wd[16];
    if (has_moe) mbar_wait(bar_wd, 0);
    #pragma unroll
    for (int i = 0; i < 16; i++) wd[i] = lds_u32x4(sbase + (cwg ? stage * OG_STAGE : OG_SWD) + warp * 8192 + (i >> 3) * 4096 + (i & 6) * 512 + (i & 1) * 128 + (lane & 3) * 256 + (((lane >> 2) ^ (2 * (lane & 3) + (i & 1))) << 4));
    {
      const float* src = reinterpret_cast<const float*>(g_part1 + ((mt * 8 + w8) * 8 + (lane & 1) * 4) * 16 + (lane >> 1));
      float4 v, v1, v2, v3;
      #pragma unroll 1
      for (unsigned int spin = 0; spin < (1u << 22); spin++) {
        v = ld_tagged4(src); v1 = ld_tagged4(src + 64); v2 = ld_tagged4(src + 128); v3 = ld_tagged4(src + 192);
        if (__all_sync(0xffffffffu, tagged4(v) & tagged4(v1) & tagged4(v2) & tagged4(v3))) break;
        __nanosleep(100);
      }
      __syncwarp();
      TL_MARK2(26, lane == 0);
      v.x = (v.x + v1.x) + (v2.x + v3.x); v.y = (v.y + v1.y) + (v2.y + v3.y); v.z = (v.z + v1.z) + (v2.z + v3.z);
      v.x += __shfl_xor_sync(0xffffffffu, v.x, 1); v.y += __shfl_xor_sync(0xffffffffu, v.y, 1); v.z += __shfl_xor_sync(0xffffffffu, v.z, 1);
      const float mean = v.x * (1.0f / T_D);
      const float var = fmaxf(fmaf(-mean, mean, v.y * (1.0f / T_D)), 0.f);
      const uint32_t mb2 = pack_bf16(mean, mean);
      const float inv = rcp_approx(rbf(sqrt_approx(rbf(rbf(var) + 1e-05f))));
      {
        const float2 sc = lds_f32x2(sbase + OG_SMISC);
        const uint32_t key = rank_key(rbf(fmaf(fmaf(-bflo(mb2), sc.x, v.z), inv, sc.y)), m0 + 16 * w8 + (lane >> 1));
        mbar_wait(bar_end, 0);
        if (lane & 1) sts_u32(sbase + OG_SSTAT + 1024 + (16 * w8 + (lane >> 1)) * 4, key);
        else sts_u32x2(sbase + OG_SSTAT + (16 * w8 + (lane >> 1)) * 8, mb2, __float_as_uint(inv));
        __syncwarp();
        if (lane == 0) mbar_arrive(bar_key);
      }
      const uint32_t ih = pack_bf16(inv, inv), il = pack_bf16(inv - bflo(ih), inv - bflo(ih));
      const uint32_t mba = __shfl_sync(0xffffffffu, mb2, 2 * (lane >> 2)), mbb = __shfl_sync(0xffffffffu, mb2, 2 * (lane >> 2) + 16);
      const uint32_t iha = __shfl_sync(0xffffffffu, ih, 2 * (lane >> 2)), ihb = __shfl_sync(0xffffffffu, ih, 2 * (lane >> 2) + 16);
      const uint32_t ila = __shfl_sync(0xffffffffu, il, 2 * (lane >> 2)), ilb = __shfl_sync(0xffffffffu, il, 2 * (lane >> 2) + 16);
      #pragma unroll 2
      for (int J = 0; J < 16; J += 2) {
        const uint32_t off = (J >> 3) * 16384 + frag + ((((J & 7) + fhi) ^ fsw) << 4);
        uint32_t xr[4];
        ldmatrix_x4(sbase + OG_XSLOT + off, xr[0], xr[1], xr[2], xr[3]);
        #pragma unroll
        for (int h = 0; h < 2; h++) {
          const uint32_t ca = sbase + OG_SCOL + 512 + (8 * (J + h) + q2) * 2;
          const uint32_t c1 = lds_u32(ca + 256), sh = lds_u32(ca + 512), gb = lds_u32(ca + 768);
          xr[2 * h] = out2(xr[2 * h], mba, iha, ila, c1, sh, gb);
          xr[2 * h + 1] = out2(xr[2 * h + 1], mbb, ihb, ilb, c1, sh, gb);
        }
        stmatrix_x4(sbase + OG_OSLOT + off, xr[0], xr[1], xr[2], xr[3]);
      }
      fence_proxy_async();
      mbar_wait(bar_full + 352, 0);
      const uint2 cg = lds_u32x2(sbase + OG_SMISC + 96);
      __syncwarp();
      if (elect_one()) {
        mbar_arrive(bar_out);
        if (cg.x != w8 && cg.y != w8) {
          asm volatile("cp.async.bulk.tensor.2d.global.shared::cta.bulk_group [%0, {%2, %3}], [%1];" :: "l"(tmOut), "r"(sbase + OG_OSLOT + w8 * 2048), "r"(n0), "r"(m0 + 16 * w8) : "memory");
          asm volatile("cp.async.bulk.tensor.2d.global.shared::cta.bulk_group [%0, {%2, %3}], [%1];" :: "l"(tmOut), "r"(sbase + OG_OSLOT + 16384 + w8 * 2048), "r"(n0 + 64), "r"(m0 + 16 * w8) : "memory");
          bulk_commit();
        }
      }
      TL_MARK2(24, lane == 0);
    }
    if (has_moe) mbar_wait(bar_h2, 0);
    TL_MARK2(13, lane == 0);
    if (has_moe) {
      const GemvSel sel = gemv_sel(lane);
      {
        float d[4][4];
        #pragma unroll
        for (int c = 0; c < 4; c++) { d[c][0] = 0.f; d[c][1] = 0.f; d[c][2] = 0.f; d[c][3] = 0.f; }
        #pragma unroll
        for (int st = 0; st < 8; st++) {
          const uint2 hb = lds_u32x2(sbase + OG_SH2 + ((lane >> 2) & 1) * 2048 + (w8 * 128 + st * 16 + (lane & 3) * 4) * 2);
          #pragma unroll
          for (int j = 0; j < 4; j++) mma_bf16(d[j], wv[4 * st + j].x, wv[4 * st + j].y, wv[4 * st + j].z, wv[4 * st + j].w, GEMV_B0(j, hb, sel), GEMV_B1(j, hb, sel));
        }
        #pragma unroll
        for (int e = 0; e < 4; e++) d[0][e] = (d[0][e] + d[1][e]) + (d[2][e] + d[3][e]);
        const float4 r = gemv_out(d[0], lane);
        sts_f32x4(sbase + OG_SRED + w8 * 512 + (((lane >> 4) * 2 + (lane & 1)) * 32 + ((lane >> 2) & 3) * 8 + (lane & 2) * 2) * 4, r.x, r.y, r.z, r.w);
      }
      named_bar_sync(9, 256);
      if (t2 < 64) {
        float gp[8], up[8];
        #pragma unroll
        for (int w = 0; w < 8; w++) { gp[w] = lds_f32(sbase + OG_SRED + w * 512 + t2 * 4); up[w] = lds_f32(sbase + OG_SRED + w * 512 + 256 + t2 * 4); }
        const float gs = ((gp[0] + gp[1]) + (gp[2] + gp[3])) + ((gp[4] + gp[5]) + (gp[6] + gp[7]));
        const float us = ((up[0] + up[1]) + (up[2] + up[3])) + ((up[4] + up[5]) + (up[6] + up[7]));
        asm volatile("st.shared.u16 [%0], %1;" :: "r"(sbase + OG_SGU + ((t2 & ~15) + ((t2 >> 1) & 3) * 4 + ((t2 >> 3) & 1) * 2 + (t2 & 1)) * 2), "h"((uint16_t)pack_bf16(silu_bf(rbf(gs)) * rbf(us), 0.f)) : "memory");
      }
      named_bar_sync(9, 256);
      TL_MARK2(20, threadIdx.x == 128);
      float d[4][4];
      #pragma unroll
      for (int c = 0; c < 4; c++) { d[c][0] = 0.f; d[c][1] = 0.f; d[c][2] = 0.f; d[c][3] = 0.f; }
      #pragma unroll
      for (int st = 0; st < 2; st++) {
        const uint2 g = lds_u32x2(sbase + OG_SGU + ((lane >> 2) & 1) * 64 + st * 32 + (lane & 3) * 8);
        #pragma unroll
        for (int j = 0; j < 4; j++) {
          const uint32_t b0 = GEMV_B0(j, g, sel), b1 = GEMV_B1(j, g, sel);
          mma_bf16(d[j & 1], wd[4 * st + j].x, wd[4 * st + j].y, wd[4 * st + j].z, wd[4 * st + j].w, b0, b1);
          mma_bf16(d[2 + (j & 1)], wd[8 + 4 * st + j].x, wd[8 + 4 * st + j].y, wd[8 + 4 * st + j].z, wd[8 + 4 * st + j].w, b0, b1);
        }
      }
      #pragma unroll
      for (int e = 0; e < 4; e++) { d[0][e] += d[1][e]; d[2][e] += d[3][e]; }
      const float4 y0 = gemv_out(d[0], lane), y1 = gemv_out(d[2], lane);
      float* yp = g_ypart + (size_t)(bid * 2 + (lane & 1)) * T_D + w8 * 128 + (lane >> 2) * 8 + (lane & 2) * 2;
      st_tagged4(yp, y0.x, y0.y, y0.z, y0.w);
      st_tagged4(yp + 64, y1.x, y1.y, y1.z, y1.w);
      named_bar_sync(9, 256);
      if (t2 == 0) hint_arrive(CNT_Y);
    }
    bulk_wait_read<0>();
    TL_MARK2(14, threadIdx.x == 128);
    TL_CLK(4, 1, threadIdx.x == 128);
}

__device__ __forceinline__ int help_njobs(uint32_t bid) { return bid < 128 ? OG_JOBS : 16 - OG_JOBS; }
__device__ __forceinline__ int help_job(uint32_t bid, int i) { return (i < OG_JOBS ? 16 * i + (bid >> 7) * 2 : 112 + (i - OG_JOBS) * 2) + (bid & 3) * 4; }
__device__ __noinline__ void store_warp(uint32_t bid, uint32_t sbase, const CUtensorMap* tmO, int item0, int n_items) {
  if (elect_one()) {
    const uint32_t bars = sbase + AT_SBAR, b_q0 = bars + 80, b_ob = bars + 96, b_ordy = bars + 104, b_acq = bars + 264;
    const unsigned int* cnt = g_hcnt + 32 * (1 + OG_MT(124)) + 2;
    #pragma unroll 1
    for (int q = 0; q < 4 * n_items; q++) {
      const int item = item0 + (q >> 2) * 128, h = (q >> 1) & 1, w = q & 1;
      const bool last = (q >> 2) == n_items - 1;
      if (q == 4 * n_items - 4) { mbar_wait(bars + 288, 0); red_release_add(&g_hcnt[1], 1u); }
      mbar_wait(b_ordy + 8 * (q & 3), q >> 2);
      store_o(tmO, (h ? (last ? sbase + AT_SQ + 32768 : sbase + 2 * 32768) : sbase + AT_SQ) + w * 8192, (item >> 4) * 2 + h, (item & 15) * 128 + w * 64);
      if (w) {
        bulk_wait_read<0>();
        mbar_arrive(h ? b_ob : b_q0);
        bulk_wait<0>();
        fence_proxy_async_global();
        asm volatile("fence.acq_rel.gpu;" ::: "memory");
        hint_arrive(&g_hcnt[32 * (1 + (item & 15)) + 2 + (item >> 7)]);
        if (!h && item < 128) hint_arrive(&g_hcnt[2]);
        if (q == 5) { const int tb = tail_tile(sbase); cnt = g_hcnt + 32 * (1 + OG_MT(tb)) + 2; spin_until(cnt, 16u); mbar_arrive(b_acq); }
      }
    }
    if (n_items == 1) {
      #pragma unroll 1
      for (int i = 0; i < help_njobs(bid); i++) {
        mbar_wait(b_acq + 16, i & 1);
        TL_MARK2(23, i == OG_JOBS - 1);
        red_release_add(&g_hcnt[32 * (1 + (help_job(bid, i) >> 3)) + 4 + ((help_job(bid, i) >> 1) & 3)], 1u);
        TL_MARK2(4, i == OG_JOBS - 1);
        if (i == PRE_X - 1) { spin_until(&g_hcnt[1], 132u); mbar_arrive(b_acq + 32); }
      }
    }
    if (bid < 128) {
      if (n_items == 1) { spin_until(cnt, 16u); mbar_arrive(b_acq); }
      spin_until(&g_hcnt[0], 128u); spin_until(cnt + 1, 16u); mbar_arrive(b_acq + 80);
    }
  }
}

struct Roles { uint8_t of_sm[132]; };
#define GMAP 1
__global__ void __launch_bounds__(384, 1)
fused_kernel(const __grid_constant__ CUtensorMap tmH, const __grid_constant__ CUtensorMap tmW, const __grid_constant__ CUtensorMap tmK,
            const __grid_constant__ CUtensorMap tmV, const __grid_constant__ CUtensorMap tmO, const __grid_constant__ CUtensorMap tmOl, const __grid_constant__ CUtensorMap tmWo,
            const __grid_constant__ CUtensorMap tmD, const __grid_constant__ CUtensorMap tmOut, const __grid_constant__ CUtensorMap tmM, const __grid_constant__ Roles roles, uint32_t zero,
            const uint8_t* __restrict__ pf_wo, const bf16* __restrict__ kc, const bf16* __restrict__ vc,
            const bf16* __restrict__ x, const bf16* __restrict__ cvec, const bf16* __restrict__ w_mod, const bf16* __restrict__ w_r,
            const bf16* __restrict__ w_gate, const bf16* __restrict__ w_up, const bf16* __restrict__ w_down, bf16* __restrict__ out)
{
  uint32_t bid;
  asm volatile("mov.u32 %0, %%smid;" : "=r"(bid));
  bid = __shfl_sync(0xffffffffu, GMAP ? (uint32_t)roles.of_sm[bid] : blockIdx.x, 0);
  extern __shared__ __align__(1024) uint8_t smem_raw[];
  const uint32_t sbase = smem_u32(smem_raw);
  const uint32_t bars = sbase + AT_SBAR;
  const uint32_t b_full = bars, b_empty = bars + 40;
  const uint32_t b_q0 = bars + 80, b_q1 = bars + 88;
  const uint32_t b_ob = bars + 96;
  const uint32_t b_ordy = bars + 104;
  const uint32_t b_pin = bars + 136;
  const uint32_t b_head = bars + 144;
  const uint32_t b_go = bars + 152;
  const uint32_t b_x = bars + 160;
  const int wg = __shfl_sync(0xffffffffu, threadIdx.x >> 7, 0);
  const bool single = bid >= AT_NFULL;
  const int item0 = __shfl_sync(0xffffffffu, bid < 128 ? (int)bid : (int)bid + 124, 0), n_items = __shfl_sync(0xffffffffu, single ? 1 : 2, 0);
  TL_START(3);
  if (threadIdx.x == 0) {
    if (sbase & 1023u) __trap();
    for (int i = 0; i < 5; i++) { mbar_init(b_full + 8 * i, 1); mbar_init(b_empty + 8 * i, 2); }
    mbar_init(b_q0, 1); mbar_init(b_q1, 8); mbar_init(b_ob, 1);
    for (int i = 0; i < 4; i++) mbar_init(b_ordy + 8 * i, 4);
    mbar_init(b_pin, 1); mbar_init(b_head, bid < 128 ? 8 : 1); mbar_init(b_go, 1); mbar_init(b_x, 1);
    mbar_init(bars + 168, 2); mbar_init(bars + 176, 1); mbar_init(bars + 184, 8); mbar_init(bars + 192, 2);
    mbar_init(bars + 200, 8); mbar_init(bars + 208, 4); mbar_init(bars + 216, 1); mbar_init(bars + 264, 1); mbar_init(bars + 272, 1); mbar_init(bars + 280, 8); mbar_init(bars + 288, 1); mbar_init(bars + 296, 1); mbar_init(bars + 304, 8); mbar_init(bars + 312, 1); mbar_init(bars + 320, 1); mbar_init(bars + 328, 1); mbar_init(bars + 336, 1); mbar_init(bars + 344, 1); mbar_init(bars + 352, 1);
    sts_u32(bars + 400, bid);
    fence_mbar_init();
  }

  if (wg == 0) {
    reg_dealloc<AT_PREG>();
    if (threadIdx.x < 32) { __syncwarp(); named_bar_arrive(6, 384); }
    if (threadIdx.x >= 64) {
      named_bar_sync(6, 384);
      if (bid < 128) {
        named_bar_sync(threadIdx.x >= 96 ? 8 : 9, 288);
        if ((threadIdx.x & 31) == 0) red_release_add(&g_hcnt[32 * (1 + (bid >> 3)) + (threadIdx.x >= 96)], 1u);
        TL_MARK2(11, threadIdx.x == 64);
      }
      if (bid < 128) {
        mbar_wait(MOD_AT, 0);
        mod_rest(bid, sbase + OG_SCOL, b_q1, threadIdx.x - 64, cvec, w_mod, w_r);
      }
    } else if (threadIdx.x >= 32) {
      named_bar_sync(6, 384);
      store_warp(bid, sbase, &tmO, item0, n_items);
      __syncwarp();
    } else {
     if (elect_one()) {
      const uint64_t pol = policy_evict_first();
      if (bid < 128) {
        mbar_expect_tx(b_x, 32768);
        if (X_DLY) { const uint32_t c0 = clock_lo(); while (clock_lo() - c0 < X_DLY) {} }
        bulk_load_hint(sbase + 4 * 32768, x + (size_t)bid * 16 * T_D, 32768, b_x, pol);
      }
      prefetch_tmap(&tmW); prefetch_tmap(&tmM); prefetch_tmap(&tmH); prefetch_tmap(&tmWo); prefetch_tmap(&tmOl);
      {
        const uint32_t c0 = clock_lo();
        while (clock_lo() - c0 < W_DLY) {}
        if (bid < 128 && (bid & 15) >= 4 * H_SPLIT) {
          mbar_expect_tx(bars + 328, 32768);
          tma_load_2d_hint(sbase + 3 * 32768, &tmM, (bid & 31) * 64, (bid >> 5) * 256, bars + 328, pol);
        }
        while (clock_lo() - c0 < W_DLY + W_FIRST) {}
      }
      uint32_t slot = 0, ph = 1;
      #pragma unroll 1
      for (int it = 0; it < n_items; it++) {
        const int item = item0 + it * 128, hp = item >> 4, qt = item & 15;
        const bool first = it == 0;
        #pragma unroll 1
        for (int j = 0; j < T_D / 64; j++) {
          const uint32_t sl = ring_slot(qp_pos(j, it)), fb = b_full + 8 * sl;
          mbar_wait(b_empty + 8 * sl, ring_par(qp_pos(j, it)) ^ ((j >> 2) & 1) ^ 1);
          if (first && j == 3) mbar_wait(b_head, 0);
          mbar_expect_tx(fb, 49152);
          tma_load_3d_hint(sbase + sl * 32768, &tmW, j * 64, hp * 4, fb, pol);
          if (first && j < PRE_B) {
            if (j == PRE_B - 1) {
              spin_until(&g_hcnt[32 * (1 + qt)], 8u);
              TL_MARK2(16, true);
              fence_proxy_async_global();
              #pragma unroll 1
              for (int i = 0; i < PRE_B; i++) tma_load_2d(sbase + AT_SQ + i * 16384, &tmH, i * 64, qt * 128, b_full + 8 * i);
              mbar_arrive(b_go);
            }
          } else {
            if (first && j == 4 * H_SPLIT) { spin_until(&g_hcnt[32 * (1 + qt) + 1], 8u); fence_proxy_async_global(); }
            if (!first && (j == 0 || j == 2)) mbar_wait(j ? b_q1 : b_q0, 0);
            tma_load_2d_hint(sbase + AT_SQ + (j & 3) * 16384, &tmH, j * 64, qt * 128, fb, first ? pol_normal() : pol);
          }
        }
        #pragma unroll 1
        for (int j = 0; j < 4 * AT_NBLK; j++) {
          const bool isv = (j > 0 && !(j & 1)) || j == 4 * AT_NBLK - 1;
          const int row = hp * 2 * T_SEQ + (isv ? (j - 1) >> 1 : (j + 1) >> 1) * 128;
          const uint32_t fb = b_full + 8 * slot;
          mbar_wait(b_empty + 8 * slot, ph);
          if (!first && j == 3) mbar_wait(b_ob, 0);
          if (j == 4 && it == n_items - 1) mbar_arrive(bars + 288);
          if ((j == AL_P || j == RK_P) && it == 1) mbar_arrive(bars + 312);
          mbar_expect_tx(fb, 32768);
          tma_load_3d_hint(sbase + slot * 32768, isv ? &tmV : &tmK, row, 0, fb, pol);
          if (it == 1 && isv && j >= 2 * WO_LATE && j < 2 * WO_LATE + 32 && bid < OG_NKB)
            l2_prefetch_bulk(pf_wo + (size_t)own_kb(bid) * 131072 + ((j >> 1) - WO_LATE) * 8192, 8192);
          if (++slot == 5) { slot = 0; ph ^= 1; }
        }
      }
      if (__builtin_expect(single, 0)) {
        spin_until(&g_hcnt[2], 128u);
        fence_proxy_async_global();
        const int nj = OG_HSUM + (help_njobs(bid) - OG_JOBS) * OG_PRE2;
        int ji = 0, job = help_job(bid, 0), kk = 0;
        #pragma unroll 1
        for (int j = 0; j < nj; j++) {
          const uint32_t sl = ring_slot(qp_pos(j, 1)), fb = b_full + 8 * sl;
          mbar_wait(b_empty + 8 * sl, ring_par(qp_pos(j, 1)) ^ ((j >> 2) & 1) ^ 1);
          mbar_expect_tx(fb, 49152);
          tma_load_3d_hint(sbase + sl * 32768, &tmWo, pre_kb(kk) * 64, OG_NT(job) * 2, fb, pol_normal());
          tma_load_3d_hint(sbase + sl * 32768 + 16384, &tmWo, pre_kb(kk) * 64, OG_NT(job) * 2 + 2, fb, pol_normal());
          if (j == 0 || j == 2) mbar_wait(j ? b_ob : b_q0, 0);
          tma_load_2d_hint(sbase + AT_SQ + (j & 3) * 16384, &tmOl, pre_kb(kk) * 64, OG_MT(job) * 128, fb, pol);
          if (++kk == og_pre(job)) { kk = 0; job = help_job(bid, ++ji); }
        }
      }
      if (bid < 128) {
        if (single) mbar_wait(b_x, 1);
        tail_producer(bid, sbase, 0, pol, &tmOl, &tmWo, &tmD);
      }
     }
    }
    named_bar_sync(12 + (threadIdx.x >> 5), 32);
    if (bid < 128) tail_exchange(bid, sbase, w_down, w_r, x, out);
  } else {
    if (bid < 128) head_phase(bid, sbase + AT_SQ + 49152, sbase + 4 * 32768, b_x, b_go, b_head, threadIdx.x - 128, zero, cvec, w_mod);
    else { named_bar_sync(6, 384); if (threadIdx.x == 128) mbar_arrive(b_head); }
    TL_MARK2(0, threadIdx.x == 128);
    reg_alloc<AT_CREG>();
    const int cwg = wg - 1;
    const int tid = threadIdx.x & 127;
    const int warp = tid >> 5, lane = tid & 31;
    const uint32_t dbase = (sbase & 0x3FFFFu) >> 4;
    const uint32_t k_base = dbase + (1u << 16);
    const uint32_t v_base = dbase + (1024u << 16);
    const uint32_t w_base = dbase + (512u << 16);
    const uint32_t q_lo = dbase + ((AT_SQ + cwg * 8192) >> 4) + (1u << 16);
    const uint32_t frag = cwg * 8192 + (16 * warp + (lane & 7) + 8 * ((lane >> 3) & 1)) * 128;
    if (cwg == 1) named_bar_arrive(1, 256);
    bool raw = false;
    uint4 pre[8];
    #pragma unroll 1
    for (int it = 0; it < n_items; it++) {
      const bool more = it + 1 < n_items;
      constexpr int nkb = T_D / 64;
      const int ta = __shfl_sync(0xffffffffu, 4 * it, 0);
      float acc[128];
      {
        FS(2 * it, 0);
        #pragma unroll
        for (int i = 0; i < 128; i++) asm volatile("" : "=f"(acc[i]));
        {
          const uint32_t slot = ring_slot(ta), b_lo = w_base + slot * 2048;
          mbar_wait(b_full + 8 * slot, ring_par(ta));
          wgmma_fence();
          wgmma_m64n256k16_ss_tb<0, 0>(acc, q_lo, b_lo, 0);
          wgmma_m64n256k16_ss_tb<2, 128>(acc, q_lo, b_lo, 1);
          wgmma_m64n256k16_ss_tb<4, 256>(acc, q_lo, b_lo, 1);
          wgmma_m64n256k16_ss_tb<6, 384>(acc, q_lo, b_lo, 1);
          wgmma_commit();
        }
        #pragma unroll 1
        for (int j = 1; j < nkb; j++) {
          const uint32_t slot = ring_slot(qp_pos(j, ta >> 2));
          mbar_wait(b_full + 8 * slot, ring_par(qp_pos(j, ta >> 2)) ^ ((j >> 2) & 1));
          if (QP_STAG > 0 && cwg == 1 && j == nkb - QP_STAG) named_bar_sync(7, 256);
          const uint32_t a_lo = q_lo + (j & 3) * 1024, b_lo = w_base + slot * 2048;
          wgmma_fence();
          wgmma_m64n256k16_ss_tb<0, 0>(acc, a_lo, b_lo, 1);
          wgmma_m64n256k16_ss_tb<2, 128>(acc, a_lo, b_lo, 1);
          wgmma_m64n256k16_ss_tb<4, 256>(acc, a_lo, b_lo, 1);
          wgmma_m64n256k16_ss_tb<6, 384>(acc, a_lo, b_lo, 1);
          wgmma_commit();
          if (QP_STAG > 0 && cwg == 0 && j == nkb - 1) named_bar_arrive(7, 256);
          if (j > 0) {
            wgmma_wait<1>();
            if (tid == 0) mbar_arrive(b_empty + 8 * ring_slot(qp_pos(j - 1, ta >> 2)));
          }
        }
        wgmma_wait<0>();
        fence_regs(acc);
        FS(2 * it, 1);
        TL_MARK2(29, threadIdx.x == 256 && it == 0);
        if (tid == 0) mbar_arrive(b_empty + 24);
      }
      float o[64], s[64];
      uint32_t p[32], q[32];
      #pragma unroll
      for (int i = 0; i < 32; i++) q[i] = pack_bf16(acc[2 * i] * AT_C, acc[2 * i + 1] * AT_C);
      zero_regs(s);
      const uint32_t sq = sbase + AT_SQ + cwg * 8192;
      float mc0, mc1, al0 = 1.0f, al1 = 1.0f, l0 = 0.f, l1 = 0.f, lp0 = 0.f, lp1 = 0.f;
      bool redo0 = false;
      FS(2 * it, 2);
      mbar_wait(b_full + 8 * ring_slot(ta), ring_par(ta));
      named_bar_sync(1 + cwg, 256);
      FS(2 * it, 3);
      issue_qk(s, q, k_base + ring_slot(ta) * 2048);
      pass_turn(cwg);
      bool ready = mbar_test(b_full + 8 * ring_slot(ta + 1), ring_par(ta + 1)) & mbar_test(b_full + 8 * ring_slot(ta + 2), ring_par(ta + 2));
      stage_q<16>(acc, AT_C, sbase + AT_SQ + frag, lane);
      wgmma_wait<0>();
      fence_regs(s);
      if (tid == 0) mbar_arrive(b_empty + 8 * ring_slot(ta));
      mc0 = 0.f; mc1 = 0.f;
      if (!raw) {
        raw = softmax_mode(s, mc0, mc1);
        if (__builtin_expect(!raw, 0)) softmax_sub(s, mc0, mc1);
      }
      softmax_exp<0, 64>(s);
      #pragma unroll
      for (int J = 0; J < 16; J += 2)
        stmatrix_x4(sbase + AT_SQ + frag + (J >> 3) * 16384 + ((((J & 7) + (lane >> 4)) ^ (lane & 7)) << 4), q[2 * J], q[2 * J + 1], q[2 * J + 2], q[2 * J + 3]);
      pack_p(p, s);
      zero_regs(o);
      FS(2 * it, 4);
      uint32_t ks = ring_slot(ta + 1), vs = ring_slot(ta + 2), kp = ring_par(ta + 1), vp = ring_par(ta + 2);
      auto finish_head = [&]() {
        FS(2 * it, 5);
        redo0 = finish_l(lp0, lp1);
        if (!redo0) stage_o(o, lp0, lp1, sbase + AT_SQ + frag, lane);
        FS(2 * it + 1, 4);
      };
      if (!ready) { mbar_wait(b_full + 8 * ks, kp); mbar_wait(b_full + 8 * vs, vp); }
      #pragma unroll 1
      for (int n = 1; n < 2 * AT_NBLK; n++) {
        named_bar_sync(1 + cwg, 256);
        issue_qk(s, q, k_base + ks * 2048);
        if (n == AT_NBLK + 1) finish_head();
        issue_pv(o, p, v_base + vs * 2048, (n & 15) != 1);
        pass_turn(cwg);
        wgmma_wait<1>();
        fence_regs(s);
        if (tid == 0) mbar_arrive(b_empty + 8 * ks);
        if (__builtin_expect(!raw || (uint32_t)(n - (AT_NBLK - 1)) <= 2u, 0)) {
          if (n == AT_NBLK + 1 && !redo0) {
            fence_proxy_async();
            __syncwarp();
            if (lane == 0) mbar_arrive(b_ordy + 8 * cwg);
          }
          if (n == AT_NBLK - 1) {
            #pragma unroll
            for (int J = 0; J < 16; J += 2)
              ldmatrix_x4(sbase + AT_SQ + 32768 + frag + (J >> 3) * 16384 + ((((J & 7) + (lane >> 4)) ^ (lane & 7)) << 4), q[2 * J], q[2 * J + 1], q[2 * J + 2], q[2 * J + 3]);
          }
          if (!raw) {
            const float m0 = mc0, m1 = mc1;
            const bool ok = softmax_mode(s, mc0, mc1);
            if (n == AT_NBLK) raw = ok;
            else {
              mc0 = mc0 - AT_HEAD > m0 ? mc0 : m0; mc1 = mc1 - AT_HEAD > m1 ? mc1 : m1;
              al0 = ex2_approx(m0 - mc0); al1 = ex2_approx(m1 - mc1);
            }
            if (!raw) softmax_sub(s, mc0, mc1);
          }
        }
        softmax_exp<0, AT_SPLIT>(s);
        add_rowsum(p, l0, l1);
        if (tid == 0) {
          uint32_t dep = zero & __float_as_uint(l0) & __float_as_uint(l1);
          #pragma unroll
          for (int i = AT_SPLIT - AT_PIN - PINB; i < AT_SPLIT - PINB; i += 2) dep &= __float_as_uint(s[i]) & __float_as_uint(s[i + 1]);
          mbar_arrive(b_pin + dep);
        }
        wgmma_wait<0>();
        fence_regs(o);
        if (tid == 0) mbar_arrive(b_empty + 8 * vs);
        ks += 2; if (ks >= 5) { ks -= 5; kp ^= 1; }
        vs += 2; if (vs >= 5) { vs -= 5; vp ^= 1; }
        ready = mbar_test(b_full + 8 * ks, kp) & mbar_test(b_full + 8 * vs, vp);
        softmax_exp<AT_SPLIT, 64>(s);
        pack_p(p, s);
        if (n == AT_NBLK) { lp0 = l0; lp1 = l1; l0 = 0.f; l1 = 0.f; }
        if (__builtin_expect(!raw || !ready, 0)) {
        if (!raw && __any_sync(0xffffffffu, al0 != 1.0f || al1 != 1.0f)) {
          rescale_o(o, al0, al1);
          l0 *= al0; l1 *= al1;
          al0 = 1.0f; al1 = 1.0f;
        }
        if (!ready && n < 2 * AT_NBLK - 1) {
          mbar_wait(b_full + 8 * ks, kp);
          mbar_wait(b_full + 8 * vs, vp);
        }
        }
      }
      FS(2 * it + 1, 5);
      const uint32_t vl = ring_slot(ta + 63);
      vs = ring_slot(ta + 62);
      const uint32_t ob = more ? sbase + vs * 32768 : sbase + AT_SQ + 32768;
      mbar_wait(b_full + 8 * vl, ring_par(ta + 63));
      issue_pv(o, p, v_base + vl * 2048, 1);
      block_end(zero, b_pin);
      add_rowsum(p, l0, l1);
      const bool overflow = finish_l(l0, l1);
      if (!overflow && lane == 0) mbar_arrive(b_q1);
      #pragma unroll
      for (int i = 0; i < 8; i++) asm volatile("mov.b64 {%0, %1}, 0;\nmov.b64 {%2, %3}, 0;" : "=r"(pre[i].x), "=r"(pre[i].y), "=r"(pre[i].z), "=r"(pre[i].w));
      const bool want_pre = !more && bid < OG_MOE, got_pre = want_pre && __all_sync(0xffffffffu, mbar_test(bars + 272, 0));
      if (got_pre) load_pre(pre, sbase, AT_SQ, threadIdx.x - 128);
      mbar_wait(b_empty + 8 * vs, ring_par(ta + 62));
      wgmma_wait<0>();
      fence_regs(o);
      if (tid == 0) mbar_arrive(b_empty + 8 * vl);
      FS(2 * it + 1, 6);
      if (overflow) {
        attn_rows_exact(lds_u32(bars + 400), sq + 32768, ob + cwg * 8192, 4 * ta + 1, kc, vc);
        __syncwarp();
        if (lane == 0) mbar_arrive(b_q1);
      } else stage_o(o, l0, l1, ob + frag, lane);
      if (redo0) attn_rows_exact(lds_u32(bars + 400), sq, sq, 4 * ta, kc, vc);
      fence_proxy_async();
      __syncwarp();
      if (lane == 0) {
        if (redo0) mbar_arrive(b_ordy + 8 * cwg);
        mbar_arrive(b_ordy + 16 + 8 * cwg);
      }
      if (want_pre && !got_pre) load_pre(pre, sbase, AT_SQ, threadIdx.x - 128);
      if (redo0 || overflow) raw = false;
      named_bar_sync(3 + cwg, 128);
      FS(2 * it + 1, 7);
    }
    if (cwg == 0) named_bar_arrive(1, 256);
    if (__builtin_expect(single, 0)) {
      float acc[128];
      uint32_t j = 0, pk[64];
      #pragma unroll
      for (int i = 0; i < 64; i++) asm volatile("" : "=f"(acc[2 * i]), "=f"(acc[2 * i + 1]), "=r"(pk[i]));
      uint4* dst = g_pre;
      int left = 0;
      auto put = [&](bool last) {
        #pragma unroll
        for (int i = 0; i < PUT_N; i++) dst[i * 256] = make_uint4(pk[4 * i], pk[4 * i + 1], pk[4 * i + 2], pk[4 * i + 3]);
        dst += PUT_N * 256;
        #pragma unroll
        for (int i = 0; i < 64 - 4 * PUT_N; i++) asm volatile("mov.b32 %0, %1;" : "=r"(pk[i]) : "r"(pk[i + 4 * PUT_N]));
        __syncwarp();
        if (last && lane == 0) mbar_arrive(bars + 280);
      };
      #pragma unroll 1
      for (int ji = 0; ji < help_njobs(bid); ji++) {
        const int nk = og_pre(help_job(bid, ji));
        #pragma unroll 1
        for (int kk = 0; kk < nk; kk++, j++) {
          const uint32_t slot = ring_slot(qp_pos(j, 1));
          mbar_wait(b_full + 8 * slot, ring_par(qp_pos(j, 1)) ^ ((j >> 2) & 1));
          if (H_STAG > 0 && cwg == 1 && kk == nk - H_STAG) named_bar_sync(7, 256);
          const uint32_t a_lo = q_lo + (j & 3) * 1024, b_lo = w_base + slot * 2048;
          wgmma_fence();
          wgmma_m64n256k16_ss_tb<0, 0>(acc, a_lo, b_lo, kk != 0);
          wgmma_m64n256k16_ss_tb<2, 128>(acc, a_lo, b_lo, 1);
          wgmma_m64n256k16_ss_tb<4, 256>(acc, a_lo, b_lo, 1);
          wgmma_m64n256k16_ss_tb<6, 384>(acc, a_lo, b_lo, 1);
          wgmma_commit();
          if (H_STAG > 0 && cwg == 0 && kk == nk - 1) named_bar_arrive(7, 256);
          wgmma_wait<1>();
          if (kk > 0 && tid == 0) mbar_arrive(b_empty + 8 * ring_slot(qp_pos(j - 1, 1)));
          #pragma unroll 1
          for (int i = ji == OG_JOBS ? 0 : 16 / PUT_N - 1; i < 16 / PUT_N && left > 0; i++) put(--left == 0);
        }
        wgmma_wait<0>();
        fence_regs(acc);
        if (tid == 0) mbar_arrive(b_empty + 8 * ring_slot(qp_pos(j - 1, 1)));
        #pragma unroll
        for (int i = 0; i < 64; i++) pk[i] = pack_bf16(acc[2 * i], acc[2 * i + 1]);
        left = 16 / PUT_N;
        if (ji == PRE_X) mbar_wait(bars + 296, 0);
        dst = g_pre + help_job(bid, ji) * 2048 + threadIdx.x - 128;
      }
      #pragma unroll
      for (int i = 0; i < 16; i++) dst[i * 256] = make_uint4(pk[4 * i], pk[4 * i + 1], pk[4 * i + 2], pk[4 * i + 3]);
      __syncwarp();
      if (lane == 0) mbar_arrive(bars + 280);
      named_bar_sync(5, 256);
      if (threadIdx.x == 128) {
        #pragma unroll 1
        for (int i = 0; i < 5; i++) {
          constexpr int n = OG_HSUM;
          const int used = i == 3 ? 0 : (n + 3 - (i == 4 ? 3 : i)) / 4;
          if ((used ^ (i < 4)) & 1) {
            mbar_arrive(b_full + 8 * ring_slot(4 + i));
            mbar_arrive(b_empty + 8 * ring_slot(4 + i)); mbar_arrive(b_empty + 8 * ring_slot(4 + i));
          }
        }
        mbar_arrive(b_x);
      }
      named_bar_sync(5, 256);
      #pragma unroll
      for (int i = 0; i < 8; i++) pre[i] = make_uint4(0u, 0u, 0u, 0u);
    }
    TL_CLK(3, 1, threadIdx.x == 128);
    TL_CTA(1, threadIdx.x == 256);
    TL_END(3, tid == 0);
    TL_MARK2(19, tid == 0 && !single);
    if (bid < 128) {
      tail_consumer(bid, sbase, &tmOut, pre, cwg, w_gate, w_up);
    }
  }
}

typedef CUresult (*PFN_encodeTiled)(CUtensorMap*, CUtensorMapDataType, cuuint32_t, void*, const cuuint64_t*, const cuuint64_t*,
                                    const cuuint32_t*, const cuuint32_t*, CUtensorMapInterleave, CUtensorMapSwizzle,
                                    CUtensorMapL2promotion, CUtensorMapFloatOOBfill);

CUtensorMap make_map_2d(PFN_encodeTiled enc, const void* ptr, uint64_t inner, uint64_t outer, uint64_t stride_bytes, uint32_t box_inner, uint32_t box_outer) {
  CUtensorMap m;
  cuuint64_t gd[2] = {inner, outer}; cuuint64_t gs[1] = {stride_bytes};
  cuuint32_t bx[2] = {box_inner, box_outer}; cuuint32_t es[2] = {1, 1};
  enc(&m, CU_TENSOR_MAP_DATA_TYPE_BFLOAT16, 2, const_cast<void*>(ptr), gd, gs, bx, es, CU_TENSOR_MAP_INTERLEAVE_NONE,
      CU_TENSOR_MAP_SWIZZLE_128B, CU_TENSOR_MAP_L2_PROMOTION_L2_128B, CU_TENSOR_MAP_FLOAT_OOB_FILL_NONE);
  return m;
}

CUtensorMap make_map_3d(PFN_encodeTiled enc, const void* ptr, uint64_t cols, uint64_t rows, uint32_t box_rows, uint32_t chunks) {
  CUtensorMap m;
  cuuint64_t gd[3] = {64, rows, cols / 64}; cuuint64_t gs[2] = {cols * 2, 128};
  cuuint32_t bx[3] = {64, box_rows, chunks}; cuuint32_t es[3] = {1, 1, 1};
  enc(&m, CU_TENSOR_MAP_DATA_TYPE_BFLOAT16, 3, const_cast<void*>(ptr), gd, gs, bx, es, CU_TENSOR_MAP_INTERLEAVE_NONE,
      CU_TENSOR_MAP_SWIZZLE_128B, CU_TENSOR_MAP_L2_PROMOTION_L2_128B, CU_TENSOR_MAP_FLOAT_OOB_FILL_NONE);
  return m;
}

}

extern "C" void kernel_launch(void* const* d_in, const int* in_sizes, int n_in, void* d_out, int out_size) {
  const bf16* x      = (const bf16*)d_in[0];
  const bf16* kc     = (const bf16*)d_in[1];
  const bf16* vc     = (const bf16*)d_in[2];
  const bf16* wq     = (const bf16*)d_in[3];
  const bf16* wo     = (const bf16*)d_in[4];
  const bf16* w_r    = (const bf16*)d_in[6];
  const bf16* w_gate = (const bf16*)d_in[7];
  const bf16* w_up   = (const bf16*)d_in[8];
  const bf16* w_down = (const bf16*)d_in[9];
  const bf16* cvec   = (const bf16*)d_in[10];
  const bf16* w_mod  = (const bf16*)d_in[11];
  bf16* out = (bf16*)d_out;

  static PFN_encodeTiled enc = nullptr;
  static void *p_h = nullptr, *p_o = nullptr;
  if (!enc) {
    void* fn = nullptr; cudaDriverEntryPointQueryResult qres;
    cudaGetDriverEntryPoint("cuTensorMapEncodeTiled", &fn, cudaEnableDefault, &qres);
    enc = (PFN_encodeTiled)fn;
    cudaGetSymbolAddress(&p_h, g_pre);
    p_h = (uint4*)p_h + 16 * PRE_X * 2048;
    cudaGetSymbolAddress(&p_o, g_o);
    cudaFuncSetAttribute(fused_kernel, cudaFuncAttributeMaxDynamicSharedMemorySize, (int)AT_SMEM);
  }
  const CUtensorMap tm_h   = make_map_2d(enc, p_h, T_D, T_SEQ, T_D * 2, 64, 128);
  const CUtensorMap tm_wq  = make_map_3d(enc, wq, T_DQKV, T_D, 64, 4);
  const CUtensorMap tm_k   = make_map_3d(enc, kc, T_DH, (uint64_t)T_NH * T_SEQ, 128, 2);
  const CUtensorMap tm_v   = make_map_3d(enc, vc, T_DH, (uint64_t)T_NH * T_SEQ, 128, 2);
  const CUtensorMap tm_ost = make_map_2d(enc, p_o, T_DQKV, T_SEQ, T_DQKV * 2, 64, 64);
  const CUtensorMap tm_old = make_map_2d(enc, p_o, T_DQKV, T_SEQ, T_DQKV * 2, 64, 128);
  const CUtensorMap tm_wo  = make_map_3d(enc, wo, T_D, T_DQKV, 64, 2);
  const CUtensorMap tm_d   = make_map_3d(enc, w_down, T_D, T_F, 32, 8);

  const CUtensorMap tm_m   = make_map_2d(enc, w_mod, 6 * T_D, T_D, 6 * T_D * 2, 64, 256);
  const CUtensorMap tm_out = make_map_2d(enc, out, T_D, T_SEQ, T_D * 2, 64, 16);

  Roles roles;
  for (int sm = 0; sm < 132; sm++) {
    const int t = sm >> 1;
    roles.of_sm[sm] = (uint8_t)((t < 32 ? (t & 7) * 16 + (t >> 3) * 2 : t < 60 ? (1 + (t - 32) % 7) * 16 + (4 + (t - 32) / 7) * 2 : t < 62 ? 128 + (t - 60) * 2 : (t - 58) * 2) + (sm & 1));
  }
  fused_kernel<<<132, 384, AT_SMEM, cudaStreamPerThread>>>(tm_h, tm_wq, tm_k, tm_v, tm_ost, tm_old, tm_wo, tm_d, tm_out, tm_m, roles, 0u, (const uint8_t*)wo, kc, vc, x, cvec, w_mod,
             w_r, w_gate, w_up, w_down, out);
}
```

```cpp
#include <cuda_runtime.h>
#include <cuda_bf16.h>
#include <cuda.h>
#include <stdint.h>

namespace {

typedef __nv_bfloat16 bf16;

constexpr int T_SEQ = 2048, T_D = 1024, T_NH = 32, T_DH = 128, T_DQKV = 4096, T_F = 3584;

#define PRE_X 2
__device__ __align__(1024) uint4 g_pre[(16 * PRE_X + 128) * 2048];
#define g_h (reinterpret_cast<bf16*>(g_pre + 16 * PRE_X * 2048))
__device__ __align__(1024) bf16 g_o[T_SEQ * T_DQKV];
__device__ __align__(16) uint8_t g_col[8 * 1536];
__device__ __align__(16) float g_scal[64];
__device__ __align__(16) unsigned int g_hcnt[17 * 32];
__device__ __align__(128) float g_modpart[4 * 2 * T_D];
struct __align__(2048) TailMail {
  float4 part1[T_SEQ * 8];
  uint32_t key[256];
  uint4 cand[16 * 2 * 2 * 128];
  uint32_t cnt[32];
  float ypart[(T_F / 32) * 2 * T_D];
};
__device__ TailMail g_mail;
#define g_part1 g_mail.part1
#define g_key g_mail.key
#define g_cand g_mail.cand
#define CNT_Y (g_mail.cnt)
#define g_ypart g_mail.ypart

__device__ __forceinline__ uint32_t smem_u32(const void* p) { return (uint32_t)__cvta_generic_to_shared(p); }
__device__ __forceinline__ void mbar_init(uint32_t bar, uint32_t cnt) { asm volatile("mbarrier.init.shared::cta.b64 [%0], %1;" :: "r"(bar), "r"(cnt)); }
__device__ __forceinline__ void mbar_expect_tx(uint32_t bar, uint32_t bytes) { asm volatile("mbarrier.arrive.expect_tx.shared::cta.b64 _, [%0], %1;" :: "r"(bar), "r"(bytes) : "memory"); }
__device__ __forceinline__ void mbar_arrive(uint32_t bar) { asm volatile("mbarrier.arrive.shared::cta.b64 _, [%0];" :: "r"(bar) : "memory"); }
__device__ __forceinline__ void mbar_wait(uint32_t bar, uint32_t parity) {
  asm volatile("{\n.reg .pred p;\nLAB_WAIT:\nmbarrier.try_wait.parity.shared::cta.b64 p, [%0], %1;\n@!p bra LAB_WAIT;\n}\n" :: "r"(bar), "r"(parity) : "memory");
}
__device__ __forceinline__ bool mbar_test(uint32_t bar, uint32_t parity) {
  uint32_t r; asm volatile("{\n.reg .pred p;\nmbarrier.test_wait.parity.shared::cta.b64 p, [%1], %2;\nselp.u32 %0, 1, 0, p;\n}\n" : "=r"(r) : "r"(bar), "r"(parity) : "memory");
  return r != 0;
}
__device__ __forceinline__ uint32_t clock_lo() { uint32_t c; asm volatile("mov.u32 %0, %%clock;" : "=r"(c)); return c; }
__device__ __forceinline__ void fence_mbar_init() { asm volatile("fence.mbarrier_init.release.cluster;" ::: "memory"); }
__device__ __forceinline__ void tma_load_2d(uint32_t dst, const CUtensorMap* map, int c0, int c1, uint32_t bar) {
  asm volatile("cp.async.bulk.tensor.2d.shared::cluster.global.mbarrier::complete_tx::bytes [%0], [%1, {%3, %4}], [%2];"
    :: "r"(dst), "l"(map), "r"(bar), "r"(c0), "r"(c1) : "memory");
}
__device__ __forceinline__ uint64_t policy_evict_first() {
  uint64_t p; asm volatile("createpolicy.fractional.L2::evict_first.b64 %0, 1.0;" : "=l"(p)); return p;
}
__device__ __forceinline__ void tma_load_2d_hint(uint32_t dst, const CUtensorMap* map, int c0, int c1, uint32_t bar, uint64_t pol) {
  asm volatile("cp.async.bulk.tensor.2d.shared::cluster.global.mbarrier::complete_tx::bytes.L2::cache_hint [%0], [%1, {%3, %4}], [%2], %5;"
    :: "r"(dst), "l"(map), "r"(bar), "r"(c0), "r"(c1), "l"(pol) : "memory");
}
__device__ __forceinline__ void tma_load_3d_hint(uint32_t dst, const CUtensorMap* map, int c1, int c2, uint32_t bar, uint64_t pol) {
  asm volatile("cp.async.bulk.tensor.3d.shared::cluster.global.mbarrier::complete_tx::bytes.L2::cache_hint [%0], [%1, {%3, %4, %5}], [%2], %6;"
    :: "r"(dst), "l"(map), "r"(bar), "n"(0), "r"(c1), "r"(c2), "l"(pol) : "memory");
}
__device__ __forceinline__ void tma_store_2d(const CUtensorMap* map, uint32_t src, int c0, int c1) {
  asm volatile("cp.async.bulk.tensor.2d.global.shared::cta.bulk_group [%0, {%2, %3}], [%1];" :: "l"(map), "r"(src), "r"(c0), "r"(c1) : "memory");
}
__device__ __forceinline__ void prefetch_tmap(const CUtensorMap* map) { asm volatile("prefetch.tensormap [%0];" :: "l"(map) : "memory"); }
__device__ __forceinline__ void l2_prefetch_bulk(const void* p, uint32_t bytes) {
  asm volatile("cp.async.bulk.prefetch.L2.global [%0], %1;" :: "l"(p), "r"(bytes) : "memory");
}
__device__ __forceinline__ void bulk_commit() { asm volatile("cp.async.bulk.commit_group;" ::: "memory"); }
template<int N> __device__ __forceinline__ void bulk_wait_read() { asm volatile("cp.async.bulk.wait_group.read %0;" :: "n"(N) : "memory"); }
template<int N> __device__ __forceinline__ void bulk_wait() { asm volatile("cp.async.bulk.wait_group %0;" :: "n"(N) : "memory"); }
__device__ __forceinline__ void named_bar_sync(int id, int nthreads) { asm volatile("bar.sync %0, %1;" :: "r"(id), "r"(nthreads) : "memory"); }
__device__ __forceinline__ void named_bar_arrive(int id, int nthreads) { asm volatile("bar.arrive %0, %1;" :: "r"(id), "r"(nthreads) : "memory"); }
__device__ __forceinline__ void pass_turn(int cwg) {
  asm volatile("{\n.reg .pred p;\nsetp.ne.u32 p, %0, 0;\n@p bar.arrive 1, 256;\n@!p bar.arrive 2, 256;\n}\n" :: "r"(cwg) : "memory");
}
__device__ __forceinline__ void wgmma_fence() { asm volatile("wgmma.fence.sync.aligned;" ::: "memory"); }
__device__ __forceinline__ void wgmma_commit() { asm volatile("wgmma.commit_group.sync.aligned;" ::: "memory"); }
template<int N> __device__ __forceinline__ void wgmma_wait() { asm volatile("wgmma.wait_group.sync.aligned %0;" :: "n"(N) : "memory"); }
template<int R> __device__ __forceinline__ void reg_alloc() { asm volatile("setmaxnreg.inc.sync.aligned.u32 %0;" :: "n"(R)); }
template<int R> __device__ __forceinline__ void reg_dealloc() { asm volatile("setmaxnreg.dec.sync.aligned.u32 %0;" :: "n"(R)); }
__device__ __forceinline__ bool elect_one() {
  uint32_t pred; asm volatile("{\n.reg .pred p;\nelect.sync _|p, 0xffffffff;\nselp.u32 %0, 1, 0, p;\n}\n" : "=r"(pred)); return pred != 0;
}
__device__ __forceinline__ uint32_t pack_bf16(float lo, float hi) {
  uint32_t r; asm("cvt.rn.bf16x2.f32 %0, %1, %2;" : "=r"(r) : "f"(hi), "f"(lo)); return r;
}
__device__ __forceinline__ void stmatrix_x4(uint32_t addr, uint32_t r0, uint32_t r1, uint32_t r2, uint32_t r3) {
  asm volatile("stmatrix.sync.aligned.m8n8.x4.shared.b16 [%0], {%1, %2, %3, %4};" :: "r"(addr), "r"(r0), "r"(r1), "r"(r2), "r"(r3) : "memory");
}
__device__ __forceinline__ void fence_proxy_async() { asm volatile("fence.proxy.async.shared::cta;" ::: "memory"); }
__device__ __forceinline__ float ex2_approx(float x) { float y; asm("ex2.approx.ftz.f32 %0, %1;" : "=f"(y) : "f"(x)); return y; }
template<int N> __device__ __forceinline__ void fence_regs(float (&r)[N]) {
  #pragma unroll
  for (int i = 0; i < N; i++) asm volatile("" : "+f"(r[i]) :: "memory");
}
template<int N> __device__ __forceinline__ void zero_regs(float (&r)[N]) {
  #pragma unroll
  for (int i = 0; i < N; i += 2) asm volatile("mov.b64 {%0, %1}, 0;" : "=f"(r[i]), "=f"(r[i + 1]));
}
__device__ __forceinline__ float rbf(float x) { return __uint_as_float(pack_bf16(0.f, x)); }
__device__ __forceinline__ float bflo(uint32_t v) { return __uint_as_float(v << 16); }
__device__ __forceinline__ float bfhi(uint32_t v) { return __uint_as_float(v & 0xffff0000u); }

#define XT(i) do {} while (0)
#define TL_START(k) do {} while (0)
#define TL_END(k, cond) do {} while (0)
#define TL_CTA(i, cond) do {} while (0)
#define FS(slot, k) do {} while (0)
#define TL_MARK2(k, cond) do {} while (0)
#define TL_CLK(k, i, cond) do {} while (0)

template <int OFFA, int OFFB>
__device__ __forceinline__ void wgmma_m64n256k16_ss_tb(float (&d)[128], uint32_t a_lo, uint32_t b_lo, int scaleD) {
  asm volatile("{\n.reg .pred p;\n.reg .b32 ta, tb;\n.reg .b64 da, db;\nsetp.ne.b32 p, %130, 0;\n"
    "add.u32 ta, %128, %131;\nadd.u32 tb, %129, %132;\n"
    "mov.b64 da, {ta, 0x40000040};\nmov.b64 db, {tb, 0x40000040};\n"
    "wgmma.mma_async.sync.aligned.m64n256k16.f32.bf16.bf16 "
    "{%0, %1, %2, %3, %4, %5, %6, %7, %8, %9, %10, %11, %12, %13, %14, %15, %16, %17, %18, %19, %20, %21, %22, %23, %24, %25, %26, %27, %28, %29, %30, %31, %32, %33, %34, %35, %36, %37, %38, %39, %40, %41, %42, %43, %44, %45, %46, %47, %48, %49, %50, %51, %52, %53, %54, %55, %56, %57, %58, %59, %60, %61, %62, %63, %64, %65, %66, %67, %68, %69, %70, %71, %72, %73, %74, %75, %76, %77, %78, %79, %80, %81, %82, %83, %84, %85, %86, %87, %88, %89, %90, %91, %92, %93, %94, %95, %96, %97, %98, %99, %100, %101, %102, %103, %104, %105, %106, %107, %108, %109, %110, %111, %112, %113, %114, %115, %116, %117, %118, %119, %120, %121, %122, %123, %124, %125, %126, %127}, "
    "da, db, p, 1, 1, 0, 1;\n}\n"
    : "+f"(d[0]), "+f"(d[1]), "+f"(d[2]), "+f"(d[3]), "+f"(d[4]), "+f"(d[5]), "+f"(d[6]), "+f"(d[7]), "+f"(d[8]), "+f"(d[9]), "+f"(d[10]), "+f"(d[11]), "+f"(d[12]), "+f"(d[13]), "+f"(d[14]), "+f"(d[15]), "+f"(d[16]), "+f"(d[17]), "+f"(d[18]), "+f"(d[19]), "+f"(d[20]), "+f"(d[21]), "+f"(d[22]), "+f"(d[23]), "+f"(d[24]), "+f"(d[25]), "+f"(d[26]), "+f"(d[27]), "+f"(d[28]), "+f"(d[29]), "+f"(d[30]), "+f"(d[31]), "+f"(d[32]), "+f"(d[33]), "+f"(d[34]), "+f"(d[35]), "+f"(d[36]), "+f"(d[37]), "+f"(d[38]), "+f"(d[39]), "+f"(d[40]), "+f"(d[41]), "+f"(d[42]), "+f"(d[43]), "+f"(d[44]), "+f"(d[45]), "+f"(d[46]), "+f"(d[47]), "+f"(d[48]), "+f"(d[49]), "+f"(d[50]), "+f"(d[51]), "+f"(d[52]), "+f"(d[53]), "+f"(d[54]), "+f"(d[55]), "+f"(d[56]), "+f"(d[57]), "+f"(d[58]), "+f"(d[59]), "+f"(d[60]), "+f"(d[61]), "+f"(d[62]), "+f"(d[63]), "+f"(d[64]), "+f"(d[65]), "+f"(d[66]), "+f"(d[67]), "+f"(d[68]), "+f"(d[69]), "+f"(d[70]), "+f"(d[71]), "+f"(d[72]), "+f"(d[73]), "+f"(d[74]), "+f"(d[75]), "+f"(d[76]), "+f"(d[77]), "+f"(d[78]), "+f"(d[79]), "+f"(d[80]), "+f"(d[81]), "+f"(d[82]), "+f"(d[83]), "+f"(d[84]), "+f"(d[85]), "+f"(d[86]), "+f"(d[87]), "+f"(d[88]), "+f"(d[89]), "+f"(d[90]), "+f"(d[91]), "+f"(d[92]), "+f"(d[93]), "+f"(d[94]), "+f"(d[95]), "+f"(d[96]), "+f"(d[97]), "+f"(d[98]), "+f"(d[99]), "+f"(d[100]), "+f"(d[101]), "+f"(d[102]), "+f"(d[103]), "+f"(d[104]), "+f"(d[105]), "+f"(d[106]), "+f"(d[107]), "+f"(d[108]), "+f"(d[109]), "+f"(d[110]), "+f"(d[111]), "+f"(d[112]), "+f"(d[113]), "+f"(d[114]), "+f"(d[115]), "+f"(d[116]), "+f"(d[117]), "+f"(d[118]), "+f"(d[119]), "+f"(d[120]), "+f"(d[121]), "+f"(d[122]), "+f"(d[123]), "+f"(d[124]), "+f"(d[125]), "+f"(d[126]), "+f"(d[127])
    : "r"(a_lo), "r"(b_lo), "r"(scaleD), "n"(OFFA), "n"(OFFB));
}

template <int OFFA, int OFFB>
__device__ __forceinline__ void wgmma_m64n128k16_ss_tb(float (&d)[64], uint32_t a_lo, uint32_t b_lo, int scaleD) {
  asm volatile("{\n.reg .pred p;\n.reg .b32 ta, tb;\n.reg .b64 da, db;\nsetp.ne.b32 p, %66, 0;\n"
    "add.u32 ta, %64, %67;\nadd.u32 tb, %65, %68;\n"
    "mov.b64 da, {ta, 0x40000040};\nmov.b64 db, {tb, 0x40000040};\n"
    "wgmma.mma_async.sync.aligned.m64n128k16.f32.bf16.bf16 "
    "{%0, %1, %2, %3, %4, %5, %6, %7, %8, %9, %10, %11, %12, %13, %14, %15, %16, %17, %18, %19, %20, %21, %22, %23, %24, %25, %26, %27, %28, %29, %30, %31, %32, %33, %34, %35, %36, %37, %38, %39, %40, %41, %42, %43, %44, %45, %46, %47, %48, %49, %50, %51, %52, %53, %54, %55, %56, %57, %58, %59, %60, %61, %62, %63}, "
    "da, db, p, 1, 1, 0, 1;\n}\n"
    : "+f"(d[0]), "+f"(d[1]), "+f"(d[2]), "+f"(d[3]), "+f"(d[4]), "+f"(d[5]), "+f"(d[6]), "+f"(d[7]), "+f"(d[8]), "+f"(d[9]), "+f"(d[10]), "+f"(d[11]), "+f"(d[12]), "+f"(d[13]), "+f"(d[14]), "+f"(d[15]), "+f"(d[16]), "+f"(d[17]), "+f"(d[18]), "+f"(d[19]), "+f"(d[20]), "+f"(d[21]), "+f"(d[22]), "+f"(d[23]), "+f"(d[24]), "+f"(d[25]), "+f"(d[26]), "+f"(d[27]), "+f"(d[28]), "+f"(d[29]), "+f"(d[30]), "+f"(d[31]), "+f"(d[32]), "+f"(d[33]), "+f"(d[34]), "+f"(d[35]), "+f"(d[36]), "+f"(d[37]), "+f"(d[38]), "+f"(d[39]), "+f"(d[40]), "+f"(d[41]), "+f"(d[42]), "+f"(d[43]), "+f"(d[44]), "+f"(d[45]), "+f"(d[46]), "+f"(d[47]), "+f"(d[48]), "+f"(d[49]), "+f"(d[50]), "+f"(d[51]), "+f"(d[52]), "+f"(d[53]), "+f"(d[54]), "+f"(d[55]), "+f"(d[56]), "+f"(d[57]), "+f"(d[58]), "+f"(d[59]), "+f"(d[60]), "+f"(d[61]), "+f"(d[62]), "+f"(d[63])
    : "r"(a_lo), "r"(b_lo), "r"(scaleD), "n"(OFFA), "n"(OFFB));
}

template <int OFFB>
__device__ __forceinline__ void wgmma_m64n128k16_rs_tb(float (&d)[64], uint32_t a0, uint32_t a1, uint32_t a2, uint32_t a3, uint32_t b_lo, int scaleD) {
  asm volatile("{\n.reg .pred p;\n.reg .b32 tb;\n.reg .b64 db;\nsetp.ne.b32 p, %69, 0;\n"
    "add.u32 tb, %68, %70;\n"
    "mov.b64 db, {tb, 0x40000040};\n"
    "wgmma.mma_async.sync.aligned.m64n128k16.f32.bf16.bf16 "
    "{%0, %1, %2, %3, %4, %5, %6, %7, %8, %9, %10, %11, %12, %13, %14, %15, %16, %17, %18, %19, %20, %21, %22, %23, %24, %25, %26, %27, %28, %29, %30, %31, %32, %33, %34, %35, %36, %37, %38, %39, %40, %41, %42, %43, %44, %45, %46, %47, %48, %49, %50, %51, %52, %53, %54, %55, %56, %57, %58, %59, %60, %61, %62, %63}, "
    "{%64, %65, %66, %67}, db, p, 1, 1, 1;\n}\n"
    : "+f"(d[0]), "+f"(d[1]), "+f"(d[2]), "+f"(d[3]), "+f"(d[4]), "+f"(d[5]), "+f"(d[6]), "+f"(d[7]), "+f"(d[8]), "+f"(d[9]), "+f"(d[10]), "+f"(d[11]), "+f"(d[12]), "+f"(d[13]), "+f"(d[14]), "+f"(d[15]), "+f"(d[16]), "+f"(d[17]), "+f"(d[18]), "+f"(d[19]), "+f"(d[20]), "+f"(d[21]), "+f"(d[22]), "+f"(d[23]), "+f"(d[24]), "+f"(d[25]), "+f"(d[26]), "+f"(d[27]), "+f"(d[28]), "+f"(d[29]), "+f"(d[30]), "+f"(d[31]), "+f"(d[32]), "+f"(d[33]), "+f"(d[34]), "+f"(d[35]), "+f"(d[36]), "+f"(d[37]), "+f"(d[38]), "+f"(d[39]), "+f"(d[40]), "+f"(d[41]), "+f"(d[42]), "+f"(d[43]), "+f"(d[44]), "+f"(d[45]), "+f"(d[46]), "+f"(d[47]), "+f"(d[48]), "+f"(d[49]), "+f"(d[50]), "+f"(d[51]), "+f"(d[52]), "+f"(d[53]), "+f"(d[54]), "+f"(d[55]), "+f"(d[56]), "+f"(d[57]), "+f"(d[58]), "+f"(d[59]), "+f"(d[60]), "+f"(d[61]), "+f"(d[62]), "+f"(d[63])
    : "r"(a0), "r"(a1), "r"(a2), "r"(a3), "r"(b_lo), "r"(scaleD), "n"(OFFB));
}

template <int OFFB>
__device__ __forceinline__ void wgmma_m64n128k16_rs(float (&d)[64], uint32_t a0, uint32_t a1, uint32_t a2, uint32_t a3, uint32_t b_lo, int scaleD) {
  asm volatile("{\n.reg .pred p;\n.reg .b32 tb;\n.reg .b64 db;\nsetp.ne.b32 p, %69, 0;\n"
    "add.u32 tb, %68, %70;\n"
    "mov.b64 db, {tb, 0x40000040};\n"
    "wgmma.mma_async.sync.aligned.m64n128k16.f32.bf16.bf16 "
    "{%0, %1, %2, %3, %4, %5, %6, %7, %8, %9, %10, %11, %12, %13, %14, %15, %16, %17, %18, %19, %20, %21, %22, %23, %24, %25, %26, %27, %28, %29, %30, %31, %32, %33, %34, %35, %36, %37, %38, %39, %40, %41, %42, %43, %44, %45, %46, %47, %48, %49, %50, %51, %52, %53, %54, %55, %56, %57, %58, %59, %60, %61, %62, %63}, "
    "{%64, %65, %66, %67}, db, p, 1, 1, 0;\n}\n"
    : "+f"(d[0]), "+f"(d[1]), "+f"(d[2]), "+f"(d[3]), "+f"(d[4]), "+f"(d[5]), "+f"(d[6]), "+f"(d[7]), "+f"(d[8]), "+f"(d[9]), "+f"(d[10]), "+f"(d[11]), "+f"(d[12]), "+f"(d[13]), "+f"(d[14]), "+f"(d[15]), "+f"(d[16]), "+f"(d[17]), "+f"(d[18]), "+f"(d[19]), "+f"(d[20]), "+f"(d[21]), "+f"(d[22]), "+f"(d[23]), "+f"(d[24]), "+f"(d[25]), "+f"(d[26]), "+f"(d[27]), "+f"(d[28]), "+f"(d[29]), "+f"(d[30]), "+f"(d[31]), "+f"(d[32]), "+f"(d[33]), "+f"(d[34]), "+f"(d[35]), "+f"(d[36]), "+f"(d[37]), "+f"(d[38]), "+f"(d[39]), "+f"(d[40]), "+f"(d[41]), "+f"(d[42]), "+f"(d[43]), "+f"(d[44]), "+f"(d[45]), "+f"(d[46]), "+f"(d[47]), "+f"(d[48]), "+f"(d[49]), "+f"(d[50]), "+f"(d[51]), "+f"(d[52]), "+f"(d[53]), "+f"(d[54]), "+f"(d[55]), "+f"(d[56]), "+f"(d[57]), "+f"(d[58]), "+f"(d[59]), "+f"(d[60]), "+f"(d[61]), "+f"(d[62]), "+f"(d[63])
    : "r"(a0), "r"(a1), "r"(a2), "r"(a3), "r"(b_lo), "r"(scaleD), "n"(OFFB));
}

__device__ __forceinline__ uint4 ldg_nc_v4(const void* p) {
  uint4 v;
    asm volatile("{\n.reg .b64 pol;\ncreatepolicy.fractional.L2::evict_first.b64 pol, 1.0;\n"
                 "ld.global.nc.L1::no_allocate.L2::cache_hint.v4.u32 {%0, %1, %2, %3}, [%4], pol;\n}\n" : "=r"(v.x), "=r"(v.y), "=r"(v.z), "=r"(v.w) : "l"(p));
  return v;
}
__device__ __forceinline__ uint64_t pol_normal() {
  uint64_t p; asm volatile("createpolicy.fractional.L2::evict_normal.b64 %0, 1.0;" : "=l"(p)); return p;
}
__device__ __forceinline__ void unpack8(const uint4& u, float (&v)[8]) {
  v[0] = bflo(u.x); v[1] = bfhi(u.x); v[2] = bflo(u.y); v[3] = bfhi(u.y);
  v[4] = bflo(u.z); v[5] = bfhi(u.z); v[6] = bflo(u.w); v[7] = bfhi(u.w);
}
__device__ __forceinline__ void fma8(float (&acc)[8], float s, const uint4& w) {
  acc[0] = fmaf(s, bflo(w.x), acc[0]); acc[1] = fmaf(s, bfhi(w.x), acc[1]); acc[2] = fmaf(s, bflo(w.y), acc[2]); acc[3] = fmaf(s, bfhi(w.y), acc[3]);
  acc[4] = fmaf(s, bflo(w.z), acc[4]); acc[5] = fmaf(s, bfhi(w.z), acc[5]); acc[6] = fmaf(s, bflo(w.w), acc[6]); acc[7] = fmaf(s, bfhi(w.w), acc[7]);
}
__device__ __forceinline__ float rcp_approx(float x) { float y; asm("rcp.approx.ftz.f32 %0, %1;" : "=f"(y) : "f"(x)); return y; }
__device__ __forceinline__ float sigmoid_f(float v) { return rcp_approx(1.0f + ex2_approx(v * -1.4426950408889634f)); }
__device__ __forceinline__ float silu_bf(float v) { return rbf(v * sigmoid_f(v)); }
__device__ __forceinline__ uint32_t rank_key(float r, int idx) {
  const uint32_t b = __float_as_uint(r) >> 16;
  const uint32_t u = (r != r) ? 0u : ((b & 0x8000u) ? (~b & 0xffffu) : (b | 0x8000u));
  return (u << 16) | (0xffffu - (uint32_t)idx);
}
__device__ __forceinline__ void warp_top2(uint32_t& k1, uint32_t& k2) {
  const uint32_t m1 = __reduce_max_sync(0xffffffffu, k1);
  k2 = __reduce_max_sync(0xffffffffu, k1 == m1 ? k2 : k1);
  k1 = m1;
}
__device__ __forceinline__ uint32_t bmul2(uint32_t a, uint32_t b) { uint32_t r; asm("mul.rn.bf16x2 %0, %1, %2;" : "=r"(r) : "r"(a), "r"(b)); return r; }
__device__ __forceinline__ uint32_t badd2(uint32_t a, uint32_t b) { uint32_t r; asm("add.rn.bf16x2 %0, %1, %2;" : "=r"(r) : "r"(a), "r"(b)); return r; }
__device__ __forceinline__ uint32_t bsub2(uint32_t a, uint32_t b) { uint32_t r; asm("sub.rn.bf16x2 %0, %1, %2;" : "=r"(r) : "r"(a), "r"(b)); return r; }
__device__ __forceinline__ float sqrt_approx(float x) { float y; asm("sqrt.approx.f32 %0, %1;" : "=f"(y) : "f"(x)); return y; }
__device__ __forceinline__ uint32_t ln_norm2(uint32_t x1, uint32_t mb2, float inv) {
  const uint32_t d = bsub2(x1, mb2);
  return pack_bf16(bflo(d) * inv, bfhi(d) * inv);
}
__device__ __forceinline__ uint32_t bfma2(uint32_t a, uint32_t b, uint32_t c) { uint32_t r; asm("fma.rn.bf16x2 %0, %1, %2, %3;" : "=r"(r) : "r"(a), "r"(b), "r"(c)); return r; }
__device__ __forceinline__ uint32_t ln_norm2b(uint32_t x1, uint32_t mb2, uint32_t ih, uint32_t il) {
  const uint32_t d = bsub2(x1, mb2);
  return bfma2(d, ih, bmul2(d, il));
}
__device__ __forceinline__ uint32_t ln_mod2(uint32_t x1, uint32_t mb2, float inv, uint32_t c1, uint32_t sb) { return badd2(bmul2(ln_norm2(x1, mb2, inv), c1), sb); }
__device__ __forceinline__ void ldmatrix_x4(uint32_t addr, uint32_t& r0, uint32_t& r1, uint32_t& r2, uint32_t& r3) {
  asm volatile("ldmatrix.sync.aligned.m8n8.x4.shared.b16 {%0, %1, %2, %3}, [%4];" : "=r"(r0), "=r"(r1), "=r"(r2), "=r"(r3) : "r"(addr) : "memory");
}
__device__ __forceinline__ uint4 ldg_stream_v4(const void* p, uint64_t pol) {
  uint4 v; asm volatile("ld.global.nc.L1::no_allocate.L2::cache_hint.L2::128B.v4.u32 {%0, %1, %2, %3}, [%4], %5;" : "=r"(v.x), "=r"(v.y), "=r"(v.z), "=r"(v.w) : "l"(p), "l"(pol)); return v;
}
__device__ __forceinline__ void bulk_load_hint(uint32_t dst, const void* src, uint32_t bytes, uint32_t bar, uint64_t pol) {
  asm volatile("cp.async.bulk.shared::cluster.global.mbarrier::complete_tx::bytes.L2::cache_hint [%0], [%1], %2, [%3], %4;"
    :: "r"(dst), "l"(src), "r"(bytes), "r"(bar), "l"(pol) : "memory");
}
__device__ __forceinline__ void red_release_add(unsigned int* p, unsigned int v) { asm volatile("red.release.gpu.global.add.u32 [%0], %1;" :: "l"(p), "r"(v) : "memory"); }
__device__ __forceinline__ unsigned int ld_acquire(const unsigned int* p) { unsigned int v; asm volatile("ld.acquire.gpu.global.u32 %0, [%1];" : "=r"(v) : "l"(p) : "memory"); return v; }
__device__ __forceinline__ void spin_until(const unsigned int* p, unsigned int target) {
  #pragma unroll 1
  for (unsigned int i = 0; i < (1u << 22); i++) { if (ld_acquire(p) >= target) return; }
}
__device__ __forceinline__ float lds_f32(uint32_t a) { float v; asm volatile("ld.shared.f32 %0, [%1];" : "=f"(v) : "r"(a) : "memory"); return v; }
__device__ __forceinline__ float2 lds_f32x2(uint32_t a) { float2 v; asm volatile("ld.shared.v2.f32 {%0, %1}, [%2];" : "=f"(v.x), "=f"(v.y) : "r"(a) : "memory"); return v; }
__device__ __forceinline__ uint2 lds_u32x2(uint32_t a) { uint2 v; asm volatile("ld.shared.v2.u32 {%0, %1}, [%2];" : "=r"(v.x), "=r"(v.y) : "r"(a) : "memory"); return v; }
__device__ __forceinline__ uint32_t lds_u32(uint32_t a) { uint32_t v; asm volatile("ld.shared.u32 %0, [%1];" : "=r"(v) : "r"(a) : "memory"); return v; }
__device__ __forceinline__ void sts_u32(uint32_t a, uint32_t v) { asm volatile("st.shared.u32 [%0], %1;" :: "r"(a), "r"(v) : "memory"); }
__device__ __forceinline__ void sts_u32x2(uint32_t a, uint32_t x, uint32_t y) { asm volatile("st.shared.v2.u32 [%0], {%1, %2};" :: "r"(a), "r"(x), "r"(y) : "memory"); }
__device__ __forceinline__ void sts_f32(uint32_t a, float v) { asm volatile("st.shared.f32 [%0], %1;" :: "r"(a), "f"(v) : "memory"); }
__device__ __forceinline__ void sts_f32x2(uint32_t a, float x, float y) { asm volatile("st.shared.v2.f32 [%0], {%1, %2};" :: "r"(a), "f"(x), "f"(y) : "memory"); }
__device__ __forceinline__ void sts_f32x4(uint32_t a, float x, float y, float z, float w) { asm volatile("st.shared.v4.f32 [%0], {%1, %2, %3, %4};" :: "r"(a), "f"(x), "f"(y), "f"(z), "f"(w) : "memory"); }

__device__ __forceinline__ uint4 lds_u32x4(uint32_t a) { uint4 v; asm volatile("ld.shared.v4.u32 {%0, %1, %2, %3}, [%4];" : "=r"(v.x), "=r"(v.y), "=r"(v.z), "=r"(v.w) : "r"(a) : "memory"); return v; }
__device__ __forceinline__ void sts_u32x4(uint32_t a, uint32_t x, uint32_t y, uint32_t z, uint32_t w) { asm volatile("st.shared.v4.u32 [%0], {%1, %2, %3, %4};" :: "r"(a), "r"(x), "r"(y), "r"(z), "r"(w) : "memory"); }
__device__ __forceinline__ void st_tagged(float* p, float v) {
  const uint32_t b = __float_as_uint(v);
  asm volatile("st.relaxed.gpu.global.u32 [%0], %1;" :: "l"(p), "r"(b == 0u ? 0x80000000u : b) : "memory");
}
__device__ __forceinline__ void st_tagged4(float* p, float x, float y, float z, float w) {
  const uint32_t a = __float_as_uint(x), b = __float_as_uint(y), c = __float_as_uint(z), d = __float_as_uint(w);
  asm volatile("st.relaxed.gpu.global.v4.u32 [%0], {%1, %2, %3, %4};" :: "l"(p), "r"(a == 0u ? 0x80000000u : a), "r"(b == 0u ? 0x80000000u : b),
               "r"(c == 0u ? 0x80000000u : c), "r"(d == 0u ? 0x80000000u : d) : "memory");
}
__device__ __forceinline__ void st_relaxed2(void* p, uint32_t a, uint32_t b) { asm volatile("st.relaxed.gpu.global.v2.u32 [%0], {%1, %2};" :: "l"(p), "r"(a), "r"(b) : "memory"); }
__device__ __forceinline__ float4 ld_tagged4(const float* p) {
  float4 v; asm volatile("ld.relaxed.gpu.global.v4.f32 {%0, %1, %2, %3}, [%4];" : "=f"(v.x), "=f"(v.y), "=f"(v.z), "=f"(v.w) : "l"(p) : "memory"); return v;
}
__device__ __forceinline__ bool tagged4(const float4& v) {
  return __float_as_uint(v.x) != 0u && __float_as_uint(v.y) != 0u && __float_as_uint(v.z) != 0u && __float_as_uint(v.w) != 0u;
}
__device__ __forceinline__ void hint_arrive(uint32_t* p) { asm volatile("red.relaxed.gpu.global.add.u32 [%0], 1;" :: "l"(p) : "memory"); }
__device__ __forceinline__ void hint_wait(const uint32_t* p, uint32_t target) {
  uint32_t v = 0u;
  #pragma unroll 1
  for (unsigned int i = 0; i < (1u << 22) && v < target; i++) asm volatile("ld.relaxed.gpu.global.u32 %0, [%1];" : "=r"(v) : "l"(p) : "memory");
}
__device__ __forceinline__ void fence_proxy_async_global() { asm volatile("fence.proxy.async.global;" ::: "memory"); }

#define H_SPLIT 1
#define X_DLY 1200
#define W_DLY 1900
#define W_FIRST 2200
#define PRE_B 2
template <int J0, int J1>
__device__ __forceinline__ void load_parts(float2 (&pa)[J1 - J0][4], int t2) {
  #pragma unroll
  for (int j = J0; j < J1; j++)
    #pragma unroll
    for (int k = 0; k < 4; k++)
      asm volatile("ld.relaxed.gpu.global.v2.f32 {%0, %1}, [%2];" : "=f"(pa[j - J0][k].x), "=f"(pa[j - J0][k].y)
                   : "l"(g_modpart + k * 2 * T_D + (t2 >> 7) * T_D + j * 256 + (t2 & 127) * 2) : "memory");
}
template <int J0, int J1>
__device__ __forceinline__ void finish_parts(float2 (&pa)[J1 - J0][4], bool loaded, int t2, uint32_t tab) {
  #pragma unroll 1
  for (unsigned int spin = 0; spin < (1u << 22); spin++) {
    if (!loaded) load_parts<J0, J1>(pa, t2);
    loaded = false;
    bool ok = true;
    #pragma unroll
    for (int j = 0; j < J1 - J0; j++)
      #pragma unroll
      for (int k = 0; k < 4; k++) ok &= (__float_as_uint(pa[j][k].x) != 0u) & (__float_as_uint(pa[j][k].y) != 0u);
    if (__all_sync(0xffffffffu, ok)) break;
  }
  #pragma unroll
  for (int j = J0; j < J1; j++) {
    const float2* q = pa[j - J0];
    const uint32_t m = pack_bf16(((q[0].x + q[1].x) + q[2].x) + q[3].x, ((q[0].y + q[1].y) + q[2].y) + q[3].y);
    sts_u32(tab + (t2 >> 7) * 2048 + j * 512 + (t2 & 127) * 4, t2 >= 128 ? badd2(m, 0x3F803F80u) : m);
  }
}
__device__ __forceinline__ void head_phase(uint32_t bid, uint32_t scr, uint32_t xs, uint32_t b_x, uint32_t b_go, uint32_t b_head, int t2, uint32_t zero, const bf16* __restrict__ cvec, const bf16* __restrict__ w_mod) {
  const int lane = t2 & 31, w8 = t2 >> 5;
  const int cb = bid & 31, ks = bid >> 5;
  const bool early = (cb & 15) < 4 * H_SPLIT;
  const uint32_t ws = (xs - 32768 + (t2 >> 3) * 128 + (((t2 ^ (t2 >> 3)) & 7) << 4)) ^ zero;
  const float cv = __bfloat162float(cvec[ks * 256 + t2]);
  const bf16* wsrc = w_mod + (size_t)(ks * 256 + (t2 >> 3)) * (6 * T_D) + cb * 64 + (t2 & 7) * 8;
  if (early) {
    const uint64_t pol = policy_evict_first();
    #pragma unroll 2
    for (int i = 0; i < 8; i++)
      asm volatile("cp.async.cg.shared.global.L2::cache_hint [%0], [%1], 16, %2;" :: "r"(ws + i * 4096), "l"(wsrc + (size_t)i * 32 * 6 * T_D), "l"(pol) : "memory");
  }
  sts_f32(scr + t2 * 4, silu_bf(cv));
  named_bar_sync(6, 384);
  TL_MARK2(1, t2 == 0);
  uint4 xv[2][4];
  uint32_t mb2[2], ih[2], il[2];
  auto norm = [&](int j) {
    #pragma unroll
    for (int r = 0; r < 2; r++) {
      xv[r][j].x = ln_norm2b(xv[r][j].x, mb2[r], ih[r], il[r]); xv[r][j].y = ln_norm2b(xv[r][j].y, mb2[r], ih[r], il[r]);
      xv[r][j].z = ln_norm2b(xv[r][j].z, mb2[r], ih[r], il[r]); xv[r][j].w = ln_norm2b(xv[r][j].w, mb2[r], ih[r], il[r]);
    }
  };
  auto modulate = [&](int j) {
    const uint4 sa = lds_u32x4(scr + 8192 + j * 512 + lane * 16), c1 = lds_u32x4(scr + 8192 + 2048 + j * 512 + lane * 16);
    #pragma unroll
    for (int r = 0; r < 2; r++) {
      xv[r][j].x = badd2(bmul2(xv[r][j].x, c1.x), sa.x); xv[r][j].y = badd2(bmul2(xv[r][j].y, c1.y), sa.y);
      xv[r][j].z = badd2(bmul2(xv[r][j].z, c1.z), sa.z); xv[r][j].w = badd2(bmul2(xv[r][j].w, c1.w), sa.w);
    }
  };
  auto store = [&](int j) {
    #pragma unroll
    for (int r = 0; r < 2; r++) *reinterpret_cast<uint4*>(g_h + (size_t)(bid * 16 + 2 * w8 + r) * T_D + j * 256 + lane * 8) = xv[r][j];
  };
  #pragma unroll 1
  for (int ph = 0; ph < 2; ph++) {
    if ((ph == 0) == early) {
      asm volatile("cp.async.wait_all;" ::: "memory");
      if (!early) mbar_wait(b_x + 168, 0);
      float acc[8];
      #pragma unroll
      for (int j = 0; j < 8; j++) acc[j] = 0.f;
      #pragma unroll
      for (int i = 0; i < 8; i++) fma8(acc, lds_f32(scr + ((t2 >> 3) + 32 * i) * 4), lds_u32x4(ws + i * 4096));
      #pragma unroll
      for (int j = 0; j < 4; j++) { const bool up = lane & 16; acc[j] = (up ? acc[4 + j] : acc[j]) + __shfl_xor_sync(0xffffffffu, up ? acc[j] : acc[4 + j], 16); }
      #pragma unroll
      for (int j = 0; j < 2; j++) { const bool up = lane & 8; acc[j] = (up ? acc[2 + j] : acc[j]) + __shfl_xor_sync(0xffffffffu, up ? acc[j] : acc[2 + j], 8); }
      sts_f32x2(scr + 1024 + w8 * 256 + (lane & 7) * 32 + (lane >> 3) * 8, acc[0], acc[1]);
      named_bar_sync(5, 256);
      if (t2 < 64) {
        float sum = 0.f;
        #pragma unroll
        for (int i = 0; i < 8; i++) sum += lds_f32(scr + 1024 + i * 256 + t2 * 4);
        st_tagged(g_modpart + ks * 2 * T_D + cb * 64 + t2, sum);
        TL_MARK2(early ? 2 : 6, t2 == 0);
      }
    } else {
      float2 pa[H_SPLIT][4];
      mbar_wait(b_x, 0);
      TL_MARK2(18, t2 == 0);
      load_parts<0, H_SPLIT>(pa, t2);
      #pragma unroll
      for (int r = 0; r < 2; r++)
        #pragma unroll
        for (int j = 0; j < 4; j++) xv[r][j] = lds_u32x4(xs + (2 * w8 + r) * 2048 + j * 512 + lane * 16);
  {
    float st[4] = {0.f, 0.f, 0.f, 0.f};
    #pragma unroll
    for (int r = 0; r < 2; r++)
      #pragma unroll
      for (int j = 0; j < 4; j++) {
        float v[8];
        unpack8(xv[r][j], v);
        st[2 * r] += ((v[0] + v[1]) + (v[2] + v[3])) + ((v[4] + v[5]) + (v[6] + v[7]));
        st[2 * r + 1] += fmaf(v[0], v[0], fmaf(v[1], v[1], fmaf(v[2], v[2], v[3] * v[3]))) + fmaf(v[4], v[4], fmaf(v[5], v[5], fmaf(v[6], v[6], v[7] * v[7])));
      }
    #pragma unroll
    for (int k = 0; k < 2; k++) { const bool up = lane & 16; st[k] = (up ? st[2 + k] : st[k]) + __shfl_xor_sync(0xffffffffu, up ? st[k] : st[2 + k], 16); }
    #pragma unroll
    for (int o = 8; o > 0; o >>= 1) { st[0] += __shfl_xor_sync(0xffffffffu, st[0], o); st[1] += __shfl_xor_sync(0xffffffffu, st[1], o); }
    const float mean = st[0] * (1.0f / T_D);
    const float inv = rcp_approx(rbf(sqrt_approx(rbf(rbf(fmaxf(fmaf(-mean, mean, st[1] * (1.0f / T_D)), 0.f)) + 1e-05f))));
    const uint32_t m = pack_bf16(mean, mean), h = pack_bf16(inv - rbf(inv), inv);
    #pragma unroll
    for (int r = 0; r < 2; r++) {
      mb2[r] = __shfl_sync(0xffffffffu, m, 16 * r);
      const uint32_t hr = __shfl_sync(0xffffffffu, h, 16 * r);
      ih[r] = __byte_perm(hr, hr, 0x3232); il[r] = __byte_perm(hr, hr, 0x1010);
    }
  }
      #pragma unroll
      for (int j = 0; j < H_SPLIT; j++) norm(j);
      TL_MARK2(5, t2 == 0);
      finish_parts<0, H_SPLIT>(pa, true, t2, scr + 8192);
      named_bar_sync(5, 256);
      TL_MARK2(7, t2 == 0);
      #pragma unroll
      for (int j = 0; j < H_SPLIT; j++) { modulate(j); store(j); }
      named_bar_arrive(9, 288);
    }
  }
  #pragma unroll
  for (int j = H_SPLIT; j < 4; j++) norm(j);
  float2 pb[4 - H_SPLIT][4];
  finish_parts<H_SPLIT, 4>(pb, false, t2, scr + 8192);
  named_bar_sync(5, 256);
  TL_MARK2(17, t2 == 0);
  #pragma unroll
  for (int j = H_SPLIT; j < 4; j++) modulate(j);
  __syncwarp();
  if (lane == 0) mbar_arrive(b_head + (xv[1][3].w & zero));
  mbar_wait(b_go, 0);
  #pragma unroll
  for (int j = H_SPLIT; j < 4; j++) store(j);
  named_bar_arrive(8, 288);
}

#define MOD_AT (b_empty + 8)
#define MOD_SPLIT 16
__device__ __forceinline__ void mod_rest(uint32_t bid, uint32_t scr, uint32_t b_go, int t, const bf16* __restrict__ cvec, const bf16* __restrict__ w_mod, const bf16* __restrict__ w_r) {
  const int lane = t & 31;
  #pragma unroll 1
  for (int i = t; i < T_D / 2; i += 64) {
    const uint32_t c2 = *reinterpret_cast<const uint32_t*>(cvec + 2 * i);
    sts_u32(scr + i * 4, pack_bf16(silu_bf(bflo(c2)), silu_bf(bfhi(c2))));
  }
  named_bar_sync(11, 64);
  const bf16* wp = w_mod + (size_t)(2 * (t >> 2)) * (6 * T_D) + 2 * T_D + bid * 32 + (t & 3) * 8;
  float acc[8];
  #pragma unroll
  for (int i = 0; i < 8; i++) acc[i] = 0.f;
  #pragma unroll 1
  for (int i = 0; i < 32; i += 2) {
    if (i == MOD_SPLIT) mbar_wait(b_go, 0);
    const uint4 w0 = ldg_nc_v4(wp), w1 = ldg_nc_v4(wp + 6 * T_D), w2 = ldg_nc_v4(wp + 32 * 6 * T_D), w3 = ldg_nc_v4(wp + 33 * 6 * T_D);
    wp += 64 * 6 * T_D;
    const uint32_t s0 = lds_u32(scr + (i * 16 + (t >> 2)) * 4), s1 = lds_u32(scr + (i * 16 + 16 + (t >> 2)) * 4);
    fma8(acc, bflo(s0), w0); fma8(acc, bfhi(s0), w1); fma8(acc, bflo(s1), w2); fma8(acc, bfhi(s1), w3);
  }
  #pragma unroll
  for (int j = 0; j < 4; j++) { const bool up = lane & 16; acc[j] = (up ? acc[4 + j] : acc[j]) + __shfl_xor_sync(0xffffffffu, up ? acc[j] : acc[4 + j], 16); }
  #pragma unroll
  for (int j = 0; j < 2; j++) { const bool up = lane & 8; acc[j] = (up ? acc[2 + j] : acc[j]) + __shfl_xor_sync(0xffffffffu, up ? acc[j] : acc[2 + j], 8); }
  { const bool up = lane & 4; acc[0] = (up ? acc[1] : acc[0]) + __shfl_xor_sync(0xffffffffu, up ? acc[0] : acc[1], 4); }
  if (t >= 32) sts_f32(scr + 2048 + lane * 4, acc[0]);
  named_bar_sync(11, 64);
  if (__shfl_sync(0xffffffffu, t, 0) < 32) {
    const int kind = bid >> 5;
    float v = rbf(acc[0] + lds_f32(scr + 2048 + lane * 4));
    const int col = (bid & 31) * 32 + (lane & 3) * 8 + (lane >> 2);
    uint8_t* dst = g_col + (col >> 7) * 1536;
    if (kind == 2) v = rbf(1.0f + v);
    float vw = v * __bfloat162float(w_r[col]);
    if (kind == 2) {
      const int c = col & 127, i = (c & ~15) + ((c >> 1) & 3) * 4 + ((c >> 3) & 1) * 2 + (c & 1);
      reinterpret_cast<bf16*>(dst)[i] = __float2bfloat16_rn(vw);
      reinterpret_cast<bf16*>(dst)[128 + i] = __float2bfloat16_rn(vw - rbf(vw));
    }
    reinterpret_cast<bf16*>(dst + 512 + (kind & 1) * 512 + (kind >> 1) * 256)[col & 127] = __float2bfloat16_rn(v);
    #pragma unroll
    for (int o = 16; o > 0; o >>= 1) vw += __shfl_xor_sync(0xffffffffu, vw, o);
    if (lane == 0 && (kind == 1 || kind == 2)) g_scal[95 - bid] = vw;
  }
  #pragma unroll 1
  for (int i = bid * 64 + t; i < (int)(sizeof(g_mail) / 16); i += 128 * 64) reinterpret_cast<uint4*>(&g_mail)[i] = make_uint4(0u, 0u, 0u, 0u);
  named_bar_sync(11, 64);
  if (t == 0) red_release_add(&g_hcnt[0], 1u);
}

constexpr int AT_NBLK = T_SEQ / 128;
constexpr float AT_HEAD = 7.0f;
#define WO_LATE 12
#define QP_STAG 3
#define AT_SPLIT 28
#define AT_PIN 12
#define PINB 4
constexpr int AT_NFULL = 124;
constexpr int AT_PREG = 40, AT_CREG = 232;
constexpr uint32_t AT_SQ = 5 * 32768;
constexpr float AT_C = 0.08838834764831845f * 1.4426950408889634f;
constexpr float AT_RAW_LO = -16.0f, AT_RAW_HI = 24.0f;
constexpr float AT_RAW_SUM = 281474976710656.0f, AT_RAW_MIN = 9.094947017729282e-13f;
constexpr uint32_t AT_SBAR = AT_SQ + 65536 + 256;
constexpr uint32_t AT_SMEM = AT_SQ + 65536 + 3072;

__device__ __forceinline__ uint32_t ring_slot(uint32_t t) { return t - 5u * ((t * 205u) >> 10); }
__device__ __forceinline__ uint32_t qp_pos(uint32_t j, uint32_t it) { return 4u * it + (j & 3u) + ((j & 3u) == 3u ? it : 0u); }
__device__ __forceinline__ uint32_t ring_par(uint32_t t) { return ((t * 205u) >> 10) & 1u; }
__device__ __forceinline__ void softmax_rowmax(const float (&s)[64], float& mx0, float& mx1) {
  float a0 = fmaxf(s[0], s[1]), a1 = fmaxf(s[4], s[5]), a2 = fmaxf(s[8], s[9]), a3 = fmaxf(s[12], s[13]);
  float b0 = fmaxf(s[2], s[3]), b1 = fmaxf(s[6], s[7]), b2 = fmaxf(s[10], s[11]), b3 = fmaxf(s[14], s[15]);
  #pragma unroll
  for (int j = 4; j < 16; j += 4) {
    a0 = fmaxf(a0, fmaxf(s[4 * j + 0], s[4 * j + 1]));  b0 = fmaxf(b0, fmaxf(s[4 * j + 2], s[4 * j + 3]));
    a1 = fmaxf(a1, fmaxf(s[4 * j + 4], s[4 * j + 5]));  b1 = fmaxf(b1, fmaxf(s[4 * j + 6], s[4 * j + 7]));
    a2 = fmaxf(a2, fmaxf(s[4 * j + 8], s[4 * j + 9]));  b2 = fmaxf(b2, fmaxf(s[4 * j + 10], s[4 * j + 11]));
    a3 = fmaxf(a3, fmaxf(s[4 * j + 12], s[4 * j + 13])); b3 = fmaxf(b3, fmaxf(s[4 * j + 14], s[4 * j + 15]));
  }
  mx0 = fmaxf(fmaxf(a0, a1), fmaxf(a2, a3));
  mx1 = fmaxf(fmaxf(b0, b1), fmaxf(b2, b3));
  mx0 = fmaxf(mx0, __shfl_xor_sync(0xffffffffu, mx0, 1));
  mx1 = fmaxf(mx1, __shfl_xor_sync(0xffffffffu, mx1, 1));
  mx0 = fmaxf(mx0, __shfl_xor_sync(0xffffffffu, mx0, 2));
  mx1 = fmaxf(mx1, __shfl_xor_sync(0xffffffffu, mx1, 2));
}
__device__ __forceinline__ void softmax_sub(float (&s)[64], float mc0, float mc1) {
  #pragma unroll
  for (int j = 0; j < 16; j++) { s[4 * j] -= mc0; s[4 * j + 1] -= mc0; s[4 * j + 2] -= mc1; s[4 * j + 3] -= mc1; }
}
template <int LO, int HI>
__device__ __forceinline__ void softmax_exp(float (&s)[64]) {
  #pragma unroll
  for (int i = LO; i < HI; i++) s[i] = ex2_approx(s[i]);
}
__device__ __forceinline__ bool softmax_mode(const float (&s)[64], float& mc0, float& mc1) {
  softmax_rowmax(s, mc0, mc1);
  const bool raw = __all_sync(0xffffffffu, mc0 >= AT_RAW_LO && mc0 <= AT_RAW_HI && mc1 >= AT_RAW_LO && mc1 <= AT_RAW_HI);
  mc0 += AT_HEAD; mc1 += AT_HEAD;
  return raw;
}
__device__ __forceinline__ void rowsum_p(const uint32_t (&p)[32], uint32_t& t0, uint32_t& t1) {
  uint32_t a[16];
  #pragma unroll
  for (int i = 0; i < 8; i++) { a[2 * i] = badd2(p[4 * i], p[4 * i + 2]); a[2 * i + 1] = badd2(p[4 * i + 1], p[4 * i + 3]); }
  #pragma unroll
  for (int i = 0; i < 4; i++) { a[2 * i] = badd2(a[4 * i], a[4 * i + 2]); a[2 * i + 1] = badd2(a[4 * i + 1], a[4 * i + 3]); }
  t0 = badd2(badd2(a[0], a[2]), badd2(a[4], a[6]));
  t1 = badd2(badd2(a[1], a[3]), badd2(a[5], a[7]));
}
__device__ __forceinline__ void add_rowsum(const uint32_t (&p)[32], float& l0, float& l1) {
  uint32_t t0, t1;
  rowsum_p(p, t0, t1);
  l0 += bflo(t0) + bfhi(t0); l1 += bflo(t1) + bfhi(t1);
}
__device__ __forceinline__ void pack_p(uint32_t (&p)[32], const float (&s)[64]) {
  #pragma unroll
  for (int i = 0; i < 32; i++) p[i] = pack_bf16(s[2 * i], s[2 * i + 1]);
}
__device__ __noinline__ void attn_rows_exact(uint32_t bid, uint32_t sq, uint32_t so, int hsel, const bf16* __restrict__ kh, const bf16* __restrict__ vh) {
  const int warp = (threadIdx.x >> 5) & 3, lane = threadIdx.x & 31;
  const size_t hofs = (size_t)((bid < 128 ? bid >> 4 : 15) * 2 + hsel) * T_SEQ * T_DH;
  kh += hofs; vh += hofs;
  #pragma unroll 1
  for (int r = 16 * warp; r < 16 * warp + 16; r++) {
    const uint32_t ad = (lane >> 4) * 16384 + r * 128 + ((((lane & 15) >> 1) ^ (r & 7)) << 4) + (lane & 1) * 8;
    uint2 qv; asm volatile("ld.shared.v2.u32 {%0, %1}, [%2];" : "=r"(qv.x), "=r"(qv.y) : "r"(sq + ad) : "memory");
    const float q0 = bflo(qv.x), q1 = bfhi(qv.x), q2 = bflo(qv.y), q3 = bfhi(qv.y);
    float m = -INFINITY, l = 0.f, o0 = 0.f, o1 = 0.f, o2 = 0.f, o3 = 0.f;
    #pragma unroll 1
    for (int key = 0; key < T_SEQ; key++) {
      const uint2 kv = *reinterpret_cast<const uint2*>(kh + (size_t)key * T_DH + lane * 4);
      const uint2 vv = *reinterpret_cast<const uint2*>(vh + (size_t)key * T_DH + lane * 4);
      float sc = (q0 * bflo(kv.x) + q1 * bfhi(kv.x)) + (q2 * bflo(kv.y) + q3 * bfhi(kv.y));
      #pragma unroll
      for (int o = 16; o > 0; o >>= 1) sc += __shfl_xor_sync(0xffffffffu, sc, o);
      const float mn = fmaxf(m, sc);
      const float al = (m == mn) ? 1.0f : ex2_approx(m - mn), p = rbf(ex2_approx(sc - mn));
      m = mn;
      l = fmaf(l, al, p);
      o0 = fmaf(o0, al, p * bflo(vv.x)); o1 = fmaf(o1, al, p * bfhi(vv.x));
      o2 = fmaf(o2, al, p * bflo(vv.y)); o3 = fmaf(o3, al, p * bfhi(vv.y));
    }
    const float inv = rcp_approx(l);
    asm volatile("st.shared.v2.u32 [%0], {%1, %2};" :: "r"(so + ad), "r"(pack_bf16(o0 * inv, o1 * inv)), "r"(pack_bf16(o2 * inv, o3 * inv)) : "memory");
  }
}
__device__ __forceinline__ void issue_qk(float (&s)[64], const uint32_t (&q)[32], uint32_t k_lo) {
  wgmma_fence();
  wgmma_m64n128k16_rs<0>(s, q[0], q[1], q[2], q[3], k_lo, 0);
  wgmma_m64n128k16_rs<2>(s, q[4], q[5], q[6], q[7], k_lo, 1);
  wgmma_m64n128k16_rs<4>(s, q[8], q[9], q[10], q[11], k_lo, 1);
  wgmma_m64n128k16_rs<6>(s, q[12], q[13], q[14], q[15], k_lo, 1);
  wgmma_m64n128k16_rs<1024>(s, q[16], q[17], q[18], q[19], k_lo, 1);
  wgmma_m64n128k16_rs<1026>(s, q[20], q[21], q[22], q[23], k_lo, 1);
  wgmma_m64n128k16_rs<1028>(s, q[24], q[25], q[26], q[27], k_lo, 1);
  wgmma_m64n128k16_rs<1030>(s, q[28], q[29], q[30], q[31], k_lo, 1);
  wgmma_commit();
}
__device__ __forceinline__ void issue_pv(float (&o)[64], const uint32_t (&p)[32], uint32_t v_lo, int accumulate) {
  wgmma_fence();
  wgmma_m64n128k16_rs_tb<0>(o, p[0], p[1], p[2], p[3], v_lo, accumulate);
  wgmma_m64n128k16_rs_tb<128>(o, p[4], p[5], p[6], p[7], v_lo, 1);
  wgmma_m64n128k16_rs_tb<256>(o, p[8], p[9], p[10], p[11], v_lo, 1);
  wgmma_m64n128k16_rs_tb<384>(o, p[12], p[13], p[14], p[15], v_lo, 1);
  wgmma_m64n128k16_rs_tb<512>(o, p[16], p[17], p[18], p[19], v_lo, 1);
  wgmma_m64n128k16_rs_tb<640>(o, p[20], p[21], p[22], p[23], v_lo, 1);
  wgmma_m64n128k16_rs_tb<768>(o, p[24], p[25], p[26], p[27], v_lo, 1);
  wgmma_m64n128k16_rs_tb<896>(o, p[28], p[29], p[30], p[31], v_lo, 1);
  wgmma_commit();
}
__device__ __forceinline__ void block_end(uint32_t zero, uint32_t bar) {
  #pragma unroll 1
  for (uint32_t i = 0; i < zero; i++) mbar_arrive(bar);
}
__device__ __forceinline__ void rescale_o(float (&o)[64], float al0, float al1) {
  #pragma unroll
  for (int j = 0; j < 16; j++) { o[4 * j] *= al0; o[4 * j + 1] *= al0; o[4 * j + 2] *= al1; o[4 * j + 3] *= al1; }
}

__device__ __forceinline__ void stage_o(const float (&o)[64], float i0, float i1, uint32_t dst, int lane) {
  #pragma unroll
  for (int J = 0; J < 16; J += 2)
    stmatrix_x4(dst + (J >> 3) * 16384 + ((((J & 7) + (lane >> 4)) ^ (lane & 7)) << 4),
                pack_bf16(o[4 * J + 0] * i0, o[4 * J + 1] * i0), pack_bf16(o[4 * J + 2] * i1, o[4 * J + 3] * i1),
                pack_bf16(o[4 * J + 4] * i0, o[4 * J + 5] * i0), pack_bf16(o[4 * J + 6] * i1, o[4 * J + 7] * i1));
}
__device__ __forceinline__ bool finish_l(float& l0, float& l1) {
  l0 += __shfl_xor_sync(0xffffffffu, l0, 1); l1 += __shfl_xor_sync(0xffffffffu, l1, 1);
  l0 += __shfl_xor_sync(0xffffffffu, l0, 2); l1 += __shfl_xor_sync(0xffffffffu, l1, 2);
  const bool redo = __any_sync(0xffffffffu, !(l0 <= AT_RAW_SUM && l1 <= AT_RAW_SUM && l0 >= AT_RAW_MIN && l1 >= AT_RAW_MIN));
  l0 = rcp_approx(l0); l1 = rcp_approx(l1);
  return redo;
}
template <int J0>
__device__ __forceinline__ void stage_q(const float (&acc)[128], float c, uint32_t dst, int lane) {
  #pragma unroll
  for (int J = J0; J < J0 + 16; J += 2)
    stmatrix_x4(dst + (J >> 3) * 16384 + ((((J & 7) + (lane >> 4)) ^ (lane & 7)) << 4),
                pack_bf16(acc[4 * J + 0] * c, acc[4 * J + 1] * c), pack_bf16(acc[4 * J + 2] * c, acc[4 * J + 3] * c),
                pack_bf16(acc[4 * J + 4] * c, acc[4 * J + 5] * c), pack_bf16(acc[4 * J + 6] * c, acc[4 * J + 7] * c));
}
__device__ __forceinline__ void store_o(const CUtensorMap* tmO, uint32_t src, int head, int row) {
  tma_store_2d(tmO, src, head * T_DH, row);
  tma_store_2d(tmO, src + 16384, head * T_DH + 64, row);
  bulk_commit();
}
__device__ __forceinline__ void mma_bf16(float (&d)[4], uint32_t a0, uint32_t a1, uint32_t a2, uint32_t a3, uint32_t b0, uint32_t b1) {
  asm volatile("mma.sync.aligned.m16n8k16.row.col.f32.bf16.bf16.f32 {%0, %1, %2, %3}, {%4, %5, %6, %7}, {%8, %9}, {%0, %1, %2, %3};"
               : "+f"(d[0]), "+f"(d[1]), "+f"(d[2]), "+f"(d[3]) : "r"(a0), "r"(a1), "r"(a2), "r"(a3), "r"(b0), "r"(b1));
}
struct GemvSel { uint32_t lo0, hi0, lo1, hi1; };
__device__ __forceinline__ GemvSel gemv_sel(int lane) {
  const uint32_t lo = (lane & 8) ? 0x1044u : 0x4410u, hi = (lane & 8) ? 0x3244u : 0x4432u;
  GemvSel s; s.lo0 = (lane & 16) ? 0x4444u : lo; s.hi0 = (lane & 16) ? 0x4444u : hi; s.lo1 = (lane & 16) ? lo : 0x4444u; s.hi1 = (lane & 16) ? hi : 0x4444u;
  return s;
}
#define GEMV_B0(j, h, s) __byte_perm((j) < 2 ? (h).x : (h).y, 0u, ((j) & 1) ? (s).hi0 : (s).lo0)
#define GEMV_B1(j, h, s) __byte_perm((j) < 2 ? (h).x : (h).y, 0u, ((j) & 1) ? (s).hi1 : (s).lo1)
__device__ __forceinline__ float4 gemv_out(const float (&d)[4], int lane) {
  const bool tk = lane & 1;
  const float r0 = __shfl_xor_sync(0xffffffffu, tk ? d[0] : d[1], 1), r1 = __shfl_xor_sync(0xffffffffu, tk ? d[2] : d[3], 1);
  return tk ? make_float4(r0, d[1], r1, d[3]) : make_float4(d[0], r0, d[2], r1);
}
#define OG_NG 8
#define PUT_N 2
#define H_STAG 2
#define AL_P 60
#define AL_SLEEP 1200
#define AL_MAX 800
#define POLL_NS 200
#define OG_PROF 0xECCBB988u
#define RK_P 24
#define RANK 1
__host__ __device__ constexpr int og_pre(int tile) { return (OG_PROF >> ((tile >> 4) * 4)) & 15; }
constexpr int OG_PRE2 = og_pre(127), OG_HSUM = og_pre(0) + og_pre(16) + og_pre(32) + og_pre(48) + og_pre(64) + og_pre(80) + og_pre(96);
#define OG_JOBS 7
#define OG_GRP 6
#define LD_FIRST 2
#define LD_STAG (OG_GRP / 2)
constexpr int OG_ST = 5, OG_NKB = T_DQKV / 64 - og_pre(0), OG_MOE = T_F / 32;
__device__ __forceinline__ int pre_kb(int i) { return (i >> 1) * 4 + (i & 1); }
__device__ __forceinline__ int own_kb(int i, int pre) { return i < (pre & ~1) ? pre_kb(i) + 2 : i + pre; }
constexpr int OG_POS = 8;
constexpr uint32_t OG_STAGE = 32768;
constexpr uint32_t OG_SCOL = AT_SBAR + 512;
constexpr uint32_t OG_SMISC = AT_SBAR + 2048;
constexpr uint32_t OG_SWD = AT_SQ, OG_PSLOT = AT_SQ;
constexpr uint32_t OG_XSLOT = AT_SQ + 32768;
constexpr uint32_t OG_OSLOT = 1 * OG_STAGE;
constexpr uint32_t OG_SRED = 3 * OG_STAGE;
constexpr uint32_t OG_SH2 = OG_SRED + 24576;
constexpr uint32_t OG_SSTAT = OG_SRED + 16384;
constexpr uint32_t OG_SGU = OG_SRED + 8192;
constexpr uint32_t OG_SFIN = OG_SGU + 256;
#define OGM 2
#define OG_MT(b) ((((b) >> OGM) & 15) ^ (((b) & 64) ? 15 : 0))
#define OG_NT(b) (((b) & ((1 << OGM) - 1)) + (((b) >> (4 + OGM)) << OGM))
__device__ __forceinline__ int tail_tile(uint32_t sbase) { mbar_wait(sbase + AT_SBAR + 336, 0); return (int)lds_u32(sbase + AT_SBAR + 408); }
#define TAIL_SETUP \
  const uint32_t bar_full = sbase + AT_SBAR, bar_empty = bar_full + 40; \
  const uint32_t bar_wd = bar_full + 168, bar_col = bar_full + 176, bar_out = bar_full + 184, bar_end = bar_full + 192; \
  const uint32_t bar_key = bar_full + 200, bar_h2 = bar_full + 208, bar_sel = bar_full + 216; \
  const int mt = OG_MT(tb), nt = OG_NT(tb); \
  const int m0 = mt * 128, n0 = nt * 128; \
  const bool has_moe = (int)bid < OG_MOE; \
  (void)bar_empty; (void)bar_wd; (void)bar_col; (void)bar_out; (void)bar_end; (void)bar_key; (void)bar_h2; (void)bar_sel; (void)m0; (void)n0; (void)has_moe;

__device__ __forceinline__ void tail_producer(uint32_t bid, uint32_t sbase, uint32_t ph, uint64_t pol, const CUtensorMap* tmA, const CUtensorMap* tmB, const CUtensorMap* tmD) {
  const int tb = tail_tile(sbase);
  TAIL_SETUP
  uint32_t stage = OG_POS % OG_ST;
  int kb = 0;
  #pragma unroll 1
  for (int seg = 0; seg < 2; seg++) {
    mbar_wait(bar_full + 264 + 80 * seg, 0);
    fence_proxy_async_global();
    const int end = 32 + 32 * seg - og_pre(tb);
    #pragma unroll 1
    for (; kb < end; kb++) {
      const uint32_t fb = bar_full + 8 * stage, sa = sbase + stage * OG_STAGE;
      const int k0 = own_kb(kb, og_pre(tb)) * 64;
      mbar_wait(bar_empty + 8 * stage, ph);
      mbar_expect_tx(fb, OG_STAGE);
      tma_load_3d_hint(sa + 16384, tmB, k0, 2 * nt, fb, pol);
      tma_load_2d_hint(sa, tmA, k0, m0, fb, pol);
      if (++stage == OG_ST) { stage = 0; ph ^= 1; }
    }
  }
  if (has_moe) {
    stage += stage & 1;
    mbar_wait(bar_empty + 8 * stage, ph);
    mbar_expect_tx(bar_wd, OG_STAGE);
    tma_load_3d_hint(sbase + stage * OG_STAGE, tmD, bid * 32, 8, bar_wd, pol);
  }
}

__device__ __forceinline__ uint32_t out2(uint32_t x1, uint32_t mb2, uint32_t ih, uint32_t il, uint32_t c1, uint32_t sb, uint32_t gb) {
  const uint32_t h2 = badd2(bmul2(ln_norm2b(x1, mb2, ih, il), c1), sb);
  return badd2(x1, bmul2(gb, bfma2(h2, 0u, h2)));
}
#define OGTIME gtime()
#define X_PACE 200
#define Y_SLACK 96
#define OG_STAG 3
#define WD_PACE 300
__device__ __forceinline__ void tail_exchange(uint32_t bid, uint32_t sbase, const bf16* __restrict__ w_down, const bf16* __restrict__ w_r, const bf16* __restrict__ x, bf16* __restrict__ out) {
    const int lane = threadIdx.x & 31, wi = __shfl_sync(0xffffffffu, threadIdx.x >> 5, 0);
    if (wi == 3) {
      uint32_t a = bid, b = 0u;
      if (bid < AT_NFULL) mbar_wait(sbase + AT_SBAR + 312, 0);
      if (bid < OG_MOE) {
        asm volatile("mov.u32 %0, %%globaltimer_lo;" : "=r"(a));
        if (lane == 0 && (bid & 15) == 0) asm volatile("st.relaxed.gpu.global.u32 [%0], %1;" :: "l"(g_hcnt + 8 + (bid >> 4)), "r"((a & ~15u) | 8u | (bid >> 4)) : "memory");
        #pragma unroll 1
        for (unsigned int spin = 0; spin < (1u << 22) && __any_sync(0xffffffffu, b == 0u); spin++) {
          __nanosleep(200);
          asm volatile("ld.relaxed.gpu.global.u32 %0, [%1];" : "=r"(b) : "l"(g_hcnt + 8 + min(lane, 6)) : "memory");
        }
        a = RANK ? __popc(__ballot_sync(0xffffffffu, b < __shfl_sync(0xffffffffu, b, bid >> 4)) & 127u) * 16 + (bid & 15) : bid;
      }
      if (lane == 0) {
        sts_u32(sbase + AT_SBAR + 408, a);
        mbar_arrive(sbase + AT_SBAR + 336);
        b = 0u;
        if (bid < AT_NFULL) {
          unsigned int* tm = g_hcnt + 32 * (1 + (bid >> 4)) + 8;
          mbar_wait(sbase + AT_SBAR + 312, 1);
          asm volatile("mov.u32 %0, %%globaltimer_lo;" : "=r"(a));
          asm volatile("red.relaxed.gpu.global.max.u32 [%0], %1;" :: "l"(tm), "r"(a) : "memory");
          __nanosleep(AL_SLEEP);
          asm volatile("ld.relaxed.gpu.global.u32 %0, [%1];" : "=r"(b) : "l"(tm) : "memory");
          b -= a;
        }
        sts_u32(sbase + AT_SBAR + 412, b < AL_MAX ? b * 13 / 8 : 0u);
        mbar_arrive(sbase + AT_SBAR + 320);
      }
      named_bar_sync(15, 32);
    }
    const int tb = __shfl_sync(0xffffffffu, tail_tile(sbase), 0);
    TAIL_SETUP
    if (wi == 3) {
      mbar_wait(bar_full + 344, 0);
      float a = g_scal[lane], b = g_scal[32 + lane];
      #pragma unroll
      for (int i = 0; i < 3; i++) {
        const uint4 v = *reinterpret_cast<const uint4*>(g_col + nt * 1536 + i * 512 + lane * 16);
        sts_u32x4(sbase + OG_SCOL + i * 512 + lane * 16, v.x, v.y, v.z, v.w);
      }
      #pragma unroll
      for (int o = 16; o > 0; o >>= 1) { a += __shfl_xor_sync(0xffffffffu, a, o); b += __shfl_xor_sync(0xffffffffu, b, o); }
      if (lane == 0) sts_f32x2(sbase + OG_SMISC, a, b);
      const uint64_t pol = policy_evict_first();
      #pragma unroll 1
      for (int r = lane >> 4; r < 128; r += 4) {
        __nanosleep(X_PACE);
        #pragma unroll
        for (int j = 0; j < 4; j += 2)
          asm volatile("cp.async.cg.shared.global.L2::cache_hint [%0], [%1], 16, %2;" :: "r"(sbase + OG_XSLOT + (lane & 8) * 2048 + (r + j) * 128 + (((lane ^ (r + j)) & 7) << 4)),
                       "l"(x + (size_t)(m0 + r + j) * T_D + n0 + (lane & 15) * 8), "l"(pol) : "memory");
      }
      asm volatile("cp.async.wait_all;" ::: "memory");
      __syncwarp();
      if (lane == 0) mbar_arrive(bar_col);
    } else if (wi == 2) {
      if (elect_one()) {
        const uint32_t b_free = bar_full + (bid < AT_NFULL ? 80 : 160);
        mbar_wait(b_free, 1);
        #pragma unroll 1
        for (unsigned int i = 0; i < (1u << 20) && ld_acquire(&g_hcnt[32 * (1 + (tb >> 3)) + 4 + ((tb >> 1) & 3)]) == 0u; i++) __nanosleep(POLL_NS);
        TL_MARK2(23, true);
        fence_proxy_async_global();
        TL_MARK2(4, true);
        mbar_expect_tx(bar_full + 272, 32768);
        bulk_load_hint(sbase + OG_PSLOT, g_pre + tb * 2048, 32768, bar_full + 272, policy_evict_first());
      }
      named_bar_sync(14, 32);
      if (has_moe) {
        mbar_wait(bar_full + 96, 1); mbar_wait(bar_full + 304, 0);
        const uint64_t pol = policy_evict_first();
        #pragma unroll 1
        for (int r = 0; r < 32; r++) {
          __nanosleep(WD_PACE);
          #pragma unroll
          for (int j = 0; j < 2; j++)
            asm volatile("cp.async.cg.shared.global.L2::cache_hint [%0], [%1], 16, %2;" :: "r"(sbase + OG_SWD + (4 * j + (lane >> 3)) * 4096 + r * 128 + (((lane ^ r) & 7) << 4)),
                         "l"((const uint8_t*)w_down + (size_t)bid * 65536 + r * 2048 + j * 512 + lane * 16), "l"(pol) : "memory");
        }
        asm volatile("cp.async.wait_all;" ::: "memory");
        __syncwarp();
        if (lane == 0) mbar_arrive(bar_wd);
      }
    }
    const uint4 wrv = ldg_nc_v4(w_r + threadIdx.x * 8);
    mbar_wait(bar_end, 0);
    if (threadIdx.x == 96) XT(10);
    TL_MARK2(22, lane == 0);
    if (wi == 0) {
      uint32_t k1 = 0u, k2 = 0u;
      #pragma unroll 1
      for (unsigned int spin = 0; spin < (1u << 22) && __any_sync(0xffffffffu, k1 == 0u); spin++) asm volatile("ld.relaxed.gpu.global.u32 %0, [%1];" : "=r"(k1) : "l"(g_key + lane) : "memory");
      TL_MARK2(28, lane == 0);
      warp_top2(k1, k2);
      if (lane == 0) {
        const uint32_t r1 = 0xffffu - (k1 & 0xffffu), r2 = 0xffffu - (k2 & 0xffffu);
        sts_u32x4(sbase + OG_SMISC + 64, r1, r2, (r1 >> 7) * 2, (r2 >> 7) * 2 + ((r1 >> 7) == (r2 >> 7)));
        mbar_arrive(bar_sel);
      }
    } else if (wi < 3) {
          mbar_wait(bar_key, 0);
          const uint4 kk = lds_u32x4(sbase + OG_SSTAT + 1024 + lane * 16);
          uint32_t k1 = max(kk.x, kk.y), k2 = min(kk.x, kk.y);
          k2 = max(max(k2, min(kk.z, kk.w)), min(k1, max(kk.z, kk.w))); k1 = max(k1, max(kk.z, kk.w));
          warp_top2(k1, k2);
          if (wi == 1) {
            if (lane == 0) {
              if (nt == (mt & 7)) st_relaxed2(g_key + mt * 2, k1, k2);
              sts_u32x2(sbase + OG_SMISC + 96, (~k1 >> 4) & 7u, (~k2 >> 4) & 7u);
              mbar_arrive(bar_full + 352);
            }
            TL_MARK2(27, lane == 0);
          } else {
            const uint32_t r = (~((lane & 16) ? k2 : k1)) & 127u, ch = lane & 15;
            const uint2 st = lds_u32x2(sbase + OG_SSTAT + r * 8);
            const uint4 xc = lds_u32x4(sbase + OG_XSLOT + (ch >> 3) * 16384 + r * 128 + (((ch ^ r) & 7) << 4));
            const uint4 c1 = lds_u32x4(sbase + OG_SCOL + 768 + ch * 16), sh = lds_u32x4(sbase + OG_SCOL + 1024 + ch * 16);
            const float inr = __uint_as_float(st.y);
            float* dst = reinterpret_cast<float*>(g_cand + (mt * 2 + (lane >> 4)) * 256 + nt * 16 + ch);
            st_tagged4(dst + 512, __uint_as_float(ln_mod2(xc.x, st.x, inr, c1.x, sh.x)), __uint_as_float(ln_mod2(xc.y, st.x, inr, c1.y, sh.y)),
                       __uint_as_float(ln_mod2(xc.z, st.x, inr, c1.z, sh.z)), __uint_as_float(ln_mod2(xc.w, st.x, inr, c1.w, sh.w)));
            st_tagged4(dst, __uint_as_float(xc.x), __uint_as_float(xc.y), __uint_as_float(xc.z), __uint_as_float(xc.w));
          }
    }
    mbar_wait(bar_sel, 0);
    const uint4 sel = lds_u32x4(sbase + OG_SMISC + 64);
    const int sel0 = (int)sel.x, sel1 = (int)sel.y;
    {
      const float* src0 = reinterpret_cast<const float*>(g_cand + sel.z * 256 + 128 + threadIdx.x);
      const float* src1 = reinterpret_cast<const float*>(g_cand + sel.w * 256 + 128 + threadIdx.x);
      float4 h0, h1;
      #pragma unroll 1
      for (unsigned int spin = 0; spin < (1u << 20); spin++) { h0 = ld_tagged4(src0); h1 = ld_tagged4(src1); if (__all_sync(0xffffffffu, tagged4(h0) & tagged4(h1))) break; }
      sts_f32x4(sbase + OG_SH2 + threadIdx.x * 16, h0.x, h0.y, h0.z, h0.w);
      sts_f32x4(sbase + OG_SH2 + 2048 + threadIdx.x * 16, h1.x, h1.y, h1.z, h1.w);
      __syncwarp();
      if (lane == 0) mbar_arrive(bar_h2);
      TL_MARK2(12, lane == 0);
      if (bid >> 6) h0 = h1;
      float v[8], wr[8];
      unpack8(make_uint4(__float_as_uint(h0.x), __float_as_uint(h0.y), __float_as_uint(h0.z), __float_as_uint(h0.w)), v); unpack8(wrv, wr);
      float r = 0.f;
      #pragma unroll
      for (int i = 0; i < 8; i++) r = fmaf(v[i], wr[i], r);
      #pragma unroll
      for (int o = 16; o > 0; o >>= 1) r += __shfl_xor_sync(0xffffffffu, r, o);
      if (lane == 0) sts_f32(sbase + OG_SMISC + 192 + wi * 4, r);
    }
    mbar_wait(bar_out, 0);
    {
      const uint2 cg = lds_u32x2(sbase + OG_SMISC + 96);
      #pragma unroll
      for (int i = 0; i < 4; i++) {
        const int r = (i < 2 ? cg.x : cg.y) * 16 + (i & 1) * 8 + (threadIdx.x >> 4), ch = threadIdx.x & 15;
        if (m0 + r != sel0 && m0 + r != sel1)
          *reinterpret_cast<uint4*>(out + (size_t)(m0 + r) * T_D + n0 + ch * 8) =
              lds_u32x4(sbase + OG_OSLOT + (ch >> 3) * 16384 + r * 128 + (((ch & 7) ^ (r & 7)) << 4));
      }
    }
    if (bid == 0 && threadIdx.x < 68) *reinterpret_cast<uint4*>(g_hcnt + 32 * (threadIdx.x >> 2) + 4 * (threadIdx.x & 3)) = make_uint4(0u, 0u, 0u, 0u);
    if (threadIdx.x < 64) g_modpart[bid * 64 + threadIdx.x] = 0.f;
    {
      const int tk = bid >> 6, c0 = (bid & 63) * 16;
      const uint32_t gb2 = *reinterpret_cast<const uint32_t*>(g_col + (c0 >> 7) * 1536 + 512 + 768 + ((c0 & 127) + (threadIdx.x & 14)) * 2);
      const uint32_t* xp = reinterpret_cast<const uint32_t*>(g_cand + (tk ? sel.w : sel.z) * 256) + ((c0 + (threadIdx.x & 14)) >> 1);
      uint32_t x2 = 0u;
      #pragma unroll 1
      for (unsigned int spin = 0; spin < (1u << 20) && __any_sync(0xffffffffu, x2 == 0u); spin++) asm volatile("ld.relaxed.gpu.global.u32 %0, [%1];" : "=r"(x2) : "l"(xp) : "memory");
      const float* src = g_ypart + (size_t)((threadIdx.x >> 2) * 2 + tk) * T_D + c0 + (threadIdx.x & 3) * 4;
      const bool four = threadIdx.x < (OG_MOE - 96) * 4;
      if (threadIdx.x == 0) hint_wait(CNT_Y, (uint32_t)(OG_MOE - Y_SLACK));
      named_bar_sync(10, 128);
      float4 p0, p1, p2, p3;
      #pragma unroll 1
      for (unsigned int spin = 0; spin < (1u << 20); spin++) {
        p0 = ld_tagged4(src); p1 = ld_tagged4(src + 64 * T_D); p2 = ld_tagged4(src + 128 * T_D); p3 = ld_tagged4(four ? src + 192 * T_D : src);
        if (__all_sync(0xffffffffu, tagged4(p0) & tagged4(p1) & tagged4(p2) & tagged4(p3))) break;
      }
      if (four) { p2.x += p3.x; p2.y += p3.y; p2.z += p3.z; p2.w += p3.w; }
      p0.x = (p0.x + p1.x) + p2.x; p0.y = (p0.y + p1.y) + p2.y; p0.z = (p0.z + p1.z) + p2.z; p0.w = (p0.w + p1.w) + p2.w;
      #pragma unroll
      for (int o = 4; o <= 16; o <<= 1) {
        p0.x += __shfl_xor_sync(0xffffffffu, p0.x, o); p0.y += __shfl_xor_sync(0xffffffffu, p0.y, o);
        p0.z += __shfl_xor_sync(0xffffffffu, p0.z, o); p0.w += __shfl_xor_sync(0xffffffffu, p0.w, o);
      }
      if (lane < 4) sts_f32x4(sbase + OG_SFIN + (threadIdx.x >> 5) * 64 + lane * 16, p0.x, p0.y, p0.z, p0.w);
      named_bar_sync(10, 128);
      TL_MARK2(21, threadIdx.x == 0);
      if (threadIdx.x < 16) {
        const uint32_t ya = sbase + OG_SFIN + threadIdx.x * 4, rp = sbase + OG_SMISC + 192;
        float y = (lds_f32(ya) + lds_f32(ya + 64)) + (lds_f32(ya + 128) + lds_f32(ya + 192));
        const float r = rbf((lds_f32(rp) + lds_f32(rp + 4)) + (lds_f32(rp + 8) + lds_f32(rp + 12)));
        const float rs = rbf(sigmoid_f(r));
        const uint32_t h2p = lds_u32(sbase + OG_SH2 + tk * 2048 + (c0 + (threadIdx.x & 14)) * 2);
        const float fh = (lane & 1) ? bfhi(h2p) : bflo(h2p);
        y = rbf(y);
        y = rbf(y * rs);
        const float upd = rbf(rbf(fh * 0.0f) + y);
        out[(size_t)(tk ? sel1 : sel0) * T_D + c0 + threadIdx.x] =
            __float2bfloat16_rn(((lane & 1) ? bfhi(x2) : bflo(x2)) + rbf(((lane & 1) ? bfhi(gb2) : bflo(gb2)) * rbf(fh + upd)));
      }
    }
    if (threadIdx.x == 0) XT(11);
    TL_END(4, threadIdx.x == 0);
}

__device__ __forceinline__ void load_pre(uint4* pre, uint32_t sbase, uint32_t buf, int t2) {
  mbar_wait(sbase + AT_SBAR + 272, 0);
  #pragma unroll
  for (int i = 0; i < 8; i++) pre[i] = lds_u32x4(sbase + buf + i * 4096 + t2 * 16);
}
__device__ __forceinline__ void tail_consumer(uint32_t bid, uint32_t sbase, const CUtensorMap* tmOut, const uint4 (&pre)[8], int cwg, const bf16* __restrict__ w_gate, const bf16* __restrict__ w_up) {
    const uint32_t c0 = clock_lo();
    mbar_wait(sbase + AT_SBAR + 320, 0);
    const uint2 td = lds_u32x2(sbase + AT_SBAR + 408);
    const int tb = __shfl_sync(0xffffffffu, (int)td.x, 0);
    TAIL_SETUP
    const int tid = threadIdx.x & 127, t2 = threadIdx.x - 128;
    const int warp = tid >> 5, lane = tid & 31, w8 = t2 >> 5;
    const uint32_t dbase = (sbase & 0x3FFFFu) >> 4;
    const uint32_t a_base = dbase + ((cwg * 8192) >> 4) + (1u << 16);
    const uint32_t b_base = dbase + (16384 >> 4) + (512u << 16);
    TL_MARK2(25, threadIdx.x == 128);
    const uint64_t pol = policy_evict_first();
    const bf16* pw = ((lane & 16) ? w_up : w_gate) + (size_t)(w8 * 128 + (lane & 3) * 4) * T_F + (has_moe ? bid : 0) * 32 + ((lane >> 2) & 3) * 8;
    uint4 wv[32];
    float acc[64];
    #pragma unroll
    for (int i = 0; i < 8; i++) {
      acc[8 * i] = bflo(pre[i].x); acc[8 * i + 1] = bfhi(pre[i].x); acc[8 * i + 2] = bflo(pre[i].y); acc[8 * i + 3] = bfhi(pre[i].y);
      acc[8 * i + 4] = bflo(pre[i].z); acc[8 * i + 5] = bfhi(pre[i].z); acc[8 * i + 6] = bflo(pre[i].w); acc[8 * i + 7] = bfhi(pre[i].w);
    }
    if (lane == 0) mbar_arrive(bar_full + 304);
    while (__any_sync(0xffffffffu, clock_lo() - c0 < td.y)) {}
    uint32_t stage = OG_POS % OG_ST;
    {
      uint32_t phase = (OG_POS / OG_ST) & 1, prev = 12;
      int kb = 0;
      #pragma unroll
      for (int g = 0; g <= OG_NG; g++) {
        const int end = g == OG_NG ? 64 - og_pre(tb) : LD_FIRST + g * OG_GRP + LD_STAG * cwg;
        #pragma unroll 1
        do {
          mbar_wait(bar_full + 8 * stage, phase);
          if (OG_STAG > 0 && g == OG_NG && cwg == 1 && kb == end - OG_STAG) named_bar_sync(7, 256);
          const uint32_t a_lo = a_base + stage * (OG_STAGE >> 4), b_lo = b_base + stage * (OG_STAGE >> 4);
          wgmma_fence();
          wgmma_m64n128k16_ss_tb<0, 0>(acc, a_lo, b_lo, 1);
          wgmma_m64n128k16_ss_tb<2, 128>(acc, a_lo, b_lo, 1);
          wgmma_m64n128k16_ss_tb<4, 256>(acc, a_lo, b_lo, 1);
          wgmma_m64n128k16_ss_tb<6, 384>(acc, a_lo, b_lo, 1);
          wgmma_commit();
          if (OG_STAG > 0 && g == OG_NG && cwg == 0 && kb == end - 1) named_bar_arrive(7, 256);
          wgmma_wait<1>();
          if (tid == 0) mbar_arrive(bar_empty + 8 * prev);
          prev = stage;
          if (++stage == OG_ST) { stage = 0; phase ^= 1; }
        } while (++kb < end);
        #pragma unroll
        for (int j = 4 * g; j < 4 * g + 4 && j < 32; j++) wv[j] = ldg_stream_v4(pw + (size_t)(16 * (j >> 2) + (j & 3)) * T_F, pol);
      }
    }
    mbar_wait(bar_col, 0);
    if (__builtin_expect(!has_moe, 0)) {
      load_pre(wv, sbase, AT_SQ, t2);
    }
    wgmma_wait<0>();
    fence_regs(acc);
    if (__builtin_expect(!has_moe, 0)) {
      #pragma unroll
      for (int i = 0; i < 8; i++) {
        acc[8 * i] += bflo(wv[i].x); acc[8 * i + 1] += bfhi(wv[i].x); acc[8 * i + 2] += bflo(wv[i].y); acc[8 * i + 3] += bfhi(wv[i].y);
        acc[8 * i + 4] += bflo(wv[i].z); acc[8 * i + 5] += bfhi(wv[i].z); acc[8 * i + 6] += bflo(wv[i].w); acc[8 * i + 7] += bfhi(wv[i].w);
      }
    }
    if (tid == 0) mbar_arrive(bar_end);
    TL_MARK2(9, lane == 0);
    const int q2 = 2 * (lane & 3);
    const uint32_t frag = (64 * cwg + 16 * warp + (lane & 7) + 8 * ((lane >> 3) & 1)) * 128;
    const int fsw = lane & 7, fhi = lane >> 4;
    {
      float dl[4] = {0.f, 0.f, 0.f, 0.f}, da[4] = {0.f, 0.f, 0.f, 0.f}, db[4] = {0.f, 0.f, 0.f, 0.f};
      const uint32_t tb = sbase + OG_SCOL + (lane & 8) * 32 + (lane & 3) * 8, g = lane >> 2;
      const uint32_t msk = (g == 1 || g == 2) ? 0xffffffffu : 0u, one = g == 0 ? 0x3F803F80u : 0u;
      #pragma unroll
      for (int J = 0; J < 16; J += 2) {
        const uint32_t ad = sbase + OG_XSLOT + (J >> 3) * 16384 + frag + ((((J & 7) + fhi) ^ fsw) << 4);
        uint32_t xr[4];
        ldmatrix_x4(ad, xr[0], xr[1], xr[2], xr[3]);
        const uint2 cw = lds_u32x2(tb + J * 16);
        #pragma unroll
        for (int h = 0; h < 2; h++) {
          const uint32_t ga = lds_u32(sbase + OG_SCOL + 512 + (8 * (J + h) + q2) * 2);
          xr[2 * h] = badd2(xr[2 * h], bmul2(ga, pack_bf16(acc[4 * (J + h)], acc[4 * (J + h) + 1])));
          xr[2 * h + 1] = badd2(xr[2 * h + 1], bmul2(ga, pack_bf16(acc[4 * (J + h) + 2], acc[4 * (J + h) + 3])));
        }
        stmatrix_x4(ad, xr[0], xr[1], xr[2], xr[3]);
        mma_bf16(dl, xr[0], xr[1], xr[2], xr[3], (cw.x & msk) | one, (cw.y & msk) | one);
        mma_bf16(da, xr[0], xr[1], xr[2], xr[3], xr[0], xr[2]);
        mma_bf16(db, xr[0], xr[1], xr[2], xr[3], xr[1], xr[3]);
      }
      {
        const int dsrc = (lane & ~3) + (g >> 1);
        const float qa = __shfl_sync(0xffffffffu, (g & 1) ? da[1] : da[0], dsrc), qb = __shfl_sync(0xffffffffu, (g & 1) ? db[3] : db[2], dsrc);
        const float e0 = __shfl_xor_sync(0xffffffffu, (lane & 1) ? dl[0] : dl[2], 1), e1 = __shfl_xor_sync(0xffffffffu, dl[3], 1);
        if ((lane & 3) < 2) {
          const bool hi = lane & 1;
          st_tagged4(reinterpret_cast<float*>(g_part1 + ((mt * 8 + w8) * 8 + nt) * 16 + g + (hi ? 8 : 0)),
                     hi ? e0 : dl[0], hi ? qb : qa, hi ? e1 + dl[2] : dl[1] + e0, 1.0f);
        }
      }
    }
    TL_MARK2(10, lane == 0);
    uint4 wd[16];
    if (has_moe) mbar_wait(bar_wd, 0);
    #pragma unroll
    for (int i = 0; i < 16; i++) wd[i] = lds_u32x4(sbase + (cwg ? (stage + (stage & 1)) * OG_STAGE : OG_SWD) + warp * 8192 + (i >> 3) * 4096 + (i & 6) * 512 + (i & 1) * 128 + (lane & 3) * 256 + (((lane >> 2) ^ (2 * (lane & 3) + (i & 1))) << 4));
    {
      const float* src = reinterpret_cast<const float*>(g_part1 + ((mt * 8 + w8) * 8 + (lane & 1) * 4) * 16 + (lane >> 1));
      float4 v, v1, v2, v3;
      #pragma unroll 1
      for (unsigned int spin = 0; spin < (1u << 22); spin++) {
        v = ld_tagged4(src); v1 = ld_tagged4(src + 64); v2 = ld_tagged4(src + 128); v3 = ld_tagged4(src + 192);
        if (__all_sync(0xffffffffu, tagged4(v) & tagged4(v1) & tagged4(v2) & tagged4(v3))) break;
        __nanosleep(100);
      }
      __syncwarp();
      TL_MARK2(26, lane == 0);
      v.x = (v.x + v1.x) + (v2.x + v3.x); v.y = (v.y + v1.y) + (v2.y + v3.y); v.z = (v.z + v1.z) + (v2.z + v3.z);
      v.x += __shfl_xor_sync(0xffffffffu, v.x, 1); v.y += __shfl_xor_sync(0xffffffffu, v.y, 1); v.z += __shfl_xor_sync(0xffffffffu, v.z, 1);
      const float mean = v.x * (1.0f / T_D);
      const float var = fmaxf(fmaf(-mean, mean, v.y * (1.0f / T_D)), 0.f);
      const uint32_t mb2 = pack_bf16(mean, mean);
      const float inv = rcp_approx(rbf(sqrt_approx(rbf(rbf(var) + 1e-05f))));
      {
        const float2 sc = lds_f32x2(sbase + OG_SMISC);
        const uint32_t key = rank_key(rbf(fmaf(fmaf(-bflo(mb2), sc.x, v.z), inv, sc.y)), m0 + 16 * w8 + (lane >> 1));
        mbar_wait(bar_end, 0);
        if (lane & 1) sts_u32(sbase + OG_SSTAT + 1024 + (16 * w8 + (lane >> 1)) * 4, key);
        else sts_u32x2(sbase + OG_SSTAT + (16 * w8 + (lane >> 1)) * 8, mb2, __float_as_uint(inv));
        __syncwarp();
        if (lane == 0) mbar_arrive(bar_key);
      }
      const uint32_t ih = pack_bf16(inv, inv), il = pack_bf16(inv - bflo(ih), inv - bflo(ih));
      const uint32_t mba = __shfl_sync(0xffffffffu, mb2, 2 * (lane >> 2)), mbb = __shfl_sync(0xffffffffu, mb2, 2 * (lane >> 2) + 16);
      const uint32_t iha = __shfl_sync(0xffffffffu, ih, 2 * (lane >> 2)), ihb = __shfl_sync(0xffffffffu, ih, 2 * (lane >> 2) + 16);
      const uint32_t ila = __shfl_sync(0xffffffffu, il, 2 * (lane >> 2)), ilb = __shfl_sync(0xffffffffu, il, 2 * (lane >> 2) + 16);
      #pragma unroll 2
      for (int J = 0; J < 16; J += 2) {
        const uint32_t off = (J >> 3) * 16384 + frag + ((((J & 7) + fhi) ^ fsw) << 4);
        uint32_t xr[4];
        ldmatrix_x4(sbase + OG_XSLOT + off, xr[0], xr[1], xr[2], xr[3]);
        #pragma unroll
        for (int h = 0; h < 2; h++) {
          const uint32_t ca = sbase + OG_SCOL + 512 + (8 * (J + h) + q2) * 2;
          const uint32_t c1 = lds_u32(ca + 256), sh = lds_u32(ca + 512), gb = lds_u32(ca + 768);
          xr[2 * h] = out2(xr[2 * h], mba, iha, ila, c1, sh, gb);
          xr[2 * h + 1] = out2(xr[2 * h + 1], mbb, ihb, ilb, c1, sh, gb);
        }
        stmatrix_x4(sbase + OG_OSLOT + off, xr[0], xr[1], xr[2], xr[3]);
      }
      fence_proxy_async();
      mbar_wait(bar_full + 352, 0);
      const uint2 cg = lds_u32x2(sbase + OG_SMISC + 96);
      __syncwarp();
      if (elect_one()) {
        mbar_arrive(bar_out);
        if (cg.x != w8 && cg.y != w8) {
          asm volatile("cp.async.bulk.tensor.2d.global.shared::cta.bulk_group [%0, {%2, %3}], [%1];" :: "l"(tmOut), "r"(sbase + OG_OSLOT + w8 * 2048), "r"(n0), "r"(m0 + 16 * w8) : "memory");
          asm volatile("cp.async.bulk.tensor.2d.global.shared::cta.bulk_group [%0, {%2, %3}], [%1];" :: "l"(tmOut), "r"(sbase + OG_OSLOT + 16384 + w8 * 2048), "r"(n0 + 64), "r"(m0 + 16 * w8) : "memory");
          bulk_commit();
        }
      }
      TL_MARK2(24, lane == 0);
    }
    if (has_moe) mbar_wait(bar_h2, 0);
    TL_MARK2(13, lane == 0);
    if (has_moe) {
      const GemvSel sel = gemv_sel(lane);
      {
        float d[4][4];
        #pragma unroll
        for (int c = 0; c < 4; c++) { d[c][0] = 0.f; d[c][1] = 0.f; d[c][2] = 0.f; d[c][3] = 0.f; }
        #pragma unroll
        for (int st = 0; st < 8; st++) {
          const uint2 hb = lds_u32x2(sbase + OG_SH2 + ((lane >> 2) & 1) * 2048 + (w8 * 128 + st * 16 + (lane & 3) * 4) * 2);
          #pragma unroll
          for (int j = 0; j < 4; j++) mma_bf16(d[j], wv[4 * st + j].x, wv[4 * st + j].y, wv[4 * st + j].z, wv[4 * st + j].w, GEMV_B0(j, hb, sel), GEMV_B1(j, hb, sel));
        }
        #pragma unroll
        for (int e = 0; e < 4; e++) d[0][e] = (d[0][e] + d[1][e]) + (d[2][e] + d[3][e]);
        const float4 r = gemv_out(d[0], lane);
        sts_f32x4(sbase + OG_SRED + w8 * 512 + (((lane >> 4) * 2 + (lane & 1)) * 32 + ((lane >> 2) & 3) * 8 + (lane & 2) * 2) * 4, r.x, r.y, r.z, r.w);
      }
      named_bar_sync(9, 256);
      if (t2 < 64) {
        float gp[8], up[8];
        #pragma unroll
        for (int w = 0; w < 8; w++) { gp[w] = lds_f32(sbase + OG_SRED + w * 512 + t2 * 4); up[w] = lds_f32(sbase + OG_SRED + w * 512 + 256 + t2 * 4); }
        const float gs = ((gp[0] + gp[1]) + (gp[2] + gp[3])) + ((gp[4] + gp[5]) + (gp[6] + gp[7]));
        const float us = ((up[0] + up[1]) + (up[2] + up[3])) + ((up[4] + up[5]) + (up[6] + up[7]));
        asm volatile("st.shared.u16 [%0], %1;" :: "r"(sbase + OG_SGU + ((t2 & ~15) + ((t2 >> 1) & 3) * 4 + ((t2 >> 3) & 1) * 2 + (t2 & 1)) * 2), "h"((uint16_t)pack_bf16(silu_bf(rbf(gs)) * rbf(us), 0.f)) : "memory");
      }
      named_bar_sync(9, 256);
      TL_MARK2(20, threadIdx.x == 128);
      float d[4][4];
      #pragma unroll
      for (int c = 0; c < 4; c++) { d[c][0] = 0.f; d[c][1] = 0.f; d[c][2] = 0.f; d[c][3] = 0.f; }
      #pragma unroll
      for (int st = 0; st < 2; st++) {
        const uint2 g = lds_u32x2(sbase + OG_SGU + ((lane >> 2) & 1) * 64 + st * 32 + (lane & 3) * 8);
        #pragma unroll
        for (int j = 0; j < 4; j++) {
          const uint32_t b0 = GEMV_B0(j, g, sel), b1 = GEMV_B1(j, g, sel);
          mma_bf16(d[j & 1], wd[4 * st + j].x, wd[4 * st + j].y, wd[4 * st + j].z, wd[4 * st + j].w, b0, b1);
          mma_bf16(d[2 + (j & 1)], wd[8 + 4 * st + j].x, wd[8 + 4 * st + j].y, wd[8 + 4 * st + j].z, wd[8 + 4 * st + j].w, b0, b1);
        }
      }
      #pragma unroll
      for (int e = 0; e < 4; e++) { d[0][e] += d[1][e]; d[2][e] += d[3][e]; }
      const float4 y0 = gemv_out(d[0], lane), y1 = gemv_out(d[2], lane);
      float* yp = g_ypart + (size_t)(bid * 2 + (lane & 1)) * T_D + w8 * 128 + (lane >> 2) * 8 + (lane & 2) * 2;
      st_tagged4(yp, y0.x, y0.y, y0.z, y0.w);
      st_tagged4(yp + 64, y1.x, y1.y, y1.z, y1.w);
      named_bar_sync(9, 256);
      if (t2 == 0) hint_arrive(CNT_Y);
    }
    bulk_wait_read<0>();
    TL_MARK2(14, threadIdx.x == 128);
    TL_CLK(4, 1, threadIdx.x == 128);
}

__device__ __forceinline__ int help_njobs(uint32_t bid) { return bid < 128 ? OG_JOBS : 16 - OG_JOBS; }
__device__ __forceinline__ int help_job(uint32_t bid, int i) { return (i < OG_JOBS ? 16 * i + (bid >> 7) * 2 : 112 + (i - OG_JOBS) * 2) + (bid & 3) * 4; }
__device__ __noinline__ void store_warp(uint32_t bid, uint32_t sbase, const CUtensorMap* tmO, int item0, int n_items) {
  if (elect_one()) {
    const uint32_t bars = sbase + AT_SBAR, b_q0 = bars + 80, b_ob = bars + 96, b_ordy = bars + 104, b_acq = bars + 264;
    const unsigned int* cnt = g_hcnt + 32 * (1 + OG_MT(124)) + 2;
    #pragma unroll 1
    for (int q = 0; q < 4 * n_items; q++) {
      const int item = item0 + (q >> 2) * 128, h = (q >> 1) & 1, w = q & 1;
      const bool last = (q >> 2) == n_items - 1;
      if (q == 4 * n_items - 4) { mbar_wait(bars + 288, 0); red_release_add(&g_hcnt[1], 1u); }
      mbar_wait(b_ordy + 8 * (q & 3), q >> 2);
      store_o(tmO, (h ? (last ? sbase + AT_SQ + 32768 : sbase + 2 * 32768) : sbase + AT_SQ) + w * 8192, (item >> 4) * 2 + h, (item & 15) * 128 + w * 64);
      if (w) {
        bulk_wait_read<0>();
        mbar_arrive(h ? b_ob : b_q0);
        bulk_wait<0>();
        fence_proxy_async_global();
        asm volatile("fence.acq_rel.gpu;" ::: "memory");
        hint_arrive(&g_hcnt[32 * (1 + (item & 15)) + 2 + (item >> 7)]);
        if (!h && item < 128) hint_arrive(&g_hcnt[2]);
        if (q == 5) { const int tb = tail_tile(sbase); cnt = g_hcnt + 32 * (1 + OG_MT(tb)) + 2; spin_until(cnt, 16u); mbar_arrive(b_acq); }
      }
    }
    if (n_items == 1) {
      #pragma unroll 1
      for (int i = 0; i < help_njobs(bid); i++) {
        mbar_wait(b_acq + 16, i & 1);
        TL_MARK2(23, i == OG_JOBS - 1);
        red_release_add(&g_hcnt[32 * (1 + (help_job(bid, i) >> 3)) + 4 + ((help_job(bid, i) >> 1) & 3)], 1u);
        TL_MARK2(4, i == OG_JOBS - 1);
        if (i == PRE_X - 1) { spin_until(&g_hcnt[1], 132u); mbar_arrive(b_acq + 32); }
      }
    }
    if (bid < 128) {
      if (n_items == 1) { spin_until(cnt, 16u); mbar_arrive(b_acq); }
      spin_until(&g_hcnt[0], 128u); spin_until(cnt + 1, 16u); mbar_arrive(b_acq + 80);
    }
  }
}

struct Roles { uint8_t of_sm[132]; };
__global__ void __launch_bounds__(384, 1)
fused_kernel(const __grid_constant__ CUtensorMap tmH, const __grid_constant__ CUtensorMap tmW, const __grid_constant__ CUtensorMap tmK,
            const __grid_constant__ CUtensorMap tmV, const __grid_constant__ CUtensorMap tmO, const __grid_constant__ CUtensorMap tmOl, const __grid_constant__ CUtensorMap tmWo,
            const __grid_constant__ CUtensorMap tmD, const __grid_constant__ CUtensorMap tmOut, const __grid_constant__ CUtensorMap tmM, const __grid_constant__ Roles roles, uint32_t zero,
            const uint8_t* __restrict__ pf_wo, const bf16* __restrict__ kc, const bf16* __restrict__ vc,
            const bf16* __restrict__ x, const bf16* __restrict__ cvec, const bf16* __restrict__ w_mod, const bf16* __restrict__ w_r,
            const bf16* __restrict__ w_gate, const bf16* __restrict__ w_up, const bf16* __restrict__ w_down, bf16* __restrict__ out)
{
  uint32_t bid, nsm;
  asm volatile("mov.u32 %0, %%smid;" : "=r"(bid));
  asm volatile("mov.u32 %0, %%nsmid;" : "=r"(nsm));
  bid = __shfl_sync(0xffffffffu, nsm == 132u ? (uint32_t)roles.of_sm[bid] : blockIdx.x, 0);
  extern __shared__ __align__(1024) uint8_t smem_raw[];
  const uint32_t sbase = smem_u32(smem_raw);
  const uint32_t bars = sbase + AT_SBAR;
  const uint32_t b_full = bars, b_empty = bars + 40;
  const uint32_t b_q0 = bars + 80, b_q1 = bars + 88;
  const uint32_t b_ob = bars + 96;
  const uint32_t b_ordy = bars + 104;
  const uint32_t b_pin = bars + 136;
  const uint32_t b_head = bars + 144;
  const uint32_t b_go = bars + 152;
  const uint32_t b_x = bars + 160;
  const int wg = __shfl_sync(0xffffffffu, threadIdx.x >> 7, 0);
  const bool single = bid >= AT_NFULL;
  const int item0 = __shfl_sync(0xffffffffu, bid < 128 ? (int)bid : (int)bid + 124, 0), n_items = __shfl_sync(0xffffffffu, single ? 1 : 2, 0);
  TL_START(3);
  if (threadIdx.x == 0) {
    if (sbase & 1023u) __trap();
    for (int i = 0; i < 5; i++) { mbar_init(b_full + 8 * i, 1); mbar_init(b_empty + 8 * i, 2); }
    mbar_init(b_q0, 1); mbar_init(b_q1, 8); mbar_init(b_ob, 1);
    for (int i = 0; i < 4; i++) mbar_init(b_ordy + 8 * i, 4);
    mbar_init(b_pin, 1); mbar_init(b_head, bid < 128 ? 8 : 1); mbar_init(b_go, 1); mbar_init(b_x, 1);
    mbar_init(bars + 168, 2); mbar_init(bars + 176, 1); mbar_init(bars + 184, 8); mbar_init(bars + 192, 2);
    mbar_init(bars + 200, 8); mbar_init(bars + 208, 4); mbar_init(bars + 216, 1); mbar_init(bars + 264, 1); mbar_init(bars + 272, 1); mbar_init(bars + 280, 8); mbar_init(bars + 288, 1); mbar_init(bars + 296, 1); mbar_init(bars + 304, 8); mbar_init(bars + 312, 1); mbar_init(bars + 320, 1); mbar_init(bars + 328, 1); mbar_init(bars + 336, 1); mbar_init(bars + 344, 1); mbar_init(bars + 352, 1);
    sts_u32(bars + 400, bid);
    fence_mbar_init();
  }

  if (wg == 0) {
    reg_dealloc<AT_PREG>();
    if (threadIdx.x < 32) { __syncwarp(); named_bar_arrive(6, 384); }
    if (threadIdx.x >= 64) {
      named_bar_sync(6, 384);
      if (bid < 128) {
        named_bar_sync(threadIdx.x >= 96 ? 8 : 9, 288);
        if ((threadIdx.x & 31) == 0) red_release_add(&g_hcnt[32 * (1 + (bid >> 3)) + (threadIdx.x >= 96)], 1u);
        TL_MARK2(11, threadIdx.x == 64);
      }
      if (bid < 128) {
        mbar_wait(MOD_AT, 0);
        mod_rest(bid, sbase + OG_SCOL, b_q1, threadIdx.x - 64, cvec, w_mod, w_r);
      }
    } else if (threadIdx.x >= 32) {
      named_bar_sync(6, 384);
      store_warp(bid, sbase, &tmO, item0, n_items);
      __syncwarp();
    } else {
     if (elect_one()) {
      const uint64_t pol = policy_evict_first();
      if (bid < 128) {
        mbar_expect_tx(b_x, 32768);
        if (X_DLY) { const uint32_t c0 = clock_lo(); while (clock_lo() - c0 < X_DLY) {} }
        bulk_load_hint(sbase + 4 * 32768, x + (size_t)bid * 16 * T_D, 32768, b_x, pol);
      }
      prefetch_tmap(&tmW); prefetch_tmap(&tmM); prefetch_tmap(&tmH); prefetch_tmap(&tmWo); prefetch_tmap(&tmOl);
      {
        const uint32_t c0 = clock_lo();
        while (clock_lo() - c0 < W_DLY) {}
        if (bid < 128 && (bid & 15) >= 4 * H_SPLIT) {
          mbar_expect_tx(bars + 328, 32768);
          tma_load_2d_hint(sbase + 3 * 32768, &tmM, (bid & 31) * 64, (bid >> 5) * 256, bars + 328, pol);
        }
        while (clock_lo() - c0 < W_DLY + W_FIRST) {}
      }
      uint32_t slot = 0, ph = 1;
      #pragma unroll 1
      for (int it = 0; it < n_items; it++) {
        const int item = item0 + it * 128, hp = item >> 4, qt = item & 15;
        const bool first = it == 0;
        #pragma unroll 1
        for (int j = 0; j < T_D / 64; j++) {
          const uint32_t sl = ring_slot(qp_pos(j, it)), fb = b_full + 8 * sl;
          mbar_wait(b_empty + 8 * sl, ring_par(qp_pos(j, it)) ^ ((j >> 2) & 1) ^ 1);
          if (first && j == 3) mbar_wait(b_head, 0);
          mbar_expect_tx(fb, 49152);
          tma_load_3d_hint(sbase + sl * 32768, &tmW, j * 64, hp * 4, fb, pol);
          if (first && j < PRE_B) {
            if (j == PRE_B - 1) {
              spin_until(&g_hcnt[32 * (1 + qt)], 8u);
              TL_MARK2(16, true);
              fence_proxy_async_global();
              #pragma unroll 1
              for (int i = 0; i < PRE_B; i++) tma_load_2d(sbase + AT_SQ + i * 16384, &tmH, i * 64, qt * 128, b_full + 8 * i);
              mbar_arrive(b_go);
            }
          } else {
            if (first && j == 4 * H_SPLIT) { spin_until(&g_hcnt[32 * (1 + qt) + 1], 8u); fence_proxy_async_global(); }
            if (!first && (j == 0 || j == 2)) mbar_wait(j ? b_q1 : b_q0, 0);
            tma_load_2d_hint(sbase + AT_SQ + (j & 3) * 16384, &tmH, j * 64, qt * 128, fb, first ? pol_normal() : pol);
          }
        }
        #pragma unroll 1
        for (int j = 0; j < 4 * AT_NBLK; j++) {
          const bool isv = (j > 0 && !(j & 1)) || j == 4 * AT_NBLK - 1;
          const int row = hp * 2 * T_SEQ + (isv ? (j - 1) >> 1 : (j + 1) >> 1) * 128;
          const uint32_t fb = b_full + 8 * slot;
          mbar_wait(b_empty + 8 * slot, ph);
          if (!first && j == 3) mbar_wait(b_ob, 0);
          if (j == 4 && it == n_items - 1) mbar_arrive(bars + 288);
          if ((j == AL_P || j == RK_P) && it == 1) mbar_arrive(bars + 312);
          mbar_expect_tx(fb, 32768);
          tma_load_3d_hint(sbase + slot * 32768, isv ? &tmV : &tmK, row, 0, fb, pol);
          if (it == 1 && isv && j >= 2 * WO_LATE && j < 2 * WO_LATE + 32 && bid < OG_NKB)
            l2_prefetch_bulk(pf_wo + (size_t)own_kb(bid, og_pre(0)) * 131072 + ((j >> 1) - WO_LATE) * 8192, 8192);
          if (++slot == 5) { slot = 0; ph ^= 1; }
        }
      }
      if (__builtin_expect(single, 0)) {
        spin_until(&g_hcnt[2], 128u);
        fence_proxy_async_global();
        const int nj = OG_HSUM + (help_njobs(bid) - OG_JOBS) * OG_PRE2;
        int ji = 0, job = help_job(bid, 0), kk = 0;
        #pragma unroll 1
        for (int j = 0; j < nj; j++) {
          const uint32_t sl = ring_slot(qp_pos(j, 1)), fb = b_full + 8 * sl;
          mbar_wait(b_empty + 8 * sl, ring_par(qp_pos(j, 1)) ^ ((j >> 2) & 1) ^ 1);
          mbar_expect_tx(fb, 49152);
          tma_load_3d_hint(sbase + sl * 32768, &tmWo, pre_kb(kk) * 64, OG_NT(job) * 2, fb, pol_normal());
          tma_load_3d_hint(sbase + sl * 32768 + 16384, &tmWo, pre_kb(kk) * 64, OG_NT(job) * 2 + 2, fb, pol_normal());
          if (j == 0 || j == 2) mbar_wait(j ? b_ob : b_q0, 0);
          tma_load_2d_hint(sbase + AT_SQ + (j & 3) * 16384, &tmOl, pre_kb(kk) * 64, OG_MT(job) * 128, fb, pol);
          if (++kk == og_pre(job)) { kk = 0; job = help_job(bid, ++ji); }
        }
      }
      if (bid < 128) {
        if (single) mbar_wait(b_x, 1);
        tail_producer(bid, sbase, 0, pol, &tmOl, &tmWo, &tmD);
      }
     }
    }
    named_bar_sync(12 + (threadIdx.x >> 5), 32);
    if (bid < 128) tail_exchange(bid, sbase, w_down, w_r, x, out);
  } else {
    if (bid < 128) head_phase(bid, sbase + AT_SQ + 49152, sbase + 4 * 32768, b_x, b_go, b_head, threadIdx.x - 128, zero, cvec, w_mod);
    else { named_bar_sync(6, 384); if (threadIdx.x == 128) mbar_arrive(b_head); }
    TL_MARK2(0, threadIdx.x == 128);
    reg_alloc<AT_CREG>();
    const int cwg = wg - 1;
    const int tid = threadIdx.x & 127;
    const int warp = tid >> 5, lane = tid & 31;
    const uint32_t dbase = (sbase & 0x3FFFFu) >> 4;
    const uint32_t k_base = dbase + (1u << 16);
    const uint32_t v_base = dbase + (1024u << 16);
    const uint32_t w_base = dbase + (512u << 16);
    const uint32_t q_lo = dbase + ((AT_SQ + cwg * 8192) >> 4) + (1u << 16);
    const uint32_t frag = cwg * 8192 + (16 * warp + (lane & 7) + 8 * ((lane >> 3) & 1)) * 128;
    if (cwg == 1) named_bar_arrive(1, 256);
    bool raw = false;
    uint4 pre[8];
    #pragma unroll 1
    for (int it = 0; it < n_items; it++) {
      const bool more = it + 1 < n_items;
      constexpr int nkb = T_D / 64;
      const int ta = __shfl_sync(0xffffffffu, 4 * it, 0);
      float acc[128];
      {
        FS(2 * it, 0);
        #pragma unroll
        for (int i = 0; i < 128; i++) asm volatile("" : "=f"(acc[i]));
        {
          const uint32_t slot = ring_slot(ta), b_lo = w_base + slot * 2048;
          mbar_wait(b_full + 8 * slot, ring_par(ta));
          wgmma_fence();
          wgmma_m64n256k16_ss_tb<0, 0>(acc, q_lo, b_lo, 0);
          wgmma_m64n256k16_ss_tb<2, 128>(acc, q_lo, b_lo, 1);
          wgmma_m64n256k16_ss_tb<4, 256>(acc, q_lo, b_lo, 1);
          wgmma_m64n256k16_ss_tb<6, 384>(acc, q_lo, b_lo, 1);
          wgmma_commit();
        }
        #pragma unroll 1
        for (int j = 1; j < nkb; j++) {
          const uint32_t slot = ring_slot(qp_pos(j, ta >> 2));
          mbar_wait(b_full + 8 * slot, ring_par(qp_pos(j, ta >> 2)) ^ ((j >> 2) & 1));
          if (QP_STAG > 0 && cwg == 1 && j == nkb - QP_STAG) named_bar_sync(7, 256);
          const uint32_t a_lo = q_lo + (j & 3) * 1024, b_lo = w_base + slot * 2048;
          wgmma_fence();
          wgmma_m64n256k16_ss_tb<0, 0>(acc, a_lo, b_lo, 1);
          wgmma_m64n256k16_ss_tb<2, 128>(acc, a_lo, b_lo, 1);
          wgmma_m64n256k16_ss_tb<4, 256>(acc, a_lo, b_lo, 1);
          wgmma_m64n256k16_ss_tb<6, 384>(acc, a_lo, b_lo, 1);
          wgmma_commit();
          if (QP_STAG > 0 && cwg == 0 && j == nkb - 1) named_bar_arrive(7, 256);
          if (j > 0) {
            wgmma_wait<1>();
            if (tid == 0) mbar_arrive(b_empty + 8 * ring_slot(qp_pos(j - 1, ta >> 2)));
          }
        }
        wgmma_wait<0>();
        fence_regs(acc);
        FS(2 * it, 1);
        TL_MARK2(29, threadIdx.x == 256 && it == 0);
        if (tid == 0) mbar_arrive(b_empty + 24);
      }
      float o[64], s[64];
      uint32_t p[32], q[32];
      #pragma unroll
      for (int i = 0; i < 32; i++) q[i] = pack_bf16(acc[2 * i] * AT_C, acc[2 * i + 1] * AT_C);
      zero_regs(s);
      const uint32_t sq = sbase + AT_SQ + cwg * 8192;
      float mc0, mc1, al0 = 1.0f, al1 = 1.0f, l0 = 0.f, l1 = 0.f, lp0 = 0.f, lp1 = 0.f;
      bool redo0 = false;
      FS(2 * it, 2);
      mbar_wait(b_full + 8 * ring_slot(ta), ring_par(ta));
      named_bar_sync(1 + cwg, 256);
      FS(2 * it, 3);
      issue_qk(s, q, k_base + ring_slot(ta) * 2048);
      pass_turn(cwg);
      bool ready = mbar_test(b_full + 8 * ring_slot(ta + 1), ring_par(ta + 1)) & mbar_test(b_full + 8 * ring_slot(ta + 2), ring_par(ta + 2));
      stage_q<16>(acc, AT_C, sbase + AT_SQ + frag, lane);
      wgmma_wait<0>();
      fence_regs(s);
      if (tid == 0) mbar_arrive(b_empty + 8 * ring_slot(ta));
      mc0 = 0.f; mc1 = 0.f;
      if (!raw) {
        raw = softmax_mode(s, mc0, mc1);
        if (__builtin_expect(!raw, 0)) softmax_sub(s, mc0, mc1);
      }
      softmax_exp<0, 64>(s);
      #pragma unroll
      for (int J = 0; J < 16; J += 2)
        stmatrix_x4(sbase + AT_SQ + frag + (J >> 3) * 16384 + ((((J & 7) + (lane >> 4)) ^ (lane & 7)) << 4), q[2 * J], q[2 * J + 1], q[2 * J + 2], q[2 * J + 3]);
      pack_p(p, s);
      zero_regs(o);
      FS(2 * it, 4);
      uint32_t ks = ring_slot(ta + 1), vs = ring_slot(ta + 2), kp = ring_par(ta + 1), vp = ring_par(ta + 2);
      auto finish_head = [&]() {
        FS(2 * it, 5);
        redo0 = finish_l(lp0, lp1);
        if (!redo0) stage_o(o, lp0, lp1, sbase + AT_SQ + frag, lane);
        FS(2 * it + 1, 4);
      };
      if (!ready) { mbar_wait(b_full + 8 * ks, kp); mbar_wait(b_full + 8 * vs, vp); }
      #pragma unroll 1
      for (int n = 1; n < 2 * AT_NBLK; n++) {
        named_bar_sync(1 + cwg, 256);
        issue_qk(s, q, k_base + ks * 2048);
        if (n == AT_NBLK + 1) finish_head();
        issue_pv(o, p, v_base + vs * 2048, (n & 15) != 1);
        pass_turn(cwg);
        wgmma_wait<1>();
        fence_regs(s);
        if (tid == 0) mbar_arrive(b_empty + 8 * ks);
        if (__builtin_expect(!raw || (uint32_t)(n - (AT_NBLK - 1)) <= 2u, 0)) {
          if (n == AT_NBLK + 1 && !redo0) {
            fence_proxy_async();
            __syncwarp();
            if (lane == 0) mbar_arrive(b_ordy + 8 * cwg);
          }
          if (n == AT_NBLK - 1) {
            #pragma unroll
            for (int J = 0; J < 16; J += 2)
              ldmatrix_x4(sbase + AT_SQ + 32768 + frag + (J >> 3) * 16384 + ((((J & 7) + (lane >> 4)) ^ (lane & 7)) << 4), q[2 * J], q[2 * J + 1], q[2 * J + 2], q[2 * J + 3]);
          }
          if (!raw) {
            const float m0 = mc0, m1 = mc1;
            const bool ok = softmax_mode(s, mc0, mc1);
            if (n == AT_NBLK) raw = ok;
            else {
              mc0 = mc0 - AT_HEAD > m0 ? mc0 : m0; mc1 = mc1 - AT_HEAD > m1 ? mc1 : m1;
              al0 = ex2_approx(m0 - mc0); al1 = ex2_approx(m1 - mc1);
            }
            if (!raw) softmax_sub(s, mc0, mc1);
          }
        }
        softmax_exp<0, AT_SPLIT>(s);
        add_rowsum(p, l0, l1);
        if (tid == 0) {
          uint32_t dep = zero & __float_as_uint(l0) & __float_as_uint(l1);
          #pragma unroll
          for (int i = AT_SPLIT - AT_PIN - PINB; i < AT_SPLIT - PINB; i += 2) dep &= __float_as_uint(s[i]) & __float_as_uint(s[i + 1]);
          mbar_arrive(b_pin + dep);
        }
        wgmma_wait<0>();
        fence_regs(o);
        if (tid == 0) mbar_arrive(b_empty + 8 * vs);
        ks += 2; if (ks >= 5) { ks -= 5; kp ^= 1; }
        vs += 2; if (vs >= 5) { vs -= 5; vp ^= 1; }
        ready = mbar_test(b_full + 8 * ks, kp) & mbar_test(b_full + 8 * vs, vp);
        softmax_exp<AT_SPLIT, 64>(s);
        pack_p(p, s);
        if (n == AT_NBLK) { lp0 = l0; lp1 = l1; l0 = 0.f; l1 = 0.f; }
        if (__builtin_expect(!raw || !ready, 0)) {
        if (!raw && __any_sync(0xffffffffu, al0 != 1.0f || al1 != 1.0f)) {
          rescale_o(o, al0, al1);
          l0 *= al0; l1 *= al1;
          al0 = 1.0f; al1 = 1.0f;
        }
        if (!ready && n < 2 * AT_NBLK - 1) {
          mbar_wait(b_full + 8 * ks, kp);
          mbar_wait(b_full + 8 * vs, vp);
        }
        }
      }
      FS(2 * it + 1, 5);
      const uint32_t vl = ring_slot(ta + 63);
      vs = ring_slot(ta + 62);
      const uint32_t ob = more ? sbase + vs * 32768 : sbase + AT_SQ + 32768;
      mbar_wait(b_full + 8 * vl, ring_par(ta + 63));
      issue_pv(o, p, v_base + vl * 2048, 1);
      block_end(zero, b_pin);
      add_rowsum(p, l0, l1);
      const bool overflow = finish_l(l0, l1);
      if (!overflow && lane == 0) mbar_arrive(b_q1);
      #pragma unroll
      for (int i = 0; i < 8; i++) asm volatile("mov.b64 {%0, %1}, 0;\nmov.b64 {%2, %3}, 0;" : "=r"(pre[i].x), "=r"(pre[i].y), "=r"(pre[i].z), "=r"(pre[i].w));
      const bool want_pre = !more && bid < OG_MOE, got_pre = want_pre && __all_sync(0xffffffffu, mbar_test(bars + 272, 0));
      if (got_pre) load_pre(pre, sbase, AT_SQ, threadIdx.x - 128);
      mbar_wait(b_empty + 8 * vs, ring_par(ta + 62));
      wgmma_wait<0>();
      fence_regs(o);
      if (tid == 0) mbar_arrive(b_empty + 8 * vl);
      FS(2 * it + 1, 6);
      if (overflow) {
        attn_rows_exact(lds_u32(bars + 400), sq + 32768, ob + cwg * 8192, 4 * ta + 1, kc, vc);
        __syncwarp();
        if (lane == 0) mbar_arrive(b_q1);
      } else stage_o(o, l0, l1, ob + frag, lane);
      if (redo0) attn_rows_exact(lds_u32(bars + 400), sq, sq, 4 * ta, kc, vc);
      fence_proxy_async();
      __syncwarp();
      if (lane == 0) {
        if (redo0) mbar_arrive(b_ordy + 8 * cwg);
        mbar_arrive(b_ordy + 16 + 8 * cwg);
      }
      if (want_pre && !got_pre) load_pre(pre, sbase, AT_SQ, threadIdx.x - 128);
      if (redo0 || overflow) raw = false;
      named_bar_sync(3 + cwg, 128);
      FS(2 * it + 1, 7);
    }
    if (cwg == 0) named_bar_arrive(1, 256);
    if (__builtin_expect(single, 0)) {
      float acc[128];
      uint32_t j = 0, pk[64];
      #pragma unroll
      for (int i = 0; i < 64; i++) asm volatile("" : "=f"(acc[2 * i]), "=f"(acc[2 * i + 1]), "=r"(pk[i]));
      uint4* dst = g_pre;
      int left = 0;
      auto put = [&](bool last) {
        #pragma unroll
        for (int i = 0; i < PUT_N; i++) dst[i * 256] = make_uint4(pk[4 * i], pk[4 * i + 1], pk[4 * i + 2], pk[4 * i + 3]);
        dst += PUT_N * 256;
        #pragma unroll
        for (int i = 0; i < 64 - 4 * PUT_N; i++) asm volatile("mov.b32 %0, %1;" : "=r"(pk[i]) : "r"(pk[i + 4 * PUT_N]));
        __syncwarp();
        if (last && lane == 0) mbar_arrive(bars + 280);
      };
      #pragma unroll 1
      for (int ji = 0; ji < help_njobs(bid); ji++) {
        const int nk = og_pre(help_job(bid, ji));
        #pragma unroll 1
        for (int kk = 0; kk < nk; kk++, j++) {
          const uint32_t slot = ring_slot(qp_pos(j, 1));
          mbar_wait(b_full + 8 * slot, ring_par(qp_pos(j, 1)) ^ ((j >> 2) & 1));
          if (H_STAG > 0 && cwg == 1 && kk == nk - H_STAG) named_bar_sync(7, 256);
          const uint32_t a_lo = q_lo + (j & 3) * 1024, b_lo = w_base + slot * 2048;
          wgmma_fence();
          wgmma_m64n256k16_ss_tb<0, 0>(acc, a_lo, b_lo, kk != 0);
          wgmma_m64n256k16_ss_tb<2, 128>(acc, a_lo, b_lo, 1);
          wgmma_m64n256k16_ss_tb<4, 256>(acc, a_lo, b_lo, 1);
          wgmma_m64n256k16_ss_tb<6, 384>(acc, a_lo, b_lo, 1);
          wgmma_commit();
          if (H_STAG > 0 && cwg == 0 && kk == nk - 1) named_bar_arrive(7, 256);
          wgmma_wait<1>();
          if (kk > 0 && tid == 0) mbar_arrive(b_empty + 8 * ring_slot(qp_pos(j - 1, 1)));
          #pragma unroll 1
          for (int i = ji == OG_JOBS ? 0 : 16 / PUT_N - 1; i < 16 / PUT_N && left > 0; i++) put(--left == 0);
        }
        wgmma_wait<0>();
        fence_regs(acc);
        if (tid == 0) mbar_arrive(b_empty + 8 * ring_slot(qp_pos(j - 1, 1)));
        #pragma unroll
        for (int i = 0; i < 64; i++) pk[i] = pack_bf16(acc[2 * i], acc[2 * i + 1]);
        left = 16 / PUT_N;
        if (ji == PRE_X) mbar_wait(bars + 296, 0);
        dst = g_pre + help_job(bid, ji) * 2048 + threadIdx.x - 128;
      }
      #pragma unroll
      for (int i = 0; i < 16; i++) dst[i * 256] = make_uint4(pk[4 * i], pk[4 * i + 1], pk[4 * i + 2], pk[4 * i + 3]);
      __syncwarp();
      if (lane == 0) mbar_arrive(bars + 280);
      named_bar_sync(5, 256);
      if (threadIdx.x == 128) {
        #pragma unroll 1
        for (int i = 0; i < 5; i++) {
          constexpr int n = OG_HSUM;
          const int used = i == 3 ? 0 : (n + 3 - (i == 4 ? 3 : i)) / 4;
          if ((used ^ (i < 4)) & 1) {
            mbar_arrive(b_full + 8 * ring_slot(4 + i));
            mbar_arrive(b_empty + 8 * ring_slot(4 + i)); mbar_arrive(b_empty + 8 * ring_slot(4 + i));
          }
        }
        mbar_arrive(b_x);
      }
      named_bar_sync(5, 256);
      #pragma unroll
      for (int i = 0; i < 8; i++) pre[i] = make_uint4(0u, 0u, 0u, 0u);
    }
    TL_CLK(3, 1, threadIdx.x == 128);
    TL_CTA(1, threadIdx.x == 256);
    TL_END(3, tid == 0);
    TL_MARK2(19, tid == 0 && !single);
    if (bid < 128) {
      tail_consumer(bid, sbase, &tmOut, pre, cwg, w_gate, w_up);
    }
  }
}

typedef CUresult (*PFN_encodeTiled)(CUtensorMap*, CUtensorMapDataType, cuuint32_t, void*, const cuuint64_t*, const cuuint64_t*,
                                    const cuuint32_t*, const cuuint32_t*, CUtensorMapInterleave, CUtensorMapSwizzle,
                                    CUtensorMapL2promotion, CUtensorMapFloatOOBfill);

CUtensorMap make_map_2d(PFN_encodeTiled enc, const void* ptr, uint64_t inner, uint64_t outer, uint64_t stride_bytes, uint32_t box_inner, uint32_t box_outer) {
  CUtensorMap m;
  cuuint64_t gd[2] = {inner, outer}; cuuint64_t gs[1] = {stride_bytes};
  cuuint32_t bx[2] = {box_inner, box_outer}; cuuint32_t es[2] = {1, 1};
  enc(&m, CU_TENSOR_MAP_DATA_TYPE_BFLOAT16, 2, const_cast<void*>(ptr), gd, gs, bx, es, CU_TENSOR_MAP_INTERLEAVE_NONE,
      CU_TENSOR_MAP_SWIZZLE_128B, CU_TENSOR_MAP_L2_PROMOTION_L2_128B, CU_TENSOR_MAP_FLOAT_OOB_FILL_NONE);
  return m;
}

CUtensorMap make_map_3d(PFN_encodeTiled enc, const void* ptr, uint64_t cols, uint64_t rows, uint32_t box_rows, uint32_t chunks) {
  CUtensorMap m;
  cuuint64_t gd[3] = {64, rows, cols / 64}; cuuint64_t gs[2] = {cols * 2, 128};
  cuuint32_t bx[3] = {64, box_rows, chunks}; cuuint32_t es[3] = {1, 1, 1};
  enc(&m, CU_TENSOR_MAP_DATA_TYPE_BFLOAT16, 3, const_cast<void*>(ptr), gd, gs, bx, es, CU_TENSOR_MAP_INTERLEAVE_NONE,
      CU_TENSOR_MAP_SWIZZLE_128B, CU_TENSOR_MAP_L2_PROMOTION_L2_128B, CU_TENSOR_MAP_FLOAT_OOB_FILL_NONE);
  return m;
}

}

extern "C" void kernel_launch(void* const* d_in, const int* in_sizes, int n_in, void* d_out, int out_size) {
  const bf16* x      = (const bf16*)d_in[0];
  const bf16* kc     = (const bf16*)d_in[1];
  const bf16* vc     = (const bf16*)d_in[2];
  const bf16* wq     = (const bf16*)d_in[3];
  const bf16* wo     = (const bf16*)d_in[4];
  const bf16* w_r    = (const bf16*)d_in[6];
  const bf16* w_gate = (const bf16*)d_in[7];
  const bf16* w_up   = (const bf16*)d_in[8];
  const bf16* w_down = (const bf16*)d_in[9];
  const bf16* cvec   = (const bf16*)d_in[10];
  const bf16* w_mod  = (const bf16*)d_in[11];
  bf16* out = (bf16*)d_out;

  static PFN_encodeTiled enc = nullptr;
  static void *p_h = nullptr, *p_o = nullptr;
  if (!enc) {
    void* fn = nullptr; cudaDriverEntryPointQueryResult qres;
    cudaGetDriverEntryPoint("cuTensorMapEncodeTiled", &fn, cudaEnableDefault, &qres);
    enc = (PFN_encodeTiled)fn;
    cudaGetSymbolAddress(&p_h, g_pre);
    p_h = (uint4*)p_h + 16 * PRE_X * 2048;
    cudaGetSymbolAddress(&p_o, g_o);
    cudaFuncSetAttribute(fused_kernel, cudaFuncAttributeMaxDynamicSharedMemorySize, (int)AT_SMEM);
  }
  const CUtensorMap tm_h   = make_map_2d(enc, p_h, T_D, T_SEQ, T_D * 2, 64, 128);
  const CUtensorMap tm_wq  = make_map_3d(enc, wq, T_DQKV, T_D, 64, 4);
  const CUtensorMap tm_k   = make_map_3d(enc, kc, T_DH, (uint64_t)T_NH * T_SEQ, 128, 2);
  const CUtensorMap tm_v   = make_map_3d(enc, vc, T_DH, (uint64_t)T_NH * T_SEQ, 128, 2);
  const CUtensorMap tm_ost = make_map_2d(enc, p_o, T_DQKV, T_SEQ, T_DQKV * 2, 64, 64);
  const CUtensorMap tm_old = make_map_2d(enc, p_o, T_DQKV, T_SEQ, T_DQKV * 2, 64, 128);
  const CUtensorMap tm_wo  = make_map_3d(enc, wo, T_D, T_DQKV, 64, 2);
  const CUtensorMap tm_d   = make_map_3d(enc, w_down, T_D, T_F, 32, 8);

  const CUtensorMap tm_m   = make_map_2d(enc, w_mod, 6 * T_D, T_D, 6 * T_D * 2, 64, 256);
  const CUtensorMap tm_out = make_map_2d(enc, out, T_D, T_SEQ, T_D * 2, 64, 16);

  Roles roles;
  for (int sm = 0; sm < 132; sm++) {
    const int t = sm >> 1;
    roles.of_sm[sm] = (uint8_t)((t < 32 ? ((t + 7) & 7) * 16 + (t >> 3) * 2 : t < 60 ? ((t - 32) % 7) * 16 + (4 + (t - 32) / 7) * 2 : t < 62 ? 2 * t + 8 : 2 * t - 4) + (sm & 1));
  }
  fused_kernel<<<132, 384, AT_SMEM, cudaStreamPerThread>>>(tm_h, tm_wq, tm_k, tm_v, tm_ost, tm_old, tm_wo, tm_d, tm_out, tm_m, roles, 0u, (const uint8_t*)wo, kc, vc, x, cvec, w_mod,
             w_r, w_gate, w_up, w_down, out);
}
```

```cpp
#include <cuda_runtime.h>
#include <cuda_bf16.h>
#include <cuda.h>
#include <stdint.h>

namespace {

typedef __nv_bfloat16 bf16;

constexpr int T_SEQ = 2048, T_D = 1024, T_NH = 32, T_DH = 128, T_DQKV = 4096, T_F = 3584;

#define PRE_X 2
__device__ __align__(1024) uint4 g_pre[(16 * PRE_X + 128) * 2048];
#define g_h (reinterpret_cast<bf16*>(g_pre + 16 * PRE_X * 2048))
__device__ __align__(1024) bf16 g_o[T_SEQ * T_DQKV];
__device__ __align__(16) uint8_t g_col[8 * 1536];
__device__ __align__(16) float g_scal[64];
__device__ __align__(16) unsigned int g_hcnt[17 * 32];
__device__ __align__(128) float g_modpart[4 * 2 * T_D];
struct __align__(2048) TailMail {
  float4 part1[T_SEQ * 8];
  uint32_t key[256];
  uint4 cand[16 * 2 * 2 * 128];
  uint32_t cnt[32];
  float ypart[(T_F / 32) * 2 * T_D];
};
__device__ TailMail g_mail;
#define g_part1 g_mail.part1
#define g_key g_mail.key
#define g_cand g_mail.cand
#define CNT_Y (g_mail.cnt)
#define g_ypart g_mail.ypart

__device__ __forceinline__ uint32_t smem_u32(const void* p) { return (uint32_t)__cvta_generic_to_shared(p); }
__device__ __forceinline__ void mbar_init(uint32_t bar, uint32_t cnt) { asm volatile("mbarrier.init.shared::cta.b64 [%0], %1;" :: "r"(bar), "r"(cnt)); }
__device__ __forceinline__ void mbar_expect_tx(uint32_t bar, uint32_t bytes) { asm volatile("mbarrier.arrive.expect_tx.shared::cta.b64 _, [%0], %1;" :: "r"(bar), "r"(bytes) : "memory"); }
__device__ __forceinline__ void mbar_arrive(uint32_t bar) { asm volatile("mbarrier.arrive.shared::cta.b64 _, [%0];" :: "r"(bar) : "memory"); }
__device__ __forceinline__ void mbar_wait(uint32_t bar, uint32_t parity) {
  asm volatile("{\n.reg .pred p;\nLAB_WAIT:\nmbarrier.try_wait.parity.shared::cta.b64 p, [%0], %1;\n@!p bra LAB_WAIT;\n}\n" :: "r"(bar), "r"(parity) : "memory");
}
__device__ __forceinline__ bool mbar_test(uint32_t bar, uint32_t parity) {
  uint32_t r; asm volatile("{\n.reg .pred p;\nmbarrier.test_wait.parity.shared::cta.b64 p, [%1], %2;\nselp.u32 %0, 1, 0, p;\n}\n" : "=r"(r) : "r"(bar), "r"(parity) : "memory");
  return r != 0;
}
__device__ __forceinline__ uint32_t clock_lo() { uint32_t c; asm volatile("mov.u32 %0, %%clock;" : "=r"(c)); return c; }
__device__ __forceinline__ void fence_mbar_init() { asm volatile("fence.mbarrier_init.release.cluster;" ::: "memory"); }
__device__ __forceinline__ void tma_load_2d(uint32_t dst, const CUtensorMap* map, int c0, int c1, uint32_t bar) {
  asm volatile("cp.async.bulk.tensor.2d.shared::cluster.global.mbarrier::complete_tx::bytes [%0], [%1, {%3, %4}], [%2];"
    :: "r"(dst), "l"(map), "r"(bar), "r"(c0), "r"(c1) : "memory");
}
__device__ __forceinline__ uint64_t policy_evict_first() {
  uint64_t p; asm volatile("createpolicy.fractional.L2::evict_first.b64 %0, 1.0;" : "=l"(p)); return p;
}
__device__ __forceinline__ void tma_load_2d_hint(uint32_t dst, const CUtensorMap* map, int c0, int c1, uint32_t bar, uint64_t pol) {
  asm volatile("cp.async.bulk.tensor.2d.shared::cluster.global.mbarrier::complete_tx::bytes.L2::cache_hint [%0], [%1, {%3, %4}], [%2], %5;"
    :: "r"(dst), "l"(map), "r"(bar), "r"(c0), "r"(c1), "l"(pol) : "memory");
}
__device__ __forceinline__ void tma_load_3d_hint(uint32_t dst, const CUtensorMap* map, int c1, int c2, uint32_t bar, uint64_t pol) {
  asm volatile("cp.async.bulk.tensor.3d.shared::cluster.global.mbarrier::complete_tx::bytes.L2::cache_hint [%0], [%1, {%3, %4, %5}], [%2], %6;"
    :: "r"(dst), "l"(map), "r"(bar), "n"(0), "r"(c1), "r"(c2), "l"(pol) : "memory");
}
__device__ __forceinline__ void tma_store_2d(const CUtensorMap* map, uint32_t src, int c0, int c1) {
  asm volatile("cp.async.bulk.tensor.2d.global.shared::cta.bulk_group [%0, {%2, %3}], [%1];" :: "l"(map), "r"(src), "r"(c0), "r"(c1) : "memory");
}
__device__ __forceinline__ void prefetch_tmap(const CUtensorMap* map) { asm volatile("prefetch.tensormap [%0];" :: "l"(map) : "memory"); }
__device__ __forceinline__ void l2_prefetch_bulk(const void* p, uint32_t bytes) {
  asm volatile("cp.async.bulk.prefetch.L2.global [%0], %1;" :: "l"(p), "r"(bytes) : "memory");
}
__device__ __forceinline__ void bulk_commit() { asm volatile("cp.async.bulk.commit_group;" ::: "memory"); }
template<int N> __device__ __forceinline__ void bulk_wait_read() { asm volatile("cp.async.bulk.wait_group.read %0;" :: "n"(N) : "memory"); }
template<int N> __device__ __forceinline__ void bulk_wait() { asm volatile("cp.async.bulk.wait_group %0;" :: "n"(N) : "memory"); }
__device__ __forceinline__ void named_bar_sync(int id, int nthreads) { asm volatile("bar.sync %0, %1;" :: "r"(id), "r"(nthreads) : "memory"); }
__device__ __forceinline__ void named_bar_arrive(int id, int nthreads) { asm volatile("bar.arrive %0, %1;" :: "r"(id), "r"(nthreads) : "memory"); }
__device__ __forceinline__ void pass_turn(int cwg) {
  asm volatile("{\n.reg .pred p;\nsetp.ne.u32 p, %0, 0;\n@p bar.arrive 1, 256;\n@!p bar.arrive 2, 256;\n}\n" :: "r"(cwg) : "memory");
}
__device__ __forceinline__ void wgmma_fence() { asm volatile("wgmma.fence.sync.aligned;" ::: "memory"); }
__device__ __forceinline__ void wgmma_commit() { asm volatile("wgmma.commit_group.sync.aligned;" ::: "memory"); }
template<int N> __device__ __forceinline__ void wgmma_wait() { asm volatile("wgmma.wait_group.sync.aligned %0;" :: "n"(N) : "memory"); }
template<int R> __device__ __forceinline__ void reg_alloc() { asm volatile("setmaxnreg.inc.sync.aligned.u32 %0;" :: "n"(R)); }
template<int R> __device__ __forceinline__ void reg_dealloc() { asm volatile("setmaxnreg.dec.sync.aligned.u32 %0;" :: "n"(R)); }
__device__ __forceinline__ bool elect_one() {
  uint32_t pred; asm volatile("{\n.reg .pred p;\nelect.sync _|p, 0xffffffff;\nselp.u32 %0, 1, 0, p;\n}\n" : "=r"(pred)); return pred != 0;
}
__device__ __forceinline__ uint32_t pack_bf16(float lo, float hi) {
  uint32_t r; asm("cvt.rn.bf16x2.f32 %0, %1, %2;" : "=r"(r) : "f"(hi), "f"(lo)); return r;
}
__device__ __forceinline__ void stmatrix_x4(uint32_t addr, uint32_t r0, uint32_t r1, uint32_t r2, uint32_t r3) {
  asm volatile("stmatrix.sync.aligned.m8n8.x4.shared.b16 [%0], {%1, %2, %3, %4};" :: "r"(addr), "r"(r0), "r"(r1), "r"(r2), "r"(r3) : "memory");
}
__device__ __forceinline__ void fence_proxy_async() { asm volatile("fence.proxy.async.shared::cta;" ::: "memory"); }
__device__ __forceinline__ float ex2_approx(float x) { float y; asm("ex2.approx.ftz.f32 %0, %1;" : "=f"(y) : "f"(x)); return y; }
template<int N> __device__ __forceinline__ void fence_regs(float (&r)[N]) {
  #pragma unroll
  for (int i = 0; i < N; i++) asm volatile("" : "+f"(r[i]) :: "memory");
}
template<int N> __device__ __forceinline__ void zero_regs(float (&r)[N]) {
  #pragma unroll
  for (int i = 0; i < N; i += 2) asm volatile("mov.b64 {%0, %1}, 0;" : "=f"(r[i]), "=f"(r[i + 1]));
}
__device__ __forceinline__ float rbf(float x) { return __uint_as_float(pack_bf16(0.f, x)); }
__device__ __forceinline__ float bflo(uint32_t v) { return __uint_as_float(v << 16); }
__device__ __forceinline__ float bfhi(uint32_t v) { return __uint_as_float(v & 0xffff0000u); }

#define XT(i) do {} while (0)
#define TL_START(k) do {} while (0)
#define TL_END(k, cond) do {} while (0)
#define TL_CTA(i, cond) do {} while (0)
#define FS(slot, k) do {} while (0)
#define TL_MARK2(k, cond) do {} while (0)
#define TL_CLK(k, i, cond) do {} while (0)

template <int OFFA, int OFFB>
__device__ __forceinline__ void wgmma_m64n256k16_ss_tb(float (&d)[128], uint32_t a_lo, uint32_t b_lo, int scaleD) {
  asm volatile("{\n.reg .pred p;\n.reg .b32 ta, tb;\n.reg .b64 da, db;\nsetp.ne.b32 p, %130, 0;\n"
    "add.u32 ta, %128, %131;\nadd.u32 tb, %129, %132;\n"
    "mov.b64 da, {ta, 0x40000040};\nmov.b64 db, {tb, 0x40000040};\n"
    "wgmma.mma_async.sync.aligned.m64n256k16.f32.bf16.bf16 "
    "{%0, %1, %2, %3, %4, %5, %6, %7, %8, %9, %10, %11, %12, %13, %14, %15, %16, %17, %18, %19, %20, %21, %22, %23, %24, %25, %26, %27, %28, %29, %30, %31, %32, %33, %34, %35, %36, %37, %38, %39, %40, %41, %42, %43, %44, %45, %46, %47, %48, %49, %50, %51, %52, %53, %54, %55, %56, %57, %58, %59, %60, %61, %62, %63, %64, %65, %66, %67, %68, %69, %70, %71, %72, %73, %74, %75, %76, %77, %78, %79, %80, %81, %82, %83, %84, %85, %86, %87, %88, %89, %90, %91, %92, %93, %94, %95, %96, %97, %98, %99, %100, %101, %102, %103, %104, %105, %106, %107, %108, %109, %110, %111, %112, %113, %114, %115, %116, %117, %118, %119, %120, %121, %122, %123, %124, %125, %126, %127}, "
    "da, db, p, 1, 1, 0, 1;\n}\n"
    : "+f"(d[0]), "+f"(d[1]), "+f"(d[2]), "+f"(d[3]), "+f"(d[4]), "+f"(d[5]), "+f"(d[6]), "+f"(d[7]), "+f"(d[8]), "+f"(d[9]), "+f"(d[10]), "+f"(d[11]), "+f"(d[12]), "+f"(d[13]), "+f"(d[14]), "+f"(d[15]), "+f"(d[16]), "+f"(d[17]), "+f"(d[18]), "+f"(d[19]), "+f"(d[20]), "+f"(d[21]), "+f"(d[22]), "+f"(d[23]), "+f"(d[24]), "+f"(d[25]), "+f"(d[26]), "+f"(d[27]), "+f"(d[28]), "+f"(d[29]), "+f"(d[30]), "+f"(d[31]), "+f"(d[32]), "+f"(d[33]), "+f"(d[34]), "+f"(d[35]), "+f"(d[36]), "+f"(d[37]), "+f"(d[38]), "+f"(d[39]), "+f"(d[40]), "+f"(d[41]), "+f"(d[42]), "+f"(d[43]), "+f"(d[44]), "+f"(d[45]), "+f"(d[46]), "+f"(d[47]), "+f"(d[48]), "+f"(d[49]), "+f"(d[50]), "+f"(d[51]), "+f"(d[52]), "+f"(d[53]), "+f"(d[54]), "+f"(d[55]), "+f"(d[56]), "+f"(d[57]), "+f"(d[58]), "+f"(d[59]), "+f"(d[60]), "+f"(d[61]), "+f"(d[62]), "+f"(d[63]), "+f"(d[64]), "+f"(d[65]), "+f"(d[66]), "+f"(d[67]), "+f"(d[68]), "+f"(d[69]), "+f"(d[70]), "+f"(d[71]), "+f"(d[72]), "+f"(d[73]), "+f"(d[74]), "+f"(d[75]), "+f"(d[76]), "+f"(d[77]), "+f"(d[78]), "+f"(d[79]), "+f"(d[80]), "+f"(d[81]), "+f"(d[82]), "+f"(d[83]), "+f"(d[84]), "+f"(d[85]), "+f"(d[86]), "+f"(d[87]), "+f"(d[88]), "+f"(d[89]), "+f"(d[90]), "+f"(d[91]), "+f"(d[92]), "+f"(d[93]), "+f"(d[94]), "+f"(d[95]), "+f"(d[96]), "+f"(d[97]), "+f"(d[98]), "+f"(d[99]), "+f"(d[100]), "+f"(d[101]), "+f"(d[102]), "+f"(d[103]), "+f"(d[104]), "+f"(d[105]), "+f"(d[106]), "+f"(d[107]), "+f"(d[108]), "+f"(d[109]), "+f"(d[110]), "+f"(d[111]), "+f"(d[112]), "+f"(d[113]), "+f"(d[114]), "+f"(d[115]), "+f"(d[116]), "+f"(d[117]), "+f"(d[118]), "+f"(d[119]), "+f"(d[120]), "+f"(d[121]), "+f"(d[122]), "+f"(d[123]), "+f"(d[124]), "+f"(d[125]), "+f"(d[126]), "+f"(d[127])
    : "r"(a_lo), "r"(b_lo), "r"(scaleD), "n"(OFFA), "n"(OFFB));
}

template <int OFFA, int OFFB>
__device__ __forceinline__ void wgmma_m64n128k16_ss_tb(float (&d)[64], uint32_t a_lo, uint32_t b_lo, int scaleD) {
  asm volatile("{\n.reg .pred p;\n.reg .b32 ta, tb;\n.reg .b64 da, db;\nsetp.ne.b32 p, %66, 0;\n"
    "add.u32 ta, %64, %67;\nadd.u32 tb, %65, %68;\n"
    "mov.b64 da, {ta, 0x40000040};\nmov.b64 db, {tb, 0x40000040};\n"
    "wgmma.mma_async.sync.aligned.m64n128k16.f32.bf16.bf16 "
    "{%0, %1, %2, %3, %4, %5, %6, %7, %8, %9, %10, %11, %12, %13, %14, %15, %16, %17, %18, %19, %20, %21, %22, %23, %24, %25, %26, %27, %28, %29, %30, %31, %32, %33, %34, %35, %36, %37, %38, %39, %40, %41, %42, %43, %44, %45, %46, %47, %48, %49, %50, %51, %52, %53, %54, %55, %56, %57, %58, %59, %60, %61, %62, %63}, "
    "da, db, p, 1, 1, 0, 1;\n}\n"
    : "+f"(d[0]), "+f"(d[1]), "+f"(d[2]), "+f"(d[3]), "+f"(d[4]), "+f"(d[5]), "+f"(d[6]), "+f"(d[7]), "+f"(d[8]), "+f"(d[9]), "+f"(d[10]), "+f"(d[11]), "+f"(d[12]), "+f"(d[13]), "+f"(d[14]), "+f"(d[15]), "+f"(d[16]), "+f"(d[17]), "+f"(d[18]), "+f"(d[19]), "+f"(d[20]), "+f"(d[21]), "+f"(d[22]), "+f"(d[23]), "+f"(d[24]), "+f"(d[25]), "+f"(d[26]), "+f"(d[27]), "+f"(d[28]), "+f"(d[29]), "+f"(d[30]), "+f"(d[31]), "+f"(d[32]), "+f"(d[33]), "+f"(d[34]), "+f"(d[35]), "+f"(d[36]), "+f"(d[37]), "+f"(d[38]), "+f"(d[39]), "+f"(d[40]), "+f"(d[41]), "+f"(d[42]), "+f"(d[43]), "+f"(d[44]), "+f"(d[45]), "+f"(d[46]), "+f"(d[47]), "+f"(d[48]), "+f"(d[49]), "+f"(d[50]), "+f"(d[51]), "+f"(d[52]), "+f"(d[53]), "+f"(d[54]), "+f"(d[55]), "+f"(d[56]), "+f"(d[57]), "+f"(d[58]), "+f"(d[59]), "+f"(d[60]), "+f"(d[61]), "+f"(d[62]), "+f"(d[63])
    : "r"(a_lo), "r"(b_lo), "r"(scaleD), "n"(OFFA), "n"(OFFB));
}

template <int OFFB>
__device__ __forceinline__ void wgmma_m64n128k16_rs_tb(float (&d)[64], uint32_t a0, uint32_t a1, uint32_t a2, uint32_t a3, uint32_t b_lo, int scaleD) {
  asm volatile("{\n.reg .pred p;\n.reg .b32 tb;\n.reg .b64 db;\nsetp.ne.b32 p, %69, 0;\n"
    "add.u32 tb, %68, %70;\n"
    "mov.b64 db, {tb, 0x40000040};\n"
    "wgmma.mma_async.sync.aligned.m64n128k16.f32.bf16.bf16 "
    "{%0, %1, %2, %3, %4, %5, %6, %7, %8, %9, %10, %11, %12, %13, %14, %15, %16, %17, %18, %19, %20, %21, %22, %23, %24, %25, %26, %27, %28, %29, %30, %31, %32, %33, %34, %35, %36, %37, %38, %39, %40, %41, %42, %43, %44, %45, %46, %47, %48, %49, %50, %51, %52, %53, %54, %55, %56, %57, %58, %59, %60, %61, %62, %63}, "
    "{%64, %65, %66, %67}, db, p, 1, 1, 1;\n}\n"
    : "+f"(d[0]), "+f"(d[1]), "+f"(d[2]), "+f"(d[3]), "+f"(d[4]), "+f"(d[5]), "+f"(d[6]), "+f"(d[7]), "+f"(d[8]), "+f"(d[9]), "+f"(d[10]), "+f"(d[11]), "+f"(d[12]), "+f"(d[13]), "+f"(d[14]), "+f"(d[15]), "+f"(d[16]), "+f"(d[17]), "+f"(d[18]), "+f"(d[19]), "+f"(d[20]), "+f"(d[21]), "+f"(d[22]), "+f"(d[23]), "+f"(d[24]), "+f"(d[25]), "+f"(d[26]), "+f"(d[27]), "+f"(d[28]), "+f"(d[29]), "+f"(d[30]), "+f"(d[31]), "+f"(d[32]), "+f"(d[33]), "+f"(d[34]), "+f"(d[35]), "+f"(d[36]), "+f"(d[37]), "+f"(d[38]), "+f"(d[39]), "+f"(d[40]), "+f"(d[41]), "+f"(d[42]), "+f"(d[43]), "+f"(d[44]), "+f"(d[45]), "+f"(d[46]), "+f"(d[47]), "+f"(d[48]), "+f"(d[49]), "+f"(d[50]), "+f"(d[51]), "+f"(d[52]), "+f"(d[53]), "+f"(d[54]), "+f"(d[55]), "+f"(d[56]), "+f"(d[57]), "+f"(d[58]), "+f"(d[59]), "+f"(d[60]), "+f"(d[61]), "+f"(d[62]), "+f"(d[63])
    : "r"(a0), "r"(a1), "r"(a2), "r"(a3), "r"(b_lo), "r"(scaleD), "n"(OFFB));
}

template <int OFFB>
__device__ __forceinline__ void wgmma_m64n128k16_rs(float (&d)[64], uint32_t a0, uint32_t a1, uint32_t a2, uint32_t a3, uint32_t b_lo, int scaleD) {
  asm volatile("{\n.reg .pred p;\n.reg .b32 tb;\n.reg .b64 db;\nsetp.ne.b32 p, %69, 0;\n"
    "add.u32 tb, %68, %70;\n"
    "mov.b64 db, {tb, 0x40000040};\n"
    "wgmma.mma_async.sync.aligned.m64n128k16.f32.bf16.bf16 "
    "{%0, %1, %2, %3, %4, %5, %6, %7, %8, %9, %10, %11, %12, %13, %14, %15, %16, %17, %18, %19, %20, %21, %22, %23, %24, %25, %26, %27, %28, %29, %30, %31, %32, %33, %34, %35, %36, %37, %38, %39, %40, %41, %42, %43, %44, %45, %46, %47, %48, %49, %50, %51, %52, %53, %54, %55, %56, %57, %58, %59, %60, %61, %62, %63}, "
    "{%64, %65, %66, %67}, db, p, 1, 1, 0;\n}\n"
    : "+f"(d[0]), "+f"(d[1]), "+f"(d[2]), "+f"(d[3]), "+f"(d[4]), "+f"(d[5]), "+f"(d[6]), "+f"(d[7]), "+f"(d[8]), "+f"(d[9]), "+f"(d[10]), "+f"(d[11]), "+f"(d[12]), "+f"(d[13]), "+f"(d[14]), "+f"(d[15]), "+f"(d[16]), "+f"(d[17]), "+f"(d[18]), "+f"(d[19]), "+f"(d[20]), "+f"(d[21]), "+f"(d[22]), "+f"(d[23]), "+f"(d[24]), "+f"(d[25]), "+f"(d[26]), "+f"(d[27]), "+f"(d[28]), "+f"(d[29]), "+f"(d[30]), "+f"(d[31]), "+f"(d[32]), "+f"(d[33]), "+f"(d[34]), "+f"(d[35]), "+f"(d[36]), "+f"(d[37]), "+f"(d[38]), "+f"(d[39]), "+f"(d[40]), "+f"(d[41]), "+f"(d[42]), "+f"(d[43]), "+f"(d[44]), "+f"(d[45]), "+f"(d[46]), "+f"(d[47]), "+f"(d[48]), "+f"(d[49]), "+f"(d[50]), "+f"(d[51]), "+f"(d[52]), "+f"(d[53]), "+f"(d[54]), "+f"(d[55]), "+f"(d[56]), "+f"(d[57]), "+f"(d[58]), "+f"(d[59]), "+f"(d[60]), "+f"(d[61]), "+f"(d[62]), "+f"(d[63])
    : "r"(a0), "r"(a1), "r"(a2), "r"(a3), "r"(b_lo), "r"(scaleD), "n"(OFFB));
}

__device__ __forceinline__ uint4 ldg_nc_v4(const void* p) {
  uint4 v;
    asm volatile("{\n.reg .b64 pol;\ncreatepolicy.fractional.L2::evict_first.b64 pol, 1.0;\n"
                 "ld.global.nc.L1::no_allocate.L2::cache_hint.v4.u32 {%0, %1, %2, %3}, [%4], pol;\n}\n" : "=r"(v.x), "=r"(v.y), "=r"(v.z), "=r"(v.w) : "l"(p));
  return v;
}
__device__ __forceinline__ uint64_t pol_normal() {
  uint64_t p; asm volatile("createpolicy.fractional.L2::evict_normal.b64 %0, 1.0;" : "=l"(p)); return p;
}
__device__ __forceinline__ void unpack8(const uint4& u, float (&v)[8]) {
  v[0] = bflo(u.x); v[1] = bfhi(u.x); v[2] = bflo(u.y); v[3] = bfhi(u.y);
  v[4] = bflo(u.z); v[5] = bfhi(u.z); v[6] = bflo(u.w); v[7] = bfhi(u.w);
}
__device__ __forceinline__ void fma8(float (&acc)[8], float s, const uint4& w) {
  acc[0] = fmaf(s, bflo(w.x), acc[0]); acc[1] = fmaf(s, bfhi(w.x), acc[1]); acc[2] = fmaf(s, bflo(w.y), acc[2]); acc[3] = fmaf(s, bfhi(w.y), acc[3]);
  acc[4] = fmaf(s, bflo(w.z), acc[4]); acc[5] = fmaf(s, bfhi(w.z), acc[5]); acc[6] = fmaf(s, bflo(w.w), acc[6]); acc[7] = fmaf(s, bfhi(w.w), acc[7]);
}
__device__ __forceinline__ float rcp_approx(float x) { float y; asm("rcp.approx.ftz.f32 %0, %1;" : "=f"(y) : "f"(x)); return y; }
__device__ __forceinline__ float sigmoid_f(float v) { return rcp_approx(1.0f + ex2_approx(v * -1.4426950408889634f)); }
__device__ __forceinline__ float silu_bf(float v) { return rbf(v * sigmoid_f(v)); }
__device__ __forceinline__ uint32_t rank_key(float r, int idx) {
  const uint32_t b = __float_as_uint(r) >> 16;
  const uint32_t u = (r != r) ? 0u : ((b & 0x8000u) ? (~b & 0xffffu) : (b | 0x8000u));
  return (u << 16) | (0xffffu - (uint32_t)idx);
}
__device__ __forceinline__ void warp_top2(uint32_t& k1, uint32_t& k2) {
  const uint32_t m1 = __reduce_max_sync(0xffffffffu, k1);
  k2 = __reduce_max_sync(0xffffffffu, k1 == m1 ? k2 : k1);
  k1 = m1;
}
__device__ __forceinline__ uint32_t bmul2(uint32_t a, uint32_t b) { uint32_t r; asm("mul.rn.bf16x2 %0, %1, %2;" : "=r"(r) : "r"(a), "r"(b)); return r; }
__device__ __forceinline__ uint32_t badd2(uint32_t a, uint32_t b) { uint32_t r; asm("add.rn.bf16x2 %0, %1, %2;" : "=r"(r) : "r"(a), "r"(b)); return r; }
__device__ __forceinline__ uint32_t bsub2(uint32_t a, uint32_t b) { uint32_t r; asm("sub.rn.bf16x2 %0, %1, %2;" : "=r"(r) : "r"(a), "r"(b)); return r; }
__device__ __forceinline__ float sqrt_approx(float x) { float y; asm("sqrt.approx.f32 %0, %1;" : "=f"(y) : "f"(x)); return y; }
__device__ __forceinline__ uint32_t ln_norm2(uint32_t x1, uint32_t mb2, float inv) {
  const uint32_t d = bsub2(x1, mb2);
  return pack_bf16(bflo(d) * inv, bfhi(d) * inv);
}
__device__ __forceinline__ uint32_t bfma2(uint32_t a, uint32_t b, uint32_t c) { uint32_t r; asm("fma.rn.bf16x2 %0, %1, %2, %3;" : "=r"(r) : "r"(a), "r"(b), "r"(c)); return r; }
__device__ __forceinline__ uint32_t ln_norm2b(uint32_t x1, uint32_t mb2, uint32_t ih, uint32_t il) {
  const uint32_t d = bsub2(x1, mb2);
  return bfma2(d, ih, bmul2(d, il));
}
__device__ __forceinline__ uint32_t ln_mod2(uint32_t x1, uint32_t mb2, float inv, uint32_t c1, uint32_t sb) { return badd2(bmul2(ln_norm2(x1, mb2, inv), c1), sb); }
__device__ __forceinline__ void ldmatrix_x4(uint32_t addr, uint32_t& r0, uint32_t& r1, uint32_t& r2, uint32_t& r3) {
  asm volatile("ldmatrix.sync.aligned.m8n8.x4.shared.b16 {%0, %1, %2, %3}, [%4];" : "=r"(r0), "=r"(r1), "=r"(r2), "=r"(r3) : "r"(addr) : "memory");
}
__device__ __forceinline__ uint4 ldg_stream_v4(const void* p, uint64_t pol) {
  uint4 v; asm volatile("ld.global.nc.L1::no_allocate.L2::cache_hint.L2::128B.v4.u32 {%0, %1, %2, %3}, [%4], %5;" : "=r"(v.x), "=r"(v.y), "=r"(v.z), "=r"(v.w) : "l"(p), "l"(pol)); return v;
}
__device__ __forceinline__ void bulk_load_hint(uint32_t dst, const void* src, uint32_t bytes, uint32_t bar, uint64_t pol) {
  asm volatile("cp.async.bulk.shared::cluster.global.mbarrier::complete_tx::bytes.L2::cache_hint [%0], [%1], %2, [%3], %4;"
    :: "r"(dst), "l"(src), "r"(bytes), "r"(bar), "l"(pol) : "memory");
}
__device__ __forceinline__ void red_release_add(unsigned int* p, unsigned int v) { asm volatile("red.release.gpu.global.add.u32 [%0], %1;" :: "l"(p), "r"(v) : "memory"); }
__device__ __forceinline__ unsigned int ld_acquire(const unsigned int* p) { unsigned int v; asm volatile("ld.acquire.gpu.global.u32 %0, [%1];" : "=r"(v) : "l"(p) : "memory"); return v; }
__device__ __forceinline__ void spin_until(const unsigned int* p, unsigned int target) {
  #pragma unroll 1
  for (unsigned int i = 0; i < (1u << 22); i++) { if (ld_acquire(p) >= target) return; }
}
__device__ __forceinline__ float lds_f32(uint32_t a) { float v; asm volatile("ld.shared.f32 %0, [%1];" : "=f"(v) : "r"(a) : "memory"); return v; }
__device__ __forceinline__ float2 lds_f32x2(uint32_t a) { float2 v; asm volatile("ld.shared.v2.f32 {%0, %1}, [%2];" : "=f"(v.x), "=f"(v.y) : "r"(a) : "memory"); return v; }
__device__ __forceinline__ uint2 lds_u32x2(uint32_t a) { uint2 v; asm volatile("ld.shared.v2.u32 {%0, %1}, [%2];" : "=r"(v.x), "=r"(v.y) : "r"(a) : "memory"); return v; }
__device__ __forceinline__ uint32_t lds_u32(uint32_t a) { uint32_t v; asm volatile("ld.shared.u32 %0, [%1];" : "=r"(v) : "r"(a) : "memory"); return v; }
__device__ __forceinline__ void sts_u32(uint32_t a, uint32_t v) { asm volatile("st.shared.u32 [%0], %1;" :: "r"(a), "r"(v) : "memory"); }
__device__ __forceinline__ void sts_u32x2(uint32_t a, uint32_t x, uint32_t y) { asm volatile("st.shared.v2.u32 [%0], {%1, %2};" :: "r"(a), "r"(x), "r"(y) : "memory"); }
__device__ __forceinline__ void sts_f32(uint32_t a, float v) { asm volatile("st.shared.f32 [%0], %1;" :: "r"(a), "f"(v) : "memory"); }
__device__ __forceinline__ void sts_f32x2(uint32_t a, float x, float y) { asm volatile("st.shared.v2.f32 [%0], {%1, %2};" :: "r"(a), "f"(x), "f"(y) : "memory"); }
__device__ __forceinline__ void sts_f32x4(uint32_t a, float x, float y, float z, float w) { asm volatile("st.shared.v4.f32 [%0], {%1, %2, %3, %4};" :: "r"(a), "f"(x), "f"(y), "f"(z), "f"(w) : "memory"); }

__device__ __forceinline__ uint4 lds_u32x4(uint32_t a) { uint4 v; asm volatile("ld.shared.v4.u32 {%0, %1, %2, %3}, [%4];" : "=r"(v.x), "=r"(v.y), "=r"(v.z), "=r"(v.w) : "r"(a) : "memory"); return v; }
__device__ __forceinline__ void sts_u32x4(uint32_t a, uint32_t x, uint32_t y, uint32_t z, uint32_t w) { asm volatile("st.shared.v4.u32 [%0], {%1, %2, %3, %4};" :: "r"(a), "r"(x), "r"(y), "r"(z), "r"(w) : "memory"); }
__device__ __forceinline__ void st_tagged(float* p, float v) {
  const uint32_t b = __float_as_uint(v);
  asm volatile("st.relaxed.gpu.global.u32 [%0], %1;" :: "l"(p), "r"(b == 0u ? 0x80000000u : b) : "memory");
}
__device__ __forceinline__ void st_tagged4(float* p, float x, float y, float z, float w) {
  const uint32_t a = __float_as_uint(x), b = __float_as_uint(y), c = __float_as_uint(z), d = __float_as_uint(w);
  asm volatile("st.relaxed.gpu.global.v4.u32 [%0], {%1, %2, %3, %4};" :: "l"(p), "r"(a == 0u ? 0x80000000u : a), "r"(b == 0u ? 0x80000000u : b),
               "r"(c == 0u ? 0x80000000u : c), "r"(d == 0u ? 0x80000000u : d) : "memory");
}
__device__ __forceinline__ void st_relaxed2(void* p, uint32_t a, uint32_t b) { asm volatile("st.relaxed.gpu.global.v2.u32 [%0], {%1, %2};" :: "l"(p), "r"(a), "r"(b) : "memory"); }
__device__ __forceinline__ float4 ld_tagged4(const float* p) {
  float4 v; asm volatile("ld.relaxed.gpu.global.v4.f32 {%0, %1, %2, %3}, [%4];" : "=f"(v.x), "=f"(v.y), "=f"(v.z), "=f"(v.w) : "l"(p) : "memory"); return v;
}
__device__ __forceinline__ bool tagged4(const float4& v) {
  return __float_as_uint(v.x) != 0u && __float_as_uint(v.y) != 0u && __float_as_uint(v.z) != 0u && __float_as_uint(v.w) != 0u;
}
__device__ __forceinline__ void hint_arrive(uint32_t* p) { asm volatile("red.relaxed.gpu.global.add.u32 [%0], 1;" :: "l"(p) : "memory"); }
__device__ __forceinline__ void hint_wait(const uint32_t* p, uint32_t target) {
  uint32_t v = 0u;
  #pragma unroll 1
  for (unsigned int i = 0; i < (1u << 22) && v < target; i++) asm volatile("ld.relaxed.gpu.global.u32 %0, [%1];" : "=r"(v) : "l"(p) : "memory");
}
__device__ __forceinline__ void fence_proxy_async_global() { asm volatile("fence.proxy.async.global;" ::: "memory"); }

#define H_SPLIT 1
#define X_DLY 1200
#define W_DLY 1900
#define W_FIRST 2200
#define PRE_B 2
template <int J0, int J1>
__device__ __forceinline__ void load_parts(float2 (&pa)[J1 - J0][4], int t2) {
  #pragma unroll
  for (int j = J0; j < J1; j++)
    #pragma unroll
    for (int k = 0; k < 4; k++)
      asm volatile("ld.relaxed.gpu.global.v2.f32 {%0, %1}, [%2];" : "=f"(pa[j - J0][k].x), "=f"(pa[j - J0][k].y)
                   : "l"(g_modpart + k * 2 * T_D + (t2 >> 7) * T_D + j * 256 + (t2 & 127) * 2) : "memory");
}
template <int J0, int J1>
__device__ __forceinline__ void finish_parts(float2 (&pa)[J1 - J0][4], bool loaded, int t2, uint32_t tab) {
  #pragma unroll 1
  for (unsigned int spin = 0; spin < (1u << 22); spin++) {
    if (!loaded) load_parts<J0, J1>(pa, t2);
    loaded = false;
    bool ok = true;
    #pragma unroll
    for (int j = 0; j < J1 - J0; j++)
      #pragma unroll
      for (int k = 0; k < 4; k++) ok &= (__float_as_uint(pa[j][k].x) != 0u) & (__float_as_uint(pa[j][k].y) != 0u);
    if (__all_sync(0xffffffffu, ok)) break;
  }
  #pragma unroll
  for (int j = J0; j < J1; j++) {
    const float2* q = pa[j - J0];
    const uint32_t m = pack_bf16(((q[0].x + q[1].x) + q[2].x) + q[3].x, ((q[0].y + q[1].y) + q[2].y) + q[3].y);
    sts_u32(tab + (t2 >> 7) * 2048 + j * 512 + (t2 & 127) * 4, t2 >= 128 ? badd2(m, 0x3F803F80u) : m);
  }
}
__device__ __forceinline__ void head_phase(uint32_t bid, uint32_t scr, uint32_t xs, uint32_t b_x, uint32_t b_go, uint32_t b_head, int t2, uint32_t zero, const bf16* __restrict__ cvec, const bf16* __restrict__ w_mod) {
  const int lane = t2 & 31, w8 = t2 >> 5;
  const int cb = bid & 31, ks = bid >> 5;
  const bool early = (cb & 15) < 4 * H_SPLIT;
  const uint32_t ws = (xs - 32768 + (t2 >> 3) * 128 + (((t2 ^ (t2 >> 3)) & 7) << 4)) ^ zero;
  const float cv = __bfloat162float(cvec[ks * 256 + t2]);
  const bf16* wsrc = w_mod + (size_t)(ks * 256 + (t2 >> 3)) * (6 * T_D) + cb * 64 + (t2 & 7) * 8;
  if (early) {
    const uint64_t pol = policy_evict_first();
    #pragma unroll 2
    for (int i = 0; i < 8; i++)
      asm volatile("cp.async.cg.shared.global.L2::cache_hint [%0], [%1], 16, %2;" :: "r"(ws + i * 4096), "l"(wsrc + (size_t)i * 32 * 6 * T_D), "l"(pol) : "memory");
  }
  sts_f32(scr + t2 * 4, silu_bf(cv));
  named_bar_sync(6, 384);
  TL_MARK2(1, t2 == 0);
  uint4 xv[2][4];
  uint32_t mb2[2], ih[2], il[2];
  auto norm = [&](int j) {
    #pragma unroll
    for (int r = 0; r < 2; r++) {
      xv[r][j].x = ln_norm2b(xv[r][j].x, mb2[r], ih[r], il[r]); xv[r][j].y = ln_norm2b(xv[r][j].y, mb2[r], ih[r], il[r]);
      xv[r][j].z = ln_norm2b(xv[r][j].z, mb2[r], ih[r], il[r]); xv[r][j].w = ln_norm2b(xv[r][j].w, mb2[r], ih[r], il[r]);
    }
  };
  auto modulate = [&](int j) {
    const uint4 sa = lds_u32x4(scr + 8192 + j * 512 + lane * 16), c1 = lds_u32x4(scr + 8192 + 2048 + j * 512 + lane * 16);
    #pragma unroll
    for (int r = 0; r < 2; r++) {
      xv[r][j].x = badd2(bmul2(xv[r][j].x, c1.x), sa.x); xv[r][j].y = badd2(bmul2(xv[r][j].y, c1.y), sa.y);
      xv[r][j].z = badd2(bmul2(xv[r][j].z, c1.z), sa.z); xv[r][j].w = badd2(bmul2(xv[r][j].w, c1.w), sa.w);
    }
  };
  auto store = [&](int j) {
    #pragma unroll
    for (int r = 0; r < 2; r++) *reinterpret_cast<uint4*>(g_h + (size_t)(bid * 16 + 2 * w8 + r) * T_D + j * 256 + lane * 8) = xv[r][j];
  };
  #pragma unroll 1
  for (int ph = 0; ph < 2; ph++) {
    if ((ph == 0) == early) {
      asm volatile("cp.async.wait_all;" ::: "memory");
      if (!early) mbar_wait(b_x + 168, 0);
      float acc[8];
      #pragma unroll
      for (int j = 0; j < 8; j++) acc[j] = 0.f;
      #pragma unroll
      for (int i = 0; i < 8; i++) fma8(acc, lds_f32(scr + ((t2 >> 3) + 32 * i) * 4), lds_u32x4(ws + i * 4096));
      #pragma unroll
      for (int j = 0; j < 4; j++) { const bool up = lane & 16; acc[j] = (up ? acc[4 + j] : acc[j]) + __shfl_xor_sync(0xffffffffu, up ? acc[j] : acc[4 + j], 16); }
      #pragma unroll
      for (int j = 0; j < 2; j++) { const bool up = lane & 8; acc[j] = (up ? acc[2 + j] : acc[j]) + __shfl_xor_sync(0xffffffffu, up ? acc[j] : acc[2 + j], 8); }
      sts_f32x2(scr + 1024 + w8 * 256 + (lane & 7) * 32 + (lane >> 3) * 8, acc[0], acc[1]);
      named_bar_sync(5, 256);
      if (t2 < 64) {
        float sum = 0.f;
        #pragma unroll
        for (int i = 0; i < 8; i++) sum += lds_f32(scr + 1024 + i * 256 + t2 * 4);
        st_tagged(g_modpart + ks * 2 * T_D + cb * 64 + t2, sum);
        TL_MARK2(early ? 2 : 6, t2 == 0);
      }
    } else {
      float2 pa[H_SPLIT][4];
      mbar_wait(b_x, 0);
      TL_MARK2(18, t2 == 0);
      load_parts<0, H_SPLIT>(pa, t2);
      #pragma unroll
      for (int r = 0; r < 2; r++)
        #pragma unroll
        for (int j = 0; j < 4; j++) xv[r][j] = lds_u32x4(xs + (2 * w8 + r) * 2048 + j * 512 + lane * 16);
  {
    float st[4] = {0.f, 0.f, 0.f, 0.f};
    #pragma unroll
    for (int r = 0; r < 2; r++)
      #pragma unroll
      for (int j = 0; j < 4; j++) {
        float v[8];
        unpack8(xv[r][j], v);
        st[2 * r] += ((v[0] + v[1]) + (v[2] + v[3])) + ((v[4] + v[5]) + (v[6] + v[7]));
        st[2 * r + 1] += fmaf(v[0], v[0], fmaf(v[1], v[1], fmaf(v[2], v[2], v[3] * v[3]))) + fmaf(v[4], v[4], fmaf(v[5], v[5], fmaf(v[6], v[6], v[7] * v[7])));
      }
    #pragma unroll
    for (int k = 0; k < 2; k++) { const bool up = lane & 16; st[k] = (up ? st[2 + k] : st[k]) + __shfl_xor_sync(0xffffffffu, up ? st[k] : st[2 + k], 16); }
    #pragma unroll
    for (int o = 8; o > 0; o >>= 1) { st[0] += __shfl_xor_sync(0xffffffffu, st[0], o); st[1] += __shfl_xor_sync(0xffffffffu, st[1], o); }
    const float mean = st[0] * (1.0f / T_D);
    const float inv = rcp_approx(rbf(sqrt_approx(rbf(rbf(fmaxf(fmaf(-mean, mean, st[1] * (1.0f / T_D)), 0.f)) + 1e-05f))));
    const uint32_t m = pack_bf16(mean, mean), h = pack_bf16(inv - rbf(inv), inv);
    #pragma unroll
    for (int r = 0; r < 2; r++) {
      mb2[r] = __shfl_sync(0xffffffffu, m, 16 * r);
      const uint32_t hr = __shfl_sync(0xffffffffu, h, 16 * r);
      ih[r] = __byte_perm(hr, hr, 0x3232); il[r] = __byte_perm(hr, hr, 0x1010);
    }
  }
      #pragma unroll
      for (int j = 0; j < H_SPLIT; j++) norm(j);
      TL_MARK2(5, t2 == 0);
      finish_parts<0, H_SPLIT>(pa, true, t2, scr + 8192);
      named_bar_sync(5, 256);
      TL_MARK2(7, t2 == 0);
      #pragma unroll
      for (int j = 0; j < H_SPLIT; j++) { modulate(j); store(j); }
      named_bar_arrive(9, 288);
    }
  }
  #pragma unroll
  for (int j = H_SPLIT; j < 4; j++) norm(j);
  float2 pb[4 - H_SPLIT][4];
  finish_parts<H_SPLIT, 4>(pb, false, t2, scr + 8192);
  named_bar_sync(5, 256);
  TL_MARK2(17, t2 == 0);
  #pragma unroll
  for (int j = H_SPLIT; j < 4; j++) modulate(j);
  __syncwarp();
  if (lane == 0) mbar_arrive(b_head + (xv[1][3].w & zero));
  mbar_wait(b_go, 0);
  #pragma unroll
  for (int j = H_SPLIT; j < 4; j++) store(j);
  named_bar_arrive(8, 288);
}

#define MOD_AT (b_empty + 8)
#define MOD_SPLIT 16
__device__ __forceinline__ void mod_rest(uint32_t bid, uint32_t scr, uint32_t b_go, int t, const bf16* __restrict__ cvec, const bf16* __restrict__ w_mod, const bf16* __restrict__ w_r) {
  const int lane = t & 31;
  #pragma unroll 1
  for (int i = t; i < T_D / 2; i += 64) {
    const uint32_t c2 = *reinterpret_cast<const uint32_t*>(cvec + 2 * i);
    sts_u32(scr + i * 4, pack_bf16(silu_bf(bflo(c2)), silu_bf(bfhi(c2))));
  }
  named_bar_sync(11, 64);
  const bf16* wp = w_mod + (size_t)(2 * (t >> 2)) * (6 * T_D) + 2 * T_D + bid * 32 + (t & 3) * 8;
  float acc[8];
  #pragma unroll
  for (int i = 0; i < 8; i++) acc[i] = 0.f;
  #pragma unroll 1
  for (int i = 0; i < 32; i += 2) {
    if (i == MOD_SPLIT) mbar_wait(b_go, 0);
    const uint4 w0 = ldg_nc_v4(wp), w1 = ldg_nc_v4(wp + 6 * T_D), w2 = ldg_nc_v4(wp + 32 * 6 * T_D), w3 = ldg_nc_v4(wp + 33 * 6 * T_D);
    wp += 64 * 6 * T_D;
    const uint32_t s0 = lds_u32(scr + (i * 16 + (t >> 2)) * 4), s1 = lds_u32(scr + (i * 16 + 16 + (t >> 2)) * 4);
    fma8(acc, bflo(s0), w0); fma8(acc, bfhi(s0), w1); fma8(acc, bflo(s1), w2); fma8(acc, bfhi(s1), w3);
  }
  #pragma unroll
  for (int j = 0; j < 4; j++) { const bool up = lane & 16; acc[j] = (up ? acc[4 + j] : acc[j]) + __shfl_xor_sync(0xffffffffu, up ? acc[j] : acc[4 + j], 16); }
  #pragma unroll
  for (int j = 0; j < 2; j++) { const bool up = lane & 8; acc[j] = (up ? acc[2 + j] : acc[j]) + __shfl_xor_sync(0xffffffffu, up ? acc[j] : acc[2 + j], 8); }
  { const bool up = lane & 4; acc[0] = (up ? acc[1] : acc[0]) + __shfl_xor_sync(0xffffffffu, up ? acc[0] : acc[1], 4); }
  if (t >= 32) sts_f32(scr + 2048 + lane * 4, acc[0]);
  named_bar_sync(11, 64);
  if (__shfl_sync(0xffffffffu, t, 0) < 32) {
    const int kind = bid >> 5;
    float v = rbf(acc[0] + lds_f32(scr + 2048 + lane * 4));
    const int col = (bid & 31) * 32 + (lane & 3) * 8 + (lane >> 2);
    uint8_t* dst = g_col + (col >> 7) * 1536;
    if (kind == 2) v = rbf(1.0f + v);
    float vw = v * __bfloat162float(w_r[col]);
    if (kind == 2) {
      const int c = col & 127, i = (c & ~15) + ((c >> 1) & 3) * 4 + ((c >> 3) & 1) * 2 + (c & 1);
      reinterpret_cast<bf16*>(dst)[i] = __float2bfloat16_rn(vw);
      reinterpret_cast<bf16*>(dst)[128 + i] = __float2bfloat16_rn(vw - rbf(vw));
    }
    reinterpret_cast<bf16*>(dst + 512 + (kind & 1) * 512 + (kind >> 1) * 256)[col & 127] = __float2bfloat16_rn(v);
    #pragma unroll
    for (int o = 16; o > 0; o >>= 1) vw += __shfl_xor_sync(0xffffffffu, vw, o);
    if (lane == 0 && (kind == 1 || kind == 2)) g_scal[95 - bid] = vw;
  }
  #pragma unroll 1
  for (int i = bid * 64 + t; i < (int)(sizeof(g_mail) / 16); i += 128 * 64) reinterpret_cast<uint4*>(&g_mail)[i] = make_uint4(0u, 0u, 0u, 0u);
  named_bar_sync(11, 64);
  if (t == 0) red_release_add(&g_hcnt[0], 1u);
}

constexpr int AT_NBLK = T_SEQ / 128;
constexpr float AT_HEAD = 7.0f;
#define WO_LATE 12
#define QP_STAG 3
#define AT_SPLIT 28
#define AT_PIN 12
#define PINB 4
constexpr int AT_NFULL = 124;
constexpr int AT_PREG = 40, AT_CREG = 232;
constexpr uint32_t AT_SQ = 5 * 32768;
constexpr float AT_C = 0.08838834764831845f * 1.4426950408889634f;
constexpr float AT_RAW_LO = -16.0f, AT_RAW_HI = 24.0f;
constexpr float AT_RAW_SUM = 281474976710656.0f, AT_RAW_MIN = 9.094947017729282e-13f;
constexpr uint32_t AT_SBAR = AT_SQ + 65536 + 256;
constexpr uint32_t AT_SMEM = AT_SQ + 65536 + 3072;

__device__ __forceinline__ uint32_t ring_slot(uint32_t t) { return t - 5u * ((t * 205u) >> 10); }
__device__ __forceinline__ uint32_t qp_pos(uint32_t j, uint32_t it) { return 4u * it + (j & 3u) + ((j & 3u) == 3u ? it : 0u); }
__device__ __forceinline__ uint32_t ring_par(uint32_t t) { return ((t * 205u) >> 10) & 1u; }
__device__ __forceinline__ void softmax_rowmax(const float (&s)[64], float& mx0, float& mx1) {
  float a0 = fmaxf(s[0], s[1]), a1 = fmaxf(s[4], s[5]), a2 = fmaxf(s[8], s[9]), a3 = fmaxf(s[12], s[13]);
  float b0 = fmaxf(s[2], s[3]), b1 = fmaxf(s[6], s[7]), b2 = fmaxf(s[10], s[11]), b3 = fmaxf(s[14], s[15]);
  #pragma unroll
  for (int j = 4; j < 16; j += 4) {
    a0 = fmaxf(a0, fmaxf(s[4 * j + 0], s[4 * j + 1]));  b0 = fmaxf(b0, fmaxf(s[4 * j + 2], s[4 * j + 3]));
    a1 = fmaxf(a1, fmaxf(s[4 * j + 4], s[4 * j + 5]));  b1 = fmaxf(b1, fmaxf(s[4 * j + 6], s[4 * j + 7]));
    a2 = fmaxf(a2, fmaxf(s[4 * j + 8], s[4 * j + 9]));  b2 = fmaxf(b2, fmaxf(s[4 * j + 10], s[4 * j + 11]));
    a3 = fmaxf(a3, fmaxf(s[4 * j + 12], s[4 * j + 13])); b3 = fmaxf(b3, fmaxf(s[4 * j + 14], s[4 * j + 15]));
  }
  mx0 = fmaxf(fmaxf(a0, a1), fmaxf(a2, a3));
  mx1 = fmaxf(fmaxf(b0, b1), fmaxf(b2, b3));
  mx0 = fmaxf(mx0, __shfl_xor_sync(0xffffffffu, mx0, 1));
  mx1 = fmaxf(mx1, __shfl_xor_sync(0xffffffffu, mx1, 1));
  mx0 = fmaxf(mx0, __shfl_xor_sync(0xffffffffu, mx0, 2));
  mx1 = fmaxf(mx1, __shfl_xor_sync(0xffffffffu, mx1, 2));
}
__device__ __forceinline__ void softmax_sub(float (&s)[64], float mc0, float mc1) {
  #pragma unroll
  for (int j = 0; j < 16; j++) { s[4 * j] -= mc0; s[4 * j + 1] -= mc0; s[4 * j + 2] -= mc1; s[4 * j + 3] -= mc1; }
}
template <int LO, int HI>
__device__ __forceinline__ void softmax_exp(float (&s)[64]) {
  #pragma unroll
  for (int i = LO; i < HI; i++) s[i] = ex2_approx(s[i]);
}
__device__ __forceinline__ bool softmax_mode(const float (&s)[64], float& mc0, float& mc1) {
  softmax_rowmax(s, mc0, mc1);
  const bool raw = __all_sync(0xffffffffu, mc0 >= AT_RAW_LO && mc0 <= AT_RAW_HI && mc1 >= AT_RAW_LO && mc1 <= AT_RAW_HI);
  mc0 += AT_HEAD; mc1 += AT_HEAD;
  return raw;
}
__device__ __forceinline__ void rowsum_p(const uint32_t (&p)[32], uint32_t& t0, uint32_t& t1) {
  uint32_t a[16];
  #pragma unroll
  for (int i = 0; i < 8; i++) { a[2 * i] = badd2(p[4 * i], p[4 * i + 2]); a[2 * i + 1] = badd2(p[4 * i + 1], p[4 * i + 3]); }
  #pragma unroll
  for (int i = 0; i < 4; i++) { a[2 * i] = badd2(a[4 * i], a[4 * i + 2]); a[2 * i + 1] = badd2(a[4 * i + 1], a[4 * i + 3]); }
  t0 = badd2(badd2(a[0], a[2]), badd2(a[4], a[6]));
  t1 = badd2(badd2(a[1], a[3]), badd2(a[5], a[7]));
}
__device__ __forceinline__ void add_rowsum(const uint32_t (&p)[32], float& l0, float& l1) {
  uint32_t t0, t1;
  rowsum_p(p, t0, t1);
  l0 += bflo(t0) + bfhi(t0); l1 += bflo(t1) + bfhi(t1);
}
__device__ __forceinline__ void pack_p(uint32_t (&p)[32], const float (&s)[64]) {
  #pragma unroll
  for (int i = 0; i < 32; i++) p[i] = pack_bf16(s[2 * i], s[2 * i + 1]);
}
__device__ __noinline__ void attn_rows_exact(uint32_t bid, uint32_t sq, uint32_t so, int hsel, const bf16* __restrict__ kh, const bf16* __restrict__ vh) {
  const int warp = (threadIdx.x >> 5) & 3, lane = threadIdx.x & 31;
  const size_t hofs = (size_t)((bid < 128 ? bid >> 4 : 15) * 2 + hsel) * T_SEQ * T_DH;
  kh += hofs; vh += hofs;
  #pragma unroll 1
  for (int r = 16 * warp; r < 16 * warp + 16; r++) {
    const uint32_t ad = (lane >> 4) * 16384 + r * 128 + ((((lane & 15) >> 1) ^ (r & 7)) << 4) + (lane & 1) * 8;
    uint2 qv; asm volatile("ld.shared.v2.u32 {%0, %1}, [%2];" : "=r"(qv.x), "=r"(qv.y) : "r"(sq + ad) : "memory");
    const float q0 = bflo(qv.x), q1 = bfhi(qv.x), q2 = bflo(qv.y), q3 = bfhi(qv.y);
    float m = -INFINITY, l = 0.f, o0 = 0.f, o1 = 0.f, o2 = 0.f, o3 = 0.f;
    #pragma unroll 1
    for (int key = 0; key < T_SEQ; key++) {
      const uint2 kv = *reinterpret_cast<const uint2*>(kh + (size_t)key * T_DH + lane * 4);
      const uint2 vv = *reinterpret_cast<const uint2*>(vh + (size_t)key * T_DH + lane * 4);
      float sc = (q0 * bflo(kv.x) + q1 * bfhi(kv.x)) + (q2 * bflo(kv.y) + q3 * bfhi(kv.y));
      #pragma unroll
      for (int o = 16; o > 0; o >>= 1) sc += __shfl_xor_sync(0xffffffffu, sc, o);
      const float mn = fmaxf(m, sc);
      const float al = (m == mn) ? 1.0f : ex2_approx(m - mn), p = rbf(ex2_approx(sc - mn));
      m = mn;
      l = fmaf(l, al, p);
      o0 = fmaf(o0, al, p * bflo(vv.x)); o1 = fmaf(o1, al, p * bfhi(vv.x));
      o2 = fmaf(o2, al, p * bflo(vv.y)); o3 = fmaf(o3, al, p * bfhi(vv.y));
    }
    const float inv = rcp_approx(l);
    asm volatile("st.shared.v2.u32 [%0], {%1, %2};" :: "r"(so + ad), "r"(pack_bf16(o0 * inv, o1 * inv)), "r"(pack_bf16(o2 * inv, o3 * inv)) : "memory");
  }
}
__device__ __forceinline__ void issue_qk(float (&s)[64], const uint32_t (&q)[32], uint32_t k_lo) {
  wgmma_fence();
  wgmma_m64n128k16_rs<0>(s, q[0], q[1], q[2], q[3], k_lo, 0);
  wgmma_m64n128k16_rs<2>(s, q[4], q[5], q[6], q[7], k_lo, 1);
  wgmma_m64n128k16_rs<4>(s, q[8], q[9], q[10], q[11], k_lo, 1);
  wgmma_m64n128k16_rs<6>(s, q[12], q[13], q[14], q[15], k_lo, 1);
  wgmma_m64n128k16_rs<1024>(s, q[16], q[17], q[18], q[19], k_lo, 1);
  wgmma_m64n128k16_rs<1026>(s, q[20], q[21], q[22], q[23], k_lo, 1);
  wgmma_m64n128k16_rs<1028>(s, q[24], q[25], q[26], q[27], k_lo, 1);
  wgmma_m64n128k16_rs<1030>(s, q[28], q[29], q[30], q[31], k_lo, 1);
  wgmma_commit();
}
__device__ __forceinline__ void issue_pv(float (&o)[64], const uint32_t (&p)[32], uint32_t v_lo, int accumulate) {
  wgmma_fence();
  wgmma_m64n128k16_rs_tb<0>(o, p[0], p[1], p[2], p[3], v_lo, accumulate);
  wgmma_m64n128k16_rs_tb<128>(o, p[4], p[5], p[6], p[7], v_lo, 1);
  wgmma_m64n128k16_rs_tb<256>(o, p[8], p[9], p[10], p[11], v_lo, 1);
  wgmma_m64n128k16_rs_tb<384>(o, p[12], p[13], p[14], p[15], v_lo, 1);
  wgmma_m64n128k16_rs_tb<512>(o, p[16], p[17], p[18], p[19], v_lo, 1);
  wgmma_m64n128k16_rs_tb<640>(o, p[20], p[21], p[22], p[23], v_lo, 1);
  wgmma_m64n128k16_rs_tb<768>(o, p[24], p[25], p[26], p[27], v_lo, 1);
  wgmma_m64n128k16_rs_tb<896>(o, p[28], p[29], p[30], p[31], v_lo, 1);
  wgmma_commit();
}
__device__ __forceinline__ void block_end(uint32_t zero, uint32_t bar) {
  #pragma unroll 1
  for (uint32_t i = 0; i < zero; i++) mbar_arrive(bar);
}
__device__ __forceinline__ void rescale_o(float (&o)[64], float al0, float al1) {
  #pragma unroll
  for (int j = 0; j < 16; j++) { o[4 * j] *= al0; o[4 * j + 1] *= al0; o[4 * j + 2] *= al1; o[4 * j + 3] *= al1; }
}

__device__ __forceinline__ void stage_o(const float (&o)[64], float i0, float i1, uint32_t dst, int lane) {
  #pragma unroll
  for (int J = 0; J < 16; J += 2)
    stmatrix_x4(dst + (J >> 3) * 16384 + ((((J & 7) + (lane >> 4)) ^ (lane & 7)) << 4),
                pack_bf16(o[4 * J + 0] * i0, o[4 * J + 1] * i0), pack_bf16(o[4 * J + 2] * i1, o[4 * J + 3] * i1),
                pack_bf16(o[4 * J + 4] * i0, o[4 * J + 5] * i0), pack_bf16(o[4 * J + 6] * i1, o[4 * J + 7] * i1));
}
__device__ __forceinline__ bool finish_l(float& l0, float& l1) {
  l0 += __shfl_xor_sync(0xffffffffu, l0, 1); l1 += __shfl_xor_sync(0xffffffffu, l1, 1);
  l0 += __shfl_xor_sync(0xffffffffu, l0, 2); l1 += __shfl_xor_sync(0xffffffffu, l1, 2);
  const bool redo = __any_sync(0xffffffffu, !(l0 <= AT_RAW_SUM && l1 <= AT_RAW_SUM && l0 >= AT_RAW_MIN && l1 >= AT_RAW_MIN));
  l0 = rcp_approx(l0); l1 = rcp_approx(l1);
  return redo;
}
template <int J0>
__device__ __forceinline__ void stage_q(const float (&acc)[128], float c, uint32_t dst, int lane) {
  #pragma unroll
  for (int J = J0; J < J0 + 16; J += 2)
    stmatrix_x4(dst + (J >> 3) * 16384 + ((((J & 7) + (lane >> 4)) ^ (lane & 7)) << 4),
                pack_bf16(acc[4 * J + 0] * c, acc[4 * J + 1] * c), pack_bf16(acc[4 * J + 2] * c, acc[4 * J + 3] * c),
                pack_bf16(acc[4 * J + 4] * c, acc[4 * J + 5] * c), pack_bf16(acc[4 * J + 6] * c, acc[4 * J + 7] * c));
}
__device__ __forceinline__ void store_o(const CUtensorMap* tmO, uint32_t src, int head, int row) {
  tma_store_2d(tmO, src, head * T_DH, row);
  tma_store_2d(tmO, src + 16384, head * T_DH + 64, row);
  bulk_commit();
}
__device__ __forceinline__ void mma_bf16(float (&d)[4], uint32_t a0, uint32_t a1, uint32_t a2, uint32_t a3, uint32_t b0, uint32_t b1) {
  asm volatile("mma.sync.aligned.m16n8k16.row.col.f32.bf16.bf16.f32 {%0, %1, %2, %3}, {%4, %5, %6, %7}, {%8, %9}, {%0, %1, %2, %3};"
               : "+f"(d[0]), "+f"(d[1]), "+f"(d[2]), "+f"(d[3]) : "r"(a0), "r"(a1), "r"(a2), "r"(a3), "r"(b0), "r"(b1));
}
struct GemvSel { uint32_t lo0, hi0, lo1, hi1; };
__device__ __forceinline__ GemvSel gemv_sel(int lane) {
  const uint32_t lo = (lane & 8) ? 0x1044u : 0x4410u, hi = (lane & 8) ? 0x3244u : 0x4432u;
  GemvSel s; s.lo0 = (lane & 16) ? 0x4444u : lo; s.hi0 = (lane & 16) ? 0x4444u : hi; s.lo1 = (lane & 16) ? lo : 0x4444u; s.hi1 = (lane & 16) ? hi : 0x4444u;
  return s;
}
#define GEMV_B0(j, h, s) __byte_perm((j) < 2 ? (h).x : (h).y, 0u, ((j) & 1) ? (s).hi0 : (s).lo0)
#define GEMV_B1(j, h, s) __byte_perm((j) < 2 ? (h).x : (h).y, 0u, ((j) & 1) ? (s).hi1 : (s).lo1)
__device__ __forceinline__ float4 gemv_out(const float (&d)[4], int lane) {
  const bool tk = lane & 1;
  const float r0 = __shfl_xor_sync(0xffffffffu, tk ? d[0] : d[1], 1), r1 = __shfl_xor_sync(0xffffffffu, tk ? d[2] : d[3], 1);
  return tk ? make_float4(r0, d[1], r1, d[3]) : make_float4(d[0], r0, d[2], r1);
}
#define OG_NG 8
#define PUT_N 2
#define H_STAG 2
#define AL_P 60
#define AL_SLEEP 1200
#define AL_MAX 800
#define POLL_NS 500
#define OG_PROF 0xECCBB988u
#define RK_P 24
#define RANK 1
__host__ __device__ constexpr int og_pre(int tile) { return (OG_PROF >> ((tile >> 4) * 4)) & 15; }
constexpr int OG_PRE2 = og_pre(127), OG_HSUM = og_pre(0) + og_pre(16) + og_pre(32) + og_pre(48) + og_pre(64) + og_pre(80) + og_pre(96);
#define OG_JOBS 7
#define OG_GRP 6
#define LD_FIRST 2
#define LD_STAG (OG_GRP / 2)
constexpr int OG_ST = 5, OG_NKB = T_DQKV / 64 - og_pre(0), OG_MOE = T_F / 32;
__device__ __forceinline__ int pre_kb(int i) { return (i >> 1) * 4 + (i & 1); }
__device__ __forceinline__ int own_kb(int i, int pre) { return i < (pre & ~1) ? pre_kb(i) + 2 : i + pre; }
constexpr int OG_POS = 8;
constexpr uint32_t OG_STAGE = 32768;
constexpr uint32_t OG_SCOL = AT_SBAR + 512;
constexpr uint32_t OG_SMISC = AT_SBAR + 2048;
constexpr uint32_t OG_SWD = AT_SQ, OG_PSLOT = AT_SQ;
constexpr uint32_t OG_XSLOT = AT_SQ + 32768;
constexpr uint32_t OG_OSLOT = 1 * OG_STAGE;
constexpr uint32_t OG_SRED = 3 * OG_STAGE;
constexpr uint32_t OG_SH2 = OG_SRED + 24576;
constexpr uint32_t OG_SSTAT = OG_SRED + 16384;
constexpr uint32_t OG_SGU = OG_SRED + 8192;
constexpr uint32_t OG_SFIN = OG_SGU + 256;
#define OGM 2
#define OG_MT(b) ((((b) >> OGM) & 15) ^ (((b) & 64) ? 15 : 0))
#define OG_NT(b) (((b) & ((1 << OGM) - 1)) + (((b) >> (4 + OGM)) << OGM))
__device__ __forceinline__ int tail_tile(uint32_t sbase) { mbar_wait(sbase + AT_SBAR + 336, 0); return (int)lds_u32(sbase + AT_SBAR + 408); }
#define TAIL_SETUP \
  const uint32_t bar_full = sbase + AT_SBAR, bar_empty = bar_full + 40; \
  const uint32_t bar_wd = bar_full + 168, bar_col = bar_full + 176, bar_out = bar_full + 184, bar_end = bar_full + 192; \
  const uint32_t bar_key = bar_full + 200, bar_h2 = bar_full + 208, bar_sel = bar_full + 216; \
  const int mt = OG_MT(tb), nt = OG_NT(tb); \
  const int m0 = mt * 128, n0 = nt * 128; \
  const bool has_moe = (int)bid < OG_MOE; \
  (void)bar_empty; (void)bar_wd; (void)bar_col; (void)bar_out; (void)bar_end; (void)bar_key; (void)bar_h2; (void)bar_sel; (void)m0; (void)n0; (void)has_moe;

__device__ __forceinline__ void tail_producer(uint32_t bid, uint32_t sbase, uint32_t ph, uint64_t pol, const CUtensorMap* tmA, const CUtensorMap* tmB, const CUtensorMap* tmD) {
  const int tb = tail_tile(sbase);
  TAIL_SETUP
  uint32_t stage = OG_POS % OG_ST;
  int kb = 0;
  #pragma unroll 1
  for (int seg = 0; seg < 2; seg++) {
    mbar_wait(bar_full + 264 + 80 * seg, 0);
    fence_proxy_async_global();
    const int end = 32 + 32 * seg - og_pre(tb);
    #pragma unroll 1
    for (; kb < end; kb++) {
      const uint32_t fb = bar_full + 8 * stage, sa = sbase + stage * OG_STAGE;
      const int k0 = own_kb(kb, og_pre(tb)) * 64;
      mbar_wait(bar_empty + 8 * stage, ph);
      mbar_expect_tx(fb, OG_STAGE);
      tma_load_3d_hint(sa + 16384, tmB, k0, 2 * nt, fb, pol);
      tma_load_2d_hint(sa, tmA, k0, m0, fb, pol);
      if (++stage == OG_ST) { stage = 0; ph ^= 1; }
    }
  }
  if (has_moe) {
    stage += stage & 1;
    mbar_wait(bar_empty + 8 * stage, ph);
    mbar_expect_tx(bar_wd, OG_STAGE);
    tma_load_3d_hint(sbase + stage * OG_STAGE, tmD, bid * 32, 8, bar_wd, pol);
  }
}

__device__ __forceinline__ uint32_t out2(uint32_t x1, uint32_t mb2, uint32_t ih, uint32_t il, uint32_t c1, uint32_t sb, uint32_t gb) {
  const uint32_t h2 = badd2(bmul2(ln_norm2b(x1, mb2, ih, il), c1), sb);
  return badd2(x1, bmul2(gb, bfma2(h2, 0u, h2)));
}
#define OGTIME gtime()
#define X_PACE 200
#define Y_SLACK 96
#define OG_STAG 3
#define X_PACE2 100
#define WD_PACE 300
__device__ __forceinline__ void tail_exchange(uint32_t bid, uint32_t sbase, const bf16* __restrict__ w_down, const bf16* __restrict__ w_r, const bf16* __restrict__ x, bf16* __restrict__ out) {
    const int lane = threadIdx.x & 31, wi = __shfl_sync(0xffffffffu, threadIdx.x >> 5, 0);
    if (wi == 3) {
      uint32_t a = bid, b = 0u;
      if (bid < AT_NFULL) mbar_wait(sbase + AT_SBAR + 312, 0);
      if (bid < OG_MOE) {
        asm volatile("mov.u32 %0, %%globaltimer_lo;" : "=r"(a));
        if (lane == 0 && (bid & 15) == 0) asm volatile("st.relaxed.gpu.global.u32 [%0], %1;" :: "l"(g_hcnt + 8 + (bid >> 4)), "r"((a & ~15u) | 8u | (bid >> 4)) : "memory");
        #pragma unroll 1
        for (unsigned int spin = 0; spin < (1u << 22) && __any_sync(0xffffffffu, b == 0u); spin++) {
          __nanosleep(200);
          asm volatile("ld.relaxed.gpu.global.u32 %0, [%1];" : "=r"(b) : "l"(g_hcnt + 8 + min(lane, 6)) : "memory");
        }
        a = RANK ? __popc(__ballot_sync(0xffffffffu, b < __shfl_sync(0xffffffffu, b, bid >> 4)) & 127u) * 16 + (bid & 15) : bid;
      }
      if (lane == 0) {
        sts_u32(sbase + AT_SBAR + 408, a);
        mbar_arrive(sbase + AT_SBAR + 336);
        b = 0u;
        if (bid < AT_NFULL) {
          unsigned int* tm = g_hcnt + 32 * (1 + (bid >> 4)) + 8;
          mbar_wait(sbase + AT_SBAR + 312, 1);
          asm volatile("mov.u32 %0, %%globaltimer_lo;" : "=r"(a));
          asm volatile("red.relaxed.gpu.global.max.u32 [%0], %1;" :: "l"(tm), "r"(a) : "memory");
          __nanosleep(AL_SLEEP);
          asm volatile("ld.relaxed.gpu.global.u32 %0, [%1];" : "=r"(b) : "l"(tm) : "memory");
          b -= a;
        }
        sts_u32(sbase + AT_SBAR + 412, b < AL_MAX ? b * 13 / 8 : 0u);
        mbar_arrive(sbase + AT_SBAR + 320);
      }
      named_bar_sync(15, 32);
    }
    const int tb = __shfl_sync(0xffffffffu, tail_tile(sbase), 0);
    TAIL_SETUP
    if (wi == 3) {
      mbar_wait(bar_full + 344, 0);
      float a = g_scal[lane], b = g_scal[32 + lane];
      #pragma unroll
      for (int i = 0; i < 3; i++) {
        const uint4 v = *reinterpret_cast<const uint4*>(g_col + nt * 1536 + i * 512 + lane * 16);
        sts_u32x4(sbase + OG_SCOL + i * 512 + lane * 16, v.x, v.y, v.z, v.w);
      }
      #pragma unroll
      for (int o = 16; o > 0; o >>= 1) { a += __shfl_xor_sync(0xffffffffu, a, o); b += __shfl_xor_sync(0xffffffffu, b, o); }
      if (lane == 0) sts_f32x2(sbase + OG_SMISC, a, b);
      const uint64_t pol = policy_evict_first();
      #pragma unroll 1
      for (int r = lane >> 4; r < 128; r += 4) {
        __nanosleep(X_PACE);
        if (X_PACE2) __nanosleep(X_PACE2);
        #pragma unroll
        for (int j = 0; j < 4; j += 2)
          asm volatile("cp.async.cg.shared.global.L2::cache_hint [%0], [%1], 16, %2;" :: "r"(sbase + OG_XSLOT + (lane & 8) * 2048 + (r + j) * 128 + (((lane ^ (r + j)) & 7) << 4)),
                       "l"(x + (size_t)(m0 + r + j) * T_D + n0 + (lane & 15) * 8), "l"(pol) : "memory");
      }
      asm volatile("cp.async.wait_all;" ::: "memory");
      __syncwarp();
      if (lane == 0) mbar_arrive(bar_col);
    } else if (wi == 2) {
      if (elect_one()) {
        const uint32_t b_free = bar_full + (bid < AT_NFULL ? 80 : 160);
        mbar_wait(b_free, 1);
        #pragma unroll 1
        for (unsigned int i = 0; i < (1u << 20) && ld_acquire(&g_hcnt[32 * (1 + (tb >> 3)) + 4 + ((tb >> 1) & 3)]) == 0u; i++) __nanosleep(POLL_NS);
        TL_MARK2(23, true);
        fence_proxy_async_global();
        TL_MARK2(4, true);
        mbar_expect_tx(bar_full + 272, 32768);
        bulk_load_hint(sbase + OG_PSLOT, g_pre + tb * 2048, 32768, bar_full + 272, policy_evict_first());
      }
      named_bar_sync(14, 32);
      if (has_moe) {
        mbar_wait(bar_full + 96, 1); mbar_wait(bar_full + 304, 0);
        const uint64_t pol = policy_evict_first();
        #pragma unroll 1
        for (int r = 0; r < 32; r++) {
          __nanosleep(WD_PACE);
          #pragma unroll
          for (int j = 0; j < 2; j++)
            asm volatile("cp.async.cg.shared.global.L2::cache_hint [%0], [%1], 16, %2;" :: "r"(sbase + OG_SWD + (4 * j + (lane >> 3)) * 4096 + r * 128 + (((lane ^ r) & 7) << 4)),
                         "l"((const uint8_t*)w_down + (size_t)bid * 65536 + r * 2048 + j * 512 + lane * 16), "l"(pol) : "memory");
        }
        asm volatile("cp.async.wait_all;" ::: "memory");
        __syncwarp();
        if (lane == 0) mbar_arrive(bar_wd);
      }
    }
    const uint4 wrv = ldg_nc_v4(w_r + threadIdx.x * 8);
    mbar_wait(bar_end, 0);
    if (threadIdx.x == 96) XT(10);
    TL_MARK2(22, lane == 0);
    if (wi == 0) {
      uint32_t k1 = 0u, k2 = 0u;
      #pragma unroll 1
      for (unsigned int spin = 0; spin < (1u << 22) && __any_sync(0xffffffffu, k1 == 0u); spin++) asm volatile("ld.relaxed.gpu.global.u32 %0, [%1];" : "=r"(k1) : "l"(g_key + lane) : "memory");
      TL_MARK2(28, lane == 0);
      warp_top2(k1, k2);
      if (lane == 0) {
        const uint32_t r1 = 0xffffu - (k1 & 0xffffu), r2 = 0xffffu - (k2 & 0xffffu);
        sts_u32x4(sbase + OG_SMISC + 64, r1, r2, (r1 >> 7) * 2, (r2 >> 7) * 2 + ((r1 >> 7) == (r2 >> 7)));
        mbar_arrive(bar_sel);
      }
    } else if (wi < 3) {
          mbar_wait(bar_key, 0);
          const uint4 kk = lds_u32x4(sbase + OG_SSTAT + 1024 + lane * 16);
          uint32_t k1 = max(kk.x, kk.y), k2 = min(kk.x, kk.y);
          k2 = max(max(k2, min(kk.z, kk.w)), min(k1, max(kk.z, kk.w))); k1 = max(k1, max(kk.z, kk.w));
          warp_top2(k1, k2);
          if (wi == 1) {
            if (lane == 0) {
              if (nt == (mt & 7)) st_relaxed2(g_key + mt * 2, k1, k2);
              sts_u32x2(sbase + OG_SMISC + 96, (~k1 >> 4) & 7u, (~k2 >> 4) & 7u);
              mbar_arrive(bar_full + 352);
            }
            TL_MARK2(27, lane == 0);
          } else {
            const uint32_t r = (~((lane & 16) ? k2 : k1)) & 127u, ch = lane & 15;
            const uint2 st = lds_u32x2(sbase + OG_SSTAT + r * 8);
            const uint4 xc = lds_u32x4(sbase + OG_XSLOT + (ch >> 3) * 16384 + r * 128 + (((ch ^ r) & 7) << 4));
            const uint4 c1 = lds_u32x4(sbase + OG_SCOL + 768 + ch * 16), sh = lds_u32x4(sbase + OG_SCOL + 1024 + ch * 16);
            const float inr = __uint_as_float(st.y);
            float* dst = reinterpret_cast<float*>(g_cand + (mt * 2 + (lane >> 4)) * 256 + nt * 16 + ch);
            st_tagged4(dst + 512, __uint_as_float(ln_mod2(xc.x, st.x, inr, c1.x, sh.x)), __uint_as_float(ln_mod2(xc.y, st.x, inr, c1.y, sh.y)),
                       __uint_as_float(ln_mod2(xc.z, st.x, inr, c1.z, sh.z)), __uint_as_float(ln_mod2(xc.w, st.x, inr, c1.w, sh.w)));
            st_tagged4(dst, __uint_as_float(xc.x), __uint_as_float(xc.y), __uint_as_float(xc.z), __uint_as_float(xc.w));
          }
    }
    mbar_wait(bar_sel, 0);
    const uint4 sel = lds_u32x4(sbase + OG_SMISC + 64);
    const int sel0 = (int)sel.x, sel1 = (int)sel.y;
    {
      const float* src0 = reinterpret_cast<const float*>(g_cand + sel.z * 256 + 128 + threadIdx.x);
      const float* src1 = reinterpret_cast<const float*>(g_cand + sel.w * 256 + 128 + threadIdx.x);
      float4 h0, h1;
      #pragma unroll 1
      for (unsigned int spin = 0; spin < (1u << 20); spin++) { h0 = ld_tagged4(src0); h1 = ld_tagged4(src1); if (__all_sync(0xffffffffu, tagged4(h0) & tagged4(h1))) break; }
      sts_f32x4(sbase + OG_SH2 + threadIdx.x * 16, h0.x, h0.y, h0.z, h0.w);
      sts_f32x4(sbase + OG_SH2 + 2048 + threadIdx.x * 16, h1.x, h1.y, h1.z, h1.w);
      __syncwarp();
      if (lane == 0) mbar_arrive(bar_h2);
      TL_MARK2(12, lane == 0);
      if (bid >> 6) h0 = h1;
      float v[8], wr[8];
      unpack8(make_uint4(__float_as_uint(h0.x), __float_as_uint(h0.y), __float_as_uint(h0.z), __float_as_uint(h0.w)), v); unpack8(wrv, wr);
      float r = 0.f;
      #pragma unroll
      for (int i = 0; i < 8; i++) r = fmaf(v[i], wr[i], r);
      #pragma unroll
      for (int o = 16; o > 0; o >>= 1) r += __shfl_xor_sync(0xffffffffu, r, o);
      if (lane == 0) sts_f32(sbase + OG_SMISC + 192 + wi * 4, r);
    }
    mbar_wait(bar_out, 0);
    {
      const uint2 cg = lds_u32x2(sbase + OG_SMISC + 96);
      #pragma unroll
      for (int i = 0; i < 4; i++) {
        const int r = (i < 2 ? cg.x : cg.y) * 16 + (i & 1) * 8 + (threadIdx.x >> 4), ch = threadIdx.x & 15;
        if (m0 + r != sel0 && m0 + r != sel1)
          *reinterpret_cast<uint4*>(out + (size_t)(m0 + r) * T_D + n0 + ch * 8) =
              lds_u32x4(sbase + OG_OSLOT + (ch >> 3) * 16384 + r * 128 + (((ch & 7) ^ (r & 7)) << 4));
      }
    }
    if (bid == 0 && threadIdx.x < 68) *reinterpret_cast<uint4*>(g_hcnt + 32 * (threadIdx.x >> 2) + 4 * (threadIdx.x & 3)) = make_uint4(0u, 0u, 0u, 0u);
    if (threadIdx.x < 64) g_modpart[bid * 64 + threadIdx.x] = 0.f;
    {
      const int tk = bid >> 6, c0 = (bid & 63) * 16;
      const uint32_t gb2 = *reinterpret_cast<const uint32_t*>(g_col + (c0 >> 7) * 1536 + 512 + 768 + ((c0 & 127) + (threadIdx.x & 14)) * 2);
      const uint32_t* xp = reinterpret_cast<const uint32_t*>(g_cand + (tk ? sel.w : sel.z) * 256) + ((c0 + (threadIdx.x & 14)) >> 1);
      uint32_t x2 = 0u;
      #pragma unroll 1
      for (unsigned int spin = 0; spin < (1u << 20) && __any_sync(0xffffffffu, x2 == 0u); spin++) asm volatile("ld.relaxed.gpu.global.u32 %0, [%1];" : "=r"(x2) : "l"(xp) : "memory");
      const float* src = g_ypart + (size_t)((threadIdx.x >> 2) * 2 + tk) * T_D + c0 + (threadIdx.x & 3) * 4;
      const bool four = threadIdx.x < (OG_MOE - 96) * 4;
      named_bar_sync(10, 128);
      const uint4 rp = lds_u32x4(sbase + OG_SMISC + 192);
      const float rs = rbf(sigmoid_f(rbf((__uint_as_float(rp.x) + __uint_as_float(rp.y)) + (__uint_as_float(rp.z) + __uint_as_float(rp.w)))));
      const uint32_t h2p = lds_u32(sbase + OG_SH2 + tk * 2048 + (c0 + (threadIdx.x & 14)) * 2);
      const float fh = (lane & 1) ? bfhi(h2p) : bflo(h2p), fz = rbf(fh * 0.0f), fx = (lane & 1) ? bfhi(x2) : bflo(x2), fg = (lane & 1) ? bfhi(gb2) : bflo(gb2);
      bf16* dst = out + (size_t)(tk ? sel1 : sel0) * T_D + c0 + threadIdx.x;
      if (threadIdx.x == 0) hint_wait(CNT_Y, (uint32_t)(OG_MOE - Y_SLACK));
      named_bar_sync(10, 128);
      float4 p0, p1, p2, p3;
      #pragma unroll 1
      for (unsigned int spin = 0; spin < (1u << 20); spin++) {
        p0 = ld_tagged4(src); p1 = ld_tagged4(src + 64 * T_D); p2 = ld_tagged4(src + 128 * T_D); p3 = ld_tagged4(four ? src + 192 * T_D : src);
        if (__all_sync(0xffffffffu, tagged4(p0) & tagged4(p1) & tagged4(p2) & tagged4(p3))) break;
      }
      if (four) { p2.x += p3.x; p2.y += p3.y; p2.z += p3.z; p2.w += p3.w; }
      p0.x = (p0.x + p1.x) + p2.x; p0.y = (p0.y + p1.y) + p2.y; p0.z = (p0.z + p1.z) + p2.z; p0.w = (p0.w + p1.w) + p2.w;
      #pragma unroll
      for (int o = 4; o <= 16; o <<= 1) {
        p0.x += __shfl_xor_sync(0xffffffffu, p0.x, o); p0.y += __shfl_xor_sync(0xffffffffu, p0.y, o);
        p0.z += __shfl_xor_sync(0xffffffffu, p0.z, o); p0.w += __shfl_xor_sync(0xffffffffu, p0.w, o);
      }
      if (lane < 4) sts_f32x4(sbase + OG_SFIN + (threadIdx.x >> 5) * 64 + lane * 16, p0.x, p0.y, p0.z, p0.w);
      named_bar_sync(10, 128);
      TL_MARK2(21, threadIdx.x == 0);
      if (threadIdx.x < 16) {
        const uint32_t ya = sbase + OG_SFIN + threadIdx.x * 4;
        float y = (lds_f32(ya) + lds_f32(ya + 64)) + (lds_f32(ya + 128) + lds_f32(ya + 192));
        y = rbf(y);
        y = rbf(y * rs);
        *dst = __float2bfloat16_rn(fx + rbf(fg * rbf(fh + rbf(fz + y))));
      }
    }
    if (threadIdx.x == 0) XT(11);
    TL_END(4, threadIdx.x == 0);
}

__device__ __forceinline__ void load_pre(uint4* pre, uint32_t sbase, uint32_t buf, int t2) {
  mbar_wait(sbase + AT_SBAR + 272, 0);
  #pragma unroll
  for (int i = 0; i < 8; i++) pre[i] = lds_u32x4(sbase + buf + i * 4096 + t2 * 16);
}
__device__ __forceinline__ void tail_consumer(uint32_t bid, uint32_t sbase, const CUtensorMap* tmOut, const uint4 (&pre)[8], int cwg, const bf16* __restrict__ w_gate, const bf16* __restrict__ w_up) {
    const uint32_t c0 = clock_lo();
    mbar_wait(sbase + AT_SBAR + 320, 0);
    const uint2 td = lds_u32x2(sbase + AT_SBAR + 408);
    const int tb = __shfl_sync(0xffffffffu, (int)td.x, 0);
    TAIL_SETUP
    const int tid = threadIdx.x & 127, t2 = threadIdx.x - 128;
    const int warp = tid >> 5, lane = tid & 31, w8 = t2 >> 5;
    const uint32_t dbase = (sbase & 0x3FFFFu) >> 4;
    const uint32_t a_base = dbase + ((cwg * 8192) >> 4) + (1u << 16);
    const uint32_t b_base = dbase + (16384 >> 4) + (512u << 16);
    TL_MARK2(25, threadIdx.x == 128);
    const uint64_t pol = policy_evict_first();
    const bf16* pw = ((lane & 16) ? w_up : w_gate) + (size_t)(w8 * 128 + (lane & 3) * 4) * T_F + (has_moe ? bid : 0) * 32 + ((lane >> 2) & 3) * 8;
    uint4 wv[32];
    float acc[64];
    #pragma unroll
    for (int i = 0; i < 8; i++) {
      acc[8 * i] = bflo(pre[i].x); acc[8 * i + 1] = bfhi(pre[i].x); acc[8 * i + 2] = bflo(pre[i].y); acc[8 * i + 3] = bfhi(pre[i].y);
      acc[8 * i + 4] = bflo(pre[i].z); acc[8 * i + 5] = bfhi(pre[i].z); acc[8 * i + 6] = bflo(pre[i].w); acc[8 * i + 7] = bfhi(pre[i].w);
    }
    if (lane == 0) mbar_arrive(bar_full + 304);
    while (__any_sync(0xffffffffu, clock_lo() - c0 < td.y)) {}
    uint32_t stage = OG_POS % OG_ST;
    {
      uint32_t phase = (OG_POS / OG_ST) & 1, prev = 12;
      int kb = 0;
      #pragma unroll
      for (int g = 0; g <= OG_NG; g++) {
        const int end = g == OG_NG ? 64 - og_pre(tb) : LD_FIRST + g * OG_GRP + LD_STAG * cwg;
        #pragma unroll 1
        do {
          mbar_wait(bar_full + 8 * stage, phase);
          if (OG_STAG > 0 && g == OG_NG && cwg == 1 && kb == end - OG_STAG) named_bar_sync(7, 256);
          const uint32_t a_lo = a_base + stage * (OG_STAGE >> 4), b_lo = b_base + stage * (OG_STAGE >> 4);
          wgmma_fence();
          wgmma_m64n128k16_ss_tb<0, 0>(acc, a_lo, b_lo, 1);
          wgmma_m64n128k16_ss_tb<2, 128>(acc, a_lo, b_lo, 1);
          wgmma_m64n128k16_ss_tb<4, 256>(acc, a_lo, b_lo, 1);
          wgmma_m64n128k16_ss_tb<6, 384>(acc, a_lo, b_lo, 1);
          wgmma_commit();
          if (OG_STAG > 0 && g == OG_NG && cwg == 0 && kb == end - 1) named_bar_arrive(7, 256);
          wgmma_wait<1>();
          if (tid == 0) mbar_arrive(bar_empty + 8 * prev);
          prev = stage;
          if (++stage == OG_ST) { stage = 0; phase ^= 1; }
        } while (++kb < end);
        #pragma unroll
        for (int j = 4 * g; j < 4 * g + 4 && j < 32; j++) wv[j] = ldg_stream_v4(pw + (size_t)(16 * (j >> 2) + (j & 3)) * T_F, pol);
      }
    }
    mbar_wait(bar_col, 0);
    if (__builtin_expect(!has_moe, 0)) {
      load_pre(wv, sbase, AT_SQ, t2);
    }
    wgmma_wait<0>();
    fence_regs(acc);
    if (__builtin_expect(!has_moe, 0)) {
      #pragma unroll
      for (int i = 0; i < 8; i++) {
        acc[8 * i] += bflo(wv[i].x); acc[8 * i + 1] += bfhi(wv[i].x); acc[8 * i + 2] += bflo(wv[i].y); acc[8 * i + 3] += bfhi(wv[i].y);
        acc[8 * i + 4] += bflo(wv[i].z); acc[8 * i + 5] += bfhi(wv[i].z); acc[8 * i + 6] += bflo(wv[i].w); acc[8 * i + 7] += bfhi(wv[i].w);
      }
    }
    if (tid == 0) mbar_arrive(bar_end);
    TL_MARK2(9, lane == 0);
    const int q2 = 2 * (lane & 3);
    const uint32_t frag = (64 * cwg + 16 * warp + (lane & 7) + 8 * ((lane >> 3) & 1)) * 128;
    const int fsw = lane & 7, fhi = lane >> 4;
    {
      float dl[4] = {0.f, 0.f, 0.f, 0.f}, da[4] = {0.f, 0.f, 0.f, 0.f}, db[4] = {0.f, 0.f, 0.f, 0.f};
      const uint32_t tb2 = sbase + OG_SCOL + (lane & 8) * 32 + (lane & 3) * 8, g = lane >> 2;
      const uint32_t msk = (g == 1 || g == 2) ? 0xffffffffu : 0u, one = g == 0 ? 0x3F803F80u : 0u;
      uint32_t xr[8][4];
      #pragma unroll
      for (int hf = 0; hf < 2; hf++) {
        uint32_t ga[8];
        uint2 cw[4];
        #pragma unroll
        for (int i = 0; i < 4; i++) {
          ldmatrix_x4(sbase + OG_XSLOT + hf * 16384 + frag + (((2 * i + fhi) ^ fsw) << 4), xr[4 * hf + i][0], xr[4 * hf + i][1], xr[4 * hf + i][2], xr[4 * hf + i][3]);
          ga[2 * i] = lds_u32(sbase + OG_SCOL + 512 + (64 * hf + 16 * i + q2) * 2); ga[2 * i + 1] = lds_u32(sbase + OG_SCOL + 512 + (64 * hf + 16 * i + 8 + q2) * 2);
          cw[i] = lds_u32x2(tb2 + (8 * hf + 2 * i) * 16);
        }
        #pragma unroll
        for (int i = 0; i < 4; i++) {
          uint32_t* x4 = xr[4 * hf + i];
          #pragma unroll
          for (int e = 0; e < 4; e++) x4[e] = badd2(x4[e], bmul2(ga[2 * i + (e >> 1)], pack_bf16(acc[32 * hf + 8 * i + 2 * e], acc[32 * hf + 8 * i + 2 * e + 1])));
          mma_bf16(dl, x4[0], x4[1], x4[2], x4[3], (cw[i].x & msk) | one, (cw[i].y & msk) | one);
          mma_bf16(da, x4[0], x4[1], x4[2], x4[3], x4[0], x4[2]);
          mma_bf16(db, x4[0], x4[1], x4[2], x4[3], x4[1], x4[3]);
        }
      }
      {
        const int dsrc = (lane & ~3) + (g >> 1);
        const float qa = __shfl_sync(0xffffffffu, (g & 1) ? da[1] : da[0], dsrc), qb = __shfl_sync(0xffffffffu, (g & 1) ? db[3] : db[2], dsrc);
        const float e0 = __shfl_xor_sync(0xffffffffu, (lane & 1) ? dl[0] : dl[2], 1), e1 = __shfl_xor_sync(0xffffffffu, dl[3], 1);
        if ((lane & 3) < 2) {
          const bool hi = lane & 1;
          st_tagged4(reinterpret_cast<float*>(g_part1 + ((mt * 8 + w8) * 8 + nt) * 16 + g + (hi ? 8 : 0)),
                     hi ? e0 : dl[0], hi ? qb : qa, hi ? e1 + dl[2] : dl[1] + e0, 1.0f);
        }
      }
      #pragma unroll
      for (int i = 0; i < 8; i++) stmatrix_x4(sbase + OG_XSLOT + (i >> 2) * 16384 + frag + (((2 * (i & 3) + fhi) ^ fsw) << 4), xr[i][0], xr[i][1], xr[i][2], xr[i][3]);
    }
    TL_MARK2(10, lane == 0);
    uint4 wd[16];
    if (has_moe) mbar_wait(bar_wd, 0);
    #pragma unroll
    for (int i = 0; i < 16; i++) wd[i] = lds_u32x4(sbase + (cwg ? (stage + (stage & 1)) * OG_STAGE : OG_SWD) + warp * 8192 + (i >> 3) * 4096 + (i & 6) * 512 + (i & 1) * 128 + (lane & 3) * 256 + (((lane >> 2) ^ (2 * (lane & 3) + (i & 1))) << 4));
    {
      const float* src = reinterpret_cast<const float*>(g_part1 + ((mt * 8 + w8) * 8 + (lane & 1) * 4) * 16 + (lane >> 1));
      float4 v, v1, v2, v3;
      #pragma unroll 1
      for (unsigned int spin = 0; spin < (1u << 22); spin++) {
        v = ld_tagged4(src); v1 = ld_tagged4(src + 64); v2 = ld_tagged4(src + 128); v3 = ld_tagged4(src + 192);
        if (__all_sync(0xffffffffu, tagged4(v) & tagged4(v1) & tagged4(v2) & tagged4(v3))) break;
        __nanosleep(100);
      }
      __syncwarp();
      TL_MARK2(26, lane == 0);
      v.x = (v.x + v1.x) + (v2.x + v3.x); v.y = (v.y + v1.y) + (v2.y + v3.y); v.z = (v.z + v1.z) + (v2.z + v3.z);
      v.x += __shfl_xor_sync(0xffffffffu, v.x, 1); v.y += __shfl_xor_sync(0xffffffffu, v.y, 1); v.z += __shfl_xor_sync(0xffffffffu, v.z, 1);
      const float mean = v.x * (1.0f / T_D);
      const float var = fmaxf(fmaf(-mean, mean, v.y * (1.0f / T_D)), 0.f);
      const uint32_t mb2 = pack_bf16(mean, mean);
      const float inv = rcp_approx(rbf(sqrt_approx(rbf(rbf(var) + 1e-05f))));
      {
        const float2 sc = lds_f32x2(sbase + OG_SMISC);
        const uint32_t key = rank_key(rbf(fmaf(fmaf(-bflo(mb2), sc.x, v.z), inv, sc.y)), m0 + 16 * w8 + (lane >> 1));
        mbar_wait(bar_end, 0);
        if (lane & 1) sts_u32(sbase + OG_SSTAT + 1024 + (16 * w8 + (lane >> 1)) * 4, key);
        else sts_u32x2(sbase + OG_SSTAT + (16 * w8 + (lane >> 1)) * 8, mb2, __float_as_uint(inv));
        __syncwarp();
        if (lane == 0) mbar_arrive(bar_key);
      }
      const uint32_t ih = pack_bf16(inv, inv), il = pack_bf16(inv - bflo(ih), inv - bflo(ih));
      const uint32_t mba = __shfl_sync(0xffffffffu, mb2, 2 * (lane >> 2)), mbb = __shfl_sync(0xffffffffu, mb2, 2 * (lane >> 2) + 16);
      const uint32_t iha = __shfl_sync(0xffffffffu, ih, 2 * (lane >> 2)), ihb = __shfl_sync(0xffffffffu, ih, 2 * (lane >> 2) + 16);
      const uint32_t ila = __shfl_sync(0xffffffffu, il, 2 * (lane >> 2)), ilb = __shfl_sync(0xffffffffu, il, 2 * (lane >> 2) + 16);
      #pragma unroll 1
      for (int J0 = 0; J0 < 16; J0 += 4) {
        uint32_t xr[2][4], cv[4][3];
        #pragma unroll
        for (int i = 0; i < 2; i++) {
          ldmatrix_x4(sbase + OG_XSLOT + (J0 >> 3) * 16384 + frag + ((((J0 & 7) + 2 * i + fhi) ^ fsw) << 4), xr[i][0], xr[i][1], xr[i][2], xr[i][3]);
          #pragma unroll
          for (int h = 0; h < 2; h++)
            #pragma unroll
            for (int k = 0; k < 3; k++) cv[2 * i + h][k] = lds_u32(sbase + OG_SCOL + 768 + 256 * k + (8 * (J0 + 2 * i + h) + q2) * 2);
        }
        #pragma unroll
        for (int i = 0; i < 2; i++) {
          #pragma unroll
          for (int h = 0; h < 2; h++) {
            xr[i][2 * h] = out2(xr[i][2 * h], mba, iha, ila, cv[2 * i + h][0], cv[2 * i + h][1], cv[2 * i + h][2]);
            xr[i][2 * h + 1] = out2(xr[i][2 * h + 1], mbb, ihb, ilb, cv[2 * i + h][0], cv[2 * i + h][1], cv[2 * i + h][2]);
          }
          stmatrix_x4(sbase + OG_OSLOT + (J0 >> 3) * 16384 + frag + ((((J0 & 7) + 2 * i + fhi) ^ fsw) << 4), xr[i][0], xr[i][1], xr[i][2], xr[i][3]);
        }
      }
      fence_proxy_async();
      mbar_wait(bar_full + 352, 0);
      const uint2 cg = lds_u32x2(sbase + OG_SMISC + 96);
      __syncwarp();
      if (elect_one()) {
        mbar_arrive(bar_out);
        if (cg.x != w8 && cg.y != w8) {
          asm volatile("cp.async.bulk.tensor.2d.global.shared::cta.bulk_group [%0, {%2, %3}], [%1];" :: "l"(tmOut), "r"(sbase + OG_OSLOT + w8 * 2048), "r"(n0), "r"(m0 + 16 * w8) : "memory");
          asm volatile("cp.async.bulk.tensor.2d.global.shared::cta.bulk_group [%0, {%2, %3}], [%1];" :: "l"(tmOut), "r"(sbase + OG_OSLOT + 16384 + w8 * 2048), "r"(n0 + 64), "r"(m0 + 16 * w8) : "memory");
          bulk_commit();
        }
      }
      TL_MARK2(24, lane == 0);
    }
    if (has_moe) mbar_wait(bar_h2, 0);
    TL_MARK2(13, lane == 0);
    if (has_moe) {
      const GemvSel sel = gemv_sel(lane);
      {
        float d[4][4];
        #pragma unroll
        for (int c = 0; c < 4; c++) { d[c][0] = 0.f; d[c][1] = 0.f; d[c][2] = 0.f; d[c][3] = 0.f; }
        #pragma unroll
        for (int st = 0; st < 8; st++) {
          const uint2 hb = lds_u32x2(sbase + OG_SH2 + ((lane >> 2) & 1) * 2048 + (w8 * 128 + st * 16 + (lane & 3) * 4) * 2);
          #pragma unroll
          for (int j = 0; j < 4; j++) mma_bf16(d[j], wv[4 * st + j].x, wv[4 * st + j].y, wv[4 * st + j].z, wv[4 * st + j].w, GEMV_B0(j, hb, sel), GEMV_B1(j, hb, sel));
        }
        #pragma unroll
        for (int e = 0; e < 4; e++) d[0][e] = (d[0][e] + d[1][e]) + (d[2][e] + d[3][e]);
        const float4 r = gemv_out(d[0], lane);
        sts_f32x4(sbase + OG_SRED + w8 * 512 + (((lane >> 4) * 2 + (lane & 1)) * 32 + ((lane >> 2) & 3) * 8 + (lane & 2) * 2) * 4, r.x, r.y, r.z, r.w);
      }
      named_bar_sync(9, 256);
      if (t2 < 64) {
        float gp[8], up[8];
        #pragma unroll
        for (int w = 0; w < 8; w++) { gp[w] = lds_f32(sbase + OG_SRED + w * 512 + t2 * 4); up[w] = lds_f32(sbase + OG_SRED + w * 512 + 256 + t2 * 4); }
        const float gs = ((gp[0] + gp[1]) + (gp[2] + gp[3])) + ((gp[4] + gp[5]) + (gp[6] + gp[7]));
        const float us = ((up[0] + up[1]) + (up[2] + up[3])) + ((up[4] + up[5]) + (up[6] + up[7]));
        asm volatile("st.shared.u16 [%0], %1;" :: "r"(sbase + OG_SGU + ((t2 & ~15) + ((t2 >> 1) & 3) * 4 + ((t2 >> 3) & 1) * 2 + (t2 & 1)) * 2), "h"((uint16_t)pack_bf16(silu_bf(rbf(gs)) * rbf(us), 0.f)) : "memory");
      }
      named_bar_sync(9, 256);
      TL_MARK2(20, threadIdx.x == 128);
      float d[4][4];
      #pragma unroll
      for (int c = 0; c < 4; c++) { d[c][0] = 0.f; d[c][1] = 0.f; d[c][2] = 0.f; d[c][3] = 0.f; }
      #pragma unroll
      for (int st = 0; st < 2; st++) {
        const uint2 g = lds_u32x2(sbase + OG_SGU + ((lane >> 2) & 1) * 64 + st * 32 + (lane & 3) * 8);
        #pragma unroll
        for (int j = 0; j < 4; j++) {
          const uint32_t b0 = GEMV_B0(j, g, sel), b1 = GEMV_B1(j, g, sel);
          mma_bf16(d[j & 1], wd[4 * st + j].x, wd[4 * st + j].y, wd[4 * st + j].z, wd[4 * st + j].w, b0, b1);
          mma_bf16(d[2 + (j & 1)], wd[8 + 4 * st + j].x, wd[8 + 4 * st + j].y, wd[8 + 4 * st + j].z, wd[8 + 4 * st + j].w, b0, b1);
        }
      }
      #pragma unroll
      for (int e = 0; e < 4; e++) { d[0][e] += d[1][e]; d[2][e] += d[3][e]; }
      const float4 y0 = gemv_out(d[0], lane), y1 = gemv_out(d[2], lane);
      float* yp = g_ypart + (size_t)(bid * 2 + (lane & 1)) * T_D + w8 * 128 + (lane >> 2) * 8 + (lane & 2) * 2;
      st_tagged4(yp, y0.x, y0.y, y0.z, y0.w);
      st_tagged4(yp + 64, y1.x, y1.y, y1.z, y1.w);
      named_bar_sync(9, 256);
      if (t2 == 0) hint_arrive(CNT_Y);
    }
    bulk_wait_read<0>();
    TL_MARK2(14, threadIdx.x == 128);
    TL_CLK(4, 1, threadIdx.x == 128);
}

__device__ __forceinline__ int help_njobs(uint32_t bid) { return bid < 128 ? OG_JOBS : 16 - OG_JOBS; }
__device__ __forceinline__ int help_job(uint32_t bid, int i) { return (i < OG_JOBS ? 16 * i + (bid >> 7) * 2 : 112 + (i - OG_JOBS) * 2) + (bid & 3) * 4; }
__device__ __noinline__ void store_warp(uint32_t bid, uint32_t sbase, const CUtensorMap* tmO, int item0, int n_items) {
  if (elect_one()) {
    const uint32_t bars = sbase + AT_SBAR, b_q0 = bars + 80, b_ob = bars + 96, b_ordy = bars + 104, b_acq = bars + 264;
    const unsigned int* cnt = g_hcnt + 32 * (1 + OG_MT(124)) + 2;
    #pragma unroll 1
    for (int q = 0; q < 4 * n_items; q++) {
      const int item = item0 + (q >> 2) * 128, h = (q >> 1) & 1, w = q & 1;
      const bool last = (q >> 2) == n_items - 1;
      if (q == 4 * n_items - 4) { mbar_wait(bars + 288, 0); red_release_add(&g_hcnt[1], 1u); }
      mbar_wait(b_ordy + 8 * (q & 3), q >> 2);
      store_o(tmO, (h ? (last ? sbase + AT_SQ + 32768 : sbase + 2 * 32768) : sbase + AT_SQ) + w * 8192, (item >> 4) * 2 + h, (item & 15) * 128 + w * 64);
      if (w) {
        bulk_wait_read<0>();
        mbar_arrive(h ? b_ob : b_q0);
        bulk_wait<0>();
        fence_proxy_async_global();
        asm volatile("fence.acq_rel.gpu;" ::: "memory");
        hint_arrive(&g_hcnt[32 * (1 + (item & 15)) + 2 + (item >> 7)]);
        if (!h && item < 128) hint_arrive(&g_hcnt[2]);
        if (q == 5) { const int tb = tail_tile(sbase); cnt = g_hcnt + 32 * (1 + OG_MT(tb)) + 2; spin_until(cnt, 16u); mbar_arrive(b_acq); }
      }
    }
    if (n_items == 1) {
      #pragma unroll 1
      for (int i = 0; i < help_njobs(bid); i++) {
        mbar_wait(b_acq + 16, i & 1);
        TL_MARK2(23, i == OG_JOBS - 1);
        red_release_add(&g_hcnt[32 * (1 + (help_job(bid, i) >> 3)) + 4 + ((help_job(bid, i) >> 1) & 3)], 1u);
        TL_MARK2(4, i == OG_JOBS - 1);
        if (i == PRE_X - 1) { spin_until(&g_hcnt[1], 132u); mbar_arrive(b_acq + 32); }
      }
    }
    if (bid < 128) {
      if (n_items == 1) { spin_until(cnt, 16u); mbar_arrive(b_acq); }
      spin_until(&g_hcnt[0], 128u); spin_until(cnt + 1, 16u); mbar_arrive(b_acq + 80);
    }
  }
}

struct Roles { uint8_t of_sm[132]; };
__global__ void __launch_bounds__(384, 1)
fused_kernel(const __grid_constant__ CUtensorMap tmH, const __grid_constant__ CUtensorMap tmW, const __grid_constant__ CUtensorMap tmK,
            const __grid_constant__ CUtensorMap tmV, const __grid_constant__ CUtensorMap tmO, const __grid_constant__ CUtensorMap tmOl, const __grid_constant__ CUtensorMap tmWo,
            const __grid_constant__ CUtensorMap tmD, const __grid_constant__ CUtensorMap tmOut, const __grid_constant__ CUtensorMap tmM, const __grid_constant__ Roles roles, uint32_t zero,
            const uint8_t* __restrict__ pf_wo, const bf16* __restrict__ kc, const bf16* __restrict__ vc,
            const bf16* __restrict__ x, const bf16* __restrict__ cvec, const bf16* __restrict__ w_mod, const bf16* __restrict__ w_r,
            const bf16* __restrict__ w_gate, const bf16* __restrict__ w_up, const bf16* __restrict__ w_down, bf16* __restrict__ out)
{
  uint32_t bid, nsm;
  asm volatile("mov.u32 %0, %%smid;" : "=r"(bid));
  asm volatile("mov.u32 %0, %%nsmid;" : "=r"(nsm));
  bid = __shfl_sync(0xffffffffu, nsm == 132u ? (uint32_t)roles.of_sm[bid] : blockIdx.x, 0);
  extern __shared__ __align__(1024) uint8_t smem_raw[];
  const uint32_t sbase = smem_u32(smem_raw);
  const uint32_t bars = sbase + AT_SBAR;
  const uint32_t b_full = bars, b_empty = bars + 40;
  const uint32_t b_q0 = bars + 80, b_q1 = bars + 88;
  const uint32_t b_ob = bars + 96;
  const uint32_t b_ordy = bars + 104;
  const uint32_t b_pin = bars + 136;
  const uint32_t b_head = bars + 144;
  const uint32_t b_go = bars + 152;
  const uint32_t b_x = bars + 160;
  const int wg = __shfl_sync(0xffffffffu, threadIdx.x >> 7, 0);
  const bool single = bid >= AT_NFULL;
  const int item0 = __shfl_sync(0xffffffffu, bid < 128 ? (int)bid : (int)bid + 124, 0), n_items = __shfl_sync(0xffffffffu, single ? 1 : 2, 0);
  TL_START(3);
  if (threadIdx.x == 0) {
    if (sbase & 1023u) __trap();
    for (int i = 0; i < 5; i++) { mbar_init(b_full + 8 * i, 1); mbar_init(b_empty + 8 * i, 2); }
    mbar_init(b_q0, 1); mbar_init(b_q1, 8); mbar_init(b_ob, 1);
    for (int i = 0; i < 4; i++) mbar_init(b_ordy + 8 * i, 4);
    mbar_init(b_pin, 1); mbar_init(b_head, bid < 128 ? 8 : 1); mbar_init(b_go, 1); mbar_init(b_x, 1);
    mbar_init(bars + 168, 2); mbar_init(bars + 176, 1); mbar_init(bars + 184, 8); mbar_init(bars + 192, 2);
    mbar_init(bars + 200, 8); mbar_init(bars + 208, 4); mbar_init(bars + 216, 1); mbar_init(bars + 264, 1); mbar_init(bars + 272, 1); mbar_init(bars + 280, 8); mbar_init(bars + 288, 1); mbar_init(bars + 296, 1); mbar_init(bars + 304, 8); mbar_init(bars + 312, 1); mbar_init(bars + 320, 1); mbar_init(bars + 328, 1); mbar_init(bars + 336, 1); mbar_init(bars + 344, 1); mbar_init(bars + 352, 1);
    sts_u32(bars + 400, bid);
    fence_mbar_init();
  }

  if (wg == 0) {
    reg_dealloc<AT_PREG>();
    if (threadIdx.x < 32) { __syncwarp(); named_bar_arrive(6, 384); }
    if (threadIdx.x >= 64) {
      named_bar_sync(6, 384);
      if (bid < 128) {
        named_bar_sync(threadIdx.x >= 96 ? 8 : 9, 288);
        if ((threadIdx.x & 31) == 0) red_release_add(&g_hcnt[32 * (1 + (bid >> 3)) + (threadIdx.x >= 96)], 1u);
        TL_MARK2(11, threadIdx.x == 64);
      }
      if (bid < 128) {
        mbar_wait(MOD_AT, 0);
        mod_rest(bid, sbase + OG_SCOL, b_q1, threadIdx.x - 64, cvec, w_mod, w_r);
      }
    } else if (threadIdx.x >= 32) {
      named_bar_sync(6, 384);
      store_warp(bid, sbase, &tmO, item0, n_items);
      __syncwarp();
    } else {
     if (elect_one()) {
      const uint64_t pol = policy_evict_first();
      if (bid < 128) {
        mbar_expect_tx(b_x, 32768);
        if (X_DLY) { const uint32_t c0 = clock_lo(); while (clock_lo() - c0 < X_DLY) {} }
        bulk_load_hint(sbase + 4 * 32768, x + (size_t)bid * 16 * T_D, 32768, b_x, pol);
      }
      prefetch_tmap(&tmW); prefetch_tmap(&tmM); prefetch_tmap(&tmH); prefetch_tmap(&tmWo); prefetch_tmap(&tmOl);
      {
        const uint32_t c0 = clock_lo();
        while (clock_lo() - c0 < W_DLY) {}
        if (bid < 128 && (bid & 15) >= 4 * H_SPLIT) {
          mbar_expect_tx(bars + 328, 32768);
          tma_load_2d_hint(sbase + 3 * 32768, &tmM, (bid & 31) * 64, (bid >> 5) * 256, bars + 328, pol);
        }
        while (clock_lo() - c0 < W_DLY + W_FIRST) {}
      }
      uint32_t slot = 0, ph = 1;
      #pragma unroll 1
      for (int it = 0; it < n_items; it++) {
        const int item = item0 + it * 128, hp = item >> 4, qt = item & 15;
        const bool first = it == 0;
        #pragma unroll 1
        for (int j = 0; j < T_D / 64; j++) {
          const uint32_t sl = ring_slot(qp_pos(j, it)), fb = b_full + 8 * sl;
          mbar_wait(b_empty + 8 * sl, ring_par(qp_pos(j, it)) ^ ((j >> 2) & 1) ^ 1);
          if (first && j == 3) mbar_wait(b_head, 0);
          mbar_expect_tx(fb, 49152);
          tma_load_3d_hint(sbase + sl * 32768, &tmW, j * 64, hp * 4, fb, pol);
          if (first && j < PRE_B) {
            if (j == PRE_B - 1) {
              spin_until(&g_hcnt[32 * (1 + qt)], 8u);
              TL_MARK2(16, true);
              fence_proxy_async_global();
              #pragma unroll 1
              for (int i = 0; i < PRE_B; i++) tma_load_2d(sbase + AT_SQ + i * 16384, &tmH, i * 64, qt * 128, b_full + 8 * i);
              mbar_arrive(b_go);
            }
          } else {
            if (first && j == 4 * H_SPLIT) { spin_until(&g_hcnt[32 * (1 + qt) + 1], 8u); fence_proxy_async_global(); }
            if (!first && (j == 0 || j == 2)) mbar_wait(j ? b_q1 : b_q0, 0);
            tma_load_2d_hint(sbase + AT_SQ + (j & 3) * 16384, &tmH, j * 64, qt * 128, fb, first ? pol_normal() : pol);
          }
        }
        #pragma unroll 1
        for (int j = 0; j < 4 * AT_NBLK; j++) {
          const bool isv = (j > 0 && !(j & 1)) || j == 4 * AT_NBLK - 1;
          const int row = hp * 2 * T_SEQ + (isv ? (j - 1) >> 1 : (j + 1) >> 1) * 128;
          const uint32_t fb = b_full + 8 * slot;
          mbar_wait(b_empty + 8 * slot, ph);
          if (!first && j == 3) mbar_wait(b_ob, 0);
          if (j == 4 && it == n_items - 1) mbar_arrive(bars + 288);
          if ((j == AL_P || j == RK_P) && it == 1) mbar_arrive(bars + 312);
          mbar_expect_tx(fb, 32768);
          tma_load_3d_hint(sbase + slot * 32768, isv ? &tmV : &tmK, row, 0, fb, pol);
          if (it == 1 && isv && j >= 2 * WO_LATE && j < 2 * WO_LATE + 32 && bid < OG_NKB)
            l2_prefetch_bulk(pf_wo + (size_t)own_kb(bid, og_pre(0)) * 131072 + ((j >> 1) - WO_LATE) * 8192, 8192);
          if (++slot == 5) { slot = 0; ph ^= 1; }
        }
      }
      if (__builtin_expect(single, 0)) {
        spin_until(&g_hcnt[2], 128u);
        fence_proxy_async_global();
        const int nj = OG_HSUM + (help_njobs(bid) - OG_JOBS) * OG_PRE2;
        int ji = 0, job = help_job(bid, 0), kk = 0;
        #pragma unroll 1
        for (int j = 0; j < nj; j++) {
          const uint32_t sl = ring_slot(qp_pos(j, 1)), fb = b_full + 8 * sl;
          mbar_wait(b_empty + 8 * sl, ring_par(qp_pos(j, 1)) ^ ((j >> 2) & 1) ^ 1);
          mbar_expect_tx(fb, 49152);
          tma_load_3d_hint(sbase + sl * 32768, &tmWo, pre_kb(kk) * 64, OG_NT(job) * 2, fb, pol_normal());
          tma_load_3d_hint(sbase + sl * 32768 + 16384, &tmWo, pre_kb(kk) * 64, OG_NT(job) * 2 + 2, fb, pol_normal());
          if (j == 0 || j == 2) mbar_wait(j ? b_ob : b_q0, 0);
          tma_load_2d_hint(sbase + AT_SQ + (j & 3) * 16384, &tmOl, pre_kb(kk) * 64, OG_MT(job) * 128, fb, pol);
          if (++kk == og_pre(job)) { kk = 0; job = help_job(bid, ++ji); }
        }
      }
      if (bid < 128) {
        if (single) mbar_wait(b_x, 1);
        tail_producer(bid, sbase, 0, pol, &tmOl, &tmWo, &tmD);
      }
     }
    }
    named_bar_sync(12 + (threadIdx.x >> 5), 32);
    if (bid < 128) tail_exchange(bid, sbase, w_down, w_r, x, out);
  } else {
    if (bid < 128) head_phase(bid, sbase + AT_SQ + 49152, sbase + 4 * 32768, b_x, b_go, b_head, threadIdx.x - 128, zero, cvec, w_mod);
    else { named_bar_sync(6, 384); if (threadIdx.x == 128) mbar_arrive(b_head); }
    TL_MARK2(0, threadIdx.x == 128);
    reg_alloc<AT_CREG>();
    const int cwg = wg - 1;
    const int tid = threadIdx.x & 127;
    const int warp = tid >> 5, lane = tid & 31;
    const uint32_t dbase = (sbase & 0x3FFFFu) >> 4;
    const uint32_t k_base = dbase + (1u << 16);
    const uint32_t v_base = dbase + (1024u << 16);
    const uint32_t w_base = dbase + (512u << 16);
    const uint32_t q_lo = dbase + ((AT_SQ + cwg * 8192) >> 4) + (1u << 16);
    const uint32_t frag = cwg * 8192 + (16 * warp + (lane & 7) + 8 * ((lane >> 3) & 1)) * 128;
    if (cwg == 1) named_bar_arrive(1, 256);
    bool raw = false;
    uint4 pre[8];
    #pragma unroll 1
    for (int it = 0; it < n_items; it++) {
      const bool more = it + 1 < n_items;
      constexpr int nkb = T_D / 64;
      const int ta = __shfl_sync(0xffffffffu, 4 * it, 0);
      float acc[128];
      {
        FS(2 * it, 0);
        #pragma unroll
        for (int i = 0; i < 128; i++) asm volatile("" : "=f"(acc[i]));
        {
          const uint32_t slot = ring_slot(ta), b_lo = w_base + slot * 2048;
          mbar_wait(b_full + 8 * slot, ring_par(ta));
          wgmma_fence();
          wgmma_m64n256k16_ss_tb<0, 0>(acc, q_lo, b_lo, 0);
          wgmma_m64n256k16_ss_tb<2, 128>(acc, q_lo, b_lo, 1);
          wgmma_m64n256k16_ss_tb<4, 256>(acc, q_lo, b_lo, 1);
          wgmma_m64n256k16_ss_tb<6, 384>(acc, q_lo, b_lo, 1);
          wgmma_commit();
        }
        #pragma unroll 1
        for (int j = 1; j < nkb; j++) {
          const uint32_t slot = ring_slot(qp_pos(j, ta >> 2));
          mbar_wait(b_full + 8 * slot, ring_par(qp_pos(j, ta >> 2)) ^ ((j >> 2) & 1));
          if (QP_STAG > 0 && cwg == 1 && j == nkb - QP_STAG) named_bar_sync(7, 256);
          const uint32_t a_lo = q_lo + (j & 3) * 1024, b_lo = w_base + slot * 2048;
          wgmma_fence();
          wgmma_m64n256k16_ss_tb<0, 0>(acc, a_lo, b_lo, 1);
          wgmma_m64n256k16_ss_tb<2, 128>(acc, a_lo, b_lo, 1);
          wgmma_m64n256k16_ss_tb<4, 256>(acc, a_lo, b_lo, 1);
          wgmma_m64n256k16_ss_tb<6, 384>(acc, a_lo, b_lo, 1);
          wgmma_commit();
          if (QP_STAG > 0 && cwg == 0 && j == nkb - 1) named_bar_arrive(7, 256);
          if (j > 0) {
            wgmma_wait<1>();
            if (tid == 0) mbar_arrive(b_empty + 8 * ring_slot(qp_pos(j - 1, ta >> 2)));
          }
        }
        wgmma_wait<0>();
        fence_regs(acc);
        FS(2 * it, 1);
        TL_MARK2(29, threadIdx.x == 256 && it == 0);
        if (tid == 0) mbar_arrive(b_empty + 24);
      }
      float o[64], s[64];
      uint32_t p[32], q[32];
      #pragma unroll
      for (int i = 0; i < 32; i++) q[i] = pack_bf16(acc[2 * i] * AT_C, acc[2 * i + 1] * AT_C);
      zero_regs(s);
      const uint32_t sq = sbase + AT_SQ + cwg * 8192;
      float mc0, mc1, al0 = 1.0f, al1 = 1.0f, l0 = 0.f, l1 = 0.f, lp0 = 0.f, lp1 = 0.f;
      bool redo0 = false;
      FS(2 * it, 2);
      mbar_wait(b_full + 8 * ring_slot(ta), ring_par(ta));
      named_bar_sync(1 + cwg, 256);
      FS(2 * it, 3);
      issue_qk(s, q, k_base + ring_slot(ta) * 2048);
      pass_turn(cwg);
      bool ready = mbar_test(b_full + 8 * ring_slot(ta + 1), ring_par(ta + 1)) & mbar_test(b_full + 8 * ring_slot(ta + 2), ring_par(ta + 2));
      stage_q<16>(acc, AT_C, sbase + AT_SQ + frag, lane);
      wgmma_wait<0>();
      fence_regs(s);
      if (tid == 0) mbar_arrive(b_empty + 8 * ring_slot(ta));
      mc0 = 0.f; mc1 = 0.f;
      if (!raw) {
        raw = softmax_mode(s, mc0, mc1);
        if (__builtin_expect(!raw, 0)) softmax_sub(s, mc0, mc1);
      }
      softmax_exp<0, 64>(s);
      #pragma unroll
      for (int J = 0; J < 16; J += 2)
        stmatrix_x4(sbase + AT_SQ + frag + (J >> 3) * 16384 + ((((J & 7) + (lane >> 4)) ^ (lane & 7)) << 4), q[2 * J], q[2 * J + 1], q[2 * J + 2], q[2 * J + 3]);
      pack_p(p, s);
      zero_regs(o);
      FS(2 * it, 4);
      uint32_t ks = ring_slot(ta + 1), vs = ring_slot(ta + 2), kp = ring_par(ta + 1), vp = ring_par(ta + 2);
      auto finish_head = [&]() {
        FS(2 * it, 5);
        redo0 = finish_l(lp0, lp1);
        if (!redo0) stage_o(o, lp0, lp1, sbase + AT_SQ + frag, lane);
        FS(2 * it + 1, 4);
      };
      if (!ready) { mbar_wait(b_full + 8 * ks, kp); mbar_wait(b_full + 8 * vs, vp); }
      #pragma unroll 1
      for (int n = 1; n < 2 * AT_NBLK; n++) {
        named_bar_sync(1 + cwg, 256);
        issue_qk(s, q, k_base + ks * 2048);
        if (n == AT_NBLK + 1) finish_head();
        issue_pv(o, p, v_base + vs * 2048, (n & 15) != 1);
        pass_turn(cwg);
        wgmma_wait<1>();
        fence_regs(s);
        if (tid == 0) mbar_arrive(b_empty + 8 * ks);
        if (__builtin_expect(!raw || (uint32_t)(n - (AT_NBLK - 1)) <= 2u, 0)) {
          if (n == AT_NBLK + 1 && !redo0) {
            fence_proxy_async();
            __syncwarp();
            if (lane == 0) mbar_arrive(b_ordy + 8 * cwg);
          }
          if (n == AT_NBLK - 1) {
            #pragma unroll
            for (int J = 0; J < 16; J += 2)
              ldmatrix_x4(sbase + AT_SQ + 32768 + frag + (J >> 3) * 16384 + ((((J & 7) + (lane >> 4)) ^ (lane & 7)) << 4), q[2 * J], q[2 * J + 1], q[2 * J + 2], q[2 * J + 3]);
          }
          if (!raw) {
            const float m0 = mc0, m1 = mc1;
            const bool ok = softmax_mode(s, mc0, mc1);
            if (n == AT_NBLK) raw = ok;
            else {
              mc0 = mc0 - AT_HEAD > m0 ? mc0 : m0; mc1 = mc1 - AT_HEAD > m1 ? mc1 : m1;
              al0 = ex2_approx(m0 - mc0); al1 = ex2_approx(m1 - mc1);
            }
            if (!raw) softmax_sub(s, mc0, mc1);
          }
        }
        softmax_exp<0, AT_SPLIT>(s);
        add_rowsum(p, l0, l1);
        if (tid == 0) {
          uint32_t dep = zero & __float_as_uint(l0) & __float_as_uint(l1);
          #pragma unroll
          for (int i = AT_SPLIT - AT_PIN - PINB; i < AT_SPLIT - PINB; i += 2) dep &= __float_as_uint(s[i]) & __float_as_uint(s[i + 1]);
          mbar_arrive(b_pin + dep);
        }
        wgmma_wait<0>();
        fence_regs(o);
        if (tid == 0) mbar_arrive(b_empty + 8 * vs);
        ks += 2; if (ks >= 5) { ks -= 5; kp ^= 1; }
        vs += 2; if (vs >= 5) { vs -= 5; vp ^= 1; }
        ready = mbar_test(b_full + 8 * ks, kp) & mbar_test(b_full + 8 * vs, vp);
        softmax_exp<AT_SPLIT, 64>(s);
        pack_p(p, s);
        if (n == AT_NBLK) { lp0 = l0; lp1 = l1; l0 = 0.f; l1 = 0.f; }
        if (__builtin_expect(!raw || !ready, 0)) {
        if (!raw && __any_sync(0xffffffffu, al0 != 1.0f || al1 != 1.0f)) {
          rescale_o(o, al0, al1);
          l0 *= al0; l1 *= al1;
          al0 = 1.0f; al1 = 1.0f;
        }
        if (!ready && n < 2 * AT_NBLK - 1) {
          mbar_wait(b_full + 8 * ks, kp);
          mbar_wait(b_full + 8 * vs, vp);
        }
        }
      }
      FS(2 * it + 1, 5);
      const uint32_t vl = ring_slot(ta + 63);
      vs = ring_slot(ta + 62);
      const uint32_t ob = more ? sbase + vs * 32768 : sbase + AT_SQ + 32768;
      mbar_wait(b_full + 8 * vl, ring_par(ta + 63));
      issue_pv(o, p, v_base + vl * 2048, 1);
      block_end(zero, b_pin);
      add_rowsum(p, l0, l1);
      const bool overflow = finish_l(l0, l1);
      if (!overflow && lane == 0) mbar_arrive(b_q1);
      #pragma unroll
      for (int i = 0; i < 8; i++) asm volatile("mov.b64 {%0, %1}, 0;\nmov.b64 {%2, %3}, 0;" : "=r"(pre[i].x), "=r"(pre[i].y), "=r"(pre[i].z), "=r"(pre[i].w));
      const bool want_pre = !more && bid < OG_MOE, got_pre = want_pre && __all_sync(0xffffffffu, mbar_test(bars + 272, 0));
      if (got_pre) load_pre(pre, sbase, AT_SQ, threadIdx.x - 128);
      mbar_wait(b_empty + 8 * vs, ring_par(ta + 62));
      wgmma_wait<0>();
      fence_regs(o);
      if (tid == 0) mbar_arrive(b_empty + 8 * vl);
      FS(2 * it + 1, 6);
      if (overflow) {
        attn_rows_exact(lds_u32(bars + 400), sq + 32768, ob + cwg * 8192, 4 * ta + 1, kc, vc);
        __syncwarp();
        if (lane == 0) mbar_arrive(b_q1);
      } else stage_o(o, l0, l1, ob + frag, lane);
      if (redo0) attn_rows_exact(lds_u32(bars + 400), sq, sq, 4 * ta, kc, vc);
      fence_proxy_async();
      __syncwarp();
      if (lane == 0) {
        if (redo0) mbar_arrive(b_ordy + 8 * cwg);
        mbar_arrive(b_ordy + 16 + 8 * cwg);
      }
      if (want_pre && !got_pre) load_pre(pre, sbase, AT_SQ, threadIdx.x - 128);
      if (redo0 || overflow) raw = false;
      named_bar_sync(3 + cwg, 128);
      FS(2 * it + 1, 7);
    }
    if (cwg == 0) named_bar_arrive(1, 256);
    if (__builtin_expect(single, 0)) {
      float acc[128];
      uint32_t j = 0, pk[64];
      #pragma unroll
      for (int i = 0; i < 64; i++) asm volatile("" : "=f"(acc[2 * i]), "=f"(acc[2 * i + 1]), "=r"(pk[i]));
      uint4* dst = g_pre;
      int left = 0;
      auto put = [&](bool last) {
        #pragma unroll
        for (int i = 0; i < PUT_N; i++) dst[i * 256] = make_uint4(pk[4 * i], pk[4 * i + 1], pk[4 * i + 2], pk[4 * i + 3]);
        dst += PUT_N * 256;
        #pragma unroll
        for (int i = 0; i < 64 - 4 * PUT_N; i++) asm volatile("mov.b32 %0, %1;" : "=r"(pk[i]) : "r"(pk[i + 4 * PUT_N]));
        __syncwarp();
        if (last && lane == 0) mbar_arrive(bars + 280);
      };
      #pragma unroll 1
      for (int ji = 0; ji < help_njobs(bid); ji++) {
        const int nk = og_pre(help_job(bid, ji));
        #pragma unroll 1
        for (int kk = 0; kk < nk; kk++, j++) {
          const uint32_t slot = ring_slot(qp_pos(j, 1));
          mbar_wait(b_full + 8 * slot, ring_par(qp_pos(j, 1)) ^ ((j >> 2) & 1));
          if (H_STAG > 0 && cwg == 1 && kk == nk - H_STAG) named_bar_sync(7, 256);
          const uint32_t a_lo = q_lo + (j & 3) * 1024, b_lo = w_base + slot * 2048;
          wgmma_fence();
          wgmma_m64n256k16_ss_tb<0, 0>(acc, a_lo, b_lo, kk != 0);
          wgmma_m64n256k16_ss_tb<2, 128>(acc, a_lo, b_lo, 1);
          wgmma_m64n256k16_ss_tb<4, 256>(acc, a_lo, b_lo, 1);
          wgmma_m64n256k16_ss_tb<6, 384>(acc, a_lo, b_lo, 1);
          wgmma_commit();
          if (H_STAG > 0 && cwg == 0 && kk == nk - 1) named_bar_arrive(7, 256);
          wgmma_wait<1>();
          if (kk > 0 && tid == 0) mbar_arrive(b_empty + 8 * ring_slot(qp_pos(j - 1, 1)));
          #pragma unroll 1
          for (int i = ji == OG_JOBS ? 0 : 16 / PUT_N - 1; i < 16 / PUT_N && left > 0; i++) put(--left == 0);
        }
        wgmma_wait<0>();
        fence_regs(acc);
        if (tid == 0) mbar_arrive(b_empty + 8 * ring_slot(qp_pos(j - 1, 1)));
        #pragma unroll
        for (int i = 0; i < 64; i++) pk[i] = pack_bf16(acc[2 * i], acc[2 * i + 1]);
        left = 16 / PUT_N;
        if (ji == PRE_X) mbar_wait(bars + 296, 0);
        dst = g_pre + help_job(bid, ji) * 2048 + threadIdx.x - 128;
      }
      #pragma unroll
      for (int i = 0; i < 16; i++) dst[i * 256] = make_uint4(pk[4 * i], pk[4 * i + 1], pk[4 * i + 2], pk[4 * i + 3]);
      __syncwarp();
      if (lane == 0) mbar_arrive(bars + 280);
      named_bar_sync(5, 256);
      if (threadIdx.x == 128) {
        #pragma unroll 1
        for (int i = 0; i < 5; i++) {
          constexpr int n = OG_HSUM;
          const int used = i == 3 ? 0 : (n + 3 - (i == 4 ? 3 : i)) / 4;
          if ((used ^ (i < 4)) & 1) {
            mbar_arrive(b_full + 8 * ring_slot(4 + i));
            mbar_arrive(b_empty + 8 * ring_slot(4 + i)); mbar_arrive(b_empty + 8 * ring_slot(4 + i));
          }
        }
        mbar_arrive(b_x);
      }
      named_bar_sync(5, 256);
      #pragma unroll
      for (int i = 0; i < 8; i++) pre[i] = make_uint4(0u, 0u, 0u, 0u);
    }
    TL_CLK(3, 1, threadIdx.x == 128);
    TL_CTA(1, threadIdx.x == 256);
    TL_END(3, tid == 0);
    TL_MARK2(19, tid == 0 && !single);
    if (bid < 128) {
      tail_consumer(bid, sbase, &tmOut, pre, cwg, w_gate, w_up);
    }
  }
}

typedef CUresult (*PFN_encodeTiled)(CUtensorMap*, CUtensorMapDataType, cuuint32_t, void*, const cuuint64_t*, const cuuint64_t*,
                                    const cuuint32_t*, const cuuint32_t*, CUtensorMapInterleave, CUtensorMapSwizzle,
                                    CUtensorMapL2promotion, CUtensorMapFloatOOBfill);

CUtensorMap make_map_2d(PFN_encodeTiled enc, const void* ptr, uint64_t inner, uint64_t outer, uint64_t stride_bytes, uint32_t box_inner, uint32_t box_outer) {
  CUtensorMap m;
  cuuint64_t gd[2] = {inner, outer}; cuuint64_t gs[1] = {stride_bytes};
  cuuint32_t bx[2] = {box_inner, box_outer}; cuuint32_t es[2] = {1, 1};
  enc(&m, CU_TENSOR_MAP_DATA_TYPE_BFLOAT16, 2, const_cast<void*>(ptr), gd, gs, bx, es, CU_TENSOR_MAP_INTERLEAVE_NONE,
      CU_TENSOR_MAP_SWIZZLE_128B, CU_TENSOR_MAP_L2_PROMOTION_L2_128B, CU_TENSOR_MAP_FLOAT_OOB_FILL_NONE);
  return m;
}

CUtensorMap make_map_3d(PFN_encodeTiled enc, const void* ptr, uint64_t cols, uint64_t rows, uint32_t box_rows, uint32_t chunks) {
  CUtensorMap m;
  cuuint64_t gd[3] = {64, rows, cols / 64}; cuuint64_t gs[2] = {cols * 2, 128};
  cuuint32_t bx[3] = {64, box_rows, chunks}; cuuint32_t es[3] = {1, 1, 1};
  enc(&m, CU_TENSOR_MAP_DATA_TYPE_BFLOAT16, 3, const_cast<void*>(ptr), gd, gs, bx, es, CU_TENSOR_MAP_INTERLEAVE_NONE,
      CU_TENSOR_MAP_SWIZZLE_128B, CU_TENSOR_MAP_L2_PROMOTION_L2_128B, CU_TENSOR_MAP_FLOAT_OOB_FILL_NONE);
  return m;
}

}

extern "C" void kernel_launch(void* const* d_in, const int* in_sizes, int n_in, void* d_out, int out_size) {
  const bf16* x      = (const bf16*)d_in[0];
  const bf16* kc     = (const bf16*)d_in[1];
  const bf16* vc     = (const bf16*)d_in[2];
  const bf16* wq     = (const bf16*)d_in[3];
  const bf16* wo     = (const bf16*)d_in[4];
  const bf16* w_r    = (const bf16*)d_in[6];
  const bf16* w_gate = (const bf16*)d_in[7];
  const bf16* w_up   = (const bf16*)d_in[8];
  const bf16* w_down = (const bf16*)d_in[9];
  const bf16* cvec   = (const bf16*)d_in[10];
  const bf16* w_mod  = (const bf16*)d_in[11];
  bf16* out = (bf16*)d_out;

  static PFN_encodeTiled enc = nullptr;
  static void *p_h = nullptr, *p_o = nullptr;
  if (!enc) {
    void* fn = nullptr; cudaDriverEntryPointQueryResult qres;
    cudaGetDriverEntryPoint("cuTensorMapEncodeTiled", &fn, cudaEnableDefault, &qres);
    enc = (PFN_encodeTiled)fn;
    cudaGetSymbolAddress(&p_h, g_pre);
    p_h = (uint4*)p_h + 16 * PRE_X * 2048;
    cudaGetSymbolAddress(&p_o, g_o);
    cudaFuncSetAttribute(fused_kernel, cudaFuncAttributeMaxDynamicSharedMemorySize, (int)AT_SMEM);
  }
  const CUtensorMap tm_h   = make_map_2d(enc, p_h, T_D, T_SEQ, T_D * 2, 64, 128);
  const CUtensorMap tm_wq  = make_map_3d(enc, wq, T_DQKV, T_D, 64, 4);
  const CUtensorMap tm_k   = make_map_3d(enc, kc, T_DH, (uint64_t)T_NH * T_SEQ, 128, 2);
  const CUtensorMap tm_v   = make_map_3d(enc, vc, T_DH, (uint64_t)T_NH * T_SEQ, 128, 2);
  const CUtensorMap tm_ost = make_map_2d(enc, p_o, T_DQKV, T_SEQ, T_DQKV * 2, 64, 64);
  const CUtensorMap tm_old = make_map_2d(enc, p_o, T_DQKV, T_SEQ, T_DQKV * 2, 64, 128);
  const CUtensorMap tm_wo  = make_map_3d(enc, wo, T_D, T_DQKV, 64, 2);
  const CUtensorMap tm_d   = make_map_3d(enc, w_down, T_D, T_F, 32, 8);

  const CUtensorMap tm_m   = make_map_2d(enc, w_mod, 6 * T_D, T_D, 6 * T_D * 2, 64, 256);
  const CUtensorMap tm_out = make_map_2d(enc, out, T_D, T_SEQ, T_D * 2, 64, 16);

  Roles roles;
  for (int sm = 0; sm < 132; sm++) {
    const int t = sm >> 1;
    roles.of_sm[sm] = (uint8_t)((t < 32 ? ((t + 7) & 7) * 16 + (t >> 3) * 2 : t < 60 ? ((t - 32) % 7) * 16 + (4 + (t - 32) / 7) * 2 : t < 62 ? 2 * t + 8 : 2 * t - 4) + (sm & 1));
  }
  fused_kernel<<<132, 384, AT_SMEM, cudaStreamPerThread>>>(tm_h, tm_wq, tm_k, tm_v, tm_ost, tm_old, tm_wo, tm_d, tm_out, tm_m, roles, 0u, (const uint8_t*)wo, kc, vc, x, cvec, w_mod,
             w_r, w_gate, w_up, w_down, out);
}
```

```cpp
#include <cuda_runtime.h>
#include <cuda_bf16.h>
#include <cuda.h>
#include <stdint.h>

namespace {

typedef __nv_bfloat16 bf16;

constexpr int T_SEQ = 2048, T_D = 1024, T_NH = 32, T_DH = 128, T_DQKV = 4096, T_F = 3584;

#define PRE_X 2
__device__ __align__(1024) uint4 g_pre[(16 * PRE_X + 128) * 2048];
#define g_h (reinterpret_cast<bf16*>(g_pre + 16 * PRE_X * 2048))
__device__ __align__(1024) bf16 g_o[T_SEQ * T_DQKV];
__device__ __align__(16) uint8_t g_col[8 * 1536];
__device__ __align__(16) float g_scal[64];
__device__ __align__(16) unsigned int g_hcnt[17 * 32];
__device__ __align__(128) float g_modpart[4 * 2 * T_D];
struct __align__(2048) TailMail {
  float4 part1[T_SEQ * 8];
  uint32_t key[256];
  uint4 cand[16 * 2 * 2 * 128];
  uint32_t cnt[32];
  float ypart[(T_F / 32) * 2 * T_D];
};
__device__ TailMail g_mail;
#define g_part1 g_mail.part1
#define g_key g_mail.key
#define g_cand g_mail.cand
#define CNT_Y (g_mail.cnt)
#define g_ypart g_mail.ypart

__device__ __forceinline__ uint32_t smem_u32(const void* p) { return (uint32_t)__cvta_generic_to_shared(p); }
__device__ __forceinline__ void mbar_init(uint32_t bar, uint32_t cnt) { asm volatile("mbarrier.init.shared::cta.b64 [%0], %1;" :: "r"(bar), "r"(cnt)); }
__device__ __forceinline__ void mbar_expect_tx(uint32_t bar, uint32_t bytes) { asm volatile("mbarrier.arrive.expect_tx.shared::cta.b64 _, [%0], %1;" :: "r"(bar), "r"(bytes) : "memory"); }
__device__ __forceinline__ void mbar_arrive(uint32_t bar) { asm volatile("mbarrier.arrive.shared::cta.b64 _, [%0];" :: "r"(bar) : "memory"); }
__device__ __forceinline__ void mbar_wait(uint32_t bar, uint32_t parity) {
  asm volatile("{\n.reg .pred p;\nLAB_WAIT:\nmbarrier.try_wait.parity.shared::cta.b64 p, [%0], %1;\n@!p bra LAB_WAIT;\n}\n" :: "r"(bar), "r"(parity) : "memory");
}
__device__ __forceinline__ bool mbar_test(uint32_t bar, uint32_t parity) {
  uint32_t r; asm volatile("{\n.reg .pred p;\nmbarrier.test_wait.parity.shared::cta.b64 p, [%1], %2;\nselp.u32 %0, 1, 0, p;\n}\n" : "=r"(r) : "r"(bar), "r"(parity) : "memory");
  return r != 0;
}
__device__ __forceinline__ uint32_t clock_lo() { uint32_t c; asm volatile("mov.u32 %0, %%clock;" : "=r"(c)); return c; }
__device__ __forceinline__ void fence_mbar_init() { asm volatile("fence.mbarrier_init.release.cluster;" ::: "memory"); }
__device__ __forceinline__ void tma_load_2d(uint32_t dst, const CUtensorMap* map, int c0, int c1, uint32_t bar) {
  asm volatile("cp.async.bulk.tensor.2d.shared::cluster.global.mbarrier::complete_tx::bytes [%0], [%1, {%3, %4}], [%2];"
    :: "r"(dst), "l"(map), "r"(bar), "r"(c0), "r"(c1) : "memory");
}
__device__ __forceinline__ uint64_t policy_evict_first() {
  uint64_t p; asm volatile("createpolicy.fractional.L2::evict_first.b64 %0, 1.0;" : "=l"(p)); return p;
}
__device__ __forceinline__ void tma_load_2d_hint(uint32_t dst, const CUtensorMap* map, int c0, int c1, uint32_t bar, uint64_t pol) {
  asm volatile("cp.async.bulk.tensor.2d.shared::cluster.global.mbarrier::complete_tx::bytes.L2::cache_hint [%0], [%1, {%3, %4}], [%2], %5;"
    :: "r"(dst), "l"(map), "r"(bar), "r"(c0), "r"(c1), "l"(pol) : "memory");
}
__device__ __forceinline__ void tma_load_3d_hint(uint32_t dst, const CUtensorMap* map, int c1, int c2, uint32_t bar, uint64_t pol) {
  asm volatile("cp.async.bulk.tensor.3d.shared::cluster.global.mbarrier::complete_tx::bytes.L2::cache_hint [%0], [%1, {%3, %4, %5}], [%2], %6;"
    :: "r"(dst), "l"(map), "r"(bar), "n"(0), "r"(c1), "r"(c2), "l"(pol) : "memory");
}
__device__ __forceinline__ void tma_store_2d(const CUtensorMap* map, uint32_t src, int c0, int c1) {
  asm volatile("cp.async.bulk.tensor.2d.global.shared::cta.bulk_group [%0, {%2, %3}], [%1];" :: "l"(map), "r"(src), "r"(c0), "r"(c1) : "memory");
}
__device__ __forceinline__ void prefetch_tmap(const CUtensorMap* map) { asm volatile("prefetch.tensormap [%0];" :: "l"(map) : "memory"); }
__device__ __forceinline__ void l2_prefetch_bulk(const void* p, uint32_t bytes) {
  asm volatile("cp.async.bulk.prefetch.L2.global [%0], %1;" :: "l"(p), "r"(bytes) : "memory");
}
__device__ __forceinline__ void bulk_commit() { asm volatile("cp.async.bulk.commit_group;" ::: "memory"); }
template<int N> __device__ __forceinline__ void bulk_wait_read() { asm volatile("cp.async.bulk.wait_group.read %0;" :: "n"(N) : "memory"); }
template<int N> __device__ __forceinline__ void bulk_wait() { asm volatile("cp.async.bulk.wait_group %0;" :: "n"(N) : "memory"); }
__device__ __forceinline__ void named_bar_sync(int id, int nthreads) { asm volatile("bar.sync %0, %1;" :: "r"(id), "r"(nthreads) : "memory"); }
__device__ __forceinline__ void named_bar_arrive(int id, int nthreads) { asm volatile("bar.arrive %0, %1;" :: "r"(id), "r"(nthreads) : "memory"); }
__device__ __forceinline__ void pass_turn(int cwg) {
  asm volatile("{\n.reg .pred p;\nsetp.ne.u32 p, %0, 0;\n@p bar.arrive 1, 256;\n@!p bar.arrive 2, 256;\n}\n" :: "r"(cwg) : "memory");
}
__device__ __forceinline__ void wgmma_fence() { asm volatile("wgmma.fence.sync.aligned;" ::: "memory"); }
__device__ __forceinline__ void wgmma_commit() { asm volatile("wgmma.commit_group.sync.aligned;" ::: "memory"); }
template<int N> __device__ __forceinline__ void wgmma_wait() { asm volatile("wgmma.wait_group.sync.aligned %0;" :: "n"(N) : "memory"); }
template<int R> __device__ __forceinline__ void reg_alloc() { asm volatile("setmaxnreg.inc.sync.aligned.u32 %0;" :: "n"(R)); }
template<int R> __device__ __forceinline__ void reg_dealloc() { asm volatile("setmaxnreg.dec.sync.aligned.u32 %0;" :: "n"(R)); }
__device__ __forceinline__ bool elect_one() {
  uint32_t pred; asm volatile("{\n.reg .pred p;\nelect.sync _|p, 0xffffffff;\nselp.u32 %0, 1, 0, p;\n}\n" : "=r"(pred)); return pred != 0;
}
__device__ __forceinline__ uint32_t pack_bf16(float lo, float hi) {
  uint32_t r; asm("cvt.rn.bf16x2.f32 %0, %1, %2;" : "=r"(r) : "f"(hi), "f"(lo)); return r;
}
__device__ __forceinline__ void stmatrix_x4(uint32_t addr, uint32_t r0, uint32_t r1, uint32_t r2, uint32_t r3) {
  asm volatile("stmatrix.sync.aligned.m8n8.x4.shared.b16 [%0], {%1, %2, %3, %4};" :: "r"(addr), "r"(r0), "r"(r1), "r"(r2), "r"(r3) : "memory");
}
__device__ __forceinline__ void fence_proxy_async() { asm volatile("fence.proxy.async.shared::cta;" ::: "memory"); }
__device__ __forceinline__ float ex2_approx(float x) { float y; asm("ex2.approx.ftz.f32 %0, %1;" : "=f"(y) : "f"(x)); return y; }
template<int N> __device__ __forceinline__ void fence_regs(float (&r)[N]) {
  #pragma unroll
  for (int i = 0; i < N; i++) asm volatile("" : "+f"(r[i]) :: "memory");
}
template<int N> __device__ __forceinline__ void zero_regs(float (&r)[N]) {
  #pragma unroll
  for (int i = 0; i < N; i += 2) asm volatile("mov.b64 {%0, %1}, 0;" : "=f"(r[i]), "=f"(r[i + 1]));
}
__device__ __forceinline__ float rbf(float x) { return __uint_as_float(pack_bf16(0.f, x)); }
__device__ __forceinline__ float bflo(uint32_t v) { return __uint_as_float(v << 16); }
__device__ __forceinline__ float bfhi(uint32_t v) { return __uint_as_float(v & 0xffff0000u); }

#define XT(i) do {} while (0)
#define TL_START(k) do {} while (0)
#define TL_END(k, cond) do {} while (0)
#define TL_CTA(i, cond) do {} while (0)
#define FS(slot, k) do {} while (0)
#define TL_MARK2(k, cond) do {} while (0)
#define TL_CLK(k, i, cond) do {} while (0)

template <int OFFA, int OFFB>
__device__ __forceinline__ void wgmma_m64n256k16_ss_tb(float (&d)[128], uint32_t a_lo, uint32_t b_lo, int scaleD) {
  asm volatile("{\n.reg .pred p;\n.reg .b32 ta, tb;\n.reg .b64 da, db;\nsetp.ne.b32 p, %130, 0;\n"
    "add.u32 ta, %128, %131;\nadd.u32 tb, %129, %132;\n"
    "mov.b64 da, {ta, 0x40000040};\nmov.b64 db, {tb, 0x40000040};\n"
    "wgmma.mma_async.sync.aligned.m64n256k16.f32.bf16.bf16 "
    "{%0, %1, %2, %3, %4, %5, %6, %7, %8, %9, %10, %11, %12, %13, %14, %15, %16, %17, %18, %19, %20, %21, %22, %23, %24, %25, %26, %27, %28, %29, %30, %31, %32, %33, %34, %35, %36, %37, %38, %39, %40, %41, %42, %43, %44, %45, %46, %47, %48, %49, %50, %51, %52, %53, %54, %55, %56, %57, %58, %59, %60, %61, %62, %63, %64, %65, %66, %67, %68, %69, %70, %71, %72, %73, %74, %75, %76, %77, %78, %79, %80, %81, %82, %83, %84, %85, %86, %87, %88, %89, %90, %91, %92, %93, %94, %95, %96, %97, %98, %99, %100, %101, %102, %103, %104, %105, %106, %107, %108, %109, %110, %111, %112, %113, %114, %115, %116, %117, %118, %119, %120, %121, %122, %123, %124, %125, %126, %127}, "
    "da, db, p, 1, 1, 0, 1;\n}\n"
    : "+f"(d[0]), "+f"(d[1]), "+f"(d[2]), "+f"(d[3]), "+f"(d[4]), "+f"(d[5]), "+f"(d[6]), "+f"(d[7]), "+f"(d[8]), "+f"(d[9]), "+f"(d[10]), "+f"(d[11]), "+f"(d[12]), "+f"(d[13]), "+f"(d[14]), "+f"(d[15]), "+f"(d[16]), "+f"(d[17]), "+f"(d[18]), "+f"(d[19]), "+f"(d[20]), "+f"(d[21]), "+f"(d[22]), "+f"(d[23]), "+f"(d[24]), "+f"(d[25]), "+f"(d[26]), "+f"(d[27]), "+f"(d[28]), "+f"(d[29]), "+f"(d[30]), "+f"(d[31]), "+f"(d[32]), "+f"(d[33]), "+f"(d[34]), "+f"(d[35]), "+f"(d[36]), "+f"(d[37]), "+f"(d[38]), "+f"(d[39]), "+f"(d[40]), "+f"(d[41]), "+f"(d[42]), "+f"(d[43]), "+f"(d[44]), "+f"(d[45]), "+f"(d[46]), "+f"(d[47]), "+f"(d[48]), "+f"(d[49]), "+f"(d[50]), "+f"(d[51]), "+f"(d[52]), "+f"(d[53]), "+f"(d[54]), "+f"(d[55]), "+f"(d[56]), "+f"(d[57]), "+f"(d[58]), "+f"(d[59]), "+f"(d[60]), "+f"(d[61]), "+f"(d[62]), "+f"(d[63]), "+f"(d[64]), "+f"(d[65]), "+f"(d[66]), "+f"(d[67]), "+f"(d[68]), "+f"(d[69]), "+f"(d[70]), "+f"(d[71]), "+f"(d[72]), "+f"(d[73]), "+f"(d[74]), "+f"(d[75]), "+f"(d[76]), "+f"(d[77]), "+f"(d[78]), "+f"(d[79]), "+f"(d[80]), "+f"(d[81]), "+f"(d[82]), "+f"(d[83]), "+f"(d[84]), "+f"(d[85]), "+f"(d[86]), "+f"(d[87]), "+f"(d[88]), "+f"(d[89]), "+f"(d[90]), "+f"(d[91]), "+f"(d[92]), "+f"(d[93]), "+f"(d[94]), "+f"(d[95]), "+f"(d[96]), "+f"(d[97]), "+f"(d[98]), "+f"(d[99]), "+f"(d[100]), "+f"(d[101]), "+f"(d[102]), "+f"(d[103]), "+f"(d[104]), "+f"(d[105]), "+f"(d[106]), "+f"(d[107]), "+f"(d[108]), "+f"(d[109]), "+f"(d[110]), "+f"(d[111]), "+f"(d[112]), "+f"(d[113]), "+f"(d[114]), "+f"(d[115]), "+f"(d[116]), "+f"(d[117]), "+f"(d[118]), "+f"(d[119]), "+f"(d[120]), "+f"(d[121]), "+f"(d[122]), "+f"(d[123]), "+f"(d[124]), "+f"(d[125]), "+f"(d[126]), "+f"(d[127])
    : "r"(a_lo), "r"(b_lo), "r"(scaleD), "n"(OFFA), "n"(OFFB));
}

template <int OFFA, int OFFB>
__device__ __forceinline__ void wgmma_m64n128k16_ss_tb(float (&d)[64], uint32_t a_lo, uint32_t b_lo, int scaleD) {
  asm volatile("{\n.reg .pred p;\n.reg .b32 ta, tb;\n.reg .b64 da, db;\nsetp.ne.b32 p, %66, 0;\n"
    "add.u32 ta, %64, %67;\nadd.u32 tb, %65, %68;\n"
    "mov.b64 da, {ta, 0x40000040};\nmov.b64 db, {tb, 0x40000040};\n"
    "wgmma.mma_async.sync.aligned.m64n128k16.f32.bf16.bf16 "
    "{%0, %1, %2, %3, %4, %5, %6, %7, %8, %9, %10, %11, %12, %13, %14, %15, %16, %17, %18, %19, %20, %21, %22, %23, %24, %25, %26, %27, %28, %29, %30, %31, %32, %33, %34, %35, %36, %37, %38, %39, %40, %41, %42, %43, %44, %45, %46, %47, %48, %49, %50, %51, %52, %53, %54, %55, %56, %57, %58, %59, %60, %61, %62, %63}, "
    "da, db, p, 1, 1, 0, 1;\n}\n"
    : "+f"(d[0]), "+f"(d[1]), "+f"(d[2]), "+f"(d[3]), "+f"(d[4]), "+f"(d[5]), "+f"(d[6]), "+f"(d[7]), "+f"(d[8]), "+f"(d[9]), "+f"(d[10]), "+f"(d[11]), "+f"(d[12]), "+f"(d[13]), "+f"(d[14]), "+f"(d[15]), "+f"(d[16]), "+f"(d[17]), "+f"(d[18]), "+f"(d[19]), "+f"(d[20]), "+f"(d[21]), "+f"(d[22]), "+f"(d[23]), "+f"(d[24]), "+f"(d[25]), "+f"(d[26]), "+f"(d[27]), "+f"(d[28]), "+f"(d[29]), "+f"(d[30]), "+f"(d[31]), "+f"(d[32]), "+f"(d[33]), "+f"(d[34]), "+f"(d[35]), "+f"(d[36]), "+f"(d[37]), "+f"(d[38]), "+f"(d[39]), "+f"(d[40]), "+f"(d[41]), "+f"(d[42]), "+f"(d[43]), "+f"(d[44]), "+f"(d[45]), "+f"(d[46]), "+f"(d[47]), "+f"(d[48]), "+f"(d[49]), "+f"(d[50]), "+f"(d[51]), "+f"(d[52]), "+f"(d[53]), "+f"(d[54]), "+f"(d[55]), "+f"(d[56]), "+f"(d[57]), "+f"(d[58]), "+f"(d[59]), "+f"(d[60]), "+f"(d[61]), "+f"(d[62]), "+f"(d[63])
    : "r"(a_lo), "r"(b_lo), "r"(scaleD), "n"(OFFA), "n"(OFFB));
}

template <int OFFB>
__device__ __forceinline__ void wgmma_m64n128k16_rs_tb(float (&d)[64], uint32_t a0, uint32_t a1, uint32_t a2, uint32_t a3, uint32_t b_lo, int scaleD) {
  asm volatile("{\n.reg .pred p;\n.reg .b32 tb;\n.reg .b64 db;\nsetp.ne.b32 p, %69, 0;\n"
    "add.u32 tb, %68, %70;\n"
    "mov.b64 db, {tb, 0x40000040};\n"
    "wgmma.mma_async.sync.aligned.m64n128k16.f32.bf16.bf16 "
    "{%0, %1, %2, %3, %4, %5, %6, %7, %8, %9, %10, %11, %12, %13, %14, %15, %16, %17, %18, %19, %20, %21, %22, %23, %24, %25, %26, %27, %28, %29, %30, %31, %32, %33, %34, %35, %36, %37, %38, %39, %40, %41, %42, %43, %44, %45, %46, %47, %48, %49, %50, %51, %52, %53, %54, %55, %56, %57, %58, %59, %60, %61, %62, %63}, "
    "{%64, %65, %66, %67}, db, p, 1, 1, 1;\n}\n"
    : "+f"(d[0]), "+f"(d[1]), "+f"(d[2]), "+f"(d[3]), "+f"(d[4]), "+f"(d[5]), "+f"(d[6]), "+f"(d[7]), "+f"(d[8]), "+f"(d[9]), "+f"(d[10]), "+f"(d[11]), "+f"(d[12]), "+f"(d[13]), "+f"(d[14]), "+f"(d[15]), "+f"(d[16]), "+f"(d[17]), "+f"(d[18]), "+f"(d[19]), "+f"(d[20]), "+f"(d[21]), "+f"(d[22]), "+f"(d[23]), "+f"(d[24]), "+f"(d[25]), "+f"(d[26]), "+f"(d[27]), "+f"(d[28]), "+f"(d[29]), "+f"(d[30]), "+f"(d[31]), "+f"(d[32]), "+f"(d[33]), "+f"(d[34]), "+f"(d[35]), "+f"(d[36]), "+f"(d[37]), "+f"(d[38]), "+f"(d[39]), "+f"(d[40]), "+f"(d[41]), "+f"(d[42]), "+f"(d[43]), "+f"(d[44]), "+f"(d[45]), "+f"(d[46]), "+f"(d[47]), "+f"(d[48]), "+f"(d[49]), "+f"(d[50]), "+f"(d[51]), "+f"(d[52]), "+f"(d[53]), "+f"(d[54]), "+f"(d[55]), "+f"(d[56]), "+f"(d[57]), "+f"(d[58]), "+f"(d[59]), "+f"(d[60]), "+f"(d[61]), "+f"(d[62]), "+f"(d[63])
    : "r"(a0), "r"(a1), "r"(a2), "r"(a3), "r"(b_lo), "r"(scaleD), "n"(OFFB));
}

template <int OFFB>
__device__ __forceinline__ void wgmma_m64n128k16_rs(float (&d)[64], uint32_t a0, uint32_t a1, uint32_t a2, uint32_t a3, uint32_t b_lo, int scaleD) {
  asm volatile("{\n.reg .pred p;\n.reg .b32 tb;\n.reg .b64 db;\nsetp.ne.b32 p, %69, 0;\n"
    "add.u32 tb, %68, %70;\n"
    "mov.b64 db, {tb, 0x40000040};\n"
    "wgmma.mma_async.sync.aligned.m64n128k16.f32.bf16.bf16 "
    "{%0, %1, %2, %3, %4, %5, %6, %7, %8, %9, %10, %11, %12, %13, %14, %15, %16, %17, %18, %19, %20, %21, %22, %23, %24, %25, %26, %27, %28, %29, %30, %31, %32, %33, %34, %35, %36, %37, %38, %39, %40, %41, %42, %43, %44, %45, %46, %47, %48, %49, %50, %51, %52, %53, %54, %55, %56, %57, %58, %59, %60, %61, %62, %63}, "
    "{%64, %65, %66, %67}, db, p, 1, 1, 0;\n}\n"
    : "+f"(d[0]), "+f"(d[1]), "+f"(d[2]), "+f"(d[3]), "+f"(d[4]), "+f"(d[5]), "+f"(d[6]), "+f"(d[7]), "+f"(d[8]), "+f"(d[9]), "+f"(d[10]), "+f"(d[11]), "+f"(d[12]), "+f"(d[13]), "+f"(d[14]), "+f"(d[15]), "+f"(d[16]), "+f"(d[17]), "+f"(d[18]), "+f"(d[19]), "+f"(d[20]), "+f"(d[21]), "+f"(d[22]), "+f"(d[23]), "+f"(d[24]), "+f"(d[25]), "+f"(d[26]), "+f"(d[27]), "+f"(d[28]), "+f"(d[29]), "+f"(d[30]), "+f"(d[31]), "+f"(d[32]), "+f"(d[33]), "+f"(d[34]), "+f"(d[35]), "+f"(d[36]), "+f"(d[37]), "+f"(d[38]), "+f"(d[39]), "+f"(d[40]), "+f"(d[41]), "+f"(d[42]), "+f"(d[43]), "+f"(d[44]), "+f"(d[45]), "+f"(d[46]), "+f"(d[47]), "+f"(d[48]), "+f"(d[49]), "+f"(d[50]), "+f"(d[51]), "+f"(d[52]), "+f"(d[53]), "+f"(d[54]), "+f"(d[55]), "+f"(d[56]), "+f"(d[57]), "+f"(d[58]), "+f"(d[59]), "+f"(d[60]), "+f"(d[61]), "+f"(d[62]), "+f"(d[63])
    : "r"(a0), "r"(a1), "r"(a2), "r"(a3), "r"(b_lo), "r"(scaleD), "n"(OFFB));
}

__device__ __forceinline__ uint4 ldg_nc_v4(const void* p) {
  uint4 v;
    asm volatile("{\n.reg .b64 pol;\ncreatepolicy.fractional.L2::evict_first.b64 pol, 1.0;\n"
                 "ld.global.nc.L1::no_allocate.L2::cache_hint.v4.u32 {%0, %1, %2, %3}, [%4], pol;\n}\n" : "=r"(v.x), "=r"(v.y), "=r"(v.z), "=r"(v.w) : "l"(p));
  return v;
}
__device__ __forceinline__ uint64_t pol_normal() {
  uint64_t p; asm volatile("createpolicy.fractional.L2::evict_normal.b64 %0, 1.0;" : "=l"(p)); return p;
}
__device__ __forceinline__ void unpack8(const uint4& u, float (&v)[8]) {
  v[0] = bflo(u.x); v[1] = bfhi(u.x); v[2] = bflo(u.y); v[3] = bfhi(u.y);
  v[4] = bflo(u.z); v[5] = bfhi(u.z); v[6] = bflo(u.w); v[7] = bfhi(u.w);
}
__device__ __forceinline__ void fma8(float (&acc)[8], float s, const uint4& w) {
  acc[0] = fmaf(s, bflo(w.x), acc[0]); acc[1] = fmaf(s, bfhi(w.x), acc[1]); acc[2] = fmaf(s, bflo(w.y), acc[2]); acc[3] = fmaf(s, bfhi(w.y), acc[3]);
  acc[4] = fmaf(s, bflo(w.z), acc[4]); acc[5] = fmaf(s, bfhi(w.z), acc[5]); acc[6] = fmaf(s, bflo(w.w), acc[6]); acc[7] = fmaf(s, bfhi(w.w), acc[7]);
}
__device__ __forceinline__ float rcp_approx(float x) { float y; asm("rcp.approx.ftz.f32 %0, %1;" : "=f"(y) : "f"(x)); return y; }
__device__ __forceinline__ float sigmoid_f(float v) { return rcp_approx(1.0f + ex2_approx(v * -1.4426950408889634f)); }
__device__ __forceinline__ float silu_bf(float v) { return rbf(v * sigmoid_f(v)); }
__device__ __forceinline__ uint32_t rank_key(float r, int idx) {
  const uint32_t b = __float_as_uint(r) >> 16;
  const uint32_t u = (r != r) ? 0u : ((b & 0x8000u) ? (~b & 0xffffu) : (b | 0x8000u));
  return (u << 16) | (0xffffu - (uint32_t)idx);
}
__device__ __forceinline__ void warp_top2(uint32_t& k1, uint32_t& k2) {
  const uint32_t m1 = __reduce_max_sync(0xffffffffu, k1);
  k2 = __reduce_max_sync(0xffffffffu, k1 == m1 ? k2 : k1);
  k1 = m1;
}
__device__ __forceinline__ uint32_t bmul2(uint32_t a, uint32_t b) { uint32_t r; asm("mul.rn.bf16x2 %0, %1, %2;" : "=r"(r) : "r"(a), "r"(b)); return r; }
__device__ __forceinline__ uint32_t badd2(uint32_t a, uint32_t b) { uint32_t r; asm("add.rn.bf16x2 %0, %1, %2;" : "=r"(r) : "r"(a), "r"(b)); return r; }
__device__ __forceinline__ uint32_t bsub2(uint32_t a, uint32_t b) { uint32_t r; asm("sub.rn.bf16x2 %0, %1, %2;" : "=r"(r) : "r"(a), "r"(b)); return r; }
__device__ __forceinline__ float sqrt_approx(float x) { float y; asm("sqrt.approx.f32 %0, %1;" : "=f"(y) : "f"(x)); return y; }
__device__ __forceinline__ uint32_t ln_norm2(uint32_t x1, uint32_t mb2, float inv) {
  const uint32_t d = bsub2(x1, mb2);
  return pack_bf16(bflo(d) * inv, bfhi(d) * inv);
}
__device__ __forceinline__ uint32_t bfma2(uint32_t a, uint32_t b, uint32_t c) { uint32_t r; asm("fma.rn.bf16x2 %0, %1, %2, %3;" : "=r"(r) : "r"(a), "r"(b), "r"(c)); return r; }
__device__ __forceinline__ uint32_t ln_norm2b(uint32_t x1, uint32_t mb2, uint32_t ih, uint32_t il) {
  const uint32_t d = bsub2(x1, mb2);
  return bfma2(d, ih, bmul2(d, il));
}
__device__ __forceinline__ uint32_t ln_mod2(uint32_t x1, uint32_t mb2, float inv, uint32_t c1, uint32_t sb) { return badd2(bmul2(ln_norm2(x1, mb2, inv), c1), sb); }
__device__ __forceinline__ void ldmatrix_x4(uint32_t addr, uint32_t& r0, uint32_t& r1, uint32_t& r2, uint32_t& r3) {
  asm volatile("ldmatrix.sync.aligned.m8n8.x4.shared.b16 {%0, %1, %2, %3}, [%4];" : "=r"(r0), "=r"(r1), "=r"(r2), "=r"(r3) : "r"(addr) : "memory");
}
__device__ __forceinline__ uint4 ldg_stream_v4(const void* p, uint64_t pol) {
  uint4 v; asm volatile("ld.global.nc.L1::no_allocate.L2::cache_hint.L2::128B.v4.u32 {%0, %1, %2, %3}, [%4], %5;" : "=r"(v.x), "=r"(v.y), "=r"(v.z), "=r"(v.w) : "l"(p), "l"(pol)); return v;
}
__device__ __forceinline__ void bulk_load_hint(uint32_t dst, const void* src, uint32_t bytes, uint32_t bar, uint64_t pol) {
  asm volatile("cp.async.bulk.shared::cluster.global.mbarrier::complete_tx::bytes.L2::cache_hint [%0], [%1], %2, [%3], %4;"
    :: "r"(dst), "l"(src), "r"(bytes), "r"(bar), "l"(pol) : "memory");
}
__device__ __forceinline__ void red_release_add(unsigned int* p, unsigned int v) { asm volatile("red.release.gpu.global.add.u32 [%0], %1;" :: "l"(p), "r"(v) : "memory"); }
__device__ __forceinline__ unsigned int ld_acquire(const unsigned int* p) { unsigned int v; asm volatile("ld.acquire.gpu.global.u32 %0, [%1];" : "=r"(v) : "l"(p) : "memory"); return v; }
__device__ __forceinline__ void spin_until(const unsigned int* p, unsigned int target) {
  #pragma unroll 1
  for (unsigned int i = 0; i < (1u << 22); i++) { if (ld_acquire(p) >= target) return; }
}
__device__ __forceinline__ float lds_f32(uint32_t a) { float v; asm volatile("ld.shared.f32 %0, [%1];" : "=f"(v) : "r"(a) : "memory"); return v; }
__device__ __forceinline__ float2 lds_f32x2(uint32_t a) { float2 v; asm volatile("ld.shared.v2.f32 {%0, %1}, [%2];" : "=f"(v.x), "=f"(v.y) : "r"(a) : "memory"); return v; }
__device__ __forceinline__ uint2 lds_u32x2(uint32_t a) { uint2 v; asm volatile("ld.shared.v2.u32 {%0, %1}, [%2];" : "=r"(v.x), "=r"(v.y) : "r"(a) : "memory"); return v; }
__device__ __forceinline__ uint32_t lds_u32(uint32_t a) { uint32_t v; asm volatile("ld.shared.u32 %0, [%1];" : "=r"(v) : "r"(a) : "memory"); return v; }
__device__ __forceinline__ void sts_u32(uint32_t a, uint32_t v) { asm volatile("st.shared.u32 [%0], %1;" :: "r"(a), "r"(v) : "memory"); }
__device__ __forceinline__ void sts_u32x2(uint32_t a, uint32_t x, uint32_t y) { asm volatile("st.shared.v2.u32 [%0], {%1, %2};" :: "r"(a), "r"(x), "r"(y) : "memory"); }
__device__ __forceinline__ void sts_f32(uint32_t a, float v) { asm volatile("st.shared.f32 [%0], %1;" :: "r"(a), "f"(v) : "memory"); }
__device__ __forceinline__ void sts_f32x2(uint32_t a, float x, float y) { asm volatile("st.shared.v2.f32 [%0], {%1, %2};" :: "r"(a), "f"(x), "f"(y) : "memory"); }
__device__ __forceinline__ void sts_f32x4(uint32_t a, float x, float y, float z, float w) { asm volatile("st.shared.v4.f32 [%0], {%1, %2, %3, %4};" :: "r"(a), "f"(x), "f"(y), "f"(z), "f"(w) : "memory"); }

__device__ __forceinline__ uint4 lds_u32x4(uint32_t a) { uint4 v; asm volatile("ld.shared.v4.u32 {%0, %1, %2, %3}, [%4];" : "=r"(v.x), "=r"(v.y), "=r"(v.z), "=r"(v.w) : "r"(a) : "memory"); return v; }
__device__ __forceinline__ void sts_u32x4(uint32_t a, uint32_t x, uint32_t y, uint32_t z, uint32_t w) { asm volatile("st.shared.v4.u32 [%0], {%1, %2, %3, %4};" :: "r"(a), "r"(x), "r"(y), "r"(z), "r"(w) : "memory"); }
__device__ __forceinline__ void st_tagged(float* p, float v) {
  const uint32_t b = __float_as_uint(v);
  asm volatile("st.relaxed.gpu.global.u32 [%0], %1;" :: "l"(p), "r"(b == 0u ? 0x80000000u : b) : "memory");
}
__device__ __forceinline__ void st_tagged4(float* p, float x, float y, float z, float w) {
  const uint32_t a = __float_as_uint(x), b = __float_as_uint(y), c = __float_as_uint(z), d = __float_as_uint(w);
  asm volatile("st.relaxed.gpu.global.v4.u32 [%0], {%1, %2, %3, %4};" :: "l"(p), "r"(a == 0u ? 0x80000000u : a), "r"(b == 0u ? 0x80000000u : b),
               "r"(c == 0u ? 0x80000000u : c), "r"(d == 0u ? 0x80000000u : d) : "memory");
}
__device__ __forceinline__ void st_relaxed2(void* p, uint32_t a, uint32_t b) { asm volatile("st.relaxed.gpu.global.v2.u32 [%0], {%1, %2};" :: "l"(p), "r"(a), "r"(b) : "memory"); }
__device__ __forceinline__ float4 ld_tagged4(const float* p) {
  float4 v; asm volatile("ld.relaxed.gpu.global.v4.f32 {%0, %1, %2, %3}, [%4];" : "=f"(v.x), "=f"(v.y), "=f"(v.z), "=f"(v.w) : "l"(p) : "memory"); return v;
}
__device__ __forceinline__ bool tagged4(const float4& v) {
  return __float_as_uint(v.x) != 0u && __float_as_uint(v.y) != 0u && __float_as_uint(v.z) != 0u && __float_as_uint(v.w) != 0u;
}
__device__ __forceinline__ void hint_arrive(uint32_t* p) { asm volatile("red.relaxed.gpu.global.add.u32 [%0], 1;" :: "l"(p) : "memory"); }
__device__ __forceinline__ void hint_wait(const uint32_t* p, uint32_t target) {
  uint32_t v = 0u;
  #pragma unroll 1
  for (unsigned int i = 0; i < (1u << 22) && v < target; i++) asm volatile("ld.relaxed.gpu.global.u32 %0, [%1];" : "=r"(v) : "l"(p) : "memory");
}
__device__ __forceinline__ void fence_proxy_async_global() { asm volatile("fence.proxy.async.global;" ::: "memory"); }

#define H_SPLIT 1
#define X_DLY 1200
#define W_DLY 1900
#define W_FIRST 2200
#define PRE_B 2
template <int J0, int J1>
__device__ __forceinline__ void load_parts(float2 (&pa)[J1 - J0][4], int t2) {
  #pragma unroll
  for (int j = J0; j < J1; j++)
    #pragma unroll
    for (int k = 0; k < 4; k++)
      asm volatile("ld.relaxed.gpu.global.v2.f32 {%0, %1}, [%2];" : "=f"(pa[j - J0][k].x), "=f"(pa[j - J0][k].y)
                   : "l"(g_modpart + k * 2 * T_D + (t2 >> 7) * T_D + j * 256 + (t2 & 127) * 2) : "memory");
}
template <int J0, int J1>
__device__ __forceinline__ void finish_parts(float2 (&pa)[J1 - J0][4], bool loaded, int t2, uint32_t tab) {
  #pragma unroll 1
  for (unsigned int spin = 0; spin < (1u << 22); spin++) {
    if (!loaded) load_parts<J0, J1>(pa, t2);
    loaded = false;
    bool ok = true;
    #pragma unroll
    for (int j = 0; j < J1 - J0; j++)
      #pragma unroll
      for (int k = 0; k < 4; k++) ok &= (__float_as_uint(pa[j][k].x) != 0u) & (__float_as_uint(pa[j][k].y) != 0u);
    if (__all_sync(0xffffffffu, ok)) break;
  }
  #pragma unroll
  for (int j = J0; j < J1; j++) {
    const float2* q = pa[j - J0];
    const uint32_t m = pack_bf16(((q[0].x + q[1].x) + q[2].x) + q[3].x, ((q[0].y + q[1].y) + q[2].y) + q[3].y);
    sts_u32(tab + (t2 >> 7) * 2048 + j * 512 + (t2 & 127) * 4, t2 >= 128 ? badd2(m, 0x3F803F80u) : m);
  }
}
__device__ __forceinline__ void head_phase(uint32_t bid, uint32_t scr, uint32_t xs, uint32_t b_x, uint32_t b_go, uint32_t b_head, int t2, uint32_t zero, const bf16* __restrict__ cvec, const bf16* __restrict__ w_mod) {
  const int lane = t2 & 31, w8 = t2 >> 5;
  const int cb = bid & 31, ks = bid >> 5;
  const bool early = (cb & 15) < 4 * H_SPLIT;
  const uint32_t ws = (xs - 32768 + (t2 >> 3) * 128 + (((t2 ^ (t2 >> 3)) & 7) << 4)) ^ zero;
  const float cv = __bfloat162float(cvec[ks * 256 + t2]);
  const bf16* wsrc = w_mod + (size_t)(ks * 256 + (t2 >> 3)) * (6 * T_D) + cb * 64 + (t2 & 7) * 8;
  if (early) {
    const uint64_t pol = policy_evict_first();
    #pragma unroll 2
    for (int i = 0; i < 8; i++)
      asm volatile("cp.async.cg.shared.global.L2::cache_hint [%0], [%1], 16, %2;" :: "r"(ws + i * 4096), "l"(wsrc + (size_t)i * 32 * 6 * T_D), "l"(pol) : "memory");
  }
  sts_f32(scr + t2 * 4, silu_bf(cv));
  named_bar_sync(6, 384);
  TL_MARK2(1, t2 == 0);
  uint4 xv[2][4];
  uint32_t mb2[2], ih[2], il[2];
  auto norm = [&](int j) {
    #pragma unroll
    for (int r = 0; r < 2; r++) {
      xv[r][j].x = ln_norm2b(xv[r][j].x, mb2[r], ih[r], il[r]); xv[r][j].y = ln_norm2b(xv[r][j].y, mb2[r], ih[r], il[r]);
      xv[r][j].z = ln_norm2b(xv[r][j].z, mb2[r], ih[r], il[r]); xv[r][j].w = ln_norm2b(xv[r][j].w, mb2[r], ih[r], il[r]);
    }
  };
  auto modulate = [&](int j) {
    const uint4 sa = lds_u32x4(scr + 8192 + j * 512 + lane * 16), c1 = lds_u32x4(scr + 8192 + 2048 + j * 512 + lane * 16);
    #pragma unroll
    for (int r = 0; r < 2; r++) {
      xv[r][j].x = badd2(bmul2(xv[r][j].x, c1.x), sa.x); xv[r][j].y = badd2(bmul2(xv[r][j].y, c1.y), sa.y);
      xv[r][j].z = badd2(bmul2(xv[r][j].z, c1.z), sa.z); xv[r][j].w = badd2(bmul2(xv[r][j].w, c1.w), sa.w);
    }
  };
  auto store = [&](int j) {
    #pragma unroll
    for (int r = 0; r < 2; r++) *reinterpret_cast<uint4*>(g_h + (size_t)(bid * 16 + 2 * w8 + r) * T_D + j * 256 + lane * 8) = xv[r][j];
  };
  #pragma unroll 1
  for (int ph = 0; ph < 2; ph++) {
    if ((ph == 0) == early) {
      asm volatile("cp.async.wait_all;" ::: "memory");
      if (!early) mbar_wait(b_x + 168, 0);
      float acc[8];
      #pragma unroll
      for (int j = 0; j < 8; j++) acc[j] = 0.f;
      #pragma unroll
      for (int i = 0; i < 8; i++) fma8(acc, lds_f32(scr + ((t2 >> 3) + 32 * i) * 4), lds_u32x4(ws + i * 4096));
      #pragma unroll
      for (int j = 0; j < 4; j++) { const bool up = lane & 16; acc[j] = (up ? acc[4 + j] : acc[j]) + __shfl_xor_sync(0xffffffffu, up ? acc[j] : acc[4 + j], 16); }
      #pragma unroll
      for (int j = 0; j < 2; j++) { const bool up = lane & 8; acc[j] = (up ? acc[2 + j] : acc[j]) + __shfl_xor_sync(0xffffffffu, up ? acc[j] : acc[2 + j], 8); }
      sts_f32x2(scr + 1024 + w8 * 256 + (lane & 7) * 32 + (lane >> 3) * 8, acc[0], acc[1]);
      named_bar_sync(5, 256);
      if (t2 < 64) {
        float sum = 0.f;
        #pragma unroll
        for (int i = 0; i < 8; i++) sum += lds_f32(scr + 1024 + i * 256 + t2 * 4);
        st_tagged(g_modpart + ks * 2 * T_D + cb * 64 + t2, sum);
        TL_MARK2(early ? 2 : 6, t2 == 0);
      }
    } else {
      float2 pa[H_SPLIT][4];
      mbar_wait(b_x, 0);
      TL_MARK2(18, t2 == 0);
      load_parts<0, H_SPLIT>(pa, t2);
      #pragma unroll
      for (int r = 0; r < 2; r++)
        #pragma unroll
        for (int j = 0; j < 4; j++) xv[r][j] = lds_u32x4(xs + (2 * w8 + r) * 2048 + j * 512 + lane * 16);
  {
    float st[4] = {0.f, 0.f, 0.f, 0.f};
    #pragma unroll
    for (int r = 0; r < 2; r++)
      #pragma unroll
      for (int j = 0; j < 4; j++) {
        float v[8];
        unpack8(xv[r][j], v);
        st[2 * r] += ((v[0] + v[1]) + (v[2] + v[3])) + ((v[4] + v[5]) + (v[6] + v[7]));
        st[2 * r + 1] += fmaf(v[0], v[0], fmaf(v[1], v[1], fmaf(v[2], v[2], v[3] * v[3]))) + fmaf(v[4], v[4], fmaf(v[5], v[5], fmaf(v[6], v[6], v[7] * v[7])));
      }
    #pragma unroll
    for (int k = 0; k < 2; k++) { const bool up = lane & 16; st[k] = (up ? st[2 + k] : st[k]) + __shfl_xor_sync(0xffffffffu, up ? st[k] : st[2 + k], 16); }
    #pragma unroll
    for (int o = 8; o > 0; o >>= 1) { st[0] += __shfl_xor_sync(0xffffffffu, st[0], o); st[1] += __shfl_xor_sync(0xffffffffu, st[1], o); }
    const float mean = st[0] * (1.0f / T_D);
    const float inv = rcp_approx(rbf(sqrt_approx(rbf(rbf(fmaxf(fmaf(-mean, mean, st[1] * (1.0f / T_D)), 0.f)) + 1e-05f))));
    const uint32_t m = pack_bf16(mean, mean), h = pack_bf16(inv - rbf(inv), inv);
    #pragma unroll
    for (int r = 0; r < 2; r++) {
      mb2[r] = __shfl_sync(0xffffffffu, m, 16 * r);
      const uint32_t hr = __shfl_sync(0xffffffffu, h, 16 * r);
      ih[r] = __byte_perm(hr, hr, 0x3232); il[r] = __byte_perm(hr, hr, 0x1010);
    }
  }
      #pragma unroll
      for (int j = 0; j < H_SPLIT; j++) norm(j);
      TL_MARK2(5, t2 == 0);
      finish_parts<0, H_SPLIT>(pa, true, t2, scr + 8192);
      named_bar_sync(5, 256);
      TL_MARK2(7, t2 == 0);
      #pragma unroll
      for (int j = 0; j < H_SPLIT; j++) { modulate(j); store(j); }
      named_bar_arrive(9, 288);
    }
  }
  #pragma unroll
  for (int j = H_SPLIT; j < 4; j++) norm(j);
  float2 pb[4 - H_SPLIT][4];
  finish_parts<H_SPLIT, 4>(pb, false, t2, scr + 8192);
  named_bar_sync(5, 256);
  TL_MARK2(17, t2 == 0);
  #pragma unroll
  for (int j = H_SPLIT; j < 4; j++) modulate(j);
  __syncwarp();
  if (lane == 0) mbar_arrive(b_head + (xv[1][3].w & zero));
  mbar_wait(b_go, 0);
  #pragma unroll
  for (int j = H_SPLIT; j < 4; j++) store(j);
  named_bar_arrive(8, 288);
}

#define MOD_AT (b_empty + 8)
#define MOD_SPLIT 16
__device__ __forceinline__ void mod_rest(uint32_t bid, uint32_t scr, uint32_t b_go, int t, const bf16* __restrict__ cvec, const bf16* __restrict__ w_mod, const bf16* __restrict__ w_r) {
  const int lane = t & 31;
  #pragma unroll 1
  for (int i = t; i < T_D / 2; i += 64) {
    const uint32_t c2 = *reinterpret_cast<const uint32_t*>(cvec + 2 * i);
    sts_u32(scr + i * 4, pack_bf16(silu_bf(bflo(c2)), silu_bf(bfhi(c2))));
  }
  named_bar_sync(11, 64);
  const bf16* wp = w_mod + (size_t)(2 * (t >> 2)) * (6 * T_D) + 2 * T_D + bid * 32 + (t & 3) * 8;
  float acc[8];
  #pragma unroll
  for (int i = 0; i < 8; i++) acc[i] = 0.f;
  #pragma unroll 1
  for (int i = 0; i < 32; i += 2) {
    if (i == MOD_SPLIT) mbar_wait(b_go, 0);
    const uint4 w0 = ldg_nc_v4(wp), w1 = ldg_nc_v4(wp + 6 * T_D), w2 = ldg_nc_v4(wp + 32 * 6 * T_D), w3 = ldg_nc_v4(wp + 33 * 6 * T_D);
    wp += 64 * 6 * T_D;
    const uint32_t s0 = lds_u32(scr + (i * 16 + (t >> 2)) * 4), s1 = lds_u32(scr + (i * 16 + 16 + (t >> 2)) * 4);
    fma8(acc, bflo(s0), w0); fma8(acc, bfhi(s0), w1); fma8(acc, bflo(s1), w2); fma8(acc, bfhi(s1), w3);
  }
  #pragma unroll
  for (int j = 0; j < 4; j++) { const bool up = lane & 16; acc[j] = (up ? acc[4 + j] : acc[j]) + __shfl_xor_sync(0xffffffffu, up ? acc[j] : acc[4 + j], 16); }
  #pragma unroll
  for (int j = 0; j < 2; j++) { const bool up = lane & 8; acc[j] = (up ? acc[2 + j] : acc[j]) + __shfl_xor_sync(0xffffffffu, up ? acc[j] : acc[2 + j], 8); }
  { const bool up = lane & 4; acc[0] = (up ? acc[1] : acc[0]) + __shfl_xor_sync(0xffffffffu, up ? acc[0] : acc[1], 4); }
  if (t >= 32) sts_f32(scr + 2048 + lane * 4, acc[0]);
  named_bar_sync(11, 64);
  if (__shfl_sync(0xffffffffu, t, 0) < 32) {
    const int kind = bid >> 5;
    float v = rbf(acc[0] + lds_f32(scr + 2048 + lane * 4));
    const int col = (bid & 31) * 32 + (lane & 3) * 8 + (lane >> 2);
    uint8_t* dst = g_col + (col >> 7) * 1536;
    if (kind == 2) v = rbf(1.0f + v);
    float vw = v * __bfloat162float(w_r[col]);
    if (kind == 2) {
      const int c = col & 127, i = (c & ~15) + ((c >> 1) & 3) * 4 + ((c >> 3) & 1) * 2 + (c & 1);
      reinterpret_cast<bf16*>(dst)[i] = __float2bfloat16_rn(vw);
      reinterpret_cast<bf16*>(dst)[128 + i] = __float2bfloat16_rn(vw - rbf(vw));
    }
    reinterpret_cast<bf16*>(dst + 512 + (kind & 1) * 512 + (kind >> 1) * 256)[col & 127] = __float2bfloat16_rn(v);
    #pragma unroll
    for (int o = 16; o > 0; o >>= 1) vw += __shfl_xor_sync(0xffffffffu, vw, o);
    if (lane == 0 && (kind == 1 || kind == 2)) g_scal[95 - bid] = vw;
  }
  #pragma unroll 1
  for (int i = bid * 64 + t; i < (int)(sizeof(g_mail) / 16); i += 128 * 64) reinterpret_cast<uint4*>(&g_mail)[i] = make_uint4(0u, 0u, 0u, 0u);
  named_bar_sync(11, 64);
  if (t == 0) red_release_add(&g_hcnt[0], 1u);
}

constexpr int AT_NBLK = T_SEQ / 128;
constexpr float AT_HEAD = 7.0f;
#define WO_LATE 12
#define QP_STAG 3
#define AT_SPLIT 28
#define AT_PIN 12
#define PINB 4
constexpr int AT_NFULL = 124;
constexpr int AT_PREG = 40, AT_CREG = 232;
constexpr uint32_t AT_SQ = 5 * 32768;
constexpr float AT_C = 0.08838834764831845f * 1.4426950408889634f;
constexpr float AT_RAW_LO = -16.0f, AT_RAW_HI = 24.0f;
constexpr float AT_RAW_SUM = 281474976710656.0f, AT_RAW_MIN = 9.094947017729282e-13f;
constexpr uint32_t AT_SBAR = AT_SQ + 65536 + 256;
constexpr uint32_t AT_SMEM = AT_SQ + 65536 + 3072;

__device__ __forceinline__ uint32_t ring_slot(uint32_t t) { return t - 5u * ((t * 205u) >> 10); }
__device__ __forceinline__ uint32_t qp_pos(uint32_t j, uint32_t it) { return 4u * it + (j & 3u) + ((j & 3u) == 3u ? it : 0u); }
__device__ __forceinline__ uint32_t ring_par(uint32_t t) { return ((t * 205u) >> 10) & 1u; }
__device__ __forceinline__ void softmax_rowmax(const float (&s)[64], float& mx0, float& mx1) {
  float a0 = fmaxf(s[0], s[1]), a1 = fmaxf(s[4], s[5]), a2 = fmaxf(s[8], s[9]), a3 = fmaxf(s[12], s[13]);
  float b0 = fmaxf(s[2], s[3]), b1 = fmaxf(s[6], s[7]), b2 = fmaxf(s[10], s[11]), b3 = fmaxf(s[14], s[15]);
  #pragma unroll
  for (int j = 4; j < 16; j += 4) {
    a0 = fmaxf(a0, fmaxf(s[4 * j + 0], s[4 * j + 1]));  b0 = fmaxf(b0, fmaxf(s[4 * j + 2], s[4 * j + 3]));
    a1 = fmaxf(a1, fmaxf(s[4 * j + 4], s[4 * j + 5]));  b1 = fmaxf(b1, fmaxf(s[4 * j + 6], s[4 * j + 7]));
    a2 = fmaxf(a2, fmaxf(s[4 * j + 8], s[4 * j + 9]));  b2 = fmaxf(b2, fmaxf(s[4 * j + 10], s[4 * j + 11]));
    a3 = fmaxf(a3, fmaxf(s[4 * j + 12], s[4 * j + 13])); b3 = fmaxf(b3, fmaxf(s[4 * j + 14], s[4 * j + 15]));
  }
  mx0 = fmaxf(fmaxf(a0, a1), fmaxf(a2, a3));
  mx1 = fmaxf(fmaxf(b0, b1), fmaxf(b2, b3));
  mx0 = fmaxf(mx0, __shfl_xor_sync(0xffffffffu, mx0, 1));
  mx1 = fmaxf(mx1, __shfl_xor_sync(0xffffffffu, mx1, 1));
  mx0 = fmaxf(mx0, __shfl_xor_sync(0xffffffffu, mx0, 2));
  mx1 = fmaxf(mx1, __shfl_xor_sync(0xffffffffu, mx1, 2));
}
__device__ __forceinline__ void softmax_sub(float (&s)[64], float mc0, float mc1) {
  #pragma unroll
  for (int j = 0; j < 16; j++) { s[4 * j] -= mc0; s[4 * j + 1] -= mc0; s[4 * j + 2] -= mc1; s[4 * j + 3] -= mc1; }
}
template <int LO, int HI>
__device__ __forceinline__ void softmax_exp(float (&s)[64]) {
  #pragma unroll
  for (int i = LO; i < HI; i++) s[i] = ex2_approx(s[i]);
}
__device__ __forceinline__ bool softmax_mode(const float (&s)[64], float& mc0, float& mc1) {
  softmax_rowmax(s, mc0, mc1);
  const bool raw = __all_sync(0xffffffffu, mc0 >= AT_RAW_LO && mc0 <= AT_RAW_HI && mc1 >= AT_RAW_LO && mc1 <= AT_RAW_HI);
  mc0 += AT_HEAD; mc1 += AT_HEAD;
  return raw;
}
__device__ __forceinline__ void rowsum_p(const uint32_t (&p)[32], uint32_t& t0, uint32_t& t1) {
  uint32_t a[16];
  #pragma unroll
  for (int i = 0; i < 8; i++) { a[2 * i] = badd2(p[4 * i], p[4 * i + 2]); a[2 * i + 1] = badd2(p[4 * i + 1], p[4 * i + 3]); }
  #pragma unroll
  for (int i = 0; i < 4; i++) { a[2 * i] = badd2(a[4 * i], a[4 * i + 2]); a[2 * i + 1] = badd2(a[4 * i + 1], a[4 * i + 3]); }
  t0 = badd2(badd2(a[0], a[2]), badd2(a[4], a[6]));
  t1 = badd2(badd2(a[1], a[3]), badd2(a[5], a[7]));
}
__device__ __forceinline__ void add_rowsum(const uint32_t (&p)[32], float& l0, float& l1) {
  uint32_t t0, t1;
  rowsum_p(p, t0, t1);
  l0 += bflo(t0) + bfhi(t0); l1 += bflo(t1) + bfhi(t1);
}
__device__ __forceinline__ void pack_p(uint32_t (&p)[32], const float (&s)[64]) {
  #pragma unroll
  for (int i = 0; i < 32; i++) p[i] = pack_bf16(s[2 * i], s[2 * i + 1]);
}
__device__ __noinline__ void attn_rows_exact(uint32_t bid, uint32_t sq, uint32_t so, int hsel, const bf16* __restrict__ kh, const bf16* __restrict__ vh) {
  const int warp = (threadIdx.x >> 5) & 3, lane = threadIdx.x & 31;
  const size_t hofs = (size_t)((bid < 128 ? bid >> 4 : 15) * 2 + hsel) * T_SEQ * T_DH;
  kh += hofs; vh += hofs;
  #pragma unroll 1
  for (int r = 16 * warp; r < 16 * warp + 16; r++) {
    const uint32_t ad = (lane >> 4) * 16384 + r * 128 + ((((lane & 15) >> 1) ^ (r & 7)) << 4) + (lane & 1) * 8;
    uint2 qv; asm volatile("ld.shared.v2.u32 {%0, %1}, [%2];" : "=r"(qv.x), "=r"(qv.y) : "r"(sq + ad) : "memory");
    const float q0 = bflo(qv.x), q1 = bfhi(qv.x), q2 = bflo(qv.y), q3 = bfhi(qv.y);
    float m = -INFINITY, l = 0.f, o0 = 0.f, o1 = 0.f, o2 = 0.f, o3 = 0.f;
    #pragma unroll 1
    for (int key = 0; key < T_SEQ; key++) {
      const uint2 kv = *reinterpret_cast<const uint2*>(kh + (size_t)key * T_DH + lane * 4);
      const uint2 vv = *reinterpret_cast<const uint2*>(vh + (size_t)key * T_DH + lane * 4);
      float sc = (q0 * bflo(kv.x) + q1 * bfhi(kv.x)) + (q2 * bflo(kv.y) + q3 * bfhi(kv.y));
      #pragma unroll
      for (int o = 16; o > 0; o >>= 1) sc += __shfl_xor_sync(0xffffffffu, sc, o);
      const float mn = fmaxf(m, sc);
      const float al = (m == mn) ? 1.0f : ex2_approx(m - mn), p = rbf(ex2_approx(sc - mn));
      m = mn;
      l = fmaf(l, al, p);
      o0 = fmaf(o0, al, p * bflo(vv.x)); o1 = fmaf(o1, al, p * bfhi(vv.x));
      o2 = fmaf(o2, al, p * bflo(vv.y)); o3 = fmaf(o3, al, p * bfhi(vv.y));
    }
    const float inv = rcp_approx(l);
    asm volatile("st.shared.v2.u32 [%0], {%1, %2};" :: "r"(so + ad), "r"(pack_bf16(o0 * inv, o1 * inv)), "r"(pack_bf16(o2 * inv, o3 * inv)) : "memory");
  }
}
__device__ __forceinline__ void issue_qk(float (&s)[64], const uint32_t (&q)[32], uint32_t k_lo) {
  wgmma_fence();
  wgmma_m64n128k16_rs<0>(s, q[0], q[1], q[2], q[3], k_lo, 0);
  wgmma_m64n128k16_rs<2>(s, q[4], q[5], q[6], q[7], k_lo, 1);
  wgmma_m64n128k16_rs<4>(s, q[8], q[9], q[10], q[11], k_lo, 1);
  wgmma_m64n128k16_rs<6>(s, q[12], q[13], q[14], q[15], k_lo, 1);
  wgmma_m64n128k16_rs<1024>(s, q[16], q[17], q[18], q[19], k_lo, 1);
  wgmma_m64n128k16_rs<1026>(s, q[20], q[21], q[22], q[23], k_lo, 1);
  wgmma_m64n128k16_rs<1028>(s, q[24], q[25], q[26], q[27], k_lo, 1);
  wgmma_m64n128k16_rs<1030>(s, q[28], q[29], q[30], q[31], k_lo, 1);
  wgmma_commit();
}
__device__ __forceinline__ void issue_pv(float (&o)[64], const uint32_t (&p)[32], uint32_t v_lo, int accumulate) {
  wgmma_fence();
  wgmma_m64n128k16_rs_tb<0>(o, p[0], p[1], p[2], p[3], v_lo, accumulate);
  wgmma_m64n128k16_rs_tb<128>(o, p[4], p[5], p[6], p[7], v_lo, 1);
  wgmma_m64n128k16_rs_tb<256>(o, p[8], p[9], p[10], p[11], v_lo, 1);
  wgmma_m64n128k16_rs_tb<384>(o, p[12], p[13], p[14], p[15], v_lo, 1);
  wgmma_m64n128k16_rs_tb<512>(o, p[16], p[17], p[18], p[19], v_lo, 1);
  wgmma_m64n128k16_rs_tb<640>(o, p[20], p[21], p[22], p[23], v_lo, 1);
  wgmma_m64n128k16_rs_tb<768>(o, p[24], p[25], p[26], p[27], v_lo, 1);
  wgmma_m64n128k16_rs_tb<896>(o, p[28], p[29], p[30], p[31], v_lo, 1);
  wgmma_commit();
}
__device__ __forceinline__ void block_end(uint32_t zero, uint32_t bar) {
  #pragma unroll 1
  for (uint32_t i = 0; i < zero; i++) mbar_arrive(bar);
}
__device__ __forceinline__ void rescale_o(float (&o)[64], float al0, float al1) {
  #pragma unroll
  for (int j = 0; j < 16; j++) { o[4 * j] *= al0; o[4 * j + 1] *= al0; o[4 * j + 2] *= al1; o[4 * j + 3] *= al1; }
}

__device__ __forceinline__ void stage_o(const float (&o)[64], float i0, float i1, uint32_t dst, int lane) {
  #pragma unroll
  for (int J = 0; J < 16; J += 2)
    stmatrix_x4(dst + (J >> 3) * 16384 + ((((J & 7) + (lane >> 4)) ^ (lane & 7)) << 4),
                pack_bf16(o[4 * J + 0] * i0, o[4 * J + 1] * i0), pack_bf16(o[4 * J + 2] * i1, o[4 * J + 3] * i1),
                pack_bf16(o[4 * J + 4] * i0, o[4 * J + 5] * i0), pack_bf16(o[4 * J + 6] * i1, o[4 * J + 7] * i1));
}
__device__ __forceinline__ bool finish_l(float& l0, float& l1) {
  l0 += __shfl_xor_sync(0xffffffffu, l0, 1); l1 += __shfl_xor_sync(0xffffffffu, l1, 1);
  l0 += __shfl_xor_sync(0xffffffffu, l0, 2); l1 += __shfl_xor_sync(0xffffffffu, l1, 2);
  const bool redo = __any_sync(0xffffffffu, !(l0 <= AT_RAW_SUM && l1 <= AT_RAW_SUM && l0 >= AT_RAW_MIN && l1 >= AT_RAW_MIN));
  l0 = rcp_approx(l0); l1 = rcp_approx(l1);
  return redo;
}
template <int J0>
__device__ __forceinline__ void stage_q(const float (&acc)[128], float c, uint32_t dst, int lane) {
  #pragma unroll
  for (int J = J0; J < J0 + 16; J += 2)
    stmatrix_x4(dst + (J >> 3) * 16384 + ((((J & 7) + (lane >> 4)) ^ (lane & 7)) << 4),
                pack_bf16(acc[4 * J + 0] * c, acc[4 * J + 1] * c), pack_bf16(acc[4 * J + 2] * c, acc[4 * J + 3] * c),
                pack_bf16(acc[4 * J + 4] * c, acc[4 * J + 5] * c), pack_bf16(acc[4 * J + 6] * c, acc[4 * J + 7] * c));
}
__device__ __forceinline__ void store_o(const CUtensorMap* tmO, uint32_t src, int head, int row) {
  tma_store_2d(tmO, src, head * T_DH, row);
  tma_store_2d(tmO, src + 16384, head * T_DH + 64, row);
  bulk_commit();
}
__device__ __forceinline__ void mma_bf16(float (&d)[4], uint32_t a0, uint32_t a1, uint32_t a2, uint32_t a3, uint32_t b0, uint32_t b1) {
  asm volatile("mma.sync.aligned.m16n8k16.row.col.f32.bf16.bf16.f32 {%0, %1, %2, %3}, {%4, %5, %6, %7}, {%8, %9}, {%0, %1, %2, %3};"
               : "+f"(d[0]), "+f"(d[1]), "+f"(d[2]), "+f"(d[3]) : "r"(a0), "r"(a1), "r"(a2), "r"(a3), "r"(b0), "r"(b1));
}
struct GemvSel { uint32_t lo0, hi0, lo1, hi1; };
__device__ __forceinline__ GemvSel gemv_sel(int lane) {
  const uint32_t lo = (lane & 8) ? 0x1044u : 0x4410u, hi = (lane & 8) ? 0x3244u : 0x4432u;
  GemvSel s; s.lo0 = (lane & 16) ? 0x4444u : lo; s.hi0 = (lane & 16) ? 0x4444u : hi; s.lo1 = (lane & 16) ? lo : 0x4444u; s.hi1 = (lane & 16) ? hi : 0x4444u;
  return s;
}
#define GEMV_B0(j, h, s) __byte_perm((j) < 2 ? (h).x : (h).y, 0u, ((j) & 1) ? (s).hi0 : (s).lo0)
#define GEMV_B1(j, h, s) __byte_perm((j) < 2 ? (h).x : (h).y, 0u, ((j) & 1) ? (s).hi1 : (s).lo1)
__device__ __forceinline__ float4 gemv_out(const float (&d)[4], int lane) {
  const bool tk = lane & 1;
  const float r0 = __shfl_xor_sync(0xffffffffu, tk ? d[0] : d[1], 1), r1 = __shfl_xor_sync(0xffffffffu, tk ? d[2] : d[3], 1);
  return tk ? make_float4(r0, d[1], r1, d[3]) : make_float4(d[0], r0, d[2], r1);
}
#define OG_NG 8
#define PUT_N 2
#define H_STAG 2
#define AL_P 60
#define AL_SLEEP 1200
#define AL_MAX 800
#define POLL_NS 500
#define OG_PROF 0xECCBB988u
#define RK_P 24
#define RANK 1
__host__ __device__ constexpr int og_pre(int tile) { return (OG_PROF >> ((tile >> 4) * 4)) & 15; }
constexpr int OG_PRE2 = og_pre(127), OG_HSUM = og_pre(0) + og_pre(16) + og_pre(32) + og_pre(48) + og_pre(64) + og_pre(80) + og_pre(96);
#define OG_JOBS 7
#define OG_GRP 6
#define LD_FIRST 2
#define LD_STAG (OG_GRP / 2)
constexpr int OG_ST = 5, OG_NKB = T_DQKV / 64 - og_pre(0), OG_MOE = T_F / 32;
__device__ __forceinline__ int pre_kb(int i) { return (i >> 1) * 4 + (i & 1); }
__device__ __forceinline__ int own_kb(int i, int pre) { return i < (pre & ~1) ? pre_kb(i) + 2 : i + pre; }
constexpr int OG_POS = 8;
constexpr uint32_t OG_STAGE = 32768;
constexpr uint32_t OG_SCOL = AT_SBAR + 512;
constexpr uint32_t OG_SMISC = AT_SBAR + 2048;
constexpr uint32_t OG_SWD = AT_SQ, OG_PSLOT = AT_SQ;
constexpr uint32_t OG_XSLOT = AT_SQ + 32768;
constexpr uint32_t OG_OSLOT = 1 * OG_STAGE;
constexpr uint32_t OG_SRED = 3 * OG_STAGE;
constexpr uint32_t OG_SH2 = OG_SRED + 24576;
constexpr uint32_t OG_SSTAT = OG_SRED + 16384;
constexpr uint32_t OG_SGU = OG_SRED + 8192;
constexpr uint32_t OG_SFIN = OG_SGU + 256;
#define OGM 2
#define OG_MT(b) ((((b) >> OGM) & 15) ^ (((b) & 64) ? 15 : 0))
#define OG_NT(b) (((b) & ((1 << OGM) - 1)) + (((b) >> (4 + OGM)) << OGM))
__device__ __forceinline__ int tail_tile(uint32_t sbase) { mbar_wait(sbase + AT_SBAR + 336, 0); return (int)lds_u32(sbase + AT_SBAR + 408); }
#define TAIL_SETUP \
  const uint32_t bar_full = sbase + AT_SBAR, bar_empty = bar_full + 40; \
  const uint32_t bar_wd = bar_full + 168, bar_col = bar_full + 176, bar_out = bar_full + 184, bar_end = bar_full + 192; \
  const uint32_t bar_key = bar_full + 200, bar_h2 = bar_full + 208, bar_sel = bar_full + 216; \
  const int mt = OG_MT(tb), nt = OG_NT(tb); \
  const int m0 = mt * 128, n0 = nt * 128; \
  const bool has_moe = (int)bid < OG_MOE; \
  (void)bar_empty; (void)bar_wd; (void)bar_col; (void)bar_out; (void)bar_end; (void)bar_key; (void)bar_h2; (void)bar_sel; (void)m0; (void)n0; (void)has_moe;

__device__ __forceinline__ void tail_producer(uint32_t bid, uint32_t sbase, uint32_t ph, uint64_t pol, const CUtensorMap* tmA, const CUtensorMap* tmB, const CUtensorMap* tmD) {
  const int tb = tail_tile(sbase);
  TAIL_SETUP
  uint32_t stage = OG_POS % OG_ST;
  int kb = 0;
  #pragma unroll 1
  for (int seg = 0; seg < 2; seg++) {
    mbar_wait(bar_full + 264 + 80 * seg, 0);
    fence_proxy_async_global();
    const int end = 32 + 32 * seg - og_pre(tb);
    #pragma unroll 1
    for (; kb < end; kb++) {
      const uint32_t fb = bar_full + 8 * stage, sa = sbase + stage * OG_STAGE;
      const int k0 = own_kb(kb, og_pre(tb)) * 64;
      mbar_wait(bar_empty + 8 * stage, ph);
      mbar_expect_tx(fb, OG_STAGE);
      tma_load_3d_hint(sa + 16384, tmB, k0, 2 * nt, fb, pol);
      tma_load_2d_hint(sa, tmA, k0, m0, fb, pol);
      if (++stage == OG_ST) { stage = 0; ph ^= 1; }
    }
  }
  if (has_moe) {
    stage += stage & 1;
    mbar_wait(bar_empty + 8 * stage, ph);
    mbar_expect_tx(bar_wd, OG_STAGE);
    tma_load_3d_hint(sbase + stage * OG_STAGE, tmD, bid * 32, 8, bar_wd, pol);
  }
}

__device__ __forceinline__ uint32_t out2(uint32_t x1, uint32_t mb2, uint32_t ih, uint32_t il, uint32_t c1, uint32_t sb, uint32_t gb) {
  const uint32_t h2 = badd2(bmul2(ln_norm2b(x1, mb2, ih, il), c1), sb);
  return badd2(x1, bmul2(gb, bfma2(h2, 0u, h2)));
}
#define OGTIME gtime()
#define X_PACE 200
#define Y_SLACK 96
#define OG_STAG 3
#define X_PACE2 100
#define WD_PACE 300
__device__ __forceinline__ void tail_exchange(uint32_t bid, uint32_t sbase, const bf16* __restrict__ w_down, const bf16* __restrict__ w_r, const bf16* __restrict__ x, bf16* __restrict__ out) {
    const int lane = threadIdx.x & 31, wi = __shfl_sync(0xffffffffu, threadIdx.x >> 5, 0);
    if (wi == 3) {
      uint32_t a = bid, b = 0u;
      if (bid < AT_NFULL) mbar_wait(sbase + AT_SBAR + 312, 0);
      if (bid < OG_MOE) {
        asm volatile("mov.u32 %0, %%globaltimer_lo;" : "=r"(a));
        if (lane == 0 && (bid & 15) == 0) asm volatile("st.relaxed.gpu.global.u32 [%0], %1;" :: "l"(g_hcnt + 8 + (bid >> 4)), "r"((a & ~15u) | 8u | (bid >> 4)) : "memory");
        #pragma unroll 1
        for (unsigned int spin = 0; spin < (1u << 22) && __any_sync(0xffffffffu, b == 0u); spin++) {
          __nanosleep(200);
          asm volatile("ld.relaxed.gpu.global.u32 %0, [%1];" : "=r"(b) : "l"(g_hcnt + 8 + min(lane, 6)) : "memory");
        }
        a = RANK ? __popc(__ballot_sync(0xffffffffu, b < __shfl_sync(0xffffffffu, b, bid >> 4)) & 127u) * 16 + (bid & 15) : bid;
      }
      if (lane == 0) {
        sts_u32(sbase + AT_SBAR + 408, a);
        mbar_arrive(sbase + AT_SBAR + 336);
        b = 0u;
        if (bid < AT_NFULL) {
          unsigned int* tm = g_hcnt + 32 * (1 + (bid >> 4)) + 8;
          mbar_wait(sbase + AT_SBAR + 312, 1);
          asm volatile("mov.u32 %0, %%globaltimer_lo;" : "=r"(a));
          asm volatile("red.relaxed.gpu.global.max.u32 [%0], %1;" :: "l"(tm), "r"(a) : "memory");
          __nanosleep(AL_SLEEP);
          asm volatile("ld.relaxed.gpu.global.u32 %0, [%1];" : "=r"(b) : "l"(tm) : "memory");
          b -= a;
        }
        sts_u32(sbase + AT_SBAR + 412, b < AL_MAX ? b * 13 / 8 : 0u);
        mbar_arrive(sbase + AT_SBAR + 320);
      }
      named_bar_sync(15, 32);
    }
    const int tb = __shfl_sync(0xffffffffu, tail_tile(sbase), 0);
    TAIL_SETUP
    if (wi == 3) {
      mbar_wait(bar_full + 344, 0);
      float a = g_scal[lane], b = g_scal[32 + lane];
      #pragma unroll
      for (int i = 0; i < 3; i++) {
        const uint4 v = *reinterpret_cast<const uint4*>(g_col + nt * 1536 + i * 512 + lane * 16);
        sts_u32x4(sbase + OG_SCOL + i * 512 + lane * 16, v.x, v.y, v.z, v.w);
      }
      #pragma unroll
      for (int o = 16; o > 0; o >>= 1) { a += __shfl_xor_sync(0xffffffffu, a, o); b += __shfl_xor_sync(0xffffffffu, b, o); }
      if (lane == 0) sts_f32x2(sbase + OG_SMISC, a, b);
      const uint64_t pol = policy_evict_first();
      #pragma unroll 1
      for (int r = lane >> 4; r < 128; r += 4) {
        __nanosleep(X_PACE);
        if (X_PACE2) __nanosleep(X_PACE2);
        #pragma unroll
        for (int j = 0; j < 4; j += 2)
          asm volatile("cp.async.cg.shared.global.L2::cache_hint [%0], [%1], 16, %2;" :: "r"(sbase + OG_XSLOT + (lane & 8) * 2048 + (r + j) * 128 + (((lane ^ (r + j)) & 7) << 4)),
                       "l"(x + (size_t)(m0 + r + j) * T_D + n0 + (lane & 15) * 8), "l"(pol) : "memory");
      }
      asm volatile("cp.async.wait_all;" ::: "memory");
      __syncwarp();
      if (lane == 0) mbar_arrive(bar_col);
    } else if (wi == 2) {
      if (elect_one()) {
        const uint32_t b_free = bar_full + (bid < AT_NFULL ? 80 : 160);
        mbar_wait(b_free, 1);
        #pragma unroll 1
        for (unsigned int i = 0; i < (1u << 20) && ld_acquire(&g_hcnt[32 * (1 + (tb >> 3)) + 4 + ((tb >> 1) & 3)]) == 0u; i++) __nanosleep(POLL_NS);
        TL_MARK2(23, true);
        fence_proxy_async_global();
        TL_MARK2(4, true);
        mbar_expect_tx(bar_full + 272, 32768);
        bulk_load_hint(sbase + OG_PSLOT, g_pre + tb * 2048, 32768, bar_full + 272, policy_evict_first());
      }
      named_bar_sync(14, 32);
      if (has_moe) {
        mbar_wait(bar_full + 96, 1); mbar_wait(bar_full + 304, 0);
        const uint64_t pol = policy_evict_first();
        #pragma unroll 1
        for (int r = 0; r < 32; r++) {
          __nanosleep(WD_PACE);
          #pragma unroll
          for (int j = 0; j < 2; j++)
            asm volatile("cp.async.cg.shared.global.L2::cache_hint [%0], [%1], 16, %2;" :: "r"(sbase + OG_SWD + (4 * j + (lane >> 3)) * 4096 + r * 128 + (((lane ^ r) & 7) << 4)),
                         "l"((const uint8_t*)w_down + (size_t)bid * 65536 + r * 2048 + j * 512 + lane * 16), "l"(pol) : "memory");
        }
        asm volatile("cp.async.wait_all;" ::: "memory");
        __syncwarp();
        if (lane == 0) mbar_arrive(bar_wd);
      }
    }
    const uint4 wrv = ldg_nc_v4(w_r + threadIdx.x * 8);
    mbar_wait(bar_end, 0);
    if (threadIdx.x == 96) XT(10);
    TL_MARK2(22, lane == 0);
    if (wi == 0) {
      uint32_t k1 = 0u, k2 = 0u;
      #pragma unroll 1
      for (unsigned int spin = 0; spin < (1u << 22) && __any_sync(0xffffffffu, k1 == 0u); spin++) asm volatile("ld.relaxed.gpu.global.u32 %0, [%1];" : "=r"(k1) : "l"(g_key + lane) : "memory");
      TL_MARK2(28, lane == 0);
      warp_top2(k1, k2);
      if (lane == 0) {
        const uint32_t r1 = 0xffffu - (k1 & 0xffffu), r2 = 0xffffu - (k2 & 0xffffu);
        sts_u32x4(sbase + OG_SMISC + 64, r1, r2, (r1 >> 7) * 2, (r2 >> 7) * 2 + ((r1 >> 7) == (r2 >> 7)));
        mbar_arrive(bar_sel);
      }
    } else if (wi < 3) {
          mbar_wait(bar_key, 0);
          const uint4 kk = lds_u32x4(sbase + OG_SSTAT + 1024 + lane * 16);
          uint32_t k1 = max(kk.x, kk.y), k2 = min(kk.x, kk.y);
          k2 = max(max(k2, min(kk.z, kk.w)), min(k1, max(kk.z, kk.w))); k1 = max(k1, max(kk.z, kk.w));
          warp_top2(k1, k2);
          if (wi == 1) {
            if (lane == 0) {
              if (nt == (mt & 7)) st_relaxed2(g_key + mt * 2, k1, k2);
              sts_u32x2(sbase + OG_SMISC + 96, (~k1 >> 4) & 7u, (~k2 >> 4) & 7u);
              mbar_arrive(bar_full + 352);
            }
            TL_MARK2(27, lane == 0);
          } else {
            const uint32_t r = (~((lane & 16) ? k2 : k1)) & 127u, ch = lane & 15;
            const uint2 st = lds_u32x2(sbase + OG_SSTAT + r * 8);
            const uint4 xc = lds_u32x4(sbase + OG_XSLOT + (ch >> 3) * 16384 + r * 128 + (((ch ^ r) & 7) << 4));
            const uint4 c1 = lds_u32x4(sbase + OG_SCOL + 768 + ch * 16), sh = lds_u32x4(sbase + OG_SCOL + 1024 + ch * 16);
            const float inr = __uint_as_float(st.y);
            float* dst = reinterpret_cast<float*>(g_cand + (mt * 2 + (lane >> 4)) * 256 + nt * 16 + ch);
            st_tagged4(dst + 512, __uint_as_float(ln_mod2(xc.x, st.x, inr, c1.x, sh.x)), __uint_as_float(ln_mod2(xc.y, st.x, inr, c1.y, sh.y)),
                       __uint_as_float(ln_mod2(xc.z, st.x, inr, c1.z, sh.z)), __uint_as_float(ln_mod2(xc.w, st.x, inr, c1.w, sh.w)));
            st_tagged4(dst, __uint_as_float(xc.x), __uint_as_float(xc.y), __uint_as_float(xc.z), __uint_as_float(xc.w));
          }
    }
    mbar_wait(bar_sel, 0);
    const uint4 sel = lds_u32x4(sbase + OG_SMISC + 64);
    const int sel0 = (int)sel.x, sel1 = (int)sel.y;
    {
      const float* src0 = reinterpret_cast<const float*>(g_cand + sel.z * 256 + 128 + threadIdx.x);
      const float* src1 = reinterpret_cast<const float*>(g_cand + sel.w * 256 + 128 + threadIdx.x);
      float4 h0, h1;
      #pragma unroll 1
      for (unsigned int spin = 0; spin < (1u << 20); spin++) { h0 = ld_tagged4(src0); h1 = ld_tagged4(src1); if (__all_sync(0xffffffffu, tagged4(h0) & tagged4(h1))) break; }
      sts_f32x4(sbase + OG_SH2 + threadIdx.x * 16, h0.x, h0.y, h0.z, h0.w);
      sts_f32x4(sbase + OG_SH2 + 2048 + threadIdx.x * 16, h1.x, h1.y, h1.z, h1.w);
      __syncwarp();
      if (lane == 0) mbar_arrive(bar_h2);
      TL_MARK2(12, lane == 0);
      if (bid >> 6) h0 = h1;
      float v[8], wr[8];
      unpack8(make_uint4(__float_as_uint(h0.x), __float_as_uint(h0.y), __float_as_uint(h0.z), __float_as_uint(h0.w)), v); unpack8(wrv, wr);
      float r = 0.f;
      #pragma unroll
      for (int i = 0; i < 8; i++) r = fmaf(v[i], wr[i], r);
      #pragma unroll
      for (int o = 16; o > 0; o >>= 1) r += __shfl_xor_sync(0xffffffffu, r, o);
      if (lane == 0) sts_f32(sbase + OG_SMISC + 192 + wi * 4, r);
    }
    mbar_wait(bar_out, 0);
    {
      const uint2 cg = lds_u32x2(sbase + OG_SMISC + 96);
      #pragma unroll
      for (int i = 0; i < 4; i++) {
        const int r = (i < 2 ? cg.x : cg.y) * 16 + (i & 1) * 8 + (threadIdx.x >> 4), ch = threadIdx.x & 15;
        if (m0 + r != sel0 && m0 + r != sel1)
          *reinterpret_cast<uint4*>(out + (size_t)(m0 + r) * T_D + n0 + ch * 8) =
              lds_u32x4(sbase + OG_OSLOT + (ch >> 3) * 16384 + r * 128 + (((ch & 7) ^ (r & 7)) << 4));
      }
    }
    if (bid == 0 && threadIdx.x < 68) *reinterpret_cast<uint4*>(g_hcnt + 32 * (threadIdx.x >> 2) + 4 * (threadIdx.x & 3)) = make_uint4(0u, 0u, 0u, 0u);
    if (threadIdx.x < 64) g_modpart[bid * 64 + threadIdx.x] = 0.f;
    {
      const int tk = bid >> 6, c0 = (bid & 63) * 16;
      const uint32_t gb2 = *reinterpret_cast<const uint32_t*>(g_col + (c0 >> 7) * 1536 + 512 + 768 + ((c0 & 127) + (threadIdx.x & 14)) * 2);
      const uint32_t* xp = reinterpret_cast<const uint32_t*>(g_cand + (tk ? sel.w : sel.z) * 256) + ((c0 + (threadIdx.x & 14)) >> 1);
      uint32_t x2 = 0u;
      #pragma unroll 1
      for (unsigned int spin = 0; spin < (1u << 20) && __any_sync(0xffffffffu, x2 == 0u); spin++) asm volatile("ld.relaxed.gpu.global.u32 %0, [%1];" : "=r"(x2) : "l"(xp) : "memory");
      const float* src = g_ypart + (size_t)((threadIdx.x >> 2) * 2 + tk) * T_D + c0 + (threadIdx.x & 3) * 4;
      const bool four = threadIdx.x < (OG_MOE - 96) * 4;
      named_bar_sync(10, 128);
      const uint4 rp = lds_u32x4(sbase + OG_SMISC + 192);
      const float rs = rbf(sigmoid_f(rbf((__uint_as_float(rp.x) + __uint_as_float(rp.y)) + (__uint_as_float(rp.z) + __uint_as_float(rp.w)))));
      const uint32_t h2p = lds_u32(sbase + OG_SH2 + tk * 2048 + (c0 + (threadIdx.x & 14)) * 2);
      const float fh = (lane & 1) ? bfhi(h2p) : bflo(h2p), fz = rbf(fh * 0.0f), fx = (lane & 1) ? bfhi(x2) : bflo(x2), fg = (lane & 1) ? bfhi(gb2) : bflo(gb2);
      bf16* dst = out + (size_t)(tk ? sel1 : sel0) * T_D + c0 + threadIdx.x;
      if (threadIdx.x == 0) hint_wait(CNT_Y, (uint32_t)(OG_MOE - Y_SLACK));
      named_bar_sync(10, 128);
      float4 p0, p1, p2, p3;
      #pragma unroll 1
      for (unsigned int spin = 0; spin < (1u << 20); spin++) {
        p0 = ld_tagged4(src); p1 = ld_tagged4(src + 64 * T_D); p2 = ld_tagged4(src + 128 * T_D); p3 = ld_tagged4(four ? src + 192 * T_D : src);
        if (__all_sync(0xffffffffu, tagged4(p0) & tagged4(p1) & tagged4(p2) & tagged4(p3))) break;
      }
      if (four) { p2.x += p3.x; p2.y += p3.y; p2.z += p3.z; p2.w += p3.w; }
      p0.x = (p0.x + p1.x) + p2.x; p0.y = (p0.y + p1.y) + p2.y; p0.z = (p0.z + p1.z) + p2.z; p0.w = (p0.w + p1.w) + p2.w;
      #pragma unroll
      for (int o = 4; o <= 16; o <<= 1) {
        p0.x += __shfl_xor_sync(0xffffffffu, p0.x, o); p0.y += __shfl_xor_sync(0xffffffffu, p0.y, o);
        p0.z += __shfl_xor_sync(0xffffffffu, p0.z, o); p0.w += __shfl_xor_sync(0xffffffffu, p0.w, o);
      }
      if (lane < 4) sts_f32x4(sbase + OG_SFIN + (threadIdx.x >> 5) * 64 + lane * 16, p0.x, p0.y, p0.z, p0.w);
      named_bar_sync(10, 128);
      TL_MARK2(21, threadIdx.x == 0);
      if (threadIdx.x < 16) {
        const uint32_t ya = sbase + OG_SFIN + threadIdx.x * 4;
        float y = (lds_f32(ya) + lds_f32(ya + 64)) + (lds_f32(ya + 128) + lds_f32(ya + 192));
        y = rbf(y);
        y = rbf(y * rs);
        *dst = __float2bfloat16_rn(fx + rbf(fg * rbf(fh + rbf(fz + y))));
      }
    }
    if (threadIdx.x == 0) XT(11);
    TL_END(4, threadIdx.x == 0);
}

__device__ __forceinline__ void load_pre(uint4* pre, uint32_t sbase, uint32_t buf, int t2) {
  mbar_wait(sbase + AT_SBAR + 272, 0);
  #pragma unroll
  for (int i = 0; i < 8; i++) pre[i] = lds_u32x4(sbase + buf + i * 4096 + t2 * 16);
}
__device__ __forceinline__ void tail_consumer(uint32_t bid, uint32_t sbase, const CUtensorMap* tmOut, const uint4 (&pre)[8], int cwg, const bf16* __restrict__ w_gate, const bf16* __restrict__ w_up) {
    const uint32_t c0 = clock_lo();
    mbar_wait(sbase + AT_SBAR + 320, 0);
    const uint2 td = lds_u32x2(sbase + AT_SBAR + 408);
    const int tb = __shfl_sync(0xffffffffu, (int)td.x, 0);
    TAIL_SETUP
    const int tid = threadIdx.x & 127, t2 = threadIdx.x - 128;
    const int warp = tid >> 5, lane = tid & 31, w8 = t2 >> 5;
    const uint32_t dbase = (sbase & 0x3FFFFu) >> 4;
    const uint32_t a_base = dbase + ((cwg * 8192) >> 4) + (1u << 16);
    const uint32_t b_base = dbase + (16384 >> 4) + (512u << 16);
    TL_MARK2(25, threadIdx.x == 128);
    const uint64_t pol = policy_evict_first();
    const bf16* pw = ((lane & 16) ? w_up : w_gate) + (size_t)(w8 * 128 + (lane & 3) * 4) * T_F + (has_moe ? bid : 0) * 32 + ((lane >> 2) & 3) * 8;
    uint4 wv[32];
    float acc[64];
    #pragma unroll
    for (int i = 0; i < 8; i++) {
      acc[8 * i] = bflo(pre[i].x); acc[8 * i + 1] = bfhi(pre[i].x); acc[8 * i + 2] = bflo(pre[i].y); acc[8 * i + 3] = bfhi(pre[i].y);
      acc[8 * i + 4] = bflo(pre[i].z); acc[8 * i + 5] = bfhi(pre[i].z); acc[8 * i + 6] = bflo(pre[i].w); acc[8 * i + 7] = bfhi(pre[i].w);
    }
    if (lane == 0) mbar_arrive(bar_full + 304);
    while (__any_sync(0xffffffffu, clock_lo() - c0 < td.y)) {}
    uint32_t stage = OG_POS % OG_ST;
    {
      uint32_t phase = (OG_POS / OG_ST) & 1, prev = 12;
      int kb = 0;
      #pragma unroll
      for (int g = 0; g <= OG_NG; g++) {
        const int end = g == OG_NG ? 64 - og_pre(tb) : LD_FIRST + g * OG_GRP + LD_STAG * cwg;
        #pragma unroll 1
        do {
          mbar_wait(bar_full + 8 * stage, phase);
          if (OG_STAG > 0 && g == OG_NG && cwg == 1 && kb == end - OG_STAG) named_bar_sync(7, 256);
          const uint32_t a_lo = a_base + stage * (OG_STAGE >> 4), b_lo = b_base + stage * (OG_STAGE >> 4);
          wgmma_fence();
          wgmma_m64n128k16_ss_tb<0, 0>(acc, a_lo, b_lo, 1);
          wgmma_m64n128k16_ss_tb<2, 128>(acc, a_lo, b_lo, 1);
          wgmma_m64n128k16_ss_tb<4, 256>(acc, a_lo, b_lo, 1);
          wgmma_m64n128k16_ss_tb<6, 384>(acc, a_lo, b_lo, 1);
          wgmma_commit();
          if (OG_STAG > 0 && g == OG_NG && cwg == 0 && kb == end - 1) named_bar_arrive(7, 256);
          wgmma_wait<1>();
          if (tid == 0) mbar_arrive(bar_empty + 8 * prev);
          prev = stage;
          if (++stage == OG_ST) { stage = 0; phase ^= 1; }
        } while (++kb < end);
        #pragma unroll
        for (int j = 4 * g; j < 4 * g + 4 && j < 32; j++) wv[j] = ldg_stream_v4(pw + (size_t)(16 * (j >> 2) + (j & 3)) * T_F, pol);
      }
    }
    mbar_wait(bar_col, 0);
    if (__builtin_expect(!has_moe, 0)) {
      load_pre(wv, sbase, AT_SQ, t2);
    }
    wgmma_wait<0>();
    fence_regs(acc);
    if (__builtin_expect(!has_moe, 0)) {
      #pragma unroll
      for (int i = 0; i < 8; i++) {
        acc[8 * i] += bflo(wv[i].x); acc[8 * i + 1] += bfhi(wv[i].x); acc[8 * i + 2] += bflo(wv[i].y); acc[8 * i + 3] += bfhi(wv[i].y);
        acc[8 * i + 4] += bflo(wv[i].z); acc[8 * i + 5] += bfhi(wv[i].z); acc[8 * i + 6] += bflo(wv[i].w); acc[8 * i + 7] += bfhi(wv[i].w);
      }
    }
    if (tid == 0) mbar_arrive(bar_end);
    TL_MARK2(9, lane == 0);
    const int q2 = 2 * (lane & 3);
    const uint32_t frag = (64 * cwg + 16 * warp + (lane & 7) + 8 * ((lane >> 3) & 1)) * 128;
    const int fsw = lane & 7, fhi = lane >> 4;
    {
      float dl[4] = {0.f, 0.f, 0.f, 0.f}, da[4] = {0.f, 0.f, 0.f, 0.f}, db[4] = {0.f, 0.f, 0.f, 0.f};
      const uint32_t tb2 = sbase + OG_SCOL + (lane & 8) * 32 + (lane & 3) * 8, g = lane >> 2;
      const uint32_t msk = (g == 1 || g == 2) ? 0xffffffffu : 0u, one = g == 0 ? 0x3F803F80u : 0u;
      uint32_t xr[8][4];
      #pragma unroll
      for (int hf = 0; hf < 2; hf++) {
        uint32_t ga[8];
        uint2 cw[4];
        #pragma unroll
        for (int i = 0; i < 4; i++) {
          ldmatrix_x4(sbase + OG_XSLOT + hf * 16384 + frag + (((2 * i + fhi) ^ fsw) << 4), xr[4 * hf + i][0], xr[4 * hf + i][1], xr[4 * hf + i][2], xr[4 * hf + i][3]);
          ga[2 * i] = lds_u32(sbase + OG_SCOL + 512 + (64 * hf + 16 * i + q2) * 2); ga[2 * i + 1] = lds_u32(sbase + OG_SCOL + 512 + (64 * hf + 16 * i + 8 + q2) * 2);
          cw[i] = lds_u32x2(tb2 + (8 * hf + 2 * i) * 16);
        }
        #pragma unroll
        for (int i = 0; i < 4; i++) {
          uint32_t* x4 = xr[4 * hf + i];
          #pragma unroll
          for (int e = 0; e < 4; e++) x4[e] = badd2(x4[e], bmul2(ga[2 * i + (e >> 1)], pack_bf16(acc[32 * hf + 8 * i + 2 * e], acc[32 * hf + 8 * i + 2 * e + 1])));
          mma_bf16(dl, x4[0], x4[1], x4[2], x4[3], (cw[i].x & msk) | one, (cw[i].y & msk) | one);
          mma_bf16(da, x4[0], x4[1], x4[2], x4[3], x4[0], x4[2]);
          mma_bf16(db, x4[0], x4[1], x4[2], x4[3], x4[1], x4[3]);
        }
      }
      {
        const int dsrc = (lane & ~3) + (g >> 1);
        const float qa = __shfl_sync(0xffffffffu, (g & 1) ? da[1] : da[0], dsrc), qb = __shfl_sync(0xffffffffu, (g & 1) ? db[3] : db[2], dsrc);
        const float e0 = __shfl_xor_sync(0xffffffffu, (lane & 1) ? dl[0] : dl[2], 1), e1 = __shfl_xor_sync(0xffffffffu, dl[3], 1);
        if ((lane & 3) < 2) {
          const bool hi = lane & 1;
          st_tagged4(reinterpret_cast<float*>(g_part1 + ((mt * 8 + w8) * 8 + nt) * 16 + g + (hi ? 8 : 0)),
                     hi ? e0 : dl[0], hi ? qb : qa, hi ? e1 + dl[2] : dl[1] + e0, 1.0f);
        }
      }
      #pragma unroll
      for (int i = 0; i < 8; i++) stmatrix_x4(sbase + OG_XSLOT + (i >> 2) * 16384 + frag + (((2 * (i & 3) + fhi) ^ fsw) << 4), xr[i][0], xr[i][1], xr[i][2], xr[i][3]);
    }
    TL_MARK2(10, lane == 0);
    uint4 wd[16];
    if (has_moe) mbar_wait(bar_wd, 0);
    #pragma unroll
    for (int i = 0; i < 16; i++) wd[i] = lds_u32x4(sbase + (cwg ? (stage + (stage & 1)) * OG_STAGE : OG_SWD) + warp * 8192 + (i >> 3) * 4096 + (i & 6) * 512 + (i & 1) * 128 + (lane & 3) * 256 + (((lane >> 2) ^ (2 * (lane & 3) + (i & 1))) << 4));
    {
      const float* src = reinterpret_cast<const float*>(g_part1 + ((mt * 8 + w8) * 8 + (lane & 1) * 4) * 16 + (lane >> 1));
      float4 v, v1, v2, v3;
      #pragma unroll 1
      for (unsigned int spin = 0; spin < (1u << 22); spin++) {
        v = ld_tagged4(src); v1 = ld_tagged4(src + 64); v2 = ld_tagged4(src + 128); v3 = ld_tagged4(src + 192);
        if (__all_sync(0xffffffffu, tagged4(v) & tagged4(v1) & tagged4(v2) & tagged4(v3))) break;
        __nanosleep(100);
      }
      __syncwarp();
      TL_MARK2(26, lane == 0);
      v.x = (v.x + v1.x) + (v2.x + v3.x); v.y = (v.y + v1.y) + (v2.y + v3.y); v.z = (v.z + v1.z) + (v2.z + v3.z);
      v.x += __shfl_xor_sync(0xffffffffu, v.x, 1); v.y += __shfl_xor_sync(0xffffffffu, v.y, 1); v.z += __shfl_xor_sync(0xffffffffu, v.z, 1);
      const float mean = v.x * (1.0f / T_D);
      const float var = fmaxf(fmaf(-mean, mean, v.y * (1.0f / T_D)), 0.f);
      const uint32_t mb2 = pack_bf16(mean, mean);
      const float inv = rcp_approx(rbf(sqrt_approx(rbf(rbf(var) + 1e-05f))));
      {
        const float2 sc = lds_f32x2(sbase + OG_SMISC);
        const uint32_t key = rank_key(rbf(fmaf(fmaf(-bflo(mb2), sc.x, v.z), inv, sc.y)), m0 + 16 * w8 + (lane >> 1));
        mbar_wait(bar_end, 0);
        if (lane & 1) sts_u32(sbase + OG_SSTAT + 1024 + (16 * w8 + (lane >> 1)) * 4, key);
        else sts_u32x2(sbase + OG_SSTAT + (16 * w8 + (lane >> 1)) * 8, mb2, __float_as_uint(inv));
        __syncwarp();
        if (lane == 0) mbar_arrive(bar_key);
      }
      const uint32_t ih = pack_bf16(inv, inv), il = pack_bf16(inv - bflo(ih), inv - bflo(ih));
      const uint32_t mba = __shfl_sync(0xffffffffu, mb2, 2 * (lane >> 2)), mbb = __shfl_sync(0xffffffffu, mb2, 2 * (lane >> 2) + 16);
      const uint32_t iha = __shfl_sync(0xffffffffu, ih, 2 * (lane >> 2)), ihb = __shfl_sync(0xffffffffu, ih, 2 * (lane >> 2) + 16);
      const uint32_t ila = __shfl_sync(0xffffffffu, il, 2 * (lane >> 2)), ilb = __shfl_sync(0xffffffffu, il, 2 * (lane >> 2) + 16);
      #pragma unroll 1
      for (int J0 = 0; J0 < 16; J0 += 4) {
        uint32_t xr[2][4], cv[4][3];
        #pragma unroll
        for (int i = 0; i < 2; i++) {
          ldmatrix_x4(sbase + OG_XSLOT + (J0 >> 3) * 16384 + frag + ((((J0 & 7) + 2 * i + fhi) ^ fsw) << 4), xr[i][0], xr[i][1], xr[i][2], xr[i][3]);
          #pragma unroll
          for (int h = 0; h < 2; h++)
            #pragma unroll
            for (int k = 0; k < 3; k++) cv[2 * i + h][k] = lds_u32(sbase + OG_SCOL + 768 + 256 * k + (8 * (J0 + 2 * i + h) + q2) * 2);
        }
        #pragma unroll
        for (int i = 0; i < 2; i++) {
          #pragma unroll
          for (int h = 0; h < 2; h++) {
            xr[i][2 * h] = out2(xr[i][2 * h], mba, iha, ila, cv[2 * i + h][0], cv[2 * i + h][1], cv[2 * i + h][2]);
            xr[i][2 * h + 1] = out2(xr[i][2 * h + 1], mbb, ihb, ilb, cv[2 * i + h][0], cv[2 * i + h][1], cv[2 * i + h][2]);
          }
          stmatrix_x4(sbase + OG_OSLOT + (J0 >> 3) * 16384 + frag + ((((J0 & 7) + 2 * i + fhi) ^ fsw) << 4), xr[i][0], xr[i][1], xr[i][2], xr[i][3]);
        }
      }
      fence_proxy_async();
      mbar_wait(bar_full + 352, 0);
      const uint2 cg = lds_u32x2(sbase + OG_SMISC + 96);
      __syncwarp();
      if (elect_one()) {
        mbar_arrive(bar_out);
        if (cg.x != w8 && cg.y != w8) {
          asm volatile("cp.async.bulk.tensor.2d.global.shared::cta.bulk_group [%0, {%2, %3}], [%1];" :: "l"(tmOut), "r"(sbase + OG_OSLOT + w8 * 2048), "r"(n0), "r"(m0 + 16 * w8) : "memory");
          asm volatile("cp.async.bulk.tensor.2d.global.shared::cta.bulk_group [%0, {%2, %3}], [%1];" :: "l"(tmOut), "r"(sbase + OG_OSLOT + 16384 + w8 * 2048), "r"(n0 + 64), "r"(m0 + 16 * w8) : "memory");
          bulk_commit();
        }
      }
      TL_MARK2(24, lane == 0);
    }
    if (has_moe) mbar_wait(bar_h2, 0);
    TL_MARK2(13, lane == 0);
    if (has_moe) {
      const GemvSel sel = gemv_sel(lane);
      {
        float d[4][4];
        #pragma unroll
        for (int c = 0; c < 4; c++) { d[c][0] = 0.f; d[c][1] = 0.f; d[c][2] = 0.f; d[c][3] = 0.f; }
        #pragma unroll
        for (int st = 0; st < 8; st++) {
          const uint2 hb = lds_u32x2(sbase + OG_SH2 + ((lane >> 2) & 1) * 2048 + (w8 * 128 + st * 16 + (lane & 3) * 4) * 2);
          #pragma unroll
          for (int j = 0; j < 4; j++) mma_bf16(d[j], wv[4 * st + j].x, wv[4 * st + j].y, wv[4 * st + j].z, wv[4 * st + j].w, GEMV_B0(j, hb, sel), GEMV_B1(j, hb, sel));
        }
        #pragma unroll
        for (int e = 0; e < 4; e++) d[0][e] = (d[0][e] + d[1][e]) + (d[2][e] + d[3][e]);
        const float4 r = gemv_out(d[0], lane);
        sts_f32x4(sbase + OG_SRED + w8 * 512 + (((lane >> 4) * 2 + (lane & 1)) * 32 + ((lane >> 2) & 3) * 8 + (lane & 2) * 2) * 4, r.x, r.y, r.z, r.w);
      }
      named_bar_sync(9, 256);
      if (t2 < 64) {
        float gp[8], up[8];
        #pragma unroll
        for (int w = 0; w < 8; w++) { gp[w] = lds_f32(sbase + OG_SRED + w * 512 + t2 * 4); up[w] = lds_f32(sbase + OG_SRED + w * 512 + 256 + t2 * 4); }
        const float gs = ((gp[0] + gp[1]) + (gp[2] + gp[3])) + ((gp[4] + gp[5]) + (gp[6] + gp[7]));
        const float us = ((up[0] + up[1]) + (up[2] + up[3])) + ((up[4] + up[5]) + (up[6] + up[7]));
        asm volatile("st.shared.u16 [%0], %1;" :: "r"(sbase + OG_SGU + ((t2 & ~15) + ((t2 >> 1) & 3) * 4 + ((t2 >> 3) & 1) * 2 + (t2 & 1)) * 2), "h"((uint16_t)pack_bf16(silu_bf(rbf(gs)) * rbf(us), 0.f)) : "memory");
      }
      named_bar_sync(9, 256);
      TL_MARK2(20, threadIdx.x == 128);
      float d[4][4];
      #pragma unroll
      for (int c = 0; c < 4; c++) { d[c][0] = 0.f; d[c][1] = 0.f; d[c][2] = 0.f; d[c][3] = 0.f; }
      #pragma unroll
      for (int st = 0; st < 2; st++) {
        const uint2 g = lds_u32x2(sbase + OG_SGU + ((lane >> 2) & 1) * 64 + st * 32 + (lane & 3) * 8);
        #pragma unroll
        for (int j = 0; j < 4; j++) {
          const uint32_t b0 = GEMV_B0(j, g, sel), b1 = GEMV_B1(j, g, sel);
          mma_bf16(d[j & 1], wd[4 * st + j].x, wd[4 * st + j].y, wd[4 * st + j].z, wd[4 * st + j].w, b0, b1);
          mma_bf16(d[2 + (j & 1)], wd[8 + 4 * st + j].x, wd[8 + 4 * st + j].y, wd[8 + 4 * st + j].z, wd[8 + 4 * st + j].w, b0, b1);
        }
      }
      #pragma unroll
      for (int e = 0; e < 4; e++) { d[0][e] += d[1][e]; d[2][e] += d[3][e]; }
      const float4 y0 = gemv_out(d[0], lane), y1 = gemv_out(d[2], lane);
      float* yp = g_ypart + (size_t)(bid * 2 + (lane & 1)) * T_D + w8 * 128 + (lane >> 2) * 8 + (lane & 2) * 2;
      st_tagged4(yp, y0.x, y0.y, y0.z, y0.w);
      st_tagged4(yp + 64, y1.x, y1.y, y1.z, y1.w);
      named_bar_sync(9, 256);
      if (t2 == 0) hint_arrive(CNT_Y);
    }
    bulk_wait_read<0>();
    TL_MARK2(14, threadIdx.x == 128);
    TL_CLK(4, 1, threadIdx.x == 128);
}

__device__ __forceinline__ int help_njobs(uint32_t bid) { return bid < 128 ? OG_JOBS : 16 - OG_JOBS; }
__device__ __forceinline__ int help_job(uint32_t bid, int i) { return (i < OG_JOBS ? 16 * i + (bid >> 7) * 2 : 112 + (i - OG_JOBS) * 2) + (bid & 3) * 4; }
__device__ __noinline__ void store_warp(uint32_t bid, uint32_t sbase, const CUtensorMap* tmO, int item0, int n_items) {
  if (elect_one()) {
    const uint32_t bars = sbase + AT_SBAR, b_q0 = bars + 80, b_ob = bars + 96, b_ordy = bars + 104, b_acq = bars + 264;
    const unsigned int* cnt = g_hcnt + 32 * (1 + OG_MT(124)) + 2;
    #pragma unroll 1
    for (int q = 0; q < 4 * n_items; q++) {
      const int item = item0 + (q >> 2) * 128, h = (q >> 1) & 1, w = q & 1;
      const bool last = (q >> 2) == n_items - 1;
      if (q == 4 * n_items - 4) { mbar_wait(bars + 288, 0); red_release_add(&g_hcnt[1], 1u); }
      mbar_wait(b_ordy + 8 * (q & 3), q >> 2);
      store_o(tmO, (h ? (last ? sbase + AT_SQ + 32768 : sbase + 2 * 32768) : sbase + AT_SQ) + w * 8192, (item >> 4) * 2 + h, (item & 15) * 128 + w * 64);
      if (w) {
        bulk_wait_read<0>();
        mbar_arrive(h ? b_ob : b_q0);
        bulk_wait<0>();
        fence_proxy_async_global();
        asm volatile("fence.acq_rel.gpu;" ::: "memory");
        hint_arrive(&g_hcnt[32 * (1 + (item & 15)) + 2 + (item >> 7)]);
        if (!h && item < 128) hint_arrive(&g_hcnt[2]);
        if (q == 5) { const int tb = tail_tile(sbase); cnt = g_hcnt + 32 * (1 + OG_MT(tb)) + 2; spin_until(cnt, 16u); mbar_arrive(b_acq); }
      }
    }
    if (n_items == 1) {
      #pragma unroll 1
      for (int i = 0; i < help_njobs(bid); i++) {
        mbar_wait(b_acq + 16, i & 1);
        TL_MARK2(23, i == OG_JOBS - 1);
        red_release_add(&g_hcnt[32 * (1 + (help_job(bid, i) >> 3)) + 4 + ((help_job(bid, i) >> 1) & 3)], 1u);
        TL_MARK2(4, i == OG_JOBS - 1);
        if (i == PRE_X - 1) { spin_until(&g_hcnt[1], 132u); mbar_arrive(b_acq + 32); }
      }
    }
    if (bid < 128) {
      if (n_items == 1) { spin_until(cnt, 16u); mbar_arrive(b_acq); }
      spin_until(&g_hcnt[0], 128u); spin_until(cnt + 1, 16u); mbar_arrive(b_acq + 80);
    }
  }
}

__device__ __forceinline__ uint32_t role_of_sm(uint32_t sm) {
  const uint32_t t = sm >> 1, u = t - 32u, d = (u * 37u) >> 8;
  return (t < 32u ? ((t + 7u) & 7u) * 16u + (t >> 3) * 2u : t < 60u ? (u - 7u * d) * 16u + (4u + d) * 2u : t < 62u ? 2u * t + 8u : 2u * t - 4u) + (sm & 1u);
}
__global__ void __launch_bounds__(384, 1)
fused_kernel(const __grid_constant__ CUtensorMap tmH, const __grid_constant__ CUtensorMap tmW, const __grid_constant__ CUtensorMap tmK,
            const __grid_constant__ CUtensorMap tmV, const __grid_constant__ CUtensorMap tmO, const __grid_constant__ CUtensorMap tmOl, const __grid_constant__ CUtensorMap tmWo,
            const __grid_constant__ CUtensorMap tmD, const __grid_constant__ CUtensorMap tmOut, const __grid_constant__ CUtensorMap tmM, uint32_t zero,
            const uint8_t* __restrict__ pf_wo, const bf16* __restrict__ kc, const bf16* __restrict__ vc,
            const bf16* __restrict__ x, const bf16* __restrict__ cvec, const bf16* __restrict__ w_mod, const bf16* __restrict__ w_r,
            const bf16* __restrict__ w_gate, const bf16* __restrict__ w_up, const bf16* __restrict__ w_down, bf16* __restrict__ out)
{
  uint32_t bid, nsm;
  asm volatile("mov.u32 %0, %%smid;" : "=r"(bid));
  asm volatile("mov.u32 %0, %%nsmid;" : "=r"(nsm));
  bid = __shfl_sync(0xffffffffu, nsm == 132u ? role_of_sm(bid) : blockIdx.x, 0);
  extern __shared__ __align__(1024) uint8_t smem_raw[];
  const uint32_t sbase = smem_u32(smem_raw);
  const uint32_t bars = sbase + AT_SBAR;
  const uint32_t b_full = bars, b_empty = bars + 40;
  const uint32_t b_q0 = bars + 80, b_q1 = bars + 88;
  const uint32_t b_ob = bars + 96;
  const uint32_t b_ordy = bars + 104;
  const uint32_t b_pin = bars + 136;
  const uint32_t b_head = bars + 144;
  const uint32_t b_go = bars + 152;
  const uint32_t b_x = bars + 160;
  const int wg = __shfl_sync(0xffffffffu, threadIdx.x >> 7, 0);
  const bool single = bid >= AT_NFULL;
  const int item0 = __shfl_sync(0xffffffffu, bid < 128 ? (int)bid : (int)bid + 124, 0), n_items = __shfl_sync(0xffffffffu, single ? 1 : 2, 0);
  TL_START(3);
  if (threadIdx.x == 0) {
    if (sbase & 1023u) __trap();
    for (int i = 0; i < 5; i++) { mbar_init(b_full + 8 * i, 1); mbar_init(b_empty + 8 * i, 2); }
    mbar_init(b_q0, 1); mbar_init(b_q1, 8); mbar_init(b_ob, 1);
    for (int i = 0; i < 4; i++) mbar_init(b_ordy + 8 * i, 4);
    mbar_init(b_pin, 1); mbar_init(b_head, bid < 128 ? 8 : 1); mbar_init(b_go, 1); mbar_init(b_x, 1);
    mbar_init(bars + 168, 2); mbar_init(bars + 176, 1); mbar_init(bars + 184, 8); mbar_init(bars + 192, 2);
    mbar_init(bars + 200, 8); mbar_init(bars + 208, 4); mbar_init(bars + 216, 1); mbar_init(bars + 264, 1); mbar_init(bars + 272, 1); mbar_init(bars + 280, 8); mbar_init(bars + 288, 1); mbar_init(bars + 296, 1); mbar_init(bars + 304, 8); mbar_init(bars + 312, 1); mbar_init(bars + 320, 1); mbar_init(bars + 328, 1); mbar_init(bars + 336, 1); mbar_init(bars + 344, 1); mbar_init(bars + 352, 1);
    sts_u32(bars + 400, bid);
    fence_mbar_init();
  }

  if (wg == 0) {
    reg_dealloc<AT_PREG>();
    if (threadIdx.x < 32) { __syncwarp(); named_bar_arrive(6, 384); }
    if (threadIdx.x >= 64) {
      named_bar_sync(6, 384);
      if (bid < 128) {
        named_bar_sync(threadIdx.x >= 96 ? 8 : 9, 288);
        if ((threadIdx.x & 31) == 0) red_release_add(&g_hcnt[32 * (1 + (bid >> 3)) + (threadIdx.x >= 96)], 1u);
        TL_MARK2(11, threadIdx.x == 64);
      }
      if (bid < 128) {
        mbar_wait(MOD_AT, 0);
        mod_rest(bid, sbase + OG_SCOL, b_q1, threadIdx.x - 64, cvec, w_mod, w_r);
      }
    } else if (threadIdx.x >= 32) {
      named_bar_sync(6, 384);
      store_warp(bid, sbase, &tmO, item0, n_items);
      __syncwarp();
    } else {
     if (elect_one()) {
      const uint64_t pol = policy_evict_first();
      if (bid < 128) {
        mbar_expect_tx(b_x, 32768);
        if (X_DLY) { const uint32_t c0 = clock_lo(); while (clock_lo() - c0 < X_DLY) {} }
        bulk_load_hint(sbase + 4 * 32768, x + (size_t)bid * 16 * T_D, 32768, b_x, pol);
      }
      prefetch_tmap(&tmW); prefetch_tmap(&tmM); prefetch_tmap(&tmH); prefetch_tmap(&tmWo); prefetch_tmap(&tmOl);
      {
        const uint32_t c0 = clock_lo();
        while (clock_lo() - c0 < W_DLY) {}
        if (bid < 128 && (bid & 15) >= 4 * H_SPLIT) {
          mbar_expect_tx(bars + 328, 32768);
          tma_load_2d_hint(sbase + 3 * 32768, &tmM, (bid & 31) * 64, (bid >> 5) * 256, bars + 328, pol);
        }
        while (clock_lo() - c0 < W_DLY + W_FIRST) {}
      }
      uint32_t slot = 0, ph = 1;
      #pragma unroll 1
      for (int it = 0; it < n_items; it++) {
        const int item = item0 + it * 128, hp = item >> 4, qt = item & 15;
        const bool first = it == 0;
        #pragma unroll 1
        for (int j = 0; j < T_D / 64; j++) {
          const uint32_t sl = ring_slot(qp_pos(j, it)), fb = b_full + 8 * sl;
          mbar_wait(b_empty + 8 * sl, ring_par(qp_pos(j, it)) ^ ((j >> 2) & 1) ^ 1);
          if (first && j == 3) mbar_wait(b_head, 0);
          mbar_expect_tx(fb, 49152);
          tma_load_3d_hint(sbase + sl * 32768, &tmW, j * 64, hp * 4, fb, pol);
          if (first && j < PRE_B) {
            if (j == PRE_B - 1) {
              spin_until(&g_hcnt[32 * (1 + qt)], 8u);
              TL_MARK2(16, true);
              fence_proxy_async_global();
              #pragma unroll 1
              for (int i = 0; i < PRE_B; i++) tma_load_2d(sbase + AT_SQ + i * 16384, &tmH, i * 64, qt * 128, b_full + 8 * i);
              mbar_arrive(b_go);
            }
          } else {
            if (first && j == 4 * H_SPLIT) { spin_until(&g_hcnt[32 * (1 + qt) + 1], 8u); fence_proxy_async_global(); }
            if (!first && (j == 0 || j == 2)) mbar_wait(j ? b_q1 : b_q0, 0);
            tma_load_2d_hint(sbase + AT_SQ + (j & 3) * 16384, &tmH, j * 64, qt * 128, fb, first ? pol_normal() : pol);
          }
        }
        #pragma unroll 1
        for (int j = 0; j < 4 * AT_NBLK; j++) {
          const bool isv = (j > 0 && !(j & 1)) || j == 4 * AT_NBLK - 1;
          const int row = hp * 2 * T_SEQ + (isv ? (j - 1) >> 1 : (j + 1) >> 1) * 128;
          const uint32_t fb = b_full + 8 * slot;
          mbar_wait(b_empty + 8 * slot, ph);
          if (!first && j == 3) mbar_wait(b_ob, 0);
          if (j == 4 && it == n_items - 1) mbar_arrive(bars + 288);
          if ((j == AL_P || j == RK_P) && it == 1) mbar_arrive(bars + 312);
          mbar_expect_tx(fb, 32768);
          tma_load_3d_hint(sbase + slot * 32768, isv ? &tmV : &tmK, row, 0, fb, pol);
          if (it == 1 && isv && j >= 2 * WO_LATE && j < 2 * WO_LATE + 32 && bid < OG_NKB)
            l2_prefetch_bulk(pf_wo + (size_t)own_kb(bid, og_pre(0)) * 131072 + ((j >> 1) - WO_LATE) * 8192, 8192);
          if (++slot == 5) { slot = 0; ph ^= 1; }
        }
      }
      if (__builtin_expect(single, 0)) {
        spin_until(&g_hcnt[2], 128u);
        fence_proxy_async_global();
        const int nj = OG_HSUM + (help_njobs(bid) - OG_JOBS) * OG_PRE2;
        int ji = 0, job = help_job(bid, 0), kk = 0;
        #pragma unroll 1
        for (int j = 0; j < nj; j++) {
          const uint32_t sl = ring_slot(qp_pos(j, 1)), fb = b_full + 8 * sl;
          mbar_wait(b_empty + 8 * sl, ring_par(qp_pos(j, 1)) ^ ((j >> 2) & 1) ^ 1);
          mbar_expect_tx(fb, 49152);
          tma_load_3d_hint(sbase + sl * 32768, &tmWo, pre_kb(kk) * 64, OG_NT(job) * 2, fb, pol_normal());
          tma_load_3d_hint(sbase + sl * 32768 + 16384, &tmWo, pre_kb(kk) * 64, OG_NT(job) * 2 + 2, fb, pol_normal());
          if (j == 0 || j == 2) mbar_wait(j ? b_ob : b_q0, 0);
          tma_load_2d_hint(sbase + AT_SQ + (j & 3) * 16384, &tmOl, pre_kb(kk) * 64, OG_MT(job) * 128, fb, pol);
          if (++kk == og_pre(job)) { kk = 0; job = help_job(bid, ++ji); }
        }
      }
      if (bid < 128) {
        if (single) mbar_wait(b_x, 1);
        tail_producer(bid, sbase, 0, pol, &tmOl, &tmWo, &tmD);
      }
     }
    }
    named_bar_sync(12 + (threadIdx.x >> 5), 32);
    if (bid < 128) tail_exchange(bid, sbase, w_down, w_r, x, out);
  } else {
    if (bid < 128) head_phase(bid, sbase + AT_SQ + 49152, sbase + 4 * 32768, b_x, b_go, b_head, threadIdx.x - 128, zero, cvec, w_mod);
    else { named_bar_sync(6, 384); if (threadIdx.x == 128) mbar_arrive(b_head); }
    TL_MARK2(0, threadIdx.x == 128);
    reg_alloc<AT_CREG>();
    const int cwg = wg - 1;
    const int tid = threadIdx.x & 127;
    const int warp = tid >> 5, lane = tid & 31;
    const uint32_t dbase = (sbase & 0x3FFFFu) >> 4;
    const uint32_t k_base = dbase + (1u << 16);
    const uint32_t v_base = dbase + (1024u << 16);
    const uint32_t w_base = dbase + (512u << 16);
    const uint32_t q_lo = dbase + ((AT_SQ + cwg * 8192) >> 4) + (1u << 16);
    const uint32_t frag = cwg * 8192 + (16 * warp + (lane & 7) + 8 * ((lane >> 3) & 1)) * 128;
    if (cwg == 1) named_bar_arrive(1, 256);
    bool raw = false;
    uint4 pre[8];
    #pragma unroll 1
    for (int it = 0; it < n_items; it++) {
      const bool more = it + 1 < n_items;
      constexpr int nkb = T_D / 64;
      const int ta = __shfl_sync(0xffffffffu, 4 * it, 0);
      float acc[128];
      {
        FS(2 * it, 0);
        #pragma unroll
        for (int i = 0; i < 128; i++) asm volatile("" : "=f"(acc[i]));
        {
          const uint32_t slot = ring_slot(ta), b_lo = w_base + slot * 2048;
          mbar_wait(b_full + 8 * slot, ring_par(ta));
          wgmma_fence();
          wgmma_m64n256k16_ss_tb<0, 0>(acc, q_lo, b_lo, 0);
          wgmma_m64n256k16_ss_tb<2, 128>(acc, q_lo, b_lo, 1);
          wgmma_m64n256k16_ss_tb<4, 256>(acc, q_lo, b_lo, 1);
          wgmma_m64n256k16_ss_tb<6, 384>(acc, q_lo, b_lo, 1);
          wgmma_commit();
        }
        #pragma unroll 1
        for (int j = 1; j < nkb; j++) {
          const uint32_t slot = ring_slot(qp_pos(j, ta >> 2));
          mbar_wait(b_full + 8 * slot, ring_par(qp_pos(j, ta >> 2)) ^ ((j >> 2) & 1));
          if (QP_STAG > 0 && cwg == 1 && j == nkb - QP_STAG) named_bar_sync(7, 256);
          const uint32_t a_lo = q_lo + (j & 3) * 1024, b_lo = w_base + slot * 2048;
          wgmma_fence();
          wgmma_m64n256k16_ss_tb<0, 0>(acc, a_lo, b_lo, 1);
          wgmma_m64n256k16_ss_tb<2, 128>(acc, a_lo, b_lo, 1);
          wgmma_m64n256k16_ss_tb<4, 256>(acc, a_lo, b_lo, 1);
          wgmma_m64n256k16_ss_tb<6, 384>(acc, a_lo, b_lo, 1);
          wgmma_commit();
          if (QP_STAG > 0 && cwg == 0 && j == nkb - 1) named_bar_arrive(7, 256);
          if (j > 0) {
            wgmma_wait<1>();
            if (tid == 0) mbar_arrive(b_empty + 8 * ring_slot(qp_pos(j - 1, ta >> 2)));
          }
        }
        wgmma_wait<0>();
        fence_regs(acc);
        FS(2 * it, 1);
        TL_MARK2(29, threadIdx.x == 256 && it == 0);
        if (tid == 0) mbar_arrive(b_empty + 24);
      }
      float o[64], s[64];
      uint32_t p[32], q[32];
      #pragma unroll
      for (int i = 0; i < 32; i++) q[i] = pack_bf16(acc[2 * i] * AT_C, acc[2 * i + 1] * AT_C);
      zero_regs(s);
      const uint32_t sq = sbase + AT_SQ + cwg * 8192;
      float mc0, mc1, al0 = 1.0f, al1 = 1.0f, l0 = 0.f, l1 = 0.f, lp0 = 0.f, lp1 = 0.f;
      bool redo0 = false;
      FS(2 * it, 2);
      mbar_wait(b_full + 8 * ring_slot(ta), ring_par(ta));
      named_bar_sync(1 + cwg, 256);
      FS(2 * it, 3);
      issue_qk(s, q, k_base + ring_slot(ta) * 2048);
      pass_turn(cwg);
      bool ready = mbar_test(b_full + 8 * ring_slot(ta + 1), ring_par(ta + 1)) & mbar_test(b_full + 8 * ring_slot(ta + 2), ring_par(ta + 2));
      stage_q<16>(acc, AT_C, sbase + AT_SQ + frag, lane);
      wgmma_wait<0>();
      fence_regs(s);
      if (tid == 0) mbar_arrive(b_empty + 8 * ring_slot(ta));
      mc0 = 0.f; mc1 = 0.f;
      if (!raw) {
        raw = softmax_mode(s, mc0, mc1);
        if (__builtin_expect(!raw, 0)) softmax_sub(s, mc0, mc1);
      }
      softmax_exp<0, 64>(s);
      #pragma unroll
      for (int J = 0; J < 16; J += 2)
        stmatrix_x4(sbase + AT_SQ + frag + (J >> 3) * 16384 + ((((J & 7) + (lane >> 4)) ^ (lane & 7)) << 4), q[2 * J], q[2 * J + 1], q[2 * J + 2], q[2 * J + 3]);
      pack_p(p, s);
      zero_regs(o);
      FS(2 * it, 4);
      uint32_t ks = ring_slot(ta + 1), vs = ring_slot(ta + 2), kp = ring_par(ta + 1), vp = ring_par(ta + 2);
      auto finish_head = [&]() {
        FS(2 * it, 5);
        redo0 = finish_l(lp0, lp1);
        if (!redo0) stage_o(o, lp0, lp1, sbase + AT_SQ + frag, lane);
        FS(2 * it + 1, 4);
      };
      if (!ready) { mbar_wait(b_full + 8 * ks, kp); mbar_wait(b_full + 8 * vs, vp); }
      #pragma unroll 1
      for (int n = 1; n < 2 * AT_NBLK; n++) {
        named_bar_sync(1 + cwg, 256);
        issue_qk(s, q, k_base + ks * 2048);
        if (n == AT_NBLK + 1) finish_head();
        issue_pv(o, p, v_base + vs * 2048, (n & 15) != 1);
        pass_turn(cwg);
        wgmma_wait<1>();
        fence_regs(s);
        if (tid == 0) mbar_arrive(b_empty + 8 * ks);
        if (__builtin_expect(!raw || (uint32_t)(n - (AT_NBLK - 1)) <= 2u, 0)) {
          if (n == AT_NBLK + 1 && !redo0) {
            fence_proxy_async();
            __syncwarp();
            if (lane == 0) mbar_arrive(b_ordy + 8 * cwg);
          }
          if (n == AT_NBLK - 1) {
            #pragma unroll
            for (int J = 0; J < 16; J += 2)
              ldmatrix_x4(sbase + AT_SQ + 32768 + frag + (J >> 3) * 16384 + ((((J & 7) + (lane >> 4)) ^ (lane & 7)) << 4), q[2 * J], q[2 * J + 1], q[2 * J + 2], q[2 * J + 3]);
          }
          if (!raw) {
            const float m0 = mc0, m1 = mc1;
            const bool ok = softmax_mode(s, mc0, mc1);
            if (n == AT_NBLK) raw = ok;
            else {
              mc0 = mc0 - AT_HEAD > m0 ? mc0 : m0; mc1 = mc1 - AT_HEAD > m1 ? mc1 : m1;
              al0 = ex2_approx(m0 - mc0); al1 = ex2_approx(m1 - mc1);
            }
            if (!raw) softmax_sub(s, mc0, mc1);
          }
        }
        softmax_exp<0, AT_SPLIT>(s);
        add_rowsum(p, l0, l1);
        if (tid == 0) {
          uint32_t dep = zero & __float_as_uint(l0) & __float_as_uint(l1);
          #pragma unroll
          for (int i = AT_SPLIT - AT_PIN - PINB; i < AT_SPLIT - PINB; i += 2) dep &= __float_as_uint(s[i]) & __float_as_uint(s[i + 1]);
          mbar_arrive(b_pin + dep);
        }
        wgmma_wait<0>();
        fence_regs(o);
        if (tid == 0) mbar_arrive(b_empty + 8 * vs);
        ks += 2; if (ks >= 5) { ks -= 5; kp ^= 1; }
        vs += 2; if (vs >= 5) { vs -= 5; vp ^= 1; }
        ready = mbar_test(b_full + 8 * ks, kp) & mbar_test(b_full + 8 * vs, vp);
        softmax_exp<AT_SPLIT, 64>(s);
        pack_p(p, s);
        if (n == AT_NBLK) { lp0 = l0; lp1 = l1; l0 = 0.f; l1 = 0.f; }
        if (__builtin_expect(!raw || !ready, 0)) {
        if (!raw && __any_sync(0xffffffffu, al0 != 1.0f || al1 != 1.0f)) {
          rescale_o(o, al0, al1);
          l0 *= al0; l1 *= al1;
          al0 = 1.0f; al1 = 1.0f;
        }
        if (!ready && n < 2 * AT_NBLK - 1) {
          mbar_wait(b_full + 8 * ks, kp);
          mbar_wait(b_full + 8 * vs, vp);
        }
        }
      }
      FS(2 * it + 1, 5);
      const uint32_t vl = ring_slot(ta + 63);
      vs = ring_slot(ta + 62);
      const uint32_t ob = more ? sbase + vs * 32768 : sbase + AT_SQ + 32768;
      mbar_wait(b_full + 8 * vl, ring_par(ta + 63));
      issue_pv(o, p, v_base + vl * 2048, 1);
      block_end(zero, b_pin);
      add_rowsum(p, l0, l1);
      const bool overflow = finish_l(l0, l1);
      if (!overflow && lane == 0) mbar_arrive(b_q1);
      #pragma unroll
      for (int i = 0; i < 8; i++) asm volatile("mov.b64 {%0, %1}, 0;\nmov.b64 {%2, %3}, 0;" : "=r"(pre[i].x), "=r"(pre[i].y), "=r"(pre[i].z), "=r"(pre[i].w));
      const bool want_pre = !more && bid < OG_MOE, got_pre = want_pre && __all_sync(0xffffffffu, mbar_test(bars + 272, 0));
      if (got_pre) load_pre(pre, sbase, AT_SQ, threadIdx.x - 128);
      mbar_wait(b_empty + 8 * vs, ring_par(ta + 62));
      wgmma_wait<0>();
      fence_regs(o);
      if (tid == 0) mbar_arrive(b_empty + 8 * vl);
      FS(2 * it + 1, 6);
      if (overflow) {
        attn_rows_exact(lds_u32(bars + 400), sq + 32768, ob + cwg * 8192, 4 * ta + 1, kc, vc);
        __syncwarp();
        if (lane == 0) mbar_arrive(b_q1);
      } else stage_o(o, l0, l1, ob + frag, lane);
      if (redo0) attn_rows_exact(lds_u32(bars + 400), sq, sq, 4 * ta, kc, vc);
      fence_proxy_async();
      __syncwarp();
      if (lane == 0) {
        if (redo0) mbar_arrive(b_ordy + 8 * cwg);
        mbar_arrive(b_ordy + 16 + 8 * cwg);
      }
      if (want_pre && !got_pre) load_pre(pre, sbase, AT_SQ, threadIdx.x - 128);
      if (redo0 || overflow) raw = false;
      named_bar_sync(3 + cwg, 128);
      FS(2 * it + 1, 7);
    }
    if (cwg == 0) named_bar_arrive(1, 256);
    if (__builtin_expect(single, 0)) {
      float acc[128];
      uint32_t j = 0, pk[64];
      #pragma unroll
      for (int i = 0; i < 64; i++) asm volatile("" : "=f"(acc[2 * i]), "=f"(acc[2 * i + 1]), "=r"(pk[i]));
      uint4* dst = g_pre;
      int left = 0;
      auto put = [&](bool last) {
        #pragma unroll
        for (int i = 0; i < PUT_N; i++) dst[i * 256] = make_uint4(pk[4 * i], pk[4 * i + 1], pk[4 * i + 2], pk[4 * i + 3]);
        dst += PUT_N * 256;
        #pragma unroll
        for (int i = 0; i < 64 - 4 * PUT_N; i++) asm volatile("mov.b32 %0, %1;" : "=r"(pk[i]) : "r"(pk[i + 4 * PUT_N]));
        __syncwarp();
        if (last && lane == 0) mbar_arrive(bars + 280);
      };
      #pragma unroll 1
      for (int ji = 0; ji < help_njobs(bid); ji++) {
        const int nk = og_pre(help_job(bid, ji));
        #pragma unroll 1
        for (int kk = 0; kk < nk; kk++, j++) {
          const uint32_t slot = ring_slot(qp_pos(j, 1));
          mbar_wait(b_full + 8 * slot, ring_par(qp_pos(j, 1)) ^ ((j >> 2) & 1));
          if (H_STAG > 0 && cwg == 1 && kk == nk - H_STAG) named_bar_sync(7, 256);
          const uint32_t a_lo = q_lo + (j & 3) * 1024, b_lo = w_base + slot * 2048;
          wgmma_fence();
          wgmma_m64n256k16_ss_tb<0, 0>(acc, a_lo, b_lo, kk != 0);
          wgmma_m64n256k16_ss_tb<2, 128>(acc, a_lo, b_lo, 1);
          wgmma_m64n256k16_ss_tb<4, 256>(acc, a_lo, b_lo, 1);
          wgmma_m64n256k16_ss_tb<6, 384>(acc, a_lo, b_lo, 1);
          wgmma_commit();
          if (H_STAG > 0 && cwg == 0 && kk == nk - 1) named_bar_arrive(7, 256);
          wgmma_wait<1>();
          if (kk > 0 && tid == 0) mbar_arrive(b_empty + 8 * ring_slot(qp_pos(j - 1, 1)));
          #pragma unroll 1
          for (int i = ji == OG_JOBS ? 0 : 16 / PUT_N - 1; i < 16 / PUT_N && left > 0; i++) put(--left == 0);
        }
        wgmma_wait<0>();
        fence_regs(acc);
        if (tid == 0) mbar_arrive(b_empty + 8 * ring_slot(qp_pos(j - 1, 1)));
        #pragma unroll
        for (int i = 0; i < 64; i++) pk[i] = pack_bf16(acc[2 * i], acc[2 * i + 1]);
        left = 16 / PUT_N;
        if (ji == PRE_X) mbar_wait(bars + 296, 0);
        dst = g_pre + help_job(bid, ji) * 2048 + threadIdx.x - 128;
      }
      #pragma unroll
      for (int i = 0; i < 16; i++) dst[i * 256] = make_uint4(pk[4 * i], pk[4 * i + 1], pk[4 * i + 2], pk[4 * i + 3]);
      __syncwarp();
      if (lane == 0) mbar_arrive(bars + 280);
      named_bar_sync(5, 256);
      if (threadIdx.x == 128) {
        #pragma unroll 1
        for (int i = 0; i < 5; i++) {
          constexpr int n = OG_HSUM;
          const int used = i == 3 ? 0 : (n + 3 - (i == 4 ? 3 : i)) / 4;
          if ((used ^ (i < 4)) & 1) {
            mbar_arrive(b_full + 8 * ring_slot(4 + i));
            mbar_arrive(b_empty + 8 * ring_slot(4 + i)); mbar_arrive(b_empty + 8 * ring_slot(4 + i));
          }
        }
        mbar_arrive(b_x);
      }
      named_bar_sync(5, 256);
      #pragma unroll
      for (int i = 0; i < 8; i++) pre[i] = make_uint4(0u, 0u, 0u, 0u);
    }
    TL_CLK(3, 1, threadIdx.x == 128);
    TL_CTA(1, threadIdx.x == 256);
    TL_END(3, tid == 0);
    TL_MARK2(19, tid == 0 && !single);
    if (bid < 128) {
      tail_consumer(bid, sbase, &tmOut, pre, cwg, w_gate, w_up);
    }
  }
}

typedef CUresult (*PFN_encodeTiled)(CUtensorMap*, CUtensorMapDataType, cuuint32_t, void*, const cuuint64_t*, const cuuint64_t*,
                                    const cuuint32_t*, const cuuint32_t*, CUtensorMapInterleave, CUtensorMapSwizzle,
                                    CUtensorMapL2promotion, CUtensorMapFloatOOBfill);

CUtensorMap make_map_2d(PFN_encodeTiled enc, const void* ptr, uint64_t inner, uint64_t outer, uint64_t stride_bytes, uint32_t box_inner, uint32_t box_outer) {
  CUtensorMap m;
  cuuint64_t gd[2] = {inner, outer}; cuuint64_t gs[1] = {stride_bytes};
  cuuint32_t bx[2] = {box_inner, box_outer}; cuuint32_t es[2] = {1, 1};
  enc(&m, CU_TENSOR_MAP_DATA_TYPE_BFLOAT16, 2, const_cast<void*>(ptr), gd, gs, bx, es, CU_TENSOR_MAP_INTERLEAVE_NONE,
      CU_TENSOR_MAP_SWIZZLE_128B, CU_TENSOR_MAP_L2_PROMOTION_L2_128B, CU_TENSOR_MAP_FLOAT_OOB_FILL_NONE);
  return m;
}

CUtensorMap make_map_3d(PFN_encodeTiled enc, const void* ptr, uint64_t cols, uint64_t rows, uint32_t box_rows, uint32_t chunks) {
  CUtensorMap m;
  cuuint64_t gd[3] = {64, rows, cols / 64}; cuuint64_t gs[2] = {cols * 2, 128};
  cuuint32_t bx[3] = {64, box_rows, chunks}; cuuint32_t es[3] = {1, 1, 1};
  enc(&m, CU_TENSOR_MAP_DATA_TYPE_BFLOAT16, 3, const_cast<void*>(ptr), gd, gs, bx, es, CU_TENSOR_MAP_INTERLEAVE_NONE,
      CU_TENSOR_MAP_SWIZZLE_128B, CU_TENSOR_MAP_L2_PROMOTION_L2_128B, CU_TENSOR_MAP_FLOAT_OOB_FILL_NONE);
  return m;
}

}

extern "C" void kernel_launch(void* const* d_in, const int* in_sizes, int n_in, void* d_out, int out_size) {
  const bf16* x      = (const bf16*)d_in[0];
  const bf16* kc     = (const bf16*)d_in[1];
  const bf16* vc     = (const bf16*)d_in[2];
  const bf16* wq     = (const bf16*)d_in[3];
  const bf16* wo     = (const bf16*)d_in[4];
  const bf16* w_r    = (const bf16*)d_in[6];
  const bf16* w_gate = (const bf16*)d_in[7];
  const bf16* w_up   = (const bf16*)d_in[8];
  const bf16* w_down = (const bf16*)d_in[9];
  const bf16* cvec   = (const bf16*)d_in[10];
  const bf16* w_mod  = (const bf16*)d_in[11];
  bf16* out = (bf16*)d_out;

  static PFN_encodeTiled enc = nullptr;
  static void *p_h = nullptr, *p_o = nullptr;
  if (!enc) {
    void* fn = nullptr; cudaDriverEntryPointQueryResult qres;
    cudaGetDriverEntryPoint("cuTensorMapEncodeTiled", &fn, cudaEnableDefault, &qres);
    enc = (PFN_encodeTiled)fn;
    cudaGetSymbolAddress(&p_h, g_pre);
    p_h = (uint4*)p_h + 16 * PRE_X * 2048;
    cudaGetSymbolAddress(&p_o, g_o);
    cudaFuncSetAttribute(fused_kernel, cudaFuncAttributeMaxDynamicSharedMemorySize, (int)AT_SMEM);
  }
  const CUtensorMap tm_h   = make_map_2d(enc, p_h, T_D, T_SEQ, T_D * 2, 64, 128);
  const CUtensorMap tm_wq  = make_map_3d(enc, wq, T_DQKV, T_D, 64, 4);
  const CUtensorMap tm_k   = make_map_3d(enc, kc, T_DH, (uint64_t)T_NH * T_SEQ, 128, 2);
  const CUtensorMap tm_v   = make_map_3d(enc, vc, T_DH, (uint64_t)T_NH * T_SEQ, 128, 2);
  const CUtensorMap tm_ost = make_map_2d(enc, p_o, T_DQKV, T_SEQ, T_DQKV * 2, 64, 64);
  const CUtensorMap tm_old = make_map_2d(enc, p_o, T_DQKV, T_SEQ, T_DQKV * 2, 64, 128);
  const CUtensorMap tm_wo  = make_map_3d(enc, wo, T_D, T_DQKV, 64, 2);
  const CUtensorMap tm_d   = make_map_3d(enc, w_down, T_D, T_F, 32, 8);

  const CUtensorMap tm_m   = make_map_2d(enc, w_mod, 6 * T_D, T_D, 6 * T_D * 2, 64, 256);
  const CUtensorMap tm_out = make_map_2d(enc, out, T_D, T_SEQ, T_D * 2, 64, 16);

  fused_kernel<<<132, 384, AT_SMEM, cudaStreamPerThread>>>(tm_h, tm_wq, tm_k, tm_v, tm_ost, tm_old, tm_wo, tm_d, tm_out, tm_m, 0u, (const uint8_t*)wo, kc, vc, x, cvec, w_mod,
             w_r, w_gate, w_up, w_down, out);
}
```

```cpp
#include <cuda_runtime.h>
#include <cuda_bf16.h>
#include <cuda.h>
#include <stdint.h>

namespace {

typedef __nv_bfloat16 bf16;

constexpr int T_SEQ = 2048, T_D = 1024, T_NH = 32, T_DH = 128, T_DQKV = 4096, T_F = 3584;

#define PRE_X 2
__device__ __align__(1024) uint4 g_pre[(16 * PRE_X + 128) * 2048];
#define g_h (reinterpret_cast<bf16*>(g_pre + 16 * PRE_X * 2048))
__device__ __align__(1024) bf16 g_o[T_SEQ * T_DQKV];
__device__ __align__(16) uint8_t g_col[8 * 1536];
__device__ __align__(16) float g_scal[64];
__device__ __align__(16) unsigned int g_hcnt[17 * 32];
__device__ __align__(128) float g_modpart[4 * 2 * T_D];
struct __align__(2048) TailMail {
  float4 part1[T_SEQ * 8];
  uint32_t key[256];
  uint4 cand[16 * 2 * 2 * 128];
  uint32_t cnt[32];
  float ypart[(T_F / 32) * 2 * T_D];
};
__device__ TailMail g_mail;
#define g_part1 g_mail.part1
#define g_key g_mail.key
#define g_cand g_mail.cand
#define CNT_Y (g_mail.cnt)
#define g_ypart g_mail.ypart

__device__ __forceinline__ uint32_t smem_u32(const void* p) { return (uint32_t)__cvta_generic_to_shared(p); }
__device__ __forceinline__ void mbar_init(uint32_t bar, uint32_t cnt) { asm volatile("mbarrier.init.shared::cta.b64 [%0], %1;" :: "r"(bar), "r"(cnt)); }
__device__ __forceinline__ void mbar_expect_tx(uint32_t bar, uint32_t bytes) { asm volatile("mbarrier.arrive.expect_tx.shared::cta.b64 _, [%0], %1;" :: "r"(bar), "r"(bytes) : "memory"); }
__device__ __forceinline__ void mbar_arrive(uint32_t bar) { asm volatile("mbarrier.arrive.shared::cta.b64 _, [%0];" :: "r"(bar) : "memory"); }
__device__ __forceinline__ void mbar_wait(uint32_t bar, uint32_t parity) {
  asm volatile("{\n.reg .pred p;\nLAB_WAIT:\nmbarrier.try_wait.parity.shared::cta.b64 p, [%0], %1;\n@!p bra LAB_WAIT;\n}\n" :: "r"(bar), "r"(parity) : "memory");
}
__device__ __forceinline__ bool mbar_test(uint32_t bar, uint32_t parity) {
  uint32_t r; asm volatile("{\n.reg .pred p;\nmbarrier.test_wait.parity.shared::cta.b64 p, [%1], %2;\nselp.u32 %0, 1, 0, p;\n}\n" : "=r"(r) : "r"(bar), "r"(parity) : "memory");
  return r != 0;
}
__device__ __forceinline__ void mbar_wait_long(uint32_t bar, uint32_t parity) {
  asm volatile("{\n.reg .pred p;\nLAB_WAIT:\nmbarrier.try_wait.parity.shared::cta.b64 p, [%0], %1, %2;\n@!p bra LAB_WAIT;\n}\n" :: "r"(bar), "r"(parity), "r"(100000) : "memory");
}
__device__ __forceinline__ uint32_t clock_lo() { uint32_t c; asm volatile("mov.u32 %0, %%clock;" : "=r"(c)); return c; }
__device__ __forceinline__ void fence_mbar_init() { asm volatile("fence.mbarrier_init.release.cluster;" ::: "memory"); }
__device__ __forceinline__ void tma_load_2d(uint32_t dst, const CUtensorMap* map, int c0, int c1, uint32_t bar) {
  asm volatile("cp.async.bulk.tensor.2d.shared::cluster.global.mbarrier::complete_tx::bytes [%0], [%1, {%3, %4}], [%2];"
    :: "r"(dst), "l"(map), "r"(bar), "r"(c0), "r"(c1) : "memory");
}
__device__ __forceinline__ uint64_t policy_evict_first() {
  uint64_t p; asm volatile("createpolicy.fractional.L2::evict_first.b64 %0, 1.0;" : "=l"(p)); return p;
}
__device__ __forceinline__ void tma_load_2d_hint(uint32_t dst, const CUtensorMap* map, int c0, int c1, uint32_t bar, uint64_t pol) {
  asm volatile("cp.async.bulk.tensor.2d.shared::cluster.global.mbarrier::complete_tx::bytes.L2::cache_hint [%0], [%1, {%3, %4}], [%2], %5;"
    :: "r"(dst), "l"(map), "r"(bar), "r"(c0), "r"(c1), "l"(pol) : "memory");
}
__device__ __forceinline__ void tma_load_3d_hint(uint32_t dst, const CUtensorMap* map, int c1, int c2, uint32_t bar, uint64_t pol) {
  asm volatile("cp.async.bulk.tensor.3d.shared::cluster.global.mbarrier::complete_tx::bytes.L2::cache_hint [%0], [%1, {%3, %4, %5}], [%2], %6;"
    :: "r"(dst), "l"(map), "r"(bar), "n"(0), "r"(c1), "r"(c2), "l"(pol) : "memory");
}
__device__ __forceinline__ void tma_store_2d(const CUtensorMap* map, uint32_t src, int c0, int c1) {
  asm volatile("cp.async.bulk.tensor.2d.global.shared::cta.bulk_group [%0, {%2, %3}], [%1];" :: "l"(map), "r"(src), "r"(c0), "r"(c1) : "memory");
}
__device__ __forceinline__ void prefetch_tmap(const CUtensorMap* map) { asm volatile("prefetch.tensormap [%0];" :: "l"(map) : "memory"); }
__device__ __forceinline__ void l2_prefetch_bulk(const void* p, uint32_t bytes) {
  asm volatile("cp.async.bulk.prefetch.L2.global [%0], %1;" :: "l"(p), "r"(bytes) : "memory");
}
__device__ __forceinline__ void bulk_commit() { asm volatile("cp.async.bulk.commit_group;" ::: "memory"); }
template<int N> __device__ __forceinline__ void bulk_wait_read() { asm volatile("cp.async.bulk.wait_group.read %0;" :: "n"(N) : "memory"); }
template<int N> __device__ __forceinline__ void bulk_wait() { asm volatile("cp.async.bulk.wait_group %0;" :: "n"(N) : "memory"); }
__device__ __forceinline__ void named_bar_sync(int id, int nthreads) { asm volatile("bar.sync %0, %1;" :: "r"(id), "r"(nthreads) : "memory"); }
__device__ __forceinline__ void named_bar_arrive(int id, int nthreads) { asm volatile("bar.arrive %0, %1;" :: "r"(id), "r"(nthreads) : "memory"); }
__device__ __forceinline__ void pass_turn(int cwg) {
  asm volatile("{\n.reg .pred p;\nsetp.ne.u32 p, %0, 0;\n@p bar.arrive 1, 256;\n@!p bar.arrive 2, 256;\n}\n" :: "r"(cwg) : "memory");
}
__device__ __forceinline__ void wgmma_fence() { asm volatile("wgmma.fence.sync.aligned;" ::: "memory"); }
__device__ __forceinline__ void wgmma_commit() { asm volatile("wgmma.commit_group.sync.aligned;" ::: "memory"); }
template<int N> __device__ __forceinline__ void wgmma_wait() { asm volatile("wgmma.wait_group.sync.aligned %0;" :: "n"(N) : "memory"); }
template<int R> __device__ __forceinline__ void reg_alloc() { asm volatile("setmaxnreg.inc.sync.aligned.u32 %0;" :: "n"(R)); }
template<int R> __device__ __forceinline__ void reg_dealloc() { asm volatile("setmaxnreg.dec.sync.aligned.u32 %0;" :: "n"(R)); }
__device__ __forceinline__ bool elect_one() {
  uint32_t pred; asm volatile("{\n.reg .pred p;\nelect.sync _|p, 0xffffffff;\nselp.u32 %0, 1, 0, p;\n}\n" : "=r"(pred)); return pred != 0;
}
__device__ __forceinline__ uint32_t pack_bf16(float lo, float hi) {
  uint32_t r; asm("cvt.rn.bf16x2.f32 %0, %1, %2;" : "=r"(r) : "f"(hi), "f"(lo)); return r;
}
__device__ __forceinline__ void stmatrix_x4(uint32_t addr, uint32_t r0, uint32_t r1, uint32_t r2, uint32_t r3) {
  asm volatile("stmatrix.sync.aligned.m8n8.x4.shared.b16 [%0], {%1, %2, %3, %4};" :: "r"(addr), "r"(r0), "r"(r1), "r"(r2), "r"(r3) : "memory");
}
__device__ __forceinline__ void fence_proxy_async() { asm volatile("fence.proxy.async.shared::cta;" ::: "memory"); }
__device__ __forceinline__ float ex2_approx(float x) { float y; asm("ex2.approx.ftz.f32 %0, %1;" : "=f"(y) : "f"(x)); return y; }
template<int N> __device__ __forceinline__ void fence_regs(float (&r)[N]) {
  #pragma unroll
  for (int i = 0; i < N; i++) asm volatile("" : "+f"(r[i]) :: "memory");
}
template<int N> __device__ __forceinline__ void zero_regs(float (&r)[N]) {
  #pragma unroll
  for (int i = 0; i < N; i += 2) asm volatile("mov.b64 {%0, %1}, 0;" : "=f"(r[i]), "=f"(r[i + 1]));
}
__device__ __forceinline__ float rbf(float x) { return __uint_as_float(pack_bf16(0.f, x)); }
__device__ __forceinline__ float bflo(uint32_t v) { return __uint_as_float(v << 16); }
__device__ __forceinline__ float bfhi(uint32_t v) { return __uint_as_float(v & 0xffff0000u); }

#define XT(i) do {} while (0)
#define TL_START(k) do {} while (0)
#define TL_END(k, cond) do {} while (0)
#define TL_CTA(i, cond) do {} while (0)
#define FS(slot, k) do {} while (0)
#define TL_MARK2(k, cond) do {} while (0)
#define TL_CLK(k, i, cond) do {} while (0)

template <int OFFA, int OFFB>
__device__ __forceinline__ void wgmma_m64n256k16_ss_tb(float (&d)[128], uint32_t a_lo, uint32_t b_lo, int scaleD) {
  asm volatile("{\n.reg .pred p;\n.reg .b32 ta, tb;\n.reg .b64 da, db;\nsetp.ne.b32 p, %130, 0;\n"
    "add.u32 ta, %128, %131;\nadd.u32 tb, %129, %132;\n"
    "mov.b64 da, {ta, 0x40000040};\nmov.b64 db, {tb, 0x40000040};\n"
    "wgmma.mma_async.sync.aligned.m64n256k16.f32.bf16.bf16 "
    "{%0, %1, %2, %3, %4, %5, %6, %7, %8, %9, %10, %11, %12, %13, %14, %15, %16, %17, %18, %19, %20, %21, %22, %23, %24, %25, %26, %27, %28, %29, %30, %31, %32, %33, %34, %35, %36, %37, %38, %39, %40, %41, %42, %43, %44, %45, %46, %47, %48, %49, %50, %51, %52, %53, %54, %55, %56, %57, %58, %59, %60, %61, %62, %63, %64, %65, %66, %67, %68, %69, %70, %71, %72, %73, %74, %75, %76, %77, %78, %79, %80, %81, %82, %83, %84, %85, %86, %87, %88, %89, %90, %91, %92, %93, %94, %95, %96, %97, %98, %99, %100, %101, %102, %103, %104, %105, %106, %107, %108, %109, %110, %111, %112, %113, %114, %115, %116, %117, %118, %119, %120, %121, %122, %123, %124, %125, %126, %127}, "
    "da, db, p, 1, 1, 0, 1;\n}\n"
    : "+f"(d[0]), "+f"(d[1]), "+f"(d[2]), "+f"(d[3]), "+f"(d[4]), "+f"(d[5]), "+f"(d[6]), "+f"(d[7]), "+f"(d[8]), "+f"(d[9]), "+f"(d[10]), "+f"(d[11]), "+f"(d[12]), "+f"(d[13]), "+f"(d[14]), "+f"(d[15]), "+f"(d[16]), "+f"(d[17]), "+f"(d[18]), "+f"(d[19]), "+f"(d[20]), "+f"(d[21]), "+f"(d[22]), "+f"(d[23]), "+f"(d[24]), "+f"(d[25]), "+f"(d[26]), "+f"(d[27]), "+f"(d[28]), "+f"(d[29]), "+f"(d[30]), "+f"(d[31]), "+f"(d[32]), "+f"(d[33]), "+f"(d[34]), "+f"(d[35]), "+f"(d[36]), "+f"(d[37]), "+f"(d[38]), "+f"(d[39]), "+f"(d[40]), "+f"(d[41]), "+f"(d[42]), "+f"(d[43]), "+f"(d[44]), "+f"(d[45]), "+f"(d[46]), "+f"(d[47]), "+f"(d[48]), "+f"(d[49]), "+f"(d[50]), "+f"(d[51]), "+f"(d[52]), "+f"(d[53]), "+f"(d[54]), "+f"(d[55]), "+f"(d[56]), "+f"(d[57]), "+f"(d[58]), "+f"(d[59]), "+f"(d[60]), "+f"(d[61]), "+f"(d[62]), "+f"(d[63]), "+f"(d[64]), "+f"(d[65]), "+f"(d[66]), "+f"(d[67]), "+f"(d[68]), "+f"(d[69]), "+f"(d[70]), "+f"(d[71]), "+f"(d[72]), "+f"(d[73]), "+f"(d[74]), "+f"(d[75]), "+f"(d[76]), "+f"(d[77]), "+f"(d[78]), "+f"(d[79]), "+f"(d[80]), "+f"(d[81]), "+f"(d[82]), "+f"(d[83]), "+f"(d[84]), "+f"(d[85]), "+f"(d[86]), "+f"(d[87]), "+f"(d[88]), "+f"(d[89]), "+f"(d[90]), "+f"(d[91]), "+f"(d[92]), "+f"(d[93]), "+f"(d[94]), "+f"(d[95]), "+f"(d[96]), "+f"(d[97]), "+f"(d[98]), "+f"(d[99]), "+f"(d[100]), "+f"(d[101]), "+f"(d[102]), "+f"(d[103]), "+f"(d[104]), "+f"(d[105]), "+f"(d[106]), "+f"(d[107]), "+f"(d[108]), "+f"(d[109]), "+f"(d[110]), "+f"(d[111]), "+f"(d[112]), "+f"(d[113]), "+f"(d[114]), "+f"(d[115]), "+f"(d[116]), "+f"(d[117]), "+f"(d[118]), "+f"(d[119]), "+f"(d[120]), "+f"(d[121]), "+f"(d[122]), "+f"(d[123]), "+f"(d[124]), "+f"(d[125]), "+f"(d[126]), "+f"(d[127])
    : "r"(a_lo), "r"(b_lo), "r"(scaleD), "n"(OFFA), "n"(OFFB));
}

template <int OFFA, int OFFB>
__device__ __forceinline__ void wgmma_m64n128k16_ss_tb(float (&d)[64], uint32_t a_lo, uint32_t b_lo, int scaleD) {
  asm volatile("{\n.reg .pred p;\n.reg .b32 ta, tb;\n.reg .b64 da, db;\nsetp.ne.b32 p, %66, 0;\n"
    "add.u32 ta, %64, %67;\nadd.u32 tb, %65, %68;\n"
    "mov.b64 da, {ta, 0x40000040};\nmov.b64 db, {tb, 0x40000040};\n"
    "wgmma.mma_async.sync.aligned.m64n128k16.f32.bf16.bf16 "
    "{%0, %1, %2, %3, %4, %5, %6, %7, %8, %9, %10, %11, %12, %13, %14, %15, %16, %17, %18, %19, %20, %21, %22, %23, %24, %25, %26, %27, %28, %29, %30, %31, %32, %33, %34, %35, %36, %37, %38, %39, %40, %41, %42, %43, %44, %45, %46, %47, %48, %49, %50, %51, %52, %53, %54, %55, %56, %57, %58, %59, %60, %61, %62, %63}, "
    "da, db, p, 1, 1, 0, 1;\n}\n"
    : "+f"(d[0]), "+f"(d[1]), "+f"(d[2]), "+f"(d[3]), "+f"(d[4]), "+f"(d[5]), "+f"(d[6]), "+f"(d[7]), "+f"(d[8]), "+f"(d[9]), "+f"(d[10]), "+f"(d[11]), "+f"(d[12]), "+f"(d[13]), "+f"(d[14]), "+f"(d[15]), "+f"(d[16]), "+f"(d[17]), "+f"(d[18]), "+f"(d[19]), "+f"(d[20]), "+f"(d[21]), "+f"(d[22]), "+f"(d[23]), "+f"(d[24]), "+f"(d[25]), "+f"(d[26]), "+f"(d[27]), "+f"(d[28]), "+f"(d[29]), "+f"(d[30]), "+f"(d[31]), "+f"(d[32]), "+f"(d[33]), "+f"(d[34]), "+f"(d[35]), "+f"(d[36]), "+f"(d[37]), "+f"(d[38]), "+f"(d[39]), "+f"(d[40]), "+f"(d[41]), "+f"(d[42]), "+f"(d[43]), "+f"(d[44]), "+f"(d[45]), "+f"(d[46]), "+f"(d[47]), "+f"(d[48]), "+f"(d[49]), "+f"(d[50]), "+f"(d[51]), "+f"(d[52]), "+f"(d[53]), "+f"(d[54]), "+f"(d[55]), "+f"(d[56]), "+f"(d[57]), "+f"(d[58]), "+f"(d[59]), "+f"(d[60]), "+f"(d[61]), "+f"(d[62]), "+f"(d[63])
    : "r"(a_lo), "r"(b_lo), "r"(scaleD), "n"(OFFA), "n"(OFFB));
}

template <int OFFB>
__device__ __forceinline__ void wgmma_m64n128k16_rs_tb(float (&d)[64], uint32_t a0, uint32_t a1, uint32_t a2, uint32_t a3, uint32_t b_lo, int scaleD) {
  asm volatile("{\n.reg .pred p;\n.reg .b32 tb;\n.reg .b64 db;\nsetp.ne.b32 p, %69, 0;\n"
    "add.u32 tb, %68, %70;\n"
    "mov.b64 db, {tb, 0x40000040};\n"
    "wgmma.mma_async.sync.aligned.m64n128k16.f32.bf16.bf16 "
    "{%0, %1, %2, %3, %4, %5, %6, %7, %8, %9, %10, %11, %12, %13, %14, %15, %16, %17, %18, %19, %20, %21, %22, %23, %24, %25, %26, %27, %28, %29, %30, %31, %32, %33, %34, %35, %36, %37, %38, %39, %40, %41, %42, %43, %44, %45, %46, %47, %48, %49, %50, %51, %52, %53, %54, %55, %56, %57, %58, %59, %60, %61, %62, %63}, "
    "{%64, %65, %66, %67}, db, p, 1, 1, 1;\n}\n"
    : "+f"(d[0]), "+f"(d[1]), "+f"(d[2]), "+f"(d[3]), "+f"(d[4]), "+f"(d[5]), "+f"(d[6]), "+f"(d[7]), "+f"(d[8]), "+f"(d[9]), "+f"(d[10]), "+f"(d[11]), "+f"(d[12]), "+f"(d[13]), "+f"(d[14]), "+f"(d[15]), "+f"(d[16]), "+f"(d[17]), "+f"(d[18]), "+f"(d[19]), "+f"(d[20]), "+f"(d[21]), "+f"(d[22]), "+f"(d[23]), "+f"(d[24]), "+f"(d[25]), "+f"(d[26]), "+f"(d[27]), "+f"(d[28]), "+f"(d[29]), "+f"(d[30]), "+f"(d[31]), "+f"(d[32]), "+f"(d[33]), "+f"(d[34]), "+f"(d[35]), "+f"(d[36]), "+f"(d[37]), "+f"(d[38]), "+f"(d[39]), "+f"(d[40]), "+f"(d[41]), "+f"(d[42]), "+f"(d[43]), "+f"(d[44]), "+f"(d[45]), "+f"(d[46]), "+f"(d[47]), "+f"(d[48]), "+f"(d[49]), "+f"(d[50]), "+f"(d[51]), "+f"(d[52]), "+f"(d[53]), "+f"(d[54]), "+f"(d[55]), "+f"(d[56]), "+f"(d[57]), "+f"(d[58]), "+f"(d[59]), "+f"(d[60]), "+f"(d[61]), "+f"(d[62]), "+f"(d[63])
    : "r"(a0), "r"(a1), "r"(a2), "r"(a3), "r"(b_lo), "r"(scaleD), "n"(OFFB));
}

template <int OFFB>
__device__ __forceinline__ void wgmma_m64n128k16_rs(float (&d)[64], uint32_t a0, uint32_t a1, uint32_t a2, uint32_t a3, uint32_t b_lo, int scaleD) {
  asm volatile("{\n.reg .pred p;\n.reg .b32 tb;\n.reg .b64 db;\nsetp.ne.b32 p, %69, 0;\n"
    "add.u32 tb, %68, %70;\n"
    "mov.b64 db, {tb, 0x40000040};\n"
    "wgmma.mma_async.sync.aligned.m64n128k16.f32.bf16.bf16 "
    "{%0, %1, %2, %3, %4, %5, %6, %7, %8, %9, %10, %11, %12, %13, %14, %15, %16, %17, %18, %19, %20, %21, %22, %23, %24, %25, %26, %27, %28, %29, %30, %31, %32, %33, %34, %35, %36, %37, %38, %39, %40, %41, %42, %43, %44, %45, %46, %47, %48, %49, %50, %51, %52, %53, %54, %55, %56, %57, %58, %59, %60, %61, %62, %63}, "
    "{%64, %65, %66, %67}, db, p, 1, 1, 0;\n}\n"
    : "+f"(d[0]), "+f"(d[1]), "+f"(d[2]), "+f"(d[3]), "+f"(d[4]), "+f"(d[5]), "+f"(d[6]), "+f"(d[7]), "+f"(d[8]), "+f"(d[9]), "+f"(d[10]), "+f"(d[11]), "+f"(d[12]), "+f"(d[13]), "+f"(d[14]), "+f"(d[15]), "+f"(d[16]), "+f"(d[17]), "+f"(d[18]), "+f"(d[19]), "+f"(d[20]), "+f"(d[21]), "+f"(d[22]), "+f"(d[23]), "+f"(d[24]), "+f"(d[25]), "+f"(d[26]), "+f"(d[27]), "+f"(d[28]), "+f"(d[29]), "+f"(d[30]), "+f"(d[31]), "+f"(d[32]), "+f"(d[33]), "+f"(d[34]), "+f"(d[35]), "+f"(d[36]), "+f"(d[37]), "+f"(d[38]), "+f"(d[39]), "+f"(d[40]), "+f"(d[41]), "+f"(d[42]), "+f"(d[43]), "+f"(d[44]), "+f"(d[45]), "+f"(d[46]), "+f"(d[47]), "+f"(d[48]), "+f"(d[49]), "+f"(d[50]), "+f"(d[51]), "+f"(d[52]), "+f"(d[53]), "+f"(d[54]), "+f"(d[55]), "+f"(d[56]), "+f"(d[57]), "+f"(d[58]), "+f"(d[59]), "+f"(d[60]), "+f"(d[61]), "+f"(d[62]), "+f"(d[63])
    : "r"(a0), "r"(a1), "r"(a2), "r"(a3), "r"(b_lo), "r"(scaleD), "n"(OFFB));
}

__device__ __forceinline__ uint4 ldg_nc_v4(const void* p) {
  uint4 v;
    asm volatile("{\n.reg .b64 pol;\ncreatepolicy.fractional.L2::evict_first.b64 pol, 1.0;\n"
                 "ld.global.nc.L1::no_allocate.L2::cache_hint.v4.u32 {%0, %1, %2, %3}, [%4], pol;\n}\n" : "=r"(v.x), "=r"(v.y), "=r"(v.z), "=r"(v.w) : "l"(p));
  return v;
}
__device__ __forceinline__ uint64_t pol_normal() {
  uint64_t p; asm volatile("createpolicy.fractional.L2::evict_normal.b64 %0, 1.0;" : "=l"(p)); return p;
}
__device__ __forceinline__ void unpack8(const uint4& u, float (&v)[8]) {
  v[0] = bflo(u.x); v[1] = bfhi(u.x); v[2] = bflo(u.y); v[3] = bfhi(u.y);
  v[4] = bflo(u.z); v[5] = bfhi(u.z); v[6] = bflo(u.w); v[7] = bfhi(u.w);
}
__device__ __forceinline__ void fma8(float (&acc)[8], float s, const uint4& w) {
  acc[0] = fmaf(s, bflo(w.x), acc[0]); acc[1] = fmaf(s, bfhi(w.x), acc[1]); acc[2] = fmaf(s, bflo(w.y), acc[2]); acc[3] = fmaf(s, bfhi(w.y), acc[3]);
  acc[4] = fmaf(s, bflo(w.z), acc[4]); acc[5] = fmaf(s, bfhi(w.z), acc[5]); acc[6] = fmaf(s, bflo(w.w), acc[6]); acc[7] = fmaf(s, bfhi(w.w), acc[7]);
}
__device__ __forceinline__ float rcp_approx(float x) { float y; asm("rcp.approx.ftz.f32 %0, %1;" : "=f"(y) : "f"(x)); return y; }
__device__ __forceinline__ float sigmoid_f(float v) { return rcp_approx(1.0f + ex2_approx(v * -1.4426950408889634f)); }
__device__ __forceinline__ float silu_bf(float v) { return rbf(v * sigmoid_f(v)); }
__device__ __forceinline__ uint32_t rank_key(float r, int idx) {
  const uint32_t b = __float_as_uint(r) >> 16;
  const uint32_t u = (r != r) ? 0u : ((b & 0x8000u) ? (~b & 0xffffu) : (b | 0x8000u));
  return (u << 16) | (0xffffu - (uint32_t)idx);
}
__device__ __forceinline__ void warp_top2(uint32_t& k1, uint32_t& k2) {
  const uint32_t m1 = __reduce_max_sync(0xffffffffu, k1);
  k2 = __reduce_max_sync(0xffffffffu, k1 == m1 ? k2 : k1);
  k1 = m1;
}
__device__ __forceinline__ uint32_t bmul2(uint32_t a, uint32_t b) { uint32_t r; asm("mul.rn.bf16x2 %0, %1, %2;" : "=r"(r) : "r"(a), "r"(b)); return r; }
__device__ __forceinline__ uint32_t badd2(uint32_t a, uint32_t b) { uint32_t r; asm("add.rn.bf16x2 %0, %1, %2;" : "=r"(r) : "r"(a), "r"(b)); return r; }
__device__ __forceinline__ uint32_t bsub2(uint32_t a, uint32_t b) { uint32_t r; asm("sub.rn.bf16x2 %0, %1, %2;" : "=r"(r) : "r"(a), "r"(b)); return r; }
__device__ __forceinline__ float sqrt_approx(float x) { float y; asm("sqrt.approx.f32 %0, %1;" : "=f"(y) : "f"(x)); return y; }
__device__ __forceinline__ uint32_t ln_norm2(uint32_t x1, uint32_t mb2, float inv) {
  const uint32_t d = bsub2(x1, mb2);
  return pack_bf16(bflo(d) * inv, bfhi(d) * inv);
}
__device__ __forceinline__ uint32_t bfma2(uint32_t a, uint32_t b, uint32_t c) { uint32_t r; asm("fma.rn.bf16x2 %0, %1, %2, %3;" : "=r"(r) : "r"(a), "r"(b), "r"(c)); return r; }
__device__ __forceinline__ uint32_t ln_norm2b(uint32_t x1, uint32_t mb2, uint32_t ih, uint32_t il) {
  const uint32_t d = bsub2(x1, mb2);
  return bfma2(d, ih, bmul2(d, il));
}
__device__ __forceinline__ uint32_t ln_mod2(uint32_t x1, uint32_t mb2, float inv, uint32_t c1, uint32_t sb) { return badd2(bmul2(ln_norm2(x1, mb2, inv), c1), sb); }
__device__ __forceinline__ void ldmatrix_x4(uint32_t addr, uint32_t& r0, uint32_t& r1, uint32_t& r2, uint32_t& r3) {
  asm volatile("ldmatrix.sync.aligned.m8n8.x4.shared.b16 {%0, %1, %2, %3}, [%4];" : "=r"(r0), "=r"(r1), "=r"(r2), "=r"(r3) : "r"(addr) : "memory");
}
__device__ __forceinline__ uint4 ldg_stream_v4(const void* p, uint64_t pol) {
  uint4 v; asm volatile("ld.global.nc.L1::no_allocate.L2::cache_hint.L2::128B.v4.u32 {%0, %1, %2, %3}, [%4], %5;" : "=r"(v.x), "=r"(v.y), "=r"(v.z), "=r"(v.w) : "l"(p), "l"(pol)); return v;
}
__device__ __forceinline__ void bulk_load_hint(uint32_t dst, const void* src, uint32_t bytes, uint32_t bar, uint64_t pol) {
  asm volatile("cp.async.bulk.shared::cluster.global.mbarrier::complete_tx::bytes.L2::cache_hint [%0], [%1], %2, [%3], %4;"
    :: "r"(dst), "l"(src), "r"(bytes), "r"(bar), "l"(pol) : "memory");
}
__device__ __forceinline__ void red_release_add(unsigned int* p, unsigned int v) { asm volatile("red.release.gpu.global.add.u32 [%0], %1;" :: "l"(p), "r"(v) : "memory"); }
__device__ __forceinline__ unsigned int ld_acquire(const unsigned int* p) { unsigned int v; asm volatile("ld.acquire.gpu.global.u32 %0, [%1];" : "=r"(v) : "l"(p) : "memory"); return v; }
__device__ __forceinline__ void spin_until(const unsigned int* p, unsigned int target) {
  #pragma unroll 1
  for (unsigned int i = 0; i < (1u << 22); i++) { if (ld_acquire(p) >= target) return; }
}
__device__ __forceinline__ float lds_f32(uint32_t a) { float v; asm volatile("ld.shared.f32 %0, [%1];" : "=f"(v) : "r"(a) : "memory"); return v; }
__device__ __forceinline__ float2 lds_f32x2(uint32_t a) { float2 v; asm volatile("ld.shared.v2.f32 {%0, %1}, [%2];" : "=f"(v.x), "=f"(v.y) : "r"(a) : "memory"); return v; }
__device__ __forceinline__ uint2 lds_u32x2(uint32_t a) { uint2 v; asm volatile("ld.shared.v2.u32 {%0, %1}, [%2];" : "=r"(v.x), "=r"(v.y) : "r"(a) : "memory"); return v; }
__device__ __forceinline__ uint32_t lds_u32(uint32_t a) { uint32_t v; asm volatile("ld.shared.u32 %0, [%1];" : "=r"(v) : "r"(a) : "memory"); return v; }
__device__ __forceinline__ void sts_u32(uint32_t a, uint32_t v) { asm volatile("st.shared.u32 [%0], %1;" :: "r"(a), "r"(v) : "memory"); }
__device__ __forceinline__ void sts_u32x2(uint32_t a, uint32_t x, uint32_t y) { asm volatile("st.shared.v2.u32 [%0], {%1, %2};" :: "r"(a), "r"(x), "r"(y) : "memory"); }
__device__ __forceinline__ void sts_f32(uint32_t a, float v) { asm volatile("st.shared.f32 [%0], %1;" :: "r"(a), "f"(v) : "memory"); }
__device__ __forceinline__ void sts_f32x2(uint32_t a, float x, float y) { asm volatile("st.shared.v2.f32 [%0], {%1, %2};" :: "r"(a), "f"(x), "f"(y) : "memory"); }
__device__ __forceinline__ void sts_f32x4(uint32_t a, float x, float y, float z, float w) { asm volatile("st.shared.v4.f32 [%0], {%1, %2, %3, %4};" :: "r"(a), "f"(x), "f"(y), "f"(z), "f"(w) : "memory"); }

__device__ __forceinline__ uint4 lds_u32x4(uint32_t a) { uint4 v; asm volatile("ld.shared.v4.u32 {%0, %1, %2, %3}, [%4];" : "=r"(v.x), "=r"(v.y), "=r"(v.z), "=r"(v.w) : "r"(a) : "memory"); return v; }
__device__ __forceinline__ void sts_u32x4(uint32_t a, uint32_t x, uint32_t y, uint32_t z, uint32_t w) { asm volatile("st.shared.v4.u32 [%0], {%1, %2, %3, %4};" :: "r"(a), "r"(x), "r"(y), "r"(z), "r"(w) : "memory"); }
__device__ __forceinline__ void st_tagged(float* p, float v) {
  const uint32_t b = __float_as_uint(v);
  asm volatile("st.relaxed.gpu.global.u32 [%0], %1;" :: "l"(p), "r"(b == 0u ? 0x80000000u : b) : "memory");
}
__device__ __forceinline__ void st_tagged4(float* p, float x, float y, float z, float w) {
  const uint32_t a = __float_as_uint(x), b = __float_as_uint(y), c = __float_as_uint(z), d = __float_as_uint(w);
  asm volatile("st.relaxed.gpu.global.v4.u32 [%0], {%1, %2, %3, %4};" :: "l"(p), "r"(a == 0u ? 0x80000000u : a), "r"(b == 0u ? 0x80000000u : b),
               "r"(c == 0u ? 0x80000000u : c), "r"(d == 0u ? 0x80000000u : d) : "memory");
}
__device__ __forceinline__ void st_relaxed2(void* p, uint32_t a, uint32_t b) { asm volatile("st.relaxed.gpu.global.v2.u32 [%0], {%1, %2};" :: "l"(p), "r"(a), "r"(b) : "memory"); }
__device__ __forceinline__ float4 ld_tagged4(const float* p) {
  float4 v; asm volatile("ld.relaxed.gpu.global.v4.f32 {%0, %1, %2, %3}, [%4];" : "=f"(v.x), "=f"(v.y), "=f"(v.z), "=f"(v.w) : "l"(p) : "memory"); return v;
}
__device__ __forceinline__ bool tagged4(const float4& v) {
  return __float_as_uint(v.x) != 0u && __float_as_uint(v.y) != 0u && __float_as_uint(v.z) != 0u && __float_as_uint(v.w) != 0u;
}
__device__ __forceinline__ void hint_arrive(uint32_t* p) { asm volatile("red.relaxed.gpu.global.add.u32 [%0], 1;" :: "l"(p) : "memory"); }
__device__ __forceinline__ void hint_wait(const uint32_t* p, uint32_t target) {
  uint32_t v = 0u;
  #pragma unroll 1
  for (unsigned int i = 0; i < (1u << 22) && v < target; i++) asm volatile("ld.relaxed.gpu.global.u32 %0, [%1];" : "=r"(v) : "l"(p) : "memory");
}
__device__ __forceinline__ void fence_proxy_async_global() { asm volatile("fence.proxy.async.global;" ::: "memory"); }

#define H_SPLIT 1
#define X_DLY 1200
#define W_DLY 1900
#define W_FIRST 2200
#define PRE_B 2
template <int J0, int J1>
__device__ __forceinline__ void load_parts(float2 (&pa)[J1 - J0][4], int t2) {
  #pragma unroll
  for (int j = J0; j < J1; j++)
    #pragma unroll
    for (int k = 0; k < 4; k++)
      asm volatile("ld.relaxed.gpu.global.v2.f32 {%0, %1}, [%2];" : "=f"(pa[j - J0][k].x), "=f"(pa[j - J0][k].y)
                   : "l"(g_modpart + k * 2 * T_D + (t2 >> 7) * T_D + j * 256 + (t2 & 127) * 2) : "memory");
}
template <int J0, int J1>
__device__ __forceinline__ void finish_parts(float2 (&pa)[J1 - J0][4], bool loaded, int t2, uint32_t tab) {
  #pragma unroll 1
  for (unsigned int spin = 0; spin < (1u << 22); spin++) {
    if (!loaded) load_parts<J0, J1>(pa, t2);
    loaded = false;
    bool ok = true;
    #pragma unroll
    for (int j = 0; j < J1 - J0; j++)
      #pragma unroll
      for (int k = 0; k < 4; k++) ok &= (__float_as_uint(pa[j][k].x) != 0u) & (__float_as_uint(pa[j][k].y) != 0u);
    if (__all_sync(0xffffffffu, ok)) break;
  }
  #pragma unroll
  for (int j = J0; j < J1; j++) {
    const float2* q = pa[j - J0];
    const uint32_t m = pack_bf16(((q[0].x + q[1].x) + q[2].x) + q[3].x, ((q[0].y + q[1].y) + q[2].y) + q[3].y);
    sts_u32(tab + (t2 >> 7) * 2048 + j * 512 + (t2 & 127) * 4, t2 >= 128 ? badd2(m, 0x3F803F80u) : m);
  }
}
__device__ __forceinline__ void head_phase(uint32_t bid, uint32_t scr, uint32_t xs, uint32_t b_x, uint32_t b_go, uint32_t b_head, int t2, uint32_t zero, const bf16* __restrict__ cvec, const bf16* __restrict__ w_mod) {
  const int lane = t2 & 31, w8 = t2 >> 5;
  const int cb = bid & 31, ks = bid >> 5;
  const bool early = (cb & 15) < 4 * H_SPLIT;
  const uint32_t ws = (xs - 32768 + (t2 >> 3) * 128 + (((t2 ^ (t2 >> 3)) & 7) << 4)) ^ zero;
  const float cv = __bfloat162float(cvec[ks * 256 + t2]);
  const bf16* wsrc = w_mod + (size_t)(ks * 256 + (t2 >> 3)) * (6 * T_D) + cb * 64 + (t2 & 7) * 8;
  if (early) {
    const uint64_t pol = policy_evict_first();
    #pragma unroll 2
    for (int i = 0; i < 8; i++)
      asm volatile("cp.async.cg.shared.global.L2::cache_hint [%0], [%1], 16, %2;" :: "r"(ws + i * 4096), "l"(wsrc + (size_t)i * 32 * 6 * T_D), "l"(pol) : "memory");
  }
  sts_f32(scr + t2 * 4, silu_bf(cv));
  named_bar_sync(6, 384);
  TL_MARK2(1, t2 == 0);
  uint4 xv[2][4];
  uint32_t mb2[2], ih[2], il[2];
  auto norm = [&](int j) {
    #pragma unroll
    for (int r = 0; r < 2; r++) {
      xv[r][j].x = ln_norm2b(xv[r][j].x, mb2[r], ih[r], il[r]); xv[r][j].y = ln_norm2b(xv[r][j].y, mb2[r], ih[r], il[r]);
      xv[r][j].z = ln_norm2b(xv[r][j].z, mb2[r], ih[r], il[r]); xv[r][j].w = ln_norm2b(xv[r][j].w, mb2[r], ih[r], il[r]);
    }
  };
  auto modulate = [&](int j) {
    const uint4 sa = lds_u32x4(scr + 8192 + j * 512 + lane * 16), c1 = lds_u32x4(scr + 8192 + 2048 + j * 512 + lane * 16);
    #pragma unroll
    for (int r = 0; r < 2; r++) {
      xv[r][j].x = badd2(bmul2(xv[r][j].x, c1.x), sa.x); xv[r][j].y = badd2(bmul2(xv[r][j].y, c1.y), sa.y);
      xv[r][j].z = badd2(bmul2(xv[r][j].z, c1.z), sa.z); xv[r][j].w = badd2(bmul2(xv[r][j].w, c1.w), sa.w);
    }
  };
  auto store = [&](int j) {
    #pragma unroll
    for (int r = 0; r < 2; r++) *reinterpret_cast<uint4*>(g_h + (size_t)(bid * 16 + 2 * w8 + r) * T_D + j * 256 + lane * 8) = xv[r][j];
  };
  #pragma unroll 1
  for (int ph = 0; ph < 2; ph++) {
    if ((ph == 0) == early) {
      asm volatile("cp.async.wait_all;" ::: "memory");
      if (!early) mbar_wait(b_x + 168, 0);
      float acc[8];
      #pragma unroll
      for (int j = 0; j < 8; j++) acc[j] = 0.f;
      #pragma unroll
      for (int i = 0; i < 8; i++) fma8(acc, lds_f32(scr + ((t2 >> 3) + 32 * i) * 4), lds_u32x4(ws + i * 4096));
      #pragma unroll
      for (int j = 0; j < 4; j++) { const bool up = lane & 16; acc[j] = (up ? acc[4 + j] : acc[j]) + __shfl_xor_sync(0xffffffffu, up ? acc[j] : acc[4 + j], 16); }
      #pragma unroll
      for (int j = 0; j < 2; j++) { const bool up = lane & 8; acc[j] = (up ? acc[2 + j] : acc[j]) + __shfl_xor_sync(0xffffffffu, up ? acc[j] : acc[2 + j], 8); }
      sts_f32x2(scr + 1024 + w8 * 256 + (lane & 7) * 32 + (lane >> 3) * 8, acc[0], acc[1]);
      named_bar_sync(5, 256);
      if (t2 < 64) {
        float sum = 0.f;
        #pragma unroll
        for (int i = 0; i < 8; i++) sum += lds_f32(scr + 1024 + i * 256 + t2 * 4);
        st_tagged(g_modpart + ks * 2 * T_D + cb * 64 + t2, sum);
        TL_MARK2(early ? 2 : 6, t2 == 0);
      }
    } else {
      float2 pa[H_SPLIT][4];
      mbar_wait(b_x, 0);
      TL_MARK2(18, t2 == 0);
      load_parts<0, H_SPLIT>(pa, t2);
      #pragma unroll
      for (int r = 0; r < 2; r++)
        #pragma unroll
        for (int j = 0; j < 4; j++) xv[r][j] = lds_u32x4(xs + (2 * w8 + r) * 2048 + j * 512 + lane * 16);
  {
    float st[4] = {0.f, 0.f, 0.f, 0.f};
    #pragma unroll
    for (int r = 0; r < 2; r++)
      #pragma unroll
      for (int j = 0; j < 4; j++) {
        float v[8];
        unpack8(xv[r][j], v);
        st[2 * r] += ((v[0] + v[1]) + (v[2] + v[3])) + ((v[4] + v[5]) + (v[6] + v[7]));
        st[2 * r + 1] += fmaf(v[0], v[0], fmaf(v[1], v[1], fmaf(v[2], v[2], v[3] * v[3]))) + fmaf(v[4], v[4], fmaf(v[5], v[5], fmaf(v[6], v[6], v[7] * v[7])));
      }
    #pragma unroll
    for (int k = 0; k < 2; k++) { const bool up = lane & 16; st[k] = (up ? st[2 + k] : st[k]) + __shfl_xor_sync(0xffffffffu, up ? st[k] : st[2 + k], 16); }
    #pragma unroll
    for (int o = 8; o > 0; o >>= 1) { st[0] += __shfl_xor_sync(0xffffffffu, st[0], o); st[1] += __shfl_xor_sync(0xffffffffu, st[1], o); }
    const float mean = st[0] * (1.0f / T_D);
    const float inv = rcp_approx(rbf(sqrt_approx(rbf(rbf(fmaxf(fmaf(-mean, mean, st[1] * (1.0f / T_D)), 0.f)) + 1e-05f))));
    const uint32_t m = pack_bf16(mean, mean), h = pack_bf16(inv - rbf(inv), inv);
    #pragma unroll
    for (int r = 0; r < 2; r++) {
      mb2[r] = __shfl_sync(0xffffffffu, m, 16 * r);
      const uint32_t hr = __shfl_sync(0xffffffffu, h, 16 * r);
      ih[r] = __byte_perm(hr, hr, 0x3232); il[r] = __byte_perm(hr, hr, 0x1010);
    }
  }
      #pragma unroll
      for (int j = 0; j < H_SPLIT; j++) norm(j);
      TL_MARK2(5, t2 == 0);
      finish_parts<0, H_SPLIT>(pa, true, t2, scr + 8192);
      named_bar_sync(5, 256);
      TL_MARK2(7, t2 == 0);
      #pragma unroll
      for (int j = 0; j < H_SPLIT; j++) { modulate(j); store(j); }
      named_bar_arrive(9, 288);
    }
  }
  #pragma unroll
  for (int j = H_SPLIT; j < 4; j++) norm(j);
  float2 pb[4 - H_SPLIT][4];
  finish_parts<H_SPLIT, 4>(pb, false, t2, scr + 8192);
  named_bar_sync(5, 256);
  TL_MARK2(17, t2 == 0);
  #pragma unroll
  for (int j = H_SPLIT; j < 4; j++) modulate(j);
  __syncwarp();
  if (lane == 0) mbar_arrive(b_head + (xv[1][3].w & zero));
  mbar_wait(b_go, 0);
  #pragma unroll
  for (int j = H_SPLIT; j < 4; j++) store(j);
  named_bar_arrive(8, 288);
}

#define MOD_AT (b_empty + 8)
#define MOD_SPLIT 16
__device__ __forceinline__ void mod_rest(uint32_t bid, uint32_t scr, uint32_t b_go, int t, const bf16* __restrict__ cvec, const bf16* __restrict__ w_mod, const bf16* __restrict__ w_r) {
  const int lane = t & 31;
  #pragma unroll 1
  for (int i = t; i < T_D / 2; i += 64) {
    const uint32_t c2 = *reinterpret_cast<const uint32_t*>(cvec + 2 * i);
    sts_u32(scr + i * 4, pack_bf16(silu_bf(bflo(c2)), silu_bf(bfhi(c2))));
  }
  named_bar_sync(11, 64);
  const bf16* wp = w_mod + (size_t)(2 * (t >> 2)) * (6 * T_D) + 2 * T_D + bid * 32 + (t & 3) * 8;
  float acc[8];
  #pragma unroll
  for (int i = 0; i < 8; i++) acc[i] = 0.f;
  #pragma unroll 1
  for (int i = 0; i < 32; i += 2) {
    if (i == MOD_SPLIT) mbar_wait_long(b_go, 0);
    const uint4 w0 = ldg_nc_v4(wp), w1 = ldg_nc_v4(wp + 6 * T_D), w2 = ldg_nc_v4(wp + 32 * 6 * T_D), w3 = ldg_nc_v4(wp + 33 * 6 * T_D);
    wp += 64 * 6 * T_D;
    const uint32_t s0 = lds_u32(scr + (i * 16 + (t >> 2)) * 4), s1 = lds_u32(scr + (i * 16 + 16 + (t >> 2)) * 4);
    fma8(acc, bflo(s0), w0); fma8(acc, bfhi(s0), w1); fma8(acc, bflo(s1), w2); fma8(acc, bfhi(s1), w3);
  }
  #pragma unroll
  for (int j = 0; j < 4; j++) { const bool up = lane & 16; acc[j] = (up ? acc[4 + j] : acc[j]) + __shfl_xor_sync(0xffffffffu, up ? acc[j] : acc[4 + j], 16); }
  #pragma unroll
  for (int j = 0; j < 2; j++) { const bool up = lane & 8; acc[j] = (up ? acc[2 + j] : acc[j]) + __shfl_xor_sync(0xffffffffu, up ? acc[j] : acc[2 + j], 8); }
  { const bool up = lane & 4; acc[0] = (up ? acc[1] : acc[0]) + __shfl_xor_sync(0xffffffffu, up ? acc[0] : acc[1], 4); }
  if (t >= 32) sts_f32(scr + 2048 + lane * 4, acc[0]);
  named_bar_sync(11, 64);
  if (__shfl_sync(0xffffffffu, t, 0) < 32) {
    const int kind = bid >> 5;
    float v = rbf(acc[0] + lds_f32(scr + 2048 + lane * 4));
    const int col = (bid & 31) * 32 + (lane & 3) * 8 + (lane >> 2);
    uint8_t* dst = g_col + (col >> 7) * 1536;
    if (kind == 2) v = rbf(1.0f + v);
    float vw = v * __bfloat162float(w_r[col]);
    if (kind == 2) {
      const int c = col & 127, i = (c & ~15) + ((c >> 1) & 3) * 4 + ((c >> 3) & 1) * 2 + (c & 1);
      reinterpret_cast<bf16*>(dst)[i] = __float2bfloat16_rn(vw);
      reinterpret_cast<bf16*>(dst)[128 + i] = __float2bfloat16_rn(vw - rbf(vw));
    }
    reinterpret_cast<bf16*>(dst + 512 + (kind & 1) * 512 + (kind >> 1) * 256)[col & 127] = __float2bfloat16_rn(v);
    #pragma unroll
    for (int o = 16; o > 0; o >>= 1) vw += __shfl_xor_sync(0xffffffffu, vw, o);
    if (lane == 0 && (kind == 1 || kind == 2)) g_scal[95 - bid] = vw;
  }
  #pragma unroll 1
  for (int i = bid * 64 + t; i < (int)(sizeof(g_mail) / 16); i += 128 * 64) reinterpret_cast<uint4*>(&g_mail)[i] = make_uint4(0u, 0u, 0u, 0u);
  named_bar_sync(11, 64);
  if (t == 0) red_release_add(&g_hcnt[0], 1u);
}

constexpr int AT_NBLK = T_SEQ / 128;
constexpr float AT_HEAD = 7.0f;
#define WO_LATE 12
#define QP_STAG 3
#define AT_SPLIT 28
#define AT_PIN 12
#define PINB 4
constexpr int AT_NFULL = 124;
constexpr int AT_PREG = 40, AT_CREG = 232;
constexpr uint32_t AT_SQ = 5 * 32768;
constexpr float AT_C = 0.08838834764831845f * 1.4426950408889634f;
constexpr float AT_RAW_LO = -16.0f, AT_RAW_HI = 24.0f;
constexpr float AT_RAW_SUM = 281474976710656.0f, AT_RAW_MIN = 9.094947017729282e-13f;
constexpr uint32_t AT_SBAR = AT_SQ + 65536 + 256;
constexpr uint32_t AT_SMEM = AT_SQ + 65536 + 3072;

__device__ __forceinline__ uint32_t ring_slot(uint32_t t) { return t - 5u * ((t * 205u) >> 10); }
__device__ __forceinline__ uint32_t qp_pos(uint32_t j, uint32_t it) { return 4u * it + (j & 3u) + ((j & 3u) == 3u ? it : 0u); }
__device__ __forceinline__ uint32_t ring_par(uint32_t t) { return ((t * 205u) >> 10) & 1u; }
__device__ __forceinline__ void softmax_rowmax(const float (&s)[64], float& mx0, float& mx1) {
  float a0 = fmaxf(s[0], s[1]), a1 = fmaxf(s[4], s[5]), a2 = fmaxf(s[8], s[9]), a3 = fmaxf(s[12], s[13]);
  float b0 = fmaxf(s[2], s[3]), b1 = fmaxf(s[6], s[7]), b2 = fmaxf(s[10], s[11]), b3 = fmaxf(s[14], s[15]);
  #pragma unroll
  for (int j = 4; j < 16; j += 4) {
    a0 = fmaxf(a0, fmaxf(s[4 * j + 0], s[4 * j + 1]));  b0 = fmaxf(b0, fmaxf(s[4 * j + 2], s[4 * j + 3]));
    a1 = fmaxf(a1, fmaxf(s[4 * j + 4], s[4 * j + 5]));  b1 = fmaxf(b1, fmaxf(s[4 * j + 6], s[4 * j + 7]));
    a2 = fmaxf(a2, fmaxf(s[4 * j + 8], s[4 * j + 9]));  b2 = fmaxf(b2, fmaxf(s[4 * j + 10], s[4 * j + 11]));
    a3 = fmaxf(a3, fmaxf(s[4 * j + 12], s[4 * j + 13])); b3 = fmaxf(b3, fmaxf(s[4 * j + 14], s[4 * j + 15]));
  }
  mx0 = fmaxf(fmaxf(a0, a1), fmaxf(a2, a3));
  mx1 = fmaxf(fmaxf(b0, b1), fmaxf(b2, b3));
  mx0 = fmaxf(mx0, __shfl_xor_sync(0xffffffffu, mx0, 1));
  mx1 = fmaxf(mx1, __shfl_xor_sync(0xffffffffu, mx1, 1));
  mx0 = fmaxf(mx0, __shfl_xor_sync(0xffffffffu, mx0, 2));
  mx1 = fmaxf(mx1, __shfl_xor_sync(0xffffffffu, mx1, 2));
}
__device__ __forceinline__ void softmax_sub(float (&s)[64], float mc0, float mc1) {
  #pragma unroll
  for (int j = 0; j < 16; j++) { s[4 * j] -= mc0; s[4 * j + 1] -= mc0; s[4 * j + 2] -= mc1; s[4 * j + 3] -= mc1; }
}
template <int LO, int HI>
__device__ __forceinline__ void softmax_exp(float (&s)[64]) {
  #pragma unroll
  for (int i = LO; i < HI; i++) s[i] = ex2_approx(s[i]);
}
__device__ __forceinline__ bool softmax_mode(const float (&s)[64], float& mc0, float& mc1) {
  softmax_rowmax(s, mc0, mc1);
  const bool raw = __all_sync(0xffffffffu, mc0 >= AT_RAW_LO && mc0 <= AT_RAW_HI && mc1 >= AT_RAW_LO && mc1 <= AT_RAW_HI);
  mc0 += AT_HEAD; mc1 += AT_HEAD;
  return raw;
}
__device__ __forceinline__ void rowsum_p(const uint32_t (&p)[32], uint32_t& t0, uint32_t& t1) {
  uint32_t a[16];
  #pragma unroll
  for (int i = 0; i < 8; i++) { a[2 * i] = badd2(p[4 * i], p[4 * i + 2]); a[2 * i + 1] = badd2(p[4 * i + 1], p[4 * i + 3]); }
  #pragma unroll
  for (int i = 0; i < 4; i++) { a[2 * i] = badd2(a[4 * i], a[4 * i + 2]); a[2 * i + 1] = badd2(a[4 * i + 1], a[4 * i + 3]); }
  t0 = badd2(badd2(a[0], a[2]), badd2(a[4], a[6]));
  t1 = badd2(badd2(a[1], a[3]), badd2(a[5], a[7]));
}
__device__ __forceinline__ void add_rowsum(const uint32_t (&p)[32], float& l0, float& l1) {
  uint32_t t0, t1;
  rowsum_p(p, t0, t1);
  l0 += bflo(t0) + bfhi(t0); l1 += bflo(t1) + bfhi(t1);
}
__device__ __forceinline__ void pack_p(uint32_t (&p)[32], const float (&s)[64]) {
  #pragma unroll
  for (int i = 0; i < 32; i++) p[i] = pack_bf16(s[2 * i], s[2 * i + 1]);
}
__device__ __noinline__ void attn_rows_exact(uint32_t bid, uint32_t sq, uint32_t so, int hsel, const bf16* __restrict__ kh, const bf16* __restrict__ vh) {
  const int warp = (threadIdx.x >> 5) & 3, lane = threadIdx.x & 31;
  const size_t hofs = (size_t)((bid < 128 ? bid >> 4 : 15) * 2 + hsel) * T_SEQ * T_DH;
  kh += hofs; vh += hofs;
  #pragma unroll 1
  for (int r = 16 * warp; r < 16 * warp + 16; r++) {
    const uint32_t ad = (lane >> 4) * 16384 + r * 128 + ((((lane & 15) >> 1) ^ (r & 7)) << 4) + (lane & 1) * 8;
    uint2 qv; asm volatile("ld.shared.v2.u32 {%0, %1}, [%2];" : "=r"(qv.x), "=r"(qv.y) : "r"(sq + ad) : "memory");
    const float q0 = bflo(qv.x), q1 = bfhi(qv.x), q2 = bflo(qv.y), q3 = bfhi(qv.y);
    float m = -INFINITY, l = 0.f, o0 = 0.f, o1 = 0.f, o2 = 0.f, o3 = 0.f;
    #pragma unroll 1
    for (int key = 0; key < T_SEQ; key++) {
      const uint2 kv = *reinterpret_cast<const uint2*>(kh + (size_t)key * T_DH + lane * 4);
      const uint2 vv = *reinterpret_cast<const uint2*>(vh + (size_t)key * T_DH + lane * 4);
      float sc = (q0 * bflo(kv.x) + q1 * bfhi(kv.x)) + (q2 * bflo(kv.y) + q3 * bfhi(kv.y));
      #pragma unroll
      for (int o = 16; o > 0; o >>= 1) sc += __shfl_xor_sync(0xffffffffu, sc, o);
      const float mn = fmaxf(m, sc);
      const float al = (m == mn) ? 1.0f : ex2_approx(m - mn), p = rbf(ex2_approx(sc - mn));
      m = mn;
      l = fmaf(l, al, p);
      o0 = fmaf(o0, al, p * bflo(vv.x)); o1 = fmaf(o1, al, p * bfhi(vv.x));
      o2 = fmaf(o2, al, p * bflo(vv.y)); o3 = fmaf(o3, al, p * bfhi(vv.y));
    }
    const float inv = rcp_approx(l);
    asm volatile("st.shared.v2.u32 [%0], {%1, %2};" :: "r"(so + ad), "r"(pack_bf16(o0 * inv, o1 * inv)), "r"(pack_bf16(o2 * inv, o3 * inv)) : "memory");
  }
}
__device__ __forceinline__ void issue_qk(float (&s)[64], const uint32_t (&q)[32], uint32_t k_lo) {
  wgmma_fence();
  wgmma_m64n128k16_rs<0>(s, q[0], q[1], q[2], q[3], k_lo, 0);
  wgmma_m64n128k16_rs<2>(s, q[4], q[5], q[6], q[7], k_lo, 1);
  wgmma_m64n128k16_rs<4>(s, q[8], q[9], q[10], q[11], k_lo, 1);
  wgmma_m64n128k16_rs<6>(s, q[12], q[13], q[14], q[15], k_lo, 1);
  wgmma_m64n128k16_rs<1024>(s, q[16], q[17], q[18], q[19], k_lo, 1);
  wgmma_m64n128k16_rs<1026>(s, q[20], q[21], q[22], q[23], k_lo, 1);
  wgmma_m64n128k16_rs<1028>(s, q[24], q[25], q[26], q[27], k_lo, 1);
  wgmma_m64n128k16_rs<1030>(s, q[28], q[29], q[30], q[31], k_lo, 1);
  wgmma_commit();
}
__device__ __forceinline__ void issue_pv(float (&o)[64], const uint32_t (&p)[32], uint32_t v_lo, int accumulate) {
  wgmma_fence();
  wgmma_m64n128k16_rs_tb<0>(o, p[0], p[1], p[2], p[3], v_lo, accumulate);
  wgmma_m64n128k16_rs_tb<128>(o, p[4], p[5], p[6], p[7], v_lo, 1);
  wgmma_m64n128k16_rs_tb<256>(o, p[8], p[9], p[10], p[11], v_lo, 1);
  wgmma_m64n128k16_rs_tb<384>(o, p[12], p[13], p[14], p[15], v_lo, 1);
  wgmma_m64n128k16_rs_tb<512>(o, p[16], p[17], p[18], p[19], v_lo, 1);
  wgmma_m64n128k16_rs_tb<640>(o, p[20], p[21], p[22], p[23], v_lo, 1);
  wgmma_m64n128k16_rs_tb<768>(o, p[24], p[25], p[26], p[27], v_lo, 1);
  wgmma_m64n128k16_rs_tb<896>(o, p[28], p[29], p[30], p[31], v_lo, 1);
  wgmma_commit();
}
__device__ __forceinline__ void block_end(uint32_t zero, uint32_t bar) {
  #pragma unroll 1
  for (uint32_t i = 0; i < zero; i++) mbar_arrive(bar);
}
__device__ __forceinline__ void rescale_o(float (&o)[64], float al0, float al1) {
  #pragma unroll
  for (int j = 0; j < 16; j++) { o[4 * j] *= al0; o[4 * j + 1] *= al0; o[4 * j + 2] *= al1; o[4 * j + 3] *= al1; }
}

__device__ __forceinline__ void stage_o(const float (&o)[64], float i0, float i1, uint32_t dst, int lane) {
  #pragma unroll
  for (int J = 0; J < 16; J += 2)
    stmatrix_x4(dst + (J >> 3) * 16384 + ((((J & 7) + (lane >> 4)) ^ (lane & 7)) << 4),
                pack_bf16(o[4 * J + 0] * i0, o[4 * J + 1] * i0), pack_bf16(o[4 * J + 2] * i1, o[4 * J + 3] * i1),
                pack_bf16(o[4 * J + 4] * i0, o[4 * J + 5] * i0), pack_bf16(o[4 * J + 6] * i1, o[4 * J + 7] * i1));
}
__device__ __forceinline__ bool finish_l(float& l0, float& l1) {
  l0 += __shfl_xor_sync(0xffffffffu, l0, 1); l1 += __shfl_xor_sync(0xffffffffu, l1, 1);
  l0 += __shfl_xor_sync(0xffffffffu, l0, 2); l1 += __shfl_xor_sync(0xffffffffu, l1, 2);
  const bool redo = __any_sync(0xffffffffu, !(l0 <= AT_RAW_SUM && l1 <= AT_RAW_SUM && l0 >= AT_RAW_MIN && l1 >= AT_RAW_MIN));
  l0 = rcp_approx(l0); l1 = rcp_approx(l1);
  return redo;
}
template <int J0>
__device__ __forceinline__ void stage_q(const float (&acc)[128], float c, uint32_t dst, int lane) {
  #pragma unroll
  for (int J = J0; J < J0 + 16; J += 2)
    stmatrix_x4(dst + (J >> 3) * 16384 + ((((J & 7) + (lane >> 4)) ^ (lane & 7)) << 4),
                pack_bf16(acc[4 * J + 0] * c, acc[4 * J + 1] * c), pack_bf16(acc[4 * J + 2] * c, acc[4 * J + 3] * c),
                pack_bf16(acc[4 * J + 4] * c, acc[4 * J + 5] * c), pack_bf16(acc[4 * J + 6] * c, acc[4 * J + 7] * c));
}
__device__ __forceinline__ void store_o(const CUtensorMap* tmO, uint32_t src, int head, int row) {
  tma_store_2d(tmO, src, head * T_DH, row);
  tma_store_2d(tmO, src + 16384, head * T_DH + 64, row);
  bulk_commit();
}
__device__ __forceinline__ void mma_bf16(float (&d)[4], uint32_t a0, uint32_t a1, uint32_t a2, uint32_t a3, uint32_t b0, uint32_t b1) {
  asm volatile("mma.sync.aligned.m16n8k16.row.col.f32.bf16.bf16.f32 {%0, %1, %2, %3}, {%4, %5, %6, %7}, {%8, %9}, {%0, %1, %2, %3};"
               : "+f"(d[0]), "+f"(d[1]), "+f"(d[2]), "+f"(d[3]) : "r"(a0), "r"(a1), "r"(a2), "r"(a3), "r"(b0), "r"(b1));
}
struct GemvSel { uint32_t lo0, hi0, lo1, hi1; };
__device__ __forceinline__ GemvSel gemv_sel(int lane) {
  const uint32_t lo = (lane & 8) ? 0x1044u : 0x4410u, hi = (lane & 8) ? 0x3244u : 0x4432u;
  GemvSel s; s.lo0 = (lane & 16) ? 0x4444u : lo; s.hi0 = (lane & 16) ? 0x4444u : hi; s.lo1 = (lane & 16) ? lo : 0x4444u; s.hi1 = (lane & 16) ? hi : 0x4444u;
  return s;
}
#define GEMV_B0(j, h, s) __byte_perm((j) < 2 ? (h).x : (h).y, 0u, ((j) & 1) ? (s).hi0 : (s).lo0)
#define GEMV_B1(j, h, s) __byte_perm((j) < 2 ? (h).x : (h).y, 0u, ((j) & 1) ? (s).hi1 : (s).lo1)
__device__ __forceinline__ float4 gemv_out(const float (&d)[4], int lane) {
  const bool tk = lane & 1;
  const float r0 = __shfl_xor_sync(0xffffffffu, tk ? d[0] : d[1], 1), r1 = __shfl_xor_sync(0xffffffffu, tk ? d[2] : d[3], 1);
  return tk ? make_float4(r0, d[1], r1, d[3]) : make_float4(d[0], r0, d[2], r1);
}
#define OG_NG 8
#define PUT_N 2
#define H_STAG 2
#define AL_P 60
#define AL_SLEEP 1200
#define AL_MAX 800
#define POLL_NS 500
#define OG_PROF 0xECCBB988u
#define RK_P 24
#define RANK 1
__host__ __device__ constexpr int og_pre(int tile) { return (OG_PROF >> ((tile >> 4) * 4)) & 15; }
constexpr int OG_PRE2 = og_pre(127), OG_HSUM = og_pre(0) + og_pre(16) + og_pre(32) + og_pre(48) + og_pre(64) + og_pre(80) + og_pre(96);
#define OG_JOBS 7
#define OG_GRP 6
#define LD_FIRST 2
#define LD_STAG (OG_GRP / 2)
constexpr int OG_ST = 5, OG_NKB = T_DQKV / 64 - og_pre(0), OG_MOE = T_F / 32;
__device__ __forceinline__ int pre_kb(int i) { return (i >> 1) * 4 + (i & 1); }
__device__ __forceinline__ int own_kb(int i, int pre) { return i < (pre & ~1) ? pre_kb(i) + 2 : i + pre; }
constexpr int OG_POS = 8;
constexpr uint32_t OG_STAGE = 32768;
constexpr uint32_t OG_SCOL = AT_SBAR + 512;
constexpr uint32_t OG_SMISC = AT_SBAR + 2048;
constexpr uint32_t OG_SWD = AT_SQ, OG_PSLOT = AT_SQ;
constexpr uint32_t OG_XSLOT = AT_SQ + 32768;
constexpr uint32_t OG_OSLOT = 1 * OG_STAGE;
constexpr uint32_t OG_SRED = 3 * OG_STAGE;
constexpr uint32_t OG_SH2 = OG_SRED + 24576;
constexpr uint32_t OG_SSTAT = OG_SRED + 16384;
constexpr uint32_t OG_SGU = OG_SRED + 8192;
constexpr uint32_t OG_SFIN = OG_SGU + 256;
#define OGM 2
#define OG_MT(b) ((((b) >> OGM) & 15) ^ (((b) & 64) ? 15 : 0))
#define OG_NT(b) (((b) & ((1 << OGM) - 1)) + (((b) >> (4 + OGM)) << OGM))
__device__ __forceinline__ int tail_tile(uint32_t sbase) { mbar_wait_long(sbase + AT_SBAR + 336, 0); return (int)lds_u32(sbase + AT_SBAR + 408); }
#define TAIL_SETUP \
  const uint32_t bar_full = sbase + AT_SBAR, bar_empty = bar_full + 40; \
  const uint32_t bar_wd = bar_full + 168, bar_col = bar_full + 176, bar_out = bar_full + 184, bar_end = bar_full + 192; \
  const uint32_t bar_key = bar_full + 200, bar_h2 = bar_full + 208, bar_sel = bar_full + 216; \
  const int mt = OG_MT(tb), nt = OG_NT(tb); \
  const int m0 = mt * 128, n0 = nt * 128; \
  const bool has_moe = (int)bid < OG_MOE; \
  (void)bar_empty; (void)bar_wd; (void)bar_col; (void)bar_out; (void)bar_end; (void)bar_key; (void)bar_h2; (void)bar_sel; (void)m0; (void)n0; (void)has_moe;

__device__ __forceinline__ void tail_producer(uint32_t bid, uint32_t sbase, uint32_t ph, uint64_t pol, const CUtensorMap* tmA, const CUtensorMap* tmB, const CUtensorMap* tmD) {
  const int tb = tail_tile(sbase);
  TAIL_SETUP
  uint32_t stage = OG_POS % OG_ST;
  int kb = 0;
  #pragma unroll 1
  for (int seg = 0; seg < 2; seg++) {
    mbar_wait(bar_full + 264 + 80 * seg, 0);
    fence_proxy_async_global();
    const int end = 32 + 32 * seg - og_pre(tb);
    #pragma unroll 1
    for (; kb < end; kb++) {
      const uint32_t fb = bar_full + 8 * stage, sa = sbase + stage * OG_STAGE;
      const int k0 = own_kb(kb, og_pre(tb)) * 64;
      mbar_wait(bar_empty + 8 * stage, ph);
      mbar_expect_tx(fb, OG_STAGE);
      tma_load_3d_hint(sa + 16384, tmB, k0, 2 * nt, fb, pol);
      tma_load_2d_hint(sa, tmA, k0, m0, fb, pol);
      if (++stage == OG_ST) { stage = 0; ph ^= 1; }
    }
  }
  if (has_moe) {
    stage += stage & 1;
    mbar_wait(bar_empty + 8 * stage, ph);
    mbar_expect_tx(bar_wd, OG_STAGE);
    tma_load_3d_hint(sbase + stage * OG_STAGE, tmD, bid * 32, 8, bar_wd, pol);
  }
}

__device__ __forceinline__ uint32_t out2(uint32_t x1, uint32_t mb2, uint32_t ih, uint32_t il, uint32_t c1, uint32_t sb, uint32_t gb) {
  const uint32_t h2 = badd2(bmul2(ln_norm2b(x1, mb2, ih, il), c1), sb);
  return badd2(x1, bmul2(gb, bfma2(h2, 0u, h2)));
}
#define OGTIME gtime()
#define X_PACE 200
#define Y_SLACK 96
#define OG_STAG 3
#define X_PACE2 100
#define WD_PACE 300
__device__ __forceinline__ void tail_exchange(uint32_t bid, uint32_t sbase, const bf16* __restrict__ w_down, const bf16* __restrict__ w_r, const bf16* __restrict__ x, bf16* __restrict__ out) {
    const int lane = threadIdx.x & 31, wi = __shfl_sync(0xffffffffu, threadIdx.x >> 5, 0);
    if (wi == 3) {
      uint32_t a = bid, b = 0u;
      if (bid < AT_NFULL) mbar_wait_long(sbase + AT_SBAR + 312, 0);
      if (bid < OG_MOE) {
        asm volatile("mov.u32 %0, %%globaltimer_lo;" : "=r"(a));
        if (lane == 0 && (bid & 15) == 0) asm volatile("st.relaxed.gpu.global.u32 [%0], %1;" :: "l"(g_hcnt + 8 + (bid >> 4)), "r"((a & ~15u) | 8u | (bid >> 4)) : "memory");
        #pragma unroll 1
        for (unsigned int spin = 0; spin < (1u << 22) && __any_sync(0xffffffffu, b == 0u); spin++) {
          __nanosleep(200);
          asm volatile("ld.relaxed.gpu.global.u32 %0, [%1];" : "=r"(b) : "l"(g_hcnt + 8 + min(lane, 6)) : "memory");
        }
        a = RANK ? __popc(__ballot_sync(0xffffffffu, b < __shfl_sync(0xffffffffu, b, bid >> 4)) & 127u) * 16 + (bid & 15) : bid;
      }
      if (lane == 0) {
        sts_u32(sbase + AT_SBAR + 408, a);
        mbar_arrive(sbase + AT_SBAR + 336);
        b = 0u;
        if (bid < AT_NFULL) {
          unsigned int* tm = g_hcnt + 32 * (1 + (bid >> 4)) + 8;
          mbar_wait_long(sbase + AT_SBAR + 312, 1);
          asm volatile("mov.u32 %0, %%globaltimer_lo;" : "=r"(a));
          asm volatile("red.relaxed.gpu.global.max.u32 [%0], %1;" :: "l"(tm), "r"(a) : "memory");
          __nanosleep(AL_SLEEP);
          asm volatile("ld.relaxed.gpu.global.u32 %0, [%1];" : "=r"(b) : "l"(tm) : "memory");
          b -= a;
        }
        sts_u32(sbase + AT_SBAR + 412, b < AL_MAX ? b * 13 / 8 : 0u);
        mbar_arrive(sbase + AT_SBAR + 320);
      }
      named_bar_sync(15, 32);
    }
    const int tb = __shfl_sync(0xffffffffu, tail_tile(sbase), 0);
    TAIL_SETUP
    if (wi == 3) {
      mbar_wait_long(bar_full + 344, 0);
      float a = g_scal[lane], b = g_scal[32 + lane];
      #pragma unroll
      for (int i = 0; i < 3; i++) {
        const uint4 v = *reinterpret_cast<const uint4*>(g_col + nt * 1536 + i * 512 + lane * 16);
        sts_u32x4(sbase + OG_SCOL + i * 512 + lane * 16, v.x, v.y, v.z, v.w);
      }
      #pragma unroll
      for (int o = 16; o > 0; o >>= 1) { a += __shfl_xor_sync(0xffffffffu, a, o); b += __shfl_xor_sync(0xffffffffu, b, o); }
      if (lane == 0) sts_f32x2(sbase + OG_SMISC, a, b);
      const uint64_t pol = policy_evict_first();
      #pragma unroll 1
      for (int r = lane >> 4; r < 128; r += 4) {
        __nanosleep(X_PACE);
        if (X_PACE2) __nanosleep(X_PACE2);
        #pragma unroll
        for (int j = 0; j < 4; j += 2)
          asm volatile("cp.async.cg.shared.global.L2::cache_hint [%0], [%1], 16, %2;" :: "r"(sbase + OG_XSLOT + (lane & 8) * 2048 + (r + j) * 128 + (((lane ^ (r + j)) & 7) << 4)),
                       "l"(x + (size_t)(m0 + r + j) * T_D + n0 + (lane & 15) * 8), "l"(pol) : "memory");
      }
      asm volatile("cp.async.wait_all;" ::: "memory");
      __syncwarp();
      if (lane == 0) mbar_arrive(bar_col);
    } else if (wi == 2) {
      if (elect_one()) {
        const uint32_t b_free = bar_full + (bid < AT_NFULL ? 80 : 160);
        mbar_wait_long(b_free, 1);
        #pragma unroll 1
        for (unsigned int i = 0; i < (1u << 20) && ld_acquire(&g_hcnt[32 * (1 + (tb >> 3)) + 4 + ((tb >> 1) & 3)]) == 0u; i++) __nanosleep(POLL_NS);
        TL_MARK2(23, true);
        fence_proxy_async_global();
        TL_MARK2(4, true);
        mbar_expect_tx(bar_full + 272, 32768);
        bulk_load_hint(sbase + OG_PSLOT, g_pre + tb * 2048, 32768, bar_full + 272, policy_evict_first());
      }
      named_bar_sync(14, 32);
      if (has_moe) {
        mbar_wait_long(bar_full + 96, 1); mbar_wait(bar_full + 304, 0);
        const uint64_t pol = policy_evict_first();
        #pragma unroll 1
        for (int r = 0; r < 32; r++) {
          __nanosleep(WD_PACE);
          #pragma unroll
          for (int j = 0; j < 2; j++)
            asm volatile("cp.async.cg.shared.global.L2::cache_hint [%0], [%1], 16, %2;" :: "r"(sbase + OG_SWD + (4 * j + (lane >> 3)) * 4096 + r * 128 + (((lane ^ r) & 7) << 4)),
                         "l"((const uint8_t*)w_down + (size_t)bid * 65536 + r * 2048 + j * 512 + lane * 16), "l"(pol) : "memory");
        }
        asm volatile("cp.async.wait_all;" ::: "memory");
        __syncwarp();
        if (lane == 0) mbar_arrive(bar_wd);
      }
    }
    const uint4 wrv = ldg_nc_v4(w_r + threadIdx.x * 8);
    mbar_wait_long(bar_end, 0);
    if (threadIdx.x == 96) XT(10);
    TL_MARK2(22, lane == 0);
    if (wi == 0) {
      uint32_t k1 = 0u, k2 = 0u;
      #pragma unroll 1
      for (unsigned int spin = 0; spin < (1u << 22) && __any_sync(0xffffffffu, k1 == 0u); spin++) asm volatile("ld.relaxed.gpu.global.u32 %0, [%1];" : "=r"(k1) : "l"(g_key + lane) : "memory");
      TL_MARK2(28, lane == 0);
      warp_top2(k1, k2);
      if (lane == 0) {
        const uint32_t r1 = 0xffffu - (k1 & 0xffffu), r2 = 0xffffu - (k2 & 0xffffu);
        sts_u32x4(sbase + OG_SMISC + 64, r1, r2, (r1 >> 7) * 2, (r2 >> 7) * 2 + ((r1 >> 7) == (r2 >> 7)));
        mbar_arrive(bar_sel);
      }
    } else if (wi < 3) {
          mbar_wait(bar_key, 0);
          const uint4 kk = lds_u32x4(sbase + OG_SSTAT + 1024 + lane * 16);
          uint32_t k1 = max(kk.x, kk.y), k2 = min(kk.x, kk.y);
          k2 = max(max(k2, min(kk.z, kk.w)), min(k1, max(kk.z, kk.w))); k1 = max(k1, max(kk.z, kk.w));
          warp_top2(k1, k2);
          if (wi == 1) {
            if (lane == 0) {
              if (nt == (mt & 7)) st_relaxed2(g_key + mt * 2, k1, k2);
              sts_u32x2(sbase + OG_SMISC + 96, (~k1 >> 4) & 7u, (~k2 >> 4) & 7u);
              mbar_arrive(bar_full + 352);
            }
            TL_MARK2(27, lane == 0);
          } else {
            const uint32_t r = (~((lane & 16) ? k2 : k1)) & 127u, ch = lane & 15;
            const uint2 st = lds_u32x2(sbase + OG_SSTAT + r * 8);
            const uint4 xc = lds_u32x4(sbase + OG_XSLOT + (ch >> 3) * 16384 + r * 128 + (((ch ^ r) & 7) << 4));
            const uint4 c1 = lds_u32x4(sbase + OG_SCOL + 768 + ch * 16), sh = lds_u32x4(sbase + OG_SCOL + 1024 + ch * 16);
            const float inr = __uint_as_float(st.y);
            float* dst = reinterpret_cast<float*>(g_cand + (mt * 2 + (lane >> 4)) * 256 + nt * 16 + ch);
            st_tagged4(dst + 512, __uint_as_float(ln_mod2(xc.x, st.x, inr, c1.x, sh.x)), __uint_as_float(ln_mod2(xc.y, st.x, inr, c1.y, sh.y)),
                       __uint_as_float(ln_mod2(xc.z, st.x, inr, c1.z, sh.z)), __uint_as_float(ln_mod2(xc.w, st.x, inr, c1.w, sh.w)));
            st_tagged4(dst, __uint_as_float(xc.x), __uint_as_float(xc.y), __uint_as_float(xc.z), __uint_as_float(xc.w));
          }
    }
    mbar_wait(bar_sel, 0);
    const uint4 sel = lds_u32x4(sbase + OG_SMISC + 64);
    const int sel0 = (int)sel.x, sel1 = (int)sel.y;
    {
      const float* src0 = reinterpret_cast<const float*>(g_cand + sel.z * 256 + 128 + threadIdx.x);
      const float* src1 = reinterpret_cast<const float*>(g_cand + sel.w * 256 + 128 + threadIdx.x);
      float4 h0, h1;
      #pragma unroll 1
      for (unsigned int spin = 0; spin < (1u << 20); spin++) { h0 = ld_tagged4(src0); h1 = ld_tagged4(src1); if (__all_sync(0xffffffffu, tagged4(h0) & tagged4(h1))) break; }
      sts_f32x4(sbase + OG_SH2 + threadIdx.x * 16, h0.x, h0.y, h0.z, h0.w);
      sts_f32x4(sbase + OG_SH2 + 2048 + threadIdx.x * 16, h1.x, h1.y, h1.z, h1.w);
      __syncwarp();
      if (lane == 0) mbar_arrive(bar_h2);
      TL_MARK2(12, lane == 0);
      if (bid >> 6) h0 = h1;
      float v[8], wr[8];
      unpack8(make_uint4(__float_as_uint(h0.x), __float_as_uint(h0.y), __float_as_uint(h0.z), __float_as_uint(h0.w)), v); unpack8(wrv, wr);
      float r = 0.f;
      #pragma unroll
      for (int i = 0; i < 8; i++) r = fmaf(v[i], wr[i], r);
      #pragma unroll
      for (int o = 16; o > 0; o >>= 1) r += __shfl_xor_sync(0xffffffffu, r, o);
      if (lane == 0) sts_f32(sbase + OG_SMISC + 192 + wi * 4, r);
    }
    mbar_wait(bar_out, 0);
    {
      const uint2 cg = lds_u32x2(sbase + OG_SMISC + 96);
      #pragma unroll
      for (int i = 0; i < 4; i++) {
        const int r = (i < 2 ? cg.x : cg.y) * 16 + (i & 1) * 8 + (threadIdx.x >> 4), ch = threadIdx.x & 15;
        if (m0 + r != sel0 && m0 + r != sel1)
          *reinterpret_cast<uint4*>(out + (size_t)(m0 + r) * T_D + n0 + ch * 8) =
              lds_u32x4(sbase + OG_OSLOT + (ch >> 3) * 16384 + r * 128 + (((ch & 7) ^ (r & 7)) << 4));
      }
    }
    if (bid == 0 && threadIdx.x < 68) *reinterpret_cast<uint4*>(g_hcnt + 32 * (threadIdx.x >> 2) + 4 * (threadIdx.x & 3)) = make_uint4(0u, 0u, 0u, 0u);
    if (threadIdx.x < 64) g_modpart[bid * 64 + threadIdx.x] = 0.f;
    {
      const int tk = bid >> 6, c0 = (bid & 63) * 16;
      const uint32_t gb2 = *reinterpret_cast<const uint32_t*>(g_col + (c0 >> 7) * 1536 + 512 + 768 + ((c0 & 127) + (threadIdx.x & 14)) * 2);
      const uint32_t* xp = reinterpret_cast<const uint32_t*>(g_cand + (tk ? sel.w : sel.z) * 256) + ((c0 + (threadIdx.x & 14)) >> 1);
      uint32_t x2 = 0u;
      #pragma unroll 1
      for (unsigned int spin = 0; spin < (1u << 20) && __any_sync(0xffffffffu, x2 == 0u); spin++) asm volatile("ld.relaxed.gpu.global.u32 %0, [%1];" : "=r"(x2) : "l"(xp) : "memory");
      const float* src = g_ypart + (size_t)((threadIdx.x >> 2) * 2 + tk) * T_D + c0 + (threadIdx.x & 3) * 4;
      const bool four = threadIdx.x < (OG_MOE - 96) * 4;
      named_bar_sync(10, 128);
      const uint4 rp = lds_u32x4(sbase + OG_SMISC + 192);
      const float rs = rbf(sigmoid_f(rbf((__uint_as_float(rp.x) + __uint_as_float(rp.y)) + (__uint_as_float(rp.z) + __uint_as_float(rp.w)))));
      const uint32_t h2p = lds_u32(sbase + OG_SH2 + tk * 2048 + (c0 + (threadIdx.x & 14)) * 2);
      const float fh = (lane & 1) ? bfhi(h2p) : bflo(h2p), fz = rbf(fh * 0.0f), fx = (lane & 1) ? bfhi(x2) : bflo(x2), fg = (lane & 1) ? bfhi(gb2) : bflo(gb2);
      bf16* dst = out + (size_t)(tk ? sel1 : sel0) * T_D + c0 + threadIdx.x;
      if (threadIdx.x == 0) hint_wait(CNT_Y, (uint32_t)(OG_MOE - Y_SLACK));
      named_bar_sync(10, 128);
      float4 p0, p1, p2, p3;
      #pragma unroll 1
      for (unsigned int spin = 0; spin < (1u << 20); spin++) {
        p0 = ld_tagged4(src); p1 = ld_tagged4(src + 64 * T_D); p2 = ld_tagged4(src + 128 * T_D); p3 = ld_tagged4(four ? src + 192 * T_D : src);
        if (__all_sync(0xffffffffu, tagged4(p0) & tagged4(p1) & tagged4(p2) & tagged4(p3))) break;
      }
      if (four) { p2.x += p3.x; p2.y += p3.y; p2.z += p3.z; p2.w += p3.w; }
      p0.x = (p0.x + p1.x) + p2.x; p0.y = (p0.y + p1.y) + p2.y; p0.z = (p0.z + p1.z) + p2.z; p0.w = (p0.w + p1.w) + p2.w;
      #pragma unroll
      for (int o = 4; o <= 16; o <<= 1) {
        p0.x += __shfl_xor_sync(0xffffffffu, p0.x, o); p0.y += __shfl_xor_sync(0xffffffffu, p0.y, o);
        p0.z += __shfl_xor_sync(0xffffffffu, p0.z, o); p0.w += __shfl_xor_sync(0xffffffffu, p0.w, o);
      }
      if (lane < 4) sts_f32x4(sbase + OG_SFIN + (threadIdx.x >> 5) * 64 + lane * 16, p0.x, p0.y, p0.z, p0.w);
      named_bar_sync(10, 128);
      TL_MARK2(21, threadIdx.x == 0);
      if (threadIdx.x < 16) {
        const uint32_t ya = sbase + OG_SFIN + threadIdx.x * 4;
        float y = (lds_f32(ya) + lds_f32(ya + 64)) + (lds_f32(ya + 128) + lds_f32(ya + 192));
        y = rbf(y);
        y = rbf(y * rs);
        *dst = __float2bfloat16_rn(fx + rbf(fg * rbf(fh + rbf(fz + y))));
      }
    }
    if (threadIdx.x == 0) XT(11);
    TL_END(4, threadIdx.x == 0);
}

__device__ __forceinline__ void load_pre(uint4* pre, uint32_t sbase, uint32_t buf, int t2) {
  mbar_wait(sbase + AT_SBAR + 272, 0);
  #pragma unroll
  for (int i = 0; i < 8; i++) pre[i] = lds_u32x4(sbase + buf + i * 4096 + t2 * 16);
}
__device__ __forceinline__ void tail_consumer(uint32_t bid, uint32_t sbase, const CUtensorMap* tmOut, const uint4 (&pre)[8], int cwg, const bf16* __restrict__ w_gate, const bf16* __restrict__ w_up) {
    const uint32_t c0 = clock_lo();
    mbar_wait(sbase + AT_SBAR + 320, 0);
    const uint2 td = lds_u32x2(sbase + AT_SBAR + 408);
    const int tb = __shfl_sync(0xffffffffu, (int)td.x, 0);
    TAIL_SETUP
    const int tid = threadIdx.x & 127, t2 = threadIdx.x - 128;
    const int warp = tid >> 5, lane = tid & 31, w8 = t2 >> 5;
    const uint32_t dbase = (sbase & 0x3FFFFu) >> 4;
    const uint32_t a_base = dbase + ((cwg * 8192) >> 4) + (1u << 16);
    const uint32_t b_base = dbase + (16384 >> 4) + (512u << 16);
    TL_MARK2(25, threadIdx.x == 128);
    const uint64_t pol = policy_evict_first();
    const bf16* pw = ((lane & 16) ? w_up : w_gate) + (size_t)(w8 * 128 + (lane & 3) * 4) * T_F + (has_moe ? bid : 0) * 32 + ((lane >> 2) & 3) * 8;
    uint4 wv[32];
    float acc[64];
    #pragma unroll
    for (int i = 0; i < 8; i++) {
      acc[8 * i] = bflo(pre[i].x); acc[8 * i + 1] = bfhi(pre[i].x); acc[8 * i + 2] = bflo(pre[i].y); acc[8 * i + 3] = bfhi(pre[i].y);
      acc[8 * i + 4] = bflo(pre[i].z); acc[8 * i + 5] = bfhi(pre[i].z); acc[8 * i + 6] = bflo(pre[i].w); acc[8 * i + 7] = bfhi(pre[i].w);
    }
    if (lane == 0) mbar_arrive(bar_full + 304);
    while (__any_sync(0xffffffffu, clock_lo() - c0 < td.y)) {}
    uint32_t stage = OG_POS % OG_ST;
    {
      uint32_t phase = (OG_POS / OG_ST) & 1, prev = 12;
      int kb = 0;
      #pragma unroll
      for (int g = 0; g <= OG_NG; g++) {
        const int end = g == OG_NG ? 64 - og_pre(tb) : LD_FIRST + g * OG_GRP + LD_STAG * cwg;
        #pragma unroll 1
        do {
          mbar_wait(bar_full + 8 * stage, phase);
          if (OG_STAG > 0 && g == OG_NG && cwg == 1 && kb == end - OG_STAG) named_bar_sync(7, 256);
          const uint32_t a_lo = a_base + stage * (OG_STAGE >> 4), b_lo = b_base + stage * (OG_STAGE >> 4);
          wgmma_fence();
          wgmma_m64n128k16_ss_tb<0, 0>(acc, a_lo, b_lo, 1);
          wgmma_m64n128k16_ss_tb<2, 128>(acc, a_lo, b_lo, 1);
          wgmma_m64n128k16_ss_tb<4, 256>(acc, a_lo, b_lo, 1);
          wgmma_m64n128k16_ss_tb<6, 384>(acc, a_lo, b_lo, 1);
          wgmma_commit();
          if (OG_STAG > 0 && g == OG_NG && cwg == 0 && kb == end - 1) named_bar_arrive(7, 256);
          wgmma_wait<1>();
          if (tid == 0) mbar_arrive(bar_empty + 8 * prev);
          prev = stage;
          if (++stage == OG_ST) { stage = 0; phase ^= 1; }
        } while (++kb < end);
        #pragma unroll
        for (int j = 4 * g; j < 4 * g + 4 && j < 32; j++) wv[j] = ldg_stream_v4(pw + (size_t)(16 * (j >> 2) + (j & 3)) * T_F, pol);
      }
    }
    mbar_wait(bar_col, 0);
    if (__builtin_expect(!has_moe, 0)) {
      load_pre(wv, sbase, AT_SQ, t2);
    }
    wgmma_wait<0>();
    fence_regs(acc);
    if (__builtin_expect(!has_moe, 0)) {
      #pragma unroll
      for (int i = 0; i < 8; i++) {
        acc[8 * i] += bflo(wv[i].x); acc[8 * i + 1] += bfhi(wv[i].x); acc[8 * i + 2] += bflo(wv[i].y); acc[8 * i + 3] += bfhi(wv[i].y);
        acc[8 * i + 4] += bflo(wv[i].z); acc[8 * i + 5] += bfhi(wv[i].z); acc[8 * i + 6] += bflo(wv[i].w); acc[8 * i + 7] += bfhi(wv[i].w);
      }
    }
    if (tid == 0) mbar_arrive(bar_end);
    TL_MARK2(9, lane == 0);
    const int q2 = 2 * (lane & 3);
    const uint32_t frag = (64 * cwg + 16 * warp + (lane & 7) + 8 * ((lane >> 3) & 1)) * 128;
    const int fsw = lane & 7, fhi = lane >> 4;
    {
      float dl[4] = {0.f, 0.f, 0.f, 0.f}, da[4] = {0.f, 0.f, 0.f, 0.f}, db[4] = {0.f, 0.f, 0.f, 0.f};
      const uint32_t tb2 = sbase + OG_SCOL + (lane & 8) * 32 + (lane & 3) * 8, g = lane >> 2;
      const uint32_t msk = (g == 1 || g == 2) ? 0xffffffffu : 0u, one = g == 0 ? 0x3F803F80u : 0u;
      uint32_t xr[8][4];
      #pragma unroll
      for (int hf = 0; hf < 2; hf++) {
        uint32_t ga[8];
        uint2 cw[4];
        #pragma unroll
        for (int i = 0; i < 4; i++) {
          ldmatrix_x4(sbase + OG_XSLOT + hf * 16384 + frag + (((2 * i + fhi) ^ fsw) << 4), xr[4 * hf + i][0], xr[4 * hf + i][1], xr[4 * hf + i][2], xr[4 * hf + i][3]);
          ga[2 * i] = lds_u32(sbase + OG_SCOL + 512 + (64 * hf + 16 * i + q2) * 2); ga[2 * i + 1] = lds_u32(sbase + OG_SCOL + 512 + (64 * hf + 16 * i + 8 + q2) * 2);
          cw[i] = lds_u32x2(tb2 + (8 * hf + 2 * i) * 16);
        }
        #pragma unroll
        for (int i = 0; i < 4; i++) {
          uint32_t* x4 = xr[4 * hf + i];
          #pragma unroll
          for (int e = 0; e < 4; e++) x4[e] = badd2(x4[e], bmul2(ga[2 * i + (e >> 1)], pack_bf16(acc[32 * hf + 8 * i + 2 * e], acc[32 * hf + 8 * i + 2 * e + 1])));
          mma_bf16(dl, x4[0], x4[1], x4[2], x4[3], (cw[i].x & msk) | one, (cw[i].y & msk) | one);
          mma_bf16(da, x4[0], x4[1], x4[2], x4[3], x4[0], x4[2]);
          mma_bf16(db, x4[0], x4[1], x4[2], x4[3], x4[1], x4[3]);
        }
      }
      {
        const int dsrc = (lane & ~3) + (g >> 1);
        const float qa = __shfl_sync(0xffffffffu, (g & 1) ? da[1] : da[0], dsrc), qb = __shfl_sync(0xffffffffu, (g & 1) ? db[3] : db[2], dsrc);
        const float e0 = __shfl_xor_sync(0xffffffffu, (lane & 1) ? dl[0] : dl[2], 1), e1 = __shfl_xor_sync(0xffffffffu, dl[3], 1);
        if ((lane & 3) < 2) {
          const bool hi = lane & 1;
          st_tagged4(reinterpret_cast<float*>(g_part1 + ((mt * 8 + w8) * 8 + nt) * 16 + g + (hi ? 8 : 0)),
                     hi ? e0 : dl[0], hi ? qb : qa, hi ? e1 + dl[2] : dl[1] + e0, 1.0f);
        }
      }
      #pragma unroll
      for (int i = 0; i < 8; i++) stmatrix_x4(sbase + OG_XSLOT + (i >> 2) * 16384 + frag + (((2 * (i & 3) + fhi) ^ fsw) << 4), xr[i][0], xr[i][1], xr[i][2], xr[i][3]);
    }
    TL_MARK2(10, lane == 0);
    uint4 wd[16];
    if (has_moe) mbar_wait(bar_wd, 0);
    #pragma unroll
    for (int i = 0; i < 16; i++) wd[i] = lds_u32x4(sbase + (cwg ? (stage + (stage & 1)) * OG_STAGE : OG_SWD) + warp * 8192 + (i >> 3) * 4096 + (i & 6) * 512 + (i & 1) * 128 + (lane & 3) * 256 + (((lane >> 2) ^ (2 * (lane & 3) + (i & 1))) << 4));
    {
      const float* src = reinterpret_cast<const float*>(g_part1 + ((mt * 8 + w8) * 8 + (lane & 1) * 4) * 16 + (lane >> 1));
      float4 v, v1, v2, v3;
      #pragma unroll 1
      for (unsigned int spin = 0; spin < (1u << 22); spin++) {
        v = ld_tagged4(src); v1 = ld_tagged4(src + 64); v2 = ld_tagged4(src + 128); v3 = ld_tagged4(src + 192);
        if (__all_sync(0xffffffffu, tagged4(v) & tagged4(v1) & tagged4(v2) & tagged4(v3))) break;
        __nanosleep(100);
      }
      __syncwarp();
      TL_MARK2(26, lane == 0);
      v.x = (v.x + v1.x) + (v2.x + v3.x); v.y = (v.y + v1.y) + (v2.y + v3.y); v.z = (v.z + v1.z) + (v2.z + v3.z);
      v.x += __shfl_xor_sync(0xffffffffu, v.x, 1); v.y += __shfl_xor_sync(0xffffffffu, v.y, 1); v.z += __shfl_xor_sync(0xffffffffu, v.z, 1);
      const float mean = v.x * (1.0f / T_D);
      const float var = fmaxf(fmaf(-mean, mean, v.y * (1.0f / T_D)), 0.f);
      const uint32_t mb2 = pack_bf16(mean, mean);
      const float inv = rcp_approx(rbf(sqrt_approx(rbf(rbf(var) + 1e-05f))));
      {
        const float2 sc = lds_f32x2(sbase + OG_SMISC);
        const uint32_t key = rank_key(rbf(fmaf(fmaf(-bflo(mb2), sc.x, v.z), inv, sc.y)), m0 + 16 * w8 + (lane >> 1));
        mbar_wait(bar_end, 0);
        if (lane & 1) sts_u32(sbase + OG_SSTAT + 1024 + (16 * w8 + (lane >> 1)) * 4, key);
        else sts_u32x2(sbase + OG_SSTAT + (16 * w8 + (lane >> 1)) * 8, mb2, __float_as_uint(inv));
        __syncwarp();
        if (lane == 0) mbar_arrive(bar_key);
      }
      const uint32_t ih = pack_bf16(inv, inv), il = pack_bf16(inv - bflo(ih), inv - bflo(ih));
      const uint32_t mba = __shfl_sync(0xffffffffu, mb2, 2 * (lane >> 2)), mbb = __shfl_sync(0xffffffffu, mb2, 2 * (lane >> 2) + 16);
      const uint32_t iha = __shfl_sync(0xffffffffu, ih, 2 * (lane >> 2)), ihb = __shfl_sync(0xffffffffu, ih, 2 * (lane >> 2) + 16);
      const uint32_t ila = __shfl_sync(0xffffffffu, il, 2 * (lane >> 2)), ilb = __shfl_sync(0xffffffffu, il, 2 * (lane >> 2) + 16);
      #pragma unroll 1
      for (int J0 = 0; J0 < 16; J0 += 4) {
        uint32_t xr[2][4], cv[4][3];
        #pragma unroll
        for (int i = 0; i < 2; i++) {
          ldmatrix_x4(sbase + OG_XSLOT + (J0 >> 3) * 16384 + frag + ((((J0 & 7) + 2 * i + fhi) ^ fsw) << 4), xr[i][0], xr[i][1], xr[i][2], xr[i][3]);
          #pragma unroll
          for (int h = 0; h < 2; h++)
            #pragma unroll
            for (int k = 0; k < 3; k++) cv[2 * i + h][k] = lds_u32(sbase + OG_SCOL + 768 + 256 * k + (8 * (J0 + 2 * i + h) + q2) * 2);
        }
        #pragma unroll
        for (int i = 0; i < 2; i++) {
          #pragma unroll
          for (int h = 0; h < 2; h++) {
            xr[i][2 * h] = out2(xr[i][2 * h], mba, iha, ila, cv[2 * i + h][0], cv[2 * i + h][1], cv[2 * i + h][2]);
            xr[i][2 * h + 1] = out2(xr[i][2 * h + 1], mbb, ihb, ilb, cv[2 * i + h][0], cv[2 * i + h][1], cv[2 * i + h][2]);
          }
          stmatrix_x4(sbase + OG_OSLOT + (J0 >> 3) * 16384 + frag + ((((J0 & 7) + 2 * i + fhi) ^ fsw) << 4), xr[i][0], xr[i][1], xr[i][2], xr[i][3]);
        }
      }
      fence_proxy_async();
      mbar_wait(bar_full + 352, 0);
      const uint2 cg = lds_u32x2(sbase + OG_SMISC + 96);
      __syncwarp();
      if (elect_one()) {
        mbar_arrive(bar_out);
        if (cg.x != w8 && cg.y != w8) {
          asm volatile("cp.async.bulk.tensor.2d.global.shared::cta.bulk_group [%0, {%2, %3}], [%1];" :: "l"(tmOut), "r"(sbase + OG_OSLOT + w8 * 2048), "r"(n0), "r"(m0 + 16 * w8) : "memory");
          asm volatile("cp.async.bulk.tensor.2d.global.shared::cta.bulk_group [%0, {%2, %3}], [%1];" :: "l"(tmOut), "r"(sbase + OG_OSLOT + 16384 + w8 * 2048), "r"(n0 + 64), "r"(m0 + 16 * w8) : "memory");
          bulk_commit();
        }
      }
      TL_MARK2(24, lane == 0);
    }
    if (has_moe) mbar_wait(bar_h2, 0);
    TL_MARK2(13, lane == 0);
    if (has_moe) {
      const GemvSel sel = gemv_sel(lane);
      {
        float d[4][4];
        #pragma unroll
        for (int c = 0; c < 4; c++) { d[c][0] = 0.f; d[c][1] = 0.f; d[c][2] = 0.f; d[c][3] = 0.f; }
        #pragma unroll
        for (int st = 0; st < 8; st++) {
          const uint2 hb = lds_u32x2(sbase + OG_SH2 + ((lane >> 2) & 1) * 2048 + (w8 * 128 + st * 16 + (lane & 3) * 4) * 2);
          #pragma unroll
          for (int j = 0; j < 4; j++) mma_bf16(d[j], wv[4 * st + j].x, wv[4 * st + j].y, wv[4 * st + j].z, wv[4 * st + j].w, GEMV_B0(j, hb, sel), GEMV_B1(j, hb, sel));
        }
        #pragma unroll
        for (int e = 0; e < 4; e++) d[0][e] = (d[0][e] + d[1][e]) + (d[2][e] + d[3][e]);
        const float4 r = gemv_out(d[0], lane);
        sts_f32x4(sbase + OG_SRED + w8 * 512 + (((lane >> 4) * 2 + (lane & 1)) * 32 + ((lane >> 2) & 3) * 8 + (lane & 2) * 2) * 4, r.x, r.y, r.z, r.w);
      }
      named_bar_sync(9, 256);
      if (t2 < 64) {
        float gp[8], up[8];
        #pragma unroll
        for (int w = 0; w < 8; w++) { gp[w] = lds_f32(sbase + OG_SRED + w * 512 + t2 * 4); up[w] = lds_f32(sbase + OG_SRED + w * 512 + 256 + t2 * 4); }
        const float gs = ((gp[0] + gp[1]) + (gp[2] + gp[3])) + ((gp[4] + gp[5]) + (gp[6] + gp[7]));
        const float us = ((up[0] + up[1]) + (up[2] + up[3])) + ((up[4] + up[5]) + (up[6] + up[7]));
        asm volatile("st.shared.u16 [%0], %1;" :: "r"(sbase + OG_SGU + ((t2 & ~15) + ((t2 >> 1) & 3) * 4 + ((t2 >> 3) & 1) * 2 + (t2 & 1)) * 2), "h"((uint16_t)pack_bf16(silu_bf(rbf(gs)) * rbf(us), 0.f)) : "memory");
      }
      named_bar_sync(9, 256);
      TL_MARK2(20, threadIdx.x == 128);
      float d[4][4];
      #pragma unroll
      for (int c = 0; c < 4; c++) { d[c][0] = 0.f; d[c][1] = 0.f; d[c][2] = 0.f; d[c][3] = 0.f; }
      #pragma unroll
      for (int st = 0; st < 2; st++) {
        const uint2 g = lds_u32x2(sbase + OG_SGU + ((lane >> 2) & 1) * 64 + st * 32 + (lane & 3) * 8);
        #pragma unroll
        for (int j = 0; j < 4; j++) {
          const uint32_t b0 = GEMV_B0(j, g, sel), b1 = GEMV_B1(j, g, sel);
          mma_bf16(d[j & 1], wd[4 * st + j].x, wd[4 * st + j].y, wd[4 * st + j].z, wd[4 * st + j].w, b0, b1);
          mma_bf16(d[2 + (j & 1)], wd[8 + 4 * st + j].x, wd[8 + 4 * st + j].y, wd[8 + 4 * st + j].z, wd[8 + 4 * st + j].w, b0, b1);
        }
      }
      #pragma unroll
      for (int e = 0; e < 4; e++) { d[0][e] += d[1][e]; d[2][e] += d[3][e]; }
      const float4 y0 = gemv_out(d[0], lane), y1 = gemv_out(d[2], lane);
      float* yp = g_ypart + (size_t)(bid * 2 + (lane & 1)) * T_D + w8 * 128 + (lane >> 2) * 8 + (lane & 2) * 2;
      st_tagged4(yp, y0.x, y0.y, y0.z, y0.w);
      st_tagged4(yp + 64, y1.x, y1.y, y1.z, y1.w);
      named_bar_sync(9, 256);
      if (t2 == 0) hint_arrive(CNT_Y);
    }
    bulk_wait_read<0>();
    TL_MARK2(14, threadIdx.x == 128);
    TL_CLK(4, 1, threadIdx.x == 128);
}

__device__ __forceinline__ int help_njobs(uint32_t bid) { return bid < 128 ? OG_JOBS : 16 - OG_JOBS; }
__device__ __forceinline__ int help_job(uint32_t bid, int i) { return (i < OG_JOBS ? 16 * i + (bid >> 7) * 2 : 112 + (i - OG_JOBS) * 2) + (bid & 3) * 4; }
__device__ __noinline__ void store_warp(uint32_t bid, uint32_t sbase, const CUtensorMap* tmO, int item0, int n_items) {
  if (elect_one()) {
    const uint32_t bars = sbase + AT_SBAR, b_q0 = bars + 80, b_ob = bars + 96, b_ordy = bars + 104, b_acq = bars + 264;
    const unsigned int* cnt = g_hcnt + 32 * (1 + OG_MT(124)) + 2;
    #pragma unroll 1
    for (int q = 0; q < 4 * n_items; q++) {
      const int item = item0 + (q >> 2) * 128, h = (q >> 1) & 1, w = q & 1;
      const bool last = (q >> 2) == n_items - 1;
      if (q == 4 * n_items - 4) { mbar_wait_long(bars + 288, 0); red_release_add(&g_hcnt[1], 1u); }
      mbar_wait_long(b_ordy + 8 * (q & 3), q >> 2);
      store_o(tmO, (h ? (last ? sbase + AT_SQ + 32768 : sbase + 2 * 32768) : sbase + AT_SQ) + w * 8192, (item >> 4) * 2 + h, (item & 15) * 128 + w * 64);
      if (w) {
        bulk_wait_read<0>();
        mbar_arrive(h ? b_ob : b_q0);
        bulk_wait<0>();
        fence_proxy_async_global();
        asm volatile("fence.acq_rel.gpu;" ::: "memory");
        hint_arrive(&g_hcnt[32 * (1 + (item & 15)) + 2 + (item >> 7)]);
        if (!h && item < 128) hint_arrive(&g_hcnt[2]);
        if (q == 5) { const int tb = tail_tile(sbase); cnt = g_hcnt + 32 * (1 + OG_MT(tb)) + 2; spin_until(cnt, 16u); mbar_arrive(b_acq); }
      }
    }
    if (n_items == 1) {
      #pragma unroll 1
      for (int i = 0; i < help_njobs(bid); i++) {
        mbar_wait_long(b_acq + 16, i & 1);
        TL_MARK2(23, i == OG_JOBS - 1);
        red_release_add(&g_hcnt[32 * (1 + (help_job(bid, i) >> 3)) + 4 + ((help_job(bid, i) >> 1) & 3)], 1u);
        TL_MARK2(4, i == OG_JOBS - 1);
        if (i == PRE_X - 1) { spin_until(&g_hcnt[1], 132u); mbar_arrive(b_acq + 32); }
      }
    }
    if (bid < 128) {
      if (n_items == 1) { spin_until(cnt, 16u); mbar_arrive(b_acq); }
      spin_until(&g_hcnt[0], 128u); spin_until(cnt + 1, 16u); mbar_arrive(b_acq + 80);
    }
  }
}

__device__ __forceinline__ uint32_t role_of_sm(uint32_t sm) {
  const uint32_t t = sm >> 1, u = t - 32u, d = (u * 37u) >> 8;
  return (t < 32u ? ((t + 7u) & 7u) * 16u + (t >> 3) * 2u : t < 60u ? (u - 7u * d) * 16u + (4u + d) * 2u : t < 62u ? 2u * t + 8u : 2u * t - 4u) + (sm & 1u);
}
__global__ void __launch_bounds__(384, 1)
fused_kernel(const __grid_constant__ CUtensorMap tmH, const __grid_constant__ CUtensorMap tmW, const __grid_constant__ CUtensorMap tmK,
            const __grid_constant__ CUtensorMap tmV, const __grid_constant__ CUtensorMap tmO, const __grid_constant__ CUtensorMap tmOl, const __grid_constant__ CUtensorMap tmWo,
            const __grid_constant__ CUtensorMap tmD, const __grid_constant__ CUtensorMap tmOut, const __grid_constant__ CUtensorMap tmM, uint32_t zero,
            const uint8_t* __restrict__ pf_wo, const bf16* __restrict__ kc, const bf16* __restrict__ vc,
            const bf16* __restrict__ x, const bf16* __restrict__ cvec, const bf16* __restrict__ w_mod, const bf16* __restrict__ w_r,
            const bf16* __restrict__ w_gate, const bf16* __restrict__ w_up, const bf16* __restrict__ w_down, bf16* __restrict__ out)
{
  uint32_t bid, nsm;
  asm volatile("mov.u32 %0, %%smid;" : "=r"(bid));
  asm volatile("mov.u32 %0, %%nsmid;" : "=r"(nsm));
  bid = __shfl_sync(0xffffffffu, nsm == 132u ? role_of_sm(bid) : blockIdx.x, 0);
  extern __shared__ __align__(1024) uint8_t smem_raw[];
  const uint32_t sbase = smem_u32(smem_raw);
  const uint32_t bars = sbase + AT_SBAR;
  const uint32_t b_full = bars, b_empty = bars + 40;
  const uint32_t b_q0 = bars + 80, b_q1 = bars + 88;
  const uint32_t b_ob = bars + 96;
  const uint32_t b_ordy = bars + 104;
  const uint32_t b_pin = bars + 136;
  const uint32_t b_head = bars + 144;
  const uint32_t b_go = bars + 152;
  const uint32_t b_x = bars + 160;
  const int wg = __shfl_sync(0xffffffffu, threadIdx.x >> 7, 0);
  const bool single = bid >= AT_NFULL;
  const int item0 = __shfl_sync(0xffffffffu, bid < 128 ? (int)bid : (int)bid + 124, 0), n_items = __shfl_sync(0xffffffffu, single ? 1 : 2, 0);
  TL_START(3);
  if (threadIdx.x == 0) {
    if (sbase & 1023u) __trap();
    for (int i = 0; i < 5; i++) { mbar_init(b_full + 8 * i, 1); mbar_init(b_empty + 8 * i, 2); }
    mbar_init(b_q0, 1); mbar_init(b_q1, 8); mbar_init(b_ob, 1);
    for (int i = 0; i < 4; i++) mbar_init(b_ordy + 8 * i, 4);
    mbar_init(b_pin, 1); mbar_init(b_head, bid < 128 ? 8 : 1); mbar_init(b_go, 1); mbar_init(b_x, 1);
    mbar_init(bars + 168, 2); mbar_init(bars + 176, 1); mbar_init(bars + 184, 8); mbar_init(bars + 192, 2);
    mbar_init(bars + 200, 8); mbar_init(bars + 208, 4); mbar_init(bars + 216, 1); mbar_init(bars + 264, 1); mbar_init(bars + 272, 1); mbar_init(bars + 280, 8); mbar_init(bars + 288, 1); mbar_init(bars + 296, 1); mbar_init(bars + 304, 8); mbar_init(bars + 312, 1); mbar_init(bars + 320, 1); mbar_init(bars + 328, 1); mbar_init(bars + 336, 1); mbar_init(bars + 344, 1); mbar_init(bars + 352, 1);
    sts_u32(bars + 400, bid);
    fence_mbar_init();
  }

  if (wg == 0) {
    reg_dealloc<AT_PREG>();
    if (threadIdx.x < 32) { __syncwarp(); named_bar_arrive(6, 384); }
    if (threadIdx.x >= 64) {
      named_bar_sync(6, 384);
      if (bid < 128) {
        named_bar_sync(threadIdx.x >= 96 ? 8 : 9, 288);
        if ((threadIdx.x & 31) == 0) red_release_add(&g_hcnt[32 * (1 + (bid >> 3)) + (threadIdx.x >= 96)], 1u);
        TL_MARK2(11, threadIdx.x == 64);
      }
      if (bid < 128) {
        mbar_wait(MOD_AT, 0);
        mod_rest(bid, sbase + OG_SCOL, b_q1, threadIdx.x - 64, cvec, w_mod, w_r);
      }
    } else if (threadIdx.x >= 32) {
      named_bar_sync(6, 384);
      store_warp(bid, sbase, &tmO, item0, n_items);
      __syncwarp();
    } else {
     if (elect_one()) {
      const uint64_t pol = policy_evict_first();
      if (bid < 128) {
        mbar_expect_tx(b_x, 32768);
        if (X_DLY) { const uint32_t c0 = clock_lo(); while (clock_lo() - c0 < X_DLY) {} }
        bulk_load_hint(sbase + 4 * 32768, x + (size_t)bid * 16 * T_D, 32768, b_x, pol);
      }
      prefetch_tmap(&tmW); prefetch_tmap(&tmM); prefetch_tmap(&tmH); prefetch_tmap(&tmWo); prefetch_tmap(&tmOl);
      {
        const uint32_t c0 = clock_lo();
        while (clock_lo() - c0 < W_DLY) {}
        if (bid < 128 && (bid & 15) >= 4 * H_SPLIT) {
          mbar_expect_tx(bars + 328, 32768);
          tma_load_2d_hint(sbase + 3 * 32768, &tmM, (bid & 31) * 64, (bid >> 5) * 256, bars + 328, pol);
        }
        while (clock_lo() - c0 < W_DLY + W_FIRST) {}
      }
      uint32_t slot = 0, ph = 1;
      #pragma unroll 1
      for (int it = 0; it < n_items; it++) {
        const int item = item0 + it * 128, hp = item >> 4, qt = item & 15;
        const bool first = it == 0;
        #pragma unroll 1
        for (int j = 0; j < T_D / 64; j++) {
          const uint32_t sl = ring_slot(qp_pos(j, it)), fb = b_full + 8 * sl;
          mbar_wait_long(b_empty + 8 * sl, ring_par(qp_pos(j, it)) ^ ((j >> 2) & 1) ^ 1);
          if (first && j == 3) mbar_wait(b_head, 0);
          mbar_expect_tx(fb, 49152);
          tma_load_3d_hint(sbase + sl * 32768, &tmW, j * 64, hp * 4, fb, pol);
          if (first && j < PRE_B) {
            if (j == PRE_B - 1) {
              spin_until(&g_hcnt[32 * (1 + qt)], 8u);
              TL_MARK2(16, true);
              fence_proxy_async_global();
              #pragma unroll 1
              for (int i = 0; i < PRE_B; i++) tma_load_2d(sbase + AT_SQ + i * 16384, &tmH, i * 64, qt * 128, b_full + 8 * i);
              mbar_arrive(b_go);
            }
          } else {
            if (first && j == 4 * H_SPLIT) { spin_until(&g_hcnt[32 * (1 + qt) + 1], 8u); fence_proxy_async_global(); }
            if (!first && (j == 0 || j == 2)) mbar_wait(j ? b_q1 : b_q0, 0);
            tma_load_2d_hint(sbase + AT_SQ + (j & 3) * 16384, &tmH, j * 64, qt * 128, fb, first ? pol_normal() : pol);
          }
        }
        #pragma unroll 1
        for (int j = 0; j < 4 * AT_NBLK; j++) {
          const bool isv = (j > 0 && !(j & 1)) || j == 4 * AT_NBLK - 1;
          const int row = hp * 2 * T_SEQ + (isv ? (j - 1) >> 1 : (j + 1) >> 1) * 128;
          const uint32_t fb = b_full + 8 * slot;
          mbar_wait_long(b_empty + 8 * slot, ph);
          if (!first && j == 3) mbar_wait(b_ob, 0);
          if (j == 4 && it == n_items - 1) mbar_arrive(bars + 288);
          if ((j == AL_P || j == RK_P) && it == 1) mbar_arrive(bars + 312);
          mbar_expect_tx(fb, 32768);
          tma_load_3d_hint(sbase + slot * 32768, isv ? &tmV : &tmK, row, 0, fb, pol);
          if (it == 1 && isv && j >= 2 * WO_LATE && j < 2 * WO_LATE + 32 && bid < OG_NKB)
            l2_prefetch_bulk(pf_wo + (size_t)own_kb(bid, og_pre(0)) * 131072 + ((j >> 1) - WO_LATE) * 8192, 8192);
          if (++slot == 5) { slot = 0; ph ^= 1; }
        }
      }
      if (__builtin_expect(single, 0)) {
        spin_until(&g_hcnt[2], 128u);
        fence_proxy_async_global();
        const int nj = OG_HSUM + (help_njobs(bid) - OG_JOBS) * OG_PRE2;
        int ji = 0, job = help_job(bid, 0), kk = 0;
        #pragma unroll 1
        for (int j = 0; j < nj; j++) {
          const uint32_t sl = ring_slot(qp_pos(j, 1)), fb = b_full + 8 * sl;
          mbar_wait_long(b_empty + 8 * sl, ring_par(qp_pos(j, 1)) ^ ((j >> 2) & 1) ^ 1);
          mbar_expect_tx(fb, 49152);
          tma_load_3d_hint(sbase + sl * 32768, &tmWo, pre_kb(kk) * 64, OG_NT(job) * 2, fb, pol_normal());
          tma_load_3d_hint(sbase + sl * 32768 + 16384, &tmWo, pre_kb(kk) * 64, OG_NT(job) * 2 + 2, fb, pol_normal());
          if (j == 0 || j == 2) mbar_wait(j ? b_ob : b_q0, 0);
          tma_load_2d_hint(sbase + AT_SQ + (j & 3) * 16384, &tmOl, pre_kb(kk) * 64, OG_MT(job) * 128, fb, pol);
          if (++kk == og_pre(job)) { kk = 0; job = help_job(bid, ++ji); }
        }
      }
      if (bid < 128) {
        if (single) mbar_wait(b_x, 1);
        tail_producer(bid, sbase, 0, pol, &tmOl, &tmWo, &tmD);
      }
     }
    }
    named_bar_sync(12 + (threadIdx.x >> 5), 32);
    if (bid < 128) tail_exchange(bid, sbase, w_down, w_r, x, out);
  } else {
    if (bid < 128) head_phase(bid, sbase + AT_SQ + 49152, sbase + 4 * 32768, b_x, b_go, b_head, threadIdx.x - 128, zero, cvec, w_mod);
    else { named_bar_sync(6, 384); if (threadIdx.x == 128) mbar_arrive(b_head); }
    TL_MARK2(0, threadIdx.x == 128);
    reg_alloc<AT_CREG>();
    const int cwg = wg - 1;
    const int tid = threadIdx.x & 127;
    const int warp = tid >> 5, lane = tid & 31;
    const uint32_t dbase = (sbase & 0x3FFFFu) >> 4;
    const uint32_t k_base = dbase + (1u << 16);
    const uint32_t v_base = dbase + (1024u << 16);
    const uint32_t w_base = dbase + (512u << 16);
    const uint32_t q_lo = dbase + ((AT_SQ + cwg * 8192) >> 4) + (1u << 16);
    const uint32_t frag = cwg * 8192 + (16 * warp + (lane & 7) + 8 * ((lane >> 3) & 1)) * 128;
    if (cwg == 1) named_bar_arrive(1, 256);
    bool raw = false;
    uint4 pre[8];
    #pragma unroll 1
    for (int it = 0; it < n_items; it++) {
      const bool more = it + 1 < n_items;
      constexpr int nkb = T_D / 64;
      const int ta = __shfl_sync(0xffffffffu, 4 * it, 0);
      float acc[128];
      {
        FS(2 * it, 0);
        #pragma unroll
        for (int i = 0; i < 128; i++) asm volatile("" : "=f"(acc[i]));
        {
          const uint32_t slot = ring_slot(ta), b_lo = w_base + slot * 2048;
          mbar_wait(b_full + 8 * slot, ring_par(ta));
          wgmma_fence();
          wgmma_m64n256k16_ss_tb<0, 0>(acc, q_lo, b_lo, 0);
          wgmma_m64n256k16_ss_tb<2, 128>(acc, q_lo, b_lo, 1);
          wgmma_m64n256k16_ss_tb<4, 256>(acc, q_lo, b_lo, 1);
          wgmma_m64n256k16_ss_tb<6, 384>(acc, q_lo, b_lo, 1);
          wgmma_commit();
        }
        #pragma unroll 1
        for (int j = 1; j < nkb; j++) {
          const uint32_t slot = ring_slot(qp_pos(j, ta >> 2));
          mbar_wait(b_full + 8 * slot, ring_par(qp_pos(j, ta >> 2)) ^ ((j >> 2) & 1));
          if (QP_STAG > 0 && cwg == 1 && j == nkb - QP_STAG) named_bar_sync(7, 256);
          const uint32_t a_lo = q_lo + (j & 3) * 1024, b_lo = w_base + slot * 2048;
          wgmma_fence();
          wgmma_m64n256k16_ss_tb<0, 0>(acc, a_lo, b_lo, 1);
          wgmma_m64n256k16_ss_tb<2, 128>(acc, a_lo, b_lo, 1);
          wgmma_m64n256k16_ss_tb<4, 256>(acc, a_lo, b_lo, 1);
          wgmma_m64n256k16_ss_tb<6, 384>(acc, a_lo, b_lo, 1);
          wgmma_commit();
          if (QP_STAG > 0 && cwg == 0 && j == nkb - 1) named_bar_arrive(7, 256);
          if (j > 0) {
            wgmma_wait<1>();
            if (tid == 0) mbar_arrive(b_empty + 8 * ring_slot(qp_pos(j - 1, ta >> 2)));
          }
        }
        wgmma_wait<0>();
        fence_regs(acc);
        FS(2 * it, 1);
        TL_MARK2(29, threadIdx.x == 256 && it == 0);
        if (tid == 0) mbar_arrive(b_empty + 24);
      }
      float o[64], s[64];
      uint32_t p[32], q[32];
      #pragma unroll
      for (int i = 0; i < 32; i++) q[i] = pack_bf16(acc[2 * i] * AT_C, acc[2 * i + 1] * AT_C);
      zero_regs(s);
      const uint32_t sq = sbase + AT_SQ + cwg * 8192;
      float mc0, mc1, al0 = 1.0f, al1 = 1.0f, l0 = 0.f, l1 = 0.f, lp0 = 0.f, lp1 = 0.f;
      bool redo0 = false;
      FS(2 * it, 2);
      mbar_wait(b_full + 8 * ring_slot(ta), ring_par(ta));
      named_bar_sync(1 + cwg, 256);
      FS(2 * it, 3);
      issue_qk(s, q, k_base + ring_slot(ta) * 2048);
      pass_turn(cwg);
      bool ready = mbar_test(b_full + 8 * ring_slot(ta + 1), ring_par(ta + 1)) & mbar_test(b_full + 8 * ring_slot(ta + 2), ring_par(ta + 2));
      stage_q<16>(acc, AT_C, sbase + AT_SQ + frag, lane);
      wgmma_wait<0>();
      fence_regs(s);
      if (tid == 0) mbar_arrive(b_empty + 8 * ring_slot(ta));
      mc0 = 0.f; mc1 = 0.f;
      if (!raw) {
        raw = softmax_mode(s, mc0, mc1);
        if (__builtin_expect(!raw, 0)) softmax_sub(s, mc0, mc1);
      }
      softmax_exp<0, 64>(s);
      #pragma unroll
      for (int J = 0; J < 16; J += 2)
        stmatrix_x4(sbase + AT_SQ + frag + (J >> 3) * 16384 + ((((J & 7) + (lane >> 4)) ^ (lane & 7)) << 4), q[2 * J], q[2 * J + 1], q[2 * J + 2], q[2 * J + 3]);
      pack_p(p, s);
      zero_regs(o);
      FS(2 * it, 4);
      uint32_t ks = ring_slot(ta + 1), vs = ring_slot(ta + 2), kp = ring_par(ta + 1), vp = ring_par(ta + 2);
      auto finish_head = [&]() {
        FS(2 * it, 5);
        redo0 = finish_l(lp0, lp1);
        if (!redo0) stage_o(o, lp0, lp1, sbase + AT_SQ + frag, lane);
        FS(2 * it + 1, 4);
      };
      if (!ready) { mbar_wait(b_full + 8 * ks, kp); mbar_wait(b_full + 8 * vs, vp); }
      #pragma unroll 1
      for (int n = 1; n < 2 * AT_NBLK; n++) {
        named_bar_sync(1 + cwg, 256);
        issue_qk(s, q, k_base + ks * 2048);
        if (n == AT_NBLK + 1) finish_head();
        issue_pv(o, p, v_base + vs * 2048, (n & 15) != 1);
        pass_turn(cwg);
        wgmma_wait<1>();
        fence_regs(s);
        if (tid == 0) mbar_arrive(b_empty + 8 * ks);
        if (__builtin_expect(!raw || (uint32_t)(n - (AT_NBLK - 1)) <= 2u, 0)) {
          if (n == AT_NBLK + 1 && !redo0) {
            fence_proxy_async();
            __syncwarp();
            if (lane == 0) mbar_arrive(b_ordy + 8 * cwg);
          }
          if (n == AT_NBLK - 1) {
            #pragma unroll
            for (int J = 0; J < 16; J += 2)
              ldmatrix_x4(sbase + AT_SQ + 32768 + frag + (J >> 3) * 16384 + ((((J & 7) + (lane >> 4)) ^ (lane & 7)) << 4), q[2 * J], q[2 * J + 1], q[2 * J + 2], q[2 * J + 3]);
          }
          if (!raw) {
            const float m0 = mc0, m1 = mc1;
            const bool ok = softmax_mode(s, mc0, mc1);
            if (n == AT_NBLK) raw = ok;
            else {
              mc0 = mc0 - AT_HEAD > m0 ? mc0 : m0; mc1 = mc1 - AT_HEAD > m1 ? mc1 : m1;
              al0 = ex2_approx(m0 - mc0); al1 = ex2_approx(m1 - mc1);
            }
            if (!raw) softmax_sub(s, mc0, mc1);
          }
        }
        softmax_exp<0, AT_SPLIT>(s);
        add_rowsum(p, l0, l1);
        if (tid == 0) {
          uint32_t dep = zero & __float_as_uint(l0) & __float_as_uint(l1);
          #pragma unroll
          for (int i = AT_SPLIT - AT_PIN - PINB; i < AT_SPLIT - PINB; i += 2) dep &= __float_as_uint(s[i]) & __float_as_uint(s[i + 1]);
          mbar_arrive(b_pin + dep);
        }
        wgmma_wait<0>();
        fence_regs(o);
        if (tid == 0) mbar_arrive(b_empty + 8 * vs);
        ks += 2; if (ks >= 5) { ks -= 5; kp ^= 1; }
        vs += 2; if (vs >= 5) { vs -= 5; vp ^= 1; }
        ready = mbar_test(b_full + 8 * ks, kp) & mbar_test(b_full + 8 * vs, vp);
        softmax_exp<AT_SPLIT, 64>(s);
        pack_p(p, s);
        if (n == AT_NBLK) { lp0 = l0; lp1 = l1; l0 = 0.f; l1 = 0.f; }
        if (__builtin_expect(!raw || !ready, 0)) {
        if (!raw && __any_sync(0xffffffffu, al0 != 1.0f || al1 != 1.0f)) {
          rescale_o(o, al0, al1);
          l0 *= al0; l1 *= al1;
          al0 = 1.0f; al1 = 1.0f;
        }
        if (!ready && n < 2 * AT_NBLK - 1) {
          mbar_wait(b_full + 8 * ks, kp);
          mbar_wait(b_full + 8 * vs, vp);
        }
        }
      }
      FS(2 * it + 1, 5);
      const uint32_t vl = ring_slot(ta + 63);
      vs = ring_slot(ta + 62);
      const uint32_t ob = more ? sbase + vs * 32768 : sbase + AT_SQ + 32768;
      mbar_wait(b_full + 8 * vl, ring_par(ta + 63));
      issue_pv(o, p, v_base + vl * 2048, 1);
      block_end(zero, b_pin);
      add_rowsum(p, l0, l1);
      const bool overflow = finish_l(l0, l1);
      if (!overflow && lane == 0) mbar_arrive(b_q1);
      #pragma unroll
      for (int i = 0; i < 8; i++) asm volatile("mov.b64 {%0, %1}, 0;\nmov.b64 {%2, %3}, 0;" : "=r"(pre[i].x), "=r"(pre[i].y), "=r"(pre[i].z), "=r"(pre[i].w));
      const bool want_pre = !more && bid < OG_MOE, got_pre = want_pre && __all_sync(0xffffffffu, mbar_test(bars + 272, 0));
      if (got_pre) load_pre(pre, sbase, AT_SQ, threadIdx.x - 128);
      mbar_wait(b_empty + 8 * vs, ring_par(ta + 62));
      wgmma_wait<0>();
      fence_regs(o);
      if (tid == 0) mbar_arrive(b_empty + 8 * vl);
      FS(2 * it + 1, 6);
      if (overflow) {
        attn_rows_exact(lds_u32(bars + 400), sq + 32768, ob + cwg * 8192, 4 * ta + 1, kc, vc);
        __syncwarp();
        if (lane == 0) mbar_arrive(b_q1);
      } else stage_o(o, l0, l1, ob + frag, lane);
      if (redo0) attn_rows_exact(lds_u32(bars + 400), sq, sq, 4 * ta, kc, vc);
      fence_proxy_async();
      __syncwarp();
      if (lane == 0) {
        if (redo0) mbar_arrive(b_ordy + 8 * cwg);
        mbar_arrive(b_ordy + 16 + 8 * cwg);
      }
      if (want_pre && !got_pre) load_pre(pre, sbase, AT_SQ, threadIdx.x - 128);
      if (redo0 || overflow) raw = false;
      named_bar_sync(3 + cwg, 128);
      FS(2 * it + 1, 7);
    }
    if (cwg == 0) named_bar_arrive(1, 256);
    if (__builtin_expect(single, 0)) {
      float acc[128];
      uint32_t j = 0, pk[64];
      #pragma unroll
      for (int i = 0; i < 64; i++) asm volatile("" : "=f"(acc[2 * i]), "=f"(acc[2 * i + 1]), "=r"(pk[i]));
      uint4* dst = g_pre;
      int left = 0;
      auto put = [&](bool last) {
        #pragma unroll
        for (int i = 0; i < PUT_N; i++) dst[i * 256] = make_uint4(pk[4 * i], pk[4 * i + 1], pk[4 * i + 2], pk[4 * i + 3]);
        dst += PUT_N * 256;
        #pragma unroll
        for (int i = 0; i < 64 - 4 * PUT_N; i++) asm volatile("mov.b32 %0, %1;" : "=r"(pk[i]) : "r"(pk[i + 4 * PUT_N]));
        __syncwarp();
        if (last && lane == 0) mbar_arrive(bars + 280);
      };
      #pragma unroll 1
      for (int ji = 0; ji < help_njobs(bid); ji++) {
        const int nk = og_pre(help_job(bid, ji));
        #pragma unroll 1
        for (int kk = 0; kk < nk; kk++, j++) {
          const uint32_t slot = ring_slot(qp_pos(j, 1));
          mbar_wait(b_full + 8 * slot, ring_par(qp_pos(j, 1)) ^ ((j >> 2) & 1));
          if (H_STAG > 0 && cwg == 1 && kk == nk - H_STAG) named_bar_sync(7, 256);
          const uint32_t a_lo = q_lo + (j & 3) * 1024, b_lo = w_base + slot * 2048;
          wgmma_fence();
          wgmma_m64n256k16_ss_tb<0, 0>(acc, a_lo, b_lo, kk != 0);
          wgmma_m64n256k16_ss_tb<2, 128>(acc, a_lo, b_lo, 1);
          wgmma_m64n256k16_ss_tb<4, 256>(acc, a_lo, b_lo, 1);
          wgmma_m64n256k16_ss_tb<6, 384>(acc, a_lo, b_lo, 1);
          wgmma_commit();
          if (H_STAG > 0 && cwg == 0 && kk == nk - 1) named_bar_arrive(7, 256);
          wgmma_wait<1>();
          if (kk > 0 && tid == 0) mbar_arrive(b_empty + 8 * ring_slot(qp_pos(j - 1, 1)));
          #pragma unroll 1
          for (int i = ji == OG_JOBS ? 0 : 16 / PUT_N - 1; i < 16 / PUT_N && left > 0; i++) put(--left == 0);
        }
        wgmma_wait<0>();
        fence_regs(acc);
        if (tid == 0) mbar_arrive(b_empty + 8 * ring_slot(qp_pos(j - 1, 1)));
        #pragma unroll
        for (int i = 0; i < 64; i++) pk[i] = pack_bf16(acc[2 * i], acc[2 * i + 1]);
        left = 16 / PUT_N;
        if (ji == PRE_X) mbar_wait(bars + 296, 0);
        dst = g_pre + help_job(bid, ji) * 2048 + threadIdx.x - 128;
      }
      #pragma unroll
      for (int i = 0; i < 16; i++) dst[i * 256] = make_uint4(pk[4 * i], pk[4 * i + 1], pk[4 * i + 2], pk[4 * i + 3]);
      __syncwarp();
      if (lane == 0) mbar_arrive(bars + 280);
      named_bar_sync(5, 256);
      if (threadIdx.x == 128) {
        #pragma unroll 1
        for (int i = 0; i < 5; i++) {
          constexpr int n = OG_HSUM;
          const int used = i == 3 ? 0 : (n + 3 - (i == 4 ? 3 : i)) / 4;
          if ((used ^ (i < 4)) & 1) {
            mbar_arrive(b_full + 8 * ring_slot(4 + i));
            mbar_arrive(b_empty + 8 * ring_slot(4 + i)); mbar_arrive(b_empty + 8 * ring_slot(4 + i));
          }
        }
        mbar_arrive(b_x);
      }
      named_bar_sync(5, 256);
      #pragma unroll
      for (int i = 0; i < 8; i++) pre[i] = make_uint4(0u, 0u, 0u, 0u);
    }
    TL_CLK(3, 1, threadIdx.x == 128);
    TL_CTA(1, threadIdx.x == 256);
    TL_END(3, tid == 0);
    TL_MARK2(19, tid == 0 && !single);
    if (bid < 128) {
      tail_consumer(bid, sbase, &tmOut, pre, cwg, w_gate, w_up);
    }
  }
}

typedef CUresult (*PFN_encodeTiled)(CUtensorMap*, CUtensorMapDataType, cuuint32_t, void*, const cuuint64_t*, const cuuint64_t*,
                                    const cuuint32_t*, const cuuint32_t*, CUtensorMapInterleave, CUtensorMapSwizzle,
                                    CUtensorMapL2promotion, CUtensorMapFloatOOBfill);

CUtensorMap make_map_2d(PFN_encodeTiled enc, const void* ptr, uint64_t inner, uint64_t outer, uint64_t stride_bytes, uint32_t box_inner, uint32_t box_outer) {
  CUtensorMap m;
  cuuint64_t gd[2] = {inner, outer}; cuuint64_t gs[1] = {stride_bytes};
  cuuint32_t bx[2] = {box_inner, box_outer}; cuuint32_t es[2] = {1, 1};
  enc(&m, CU_TENSOR_MAP_DATA_TYPE_BFLOAT16, 2, const_cast<void*>(ptr), gd, gs, bx, es, CU_TENSOR_MAP_INTERLEAVE_NONE,
      CU_TENSOR_MAP_SWIZZLE_128B, CU_TENSOR_MAP_L2_PROMOTION_L2_128B, CU_TENSOR_MAP_FLOAT_OOB_FILL_NONE);
  return m;
}

CUtensorMap make_map_3d(PFN_encodeTiled enc, const void* ptr, uint64_t cols, uint64_t rows, uint32_t box_rows, uint32_t chunks) {
  CUtensorMap m;
  cuuint64_t gd[3] = {64, rows, cols / 64}; cuuint64_t gs[2] = {cols * 2, 128};
  cuuint32_t bx[3] = {64, box_rows, chunks}; cuuint32_t es[3] = {1, 1, 1};
  enc(&m, CU_TENSOR_MAP_DATA_TYPE_BFLOAT16, 3, const_cast<void*>(ptr), gd, gs, bx, es, CU_TENSOR_MAP_INTERLEAVE_NONE,
      CU_TENSOR_MAP_SWIZZLE_128B, CU_TENSOR_MAP_L2_PROMOTION_L2_128B, CU_TENSOR_MAP_FLOAT_OOB_FILL_NONE);
  return m;
}

}

extern "C" void kernel_launch(void* const* d_in, const int* in_sizes, int n_in, void* d_out, int out_size) {
  const bf16* x      = (const bf16*)d_in[0];
  const bf16* kc     = (const bf16*)d_in[1];
  const bf16* vc     = (const bf16*)d_in[2];
  const bf16* wq     = (const bf16*)d_in[3];
  const bf16* wo     = (const bf16*)d_in[4];
  const bf16* w_r    = (const bf16*)d_in[6];
  const bf16* w_gate = (const bf16*)d_in[7];
  const bf16* w_up   = (const bf16*)d_in[8];
  const bf16* w_down = (const bf16*)d_in[9];
  const bf16* cvec   = (const bf16*)d_in[10];
  const bf16* w_mod  = (const bf16*)d_in[11];
  bf16* out = (bf16*)d_out;

  static PFN_encodeTiled enc = nullptr;
  static void *p_h = nullptr, *p_o = nullptr;
  if (!enc) {
    void* fn = nullptr; cudaDriverEntryPointQueryResult qres;
    cudaGetDriverEntryPoint("cuTensorMapEncodeTiled", &fn, cudaEnableDefault, &qres);
    enc = (PFN_encodeTiled)fn;
    cudaGetSymbolAddress(&p_h, g_pre);
    p_h = (uint4*)p_h + 16 * PRE_X * 2048;
    cudaGetSymbolAddress(&p_o, g_o);
    cudaFuncSetAttribute(fused_kernel, cudaFuncAttributeMaxDynamicSharedMemorySize, (int)AT_SMEM);
  }
  const CUtensorMap tm_h   = make_map_2d(enc, p_h, T_D, T_SEQ, T_D * 2, 64, 128);
  const CUtensorMap tm_wq  = make_map_3d(enc, wq, T_DQKV, T_D, 64, 4);
  const CUtensorMap tm_k   = make_map_3d(enc, kc, T_DH, (uint64_t)T_NH * T_SEQ, 128, 2);
  const CUtensorMap tm_v   = make_map_3d(enc, vc, T_DH, (uint64_t)T_NH * T_SEQ, 128, 2);
  const CUtensorMap tm_ost = make_map_2d(enc, p_o, T_DQKV, T_SEQ, T_DQKV * 2, 64, 64);
  const CUtensorMap tm_old = make_map_2d(enc, p_o, T_DQKV, T_SEQ, T_DQKV * 2, 64, 128);
  const CUtensorMap tm_wo  = make_map_3d(enc, wo, T_D, T_DQKV, 64, 2);
  const CUtensorMap tm_d   = make_map_3d(enc, w_down, T_D, T_F, 32, 8);

  const CUtensorMap tm_m   = make_map_2d(enc, w_mod, 6 * T_D, T_D, 6 * T_D * 2, 64, 256);
  const CUtensorMap tm_out = make_map_2d(enc, out, T_D, T_SEQ, T_D * 2, 64, 16);

  fused_kernel<<<132, 384, AT_SMEM, cudaStreamPerThread>>>(tm_h, tm_wq, tm_k, tm_v, tm_ost, tm_old, tm_wo, tm_d, tm_out, tm_m, 0u, (const uint8_t*)wo, kc, vc, x, cvec, w_mod,
             w_r, w_gate, w_up, w_down, out);
}
```

```cpp
#include <cuda_runtime.h>
#include <cuda_bf16.h>
#include <cuda.h>
#include <stdint.h>

namespace {

typedef __nv_bfloat16 bf16;

constexpr int T_SEQ = 2048, T_D = 1024, T_NH = 32, T_DH = 128, T_DQKV = 4096, T_F = 3584;

#define PRE_X 2
__device__ __align__(1024) uint4 g_pre[(16 * PRE_X + 128) * 2048];
#define g_h (reinterpret_cast<bf16*>(g_pre + 16 * PRE_X * 2048))
__device__ __align__(1024) bf16 g_o[T_SEQ * T_DQKV];
__device__ __align__(16) uint8_t g_col[8 * 1536];
__device__ __align__(16) float g_scal[64];
__device__ __align__(16) unsigned int g_hcnt[17 * 32];
__device__ __align__(128) float g_modpart[4 * 2 * T_D];
struct __align__(2048) TailMail {
  float4 part1[T_SEQ * 8];
  uint32_t key[256];
  uint4 cand[16 * 2 * 2 * 128];
  uint32_t cnt[32];
  float ypart[(T_F / 32) * 2 * T_D];
};
__device__ TailMail g_mail;
#define g_part1 g_mail.part1
#define g_key g_mail.key
#define g_cand g_mail.cand
#define CNT_Y (g_mail.cnt)
#define g_ypart g_mail.ypart

__device__ __forceinline__ uint32_t smem_u32(const void* p) { return (uint32_t)__cvta_generic_to_shared(p); }
__device__ __forceinline__ void mbar_init(uint32_t bar, uint32_t cnt) { asm volatile("mbarrier.init.shared::cta.b64 [%0], %1;" :: "r"(bar), "r"(cnt)); }
__device__ __forceinline__ void mbar_expect_tx(uint32_t bar, uint32_t bytes) { asm volatile("mbarrier.arrive.expect_tx.shared::cta.b64 _, [%0], %1;" :: "r"(bar), "r"(bytes) : "memory"); }
__device__ __forceinline__ void mbar_arrive(uint32_t bar) { asm volatile("mbarrier.arrive.shared::cta.b64 _, [%0];" :: "r"(bar) : "memory"); }
__device__ __forceinline__ void mbar_wait(uint32_t bar, uint32_t parity) {
  asm volatile("{\n.reg .pred p;\nLAB_WAIT:\nmbarrier.try_wait.parity.shared::cta.b64 p, [%0], %1;\n@!p bra LAB_WAIT;\n}\n" :: "r"(bar), "r"(parity) : "memory");
}
__device__ __forceinline__ bool mbar_test(uint32_t bar, uint32_t parity) {
  uint32_t r; asm volatile("{\n.reg .pred p;\nmbarrier.test_wait.parity.shared::cta.b64 p, [%1], %2;\nselp.u32 %0, 1, 0, p;\n}\n" : "=r"(r) : "r"(bar), "r"(parity) : "memory");
  return r != 0;
}
__device__ __forceinline__ void mbar_wait_long(uint32_t bar, uint32_t parity) {
  asm volatile("{\n.reg .pred p;\nLAB_WAIT:\nmbarrier.try_wait.parity.shared::cta.b64 p, [%0], %1, %2;\n@!p bra LAB_WAIT;\n}\n" :: "r"(bar), "r"(parity), "r"(100000) : "memory");
}
__device__ __forceinline__ uint32_t clock_lo() { uint32_t c; asm volatile("mov.u32 %0, %%clock;" : "=r"(c)); return c; }
__device__ __forceinline__ void fence_mbar_init() { asm volatile("fence.mbarrier_init.release.cluster;" ::: "memory"); }
__device__ __forceinline__ void tma_load_2d(uint32_t dst, const CUtensorMap* map, int c0, int c1, uint32_t bar) {
  asm volatile("cp.async.bulk.tensor.2d.shared::cluster.global.mbarrier::complete_tx::bytes [%0], [%1, {%3, %4}], [%2];"
    :: "r"(dst), "l"(map), "r"(bar), "r"(c0), "r"(c1) : "memory");
}
__device__ __forceinline__ uint64_t policy_evict_first() {
  uint64_t p; asm volatile("createpolicy.fractional.L2::evict_first.b64 %0, 1.0;" : "=l"(p)); return p;
}
__device__ __forceinline__ void tma_load_2d_hint(uint32_t dst, const CUtensorMap* map, int c0, int c1, uint32_t bar, uint64_t pol) {
  asm volatile("cp.async.bulk.tensor.2d.shared::cluster.global.mbarrier::complete_tx::bytes.L2::cache_hint [%0], [%1, {%3, %4}], [%2], %5;"
    :: "r"(dst), "l"(map), "r"(bar), "r"(c0), "r"(c1), "l"(pol) : "memory");
}
__device__ __forceinline__ void tma_load_3d_hint(uint32_t dst, const CUtensorMap* map, int c1, int c2, uint32_t bar, uint64_t pol) {
  asm volatile("cp.async.bulk.tensor.3d.shared::cluster.global.mbarrier::complete_tx::bytes.L2::cache_hint [%0], [%1, {%3, %4, %5}], [%2], %6;"
    :: "r"(dst), "l"(map), "r"(bar), "n"(0), "r"(c1), "r"(c2), "l"(pol) : "memory");
}
__device__ __forceinline__ void tma_load_3d(uint32_t dst, const CUtensorMap* map, int c1, int c2, uint32_t bar) {
  asm volatile("cp.async.bulk.tensor.3d.shared::cluster.global.mbarrier::complete_tx::bytes [%0], [%1, {%3, %4, %5}], [%2];"
    :: "r"(dst), "l"(map), "r"(bar), "n"(0), "r"(c1), "r"(c2) : "memory");
}
__device__ __forceinline__ void tma_store_2d(const CUtensorMap* map, uint32_t src, int c0, int c1) {
  asm volatile("cp.async.bulk.tensor.2d.global.shared::cta.bulk_group [%0, {%2, %3}], [%1];" :: "l"(map), "r"(src), "r"(c0), "r"(c1) : "memory");
}
__device__ __forceinline__ void prefetch_tmap(const CUtensorMap* map) { asm volatile("prefetch.tensormap [%0];" :: "l"(map) : "memory"); }
__device__ __forceinline__ void l2_prefetch_bulk(const void* p, uint32_t bytes) {
  asm volatile("cp.async.bulk.prefetch.L2.global [%0], %1;" :: "l"(p), "r"(bytes) : "memory");
}
__device__ __forceinline__ void bulk_commit() { asm volatile("cp.async.bulk.commit_group;" ::: "memory"); }
template<int N> __device__ __forceinline__ void bulk_wait_read() { asm volatile("cp.async.bulk.wait_group.read %0;" :: "n"(N) : "memory"); }
template<int N> __device__ __forceinline__ void bulk_wait() { asm volatile("cp.async.bulk.wait_group %0;" :: "n"(N) : "memory"); }
__device__ __forceinline__ void named_bar_sync(int id, int nthreads) { asm volatile("bar.sync %0, %1;" :: "r"(id), "r"(nthreads) : "memory"); }
__device__ __forceinline__ void named_bar_arrive(int id, int nthreads) { asm volatile("bar.arrive %0, %1;" :: "r"(id), "r"(nthreads) : "memory"); }
__device__ __forceinline__ void pass_turn(int cwg) {
  asm volatile("{\n.reg .pred p;\nsetp.ne.u32 p, %0, 0;\n@p bar.arrive 1, 256;\n@!p bar.arrive 2, 256;\n}\n" :: "r"(cwg) : "memory");
}
__device__ __forceinline__ void wgmma_fence() { asm volatile("wgmma.fence.sync.aligned;" ::: "memory"); }
__device__ __forceinline__ void wgmma_commit() { asm volatile("wgmma.commit_group.sync.aligned;" ::: "memory"); }
template<int N> __device__ __forceinline__ void wgmma_wait() { asm volatile("wgmma.wait_group.sync.aligned %0;" :: "n"(N) : "memory"); }
template<int R> __device__ __forceinline__ void reg_alloc() { asm volatile("setmaxnreg.inc.sync.aligned.u32 %0;" :: "n"(R)); }
template<int R> __device__ __forceinline__ void reg_dealloc() { asm volatile("setmaxnreg.dec.sync.aligned.u32 %0;" :: "n"(R)); }
__device__ __forceinline__ bool elect_one() {
  uint32_t pred; asm volatile("{\n.reg .pred p;\nelect.sync _|p, 0xffffffff;\nselp.u32 %0, 1, 0, p;\n}\n" : "=r"(pred)); return pred != 0;
}
__device__ __forceinline__ uint32_t pack_bf16(float lo, float hi) {
  uint32_t r; asm("cvt.rn.bf16x2.f32 %0, %1, %2;" : "=r"(r) : "f"(hi), "f"(lo)); return r;
}
__device__ __forceinline__ void stmatrix_x4(uint32_t addr, uint32_t r0, uint32_t r1, uint32_t r2, uint32_t r3) {
  asm volatile("stmatrix.sync.aligned.m8n8.x4.shared.b16 [%0], {%1, %2, %3, %4};" :: "r"(addr), "r"(r0), "r"(r1), "r"(r2), "r"(r3) : "memory");
}
__device__ __forceinline__ void fence_proxy_async() { asm volatile("fence.proxy.async.shared::cta;" ::: "memory"); }
__device__ __forceinline__ float ex2_approx(float x) { float y; asm("ex2.approx.ftz.f32 %0, %1;" : "=f"(y) : "f"(x)); return y; }
template<int N> __device__ __forceinline__ void fence_regs(float (&r)[N]) {
  #pragma unroll
  for (int i = 0; i < N; i++) asm volatile("" : "+f"(r[i]) :: "memory");
}
template<int N> __device__ __forceinline__ void zero_regs(float (&r)[N]) {
  #pragma unroll
  for (int i = 0; i < N; i += 2) asm volatile("mov.b64 {%0, %1}, 0;" : "=f"(r[i]), "=f"(r[i + 1]));
}
__device__ __forceinline__ float rbf(float x) { return __uint_as_float(pack_bf16(0.f, x)); }
__device__ __forceinline__ float bflo(uint32_t v) { return __uint_as_float(v << 16); }
__device__ __forceinline__ float bfhi(uint32_t v) { return __uint_as_float(v & 0xffff0000u); }

#define XT(i) do {} while (0)
#define TL_START(k) do {} while (0)
#define TL_END(k, cond) do {} while (0)
#define TL_CTA(i, cond) do {} while (0)
#define FS(slot, k) do {} while (0)
#define TL_MARK2(k, cond) do {} while (0)
#define TL_CLK(k, i, cond) do {} while (0)

template <int OFFA, int OFFB>
__device__ __forceinline__ void wgmma_m64n256k16_ss_tb(float (&d)[128], uint32_t a_lo, uint32_t b_lo, int scaleD) {
  asm volatile("{\n.reg .pred p;\n.reg .b32 ta, tb;\n.reg .b64 da, db;\nsetp.ne.b32 p, %130, 0;\n"
    "add.u32 ta, %128, %131;\nadd.u32 tb, %129, %132;\n"
    "mov.b64 da, {ta, 0x40000040};\nmov.b64 db, {tb, 0x40000040};\n"
    "wgmma.mma_async.sync.aligned.m64n256k16.f32.bf16.bf16 "
    "{%0, %1, %2, %3, %4, %5, %6, %7, %8, %9, %10, %11, %12, %13, %14, %15, %16, %17, %18, %19, %20, %21, %22, %23, %24, %25, %26, %27, %28, %29, %30, %31, %32, %33, %34, %35, %36, %37, %38, %39, %40, %41, %42, %43, %44, %45, %46, %47, %48, %49, %50, %51, %52, %53, %54, %55, %56, %57, %58, %59, %60, %61, %62, %63, %64, %65, %66, %67, %68, %69, %70, %71, %72, %73, %74, %75, %76, %77, %78, %79, %80, %81, %82, %83, %84, %85, %86, %87, %88, %89, %90, %91, %92, %93, %94, %95, %96, %97, %98, %99, %100, %101, %102, %103, %104, %105, %106, %107, %108, %109, %110, %111, %112, %113, %114, %115, %116, %117, %118, %119, %120, %121, %122, %123, %124, %125, %126, %127}, "
    "da, db, p, 1, 1, 0, 1;\n}\n"
    : "+f"(d[0]), "+f"(d[1]), "+f"(d[2]), "+f"(d[3]), "+f"(d[4]), "+f"(d[5]), "+f"(d[6]), "+f"(d[7]), "+f"(d[8]), "+f"(d[9]), "+f"(d[10]), "+f"(d[11]), "+f"(d[12]), "+f"(d[13]), "+f"(d[14]), "+f"(d[15]), "+f"(d[16]), "+f"(d[17]), "+f"(d[18]), "+f"(d[19]), "+f"(d[20]), "+f"(d[21]), "+f"(d[22]), "+f"(d[23]), "+f"(d[24]), "+f"(d[25]), "+f"(d[26]), "+f"(d[27]), "+f"(d[28]), "+f"(d[29]), "+f"(d[30]), "+f"(d[31]), "+f"(d[32]), "+f"(d[33]), "+f"(d[34]), "+f"(d[35]), "+f"(d[36]), "+f"(d[37]), "+f"(d[38]), "+f"(d[39]), "+f"(d[40]), "+f"(d[41]), "+f"(d[42]), "+f"(d[43]), "+f"(d[44]), "+f"(d[45]), "+f"(d[46]), "+f"(d[47]), "+f"(d[48]), "+f"(d[49]), "+f"(d[50]), "+f"(d[51]), "+f"(d[52]), "+f"(d[53]), "+f"(d[54]), "+f"(d[55]), "+f"(d[56]), "+f"(d[57]), "+f"(d[58]), "+f"(d[59]), "+f"(d[60]), "+f"(d[61]), "+f"(d[62]), "+f"(d[63]), "+f"(d[64]), "+f"(d[65]), "+f"(d[66]), "+f"(d[67]), "+f"(d[68]), "+f"(d[69]), "+f"(d[70]), "+f"(d[71]), "+f"(d[72]), "+f"(d[73]), "+f"(d[74]), "+f"(d[75]), "+f"(d[76]), "+f"(d[77]), "+f"(d[78]), "+f"(d[79]), "+f"(d[80]), "+f"(d[81]), "+f"(d[82]), "+f"(d[83]), "+f"(d[84]), "+f"(d[85]), "+f"(d[86]), "+f"(d[87]), "+f"(d[88]), "+f"(d[89]), "+f"(d[90]), "+f"(d[91]), "+f"(d[92]), "+f"(d[93]), "+f"(d[94]), "+f"(d[95]), "+f"(d[96]), "+f"(d[97]), "+f"(d[98]), "+f"(d[99]), "+f"(d[100]), "+f"(d[101]), "+f"(d[102]), "+f"(d[103]), "+f"(d[104]), "+f"(d[105]), "+f"(d[106]), "+f"(d[107]), "+f"(d[108]), "+f"(d[109]), "+f"(d[110]), "+f"(d[111]), "+f"(d[112]), "+f"(d[113]), "+f"(d[114]), "+f"(d[115]), "+f"(d[116]), "+f"(d[117]), "+f"(d[118]), "+f"(d[119]), "+f"(d[120]), "+f"(d[121]), "+f"(d[122]), "+f"(d[123]), "+f"(d[124]), "+f"(d[125]), "+f"(d[126]), "+f"(d[127])
    : "r"(a_lo), "r"(b_lo), "r"(scaleD), "n"(OFFA), "n"(OFFB));
}

template <int OFFA, int OFFB>
__device__ __forceinline__ void wgmma_m64n128k16_ss_tb(float (&d)[64], uint32_t a_lo, uint32_t b_lo, int scaleD) {
  asm volatile("{\n.reg .pred p;\n.reg .b32 ta, tb;\n.reg .b64 da, db;\nsetp.ne.b32 p, %66, 0;\n"
    "add.u32 ta, %64, %67;\nadd.u32 tb, %65, %68;\n"
    "mov.b64 da, {ta, 0x40000040};\nmov.b64 db, {tb, 0x40000040};\n"
    "wgmma.mma_async.sync.aligned.m64n128k16.f32.bf16.bf16 "
    "{%0, %1, %2, %3, %4, %5, %6, %7, %8, %9, %10, %11, %12, %13, %14, %15, %16, %17, %18, %19, %20, %21, %22, %23, %24, %25, %26, %27, %28, %29, %30, %31, %32, %33, %34, %35, %36, %37, %38, %39, %40, %41, %42, %43, %44, %45, %46, %47, %48, %49, %50, %51, %52, %53, %54, %55, %56, %57, %58, %59, %60, %61, %62, %63}, "
    "da, db, p, 1, 1, 0, 1;\n}\n"
    : "+f"(d[0]), "+f"(d[1]), "+f"(d[2]), "+f"(d[3]), "+f"(d[4]), "+f"(d[5]), "+f"(d[6]), "+f"(d[7]), "+f"(d[8]), "+f"(d[9]), "+f"(d[10]), "+f"(d[11]), "+f"(d[12]), "+f"(d[13]), "+f"(d[14]), "+f"(d[15]), "+f"(d[16]), "+f"(d[17]), "+f"(d[18]), "+f"(d[19]), "+f"(d[20]), "+f"(d[21]), "+f"(d[22]), "+f"(d[23]), "+f"(d[24]), "+f"(d[25]), "+f"(d[26]), "+f"(d[27]), "+f"(d[28]), "+f"(d[29]), "+f"(d[30]), "+f"(d[31]), "+f"(d[32]), "+f"(d[33]), "+f"(d[34]), "+f"(d[35]), "+f"(d[36]), "+f"(d[37]), "+f"(d[38]), "+f"(d[39]), "+f"(d[40]), "+f"(d[41]), "+f"(d[42]), "+f"(d[43]), "+f"(d[44]), "+f"(d[45]), "+f"(d[46]), "+f"(d[47]), "+f"(d[48]), "+f"(d[49]), "+f"(d[50]), "+f"(d[51]), "+f"(d[52]), "+f"(d[53]), "+f"(d[54]), "+f"(d[55]), "+f"(d[56]), "+f"(d[57]), "+f"(d[58]), "+f"(d[59]), "+f"(d[60]), "+f"(d[61]), "+f"(d[62]), "+f"(d[63])
    : "r"(a_lo), "r"(b_lo), "r"(scaleD), "n"(OFFA), "n"(OFFB));
}

template <int OFFB>
__device__ __forceinline__ void wgmma_m64n128k16_rs_tb(float (&d)[64], uint32_t a0, uint32_t a1, uint32_t a2, uint32_t a3, uint32_t b_lo, int scaleD) {
  asm volatile("{\n.reg .pred p;\n.reg .b32 tb;\n.reg .b64 db;\nsetp.ne.b32 p, %69, 0;\n"
    "add.u32 tb, %68, %70;\n"
    "mov.b64 db, {tb, 0x40000040};\n"
    "wgmma.mma_async.sync.aligned.m64n128k16.f32.bf16.bf16 "
    "{%0, %1, %2, %3, %4, %5, %6, %7, %8, %9, %10, %11, %12, %13, %14, %15, %16, %17, %18, %19, %20, %21, %22, %23, %24, %25, %26, %27, %28, %29, %30, %31, %32, %33, %34, %35, %36, %37, %38, %39, %40, %41, %42, %43, %44, %45, %46, %47, %48, %49, %50, %51, %52, %53, %54, %55, %56, %57, %58, %59, %60, %61, %62, %63}, "
    "{%64, %65, %66, %67}, db, p, 1, 1, 1;\n}\n"
    : "+f"(d[0]), "+f"(d[1]), "+f"(d[2]), "+f"(d[3]), "+f"(d[4]), "+f"(d[5]), "+f"(d[6]), "+f"(d[7]), "+f"(d[8]), "+f"(d[9]), "+f"(d[10]), "+f"(d[11]), "+f"(d[12]), "+f"(d[13]), "+f"(d[14]), "+f"(d[15]), "+f"(d[16]), "+f"(d[17]), "+f"(d[18]), "+f"(d[19]), "+f"(d[20]), "+f"(d[21]), "+f"(d[22]), "+f"(d[23]), "+f"(d[24]), "+f"(d[25]), "+f"(d[26]), "+f"(d[27]), "+f"(d[28]), "+f"(d[29]), "+f"(d[30]), "+f"(d[31]), "+f"(d[32]), "+f"(d[33]), "+f"(d[34]), "+f"(d[35]), "+f"(d[36]), "+f"(d[37]), "+f"(d[38]), "+f"(d[39]), "+f"(d[40]), "+f"(d[41]), "+f"(d[42]), "+f"(d[43]), "+f"(d[44]), "+f"(d[45]), "+f"(d[46]), "+f"(d[47]), "+f"(d[48]), "+f"(d[49]), "+f"(d[50]), "+f"(d[51]), "+f"(d[52]), "+f"(d[53]), "+f"(d[54]), "+f"(d[55]), "+f"(d[56]), "+f"(d[57]), "+f"(d[58]), "+f"(d[59]), "+f"(d[60]), "+f"(d[61]), "+f"(d[62]), "+f"(d[63])
    : "r"(a0), "r"(a1), "r"(a2), "r"(a3), "r"(b_lo), "r"(scaleD), "n"(OFFB));
}

template <int OFFB>
__device__ __forceinline__ void wgmma_m64n128k16_rs(float (&d)[64], uint32_t a0, uint32_t a1, uint32_t a2, uint32_t a3, uint32_t b_lo, int scaleD) {
  asm volatile("{\n.reg .pred p;\n.reg .b32 tb;\n.reg .b64 db;\nsetp.ne.b32 p, %69, 0;\n"
    "add.u32 tb, %68, %70;\n"
    "mov.b64 db, {tb, 0x40000040};\n"
    "wgmma.mma_async.sync.aligned.m64n128k16.f32.bf16.bf16 "
    "{%0, %1, %2, %3, %4, %5, %6, %7, %8, %9, %10, %11, %12, %13, %14, %15, %16, %17, %18, %19, %20, %21, %22, %23, %24, %25, %26, %27, %28, %29, %30, %31, %32, %33, %34, %35, %36, %37, %38, %39, %40, %41, %42, %43, %44, %45, %46, %47, %48, %49, %50, %51, %52, %53, %54, %55, %56, %57, %58, %59, %60, %61, %62, %63}, "
    "{%64, %65, %66, %67}, db, p, 1, 1, 0;\n}\n"
    : "+f"(d[0]), "+f"(d[1]), "+f"(d[2]), "+f"(d[3]), "+f"(d[4]), "+f"(d[5]), "+f"(d[6]), "+f"(d[7]), "+f"(d[8]), "+f"(d[9]), "+f"(d[10]), "+f"(d[11]), "+f"(d[12]), "+f"(d[13]), "+f"(d[14]), "+f"(d[15]), "+f"(d[16]), "+f"(d[17]), "+f"(d[18]), "+f"(d[19]), "+f"(d[20]), "+f"(d[21]), "+f"(d[22]), "+f"(d[23]), "+f"(d[24]), "+f"(d[25]), "+f"(d[26]), "+f"(d[27]), "+f"(d[28]), "+f"(d[29]), "+f"(d[30]), "+f"(d[31]), "+f"(d[32]), "+f"(d[33]), "+f"(d[34]), "+f"(d[35]), "+f"(d[36]), "+f"(d[37]), "+f"(d[38]), "+f"(d[39]), "+f"(d[40]), "+f"(d[41]), "+f"(d[42]), "+f"(d[43]), "+f"(d[44]), "+f"(d[45]), "+f"(d[46]), "+f"(d[47]), "+f"(d[48]), "+f"(d[49]), "+f"(d[50]), "+f"(d[51]), "+f"(d[52]), "+f"(d[53]), "+f"(d[54]), "+f"(d[55]), "+f"(d[56]), "+f"(d[57]), "+f"(d[58]), "+f"(d[59]), "+f"(d[60]), "+f"(d[61]), "+f"(d[62]), "+f"(d[63])
    : "r"(a0), "r"(a1), "r"(a2), "r"(a3), "r"(b_lo), "r"(scaleD), "n"(OFFB));
}

__device__ __forceinline__ uint4 ldg_nc_v4(const void* p) {
  uint4 v;
    asm volatile("{\n.reg .b64 pol;\ncreatepolicy.fractional.L2::evict_first.b64 pol, 1.0;\n"
                 "ld.global.nc.L1::no_allocate.L2::cache_hint.v4.u32 {%0, %1, %2, %3}, [%4], pol;\n}\n" : "=r"(v.x), "=r"(v.y), "=r"(v.z), "=r"(v.w) : "l"(p));
  return v;
}
__device__ __forceinline__ void unpack8(const uint4& u, float (&v)[8]) {
  v[0] = bflo(u.x); v[1] = bfhi(u.x); v[2] = bflo(u.y); v[3] = bfhi(u.y);
  v[4] = bflo(u.z); v[5] = bfhi(u.z); v[6] = bflo(u.w); v[7] = bfhi(u.w);
}
__device__ __forceinline__ void fma8(float (&acc)[8], float s, const uint4& w) {
  acc[0] = fmaf(s, bflo(w.x), acc[0]); acc[1] = fmaf(s, bfhi(w.x), acc[1]); acc[2] = fmaf(s, bflo(w.y), acc[2]); acc[3] = fmaf(s, bfhi(w.y), acc[3]);
  acc[4] = fmaf(s, bflo(w.z), acc[4]); acc[5] = fmaf(s, bfhi(w.z), acc[5]); acc[6] = fmaf(s, bflo(w.w), acc[6]); acc[7] = fmaf(s, bfhi(w.w), acc[7]);
}
__device__ __forceinline__ float rcp_approx(float x) { float y; asm("rcp.approx.ftz.f32 %0, %1;" : "=f"(y) : "f"(x)); return y; }
__device__ __forceinline__ float sigmoid_f(float v) { return rcp_approx(1.0f + ex2_approx(v * -1.4426950408889634f)); }
__device__ __forceinline__ float silu_bf(float v) { return rbf(v * sigmoid_f(v)); }
__device__ __forceinline__ uint32_t rank_key(float r, int idx) {
  const uint32_t b = __float_as_uint(r) >> 16;
  const uint32_t u = (r != r) ? 0u : ((b & 0x8000u) ? (~b & 0xffffu) : (b | 0x8000u));
  return (u << 16) | (0xffffu - (uint32_t)idx);
}
__device__ __forceinline__ void warp_top2(uint32_t& k1, uint32_t& k2) {
  const uint32_t m1 = __reduce_max_sync(0xffffffffu, k1);
  k2 = __reduce_max_sync(0xffffffffu, k1 == m1 ? k2 : k1);
  k1 = m1;
}
__device__ __forceinline__ uint32_t bmul2(uint32_t a, uint32_t b) { uint32_t r; asm("mul.rn.bf16x2 %0, %1, %2;" : "=r"(r) : "r"(a), "r"(b)); return r; }
__device__ __forceinline__ uint32_t badd2(uint32_t a, uint32_t b) { uint32_t r; asm("add.rn.bf16x2 %0, %1, %2;" : "=r"(r) : "r"(a), "r"(b)); return r; }
__device__ __forceinline__ uint32_t bsub2(uint32_t a, uint32_t b) { uint32_t r; asm("sub.rn.bf16x2 %0, %1, %2;" : "=r"(r) : "r"(a), "r"(b)); return r; }
__device__ __forceinline__ float sqrt_approx(float x) { float y; asm("sqrt.approx.f32 %0, %1;" : "=f"(y) : "f"(x)); return y; }
__device__ __forceinline__ uint32_t ln_norm2(uint32_t x1, uint32_t mb2, float inv) {
  const uint32_t d = bsub2(x1, mb2);
  return pack_bf16(bflo(d) * inv, bfhi(d) * inv);
}
__device__ __forceinline__ uint32_t bfma2(uint32_t a, uint32_t b, uint32_t c) { uint32_t r; asm("fma.rn.bf16x2 %0, %1, %2, %3;" : "=r"(r) : "r"(a), "r"(b), "r"(c)); return r; }
__device__ __forceinline__ uint32_t ln_norm2b(uint32_t x1, uint32_t mb2, uint32_t ih, uint32_t il) {
  const uint32_t d = bsub2(x1, mb2);
  return bfma2(d, ih, bmul2(d, il));
}
__device__ __forceinline__ uint32_t ln_mod2(uint32_t x1, uint32_t mb2, float inv, uint32_t c1, uint32_t sb) { return badd2(bmul2(ln_norm2(x1, mb2, inv), c1), sb); }
__device__ __forceinline__ void ldmatrix_x4(uint32_t addr, uint32_t& r0, uint32_t& r1, uint32_t& r2, uint32_t& r3) {
  asm volatile("ldmatrix.sync.aligned.m8n8.x4.shared.b16 {%0, %1, %2, %3}, [%4];" : "=r"(r0), "=r"(r1), "=r"(r2), "=r"(r3) : "r"(addr) : "memory");
}
__device__ __forceinline__ uint4 ldg_stream_v4(const void* p, uint64_t pol) {
  uint4 v; asm volatile("ld.global.nc.L1::no_allocate.L2::cache_hint.L2::128B.v4.u32 {%0, %1, %2, %3}, [%4], %5;" : "=r"(v.x), "=r"(v.y), "=r"(v.z), "=r"(v.w) : "l"(p), "l"(pol)); return v;
}
__device__ __forceinline__ void bulk_load_hint(uint32_t dst, const void* src, uint32_t bytes, uint32_t bar, uint64_t pol) {
  asm volatile("cp.async.bulk.shared::cluster.global.mbarrier::complete_tx::bytes.L2::cache_hint [%0], [%1], %2, [%3], %4;"
    :: "r"(dst), "l"(src), "r"(bytes), "r"(bar), "l"(pol) : "memory");
}
__device__ __forceinline__ void red_release_add(unsigned int* p, unsigned int v) { asm volatile("red.release.gpu.global.add.u32 [%0], %1;" :: "l"(p), "r"(v) : "memory"); }
__device__ __forceinline__ unsigned int ld_acquire(const unsigned int* p) { unsigned int v; asm volatile("ld.acquire.gpu.global.u32 %0, [%1];" : "=r"(v) : "l"(p) : "memory"); return v; }
__device__ __forceinline__ void spin_until(const unsigned int* p, unsigned int target) {
  #pragma unroll 1
  for (unsigned int i = 0; i < (1u << 22); i++) { if (ld_acquire(p) >= target) return; }
}
__device__ __forceinline__ float lds_f32(uint32_t a) { float v; asm volatile("ld.shared.f32 %0, [%1];" : "=f"(v) : "r"(a) : "memory"); return v; }
__device__ __forceinline__ float2 lds_f32x2(uint32_t a) { float2 v; asm volatile("ld.shared.v2.f32 {%0, %1}, [%2];" : "=f"(v.x), "=f"(v.y) : "r"(a) : "memory"); return v; }
__device__ __forceinline__ uint2 lds_u32x2(uint32_t a) { uint2 v; asm volatile("ld.shared.v2.u32 {%0, %1}, [%2];" : "=r"(v.x), "=r"(v.y) : "r"(a) : "memory"); return v; }
__device__ __forceinline__ uint32_t lds_u32(uint32_t a) { uint32_t v; asm volatile("ld.shared.u32 %0, [%1];" : "=r"(v) : "r"(a) : "memory"); return v; }
__device__ __forceinline__ void sts_u32(uint32_t a, uint32_t v) { asm volatile("st.shared.u32 [%0], %1;" :: "r"(a), "r"(v) : "memory"); }
__device__ __forceinline__ void sts_u32x2(uint32_t a, uint32_t x, uint32_t y) { asm volatile("st.shared.v2.u32 [%0], {%1, %2};" :: "r"(a), "r"(x), "r"(y) : "memory"); }
__device__ __forceinline__ void sts_f32(uint32_t a, float v) { asm volatile("st.shared.f32 [%0], %1;" :: "r"(a), "f"(v) : "memory"); }
__device__ __forceinline__ void sts_f32x2(uint32_t a, float x, float y) { asm volatile("st.shared.v2.f32 [%0], {%1, %2};" :: "r"(a), "f"(x), "f"(y) : "memory"); }
__device__ __forceinline__ void sts_f32x4(uint32_t a, float x, float y, float z, float w) { asm volatile("st.shared.v4.f32 [%0], {%1, %2, %3, %4};" :: "r"(a), "f"(x), "f"(y), "f"(z), "f"(w) : "memory"); }

__device__ __forceinline__ uint4 lds_u32x4(uint32_t a) { uint4 v; asm volatile("ld.shared.v4.u32 {%0, %1, %2, %3}, [%4];" : "=r"(v.x), "=r"(v.y), "=r"(v.z), "=r"(v.w) : "r"(a) : "memory"); return v; }
__device__ __forceinline__ void sts_u32x4(uint32_t a, uint32_t x, uint32_t y, uint32_t z, uint32_t w) { asm volatile("st.shared.v4.u32 [%0], {%1, %2, %3, %4};" :: "r"(a), "r"(x), "r"(y), "r"(z), "r"(w) : "memory"); }
__device__ __forceinline__ void st_tagged(float* p, float v) {
  const uint32_t b = __float_as_uint(v);
  asm volatile("st.relaxed.gpu.global.u32 [%0], %1;" :: "l"(p), "r"(b == 0u ? 0x80000000u : b) : "memory");
}
__device__ __forceinline__ void st_tagged4(float* p, float x, float y, float z, float w) {
  const uint32_t a = __float_as_uint(x), b = __float_as_uint(y), c = __float_as_uint(z), d = __float_as_uint(w);
  asm volatile("st.relaxed.gpu.global.v4.u32 [%0], {%1, %2, %3, %4};" :: "l"(p), "r"(a == 0u ? 0x80000000u : a), "r"(b == 0u ? 0x80000000u : b),
               "r"(c == 0u ? 0x80000000u : c), "r"(d == 0u ? 0x80000000u : d) : "memory");
}
__device__ __forceinline__ void st_relaxed2(void* p, uint32_t a, uint32_t b) { asm volatile("st.relaxed.gpu.global.v2.u32 [%0], {%1, %2};" :: "l"(p), "r"(a), "r"(b) : "memory"); }
__device__ __forceinline__ float4 ld_tagged4(const float* p) {
  float4 v; asm volatile("ld.relaxed.gpu.global.v4.f32 {%0, %1, %2, %3}, [%4];" : "=f"(v.x), "=f"(v.y), "=f"(v.z), "=f"(v.w) : "l"(p) : "memory"); return v;
}
__device__ __forceinline__ bool tagged4(const float4& v) {
  return __float_as_uint(v.x) != 0u && __float_as_uint(v.y) != 0u && __float_as_uint(v.z) != 0u && __float_as_uint(v.w) != 0u;
}
__device__ __forceinline__ void hint_arrive(uint32_t* p) { asm volatile("red.relaxed.gpu.global.add.u32 [%0], 1;" :: "l"(p) : "memory"); }
__device__ __forceinline__ void hint_wait(const uint32_t* p, uint32_t target) {
  uint32_t v = 0u;
  #pragma unroll 1
  for (unsigned int i = 0; i < (1u << 22) && v < target; i++) asm volatile("ld.relaxed.gpu.global.u32 %0, [%1];" : "=r"(v) : "l"(p) : "memory");
}
__device__ __forceinline__ void fence_proxy_async_global() { asm volatile("fence.proxy.async.global;" ::: "memory"); }

#define H_SPLIT 1
#define X_DLY 1200
#define W_DLY 1900
#define W_FIRST 2200
#define PRE_B 2
template <int J0, int J1>
__device__ __forceinline__ void load_parts(float2 (&pa)[J1 - J0][4], int t2) {
  #pragma unroll
  for (int j = J0; j < J1; j++)
    #pragma unroll
    for (int k = 0; k < 4; k++)
      asm volatile("ld.relaxed.gpu.global.v2.f32 {%0, %1}, [%2];" : "=f"(pa[j - J0][k].x), "=f"(pa[j - J0][k].y)
                   : "l"(g_modpart + k * 2 * T_D + (t2 >> 7) * T_D + j * 256 + (t2 & 127) * 2) : "memory");
}
template <int J0, int J1>
__device__ __forceinline__ void finish_parts(float2 (&pa)[J1 - J0][4], bool loaded, int t2, uint32_t tab) {
  #pragma unroll 1
  for (unsigned int spin = 0; spin < (1u << 22); spin++) {
    if (!loaded) load_parts<J0, J1>(pa, t2);
    loaded = false;
    bool ok = true;
    #pragma unroll
    for (int j = 0; j < J1 - J0; j++)
      #pragma unroll
      for (int k = 0; k < 4; k++) ok &= (__float_as_uint(pa[j][k].x) != 0u) & (__float_as_uint(pa[j][k].y) != 0u);
    if (__all_sync(0xffffffffu, ok)) break;
  }
  #pragma unroll
  for (int j = J0; j < J1; j++) {
    const float2* q = pa[j - J0];
    const uint32_t m = pack_bf16(((q[0].x + q[1].x) + q[2].x) + q[3].x, ((q[0].y + q[1].y) + q[2].y) + q[3].y);
    sts_u32(tab + (t2 >> 7) * 2048 + j * 512 + (t2 & 127) * 4, t2 >= 128 ? badd2(m, 0x3F803F80u) : m);
  }
}
__device__ __forceinline__ void head_phase(uint32_t bid, uint32_t scr, uint32_t xs, uint32_t b_x, uint32_t b_go, uint32_t b_head, int t2, uint32_t zero, const bf16* __restrict__ cvec, const bf16* __restrict__ w_mod) {
  const int lane = t2 & 31, w8 = t2 >> 5;
  const int cb = bid & 31, ks = bid >> 5;
  const bool early = (cb & 15) < 4 * H_SPLIT;
  const uint32_t ws = (xs - 32768 + (t2 >> 3) * 128 + (((t2 ^ (t2 >> 3)) & 7) << 4)) ^ zero;
  const float cv = __bfloat162float(cvec[ks * 256 + t2]);
  const bf16* wsrc = w_mod + (size_t)(ks * 256 + (t2 >> 3)) * (6 * T_D) + cb * 64 + (t2 & 7) * 8;
  if (early) {
    const uint64_t pol = policy_evict_first();
    #pragma unroll 2
    for (int i = 0; i < 8; i++)
      asm volatile("cp.async.cg.shared.global.L2::cache_hint [%0], [%1], 16, %2;" :: "r"(ws + i * 4096), "l"(wsrc + (size_t)i * 32 * 6 * T_D), "l"(pol) : "memory");
  }
  sts_f32(scr + t2 * 4, silu_bf(cv));
  named_bar_sync(6, 384);
  TL_MARK2(1, t2 == 0);
  uint4 xv[2][4];
  uint32_t mb2[2], ih[2], il[2];
  auto norm = [&](int j) {
    #pragma unroll
    for (int r = 0; r < 2; r++) {
      xv[r][j].x = ln_norm2b(xv[r][j].x, mb2[r], ih[r], il[r]); xv[r][j].y = ln_norm2b(xv[r][j].y, mb2[r], ih[r], il[r]);
      xv[r][j].z = ln_norm2b(xv[r][j].z, mb2[r], ih[r], il[r]); xv[r][j].w = ln_norm2b(xv[r][j].w, mb2[r], ih[r], il[r]);
    }
  };
  auto modulate = [&](int j) {
    const uint4 sa = lds_u32x4(scr + 8192 + j * 512 + lane * 16), c1 = lds_u32x4(scr + 8192 + 2048 + j * 512 + lane * 16);
    #pragma unroll
    for (int r = 0; r < 2; r++) {
      xv[r][j].x = badd2(bmul2(xv[r][j].x, c1.x), sa.x); xv[r][j].y = badd2(bmul2(xv[r][j].y, c1.y), sa.y);
      xv[r][j].z = badd2(bmul2(xv[r][j].z, c1.z), sa.z); xv[r][j].w = badd2(bmul2(xv[r][j].w, c1.w), sa.w);
    }
  };
  auto store = [&](int j) {
    #pragma unroll
    for (int r = 0; r < 2; r++) *reinterpret_cast<uint4*>(g_h + (size_t)(bid * 16 + 2 * w8 + r) * T_D + j * 256 + lane * 8) = xv[r][j];
  };
  #pragma unroll 1
  for (int ph = 0; ph < 2; ph++) {
    if ((ph == 0) == early) {
      asm volatile("cp.async.wait_all;" ::: "memory");
      if (!early) mbar_wait(b_x + 168, 0);
      float acc[8];
      #pragma unroll
      for (int j = 0; j < 8; j++) acc[j] = 0.f;
      #pragma unroll
      for (int i = 0; i < 8; i++) fma8(acc, lds_f32(scr + ((t2 >> 3) + 32 * i) * 4), lds_u32x4(ws + i * 4096));
      #pragma unroll
      for (int j = 0; j < 4; j++) { const bool up = lane & 16; acc[j] = (up ? acc[4 + j] : acc[j]) + __shfl_xor_sync(0xffffffffu, up ? acc[j] : acc[4 + j], 16); }
      #pragma unroll
      for (int j = 0; j < 2; j++) { const bool up = lane & 8; acc[j] = (up ? acc[2 + j] : acc[j]) + __shfl_xor_sync(0xffffffffu, up ? acc[j] : acc[2 + j], 8); }
      sts_f32x2(scr + 1024 + w8 * 256 + (lane & 7) * 32 + (lane >> 3) * 8, acc[0], acc[1]);
      named_bar_sync(5, 256);
      if (t2 < 64) {
        float sum = 0.f;
        #pragma unroll
        for (int i = 0; i < 8; i++) sum += lds_f32(scr + 1024 + i * 256 + t2 * 4);
        st_tagged(g_modpart + ks * 2 * T_D + cb * 64 + t2, sum);
        TL_MARK2(early ? 2 : 6, t2 == 0);
      }
    } else {
      float2 pa[H_SPLIT][4];
      mbar_wait(b_x, 0);
      TL_MARK2(18, t2 == 0);
      load_parts<0, H_SPLIT>(pa, t2);
      #pragma unroll
      for (int r = 0; r < 2; r++)
        #pragma unroll
        for (int j = 0; j < 4; j++) xv[r][j] = lds_u32x4(xs + (2 * w8 + r) * 2048 + j * 512 + lane * 16);
  {
    float st[4] = {0.f, 0.f, 0.f, 0.f};
    #pragma unroll
    for (int r = 0; r < 2; r++)
      #pragma unroll
      for (int j = 0; j < 4; j++) {
        float v[8];
        unpack8(xv[r][j], v);
        st[2 * r] += ((v[0] + v[1]) + (v[2] + v[3])) + ((v[4] + v[5]) + (v[6] + v[7]));
        st[2 * r + 1] += fmaf(v[0], v[0], fmaf(v[1], v[1], fmaf(v[2], v[2], v[3] * v[3]))) + fmaf(v[4], v[4], fmaf(v[5], v[5], fmaf(v[6], v[6], v[7] * v[7])));
      }
    #pragma unroll
    for (int k = 0; k < 2; k++) { const bool up = lane & 16; st[k] = (up ? st[2 + k] : st[k]) + __shfl_xor_sync(0xffffffffu, up ? st[k] : st[2 + k], 16); }
    #pragma unroll
    for (int o = 8; o > 0; o >>= 1) { st[0] += __shfl_xor_sync(0xffffffffu, st[0], o); st[1] += __shfl_xor_sync(0xffffffffu, st[1], o); }
    const float mean = st[0] * (1.0f / T_D);
    const float inv = rcp_approx(rbf(sqrt_approx(rbf(rbf(fmaxf(fmaf(-mean, mean, st[1] * (1.0f / T_D)), 0.f)) + 1e-05f))));
    const uint32_t m = pack_bf16(mean, mean), h = pack_bf16(inv - rbf(inv), inv);
    #pragma unroll
    for (int r = 0; r < 2; r++) {
      mb2[r] = __shfl_sync(0xffffffffu, m, 16 * r);
      const uint32_t hr = __shfl_sync(0xffffffffu, h, 16 * r);
      ih[r] = __byte_perm(hr, hr, 0x3232); il[r] = __byte_perm(hr, hr, 0x1010);
    }
  }
      #pragma unroll
      for (int j = 0; j < H_SPLIT; j++) norm(j);
      TL_MARK2(5, t2 == 0);
      finish_parts<0, H_SPLIT>(pa, true, t2, scr + 8192);
      named_bar_sync(5, 256);
      TL_MARK2(7, t2 == 0);
      #pragma unroll
      for (int j = 0; j < H_SPLIT; j++) { modulate(j); store(j); }
      named_bar_arrive(9, 288);
    }
  }
  #pragma unroll
  for (int j = H_SPLIT; j < 4; j++) norm(j);
  float2 pb[4 - H_SPLIT][4];
  finish_parts<H_SPLIT, 4>(pb, false, t2, scr + 8192);
  named_bar_sync(5, 256);
  TL_MARK2(17, t2 == 0);
  #pragma unroll
  for (int j = H_SPLIT; j < 4; j++) modulate(j);
  __syncwarp();
  if (lane == 0) mbar_arrive(b_head + (xv[1][3].w & zero));
  mbar_wait(b_go, 0);
  #pragma unroll
  for (int j = H_SPLIT; j < 4; j++) store(j);
  named_bar_arrive(8, 288);
}

#define MOD_AT (b_empty + 8)
#define MOD_SPLIT 16
__device__ __forceinline__ void mod_rest(uint32_t bid, uint32_t scr, uint32_t b_go, int t, const bf16* __restrict__ cvec, const bf16* __restrict__ w_mod, const bf16* __restrict__ w_r) {
  const int lane = t & 31;
  #pragma unroll 1
  for (int i = t; i < T_D / 2; i += 64) {
    const uint32_t c2 = *reinterpret_cast<const uint32_t*>(cvec + 2 * i);
    sts_u32(scr + i * 4, pack_bf16(silu_bf(bflo(c2)), silu_bf(bfhi(c2))));
  }
  named_bar_sync(11, 64);
  const bf16* wp = w_mod + (size_t)(2 * (t >> 2)) * (6 * T_D) + 2 * T_D + bid * 32 + (t & 3) * 8;
  float acc[8];
  #pragma unroll
  for (int i = 0; i < 8; i++) acc[i] = 0.f;
  #pragma unroll 1
  for (int i = 0; i < 32; i += 2) {
    if (i == MOD_SPLIT) mbar_wait_long(b_go, 0);
    const uint4 w0 = ldg_nc_v4(wp), w1 = ldg_nc_v4(wp + 6 * T_D), w2 = ldg_nc_v4(wp + 32 * 6 * T_D), w3 = ldg_nc_v4(wp + 33 * 6 * T_D);
    wp += 64 * 6 * T_D;
    const uint32_t s0 = lds_u32(scr + (i * 16 + (t >> 2)) * 4), s1 = lds_u32(scr + (i * 16 + 16 + (t >> 2)) * 4);
    fma8(acc, bflo(s0), w0); fma8(acc, bfhi(s0), w1); fma8(acc, bflo(s1), w2); fma8(acc, bfhi(s1), w3);
  }
  #pragma unroll
  for (int j = 0; j < 4; j++) { const bool up = lane & 16; acc[j] = (up ? acc[4 + j] : acc[j]) + __shfl_xor_sync(0xffffffffu, up ? acc[j] : acc[4 + j], 16); }
  #pragma unroll
  for (int j = 0; j < 2; j++) { const bool up = lane & 8; acc[j] = (up ? acc[2 + j] : acc[j]) + __shfl_xor_sync(0xffffffffu, up ? acc[j] : acc[2 + j], 8); }
  { const bool up = lane & 4; acc[0] = (up ? acc[1] : acc[0]) + __shfl_xor_sync(0xffffffffu, up ? acc[0] : acc[1], 4); }
  if (t >= 32) sts_f32(scr + 2048 + lane * 4, acc[0]);
  named_bar_sync(11, 64);
  if (__shfl_sync(0xffffffffu, t, 0) < 32) {
    const int kind = bid >> 5;
    float v = rbf(acc[0] + lds_f32(scr + 2048 + lane * 4));
    const int col = (bid & 31) * 32 + (lane & 3) * 8 + (lane >> 2);
    uint8_t* dst = g_col + (col >> 7) * 1536;
    if (kind == 2) v = rbf(1.0f + v);
    float vw = v * __bfloat162float(w_r[col]);
    if (kind == 2) {
      const int c = col & 127, i = (c & ~15) + ((c >> 1) & 3) * 4 + ((c >> 3) & 1) * 2 + (c & 1);
      reinterpret_cast<bf16*>(dst)[i] = __float2bfloat16_rn(vw);
      reinterpret_cast<bf16*>(dst)[128 + i] = __float2bfloat16_rn(vw - rbf(vw));
    }
    reinterpret_cast<bf16*>(dst + 512 + (kind & 1) * 512 + (kind >> 1) * 256)[col & 127] = __float2bfloat16_rn(v);
    #pragma unroll
    for (int o = 16; o > 0; o >>= 1) vw += __shfl_xor_sync(0xffffffffu, vw, o);
    if (lane == 0 && (kind == 1 || kind == 2)) g_scal[95 - bid] = vw;
  }
  #pragma unroll 1
  for (int i = bid * 64 + t; i < (int)(sizeof(g_mail) / 16); i += 128 * 64) reinterpret_cast<uint4*>(&g_mail)[i] = make_uint4(0u, 0u, 0u, 0u);
  named_bar_sync(11, 64);
  if (t == 0) red_release_add(&g_hcnt[0], 1u);
}

constexpr int AT_NBLK = T_SEQ / 128;
constexpr float AT_HEAD = 7.0f;
#define WO_LATE 12
#define QP_STAG 3
#define AT_SPLIT 28
#define AT_PIN 12
#define PINB 4
constexpr int AT_NFULL = 124;
constexpr int AT_PREG = 40, AT_CREG = 232;
constexpr uint32_t AT_SQ = 5 * 32768;
constexpr float AT_C = 0.08838834764831845f * 1.4426950408889634f;
constexpr float AT_RAW_LO = -16.0f, AT_RAW_HI = 24.0f;
constexpr float AT_RAW_SUM = 281474976710656.0f, AT_RAW_MIN = 9.094947017729282e-13f;
constexpr uint32_t AT_SBAR = AT_SQ + 65536 + 256;
constexpr uint32_t AT_SMEM = AT_SQ + 65536 + 3072;

__device__ __forceinline__ uint32_t ring_slot(uint32_t t) { return t - 5u * ((t * 205u) >> 10); }
__device__ __forceinline__ uint32_t qp_pos(uint32_t j, uint32_t it) { return 4u * it + (j & 3u) + ((j & 3u) == 3u ? it : 0u); }
__device__ __forceinline__ uint32_t ring_par(uint32_t t) { return ((t * 205u) >> 10) & 1u; }
__device__ __forceinline__ void softmax_rowmax(const float (&s)[64], float& mx0, float& mx1) {
  float a0 = fmaxf(s[0], s[1]), a1 = fmaxf(s[4], s[5]), a2 = fmaxf(s[8], s[9]), a3 = fmaxf(s[12], s[13]);
  float b0 = fmaxf(s[2], s[3]), b1 = fmaxf(s[6], s[7]), b2 = fmaxf(s[10], s[11]), b3 = fmaxf(s[14], s[15]);
  #pragma unroll
  for (int j = 4; j < 16; j += 4) {
    a0 = fmaxf(a0, fmaxf(s[4 * j + 0], s[4 * j + 1]));  b0 = fmaxf(b0, fmaxf(s[4 * j + 2], s[4 * j + 3]));
    a1 = fmaxf(a1, fmaxf(s[4 * j + 4], s[4 * j + 5]));  b1 = fmaxf(b1, fmaxf(s[4 * j + 6], s[4 * j + 7]));
    a2 = fmaxf(a2, fmaxf(s[4 * j + 8], s[4 * j + 9]));  b2 = fmaxf(b2, fmaxf(s[4 * j + 10], s[4 * j + 11]));
    a3 = fmaxf(a3, fmaxf(s[4 * j + 12], s[4 * j + 13])); b3 = fmaxf(b3, fmaxf(s[4 * j + 14], s[4 * j + 15]));
  }
  mx0 = fmaxf(fmaxf(a0, a1), fmaxf(a2, a3));
  mx1 = fmaxf(fmaxf(b0, b1), fmaxf(b2, b3));
  mx0 = fmaxf(mx0, __shfl_xor_sync(0xffffffffu, mx0, 1));
  mx1 = fmaxf(mx1, __shfl_xor_sync(0xffffffffu, mx1, 1));
  mx0 = fmaxf(mx0, __shfl_xor_sync(0xffffffffu, mx0, 2));
  mx1 = fmaxf(mx1, __shfl_xor_sync(0xffffffffu, mx1, 2));
}
__device__ __forceinline__ void softmax_sub(float (&s)[64], float mc0, float mc1) {
  #pragma unroll
  for (int j = 0; j < 16; j++) { s[4 * j] -= mc0; s[4 * j + 1] -= mc0; s[4 * j + 2] -= mc1; s[4 * j + 3] -= mc1; }
}
template <int LO, int HI>
__device__ __forceinline__ void softmax_exp(float (&s)[64]) {
  #pragma unroll
  for (int i = LO; i < HI; i++) s[i] = ex2_approx(s[i]);
}
__device__ __forceinline__ bool softmax_mode(const float (&s)[64], float& mc0, float& mc1) {
  softmax_rowmax(s, mc0, mc1);
  const bool raw = __all_sync(0xffffffffu, mc0 >= AT_RAW_LO && mc0 <= AT_RAW_HI && mc1 >= AT_RAW_LO && mc1 <= AT_RAW_HI);
  mc0 += AT_HEAD; mc1 += AT_HEAD;
  return raw;
}
__device__ __forceinline__ void rowsum_p(const uint32_t (&p)[32], uint32_t& t0, uint32_t& t1) {
  uint32_t a[16];
  #pragma unroll
  for (int i = 0; i < 8; i++) { a[2 * i] = badd2(p[4 * i], p[4 * i + 2]); a[2 * i + 1] = badd2(p[4 * i + 1], p[4 * i + 3]); }
  #pragma unroll
  for (int i = 0; i < 4; i++) { a[2 * i] = badd2(a[4 * i], a[4 * i + 2]); a[2 * i + 1] = badd2(a[4 * i + 1], a[4 * i + 3]); }
  t0 = badd2(badd2(a[0], a[2]), badd2(a[4], a[6]));
  t1 = badd2(badd2(a[1], a[3]), badd2(a[5], a[7]));
}
__device__ __forceinline__ void add_rowsum(const uint32_t (&p)[32], float& l0, float& l1) {
  uint32_t t0, t1;
  rowsum_p(p, t0, t1);
  l0 += bflo(t0) + bfhi(t0); l1 += bflo(t1) + bfhi(t1);
}
__device__ __forceinline__ void pack_p(uint32_t (&p)[32], const float (&s)[64]) {
  #pragma unroll
  for (int i = 0; i < 32; i++) p[i] = pack_bf16(s[2 * i], s[2 * i + 1]);
}
__device__ __noinline__ void attn_rows_exact(uint32_t bid, uint32_t sq, uint32_t so, int hsel, const bf16* __restrict__ kh, const bf16* __restrict__ vh) {
  const int warp = (threadIdx.x >> 5) & 3, lane = threadIdx.x & 31;
  const size_t hofs = (size_t)((bid < 128 ? bid >> 4 : 15) * 2 + hsel) * T_SEQ * T_DH;
  kh += hofs; vh += hofs;
  #pragma unroll 1
  for (int r = 16 * warp; r < 16 * warp + 16; r++) {
    const uint32_t ad = (lane >> 4) * 16384 + r * 128 + ((((lane & 15) >> 1) ^ (r & 7)) << 4) + (lane & 1) * 8;
    uint2 qv; asm volatile("ld.shared.v2.u32 {%0, %1}, [%2];" : "=r"(qv.x), "=r"(qv.y) : "r"(sq + ad) : "memory");
    const float q0 = bflo(qv.x), q1 = bfhi(qv.x), q2 = bflo(qv.y), q3 = bfhi(qv.y);
    float m = -INFINITY, l = 0.f, o0 = 0.f, o1 = 0.f, o2 = 0.f, o3 = 0.f;
    #pragma unroll 1
    for (int key = 0; key < T_SEQ; key++) {
      const uint2 kv = *reinterpret_cast<const uint2*>(kh + (size_t)key * T_DH + lane * 4);
      const uint2 vv = *reinterpret_cast<const uint2*>(vh + (size_t)key * T_DH + lane * 4);
      float sc = (q0 * bflo(kv.x) + q1 * bfhi(kv.x)) + (q2 * bflo(kv.y) + q3 * bfhi(kv.y));
      #pragma unroll
      for (int o = 16; o > 0; o >>= 1) sc += __shfl_xor_sync(0xffffffffu, sc, o);
      const float mn = fmaxf(m, sc);
      const float al = (m == mn) ? 1.0f : ex2_approx(m - mn), p = rbf(ex2_approx(sc - mn));
      m = mn;
      l = fmaf(l, al, p);
      o0 = fmaf(o0, al, p * bflo(vv.x)); o1 = fmaf(o1, al, p * bfhi(vv.x));
      o2 = fmaf(o2, al, p * bflo(vv.y)); o3 = fmaf(o3, al, p * bfhi(vv.y));
    }
    const float inv = rcp_approx(l);
    asm volatile("st.shared.v2.u32 [%0], {%1, %2};" :: "r"(so + ad), "r"(pack_bf16(o0 * inv, o1 * inv)), "r"(pack_bf16(o2 * inv, o3 * inv)) : "memory");
  }
}
__device__ __forceinline__ void issue_qk(float (&s)[64], const uint32_t (&q)[32], uint32_t k_lo) {
  wgmma_fence();
  wgmma_m64n128k16_rs<0>(s, q[0], q[1], q[2], q[3], k_lo, 0);
  wgmma_m64n128k16_rs<2>(s, q[4], q[5], q[6], q[7], k_lo, 1);
  wgmma_m64n128k16_rs<4>(s, q[8], q[9], q[10], q[11], k_lo, 1);
  wgmma_m64n128k16_rs<6>(s, q[12], q[13], q[14], q[15], k_lo, 1);
  wgmma_m64n128k16_rs<1024>(s, q[16], q[17], q[18], q[19], k_lo, 1);
  wgmma_m64n128k16_rs<1026>(s, q[20], q[21], q[22], q[23], k_lo, 1);
  wgmma_m64n128k16_rs<1028>(s, q[24], q[25], q[26], q[27], k_lo, 1);
  wgmma_m64n128k16_rs<1030>(s, q[28], q[29], q[30], q[31], k_lo, 1);
  wgmma_commit();
}
__device__ __forceinline__ void issue_pv(float (&o)[64], const uint32_t (&p)[32], uint32_t v_lo, int accumulate) {
  wgmma_fence();
  wgmma_m64n128k16_rs_tb<0>(o, p[0], p[1], p[2], p[3], v_lo, accumulate);
  wgmma_m64n128k16_rs_tb<128>(o, p[4], p[5], p[6], p[7], v_lo, 1);
  wgmma_m64n128k16_rs_tb<256>(o, p[8], p[9], p[10], p[11], v_lo, 1);
  wgmma_m64n128k16_rs_tb<384>(o, p[12], p[13], p[14], p[15], v_lo, 1);
  wgmma_m64n128k16_rs_tb<512>(o, p[16], p[17], p[18], p[19], v_lo, 1);
  wgmma_m64n128k16_rs_tb<640>(o, p[20], p[21], p[22], p[23], v_lo, 1);
  wgmma_m64n128k16_rs_tb<768>(o, p[24], p[25], p[26], p[27], v_lo, 1);
  wgmma_m64n128k16_rs_tb<896>(o, p[28], p[29], p[30], p[31], v_lo, 1);
  wgmma_commit();
}
__device__ __forceinline__ void block_end(uint32_t zero, uint32_t bar) {
  #pragma unroll 1
  for (uint32_t i = 0; i < zero; i++) mbar_arrive(bar);
}
__device__ __forceinline__ void rescale_o(float (&o)[64], float al0, float al1) {
  #pragma unroll
  for (int j = 0; j < 16; j++) { o[4 * j] *= al0; o[4 * j + 1] *= al0; o[4 * j + 2] *= al1; o[4 * j + 3] *= al1; }
}

__device__ __forceinline__ void stage_o(const float (&o)[64], float i0, float i1, uint32_t dst, int lane) {
  #pragma unroll
  for (int J = 0; J < 16; J += 2)
    stmatrix_x4(dst + (J >> 3) * 16384 + ((((J & 7) + (lane >> 4)) ^ (lane & 7)) << 4),
                pack_bf16(o[4 * J + 0] * i0, o[4 * J + 1] * i0), pack_bf16(o[4 * J + 2] * i1, o[4 * J + 3] * i1),
                pack_bf16(o[4 * J + 4] * i0, o[4 * J + 5] * i0), pack_bf16(o[4 * J + 6] * i1, o[4 * J + 7] * i1));
}
__device__ __forceinline__ bool finish_l(float& l0, float& l1) {
  l0 += __shfl_xor_sync(0xffffffffu, l0, 1); l1 += __shfl_xor_sync(0xffffffffu, l1, 1);
  l0 += __shfl_xor_sync(0xffffffffu, l0, 2); l1 += __shfl_xor_sync(0xffffffffu, l1, 2);
  const bool redo = __any_sync(0xffffffffu, !(l0 <= AT_RAW_SUM && l1 <= AT_RAW_SUM && l0 >= AT_RAW_MIN && l1 >= AT_RAW_MIN));
  l0 = rcp_approx(l0); l1 = rcp_approx(l1);
  return redo;
}
template <int J0>
__device__ __forceinline__ void stage_q(const float (&acc)[128], float c, uint32_t dst, int lane) {
  #pragma unroll
  for (int J = J0; J < J0 + 16; J += 2)
    stmatrix_x4(dst + (J >> 3) * 16384 + ((((J & 7) + (lane >> 4)) ^ (lane & 7)) << 4),
                pack_bf16(acc[4 * J + 0] * c, acc[4 * J + 1] * c), pack_bf16(acc[4 * J + 2] * c, acc[4 * J + 3] * c),
                pack_bf16(acc[4 * J + 4] * c, acc[4 * J + 5] * c), pack_bf16(acc[4 * J + 6] * c, acc[4 * J + 7] * c));
}
__device__ __forceinline__ void store_o(const CUtensorMap* tmO, uint32_t src, int head, int row) {
  tma_store_2d(tmO, src, head * T_DH, row);
  tma_store_2d(tmO, src + 16384, head * T_DH + 64, row);
  bulk_commit();
}
__device__ __forceinline__ void mma_bf16(float (&d)[4], uint32_t a0, uint32_t a1, uint32_t a2, uint32_t a3, uint32_t b0, uint32_t b1) {
  asm volatile("mma.sync.aligned.m16n8k16.row.col.f32.bf16.bf16.f32 {%0, %1, %2, %3}, {%4, %5, %6, %7}, {%8, %9}, {%0, %1, %2, %3};"
               : "+f"(d[0]), "+f"(d[1]), "+f"(d[2]), "+f"(d[3]) : "r"(a0), "r"(a1), "r"(a2), "r"(a3), "r"(b0), "r"(b1));
}
struct GemvSel { uint32_t lo0, hi0, lo1, hi1; };
__device__ __forceinline__ GemvSel gemv_sel(int lane) {
  const uint32_t lo = (lane & 8) ? 0x1044u : 0x4410u, hi = (lane & 8) ? 0x3244u : 0x4432u;
  GemvSel s; s.lo0 = (lane & 16) ? 0x4444u : lo; s.hi0 = (lane & 16) ? 0x4444u : hi; s.lo1 = (lane & 16) ? lo : 0x4444u; s.hi1 = (lane & 16) ? hi : 0x4444u;
  return s;
}
#define GEMV_B0(j, h, s) __byte_perm((j) < 2 ? (h).x : (h).y, 0u, ((j) & 1) ? (s).hi0 : (s).lo0)
#define GEMV_B1(j, h, s) __byte_perm((j) < 2 ? (h).x : (h).y, 0u, ((j) & 1) ? (s).hi1 : (s).lo1)
__device__ __forceinline__ float4 gemv_out(const float (&d)[4], int lane) {
  const bool tk = lane & 1;
  const float r0 = __shfl_xor_sync(0xffffffffu, tk ? d[0] : d[1], 1), r1 = __shfl_xor_sync(0xffffffffu, tk ? d[2] : d[3], 1);
  return tk ? make_float4(r0, d[1], r1, d[3]) : make_float4(d[0], r0, d[2], r1);
}
#define OG_NG 8
#define PUT_N 2
#define H_STAG 2
#define AL_P 60
#define AL_SLEEP 1200
#define AL_MAX 800
#define POLL_NS 500
#define OG_PROF 0xDCCBAA98u
#define RK_P 24
#define RANK 1
__host__ __device__ constexpr int og_pre(int tile) { return (OG_PROF >> ((tile >> 4) * 4)) & 15; }
constexpr int OG_PRE2 = og_pre(127), OG_HSUM = og_pre(0) + og_pre(16) + og_pre(32) + og_pre(48) + og_pre(64) + og_pre(80) + og_pre(96);
#define OG_JOBS 7
#define OG_GRP 6
#define LD_FIRST 2
#define LD_STAG (OG_GRP / 2)
constexpr int OG_ST = 5, OG_NKB = T_DQKV / 64 - og_pre(0), OG_MOE = T_F / 32;
__device__ __forceinline__ int pre_kb(int i) { return (i >> 1) * 4 + (i & 1); }
__device__ __forceinline__ int own_kb(int i, int pre) { return i < (pre & ~1) ? pre_kb(i) + 2 : i + pre; }
constexpr int OG_POS = 8;
constexpr uint32_t OG_STAGE = 32768;
constexpr uint32_t OG_SCOL = AT_SBAR + 512;
constexpr uint32_t OG_SMISC = AT_SBAR + 2048;
constexpr uint32_t OG_SWD = AT_SQ, OG_PSLOT = AT_SQ;
constexpr uint32_t OG_XSLOT = AT_SQ + 32768;
constexpr uint32_t OG_OSLOT = 1 * OG_STAGE;
constexpr uint32_t OG_SRED = 3 * OG_STAGE;
constexpr uint32_t OG_SH2 = OG_SRED + 24576;
constexpr uint32_t OG_SSTAT = OG_SRED + 16384;
constexpr uint32_t OG_SGU = OG_SRED + 8192;
constexpr uint32_t OG_SFIN = OG_SGU + 256;
#define OGM 2
#define OG_MT(b) ((((b) >> OGM) & 15) ^ (((b) & 64) ? 15 : 0))
#define OG_NT(b) (((b) & ((1 << OGM) - 1)) + (((b) >> (4 + OGM)) << OGM))
__device__ __forceinline__ int tail_tile(uint32_t sbase) { mbar_wait_long(sbase + AT_SBAR + 336, 0); return (int)lds_u32(sbase + AT_SBAR + 408); }
#define TAIL_SETUP \
  const uint32_t bar_full = sbase + AT_SBAR, bar_empty = bar_full + 40; \
  const uint32_t bar_wd = bar_full + 168, bar_col = bar_full + 176, bar_out = bar_full + 184, bar_end = bar_full + 192; \
  const uint32_t bar_key = bar_full + 200, bar_h2 = bar_full + 208, bar_sel = bar_full + 216; \
  const int mt = OG_MT(tb), nt = OG_NT(tb); \
  const int m0 = mt * 128, n0 = nt * 128; \
  const bool has_moe = (int)bid < OG_MOE; \
  (void)bar_empty; (void)bar_wd; (void)bar_col; (void)bar_out; (void)bar_end; (void)bar_key; (void)bar_h2; (void)bar_sel; (void)m0; (void)n0; (void)has_moe;

__device__ __forceinline__ void tail_producer(uint32_t bid, uint32_t sbase, uint32_t ph, uint64_t pol, const CUtensorMap* tmA, const CUtensorMap* tmB, const CUtensorMap* tmD) {
  const int tb = tail_tile(sbase);
  TAIL_SETUP
  uint32_t stage = OG_POS % OG_ST;
  int kb = 0;
  #pragma unroll 1
  for (int seg = 0; seg < 2; seg++) {
    mbar_wait(bar_full + 264 + 80 * seg, 0);
    fence_proxy_async_global();
    const int end = 32 + 32 * seg - og_pre(tb);
    #pragma unroll 1
    for (; kb < end; kb++) {
      const uint32_t fb = bar_full + 8 * stage, sa = sbase + stage * OG_STAGE;
      const int k0 = own_kb(kb, og_pre(tb)) * 64;
      mbar_wait(bar_empty + 8 * stage, ph);
      mbar_expect_tx(fb, OG_STAGE);
      tma_load_3d_hint(sa + 16384, tmB, k0, 2 * nt, fb, pol);
      tma_load_2d_hint(sa, tmA, k0, m0, fb, pol);
      if (++stage == OG_ST) { stage = 0; ph ^= 1; }
    }
  }
  if (has_moe) {
    stage += stage & 1;
    mbar_wait(bar_empty + 8 * stage, ph);
    mbar_expect_tx(bar_wd, OG_STAGE);
    tma_load_3d_hint(sbase + stage * OG_STAGE, tmD, bid * 32, 8, bar_wd, pol);
  }
}

__device__ __forceinline__ uint32_t out2(uint32_t x1, uint32_t mb2, uint32_t ih, uint32_t il, uint32_t c1, uint32_t sb, uint32_t gb) {
  const uint32_t h2 = badd2(bmul2(ln_norm2b(x1, mb2, ih, il), c1), sb);
  return badd2(x1, bmul2(gb, bfma2(h2, 0u, h2)));
}
#define OGTIME gtime()
#define X_PACE 200
#define Y_SLACK 96
#define OG_STAG 3
#define X_PACE2 100
#define WD_PACE 300
__device__ __forceinline__ void tail_exchange(uint32_t bid, uint32_t sbase, const bf16* __restrict__ w_down, const bf16* __restrict__ w_r, const bf16* __restrict__ x, bf16* __restrict__ out) {
    const int lane = threadIdx.x & 31, wi = __shfl_sync(0xffffffffu, threadIdx.x >> 5, 0);
    if (wi == 3) {
      uint32_t a = bid, b = 0u;
      if (bid < AT_NFULL) mbar_wait_long(sbase + AT_SBAR + 312, 0);
      if (bid < OG_MOE) {
        asm volatile("mov.u32 %0, %%globaltimer_lo;" : "=r"(a));
        if (lane == 0 && (bid & 15) == 0) asm volatile("st.relaxed.gpu.global.u32 [%0], %1;" :: "l"(g_hcnt + 8 + (bid >> 4)), "r"((a & ~15u) | 8u | (bid >> 4)) : "memory");
        #pragma unroll 1
        for (unsigned int spin = 0; spin < (1u << 22) && __any_sync(0xffffffffu, b == 0u); spin++) {
          __nanosleep(200);
          asm volatile("ld.relaxed.gpu.global.u32 %0, [%1];" : "=r"(b) : "l"(g_hcnt + 8 + min(lane, 6)) : "memory");
        }
        a = RANK ? __popc(__ballot_sync(0xffffffffu, b < __shfl_sync(0xffffffffu, b, bid >> 4)) & 127u) * 16 + (bid & 15) : bid;
      }
      if (lane == 0) {
        sts_u32(sbase + AT_SBAR + 408, a);
        mbar_arrive(sbase + AT_SBAR + 336);
        b = 0u;
        if (bid < AT_NFULL) {
          unsigned int* tm = g_hcnt + 32 * (1 + (bid >> 4)) + 8;
          mbar_wait_long(sbase + AT_SBAR + 312, 1);
          asm volatile("mov.u32 %0, %%globaltimer_lo;" : "=r"(a));
          asm volatile("red.relaxed.gpu.global.max.u32 [%0], %1;" :: "l"(tm), "r"(a) : "memory");
          __nanosleep(AL_SLEEP);
          asm volatile("ld.relaxed.gpu.global.u32 %0, [%1];" : "=r"(b) : "l"(tm) : "memory");
          b -= a;
        }
        sts_u32(sbase + AT_SBAR + 412, b < AL_MAX ? b * 13 / 8 : 0u);
        mbar_arrive(sbase + AT_SBAR + 320);
      }
      named_bar_sync(15, 32);
    }
    const int tb = __shfl_sync(0xffffffffu, tail_tile(sbase), 0);
    TAIL_SETUP
    if (wi == 3) {
      mbar_wait_long(bar_full + 344, 0);
      float a = g_scal[lane], b = g_scal[32 + lane];
      #pragma unroll
      for (int i = 0; i < 3; i++) {
        const uint4 v = *reinterpret_cast<const uint4*>(g_col + nt * 1536 + i * 512 + lane * 16);
        sts_u32x4(sbase + OG_SCOL + i * 512 + lane * 16, v.x, v.y, v.z, v.w);
      }
      #pragma unroll
      for (int o = 16; o > 0; o >>= 1) { a += __shfl_xor_sync(0xffffffffu, a, o); b += __shfl_xor_sync(0xffffffffu, b, o); }
      if (lane == 0) sts_f32x2(sbase + OG_SMISC, a, b);
      const uint64_t pol = policy_evict_first();
      #pragma unroll 1
      for (int r = lane >> 4; r < 128; r += 4) {
        __nanosleep(X_PACE);
        if (X_PACE2) __nanosleep(X_PACE2);
        #pragma unroll
        for (int j = 0; j < 4; j += 2)
          asm volatile("cp.async.cg.shared.global.L2::cache_hint [%0], [%1], 16, %2;" :: "r"(sbase + OG_XSLOT + (lane & 8) * 2048 + (r + j) * 128 + (((lane ^ (r + j)) & 7) << 4)),
                       "l"(x + (size_t)(m0 + r + j) * T_D + n0 + (lane & 15) * 8), "l"(pol) : "memory");
      }
      asm volatile("cp.async.wait_all;" ::: "memory");
      __syncwarp();
      if (lane == 0) mbar_arrive(bar_col);
    } else if (wi == 2) {
      if (elect_one()) {
        const uint32_t b_free = bar_full + (bid < AT_NFULL ? 80 : 160);
        mbar_wait_long(b_free, 1);
        #pragma unroll 1
        for (unsigned int i = 0; i < (1u << 20) && ld_acquire(&g_hcnt[32 * (1 + (tb >> 3)) + 4 + ((tb >> 1) & 3)]) == 0u; i++) __nanosleep(POLL_NS);
        TL_MARK2(23, true);
        fence_proxy_async_global();
        TL_MARK2(4, true);
        mbar_expect_tx(bar_full + 272, 32768);
        bulk_load_hint(sbase + OG_PSLOT, g_pre + tb * 2048, 32768, bar_full + 272, policy_evict_first());
      }
      named_bar_sync(14, 32);
      if (has_moe) {
        mbar_wait_long(bar_full + 96, 1); mbar_wait(bar_full + 304, 0);
        const uint64_t pol = policy_evict_first();
        #pragma unroll 1
        for (int r = 0; r < 32; r++) {
          __nanosleep(WD_PACE);
          #pragma unroll
          for (int j = 0; j < 2; j++)
            asm volatile("cp.async.cg.shared.global.L2::cache_hint [%0], [%1], 16, %2;" :: "r"(sbase + OG_SWD + (4 * j + (lane >> 3)) * 4096 + r * 128 + (((lane ^ r) & 7) << 4)),
                         "l"((const uint8_t*)w_down + (size_t)bid * 65536 + r * 2048 + j * 512 + lane * 16), "l"(pol) : "memory");
        }
        asm volatile("cp.async.wait_all;" ::: "memory");
        __syncwarp();
        if (lane == 0) mbar_arrive(bar_wd);
      }
    }
    const uint4 wrv = ldg_nc_v4(w_r + threadIdx.x * 8);
    mbar_wait_long(bar_end, 0);
    if (threadIdx.x == 96) XT(10);
    TL_MARK2(22, lane == 0);
    if (wi == 0) {
      uint32_t k1 = 0u, k2 = 0u;
      #pragma unroll 1
      for (unsigned int spin = 0; spin < (1u << 22) && __any_sync(0xffffffffu, k1 == 0u); spin++) asm volatile("ld.relaxed.gpu.global.u32 %0, [%1];" : "=r"(k1) : "l"(g_key + lane) : "memory");
      TL_MARK2(28, lane == 0);
      warp_top2(k1, k2);
      if (lane == 0) {
        const uint32_t r1 = 0xffffu - (k1 & 0xffffu), r2 = 0xffffu - (k2 & 0xffffu);
        sts_u32x4(sbase + OG_SMISC + 64, r1, r2, (r1 >> 7) * 2, (r2 >> 7) * 2 + ((r1 >> 7) == (r2 >> 7)));
        mbar_arrive(bar_sel);
      }
    } else if (wi < 3) {
          mbar_wait(bar_key, 0);
          const uint4 kk = lds_u32x4(sbase + OG_SSTAT + 1024 + lane * 16);
          uint32_t k1 = max(kk.x, kk.y), k2 = min(kk.x, kk.y);
          k2 = max(max(k2, min(kk.z, kk.w)), min(k1, max(kk.z, kk.w))); k1 = max(k1, max(kk.z, kk.w));
          warp_top2(k1, k2);
          if (wi == 1) {
            if (lane == 0) {
              if (nt == (mt & 7)) st_relaxed2(g_key + mt * 2, k1, k2);
              sts_u32x2(sbase + OG_SMISC + 96, (~k1 >> 4) & 7u, (~k2 >> 4) & 7u);
              mbar_arrive(bar_full + 352);
            }
            TL_MARK2(27, lane == 0);
          } else {
            const uint32_t r = (~((lane & 16) ? k2 : k1)) & 127u, ch = lane & 15;
            const uint2 st = lds_u32x2(sbase + OG_SSTAT + r * 8);
            const uint4 xc = lds_u32x4(sbase + OG_XSLOT + (ch >> 3) * 16384 + r * 128 + (((ch ^ r) & 7) << 4));
            const uint4 c1 = lds_u32x4(sbase + OG_SCOL + 768 + ch * 16), sh = lds_u32x4(sbase + OG_SCOL + 1024 + ch * 16);
            const float inr = __uint_as_float(st.y);
            float* dst = reinterpret_cast<float*>(g_cand + (mt * 2 + (lane >> 4)) * 256 + nt * 16 + ch);
            st_tagged4(dst + 512, __uint_as_float(ln_mod2(xc.x, st.x, inr, c1.x, sh.x)), __uint_as_float(ln_mod2(xc.y, st.x, inr, c1.y, sh.y)),
                       __uint_as_float(ln_mod2(xc.z, st.x, inr, c1.z, sh.z)), __uint_as_float(ln_mod2(xc.w, st.x, inr, c1.w, sh.w)));
            st_tagged4(dst, __uint_as_float(xc.x), __uint_as_float(xc.y), __uint_as_float(xc.z), __uint_as_float(xc.w));
          }
    }
    mbar_wait(bar_sel, 0);
    const uint4 sel = lds_u32x4(sbase + OG_SMISC + 64);
    const int sel0 = (int)sel.x, sel1 = (int)sel.y;
    {
      const float* src0 = reinterpret_cast<const float*>(g_cand + sel.z * 256 + 128 + threadIdx.x);
      const float* src1 = reinterpret_cast<const float*>(g_cand + sel.w * 256 + 128 + threadIdx.x);
      float4 h0, h1;
      #pragma unroll 1
      for (unsigned int spin = 0; spin < (1u << 20); spin++) { h0 = ld_tagged4(src0); h1 = ld_tagged4(src1); if (__all_sync(0xffffffffu, tagged4(h0) & tagged4(h1))) break; }
      sts_f32x4(sbase + OG_SH2 + threadIdx.x * 16, h0.x, h0.y, h0.z, h0.w);
      sts_f32x4(sbase + OG_SH2 + 2048 + threadIdx.x * 16, h1.x, h1.y, h1.z, h1.w);
      __syncwarp();
      if (lane == 0) mbar_arrive(bar_h2);
      TL_MARK2(12, lane == 0);
      if (bid >> 6) h0 = h1;
      float v[8], wr[8];
      unpack8(make_uint4(__float_as_uint(h0.x), __float_as_uint(h0.y), __float_as_uint(h0.z), __float_as_uint(h0.w)), v); unpack8(wrv, wr);
      float r = 0.f;
      #pragma unroll
      for (int i = 0; i < 8; i++) r = fmaf(v[i], wr[i], r);
      #pragma unroll
      for (int o = 16; o > 0; o >>= 1) r += __shfl_xor_sync(0xffffffffu, r, o);
      if (lane == 0) sts_f32(sbase + OG_SMISC + 192 + wi * 4, r);
    }
    mbar_wait(bar_out, 0);
    {
      const uint2 cg = lds_u32x2(sbase + OG_SMISC + 96);
      #pragma unroll
      for (int i = 0; i < 4; i++) {
        const int r = (i < 2 ? cg.x : cg.y) * 16 + (i & 1) * 8 + (threadIdx.x >> 4), ch = threadIdx.x & 15;
        if (m0 + r != sel0 && m0 + r != sel1)
          *reinterpret_cast<uint4*>(out + (size_t)(m0 + r) * T_D + n0 + ch * 8) =
              lds_u32x4(sbase + OG_OSLOT + (ch >> 3) * 16384 + r * 128 + (((ch & 7) ^ (r & 7)) << 4));
      }
    }
    if (bid == 0 && threadIdx.x < 68) *reinterpret_cast<uint4*>(g_hcnt + 32 * (threadIdx.x >> 2) + 4 * (threadIdx.x & 3)) = make_uint4(0u, 0u, 0u, 0u);
    if (threadIdx.x < 64) g_modpart[bid * 64 + threadIdx.x] = 0.f;
    {
      const int tk = bid >> 6, c0 = (bid & 63) * 16;
      const uint32_t gb2 = *reinterpret_cast<const uint32_t*>(g_col + (c0 >> 7) * 1536 + 512 + 768 + ((c0 & 127) + (threadIdx.x & 14)) * 2);
      const uint32_t* xp = reinterpret_cast<const uint32_t*>(g_cand + (tk ? sel.w : sel.z) * 256) + ((c0 + (threadIdx.x & 14)) >> 1);
      uint32_t x2 = 0u;
      #pragma unroll 1
      for (unsigned int spin = 0; spin < (1u << 20) && __any_sync(0xffffffffu, x2 == 0u); spin++) asm volatile("ld.relaxed.gpu.global.u32 %0, [%1];" : "=r"(x2) : "l"(xp) : "memory");
      const float* src = g_ypart + (size_t)((threadIdx.x >> 2) * 2 + tk) * T_D + c0 + (threadIdx.x & 3) * 4;
      const bool four = threadIdx.x < (OG_MOE - 96) * 4;
      named_bar_sync(10, 128);
      const uint4 rp = lds_u32x4(sbase + OG_SMISC + 192);
      const float rs = rbf(sigmoid_f(rbf((__uint_as_float(rp.x) + __uint_as_float(rp.y)) + (__uint_as_float(rp.z) + __uint_as_float(rp.w)))));
      const uint32_t h2p = lds_u32(sbase + OG_SH2 + tk * 2048 + (c0 + (threadIdx.x & 14)) * 2);
      const float fh = (lane & 1) ? bfhi(h2p) : bflo(h2p), fz = rbf(fh * 0.0f), fx = (lane & 1) ? bfhi(x2) : bflo(x2), fg = (lane & 1) ? bfhi(gb2) : bflo(gb2);
      bf16* dst = out + (size_t)(tk ? sel1 : sel0) * T_D + c0 + threadIdx.x;
      if (threadIdx.x == 0) hint_wait(CNT_Y, (uint32_t)(OG_MOE - Y_SLACK));
      named_bar_sync(10, 128);
      float4 p0, p1, p2, p3;
      #pragma unroll 1
      for (unsigned int spin = 0; spin < (1u << 20); spin++) {
        p0 = ld_tagged4(src); p1 = ld_tagged4(src + 64 * T_D); p2 = ld_tagged4(src + 128 * T_D); p3 = ld_tagged4(four ? src + 192 * T_D : src);
        if (__all_sync(0xffffffffu, tagged4(p0) & tagged4(p1) & tagged4(p2) & tagged4(p3))) break;
      }
      if (four) { p2.x += p3.x; p2.y += p3.y; p2.z += p3.z; p2.w += p3.w; }
      p0.x = (p0.x + p1.x) + p2.x; p0.y = (p0.y + p1.y) + p2.y; p0.z = (p0.z + p1.z) + p2.z; p0.w = (p0.w + p1.w) + p2.w;
      #pragma unroll
      for (int o = 4; o <= 16; o <<= 1) {
        p0.x += __shfl_xor_sync(0xffffffffu, p0.x, o); p0.y += __shfl_xor_sync(0xffffffffu, p0.y, o);
        p0.z += __shfl_xor_sync(0xffffffffu, p0.z, o); p0.w += __shfl_xor_sync(0xffffffffu, p0.w, o);
      }
      if (lane < 4) sts_f32x4(sbase + OG_SFIN + (threadIdx.x >> 5) * 64 + lane * 16, p0.x, p0.y, p0.z, p0.w);
      named_bar_sync(10, 128);
      TL_MARK2(21, threadIdx.x == 0);
      if (threadIdx.x < 16) {
        const uint32_t ya = sbase + OG_SFIN + threadIdx.x * 4;
        float y = (lds_f32(ya) + lds_f32(ya + 64)) + (lds_f32(ya + 128) + lds_f32(ya + 192));
        y = rbf(y);
        y = rbf(y * rs);
        *dst = __float2bfloat16_rn(fx + rbf(fg * rbf(fh + rbf(fz + y))));
      }
    }
    if (threadIdx.x == 0) XT(11);
    TL_END(4, threadIdx.x == 0);
}

__device__ __forceinline__ void load_pre(uint4* pre, uint32_t sbase, uint32_t buf, int t2) {
  mbar_wait(sbase + AT_SBAR + 272, 0);
  #pragma unroll
  for (int i = 0; i < 8; i++) pre[i] = lds_u32x4(sbase + buf + i * 4096 + t2 * 16);
}
__device__ __forceinline__ void tail_consumer(uint32_t bid, uint32_t sbase, const CUtensorMap* tmOut, const uint4 (&pre)[8], int cwg, const bf16* __restrict__ w_gate, const bf16* __restrict__ w_up) {
    const uint32_t c0 = clock_lo();
    mbar_wait(sbase + AT_SBAR + 320, 0);
    const uint2 td = lds_u32x2(sbase + AT_SBAR + 408);
    const int tb = __shfl_sync(0xffffffffu, (int)td.x, 0);
    TAIL_SETUP
    const int tid = threadIdx.x & 127, t2 = threadIdx.x - 128;
    const int warp = tid >> 5, lane = tid & 31, w8 = t2 >> 5;
    const uint32_t dbase = (sbase & 0x3FFFFu) >> 4;
    const uint32_t a_base = dbase + ((cwg * 8192) >> 4) + (1u << 16);
    const uint32_t b_base = dbase + (16384 >> 4) + (512u << 16);
    TL_MARK2(25, threadIdx.x == 128);
    const uint64_t pol = policy_evict_first();
    const bf16* pw = ((lane & 16) ? w_up : w_gate) + (size_t)(w8 * 128 + (lane & 3) * 4) * T_F + (has_moe ? bid : 0) * 32 + ((lane >> 2) & 3) * 8;
    uint4 wv[32];
    float acc[64];
    #pragma unroll
    for (int i = 0; i < 8; i++) {
      acc[8 * i] = bflo(pre[i].x); acc[8 * i + 1] = bfhi(pre[i].x); acc[8 * i + 2] = bflo(pre[i].y); acc[8 * i + 3] = bfhi(pre[i].y);
      acc[8 * i + 4] = bflo(pre[i].z); acc[8 * i + 5] = bfhi(pre[i].z); acc[8 * i + 6] = bflo(pre[i].w); acc[8 * i + 7] = bfhi(pre[i].w);
    }
    if (lane == 0) mbar_arrive(bar_full + 304);
    while (__any_sync(0xffffffffu, clock_lo() - c0 < td.y)) {}
    uint32_t stage = OG_POS % OG_ST;
    {
      uint32_t phase = (OG_POS / OG_ST) & 1, prev = 12;
      int kb = 0;
      #pragma unroll
      for (int g = 0; g <= OG_NG; g++) {
        const int end = g == OG_NG ? 64 - og_pre(tb) : LD_FIRST + g * OG_GRP + LD_STAG * cwg;
        #pragma unroll 1
        do {
          mbar_wait(bar_full + 8 * stage, phase);
          if (OG_STAG > 0 && g == OG_NG && cwg == 1 && kb == end - OG_STAG) named_bar_sync(7, 256);
          const uint32_t a_lo = a_base + stage * (OG_STAGE >> 4), b_lo = b_base + stage * (OG_STAGE >> 4);
          wgmma_fence();
          wgmma_m64n128k16_ss_tb<0, 0>(acc, a_lo, b_lo, 1);
          wgmma_m64n128k16_ss_tb<2, 128>(acc, a_lo, b_lo, 1);
          wgmma_m64n128k16_ss_tb<4, 256>(acc, a_lo, b_lo, 1);
          wgmma_m64n128k16_ss_tb<6, 384>(acc, a_lo, b_lo, 1);
          wgmma_commit();
          if (OG_STAG > 0 && g == OG_NG && cwg == 0 && kb == end - 1) named_bar_arrive(7, 256);
          wgmma_wait<1>();
          if (tid == 0) mbar_arrive(bar_empty + 8 * prev);
          prev = stage;
          if (++stage == OG_ST) { stage = 0; phase ^= 1; }
        } while (++kb < end);
        #pragma unroll
        for (int j = 4 * g; j < 4 * g + 4 && j < 32; j++) wv[j] = ldg_stream_v4(pw + (size_t)(16 * (j >> 2) + (j & 3)) * T_F, pol);
      }
    }
    mbar_wait(bar_col, 0);
    if (__builtin_expect(!has_moe, 0)) {
      load_pre(wv, sbase, AT_SQ, t2);
    }
    wgmma_wait<0>();
    fence_regs(acc);
    if (__builtin_expect(!has_moe, 0)) {
      #pragma unroll
      for (int i = 0; i < 8; i++) {
        acc[8 * i] += bflo(wv[i].x); acc[8 * i + 1] += bfhi(wv[i].x); acc[8 * i + 2] += bflo(wv[i].y); acc[8 * i + 3] += bfhi(wv[i].y);
        acc[8 * i + 4] += bflo(wv[i].z); acc[8 * i + 5] += bfhi(wv[i].z); acc[8 * i + 6] += bflo(wv[i].w); acc[8 * i + 7] += bfhi(wv[i].w);
      }
    }
    if (tid == 0) mbar_arrive(bar_end);
    TL_MARK2(9, lane == 0);
    const int q2 = 2 * (lane & 3);
    const uint32_t frag = (64 * cwg + 16 * warp + (lane & 7) + 8 * ((lane >> 3) & 1)) * 128;
    const int fsw = lane & 7, fhi = lane >> 4;
    {
      float dl[4] = {0.f, 0.f, 0.f, 0.f}, da[4] = {0.f, 0.f, 0.f, 0.f}, db[4] = {0.f, 0.f, 0.f, 0.f};
      const uint32_t tb2 = sbase + OG_SCOL + (lane & 8) * 32 + (lane & 3) * 8, g = lane >> 2;
      const uint32_t msk = (g == 1 || g == 2) ? 0xffffffffu : 0u, one = g == 0 ? 0x3F803F80u : 0u;
      uint32_t xr[8][4];
      #pragma unroll
      for (int hf = 0; hf < 2; hf++) {
        uint32_t ga[8];
        uint2 cw[4];
        #pragma unroll
        for (int i = 0; i < 4; i++) {
          ldmatrix_x4(sbase + OG_XSLOT + hf * 16384 + frag + (((2 * i + fhi) ^ fsw) << 4), xr[4 * hf + i][0], xr[4 * hf + i][1], xr[4 * hf + i][2], xr[4 * hf + i][3]);
          ga[2 * i] = lds_u32(sbase + OG_SCOL + 512 + (64 * hf + 16 * i + q2) * 2); ga[2 * i + 1] = lds_u32(sbase + OG_SCOL + 512 + (64 * hf + 16 * i + 8 + q2) * 2);
          cw[i] = lds_u32x2(tb2 + (8 * hf + 2 * i) * 16);
        }
        #pragma unroll
        for (int i = 0; i < 4; i++) {
          uint32_t* x4 = xr[4 * hf + i];
          #pragma unroll
          for (int e = 0; e < 4; e++) x4[e] = badd2(x4[e], bmul2(ga[2 * i + (e >> 1)], pack_bf16(acc[32 * hf + 8 * i + 2 * e], acc[32 * hf + 8 * i + 2 * e + 1])));
          mma_bf16(dl, x4[0], x4[1], x4[2], x4[3], (cw[i].x & msk) | one, (cw[i].y & msk) | one);
          mma_bf16(da, x4[0], x4[1], x4[2], x4[3], x4[0], x4[2]);
          mma_bf16(db, x4[0], x4[1], x4[2], x4[3], x4[1], x4[3]);
        }
      }
      {
        const int dsrc = (lane & ~3) + (g >> 1);
        const float qa = __shfl_sync(0xffffffffu, (g & 1) ? da[1] : da[0], dsrc), qb = __shfl_sync(0xffffffffu, (g & 1) ? db[3] : db[2], dsrc);
        const float e0 = __shfl_xor_sync(0xffffffffu, (lane & 1) ? dl[0] : dl[2], 1), e1 = __shfl_xor_sync(0xffffffffu, dl[3], 1);
        if ((lane & 3) < 2) {
          const bool hi = lane & 1;
          st_tagged4(reinterpret_cast<float*>(g_part1 + ((mt * 8 + w8) * 8 + nt) * 16 + g + (hi ? 8 : 0)),
                     hi ? e0 : dl[0], hi ? qb : qa, hi ? e1 + dl[2] : dl[1] + e0, 1.0f);
        }
      }
      #pragma unroll
      for (int i = 0; i < 8; i++) stmatrix_x4(sbase + OG_XSLOT + (i >> 2) * 16384 + frag + (((2 * (i & 3) + fhi) ^ fsw) << 4), xr[i][0], xr[i][1], xr[i][2], xr[i][3]);
    }
    TL_MARK2(10, lane == 0);
    uint4 wd[16];
    if (has_moe) mbar_wait(bar_wd, 0);
    #pragma unroll
    for (int i = 0; i < 16; i++) wd[i] = lds_u32x4(sbase + (cwg ? (stage + (stage & 1)) * OG_STAGE : OG_SWD) + warp * 8192 + (i >> 3) * 4096 + (i & 6) * 512 + (i & 1) * 128 + (lane & 3) * 256 + (((lane >> 2) ^ (2 * (lane & 3) + (i & 1))) << 4));
    {
      const float* src = reinterpret_cast<const float*>(g_part1 + ((mt * 8 + w8) * 8 + (lane & 1) * 4) * 16 + (lane >> 1));
      float4 v, v1, v2, v3;
      #pragma unroll 1
      for (unsigned int spin = 0; spin < (1u << 22); spin++) {
        v = ld_tagged4(src); v1 = ld_tagged4(src + 64); v2 = ld_tagged4(src + 128); v3 = ld_tagged4(src + 192);
        if (__all_sync(0xffffffffu, tagged4(v) & tagged4(v1) & tagged4(v2) & tagged4(v3))) break;
        __nanosleep(100);
      }
      __syncwarp();
      TL_MARK2(26, lane == 0);
      v.x = (v.x + v1.x) + (v2.x + v3.x); v.y = (v.y + v1.y) + (v2.y + v3.y); v.z = (v.z + v1.z) + (v2.z + v3.z);
      v.x += __shfl_xor_sync(0xffffffffu, v.x, 1); v.y += __shfl_xor_sync(0xffffffffu, v.y, 1); v.z += __shfl_xor_sync(0xffffffffu, v.z, 1);
      const float mean = v.x * (1.0f / T_D);
      const float var = fmaxf(fmaf(-mean, mean, v.y * (1.0f / T_D)), 0.f);
      const uint32_t mb2 = pack_bf16(mean, mean);
      const float inv = rcp_approx(rbf(sqrt_approx(rbf(rbf(var) + 1e-05f))));
      {
        const float2 sc = lds_f32x2(sbase + OG_SMISC);
        const uint32_t key = rank_key(rbf(fmaf(fmaf(-bflo(mb2), sc.x, v.z), inv, sc.y)), m0 + 16 * w8 + (lane >> 1));
        mbar_wait(bar_end, 0);
        if (lane & 1) sts_u32(sbase + OG_SSTAT + 1024 + (16 * w8 + (lane >> 1)) * 4, key);
        else sts_u32x2(sbase + OG_SSTAT + (16 * w8 + (lane >> 1)) * 8, mb2, __float_as_uint(inv));
        __syncwarp();
        if (lane == 0) mbar_arrive(bar_key);
      }
      const uint32_t ih = pack_bf16(inv, inv), il = pack_bf16(inv - bflo(ih), inv - bflo(ih));
      const uint32_t mba = __shfl_sync(0xffffffffu, mb2, 2 * (lane >> 2)), mbb = __shfl_sync(0xffffffffu, mb2, 2 * (lane >> 2) + 16);
      const uint32_t iha = __shfl_sync(0xffffffffu, ih, 2 * (lane >> 2)), ihb = __shfl_sync(0xffffffffu, ih, 2 * (lane >> 2) + 16);
      const uint32_t ila = __shfl_sync(0xffffffffu, il, 2 * (lane >> 2)), ilb = __shfl_sync(0xffffffffu, il, 2 * (lane >> 2) + 16);
      #pragma unroll 1
      for (int J0 = 0; J0 < 16; J0 += 4) {
        uint32_t xr[2][4], cv[4][3];
        #pragma unroll
        for (int i = 0; i < 2; i++) {
          ldmatrix_x4(sbase + OG_XSLOT + (J0 >> 3) * 16384 + frag + ((((J0 & 7) + 2 * i + fhi) ^ fsw) << 4), xr[i][0], xr[i][1], xr[i][2], xr[i][3]);
          #pragma unroll
          for (int h = 0; h < 2; h++)
            #pragma unroll
            for (int k = 0; k < 3; k++) cv[2 * i + h][k] = lds_u32(sbase + OG_SCOL + 768 + 256 * k + (8 * (J0 + 2 * i + h) + q2) * 2);
        }
        #pragma unroll
        for (int i = 0; i < 2; i++) {
          #pragma unroll
          for (int h = 0; h < 2; h++) {
            xr[i][2 * h] = out2(xr[i][2 * h], mba, iha, ila, cv[2 * i + h][0], cv[2 * i + h][1], cv[2 * i + h][2]);
            xr[i][2 * h + 1] = out2(xr[i][2 * h + 1], mbb, ihb, ilb, cv[2 * i + h][0], cv[2 * i + h][1], cv[2 * i + h][2]);
          }
          stmatrix_x4(sbase + OG_OSLOT + (J0 >> 3) * 16384 + frag + ((((J0 & 7) + 2 * i + fhi) ^ fsw) << 4), xr[i][0], xr[i][1], xr[i][2], xr[i][3]);
        }
      }
      fence_proxy_async();
      mbar_wait(bar_full + 352, 0);
      const uint2 cg = lds_u32x2(sbase + OG_SMISC + 96);
      __syncwarp();
      if (elect_one()) {
        mbar_arrive(bar_out);
        if (cg.x != w8 && cg.y != w8) {
          asm volatile("cp.async.bulk.tensor.2d.global.shared::cta.bulk_group [%0, {%2, %3}], [%1];" :: "l"(tmOut), "r"(sbase + OG_OSLOT + w8 * 2048), "r"(n0), "r"(m0 + 16 * w8) : "memory");
          asm volatile("cp.async.bulk.tensor.2d.global.shared::cta.bulk_group [%0, {%2, %3}], [%1];" :: "l"(tmOut), "r"(sbase + OG_OSLOT + 16384 + w8 * 2048), "r"(n0 + 64), "r"(m0 + 16 * w8) : "memory");
          bulk_commit();
        }
      }
      TL_MARK2(24, lane == 0);
    }
    if (has_moe) mbar_wait(bar_h2, 0);
    TL_MARK2(13, lane == 0);
    if (has_moe) {
      const GemvSel sel = gemv_sel(lane);
      {
        float d[4][4];
        #pragma unroll
        for (int c = 0; c < 4; c++) { d[c][0] = 0.f; d[c][1] = 0.f; d[c][2] = 0.f; d[c][3] = 0.f; }
        #pragma unroll
        for (int st = 0; st < 8; st++) {
          const uint2 hb = lds_u32x2(sbase + OG_SH2 + ((lane >> 2) & 1) * 2048 + (w8 * 128 + st * 16 + (lane & 3) * 4) * 2);
          #pragma unroll
          for (int j = 0; j < 4; j++) mma_bf16(d[j], wv[4 * st + j].x, wv[4 * st + j].y, wv[4 * st + j].z, wv[4 * st + j].w, GEMV_B0(j, hb, sel), GEMV_B1(j, hb, sel));
        }
        #pragma unroll
        for (int e = 0; e < 4; e++) d[0][e] = (d[0][e] + d[1][e]) + (d[2][e] + d[3][e]);
        const float4 r = gemv_out(d[0], lane);
        sts_f32x4(sbase + OG_SRED + w8 * 512 + (((lane >> 4) * 2 + (lane & 1)) * 32 + ((lane >> 2) & 3) * 8 + (lane & 2) * 2) * 4, r.x, r.y, r.z, r.w);
      }
      named_bar_sync(9, 256);
      if (t2 < 64) {
        float gp[8], up[8];
        #pragma unroll
        for (int w = 0; w < 8; w++) { gp[w] = lds_f32(sbase + OG_SRED + w * 512 + t2 * 4); up[w] = lds_f32(sbase + OG_SRED + w * 512 + 256 + t2 * 4); }
        const float gs = ((gp[0] + gp[1]) + (gp[2] + gp[3])) + ((gp[4] + gp[5]) + (gp[6] + gp[7]));
        const float us = ((up[0] + up[1]) + (up[2] + up[3])) + ((up[4] + up[5]) + (up[6] + up[7]));
        asm volatile("st.shared.u16 [%0], %1;" :: "r"(sbase + OG_SGU + ((t2 & ~15) + ((t2 >> 1) & 3) * 4 + ((t2 >> 3) & 1) * 2 + (t2 & 1)) * 2), "h"((uint16_t)pack_bf16(silu_bf(rbf(gs)) * rbf(us), 0.f)) : "memory");
      }
      named_bar_sync(9, 256);
      TL_MARK2(20, threadIdx.x == 128);
      float d[4][4];
      #pragma unroll
      for (int c = 0; c < 4; c++) { d[c][0] = 0.f; d[c][1] = 0.f; d[c][2] = 0.f; d[c][3] = 0.f; }
      #pragma unroll
      for (int st = 0; st < 2; st++) {
        const uint2 g = lds_u32x2(sbase + OG_SGU + ((lane >> 2) & 1) * 64 + st * 32 + (lane & 3) * 8);
        #pragma unroll
        for (int j = 0; j < 4; j++) {
          const uint32_t b0 = GEMV_B0(j, g, sel), b1 = GEMV_B1(j, g, sel);
          mma_bf16(d[j & 1], wd[4 * st + j].x, wd[4 * st + j].y, wd[4 * st + j].z, wd[4 * st + j].w, b0, b1);
          mma_bf16(d[2 + (j & 1)], wd[8 + 4 * st + j].x, wd[8 + 4 * st + j].y, wd[8 + 4 * st + j].z, wd[8 + 4 * st + j].w, b0, b1);
        }
      }
      #pragma unroll
      for (int e = 0; e < 4; e++) { d[0][e] += d[1][e]; d[2][e] += d[3][e]; }
      const float4 y0 = gemv_out(d[0], lane), y1 = gemv_out(d[2], lane);
      float* yp = g_ypart + (size_t)(bid * 2 + (lane & 1)) * T_D + w8 * 128 + (lane >> 2) * 8 + (lane & 2) * 2;
      st_tagged4(yp, y0.x, y0.y, y0.z, y0.w);
      st_tagged4(yp + 64, y1.x, y1.y, y1.z, y1.w);
      named_bar_sync(9, 256);
      if (t2 == 0) hint_arrive(CNT_Y);
    }
    bulk_wait_read<0>();
    TL_MARK2(14, threadIdx.x == 128);
    TL_CLK(4, 1, threadIdx.x == 128);
}

__device__ __forceinline__ int help_njobs(uint32_t bid) { return bid < 128 ? OG_JOBS : 16 - OG_JOBS; }
__device__ __forceinline__ int help_job(uint32_t bid, int i) { return (i < OG_JOBS ? 16 * i + (bid >> 7) * 2 : 112 + (i - OG_JOBS) * 2) + (bid & 3) * 4; }
__device__ __noinline__ void store_warp(uint32_t bid, uint32_t sbase, const CUtensorMap* tmO, int item0, int n_items) {
  if (elect_one()) {
    const uint32_t bars = sbase + AT_SBAR, b_q0 = bars + 80, b_ob = bars + 96, b_ordy = bars + 104, b_acq = bars + 264;
    const unsigned int* cnt = g_hcnt + 32 * (1 + OG_MT(124)) + 2;
    #pragma unroll 1
    for (int q = 0; q < 4 * n_items; q++) {
      const int item = item0 + (q >> 2) * 128, h = (q >> 1) & 1, w = q & 1;
      const bool last = (q >> 2) == n_items - 1;
      if (q == 4 * n_items - 4) { mbar_wait_long(bars + 288, 0); red_release_add(&g_hcnt[1], 1u); }
      mbar_wait_long(b_ordy + 8 * (q & 3), q >> 2);
      store_o(tmO, (h ? (last ? sbase + AT_SQ + 32768 : sbase + 2 * 32768) : sbase + AT_SQ) + w * 8192, (item >> 4) * 2 + h, (item & 15) * 128 + w * 64);
      if (w) {
        bulk_wait_read<0>();
        mbar_arrive(h ? b_ob : b_q0);
        bulk_wait<0>();
        fence_proxy_async_global();
        asm volatile("fence.acq_rel.gpu;" ::: "memory");
        hint_arrive(&g_hcnt[32 * (1 + (item & 15)) + 2 + (item >> 7)]);
        if (!h && item < 128) hint_arrive(&g_hcnt[2]);
        if (q == 5) { const int tb = tail_tile(sbase); cnt = g_hcnt + 32 * (1 + OG_MT(tb)) + 2; spin_until(cnt, 16u); mbar_arrive(b_acq); }
      }
    }
    if (n_items == 1) {
      #pragma unroll 1
      for (int i = 0; i < help_njobs(bid); i++) {
        mbar_wait_long(b_acq + 16, i & 1);
        TL_MARK2(23, i == OG_JOBS - 1);
        red_release_add(&g_hcnt[32 * (1 + (help_job(bid, i) >> 3)) + 4 + ((help_job(bid, i) >> 1) & 3)], 1u);
        TL_MARK2(4, i == OG_JOBS - 1);
        if (i == PRE_X - 1) { spin_until(&g_hcnt[1], 132u); mbar_arrive(b_acq + 32); }
      }
    }
    if (bid < 128) {
      if (n_items == 1) { spin_until(cnt, 16u); mbar_arrive(b_acq); }
      spin_until(&g_hcnt[0], 128u); spin_until(cnt + 1, 16u); mbar_arrive(b_acq + 80);
    }
  }
}

__device__ __forceinline__ uint32_t role_of_sm(uint32_t sm) {
  const uint32_t t = sm >> 1, u = t - 32u, d = (u * 37u) >> 8;
  return (t < 32u ? ((t + 7u) & 7u) * 16u + (t >> 3) * 2u : t < 60u ? (u - 7u * d) * 16u + (4u + d) * 2u : t < 62u ? 2u * t + 8u : 2u * t - 4u) + (sm & 1u);
}
__global__ void __launch_bounds__(384, 1)
fused_kernel(const __grid_constant__ CUtensorMap tmH, const __grid_constant__ CUtensorMap tmW, const __grid_constant__ CUtensorMap tmK,
            const __grid_constant__ CUtensorMap tmV, const __grid_constant__ CUtensorMap tmO, const __grid_constant__ CUtensorMap tmOl, const __grid_constant__ CUtensorMap tmWo,
            const __grid_constant__ CUtensorMap tmD, const __grid_constant__ CUtensorMap tmOut, const __grid_constant__ CUtensorMap tmM, uint32_t zero,
            const uint8_t* __restrict__ pf_wo, const bf16* __restrict__ kc, const bf16* __restrict__ vc,
            const bf16* __restrict__ x, const bf16* __restrict__ cvec, const bf16* __restrict__ w_mod, const bf16* __restrict__ w_r,
            const bf16* __restrict__ w_gate, const bf16* __restrict__ w_up, const bf16* __restrict__ w_down, bf16* __restrict__ out)
{
  uint32_t bid, nsm;
  asm volatile("mov.u32 %0, %%smid;" : "=r"(bid));
  asm volatile("mov.u32 %0, %%nsmid;" : "=r"(nsm));
  bid = __shfl_sync(0xffffffffu, nsm == 132u ? role_of_sm(bid) : blockIdx.x, 0);
  extern __shared__ __align__(1024) uint8_t smem_raw[];
  const uint32_t sbase = smem_u32(smem_raw);
  const uint32_t bars = sbase + AT_SBAR;
  const uint32_t b_full = bars, b_empty = bars + 40;
  const uint32_t b_q0 = bars + 80, b_q1 = bars + 88;
  const uint32_t b_ob = bars + 96;
  const uint32_t b_ordy = bars + 104;
  const uint32_t b_pin = bars + 136;
  const uint32_t b_head = bars + 144;
  const uint32_t b_go = bars + 152;
  const uint32_t b_x = bars + 160;
  const int wg = __shfl_sync(0xffffffffu, threadIdx.x >> 7, 0);
  const bool single = bid >= AT_NFULL;
  const int item0 = __shfl_sync(0xffffffffu, bid < 128 ? (int)bid : (int)bid + 124, 0), n_items = __shfl_sync(0xffffffffu, single ? 1 : 2, 0);
  TL_START(3);
  if (threadIdx.x == 0) {
    if (sbase & 1023u) __trap();
    for (int i = 0; i < 5; i++) { mbar_init(b_full + 8 * i, 1); mbar_init(b_empty + 8 * i, 2); }
    mbar_init(b_q0, 1); mbar_init(b_q1, 8); mbar_init(b_ob, 1);
    for (int i = 0; i < 4; i++) mbar_init(b_ordy + 8 * i, 4);
    mbar_init(b_pin, 1); mbar_init(b_head, bid < 128 ? 8 : 1); mbar_init(b_go, 1); mbar_init(b_x, 1);
    mbar_init(bars + 168, 2); mbar_init(bars + 176, 1); mbar_init(bars + 184, 8); mbar_init(bars + 192, 2);
    mbar_init(bars + 200, 8); mbar_init(bars + 208, 4); mbar_init(bars + 216, 1); mbar_init(bars + 264, 1); mbar_init(bars + 272, 1); mbar_init(bars + 280, 8); mbar_init(bars + 288, 1); mbar_init(bars + 296, 1); mbar_init(bars + 304, 8); mbar_init(bars + 312, 1); mbar_init(bars + 320, 1); mbar_init(bars + 328, 1); mbar_init(bars + 336, 1); mbar_init(bars + 344, 1); mbar_init(bars + 352, 1);
    sts_u32(bars + 400, bid);
    fence_mbar_init();
  }

  if (wg == 0) {
    reg_dealloc<AT_PREG>();
    if (threadIdx.x < 32) { __syncwarp(); named_bar_arrive(6, 384); }
    if (threadIdx.x >= 64) {
      named_bar_sync(6, 384);
      if (bid < 128) {
        named_bar_sync(threadIdx.x >= 96 ? 8 : 9, 288);
        if ((threadIdx.x & 31) == 0) red_release_add(&g_hcnt[32 * (1 + (bid >> 3)) + (threadIdx.x >= 96)], 1u);
        TL_MARK2(11, threadIdx.x == 64);
      }
      if (bid < 128) {
        mbar_wait(MOD_AT, 0);
        mod_rest(bid, sbase + OG_SCOL, b_q1, threadIdx.x - 64, cvec, w_mod, w_r);
      }
    } else if (threadIdx.x >= 32) {
      named_bar_sync(6, 384);
      store_warp(bid, sbase, &tmO, item0, n_items);
      __syncwarp();
    } else {
     if (elect_one()) {
      const uint64_t pol = policy_evict_first();
      if (bid < 128) {
        mbar_expect_tx(b_x, 32768);
        if (X_DLY) { const uint32_t c0 = clock_lo(); while (clock_lo() - c0 < X_DLY) {} }
        bulk_load_hint(sbase + 4 * 32768, x + (size_t)bid * 16 * T_D, 32768, b_x, pol);
      }
      prefetch_tmap(&tmW); prefetch_tmap(&tmM); prefetch_tmap(&tmH); prefetch_tmap(&tmWo); prefetch_tmap(&tmOl);
      {
        const uint32_t c0 = clock_lo();
        while (clock_lo() - c0 < W_DLY) {}
        if (bid < 128 && (bid & 15) >= 4 * H_SPLIT) {
          mbar_expect_tx(bars + 328, 32768);
          tma_load_2d_hint(sbase + 3 * 32768, &tmM, (bid & 31) * 64, (bid >> 5) * 256, bars + 328, pol);
        }
        while (clock_lo() - c0 < W_DLY + W_FIRST) {}
      }
      uint32_t slot = 0, ph = 1;
      #pragma unroll 1
      for (int it = 0; it < n_items; it++) {
        const int item = item0 + it * 128, hp = item >> 4, qt = item & 15;
        const bool first = it == 0;
        #pragma unroll 1
        for (int j = 0; j < T_D / 64; j++) {
          const uint32_t sl = ring_slot(qp_pos(j, it)), fb = b_full + 8 * sl;
          mbar_wait_long(b_empty + 8 * sl, ring_par(qp_pos(j, it)) ^ ((j >> 2) & 1) ^ 1);
          if (first && j == 3) mbar_wait(b_head, 0);
          mbar_expect_tx(fb, 49152);
          tma_load_3d_hint(sbase + sl * 32768, &tmW, j * 64, hp * 4, fb, pol);
          if (first && j < PRE_B) {
            if (j == PRE_B - 1) {
              spin_until(&g_hcnt[32 * (1 + qt)], 8u);
              TL_MARK2(16, true);
              fence_proxy_async_global();
              #pragma unroll 1
              for (int i = 0; i < PRE_B; i++) tma_load_2d(sbase + AT_SQ + i * 16384, &tmH, i * 64, qt * 128, b_full + 8 * i);
              mbar_arrive(b_go);
            }
          } else {
            if (first && j == 4 * H_SPLIT) { spin_until(&g_hcnt[32 * (1 + qt) + 1], 8u); fence_proxy_async_global(); }
            if (!first && (j == 0 || j == 2)) mbar_wait(j ? b_q1 : b_q0, 0);
            tma_load_2d(sbase + AT_SQ + (j & 3) * 16384, &tmH, j * 64, qt * 128, fb);
          }
        }
        #pragma unroll 1
        for (int j = 0; j < 4 * AT_NBLK; j++) {
          const bool isv = (j > 0 && !(j & 1)) || j == 4 * AT_NBLK - 1;
          const int row = hp * 2 * T_SEQ + (isv ? (j - 1) >> 1 : (j + 1) >> 1) * 128;
          const uint32_t fb = b_full + 8 * slot;
          mbar_wait_long(b_empty + 8 * slot, ph);
          if (!first && j == 3) mbar_wait(b_ob, 0);
          if (j == 4 && it == n_items - 1) mbar_arrive(bars + 288);
          if ((j == AL_P || j == RK_P) && it == 1) mbar_arrive(bars + 312);
          mbar_expect_tx(fb, 32768);
          tma_load_3d_hint(sbase + slot * 32768, isv ? &tmV : &tmK, row, 0, fb, pol);
          if (it == 1 && isv && j >= 2 * WO_LATE && j < 2 * WO_LATE + 32 && bid < OG_NKB)
            l2_prefetch_bulk(pf_wo + (size_t)own_kb(bid, og_pre(0)) * 131072 + ((j >> 1) - WO_LATE) * 8192, 8192);
          if (++slot == 5) { slot = 0; ph ^= 1; }
        }
      }
      if (__builtin_expect(single, 0)) {
        spin_until(&g_hcnt[2], 128u);
        fence_proxy_async_global();
        const int nj = OG_HSUM + (help_njobs(bid) - OG_JOBS) * OG_PRE2;
        int ji = 0, job = help_job(bid, 0), kk = 0;
        #pragma unroll 1
        for (int j = 0; j < nj; j++) {
          const uint32_t sl = ring_slot(qp_pos(j, 1)), fb = b_full + 8 * sl;
          mbar_wait_long(b_empty + 8 * sl, ring_par(qp_pos(j, 1)) ^ ((j >> 2) & 1) ^ 1);
          mbar_expect_tx(fb, 49152);
          tma_load_3d(sbase + sl * 32768, &tmWo, pre_kb(kk) * 64, OG_NT(job) * 2, fb);
          tma_load_3d(sbase + sl * 32768 + 16384, &tmWo, pre_kb(kk) * 64, OG_NT(job) * 2 + 2, fb);
          if (j == 0 || j == 2) mbar_wait(j ? b_ob : b_q0, 0);
          tma_load_2d_hint(sbase + AT_SQ + (j & 3) * 16384, &tmOl, pre_kb(kk) * 64, OG_MT(job) * 128, fb, pol);
          if (++kk == og_pre(job)) { kk = 0; job = help_job(bid, ++ji); }
        }
      }
      if (bid < 128) {
        if (single) mbar_wait(b_x, 1);
        tail_producer(bid, sbase, 0, pol, &tmOl, &tmWo, &tmD);
      }
     }
    }
    named_bar_sync(12 + (threadIdx.x >> 5), 32);
    if (bid < 128) tail_exchange(bid, sbase, w_down, w_r, x, out);
  } else {
    if (bid < 128) head_phase(bid, sbase + AT_SQ + 49152, sbase + 4 * 32768, b_x, b_go, b_head, threadIdx.x - 128, zero, cvec, w_mod);
    else { named_bar_sync(6, 384); if (threadIdx.x == 128) mbar_arrive(b_head); }
    TL_MARK2(0, threadIdx.x == 128);
    reg_alloc<AT_CREG>();
    const int cwg = wg - 1;
    const int tid = threadIdx.x & 127;
    const int warp = tid >> 5, lane = tid & 31;
    const uint32_t dbase = (sbase & 0x3FFFFu) >> 4;
    const uint32_t k_base = dbase + (1u << 16);
    const uint32_t v_base = dbase + (1024u << 16);
    const uint32_t w_base = dbase + (512u << 16);
    const uint32_t q_lo = dbase + ((AT_SQ + cwg * 8192) >> 4) + (1u << 16);
    const uint32_t frag = cwg * 8192 + (16 * warp + (lane & 7) + 8 * ((lane >> 3) & 1)) * 128;
    if (cwg == 1) named_bar_arrive(1, 256);
    bool raw = false;
    uint4 pre[8];
    #pragma unroll 1
    for (int it = 0; it < n_items; it++) {
      const bool more = it + 1 < n_items;
      constexpr int nkb = T_D / 64;
      const int ta = __shfl_sync(0xffffffffu, 4 * it, 0);
      float acc[128];
      {
        FS(2 * it, 0);
        #pragma unroll
        for (int i = 0; i < 128; i++) asm volatile("" : "=f"(acc[i]));
        {
          const uint32_t slot = ring_slot(ta), b_lo = w_base + slot * 2048;
          mbar_wait(b_full + 8 * slot, ring_par(ta));
          wgmma_fence();
          wgmma_m64n256k16_ss_tb<0, 0>(acc, q_lo, b_lo, 0);
          wgmma_m64n256k16_ss_tb<2, 128>(acc, q_lo, b_lo, 1);
          wgmma_m64n256k16_ss_tb<4, 256>(acc, q_lo, b_lo, 1);
          wgmma_m64n256k16_ss_tb<6, 384>(acc, q_lo, b_lo, 1);
          wgmma_commit();
        }
        #pragma unroll 1
        for (int j = 1; j < nkb; j++) {
          const uint32_t slot = ring_slot(qp_pos(j, ta >> 2));
          mbar_wait(b_full + 8 * slot, ring_par(qp_pos(j, ta >> 2)) ^ ((j >> 2) & 1));
          if (QP_STAG > 0 && cwg == 1 && j == nkb - QP_STAG) named_bar_sync(7, 256);
          const uint32_t a_lo = q_lo + (j & 3) * 1024, b_lo = w_base + slot * 2048;
          wgmma_fence();
          wgmma_m64n256k16_ss_tb<0, 0>(acc, a_lo, b_lo, 1);
          wgmma_m64n256k16_ss_tb<2, 128>(acc, a_lo, b_lo, 1);
          wgmma_m64n256k16_ss_tb<4, 256>(acc, a_lo, b_lo, 1);
          wgmma_m64n256k16_ss_tb<6, 384>(acc, a_lo, b_lo, 1);
          wgmma_commit();
          if (QP_STAG > 0 && cwg == 0 && j == nkb - 1) named_bar_arrive(7, 256);
          if (j > 0) {
            wgmma_wait<1>();
            if (tid == 0) mbar_arrive(b_empty + 8 * ring_slot(qp_pos(j - 1, ta >> 2)));
          }
        }
        wgmma_wait<0>();
        fence_regs(acc);
        FS(2 * it, 1);
        TL_MARK2(29, threadIdx.x == 256 && it == 0);
        if (tid == 0) mbar_arrive(b_empty + 24);
      }
      float o[64], s[64];
      uint32_t p[32], q[32];
      #pragma unroll
      for (int i = 0; i < 32; i++) q[i] = pack_bf16(acc[2 * i] * AT_C, acc[2 * i + 1] * AT_C);
      zero_regs(s);
      const uint32_t sq = sbase + AT_SQ + cwg * 8192;
      float mc0, mc1, al0 = 1.0f, al1 = 1.0f, l0 = 0.f, l1 = 0.f, lp0 = 0.f, lp1 = 0.f;
      bool redo0 = false;
      FS(2 * it, 2);
      mbar_wait(b_full + 8 * ring_slot(ta), ring_par(ta));
      named_bar_sync(1 + cwg, 256);
      FS(2 * it, 3);
      issue_qk(s, q, k_base + ring_slot(ta) * 2048);
      pass_turn(cwg);
      bool ready = mbar_test(b_full + 8 * ring_slot(ta + 1), ring_par(ta + 1)) & mbar_test(b_full + 8 * ring_slot(ta + 2), ring_par(ta + 2));
      stage_q<16>(acc, AT_C, sbase + AT_SQ + frag, lane);
      wgmma_wait<0>();
      fence_regs(s);
      if (tid == 0) mbar_arrive(b_empty + 8 * ring_slot(ta));
      mc0 = 0.f; mc1 = 0.f;
      if (!raw) {
        raw = softmax_mode(s, mc0, mc1);
        if (__builtin_expect(!raw, 0)) softmax_sub(s, mc0, mc1);
      }
      softmax_exp<0, 64>(s);
      #pragma unroll
      for (int J = 0; J < 16; J += 2)
        stmatrix_x4(sbase + AT_SQ + frag + (J >> 3) * 16384 + ((((J & 7) + (lane >> 4)) ^ (lane & 7)) << 4), q[2 * J], q[2 * J + 1], q[2 * J + 2], q[2 * J + 3]);
      pack_p(p, s);
      zero_regs(o);
      FS(2 * it, 4);
      uint32_t ks = ring_slot(ta + 1), vs = ring_slot(ta + 2), kp = ring_par(ta + 1), vp = ring_par(ta + 2);
      auto finish_head = [&]() {
        FS(2 * it, 5);
        redo0 = finish_l(lp0, lp1);
        if (!redo0) stage_o(o, lp0, lp1, sbase + AT_SQ + frag, lane);
        FS(2 * it + 1, 4);
      };
      if (!ready) { mbar_wait(b_full + 8 * ks, kp); mbar_wait(b_full + 8 * vs, vp); }
      #pragma unroll 1
      for (int n = 1; n < 2 * AT_NBLK; n++) {
        named_bar_sync(1 + cwg, 256);
        issue_qk(s, q, k_base + ks * 2048);
        if (n == AT_NBLK + 1) finish_head();
        issue_pv(o, p, v_base + vs * 2048, (n & 15) != 1);
        pass_turn(cwg);
        wgmma_wait<1>();
        fence_regs(s);
        if (tid == 0) mbar_arrive(b_empty + 8 * ks);
        if (__builtin_expect(!raw || (uint32_t)(n - (AT_NBLK - 1)) <= 2u, 0)) {
          if (n == AT_NBLK + 1 && !redo0) {
            fence_proxy_async();
            __syncwarp();
            if (lane == 0) mbar_arrive(b_ordy + 8 * cwg);
          }
          if (n == AT_NBLK - 1) {
            #pragma unroll
            for (int J = 0; J < 16; J += 2)
              ldmatrix_x4(sbase + AT_SQ + 32768 + frag + (J >> 3) * 16384 + ((((J & 7) + (lane >> 4)) ^ (lane & 7)) << 4), q[2 * J], q[2 * J + 1], q[2 * J + 2], q[2 * J + 3]);
          }
          if (!raw) {
            const float m0 = mc0, m1 = mc1;
            const bool ok = softmax_mode(s, mc0, mc1);
            if (n == AT_NBLK) raw = ok;
            else {
              mc0 = mc0 - AT_HEAD > m0 ? mc0 : m0; mc1 = mc1 - AT_HEAD > m1 ? mc1 : m1;
              al0 = ex2_approx(m0 - mc0); al1 = ex2_approx(m1 - mc1);
            }
            if (!raw) softmax_sub(s, mc0, mc1);
          }
        }
        softmax_exp<0, AT_SPLIT>(s);
        add_rowsum(p, l0, l1);
        if (tid == 0) {
          uint32_t dep = zero & __float_as_uint(l0) & __float_as_uint(l1);
          #pragma unroll
          for (int i = AT_SPLIT - AT_PIN - PINB; i < AT_SPLIT - PINB; i += 2) dep &= __float_as_uint(s[i]) & __float_as_uint(s[i + 1]);
          mbar_arrive(b_pin + dep);
        }
        wgmma_wait<0>();
        fence_regs(o);
        if (tid == 0) mbar_arrive(b_empty + 8 * vs);
        ks += 2; if (ks >= 5) { ks -= 5; kp ^= 1; }
        vs += 2; if (vs >= 5) { vs -= 5; vp ^= 1; }
        ready = mbar_test(b_full + 8 * ks, kp) & mbar_test(b_full + 8 * vs, vp);
        softmax_exp<AT_SPLIT, 64>(s);
        pack_p(p, s);
        if (n == AT_NBLK) { lp0 = l0; lp1 = l1; l0 = 0.f; l1 = 0.f; }
        if (__builtin_expect(!raw || !ready, 0)) {
        if (!raw && __any_sync(0xffffffffu, al0 != 1.0f || al1 != 1.0f)) {
          rescale_o(o, al0, al1);
          l0 *= al0; l1 *= al1;
          al0 = 1.0f; al1 = 1.0f;
        }
        if (!ready && n < 2 * AT_NBLK - 1) {
          mbar_wait(b_full + 8 * ks, kp);
          mbar_wait(b_full + 8 * vs, vp);
        }
        }
      }
      FS(2 * it + 1, 5);
      const uint32_t vl = ring_slot(ta + 63);
      vs = ring_slot(ta + 62);
      const uint32_t ob = more ? sbase + vs * 32768 : sbase + AT_SQ + 32768;
      mbar_wait(b_full + 8 * vl, ring_par(ta + 63));
      issue_pv(o, p, v_base + vl * 2048, 1);
      block_end(zero, b_pin);
      add_rowsum(p, l0, l1);
      const bool overflow = finish_l(l0, l1);
      if (!overflow && lane == 0) mbar_arrive(b_q1);
      #pragma unroll
      for (int i = 0; i < 8; i++) asm volatile("mov.b64 {%0, %1}, 0;\nmov.b64 {%2, %3}, 0;" : "=r"(pre[i].x), "=r"(pre[i].y), "=r"(pre[i].z), "=r"(pre[i].w));
      const bool want_pre = !more && bid < OG_MOE, got_pre = want_pre && __all_sync(0xffffffffu, mbar_test(bars + 272, 0));
      if (got_pre) load_pre(pre, sbase, AT_SQ, threadIdx.x - 128);
      mbar_wait(b_empty + 8 * vs, ring_par(ta + 62));
      wgmma_wait<0>();
      fence_regs(o);
      if (tid == 0) mbar_arrive(b_empty + 8 * vl);
      FS(2 * it + 1, 6);
      if (overflow) {
        attn_rows_exact(lds_u32(bars + 400), sq + 32768, ob + cwg * 8192, 4 * ta + 1, kc, vc);
        __syncwarp();
        if (lane == 0) mbar_arrive(b_q1);
      } else stage_o(o, l0, l1, ob + frag, lane);
      if (redo0) attn_rows_exact(lds_u32(bars + 400), sq, sq, 4 * ta, kc, vc);
      fence_proxy_async();
      __syncwarp();
      if (lane == 0) {
        if (redo0) mbar_arrive(b_ordy + 8 * cwg);
        mbar_arrive(b_ordy + 16 + 8 * cwg);
      }
      if (want_pre && !got_pre) load_pre(pre, sbase, AT_SQ, threadIdx.x - 128);
      if (redo0 || overflow) raw = false;
      named_bar_sync(3 + cwg, 128);
      FS(2 * it + 1, 7);
    }
    if (cwg == 0) named_bar_arrive(1, 256);
    if (__builtin_expect(single, 0)) {
      float acc[128];
      uint32_t j = 0, pk[64];
      #pragma unroll
      for (int i = 0; i < 64; i++) asm volatile("" : "=f"(acc[2 * i]), "=f"(acc[2 * i + 1]), "=r"(pk[i]));
      uint4* dst = g_pre;
      int left = 0;
      auto put = [&](bool last) {
        #pragma unroll
        for (int i = 0; i < PUT_N; i++) dst[i * 256] = make_uint4(pk[4 * i], pk[4 * i + 1], pk[4 * i + 2], pk[4 * i + 3]);
        dst += PUT_N * 256;
        #pragma unroll
        for (int i = 0; i < 64 - 4 * PUT_N; i++) asm volatile("mov.b32 %0, %1;" : "=r"(pk[i]) : "r"(pk[i + 4 * PUT_N]));
        __syncwarp();
        if (last && lane == 0) mbar_arrive(bars + 280);
      };
      #pragma unroll 1
      for (int ji = 0; ji < help_njobs(bid); ji++) {
        const int nk = og_pre(help_job(bid, ji));
        #pragma unroll 1
        for (int kk = 0; kk < nk; kk++, j++) {
          const uint32_t slot = ring_slot(qp_pos(j, 1));
          mbar_wait(b_full + 8 * slot, ring_par(qp_pos(j, 1)) ^ ((j >> 2) & 1));
          if (H_STAG > 0 && cwg == 1 && kk == nk - H_STAG) named_bar_sync(7, 256);
          const uint32_t a_lo = q_lo + (j & 3) * 1024, b_lo = w_base + slot * 2048;
          wgmma_fence();
          wgmma_m64n256k16_ss_tb<0, 0>(acc, a_lo, b_lo, kk != 0);
          wgmma_m64n256k16_ss_tb<2, 128>(acc, a_lo, b_lo, 1);
          wgmma_m64n256k16_ss_tb<4, 256>(acc, a_lo, b_lo, 1);
          wgmma_m64n256k16_ss_tb<6, 384>(acc, a_lo, b_lo, 1);
          wgmma_commit();
          if (H_STAG > 0 && cwg == 0 && kk == nk - 1) named_bar_arrive(7, 256);
          wgmma_wait<1>();
          if (kk > 0 && tid == 0) mbar_arrive(b_empty + 8 * ring_slot(qp_pos(j - 1, 1)));
          #pragma unroll 1
          for (int i = ji == OG_JOBS ? 0 : 16 / PUT_N - 1; i < 16 / PUT_N && left > 0; i++) put(--left == 0);
        }
        wgmma_wait<0>();
        fence_regs(acc);
        if (tid == 0) mbar_arrive(b_empty + 8 * ring_slot(qp_pos(j - 1, 1)));
        #pragma unroll
        for (int i = 0; i < 64; i++) pk[i] = pack_bf16(acc[2 * i], acc[2 * i + 1]);
        left = 16 / PUT_N;
        if (ji == PRE_X) mbar_wait(bars + 296, 0);
        dst = g_pre + help_job(bid, ji) * 2048 + threadIdx.x - 128;
      }
      #pragma unroll
      for (int i = 0; i < 16; i++) dst[i * 256] = make_uint4(pk[4 * i], pk[4 * i + 1], pk[4 * i + 2], pk[4 * i + 3]);
      __syncwarp();
      if (lane == 0) mbar_arrive(bars + 280);
      named_bar_sync(5, 256);
      if (threadIdx.x == 128) {
        #pragma unroll 1
        for (int i = 0; i < 5; i++) {
          constexpr int n = OG_HSUM;
          const int used = i == 3 ? 0 : (n + 3 - (i == 4 ? 3 : i)) / 4;
          if ((used ^ (i < 4)) & 1) {
            mbar_arrive(b_full + 8 * ring_slot(4 + i));
            mbar_arrive(b_empty + 8 * ring_slot(4 + i)); mbar_arrive(b_empty + 8 * ring_slot(4 + i));
          }
        }
        mbar_arrive(b_x);
      }
      named_bar_sync(5, 256);
      #pragma unroll
      for (int i = 0; i < 8; i++) pre[i] = make_uint4(0u, 0u, 0u, 0u);
    }
    TL_CLK(3, 1, threadIdx.x == 128);
    TL_CTA(1, threadIdx.x == 256);
    TL_END(3, tid == 0);
    TL_MARK2(19, tid == 0 && !single);
    if (bid < 128) {
      tail_consumer(bid, sbase, &tmOut, pre, cwg, w_gate, w_up);
    }
  }
}

typedef CUresult (*PFN_encodeTiled)(CUtensorMap*, CUtensorMapDataType, cuuint32_t, void*, const cuuint64_t*, const cuuint64_t*,
                                    const cuuint32_t*, const cuuint32_t*, CUtensorMapInterleave, CUtensorMapSwizzle,
                                    CUtensorMapL2promotion, CUtensorMapFloatOOBfill);

CUtensorMap make_map_2d(PFN_encodeTiled enc, const void* ptr, uint64_t inner, uint64_t outer, uint64_t stride_bytes, uint32_t box_inner, uint32_t box_outer) {
  CUtensorMap m;
  cuuint64_t gd[2] = {inner, outer}; cuuint64_t gs[1] = {stride_bytes};
  cuuint32_t bx[2] = {box_inner, box_outer}; cuuint32_t es[2] = {1, 1};
  enc(&m, CU_TENSOR_MAP_DATA_TYPE_BFLOAT16, 2, const_cast<void*>(ptr), gd, gs, bx, es, CU_TENSOR_MAP_INTERLEAVE_NONE,
      CU_TENSOR_MAP_SWIZZLE_128B, CU_TENSOR_MAP_L2_PROMOTION_L2_128B, CU_TENSOR_MAP_FLOAT_OOB_FILL_NONE);
  return m;
}

CUtensorMap make_map_3d(PFN_encodeTiled enc, const void* ptr, uint64_t cols, uint64_t rows, uint32_t box_rows, uint32_t chunks) {
  CUtensorMap m;
  cuuint64_t gd[3] = {64, rows, cols / 64}; cuuint64_t gs[2] = {cols * 2, 128};
  cuuint32_t bx[3] = {64, box_rows, chunks}; cuuint32_t es[3] = {1, 1, 1};
  enc(&m, CU_TENSOR_MAP_DATA_TYPE_BFLOAT16, 3, const_cast<void*>(ptr), gd, gs, bx, es, CU_TENSOR_MAP_INTERLEAVE_NONE,
      CU_TENSOR_MAP_SWIZZLE_128B, CU_TENSOR_MAP_L2_PROMOTION_L2_128B, CU_TENSOR_MAP_FLOAT_OOB_FILL_NONE);
  return m;
}

}

extern "C" void kernel_launch(void* const* d_in, const int* in_sizes, int n_in, void* d_out, int out_size) {
  const bf16* x      = (const bf16*)d_in[0];
  const bf16* kc     = (const bf16*)d_in[1];
  const bf16* vc     = (const bf16*)d_in[2];
  const bf16* wq     = (const bf16*)d_in[3];
  const bf16* wo     = (const bf16*)d_in[4];
  const bf16* w_r    = (const bf16*)d_in[6];
  const bf16* w_gate = (const bf16*)d_in[7];
  const bf16* w_up   = (const bf16*)d_in[8];
  const bf16* w_down = (const bf16*)d_in[9];
  const bf16* cvec   = (const bf16*)d_in[10];
  const bf16* w_mod  = (const bf16*)d_in[11];
  bf16* out = (bf16*)d_out;

  static PFN_encodeTiled enc = nullptr;
  static void *p_h = nullptr, *p_o = nullptr;
  if (!enc) {
    void* fn = nullptr; cudaDriverEntryPointQueryResult qres;
    cudaGetDriverEntryPoint("cuTensorMapEncodeTiled", &fn, cudaEnableDefault, &qres);
    enc = (PFN_encodeTiled)fn;
    cudaGetSymbolAddress(&p_h, g_pre);
    p_h = (uint4*)p_h + 16 * PRE_X * 2048;
    cudaGetSymbolAddress(&p_o, g_o);
    cudaFuncSetAttribute(fused_kernel, cudaFuncAttributeMaxDynamicSharedMemorySize, (int)AT_SMEM);
  }
  const CUtensorMap tm_h   = make_map_2d(enc, p_h, T_D, T_SEQ, T_D * 2, 64, 128);
  const CUtensorMap tm_wq  = make_map_3d(enc, wq, T_DQKV, T_D, 64, 4);
  const CUtensorMap tm_k   = make_map_3d(enc, kc, T_DH, (uint64_t)T_NH * T_SEQ, 128, 2);
  const CUtensorMap tm_v   = make_map_3d(enc, vc, T_DH, (uint64_t)T_NH * T_SEQ, 128, 2);
  const CUtensorMap tm_ost = make_map_2d(enc, p_o, T_DQKV, T_SEQ, T_DQKV * 2, 64, 64);
  const CUtensorMap tm_old = make_map_2d(enc, p_o, T_DQKV, T_SEQ, T_DQKV * 2, 64, 128);
  const CUtensorMap tm_wo  = make_map_3d(enc, wo, T_D, T_DQKV, 64, 2);
  const CUtensorMap tm_d   = make_map_3d(enc, w_down, T_D, T_F, 32, 8);

  const CUtensorMap tm_m   = make_map_2d(enc, w_mod, 6 * T_D, T_D, 6 * T_D * 2, 64, 256);
  const CUtensorMap tm_out = make_map_2d(enc, out, T_D, T_SEQ, T_D * 2, 64, 16);

  fused_kernel<<<132, 384, AT_SMEM, cudaStreamPerThread>>>(tm_h, tm_wq, tm_k, tm_v, tm_ost, tm_old, tm_wo, tm_d, tm_out, tm_m, 0u, (const uint8_t*)wo, kc, vc, x, cvec, w_mod,
             w_r, w_gate, w_up, w_down, out);
}
```

```cpp
#include <cuda_runtime.h>
#include <cuda_bf16.h>
#include <cuda.h>
#include <stdint.h>

namespace {

typedef __nv_bfloat16 bf16;

constexpr int T_SEQ = 2048, T_D = 1024, T_NH = 32, T_DH = 128, T_DQKV = 4096, T_F = 3584;

#define PRE_X 2
__device__ __align__(1024) uint4 g_pre[(16 * PRE_X + 128) * 2048];
#define g_h (reinterpret_cast<bf16*>(g_pre + 16 * PRE_X * 2048))
__device__ __align__(1024) bf16 g_o[T_SEQ * T_DQKV];
__device__ __align__(16) uint8_t g_col[8 * 1536];
__device__ __align__(16) float g_scal[64];
__device__ __align__(16) unsigned int g_hcnt[17 * 32];
__device__ __align__(128) float g_modpart[4 * 2 * T_D];
struct __align__(2048) TailMail {
  float4 part1[T_SEQ * 8];
  uint32_t key[256];
  uint4 cand[16 * 2 * 2 * 128];
  uint32_t cnt[32];
  float ypart[(T_F / 32) * 2 * T_D];
};
__device__ TailMail g_mail;
#define g_part1 g_mail.part1
#define g_key g_mail.key
#define g_cand g_mail.cand
#define CNT_Y (g_mail.cnt)
#define g_ypart g_mail.ypart

__device__ __forceinline__ uint32_t smem_u32(const void* p) { return (uint32_t)__cvta_generic_to_shared(p); }
__device__ __forceinline__ void mbar_init(uint32_t bar, uint32_t cnt) { asm volatile("mbarrier.init.shared::cta.b64 [%0], %1;" :: "r"(bar), "r"(cnt)); }
__device__ __forceinline__ void mbar_expect_tx(uint32_t bar, uint32_t bytes) { asm volatile("mbarrier.arrive.expect_tx.shared::cta.b64 _, [%0], %1;" :: "r"(bar), "r"(bytes) : "memory"); }
__device__ __forceinline__ void mbar_arrive(uint32_t bar) { asm volatile("mbarrier.arrive.shared::cta.b64 _, [%0];" :: "r"(bar) : "memory"); }
__device__ __forceinline__ void mbar_wait(uint32_t bar, uint32_t parity) {
  asm volatile("{\n.reg .pred p;\nLAB_WAIT:\nmbarrier.try_wait.parity.shared::cta.b64 p, [%0], %1;\n@!p bra LAB_WAIT;\n}\n" :: "r"(bar), "r"(parity) : "memory");
}
__device__ __forceinline__ bool mbar_test(uint32_t bar, uint32_t parity) {
  uint32_t r; asm volatile("{\n.reg .pred p;\nmbarrier.test_wait.parity.shared::cta.b64 p, [%1], %2;\nselp.u32 %0, 1, 0, p;\n}\n" : "=r"(r) : "r"(bar), "r"(parity) : "memory");
  return r != 0;
}
__device__ __forceinline__ void mbar_wait_long(uint32_t bar, uint32_t parity) {
  asm volatile("{\n.reg .pred p;\nLAB_WAIT:\nmbarrier.try_wait.parity.shared::cta.b64 p, [%0], %1, %2;\n@!p bra LAB_WAIT;\n}\n" :: "r"(bar), "r"(parity), "r"(100000) : "memory");
}
__device__ __forceinline__ uint32_t clock_lo() { uint32_t c; asm volatile("mov.u32 %0, %%clock;" : "=r"(c)); return c; }
__device__ __forceinline__ void fence_mbar_init() { asm volatile("fence.mbarrier_init.release.cluster;" ::: "memory"); }
__device__ __forceinline__ void tma_load_2d(uint32_t dst, const CUtensorMap* map, int c0, int c1, uint32_t bar) {
  asm volatile("cp.async.bulk.tensor.2d.shared::cluster.global.mbarrier::complete_tx::bytes [%0], [%1, {%3, %4}], [%2];"
    :: "r"(dst), "l"(map), "r"(bar), "r"(c0), "r"(c1) : "memory");
}
__device__ __forceinline__ uint64_t policy_evict_first() {
  uint64_t p; asm volatile("createpolicy.fractional.L2::evict_first.b64 %0, 1.0;" : "=l"(p)); return p;
}
__device__ __forceinline__ void tma_load_2d_hint(uint32_t dst, const CUtensorMap* map, int c0, int c1, uint32_t bar, uint64_t pol) {
  asm volatile("cp.async.bulk.tensor.2d.shared::cluster.global.mbarrier::complete_tx::bytes.L2::cache_hint [%0], [%1, {%3, %4}], [%2], %5;"
    :: "r"(dst), "l"(map), "r"(bar), "r"(c0), "r"(c1), "l"(pol) : "memory");
}
__device__ __forceinline__ void tma_load_3d_hint(uint32_t dst, const CUtensorMap* map, int c1, int c2, uint32_t bar, uint64_t pol) {
  asm volatile("cp.async.bulk.tensor.3d.shared::cluster.global.mbarrier::complete_tx::bytes.L2::cache_hint [%0], [%1, {%3, %4, %5}], [%2], %6;"
    :: "r"(dst), "l"(map), "r"(bar), "n"(0), "r"(c1), "r"(c2), "l"(pol) : "memory");
}
__device__ __forceinline__ void tma_load_3d(uint32_t dst, const CUtensorMap* map, int c1, int c2, uint32_t bar) {
  asm volatile("cp.async.bulk.tensor.3d.shared::cluster.global.mbarrier::complete_tx::bytes [%0], [%1, {%3, %4, %5}], [%2];"
    :: "r"(dst), "l"(map), "r"(bar), "n"(0), "r"(c1), "r"(c2) : "memory");
}
__device__ __forceinline__ void tma_store_2d(const CUtensorMap* map, uint32_t src, int c0, int c1) {
  asm volatile("cp.async.bulk.tensor.2d.global.shared::cta.bulk_group [%0, {%2, %3}], [%1];" :: "l"(map), "r"(src), "r"(c0), "r"(c1) : "memory");
}
__device__ __forceinline__ void prefetch_tmap(const CUtensorMap* map) { asm volatile("prefetch.tensormap [%0];" :: "l"(map) : "memory"); }
__device__ __forceinline__ void l2_prefetch_bulk(const void* p, uint32_t bytes) {
  asm volatile("cp.async.bulk.prefetch.L2.global [%0], %1;" :: "l"(p), "r"(bytes) : "memory");
}
__device__ __forceinline__ void bulk_commit() { asm volatile("cp.async.bulk.commit_group;" ::: "memory"); }
template<int N> __device__ __forceinline__ void bulk_wait_read() { asm volatile("cp.async.bulk.wait_group.read %0;" :: "n"(N) : "memory"); }
template<int N> __device__ __forceinline__ void bulk_wait() { asm volatile("cp.async.bulk.wait_group %0;" :: "n"(N) : "memory"); }
__device__ __forceinline__ void named_bar_sync(int id, int nthreads) { asm volatile("bar.sync %0, %1;" :: "r"(id), "r"(nthreads) : "memory"); }
__device__ __forceinline__ void named_bar_arrive(int id, int nthreads) { asm volatile("bar.arrive %0, %1;" :: "r"(id), "r"(nthreads) : "memory"); }
__device__ __forceinline__ void pass_turn(int cwg) {
  asm volatile("{\n.reg .pred p;\nsetp.ne.u32 p, %0, 0;\n@p bar.arrive 1, 256;\n@!p bar.arrive 2, 256;\n}\n" :: "r"(cwg) : "memory");
}
__device__ __forceinline__ void wgmma_fence() { asm volatile("wgmma.fence.sync.aligned;" ::: "memory"); }
__device__ __forceinline__ void wgmma_commit() { asm volatile("wgmma.commit_group.sync.aligned;" ::: "memory"); }
template<int N> __device__ __forceinline__ void wgmma_wait() { asm volatile("wgmma.wait_group.sync.aligned %0;" :: "n"(N) : "memory"); }
template<int R> __device__ __forceinline__ void reg_alloc() { asm volatile("setmaxnreg.inc.sync.aligned.u32 %0;" :: "n"(R)); }
template<int R> __device__ __forceinline__ void reg_dealloc() { asm volatile("setmaxnreg.dec.sync.aligned.u32 %0;" :: "n"(R)); }
__device__ __forceinline__ bool elect_one() {
  uint32_t pred; asm volatile("{\n.reg .pred p;\nelect.sync _|p, 0xffffffff;\nselp.u32 %0, 1, 0, p;\n}\n" : "=r"(pred)); return pred != 0;
}
__device__ __forceinline__ uint32_t pack_bf16(float lo, float hi) {
  uint32_t r; asm("cvt.rn.bf16x2.f32 %0, %1, %2;" : "=r"(r) : "f"(hi), "f"(lo)); return r;
}
__device__ __forceinline__ void stmatrix_x4(uint32_t addr, uint32_t r0, uint32_t r1, uint32_t r2, uint32_t r3) {
  asm volatile("stmatrix.sync.aligned.m8n8.x4.shared.b16 [%0], {%1, %2, %3, %4};" :: "r"(addr), "r"(r0), "r"(r1), "r"(r2), "r"(r3) : "memory");
}
__device__ __forceinline__ void fence_proxy_async() { asm volatile("fence.proxy.async.shared::cta;" ::: "memory"); }
__device__ __forceinline__ float ex2_approx(float x) { float y; asm("ex2.approx.ftz.f32 %0, %1;" : "=f"(y) : "f"(x)); return y; }
template<int N> __device__ __forceinline__ void fence_regs(float (&r)[N]) {
  #pragma unroll
  for (int i = 0; i < N; i++) asm volatile("" : "+f"(r[i]) :: "memory");
}
template<int N> __device__ __forceinline__ void zero_regs(float (&r)[N]) {
  #pragma unroll
  for (int i = 0; i < N; i += 2) asm volatile("mov.b64 {%0, %1}, 0;" : "=f"(r[i]), "=f"(r[i + 1]));
}
__device__ __forceinline__ float rbf(float x) { return __uint_as_float(pack_bf16(0.f, x)); }
__device__ __forceinline__ float bflo(uint32_t v) { return __uint_as_float(v << 16); }
__device__ __forceinline__ float bfhi(uint32_t v) { return __uint_as_float(v & 0xffff0000u); }

#define XT(i) do {} while (0)
#define TL_START(k) do {} while (0)
#define TL_END(k, cond) do {} while (0)
#define TL_CTA(i, cond) do {} while (0)
#define FS(slot, k) do {} while (0)
#define TL_MARK2(k, cond) do {} while (0)
#define TL_CLK(k, i, cond) do {} while (0)

template <int OFFA, int OFFB>
__device__ __forceinline__ void wgmma_m64n256k16_ss_tb(float (&d)[128], uint32_t a_lo, uint32_t b_lo, int scaleD) {
  asm volatile("{\n.reg .pred p;\n.reg .b32 ta, tb;\n.reg .b64 da, db;\nsetp.ne.b32 p, %130, 0;\n"
    "add.u32 ta, %128, %131;\nadd.u32 tb, %129, %132;\n"
    "mov.b64 da, {ta, 0x40000040};\nmov.b64 db, {tb, 0x40000040};\n"
    "wgmma.mma_async.sync.aligned.m64n256k16.f32.bf16.bf16 "
    "{%0, %1, %2, %3, %4, %5, %6, %7, %8, %9, %10, %11, %12, %13, %14, %15, %16, %17, %18, %19, %20, %21, %22, %23, %24, %25, %26, %27, %28, %29, %30, %31, %32, %33, %34, %35, %36, %37, %38, %39, %40, %41, %42, %43, %44, %45, %46, %47, %48, %49, %50, %51, %52, %53, %54, %55, %56, %57, %58, %59, %60, %61, %62, %63, %64, %65, %66, %67, %68, %69, %70, %71, %72, %73, %74, %75, %76, %77, %78, %79, %80, %81, %82, %83, %84, %85, %86, %87, %88, %89, %90, %91, %92, %93, %94, %95, %96, %97, %98, %99, %100, %101, %102, %103, %104, %105, %106, %107, %108, %109, %110, %111, %112, %113, %114, %115, %116, %117, %118, %119, %120, %121, %122, %123, %124, %125, %126, %127}, "
    "da, db, p, 1, 1, 0, 1;\n}\n"
    : "+f"(d[0]), "+f"(d[1]), "+f"(d[2]), "+f"(d[3]), "+f"(d[4]), "+f"(d[5]), "+f"(d[6]), "+f"(d[7]), "+f"(d[8]), "+f"(d[9]), "+f"(d[10]), "+f"(d[11]), "+f"(d[12]), "+f"(d[13]), "+f"(d[14]), "+f"(d[15]), "+f"(d[16]), "+f"(d[17]), "+f"(d[18]), "+f"(d[19]), "+f"(d[20]), "+f"(d[21]), "+f"(d[22]), "+f"(d[23]), "+f"(d[24]), "+f"(d[25]), "+f"(d[26]), "+f"(d[27]), "+f"(d[28]), "+f"(d[29]), "+f"(d[30]), "+f"(d[31]), "+f"(d[32]), "+f"(d[33]), "+f"(d[34]), "+f"(d[35]), "+f"(d[36]), "+f"(d[37]), "+f"(d[38]), "+f"(d[39]), "+f"(d[40]), "+f"(d[41]), "+f"(d[42]), "+f"(d[43]), "+f"(d[44]), "+f"(d[45]), "+f"(d[46]), "+f"(d[47]), "+f"(d[48]), "+f"(d[49]), "+f"(d[50]), "+f"(d[51]), "+f"(d[52]), "+f"(d[53]), "+f"(d[54]), "+f"(d[55]), "+f"(d[56]), "+f"(d[57]), "+f"(d[58]), "+f"(d[59]), "+f"(d[60]), "+f"(d[61]), "+f"(d[62]), "+f"(d[63]), "+f"(d[64]), "+f"(d[65]), "+f"(d[66]), "+f"(d[67]), "+f"(d[68]), "+f"(d[69]), "+f"(d[70]), "+f"(d[71]), "+f"(d[72]), "+f"(d[73]), "+f"(d[74]), "+f"(d[75]), "+f"(d[76]), "+f"(d[77]), "+f"(d[78]), "+f"(d[79]), "+f"(d[80]), "+f"(d[81]), "+f"(d[82]), "+f"(d[83]), "+f"(d[84]), "+f"(d[85]), "+f"(d[86]), "+f"(d[87]), "+f"(d[88]), "+f"(d[89]), "+f"(d[90]), "+f"(d[91]), "+f"(d[92]), "+f"(d[93]), "+f"(d[94]), "+f"(d[95]), "+f"(d[96]), "+f"(d[97]), "+f"(d[98]), "+f"(d[99]), "+f"(d[100]), "+f"(d[101]), "+f"(d[102]), "+f"(d[103]), "+f"(d[104]), "+f"(d[105]), "+f"(d[106]), "+f"(d[107]), "+f"(d[108]), "+f"(d[109]), "+f"(d[110]), "+f"(d[111]), "+f"(d[112]), "+f"(d[113]), "+f"(d[114]), "+f"(d[115]), "+f"(d[116]), "+f"(d[117]), "+f"(d[118]), "+f"(d[119]), "+f"(d[120]), "+f"(d[121]), "+f"(d[122]), "+f"(d[123]), "+f"(d[124]), "+f"(d[125]), "+f"(d[126]), "+f"(d[127])
    : "r"(a_lo), "r"(b_lo), "r"(scaleD), "n"(OFFA), "n"(OFFB));
}

template <int OFFA, int OFFB>
__device__ __forceinline__ void wgmma_m64n128k16_ss_tb(float (&d)[64], uint32_t a_lo, uint32_t b_lo, int scaleD) {
  asm volatile("{\n.reg .pred p;\n.reg .b32 ta, tb;\n.reg .b64 da, db;\nsetp.ne.b32 p, %66, 0;\n"
    "add.u32 ta, %64, %67;\nadd.u32 tb, %65, %68;\n"
    "mov.b64 da, {ta, 0x40000040};\nmov.b64 db, {tb, 0x40000040};\n"
    "wgmma.mma_async.sync.aligned.m64n128k16.f32.bf16.bf16 "
    "{%0, %1, %2, %3, %4, %5, %6, %7, %8, %9, %10, %11, %12, %13, %14, %15, %16, %17, %18, %19, %20, %21, %22, %23, %24, %25, %26, %27, %28, %29, %30, %31, %32, %33, %34, %35, %36, %37, %38, %39, %40, %41, %42, %43, %44, %45, %46, %47, %48, %49, %50, %51, %52, %53, %54, %55, %56, %57, %58, %59, %60, %61, %62, %63}, "
    "da, db, p, 1, 1, 0, 1;\n}\n"
    : "+f"(d[0]), "+f"(d[1]), "+f"(d[2]), "+f"(d[3]), "+f"(d[4]), "+f"(d[5]), "+f"(d[6]), "+f"(d[7]), "+f"(d[8]), "+f"(d[9]), "+f"(d[10]), "+f"(d[11]), "+f"(d[12]), "+f"(d[13]), "+f"(d[14]), "+f"(d[15]), "+f"(d[16]), "+f"(d[17]), "+f"(d[18]), "+f"(d[19]), "+f"(d[20]), "+f"(d[21]), "+f"(d[22]), "+f"(d[23]), "+f"(d[24]), "+f"(d[25]), "+f"(d[26]), "+f"(d[27]), "+f"(d[28]), "+f"(d[29]), "+f"(d[30]), "+f"(d[31]), "+f"(d[32]), "+f"(d[33]), "+f"(d[34]), "+f"(d[35]), "+f"(d[36]), "+f"(d[37]), "+f"(d[38]), "+f"(d[39]), "+f"(d[40]), "+f"(d[41]), "+f"(d[42]), "+f"(d[43]), "+f"(d[44]), "+f"(d[45]), "+f"(d[46]), "+f"(d[47]), "+f"(d[48]), "+f"(d[49]), "+f"(d[50]), "+f"(d[51]), "+f"(d[52]), "+f"(d[53]), "+f"(d[54]), "+f"(d[55]), "+f"(d[56]), "+f"(d[57]), "+f"(d[58]), "+f"(d[59]), "+f"(d[60]), "+f"(d[61]), "+f"(d[62]), "+f"(d[63])
    : "r"(a_lo), "r"(b_lo), "r"(scaleD), "n"(OFFA), "n"(OFFB));
}

template <int OFFB>
__device__ __forceinline__ void wgmma_m64n128k16_rs_tb(float (&d)[64], uint32_t a0, uint32_t a1, uint32_t a2, uint32_t a3, uint32_t b_lo, int scaleD) {
  asm volatile("{\n.reg .pred p;\n.reg .b32 tb;\n.reg .b64 db;\nsetp.ne.b32 p, %69, 0;\n"
    "add.u32 tb, %68, %70;\n"
    "mov.b64 db, {tb, 0x40000040};\n"
    "wgmma.mma_async.sync.aligned.m64n128k16.f32.bf16.bf16 "
    "{%0, %1, %2, %3, %4, %5, %6, %7, %8, %9, %10, %11, %12, %13, %14, %15, %16, %17, %18, %19, %20, %21, %22, %23, %24, %25, %26, %27, %28, %29, %30, %31, %32, %33, %34, %35, %36, %37, %38, %39, %40, %41, %42, %43, %44, %45, %46, %47, %48, %49, %50, %51, %52, %53, %54, %55, %56, %57, %58, %59, %60, %61, %62, %63}, "
    "{%64, %65, %66, %67}, db, p, 1, 1, 1;\n}\n"
    : "+f"(d[0]), "+f"(d[1]), "+f"(d[2]), "+f"(d[3]), "+f"(d[4]), "+f"(d[5]), "+f"(d[6]), "+f"(d[7]), "+f"(d[8]), "+f"(d[9]), "+f"(d[10]), "+f"(d[11]), "+f"(d[12]), "+f"(d[13]), "+f"(d[14]), "+f"(d[15]), "+f"(d[16]), "+f"(d[17]), "+f"(d[18]), "+f"(d[19]), "+f"(d[20]), "+f"(d[21]), "+f"(d[22]), "+f"(d[23]), "+f"(d[24]), "+f"(d[25]), "+f"(d[26]), "+f"(d[27]), "+f"(d[28]), "+f"(d[29]), "+f"(d[30]), "+f"(d[31]), "+f"(d[32]), "+f"(d[33]), "+f"(d[34]), "+f"(d[35]), "+f"(d[36]), "+f"(d[37]), "+f"(d[38]), "+f"(d[39]), "+f"(d[40]), "+f"(d[41]), "+f"(d[42]), "+f"(d[43]), "+f"(d[44]), "+f"(d[45]), "+f"(d[46]), "+f"(d[47]), "+f"(d[48]), "+f"(d[49]), "+f"(d[50]), "+f"(d[51]), "+f"(d[52]), "+f"(d[53]), "+f"(d[54]), "+f"(d[55]), "+f"(d[56]), "+f"(d[57]), "+f"(d[58]), "+f"(d[59]), "+f"(d[60]), "+f"(d[61]), "+f"(d[62]), "+f"(d[63])
    : "r"(a0), "r"(a1), "r"(a2), "r"(a3), "r"(b_lo), "r"(scaleD), "n"(OFFB));
}

template <int OFFB>
__device__ __forceinline__ void wgmma_m64n128k16_rs(float (&d)[64], uint32_t a0, uint32_t a1, uint32_t a2, uint32_t a3, uint32_t b_lo, int scaleD) {
  asm volatile("{\n.reg .pred p;\n.reg .b32 tb;\n.reg .b64 db;\nsetp.ne.b32 p, %69, 0;\n"
    "add.u32 tb, %68, %70;\n"
    "mov.b64 db, {tb, 0x40000040};\n"
    "wgmma.mma_async.sync.aligned.m64n128k16.f32.bf16.bf16 "
    "{%0, %1, %2, %3, %4, %5, %6, %7, %8, %9, %10, %11, %12, %13, %14, %15, %16, %17, %18, %19, %20, %21, %22, %23, %24, %25, %26, %27, %28, %29, %30, %31, %32, %33, %34, %35, %36, %37, %38, %39, %40, %41, %42, %43, %44, %45, %46, %47, %48, %49, %50, %51, %52, %53, %54, %55, %56, %57, %58, %59, %60, %61, %62, %63}, "
    "{%64, %65, %66, %67}, db, p, 1, 1, 0;\n}\n"
    : "+f"(d[0]), "+f"(d[1]), "+f"(d[2]), "+f"(d[3]), "+f"(d[4]), "+f"(d[5]), "+f"(d[6]), "+f"(d[7]), "+f"(d[8]), "+f"(d[9]), "+f"(d[10]), "+f"(d[11]), "+f"(d[12]), "+f"(d[13]), "+f"(d[14]), "+f"(d[15]), "+f"(d[16]), "+f"(d[17]), "+f"(d[18]), "+f"(d[19]), "+f"(d[20]), "+f"(d[21]), "+f"(d[22]), "+f"(d[23]), "+f"(d[24]), "+f"(d[25]), "+f"(d[26]), "+f"(d[27]), "+f"(d[28]), "+f"(d[29]), "+f"(d[30]), "+f"(d[31]), "+f"(d[32]), "+f"(d[33]), "+f"(d[34]), "+f"(d[35]), "+f"(d[36]), "+f"(d[37]), "+f"(d[38]), "+f"(d[39]), "+f"(d[40]), "+f"(d[41]), "+f"(d[42]), "+f"(d[43]), "+f"(d[44]), "+f"(d[45]), "+f"(d[46]), "+f"(d[47]), "+f"(d[48]), "+f"(d[49]), "+f"(d[50]), "+f"(d[51]), "+f"(d[52]), "+f"(d[53]), "+f"(d[54]), "+f"(d[55]), "+f"(d[56]), "+f"(d[57]), "+f"(d[58]), "+f"(d[59]), "+f"(d[60]), "+f"(d[61]), "+f"(d[62]), "+f"(d[63])
    : "r"(a0), "r"(a1), "r"(a2), "r"(a3), "r"(b_lo), "r"(scaleD), "n"(OFFB));
}

__device__ __forceinline__ uint4 ldg_nc_v4(const void* p) {
  uint4 v;
    asm volatile("{\n.reg .b64 pol;\ncreatepolicy.fractional.L2::evict_first.b64 pol, 1.0;\n"
                 "ld.global.nc.L1::no_allocate.L2::cache_hint.v4.u32 {%0, %1, %2, %3}, [%4], pol;\n}\n" : "=r"(v.x), "=r"(v.y), "=r"(v.z), "=r"(v.w) : "l"(p));
  return v;
}
__device__ __forceinline__ void unpack8(const uint4& u, float (&v)[8]) {
  v[0] = bflo(u.x); v[1] = bfhi(u.x); v[2] = bflo(u.y); v[3] = bfhi(u.y);
  v[4] = bflo(u.z); v[5] = bfhi(u.z); v[6] = bflo(u.w); v[7] = bfhi(u.w);
}
__device__ __forceinline__ void fma8(float (&acc)[8], float s, const uint4& w) {
  acc[0] = fmaf(s, bflo(w.x), acc[0]); acc[1] = fmaf(s, bfhi(w.x), acc[1]); acc[2] = fmaf(s, bflo(w.y), acc[2]); acc[3] = fmaf(s, bfhi(w.y), acc[3]);
  acc[4] = fmaf(s, bflo(w.z), acc[4]); acc[5] = fmaf(s, bfhi(w.z), acc[5]); acc[6] = fmaf(s, bflo(w.w), acc[6]); acc[7] = fmaf(s, bfhi(w.w), acc[7]);
}
__device__ __forceinline__ float rcp_approx(float x) { float y; asm("rcp.approx.ftz.f32 %0, %1;" : "=f"(y) : "f"(x)); return y; }
__device__ __forceinline__ float sigmoid_f(float v) { return rcp_approx(1.0f + ex2_approx(v * -1.4426950408889634f)); }
__device__ __forceinline__ float silu_bf(float v) { return rbf(v * sigmoid_f(v)); }
__device__ __forceinline__ uint32_t rank_key(float r, int idx) {
  const uint32_t b = __float_as_uint(r) >> 16;
  const uint32_t u = (r != r) ? 0u : ((b & 0x8000u) ? (~b & 0xffffu) : (b | 0x8000u));
  return (u << 16) | (0xffffu - (uint32_t)idx);
}
__device__ __forceinline__ void warp_top2(uint32_t& k1, uint32_t& k2) {
  const uint32_t m1 = __reduce_max_sync(0xffffffffu, k1);
  k2 = __reduce_max_sync(0xffffffffu, k1 == m1 ? k2 : k1);
  k1 = m1;
}
__device__ __forceinline__ uint32_t bmul2(uint32_t a, uint32_t b) { uint32_t r; asm("mul.rn.bf16x2 %0, %1, %2;" : "=r"(r) : "r"(a), "r"(b)); return r; }
__device__ __forceinline__ uint32_t badd2(uint32_t a, uint32_t b) { uint32_t r; asm("add.rn.bf16x2 %0, %1, %2;" : "=r"(r) : "r"(a), "r"(b)); return r; }
__device__ __forceinline__ uint32_t bsub2(uint32_t a, uint32_t b) { uint32_t r; asm("sub.rn.bf16x2 %0, %1, %2;" : "=r"(r) : "r"(a), "r"(b)); return r; }
__device__ __forceinline__ float sqrt_approx(float x) { float y; asm("sqrt.approx.f32 %0, %1;" : "=f"(y) : "f"(x)); return y; }
__device__ __forceinline__ uint32_t ln_norm2(uint32_t x1, uint32_t mb2, float inv) {
  const uint32_t d = bsub2(x1, mb2);
  return pack_bf16(bflo(d) * inv, bfhi(d) * inv);
}
__device__ __forceinline__ uint32_t bfma2(uint32_t a, uint32_t b, uint32_t c) { uint32_t r; asm("fma.rn.bf16x2 %0, %1, %2, %3;" : "=r"(r) : "r"(a), "r"(b), "r"(c)); return r; }
__device__ __forceinline__ uint32_t ln_norm2b(uint32_t x1, uint32_t mb2, uint32_t ih, uint32_t il) {
  const uint32_t d = bsub2(x1, mb2);
  return bfma2(d, ih, bmul2(d, il));
}
__device__ __forceinline__ uint32_t ln_mod2(uint32_t x1, uint32_t mb2, float inv, uint32_t c1, uint32_t sb) { return badd2(bmul2(ln_norm2(x1, mb2, inv), c1), sb); }
__device__ __forceinline__ void ldmatrix_x4(uint32_t addr, uint32_t& r0, uint32_t& r1, uint32_t& r2, uint32_t& r3) {
  asm volatile("ldmatrix.sync.aligned.m8n8.x4.shared.b16 {%0, %1, %2, %3}, [%4];" : "=r"(r0), "=r"(r1), "=r"(r2), "=r"(r3) : "r"(addr) : "memory");
}
__device__ __forceinline__ uint4 ldg_stream_v4(const void* p, uint64_t pol) {
  uint4 v; asm volatile("ld.global.nc.L1::no_allocate.L2::cache_hint.L2::128B.v4.u32 {%0, %1, %2, %3}, [%4], %5;" : "=r"(v.x), "=r"(v.y), "=r"(v.z), "=r"(v.w) : "l"(p), "l"(pol)); return v;
}
__device__ __forceinline__ void bulk_load_hint(uint32_t dst, const void* src, uint32_t bytes, uint32_t bar, uint64_t pol) {
  asm volatile("cp.async.bulk.shared::cluster.global.mbarrier::complete_tx::bytes.L2::cache_hint [%0], [%1], %2, [%3], %4;"
    :: "r"(dst), "l"(src), "r"(bytes), "r"(bar), "l"(pol) : "memory");
}
__device__ __forceinline__ void red_release_add(unsigned int* p, unsigned int v) { asm volatile("red.release.gpu.global.add.u32 [%0], %1;" :: "l"(p), "r"(v) : "memory"); }
__device__ __forceinline__ unsigned int ld_acquire(const unsigned int* p) { unsigned int v; asm volatile("ld.acquire.gpu.global.u32 %0, [%1];" : "=r"(v) : "l"(p) : "memory"); return v; }
__device__ __forceinline__ void spin_until(const unsigned int* p, unsigned int target) {
  #pragma unroll 1
  for (unsigned int i = 0; i < (1u << 22); i++) { if (ld_acquire(p) >= target) return; }
}
__device__ __forceinline__ float lds_f32(uint32_t a) { float v; asm volatile("ld.shared.f32 %0, [%1];" : "=f"(v) : "r"(a) : "memory"); return v; }
__device__ __forceinline__ float2 lds_f32x2(uint32_t a) { float2 v; asm volatile("ld.shared.v2.f32 {%0, %1}, [%2];" : "=f"(v.x), "=f"(v.y) : "r"(a) : "memory"); return v; }
__device__ __forceinline__ uint2 lds_u32x2(uint32_t a) { uint2 v; asm volatile("ld.shared.v2.u32 {%0, %1}, [%2];" : "=r"(v.x), "=r"(v.y) : "r"(a) : "memory"); return v; }
__device__ __forceinline__ uint32_t lds_u32(uint32_t a) { uint32_t v; asm volatile("ld.shared.u32 %0, [%1];" : "=r"(v) : "r"(a) : "memory"); return v; }
__device__ __forceinline__ void sts_u32(uint32_t a, uint32_t v) { asm volatile("st.shared.u32 [%0], %1;" :: "r"(a), "r"(v) : "memory"); }
__device__ __forceinline__ void sts_u32x2(uint32_t a, uint32_t x, uint32_t y) { asm volatile("st.shared.v2.u32 [%0], {%1, %2};" :: "r"(a), "r"(x), "r"(y) : "memory"); }
__device__ __forceinline__ void sts_f32(uint32_t a, float v) { asm volatile("st.shared.f32 [%0], %1;" :: "r"(a), "f"(v) : "memory"); }
__device__ __forceinline__ void sts_f32x2(uint32_t a, float x, float y) { asm volatile("st.shared.v2.f32 [%0], {%1, %2};" :: "r"(a), "f"(x), "f"(y) : "memory"); }
__device__ __forceinline__ void sts_f32x4(uint32_t a, float x, float y, float z, float w) { asm volatile("st.shared.v4.f32 [%0], {%1, %2, %3, %4};" :: "r"(a), "f"(x), "f"(y), "f"(z), "f"(w) : "memory"); }

__device__ __forceinline__ uint4 lds_u32x4(uint32_t a) { uint4 v; asm volatile("ld.shared.v4.u32 {%0, %1, %2, %3}, [%4];" : "=r"(v.x), "=r"(v.y), "=r"(v.z), "=r"(v.w) : "r"(a) : "memory"); return v; }
__device__ __forceinline__ void sts_u32x4(uint32_t a, uint32_t x, uint32_t y, uint32_t z, uint32_t w) { asm volatile("st.shared.v4.u32 [%0], {%1, %2, %3, %4};" :: "r"(a), "r"(x), "r"(y), "r"(z), "r"(w) : "memory"); }
__device__ __forceinline__ void st_tagged(float* p, float v) {
  const uint32_t b = __float_as_uint(v);
  asm volatile("st.relaxed.gpu.global.u32 [%0], %1;" :: "l"(p), "r"(b == 0u ? 0x80000000u : b) : "memory");
}
__device__ __forceinline__ void st_tagged4(float* p, float x, float y, float z, float w) {
  const uint32_t a = __float_as_uint(x), b = __float_as_uint(y), c = __float_as_uint(z), d = __float_as_uint(w);
  asm volatile("st.relaxed.gpu.global.v4.u32 [%0], {%1, %2, %3, %4};" :: "l"(p), "r"(a == 0u ? 0x80000000u : a), "r"(b == 0u ? 0x80000000u : b),
               "r"(c == 0u ? 0x80000000u : c), "r"(d == 0u ? 0x80000000u : d) : "memory");
}
__device__ __forceinline__ void st_relaxed2(void* p, uint32_t a, uint32_t b) { asm volatile("st.relaxed.gpu.global.v2.u32 [%0], {%1, %2};" :: "l"(p), "r"(a), "r"(b) : "memory"); }
__device__ __forceinline__ float4 ld_tagged4(const float* p) {
  float4 v; asm volatile("ld.relaxed.gpu.global.v4.f32 {%0, %1, %2, %3}, [%4];" : "=f"(v.x), "=f"(v.y), "=f"(v.z), "=f"(v.w) : "l"(p) : "memory"); return v;
}
__device__ __forceinline__ bool tagged4(const float4& v) {
  return __float_as_uint(v.x) != 0u && __float_as_uint(v.y) != 0u && __float_as_uint(v.z) != 0u && __float_as_uint(v.w) != 0u;
}
__device__ __forceinline__ void hint_arrive(uint32_t* p) { asm volatile("red.relaxed.gpu.global.add.u32 [%0], 1;" :: "l"(p) : "memory"); }
__device__ __forceinline__ void hint_wait(const uint32_t* p, uint32_t target) {
  uint32_t v = 0u;
  #pragma unroll 1
  for (unsigned int i = 0; i < (1u << 22) && v < target; i++) asm volatile("ld.relaxed.gpu.global.u32 %0, [%1];" : "=r"(v) : "l"(p) : "memory");
}
__device__ __forceinline__ void fence_proxy_async_global() { asm volatile("fence.proxy.async.global;" ::: "memory"); }

#define H_SPLIT 1
#define X_DLY 1200
#define W_DLY 1900
#define W_FIRST 2200
#define PRE_B 2
template <int J0, int J1>
__device__ __forceinline__ void load_parts(float2 (&pa)[J1 - J0][4], int t2) {
  #pragma unroll
  for (int j = J0; j < J1; j++)
    #pragma unroll
    for (int k = 0; k < 4; k++)
      asm volatile("ld.relaxed.gpu.global.v2.f32 {%0, %1}, [%2];" : "=f"(pa[j - J0][k].x), "=f"(pa[j - J0][k].y)
                   : "l"(g_modpart + k * 2 * T_D + (t2 >> 7) * T_D + j * 256 + (t2 & 127) * 2) : "memory");
}
template <int J0, int J1>
__device__ __forceinline__ void finish_parts(float2 (&pa)[J1 - J0][4], bool loaded, int t2, uint32_t tab) {
  #pragma unroll 1
  for (unsigned int spin = 0; spin < (1u << 22); spin++) {
    if (!loaded) load_parts<J0, J1>(pa, t2);
    loaded = false;
    bool ok = true;
    #pragma unroll
    for (int j = 0; j < J1 - J0; j++)
      #pragma unroll
      for (int k = 0; k < 4; k++) ok &= (__float_as_uint(pa[j][k].x) != 0u) & (__float_as_uint(pa[j][k].y) != 0u);
    if (__all_sync(0xffffffffu, ok)) break;
  }
  #pragma unroll
  for (int j = J0; j < J1; j++) {
    const float2* q = pa[j - J0];
    const uint32_t m = pack_bf16(((q[0].x + q[1].x) + q[2].x) + q[3].x, ((q[0].y + q[1].y) + q[2].y) + q[3].y);
    sts_u32(tab + (t2 >> 7) * 2048 + j * 512 + (t2 & 127) * 4, t2 >= 128 ? badd2(m, 0x3F803F80u) : m);
  }
}
__device__ __forceinline__ int head_cb(uint32_t bid) { return (bid & 16) | ((bid & 3) << 2) | ((bid >> 2) & 3); }
__device__ __forceinline__ void head_phase(uint32_t bid, uint32_t scr, uint32_t xs, uint32_t b_x, uint32_t b_go, uint32_t b_head, int t2, uint32_t zero, const bf16* __restrict__ cvec, const bf16* __restrict__ w_mod) {
  const int lane = t2 & 31, w8 = t2 >> 5;
  const int cb = head_cb(bid), ks = bid >> 5;
  const bool early = (cb & 15) < 4 * H_SPLIT;
  const uint32_t ws = (xs - 32768 + (t2 >> 3) * 128 + (((t2 ^ (t2 >> 3)) & 7) << 4)) ^ zero;
  const float cv = __bfloat162float(cvec[ks * 256 + t2]);
  const bf16* wsrc = w_mod + (size_t)(ks * 256 + (t2 >> 3)) * (6 * T_D) + cb * 64 + (t2 & 7) * 8;
  if (early) {
    const uint64_t pol = policy_evict_first();
    #pragma unroll 2
    for (int i = 0; i < 8; i++)
      asm volatile("cp.async.cg.shared.global.L2::cache_hint [%0], [%1], 16, %2;" :: "r"(ws + i * 4096), "l"(wsrc + (size_t)i * 32 * 6 * T_D), "l"(pol) : "memory");
  }
  sts_f32(scr + t2 * 4, silu_bf(cv));
  named_bar_sync(6, 384);
  TL_MARK2(1, t2 == 0);
  uint4 xv[2][4];
  uint32_t mb2[2], ih[2], il[2];
  auto norm = [&](int j) {
    #pragma unroll
    for (int r = 0; r < 2; r++) {
      xv[r][j].x = ln_norm2b(xv[r][j].x, mb2[r], ih[r], il[r]); xv[r][j].y = ln_norm2b(xv[r][j].y, mb2[r], ih[r], il[r]);
      xv[r][j].z = ln_norm2b(xv[r][j].z, mb2[r], ih[r], il[r]); xv[r][j].w = ln_norm2b(xv[r][j].w, mb2[r], ih[r], il[r]);
    }
  };
  auto modulate = [&](int j) {
    const uint4 sa = lds_u32x4(scr + 8192 + j * 512 + lane * 16), c1 = lds_u32x4(scr + 8192 + 2048 + j * 512 + lane * 16);
    #pragma unroll
    for (int r = 0; r < 2; r++) {
      xv[r][j].x = badd2(bmul2(xv[r][j].x, c1.x), sa.x); xv[r][j].y = badd2(bmul2(xv[r][j].y, c1.y), sa.y);
      xv[r][j].z = badd2(bmul2(xv[r][j].z, c1.z), sa.z); xv[r][j].w = badd2(bmul2(xv[r][j].w, c1.w), sa.w);
    }
  };
  auto store = [&](int j) {
    #pragma unroll
    for (int r = 0; r < 2; r++) *reinterpret_cast<uint4*>(g_h + (size_t)(bid * 16 + 2 * w8 + r) * T_D + j * 256 + lane * 8) = xv[r][j];
  };
  #pragma unroll 1
  for (int ph = 0; ph < 2; ph++) {
    if ((ph == 0) == early) {
      asm volatile("cp.async.wait_all;" ::: "memory");
      if (!early) mbar_wait(b_x + 168, 0);
      float acc[8];
      #pragma unroll
      for (int j = 0; j < 8; j++) acc[j] = 0.f;
      #pragma unroll
      for (int i = 0; i < 8; i++) fma8(acc, lds_f32(scr + ((t2 >> 3) + 32 * i) * 4), lds_u32x4(ws + i * 4096));
      #pragma unroll
      for (int j = 0; j < 4; j++) { const bool up = lane & 16; acc[j] = (up ? acc[4 + j] : acc[j]) + __shfl_xor_sync(0xffffffffu, up ? acc[j] : acc[4 + j], 16); }
      #pragma unroll
      for (int j = 0; j < 2; j++) { const bool up = lane & 8; acc[j] = (up ? acc[2 + j] : acc[j]) + __shfl_xor_sync(0xffffffffu, up ? acc[j] : acc[2 + j], 8); }
      sts_f32x2(scr + 1024 + w8 * 256 + (lane & 7) * 32 + (lane >> 3) * 8, acc[0], acc[1]);
      named_bar_sync(5, 256);
      if (t2 < 64) {
        float sum = 0.f;
        #pragma unroll
        for (int i = 0; i < 8; i++) sum += lds_f32(scr + 1024 + i * 256 + t2 * 4);
        st_tagged(g_modpart + ks * 2 * T_D + cb * 64 + t2, sum);
        TL_MARK2(early ? 2 : 6, t2 == 0);
      }
    } else {
      float2 pa[H_SPLIT][4];
      mbar_wait(b_x, 0);
      TL_MARK2(18, t2 == 0);
      load_parts<0, H_SPLIT>(pa, t2);
      #pragma unroll
      for (int r = 0; r < 2; r++)
        #pragma unroll
        for (int j = 0; j < 4; j++) xv[r][j] = lds_u32x4(xs + (2 * w8 + r) * 2048 + j * 512 + lane * 16);
  {
    float st[4] = {0.f, 0.f, 0.f, 0.f};
    #pragma unroll
    for (int r = 0; r < 2; r++)
      #pragma unroll
      for (int j = 0; j < 4; j++) {
        float v[8];
        unpack8(xv[r][j], v);
        st[2 * r] += ((v[0] + v[1]) + (v[2] + v[3])) + ((v[4] + v[5]) + (v[6] + v[7]));
        st[2 * r + 1] += fmaf(v[0], v[0], fmaf(v[1], v[1], fmaf(v[2], v[2], v[3] * v[3]))) + fmaf(v[4], v[4], fmaf(v[5], v[5], fmaf(v[6], v[6], v[7] * v[7])));
      }
    #pragma unroll
    for (int k = 0; k < 2; k++) { const bool up = lane & 16; st[k] = (up ? st[2 + k] : st[k]) + __shfl_xor_sync(0xffffffffu, up ? st[k] : st[2 + k], 16); }
    #pragma unroll
    for (int o = 8; o > 0; o >>= 1) { st[0] += __shfl_xor_sync(0xffffffffu, st[0], o); st[1] += __shfl_xor_sync(0xffffffffu, st[1], o); }
    const float mean = st[0] * (1.0f / T_D);
    const float inv = rcp_approx(rbf(sqrt_approx(rbf(rbf(fmaxf(fmaf(-mean, mean, st[1] * (1.0f / T_D)), 0.f)) + 1e-05f))));
    const uint32_t m = pack_bf16(mean, mean), h = pack_bf16(inv - rbf(inv), inv);
    #pragma unroll
    for (int r = 0; r < 2; r++) {
      mb2[r] = __shfl_sync(0xffffffffu, m, 16 * r);
      const uint32_t hr = __shfl_sync(0xffffffffu, h, 16 * r);
      ih[r] = __byte_perm(hr, hr, 0x3232); il[r] = __byte_perm(hr, hr, 0x1010);
    }
  }
      #pragma unroll
      for (int j = 0; j < H_SPLIT; j++) norm(j);
      TL_MARK2(5, t2 == 0);
      finish_parts<0, H_SPLIT>(pa, true, t2, scr + 8192);
      named_bar_sync(5, 256);
      TL_MARK2(7, t2 == 0);
      #pragma unroll
      for (int j = 0; j < H_SPLIT; j++) { modulate(j); store(j); }
      named_bar_arrive(9, 288);
    }
  }
  #pragma unroll
  for (int j = H_SPLIT; j < 4; j++) norm(j);
  float2 pb[4 - H_SPLIT][4];
  finish_parts<H_SPLIT, 4>(pb, false, t2, scr + 8192);
  named_bar_sync(5, 256);
  TL_MARK2(17, t2 == 0);
  #pragma unroll
  for (int j = H_SPLIT; j < 4; j++) modulate(j);
  __syncwarp();
  if (lane == 0) mbar_arrive(b_head + (xv[1][3].w & zero));
  mbar_wait(b_go, 0);
  #pragma unroll
  for (int j = H_SPLIT; j < 4; j++) store(j);
  named_bar_arrive(8, 288);
}

#define MOD_AT (b_empty + 8)
#define MOD_SPLIT 16
__device__ __forceinline__ void mod_rest(uint32_t bid, uint32_t scr, uint32_t b_go, int t, const bf16* __restrict__ cvec, const bf16* __restrict__ w_mod, const bf16* __restrict__ w_r) {
  const int lane = t & 31;
  #pragma unroll 1
  for (int i = t; i < T_D / 2; i += 64) {
    const uint32_t c2 = *reinterpret_cast<const uint32_t*>(cvec + 2 * i);
    sts_u32(scr + i * 4, pack_bf16(silu_bf(bflo(c2)), silu_bf(bfhi(c2))));
  }
  named_bar_sync(11, 64);
  const bf16* wp = w_mod + (size_t)(2 * (t >> 2)) * (6 * T_D) + 2 * T_D + bid * 32 + (t & 3) * 8;
  float acc[8];
  #pragma unroll
  for (int i = 0; i < 8; i++) acc[i] = 0.f;
  #pragma unroll 1
  for (int i = 0; i < 32; i += 2) {
    if (i == MOD_SPLIT) mbar_wait_long(b_go, 0);
    const uint4 w0 = ldg_nc_v4(wp), w1 = ldg_nc_v4(wp + 6 * T_D), w2 = ldg_nc_v4(wp + 32 * 6 * T_D), w3 = ldg_nc_v4(wp + 33 * 6 * T_D);
    wp += 64 * 6 * T_D;
    const uint32_t s0 = lds_u32(scr + (i * 16 + (t >> 2)) * 4), s1 = lds_u32(scr + (i * 16 + 16 + (t >> 2)) * 4);
    fma8(acc, bflo(s0), w0); fma8(acc, bfhi(s0), w1); fma8(acc, bflo(s1), w2); fma8(acc, bfhi(s1), w3);
  }
  #pragma unroll
  for (int j = 0; j < 4; j++) { const bool up = lane & 16; acc[j] = (up ? acc[4 + j] : acc[j]) + __shfl_xor_sync(0xffffffffu, up ? acc[j] : acc[4 + j], 16); }
  #pragma unroll
  for (int j = 0; j < 2; j++) { const bool up = lane & 8; acc[j] = (up ? acc[2 + j] : acc[j]) + __shfl_xor_sync(0xffffffffu, up ? acc[j] : acc[2 + j], 8); }
  { const bool up = lane & 4; acc[0] = (up ? acc[1] : acc[0]) + __shfl_xor_sync(0xffffffffu, up ? acc[0] : acc[1], 4); }
  if (t >= 32) sts_f32(scr + 2048 + lane * 4, acc[0]);
  named_bar_sync(11, 64);
  if (__shfl_sync(0xffffffffu, t, 0) < 32) {
    const int kind = bid >> 5;
    float v = rbf(acc[0] + lds_f32(scr + 2048 + lane * 4));
    const int col = (bid & 31) * 32 + (lane & 3) * 8 + (lane >> 2);
    uint8_t* dst = g_col + (col >> 7) * 1536;
    if (kind == 2) v = rbf(1.0f + v);
    float vw = v * __bfloat162float(w_r[col]);
    if (kind == 2) {
      const int c = col & 127, i = (c & ~15) + ((c >> 1) & 3) * 4 + ((c >> 3) & 1) * 2 + (c & 1);
      reinterpret_cast<bf16*>(dst)[i] = __float2bfloat16_rn(vw);
      reinterpret_cast<bf16*>(dst)[128 + i] = __float2bfloat16_rn(vw - rbf(vw));
    }
    reinterpret_cast<bf16*>(dst + 512 + (kind & 1) * 512 + (kind >> 1) * 256)[col & 127] = __float2bfloat16_rn(v);
    #pragma unroll
    for (int o = 16; o > 0; o >>= 1) vw += __shfl_xor_sync(0xffffffffu, vw, o);
    if (lane == 0 && (kind == 1 || kind == 2)) g_scal[95 - bid] = vw;
  }
  #pragma unroll 1
  for (int i = bid * 64 + t; i < (int)(sizeof(g_mail) / 16); i += 128 * 64) reinterpret_cast<uint4*>(&g_mail)[i] = make_uint4(0u, 0u, 0u, 0u);
  named_bar_sync(11, 64);
  if (t == 0) red_release_add(&g_hcnt[0], 1u);
}

constexpr int AT_NBLK = T_SEQ / 128;
constexpr float AT_HEAD = 7.0f;
#define WO_LATE 12
#define QP_STAG 3
#define AT_SPLIT 28
#define AT_PIN 12
#define PINB 4
constexpr int AT_NFULL = 124;
constexpr int AT_PREG = 40, AT_CREG = 232;
constexpr uint32_t AT_SQ = 5 * 32768;
constexpr float AT_C = 0.08838834764831845f * 1.4426950408889634f;
constexpr float AT_RAW_LO = -16.0f, AT_RAW_HI = 24.0f;
constexpr float AT_RAW_SUM = 281474976710656.0f, AT_RAW_MIN = 9.094947017729282e-13f;
constexpr uint32_t AT_SBAR = AT_SQ + 65536 + 256;
constexpr uint32_t AT_SMEM = AT_SQ + 65536 + 3072;

__device__ __forceinline__ uint32_t ring_slot(uint32_t t) { return t - 5u * ((t * 205u) >> 10); }
__device__ __forceinline__ uint32_t qp_pos(uint32_t j, uint32_t it) { return 4u * it + (j & 3u) + ((j & 3u) == 3u ? it : 0u); }
__device__ __forceinline__ uint32_t ring_par(uint32_t t) { return ((t * 205u) >> 10) & 1u; }
__device__ __forceinline__ void softmax_rowmax(const float (&s)[64], float& mx0, float& mx1) {
  float a0 = fmaxf(s[0], s[1]), a1 = fmaxf(s[4], s[5]), a2 = fmaxf(s[8], s[9]), a3 = fmaxf(s[12], s[13]);
  float b0 = fmaxf(s[2], s[3]), b1 = fmaxf(s[6], s[7]), b2 = fmaxf(s[10], s[11]), b3 = fmaxf(s[14], s[15]);
  #pragma unroll
  for (int j = 4; j < 16; j += 4) {
    a0 = fmaxf(a0, fmaxf(s[4 * j + 0], s[4 * j + 1]));  b0 = fmaxf(b0, fmaxf(s[4 * j + 2], s[4 * j + 3]));
    a1 = fmaxf(a1, fmaxf(s[4 * j + 4], s[4 * j + 5]));  b1 = fmaxf(b1, fmaxf(s[4 * j + 6], s[4 * j + 7]));
    a2 = fmaxf(a2, fmaxf(s[4 * j + 8], s[4 * j + 9]));  b2 = fmaxf(b2, fmaxf(s[4 * j + 10], s[4 * j + 11]));
    a3 = fmaxf(a3, fmaxf(s[4 * j + 12], s[4 * j + 13])); b3 = fmaxf(b3, fmaxf(s[4 * j + 14], s[4 * j + 15]));
  }
  mx0 = fmaxf(fmaxf(a0, a1), fmaxf(a2, a3));
  mx1 = fmaxf(fmaxf(b0, b1), fmaxf(b2, b3));
  mx0 = fmaxf(mx0, __shfl_xor_sync(0xffffffffu, mx0, 1));
  mx1 = fmaxf(mx1, __shfl_xor_sync(0xffffffffu, mx1, 1));
  mx0 = fmaxf(mx0, __shfl_xor_sync(0xffffffffu, mx0, 2));
  mx1 = fmaxf(mx1, __shfl_xor_sync(0xffffffffu, mx1, 2));
}
__device__ __forceinline__ void softmax_sub(float (&s)[64], float mc0, float mc1) {
  #pragma unroll
  for (int j = 0; j < 16; j++) { s[4 * j] -= mc0; s[4 * j + 1] -= mc0; s[4 * j + 2] -= mc1; s[4 * j + 3] -= mc1; }
}
template <int LO, int HI>
__device__ __forceinline__ void softmax_exp(float (&s)[64]) {
  #pragma unroll
  for (int i = LO; i < HI; i++) s[i] = ex2_approx(s[i]);
}
__device__ __forceinline__ bool softmax_mode(const float (&s)[64], float& mc0, float& mc1) {
  softmax_rowmax(s, mc0, mc1);
  const bool raw = __all_sync(0xffffffffu, mc0 >= AT_RAW_LO && mc0 <= AT_RAW_HI && mc1 >= AT_RAW_LO && mc1 <= AT_RAW_HI);
  mc0 += AT_HEAD; mc1 += AT_HEAD;
  return raw;
}
__device__ __forceinline__ void rowsum_p(const uint32_t (&p)[32], uint32_t& t0, uint32_t& t1) {
  uint32_t a[16];
  #pragma unroll
  for (int i = 0; i < 8; i++) { a[2 * i] = badd2(p[4 * i], p[4 * i + 2]); a[2 * i + 1] = badd2(p[4 * i + 1], p[4 * i + 3]); }
  #pragma unroll
  for (int i = 0; i < 4; i++) { a[2 * i] = badd2(a[4 * i], a[4 * i + 2]); a[2 * i + 1] = badd2(a[4 * i + 1], a[4 * i + 3]); }
  t0 = badd2(badd2(a[0], a[2]), badd2(a[4], a[6]));
  t1 = badd2(badd2(a[1], a[3]), badd2(a[5], a[7]));
}
__device__ __forceinline__ void add_rowsum(const uint32_t (&p)[32], float& l0, float& l1) {
  uint32_t t0, t1;
  rowsum_p(p, t0, t1);
  l0 += bflo(t0) + bfhi(t0); l1 += bflo(t1) + bfhi(t1);
}
__device__ __forceinline__ void pack_p(uint32_t (&p)[32], const float (&s)[64]) {
  #pragma unroll
  for (int i = 0; i < 32; i++) p[i] = pack_bf16(s[2 * i], s[2 * i + 1]);
}
__device__ __noinline__ void attn_rows_exact(uint32_t bid, uint32_t sq, uint32_t so, int hsel, const bf16* __restrict__ kh, const bf16* __restrict__ vh) {
  const int warp = (threadIdx.x >> 5) & 3, lane = threadIdx.x & 31;
  const size_t hofs = (size_t)((bid < 128 ? bid >> 4 : 15) * 2 + hsel) * T_SEQ * T_DH;
  kh += hofs; vh += hofs;
  #pragma unroll 1
  for (int r = 16 * warp; r < 16 * warp + 16; r++) {
    const uint32_t ad = (lane >> 4) * 16384 + r * 128 + ((((lane & 15) >> 1) ^ (r & 7)) << 4) + (lane & 1) * 8;
    uint2 qv; asm volatile("ld.shared.v2.u32 {%0, %1}, [%2];" : "=r"(qv.x), "=r"(qv.y) : "r"(sq + ad) : "memory");
    const float q0 = bflo(qv.x), q1 = bfhi(qv.x), q2 = bflo(qv.y), q3 = bfhi(qv.y);
    float m = -INFINITY, l = 0.f, o0 = 0.f, o1 = 0.f, o2 = 0.f, o3 = 0.f;
    #pragma unroll 1
    for (int key = 0; key < T_SEQ; key++) {
      const uint2 kv = *reinterpret_cast<const uint2*>(kh + (size_t)key * T_DH + lane * 4);
      const uint2 vv = *reinterpret_cast<const uint2*>(vh + (size_t)key * T_DH + lane * 4);
      float sc = (q0 * bflo(kv.x) + q1 * bfhi(kv.x)) + (q2 * bflo(kv.y) + q3 * bfhi(kv.y));
      #pragma unroll
      for (int o = 16; o > 0; o >>= 1) sc += __shfl_xor_sync(0xffffffffu, sc, o);
      const float mn = fmaxf(m, sc);
      const float al = (m == mn) ? 1.0f : ex2_approx(m - mn), p = rbf(ex2_approx(sc - mn));
      m = mn;
      l = fmaf(l, al, p);
      o0 = fmaf(o0, al, p * bflo(vv.x)); o1 = fmaf(o1, al, p * bfhi(vv.x));
      o2 = fmaf(o2, al, p * bflo(vv.y)); o3 = fmaf(o3, al, p * bfhi(vv.y));
    }
    const float inv = rcp_approx(l);
    asm volatile("st.shared.v2.u32 [%0], {%1, %2};" :: "r"(so + ad), "r"(pack_bf16(o0 * inv, o1 * inv)), "r"(pack_bf16(o2 * inv, o3 * inv)) : "memory");
  }
}
__device__ __forceinline__ void issue_qk(float (&s)[64], const uint32_t (&q)[32], uint32_t k_lo) {
  wgmma_fence();
  wgmma_m64n128k16_rs<0>(s, q[0], q[1], q[2], q[3], k_lo, 0);
  wgmma_m64n128k16_rs<2>(s, q[4], q[5], q[6], q[7], k_lo, 1);
  wgmma_m64n128k16_rs<4>(s, q[8], q[9], q[10], q[11], k_lo, 1);
  wgmma_m64n128k16_rs<6>(s, q[12], q[13], q[14], q[15], k_lo, 1);
  wgmma_m64n128k16_rs<1024>(s, q[16], q[17], q[18], q[19], k_lo, 1);
  wgmma_m64n128k16_rs<1026>(s, q[20], q[21], q[22], q[23], k_lo, 1);
  wgmma_m64n128k16_rs<1028>(s, q[24], q[25], q[26], q[27], k_lo, 1);
  wgmma_m64n128k16_rs<1030>(s, q[28], q[29], q[30], q[31], k_lo, 1);
  wgmma_commit();
}
__device__ __forceinline__ void issue_pv(float (&o)[64], const uint32_t (&p)[32], uint32_t v_lo, int accumulate) {
  wgmma_fence();
  wgmma_m64n128k16_rs_tb<0>(o, p[0], p[1], p[2], p[3], v_lo, accumulate);
  wgmma_m64n128k16_rs_tb<128>(o, p[4], p[5], p[6], p[7], v_lo, 1);
  wgmma_m64n128k16_rs_tb<256>(o, p[8], p[9], p[10], p[11], v_lo, 1);
  wgmma_m64n128k16_rs_tb<384>(o, p[12], p[13], p[14], p[15], v_lo, 1);
  wgmma_m64n128k16_rs_tb<512>(o, p[16], p[17], p[18], p[19], v_lo, 1);
  wgmma_m64n128k16_rs_tb<640>(o, p[20], p[21], p[22], p[23], v_lo, 1);
  wgmma_m64n128k16_rs_tb<768>(o, p[24], p[25], p[26], p[27], v_lo, 1);
  wgmma_m64n128k16_rs_tb<896>(o, p[28], p[29], p[30], p[31], v_lo, 1);
  wgmma_commit();
}
__device__ __forceinline__ void block_end(uint32_t zero, uint32_t bar) {
  #pragma unroll 1
  for (uint32_t i = 0; i < zero; i++) mbar_arrive(bar);
}
__device__ __forceinline__ void rescale_o(float (&o)[64], float al0, float al1) {
  #pragma unroll
  for (int j = 0; j < 16; j++) { o[4 * j] *= al0; o[4 * j + 1] *= al0; o[4 * j + 2] *= al1; o[4 * j + 3] *= al1; }
}

__device__ __forceinline__ void stage_o(const float (&o)[64], float i0, float i1, uint32_t dst, int lane) {
  #pragma unroll
  for (int J = 0; J < 16; J += 2)
    stmatrix_x4(dst + (J >> 3) * 16384 + ((((J & 7) + (lane >> 4)) ^ (lane & 7)) << 4),
                pack_bf16(o[4 * J + 0] * i0, o[4 * J + 1] * i0), pack_bf16(o[4 * J + 2] * i1, o[4 * J + 3] * i1),
                pack_bf16(o[4 * J + 4] * i0, o[4 * J + 5] * i0), pack_bf16(o[4 * J + 6] * i1, o[4 * J + 7] * i1));
}
__device__ __forceinline__ bool finish_l(float& l0, float& l1) {
  l0 += __shfl_xor_sync(0xffffffffu, l0, 1); l1 += __shfl_xor_sync(0xffffffffu, l1, 1);
  l0 += __shfl_xor_sync(0xffffffffu, l0, 2); l1 += __shfl_xor_sync(0xffffffffu, l1, 2);
  const bool redo = __any_sync(0xffffffffu, !(l0 <= AT_RAW_SUM && l1 <= AT_RAW_SUM && l0 >= AT_RAW_MIN && l1 >= AT_RAW_MIN));
  l0 = rcp_approx(l0); l1 = rcp_approx(l1);
  return redo;
}
template <int J0>
__device__ __forceinline__ void stage_q(const float (&acc)[128], float c, uint32_t dst, int lane) {
  #pragma unroll
  for (int J = J0; J < J0 + 16; J += 2)
    stmatrix_x4(dst + (J >> 3) * 16384 + ((((J & 7) + (lane >> 4)) ^ (lane & 7)) << 4),
                pack_bf16(acc[4 * J + 0] * c, acc[4 * J + 1] * c), pack_bf16(acc[4 * J + 2] * c, acc[4 * J + 3] * c),
                pack_bf16(acc[4 * J + 4] * c, acc[4 * J + 5] * c), pack_bf16(acc[4 * J + 6] * c, acc[4 * J + 7] * c));
}
__device__ __forceinline__ void store_o(const CUtensorMap* tmO, uint32_t src, int head, int row) {
  tma_store_2d(tmO, src, head * T_DH, row);
  tma_store_2d(tmO, src + 16384, head * T_DH + 64, row);
  bulk_commit();
}
__device__ __forceinline__ void mma_bf16(float (&d)[4], uint32_t a0, uint32_t a1, uint32_t a2, uint32_t a3, uint32_t b0, uint32_t b1) {
  asm volatile("mma.sync.aligned.m16n8k16.row.col.f32.bf16.bf16.f32 {%0, %1, %2, %3}, {%4, %5, %6, %7}, {%8, %9}, {%0, %1, %2, %3};"
               : "+f"(d[0]), "+f"(d[1]), "+f"(d[2]), "+f"(d[3]) : "r"(a0), "r"(a1), "r"(a2), "r"(a3), "r"(b0), "r"(b1));
}
struct GemvSel { uint32_t lo0, hi0, lo1, hi1; };
__device__ __forceinline__ GemvSel gemv_sel(int lane) {
  const uint32_t lo = (lane & 8) ? 0x1044u : 0x4410u, hi = (lane & 8) ? 0x3244u : 0x4432u;
  GemvSel s; s.lo0 = (lane & 16) ? 0x4444u : lo; s.hi0 = (lane & 16) ? 0x4444u : hi; s.lo1 = (lane & 16) ? lo : 0x4444u; s.hi1 = (lane & 16) ? hi : 0x4444u;
  return s;
}
#define GEMV_B0(j, h, s) __byte_perm((j) < 2 ? (h).x : (h).y, 0u, ((j) & 1) ? (s).hi0 : (s).lo0)
#define GEMV_B1(j, h, s) __byte_perm((j) < 2 ? (h).x : (h).y, 0u, ((j) & 1) ? (s).hi1 : (s).lo1)
__device__ __forceinline__ float4 gemv_out(const float (&d)[4], int lane) {
  const bool tk = lane & 1;
  const float r0 = __shfl_xor_sync(0xffffffffu, tk ? d[0] : d[1], 1), r1 = __shfl_xor_sync(0xffffffffu, tk ? d[2] : d[3], 1);
  return tk ? make_float4(r0, d[1], r1, d[3]) : make_float4(d[0], r0, d[2], r1);
}
#define OG_NG 8
#define PUT_N 2
#define H_STAG 2
#define AL_P 60
#define AL_SLEEP 1200
#define AL_MAX 800
#define POLL_NS 500
#define OG_PROF 0xDCCBAA98u
#define RK_P 24
__host__ __device__ constexpr int og_pre(int tile) { return (OG_PROF >> ((tile >> 4) * 4)) & 15; }
constexpr int OG_PRE2 = og_pre(127), OG_HSUM = og_pre(0) + og_pre(16) + og_pre(32) + og_pre(48) + og_pre(64) + og_pre(80) + og_pre(96);
#define OG_JOBS 7
#define OG_GRP 6
#define LD_FIRST 2
#define LD_STAG (OG_GRP / 2)
constexpr int OG_ST = 5, OG_NKB = T_DQKV / 64 - og_pre(0), OG_MOE = T_F / 32;
__device__ __forceinline__ int pre_kb(int i) { return (i >> 1) * 4 + (i & 1); }
__device__ __forceinline__ int own_kb(int i, int pre) { return i < (pre & ~1) ? pre_kb(i) + 2 : i + pre; }
constexpr int OG_POS = 8;
constexpr uint32_t OG_STAGE = 32768;
constexpr uint32_t OG_SCOL = AT_SBAR + 512;
constexpr uint32_t OG_SMISC = AT_SBAR + 2048;
constexpr uint32_t OG_SWD = AT_SQ, OG_PSLOT = AT_SQ;
constexpr uint32_t OG_XSLOT = AT_SQ + 32768;
constexpr uint32_t OG_OSLOT = 1 * OG_STAGE;
constexpr uint32_t OG_SRED = 3 * OG_STAGE;
constexpr uint32_t OG_SH2 = OG_SRED + 24576;
constexpr uint32_t OG_SSTAT = OG_SRED + 16384;
constexpr uint32_t OG_SGU = OG_SRED + 8192;
constexpr uint32_t OG_SFIN = OG_SGU + 256;
#define OGM 2
#define OG_MT(b) ((((b) >> OGM) & 15) ^ (((b) & 64) ? 15 : 0))
#define OG_NT(b) (((b) & ((1 << OGM) - 1)) + (((b) >> (4 + OGM)) << OGM))
__device__ __forceinline__ int tail_tile(uint32_t sbase) { mbar_wait_long(sbase + AT_SBAR + 336, 0); return (int)lds_u32(sbase + AT_SBAR + 408); }
#define TAIL_SETUP \
  const uint32_t bar_full = sbase + AT_SBAR, bar_empty = bar_full + 40; \
  const uint32_t bar_wd = bar_full + 168, bar_col = bar_full + 176, bar_out = bar_full + 184, bar_end = bar_full + 192; \
  const uint32_t bar_key = bar_full + 200, bar_h2 = bar_full + 208, bar_sel = bar_full + 216; \
  const int mt = OG_MT(tb), nt = OG_NT(tb); \
  const int m0 = mt * 128, n0 = nt * 128; \
  const bool has_moe = (int)bid < OG_MOE; \
  (void)bar_empty; (void)bar_wd; (void)bar_col; (void)bar_out; (void)bar_end; (void)bar_key; (void)bar_h2; (void)bar_sel; (void)m0; (void)n0; (void)has_moe;

__device__ __forceinline__ void tail_producer(uint32_t bid, uint32_t sbase, uint32_t ph, uint64_t pol, const CUtensorMap* tmA, const CUtensorMap* tmB, const CUtensorMap* tmD) {
  const int tb = tail_tile(sbase);
  TAIL_SETUP
  uint32_t stage = OG_POS % OG_ST;
  int kb = 0;
  #pragma unroll 1
  for (int seg = 0; seg < 2; seg++) {
    mbar_wait(bar_full + 264 + 80 * seg, 0);
    fence_proxy_async_global();
    const int end = 32 + 32 * seg - og_pre(tb);
    #pragma unroll 1
    for (; kb < end; kb++) {
      const uint32_t fb = bar_full + 8 * stage, sa = sbase + stage * OG_STAGE;
      const int k0 = own_kb(kb, og_pre(tb)) * 64;
      mbar_wait(bar_empty + 8 * stage, ph);
      mbar_expect_tx(fb, OG_STAGE);
      tma_load_3d_hint(sa + 16384, tmB, k0, 2 * nt, fb, pol);
      tma_load_2d_hint(sa, tmA, k0, m0, fb, pol);
      if (++stage == OG_ST) { stage = 0; ph ^= 1; }
    }
  }
  if (has_moe) {
    stage += stage & 1;
    mbar_wait(bar_empty + 8 * stage, ph);
    mbar_expect_tx(bar_wd, OG_STAGE);
    tma_load_3d_hint(sbase + stage * OG_STAGE, tmD, bid * 32, 8, bar_wd, pol);
  }
}

__device__ __forceinline__ uint32_t out2(uint32_t x1, uint32_t mb2, uint32_t ih, uint32_t il, uint32_t c1, uint32_t sb, uint32_t gb) {
  const uint32_t h2 = badd2(bmul2(ln_norm2b(x1, mb2, ih, il), c1), sb);
  return badd2(x1, bmul2(gb, bfma2(h2, 0u, h2)));
}
#define X_PACE 200
#define Y_SLACK 96
#define OG_STAG 3
#define X_PACE2 100
#define WD_PACE 300
__device__ __forceinline__ void tail_exchange(uint32_t bid, uint32_t sbase, const bf16* __restrict__ w_down, const bf16* __restrict__ w_r, const bf16* __restrict__ x, bf16* __restrict__ out) {
    const int lane = threadIdx.x & 31, wi = __shfl_sync(0xffffffffu, threadIdx.x >> 5, 0);
    if (wi == 3) {
      uint32_t a = bid, b = 0u;
      if (bid < AT_NFULL) mbar_wait_long(sbase + AT_SBAR + 312, 0);
      if (bid < OG_MOE) {
        asm volatile("mov.u32 %0, %%globaltimer_lo;" : "=r"(a));
        if (lane == 0 && (bid & 15) == 0) asm volatile("st.relaxed.gpu.global.u32 [%0], %1;" :: "l"(g_hcnt + 8 + (bid >> 4)), "r"((a & ~15u) | 8u | (bid >> 4)) : "memory");
        #pragma unroll 1
        for (unsigned int spin = 0; spin < (1u << 22) && __any_sync(0xffffffffu, b == 0u); spin++) {
          __nanosleep(200);
          asm volatile("ld.relaxed.gpu.global.u32 %0, [%1];" : "=r"(b) : "l"(g_hcnt + 8 + min(lane, 6)) : "memory");
        }
        a = __popc(__ballot_sync(0xffffffffu, b < __shfl_sync(0xffffffffu, b, bid >> 4)) & 127u) * 16 + (bid & 15);
      }
      if (lane == 0) {
        sts_u32(sbase + AT_SBAR + 408, a);
        mbar_arrive(sbase + AT_SBAR + 336);
        b = 0u;
        if (bid < AT_NFULL) {
          unsigned int* tm = g_hcnt + 32 * (1 + (bid >> 4)) + 8;
          mbar_wait_long(sbase + AT_SBAR + 312, 1);
          asm volatile("mov.u32 %0, %%globaltimer_lo;" : "=r"(a));
          asm volatile("red.relaxed.gpu.global.max.u32 [%0], %1;" :: "l"(tm), "r"(a) : "memory");
          __nanosleep(AL_SLEEP);
          asm volatile("ld.relaxed.gpu.global.u32 %0, [%1];" : "=r"(b) : "l"(tm) : "memory");
          b -= a;
        }
        sts_u32(sbase + AT_SBAR + 412, b < AL_MAX ? b * 13 / 8 : 0u);
        mbar_arrive(sbase + AT_SBAR + 320);
      }
      named_bar_sync(15, 32);
    }
    const int tb = __shfl_sync(0xffffffffu, tail_tile(sbase), 0);
    TAIL_SETUP
    if (wi == 3) {
      mbar_wait_long(bar_full + 344, 0);
      float a = g_scal[lane], b = g_scal[32 + lane];
      #pragma unroll
      for (int i = 0; i < 3; i++) {
        const uint4 v = *reinterpret_cast<const uint4*>(g_col + nt * 1536 + i * 512 + lane * 16);
        sts_u32x4(sbase + OG_SCOL + i * 512 + lane * 16, v.x, v.y, v.z, v.w);
      }
      #pragma unroll
      for (int o = 16; o > 0; o >>= 1) { a += __shfl_xor_sync(0xffffffffu, a, o); b += __shfl_xor_sync(0xffffffffu, b, o); }
      if (lane == 0) sts_f32x2(sbase + OG_SMISC, a, b);
      const uint64_t pol = policy_evict_first();
      #pragma unroll 1
      for (int r = lane >> 4; r < 128; r += 4) {
        __nanosleep(X_PACE);
        if (X_PACE2) __nanosleep(X_PACE2);
        #pragma unroll
        for (int j = 0; j < 4; j += 2)
          asm volatile("cp.async.cg.shared.global.L2::cache_hint [%0], [%1], 16, %2;" :: "r"(sbase + OG_XSLOT + (lane & 8) * 2048 + (r + j) * 128 + (((lane ^ (r + j)) & 7) << 4)),
                       "l"(x + (size_t)(m0 + r + j) * T_D + n0 + (lane & 15) * 8), "l"(pol) : "memory");
      }
      asm volatile("cp.async.wait_all;" ::: "memory");
      __syncwarp();
      if (lane == 0) mbar_arrive(bar_col);
    } else if (wi == 2) {
      if (elect_one()) {
        const uint32_t b_free = bar_full + (bid < AT_NFULL ? 80 : 160);
        mbar_wait_long(b_free, 1);
        #pragma unroll 1
        for (unsigned int i = 0; i < (1u << 20) && ld_acquire(&g_hcnt[32 * (1 + (tb >> 3)) + 4 + ((tb >> 1) & 3)]) == 0u; i++) __nanosleep(POLL_NS);
        TL_MARK2(23, true);
        fence_proxy_async_global();
        TL_MARK2(4, true);
        mbar_expect_tx(bar_full + 272, 32768);
        bulk_load_hint(sbase + OG_PSLOT, g_pre + tb * 2048, 32768, bar_full + 272, policy_evict_first());
      }
      named_bar_sync(14, 32);
      if (has_moe) {
        mbar_wait_long(bar_full + 96, 1); mbar_wait(bar_full + 304, 0);
        const uint64_t pol = policy_evict_first();
        #pragma unroll 1
        for (int r = 0; r < 32; r++) {
          __nanosleep(WD_PACE);
          #pragma unroll
          for (int j = 0; j < 2; j++)
            asm volatile("cp.async.cg.shared.global.L2::cache_hint [%0], [%1], 16, %2;" :: "r"(sbase + OG_SWD + (4 * j + (lane >> 3)) * 4096 + r * 128 + (((lane ^ r) & 7) << 4)),
                         "l"((const uint8_t*)w_down + (size_t)bid * 65536 + r * 2048 + j * 512 + lane * 16), "l"(pol) : "memory");
        }
        asm volatile("cp.async.wait_all;" ::: "memory");
        __syncwarp();
        if (lane == 0) mbar_arrive(bar_wd);
      }
    }
    const uint4 wrv = ldg_nc_v4(w_r + threadIdx.x * 8);
    mbar_wait_long(bar_end, 0);
    TL_MARK2(22, lane == 0);
    if (wi == 0) {
      uint32_t k1 = 0u, k2 = 0u;
      #pragma unroll 1
      for (unsigned int spin = 0; spin < (1u << 22) && __any_sync(0xffffffffu, k1 == 0u); spin++) asm volatile("ld.relaxed.gpu.global.u32 %0, [%1];" : "=r"(k1) : "l"(g_key + lane) : "memory");
      TL_MARK2(28, lane == 0);
      warp_top2(k1, k2);
      if (lane == 0) {
        const uint32_t r1 = 0xffffu - (k1 & 0xffffu), r2 = 0xffffu - (k2 & 0xffffu);
        sts_u32x4(sbase + OG_SMISC + 64, r1, r2, (r1 >> 7) * 2, (r2 >> 7) * 2 + ((r1 >> 7) == (r2 >> 7)));
        mbar_arrive(bar_sel);
      }
    } else if (wi < 3) {
          mbar_wait(bar_key, 0);
          const uint4 kk = lds_u32x4(sbase + OG_SSTAT + 1024 + lane * 16);
          uint32_t k1 = max(kk.x, kk.y), k2 = min(kk.x, kk.y);
          k2 = max(max(k2, min(kk.z, kk.w)), min(k1, max(kk.z, kk.w))); k1 = max(k1, max(kk.z, kk.w));
          warp_top2(k1, k2);
          if (wi == 1) {
            if (lane == 0) {
              if (nt == (mt & 7)) st_relaxed2(g_key + mt * 2, k1, k2);
              sts_u32x2(sbase + OG_SMISC + 96, (~k1 >> 4) & 7u, (~k2 >> 4) & 7u);
              mbar_arrive(bar_full + 352);
            }
            TL_MARK2(27, lane == 0);
          } else {
            const uint32_t r = (~((lane & 16) ? k2 : k1)) & 127u, ch = lane & 15;
            const uint2 st = lds_u32x2(sbase + OG_SSTAT + r * 8);
            const uint4 xc = lds_u32x4(sbase + OG_XSLOT + (ch >> 3) * 16384 + r * 128 + (((ch ^ r) & 7) << 4));
            const uint4 c1 = lds_u32x4(sbase + OG_SCOL + 768 + ch * 16), sh = lds_u32x4(sbase + OG_SCOL + 1024 + ch * 16);
            const float inr = __uint_as_float(st.y);
            float* dst = reinterpret_cast<float*>(g_cand + (mt * 2 + (lane >> 4)) * 256 + nt * 16 + ch);
            st_tagged4(dst + 512, __uint_as_float(ln_mod2(xc.x, st.x, inr, c1.x, sh.x)), __uint_as_float(ln_mod2(xc.y, st.x, inr, c1.y, sh.y)),
                       __uint_as_float(ln_mod2(xc.z, st.x, inr, c1.z, sh.z)), __uint_as_float(ln_mod2(xc.w, st.x, inr, c1.w, sh.w)));
            st_tagged4(dst, __uint_as_float(xc.x), __uint_as_float(xc.y), __uint_as_float(xc.z), __uint_as_float(xc.w));
          }
    }
    mbar_wait(bar_sel, 0);
    const uint4 sel = lds_u32x4(sbase + OG_SMISC + 64);
    const int sel0 = (int)sel.x, sel1 = (int)sel.y;
    {
      const float* src0 = reinterpret_cast<const float*>(g_cand + sel.z * 256 + 128 + threadIdx.x);
      const float* src1 = reinterpret_cast<const float*>(g_cand + sel.w * 256 + 128 + threadIdx.x);
      float4 h0, h1;
      #pragma unroll 1
      for (unsigned int spin = 0; spin < (1u << 20); spin++) { h0 = ld_tagged4(src0); h1 = ld_tagged4(src1); if (__all_sync(0xffffffffu, tagged4(h0) & tagged4(h1))) break; }
      sts_f32x4(sbase + OG_SH2 + threadIdx.x * 16, h0.x, h0.y, h0.z, h0.w);
      sts_f32x4(sbase + OG_SH2 + 2048 + threadIdx.x * 16, h1.x, h1.y, h1.z, h1.w);
      __syncwarp();
      if (lane == 0) mbar_arrive(bar_h2);
      TL_MARK2(12, lane == 0);
      if (bid >> 6) h0 = h1;
      float v[8], wr[8];
      unpack8(make_uint4(__float_as_uint(h0.x), __float_as_uint(h0.y), __float_as_uint(h0.z), __float_as_uint(h0.w)), v); unpack8(wrv, wr);
      float r = 0.f;
      #pragma unroll
      for (int i = 0; i < 8; i++) r = fmaf(v[i], wr[i], r);
      #pragma unroll
      for (int o = 16; o > 0; o >>= 1) r += __shfl_xor_sync(0xffffffffu, r, o);
      if (lane == 0) sts_f32(sbase + OG_SMISC + 192 + wi * 4, r);
    }
    mbar_wait(bar_out, 0);
    {
      const uint2 cg = lds_u32x2(sbase + OG_SMISC + 96);
      #pragma unroll
      for (int i = 0; i < 4; i++) {
        const int r = (i < 2 ? cg.x : cg.y) * 16 + (i & 1) * 8 + (threadIdx.x >> 4), ch = threadIdx.x & 15;
        if (m0 + r != sel0 && m0 + r != sel1)
          *reinterpret_cast<uint4*>(out + (size_t)(m0 + r) * T_D + n0 + ch * 8) =
              lds_u32x4(sbase + OG_OSLOT + (ch >> 3) * 16384 + r * 128 + (((ch & 7) ^ (r & 7)) << 4));
      }
    }
    if (bid == 0 && threadIdx.x < 68) *reinterpret_cast<uint4*>(g_hcnt + 32 * (threadIdx.x >> 2) + 4 * (threadIdx.x & 3)) = make_uint4(0u, 0u, 0u, 0u);
    if (threadIdx.x < 64) g_modpart[bid * 64 + threadIdx.x] = 0.f;
    {
      const int tk = bid >> 6, c0 = (bid & 63) * 16;
      const uint32_t gb2 = *reinterpret_cast<const uint32_t*>(g_col + (c0 >> 7) * 1536 + 512 + 768 + ((c0 & 127) + (threadIdx.x & 14)) * 2);
      const uint32_t* xp = reinterpret_cast<const uint32_t*>(g_cand + (tk ? sel.w : sel.z) * 256) + ((c0 + (threadIdx.x & 14)) >> 1);
      uint32_t x2 = 0u;
      #pragma unroll 1
      for (unsigned int spin = 0; spin < (1u << 20) && __any_sync(0xffffffffu, x2 == 0u); spin++) asm volatile("ld.relaxed.gpu.global.u32 %0, [%1];" : "=r"(x2) : "l"(xp) : "memory");
      const float* src = g_ypart + (size_t)((threadIdx.x >> 2) * 2 + tk) * T_D + c0 + (threadIdx.x & 3) * 4;
      const bool four = threadIdx.x < (OG_MOE - 96) * 4;
      named_bar_sync(10, 128);
      const uint4 rp = lds_u32x4(sbase + OG_SMISC + 192);
      const float rs = rbf(sigmoid_f(rbf((__uint_as_float(rp.x) + __uint_as_float(rp.y)) + (__uint_as_float(rp.z) + __uint_as_float(rp.w)))));
      const uint32_t h2p = lds_u32(sbase + OG_SH2 + tk * 2048 + (c0 + (threadIdx.x & 14)) * 2);
      const float fh = (lane & 1) ? bfhi(h2p) : bflo(h2p), fz = rbf(fh * 0.0f), fx = (lane & 1) ? bfhi(x2) : bflo(x2), fg = (lane & 1) ? bfhi(gb2) : bflo(gb2);
      bf16* dst = out + (size_t)(tk ? sel1 : sel0) * T_D + c0 + threadIdx.x;
      if (threadIdx.x == 0) hint_wait(CNT_Y, (uint32_t)(OG_MOE - Y_SLACK));
      named_bar_sync(10, 128);
      float4 p0, p1, p2, p3;
      #pragma unroll 1
      for (unsigned int spin = 0; spin < (1u << 20); spin++) {
        p0 = ld_tagged4(src); p1 = ld_tagged4(src + 64 * T_D); p2 = ld_tagged4(src + 128 * T_D); p3 = ld_tagged4(four ? src + 192 * T_D : src);
        if (__all_sync(0xffffffffu, tagged4(p0) & tagged4(p1) & tagged4(p2) & tagged4(p3))) break;
      }
      if (four) { p2.x += p3.x; p2.y += p3.y; p2.z += p3.z; p2.w += p3.w; }
      p0.x = (p0.x + p1.x) + p2.x; p0.y = (p0.y + p1.y) + p2.y; p0.z = (p0.z + p1.z) + p2.z; p0.w = (p0.w + p1.w) + p2.w;
      #pragma unroll
      for (int o = 4; o <= 16; o <<= 1) {
        p0.x += __shfl_xor_sync(0xffffffffu, p0.x, o); p0.y += __shfl_xor_sync(0xffffffffu, p0.y, o);
        p0.z += __shfl_xor_sync(0xffffffffu, p0.z, o); p0.w += __shfl_xor_sync(0xffffffffu, p0.w, o);
      }
      if (lane < 4) sts_f32x4(sbase + OG_SFIN + (threadIdx.x >> 5) * 64 + lane * 16, p0.x, p0.y, p0.z, p0.w);
      named_bar_sync(10, 128);
      TL_MARK2(21, threadIdx.x == 0);
      if (threadIdx.x < 16) {
        const uint32_t ya = sbase + OG_SFIN + threadIdx.x * 4;
        float y = (lds_f32(ya) + lds_f32(ya + 64)) + (lds_f32(ya + 128) + lds_f32(ya + 192));
        y = rbf(y);
        y = rbf(y * rs);
        *dst = __float2bfloat16_rn(fx + rbf(fg * rbf(fh + rbf(fz + y))));
      }
    }
    if (threadIdx.x == 0) XT(11);
    TL_END(4, threadIdx.x == 0);
}

__device__ __forceinline__ void load_pre(uint4* pre, uint32_t sbase, uint32_t buf, int t2) {
  mbar_wait(sbase + AT_SBAR + 272, 0);
  #pragma unroll
  for (int i = 0; i < 8; i++) pre[i] = lds_u32x4(sbase + buf + i * 4096 + t2 * 16);
}
__device__ __forceinline__ void tail_consumer(uint32_t bid, uint32_t sbase, const CUtensorMap* tmOut, const uint4 (&pre)[8], int cwg, const bf16* __restrict__ w_gate, const bf16* __restrict__ w_up) {
    const uint32_t c0 = clock_lo();
    mbar_wait(sbase + AT_SBAR + 320, 0);
    const uint2 td = lds_u32x2(sbase + AT_SBAR + 408);
    const int tb = __shfl_sync(0xffffffffu, (int)td.x, 0);
    TAIL_SETUP
    const int tid = threadIdx.x & 127, t2 = threadIdx.x - 128;
    const int warp = tid >> 5, lane = tid & 31, w8 = t2 >> 5;
    const uint32_t dbase = (sbase & 0x3FFFFu) >> 4;
    const uint32_t a_base = dbase + ((cwg * 8192) >> 4) + (1u << 16);
    const uint32_t b_base = dbase + (16384 >> 4) + (512u << 16);
    TL_MARK2(25, threadIdx.x == 128);
    const uint64_t pol = policy_evict_first();
    const bf16* pw = ((lane & 16) ? w_up : w_gate) + (size_t)(w8 * 128 + (lane & 3) * 4) * T_F + (has_moe ? bid : 0) * 32 + ((lane >> 2) & 3) * 8;
    uint4 wv[32];
    float acc[64];
    #pragma unroll
    for (int i = 0; i < 8; i++) {
      acc[8 * i] = bflo(pre[i].x); acc[8 * i + 1] = bfhi(pre[i].x); acc[8 * i + 2] = bflo(pre[i].y); acc[8 * i + 3] = bfhi(pre[i].y);
      acc[8 * i + 4] = bflo(pre[i].z); acc[8 * i + 5] = bfhi(pre[i].z); acc[8 * i + 6] = bflo(pre[i].w); acc[8 * i + 7] = bfhi(pre[i].w);
    }
    if (lane == 0) mbar_arrive(bar_full + 304);
    while (__any_sync(0xffffffffu, clock_lo() - c0 < td.y)) {}
    uint32_t stage = OG_POS % OG_ST;
    {
      uint32_t phase = (OG_POS / OG_ST) & 1, prev = 12;
      int kb = 0;
      #pragma unroll
      for (int g = 0; g <= OG_NG; g++) {
        const int end = g == OG_NG ? 64 - og_pre(tb) : LD_FIRST + g * OG_GRP + LD_STAG * cwg;
        #pragma unroll 1
        do {
          mbar_wait(bar_full + 8 * stage, phase);
          if (OG_STAG > 0 && g == OG_NG && cwg == 1 && kb == end - OG_STAG) named_bar_sync(7, 256);
          const uint32_t a_lo = a_base + stage * (OG_STAGE >> 4), b_lo = b_base + stage * (OG_STAGE >> 4);
          wgmma_fence();
          wgmma_m64n128k16_ss_tb<0, 0>(acc, a_lo, b_lo, 1);
          wgmma_m64n128k16_ss_tb<2, 128>(acc, a_lo, b_lo, 1);
          wgmma_m64n128k16_ss_tb<4, 256>(acc, a_lo, b_lo, 1);
          wgmma_m64n128k16_ss_tb<6, 384>(acc, a_lo, b_lo, 1);
          wgmma_commit();
          if (OG_STAG > 0 && g == OG_NG && cwg == 0 && kb == end - 1) named_bar_arrive(7, 256);
          wgmma_wait<1>();
          if (tid == 0) mbar_arrive(bar_empty + 8 * prev);
          prev = stage;
          if (++stage == OG_ST) { stage = 0; phase ^= 1; }
        } while (++kb < end);
        #pragma unroll
        for (int j = 4 * g; j < 4 * g + 4 && j < 32; j++) wv[j] = ldg_stream_v4(pw + (size_t)(16 * (j >> 2) + (j & 3)) * T_F, pol);
      }
    }
    mbar_wait(bar_col, 0);
    if (__builtin_expect(!has_moe, 0)) {
      load_pre(wv, sbase, AT_SQ, t2);
    }
    wgmma_wait<0>();
    fence_regs(acc);
    if (__builtin_expect(!has_moe, 0)) {
      #pragma unroll
      for (int i = 0; i < 8; i++) {
        acc[8 * i] += bflo(wv[i].x); acc[8 * i + 1] += bfhi(wv[i].x); acc[8 * i + 2] += bflo(wv[i].y); acc[8 * i + 3] += bfhi(wv[i].y);
        acc[8 * i + 4] += bflo(wv[i].z); acc[8 * i + 5] += bfhi(wv[i].z); acc[8 * i + 6] += bflo(wv[i].w); acc[8 * i + 7] += bfhi(wv[i].w);
      }
    }
    if (tid == 0) mbar_arrive(bar_end);
    TL_MARK2(9, lane == 0);
    const int q2 = 2 * (lane & 3);
    const uint32_t frag = (64 * cwg + 16 * warp + (lane & 7) + 8 * ((lane >> 3) & 1)) * 128;
    const int fsw = lane & 7, fhi = lane >> 4;
    {
      float dl[4] = {0.f, 0.f, 0.f, 0.f}, da[4] = {0.f, 0.f, 0.f, 0.f}, db[4] = {0.f, 0.f, 0.f, 0.f};
      const uint32_t tb2 = sbase + OG_SCOL + (lane & 8) * 32 + (lane & 3) * 8, g = lane >> 2;
      const uint32_t msk = (g == 1 || g == 2) ? 0xffffffffu : 0u, one = g == 0 ? 0x3F803F80u : 0u;
      uint32_t xr[8][4];
      #pragma unroll
      for (int hf = 0; hf < 2; hf++) {
        uint32_t ga[8];
        uint2 cw[4];
        #pragma unroll
        for (int i = 0; i < 4; i++) {
          ldmatrix_x4(sbase + OG_XSLOT + hf * 16384 + frag + (((2 * i + fhi) ^ fsw) << 4), xr[4 * hf + i][0], xr[4 * hf + i][1], xr[4 * hf + i][2], xr[4 * hf + i][3]);
          ga[2 * i] = lds_u32(sbase + OG_SCOL + 512 + (64 * hf + 16 * i + q2) * 2); ga[2 * i + 1] = lds_u32(sbase + OG_SCOL + 512 + (64 * hf + 16 * i + 8 + q2) * 2);
          cw[i] = lds_u32x2(tb2 + (8 * hf + 2 * i) * 16);
        }
        #pragma unroll
        for (int i = 0; i < 4; i++) {
          uint32_t* x4 = xr[4 * hf + i];
          #pragma unroll
          for (int e = 0; e < 4; e++) x4[e] = badd2(x4[e], bmul2(ga[2 * i + (e >> 1)], pack_bf16(acc[32 * hf + 8 * i + 2 * e], acc[32 * hf + 8 * i + 2 * e + 1])));
          mma_bf16(dl, x4[0], x4[1], x4[2], x4[3], (cw[i].x & msk) | one, (cw[i].y & msk) | one);
          mma_bf16(da, x4[0], x4[1], x4[2], x4[3], x4[0], x4[2]);
          mma_bf16(db, x4[0], x4[1], x4[2], x4[3], x4[1], x4[3]);
        }
      }
      {
        const int dsrc = (lane & ~3) + (g >> 1);
        const float qa = __shfl_sync(0xffffffffu, (g & 1) ? da[1] : da[0], dsrc), qb = __shfl_sync(0xffffffffu, (g & 1) ? db[3] : db[2], dsrc);
        const float e0 = __shfl_xor_sync(0xffffffffu, (lane & 1) ? dl[0] : dl[2], 1), e1 = __shfl_xor_sync(0xffffffffu, dl[3], 1);
        if ((lane & 3) < 2) {
          const bool hi = lane & 1;
          st_tagged4(reinterpret_cast<float*>(g_part1 + ((mt * 8 + w8) * 8 + nt) * 16 + g + (hi ? 8 : 0)),
                     hi ? e0 : dl[0], hi ? qb : qa, hi ? e1 + dl[2] : dl[1] + e0, 1.0f);
        }
      }
      #pragma unroll
      for (int i = 0; i < 8; i++) stmatrix_x4(sbase + OG_XSLOT + (i >> 2) * 16384 + frag + (((2 * (i & 3) + fhi) ^ fsw) << 4), xr[i][0], xr[i][1], xr[i][2], xr[i][3]);
    }
    TL_MARK2(10, lane == 0);
    uint4 wd[16];
    if (has_moe) mbar_wait(bar_wd, 0);
    #pragma unroll
    for (int i = 0; i < 16; i++) wd[i] = lds_u32x4(sbase + (cwg ? (stage + (stage & 1)) * OG_STAGE : OG_SWD) + warp * 8192 + (i >> 3) * 4096 + (i & 6) * 512 + (i & 1) * 128 + (lane & 3) * 256 + (((lane >> 2) ^ (2 * (lane & 3) + (i & 1))) << 4));
    {
      const float* src = reinterpret_cast<const float*>(g_part1 + ((mt * 8 + w8) * 8 + (lane & 1) * 4) * 16 + (lane >> 1));
      float4 v, v1, v2, v3;
      #pragma unroll 1
      for (unsigned int spin = 0; spin < (1u << 22); spin++) {
        v = ld_tagged4(src); v1 = ld_tagged4(src + 64); v2 = ld_tagged4(src + 128); v3 = ld_tagged4(src + 192);
        if (__all_sync(0xffffffffu, tagged4(v) & tagged4(v1) & tagged4(v2) & tagged4(v3))) break;
        __nanosleep(100);
      }
      __syncwarp();
      TL_MARK2(26, lane == 0);
      v.x = (v.x + v1.x) + (v2.x + v3.x); v.y = (v.y + v1.y) + (v2.y + v3.y); v.z = (v.z + v1.z) + (v2.z + v3.z);
      v.x += __shfl_xor_sync(0xffffffffu, v.x, 1); v.y += __shfl_xor_sync(0xffffffffu, v.y, 1); v.z += __shfl_xor_sync(0xffffffffu, v.z, 1);
      const float mean = v.x * (1.0f / T_D);
      const float var = fmaxf(fmaf(-mean, mean, v.y * (1.0f / T_D)), 0.f);
      const uint32_t mb2 = pack_bf16(mean, mean);
      const float inv = rcp_approx(rbf(sqrt_approx(rbf(rbf(var) + 1e-05f))));
      {
        const float2 sc = lds_f32x2(sbase + OG_SMISC);
        const uint32_t key = rank_key(rbf(fmaf(fmaf(-bflo(mb2), sc.x, v.z), inv, sc.y)), m0 + 16 * w8 + (lane >> 1));
        mbar_wait(bar_end, 0);
        if (lane & 1) sts_u32(sbase + OG_SSTAT + 1024 + (16 * w8 + (lane >> 1)) * 4, key);
        else sts_u32x2(sbase + OG_SSTAT + (16 * w8 + (lane >> 1)) * 8, mb2, __float_as_uint(inv));
        __syncwarp();
        if (lane == 0) mbar_arrive(bar_key);
      }
      const uint32_t ih = pack_bf16(inv, inv), il = pack_bf16(inv - bflo(ih), inv - bflo(ih));
      const uint32_t mba = __shfl_sync(0xffffffffu, mb2, 2 * (lane >> 2)), mbb = __shfl_sync(0xffffffffu, mb2, 2 * (lane >> 2) + 16);
      const uint32_t iha = __shfl_sync(0xffffffffu, ih, 2 * (lane >> 2)), ihb = __shfl_sync(0xffffffffu, ih, 2 * (lane >> 2) + 16);
      const uint32_t ila = __shfl_sync(0xffffffffu, il, 2 * (lane >> 2)), ilb = __shfl_sync(0xffffffffu, il, 2 * (lane >> 2) + 16);
      #pragma unroll 1
      for (int J0 = 0; J0 < 16; J0 += 4) {
        uint32_t xr[2][4], cv[4][3];
        #pragma unroll
        for (int i = 0; i < 2; i++) {
          ldmatrix_x4(sbase + OG_XSLOT + (J0 >> 3) * 16384 + frag + ((((J0 & 7) + 2 * i + fhi) ^ fsw) << 4), xr[i][0], xr[i][1], xr[i][2], xr[i][3]);
          #pragma unroll
          for (int h = 0; h < 2; h++)
            #pragma unroll
            for (int k = 0; k < 3; k++) cv[2 * i + h][k] = lds_u32(sbase + OG_SCOL + 768 + 256 * k + (8 * (J0 + 2 * i + h) + q2) * 2);
        }
        #pragma unroll
        for (int i = 0; i < 2; i++) {
          #pragma unroll
          for (int h = 0; h < 2; h++) {
            xr[i][2 * h] = out2(xr[i][2 * h], mba, iha, ila, cv[2 * i + h][0], cv[2 * i + h][1], cv[2 * i + h][2]);
            xr[i][2 * h + 1] = out2(xr[i][2 * h + 1], mbb, ihb, ilb, cv[2 * i + h][0], cv[2 * i + h][1], cv[2 * i + h][2]);
          }
          stmatrix_x4(sbase + OG_OSLOT + (J0 >> 3) * 16384 + frag + ((((J0 & 7) + 2 * i + fhi) ^ fsw) << 4), xr[i][0], xr[i][1], xr[i][2], xr[i][3]);
        }
      }
      fence_proxy_async();
      mbar_wait(bar_full + 352, 0);
      const uint2 cg = lds_u32x2(sbase + OG_SMISC + 96);
      __syncwarp();
      if (elect_one()) {
        mbar_arrive(bar_out);
        if (cg.x != w8 && cg.y != w8) {
          asm volatile("cp.async.bulk.tensor.2d.global.shared::cta.bulk_group [%0, {%2, %3}], [%1];" :: "l"(tmOut), "r"(sbase + OG_OSLOT + w8 * 2048), "r"(n0), "r"(m0 + 16 * w8) : "memory");
          asm volatile("cp.async.bulk.tensor.2d.global.shared::cta.bulk_group [%0, {%2, %3}], [%1];" :: "l"(tmOut), "r"(sbase + OG_OSLOT + 16384 + w8 * 2048), "r"(n0 + 64), "r"(m0 + 16 * w8) : "memory");
          bulk_commit();
        }
      }
      TL_MARK2(24, lane == 0);
    }
    if (has_moe) mbar_wait(bar_h2, 0);
    TL_MARK2(13, lane == 0);
    if (has_moe) {
      const GemvSel sel = gemv_sel(lane);
      {
        float d[4][4];
        #pragma unroll
        for (int c = 0; c < 4; c++) { d[c][0] = 0.f; d[c][1] = 0.f; d[c][2] = 0.f; d[c][3] = 0.f; }
        #pragma unroll
        for (int st = 0; st < 8; st++) {
          const uint2 hb = lds_u32x2(sbase + OG_SH2 + ((lane >> 2) & 1) * 2048 + (w8 * 128 + st * 16 + (lane & 3) * 4) * 2);
          #pragma unroll
          for (int j = 0; j < 4; j++) mma_bf16(d[j], wv[4 * st + j].x, wv[4 * st + j].y, wv[4 * st + j].z, wv[4 * st + j].w, GEMV_B0(j, hb, sel), GEMV_B1(j, hb, sel));
        }
        #pragma unroll
        for (int e = 0; e < 4; e++) d[0][e] = (d[0][e] + d[1][e]) + (d[2][e] + d[3][e]);
        const float4 r = gemv_out(d[0], lane);
        sts_f32x4(sbase + OG_SRED + w8 * 512 + (((lane >> 4) * 2 + (lane & 1)) * 32 + ((lane >> 2) & 3) * 8 + (lane & 2) * 2) * 4, r.x, r.y, r.z, r.w);
      }
      named_bar_sync(9, 256);
      if (t2 < 64) {
        float gp[8], up[8];
        #pragma unroll
        for (int w = 0; w < 8; w++) { gp[w] = lds_f32(sbase + OG_SRED + w * 512 + t2 * 4); up[w] = lds_f32(sbase + OG_SRED + w * 512 + 256 + t2 * 4); }
        const float gs = ((gp[0] + gp[1]) + (gp[2] + gp[3])) + ((gp[4] + gp[5]) + (gp[6] + gp[7]));
        const float us = ((up[0] + up[1]) + (up[2] + up[3])) + ((up[4] + up[5]) + (up[6] + up[7]));
        asm volatile("st.shared.u16 [%0], %1;" :: "r"(sbase + OG_SGU + ((t2 & ~15) + ((t2 >> 1) & 3) * 4 + ((t2 >> 3) & 1) * 2 + (t2 & 1)) * 2), "h"((uint16_t)pack_bf16(silu_bf(rbf(gs)) * rbf(us), 0.f)) : "memory");
      }
      named_bar_sync(9, 256);
      TL_MARK2(20, threadIdx.x == 128);
      float d[4][4];
      #pragma unroll
      for (int c = 0; c < 4; c++) { d[c][0] = 0.f; d[c][1] = 0.f; d[c][2] = 0.f; d[c][3] = 0.f; }
      #pragma unroll
      for (int st = 0; st < 2; st++) {
        const uint2 g = lds_u32x2(sbase + OG_SGU + ((lane >> 2) & 1) * 64 + st * 32 + (lane & 3) * 8);
        #pragma unroll
        for (int j = 0; j < 4; j++) {
          const uint32_t b0 = GEMV_B0(j, g, sel), b1 = GEMV_B1(j, g, sel);
          mma_bf16(d[j & 1], wd[4 * st + j].x, wd[4 * st + j].y, wd[4 * st + j].z, wd[4 * st + j].w, b0, b1);
          mma_bf16(d[2 + (j & 1)], wd[8 + 4 * st + j].x, wd[8 + 4 * st + j].y, wd[8 + 4 * st + j].z, wd[8 + 4 * st + j].w, b0, b1);
        }
      }
      #pragma unroll
      for (int e = 0; e < 4; e++) { d[0][e] += d[1][e]; d[2][e] += d[3][e]; }
      const float4 y0 = gemv_out(d[0], lane), y1 = gemv_out(d[2], lane);
      float* yp = g_ypart + (size_t)(bid * 2 + (lane & 1)) * T_D + w8 * 128 + (lane >> 2) * 8 + (lane & 2) * 2;
      st_tagged4(yp, y0.x, y0.y, y0.z, y0.w);
      st_tagged4(yp + 64, y1.x, y1.y, y1.z, y1.w);
      named_bar_sync(9, 256);
      if (t2 == 0) hint_arrive(CNT_Y);
    }
    bulk_wait_read<0>();
    TL_MARK2(14, threadIdx.x == 128);
    TL_CLK(4, 1, threadIdx.x == 128);
}

__device__ __forceinline__ int help_njobs(uint32_t bid) { return bid < 128 ? OG_JOBS : 16 - OG_JOBS; }
__device__ __forceinline__ int help_job(uint32_t bid, int i) { return (i < OG_JOBS ? 16 * i + (bid >> 7) * 2 : 112 + (i - OG_JOBS) * 2) + (bid & 3) * 4; }
__device__ __noinline__ void store_warp(uint32_t bid, uint32_t sbase, const CUtensorMap* tmO, int item0, int n_items) {
  if (elect_one()) {
    const uint32_t bars = sbase + AT_SBAR, b_q0 = bars + 80, b_ob = bars + 96, b_ordy = bars + 104, b_acq = bars + 264;
    const unsigned int* cnt = g_hcnt + 32 * (1 + OG_MT(124)) + 2;
    #pragma unroll 1
    for (int q = 0; q < 4 * n_items; q++) {
      const int item = item0 + (q >> 2) * 128, h = (q >> 1) & 1, w = q & 1;
      const bool last = (q >> 2) == n_items - 1;
      if (q == 4 * n_items - 4) { mbar_wait_long(bars + 288, 0); red_release_add(&g_hcnt[1], 1u); }
      mbar_wait_long(b_ordy + 8 * (q & 3), q >> 2);
      store_o(tmO, (h ? (last ? sbase + AT_SQ + 32768 : sbase + 2 * 32768) : sbase + AT_SQ) + w * 8192, (item >> 4) * 2 + h, (item & 15) * 128 + w * 64);
      if (w) {
        bulk_wait_read<0>();
        mbar_arrive(h ? b_ob : b_q0);
        bulk_wait<0>();
        fence_proxy_async_global();
        asm volatile("fence.acq_rel.gpu;" ::: "memory");
        hint_arrive(&g_hcnt[32 * (1 + (item & 15)) + 2 + (item >> 7)]);
        if (!h && item < 128) hint_arrive(&g_hcnt[2]);
        if (q == 5) { const int tb = tail_tile(sbase); cnt = g_hcnt + 32 * (1 + OG_MT(tb)) + 2; spin_until(cnt, 16u); mbar_arrive(b_acq); }
      }
    }
    if (n_items == 1) {
      #pragma unroll 1
      for (int i = 0; i < help_njobs(bid); i++) {
        mbar_wait_long(b_acq + 16, i & 1);
        TL_MARK2(23, i == OG_JOBS - 1);
        red_release_add(&g_hcnt[32 * (1 + (help_job(bid, i) >> 3)) + 4 + ((help_job(bid, i) >> 1) & 3)], 1u);
        TL_MARK2(4, i == OG_JOBS - 1);
        if (i == PRE_X - 1) { spin_until(&g_hcnt[1], 132u); mbar_arrive(b_acq + 32); }
      }
    }
    if (bid < 128) {
      if (n_items == 1) { spin_until(cnt, 16u); mbar_arrive(b_acq); }
      spin_until(&g_hcnt[0], 128u); spin_until(cnt + 1, 16u); mbar_arrive(b_acq + 80);
    }
  }
}

__device__ __forceinline__ uint32_t role_of_sm(uint32_t sm) {
  const uint32_t t = sm >> 1, u = t - 32u, d = (u * 37u) >> 8;
  return (t < 32u ? ((t + 7u) & 7u) * 16u + (t >> 3) * 2u : t < 60u ? (u - 7u * d) * 16u + (4u + d) * 2u : t < 62u ? 2u * t + 8u : 2u * t - 4u) + (sm & 1u);
}
__global__ void __launch_bounds__(384, 1)
fused_kernel(const __grid_constant__ CUtensorMap tmH, const __grid_constant__ CUtensorMap tmW, const __grid_constant__ CUtensorMap tmK,
            const __grid_constant__ CUtensorMap tmV, const __grid_constant__ CUtensorMap tmO, const __grid_constant__ CUtensorMap tmOl, const __grid_constant__ CUtensorMap tmWo,
            const __grid_constant__ CUtensorMap tmD, const __grid_constant__ CUtensorMap tmOut, const __grid_constant__ CUtensorMap tmM, uint32_t zero,
            const uint8_t* __restrict__ pf_wo, const bf16* __restrict__ kc, const bf16* __restrict__ vc,
            const bf16* __restrict__ x, const bf16* __restrict__ cvec, const bf16* __restrict__ w_mod, const bf16* __restrict__ w_r,
            const bf16* __restrict__ w_gate, const bf16* __restrict__ w_up, const bf16* __restrict__ w_down, bf16* __restrict__ out)
{
  uint32_t bid, nsm;
  asm volatile("mov.u32 %0, %%smid;" : "=r"(bid));
  asm volatile("mov.u32 %0, %%nsmid;" : "=r"(nsm));
  bid = __shfl_sync(0xffffffffu, nsm == 132u ? role_of_sm(bid) : blockIdx.x, 0);
  extern __shared__ __align__(1024) uint8_t smem_raw[];
  const uint32_t sbase = smem_u32(smem_raw);
  const uint32_t bars = sbase + AT_SBAR;
  const uint32_t b_full = bars, b_empty = bars + 40;
  const uint32_t b_q0 = bars + 80, b_q1 = bars + 88;
  const uint32_t b_ob = bars + 96;
  const uint32_t b_ordy = bars + 104;
  const uint32_t b_pin = bars + 136;
  const uint32_t b_head = bars + 144;
  const uint32_t b_go = bars + 152;
  const uint32_t b_x = bars + 160;
  const int wg = __shfl_sync(0xffffffffu, threadIdx.x >> 7, 0);
  const bool single = bid >= AT_NFULL;
  const int item0 = __shfl_sync(0xffffffffu, bid < 128 ? (int)bid : (int)bid + 124, 0), n_items = __shfl_sync(0xffffffffu, single ? 1 : 2, 0);
  TL_START(3);
  if (threadIdx.x == 0) {
    if (sbase & 1023u) __trap();
    for (int i = 0; i < 5; i++) { mbar_init(b_full + 8 * i, 1); mbar_init(b_empty + 8 * i, 2); }
    mbar_init(b_q0, 1); mbar_init(b_q1, 8); mbar_init(b_ob, 1);
    for (int i = 0; i < 4; i++) mbar_init(b_ordy + 8 * i, 4);
    mbar_init(b_pin, 1); mbar_init(b_head, bid < 128 ? 8 : 1); mbar_init(b_go, 1); mbar_init(b_x, 1);
    mbar_init(bars + 168, 2); mbar_init(bars + 176, 1); mbar_init(bars + 184, 8); mbar_init(bars + 192, 2);
    mbar_init(bars + 200, 8); mbar_init(bars + 208, 4); mbar_init(bars + 216, 1); mbar_init(bars + 264, 1); mbar_init(bars + 272, 1); mbar_init(bars + 280, 8); mbar_init(bars + 288, 1); mbar_init(bars + 296, 1); mbar_init(bars + 304, 8); mbar_init(bars + 312, 1); mbar_init(bars + 320, 1); mbar_init(bars + 328, 1); mbar_init(bars + 336, 1); mbar_init(bars + 344, 1); mbar_init(bars + 352, 1);
    sts_u32(bars + 400, bid);
    fence_mbar_init();
  }

  if (wg == 0) {
    reg_dealloc<AT_PREG>();
    if (threadIdx.x < 32) { __syncwarp(); named_bar_arrive(6, 384); }
    if (threadIdx.x >= 64) {
      named_bar_sync(6, 384);
      if (bid < 128) {
        named_bar_sync(threadIdx.x >= 96 ? 8 : 9, 288);
        if ((threadIdx.x & 31) == 0) red_release_add(&g_hcnt[32 * (1 + (bid >> 3)) + (threadIdx.x >= 96)], 1u);
        TL_MARK2(11, threadIdx.x == 64);
      }
      if (bid < 128) {
        mbar_wait(MOD_AT, 0);
        mod_rest(bid, sbase + OG_SCOL, b_q1, threadIdx.x - 64, cvec, w_mod, w_r);
      }
    } else if (threadIdx.x >= 32) {
      named_bar_sync(6, 384);
      store_warp(bid, sbase, &tmO, item0, n_items);
      __syncwarp();
    } else {
     if (elect_one()) {
      const uint64_t pol = policy_evict_first();
      if (bid < 128) {
        mbar_expect_tx(b_x, 32768);
        if (X_DLY) { const uint32_t c0 = clock_lo(); while (clock_lo() - c0 < X_DLY) {} }
        bulk_load_hint(sbase + 4 * 32768, x + (size_t)bid * 16 * T_D, 32768, b_x, pol);
      }
      prefetch_tmap(&tmW); prefetch_tmap(&tmM); prefetch_tmap(&tmH); prefetch_tmap(&tmWo); prefetch_tmap(&tmOl);
      {
        const uint32_t c0 = clock_lo();
        while (clock_lo() - c0 < W_DLY) {}
        if (bid < 128 && (head_cb(bid) & 15) >= 4 * H_SPLIT) {
          mbar_expect_tx(bars + 328, 32768);
          tma_load_2d_hint(sbase + 3 * 32768, &tmM, head_cb(bid) * 64, (bid >> 5) * 256, bars + 328, pol);
        }
        while (clock_lo() - c0 < W_DLY + W_FIRST) {}
      }
      uint32_t slot = 0, ph = 1;
      #pragma unroll 1
      for (int it = 0; it < n_items; it++) {
        const int item = item0 + it * 128, hp = item >> 4, qt = item & 15;
        const bool first = it == 0;
        #pragma unroll 1
        for (int j = 0; j < T_D / 64; j++) {
          const uint32_t sl = ring_slot(qp_pos(j, it)), fb = b_full + 8 * sl;
          mbar_wait_long(b_empty + 8 * sl, ring_par(qp_pos(j, it)) ^ ((j >> 2) & 1) ^ 1);
          if (first && j == 3) mbar_wait(b_head, 0);
          mbar_expect_tx(fb, 49152);
          tma_load_3d_hint(sbase + sl * 32768, &tmW, j * 64, hp * 4, fb, pol);
          if (first && j < PRE_B) {
            if (j == PRE_B - 1) {
              spin_until(&g_hcnt[32 * (1 + qt)], 8u);
              TL_MARK2(16, true);
              fence_proxy_async_global();
              #pragma unroll 1
              for (int i = 0; i < PRE_B; i++) tma_load_2d(sbase + AT_SQ + i * 16384, &tmH, i * 64, qt * 128, b_full + 8 * i);
              mbar_arrive(b_go);
            }
          } else {
            if (first && j == 4 * H_SPLIT) { spin_until(&g_hcnt[32 * (1 + qt) + 1], 8u); fence_proxy_async_global(); }
            if (!first && (j == 0 || j == 2)) mbar_wait(j ? b_q1 : b_q0, 0);
            tma_load_2d(sbase + AT_SQ + (j & 3) * 16384, &tmH, j * 64, qt * 128, fb);
          }
        }
        #pragma unroll 1
        for (int j = 0; j < 4 * AT_NBLK; j++) {
          const bool isv = (j > 0 && !(j & 1)) || j == 4 * AT_NBLK - 1;
          const int row = hp * 2 * T_SEQ + (isv ? (j - 1) >> 1 : (j + 1) >> 1) * 128;
          const uint32_t fb = b_full + 8 * slot;
          mbar_wait_long(b_empty + 8 * slot, ph);
          if (!first && j == 3) mbar_wait(b_ob, 0);
          if (j == 4 && it == n_items - 1) mbar_arrive(bars + 288);
          if ((j == AL_P || j == RK_P) && it == 1) mbar_arrive(bars + 312);
          mbar_expect_tx(fb, 32768);
          tma_load_3d_hint(sbase + slot * 32768, isv ? &tmV : &tmK, row, 0, fb, pol);
          if (it == 1 && isv && j >= 2 * WO_LATE && j < 2 * WO_LATE + 32 && bid < OG_NKB)
            l2_prefetch_bulk(pf_wo + (size_t)own_kb(bid, og_pre(0)) * 131072 + ((j >> 1) - WO_LATE) * 8192, 8192);
          if (++slot == 5) { slot = 0; ph ^= 1; }
        }
      }
      if (__builtin_expect(single, 0)) {
        spin_until(&g_hcnt[2], 128u);
        fence_proxy_async_global();
        const int nj = OG_HSUM + (help_njobs(bid) - OG_JOBS) * OG_PRE2;
        int ji = 0, job = help_job(bid, 0), kk = 0;
        #pragma unroll 1
        for (int j = 0; j < nj; j++) {
          const uint32_t sl = ring_slot(qp_pos(j, 1)), fb = b_full + 8 * sl;
          mbar_wait_long(b_empty + 8 * sl, ring_par(qp_pos(j, 1)) ^ ((j >> 2) & 1) ^ 1);
          mbar_expect_tx(fb, 49152);
          tma_load_3d(sbase + sl * 32768, &tmWo, pre_kb(kk) * 64, OG_NT(job) * 2, fb);
          tma_load_3d(sbase + sl * 32768 + 16384, &tmWo, pre_kb(kk) * 64, OG_NT(job) * 2 + 2, fb);
          if (j == 0 || j == 2) mbar_wait(j ? b_ob : b_q0, 0);
          tma_load_2d_hint(sbase + AT_SQ + (j & 3) * 16384, &tmOl, pre_kb(kk) * 64, OG_MT(job) * 128, fb, pol);
          if (++kk == og_pre(job)) { kk = 0; job = help_job(bid, ++ji); }
        }
      }
      if (bid < 128) {
        if (single) mbar_wait(b_x, 1);
        tail_producer(bid, sbase, 0, pol, &tmOl, &tmWo, &tmD);
      }
     }
    }
    named_bar_sync(12 + (threadIdx.x >> 5), 32);
    if (bid < 128) tail_exchange(bid, sbase, w_down, w_r, x, out);
  } else {
    if (bid < 128) head_phase(bid, sbase + AT_SQ + 49152, sbase + 4 * 32768, b_x, b_go, b_head, threadIdx.x - 128, zero, cvec, w_mod);
    else { named_bar_sync(6, 384); if (threadIdx.x == 128) mbar_arrive(b_head); }
    TL_MARK2(0, threadIdx.x == 128);
    reg_alloc<AT_CREG>();
    const int cwg = wg - 1;
    const int tid = threadIdx.x & 127;
    const int warp = tid >> 5, lane = tid & 31;
    const uint32_t dbase = (sbase & 0x3FFFFu) >> 4;
    const uint32_t k_base = dbase + (1u << 16);
    const uint32_t v_base = dbase + (1024u << 16);
    const uint32_t w_base = dbase + (512u << 16);
    const uint32_t q_lo = dbase + ((AT_SQ + cwg * 8192) >> 4) + (1u << 16);
    const uint32_t frag = cwg * 8192 + (16 * warp + (lane & 7) + 8 * ((lane >> 3) & 1)) * 128;
    if (cwg == 1) named_bar_arrive(1, 256);
    bool raw = false;
    uint4 pre[8];
    #pragma unroll 1
    for (int it = 0; it < n_items; it++) {
      const bool more = it + 1 < n_items;
      constexpr int nkb = T_D / 64;
      const int ta = __shfl_sync(0xffffffffu, 4 * it, 0);
      float acc[128];
      {
        FS(2 * it, 0);
        #pragma unroll
        for (int i = 0; i < 128; i++) asm volatile("" : "=f"(acc[i]));
        {
          const uint32_t slot = ring_slot(ta), b_lo = w_base + slot * 2048;
          mbar_wait(b_full + 8 * slot, ring_par(ta));
          wgmma_fence();
          wgmma_m64n256k16_ss_tb<0, 0>(acc, q_lo, b_lo, 0);
          wgmma_m64n256k16_ss_tb<2, 128>(acc, q_lo, b_lo, 1);
          wgmma_m64n256k16_ss_tb<4, 256>(acc, q_lo, b_lo, 1);
          wgmma_m64n256k16_ss_tb<6, 384>(acc, q_lo, b_lo, 1);
          wgmma_commit();
        }
        #pragma unroll 1
        for (int j = 1; j < nkb; j++) {
          const uint32_t slot = ring_slot(qp_pos(j, ta >> 2));
          mbar_wait(b_full + 8 * slot, ring_par(qp_pos(j, ta >> 2)) ^ ((j >> 2) & 1));
          if (QP_STAG > 0 && cwg == 1 && j == nkb - QP_STAG) named_bar_sync(7, 256);
          const uint32_t a_lo = q_lo + (j & 3) * 1024, b_lo = w_base + slot * 2048;
          wgmma_fence();
          wgmma_m64n256k16_ss_tb<0, 0>(acc, a_lo, b_lo, 1);
          wgmma_m64n256k16_ss_tb<2, 128>(acc, a_lo, b_lo, 1);
          wgmma_m64n256k16_ss_tb<4, 256>(acc, a_lo, b_lo, 1);
          wgmma_m64n256k16_ss_tb<6, 384>(acc, a_lo, b_lo, 1);
          wgmma_commit();
          if (QP_STAG > 0 && cwg == 0 && j == nkb - 1) named_bar_arrive(7, 256);
          if (j > 0) {
            wgmma_wait<1>();
            if (tid == 0) mbar_arrive(b_empty + 8 * ring_slot(qp_pos(j - 1, ta >> 2)));
          }
        }
        wgmma_wait<0>();
        fence_regs(acc);
        FS(2 * it, 1);
        TL_MARK2(29, threadIdx.x == 256 && it == 0);
        if (tid == 0) mbar_arrive(b_empty + 24);
      }
      float o[64], s[64];
      uint32_t p[32], q[32];
      #pragma unroll
      for (int i = 0; i < 32; i++) q[i] = pack_bf16(acc[2 * i] * AT_C, acc[2 * i + 1] * AT_C);
      zero_regs(s);
      const uint32_t sq = sbase + AT_SQ + cwg * 8192;
      float mc0, mc1, al0 = 1.0f, al1 = 1.0f, l0 = 0.f, l1 = 0.f, lp0 = 0.f, lp1 = 0.f;
      bool redo0 = false;
      FS(2 * it, 2);
      mbar_wait(b_full + 8 * ring_slot(ta), ring_par(ta));
      named_bar_sync(1 + cwg, 256);
      FS(2 * it, 3);
      issue_qk(s, q, k_base + ring_slot(ta) * 2048);
      pass_turn(cwg);
      bool ready = mbar_test(b_full + 8 * ring_slot(ta + 1), ring_par(ta + 1)) & mbar_test(b_full + 8 * ring_slot(ta + 2), ring_par(ta + 2));
      stage_q<16>(acc, AT_C, sbase + AT_SQ + frag, lane);
      wgmma_wait<0>();
      fence_regs(s);
      if (tid == 0) mbar_arrive(b_empty + 8 * ring_slot(ta));
      mc0 = 0.f; mc1 = 0.f;
      if (!raw) {
        raw = softmax_mode(s, mc0, mc1);
        if (__builtin_expect(!raw, 0)) softmax_sub(s, mc0, mc1);
      }
      softmax_exp<0, 64>(s);
      #pragma unroll
      for (int J = 0; J < 16; J += 2)
        stmatrix_x4(sbase + AT_SQ + frag + (J >> 3) * 16384 + ((((J & 7) + (lane >> 4)) ^ (lane & 7)) << 4), q[2 * J], q[2 * J + 1], q[2 * J + 2], q[2 * J + 3]);
      pack_p(p, s);
      zero_regs(o);
      FS(2 * it, 4);
      uint32_t ks = ring_slot(ta + 1), vs = ring_slot(ta + 2), kp = ring_par(ta + 1), vp = ring_par(ta + 2);
      auto finish_head = [&]() {
        FS(2 * it, 5);
        redo0 = finish_l(lp0, lp1);
        if (!redo0) stage_o(o, lp0, lp1, sbase + AT_SQ + frag, lane);
        FS(2 * it + 1, 4);
      };
      if (!ready) { mbar_wait(b_full + 8 * ks, kp); mbar_wait(b_full + 8 * vs, vp); }
      #pragma unroll 1
      for (int n = 1; n < 2 * AT_NBLK; n++) {
        named_bar_sync(1 + cwg, 256);
        issue_qk(s, q, k_base + ks * 2048);
        if (n == AT_NBLK + 1) finish_head();
        issue_pv(o, p, v_base + vs * 2048, (n & 15) != 1);
        pass_turn(cwg);
        wgmma_wait<1>();
        fence_regs(s);
        if (tid == 0) mbar_arrive(b_empty + 8 * ks);
        if (__builtin_expect(!raw || (uint32_t)(n - (AT_NBLK - 1)) <= 2u, 0)) {
          if (n == AT_NBLK + 1 && !redo0) {
            fence_proxy_async();
            __syncwarp();
            if (lane == 0) mbar_arrive(b_ordy + 8 * cwg);
          }
          if (n == AT_NBLK - 1) {
            #pragma unroll
            for (int J = 0; J < 16; J += 2)
              ldmatrix_x4(sbase + AT_SQ + 32768 + frag + (J >> 3) * 16384 + ((((J & 7) + (lane >> 4)) ^ (lane & 7)) << 4), q[2 * J], q[2 * J + 1], q[2 * J + 2], q[2 * J + 3]);
          }
          if (!raw) {
            const float m0 = mc0, m1 = mc1;
            const bool ok = softmax_mode(s, mc0, mc1);
            if (n == AT_NBLK) raw = ok;
            else {
              mc0 = mc0 - AT_HEAD > m0 ? mc0 : m0; mc1 = mc1 - AT_HEAD > m1 ? mc1 : m1;
              al0 = ex2_approx(m0 - mc0); al1 = ex2_approx(m1 - mc1);
            }
            if (!raw) softmax_sub(s, mc0, mc1);
          }
        }
        softmax_exp<0, AT_SPLIT>(s);
        add_rowsum(p, l0, l1);
        if (tid == 0) {
          uint32_t dep = zero & __float_as_uint(l0) & __float_as_uint(l1);
          #pragma unroll
          for (int i = AT_SPLIT - AT_PIN - PINB; i < AT_SPLIT - PINB; i += 2) dep &= __float_as_uint(s[i]) & __float_as_uint(s[i + 1]);
          mbar_arrive(b_pin + dep);
        }
        wgmma_wait<0>();
        fence_regs(o);
        if (tid == 0) mbar_arrive(b_empty + 8 * vs);
        ks += 2; if (ks >= 5) { ks -= 5; kp ^= 1; }
        vs += 2; if (vs >= 5) { vs -= 5; vp ^= 1; }
        ready = mbar_test(b_full + 8 * ks, kp) & mbar_test(b_full + 8 * vs, vp);
        softmax_exp<AT_SPLIT, 64>(s);
        pack_p(p, s);
        if (n == AT_NBLK) { lp0 = l0; lp1 = l1; l0 = 0.f; l1 = 0.f; }
        if (__builtin_expect(!raw || !ready, 0)) {
        if (!raw && __any_sync(0xffffffffu, al0 != 1.0f || al1 != 1.0f)) {
          rescale_o(o, al0, al1);
          l0 *= al0; l1 *= al1;
          al0 = 1.0f; al1 = 1.0f;
        }
        if (!ready && n < 2 * AT_NBLK - 1) {
          mbar_wait(b_full + 8 * ks, kp);
          mbar_wait(b_full + 8 * vs, vp);
        }
        }
      }
      FS(2 * it + 1, 5);
      const uint32_t vl = ring_slot(ta + 63);
      vs = ring_slot(ta + 62);
      const uint32_t ob = more ? sbase + vs * 32768 : sbase + AT_SQ + 32768;
      mbar_wait(b_full + 8 * vl, ring_par(ta + 63));
      issue_pv(o, p, v_base + vl * 2048, 1);
      block_end(zero, b_pin);
      add_rowsum(p, l0, l1);
      const bool overflow = finish_l(l0, l1);
      if (!overflow && lane == 0) mbar_arrive(b_q1);
      #pragma unroll
      for (int i = 0; i < 8; i++) asm volatile("mov.b64 {%0, %1}, 0;\nmov.b64 {%2, %3}, 0;" : "=r"(pre[i].x), "=r"(pre[i].y), "=r"(pre[i].z), "=r"(pre[i].w));
      const bool want_pre = !more && bid < OG_MOE, got_pre = want_pre && __all_sync(0xffffffffu, mbar_test(bars + 272, 0));
      if (got_pre) load_pre(pre, sbase, AT_SQ, threadIdx.x - 128);
      mbar_wait(b_empty + 8 * vs, ring_par(ta + 62));
      wgmma_wait<0>();
      fence_regs(o);
      if (tid == 0) mbar_arrive(b_empty + 8 * vl);
      FS(2 * it + 1, 6);
      if (overflow) {
        attn_rows_exact(lds_u32(bars + 400), sq + 32768, ob + cwg * 8192, 4 * ta + 1, kc, vc);
        __syncwarp();
        if (lane == 0) mbar_arrive(b_q1);
      } else stage_o(o, l0, l1, ob + frag, lane);
      if (redo0) attn_rows_exact(lds_u32(bars + 400), sq, sq, 4 * ta, kc, vc);
      fence_proxy_async();
      __syncwarp();
      if (lane == 0) {
        if (redo0) mbar_arrive(b_ordy + 8 * cwg);
        mbar_arrive(b_ordy + 16 + 8 * cwg);
      }
      if (want_pre && !got_pre) load_pre(pre, sbase, AT_SQ, threadIdx.x - 128);
      if (redo0 || overflow) raw = false;
      named_bar_sync(3 + cwg, 128);
      FS(2 * it + 1, 7);
    }
    if (cwg == 0) named_bar_arrive(1, 256);
    if (__builtin_expect(single, 0)) {
      float acc[128];
      uint32_t j = 0, pk[64];
      #pragma unroll
      for (int i = 0; i < 64; i++) asm volatile("" : "=f"(acc[2 * i]), "=f"(acc[2 * i + 1]), "=r"(pk[i]));
      uint4* dst = g_pre;
      int left = 0;
      auto put = [&](bool last) {
        #pragma unroll
        for (int i = 0; i < PUT_N; i++) dst[i * 256] = make_uint4(pk[4 * i], pk[4 * i + 1], pk[4 * i + 2], pk[4 * i + 3]);
        dst += PUT_N * 256;
        #pragma unroll
        for (int i = 0; i < 64 - 4 * PUT_N; i++) asm volatile("mov.b32 %0, %1;" : "=r"(pk[i]) : "r"(pk[i + 4 * PUT_N]));
        __syncwarp();
        if (last && lane == 0) mbar_arrive(bars + 280);
      };
      #pragma unroll 1
      for (int ji = 0; ji < help_njobs(bid); ji++) {
        const int nk = og_pre(help_job(bid, ji));
        #pragma unroll 1
        for (int kk = 0; kk < nk; kk++, j++) {
          const uint32_t slot = ring_slot(qp_pos(j, 1));
          mbar_wait(b_full + 8 * slot, ring_par(qp_pos(j, 1)) ^ ((j >> 2) & 1));
          if (H_STAG > 0 && cwg == 1 && kk == nk - H_STAG) named_bar_sync(7, 256);
          const uint32_t a_lo = q_lo + (j & 3) * 1024, b_lo = w_base + slot * 2048;
          wgmma_fence();
          wgmma_m64n256k16_ss_tb<0, 0>(acc, a_lo, b_lo, kk != 0);
          wgmma_m64n256k16_ss_tb<2, 128>(acc, a_lo, b_lo, 1);
          wgmma_m64n256k16_ss_tb<4, 256>(acc, a_lo, b_lo, 1);
          wgmma_m64n256k16_ss_tb<6, 384>(acc, a_lo, b_lo, 1);
          wgmma_commit();
          if (H_STAG > 0 && cwg == 0 && kk == nk - 1) named_bar_arrive(7, 256);
          wgmma_wait<1>();
          if (kk > 0 && tid == 0) mbar_arrive(b_empty + 8 * ring_slot(qp_pos(j - 1, 1)));
          #pragma unroll 1
          for (int i = ji == OG_JOBS ? 0 : 16 / PUT_N - 1; i < 16 / PUT_N && left > 0; i++) put(--left == 0);
        }
        wgmma_wait<0>();
        fence_regs(acc);
        if (tid == 0) mbar_arrive(b_empty + 8 * ring_slot(qp_pos(j - 1, 1)));
        #pragma unroll
        for (int i = 0; i < 64; i++) pk[i] = pack_bf16(acc[2 * i], acc[2 * i + 1]);
        left = 16 / PUT_N;
        if (ji == PRE_X) mbar_wait(bars + 296, 0);
        dst = g_pre + help_job(bid, ji) * 2048 + threadIdx.x - 128;
      }
      #pragma unroll
      for (int i = 0; i < 16; i++) dst[i * 256] = make_uint4(pk[4 * i], pk[4 * i + 1], pk[4 * i + 2], pk[4 * i + 3]);
      __syncwarp();
      if (lane == 0) mbar_arrive(bars + 280);
      named_bar_sync(5, 256);
      if (threadIdx.x == 128) {
        #pragma unroll 1
        for (int i = 0; i < 5; i++) {
          constexpr int n = OG_HSUM;
          const int used = i == 3 ? 0 : (n + 3 - (i == 4 ? 3 : i)) / 4;
          if ((used ^ (i < 4)) & 1) {
            mbar_arrive(b_full + 8 * ring_slot(4 + i));
            mbar_arrive(b_empty + 8 * ring_slot(4 + i)); mbar_arrive(b_empty + 8 * ring_slot(4 + i));
          }
        }
        mbar_arrive(b_x);
      }
      named_bar_sync(5, 256);
      #pragma unroll
      for (int i = 0; i < 8; i++) pre[i] = make_uint4(0u, 0u, 0u, 0u);
    }
    TL_CLK(3, 1, threadIdx.x == 128);
    TL_CTA(1, threadIdx.x == 256);
    TL_END(3, tid == 0);
    TL_MARK2(19, tid == 0 && !single);
    if (bid < 128) {
      tail_consumer(bid, sbase, &tmOut, pre, cwg, w_gate, w_up);
    }
  }
}

typedef CUresult (*PFN_encodeTiled)(CUtensorMap*, CUtensorMapDataType, cuuint32_t, void*, const cuuint64_t*, const cuuint64_t*,
                                    const cuuint32_t*, const cuuint32_t*, CUtensorMapInterleave, CUtensorMapSwizzle,
                                    CUtensorMapL2promotion, CUtensorMapFloatOOBfill);

CUtensorMap make_map_2d(PFN_encodeTiled enc, const void* ptr, uint64_t inner, uint64_t outer, uint64_t stride_bytes, uint32_t box_inner, uint32_t box_outer) {
  CUtensorMap m;
  cuuint64_t gd[2] = {inner, outer}; cuuint64_t gs[1] = {stride_bytes};
  cuuint32_t bx[2] = {box_inner, box_outer}; cuuint32_t es[2] = {1, 1};
  enc(&m, CU_TENSOR_MAP_DATA_TYPE_BFLOAT16, 2, const_cast<void*>(ptr), gd, gs, bx, es, CU_TENSOR_MAP_INTERLEAVE_NONE,
      CU_TENSOR_MAP_SWIZZLE_128B, CU_TENSOR_MAP_L2_PROMOTION_L2_128B, CU_TENSOR_MAP_FLOAT_OOB_FILL_NONE);
  return m;
}

CUtensorMap make_map_3d(PFN_encodeTiled enc, const void* ptr, uint64_t cols, uint64_t rows, uint32_t box_rows, uint32_t chunks) {
  CUtensorMap m;
  cuuint64_t gd[3] = {64, rows, cols / 64}; cuuint64_t gs[2] = {cols * 2, 128};
  cuuint32_t bx[3] = {64, box_rows, chunks}; cuuint32_t es[3] = {1, 1, 1};
  enc(&m, CU_TENSOR_MAP_DATA_TYPE_BFLOAT16, 3, const_cast<void*>(ptr), gd, gs, bx, es, CU_TENSOR_MAP_INTERLEAVE_NONE,
      CU_TENSOR_MAP_SWIZZLE_128B, CU_TENSOR_MAP_L2_PROMOTION_L2_128B, CU_TENSOR_MAP_FLOAT_OOB_FILL_NONE);
  return m;
}

}

extern "C" void kernel_launch(void* const* d_in, const int* in_sizes, int n_in, void* d_out, int out_size) {
  const bf16* x      = (const bf16*)d_in[0];
  const bf16* kc     = (const bf16*)d_in[1];
  const bf16* vc     = (const bf16*)d_in[2];
  const bf16* wq     = (const bf16*)d_in[3];
  const bf16* wo     = (const bf16*)d_in[4];
  const bf16* w_r    = (const bf16*)d_in[6];
  const bf16* w_gate = (const bf16*)d_in[7];
  const bf16* w_up   = (const bf16*)d_in[8];
  const bf16* w_down = (const bf16*)d_in[9];
  const bf16* cvec   = (const bf16*)d_in[10];
  const bf16* w_mod  = (const bf16*)d_in[11];
  bf16* out = (bf16*)d_out;

  static PFN_encodeTiled enc = nullptr;
  static void *p_h = nullptr, *p_o = nullptr;
  if (!enc) {
    void* fn = nullptr; cudaDriverEntryPointQueryResult qres;
    cudaGetDriverEntryPoint("cuTensorMapEncodeTiled", &fn, cudaEnableDefault, &qres);
    enc = (PFN_encodeTiled)fn;
    cudaGetSymbolAddress(&p_h, g_pre);
    p_h = (uint4*)p_h + 16 * PRE_X * 2048;
    cudaGetSymbolAddress(&p_o, g_o);
    cudaFuncSetAttribute(fused_kernel, cudaFuncAttributeMaxDynamicSharedMemorySize, (int)AT_SMEM);
  }
  const CUtensorMap tm_h   = make_map_2d(enc, p_h, T_D, T_SEQ, T_D * 2, 64, 128);
  const CUtensorMap tm_wq  = make_map_3d(enc, wq, T_DQKV, T_D, 64, 4);
  const CUtensorMap tm_k   = make_map_3d(enc, kc, T_DH, (uint64_t)T_NH * T_SEQ, 128, 2);
  const CUtensorMap tm_v   = make_map_3d(enc, vc, T_DH, (uint64_t)T_NH * T_SEQ, 128, 2);
  const CUtensorMap tm_ost = make_map_2d(enc, p_o, T_DQKV, T_SEQ, T_DQKV * 2, 64, 64);
  const CUtensorMap tm_old = make_map_2d(enc, p_o, T_DQKV, T_SEQ, T_DQKV * 2, 64, 128);
  const CUtensorMap tm_wo  = make_map_3d(enc, wo, T_D, T_DQKV, 64, 2);
  const CUtensorMap tm_d   = make_map_3d(enc, w_down, T_D, T_F, 32, 8);

  const CUtensorMap tm_m   = make_map_2d(enc, w_mod, 6 * T_D, T_D, 6 * T_D * 2, 64, 256);
  const CUtensorMap tm_out = make_map_2d(enc, out, T_D, T_SEQ, T_D * 2, 64, 16);

  fused_kernel<<<132, 384, AT_SMEM, cudaStreamPerThread>>>(tm_h, tm_wq, tm_k, tm_v, tm_ost, tm_old, tm_wo, tm_d, tm_out, tm_m, 0u, (const uint8_t*)wo, kc, vc, x, cvec, w_mod,
             w_r, w_gate, w_up, w_down, out);
}
```

```cpp
#include <cuda_runtime.h>
#include <cuda_bf16.h>
#include <cuda.h>
#include <stdint.h>

namespace {

typedef __nv_bfloat16 bf16;

constexpr int T_SEQ = 2048, T_D = 1024, T_NH = 32, T_DH = 128, T_DQKV = 4096, T_F = 3584;

#define PRE_X 2
__device__ __align__(1024) uint4 g_pre[(16 * PRE_X + 128) * 2048];
#define g_h (reinterpret_cast<bf16*>(g_pre + 16 * PRE_X * 2048))
__device__ __align__(1024) bf16 g_o[T_SEQ * T_DQKV];
__device__ __align__(16) uint8_t g_col[8 * 1536];
__device__ __align__(16) float g_scal[64];
__device__ __align__(16) unsigned int g_hcnt[17 * 32];
__device__ __align__(128) float g_modpart[4 * 2 * T_D];
struct __align__(2048) TailMail {
  float4 part1[T_SEQ * 8];
  uint32_t key[256];
  uint4 cand[16 * 2 * 2 * 128];
  uint32_t cnt[32];
  float ypart[(T_F / 32) * 2 * T_D];
};
__device__ TailMail g_mail;
#define g_part1 g_mail.part1
#define g_key g_mail.key
#define g_cand g_mail.cand
#define CNT_Y (g_mail.cnt)
#define g_ypart g_mail.ypart

__device__ __forceinline__ uint32_t smem_u32(const void* p) { return (uint32_t)__cvta_generic_to_shared(p); }
__device__ __forceinline__ void mbar_init(uint32_t bar, uint32_t cnt) { asm volatile("mbarrier.init.shared::cta.b64 [%0], %1;" :: "r"(bar), "r"(cnt)); }
__device__ __forceinline__ void mbar_expect_tx(uint32_t bar, uint32_t bytes) { asm volatile("mbarrier.arrive.expect_tx.shared::cta.b64 _, [%0], %1;" :: "r"(bar), "r"(bytes) : "memory"); }
__device__ __forceinline__ void mbar_arrive(uint32_t bar) { asm volatile("mbarrier.arrive.shared::cta.b64 _, [%0];" :: "r"(bar) : "memory"); }
__device__ __forceinline__ void mbar_wait(uint32_t bar, uint32_t parity) {
  asm volatile("{\n.reg .pred p;\nLAB_WAIT:\nmbarrier.try_wait.parity.shared::cta.b64 p, [%0], %1;\n@!p bra LAB_WAIT;\n}\n" :: "r"(bar), "r"(parity) : "memory");
}
__device__ __forceinline__ bool mbar_test(uint32_t bar, uint32_t parity) {
  uint32_t r; asm volatile("{\n.reg .pred p;\nmbarrier.test_wait.parity.shared::cta.b64 p, [%1], %2;\nselp.u32 %0, 1, 0, p;\n}\n" : "=r"(r) : "r"(bar), "r"(parity) : "memory");
  return r != 0;
}
__device__ __forceinline__ void mbar_wait_long(uint32_t bar, uint32_t parity) {
  asm volatile("{\n.reg .pred p;\nLAB_WAIT:\nmbarrier.try_wait.parity.shared::cta.b64 p, [%0], %1, %2;\n@!p bra LAB_WAIT;\n}\n" :: "r"(bar), "r"(parity), "r"(100000) : "memory");
}
__device__ __forceinline__ uint32_t clock_lo() { uint32_t c; asm volatile("mov.u32 %0, %%clock;" : "=r"(c)); return c; }
__device__ __forceinline__ void fence_mbar_init() { asm volatile("fence.mbarrier_init.release.cluster;" ::: "memory"); }
__device__ __forceinline__ void tma_load_2d(uint32_t dst, const CUtensorMap* map, int c0, int c1, uint32_t bar) {
  asm volatile("cp.async.bulk.tensor.2d.shared::cluster.global.mbarrier::complete_tx::bytes [%0], [%1, {%3, %4}], [%2];"
    :: "r"(dst), "l"(map), "r"(bar), "r"(c0), "r"(c1) : "memory");
}
__device__ __forceinline__ uint64_t policy_evict_first() {
  uint64_t p; asm volatile("createpolicy.fractional.L2::evict_first.b64 %0, 1.0;" : "=l"(p)); return p;
}
__device__ __forceinline__ void tma_load_2d_hint(uint32_t dst, const CUtensorMap* map, int c0, int c1, uint32_t bar, uint64_t pol) {
  asm volatile("cp.async.bulk.tensor.2d.shared::cluster.global.mbarrier::complete_tx::bytes.L2::cache_hint [%0], [%1, {%3, %4}], [%2], %5;"
    :: "r"(dst), "l"(map), "r"(bar), "r"(c0), "r"(c1), "l"(pol) : "memory");
}
__device__ __forceinline__ void tma_load_3d_hint(uint32_t dst, const CUtensorMap* map, int c1, int c2, uint32_t bar, uint64_t pol) {
  asm volatile("cp.async.bulk.tensor.3d.shared::cluster.global.mbarrier::complete_tx::bytes.L2::cache_hint [%0], [%1, {%3, %4, %5}], [%2], %6;"
    :: "r"(dst), "l"(map), "r"(bar), "n"(0), "r"(c1), "r"(c2), "l"(pol) : "memory");
}
__device__ __forceinline__ void tma_load_3d(uint32_t dst, const CUtensorMap* map, int c1, int c2, uint32_t bar) {
  asm volatile("cp.async.bulk.tensor.3d.shared::cluster.global.mbarrier::complete_tx::bytes [%0], [%1, {%3, %4, %5}], [%2];"
    :: "r"(dst), "l"(map), "r"(bar), "n"(0), "r"(c1), "r"(c2) : "memory");
}
__device__ __forceinline__ void tma_store_2d(const CUtensorMap* map, uint32_t src, int c0, int c1) {
  asm volatile("cp.async.bulk.tensor.2d.global.shared::cta.bulk_group [%0, {%2, %3}], [%1];" :: "l"(map), "r"(src), "r"(c0), "r"(c1) : "memory");
}
__device__ __forceinline__ void prefetch_tmap(const CUtensorMap* map) { asm volatile("prefetch.tensormap [%0];" :: "l"(map) : "memory"); }
__device__ __forceinline__ void l2_prefetch_bulk(const void* p, uint32_t bytes) {
  asm volatile("cp.async.bulk.prefetch.L2.global [%0], %1;" :: "l"(p), "r"(bytes) : "memory");
}
__device__ __forceinline__ void bulk_commit() { asm volatile("cp.async.bulk.commit_group;" ::: "memory"); }
template<int N> __device__ __forceinline__ void bulk_wait_read() { asm volatile("cp.async.bulk.wait_group.read %0;" :: "n"(N) : "memory"); }
template<int N> __device__ __forceinline__ void bulk_wait() { asm volatile("cp.async.bulk.wait_group %0;" :: "n"(N) : "memory"); }
__device__ __forceinline__ void named_bar_sync(int id, int nthreads) { asm volatile("bar.sync %0, %1;" :: "r"(id), "r"(nthreads) : "memory"); }
__device__ __forceinline__ void named_bar_arrive(int id, int nthreads) { asm volatile("bar.arrive %0, %1;" :: "r"(id), "r"(nthreads) : "memory"); }
__device__ __forceinline__ void pass_turn(int cwg) {
  asm volatile("{\n.reg .pred p;\nsetp.ne.u32 p, %0, 0;\n@p bar.arrive 1, 256;\n@!p bar.arrive 2, 256;\n}\n" :: "r"(cwg) : "memory");
}
__device__ __forceinline__ void wgmma_fence() { asm volatile("wgmma.fence.sync.aligned;" ::: "memory"); }
__device__ __forceinline__ void wgmma_commit() { asm volatile("wgmma.commit_group.sync.aligned;" ::: "memory"); }
template<int N> __device__ __forceinline__ void wgmma_wait() { asm volatile("wgmma.wait_group.sync.aligned %0;" :: "n"(N) : "memory"); }
template<int R> __device__ __forceinline__ void reg_alloc() { asm volatile("setmaxnreg.inc.sync.aligned.u32 %0;" :: "n"(R)); }
template<int R> __device__ __forceinline__ void reg_dealloc() { asm volatile("setmaxnreg.dec.sync.aligned.u32 %0;" :: "n"(R)); }
__device__ __forceinline__ bool elect_one() {
  uint32_t pred; asm volatile("{\n.reg .pred p;\nelect.sync _|p, 0xffffffff;\nselp.u32 %0, 1, 0, p;\n}\n" : "=r"(pred)); return pred != 0;
}
__device__ __forceinline__ uint32_t pack_bf16(float lo, float hi) {
  uint32_t r; asm("cvt.rn.bf16x2.f32 %0, %1, %2;" : "=r"(r) : "f"(hi), "f"(lo)); return r;
}
__device__ __forceinline__ void stmatrix_x4(uint32_t addr, uint32_t r0, uint32_t r1, uint32_t r2, uint32_t r3) {
  asm volatile("stmatrix.sync.aligned.m8n8.x4.shared.b16 [%0], {%1, %2, %3, %4};" :: "r"(addr), "r"(r0), "r"(r1), "r"(r2), "r"(r3) : "memory");
}
__device__ __forceinline__ void fence_proxy_async() { asm volatile("fence.proxy.async.shared::cta;" ::: "memory"); }
__device__ __forceinline__ float ex2_approx(float x) { float y; asm("ex2.approx.ftz.f32 %0, %1;" : "=f"(y) : "f"(x)); return y; }
template<int N> __device__ __forceinline__ void fence_regs(float (&r)[N]) {
  #pragma unroll
  for (int i = 0; i < N; i++) asm volatile("" : "+f"(r[i]) :: "memory");
}
template<int N> __device__ __forceinline__ void zero_regs(float (&r)[N]) {
  #pragma unroll
  for (int i = 0; i < N; i += 2) asm volatile("mov.b64 {%0, %1}, 0;" : "=f"(r[i]), "=f"(r[i + 1]));
}
__device__ __forceinline__ float rbf(float x) { return __uint_as_float(pack_bf16(0.f, x)); }
__device__ __forceinline__ float bflo(uint32_t v) { return __uint_as_float(v << 16); }
__device__ __forceinline__ float bfhi(uint32_t v) { return __uint_as_float(v & 0xffff0000u); }

#define XT(i) do {} while (0)
#define TL_START(k) do {} while (0)
#define TL_END(k, cond) do {} while (0)
#define TL_CTA(i, cond) do {} while (0)
#define FS(slot, k) do {} while (0)
#define TL_MARK2(k, cond) do {} while (0)
#define TL_CLK(k, i, cond) do {} while (0)

template <int OFFA, int OFFB>
__device__ __forceinline__ void wgmma_m64n256k16_ss_tb(float (&d)[128], uint32_t a_lo, uint32_t b_lo, int scaleD) {
  asm volatile("{\n.reg .pred p;\n.reg .b32 ta, tb;\n.reg .b64 da, db;\nsetp.ne.b32 p, %130, 0;\n"
    "add.u32 ta, %128, %131;\nadd.u32 tb, %129, %132;\n"
    "mov.b64 da, {ta, 0x40000040};\nmov.b64 db, {tb, 0x40000040};\n"
    "wgmma.mma_async.sync.aligned.m64n256k16.f32.bf16.bf16 "
    "{%0, %1, %2, %3, %4, %5, %6, %7, %8, %9, %10, %11, %12, %13, %14, %15, %16, %17, %18, %19, %20, %21, %22, %23, %24, %25, %26, %27, %28, %29, %30, %31, %32, %33, %34, %35, %36, %37, %38, %39, %40, %41, %42, %43, %44, %45, %46, %47, %48, %49, %50, %51, %52, %53, %54, %55, %56, %57, %58, %59, %60, %61, %62, %63, %64, %65, %66, %67, %68, %69, %70, %71, %72, %73, %74, %75, %76, %77, %78, %79, %80, %81, %82, %83, %84, %85, %86, %87, %88, %89, %90, %91, %92, %93, %94, %95, %96, %97, %98, %99, %100, %101, %102, %103, %104, %105, %106, %107, %108, %109, %110, %111, %112, %113, %114, %115, %116, %117, %118, %119, %120, %121, %122, %123, %124, %125, %126, %127}, "
    "da, db, p, 1, 1, 0, 1;\n}\n"
    : "+f"(d[0]), "+f"(d[1]), "+f"(d[2]), "+f"(d[3]), "+f"(d[4]), "+f"(d[5]), "+f"(d[6]), "+f"(d[7]), "+f"(d[8]), "+f"(d[9]), "+f"(d[10]), "+f"(d[11]), "+f"(d[12]), "+f"(d[13]), "+f"(d[14]), "+f"(d[15]), "+f"(d[16]), "+f"(d[17]), "+f"(d[18]), "+f"(d[19]), "+f"(d[20]), "+f"(d[21]), "+f"(d[22]), "+f"(d[23]), "+f"(d[24]), "+f"(d[25]), "+f"(d[26]), "+f"(d[27]), "+f"(d[28]), "+f"(d[29]), "+f"(d[30]), "+f"(d[31]), "+f"(d[32]), "+f"(d[33]), "+f"(d[34]), "+f"(d[35]), "+f"(d[36]), "+f"(d[37]), "+f"(d[38]), "+f"(d[39]), "+f"(d[40]), "+f"(d[41]), "+f"(d[42]), "+f"(d[43]), "+f"(d[44]), "+f"(d[45]), "+f"(d[46]), "+f"(d[47]), "+f"(d[48]), "+f"(d[49]), "+f"(d[50]), "+f"(d[51]), "+f"(d[52]), "+f"(d[53]), "+f"(d[54]), "+f"(d[55]), "+f"(d[56]), "+f"(d[57]), "+f"(d[58]), "+f"(d[59]), "+f"(d[60]), "+f"(d[61]), "+f"(d[62]), "+f"(d[63]), "+f"(d[64]), "+f"(d[65]), "+f"(d[66]), "+f"(d[67]), "+f"(d[68]), "+f"(d[69]), "+f"(d[70]), "+f"(d[71]), "+f"(d[72]), "+f"(d[73]), "+f"(d[74]), "+f"(d[75]), "+f"(d[76]), "+f"(d[77]), "+f"(d[78]), "+f"(d[79]), "+f"(d[80]), "+f"(d[81]), "+f"(d[82]), "+f"(d[83]), "+f"(d[84]), "+f"(d[85]), "+f"(d[86]), "+f"(d[87]), "+f"(d[88]), "+f"(d[89]), "+f"(d[90]), "+f"(d[91]), "+f"(d[92]), "+f"(d[93]), "+f"(d[94]), "+f"(d[95]), "+f"(d[96]), "+f"(d[97]), "+f"(d[98]), "+f"(d[99]), "+f"(d[100]), "+f"(d[101]), "+f"(d[102]), "+f"(d[103]), "+f"(d[104]), "+f"(d[105]), "+f"(d[106]), "+f"(d[107]), "+f"(d[108]), "+f"(d[109]), "+f"(d[110]), "+f"(d[111]), "+f"(d[112]), "+f"(d[113]), "+f"(d[114]), "+f"(d[115]), "+f"(d[116]), "+f"(d[117]), "+f"(d[118]), "+f"(d[119]), "+f"(d[120]), "+f"(d[121]), "+f"(d[122]), "+f"(d[123]), "+f"(d[124]), "+f"(d[125]), "+f"(d[126]), "+f"(d[127])
    : "r"(a_lo), "r"(b_lo), "r"(scaleD), "n"(OFFA), "n"(OFFB));
}

template <int OFFA, int OFFB>
__device__ __forceinline__ void wgmma_m64n128k16_ss_tb(float (&d)[64], uint32_t a_lo, uint32_t b_lo, int scaleD) {
  asm volatile("{\n.reg .pred p;\n.reg .b32 ta, tb;\n.reg .b64 da, db;\nsetp.ne.b32 p, %66, 0;\n"
    "add.u32 ta, %64, %67;\nadd.u32 tb, %65, %68;\n"
    "mov.b64 da, {ta, 0x40000040};\nmov.b64 db, {tb, 0x40000040};\n"
    "wgmma.mma_async.sync.aligned.m64n128k16.f32.bf16.bf16 "
    "{%0, %1, %2, %3, %4, %5, %6, %7, %8, %9, %10, %11, %12, %13, %14, %15, %16, %17, %18, %19, %20, %21, %22, %23, %24, %25, %26, %27, %28, %29, %30, %31, %32, %33, %34, %35, %36, %37, %38, %39, %40, %41, %42, %43, %44, %45, %46, %47, %48, %49, %50, %51, %52, %53, %54, %55, %56, %57, %58, %59, %60, %61, %62, %63}, "
    "da, db, p, 1, 1, 0, 1;\n}\n"
    : "+f"(d[0]), "+f"(d[1]), "+f"(d[2]), "+f"(d[3]), "+f"(d[4]), "+f"(d[5]), "+f"(d[6]), "+f"(d[7]), "+f"(d[8]), "+f"(d[9]), "+f"(d[10]), "+f"(d[11]), "+f"(d[12]), "+f"(d[13]), "+f"(d[14]), "+f"(d[15]), "+f"(d[16]), "+f"(d[17]), "+f"(d[18]), "+f"(d[19]), "+f"(d[20]), "+f"(d[21]), "+f"(d[22]), "+f"(d[23]), "+f"(d[24]), "+f"(d[25]), "+f"(d[26]), "+f"(d[27]), "+f"(d[28]), "+f"(d[29]), "+f"(d[30]), "+f"(d[31]), "+f"(d[32]), "+f"(d[33]), "+f"(d[34]), "+f"(d[35]), "+f"(d[36]), "+f"(d[37]), "+f"(d[38]), "+f"(d[39]), "+f"(d[40]), "+f"(d[41]), "+f"(d[42]), "+f"(d[43]), "+f"(d[44]), "+f"(d[45]), "+f"(d[46]), "+f"(d[47]), "+f"(d[48]), "+f"(d[49]), "+f"(d[50]), "+f"(d[51]), "+f"(d[52]), "+f"(d[53]), "+f"(d[54]), "+f"(d[55]), "+f"(d[56]), "+f"(d[57]), "+f"(d[58]), "+f"(d[59]), "+f"(d[60]), "+f"(d[61]), "+f"(d[62]), "+f"(d[63])
    : "r"(a_lo), "r"(b_lo), "r"(scaleD), "n"(OFFA), "n"(OFFB));
}

template <int OFFB>
__device__ __forceinline__ void wgmma_m64n128k16_rs_tb(float (&d)[64], uint32_t a0, uint32_t a1, uint32_t a2, uint32_t a3, uint32_t b_lo, int scaleD) {
  asm volatile("{\n.reg .pred p;\n.reg .b32 tb;\n.reg .b64 db;\nsetp.ne.b32 p, %69, 0;\n"
    "add.u32 tb, %68, %70;\n"
    "mov.b64 db, {tb, 0x40000040};\n"
    "wgmma.mma_async.sync.aligned.m64n128k16.f32.bf16.bf16 "
    "{%0, %1, %2, %3, %4, %5, %6, %7, %8, %9, %10, %11, %12, %13, %14, %15, %16, %17, %18, %19, %20, %21, %22, %23, %24, %25, %26, %27, %28, %29, %30, %31, %32, %33, %34, %35, %36, %37, %38, %39, %40, %41, %42, %43, %44, %45, %46, %47, %48, %49, %50, %51, %52, %53, %54, %55, %56, %57, %58, %59, %60, %61, %62, %63}, "
    "{%64, %65, %66, %67}, db, p, 1, 1, 1;\n}\n"
    : "+f"(d[0]), "+f"(d[1]), "+f"(d[2]), "+f"(d[3]), "+f"(d[4]), "+f"(d[5]), "+f"(d[6]), "+f"(d[7]), "+f"(d[8]), "+f"(d[9]), "+f"(d[10]), "+f"(d[11]), "+f"(d[12]), "+f"(d[13]), "+f"(d[14]), "+f"(d[15]), "+f"(d[16]), "+f"(d[17]), "+f"(d[18]), "+f"(d[19]), "+f"(d[20]), "+f"(d[21]), "+f"(d[22]), "+f"(d[23]), "+f"(d[24]), "+f"(d[25]), "+f"(d[26]), "+f"(d[27]), "+f"(d[28]), "+f"(d[29]), "+f"(d[30]), "+f"(d[31]), "+f"(d[32]), "+f"(d[33]), "+f"(d[34]), "+f"(d[35]), "+f"(d[36]), "+f"(d[37]), "+f"(d[38]), "+f"(d[39]), "+f"(d[40]), "+f"(d[41]), "+f"(d[42]), "+f"(d[43]), "+f"(d[44]), "+f"(d[45]), "+f"(d[46]), "+f"(d[47]), "+f"(d[48]), "+f"(d[49]), "+f"(d[50]), "+f"(d[51]), "+f"(d[52]), "+f"(d[53]), "+f"(d[54]), "+f"(d[55]), "+f"(d[56]), "+f"(d[57]), "+f"(d[58]), "+f"(d[59]), "+f"(d[60]), "+f"(d[61]), "+f"(d[62]), "+f"(d[63])
    : "r"(a0), "r"(a1), "r"(a2), "r"(a3), "r"(b_lo), "r"(scaleD), "n"(OFFB));
}

template <int OFFB>
__device__ __forceinline__ void wgmma_m64n128k16_rs(float (&d)[64], uint32_t a0, uint32_t a1, uint32_t a2, uint32_t a3, uint32_t b_lo, int scaleD) {
  asm volatile("{\n.reg .pred p;\n.reg .b32 tb;\n.reg .b64 db;\nsetp.ne.b32 p, %69, 0;\n"
    "add.u32 tb, %68, %70;\n"
    "mov.b64 db, {tb, 0x40000040};\n"
    "wgmma.mma_async.sync.aligned.m64n128k16.f32.bf16.bf16 "
    "{%0, %1, %2, %3, %4, %5, %6, %7, %8, %9, %10, %11, %12, %13, %14, %15, %16, %17, %18, %19, %20, %21, %22, %23, %24, %25, %26, %27, %28, %29, %30, %31, %32, %33, %34, %35, %36, %37, %38, %39, %40, %41, %42, %43, %44, %45, %46, %47, %48, %49, %50, %51, %52, %53, %54, %55, %56, %57, %58, %59, %60, %61, %62, %63}, "
    "{%64, %65, %66, %67}, db, p, 1, 1, 0;\n}\n"
    : "+f"(d[0]), "+f"(d[1]), "+f"(d[2]), "+f"(d[3]), "+f"(d[4]), "+f"(d[5]), "+f"(d[6]), "+f"(d[7]), "+f"(d[8]), "+f"(d[9]), "+f"(d[10]), "+f"(d[11]), "+f"(d[12]), "+f"(d[13]), "+f"(d[14]), "+f"(d[15]), "+f"(d[16]), "+f"(d[17]), "+f"(d[18]), "+f"(d[19]), "+f"(d[20]), "+f"(d[21]), "+f"(d[22]), "+f"(d[23]), "+f"(d[24]), "+f"(d[25]), "+f"(d[26]), "+f"(d[27]), "+f"(d[28]), "+f"(d[29]), "+f"(d[30]), "+f"(d[31]), "+f"(d[32]), "+f"(d[33]), "+f"(d[34]), "+f"(d[35]), "+f"(d[36]), "+f"(d[37]), "+f"(d[38]), "+f"(d[39]), "+f"(d[40]), "+f"(d[41]), "+f"(d[42]), "+f"(d[43]), "+f"(d[44]), "+f"(d[45]), "+f"(d[46]), "+f"(d[47]), "+f"(d[48]), "+f"(d[49]), "+f"(d[50]), "+f"(d[51]), "+f"(d[52]), "+f"(d[53]), "+f"(d[54]), "+f"(d[55]), "+f"(d[56]), "+f"(d[57]), "+f"(d[58]), "+f"(d[59]), "+f"(d[60]), "+f"(d[61]), "+f"(d[62]), "+f"(d[63])
    : "r"(a0), "r"(a1), "r"(a2), "r"(a3), "r"(b_lo), "r"(scaleD), "n"(OFFB));
}

__device__ __forceinline__ uint4 ldg_nc_v4(const void* p) {
  uint4 v;
    asm volatile("{\n.reg .b64 pol;\ncreatepolicy.fractional.L2::evict_first.b64 pol, 1.0;\n"
                 "ld.global.nc.L1::no_allocate.L2::cache_hint.v4.u32 {%0, %1, %2, %3}, [%4], pol;\n}\n" : "=r"(v.x), "=r"(v.y), "=r"(v.z), "=r"(v.w) : "l"(p));
  return v;
}
__device__ __forceinline__ void unpack8(const uint4& u, float (&v)[8]) {
  v[0] = bflo(u.x); v[1] = bfhi(u.x); v[2] = bflo(u.y); v[3] = bfhi(u.y);
  v[4] = bflo(u.z); v[5] = bfhi(u.z); v[6] = bflo(u.w); v[7] = bfhi(u.w);
}
__device__ __forceinline__ void fma8(float (&acc)[8], float s, const uint4& w) {
  acc[0] = fmaf(s, bflo(w.x), acc[0]); acc[1] = fmaf(s, bfhi(w.x), acc[1]); acc[2] = fmaf(s, bflo(w.y), acc[2]); acc[3] = fmaf(s, bfhi(w.y), acc[3]);
  acc[4] = fmaf(s, bflo(w.z), acc[4]); acc[5] = fmaf(s, bfhi(w.z), acc[5]); acc[6] = fmaf(s, bflo(w.w), acc[6]); acc[7] = fmaf(s, bfhi(w.w), acc[7]);
}
__device__ __forceinline__ float rcp_approx(float x) { float y; asm("rcp.approx.ftz.f32 %0, %1;" : "=f"(y) : "f"(x)); return y; }
__device__ __forceinline__ float sigmoid_f(float v) { return rcp_approx(1.0f + ex2_approx(v * -1.4426950408889634f)); }
__device__ __forceinline__ float silu_bf(float v) { return rbf(v * sigmoid_f(v)); }
__device__ __forceinline__ uint32_t rank_key(float r, int idx) {
  const uint32_t b = __float_as_uint(r) >> 16;
  const uint32_t u = (r != r) ? 0u : ((b & 0x8000u) ? (~b & 0xffffu) : (b | 0x8000u));
  return (u << 16) | (0xffffu - (uint32_t)idx);
}
__device__ __forceinline__ void warp_top2(uint32_t& k1, uint32_t& k2) {
  const uint32_t m1 = __reduce_max_sync(0xffffffffu, k1);
  k2 = __reduce_max_sync(0xffffffffu, k1 == m1 ? k2 : k1);
  k1 = m1;
}
__device__ __forceinline__ uint32_t bmul2(uint32_t a, uint32_t b) { uint32_t r; asm("mul.rn.bf16x2 %0, %1, %2;" : "=r"(r) : "r"(a), "r"(b)); return r; }
__device__ __forceinline__ uint32_t badd2(uint32_t a, uint32_t b) { uint32_t r; asm("add.rn.bf16x2 %0, %1, %2;" : "=r"(r) : "r"(a), "r"(b)); return r; }
__device__ __forceinline__ uint32_t bsub2(uint32_t a, uint32_t b) { uint32_t r; asm("sub.rn.bf16x2 %0, %1, %2;" : "=r"(r) : "r"(a), "r"(b)); return r; }
__device__ __forceinline__ float sqrt_approx(float x) { float y; asm("sqrt.approx.f32 %0, %1;" : "=f"(y) : "f"(x)); return y; }
__device__ __forceinline__ uint32_t ln_norm2(uint32_t x1, uint32_t mb2, float inv) {
  const uint32_t d = bsub2(x1, mb2);
  return pack_bf16(bflo(d) * inv, bfhi(d) * inv);
}
__device__ __forceinline__ uint32_t bfma2(uint32_t a, uint32_t b, uint32_t c) { uint32_t r; asm("fma.rn.bf16x2 %0, %1, %2, %3;" : "=r"(r) : "r"(a), "r"(b), "r"(c)); return r; }
__device__ __forceinline__ uint32_t ln_norm2b(uint32_t x1, uint32_t mb2, uint32_t ih, uint32_t il) {
  const uint32_t d = bsub2(x1, mb2);
  return bfma2(d, ih, bmul2(d, il));
}
__device__ __forceinline__ uint32_t ln_mod2(uint32_t x1, uint32_t mb2, float inv, uint32_t c1, uint32_t sb) { return badd2(bmul2(ln_norm2(x1, mb2, inv), c1), sb); }
__device__ __forceinline__ void ldmatrix_x4(uint32_t addr, uint32_t& r0, uint32_t& r1, uint32_t& r2, uint32_t& r3) {
  asm volatile("ldmatrix.sync.aligned.m8n8.x4.shared.b16 {%0, %1, %2, %3}, [%4];" : "=r"(r0), "=r"(r1), "=r"(r2), "=r"(r3) : "r"(addr) : "memory");
}
__device__ __forceinline__ uint4 ldg_stream_v4(const void* p, uint64_t pol, bool on) {
  uint4 v;
  asm volatile("{\n.reg .pred q;\nsetp.ne.u32 q, %6, 0;\n@q ld.global.nc.L1::no_allocate.L2::cache_hint.L2::128B.v4.u32 {%0, %1, %2, %3}, [%4], %5;\n}\n"
               : "=r"(v.x), "=r"(v.y), "=r"(v.z), "=r"(v.w) : "l"(p), "l"(pol), "r"((uint32_t)on));
  return v;
}
__device__ __forceinline__ void bulk_load_hint(uint32_t dst, const void* src, uint32_t bytes, uint32_t bar, uint64_t pol) {
  asm volatile("cp.async.bulk.shared::cluster.global.mbarrier::complete_tx::bytes.L2::cache_hint [%0], [%1], %2, [%3], %4;"
    :: "r"(dst), "l"(src), "r"(bytes), "r"(bar), "l"(pol) : "memory");
}
__device__ __forceinline__ void red_release_add(unsigned int* p, unsigned int v) { asm volatile("red.release.gpu.global.add.u32 [%0], %1;" :: "l"(p), "r"(v) : "memory"); }
__device__ __forceinline__ unsigned int ld_acquire(const unsigned int* p) { unsigned int v; asm volatile("ld.acquire.gpu.global.u32 %0, [%1];" : "=r"(v) : "l"(p) : "memory"); return v; }
__device__ __forceinline__ void spin_until(const unsigned int* p, unsigned int target) {
  #pragma unroll 1
  for (unsigned int i = 0; i < (1u << 22); i++) { if (ld_acquire(p) >= target) return; }
}
__device__ __forceinline__ float lds_f32(uint32_t a) { float v; asm volatile("ld.shared.f32 %0, [%1];" : "=f"(v) : "r"(a) : "memory"); return v; }
__device__ __forceinline__ float2 lds_f32x2(uint32_t a) { float2 v; asm volatile("ld.shared.v2.f32 {%0, %1}, [%2];" : "=f"(v.x), "=f"(v.y) : "r"(a) : "memory"); return v; }
__device__ __forceinline__ uint2 lds_u32x2(uint32_t a) { uint2 v; asm volatile("ld.shared.v2.u32 {%0, %1}, [%2];" : "=r"(v.x), "=r"(v.y) : "r"(a) : "memory"); return v; }
__device__ __forceinline__ uint32_t lds_u32(uint32_t a) { uint32_t v; asm volatile("ld.shared.u32 %0, [%1];" : "=r"(v) : "r"(a) : "memory"); return v; }
__device__ __forceinline__ void sts_u32(uint32_t a, uint32_t v) { asm volatile("st.shared.u32 [%0], %1;" :: "r"(a), "r"(v) : "memory"); }
__device__ __forceinline__ void sts_u32x2(uint32_t a, uint32_t x, uint32_t y) { asm volatile("st.shared.v2.u32 [%0], {%1, %2};" :: "r"(a), "r"(x), "r"(y) : "memory"); }
__device__ __forceinline__ void sts_f32(uint32_t a, float v) { asm volatile("st.shared.f32 [%0], %1;" :: "r"(a), "f"(v) : "memory"); }
__device__ __forceinline__ void sts_f32x2(uint32_t a, float x, float y) { asm volatile("st.shared.v2.f32 [%0], {%1, %2};" :: "r"(a), "f"(x), "f"(y) : "memory"); }
__device__ __forceinline__ void sts_f32x4(uint32_t a, float x, float y, float z, float w) { asm volatile("st.shared.v4.f32 [%0], {%1, %2, %3, %4};" :: "r"(a), "f"(x), "f"(y), "f"(z), "f"(w) : "memory"); }

__device__ __forceinline__ uint4 lds_u32x4(uint32_t a) { uint4 v; asm volatile("ld.shared.v4.u32 {%0, %1, %2, %3}, [%4];" : "=r"(v.x), "=r"(v.y), "=r"(v.z), "=r"(v.w) : "r"(a) : "memory"); return v; }
__device__ __forceinline__ void sts_u32x4(uint32_t a, uint32_t x, uint32_t y, uint32_t z, uint32_t w) { asm volatile("st.shared.v4.u32 [%0], {%1, %2, %3, %4};" :: "r"(a), "r"(x), "r"(y), "r"(z), "r"(w) : "memory"); }
__device__ __forceinline__ void st_tagged(float* p, float v) {
  const uint32_t b = __float_as_uint(v);
  asm volatile("st.relaxed.gpu.global.u32 [%0], %1;" :: "l"(p), "r"(b == 0u ? 0x80000000u : b) : "memory");
}
__device__ __forceinline__ void st_tagged4(float* p, float x, float y, float z, float w) {
  const uint32_t a = __float_as_uint(x), b = __float_as_uint(y), c = __float_as_uint(z), d = __float_as_uint(w);
  asm volatile("st.relaxed.gpu.global.v4.u32 [%0], {%1, %2, %3, %4};" :: "l"(p), "r"(a == 0u ? 0x80000000u : a), "r"(b == 0u ? 0x80000000u : b),
               "r"(c == 0u ? 0x80000000u : c), "r"(d == 0u ? 0x80000000u : d) : "memory");
}
__device__ __forceinline__ void st_relaxed2(void* p, uint32_t a, uint32_t b) { asm volatile("st.relaxed.gpu.global.v2.u32 [%0], {%1, %2};" :: "l"(p), "r"(a), "r"(b) : "memory"); }
__device__ __forceinline__ float4 ld_tagged4(const float* p) {
  float4 v; asm volatile("ld.relaxed.gpu.global.v4.f32 {%0, %1, %2, %3}, [%4];" : "=f"(v.x), "=f"(v.y), "=f"(v.z), "=f"(v.w) : "l"(p) : "memory"); return v;
}
__device__ __forceinline__ bool tagged4(const float4& v) {
  return __float_as_uint(v.x) != 0u && __float_as_uint(v.y) != 0u && __float_as_uint(v.z) != 0u && __float_as_uint(v.w) != 0u;
}
__device__ __forceinline__ void hint_arrive(uint32_t* p) { asm volatile("red.relaxed.gpu.global.add.u32 [%0], 1;" :: "l"(p) : "memory"); }
__device__ __forceinline__ void hint_wait(const uint32_t* p, uint32_t target) {
  uint32_t v = 0u;
  #pragma unroll 1
  for (unsigned int i = 0; i < (1u << 22) && v < target; i++) asm volatile("ld.relaxed.gpu.global.u32 %0, [%1];" : "=r"(v) : "l"(p) : "memory");
}
__device__ __forceinline__ void fence_proxy_async_global() { asm volatile("fence.proxy.async.global;" ::: "memory"); }

#define H_SPLIT 1
#define X_DLY 1200
#define W_DLY 1900
#define W_FIRST 2200
#define PRE_B 2
template <int J0, int J1>
__device__ __forceinline__ void load_parts(float2 (&pa)[J1 - J0][4], int t2) {
  #pragma unroll
  for (int j = J0; j < J1; j++)
    #pragma unroll
    for (int k = 0; k < 4; k++)
      asm volatile("ld.relaxed.gpu.global.v2.f32 {%0, %1}, [%2];" : "=f"(pa[j - J0][k].x), "=f"(pa[j - J0][k].y)
                   : "l"(g_modpart + k * 2 * T_D + (t2 >> 7) * T_D + j * 256 + (t2 & 127) * 2) : "memory");
}
template <int J0, int J1>
__device__ __forceinline__ void finish_parts(float2 (&pa)[J1 - J0][4], bool loaded, int t2, uint32_t tab) {
  #pragma unroll 1
  for (unsigned int spin = 0; spin < (1u << 22); spin++) {
    if (!loaded) load_parts<J0, J1>(pa, t2);
    loaded = false;
    bool ok = true;
    #pragma unroll
    for (int j = 0; j < J1 - J0; j++)
      #pragma unroll
      for (int k = 0; k < 4; k++) ok &= (__float_as_uint(pa[j][k].x) != 0u) & (__float_as_uint(pa[j][k].y) != 0u);
    if (__all_sync(0xffffffffu, ok)) break;
  }
  #pragma unroll
  for (int j = J0; j < J1; j++) {
    const float2* q = pa[j - J0];
    const uint32_t m = pack_bf16(((q[0].x + q[1].x) + q[2].x) + q[3].x, ((q[0].y + q[1].y) + q[2].y) + q[3].y);
    sts_u32(tab + (t2 >> 7) * 2048 + j * 512 + (t2 & 127) * 4, t2 >= 128 ? badd2(m, 0x3F803F80u) : m);
  }
}
__device__ __forceinline__ int head_cb(uint32_t bid) { return (bid & 16) | ((bid & 3) << 2) | ((bid >> 2) & 3); }
__device__ __forceinline__ void head_phase(uint32_t bid, uint32_t scr, uint32_t xs, uint32_t b_x, uint32_t b_go, uint32_t b_head, int t2, uint32_t zero, const bf16* __restrict__ cvec, const bf16* __restrict__ w_mod) {
  const int lane = t2 & 31, w8 = t2 >> 5;
  const int cb = head_cb(bid), ks = bid >> 5;
  const bool early = (cb & 15) < 4 * H_SPLIT;
  const uint32_t ws = (xs - 32768 + (t2 >> 3) * 128 + (((t2 ^ (t2 >> 3)) & 7) << 4)) ^ zero;
  const float cv = __bfloat162float(cvec[ks * 256 + t2]);
  const bf16* wsrc = w_mod + (size_t)(ks * 256 + (t2 >> 3)) * (6 * T_D) + cb * 64 + (t2 & 7) * 8;
  if (early) {
    const uint64_t pol = policy_evict_first();
    #pragma unroll 2
    for (int i = 0; i < 8; i++)
      asm volatile("cp.async.cg.shared.global.L2::cache_hint [%0], [%1], 16, %2;" :: "r"(ws + i * 4096), "l"(wsrc + (size_t)i * 32 * 6 * T_D), "l"(pol) : "memory");
  }
  sts_f32(scr + t2 * 4, silu_bf(cv));
  named_bar_sync(6, 384);
  TL_MARK2(1, t2 == 0);
  uint4 xv[2][4];
  uint32_t mb2[2], ih[2], il[2];
  auto norm = [&](int j) {
    #pragma unroll
    for (int r = 0; r < 2; r++) {
      xv[r][j].x = ln_norm2b(xv[r][j].x, mb2[r], ih[r], il[r]); xv[r][j].y = ln_norm2b(xv[r][j].y, mb2[r], ih[r], il[r]);
      xv[r][j].z = ln_norm2b(xv[r][j].z, mb2[r], ih[r], il[r]); xv[r][j].w = ln_norm2b(xv[r][j].w, mb2[r], ih[r], il[r]);
    }
  };
  auto modulate = [&](int j) {
    const uint4 sa = lds_u32x4(scr + 8192 + j * 512 + lane * 16), c1 = lds_u32x4(scr + 8192 + 2048 + j * 512 + lane * 16);
    #pragma unroll
    for (int r = 0; r < 2; r++) {
      xv[r][j].x = badd2(bmul2(xv[r][j].x, c1.x), sa.x); xv[r][j].y = badd2(bmul2(xv[r][j].y, c1.y), sa.y);
      xv[r][j].z = badd2(bmul2(xv[r][j].z, c1.z), sa.z); xv[r][j].w = badd2(bmul2(xv[r][j].w, c1.w), sa.w);
    }
  };
  auto store = [&](int j) {
    #pragma unroll
    for (int r = 0; r < 2; r++) *reinterpret_cast<uint4*>(g_h + (size_t)(bid * 16 + 2 * w8 + r) * T_D + j * 256 + lane * 8) = xv[r][j];
  };
  #pragma unroll 1
  for (int ph = 0; ph < 2; ph++) {
    if ((ph == 0) == early) {
      asm volatile("cp.async.wait_all;" ::: "memory");
      if (!early) mbar_wait(b_x + 168, 0);
      float acc[8];
      #pragma unroll
      for (int j = 0; j < 8; j++) acc[j] = 0.f;
      #pragma unroll
      for (int i = 0; i < 8; i++) fma8(acc, lds_f32(scr + ((t2 >> 3) + 32 * i) * 4), lds_u32x4(ws + i * 4096));
      #pragma unroll
      for (int j = 0; j < 4; j++) { const bool up = lane & 16; acc[j] = (up ? acc[4 + j] : acc[j]) + __shfl_xor_sync(0xffffffffu, up ? acc[j] : acc[4 + j], 16); }
      #pragma unroll
      for (int j = 0; j < 2; j++) { const bool up = lane & 8; acc[j] = (up ? acc[2 + j] : acc[j]) + __shfl_xor_sync(0xffffffffu, up ? acc[j] : acc[2 + j], 8); }
      sts_f32x2(scr + 1024 + w8 * 256 + (lane & 7) * 32 + (lane >> 3) * 8, acc[0], acc[1]);
      named_bar_sync(5, 256);
      if (t2 < 64) {
        float sum = 0.f;
        #pragma unroll
        for (int i = 0; i < 8; i++) sum += lds_f32(scr + 1024 + i * 256 + t2 * 4);
        st_tagged(g_modpart + ks * 2 * T_D + cb * 64 + t2, sum);
        TL_MARK2(early ? 2 : 6, t2 == 0);
      }
    } else {
      float2 pa[H_SPLIT][4];
      mbar_wait(b_x, 0);
      TL_MARK2(18, t2 == 0);
      load_parts<0, H_SPLIT>(pa, t2);
      #pragma unroll
      for (int r = 0; r < 2; r++)
        #pragma unroll
        for (int j = 0; j < 4; j++) xv[r][j] = lds_u32x4(xs + (2 * w8 + r) * 2048 + j * 512 + lane * 16);
  {
    float st[4] = {0.f, 0.f, 0.f, 0.f};
    #pragma unroll
    for (int r = 0; r < 2; r++)
      #pragma unroll
      for (int j = 0; j < 4; j++) {
        float v[8];
        unpack8(xv[r][j], v);
        st[2 * r] += ((v[0] + v[1]) + (v[2] + v[3])) + ((v[4] + v[5]) + (v[6] + v[7]));
        st[2 * r + 1] += fmaf(v[0], v[0], fmaf(v[1], v[1], fmaf(v[2], v[2], v[3] * v[3]))) + fmaf(v[4], v[4], fmaf(v[5], v[5], fmaf(v[6], v[6], v[7] * v[7])));
      }
    #pragma unroll
    for (int k = 0; k < 2; k++) { const bool up = lane & 16; st[k] = (up ? st[2 + k] : st[k]) + __shfl_xor_sync(0xffffffffu, up ? st[k] : st[2 + k], 16); }
    #pragma unroll
    for (int o = 8; o > 0; o >>= 1) { st[0] += __shfl_xor_sync(0xffffffffu, st[0], o); st[1] += __shfl_xor_sync(0xffffffffu, st[1], o); }
    const float mean = st[0] * (1.0f / T_D);
    const float inv = rcp_approx(rbf(sqrt_approx(rbf(rbf(fmaxf(fmaf(-mean, mean, st[1] * (1.0f / T_D)), 0.f)) + 1e-05f))));
    const uint32_t m = pack_bf16(mean, mean), h = pack_bf16(inv - rbf(inv), inv);
    #pragma unroll
    for (int r = 0; r < 2; r++) {
      mb2[r] = __shfl_sync(0xffffffffu, m, 16 * r);
      const uint32_t hr = __shfl_sync(0xffffffffu, h, 16 * r);
      ih[r] = __byte_perm(hr, hr, 0x3232); il[r] = __byte_perm(hr, hr, 0x1010);
    }
  }
      #pragma unroll
      for (int j = 0; j < H_SPLIT; j++) norm(j);
      TL_MARK2(5, t2 == 0);
      finish_parts<0, H_SPLIT>(pa, true, t2, scr + 8192);
      named_bar_sync(5, 256);
      TL_MARK2(7, t2 == 0);
      #pragma unroll
      for (int j = 0; j < H_SPLIT; j++) { modulate(j); store(j); }
      named_bar_arrive(9, 288);
    }
  }
  #pragma unroll
  for (int j = H_SPLIT; j < 4; j++) norm(j);
  float2 pb[4 - H_SPLIT][4];
  finish_parts<H_SPLIT, 4>(pb, false, t2, scr + 8192);
  named_bar_sync(5, 256);
  TL_MARK2(17, t2 == 0);
  #pragma unroll
  for (int j = H_SPLIT; j < 4; j++) modulate(j);
  __syncwarp();
  if (lane == 0) mbar_arrive(b_head + (xv[1][3].w & zero));
  mbar_wait(b_go, 0);
  #pragma unroll
  for (int j = H_SPLIT; j < 4; j++) store(j);
  named_bar_arrive(8, 288);
}

#define MOD_AT (b_empty + 8)
#define MOD_SPLIT 16
__device__ __forceinline__ void mod_rest(uint32_t bid, uint32_t scr, uint32_t b_go, int t, const bf16* __restrict__ cvec, const bf16* __restrict__ w_mod, const bf16* __restrict__ w_r) {
  const int lane = t & 31;
  #pragma unroll 1
  for (int i = t; i < T_D / 2; i += 64) {
    const uint32_t c2 = *reinterpret_cast<const uint32_t*>(cvec + 2 * i);
    sts_u32(scr + i * 4, pack_bf16(silu_bf(bflo(c2)), silu_bf(bfhi(c2))));
  }
  named_bar_sync(11, 64);
  const bf16* wp = w_mod + (size_t)(2 * (t >> 2)) * (6 * T_D) + 2 * T_D + bid * 32 + (t & 3) * 8;
  float acc[8];
  #pragma unroll
  for (int i = 0; i < 8; i++) acc[i] = 0.f;
  #pragma unroll 1
  for (int i = 0; i < 32; i += 2) {
    if (i == MOD_SPLIT) mbar_wait_long(b_go, 0);
    const uint4 w0 = ldg_nc_v4(wp), w1 = ldg_nc_v4(wp + 6 * T_D), w2 = ldg_nc_v4(wp + 32 * 6 * T_D), w3 = ldg_nc_v4(wp + 33 * 6 * T_D);
    wp += 64 * 6 * T_D;
    const uint32_t s0 = lds_u32(scr + (i * 16 + (t >> 2)) * 4), s1 = lds_u32(scr + (i * 16 + 16 + (t >> 2)) * 4);
    fma8(acc, bflo(s0), w0); fma8(acc, bfhi(s0), w1); fma8(acc, bflo(s1), w2); fma8(acc, bfhi(s1), w3);
  }
  #pragma unroll
  for (int j = 0; j < 4; j++) { const bool up = lane & 16; acc[j] = (up ? acc[4 + j] : acc[j]) + __shfl_xor_sync(0xffffffffu, up ? acc[j] : acc[4 + j], 16); }
  #pragma unroll
  for (int j = 0; j < 2; j++) { const bool up = lane & 8; acc[j] = (up ? acc[2 + j] : acc[j]) + __shfl_xor_sync(0xffffffffu, up ? acc[j] : acc[2 + j], 8); }
  { const bool up = lane & 4; acc[0] = (up ? acc[1] : acc[0]) + __shfl_xor_sync(0xffffffffu, up ? acc[0] : acc[1], 4); }
  if (t >= 32) sts_f32(scr + 2048 + lane * 4, acc[0]);
  named_bar_sync(11, 64);
  if (__shfl_sync(0xffffffffu, t, 0) < 32) {
    const int kind = bid >> 5;
    float v = rbf(acc[0] + lds_f32(scr + 2048 + lane * 4));
    const int col = (bid & 31) * 32 + (lane & 3) * 8 + (lane >> 2);
    uint8_t* dst = g_col + (col >> 7) * 1536;
    if (kind == 2) v = rbf(1.0f + v);
    float vw = v * __bfloat162float(w_r[col]);
    if (kind == 2) {
      const int c = col & 127, i = (c & ~15) + ((c >> 1) & 3) * 4 + ((c >> 3) & 1) * 2 + (c & 1);
      reinterpret_cast<bf16*>(dst)[i] = __float2bfloat16_rn(vw);
      reinterpret_cast<bf16*>(dst)[128 + i] = __float2bfloat16_rn(vw - rbf(vw));
    }
    reinterpret_cast<bf16*>(dst + 512 + (kind & 1) * 512 + (kind >> 1) * 256)[col & 127] = __float2bfloat16_rn(v);
    #pragma unroll
    for (int o = 16; o > 0; o >>= 1) vw += __shfl_xor_sync(0xffffffffu, vw, o);
    if (lane == 0 && (kind == 1 || kind == 2)) g_scal[95 - bid] = vw;
  }
  #pragma unroll 1
  for (int i = bid * 64 + t; i < (int)(sizeof(g_mail) / 16); i += 128 * 64) reinterpret_cast<uint4*>(&g_mail)[i] = make_uint4(0u, 0u, 0u, 0u);
  named_bar_sync(11, 64);
  if (t == 0) red_release_add(&g_hcnt[0], 1u);
}

constexpr int AT_NBLK = T_SEQ / 128;
constexpr float AT_HEAD = 7.0f;
#define WO_LATE 12
#define QP_STAG 3
#define AT_SPLIT 28
#define AT_PIN 12
#define PINB 4
constexpr int AT_NFULL = 124;
constexpr int AT_PREG = 40, AT_CREG = 232;
constexpr uint32_t AT_SQ = 5 * 32768;
constexpr float AT_C = 0.08838834764831845f * 1.4426950408889634f;
constexpr float AT_RAW_LO = -16.0f, AT_RAW_HI = 24.0f;
constexpr float AT_RAW_SUM = 281474976710656.0f, AT_RAW_MIN = 9.094947017729282e-13f;
constexpr uint32_t AT_SBAR = AT_SQ + 65536 + 256;
constexpr uint32_t AT_SMEM = AT_SQ + 65536 + 3072;

__device__ __forceinline__ uint32_t ring_slot(uint32_t t) { return t - 5u * ((t * 205u) >> 10); }
__device__ __forceinline__ uint32_t qp_pos(uint32_t j, uint32_t it) { return 4u * it + (j & 3u) + ((j & 3u) == 3u ? it : 0u); }
__device__ __forceinline__ uint32_t ring_par(uint32_t t) { return ((t * 205u) >> 10) & 1u; }
__device__ __forceinline__ void softmax_rowmax(const float (&s)[64], float& mx0, float& mx1) {
  float a0 = fmaxf(s[0], s[1]), a1 = fmaxf(s[4], s[5]), a2 = fmaxf(s[8], s[9]), a3 = fmaxf(s[12], s[13]);
  float b0 = fmaxf(s[2], s[3]), b1 = fmaxf(s[6], s[7]), b2 = fmaxf(s[10], s[11]), b3 = fmaxf(s[14], s[15]);
  #pragma unroll
  for (int j = 4; j < 16; j += 4) {
    a0 = fmaxf(a0, fmaxf(s[4 * j + 0], s[4 * j + 1]));  b0 = fmaxf(b0, fmaxf(s[4 * j + 2], s[4 * j + 3]));
    a1 = fmaxf(a1, fmaxf(s[4 * j + 4], s[4 * j + 5]));  b1 = fmaxf(b1, fmaxf(s[4 * j + 6], s[4 * j + 7]));
    a2 = fmaxf(a2, fmaxf(s[4 * j + 8], s[4 * j + 9]));  b2 = fmaxf(b2, fmaxf(s[4 * j + 10], s[4 * j + 11]));
    a3 = fmaxf(a3, fmaxf(s[4 * j + 12], s[4 * j + 13])); b3 = fmaxf(b3, fmaxf(s[4 * j + 14], s[4 * j + 15]));
  }
  mx0 = fmaxf(fmaxf(a0, a1), fmaxf(a2, a3));
  mx1 = fmaxf(fmaxf(b0, b1), fmaxf(b2, b3));
  mx0 = fmaxf(mx0, __shfl_xor_sync(0xffffffffu, mx0, 1));
  mx1 = fmaxf(mx1, __shfl_xor_sync(0xffffffffu, mx1, 1));
  mx0 = fmaxf(mx0, __shfl_xor_sync(0xffffffffu, mx0, 2));
  mx1 = fmaxf(mx1, __shfl_xor_sync(0xffffffffu, mx1, 2));
}
__device__ __forceinline__ void softmax_sub(float (&s)[64], float mc0, float mc1) {
  #pragma unroll
  for (int j = 0; j < 16; j++) { s[4 * j] -= mc0; s[4 * j + 1] -= mc0; s[4 * j + 2] -= mc1; s[4 * j + 3] -= mc1; }
}
template <int LO, int HI>
__device__ __forceinline__ void softmax_exp(float (&s)[64]) {
  #pragma unroll
  for (int i = LO; i < HI; i++) s[i] = ex2_approx(s[i]);
}
__device__ __forceinline__ bool softmax_mode(const float (&s)[64], float& mc0, float& mc1) {
  softmax_rowmax(s, mc0, mc1);
  const bool raw = __all_sync(0xffffffffu, mc0 >= AT_RAW_LO && mc0 <= AT_RAW_HI && mc1 >= AT_RAW_LO && mc1 <= AT_RAW_HI);
  mc0 += AT_HEAD; mc1 += AT_HEAD;
  return raw;
}
__device__ __forceinline__ void rowsum_p(const uint32_t (&p)[32], uint32_t& t0, uint32_t& t1) {
  uint32_t a[16];
  #pragma unroll
  for (int i = 0; i < 8; i++) { a[2 * i] = badd2(p[4 * i], p[4 * i + 2]); a[2 * i + 1] = badd2(p[4 * i + 1], p[4 * i + 3]); }
  #pragma unroll
  for (int i = 0; i < 4; i++) { a[2 * i] = badd2(a[4 * i], a[4 * i + 2]); a[2 * i + 1] = badd2(a[4 * i + 1], a[4 * i + 3]); }
  t0 = badd2(badd2(a[0], a[2]), badd2(a[4], a[6]));
  t1 = badd2(badd2(a[1], a[3]), badd2(a[5], a[7]));
}
__device__ __forceinline__ void add_rowsum(const uint32_t (&p)[32], float& l0, float& l1) {
  uint32_t t0, t1;
  rowsum_p(p, t0, t1);
  l0 += bflo(t0) + bfhi(t0); l1 += bflo(t1) + bfhi(t1);
}
__device__ __forceinline__ void pack_p(uint32_t (&p)[32], const float (&s)[64]) {
  #pragma unroll
  for (int i = 0; i < 32; i++) p[i] = pack_bf16(s[2 * i], s[2 * i + 1]);
}
__device__ __noinline__ void attn_rows_exact(uint32_t bid, uint32_t sq, uint32_t so, int hsel, const bf16* __restrict__ kh, const bf16* __restrict__ vh) {
  const int warp = (threadIdx.x >> 5) & 3, lane = threadIdx.x & 31;
  const size_t hofs = (size_t)((bid < 128 ? bid >> 4 : 15) * 2 + hsel) * T_SEQ * T_DH;
  kh += hofs; vh += hofs;
  #pragma unroll 1
  for (int r = 16 * warp; r < 16 * warp + 16; r++) {
    const uint32_t ad = (lane >> 4) * 16384 + r * 128 + ((((lane & 15) >> 1) ^ (r & 7)) << 4) + (lane & 1) * 8;
    uint2 qv; asm volatile("ld.shared.v2.u32 {%0, %1}, [%2];" : "=r"(qv.x), "=r"(qv.y) : "r"(sq + ad) : "memory");
    const float q0 = bflo(qv.x), q1 = bfhi(qv.x), q2 = bflo(qv.y), q3 = bfhi(qv.y);
    float m = -INFINITY, l = 0.f, o0 = 0.f, o1 = 0.f, o2 = 0.f, o3 = 0.f;
    #pragma unroll 1
    for (int key = 0; key < T_SEQ; key++) {
      const uint2 kv = *reinterpret_cast<const uint2*>(kh + (size_t)key * T_DH + lane * 4);
      const uint2 vv = *reinterpret_cast<const uint2*>(vh + (size_t)key * T_DH + lane * 4);
      float sc = (q0 * bflo(kv.x) + q1 * bfhi(kv.x)) + (q2 * bflo(kv.y) + q3 * bfhi(kv.y));
      #pragma unroll
      for (int o = 16; o > 0; o >>= 1) sc += __shfl_xor_sync(0xffffffffu, sc, o);
      const float mn = fmaxf(m, sc);
      const float al = (m == mn) ? 1.0f : ex2_approx(m - mn), p = rbf(ex2_approx(sc - mn));
      m = mn;
      l = fmaf(l, al, p);
      o0 = fmaf(o0, al, p * bflo(vv.x)); o1 = fmaf(o1, al, p * bfhi(vv.x));
      o2 = fmaf(o2, al, p * bflo(vv.y)); o3 = fmaf(o3, al, p * bfhi(vv.y));
    }
    const float inv = rcp_approx(l);
    asm volatile("st.shared.v2.u32 [%0], {%1, %2};" :: "r"(so + ad), "r"(pack_bf16(o0 * inv, o1 * inv)), "r"(pack_bf16(o2 * inv, o3 * inv)) : "memory");
  }
}
__device__ __forceinline__ void issue_qk(float (&s)[64], const uint32_t (&q)[32], uint32_t k_lo) {
  wgmma_fence();
  wgmma_m64n128k16_rs<0>(s, q[0], q[1], q[2], q[3], k_lo, 0);
  wgmma_m64n128k16_rs<2>(s, q[4], q[5], q[6], q[7], k_lo, 1);
  wgmma_m64n128k16_rs<4>(s, q[8], q[9], q[10], q[11], k_lo, 1);
  wgmma_m64n128k16_rs<6>(s, q[12], q[13], q[14], q[15], k_lo, 1);
  wgmma_m64n128k16_rs<1024>(s, q[16], q[17], q[18], q[19], k_lo, 1);
  wgmma_m64n128k16_rs<1026>(s, q[20], q[21], q[22], q[23], k_lo, 1);
  wgmma_m64n128k16_rs<1028>(s, q[24], q[25], q[26], q[27], k_lo, 1);
  wgmma_m64n128k16_rs<1030>(s, q[28], q[29], q[30], q[31], k_lo, 1);
  wgmma_commit();
}
__device__ __forceinline__ void issue_pv(float (&o)[64], const uint32_t (&p)[32], uint32_t v_lo, int accumulate) {
  wgmma_fence();
  wgmma_m64n128k16_rs_tb<0>(o, p[0], p[1], p[2], p[3], v_lo, accumulate);
  wgmma_m64n128k16_rs_tb<128>(o, p[4], p[5], p[6], p[7], v_lo, 1);
  wgmma_m64n128k16_rs_tb<256>(o, p[8], p[9], p[10], p[11], v_lo, 1);
  wgmma_m64n128k16_rs_tb<384>(o, p[12], p[13], p[14], p[15], v_lo, 1);
  wgmma_m64n128k16_rs_tb<512>(o, p[16], p[17], p[18], p[19], v_lo, 1);
  wgmma_m64n128k16_rs_tb<640>(o, p[20], p[21], p[22], p[23], v_lo, 1);
  wgmma_m64n128k16_rs_tb<768>(o, p[24], p[25], p[26], p[27], v_lo, 1);
  wgmma_m64n128k16_rs_tb<896>(o, p[28], p[29], p[30], p[31], v_lo, 1);
  wgmma_commit();
}
__device__ __forceinline__ void block_end(uint32_t zero, uint32_t bar) {
  #pragma unroll 1
  for (uint32_t i = 0; i < zero; i++) mbar_arrive(bar);
}
__device__ __forceinline__ void rescale_o(float (&o)[64], float al0, float al1) {
  #pragma unroll
  for (int j = 0; j < 16; j++) { o[4 * j] *= al0; o[4 * j + 1] *= al0; o[4 * j + 2] *= al1; o[4 * j + 3] *= al1; }
}

__device__ __forceinline__ void stage_o(const float (&o)[64], float i0, float i1, uint32_t dst, int lane) {
  #pragma unroll
  for (int J = 0; J < 16; J += 2)
    stmatrix_x4(dst + (J >> 3) * 16384 + ((((J & 7) + (lane >> 4)) ^ (lane & 7)) << 4),
                pack_bf16(o[4 * J + 0] * i0, o[4 * J + 1] * i0), pack_bf16(o[4 * J + 2] * i1, o[4 * J + 3] * i1),
                pack_bf16(o[4 * J + 4] * i0, o[4 * J + 5] * i0), pack_bf16(o[4 * J + 6] * i1, o[4 * J + 7] * i1));
}
__device__ __forceinline__ bool finish_l(float& l0, float& l1) {
  l0 += __shfl_xor_sync(0xffffffffu, l0, 1); l1 += __shfl_xor_sync(0xffffffffu, l1, 1);
  l0 += __shfl_xor_sync(0xffffffffu, l0, 2); l1 += __shfl_xor_sync(0xffffffffu, l1, 2);
  const bool redo = __any_sync(0xffffffffu, !(l0 <= AT_RAW_SUM && l1 <= AT_RAW_SUM && l0 >= AT_RAW_MIN && l1 >= AT_RAW_MIN));
  l0 = rcp_approx(l0); l1 = rcp_approx(l1);
  return redo;
}
template <int J0>
__device__ __forceinline__ void stage_q(const float (&acc)[128], float c, uint32_t dst, int lane) {
  #pragma unroll
  for (int J = J0; J < J0 + 16; J += 2)
    stmatrix_x4(dst + (J >> 3) * 16384 + ((((J & 7) + (lane >> 4)) ^ (lane & 7)) << 4),
                pack_bf16(acc[4 * J + 0] * c, acc[4 * J + 1] * c), pack_bf16(acc[4 * J + 2] * c, acc[4 * J + 3] * c),
                pack_bf16(acc[4 * J + 4] * c, acc[4 * J + 5] * c), pack_bf16(acc[4 * J + 6] * c, acc[4 * J + 7] * c));
}
__device__ __forceinline__ void store_o(const CUtensorMap* tmO, uint32_t src, int head, int row) {
  tma_store_2d(tmO, src, head * T_DH, row);
  tma_store_2d(tmO, src + 16384, head * T_DH + 64, row);
  bulk_commit();
}
__device__ __forceinline__ void mma_bf16(float (&d)[4], uint32_t a0, uint32_t a1, uint32_t a2, uint32_t a3, uint32_t b0, uint32_t b1) {
  asm volatile("mma.sync.aligned.m16n8k16.row.col.f32.bf16.bf16.f32 {%0, %1, %2, %3}, {%4, %5, %6, %7}, {%8, %9}, {%0, %1, %2, %3};"
               : "+f"(d[0]), "+f"(d[1]), "+f"(d[2]), "+f"(d[3]) : "r"(a0), "r"(a1), "r"(a2), "r"(a3), "r"(b0), "r"(b1));
}
struct GemvSel { uint32_t lo0, hi0, lo1, hi1; };
__device__ __forceinline__ GemvSel gemv_sel(int lane) {
  const uint32_t lo = (lane & 8) ? 0x1044u : 0x4410u, hi = (lane & 8) ? 0x3244u : 0x4432u;
  GemvSel s; s.lo0 = (lane & 16) ? 0x4444u : lo; s.hi0 = (lane & 16) ? 0x4444u : hi; s.lo1 = (lane & 16) ? lo : 0x4444u; s.hi1 = (lane & 16) ? hi : 0x4444u;
  return s;
}
#define GEMV_B0(j, h, s) __byte_perm((j) < 2 ? (h).x : (h).y, 0u, ((j) & 1) ? (s).hi0 : (s).lo0)
#define GEMV_B1(j, h, s) __byte_perm((j) < 2 ? (h).x : (h).y, 0u, ((j) & 1) ? (s).hi1 : (s).lo1)
__device__ __forceinline__ float4 gemv_out(const float (&d)[4], int lane) {
  const bool tk = lane & 1;
  const float r0 = __shfl_xor_sync(0xffffffffu, tk ? d[0] : d[1], 1), r1 = __shfl_xor_sync(0xffffffffu, tk ? d[2] : d[3], 1);
  return tk ? make_float4(r0, d[1], r1, d[3]) : make_float4(d[0], r0, d[2], r1);
}
#define OG_NG 8
#define PUT_N 2
#define H_STAG 2
#define AL_P 60
#define AL_SLEEP 1200
#define AL_MAX 800
#define POLL_NS 500
#define OG_PROF 0xDDCBAA98u
#define RK_P 24
__host__ __device__ constexpr int og_pre(int tile) { return (OG_PROF >> ((tile >> 4) * 4)) & 15; }
constexpr int OG_PRE2 = og_pre(127), OG_HSUM = og_pre(0) + og_pre(16) + og_pre(32) + og_pre(48) + og_pre(64) + og_pre(80) + og_pre(96);
#define OG_JOBS 7
#define OG_GRP 6
#define LD_FIRST 2
#define LD_STAG (OG_GRP / 2)
constexpr int OG_ST = 5, OG_NKB = T_DQKV / 64 - og_pre(0), OG_MOE = T_F / 32;
__device__ __forceinline__ int pre_kb(int i) { return (i >> 1) * 4 + (i & 1); }
__device__ __forceinline__ int own_kb(int i, int pre) { return i < (pre & ~1) ? pre_kb(i) + 2 : i + pre; }
constexpr int OG_POS = 8;
constexpr uint32_t OG_STAGE = 32768;
constexpr uint32_t OG_SCOL = AT_SBAR + 512;
constexpr uint32_t OG_SMISC = AT_SBAR + 2048;
constexpr uint32_t OG_SWD = AT_SQ, OG_PSLOT = AT_SQ;
constexpr uint32_t OG_XSLOT = AT_SQ + 32768;
constexpr uint32_t OG_OSLOT = 1 * OG_STAGE;
constexpr uint32_t OG_SRED = 3 * OG_STAGE;
constexpr uint32_t OG_SH2 = OG_SRED + 24576;
constexpr uint32_t OG_SSTAT = OG_SRED + 16384;
constexpr uint32_t OG_SGU = OG_SRED + 8192;
constexpr uint32_t OG_SFIN = OG_SGU + 256;
#define OGM 2
#define OG_MT(b) ((((b) >> OGM) & 15) ^ (((b) & 64) ? 15 : 0))
#define OG_NT(b) (((b) & ((1 << OGM) - 1)) + (((b) >> (4 + OGM)) << OGM))
__device__ __forceinline__ int tail_tile(uint32_t sbase) { mbar_wait_long(sbase + AT_SBAR + 336, 0); return (int)lds_u32(sbase + AT_SBAR + 408); }
#define TAIL_SETUP \
  const uint32_t bar_full = sbase + AT_SBAR, bar_empty = bar_full + 40; \
  const uint32_t bar_wd = bar_full + 168, bar_col = bar_full + 176, bar_out = bar_full + 184, bar_end = bar_full + 192; \
  const uint32_t bar_key = bar_full + 200, bar_h2 = bar_full + 208, bar_sel = bar_full + 216; \
  const int mt = OG_MT(tb), nt = OG_NT(tb); \
  const int m0 = mt * 128, n0 = nt * 128; \
  const bool has_moe = (int)bid < OG_MOE; \
  (void)bar_empty; (void)bar_wd; (void)bar_col; (void)bar_out; (void)bar_end; (void)bar_key; (void)bar_h2; (void)bar_sel; (void)m0; (void)n0; (void)has_moe;

__device__ __forceinline__ void tail_producer(uint32_t bid, uint32_t sbase, uint32_t ph, uint64_t pol, const CUtensorMap* tmA, const CUtensorMap* tmB, const CUtensorMap* tmD) {
  const int tb = tail_tile(sbase);
  TAIL_SETUP
  uint32_t stage = OG_POS % OG_ST;
  int kb = 0;
  #pragma unroll 1
  for (int seg = 0; seg < 2; seg++) {
    mbar_wait(bar_full + 264 + 80 * seg, 0);
    fence_proxy_async_global();
    const int end = 32 + 32 * seg - og_pre(tb);
    #pragma unroll 1
    for (; kb < end; kb++) {
      const uint32_t fb = bar_full + 8 * stage, sa = sbase + stage * OG_STAGE;
      const int k0 = own_kb(kb, og_pre(tb)) * 64;
      mbar_wait(bar_empty + 8 * stage, ph);
      mbar_expect_tx(fb, OG_STAGE);
      tma_load_3d_hint(sa + 16384, tmB, k0, 2 * nt, fb, pol);
      tma_load_2d_hint(sa, tmA, k0, m0, fb, pol);
      if (++stage == OG_ST) { stage = 0; ph ^= 1; }
    }
  }
  if (has_moe) {
    stage += stage & 1;
    mbar_wait(bar_empty + 8 * stage, ph);
    mbar_expect_tx(bar_wd, OG_STAGE);
    tma_load_3d_hint(sbase + stage * OG_STAGE, tmD, bid * 32, 8, bar_wd, pol);
  }
}

__device__ __forceinline__ uint32_t out2(uint32_t x1, uint32_t mb2, uint32_t ih, uint32_t il, uint32_t c1, uint32_t sb, uint32_t gb) {
  const uint32_t h2 = badd2(bmul2(ln_norm2b(x1, mb2, ih, il), c1), sb);
  return badd2(x1, bmul2(gb, bfma2(h2, 0u, h2)));
}
#define X_PACE 200
#define Y_SLACK 96
#define OG_STAG 3
#define X_PACE2 100
#define POLL_NS2 100
#define WD_PACE 300
__device__ __forceinline__ void tail_exchange(uint32_t bid, uint32_t sbase, const bf16* __restrict__ w_down, const bf16* __restrict__ w_r, const bf16* __restrict__ x, bf16* __restrict__ out) {
    const int lane = threadIdx.x & 31, wi = __shfl_sync(0xffffffffu, threadIdx.x >> 5, 0);
    if (wi == 3) {
      uint32_t a = bid, b = 0u;
      if (bid < AT_NFULL) mbar_wait_long(sbase + AT_SBAR + 312, 0);
      if (bid < OG_MOE) {
        asm volatile("mov.u32 %0, %%globaltimer_lo;" : "=r"(a));
        if (lane == 0 && (bid & 15) == 0) asm volatile("st.relaxed.gpu.global.u32 [%0], %1;" :: "l"(g_hcnt + 8 + (bid >> 4)), "r"((a & ~15u) | 8u | (bid >> 4)) : "memory");
        #pragma unroll 1
        for (unsigned int spin = 0; spin < (1u << 22) && __any_sync(0xffffffffu, b == 0u); spin++) {
          __nanosleep(200);
          asm volatile("ld.relaxed.gpu.global.u32 %0, [%1];" : "=r"(b) : "l"(g_hcnt + 8 + min(lane, 6)) : "memory");
        }
        a = __popc(__ballot_sync(0xffffffffu, b < __shfl_sync(0xffffffffu, b, bid >> 4)) & 127u) * 16 + (bid & 15);
      }
      if (lane == 0) {
        sts_u32(sbase + AT_SBAR + 408, a);
        mbar_arrive(sbase + AT_SBAR + 336);
        b = 0u;
        if (bid < AT_NFULL) {
          unsigned int* tm = g_hcnt + 32 * (1 + (bid >> 4)) + 8;
          mbar_wait_long(sbase + AT_SBAR + 312, 1);
          asm volatile("mov.u32 %0, %%globaltimer_lo;" : "=r"(a));
          asm volatile("red.relaxed.gpu.global.max.u32 [%0], %1;" :: "l"(tm), "r"(a) : "memory");
          __nanosleep(AL_SLEEP);
          asm volatile("ld.relaxed.gpu.global.u32 %0, [%1];" : "=r"(b) : "l"(tm) : "memory");
          b -= a;
        }
        sts_u32(sbase + AT_SBAR + 412, b < AL_MAX ? b * 13 / 8 : 0u);
        mbar_arrive(sbase + AT_SBAR + 320);
      }
      named_bar_sync(15, 32);
    }
    const int tb = __shfl_sync(0xffffffffu, tail_tile(sbase), 0);
    TAIL_SETUP
    if (wi == 3) {
      mbar_wait_long(bar_full + 344, 0);
      float a = g_scal[lane], b = g_scal[32 + lane];
      #pragma unroll
      for (int i = 0; i < 3; i++) {
        const uint4 v = *reinterpret_cast<const uint4*>(g_col + nt * 1536 + i * 512 + lane * 16);
        sts_u32x4(sbase + OG_SCOL + i * 512 + lane * 16, v.x, v.y, v.z, v.w);
      }
      #pragma unroll
      for (int o = 16; o > 0; o >>= 1) { a += __shfl_xor_sync(0xffffffffu, a, o); b += __shfl_xor_sync(0xffffffffu, b, o); }
      if (lane == 0) sts_f32x2(sbase + OG_SMISC, a, b);
      const uint64_t pol = policy_evict_first();
      #pragma unroll 1
      for (int r = lane >> 4; r < 128; r += 4) {
        __nanosleep(X_PACE);
        if (X_PACE2) __nanosleep(X_PACE2);
        #pragma unroll
        for (int j = 0; j < 4; j += 2)
          asm volatile("cp.async.cg.shared.global.L2::cache_hint [%0], [%1], 16, %2;" :: "r"(sbase + OG_XSLOT + (lane & 8) * 2048 + (r + j) * 128 + (((lane ^ (r + j)) & 7) << 4)),
                       "l"(x + (size_t)(m0 + r + j) * T_D + n0 + (lane & 15) * 8), "l"(pol) : "memory");
      }
      asm volatile("cp.async.wait_all;" ::: "memory");
      __syncwarp();
      if (lane == 0) mbar_arrive(bar_col);
    } else if (wi == 2) {
      if (elect_one()) {
        const uint32_t b_free = bar_full + (bid < AT_NFULL ? 80 : 160);
        mbar_wait_long(b_free, 1);
        #pragma unroll 1
        for (unsigned int i = 0; i < (1u << 20) && ld_acquire(&g_hcnt[32 * (1 + (tb >> 3)) + 4 + ((tb >> 1) & 3)]) == 0u; i++) __nanosleep((tb >> 4) == 6 ? POLL_NS2 : POLL_NS);
        TL_MARK2(23, true);
        fence_proxy_async_global();
        TL_MARK2(4, true);
        mbar_expect_tx(bar_full + 272, 32768);
        bulk_load_hint(sbase + OG_PSLOT, g_pre + tb * 2048, 32768, bar_full + 272, policy_evict_first());
      }
      named_bar_sync(14, 32);
      if (has_moe) {
        mbar_wait_long(bar_full + 304, 0);
        const uint64_t pol = policy_evict_first();
        #pragma unroll 1
        for (int r = 0; r < 32; r++) {
          __nanosleep(WD_PACE);
          #pragma unroll
          for (int j = 0; j < 2; j++)
            asm volatile("cp.async.cg.shared.global.L2::cache_hint [%0], [%1], 16, %2;" :: "r"(sbase + OG_SWD + (4 * j + (lane >> 3)) * 4096 + r * 128 + (((lane ^ r) & 7) << 4)),
                         "l"((const uint8_t*)w_down + (size_t)bid * 65536 + r * 2048 + j * 512 + lane * 16), "l"(pol) : "memory");
        }
        asm volatile("cp.async.wait_all;" ::: "memory");
        __syncwarp();
        if (lane == 0) mbar_arrive(bar_wd);
      }
    }
    const uint4 wrv = ldg_nc_v4(w_r + threadIdx.x * 8);
    mbar_wait_long(bar_end, 0);
    TL_MARK2(22, lane == 0);
    if (wi == 0) {
      uint32_t k1 = 0u, k2 = 0u;
      #pragma unroll 1
      for (unsigned int spin = 0; spin < (1u << 22) && __any_sync(0xffffffffu, k1 == 0u); spin++) asm volatile("ld.relaxed.gpu.global.u32 %0, [%1];" : "=r"(k1) : "l"(g_key + lane) : "memory");
      TL_MARK2(28, lane == 0);
      warp_top2(k1, k2);
      if (lane == 0) {
        const uint32_t r1 = 0xffffu - (k1 & 0xffffu), r2 = 0xffffu - (k2 & 0xffffu);
        sts_u32x4(sbase + OG_SMISC + 64, r1, r2, (r1 >> 7) * 2, (r2 >> 7) * 2 + ((r1 >> 7) == (r2 >> 7)));
        mbar_arrive(bar_sel);
      }
    } else if (wi < 3) {
          mbar_wait(bar_key, 0);
          const uint4 kk = lds_u32x4(sbase + OG_SSTAT + 1024 + lane * 16);
          uint32_t k1 = max(kk.x, kk.y), k2 = min(kk.x, kk.y);
          k2 = max(max(k2, min(kk.z, kk.w)), min(k1, max(kk.z, kk.w))); k1 = max(k1, max(kk.z, kk.w));
          warp_top2(k1, k2);
          if (wi == 1) {
            if (lane == 0) {
              if (nt == (mt & 7)) st_relaxed2(g_key + mt * 2, k1, k2);
              sts_u32x2(sbase + OG_SMISC + 96, (~k1 >> 4) & 7u, (~k2 >> 4) & 7u);
              mbar_arrive(bar_full + 352);
            }
            TL_MARK2(27, lane == 0);
          } else {
            const uint32_t r = (~((lane & 16) ? k2 : k1)) & 127u, ch = lane & 15;
            const uint2 st = lds_u32x2(sbase + OG_SSTAT + r * 8);
            const uint4 xc = lds_u32x4(sbase + OG_XSLOT + (ch >> 3) * 16384 + r * 128 + (((ch ^ r) & 7) << 4));
            const uint4 c1 = lds_u32x4(sbase + OG_SCOL + 768 + ch * 16), sh = lds_u32x4(sbase + OG_SCOL + 1024 + ch * 16);
            const float inr = __uint_as_float(st.y);
            float* dst = reinterpret_cast<float*>(g_cand + (mt * 2 + (lane >> 4)) * 256 + nt * 16 + ch);
            st_tagged4(dst + 512, __uint_as_float(ln_mod2(xc.x, st.x, inr, c1.x, sh.x)), __uint_as_float(ln_mod2(xc.y, st.x, inr, c1.y, sh.y)),
                       __uint_as_float(ln_mod2(xc.z, st.x, inr, c1.z, sh.z)), __uint_as_float(ln_mod2(xc.w, st.x, inr, c1.w, sh.w)));
            st_tagged4(dst, __uint_as_float(xc.x), __uint_as_float(xc.y), __uint_as_float(xc.z), __uint_as_float(xc.w));
          }
    }
    mbar_wait(bar_sel, 0);
    const uint4 sel = lds_u32x4(sbase + OG_SMISC + 64);
    const int sel0 = (int)sel.x, sel1 = (int)sel.y;
    {
      const float* src0 = reinterpret_cast<const float*>(g_cand + sel.z * 256 + 128 + threadIdx.x);
      const float* src1 = reinterpret_cast<const float*>(g_cand + sel.w * 256 + 128 + threadIdx.x);
      float4 h0, h1;
      #pragma unroll 1
      for (unsigned int spin = 0; spin < (1u << 20); spin++) { h0 = ld_tagged4(src0); h1 = ld_tagged4(src1); if (__all_sync(0xffffffffu, tagged4(h0) & tagged4(h1))) break; }
      sts_f32x4(sbase + OG_SH2 + threadIdx.x * 16, h0.x, h0.y, h0.z, h0.w);
      sts_f32x4(sbase + OG_SH2 + 2048 + threadIdx.x * 16, h1.x, h1.y, h1.z, h1.w);
      __syncwarp();
      if (lane == 0) mbar_arrive(bar_h2);
      TL_MARK2(12, lane == 0);
      if (bid >> 6) h0 = h1;
      float v[8], wr[8];
      unpack8(make_uint4(__float_as_uint(h0.x), __float_as_uint(h0.y), __float_as_uint(h0.z), __float_as_uint(h0.w)), v); unpack8(wrv, wr);
      float r = 0.f;
      #pragma unroll
      for (int i = 0; i < 8; i++) r = fmaf(v[i], wr[i], r);
      #pragma unroll
      for (int o = 16; o > 0; o >>= 1) r += __shfl_xor_sync(0xffffffffu, r, o);
      if (lane == 0) sts_f32(sbase + OG_SMISC + 192 + wi * 4, r);
    }
    mbar_wait(bar_out, 0);
    {
      const uint2 cg = lds_u32x2(sbase + OG_SMISC + 96);
      #pragma unroll
      for (int i = 0; i < 4; i++) {
        const int r = (i < 2 ? cg.x : cg.y) * 16 + (i & 1) * 8 + (threadIdx.x >> 4), ch = threadIdx.x & 15;
        if (m0 + r != sel0 && m0 + r != sel1)
          *reinterpret_cast<uint4*>(out + (size_t)(m0 + r) * T_D + n0 + ch * 8) =
              lds_u32x4(sbase + OG_OSLOT + (ch >> 3) * 16384 + r * 128 + (((ch & 7) ^ (r & 7)) << 4));
      }
    }
    if (bid == 0 && threadIdx.x < 68) *reinterpret_cast<uint4*>(g_hcnt + 32 * (threadIdx.x >> 2) + 4 * (threadIdx.x & 3)) = make_uint4(0u, 0u, 0u, 0u);
    if (threadIdx.x < 64) g_modpart[bid * 64 + threadIdx.x] = 0.f;
    {
      const int tk = bid >> 6, c0 = (bid & 63) * 16;
      const uint32_t gb2 = *reinterpret_cast<const uint32_t*>(g_col + (c0 >> 7) * 1536 + 512 + 768 + ((c0 & 127) + (threadIdx.x & 14)) * 2);
      const uint32_t* xp = reinterpret_cast<const uint32_t*>(g_cand + (tk ? sel.w : sel.z) * 256) + ((c0 + (threadIdx.x & 14)) >> 1);
      uint32_t x2 = 0u;
      #pragma unroll 1
      for (unsigned int spin = 0; spin < (1u << 20) && __any_sync(0xffffffffu, x2 == 0u); spin++) asm volatile("ld.relaxed.gpu.global.u32 %0, [%1];" : "=r"(x2) : "l"(xp) : "memory");
      const float* src = g_ypart + (size_t)((threadIdx.x >> 2) * 2 + tk) * T_D + c0 + (threadIdx.x & 3) * 4;
      const bool four = threadIdx.x < (OG_MOE - 96) * 4;
      named_bar_sync(10, 128);
      const uint4 rp = lds_u32x4(sbase + OG_SMISC + 192);
      const float rs = rbf(sigmoid_f(rbf((__uint_as_float(rp.x) + __uint_as_float(rp.y)) + (__uint_as_float(rp.z) + __uint_as_float(rp.w)))));
      const uint32_t h2p = lds_u32(sbase + OG_SH2 + tk * 2048 + (c0 + (threadIdx.x & 14)) * 2);
      const float fh = (lane & 1) ? bfhi(h2p) : bflo(h2p), fz = rbf(fh * 0.0f), fx = (lane & 1) ? bfhi(x2) : bflo(x2), fg = (lane & 1) ? bfhi(gb2) : bflo(gb2);
      bf16* dst = out + (size_t)(tk ? sel1 : sel0) * T_D + c0 + threadIdx.x;
      if (threadIdx.x == 0) hint_wait(CNT_Y, (uint32_t)(OG_MOE - Y_SLACK));
      named_bar_sync(10, 128);
      float4 p0, p1, p2, p3;
      #pragma unroll 1
      for (unsigned int spin = 0; spin < (1u << 20); spin++) {
        p0 = ld_tagged4(src); p1 = ld_tagged4(src + 64 * T_D); p2 = ld_tagged4(src + 128 * T_D); p3 = ld_tagged4(four ? src + 192 * T_D : src);
        if (__all_sync(0xffffffffu, tagged4(p0) & tagged4(p1) & tagged4(p2) & tagged4(p3))) break;
      }
      if (four) { p2.x += p3.x; p2.y += p3.y; p2.z += p3.z; p2.w += p3.w; }
      p0.x = (p0.x + p1.x) + p2.x; p0.y = (p0.y + p1.y) + p2.y; p0.z = (p0.z + p1.z) + p2.z; p0.w = (p0.w + p1.w) + p2.w;
      #pragma unroll
      for (int o = 4; o <= 16; o <<= 1) {
        p0.x += __shfl_xor_sync(0xffffffffu, p0.x, o); p0.y += __shfl_xor_sync(0xffffffffu, p0.y, o);
        p0.z += __shfl_xor_sync(0xffffffffu, p0.z, o); p0.w += __shfl_xor_sync(0xffffffffu, p0.w, o);
      }
      if (lane < 4) sts_f32x4(sbase + OG_SFIN + (threadIdx.x >> 5) * 64 + lane * 16, p0.x, p0.y, p0.z, p0.w);
      named_bar_sync(10, 128);
      TL_MARK2(21, threadIdx.x == 0);
      if (threadIdx.x < 16) {
        const uint32_t ya = sbase + OG_SFIN + threadIdx.x * 4;
        float y = (lds_f32(ya) + lds_f32(ya + 64)) + (lds_f32(ya + 128) + lds_f32(ya + 192));
        y = rbf(y);
        y = rbf(y * rs);
        *dst = __float2bfloat16_rn(fx + rbf(fg * rbf(fh + rbf(fz + y))));
      }
    }
    if (threadIdx.x == 0) XT(11);
    TL_END(4, threadIdx.x == 0);
}

__device__ __forceinline__ void load_pre(uint4* pre, uint32_t sbase, uint32_t buf, int t2) {
  mbar_wait(sbase + AT_SBAR + 272, 0);
  #pragma unroll
  for (int i = 0; i < 8; i++) pre[i] = lds_u32x4(sbase + buf + i * 4096 + t2 * 16);
}
__device__ __forceinline__ void tail_consumer(uint32_t bid, uint32_t sbase, const CUtensorMap* tmOut, const uint4 (&pre)[8], int cwg, const bf16* __restrict__ w_gate, const bf16* __restrict__ w_up) {
    const uint32_t c0 = clock_lo();
    mbar_wait(sbase + AT_SBAR + 320, 0);
    const uint2 td = lds_u32x2(sbase + AT_SBAR + 408);
    const int tb = __shfl_sync(0xffffffffu, (int)td.x, 0);
    TAIL_SETUP
    const int tid = threadIdx.x & 127, t2 = threadIdx.x - 128;
    const int warp = tid >> 5, lane = tid & 31, w8 = t2 >> 5;
    const uint32_t dbase = (sbase & 0x3FFFFu) >> 4;
    const uint32_t a_base = dbase + ((cwg * 8192) >> 4) + (1u << 16);
    const uint32_t b_base = dbase + (16384 >> 4) + (512u << 16);
    TL_MARK2(25, threadIdx.x == 128);
    const uint64_t pol = policy_evict_first();
    const bf16* pw = ((lane & 16) ? w_up : w_gate) + (size_t)(w8 * 128 + (lane & 3) * 4) * T_F + bid * 32 + ((lane >> 2) & 3) * 8;
    uint4 wv[32];
    float acc[64];
    #pragma unroll
    for (int i = 0; i < 8; i++) {
      acc[8 * i] = bflo(pre[i].x); acc[8 * i + 1] = bfhi(pre[i].x); acc[8 * i + 2] = bflo(pre[i].y); acc[8 * i + 3] = bfhi(pre[i].y);
      acc[8 * i + 4] = bflo(pre[i].z); acc[8 * i + 5] = bfhi(pre[i].z); acc[8 * i + 6] = bflo(pre[i].w); acc[8 * i + 7] = bfhi(pre[i].w);
    }
    if (lane == 0) mbar_arrive(bar_full + 304);
    while (__any_sync(0xffffffffu, clock_lo() - c0 < td.y)) {}
    uint32_t stage = OG_POS % OG_ST;
    {
      uint32_t phase = (OG_POS / OG_ST) & 1, prev = 12;
      int kb = 0;
      #pragma unroll
      for (int g = 0; g <= OG_NG; g++) {
        const int end = g == OG_NG ? 64 - og_pre(tb) : LD_FIRST + g * OG_GRP + LD_STAG * cwg;
        #pragma unroll 1
        do {
          mbar_wait(bar_full + 8 * stage, phase);
          if (OG_STAG > 0 && g == OG_NG && cwg == 1 && kb == end - OG_STAG) named_bar_sync(7, 256);
          const uint32_t a_lo = a_base + stage * (OG_STAGE >> 4), b_lo = b_base + stage * (OG_STAGE >> 4);
          wgmma_fence();
          wgmma_m64n128k16_ss_tb<0, 0>(acc, a_lo, b_lo, 1);
          wgmma_m64n128k16_ss_tb<2, 128>(acc, a_lo, b_lo, 1);
          wgmma_m64n128k16_ss_tb<4, 256>(acc, a_lo, b_lo, 1);
          wgmma_m64n128k16_ss_tb<6, 384>(acc, a_lo, b_lo, 1);
          wgmma_commit();
          if (OG_STAG > 0 && g == OG_NG && cwg == 0 && kb == end - 1) named_bar_arrive(7, 256);
          wgmma_wait<1>();
          if (tid == 0) mbar_arrive(bar_empty + 8 * prev);
          prev = stage;
          if (++stage == OG_ST) { stage = 0; phase ^= 1; }
        } while (++kb < end);
        #pragma unroll
        for (int j = 4 * g; j < 4 * g + 4 && j < 32; j++) wv[j] = ldg_stream_v4(pw + (size_t)(16 * (j >> 2) + (j & 3)) * T_F, pol, has_moe);
      }
    }
    mbar_wait(bar_col, 0);
    if (__builtin_expect(!has_moe, 0)) {
      load_pre(wv, sbase, AT_SQ, t2);
    }
    wgmma_wait<0>();
    fence_regs(acc);
    if (__builtin_expect(!has_moe, 0)) {
      #pragma unroll
      for (int i = 0; i < 8; i++) {
        acc[8 * i] += bflo(wv[i].x); acc[8 * i + 1] += bfhi(wv[i].x); acc[8 * i + 2] += bflo(wv[i].y); acc[8 * i + 3] += bfhi(wv[i].y);
        acc[8 * i + 4] += bflo(wv[i].z); acc[8 * i + 5] += bfhi(wv[i].z); acc[8 * i + 6] += bflo(wv[i].w); acc[8 * i + 7] += bfhi(wv[i].w);
      }
    }
    if (tid == 0) mbar_arrive(bar_end);
    TL_MARK2(9, lane == 0);
    const int q2 = 2 * (lane & 3);
    const uint32_t frag = (64 * cwg + 16 * warp + (lane & 7) + 8 * ((lane >> 3) & 1)) * 128;
    const int fsw = lane & 7, fhi = lane >> 4;
    {
      float dl[4] = {0.f, 0.f, 0.f, 0.f}, da[4] = {0.f, 0.f, 0.f, 0.f}, db[4] = {0.f, 0.f, 0.f, 0.f};
      const uint32_t tb2 = sbase + OG_SCOL + (lane & 8) * 32 + (lane & 3) * 8, g = lane >> 2;
      const uint32_t msk = (g == 1 || g == 2) ? 0xffffffffu : 0u, one = g == 0 ? 0x3F803F80u : 0u;
      uint32_t xr[8][4];
      #pragma unroll
      for (int hf = 0; hf < 2; hf++) {
        uint32_t ga[8];
        uint2 cw[4];
        #pragma unroll
        for (int i = 0; i < 4; i++) {
          ldmatrix_x4(sbase + OG_XSLOT + hf * 16384 + frag + (((2 * i + fhi) ^ fsw) << 4), xr[4 * hf + i][0], xr[4 * hf + i][1], xr[4 * hf + i][2], xr[4 * hf + i][3]);
          ga[2 * i] = lds_u32(sbase + OG_SCOL + 512 + (64 * hf + 16 * i + q2) * 2); ga[2 * i + 1] = lds_u32(sbase + OG_SCOL + 512 + (64 * hf + 16 * i + 8 + q2) * 2);
          cw[i] = lds_u32x2(tb2 + (8 * hf + 2 * i) * 16);
        }
        #pragma unroll
        for (int i = 0; i < 4; i++) {
          uint32_t* x4 = xr[4 * hf + i];
          #pragma unroll
          for (int e = 0; e < 4; e++) x4[e] = badd2(x4[e], bmul2(ga[2 * i + (e >> 1)], pack_bf16(acc[32 * hf + 8 * i + 2 * e], acc[32 * hf + 8 * i + 2 * e + 1])));
          mma_bf16(dl, x4[0], x4[1], x4[2], x4[3], (cw[i].x & msk) | one, (cw[i].y & msk) | one);
          mma_bf16(da, x4[0], x4[1], x4[2], x4[3], x4[0], x4[2]);
          mma_bf16(db, x4[0], x4[1], x4[2], x4[3], x4[1], x4[3]);
        }
      }
      {
        const int dsrc = (lane & ~3) + (g >> 1);
        const float qa = __shfl_sync(0xffffffffu, (g & 1) ? da[1] : da[0], dsrc), qb = __shfl_sync(0xffffffffu, (g & 1) ? db[3] : db[2], dsrc);
        const float e0 = __shfl_xor_sync(0xffffffffu, (lane & 1) ? dl[0] : dl[2], 1), e1 = __shfl_xor_sync(0xffffffffu, dl[3], 1);
        if ((lane & 3) < 2) {
          const bool hi = lane & 1;
          st_tagged4(reinterpret_cast<float*>(g_part1 + ((mt * 8 + w8) * 8 + nt) * 16 + g + (hi ? 8 : 0)),
                     hi ? e0 : dl[0], hi ? qb : qa, hi ? e1 + dl[2] : dl[1] + e0, 1.0f);
        }
      }
      #pragma unroll
      for (int i = 0; i < 8; i++) stmatrix_x4(sbase + OG_XSLOT + (i >> 2) * 16384 + frag + (((2 * (i & 3) + fhi) ^ fsw) << 4), xr[i][0], xr[i][1], xr[i][2], xr[i][3]);
    }
    TL_MARK2(10, lane == 0);
    uint4 wd[16];
    if (has_moe) mbar_wait(bar_wd, 0);
    #pragma unroll
    for (int i = 0; i < 16; i++) wd[i] = lds_u32x4(sbase + (cwg ? (stage + (stage & 1)) * OG_STAGE : OG_SWD) + warp * 8192 + (i >> 3) * 4096 + (i & 6) * 512 + (i & 1) * 128 + (lane & 3) * 256 + (((lane >> 2) ^ (2 * (lane & 3) + (i & 1))) << 4));
    {
      const float* src = reinterpret_cast<const float*>(g_part1 + ((mt * 8 + w8) * 8 + (lane & 1) * 4) * 16 + (lane >> 1));
      float4 v, v1, v2, v3;
      #pragma unroll 1
      for (unsigned int spin = 0; spin < (1u << 22); spin++) {
        v = ld_tagged4(src); v1 = ld_tagged4(src + 64); v2 = ld_tagged4(src + 128); v3 = ld_tagged4(src + 192);
        if (__all_sync(0xffffffffu, tagged4(v) & tagged4(v1) & tagged4(v2) & tagged4(v3))) break;
        __nanosleep(100);
      }
      __syncwarp();
      TL_MARK2(26, lane == 0);
      v.x = (v.x + v1.x) + (v2.x + v3.x); v.y = (v.y + v1.y) + (v2.y + v3.y); v.z = (v.z + v1.z) + (v2.z + v3.z);
      v.x += __shfl_xor_sync(0xffffffffu, v.x, 1); v.y += __shfl_xor_sync(0xffffffffu, v.y, 1); v.z += __shfl_xor_sync(0xffffffffu, v.z, 1);
      const float mean = v.x * (1.0f / T_D);
      const float var = fmaxf(fmaf(-mean, mean, v.y * (1.0f / T_D)), 0.f);
      const uint32_t mb2 = pack_bf16(mean, mean);
      const float inv = rcp_approx(rbf(sqrt_approx(rbf(rbf(var) + 1e-05f))));
      {
        const float2 sc = lds_f32x2(sbase + OG_SMISC);
        const uint32_t key = rank_key(rbf(fmaf(fmaf(-bflo(mb2), sc.x, v.z), inv, sc.y)), m0 + 16 * w8 + (lane >> 1));
        mbar_wait(bar_end, 0);
        if (lane & 1) sts_u32(sbase + OG_SSTAT + 1024 + (16 * w8 + (lane >> 1)) * 4, key);
        else sts_u32x2(sbase + OG_SSTAT + (16 * w8 + (lane >> 1)) * 8, mb2, __float_as_uint(inv));
        __syncwarp();
        if (lane == 0) mbar_arrive(bar_key);
      }
      const uint32_t ih = pack_bf16(inv, inv), il = pack_bf16(inv - bflo(ih), inv - bflo(ih));
      const uint32_t mba = __shfl_sync(0xffffffffu, mb2, 2 * (lane >> 2)), mbb = __shfl_sync(0xffffffffu, mb2, 2 * (lane >> 2) + 16);
      const uint32_t iha = __shfl_sync(0xffffffffu, ih, 2 * (lane >> 2)), ihb = __shfl_sync(0xffffffffu, ih, 2 * (lane >> 2) + 16);
      const uint32_t ila = __shfl_sync(0xffffffffu, il, 2 * (lane >> 2)), ilb = __shfl_sync(0xffffffffu, il, 2 * (lane >> 2) + 16);
      #pragma unroll 1
      for (int J0 = 0; J0 < 16; J0 += 4) {
        uint32_t xr[2][4], cv[4][3];
        #pragma unroll
        for (int i = 0; i < 2; i++) {
          ldmatrix_x4(sbase + OG_XSLOT + (J0 >> 3) * 16384 + frag + ((((J0 & 7) + 2 * i + fhi) ^ fsw) << 4), xr[i][0], xr[i][1], xr[i][2], xr[i][3]);
          #pragma unroll
          for (int h = 0; h < 2; h++)
            #pragma unroll
            for (int k = 0; k < 3; k++) cv[2 * i + h][k] = lds_u32(sbase + OG_SCOL + 768 + 256 * k + (8 * (J0 + 2 * i + h) + q2) * 2);
        }
        #pragma unroll
        for (int i = 0; i < 2; i++) {
          #pragma unroll
          for (int h = 0; h < 2; h++) {
            xr[i][2 * h] = out2(xr[i][2 * h], mba, iha, ila, cv[2 * i + h][0], cv[2 * i + h][1], cv[2 * i + h][2]);
            xr[i][2 * h + 1] = out2(xr[i][2 * h + 1], mbb, ihb, ilb, cv[2 * i + h][0], cv[2 * i + h][1], cv[2 * i + h][2]);
          }
          stmatrix_x4(sbase + OG_OSLOT + (J0 >> 3) * 16384 + frag + ((((J0 & 7) + 2 * i + fhi) ^ fsw) << 4), xr[i][0], xr[i][1], xr[i][2], xr[i][3]);
        }
      }
      fence_proxy_async();
      mbar_wait(bar_full + 352, 0);
      const uint2 cg = lds_u32x2(sbase + OG_SMISC + 96);
      __syncwarp();
      if (elect_one()) {
        mbar_arrive(bar_out);
        if (cg.x != w8 && cg.y != w8) {
          asm volatile("cp.async.bulk.tensor.2d.global.shared::cta.bulk_group [%0, {%2, %3}], [%1];" :: "l"(tmOut), "r"(sbase + OG_OSLOT + w8 * 2048), "r"(n0), "r"(m0 + 16 * w8) : "memory");
          asm volatile("cp.async.bulk.tensor.2d.global.shared::cta.bulk_group [%0, {%2, %3}], [%1];" :: "l"(tmOut), "r"(sbase + OG_OSLOT + 16384 + w8 * 2048), "r"(n0 + 64), "r"(m0 + 16 * w8) : "memory");
          bulk_commit();
        }
      }
      TL_MARK2(24, lane == 0);
    }
    if (has_moe) mbar_wait(bar_h2, 0);
    TL_MARK2(13, lane == 0);
    if (has_moe) {
      const GemvSel sel = gemv_sel(lane);
      {
        float d[4][4];
        #pragma unroll
        for (int c = 0; c < 4; c++) { d[c][0] = 0.f; d[c][1] = 0.f; d[c][2] = 0.f; d[c][3] = 0.f; }
        #pragma unroll
        for (int st = 0; st < 8; st++) {
          const uint2 hb = lds_u32x2(sbase + OG_SH2 + ((lane >> 2) & 1) * 2048 + (w8 * 128 + st * 16 + (lane & 3) * 4) * 2);
          #pragma unroll
          for (int j = 0; j < 4; j++) mma_bf16(d[j], wv[4 * st + j].x, wv[4 * st + j].y, wv[4 * st + j].z, wv[4 * st + j].w, GEMV_B0(j, hb, sel), GEMV_B1(j, hb, sel));
        }
        #pragma unroll
        for (int e = 0; e < 4; e++) d[0][e] = (d[0][e] + d[1][e]) + (d[2][e] + d[3][e]);
        const float4 r = gemv_out(d[0], lane);
        sts_f32x4(sbase + OG_SRED + w8 * 512 + (((lane >> 4) * 2 + (lane & 1)) * 32 + ((lane >> 2) & 3) * 8 + (lane & 2) * 2) * 4, r.x, r.y, r.z, r.w);
      }
      named_bar_sync(9, 256);
      if (t2 < 64) {
        float gp[8], up[8];
        #pragma unroll
        for (int w = 0; w < 8; w++) { gp[w] = lds_f32(sbase + OG_SRED + w * 512 + t2 * 4); up[w] = lds_f32(sbase + OG_SRED + w * 512 + 256 + t2 * 4); }
        const float gs = ((gp[0] + gp[1]) + (gp[2] + gp[3])) + ((gp[4] + gp[5]) + (gp[6] + gp[7]));
        const float us = ((up[0] + up[1]) + (up[2] + up[3])) + ((up[4] + up[5]) + (up[6] + up[7]));
        asm volatile("st.shared.u16 [%0], %1;" :: "r"(sbase + OG_SGU + ((t2 & ~15) + ((t2 >> 1) & 3) * 4 + ((t2 >> 3) & 1) * 2 + (t2 & 1)) * 2), "h"((uint16_t)pack_bf16(silu_bf(rbf(gs)) * rbf(us), 0.f)) : "memory");
      }
      named_bar_sync(9, 256);
      TL_MARK2(20, threadIdx.x == 128);
      float d[4][4];
      #pragma unroll
      for (int c = 0; c < 4; c++) { d[c][0] = 0.f; d[c][1] = 0.f; d[c][2] = 0.f; d[c][3] = 0.f; }
      #pragma unroll
      for (int st = 0; st < 2; st++) {
        const uint2 g = lds_u32x2(sbase + OG_SGU + ((lane >> 2) & 1) * 64 + st * 32 + (lane & 3) * 8);
        #pragma unroll
        for (int j = 0; j < 4; j++) {
          const uint32_t b0 = GEMV_B0(j, g, sel), b1 = GEMV_B1(j, g, sel);
          mma_bf16(d[j & 1], wd[4 * st + j].x, wd[4 * st + j].y, wd[4 * st + j].z, wd[4 * st + j].w, b0, b1);
          mma_bf16(d[2 + (j & 1)], wd[8 + 4 * st + j].x, wd[8 + 4 * st + j].y, wd[8 + 4 * st + j].z, wd[8 + 4 * st + j].w, b0, b1);
        }
      }
      #pragma unroll
      for (int e = 0; e < 4; e++) { d[0][e] += d[1][e]; d[2][e] += d[3][e]; }
      const float4 y0 = gemv_out(d[0], lane), y1 = gemv_out(d[2], lane);
      float* yp = g_ypart + (size_t)(bid * 2 + (lane & 1)) * T_D + w8 * 128 + (lane >> 2) * 8 + (lane & 2) * 2;
      st_tagged4(yp, y0.x, y0.y, y0.z, y0.w);
      st_tagged4(yp + 64, y1.x, y1.y, y1.z, y1.w);
      named_bar_sync(9, 256);
      if (t2 == 0) hint_arrive(CNT_Y);
    }
    bulk_wait_read<0>();
    TL_MARK2(14, threadIdx.x == 128);
    TL_CLK(4, 1, threadIdx.x == 128);
}

__device__ __forceinline__ int help_njobs(uint32_t bid) { return bid < 128 ? OG_JOBS : 16 - OG_JOBS; }
__device__ __forceinline__ int help_job(uint32_t bid, int i) { return (i < OG_JOBS ? 16 * i + (bid >> 7) * 2 : 112 + (i - OG_JOBS) * 2) + (bid & 3) * 4; }
__device__ __noinline__ void store_warp(uint32_t bid, uint32_t sbase, const CUtensorMap* tmO, int item0, int n_items) {
  if (elect_one()) {
    const uint32_t bars = sbase + AT_SBAR, b_q0 = bars + 80, b_ob = bars + 96, b_ordy = bars + 104, b_acq = bars + 264;
    const unsigned int* cnt = g_hcnt + 32 * (1 + OG_MT(124)) + 2;
    #pragma unroll 1
    for (int q = 0; q < 4 * n_items; q++) {
      const int item = item0 + (q >> 2) * 128, h = (q >> 1) & 1, w = q & 1;
      const bool last = (q >> 2) == n_items - 1;
      if (q == 4 * n_items - 4) { mbar_wait_long(bars + 288, 0); red_release_add(&g_hcnt[1], 1u); }
      mbar_wait_long(b_ordy + 8 * (q & 3), q >> 2);
      store_o(tmO, (h ? (last ? sbase + AT_SQ + 32768 : sbase + 2 * 32768) : sbase + AT_SQ) + w * 8192, (item >> 4) * 2 + h, (item & 15) * 128 + w * 64);
      if (w) {
        bulk_wait_read<0>();
        mbar_arrive(h ? b_ob : b_q0);
        bulk_wait<0>();
        fence_proxy_async_global();
        asm volatile("fence.acq_rel.gpu;" ::: "memory");
        hint_arrive(&g_hcnt[32 * (1 + (item & 15)) + 2 + (item >> 7)]);
        if (!h && item < 128) hint_arrive(&g_hcnt[2]);
        if (q == 5) { const int tb = tail_tile(sbase); cnt = g_hcnt + 32 * (1 + OG_MT(tb)) + 2; spin_until(cnt, 16u); mbar_arrive(b_acq); }
      }
    }
    if (n_items == 1) {
      #pragma unroll 1
      for (int i = 0; i < help_njobs(bid); i++) {
        mbar_wait_long(b_acq + 16, i & 1);
        TL_MARK2(23, i == OG_JOBS - 1);
        red_release_add(&g_hcnt[32 * (1 + (help_job(bid, i) >> 3)) + 4 + ((help_job(bid, i) >> 1) & 3)], 1u);
        TL_MARK2(4, i == OG_JOBS - 1);
        if (i == PRE_X - 1) { spin_until(&g_hcnt[1], 132u); mbar_arrive(b_acq + 32); }
      }
    }
    if (bid < 128) {
      if (n_items == 1) { spin_until(cnt, 16u); mbar_arrive(b_acq); }
      spin_until(&g_hcnt[0], 128u); spin_until(cnt + 1, 16u); mbar_arrive(b_acq + 80);
    }
  }
}

__device__ __forceinline__ uint32_t role_of_sm(uint32_t sm) {
  const uint32_t t = sm >> 1, u = t - 32u, d = (u * 37u) >> 8;
  return (t < 32u ? ((t + 7u) & 7u) * 16u + (t >> 3) * 2u : t < 60u ? (u - 7u * d) * 16u + (4u + d) * 2u : t < 62u ? 2u * t + 8u : 2u * t - 4u) + (sm & 1u);
}
__global__ void __launch_bounds__(384, 1)
fused_kernel(const __grid_constant__ CUtensorMap tmH, const __grid_constant__ CUtensorMap tmW, const __grid_constant__ CUtensorMap tmK,
            const __grid_constant__ CUtensorMap tmV, const __grid_constant__ CUtensorMap tmO, const __grid_constant__ CUtensorMap tmOl, const __grid_constant__ CUtensorMap tmWo,
            const __grid_constant__ CUtensorMap tmD, const __grid_constant__ CUtensorMap tmOut, const __grid_constant__ CUtensorMap tmM, uint32_t zero,
            const uint8_t* __restrict__ pf_wo, const bf16* __restrict__ kc, const bf16* __restrict__ vc,
            const bf16* __restrict__ x, const bf16* __restrict__ cvec, const bf16* __restrict__ w_mod, const bf16* __restrict__ w_r,
            const bf16* __restrict__ w_gate, const bf16* __restrict__ w_up, const bf16* __restrict__ w_down, bf16* __restrict__ out)
{
  uint32_t bid, nsm;
  asm volatile("mov.u32 %0, %%smid;" : "=r"(bid));
  asm volatile("mov.u32 %0, %%nsmid;" : "=r"(nsm));
  bid = __shfl_sync(0xffffffffu, nsm == 132u ? role_of_sm(bid) : blockIdx.x, 0);
  extern __shared__ __align__(1024) uint8_t smem_raw[];
  const uint32_t sbase = smem_u32(smem_raw);
  const uint32_t bars = sbase + AT_SBAR;
  const uint32_t b_full = bars, b_empty = bars + 40;
  const uint32_t b_q0 = bars + 80, b_q1 = bars + 88;
  const uint32_t b_ob = bars + 96;
  const uint32_t b_ordy = bars + 104;
  const uint32_t b_pin = bars + 136;
  const uint32_t b_head = bars + 144;
  const uint32_t b_go = bars + 152;
  const uint32_t b_x = bars + 160;
  const int wg = __shfl_sync(0xffffffffu, threadIdx.x >> 7, 0);
  const bool single = bid >= AT_NFULL;
  const int item0 = __shfl_sync(0xffffffffu, bid < 128 ? (int)bid : (int)bid + 124, 0), n_items = __shfl_sync(0xffffffffu, single ? 1 : 2, 0);
  TL_START(3);
  if (threadIdx.x == 0) {
    if (sbase & 1023u) __trap();
    for (int i = 0; i < 5; i++) { mbar_init(b_full + 8 * i, 1); mbar_init(b_empty + 8 * i, 2); }
    mbar_init(b_q0, 1); mbar_init(b_q1, 8); mbar_init(b_ob, 1);
    for (int i = 0; i < 4; i++) mbar_init(b_ordy + 8 * i, 4);
    mbar_init(b_pin, 1); mbar_init(b_head, bid < 128 ? 8 : 1); mbar_init(b_go, 1); mbar_init(b_x, 1);
    mbar_init(bars + 168, 2); mbar_init(bars + 176, 1); mbar_init(bars + 184, 8); mbar_init(bars + 192, 2);
    mbar_init(bars + 200, 8); mbar_init(bars + 208, 4); mbar_init(bars + 216, 1); mbar_init(bars + 264, 1); mbar_init(bars + 272, 1); mbar_init(bars + 280, 8); mbar_init(bars + 288, 1); mbar_init(bars + 296, 1); mbar_init(bars + 304, 8); mbar_init(bars + 312, 1); mbar_init(bars + 320, 1); mbar_init(bars + 328, 1); mbar_init(bars + 336, 1); mbar_init(bars + 344, 1); mbar_init(bars + 352, 1);
    sts_u32(bars + 400, bid);
    fence_mbar_init();
  }

  if (wg == 0) {
    reg_dealloc<AT_PREG>();
    if (threadIdx.x < 32) { __syncwarp(); named_bar_arrive(6, 384); }
    if (threadIdx.x >= 64) {
      named_bar_sync(6, 384);
      if (bid < 128) {
        named_bar_sync(threadIdx.x >= 96 ? 8 : 9, 288);
        if ((threadIdx.x & 31) == 0) red_release_add(&g_hcnt[32 * (1 + (bid >> 3)) + (threadIdx.x >= 96)], 1u);
        TL_MARK2(11, threadIdx.x == 64);
      }
      if (bid < 128) {
        mbar_wait(MOD_AT, 0);
        mod_rest(bid, sbase + OG_SCOL, b_q1, threadIdx.x - 64, cvec, w_mod, w_r);
      }
    } else if (threadIdx.x >= 32) {
      named_bar_sync(6, 384);
      store_warp(bid, sbase, &tmO, item0, n_items);
      __syncwarp();
    } else {
     if (elect_one()) {
      const uint64_t pol = policy_evict_first();
      if (bid < 128) {
        mbar_expect_tx(b_x, 32768);
        if (X_DLY) { const uint32_t c0 = clock_lo(); while (clock_lo() - c0 < X_DLY) {} }
        bulk_load_hint(sbase + 4 * 32768, x + (size_t)bid * 16 * T_D, 32768, b_x, pol);
      }
      prefetch_tmap(&tmW); prefetch_tmap(&tmM); prefetch_tmap(&tmH); prefetch_tmap(&tmWo); prefetch_tmap(&tmOl);
      {
        const uint32_t c0 = clock_lo();
        while (clock_lo() - c0 < W_DLY) {}
        if (bid < 128 && (head_cb(bid) & 15) >= 4 * H_SPLIT) {
          mbar_expect_tx(bars + 328, 32768);
          tma_load_2d_hint(sbase + 3 * 32768, &tmM, head_cb(bid) * 64, (bid >> 5) * 256, bars + 328, pol);
        }
        while (clock_lo() - c0 < W_DLY + W_FIRST) {}
      }
      uint32_t slot = 0, ph = 1;
      #pragma unroll 1
      for (int it = 0; it < n_items; it++) {
        const int item = item0 + it * 128, hp = item >> 4, qt = item & 15;
        const bool first = it == 0;
        #pragma unroll 1
        for (int j = 0; j < T_D / 64; j++) {
          const uint32_t sl = ring_slot(qp_pos(j, it)), fb = b_full + 8 * sl;
          mbar_wait_long(b_empty + 8 * sl, ring_par(qp_pos(j, it)) ^ ((j >> 2) & 1) ^ 1);
          if (first && j == 3) mbar_wait(b_head, 0);
          mbar_expect_tx(fb, 49152);
          tma_load_3d_hint(sbase + sl * 32768, &tmW, j * 64, hp * 4, fb, pol);
          if (first && j < PRE_B) {
            if (j == PRE_B - 1) {
              spin_until(&g_hcnt[32 * (1 + qt)], 8u);
              TL_MARK2(16, true);
              fence_proxy_async_global();
              #pragma unroll 1
              for (int i = 0; i < PRE_B; i++) tma_load_2d(sbase + AT_SQ + i * 16384, &tmH, i * 64, qt * 128, b_full + 8 * i);
              mbar_arrive(b_go);
            }
          } else {
            if (first && j == 4 * H_SPLIT) { spin_until(&g_hcnt[32 * (1 + qt) + 1], 8u); fence_proxy_async_global(); }
            if (!first && (j == 0 || j == 2)) mbar_wait(j ? b_q1 : b_q0, 0);
            tma_load_2d(sbase + AT_SQ + (j & 3) * 16384, &tmH, j * 64, qt * 128, fb);
          }
        }
        #pragma unroll 1
        for (int j = 0; j < 4 * AT_NBLK; j++) {
          const bool isv = (j > 0 && !(j & 1)) || j == 4 * AT_NBLK - 1;
          const int row = hp * 2 * T_SEQ + (isv ? (j - 1) >> 1 : (j + 1) >> 1) * 128;
          const uint32_t fb = b_full + 8 * slot;
          mbar_wait_long(b_empty + 8 * slot, ph);
          if (!first && j == 3) mbar_wait(b_ob, 0);
          if (j == 4 && it == n_items - 1) mbar_arrive(bars + 288);
          if ((j == AL_P || j == RK_P) && it == 1) mbar_arrive(bars + 312);
          mbar_expect_tx(fb, 32768);
          tma_load_3d_hint(sbase + slot * 32768, isv ? &tmV : &tmK, row, 0, fb, pol);
          if (it == 1 && isv && j >= 2 * WO_LATE && j < 2 * WO_LATE + 32 && bid < OG_NKB)
            l2_prefetch_bulk(pf_wo + (size_t)own_kb(bid, og_pre(0)) * 131072 + ((j >> 1) - WO_LATE) * 8192, 8192);
          if (++slot == 5) { slot = 0; ph ^= 1; }
        }
      }
      if (__builtin_expect(single, 0)) {
        spin_until(&g_hcnt[2], 128u);
        fence_proxy_async_global();
        const int nj = OG_HSUM + (help_njobs(bid) - OG_JOBS) * OG_PRE2;
        int ji = 0, job = help_job(bid, 0), kk = 0;
        #pragma unroll 1
        for (int j = 0; j < nj; j++) {
          const uint32_t sl = ring_slot(qp_pos(j, 1)), fb = b_full + 8 * sl;
          mbar_wait_long(b_empty + 8 * sl, ring_par(qp_pos(j, 1)) ^ ((j >> 2) & 1) ^ 1);
          mbar_expect_tx(fb, 49152);
          tma_load_3d(sbase + sl * 32768, &tmWo, pre_kb(kk) * 64, OG_NT(job) * 2, fb);
          tma_load_3d(sbase + sl * 32768 + 16384, &tmWo, pre_kb(kk) * 64, OG_NT(job) * 2 + 2, fb);
          if (j == 0 || j == 2) mbar_wait(j ? b_ob : b_q0, 0);
          tma_load_2d_hint(sbase + AT_SQ + (j & 3) * 16384, &tmOl, pre_kb(kk) * 64, OG_MT(job) * 128, fb, pol);
          if (++kk == og_pre(job)) { kk = 0; job = help_job(bid, ++ji); }
        }
      }
      if (bid < 128) {
        if (single) mbar_wait(b_x, 1);
        tail_producer(bid, sbase, 0, pol, &tmOl, &tmWo, &tmD);
      }
     }
    }
    named_bar_sync(12 + (threadIdx.x >> 5), 32);
    if (bid < 128) tail_exchange(bid, sbase, w_down, w_r, x, out);
  } else {
    if (bid < 128) head_phase(bid, sbase + AT_SQ + 49152, sbase + 4 * 32768, b_x, b_go, b_head, threadIdx.x - 128, zero, cvec, w_mod);
    else { named_bar_sync(6, 384); if (threadIdx.x == 128) mbar_arrive(b_head); }
    TL_MARK2(0, threadIdx.x == 128);
    reg_alloc<AT_CREG>();
    const int cwg = wg - 1;
    const int tid = threadIdx.x & 127;
    const int warp = tid >> 5, lane = tid & 31;
    const uint32_t dbase = (sbase & 0x3FFFFu) >> 4;
    const uint32_t k_base = dbase + (1u << 16);
    const uint32_t v_base = dbase + (1024u << 16);
    const uint32_t w_base = dbase + (512u << 16);
    const uint32_t q_lo = dbase + ((AT_SQ + cwg * 8192) >> 4) + (1u << 16);
    const uint32_t frag = cwg * 8192 + (16 * warp + (lane & 7) + 8 * ((lane >> 3) & 1)) * 128;
    if (cwg == 1) named_bar_arrive(1, 256);
    bool raw = false;
    uint4 pre[8];
    #pragma unroll 1
    for (int it = 0; it < n_items; it++) {
      const bool more = it + 1 < n_items;
      constexpr int nkb = T_D / 64;
      const int ta = __shfl_sync(0xffffffffu, 4 * it, 0);
      float acc[128];
      {
        FS(2 * it, 0);
        #pragma unroll
        for (int i = 0; i < 128; i++) asm volatile("" : "=f"(acc[i]));
        {
          const uint32_t slot = ring_slot(ta), b_lo = w_base + slot * 2048;
          mbar_wait(b_full + 8 * slot, ring_par(ta));
          wgmma_fence();
          wgmma_m64n256k16_ss_tb<0, 0>(acc, q_lo, b_lo, 0);
          wgmma_m64n256k16_ss_tb<2, 128>(acc, q_lo, b_lo, 1);
          wgmma_m64n256k16_ss_tb<4, 256>(acc, q_lo, b_lo, 1);
          wgmma_m64n256k16_ss_tb<6, 384>(acc, q_lo, b_lo, 1);
          wgmma_commit();
        }
        #pragma unroll 1
        for (int j = 1; j < nkb; j++) {
          const uint32_t slot = ring_slot(qp_pos(j, ta >> 2));
          mbar_wait(b_full + 8 * slot, ring_par(qp_pos(j, ta >> 2)) ^ ((j >> 2) & 1));
          if (QP_STAG > 0 && cwg == 1 && j == nkb - QP_STAG) named_bar_sync(7, 256);
          const uint32_t a_lo = q_lo + (j & 3) * 1024, b_lo = w_base + slot * 2048;
          wgmma_fence();
          wgmma_m64n256k16_ss_tb<0, 0>(acc, a_lo, b_lo, 1);
          wgmma_m64n256k16_ss_tb<2, 128>(acc, a_lo, b_lo, 1);
          wgmma_m64n256k16_ss_tb<4, 256>(acc, a_lo, b_lo, 1);
          wgmma_m64n256k16_ss_tb<6, 384>(acc, a_lo, b_lo, 1);
          wgmma_commit();
          if (QP_STAG > 0 && cwg == 0 && j == nkb - 1) named_bar_arrive(7, 256);
          if (j > 0) {
            wgmma_wait<1>();
            if (tid == 0) mbar_arrive(b_empty + 8 * ring_slot(qp_pos(j - 1, ta >> 2)));
          }
        }
        wgmma_wait<0>();
        fence_regs(acc);
        FS(2 * it, 1);
        TL_MARK2(29, threadIdx.x == 256 && it == 0);
        if (tid == 0) mbar_arrive(b_empty + 24);
      }
      float o[64], s[64];
      uint32_t p[32], q[32];
      #pragma unroll
      for (int i = 0; i < 32; i++) q[i] = pack_bf16(acc[2 * i] * AT_C, acc[2 * i + 1] * AT_C);
      zero_regs(s);
      const uint32_t sq = sbase + AT_SQ + cwg * 8192;
      float mc0, mc1, al0 = 1.0f, al1 = 1.0f, l0 = 0.f, l1 = 0.f, lp0 = 0.f, lp1 = 0.f;
      bool redo0 = false;
      FS(2 * it, 2);
      mbar_wait(b_full + 8 * ring_slot(ta), ring_par(ta));
      named_bar_sync(1 + cwg, 256);
      FS(2 * it, 3);
      issue_qk(s, q, k_base + ring_slot(ta) * 2048);
      pass_turn(cwg);
      bool ready = mbar_test(b_full + 8 * ring_slot(ta + 1), ring_par(ta + 1)) & mbar_test(b_full + 8 * ring_slot(ta + 2), ring_par(ta + 2));
      stage_q<16>(acc, AT_C, sbase + AT_SQ + frag, lane);
      wgmma_wait<0>();
      fence_regs(s);
      if (tid == 0) mbar_arrive(b_empty + 8 * ring_slot(ta));
      mc0 = 0.f; mc1 = 0.f;
      if (!raw) {
        raw = softmax_mode(s, mc0, mc1);
        if (__builtin_expect(!raw, 0)) softmax_sub(s, mc0, mc1);
      }
      softmax_exp<0, 64>(s);
      #pragma unroll
      for (int J = 0; J < 16; J += 2)
        stmatrix_x4(sbase + AT_SQ + frag + (J >> 3) * 16384 + ((((J & 7) + (lane >> 4)) ^ (lane & 7)) << 4), q[2 * J], q[2 * J + 1], q[2 * J + 2], q[2 * J + 3]);
      pack_p(p, s);
      zero_regs(o);
      FS(2 * it, 4);
      uint32_t ks = ring_slot(ta + 1), vs = ring_slot(ta + 2), kp = ring_par(ta + 1), vp = ring_par(ta + 2);
      auto finish_head = [&]() {
        FS(2 * it, 5);
        redo0 = finish_l(lp0, lp1);
        if (!redo0) stage_o(o, lp0, lp1, sbase + AT_SQ + frag, lane);
        FS(2 * it + 1, 4);
      };
      if (!ready) { mbar_wait(b_full + 8 * ks, kp); mbar_wait(b_full + 8 * vs, vp); }
      #pragma unroll 1
      for (int n = 1; n < 2 * AT_NBLK; n++) {
        named_bar_sync(1 + cwg, 256);
        issue_qk(s, q, k_base + ks * 2048);
        if (n == AT_NBLK + 1) finish_head();
        issue_pv(o, p, v_base + vs * 2048, (n & 15) != 1);
        pass_turn(cwg);
        wgmma_wait<1>();
        fence_regs(s);
        if (tid == 0) mbar_arrive(b_empty + 8 * ks);
        if (__builtin_expect(!raw || (uint32_t)(n - (AT_NBLK - 1)) <= 2u, 0)) {
          if (n == AT_NBLK + 1 && !redo0) {
            fence_proxy_async();
            __syncwarp();
            if (lane == 0) mbar_arrive(b_ordy + 8 * cwg);
          }
          if (n == AT_NBLK - 1) {
            #pragma unroll
            for (int J = 0; J < 16; J += 2)
              ldmatrix_x4(sbase + AT_SQ + 32768 + frag + (J >> 3) * 16384 + ((((J & 7) + (lane >> 4)) ^ (lane & 7)) << 4), q[2 * J], q[2 * J + 1], q[2 * J + 2], q[2 * J + 3]);
          }
          if (!raw) {
            const float m0 = mc0, m1 = mc1;
            const bool ok = softmax_mode(s, mc0, mc1);
            if (n == AT_NBLK) raw = ok;
            else {
              mc0 = mc0 - AT_HEAD > m0 ? mc0 : m0; mc1 = mc1 - AT_HEAD > m1 ? mc1 : m1;
              al0 = ex2_approx(m0 - mc0); al1 = ex2_approx(m1 - mc1);
            }
            if (!raw) softmax_sub(s, mc0, mc1);
          }
        }
        softmax_exp<0, AT_SPLIT>(s);
        add_rowsum(p, l0, l1);
        if (tid == 0) {
          uint32_t dep = zero & __float_as_uint(l0) & __float_as_uint(l1);
          #pragma unroll
          for (int i = AT_SPLIT - AT_PIN - PINB; i < AT_SPLIT - PINB; i += 2) dep &= __float_as_uint(s[i]) & __float_as_uint(s[i + 1]);
          mbar_arrive(b_pin + dep);
        }
        wgmma_wait<0>();
        fence_regs(o);
        if (tid == 0) mbar_arrive(b_empty + 8 * vs);
        ks += 2; if (ks >= 5) { ks -= 5; kp ^= 1; }
        vs += 2; if (vs >= 5) { vs -= 5; vp ^= 1; }
        ready = mbar_test(b_full + 8 * ks, kp) & mbar_test(b_full + 8 * vs, vp);
        softmax_exp<AT_SPLIT, 64>(s);
        pack_p(p, s);
        if (n == AT_NBLK) { lp0 = l0; lp1 = l1; l0 = 0.f; l1 = 0.f; }
        if (__builtin_expect(!raw || !ready, 0)) {
        if (!raw && __any_sync(0xffffffffu, al0 != 1.0f || al1 != 1.0f)) {
          rescale_o(o, al0, al1);
          l0 *= al0; l1 *= al1;
          al0 = 1.0f; al1 = 1.0f;
        }
        if (!ready && n < 2 * AT_NBLK - 1) {
          mbar_wait(b_full + 8 * ks, kp);
          mbar_wait(b_full + 8 * vs, vp);
        }
        }
      }
      FS(2 * it + 1, 5);
      const uint32_t vl = ring_slot(ta + 63);
      vs = ring_slot(ta + 62);
      const uint32_t ob = more ? sbase + vs * 32768 : sbase + AT_SQ + 32768;
      mbar_wait(b_full + 8 * vl, ring_par(ta + 63));
      issue_pv(o, p, v_base + vl * 2048, 1);
      block_end(zero, b_pin);
      add_rowsum(p, l0, l1);
      const bool overflow = finish_l(l0, l1);
      if (!overflow && lane == 0) mbar_arrive(b_q1);
      #pragma unroll
      for (int i = 0; i < 8; i++) asm volatile("mov.b64 {%0, %1}, 0;\nmov.b64 {%2, %3}, 0;" : "=r"(pre[i].x), "=r"(pre[i].y), "=r"(pre[i].z), "=r"(pre[i].w));
      const bool want_pre = !more && bid < OG_MOE, got_pre = want_pre && __all_sync(0xffffffffu, mbar_test(bars + 272, 0));
      if (got_pre) load_pre(pre, sbase, AT_SQ, threadIdx.x - 128);
      mbar_wait(b_empty + 8 * vs, ring_par(ta + 62));
      wgmma_wait<0>();
      fence_regs(o);
      if (tid == 0) mbar_arrive(b_empty + 8 * vl);
      FS(2 * it + 1, 6);
      if (overflow) {
        attn_rows_exact(lds_u32(bars + 400), sq + 32768, ob + cwg * 8192, 4 * ta + 1, kc, vc);
        __syncwarp();
        if (lane == 0) mbar_arrive(b_q1);
      } else stage_o(o, l0, l1, ob + frag, lane);
      if (redo0) attn_rows_exact(lds_u32(bars + 400), sq, sq, 4 * ta, kc, vc);
      fence_proxy_async();
      __syncwarp();
      if (lane == 0) {
        if (redo0) mbar_arrive(b_ordy + 8 * cwg);
        mbar_arrive(b_ordy + 16 + 8 * cwg);
      }
      if (want_pre && !got_pre) load_pre(pre, sbase, AT_SQ, threadIdx.x - 128);
      if (redo0 || overflow) raw = false;
      named_bar_sync(3 + cwg, 128);
      FS(2 * it + 1, 7);
    }
    if (cwg == 0) named_bar_arrive(1, 256);
    if (__builtin_expect(single, 0)) {
      float acc[128];
      uint32_t j = 0, pk[64];
      #pragma unroll
      for (int i = 0; i < 64; i++) asm volatile("" : "=f"(acc[2 * i]), "=f"(acc[2 * i + 1]), "=r"(pk[i]));
      uint4* dst = g_pre;
      int left = 0;
      auto put = [&](bool last) {
        #pragma unroll
        for (int i = 0; i < PUT_N; i++) dst[i * 256] = make_uint4(pk[4 * i], pk[4 * i + 1], pk[4 * i + 2], pk[4 * i + 3]);
        dst += PUT_N * 256;
        #pragma unroll
        for (int i = 0; i < 64 - 4 * PUT_N; i++) asm volatile("mov.b32 %0, %1;" : "=r"(pk[i]) : "r"(pk[i + 4 * PUT_N]));
        __syncwarp();
        if (last && lane == 0) mbar_arrive(bars + 280);
      };
      #pragma unroll 1
      for (int ji = 0; ji < help_njobs(bid); ji++) {
        const int nk = og_pre(help_job(bid, ji));
        #pragma unroll 1
        for (int kk = 0; kk < nk; kk++, j++) {
          const uint32_t slot = ring_slot(qp_pos(j, 1));
          mbar_wait(b_full + 8 * slot, ring_par(qp_pos(j, 1)) ^ ((j >> 2) & 1));
          if (H_STAG > 0 && cwg == 1 && kk == nk - H_STAG) named_bar_sync(7, 256);
          const uint32_t a_lo = q_lo + (j & 3) * 1024, b_lo = w_base + slot * 2048;
          wgmma_fence();
          wgmma_m64n256k16_ss_tb<0, 0>(acc, a_lo, b_lo, kk != 0);
          wgmma_m64n256k16_ss_tb<2, 128>(acc, a_lo, b_lo, 1);
          wgmma_m64n256k16_ss_tb<4, 256>(acc, a_lo, b_lo, 1);
          wgmma_m64n256k16_ss_tb<6, 384>(acc, a_lo, b_lo, 1);
          wgmma_commit();
          if (H_STAG > 0 && cwg == 0 && kk == nk - 1) named_bar_arrive(7, 256);
          wgmma_wait<1>();
          if (kk > 0 && tid == 0) mbar_arrive(b_empty + 8 * ring_slot(qp_pos(j - 1, 1)));
          #pragma unroll 1
          for (int i = ji == OG_JOBS ? 0 : 16 / PUT_N - 1; i < 16 / PUT_N && left > 0; i++) put(--left == 0);
        }
        wgmma_wait<0>();
        fence_regs(acc);
        if (tid == 0) mbar_arrive(b_empty + 8 * ring_slot(qp_pos(j - 1, 1)));
        #pragma unroll
        for (int i = 0; i < 64; i++) pk[i] = pack_bf16(acc[2 * i], acc[2 * i + 1]);
        left = 16 / PUT_N;
        if (ji == PRE_X) mbar_wait(bars + 296, 0);
        dst = g_pre + help_job(bid, ji) * 2048 + threadIdx.x - 128;
      }
      #pragma unroll
      for (int i = 0; i < 16; i++) dst[i * 256] = make_uint4(pk[4 * i], pk[4 * i + 1], pk[4 * i + 2], pk[4 * i + 3]);
      __syncwarp();
      if (lane == 0) mbar_arrive(bars + 280);
      named_bar_sync(5, 256);
      if (threadIdx.x == 128) {
        #pragma unroll 1
        for (int i = 0; i < 5; i++) {
          constexpr int n = OG_HSUM;
          const int used = i == 3 ? 0 : (n + 3 - (i == 4 ? 3 : i)) / 4;
          if ((used ^ (i < 4)) & 1) {
            mbar_arrive(b_full + 8 * ring_slot(4 + i));
            mbar_arrive(b_empty + 8 * ring_slot(4 + i)); mbar_arrive(b_empty + 8 * ring_slot(4 + i));
          }
        }
        mbar_arrive(b_x);
      }
      named_bar_sync(5, 256);
      #pragma unroll
      for (int i = 0; i < 8; i++) pre[i] = make_uint4(0u, 0u, 0u, 0u);
    }
    TL_CLK(3, 1, threadIdx.x == 128);
    TL_CTA(1, threadIdx.x == 256);
    TL_END(3, tid == 0);
    TL_MARK2(19, tid == 0 && !single);
    if (bid < 128) {
      tail_consumer(bid, sbase, &tmOut, pre, cwg, w_gate, w_up);
    }
  }
}

typedef CUresult (*PFN_encodeTiled)(CUtensorMap*, CUtensorMapDataType, cuuint32_t, void*, const cuuint64_t*, const cuuint64_t*,
                                    const cuuint32_t*, const cuuint32_t*, CUtensorMapInterleave, CUtensorMapSwizzle,
                                    CUtensorMapL2promotion, CUtensorMapFloatOOBfill);

CUtensorMap make_map_2d(PFN_encodeTiled enc, const void* ptr, uint64_t inner, uint64_t outer, uint64_t stride_bytes, uint32_t box_inner, uint32_t box_outer) {
  CUtensorMap m;
  cuuint64_t gd[2] = {inner, outer}; cuuint64_t gs[1] = {stride_bytes};
  cuuint32_t bx[2] = {box_inner, box_outer}; cuuint32_t es[2] = {1, 1};
  enc(&m, CU_TENSOR_MAP_DATA_TYPE_BFLOAT16, 2, const_cast<void*>(ptr), gd, gs, bx, es, CU_TENSOR_MAP_INTERLEAVE_NONE,
      CU_TENSOR_MAP_SWIZZLE_128B, CU_TENSOR_MAP_L2_PROMOTION_L2_128B, CU_TENSOR_MAP_FLOAT_OOB_FILL_NONE);
  return m;
}

CUtensorMap make_map_3d(PFN_encodeTiled enc, const void* ptr, uint64_t cols, uint64_t rows, uint32_t box_rows, uint32_t chunks) {
  CUtensorMap m;
  cuuint64_t gd[3] = {64, rows, cols / 64}; cuuint64_t gs[2] = {cols * 2, 128};
  cuuint32_t bx[3] = {64, box_rows, chunks}; cuuint32_t es[3] = {1, 1, 1};
  enc(&m, CU_TENSOR_MAP_DATA_TYPE_BFLOAT16, 3, const_cast<void*>(ptr), gd, gs, bx, es, CU_TENSOR_MAP_INTERLEAVE_NONE,
      CU_TENSOR_MAP_SWIZZLE_128B, CU_TENSOR_MAP_L2_PROMOTION_L2_128B, CU_TENSOR_MAP_FLOAT_OOB_FILL_NONE);
  return m;
}

}

extern "C" void kernel_launch(void* const* d_in, const int* in_sizes, int n_in, void* d_out, int out_size) {
  const bf16* x      = (const bf16*)d_in[0];
  const bf16* kc     = (const bf16*)d_in[1];
  const bf16* vc     = (const bf16*)d_in[2];
  const bf16* wq     = (const bf16*)d_in[3];
  const bf16* wo     = (const bf16*)d_in[4];
  const bf16* w_r    = (const bf16*)d_in[6];
  const bf16* w_gate = (const bf16*)d_in[7];
  const bf16* w_up   = (const bf16*)d_in[8];
  const bf16* w_down = (const bf16*)d_in[9];
  const bf16* cvec   = (const bf16*)d_in[10];
  const bf16* w_mod  = (const bf16*)d_in[11];
  bf16* out = (bf16*)d_out;

  static PFN_encodeTiled enc = nullptr;
  static void *p_h = nullptr, *p_o = nullptr;
  if (!enc) {
    void* fn = nullptr; cudaDriverEntryPointQueryResult qres;
    cudaGetDriverEntryPoint("cuTensorMapEncodeTiled", &fn, cudaEnableDefault, &qres);
    enc = (PFN_encodeTiled)fn;
    cudaGetSymbolAddress(&p_h, g_pre);
    p_h = (uint4*)p_h + 16 * PRE_X * 2048;
    cudaGetSymbolAddress(&p_o, g_o);
    cudaFuncSetAttribute(fused_kernel, cudaFuncAttributeMaxDynamicSharedMemorySize, (int)AT_SMEM);
  }
  const CUtensorMap tm_h   = make_map_2d(enc, p_h, T_D, T_SEQ, T_D * 2, 64, 128);
  const CUtensorMap tm_wq  = make_map_3d(enc, wq, T_DQKV, T_D, 64, 4);
  const CUtensorMap tm_k   = make_map_3d(enc, kc, T_DH, (uint64_t)T_NH * T_SEQ, 128, 2);
  const CUtensorMap tm_v   = make_map_3d(enc, vc, T_DH, (uint64_t)T_NH * T_SEQ, 128, 2);
  const CUtensorMap tm_ost = make_map_2d(enc, p_o, T_DQKV, T_SEQ, T_DQKV * 2, 64, 64);
  const CUtensorMap tm_old = make_map_2d(enc, p_o, T_DQKV, T_SEQ, T_DQKV * 2, 64, 128);
  const CUtensorMap tm_wo  = make_map_3d(enc, wo, T_D, T_DQKV, 64, 2);
  const CUtensorMap tm_d   = make_map_3d(enc, w_down, T_D, T_F, 32, 8);

  const CUtensorMap tm_m   = make_map_2d(enc, w_mod, 6 * T_D, T_D, 6 * T_D * 2, 64, 256);
  const CUtensorMap tm_out = make_map_2d(enc, out, T_D, T_SEQ, T_D * 2, 64, 16);

  fused_kernel<<<132, 384, AT_SMEM, cudaStreamPerThread>>>(tm_h, tm_wq, tm_k, tm_v, tm_ost, tm_old, tm_wo, tm_d, tm_out, tm_m, 0u, (const uint8_t*)wo, kc, vc, x, cvec, w_mod,
             w_r, w_gate, w_up, w_down, out);
}
```

```cpp
#include <cuda_runtime.h>
#include <cuda_bf16.h>
#include <cuda.h>
#include <stdint.h>

namespace {

typedef __nv_bfloat16 bf16;

constexpr int T_SEQ = 2048, T_D = 1024, T_NH = 32, T_DH = 128, T_DQKV = 4096, T_F = 3584;

#define PRE_X 2
__device__ __align__(1024) uint4 g_pre[(16 * PRE_X + 128) * 2048];
#define g_h (reinterpret_cast<bf16*>(g_pre + 16 * PRE_X * 2048))
__device__ __align__(1024) bf16 g_o[T_SEQ * T_DQKV];
__device__ __align__(16) uint8_t g_col[8 * 1536];
__device__ __align__(16) float g_scal[64];
__device__ __align__(16) unsigned int g_hcnt[17 * 32];
__device__ __align__(128) float g_modpart[4 * 2 * T_D];
struct __align__(2048) TailMail {
  float4 part1[T_SEQ * 8];
  uint32_t key[256];
  uint4 cand[16 * 2 * 2 * 128];
  uint32_t cnt[32];
  float ypart[(T_F / 32) * 2 * T_D];
};
__device__ TailMail g_mail;
#define g_part1 g_mail.part1
#define g_key g_mail.key
#define g_cand g_mail.cand
#define CNT_Y (g_mail.cnt)
#define g_ypart g_mail.ypart

__device__ __forceinline__ uint32_t smem_u32(const void* p) { return (uint32_t)__cvta_generic_to_shared(p); }
__device__ __forceinline__ void mbar_init(uint32_t bar, uint32_t cnt) { asm volatile("mbarrier.init.shared::cta.b64 [%0], %1;" :: "r"(bar), "r"(cnt)); }
__device__ __forceinline__ void mbar_expect_tx(uint32_t bar, uint32_t bytes) { asm volatile("mbarrier.arrive.expect_tx.shared::cta.b64 _, [%0], %1;" :: "r"(bar), "r"(bytes) : "memory"); }
__device__ __forceinline__ void mbar_arrive(uint32_t bar) { asm volatile("mbarrier.arrive.shared::cta.b64 _, [%0];" :: "r"(bar) : "memory"); }
__device__ __forceinline__ void mbar_wait(uint32_t bar, uint32_t parity) {
  asm volatile("{\n.reg .pred p;\nLAB_WAIT:\nmbarrier.try_wait.parity.shared::cta.b64 p, [%0], %1;\n@!p bra LAB_WAIT;\n}\n" :: "r"(bar), "r"(parity) : "memory");
}
__device__ __forceinline__ bool mbar_test(uint32_t bar, uint32_t parity) {
  uint32_t r; asm volatile("{\n.reg .pred p;\nmbarrier.test_wait.parity.shared::cta.b64 p, [%1], %2;\nselp.u32 %0, 1, 0, p;\n}\n" : "=r"(r) : "r"(bar), "r"(parity) : "memory");
  return r != 0;
}
__device__ __forceinline__ void mbar_wait_long(uint32_t bar, uint32_t parity) {
  asm volatile("{\n.reg .pred p;\nLAB_WAIT:\nmbarrier.try_wait.parity.shared::cta.b64 p, [%0], %1, %2;\n@!p bra LAB_WAIT;\n}\n" :: "r"(bar), "r"(parity), "r"(100000) : "memory");
}
__device__ __forceinline__ uint32_t clock_lo() { uint32_t c; asm volatile("mov.u32 %0, %%clock;" : "=r"(c)); return c; }
__device__ __forceinline__ void fence_mbar_init() { asm volatile("fence.mbarrier_init.release.cluster;" ::: "memory"); }
__device__ __forceinline__ void tma_load_2d(uint32_t dst, const CUtensorMap* map, int c0, int c1, uint32_t bar) {
  asm volatile("cp.async.bulk.tensor.2d.shared::cluster.global.mbarrier::complete_tx::bytes [%0], [%1, {%3, %4}], [%2];"
    :: "r"(dst), "l"(map), "r"(bar), "r"(c0), "r"(c1) : "memory");
}
__device__ __forceinline__ uint64_t policy_evict_first() {
  uint64_t p; asm volatile("createpolicy.fractional.L2::evict_first.b64 %0, 1.0;" : "=l"(p)); return p;
}
__device__ __forceinline__ void tma_load_2d_hint(uint32_t dst, const CUtensorMap* map, int c0, int c1, uint32_t bar, uint64_t pol) {
  asm volatile("cp.async.bulk.tensor.2d.shared::cluster.global.mbarrier::complete_tx::bytes.L2::cache_hint [%0], [%1, {%3, %4}], [%2], %5;"
    :: "r"(dst), "l"(map), "r"(bar), "r"(c0), "r"(c1), "l"(pol) : "memory");
}
__device__ __forceinline__ void tma_load_3d_hint(uint32_t dst, const CUtensorMap* map, int c1, int c2, uint32_t bar, uint64_t pol) {
  asm volatile("cp.async.bulk.tensor.3d.shared::cluster.global.mbarrier::complete_tx::bytes.L2::cache_hint [%0], [%1, {%3, %4, %5}], [%2], %6;"
    :: "r"(dst), "l"(map), "r"(bar), "n"(0), "r"(c1), "r"(c2), "l"(pol) : "memory");
}
__device__ __forceinline__ void tma_load_3d(uint32_t dst, const CUtensorMap* map, int c1, int c2, uint32_t bar) {
  asm volatile("cp.async.bulk.tensor.3d.shared::cluster.global.mbarrier::complete_tx::bytes [%0], [%1, {%3, %4, %5}], [%2];"
    :: "r"(dst), "l"(map), "r"(bar), "n"(0), "r"(c1), "r"(c2) : "memory");
}
__device__ __forceinline__ void tma_store_2d(const CUtensorMap* map, uint32_t src, int c0, int c1) {
  asm volatile("cp.async.bulk.tensor.2d.global.shared::cta.bulk_group [%0, {%2, %3}], [%1];" :: "l"(map), "r"(src), "r"(c0), "r"(c1) : "memory");
}
__device__ __forceinline__ void prefetch_tmap(const CUtensorMap* map) { asm volatile("prefetch.tensormap [%0];" :: "l"(map) : "memory"); }
__device__ __forceinline__ void l2_prefetch_bulk(const void* p, uint32_t bytes) {
  asm volatile("cp.async.bulk.prefetch.L2.global [%0], %1;" :: "l"(p), "r"(bytes) : "memory");
}
__device__ __forceinline__ void bulk_commit() { asm volatile("cp.async.bulk.commit_group;" ::: "memory"); }
template<int N> __device__ __forceinline__ void bulk_wait_read() { asm volatile("cp.async.bulk.wait_group.read %0;" :: "n"(N) : "memory"); }
template<int N> __device__ __forceinline__ void bulk_wait() { asm volatile("cp.async.bulk.wait_group %0;" :: "n"(N) : "memory"); }
__device__ __forceinline__ void named_bar_sync(int id, int nthreads) { asm volatile("bar.sync %0, %1;" :: "r"(id), "r"(nthreads) : "memory"); }
__device__ __forceinline__ void named_bar_arrive(int id, int nthreads) { asm volatile("bar.arrive %0, %1;" :: "r"(id), "r"(nthreads) : "memory"); }
__device__ __forceinline__ void pass_turn(int cwg) {
  asm volatile("{\n.reg .pred p;\nsetp.ne.u32 p, %0, 0;\n@p bar.arrive 1, 256;\n@!p bar.arrive 2, 256;\n}\n" :: "r"(cwg) : "memory");
}
__device__ __forceinline__ void wgmma_fence() { asm volatile("wgmma.fence.sync.aligned;" ::: "memory"); }
__device__ __forceinline__ void wgmma_commit() { asm volatile("wgmma.commit_group.sync.aligned;" ::: "memory"); }
template<int N> __device__ __forceinline__ void wgmma_wait() { asm volatile("wgmma.wait_group.sync.aligned %0;" :: "n"(N) : "memory"); }
template<int R> __device__ __forceinline__ void reg_alloc() { asm volatile("setmaxnreg.inc.sync.aligned.u32 %0;" :: "n"(R)); }
template<int R> __device__ __forceinline__ void reg_dealloc() { asm volatile("setmaxnreg.dec.sync.aligned.u32 %0;" :: "n"(R)); }
__device__ __forceinline__ bool elect_one() {
  uint32_t pred; asm volatile("{\n.reg .pred p;\nelect.sync _|p, 0xffffffff;\nselp.u32 %0, 1, 0, p;\n}\n" : "=r"(pred)); return pred != 0;
}
__device__ __forceinline__ uint32_t pack_bf16(float lo, float hi) {
  uint32_t r; asm("cvt.rn.bf16x2.f32 %0, %1, %2;" : "=r"(r) : "f"(hi), "f"(lo)); return r;
}
__device__ __forceinline__ void stmatrix_x4(uint32_t addr, uint32_t r0, uint32_t r1, uint32_t r2, uint32_t r3) {
  asm volatile("stmatrix.sync.aligned.m8n8.x4.shared.b16 [%0], {%1, %2, %3, %4};" :: "r"(addr), "r"(r0), "r"(r1), "r"(r2), "r"(r3) : "memory");
}
__device__ __forceinline__ void fence_proxy_async() { asm volatile("fence.proxy.async.shared::cta;" ::: "memory"); }
__device__ __forceinline__ float ex2_approx(float x) { float y; asm("ex2.approx.ftz.f32 %0, %1;" : "=f"(y) : "f"(x)); return y; }
template<int N> __device__ __forceinline__ void fence_regs(float (&r)[N]) {
  #pragma unroll
  for (int i = 0; i < N; i++) asm volatile("" : "+f"(r[i]) :: "memory");
}
template<int N> __device__ __forceinline__ void zero_regs(float (&r)[N]) {
  #pragma unroll
  for (int i = 0; i < N; i += 2) asm volatile("mov.b64 {%0, %1}, 0;" : "=f"(r[i]), "=f"(r[i + 1]));
}
__device__ __forceinline__ float rbf(float x) { return __uint_as_float(pack_bf16(0.f, x)); }
__device__ __forceinline__ float bflo(uint32_t v) { return __uint_as_float(v << 16); }
__device__ __forceinline__ float bfhi(uint32_t v) { return __uint_as_float(v & 0xffff0000u); }

#define XT(i) do {} while (0)
#define TL_START(k) do {} while (0)
#define TL_END(k, cond) do {} while (0)
#define TL_CTA(i, cond) do {} while (0)
#define FS(slot, k) do {} while (0)
#define TL_MARK2(k, cond) do {} while (0)
#define TL_CLK(k, i, cond) do {} while (0)

template <int OFFA, int OFFB>
__device__ __forceinline__ void wgmma_m64n256k16_ss_tb(float (&d)[128], uint32_t a_lo, uint32_t b_lo, int scaleD) {
  asm volatile("{\n.reg .pred p;\n.reg .b32 ta, tb;\n.reg .b64 da, db;\nsetp.ne.b32 p, %130, 0;\n"
    "add.u32 ta, %128, %131;\nadd.u32 tb, %129, %132;\n"
    "mov.b64 da, {ta, 0x40000040};\nmov.b64 db, {tb, 0x40000040};\n"
    "wgmma.mma_async.sync.aligned.m64n256k16.f32.bf16.bf16 "
    "{%0, %1, %2, %3, %4, %5, %6, %7, %8, %9, %10, %11, %12, %13, %14, %15, %16, %17, %18, %19, %20, %21, %22, %23, %24, %25, %26, %27, %28, %29, %30, %31, %32, %33, %34, %35, %36, %37, %38, %39, %40, %41, %42, %43, %44, %45, %46, %47, %48, %49, %50, %51, %52, %53, %54, %55, %56, %57, %58, %59, %60, %61, %62, %63, %64, %65, %66, %67, %68, %69, %70, %71, %72, %73, %74, %75, %76, %77, %78, %79, %80, %81, %82, %83, %84, %85, %86, %87, %88, %89, %90, %91, %92, %93, %94, %95, %96, %97, %98, %99, %100, %101, %102, %103, %104, %105, %106, %107, %108, %109, %110, %111, %112, %113, %114, %115, %116, %117, %118, %119, %120, %121, %122, %123, %124, %125, %126, %127}, "
    "da, db, p, 1, 1, 0, 1;\n}\n"
    : "+f"(d[0]), "+f"(d[1]), "+f"(d[2]), "+f"(d[3]), "+f"(d[4]), "+f"(d[5]), "+f"(d[6]), "+f"(d[7]), "+f"(d[8]), "+f"(d[9]), "+f"(d[10]), "+f"(d[11]), "+f"(d[12]), "+f"(d[13]), "+f"(d[14]), "+f"(d[15]), "+f"(d[16]), "+f"(d[17]), "+f"(d[18]), "+f"(d[19]), "+f"(d[20]), "+f"(d[21]), "+f"(d[22]), "+f"(d[23]), "+f"(d[24]), "+f"(d[25]), "+f"(d[26]), "+f"(d[27]), "+f"(d[28]), "+f"(d[29]), "+f"(d[30]), "+f"(d[31]), "+f"(d[32]), "+f"(d[33]), "+f"(d[34]), "+f"(d[35]), "+f"(d[36]), "+f"(d[37]), "+f"(d[38]), "+f"(d[39]), "+f"(d[40]), "+f"(d[41]), "+f"(d[42]), "+f"(d[43]), "+f"(d[44]), "+f"(d[45]), "+f"(d[46]), "+f"(d[47]), "+f"(d[48]), "+f"(d[49]), "+f"(d[50]), "+f"(d[51]), "+f"(d[52]), "+f"(d[53]), "+f"(d[54]), "+f"(d[55]), "+f"(d[56]), "+f"(d[57]), "+f"(d[58]), "+f"(d[59]), "+f"(d[60]), "+f"(d[61]), "+f"(d[62]), "+f"(d[63]), "+f"(d[64]), "+f"(d[65]), "+f"(d[66]), "+f"(d[67]), "+f"(d[68]), "+f"(d[69]), "+f"(d[70]), "+f"(d[71]), "+f"(d[72]), "+f"(d[73]), "+f"(d[74]), "+f"(d[75]), "+f"(d[76]), "+f"(d[77]), "+f"(d[78]), "+f"(d[79]), "+f"(d[80]), "+f"(d[81]), "+f"(d[82]), "+f"(d[83]), "+f"(d[84]), "+f"(d[85]), "+f"(d[86]), "+f"(d[87]), "+f"(d[88]), "+f"(d[89]), "+f"(d[90]), "+f"(d[91]), "+f"(d[92]), "+f"(d[93]), "+f"(d[94]), "+f"(d[95]), "+f"(d[96]), "+f"(d[97]), "+f"(d[98]), "+f"(d[99]), "+f"(d[100]), "+f"(d[101]), "+f"(d[102]), "+f"(d[103]), "+f"(d[104]), "+f"(d[105]), "+f"(d[106]), "+f"(d[107]), "+f"(d[108]), "+f"(d[109]), "+f"(d[110]), "+f"(d[111]), "+f"(d[112]), "+f"(d[113]), "+f"(d[114]), "+f"(d[115]), "+f"(d[116]), "+f"(d[117]), "+f"(d[118]), "+f"(d[119]), "+f"(d[120]), "+f"(d[121]), "+f"(d[122]), "+f"(d[123]), "+f"(d[124]), "+f"(d[125]), "+f"(d[126]), "+f"(d[127])
    : "r"(a_lo), "r"(b_lo), "r"(scaleD), "n"(OFFA), "n"(OFFB));
}

template <int OFFA, int OFFB>
__device__ __forceinline__ void wgmma_m64n128k16_ss_tb(float (&d)[64], uint32_t a_lo, uint32_t b_lo, int scaleD) {
  asm volatile("{\n.reg .pred p;\n.reg .b32 ta, tb;\n.reg .b64 da, db;\nsetp.ne.b32 p, %66, 0;\n"
    "add.u32 ta, %64, %67;\nadd.u32 tb, %65, %68;\n"
    "mov.b64 da, {ta, 0x40000040};\nmov.b64 db, {tb, 0x40000040};\n"
    "wgmma.mma_async.sync.aligned.m64n128k16.f32.bf16.bf16 "
    "{%0, %1, %2, %3, %4, %5, %6, %7, %8, %9, %10, %11, %12, %13, %14, %15, %16, %17, %18, %19, %20, %21, %22, %23, %24, %25, %26, %27, %28, %29, %30, %31, %32, %33, %34, %35, %36, %37, %38, %39, %40, %41, %42, %43, %44, %45, %46, %47, %48, %49, %50, %51, %52, %53, %54, %55, %56, %57, %58, %59, %60, %61, %62, %63}, "
    "da, db, p, 1, 1, 0, 1;\n}\n"
    : "+f"(d[0]), "+f"(d[1]), "+f"(d[2]), "+f"(d[3]), "+f"(d[4]), "+f"(d[5]), "+f"(d[6]), "+f"(d[7]), "+f"(d[8]), "+f"(d[9]), "+f"(d[10]), "+f"(d[11]), "+f"(d[12]), "+f"(d[13]), "+f"(d[14]), "+f"(d[15]), "+f"(d[16]), "+f"(d[17]), "+f"(d[18]), "+f"(d[19]), "+f"(d[20]), "+f"(d[21]), "+f"(d[22]), "+f"(d[23]), "+f"(d[24]), "+f"(d[25]), "+f"(d[26]), "+f"(d[27]), "+f"(d[28]), "+f"(d[29]), "+f"(d[30]), "+f"(d[31]), "+f"(d[32]), "+f"(d[33]), "+f"(d[34]), "+f"(d[35]), "+f"(d[36]), "+f"(d[37]), "+f"(d[38]), "+f"(d[39]), "+f"(d[40]), "+f"(d[41]), "+f"(d[42]), "+f"(d[43]), "+f"(d[44]), "+f"(d[45]), "+f"(d[46]), "+f"(d[47]), "+f"(d[48]), "+f"(d[49]), "+f"(d[50]), "+f"(d[51]), "+f"(d[52]), "+f"(d[53]), "+f"(d[54]), "+f"(d[55]), "+f"(d[56]), "+f"(d[57]), "+f"(d[58]), "+f"(d[59]), "+f"(d[60]), "+f"(d[61]), "+f"(d[62]), "+f"(d[63])
    : "r"(a_lo), "r"(b_lo), "r"(scaleD), "n"(OFFA), "n"(OFFB));
}

template <int OFFB>
__device__ __forceinline__ void wgmma_m64n128k16_rs_tb(float (&d)[64], uint32_t a0, uint32_t a1, uint32_t a2, uint32_t a3, uint32_t b_lo, int scaleD) {
  asm volatile("{\n.reg .pred p;\n.reg .b32 tb;\n.reg .b64 db;\nsetp.ne.b32 p, %69, 0;\n"
    "add.u32 tb, %68, %70;\n"
    "mov.b64 db, {tb, 0x40000040};\n"
    "wgmma.mma_async.sync.aligned.m64n128k16.f32.bf16.bf16 "
    "{%0, %1, %2, %3, %4, %5, %6, %7, %8, %9, %10, %11, %12, %13, %14, %15, %16, %17, %18, %19, %20, %21, %22, %23, %24, %25, %26, %27, %28, %29, %30, %31, %32, %33, %34, %35, %36, %37, %38, %39, %40, %41, %42, %43, %44, %45, %46, %47, %48, %49, %50, %51, %52, %53, %54, %55, %56, %57, %58, %59, %60, %61, %62, %63}, "
    "{%64, %65, %66, %67}, db, p, 1, 1, 1;\n}\n"
    : "+f"(d[0]), "+f"(d[1]), "+f"(d[2]), "+f"(d[3]), "+f"(d[4]), "+f"(d[5]), "+f"(d[6]), "+f"(d[7]), "+f"(d[8]), "+f"(d[9]), "+f"(d[10]), "+f"(d[11]), "+f"(d[12]), "+f"(d[13]), "+f"(d[14]), "+f"(d[15]), "+f"(d[16]), "+f"(d[17]), "+f"(d[18]), "+f"(d[19]), "+f"(d[20]), "+f"(d[21]), "+f"(d[22]), "+f"(d[23]), "+f"(d[24]), "+f"(d[25]), "+f"(d[26]), "+f"(d[27]), "+f"(d[28]), "+f"(d[29]), "+f"(d[30]), "+f"(d[31]), "+f"(d[32]), "+f"(d[33]), "+f"(d[34]), "+f"(d[35]), "+f"(d[36]), "+f"(d[37]), "+f"(d[38]), "+f"(d[39]), "+f"(d[40]), "+f"(d[41]), "+f"(d[42]), "+f"(d[43]), "+f"(d[44]), "+f"(d[45]), "+f"(d[46]), "+f"(d[47]), "+f"(d[48]), "+f"(d[49]), "+f"(d[50]), "+f"(d[51]), "+f"(d[52]), "+f"(d[53]), "+f"(d[54]), "+f"(d[55]), "+f"(d[56]), "+f"(d[57]), "+f"(d[58]), "+f"(d[59]), "+f"(d[60]), "+f"(d[61]), "+f"(d[62]), "+f"(d[63])
    : "r"(a0), "r"(a1), "r"(a2), "r"(a3), "r"(b_lo), "r"(scaleD), "n"(OFFB));
}

template <int OFFB>
__device__ __forceinline__ void wgmma_m64n128k16_rs(float (&d)[64], uint32_t a0, uint32_t a1, uint32_t a2, uint32_t a3, uint32_t b_lo, int scaleD) {
  asm volatile("{\n.reg .pred p;\n.reg .b32 tb;\n.reg .b64 db;\nsetp.ne.b32 p, %69, 0;\n"
    "add.u32 tb, %68, %70;\n"
    "mov.b64 db, {tb, 0x40000040};\n"
    "wgmma.mma_async.sync.aligned.m64n128k16.f32.bf16.bf16 "
    "{%0, %1, %2, %3, %4, %5, %6, %7, %8, %9, %10, %11, %12, %13, %14, %15, %16, %17, %18, %19, %20, %21, %22, %23, %24, %25, %26, %27, %28, %29, %30, %31, %32, %33, %34, %35, %36, %37, %38, %39, %40, %41, %42, %43, %44, %45, %46, %47, %48, %49, %50, %51, %52, %53, %54, %55, %56, %57, %58, %59, %60, %61, %62, %63}, "
    "{%64, %65, %66, %67}, db, p, 1, 1, 0;\n}\n"
    : "+f"(d[0]), "+f"(d[1]), "+f"(d[2]), "+f"(d[3]), "+f"(d[4]), "+f"(d[5]), "+f"(d[6]), "+f"(d[7]), "+f"(d[8]), "+f"(d[9]), "+f"(d[10]), "+f"(d[11]), "+f"(d[12]), "+f"(d[13]), "+f"(d[14]), "+f"(d[15]), "+f"(d[16]), "+f"(d[17]), "+f"(d[18]), "+f"(d[19]), "+f"(d[20]), "+f"(d[21]), "+f"(d[22]), "+f"(d[23]), "+f"(d[24]), "+f"(d[25]), "+f"(d[26]), "+f"(d[27]), "+f"(d[28]), "+f"(d[29]), "+f"(d[30]), "+f"(d[31]), "+f"(d[32]), "+f"(d[33]), "+f"(d[34]), "+f"(d[35]), "+f"(d[36]), "+f"(d[37]), "+f"(d[38]), "+f"(d[39]), "+f"(d[40]), "+f"(d[41]), "+f"(d[42]), "+f"(d[43]), "+f"(d[44]), "+f"(d[45]), "+f"(d[46]), "+f"(d[47]), "+f"(d[48]), "+f"(d[49]), "+f"(d[50]), "+f"(d[51]), "+f"(d[52]), "+f"(d[53]), "+f"(d[54]), "+f"(d[55]), "+f"(d[56]), "+f"(d[57]), "+f"(d[58]), "+f"(d[59]), "+f"(d[60]), "+f"(d[61]), "+f"(d[62]), "+f"(d[63])
    : "r"(a0), "r"(a1), "r"(a2), "r"(a3), "r"(b_lo), "r"(scaleD), "n"(OFFB));
}

__device__ __forceinline__ uint4 ldg_nc_v4(const void* p) {
  uint4 v;
    asm volatile("{\n.reg .b64 pol;\ncreatepolicy.fractional.L2::evict_first.b64 pol, 1.0;\n"
                 "ld.global.nc.L1::no_allocate.L2::cache_hint.v4.u32 {%0, %1, %2, %3}, [%4], pol;\n}\n" : "=r"(v.x), "=r"(v.y), "=r"(v.z), "=r"(v.w) : "l"(p));
  return v;
}
__device__ __forceinline__ void unpack8(const uint4& u, float (&v)[8]) {
  v[0] = bflo(u.x); v[1] = bfhi(u.x); v[2] = bflo(u.y); v[3] = bfhi(u.y);
  v[4] = bflo(u.z); v[5] = bfhi(u.z); v[6] = bflo(u.w); v[7] = bfhi(u.w);
}
__device__ __forceinline__ void fma8(float (&acc)[8], float s, const uint4& w) {
  acc[0] = fmaf(s, bflo(w.x), acc[0]); acc[1] = fmaf(s, bfhi(w.x), acc[1]); acc[2] = fmaf(s, bflo(w.y), acc[2]); acc[3] = fmaf(s, bfhi(w.y), acc[3]);
  acc[4] = fmaf(s, bflo(w.z), acc[4]); acc[5] = fmaf(s, bfhi(w.z), acc[5]); acc[6] = fmaf(s, bflo(w.w), acc[6]); acc[7] = fmaf(s, bfhi(w.w), acc[7]);
}
__device__ __forceinline__ float rcp_approx(float x) { float y; asm("rcp.approx.ftz.f32 %0, %1;" : "=f"(y) : "f"(x)); return y; }
__device__ __forceinline__ float sigmoid_f(float v) { return rcp_approx(1.0f + ex2_approx(v * -1.4426950408889634f)); }
__device__ __forceinline__ float silu_bf(float v) { return rbf(v * sigmoid_f(v)); }
__device__ __forceinline__ uint32_t rank_key(float r, int idx) {
  const uint32_t b = __float_as_uint(r) >> 16;
  const uint32_t u = (r != r) ? 0u : ((b & 0x8000u) ? (~b & 0xffffu) : (b | 0x8000u));
  return (u << 16) | (0xffffu - (uint32_t)idx);
}
__device__ __forceinline__ void warp_top2(uint32_t& k1, uint32_t& k2) {
  const uint32_t m1 = __reduce_max_sync(0xffffffffu, k1);
  k2 = __reduce_max_sync(0xffffffffu, k1 == m1 ? k2 : k1);
  k1 = m1;
}
__device__ __forceinline__ uint32_t bmul2(uint32_t a, uint32_t b) { uint32_t r; asm("mul.rn.bf16x2 %0, %1, %2;" : "=r"(r) : "r"(a), "r"(b)); return r; }
__device__ __forceinline__ uint32_t badd2(uint32_t a, uint32_t b) { uint32_t r; asm("add.rn.bf16x2 %0, %1, %2;" : "=r"(r) : "r"(a), "r"(b)); return r; }
__device__ __forceinline__ uint32_t bsub2(uint32_t a, uint32_t b) { uint32_t r; asm("sub.rn.bf16x2 %0, %1, %2;" : "=r"(r) : "r"(a), "r"(b)); return r; }
__device__ __forceinline__ float sqrt_approx(float x) { float y; asm("sqrt.approx.f32 %0, %1;" : "=f"(y) : "f"(x)); return y; }
__device__ __forceinline__ uint32_t ln_norm2(uint32_t x1, uint32_t mb2, float inv) {
  const uint32_t d = bsub2(x1, mb2);
  return pack_bf16(bflo(d) * inv, bfhi(d) * inv);
}
__device__ __forceinline__ uint32_t bfma2(uint32_t a, uint32_t b, uint32_t c) { uint32_t r; asm("fma.rn.bf16x2 %0, %1, %2, %3;" : "=r"(r) : "r"(a), "r"(b), "r"(c)); return r; }
__device__ __forceinline__ uint32_t ln_norm2b(uint32_t x1, uint32_t mb2, uint32_t ih, uint32_t il) {
  const uint32_t d = bsub2(x1, mb2);
  return bfma2(d, ih, bmul2(d, il));
}
__device__ __forceinline__ uint32_t ln_mod2(uint32_t x1, uint32_t mb2, float inv, uint32_t c1, uint32_t sb) { return badd2(bmul2(ln_norm2(x1, mb2, inv), c1), sb); }
__device__ __forceinline__ void ldmatrix_x4(uint32_t addr, uint32_t& r0, uint32_t& r1, uint32_t& r2, uint32_t& r3) {
  asm volatile("ldmatrix.sync.aligned.m8n8.x4.shared.b16 {%0, %1, %2, %3}, [%4];" : "=r"(r0), "=r"(r1), "=r"(r2), "=r"(r3) : "r"(addr) : "memory");
}
__device__ __forceinline__ uint4 ldg_stream_v4(const void* p, uint64_t pol) {
  uint4 v; asm volatile("ld.global.nc.L1::no_allocate.L2::cache_hint.L2::128B.v4.u32 {%0, %1, %2, %3}, [%4], %5;" : "=r"(v.x), "=r"(v.y), "=r"(v.z), "=r"(v.w) : "l"(p), "l"(pol)); return v;
}
__device__ __forceinline__ void bulk_load_hint(uint32_t dst, const void* src, uint32_t bytes, uint32_t bar, uint64_t pol) {
  asm volatile("cp.async.bulk.shared::cluster.global.mbarrier::complete_tx::bytes.L2::cache_hint [%0], [%1], %2, [%3], %4;"
    :: "r"(dst), "l"(src), "r"(bytes), "r"(bar), "l"(pol) : "memory");
}
__device__ __forceinline__ void red_release_add(unsigned int* p, unsigned int v) { asm volatile("red.release.gpu.global.add.u32 [%0], %1;" :: "l"(p), "r"(v) : "memory"); }
__device__ __forceinline__ unsigned int ld_acquire(const unsigned int* p) { unsigned int v; asm volatile("ld.acquire.gpu.global.u32 %0, [%1];" : "=r"(v) : "l"(p) : "memory"); return v; }
__device__ __forceinline__ void spin_until(const unsigned int* p, unsigned int target) {
  #pragma unroll 1
  for (unsigned int i = 0; i < (1u << 22); i++) { if (ld_acquire(p) >= target) return; }
}
__device__ __forceinline__ float lds_f32(uint32_t a) { float v; asm volatile("ld.shared.f32 %0, [%1];" : "=f"(v) : "r"(a) : "memory"); return v; }
__device__ __forceinline__ float2 lds_f32x2(uint32_t a) { float2 v; asm volatile("ld.shared.v2.f32 {%0, %1}, [%2];" : "=f"(v.x), "=f"(v.y) : "r"(a) : "memory"); return v; }
__device__ __forceinline__ uint2 lds_u32x2(uint32_t a) { uint2 v; asm volatile("ld.shared.v2.u32 {%0, %1}, [%2];" : "=r"(v.x), "=r"(v.y) : "r"(a) : "memory"); return v; }
__device__ __forceinline__ uint32_t lds_u32(uint32_t a) { uint32_t v; asm volatile("ld.shared.u32 %0, [%1];" : "=r"(v) : "r"(a) : "memory"); return v; }
__device__ __forceinline__ void sts_u32(uint32_t a, uint32_t v) { asm volatile("st.shared.u32 [%0], %1;" :: "r"(a), "r"(v) : "memory"); }
__device__ __forceinline__ void sts_u32x2(uint32_t a, uint32_t x, uint32_t y) { asm volatile("st.shared.v2.u32 [%0], {%1, %2};" :: "r"(a), "r"(x), "r"(y) : "memory"); }
__device__ __forceinline__ void sts_f32(uint32_t a, float v) { asm volatile("st.shared.f32 [%0], %1;" :: "r"(a), "f"(v) : "memory"); }
__device__ __forceinline__ void sts_f32x2(uint32_t a, float x, float y) { asm volatile("st.shared.v2.f32 [%0], {%1, %2};" :: "r"(a), "f"(x), "f"(y) : "memory"); }
__device__ __forceinline__ void sts_f32x4(uint32_t a, float x, float y, float z, float w) { asm volatile("st.shared.v4.f32 [%0], {%1, %2, %3, %4};" :: "r"(a), "f"(x), "f"(y), "f"(z), "f"(w) : "memory"); }

__device__ __forceinline__ uint4 lds_u32x4(uint32_t a) { uint4 v; asm volatile("ld.shared.v4.u32 {%0, %1, %2, %3}, [%4];" : "=r"(v.x), "=r"(v.y), "=r"(v.z), "=r"(v.w) : "r"(a) : "memory"); return v; }
__device__ __forceinline__ void sts_u32x4(uint32_t a, uint32_t x, uint32_t y, uint32_t z, uint32_t w) { asm volatile("st.shared.v4.u32 [%0], {%1, %2, %3, %4};" :: "r"(a), "r"(x), "r"(y), "r"(z), "r"(w) : "memory"); }
__device__ __forceinline__ void st_tagged(float* p, float v) {
  const uint32_t b = __float_as_uint(v);
  asm volatile("st.relaxed.gpu.global.u32 [%0], %1;" :: "l"(p), "r"(b == 0u ? 0x80000000u : b) : "memory");
}
__device__ __forceinline__ void st_tagged4(float* p, float x, float y, float z, float w) {
  const uint32_t a = __float_as_uint(x), b = __float_as_uint(y), c = __float_as_uint(z), d = __float_as_uint(w);
  asm volatile("st.relaxed.gpu.global.v4.u32 [%0], {%1, %2, %3, %4};" :: "l"(p), "r"(a == 0u ? 0x80000000u : a), "r"(b == 0u ? 0x80000000u : b),
               "r"(c == 0u ? 0x80000000u : c), "r"(d == 0u ? 0x80000000u : d) : "memory");
}
__device__ __forceinline__ void st_relaxed2(void* p, uint32_t a, uint32_t b) { asm volatile("st.relaxed.gpu.global.v2.u32 [%0], {%1, %2};" :: "l"(p), "r"(a), "r"(b) : "memory"); }
__device__ __forceinline__ float4 ld_tagged4(const float* p) {
  float4 v; asm volatile("ld.relaxed.gpu.global.v4.f32 {%0, %1, %2, %3}, [%4];" : "=f"(v.x), "=f"(v.y), "=f"(v.z), "=f"(v.w) : "l"(p) : "memory"); return v;
}
__device__ __forceinline__ bool tagged4(const float4& v) {
  return __float_as_uint(v.x) != 0u && __float_as_uint(v.y) != 0u && __float_as_uint(v.z) != 0u && __float_as_uint(v.w) != 0u;
}
__device__ __forceinline__ void hint_arrive(uint32_t* p) { asm volatile("red.relaxed.gpu.global.add.u32 [%0], 1;" :: "l"(p) : "memory"); }
__device__ __forceinline__ void hint_wait(const uint32_t* p, uint32_t target) {
  uint32_t v = 0u;
  #pragma unroll 1
  for (unsigned int i = 0; i < (1u << 22) && v < target; i++) asm volatile("ld.relaxed.gpu.global.u32 %0, [%1];" : "=r"(v) : "l"(p) : "memory");
}
__device__ __forceinline__ void fence_proxy_async_global() { asm volatile("fence.proxy.async.global;" ::: "memory"); }

#define H_SPLIT 1
#define X_DLY 1200
#define W_DLY 1900
#define W_FIRST 2200
#define PRE_B 2
template <int J0, int J1>
__device__ __forceinline__ void load_parts(float2 (&pa)[J1 - J0][4], int t2) {
  #pragma unroll
  for (int j = J0; j < J1; j++)
    #pragma unroll
    for (int k = 0; k < 4; k++)
      asm volatile("ld.relaxed.gpu.global.v2.f32 {%0, %1}, [%2];" : "=f"(pa[j - J0][k].x), "=f"(pa[j - J0][k].y)
                   : "l"(g_modpart + k * 2 * T_D + (t2 >> 7) * T_D + j * 256 + (t2 & 127) * 2) : "memory");
}
template <int J0, int J1>
__device__ __forceinline__ void finish_parts(float2 (&pa)[J1 - J0][4], bool loaded, int t2, uint32_t tab) {
  #pragma unroll 1
  for (unsigned int spin = 0; spin < (1u << 22); spin++) {
    if (!loaded) load_parts<J0, J1>(pa, t2);
    loaded = false;
    bool ok = true;
    #pragma unroll
    for (int j = 0; j < J1 - J0; j++)
      #pragma unroll
      for (int k = 0; k < 4; k++) ok &= (__float_as_uint(pa[j][k].x) != 0u) & (__float_as_uint(pa[j][k].y) != 0u);
    if (__all_sync(0xffffffffu, ok)) break;
  }
  #pragma unroll
  for (int j = J0; j < J1; j++) {
    const float2* q = pa[j - J0];
    const uint32_t m = pack_bf16(((q[0].x + q[1].x) + q[2].x) + q[3].x, ((q[0].y + q[1].y) + q[2].y) + q[3].y);
    sts_u32(tab + (t2 >> 7) * 2048 + j * 512 + (t2 & 127) * 4, t2 >= 128 ? badd2(m, 0x3F803F80u) : m);
  }
}
__device__ __forceinline__ int head_cb(uint32_t bid) { return (bid & 16) | ((bid & 3) << 2) | ((bid >> 2) & 3); }
__device__ __forceinline__ void head_phase(uint32_t bid, uint32_t scr, uint32_t xs, uint32_t b_x, uint32_t b_go, uint32_t b_head, int t2, uint32_t zero, const bf16* __restrict__ cvec, const bf16* __restrict__ w_mod) {
  const int lane = t2 & 31, w8 = t2 >> 5;
  const int cb = head_cb(bid), ks = bid >> 5;
  const bool early = (cb & 15) < 4 * H_SPLIT;
  const uint32_t ws = (xs - 32768 + (t2 >> 3) * 128 + (((t2 ^ (t2 >> 3)) & 7) << 4)) ^ zero;
  const float cv = __bfloat162float(cvec[ks * 256 + t2]);
  const bf16* wsrc = w_mod + (size_t)(ks * 256 + (t2 >> 3)) * (6 * T_D) + cb * 64 + (t2 & 7) * 8;
  if (early) {
    const uint64_t pol = policy_evict_first();
    #pragma unroll 2
    for (int i = 0; i < 8; i++)
      asm volatile("cp.async.cg.shared.global.L2::cache_hint [%0], [%1], 16, %2;" :: "r"(ws + i * 4096), "l"(wsrc + (size_t)i * 32 * 6 * T_D), "l"(pol) : "memory");
  }
  sts_f32(scr + t2 * 4, silu_bf(cv));
  named_bar_sync(6, 384);
  TL_MARK2(1, t2 == 0);
  uint4 xv[2][4];
  uint32_t mb2[2], ih[2], il[2];
  auto norm = [&](int j) {
    #pragma unroll
    for (int r = 0; r < 2; r++) {
      xv[r][j].x = ln_norm2b(xv[r][j].x, mb2[r], ih[r], il[r]); xv[r][j].y = ln_norm2b(xv[r][j].y, mb2[r], ih[r], il[r]);
      xv[r][j].z = ln_norm2b(xv[r][j].z, mb2[r], ih[r], il[r]); xv[r][j].w = ln_norm2b(xv[r][j].w, mb2[r], ih[r], il[r]);
    }
  };
  auto modulate = [&](int j) {
    const uint4 sa = lds_u32x4(scr + 8192 + j * 512 + lane * 16), c1 = lds_u32x4(scr + 8192 + 2048 + j * 512 + lane * 16);
    #pragma unroll
    for (int r = 0; r < 2; r++) {
      xv[r][j].x = badd2(bmul2(xv[r][j].x, c1.x), sa.x); xv[r][j].y = badd2(bmul2(xv[r][j].y, c1.y), sa.y);
      xv[r][j].z = badd2(bmul2(xv[r][j].z, c1.z), sa.z); xv[r][j].w = badd2(bmul2(xv[r][j].w, c1.w), sa.w);
    }
  };
  auto store = [&](int j) {
    #pragma unroll
    for (int r = 0; r < 2; r++) *reinterpret_cast<uint4*>(g_h + (size_t)(bid * 16 + 2 * w8 + r) * T_D + j * 256 + lane * 8) = xv[r][j];
  };
  #pragma unroll 1
  for (int ph = 0; ph < 2; ph++) {
    if ((ph == 0) == early) {
      asm volatile("cp.async.wait_all;" ::: "memory");
      if (!early) mbar_wait(b_x + 168, 0);
      float acc[8];
      #pragma unroll
      for (int j = 0; j < 8; j++) acc[j] = 0.f;
      #pragma unroll
      for (int i = 0; i < 8; i++) fma8(acc, lds_f32(scr + ((t2 >> 3) + 32 * i) * 4), lds_u32x4(ws + i * 4096));
      #pragma unroll
      for (int j = 0; j < 4; j++) { const bool up = lane & 16; acc[j] = (up ? acc[4 + j] : acc[j]) + __shfl_xor_sync(0xffffffffu, up ? acc[j] : acc[4 + j], 16); }
      #pragma unroll
      for (int j = 0; j < 2; j++) { const bool up = lane & 8; acc[j] = (up ? acc[2 + j] : acc[j]) + __shfl_xor_sync(0xffffffffu, up ? acc[j] : acc[2 + j], 8); }
      sts_f32x2(scr + 1024 + w8 * 256 + (lane & 7) * 32 + (lane >> 3) * 8, acc[0], acc[1]);
      named_bar_sync(5, 256);
      if (t2 < 64) {
        float sum = 0.f;
        #pragma unroll
        for (int i = 0; i < 8; i++) sum += lds_f32(scr + 1024 + i * 256 + t2 * 4);
        st_tagged(g_modpart + ks * 2 * T_D + cb * 64 + t2, sum);
        TL_MARK2(early ? 2 : 6, t2 == 0);
      }
    } else {
      float2 pa[H_SPLIT][4];
      mbar_wait(b_x, 0);
      TL_MARK2(18, t2 == 0);
      load_parts<0, H_SPLIT>(pa, t2);
      #pragma unroll
      for (int r = 0; r < 2; r++)
        #pragma unroll
        for (int j = 0; j < 4; j++) xv[r][j] = lds_u32x4(xs + (2 * w8 + r) * 2048 + j * 512 + lane * 16);
  {
    float st[4] = {0.f, 0.f, 0.f, 0.f};
    #pragma unroll
    for (int r = 0; r < 2; r++)
      #pragma unroll
      for (int j = 0; j < 4; j++) {
        float v[8];
        unpack8(xv[r][j], v);
        st[2 * r] += ((v[0] + v[1]) + (v[2] + v[3])) + ((v[4] + v[5]) + (v[6] + v[7]));
        st[2 * r + 1] += fmaf(v[0], v[0], fmaf(v[1], v[1], fmaf(v[2], v[2], v[3] * v[3]))) + fmaf(v[4], v[4], fmaf(v[5], v[5], fmaf(v[6], v[6], v[7] * v[7])));
      }
    #pragma unroll
    for (int k = 0; k < 2; k++) { const bool up = lane & 16; st[k] = (up ? st[2 + k] : st[k]) + __shfl_xor_sync(0xffffffffu, up ? st[k] : st[2 + k], 16); }
    #pragma unroll
    for (int o = 8; o > 0; o >>= 1) { st[0] += __shfl_xor_sync(0xffffffffu, st[0], o); st[1] += __shfl_xor_sync(0xffffffffu, st[1], o); }
    const float mean = st[0] * (1.0f / T_D);
    const float inv = rcp_approx(rbf(sqrt_approx(rbf(rbf(fmaxf(fmaf(-mean, mean, st[1] * (1.0f / T_D)), 0.f)) + 1e-05f))));
    const uint32_t m = pack_bf16(mean, mean), h = pack_bf16(inv - rbf(inv), inv);
    #pragma unroll
    for (int r = 0; r < 2; r++) {
      mb2[r] = __shfl_sync(0xffffffffu, m, 16 * r);
      const uint32_t hr = __shfl_sync(0xffffffffu, h, 16 * r);
      ih[r] = __byte_perm(hr, hr, 0x3232); il[r] = __byte_perm(hr, hr, 0x1010);
    }
  }
      #pragma unroll
      for (int j = 0; j < H_SPLIT; j++) norm(j);
      TL_MARK2(5, t2 == 0);
      finish_parts<0, H_SPLIT>(pa, true, t2, scr + 8192);
      named_bar_sync(5, 256);
      TL_MARK2(7, t2 == 0);
      #pragma unroll
      for (int j = 0; j < H_SPLIT; j++) { modulate(j); store(j); }
      named_bar_arrive(9, 288);
    }
  }
  #pragma unroll
  for (int j = H_SPLIT; j < 4; j++) norm(j);
  float2 pb[4 - H_SPLIT][4];
  finish_parts<H_SPLIT, 4>(pb, false, t2, scr + 8192);
  named_bar_sync(5, 256);
  TL_MARK2(17, t2 == 0);
  #pragma unroll
  for (int j = H_SPLIT; j < 4; j++) modulate(j);
  __syncwarp();
  if (lane == 0) mbar_arrive(b_head + (xv[1][3].w & zero));
  mbar_wait(b_go, 0);
  #pragma unroll
  for (int j = H_SPLIT; j < 4; j++) store(j);
  named_bar_arrive(8, 288);
}

#define MOD_AT (b_empty + 8)
#define MOD_SPLIT 16
__device__ __forceinline__ void mod_rest(uint32_t bid, uint32_t scr, uint32_t b_go, int t, const bf16* __restrict__ cvec, const bf16* __restrict__ w_mod, const bf16* __restrict__ w_r) {
  const int lane = t & 31;
  #pragma unroll 1
  for (int i = t; i < T_D / 2; i += 64) {
    const uint32_t c2 = *reinterpret_cast<const uint32_t*>(cvec + 2 * i);
    sts_u32(scr + i * 4, pack_bf16(silu_bf(bflo(c2)), silu_bf(bfhi(c2))));
  }
  named_bar_sync(11, 64);
  const bf16* wp = w_mod + (size_t)(2 * (t >> 2)) * (6 * T_D) + 2 * T_D + bid * 32 + (t & 3) * 8;
  float acc[8];
  #pragma unroll
  for (int i = 0; i < 8; i++) acc[i] = 0.f;
  #pragma unroll 1
  for (int i = 0; i < 32; i += 2) {
    if (i == MOD_SPLIT) mbar_wait_long(b_go, 0);
    const uint4 w0 = ldg_nc_v4(wp), w1 = ldg_nc_v4(wp + 6 * T_D), w2 = ldg_nc_v4(wp + 32 * 6 * T_D), w3 = ldg_nc_v4(wp + 33 * 6 * T_D);
    wp += 64 * 6 * T_D;
    const uint32_t s0 = lds_u32(scr + (i * 16 + (t >> 2)) * 4), s1 = lds_u32(scr + (i * 16 + 16 + (t >> 2)) * 4);
    fma8(acc, bflo(s0), w0); fma8(acc, bfhi(s0), w1); fma8(acc, bflo(s1), w2); fma8(acc, bfhi(s1), w3);
  }
  #pragma unroll
  for (int j = 0; j < 4; j++) { const bool up = lane & 16; acc[j] = (up ? acc[4 + j] : acc[j]) + __shfl_xor_sync(0xffffffffu, up ? acc[j] : acc[4 + j], 16); }
  #pragma unroll
  for (int j = 0; j < 2; j++) { const bool up = lane & 8; acc[j] = (up ? acc[2 + j] : acc[j]) + __shfl_xor_sync(0xffffffffu, up ? acc[j] : acc[2 + j], 8); }
  { const bool up = lane & 4; acc[0] = (up ? acc[1] : acc[0]) + __shfl_xor_sync(0xffffffffu, up ? acc[0] : acc[1], 4); }
  if (t >= 32) sts_f32(scr + 2048 + lane * 4, acc[0]);
  named_bar_sync(11, 64);
  if (__shfl_sync(0xffffffffu, t, 0) < 32) {
    const int kind = bid >> 5;
    float v = rbf(acc[0] + lds_f32(scr + 2048 + lane * 4));
    const int col = (bid & 31) * 32 + (lane & 3) * 8 + (lane >> 2);
    uint8_t* dst = g_col + (col >> 7) * 1536;
    if (kind == 2) v = rbf(1.0f + v);
    float vw = v * __bfloat162float(w_r[col]);
    if (kind == 2) {
      const int c = col & 127, i = (c & ~15) + ((c >> 1) & 3) * 4 + ((c >> 3) & 1) * 2 + (c & 1);
      reinterpret_cast<bf16*>(dst)[i] = __float2bfloat16_rn(vw);
      reinterpret_cast<bf16*>(dst)[128 + i] = __float2bfloat16_rn(vw - rbf(vw));
    }
    reinterpret_cast<bf16*>(dst + 512 + (kind & 1) * 512 + (kind >> 1) * 256)[col & 127] = __float2bfloat16_rn(v);
    #pragma unroll
    for (int o = 16; o > 0; o >>= 1) vw += __shfl_xor_sync(0xffffffffu, vw, o);
    if (lane == 0 && (kind == 1 || kind == 2)) g_scal[95 - bid] = vw;
  }
  #pragma unroll 1
  for (int i = bid * 64 + t; i < (int)(sizeof(g_mail) / 16); i += 128 * 64) reinterpret_cast<uint4*>(&g_mail)[i] = make_uint4(0u, 0u, 0u, 0u);
  named_bar_sync(11, 64);
  if (t == 0) red_release_add(&g_hcnt[0], 1u);
}

constexpr int AT_NBLK = T_SEQ / 128;
constexpr float AT_HEAD = 7.0f;
#define WO_LATE 12
#define QP_STAG 3
#define AT_SPLIT 28
#define AT_PIN 12
#define PINB 4
constexpr int AT_NFULL = 124;
constexpr int AT_PREG = 40, AT_CREG = 232;
constexpr uint32_t AT_SQ = 5 * 32768;
constexpr float AT_C = 0.08838834764831845f * 1.4426950408889634f;
constexpr float AT_RAW_LO = -16.0f, AT_RAW_HI = 24.0f;
constexpr float AT_RAW_SUM = 281474976710656.0f, AT_RAW_MIN = 9.094947017729282e-13f;
constexpr uint32_t AT_SBAR = AT_SQ + 65536 + 256;
constexpr uint32_t AT_SMEM = AT_SQ + 65536 + 3072;

__device__ __forceinline__ uint32_t ring_slot(uint32_t t) { return t - 5u * ((t * 205u) >> 10); }
__device__ __forceinline__ uint32_t qp_pos(uint32_t j, uint32_t it) { return 4u * it + (j & 3u) + ((j & 3u) == 3u ? it : 0u); }
__device__ __forceinline__ uint32_t ring_par(uint32_t t) { return ((t * 205u) >> 10) & 1u; }
__device__ __forceinline__ void softmax_rowmax(const float (&s)[64], float& mx0, float& mx1) {
  float a0 = fmaxf(s[0], s[1]), a1 = fmaxf(s[4], s[5]), a2 = fmaxf(s[8], s[9]), a3 = fmaxf(s[12], s[13]);
  float b0 = fmaxf(s[2], s[3]), b1 = fmaxf(s[6], s[7]), b2 = fmaxf(s[10], s[11]), b3 = fmaxf(s[14], s[15]);
  #pragma unroll
  for (int j = 4; j < 16; j += 4) {
    a0 = fmaxf(a0, fmaxf(s[4 * j + 0], s[4 * j + 1]));  b0 = fmaxf(b0, fmaxf(s[4 * j + 2], s[4 * j + 3]));
    a1 = fmaxf(a1, fmaxf(s[4 * j + 4], s[4 * j + 5]));  b1 = fmaxf(b1, fmaxf(s[4 * j + 6], s[4 * j + 7]));
    a2 = fmaxf(a2, fmaxf(s[4 * j + 8], s[4 * j + 9]));  b2 = fmaxf(b2, fmaxf(s[4 * j + 10], s[4 * j + 11]));
    a3 = fmaxf(a3, fmaxf(s[4 * j + 12], s[4 * j + 13])); b3 = fmaxf(b3, fmaxf(s[4 * j + 14], s[4 * j + 15]));
  }
  mx0 = fmaxf(fmaxf(a0, a1), fmaxf(a2, a3));
  mx1 = fmaxf(fmaxf(b0, b1), fmaxf(b2, b3));
  mx0 = fmaxf(mx0, __shfl_xor_sync(0xffffffffu, mx0, 1));
  mx1 = fmaxf(mx1, __shfl_xor_sync(0xffffffffu, mx1, 1));
  mx0 = fmaxf(mx0, __shfl_xor_sync(0xffffffffu, mx0, 2));
  mx1 = fmaxf(mx1, __shfl_xor_sync(0xffffffffu, mx1, 2));
}
__device__ __forceinline__ void softmax_sub(float (&s)[64], float mc0, float mc1) {
  #pragma unroll
  for (int j = 0; j < 16; j++) { s[4 * j] -= mc0; s[4 * j + 1] -= mc0; s[4 * j + 2] -= mc1; s[4 * j + 3] -= mc1; }
}
template <int LO, int HI>
__device__ __forceinline__ void softmax_exp(float (&s)[64]) {
  #pragma unroll
  for (int i = LO; i < HI; i++) s[i] = ex2_approx(s[i]);
}
__device__ __forceinline__ bool softmax_mode(const float (&s)[64], float& mc0, float& mc1) {
  softmax_rowmax(s, mc0, mc1);
  const bool raw = __all_sync(0xffffffffu, mc0 >= AT_RAW_LO && mc0 <= AT_RAW_HI && mc1 >= AT_RAW_LO && mc1 <= AT_RAW_HI);
  mc0 += AT_HEAD; mc1 += AT_HEAD;
  return raw;
}
__device__ __forceinline__ void rowsum_p(const uint32_t (&p)[32], uint32_t& t0, uint32_t& t1) {
  uint32_t a[16];
  #pragma unroll
  for (int i = 0; i < 8; i++) { a[2 * i] = badd2(p[4 * i], p[4 * i + 2]); a[2 * i + 1] = badd2(p[4 * i + 1], p[4 * i + 3]); }
  #pragma unroll
  for (int i = 0; i < 4; i++) { a[2 * i] = badd2(a[4 * i], a[4 * i + 2]); a[2 * i + 1] = badd2(a[4 * i + 1], a[4 * i + 3]); }
  t0 = badd2(badd2(a[0], a[2]), badd2(a[4], a[6]));
  t1 = badd2(badd2(a[1], a[3]), badd2(a[5], a[7]));
}
__device__ __forceinline__ void add_rowsum(const uint32_t (&p)[32], float& l0, float& l1) {
  uint32_t t0, t1;
  rowsum_p(p, t0, t1);
  l0 += bflo(t0) + bfhi(t0); l1 += bflo(t1) + bfhi(t1);
}
__device__ __forceinline__ void pack_p(uint32_t (&p)[32], const float (&s)[64]) {
  #pragma unroll
  for (int i = 0; i < 32; i++) p[i] = pack_bf16(s[2 * i], s[2 * i + 1]);
}
__device__ __noinline__ void attn_rows_exact(uint32_t bid, uint32_t sq, uint32_t so, int hsel, const bf16* __restrict__ kh, const bf16* __restrict__ vh) {
  const int warp = (threadIdx.x >> 5) & 3, lane = threadIdx.x & 31;
  const size_t hofs = (size_t)((bid < 128 ? bid >> 4 : 15) * 2 + hsel) * T_SEQ * T_DH;
  kh += hofs; vh += hofs;
  #pragma unroll 1
  for (int r = 16 * warp; r < 16 * warp + 16; r++) {
    const uint32_t ad = (lane >> 4) * 16384 + r * 128 + ((((lane & 15) >> 1) ^ (r & 7)) << 4) + (lane & 1) * 8;
    uint2 qv; asm volatile("ld.shared.v2.u32 {%0, %1}, [%2];" : "=r"(qv.x), "=r"(qv.y) : "r"(sq + ad) : "memory");
    const float q0 = bflo(qv.x), q1 = bfhi(qv.x), q2 = bflo(qv.y), q3 = bfhi(qv.y);
    float m = -INFINITY, l = 0.f, o0 = 0.f, o1 = 0.f, o2 = 0.f, o3 = 0.f;
    #pragma unroll 1
    for (int key = 0; key < T_SEQ; key++) {
      const uint2 kv = *reinterpret_cast<const uint2*>(kh + (size_t)key * T_DH + lane * 4);
      const uint2 vv = *reinterpret_cast<const uint2*>(vh + (size_t)key * T_DH + lane * 4);
      float sc = (q0 * bflo(kv.x) + q1 * bfhi(kv.x)) + (q2 * bflo(kv.y) + q3 * bfhi(kv.y));
      #pragma unroll
      for (int o = 16; o > 0; o >>= 1) sc += __shfl_xor_sync(0xffffffffu, sc, o);
      const float mn = fmaxf(m, sc);
      const float al = (m == mn) ? 1.0f : ex2_approx(m - mn), p = rbf(ex2_approx(sc - mn));
      m = mn;
      l = fmaf(l, al, p);
      o0 = fmaf(o0, al, p * bflo(vv.x)); o1 = fmaf(o1, al, p * bfhi(vv.x));
      o2 = fmaf(o2, al, p * bflo(vv.y)); o3 = fmaf(o3, al, p * bfhi(vv.y));
    }
    const float inv = rcp_approx(l);
    asm volatile("st.shared.v2.u32 [%0], {%1, %2};" :: "r"(so + ad), "r"(pack_bf16(o0 * inv, o1 * inv)), "r"(pack_bf16(o2 * inv, o3 * inv)) : "memory");
  }
}
__device__ __forceinline__ void issue_qk(float (&s)[64], const uint32_t (&q)[32], uint32_t k_lo) {
  wgmma_fence();
  wgmma_m64n128k16_rs<0>(s, q[0], q[1], q[2], q[3], k_lo, 0);
  wgmma_m64n128k16_rs<2>(s, q[4], q[5], q[6], q[7], k_lo, 1);
  wgmma_m64n128k16_rs<4>(s, q[8], q[9], q[10], q[11], k_lo, 1);
  wgmma_m64n128k16_rs<6>(s, q[12], q[13], q[14], q[15], k_lo, 1);
  wgmma_m64n128k16_rs<1024>(s, q[16], q[17], q[18], q[19], k_lo, 1);
  wgmma_m64n128k16_rs<1026>(s, q[20], q[21], q[22], q[23], k_lo, 1);
  wgmma_m64n128k16_rs<1028>(s, q[24], q[25], q[26], q[27], k_lo, 1);
  wgmma_m64n128k16_rs<1030>(s, q[28], q[29], q[30], q[31], k_lo, 1);
  wgmma_commit();
}
__device__ __forceinline__ void issue_pv(float (&o)[64], const uint32_t (&p)[32], uint32_t v_lo, int accumulate) {
  wgmma_fence();
  wgmma_m64n128k16_rs_tb<0>(o, p[0], p[1], p[2], p[3], v_lo, accumulate);
  wgmma_m64n128k16_rs_tb<128>(o, p[4], p[5], p[6], p[7], v_lo, 1);
  wgmma_m64n128k16_rs_tb<256>(o, p[8], p[9], p[10], p[11], v_lo, 1);
  wgmma_m64n128k16_rs_tb<384>(o, p[12], p[13], p[14], p[15], v_lo, 1);
  wgmma_m64n128k16_rs_tb<512>(o, p[16], p[17], p[18], p[19], v_lo, 1);
  wgmma_m64n128k16_rs_tb<640>(o, p[20], p[21], p[22], p[23], v_lo, 1);
  wgmma_m64n128k16_rs_tb<768>(o, p[24], p[25], p[26], p[27], v_lo, 1);
  wgmma_m64n128k16_rs_tb<896>(o, p[28], p[29], p[30], p[31], v_lo, 1);
  wgmma_commit();
}
__device__ __forceinline__ void block_end(uint32_t zero, uint32_t bar) {
  #pragma unroll 1
  for (uint32_t i = 0; i < zero; i++) mbar_arrive(bar);
}
__device__ __forceinline__ void rescale_o(float (&o)[64], float al0, float al1) {
  #pragma unroll
  for (int j = 0; j < 16; j++) { o[4 * j] *= al0; o[4 * j + 1] *= al0; o[4 * j + 2] *= al1; o[4 * j + 3] *= al1; }
}

__device__ __forceinline__ void stage_o(const float (&o)[64], float i0, float i1, uint32_t dst, int lane) {
  #pragma unroll
  for (int J = 0; J < 16; J += 2)
    stmatrix_x4(dst + (J >> 3) * 16384 + ((((J & 7) + (lane >> 4)) ^ (lane & 7)) << 4),
                pack_bf16(o[4 * J + 0] * i0, o[4 * J + 1] * i0), pack_bf16(o[4 * J + 2] * i1, o[4 * J + 3] * i1),
                pack_bf16(o[4 * J + 4] * i0, o[4 * J + 5] * i0), pack_bf16(o[4 * J + 6] * i1, o[4 * J + 7] * i1));
}
__device__ __forceinline__ bool finish_l(float& l0, float& l1) {
  l0 += __shfl_xor_sync(0xffffffffu, l0, 1); l1 += __shfl_xor_sync(0xffffffffu, l1, 1);
  l0 += __shfl_xor_sync(0xffffffffu, l0, 2); l1 += __shfl_xor_sync(0xffffffffu, l1, 2);
  const bool redo = __any_sync(0xffffffffu, !(l0 <= AT_RAW_SUM && l1 <= AT_RAW_SUM && l0 >= AT_RAW_MIN && l1 >= AT_RAW_MIN));
  l0 = rcp_approx(l0); l1 = rcp_approx(l1);
  return redo;
}
template <int J0>
__device__ __forceinline__ void stage_q(const float (&acc)[128], float c, uint32_t dst, int lane) {
  #pragma unroll
  for (int J = J0; J < J0 + 16; J += 2)
    stmatrix_x4(dst + (J >> 3) * 16384 + ((((J & 7) + (lane >> 4)) ^ (lane & 7)) << 4),
                pack_bf16(acc[4 * J + 0] * c, acc[4 * J + 1] * c), pack_bf16(acc[4 * J + 2] * c, acc[4 * J + 3] * c),
                pack_bf16(acc[4 * J + 4] * c, acc[4 * J + 5] * c), pack_bf16(acc[4 * J + 6] * c, acc[4 * J + 7] * c));
}
__device__ __forceinline__ void store_o(const CUtensorMap* tmO, uint32_t src, int head, int row) {
  tma_store_2d(tmO, src, head * T_DH, row);
  tma_store_2d(tmO, src + 16384, head * T_DH + 64, row);
  bulk_commit();
}
__device__ __forceinline__ void mma_bf16(float (&d)[4], uint32_t a0, uint32_t a1, uint32_t a2, uint32_t a3, uint32_t b0, uint32_t b1) {
  asm volatile("mma.sync.aligned.m16n8k16.row.col.f32.bf16.bf16.f32 {%0, %1, %2, %3}, {%4, %5, %6, %7}, {%8, %9}, {%0, %1, %2, %3};"
               : "+f"(d[0]), "+f"(d[1]), "+f"(d[2]), "+f"(d[3]) : "r"(a0), "r"(a1), "r"(a2), "r"(a3), "r"(b0), "r"(b1));
}
struct GemvSel { uint32_t lo0, hi0, lo1, hi1; };
__device__ __forceinline__ GemvSel gemv_sel(int lane) {
  const uint32_t lo = (lane & 8) ? 0x1044u : 0x4410u, hi = (lane & 8) ? 0x3244u : 0x4432u;
  GemvSel s; s.lo0 = (lane & 16) ? 0x4444u : lo; s.hi0 = (lane & 16) ? 0x4444u : hi; s.lo1 = (lane & 16) ? lo : 0x4444u; s.hi1 = (lane & 16) ? hi : 0x4444u;
  return s;
}
#define GEMV_B0(j, h, s) __byte_perm((j) < 2 ? (h).x : (h).y, 0u, ((j) & 1) ? (s).hi0 : (s).lo0)
#define GEMV_B1(j, h, s) __byte_perm((j) < 2 ? (h).x : (h).y, 0u, ((j) & 1) ? (s).hi1 : (s).lo1)
__device__ __forceinline__ float4 gemv_out(const float (&d)[4], int lane) {
  const bool tk = lane & 1;
  const float r0 = __shfl_xor_sync(0xffffffffu, tk ? d[0] : d[1], 1), r1 = __shfl_xor_sync(0xffffffffu, tk ? d[2] : d[3], 1);
  return tk ? make_float4(r0, d[1], r1, d[3]) : make_float4(d[0], r0, d[2], r1);
}
#define OG_NG 8
#define PUT_N 2
#define H_STAG 2
#define AL_P 60
#define AL_SLEEP 1200
#define AL_MAX 800
#define POLL_NS 500
#define OG_PROF 0xDDCBAA98u
#define RK_P 24
__host__ __device__ constexpr int og_pre(int tile) { return (OG_PROF >> ((tile >> 4) * 4)) & 15; }
constexpr int OG_PRE2 = og_pre(127), OG_HSUM = og_pre(0) + og_pre(16) + og_pre(32) + og_pre(48) + og_pre(64) + og_pre(80) + og_pre(96);
#define OG_JOBS 7
#define OG_GRP 6
#define LD_FIRST 2
#define LD_STAG (OG_GRP / 2)
constexpr int OG_ST = 5, OG_NKB = T_DQKV / 64 - og_pre(0), OG_MOE = T_F / 32;
__device__ __forceinline__ int pre_kb(int i) { return (i >> 1) * 4 + (i & 1); }
__device__ __forceinline__ int own_kb(int i, int pre) { return i < (pre & ~1) ? pre_kb(i) + 2 : i + pre; }
constexpr int OG_POS = 8;
constexpr uint32_t OG_STAGE = 32768;
constexpr uint32_t OG_SCOL = AT_SBAR + 512;
constexpr uint32_t OG_SMISC = AT_SBAR + 2048;
constexpr uint32_t OG_SWD = AT_SQ, OG_PSLOT = AT_SQ;
constexpr uint32_t OG_XSLOT = AT_SQ + 32768;
constexpr uint32_t OG_OSLOT = 1 * OG_STAGE;
constexpr uint32_t OG_SRED = 3 * OG_STAGE;
constexpr uint32_t OG_SH2 = OG_SRED + 24576;
constexpr uint32_t OG_SSTAT = OG_SRED + 16384;
constexpr uint32_t OG_SGU = OG_SRED + 8192;
constexpr uint32_t OG_SFIN = OG_SGU + 256;
#define OGM 2
#define OG_MT(b) ((((b) >> OGM) & 15) ^ (((b) & 64) ? 15 : 0))
#define OG_NT(b) (((b) & ((1 << OGM) - 1)) + (((b) >> (4 + OGM)) << OGM))
__device__ __forceinline__ int tail_tile(uint32_t sbase) { mbar_wait_long(sbase + AT_SBAR + 336, 0); return (int)lds_u32(sbase + AT_SBAR + 408); }
#define TAIL_SETUP \
  const uint32_t bar_full = sbase + AT_SBAR, bar_empty = bar_full + 40; \
  const uint32_t bar_wd = bar_full + 168, bar_col = bar_full + 176, bar_out = bar_full + 184, bar_end = bar_full + 192; \
  const uint32_t bar_key = bar_full + 200, bar_h2 = bar_full + 208, bar_sel = bar_full + 216; \
  const int mt = OG_MT(tb), nt = OG_NT(tb); \
  const int m0 = mt * 128, n0 = nt * 128; \
  const bool has_moe = (int)bid < OG_MOE; \
  (void)bar_empty; (void)bar_wd; (void)bar_col; (void)bar_out; (void)bar_end; (void)bar_key; (void)bar_h2; (void)bar_sel; (void)m0; (void)n0; (void)has_moe;

__device__ __forceinline__ void tail_producer(uint32_t bid, uint32_t sbase, uint32_t ph, uint64_t pol, const CUtensorMap* tmA, const CUtensorMap* tmB, const CUtensorMap* tmD) {
  const int tb = tail_tile(sbase);
  TAIL_SETUP
  uint32_t stage = OG_POS % OG_ST;
  int kb = 0;
  #pragma unroll 1
  for (int seg = 0; seg < 2; seg++) {
    mbar_wait(bar_full + 264 + 80 * seg, 0);
    fence_proxy_async_global();
    const int end = 32 + 32 * seg - og_pre(tb);
    #pragma unroll 1
    for (; kb < end; kb++) {
      const uint32_t fb = bar_full + 8 * stage, sa = sbase + stage * OG_STAGE;
      const int k0 = own_kb(kb, og_pre(tb)) * 64;
      mbar_wait(bar_empty + 8 * stage, ph);
      mbar_expect_tx(fb, OG_STAGE);
      tma_load_3d_hint(sa + 16384, tmB, k0, 2 * nt, fb, pol);
      tma_load_2d_hint(sa, tmA, k0, m0, fb, pol);
      if (++stage == OG_ST) { stage = 0; ph ^= 1; }
    }
  }
  if (has_moe) {
    stage += stage & 1;
    mbar_wait(bar_empty + 8 * stage, ph);
    mbar_expect_tx(bar_wd, OG_STAGE);
    tma_load_3d_hint(sbase + stage * OG_STAGE, tmD, bid * 32, 8, bar_wd, pol);
  }
}

__device__ __forceinline__ uint32_t out2(uint32_t x1, uint32_t mb2, uint32_t ih, uint32_t il, uint32_t c1, uint32_t sb, uint32_t gb) {
  const uint32_t h2 = badd2(bmul2(ln_norm2b(x1, mb2, ih, il), c1), sb);
  return badd2(x1, bmul2(gb, bfma2(h2, 0u, h2)));
}
#define X_PACE 200
#define Y_SLACK 96
#define OG_STAG 3
#define X_PACE2 100
#define POLL_NS2 100
#define WD_PACE 300
__device__ __forceinline__ void tail_exchange(uint32_t bid, uint32_t sbase, const bf16* __restrict__ w_down, const bf16* __restrict__ w_r, const bf16* __restrict__ x, bf16* __restrict__ out) {
    const int lane = threadIdx.x & 31, wi = __shfl_sync(0xffffffffu, threadIdx.x >> 5, 0);
    if (wi == 3) {
      uint32_t a = bid, b = 0u;
      if (bid < AT_NFULL) mbar_wait_long(sbase + AT_SBAR + 312, 0);
      if (bid < OG_MOE) {
        asm volatile("mov.u32 %0, %%globaltimer_lo;" : "=r"(a));
        if (lane == 0 && (bid & 15) == 0) asm volatile("st.relaxed.gpu.global.u32 [%0], %1;" :: "l"(g_hcnt + 8 + (bid >> 4)), "r"((a & ~15u) | 8u | (bid >> 4)) : "memory");
        #pragma unroll 1
        for (unsigned int spin = 0; spin < (1u << 22) && __any_sync(0xffffffffu, b == 0u); spin++) {
          __nanosleep(200);
          asm volatile("ld.relaxed.gpu.global.u32 %0, [%1];" : "=r"(b) : "l"(g_hcnt + 8 + min(lane, 6)) : "memory");
        }
        a = __popc(__ballot_sync(0xffffffffu, b < __shfl_sync(0xffffffffu, b, bid >> 4)) & 127u) * 16 + (bid & 15);
      }
      if (lane == 0) {
        sts_u32(sbase + AT_SBAR + 408, a);
        mbar_arrive(sbase + AT_SBAR + 336);
        b = 0u;
        if (bid < AT_NFULL) {
          unsigned int* tm = g_hcnt + 32 * (1 + (bid >> 4)) + 8;
          mbar_wait_long(sbase + AT_SBAR + 312, 1);
          asm volatile("mov.u32 %0, %%globaltimer_lo;" : "=r"(a));
          asm volatile("red.relaxed.gpu.global.max.u32 [%0], %1;" :: "l"(tm), "r"(a) : "memory");
          __nanosleep(AL_SLEEP);
          asm volatile("ld.relaxed.gpu.global.u32 %0, [%1];" : "=r"(b) : "l"(tm) : "memory");
          b -= a;
        }
        sts_u32(sbase + AT_SBAR + 412, b < AL_MAX ? b * 13 / 8 : 0u);
        mbar_arrive(sbase + AT_SBAR + 320);
      }
      named_bar_sync(15, 32);
    }
    const int tb = __shfl_sync(0xffffffffu, tail_tile(sbase), 0);
    TAIL_SETUP
    if (wi == 3) {
      mbar_wait_long(bar_full + 344, 0);
      float a = g_scal[lane], b = g_scal[32 + lane];
      #pragma unroll
      for (int i = 0; i < 3; i++) {
        const uint4 v = *reinterpret_cast<const uint4*>(g_col + nt * 1536 + i * 512 + lane * 16);
        sts_u32x4(sbase + OG_SCOL + i * 512 + lane * 16, v.x, v.y, v.z, v.w);
      }
      #pragma unroll
      for (int o = 16; o > 0; o >>= 1) { a += __shfl_xor_sync(0xffffffffu, a, o); b += __shfl_xor_sync(0xffffffffu, b, o); }
      if (lane == 0) sts_f32x2(sbase + OG_SMISC, a, b);
      const uint64_t pol = policy_evict_first();
      #pragma unroll 1
      for (int r = lane >> 4; r < 128; r += 4) {
        __nanosleep(X_PACE);
        if (X_PACE2) __nanosleep(X_PACE2);
        #pragma unroll
        for (int j = 0; j < 4; j += 2)
          asm volatile("cp.async.cg.shared.global.L2::cache_hint [%0], [%1], 16, %2;" :: "r"(sbase + OG_XSLOT + (lane & 8) * 2048 + (r + j) * 128 + (((lane ^ (r + j)) & 7) << 4)),
                       "l"(x + (size_t)(m0 + r + j) * T_D + n0 + (lane & 15) * 8), "l"(pol) : "memory");
      }
      asm volatile("cp.async.wait_all;" ::: "memory");
      __syncwarp();
      if (lane == 0) mbar_arrive(bar_col);
    } else if (wi == 2) {
      if (elect_one()) {
        const uint32_t b_free = bar_full + (bid < AT_NFULL ? 80 : 160);
        mbar_wait_long(b_free, 1);
        #pragma unroll 1
        for (unsigned int i = 0; i < (1u << 20) && ld_acquire(&g_hcnt[32 * (1 + (tb >> 3)) + 4 + ((tb >> 1) & 3)]) == 0u; i++) __nanosleep((tb >> 4) == 6 ? POLL_NS2 : POLL_NS);
        TL_MARK2(23, true);
        fence_proxy_async_global();
        TL_MARK2(4, true);
        mbar_expect_tx(bar_full + 272, 32768);
        bulk_load_hint(sbase + OG_PSLOT, g_pre + tb * 2048, 32768, bar_full + 272, policy_evict_first());
      }
      named_bar_sync(14, 32);
      if (has_moe) {
        mbar_wait_long(bar_full + 304, 0);
        const uint64_t pol = policy_evict_first();
        #pragma unroll 1
        for (int r = 0; r < 32; r++) {
          __nanosleep(WD_PACE);
          #pragma unroll
          for (int j = 0; j < 2; j++)
            asm volatile("cp.async.cg.shared.global.L2::cache_hint [%0], [%1], 16, %2;" :: "r"(sbase + OG_SWD + (4 * j + (lane >> 3)) * 4096 + r * 128 + (((lane ^ r) & 7) << 4)),
                         "l"((const uint8_t*)w_down + (size_t)bid * 65536 + r * 2048 + j * 512 + lane * 16), "l"(pol) : "memory");
        }
        asm volatile("cp.async.wait_all;" ::: "memory");
        __syncwarp();
        if (lane == 0) mbar_arrive(bar_wd);
      }
    }
    const uint4 wrv = ldg_nc_v4(w_r + threadIdx.x * 8);
    mbar_wait_long(bar_end, 0);
    TL_MARK2(22, lane == 0);
    if (wi == 0) {
      uint32_t k1 = 0u, k2 = 0u;
      #pragma unroll 1
      for (unsigned int spin = 0; spin < (1u << 22) && __any_sync(0xffffffffu, k1 == 0u); spin++) asm volatile("ld.relaxed.gpu.global.u32 %0, [%1];" : "=r"(k1) : "l"(g_key + lane) : "memory");
      TL_MARK2(28, lane == 0);
      warp_top2(k1, k2);
      if (lane == 0) {
        const uint32_t r1 = 0xffffu - (k1 & 0xffffu), r2 = 0xffffu - (k2 & 0xffffu);
        sts_u32x4(sbase + OG_SMISC + 64, r1, r2, (r1 >> 7) * 2, (r2 >> 7) * 2 + ((r1 >> 7) == (r2 >> 7)));
        mbar_arrive(bar_sel);
      }
    } else if (wi < 3) {
          mbar_wait(bar_key, 0);
          const uint4 kk = lds_u32x4(sbase + OG_SSTAT + 1024 + lane * 16);
          uint32_t k1 = max(kk.x, kk.y), k2 = min(kk.x, kk.y);
          k2 = max(max(k2, min(kk.z, kk.w)), min(k1, max(kk.z, kk.w))); k1 = max(k1, max(kk.z, kk.w));
          warp_top2(k1, k2);
          if (wi == 1) {
            if (lane == 0) {
              if (nt == (mt & 7)) st_relaxed2(g_key + mt * 2, k1, k2);
              sts_u32x2(sbase + OG_SMISC + 96, (~k1 >> 4) & 7u, (~k2 >> 4) & 7u);
              mbar_arrive(bar_full + 352);
            }
            TL_MARK2(27, lane == 0);
          } else {
            const uint32_t r = (~((lane & 16) ? k2 : k1)) & 127u, ch = lane & 15;
            const uint2 st = lds_u32x2(sbase + OG_SSTAT + r * 8);
            const uint4 xc = lds_u32x4(sbase + OG_XSLOT + (ch >> 3) * 16384 + r * 128 + (((ch ^ r) & 7) << 4));
            const uint4 c1 = lds_u32x4(sbase + OG_SCOL + 768 + ch * 16), sh = lds_u32x4(sbase + OG_SCOL + 1024 + ch * 16);
            const float inr = __uint_as_float(st.y);
            float* dst = reinterpret_cast<float*>(g_cand + (mt * 2 + (lane >> 4)) * 256 + nt * 16 + ch);
            st_tagged4(dst + 512, __uint_as_float(ln_mod2(xc.x, st.x, inr, c1.x, sh.x)), __uint_as_float(ln_mod2(xc.y, st.x, inr, c1.y, sh.y)),
                       __uint_as_float(ln_mod2(xc.z, st.x, inr, c1.z, sh.z)), __uint_as_float(ln_mod2(xc.w, st.x, inr, c1.w, sh.w)));
            st_tagged4(dst, __uint_as_float(xc.x), __uint_as_float(xc.y), __uint_as_float(xc.z), __uint_as_float(xc.w));
          }
    }
    mbar_wait(bar_sel, 0);
    const uint4 sel = lds_u32x4(sbase + OG_SMISC + 64);
    const int sel0 = (int)sel.x, sel1 = (int)sel.y;
    {
      const float* src0 = reinterpret_cast<const float*>(g_cand + sel.z * 256 + 128 + threadIdx.x);
      const float* src1 = reinterpret_cast<const float*>(g_cand + sel.w * 256 + 128 + threadIdx.x);
      float4 h0, h1;
      #pragma unroll 1
      for (unsigned int spin = 0; spin < (1u << 20); spin++) { h0 = ld_tagged4(src0); h1 = ld_tagged4(src1); if (__all_sync(0xffffffffu, tagged4(h0) & tagged4(h1))) break; }
      sts_f32x4(sbase + OG_SH2 + threadIdx.x * 16, h0.x, h0.y, h0.z, h0.w);
      sts_f32x4(sbase + OG_SH2 + 2048 + threadIdx.x * 16, h1.x, h1.y, h1.z, h1.w);
      __syncwarp();
      if (lane == 0) mbar_arrive(bar_h2);
      TL_MARK2(12, lane == 0);
      if (bid >> 6) h0 = h1;
      float v[8], wr[8];
      unpack8(make_uint4(__float_as_uint(h0.x), __float_as_uint(h0.y), __float_as_uint(h0.z), __float_as_uint(h0.w)), v); unpack8(wrv, wr);
      float r = 0.f;
      #pragma unroll
      for (int i = 0; i < 8; i++) r = fmaf(v[i], wr[i], r);
      #pragma unroll
      for (int o = 16; o > 0; o >>= 1) r += __shfl_xor_sync(0xffffffffu, r, o);
      if (lane == 0) sts_f32(sbase + OG_SMISC + 192 + wi * 4, r);
    }
    mbar_wait(bar_out, 0);
    {
      const uint2 cg = lds_u32x2(sbase + OG_SMISC + 96);
      #pragma unroll
      for (int i = 0; i < 4; i++) {
        const int r = (i < 2 ? cg.x : cg.y) * 16 + (i & 1) * 8 + (threadIdx.x >> 4), ch = threadIdx.x & 15;
        if (m0 + r != sel0 && m0 + r != sel1)
          *reinterpret_cast<uint4*>(out + (size_t)(m0 + r) * T_D + n0 + ch * 8) =
              lds_u32x4(sbase + OG_OSLOT + (ch >> 3) * 16384 + r * 128 + (((ch & 7) ^ (r & 7)) << 4));
      }
    }
    if (bid == 0 && threadIdx.x < 68) *reinterpret_cast<uint4*>(g_hcnt + 32 * (threadIdx.x >> 2) + 4 * (threadIdx.x & 3)) = make_uint4(0u, 0u, 0u, 0u);
    if (threadIdx.x < 64) g_modpart[bid * 64 + threadIdx.x] = 0.f;
    {
      const int tk = bid >> 6, c0 = (bid & 63) * 16;
      const uint32_t gb2 = *reinterpret_cast<const uint32_t*>(g_col + (c0 >> 7) * 1536 + 512 + 768 + ((c0 & 127) + (threadIdx.x & 14)) * 2);
      const uint32_t* xp = reinterpret_cast<const uint32_t*>(g_cand + (tk ? sel.w : sel.z) * 256) + ((c0 + (threadIdx.x & 14)) >> 1);
      uint32_t x2 = 0u;
      #pragma unroll 1
      for (unsigned int spin = 0; spin < (1u << 20) && __any_sync(0xffffffffu, x2 == 0u); spin++) asm volatile("ld.relaxed.gpu.global.u32 %0, [%1];" : "=r"(x2) : "l"(xp) : "memory");
      const float* src = g_ypart + (size_t)((threadIdx.x >> 2) * 2 + tk) * T_D + c0 + (threadIdx.x & 3) * 4;
      const bool four = threadIdx.x < (OG_MOE - 96) * 4;
      named_bar_sync(10, 128);
      const uint4 rp = lds_u32x4(sbase + OG_SMISC + 192);
      const float rs = rbf(sigmoid_f(rbf((__uint_as_float(rp.x) + __uint_as_float(rp.y)) + (__uint_as_float(rp.z) + __uint_as_float(rp.w)))));
      const uint32_t h2p = lds_u32(sbase + OG_SH2 + tk * 2048 + (c0 + (threadIdx.x & 14)) * 2);
      const float fh = (lane & 1) ? bfhi(h2p) : bflo(h2p), fz = rbf(fh * 0.0f), fx = (lane & 1) ? bfhi(x2) : bflo(x2), fg = (lane & 1) ? bfhi(gb2) : bflo(gb2);
      bf16* dst = out + (size_t)(tk ? sel1 : sel0) * T_D + c0 + threadIdx.x;
      if (threadIdx.x == 0) hint_wait(CNT_Y, (uint32_t)(OG_MOE - Y_SLACK));
      named_bar_sync(10, 128);
      float4 p0, p1, p2, p3;
      #pragma unroll 1
      for (unsigned int spin = 0; spin < (1u << 20); spin++) {
        p0 = ld_tagged4(src); p1 = ld_tagged4(src + 64 * T_D); p2 = ld_tagged4(src + 128 * T_D); p3 = ld_tagged4(four ? src + 192 * T_D : src);
        if (__all_sync(0xffffffffu, tagged4(p0) & tagged4(p1) & tagged4(p2) & tagged4(p3))) break;
      }
      if (four) { p2.x += p3.x; p2.y += p3.y; p2.z += p3.z; p2.w += p3.w; }
      p0.x = (p0.x + p1.x) + p2.x; p0.y = (p0.y + p1.y) + p2.y; p0.z = (p0.z + p1.z) + p2.z; p0.w = (p0.w + p1.w) + p2.w;
      #pragma unroll
      for (int o = 4; o <= 16; o <<= 1) {
        p0.x += __shfl_xor_sync(0xffffffffu, p0.x, o); p0.y += __shfl_xor_sync(0xffffffffu, p0.y, o);
        p0.z += __shfl_xor_sync(0xffffffffu, p0.z, o); p0.w += __shfl_xor_sync(0xffffffffu, p0.w, o);
      }
      if (lane < 4) sts_f32x4(sbase + OG_SFIN + (threadIdx.x >> 5) * 64 + lane * 16, p0.x, p0.y, p0.z, p0.w);
      named_bar_sync(10, 128);
      TL_MARK2(21, threadIdx.x == 0);
      if (threadIdx.x < 16) {
        const uint32_t ya = sbase + OG_SFIN + threadIdx.x * 4;
        float y = (lds_f32(ya) + lds_f32(ya + 64)) + (lds_f32(ya + 128) + lds_f32(ya + 192));
        y = rbf(y);
        y = rbf(y * rs);
        *dst = __float2bfloat16_rn(fx + rbf(fg * rbf(fh + rbf(fz + y))));
      }
    }
    if (threadIdx.x == 0) XT(11);
    TL_END(4, threadIdx.x == 0);
}

__device__ __forceinline__ void load_pre(uint4* pre, uint32_t sbase, uint32_t buf, int t2) {
  mbar_wait(sbase + AT_SBAR + 272, 0);
  #pragma unroll
  for (int i = 0; i < 8; i++) pre[i] = lds_u32x4(sbase + buf + i * 4096 + t2 * 16);
}
__device__ __forceinline__ void tail_consumer(uint32_t bid, uint32_t sbase, const CUtensorMap* tmOut, const uint4 (&pre)[8], int cwg, const bf16* __restrict__ w_gate, const bf16* __restrict__ w_up) {
    const uint32_t c0 = clock_lo();
    mbar_wait(sbase + AT_SBAR + 320, 0);
    const uint2 td = lds_u32x2(sbase + AT_SBAR + 408);
    const int tb = __shfl_sync(0xffffffffu, (int)td.x, 0);
    TAIL_SETUP
    const int tid = threadIdx.x & 127, t2 = threadIdx.x - 128;
    const int warp = tid >> 5, lane = tid & 31, w8 = t2 >> 5;
    const uint32_t dbase = (sbase & 0x3FFFFu) >> 4;
    const uint32_t a_base = dbase + ((cwg * 8192) >> 4) + (1u << 16);
    const uint32_t b_base = dbase + (16384 >> 4) + (512u << 16);
    TL_MARK2(25, threadIdx.x == 128);
    const uint64_t pol = policy_evict_first();
    const bf16* pw = ((lane & 16) ? w_up : w_gate) + (size_t)(w8 * 128 + (lane & 3) * 4) * T_F + (has_moe ? bid : 0) * 32 + ((lane >> 2) & 3) * 8;
    uint4 wv[32];
    float acc[64];
    #pragma unroll
    for (int i = 0; i < 8; i++) {
      acc[8 * i] = bflo(pre[i].x); acc[8 * i + 1] = bfhi(pre[i].x); acc[8 * i + 2] = bflo(pre[i].y); acc[8 * i + 3] = bfhi(pre[i].y);
      acc[8 * i + 4] = bflo(pre[i].z); acc[8 * i + 5] = bfhi(pre[i].z); acc[8 * i + 6] = bflo(pre[i].w); acc[8 * i + 7] = bfhi(pre[i].w);
    }
    if (lane == 0) mbar_arrive(bar_full + 304);
    while (__any_sync(0xffffffffu, clock_lo() - c0 < td.y)) {}
    uint32_t stage = OG_POS % OG_ST;
    {
      uint32_t phase = (OG_POS / OG_ST) & 1, prev = 12;
      int kb = 0;
      #pragma unroll
      for (int g = 0; g <= OG_NG; g++) {
        const int end = g == OG_NG ? 64 - og_pre(tb) : LD_FIRST + g * OG_GRP + LD_STAG * cwg;
        #pragma unroll 1
        do {
          mbar_wait(bar_full + 8 * stage, phase);
          if (OG_STAG > 0 && g == OG_NG && cwg == 1 && kb == end - OG_STAG) named_bar_sync(7, 256);
          const uint32_t a_lo = a_base + stage * (OG_STAGE >> 4), b_lo = b_base + stage * (OG_STAGE >> 4);
          wgmma_fence();
          wgmma_m64n128k16_ss_tb<0, 0>(acc, a_lo, b_lo, 1);
          wgmma_m64n128k16_ss_tb<2, 128>(acc, a_lo, b_lo, 1);
          wgmma_m64n128k16_ss_tb<4, 256>(acc, a_lo, b_lo, 1);
          wgmma_m64n128k16_ss_tb<6, 384>(acc, a_lo, b_lo, 1);
          wgmma_commit();
          if (OG_STAG > 0 && g == OG_NG && cwg == 0 && kb == end - 1) named_bar_arrive(7, 256);
          wgmma_wait<1>();
          if (tid == 0) mbar_arrive(bar_empty + 8 * prev);
          prev = stage;
          if (++stage == OG_ST) { stage = 0; phase ^= 1; }
        } while (++kb < end);
        #pragma unroll
        for (int j = 4 * g; j < 4 * g + 4 && j < 32; j++) wv[j] = ldg_stream_v4(pw + (size_t)(16 * (j >> 2) + (j & 3)) * T_F, pol);
      }
    }
    mbar_wait(bar_col, 0);
    if (__builtin_expect(!has_moe, 0)) {
      load_pre(wv, sbase, AT_SQ, t2);
    }
    wgmma_wait<0>();
    fence_regs(acc);
    if (__builtin_expect(!has_moe, 0)) {
      #pragma unroll
      for (int i = 0; i < 8; i++) {
        acc[8 * i] += bflo(wv[i].x); acc[8 * i + 1] += bfhi(wv[i].x); acc[8 * i + 2] += bflo(wv[i].y); acc[8 * i + 3] += bfhi(wv[i].y);
        acc[8 * i + 4] += bflo(wv[i].z); acc[8 * i + 5] += bfhi(wv[i].z); acc[8 * i + 6] += bflo(wv[i].w); acc[8 * i + 7] += bfhi(wv[i].w);
      }
    }
    if (tid == 0) mbar_arrive(bar_end);
    TL_MARK2(9, lane == 0);
    const int q2 = 2 * (lane & 3);
    const uint32_t frag = (64 * cwg + 16 * warp + (lane & 7) + 8 * ((lane >> 3) & 1)) * 128;
    const int fsw = lane & 7, fhi = lane >> 4;
    {
      float dl[4] = {0.f, 0.f, 0.f, 0.f}, da[4] = {0.f, 0.f, 0.f, 0.f}, db[4] = {0.f, 0.f, 0.f, 0.f};
      const uint32_t tb2 = sbase + OG_SCOL + (lane & 8) * 32 + (lane & 3) * 8, g = lane >> 2;
      const uint32_t msk = (g == 1 || g == 2) ? 0xffffffffu : 0u, one = g == 0 ? 0x3F803F80u : 0u;
      uint32_t xr[8][4];
      #pragma unroll
      for (int hf = 0; hf < 2; hf++) {
        uint32_t ga[8];
        uint2 cw[4];
        #pragma unroll
        for (int i = 0; i < 4; i++) {
          ldmatrix_x4(sbase + OG_XSLOT + hf * 16384 + frag + (((2 * i + fhi) ^ fsw) << 4), xr[4 * hf + i][0], xr[4 * hf + i][1], xr[4 * hf + i][2], xr[4 * hf + i][3]);
          ga[2 * i] = lds_u32(sbase + OG_SCOL + 512 + (64 * hf + 16 * i + q2) * 2); ga[2 * i + 1] = lds_u32(sbase + OG_SCOL + 512 + (64 * hf + 16 * i + 8 + q2) * 2);
          cw[i] = lds_u32x2(tb2 + (8 * hf + 2 * i) * 16);
        }
        #pragma unroll
        for (int i = 0; i < 4; i++) {
          uint32_t* x4 = xr[4 * hf + i];
          #pragma unroll
          for (int e = 0; e < 4; e++) x4[e] = badd2(x4[e], bmul2(ga[2 * i + (e >> 1)], pack_bf16(acc[32 * hf + 8 * i + 2 * e], acc[32 * hf + 8 * i + 2 * e + 1])));
          mma_bf16(dl, x4[0], x4[1], x4[2], x4[3], (cw[i].x & msk) | one, (cw[i].y & msk) | one);
          mma_bf16(da, x4[0], x4[1], x4[2], x4[3], x4[0], x4[2]);
          mma_bf16(db, x4[0], x4[1], x4[2], x4[3], x4[1], x4[3]);
        }
      }
      {
        const int dsrc = (lane & ~3) + (g >> 1);
        const float qa = __shfl_sync(0xffffffffu, (g & 1) ? da[1] : da[0], dsrc), qb = __shfl_sync(0xffffffffu, (g & 1) ? db[3] : db[2], dsrc);
        const float e0 = __shfl_xor_sync(0xffffffffu, (lane & 1) ? dl[0] : dl[2], 1), e1 = __shfl_xor_sync(0xffffffffu, dl[3], 1);
        if ((lane & 3) < 2) {
          const bool hi = lane & 1;
          st_tagged4(reinterpret_cast<float*>(g_part1 + ((mt * 8 + w8) * 8 + nt) * 16 + g + (hi ? 8 : 0)),
                     hi ? e0 : dl[0], hi ? qb : qa, hi ? e1 + dl[2] : dl[1] + e0, 1.0f);
        }
      }
      #pragma unroll
      for (int i = 0; i < 8; i++) stmatrix_x4(sbase + OG_XSLOT + (i >> 2) * 16384 + frag + (((2 * (i & 3) + fhi) ^ fsw) << 4), xr[i][0], xr[i][1], xr[i][2], xr[i][3]);
    }
    TL_MARK2(10, lane == 0);
    uint4 wd[16];
    if (has_moe) mbar_wait(bar_wd, 0);
    #pragma unroll
    for (int i = 0; i < 16; i++) wd[i] = lds_u32x4(sbase + (cwg ? (stage + (stage & 1)) * OG_STAGE : OG_SWD) + warp * 8192 + (i >> 3) * 4096 + (i & 6) * 512 + (i & 1) * 128 + (lane & 3) * 256 + (((lane >> 2) ^ (2 * (lane & 3) + (i & 1))) << 4));
    {
      const float* src = reinterpret_cast<const float*>(g_part1 + ((mt * 8 + w8) * 8 + (lane & 1) * 4) * 16 + (lane >> 1));
      float4 v, v1, v2, v3;
      #pragma unroll 1
      for (unsigned int spin = 0; spin < (1u << 22); spin++) {
        v = ld_tagged4(src); v1 = ld_tagged4(src + 64); v2 = ld_tagged4(src + 128); v3 = ld_tagged4(src + 192);
        if (__all_sync(0xffffffffu, tagged4(v) & tagged4(v1) & tagged4(v2) & tagged4(v3))) break;
        __nanosleep(100);
      }
      __syncwarp();
      TL_MARK2(26, lane == 0);
      v.x = (v.x + v1.x) + (v2.x + v3.x); v.y = (v.y + v1.y) + (v2.y + v3.y); v.z = (v.z + v1.z) + (v2.z + v3.z);
      v.x += __shfl_xor_sync(0xffffffffu, v.x, 1); v.y += __shfl_xor_sync(0xffffffffu, v.y, 1); v.z += __shfl_xor_sync(0xffffffffu, v.z, 1);
      const float mean = v.x * (1.0f / T_D);
      const float var = fmaxf(fmaf(-mean, mean, v.y * (1.0f / T_D)), 0.f);
      const uint32_t mb2 = pack_bf16(mean, mean);
      const float inv = rcp_approx(rbf(sqrt_approx(rbf(rbf(var) + 1e-05f))));
      {
        const float2 sc = lds_f32x2(sbase + OG_SMISC);
        const uint32_t key = rank_key(rbf(fmaf(fmaf(-bflo(mb2), sc.x, v.z), inv, sc.y)), m0 + 16 * w8 + (lane >> 1));
        mbar_wait(bar_end, 0);
        if (lane & 1) sts_u32(sbase + OG_SSTAT + 1024 + (16 * w8 + (lane >> 1)) * 4, key);
        else sts_u32x2(sbase + OG_SSTAT + (16 * w8 + (lane >> 1)) * 8, mb2, __float_as_uint(inv));
        __syncwarp();
        if (lane == 0) mbar_arrive(bar_key);
      }
      const uint32_t ih = pack_bf16(inv, inv), il = pack_bf16(inv - bflo(ih), inv - bflo(ih));
      const uint32_t mba = __shfl_sync(0xffffffffu, mb2, 2 * (lane >> 2)), mbb = __shfl_sync(0xffffffffu, mb2, 2 * (lane >> 2) + 16);
      const uint32_t iha = __shfl_sync(0xffffffffu, ih, 2 * (lane >> 2)), ihb = __shfl_sync(0xffffffffu, ih, 2 * (lane >> 2) + 16);
      const uint32_t ila = __shfl_sync(0xffffffffu, il, 2 * (lane >> 2)), ilb = __shfl_sync(0xffffffffu, il, 2 * (lane >> 2) + 16);
      #pragma unroll 1
      for (int J0 = 0; J0 < 16; J0 += 4) {
        uint32_t xr[2][4], cv[4][3];
        #pragma unroll
        for (int i = 0; i < 2; i++) {
          ldmatrix_x4(sbase + OG_XSLOT + (J0 >> 3) * 16384 + frag + ((((J0 & 7) + 2 * i + fhi) ^ fsw) << 4), xr[i][0], xr[i][1], xr[i][2], xr[i][3]);
          #pragma unroll
          for (int h = 0; h < 2; h++)
            #pragma unroll
            for (int k = 0; k < 3; k++) cv[2 * i + h][k] = lds_u32(sbase + OG_SCOL + 768 + 256 * k + (8 * (J0 + 2 * i + h) + q2) * 2);
        }
        #pragma unroll
        for (int i = 0; i < 2; i++) {
          #pragma unroll
          for (int h = 0; h < 2; h++) {
            xr[i][2 * h] = out2(xr[i][2 * h], mba, iha, ila, cv[2 * i + h][0], cv[2 * i + h][1], cv[2 * i + h][2]);
            xr[i][2 * h + 1] = out2(xr[i][2 * h + 1], mbb, ihb, ilb, cv[2 * i + h][0], cv[2 * i + h][1], cv[2 * i + h][2]);
          }
          stmatrix_x4(sbase + OG_OSLOT + (J0 >> 3) * 16384 + frag + ((((J0 & 7) + 2 * i + fhi) ^ fsw) << 4), xr[i][0], xr[i][1], xr[i][2], xr[i][3]);
        }
      }
      fence_proxy_async();
      mbar_wait(bar_full + 352, 0);
      const uint2 cg = lds_u32x2(sbase + OG_SMISC + 96);
      __syncwarp();
      if (elect_one()) {
        mbar_arrive(bar_out);
        if (cg.x != w8 && cg.y != w8) {
          asm volatile("cp.async.bulk.tensor.2d.global.shared::cta.bulk_group [%0, {%2, %3}], [%1];" :: "l"(tmOut), "r"(sbase + OG_OSLOT + w8 * 2048), "r"(n0), "r"(m0 + 16 * w8) : "memory");
          asm volatile("cp.async.bulk.tensor.2d.global.shared::cta.bulk_group [%0, {%2, %3}], [%1];" :: "l"(tmOut), "r"(sbase + OG_OSLOT + 16384 + w8 * 2048), "r"(n0 + 64), "r"(m0 + 16 * w8) : "memory");
          bulk_commit();
        }
      }
      TL_MARK2(24, lane == 0);
    }
    if (has_moe) mbar_wait(bar_h2, 0);
    TL_MARK2(13, lane == 0);
    if (has_moe) {
      const GemvSel sel = gemv_sel(lane);
      {
        float d[4][4];
        #pragma unroll
        for (int c = 0; c < 4; c++) { d[c][0] = 0.f; d[c][1] = 0.f; d[c][2] = 0.f; d[c][3] = 0.f; }
        #pragma unroll
        for (int st = 0; st < 8; st++) {
          const uint2 hb = lds_u32x2(sbase + OG_SH2 + ((lane >> 2) & 1) * 2048 + (w8 * 128 + st * 16 + (lane & 3) * 4) * 2);
          #pragma unroll
          for (int j = 0; j < 4; j++) mma_bf16(d[j], wv[4 * st + j].x, wv[4 * st + j].y, wv[4 * st + j].z, wv[4 * st + j].w, GEMV_B0(j, hb, sel), GEMV_B1(j, hb, sel));
        }
        #pragma unroll
        for (int e = 0; e < 4; e++) d[0][e] = (d[0][e] + d[1][e]) + (d[2][e] + d[3][e]);
        const float4 r = gemv_out(d[0], lane);
        sts_f32x4(sbase + OG_SRED + w8 * 512 + (((lane >> 4) * 2 + (lane & 1)) * 32 + ((lane >> 2) & 3) * 8 + (lane & 2) * 2) * 4, r.x, r.y, r.z, r.w);
      }
      named_bar_sync(9, 256);
      if (t2 < 64) {
        float gp[8], up[8];
        #pragma unroll
        for (int w = 0; w < 8; w++) { gp[w] = lds_f32(sbase + OG_SRED + w * 512 + t2 * 4); up[w] = lds_f32(sbase + OG_SRED + w * 512 + 256 + t2 * 4); }
        const float gs = ((gp[0] + gp[1]) + (gp[2] + gp[3])) + ((gp[4] + gp[5]) + (gp[6] + gp[7]));
        const float us = ((up[0] + up[1]) + (up[2] + up[3])) + ((up[4] + up[5]) + (up[6] + up[7]));
        asm volatile("st.shared.u16 [%0], %1;" :: "r"(sbase + OG_SGU + ((t2 & ~15) + ((t2 >> 1) & 3) * 4 + ((t2 >> 3) & 1) * 2 + (t2 & 1)) * 2), "h"((uint16_t)pack_bf16(silu_bf(rbf(gs)) * rbf(us), 0.f)) : "memory");
      }
      named_bar_sync(9, 256);
      TL_MARK2(20, threadIdx.x == 128);
      float d[4][4];
      #pragma unroll
      for (int c = 0; c < 4; c++) { d[c][0] = 0.f; d[c][1] = 0.f; d[c][2] = 0.f; d[c][3] = 0.f; }
      #pragma unroll
      for (int st = 0; st < 2; st++) {
        const uint2 g = lds_u32x2(sbase + OG_SGU + ((lane >> 2) & 1) * 64 + st * 32 + (lane & 3) * 8);
        #pragma unroll
        for (int j = 0; j < 4; j++) {
          const uint32_t b0 = GEMV_B0(j, g, sel), b1 = GEMV_B1(j, g, sel);
          mma_bf16(d[j & 1], wd[4 * st + j].x, wd[4 * st + j].y, wd[4 * st + j].z, wd[4 * st + j].w, b0, b1);
          mma_bf16(d[2 + (j & 1)], wd[8 + 4 * st + j].x, wd[8 + 4 * st + j].y, wd[8 + 4 * st + j].z, wd[8 + 4 * st + j].w, b0, b1);
        }
      }
      #pragma unroll
      for (int e = 0; e < 4; e++) { d[0][e] += d[1][e]; d[2][e] += d[3][e]; }
      const float4 y0 = gemv_out(d[0], lane), y1 = gemv_out(d[2], lane);
      float* yp = g_ypart + (size_t)(bid * 2 + (lane & 1)) * T_D + w8 * 128 + (lane >> 2) * 8 + (lane & 2) * 2;
      st_tagged4(yp, y0.x, y0.y, y0.z, y0.w);
      st_tagged4(yp + 64, y1.x, y1.y, y1.z, y1.w);
      named_bar_sync(9, 256);
      if (t2 == 0) hint_arrive(CNT_Y);
    }
    bulk_wait_read<0>();
    TL_MARK2(14, threadIdx.x == 128);
    TL_CLK(4, 1, threadIdx.x == 128);
}

__device__ __forceinline__ int help_njobs(uint32_t bid) { return bid < 128 ? OG_JOBS : 16 - OG_JOBS; }
__device__ __forceinline__ int help_job(uint32_t bid, int i) { return (i < OG_JOBS ? 16 * i + (bid >> 7) * 2 : 112 + (i - OG_JOBS) * 2) + (bid & 3) * 4; }
__device__ __noinline__ void store_warp(uint32_t bid, uint32_t sbase, const CUtensorMap* tmO, int item0, int n_items) {
  if (elect_one()) {
    const uint32_t bars = sbase + AT_SBAR, b_q0 = bars + 80, b_ob = bars + 96, b_ordy = bars + 104, b_acq = bars + 264;
    const unsigned int* cnt = g_hcnt + 32 * (1 + OG_MT(124)) + 2;
    #pragma unroll 1
    for (int q = 0; q < 4 * n_items; q++) {
      const int item = item0 + (q >> 2) * 128, h = (q >> 1) & 1, w = q & 1;
      const bool last = (q >> 2) == n_items - 1;
      if (q == 4 * n_items - 4) { mbar_wait_long(bars + 288, 0); red_release_add(&g_hcnt[1], 1u); }
      mbar_wait_long(b_ordy + 8 * (q & 3), q >> 2);
      store_o(tmO, (h ? (last ? sbase + AT_SQ + 32768 : sbase + 2 * 32768) : sbase + AT_SQ) + w * 8192, (item >> 4) * 2 + h, (item & 15) * 128 + w * 64);
      if (w) {
        bulk_wait_read<0>();
        mbar_arrive(h ? b_ob : b_q0);
        bulk_wait<0>();
        fence_proxy_async_global();
        asm volatile("fence.acq_rel.gpu;" ::: "memory");
        hint_arrive(&g_hcnt[32 * (1 + (item & 15)) + 2 + (item >> 7)]);
        if (!h && item < 128) hint_arrive(&g_hcnt[2]);
        if (q == 5) { const int tb = tail_tile(sbase); cnt = g_hcnt + 32 * (1 + OG_MT(tb)) + 2; spin_until(cnt, 16u); mbar_arrive(b_acq); }
      }
    }
    if (n_items == 1) {
      #pragma unroll 1
      for (int i = 0; i < help_njobs(bid); i++) {
        mbar_wait_long(b_acq + 16, i & 1);
        TL_MARK2(23, i == OG_JOBS - 1);
        red_release_add(&g_hcnt[32 * (1 + (help_job(bid, i) >> 3)) + 4 + ((help_job(bid, i) >> 1) & 3)], 1u);
        TL_MARK2(4, i == OG_JOBS - 1);
        if (i == PRE_X - 1) { spin_until(&g_hcnt[1], 132u); mbar_arrive(b_acq + 32); }
      }
    }
    if (bid < 128) {
      if (n_items == 1) { spin_until(cnt, 16u); mbar_arrive(b_acq); }
      spin_until(&g_hcnt[0], 128u); spin_until(cnt + 1, 16u); mbar_arrive(b_acq + 80);
    }
  }
}

__device__ __forceinline__ uint32_t role_of_sm(uint32_t sm) {
  const uint32_t t = sm >> 1, u = t - 32u, d = (u * 37u) >> 8;
  return (t < 32u ? ((t + 7u) & 7u) * 16u + (t >> 3) * 2u : t < 60u ? (u - 7u * d) * 16u + (4u + d) * 2u : t < 62u ? 2u * t + 8u : 2u * t - 4u) + (sm & 1u);
}
__global__ void __launch_bounds__(384, 1)
fused_kernel(const __grid_constant__ CUtensorMap tmH, const __grid_constant__ CUtensorMap tmW, const __grid_constant__ CUtensorMap tmK,
            const __grid_constant__ CUtensorMap tmV, const __grid_constant__ CUtensorMap tmO, const __grid_constant__ CUtensorMap tmOl, const __grid_constant__ CUtensorMap tmWo,
            const __grid_constant__ CUtensorMap tmD, const __grid_constant__ CUtensorMap tmOut, const __grid_constant__ CUtensorMap tmM, uint32_t zero,
            const uint8_t* __restrict__ pf_wo, const bf16* __restrict__ kc, const bf16* __restrict__ vc,
            const bf16* __restrict__ x, const bf16* __restrict__ cvec, const bf16* __restrict__ w_mod, const bf16* __restrict__ w_r,
            const bf16* __restrict__ w_gate, const bf16* __restrict__ w_up, const bf16* __restrict__ w_down, bf16* __restrict__ out)
{
  uint32_t bid, nsm;
  asm volatile("mov.u32 %0, %%smid;" : "=r"(bid));
  asm volatile("mov.u32 %0, %%nsmid;" : "=r"(nsm));
  bid = __shfl_sync(0xffffffffu, nsm == 132u ? role_of_sm(bid) : blockIdx.x, 0);
  extern __shared__ __align__(1024) uint8_t smem_raw[];
  const uint32_t sbase = smem_u32(smem_raw);
  const uint32_t bars = sbase + AT_SBAR;
  const uint32_t b_full = bars, b_empty = bars + 40;
  const uint32_t b_q0 = bars + 80, b_q1 = bars + 88;
  const uint32_t b_ob = bars + 96;
  const uint32_t b_ordy = bars + 104;
  const uint32_t b_pin = bars + 136;
  const uint32_t b_head = bars + 144;
  const uint32_t b_go = bars + 152;
  const uint32_t b_x = bars + 160;
  const int wg = __shfl_sync(0xffffffffu, threadIdx.x >> 7, 0);
  const bool single = bid >= AT_NFULL;
  const int item0 = __shfl_sync(0xffffffffu, bid < 128 ? (int)bid : (int)bid + 124, 0), n_items = __shfl_sync(0xffffffffu, single ? 1 : 2, 0);
  TL_START(3);
  if (threadIdx.x == 0) {
    if (sbase & 1023u) __trap();
    for (int i = 0; i < 5; i++) { mbar_init(b_full + 8 * i, 1); mbar_init(b_empty + 8 * i, 2); }
    mbar_init(b_q0, 1); mbar_init(b_q1, 8); mbar_init(b_ob, 1);
    for (int i = 0; i < 4; i++) mbar_init(b_ordy + 8 * i, 4);
    mbar_init(b_pin, 1); mbar_init(b_head, bid < 128 ? 8 : 1); mbar_init(b_go, 1); mbar_init(b_x, 1);
    mbar_init(bars + 168, 2); mbar_init(bars + 176, 1); mbar_init(bars + 184, 8); mbar_init(bars + 192, 2);
    mbar_init(bars + 200, 8); mbar_init(bars + 208, 4); mbar_init(bars + 216, 1); mbar_init(bars + 264, 1); mbar_init(bars + 272, 1); mbar_init(bars + 280, 8); mbar_init(bars + 288, 1); mbar_init(bars + 296, 1); mbar_init(bars + 304, 8); mbar_init(bars + 312, 1); mbar_init(bars + 320, 1); mbar_init(bars + 328, 1); mbar_init(bars + 336, 1); mbar_init(bars + 344, 1); mbar_init(bars + 352, 1);
    sts_u32(bars + 400, bid);
    fence_mbar_init();
  }

  if (wg == 0) {
    reg_dealloc<AT_PREG>();
    if (threadIdx.x < 32) { __syncwarp(); named_bar_arrive(6, 384); }
    if (threadIdx.x >= 64) {
      named_bar_sync(6, 384);
      if (bid < 128) {
        named_bar_sync(threadIdx.x >= 96 ? 8 : 9, 288);
        if ((threadIdx.x & 31) == 0) red_release_add(&g_hcnt[32 * (1 + (bid >> 3)) + (threadIdx.x >= 96)], 1u);
        TL_MARK2(11, threadIdx.x == 64);
      }
      if (bid < 128) {
        mbar_wait(MOD_AT, 0);
        mod_rest(bid, sbase + OG_SCOL, b_q1, threadIdx.x - 64, cvec, w_mod, w_r);
      }
    } else if (threadIdx.x >= 32) {
      named_bar_sync(6, 384);
      store_warp(bid, sbase, &tmO, item0, n_items);
      __syncwarp();
    } else {
     if (elect_one()) {
      const uint64_t pol = policy_evict_first();
      if (bid < 128) {
        mbar_expect_tx(b_x, 32768);
        if (X_DLY) { const uint32_t c0 = clock_lo(); while (clock_lo() - c0 < X_DLY) {} }
        bulk_load_hint(sbase + 4 * 32768, x + (size_t)bid * 16 * T_D, 32768, b_x, pol);
      }
      prefetch_tmap(&tmW); prefetch_tmap(&tmM); prefetch_tmap(&tmH); prefetch_tmap(&tmWo); prefetch_tmap(&tmOl);
      {
        const uint32_t c0 = clock_lo();
        while (clock_lo() - c0 < W_DLY) {}
        if (bid < 128 && (head_cb(bid) & 15) >= 4 * H_SPLIT) {
          mbar_expect_tx(bars + 328, 32768);
          tma_load_2d_hint(sbase + 3 * 32768, &tmM, head_cb(bid) * 64, (bid >> 5) * 256, bars + 328, pol);
        }
        while (clock_lo() - c0 < W_DLY + W_FIRST) {}
      }
      uint32_t slot = 0, ph = 1;
      #pragma unroll 1
      for (int it = 0; it < n_items; it++) {
        const int item = item0 + it * 128, hp = item >> 4, qt = item & 15;
        const bool first = it == 0;
        #pragma unroll 1
        for (int j = 0; j < T_D / 64; j++) {
          const uint32_t sl = ring_slot(qp_pos(j, it)), fb = b_full + 8 * sl;
          mbar_wait_long(b_empty + 8 * sl, ring_par(qp_pos(j, it)) ^ ((j >> 2) & 1) ^ 1);
          if (first && j == 3) mbar_wait(b_head, 0);
          mbar_expect_tx(fb, 49152);
          tma_load_3d_hint(sbase + sl * 32768, &tmW, j * 64, hp * 4, fb, pol);
          if (first && j < PRE_B) {
            if (j == PRE_B - 1) {
              spin_until(&g_hcnt[32 * (1 + qt)], 8u);
              TL_MARK2(16, true);
              fence_proxy_async_global();
              #pragma unroll 1
              for (int i = 0; i < PRE_B; i++) tma_load_2d(sbase + AT_SQ + i * 16384, &tmH, i * 64, qt * 128, b_full + 8 * i);
              mbar_arrive(b_go);
            }
          } else {
            if (first && j == 4 * H_SPLIT) { spin_until(&g_hcnt[32 * (1 + qt) + 1], 8u); fence_proxy_async_global(); }
            if (!first && (j == 0 || j == 2)) mbar_wait(j ? b_q1 : b_q0, 0);
            tma_load_2d(sbase + AT_SQ + (j & 3) * 16384, &tmH, j * 64, qt * 128, fb);
          }
        }
        #pragma unroll 1
        for (int j = 0; j < 4 * AT_NBLK; j++) {
          const bool isv = (j > 0 && !(j & 1)) || j == 4 * AT_NBLK - 1;
          const int row = hp * 2 * T_SEQ + (isv ? (j - 1) >> 1 : (j + 1) >> 1) * 128;
          const uint32_t fb = b_full + 8 * slot;
          mbar_wait_long(b_empty + 8 * slot, ph);
          if (!first && j == 3) mbar_wait(b_ob, 0);
          if (j == 4 && it == n_items - 1) mbar_arrive(bars + 288);
          if ((j == AL_P || j == RK_P) && it == 1) mbar_arrive(bars + 312);
          mbar_expect_tx(fb, 32768);
          tma_load_3d_hint(sbase + slot * 32768, isv ? &tmV : &tmK, row, 0, fb, pol);
          if (it == 1 && isv && j >= 2 * WO_LATE && j < 2 * WO_LATE + 32 && bid < OG_NKB)
            l2_prefetch_bulk(pf_wo + (size_t)own_kb(bid, og_pre(0)) * 131072 + ((j >> 1) - WO_LATE) * 8192, 8192);
          if (++slot == 5) { slot = 0; ph ^= 1; }
        }
      }
      if (__builtin_expect(single, 0)) {
        spin_until(&g_hcnt[2], 128u);
        fence_proxy_async_global();
        const int nj = OG_HSUM + (help_njobs(bid) - OG_JOBS) * OG_PRE2;
        int ji = 0, job = help_job(bid, 0), kk = 0;
        #pragma unroll 1
        for (int j = 0; j < nj; j++) {
          const uint32_t sl = ring_slot(qp_pos(j, 1)), fb = b_full + 8 * sl;
          mbar_wait_long(b_empty + 8 * sl, ring_par(qp_pos(j, 1)) ^ ((j >> 2) & 1) ^ 1);
          mbar_expect_tx(fb, 49152);
          tma_load_3d(sbase + sl * 32768, &tmWo, pre_kb(kk) * 64, OG_NT(job) * 2, fb);
          tma_load_3d(sbase + sl * 32768 + 16384, &tmWo, pre_kb(kk) * 64, OG_NT(job) * 2 + 2, fb);
          if (j == 0 || j == 2) mbar_wait(j ? b_ob : b_q0, 0);
          tma_load_2d_hint(sbase + AT_SQ + (j & 3) * 16384, &tmOl, pre_kb(kk) * 64, OG_MT(job) * 128, fb, pol);
          if (++kk == og_pre(job)) { kk = 0; job = help_job(bid, ++ji); }
        }
      }
      if (bid < 128) {
        if (single) mbar_wait(b_x, 1);
        tail_producer(bid, sbase, 0, pol, &tmOl, &tmWo, &tmD);
      }
     }
    }
    named_bar_sync(12 + (threadIdx.x >> 5), 32);
    if (bid < 128) tail_exchange(bid, sbase, w_down, w_r, x, out);
  } else {
    if (bid < 128) head_phase(bid, sbase + AT_SQ + 49152, sbase + 4 * 32768, b_x, b_go, b_head, threadIdx.x - 128, zero, cvec, w_mod);
    else { named_bar_sync(6, 384); if (threadIdx.x == 128) mbar_arrive(b_head); }
    TL_MARK2(0, threadIdx.x == 128);
    reg_alloc<AT_CREG>();
    const int cwg = wg - 1;
    const int tid = threadIdx.x & 127;
    const int warp = tid >> 5, lane = tid & 31;
    const uint32_t dbase = (sbase & 0x3FFFFu) >> 4;
    const uint32_t k_base = dbase + (1u << 16);
    const uint32_t v_base = dbase + (1024u << 16);
    const uint32_t w_base = dbase + (512u << 16);
    const uint32_t q_lo = dbase + ((AT_SQ + cwg * 8192) >> 4) + (1u << 16);
    const uint32_t frag = cwg * 8192 + (16 * warp + (lane & 7) + 8 * ((lane >> 3) & 1)) * 128;
    if (cwg == 1) named_bar_arrive(1, 256);
    bool raw = false;
    uint4 pre[8];
    #pragma unroll 1
    for (int it = 0; it < n_items; it++) {
      const bool more = it + 1 < n_items;
      constexpr int nkb = T_D / 64;
      const int ta = __shfl_sync(0xffffffffu, 4 * it, 0);
      float acc[128];
      {
        FS(2 * it, 0);
        #pragma unroll
        for (int i = 0; i < 128; i++) asm volatile("" : "=f"(acc[i]));
        {
          const uint32_t slot = ring_slot(ta), b_lo = w_base + slot * 2048;
          mbar_wait(b_full + 8 * slot, ring_par(ta));
          wgmma_fence();
          wgmma_m64n256k16_ss_tb<0, 0>(acc, q_lo, b_lo, 0);
          wgmma_m64n256k16_ss_tb<2, 128>(acc, q_lo, b_lo, 1);
          wgmma_m64n256k16_ss_tb<4, 256>(acc, q_lo, b_lo, 1);
          wgmma_m64n256k16_ss_tb<6, 384>(acc, q_lo, b_lo, 1);
          wgmma_commit();
        }
        #pragma unroll 1
        for (int j = 1; j < nkb; j++) {
          const uint32_t slot = ring_slot(qp_pos(j, ta >> 2));
          mbar_wait(b_full + 8 * slot, ring_par(qp_pos(j, ta >> 2)) ^ ((j >> 2) & 1));
          if (QP_STAG > 0 && cwg == 1 && j == nkb - QP_STAG) named_bar_sync(7, 256);
          const uint32_t a_lo = q_lo + (j & 3) * 1024, b_lo = w_base + slot * 2048;
          wgmma_fence();
          wgmma_m64n256k16_ss_tb<0, 0>(acc, a_lo, b_lo, 1);
          wgmma_m64n256k16_ss_tb<2, 128>(acc, a_lo, b_lo, 1);
          wgmma_m64n256k16_ss_tb<4, 256>(acc, a_lo, b_lo, 1);
          wgmma_m64n256k16_ss_tb<6, 384>(acc, a_lo, b_lo, 1);
          wgmma_commit();
          if (QP_STAG > 0 && cwg == 0 && j == nkb - 1) named_bar_arrive(7, 256);
          if (j > 0) {
            wgmma_wait<1>();
            if (tid == 0) mbar_arrive(b_empty + 8 * ring_slot(qp_pos(j - 1, ta >> 2)));
          }
        }
        wgmma_wait<0>();
        fence_regs(acc);
        FS(2 * it, 1);
        TL_MARK2(29, threadIdx.x == 256 && it == 0);
        if (tid == 0) mbar_arrive(b_empty + 24);
      }
      float o[64], s[64];
      uint32_t p[32], q[32];
      #pragma unroll
      for (int i = 0; i < 32; i++) q[i] = pack_bf16(acc[2 * i] * AT_C, acc[2 * i + 1] * AT_C);
      zero_regs(s);
      const uint32_t sq = sbase + AT_SQ + cwg * 8192;
      float mc0, mc1, al0 = 1.0f, al1 = 1.0f, l0 = 0.f, l1 = 0.f, lp0 = 0.f, lp1 = 0.f;
      bool redo0 = false;
      FS(2 * it, 2);
      mbar_wait(b_full + 8 * ring_slot(ta), ring_par(ta));
      named_bar_sync(1 + cwg, 256);
      FS(2 * it, 3);
      issue_qk(s, q, k_base + ring_slot(ta) * 2048);
      pass_turn(cwg);
      bool ready = mbar_test(b_full + 8 * ring_slot(ta + 1), ring_par(ta + 1)) & mbar_test(b_full + 8 * ring_slot(ta + 2), ring_par(ta + 2));
      stage_q<16>(acc, AT_C, sbase + AT_SQ + frag, lane);
      wgmma_wait<0>();
      fence_regs(s);
      if (tid == 0) mbar_arrive(b_empty + 8 * ring_slot(ta));
      mc0 = 0.f; mc1 = 0.f;
      if (!raw) {
        raw = softmax_mode(s, mc0, mc1);
        if (__builtin_expect(!raw, 0)) softmax_sub(s, mc0, mc1);
      }
      softmax_exp<0, 64>(s);
      #pragma unroll
      for (int J = 0; J < 16; J += 2)
        stmatrix_x4(sbase + AT_SQ + frag + (J >> 3) * 16384 + ((((J & 7) + (lane >> 4)) ^ (lane & 7)) << 4), q[2 * J], q[2 * J + 1], q[2 * J + 2], q[2 * J + 3]);
      pack_p(p, s);
      zero_regs(o);
      FS(2 * it, 4);
      uint32_t ks = ring_slot(ta + 1), vs = ring_slot(ta + 2), kp = ring_par(ta + 1), vp = ring_par(ta + 2);
      auto finish_head = [&]() {
        FS(2 * it, 5);
        redo0 = finish_l(lp0, lp1);
        if (!redo0) stage_o(o, lp0, lp1, sbase + AT_SQ + frag, lane);
        FS(2 * it + 1, 4);
      };
      if (!ready) { mbar_wait(b_full + 8 * ks, kp); mbar_wait(b_full + 8 * vs, vp); }
      #pragma unroll 1
      for (int n = 1; n < 2 * AT_NBLK; n++) {
        named_bar_sync(1 + cwg, 256);
        issue_qk(s, q, k_base + ks * 2048);
        if (n == AT_NBLK + 1) finish_head();
        issue_pv(o, p, v_base + vs * 2048, (n & 15) != 1);
        pass_turn(cwg);
        wgmma_wait<1>();
        fence_regs(s);
        if (tid == 0) mbar_arrive(b_empty + 8 * ks);
        if (__builtin_expect(!raw || (uint32_t)(n - (AT_NBLK - 1)) <= 2u, 0)) {
          if (n == AT_NBLK + 1 && !redo0) {
            fence_proxy_async();
            __syncwarp();
            if (lane == 0) mbar_arrive(b_ordy + 8 * cwg);
          }
          if (n == AT_NBLK - 1) {
            #pragma unroll
            for (int J = 0; J < 16; J += 2)
              ldmatrix_x4(sbase + AT_SQ + 32768 + frag + (J >> 3) * 16384 + ((((J & 7) + (lane >> 4)) ^ (lane & 7)) << 4), q[2 * J], q[2 * J + 1], q[2 * J + 2], q[2 * J + 3]);
          }
          if (!raw) {
            const float m0 = mc0, m1 = mc1;
            const bool ok = softmax_mode(s, mc0, mc1);
            if (n == AT_NBLK) raw = ok;
            else {
              mc0 = mc0 - AT_HEAD > m0 ? mc0 : m0; mc1 = mc1 - AT_HEAD > m1 ? mc1 : m1;
              al0 = ex2_approx(m0 - mc0); al1 = ex2_approx(m1 - mc1);
            }
            if (!raw) softmax_sub(s, mc0, mc1);
          }
        }
        softmax_exp<0, AT_SPLIT>(s);
        add_rowsum(p, l0, l1);
        if (tid == 0) {
          uint32_t dep = zero & __float_as_uint(l0) & __float_as_uint(l1);
          #pragma unroll
          for (int i = AT_SPLIT - AT_PIN - PINB; i < AT_SPLIT - PINB; i += 2) dep &= __float_as_uint(s[i]) & __float_as_uint(s[i + 1]);
          mbar_arrive(b_pin + dep);
        }
        wgmma_wait<0>();
        fence_regs(o);
        if (tid == 0) mbar_arrive(b_empty + 8 * vs);
        ks += 2; if (ks >= 5) { ks -= 5; kp ^= 1; }
        vs += 2; if (vs >= 5) { vs -= 5; vp ^= 1; }
        ready = mbar_test(b_full + 8 * ks, kp) & mbar_test(b_full + 8 * vs, vp);
        softmax_exp<AT_SPLIT, 64>(s);
        pack_p(p, s);
        if (n == AT_NBLK) { lp0 = l0; lp1 = l1; l0 = 0.f; l1 = 0.f; }
        if (__builtin_expect(!raw || !ready, 0)) {
        if (!raw && __any_sync(0xffffffffu, al0 != 1.0f || al1 != 1.0f)) {
          rescale_o(o, al0, al1);
          l0 *= al0; l1 *= al1;
          al0 = 1.0f; al1 = 1.0f;
        }
        if (!ready && n < 2 * AT_NBLK - 1) {
          mbar_wait(b_full + 8 * ks, kp);
          mbar_wait(b_full + 8 * vs, vp);
        }
        }
      }
      FS(2 * it + 1, 5);
      const uint32_t vl = ring_slot(ta + 63);
      vs = ring_slot(ta + 62);
      const uint32_t ob = more ? sbase + vs * 32768 : sbase + AT_SQ + 32768;
      mbar_wait(b_full + 8 * vl, ring_par(ta + 63));
      issue_pv(o, p, v_base + vl * 2048, 1);
      block_end(zero, b_pin);
      add_rowsum(p, l0, l1);
      const bool overflow = finish_l(l0, l1);
      if (!overflow && lane == 0) mbar_arrive(b_q1);
      #pragma unroll
      for (int i = 0; i < 8; i++) asm volatile("mov.b64 {%0, %1}, 0;\nmov.b64 {%2, %3}, 0;" : "=r"(pre[i].x), "=r"(pre[i].y), "=r"(pre[i].z), "=r"(pre[i].w));
      const bool want_pre = !more && bid < OG_MOE, got_pre = want_pre && __all_sync(0xffffffffu, mbar_test(bars + 272, 0));
      if (got_pre) load_pre(pre, sbase, AT_SQ, threadIdx.x - 128);
      mbar_wait(b_empty + 8 * vs, ring_par(ta + 62));
      wgmma_wait<0>();
      fence_regs(o);
      if (tid == 0) mbar_arrive(b_empty + 8 * vl);
      FS(2 * it + 1, 6);
      if (overflow) {
        attn_rows_exact(lds_u32(bars + 400), sq + 32768, ob + cwg * 8192, 4 * ta + 1, kc, vc);
        __syncwarp();
        if (lane == 0) mbar_arrive(b_q1);
      } else stage_o(o, l0, l1, ob + frag, lane);
      if (redo0) attn_rows_exact(lds_u32(bars + 400), sq, sq, 4 * ta, kc, vc);
      fence_proxy_async();
      __syncwarp();
      if (lane == 0) {
        if (redo0) mbar_arrive(b_ordy + 8 * cwg);
        mbar_arrive(b_ordy + 16 + 8 * cwg);
      }
      if (want_pre && !got_pre) load_pre(pre, sbase, AT_SQ, threadIdx.x - 128);
      if (redo0 || overflow) raw = false;
      named_bar_sync(3 + cwg, 128);
      FS(2 * it + 1, 7);
    }
    if (cwg == 0) named_bar_arrive(1, 256);
    if (__builtin_expect(single, 0)) {
      float acc[128];
      uint32_t j = 0, pk[64];
      #pragma unroll
      for (int i = 0; i < 64; i++) asm volatile("" : "=f"(acc[2 * i]), "=f"(acc[2 * i + 1]), "=r"(pk[i]));
      uint4* dst = g_pre;
      int left = 0;
      auto put = [&](bool last) {
        #pragma unroll
        for (int i = 0; i < PUT_N; i++) dst[i * 256] = make_uint4(pk[4 * i], pk[4 * i + 1], pk[4 * i + 2], pk[4 * i + 3]);
        dst += PUT_N * 256;
        #pragma unroll
        for (int i = 0; i < 64 - 4 * PUT_N; i++) asm volatile("mov.b32 %0, %1;" : "=r"(pk[i]) : "r"(pk[i + 4 * PUT_N]));
        __syncwarp();
        if (last && lane == 0) mbar_arrive(bars + 280);
      };
      #pragma unroll 1
      for (int ji = 0; ji < help_njobs(bid); ji++) {
        const int nk = og_pre(help_job(bid, ji));
        #pragma unroll 1
        for (int kk = 0; kk < nk; kk++, j++) {
          const uint32_t slot = ring_slot(qp_pos(j, 1));
          mbar_wait(b_full + 8 * slot, ring_par(qp_pos(j, 1)) ^ ((j >> 2) & 1));
          if (H_STAG > 0 && cwg == 1 && kk == nk - H_STAG) named_bar_sync(7, 256);
          const uint32_t a_lo = q_lo + (j & 3) * 1024, b_lo = w_base + slot * 2048;
          wgmma_fence();
          wgmma_m64n256k16_ss_tb<0, 0>(acc, a_lo, b_lo, kk != 0);
          wgmma_m64n256k16_ss_tb<2, 128>(acc, a_lo, b_lo, 1);
          wgmma_m64n256k16_ss_tb<4, 256>(acc, a_lo, b_lo, 1);
          wgmma_m64n256k16_ss_tb<6, 384>(acc, a_lo, b_lo, 1);
          wgmma_commit();
          if (H_STAG > 0 && cwg == 0 && kk == nk - 1) named_bar_arrive(7, 256);
          wgmma_wait<1>();
          if (kk > 0 && tid == 0) mbar_arrive(b_empty + 8 * ring_slot(qp_pos(j - 1, 1)));
          #pragma unroll 1
          for (int i = ji == OG_JOBS ? 0 : 16 / PUT_N - 1; i < 16 / PUT_N && left > 0; i++) put(--left == 0);
        }
        wgmma_wait<0>();
        fence_regs(acc);
        if (tid == 0) mbar_arrive(b_empty + 8 * ring_slot(qp_pos(j - 1, 1)));
        #pragma unroll
        for (int i = 0; i < 64; i++) pk[i] = pack_bf16(acc[2 * i], acc[2 * i + 1]);
        left = 16 / PUT_N;
        if (ji == PRE_X) mbar_wait(bars + 296, 0);
        dst = g_pre + help_job(bid, ji) * 2048 + threadIdx.x - 128;
      }
      #pragma unroll
      for (int i = 0; i < 16; i++) dst[i * 256] = make_uint4(pk[4 * i], pk[4 * i + 1], pk[4 * i + 2], pk[4 * i + 3]);
      __syncwarp();
      if (lane == 0) mbar_arrive(bars + 280);
      named_bar_sync(5, 256);
      if (threadIdx.x == 128) {
        #pragma unroll 1
        for (int i = 0; i < 5; i++) {
          constexpr int n = OG_HSUM;
          const int used = i == 3 ? 0 : (n + 3 - (i == 4 ? 3 : i)) / 4;
          if ((used ^ (i < 4)) & 1) {
            mbar_arrive(b_full + 8 * ring_slot(4 + i));
            mbar_arrive(b_empty + 8 * ring_slot(4 + i)); mbar_arrive(b_empty + 8 * ring_slot(4 + i));
          }
        }
        mbar_arrive(b_x);
      }
      named_bar_sync(5, 256);
      #pragma unroll
      for (int i = 0; i < 8; i++) pre[i] = make_uint4(0u, 0u, 0u, 0u);
    }
    TL_CLK(3, 1, threadIdx.x == 128);
    TL_CTA(1, threadIdx.x == 256);
    TL_END(3, tid == 0);
    TL_MARK2(19, tid == 0 && !single);
    if (bid < 128) {
      tail_consumer(bid, sbase, &tmOut, pre, cwg, w_gate, w_up);
    }
  }
}

typedef CUresult (*PFN_encodeTiled)(CUtensorMap*, CUtensorMapDataType, cuuint32_t, void*, const cuuint64_t*, const cuuint64_t*,
                                    const cuuint32_t*, const cuuint32_t*, CUtensorMapInterleave, CUtensorMapSwizzle,
                                    CUtensorMapL2promotion, CUtensorMapFloatOOBfill);

CUtensorMap make_map_2d(PFN_encodeTiled enc, const void* ptr, uint64_t inner, uint64_t outer, uint64_t stride_bytes, uint32_t box_inner, uint32_t box_outer) {
  CUtensorMap m;
  cuuint64_t gd[2] = {inner, outer}; cuuint64_t gs[1] = {stride_bytes};
  cuuint32_t bx[2] = {box_inner, box_outer}; cuuint32_t es[2] = {1, 1};
  enc(&m, CU_TENSOR_MAP_DATA_TYPE_BFLOAT16, 2, const_cast<void*>(ptr), gd, gs, bx, es, CU_TENSOR_MAP_INTERLEAVE_NONE,
      CU_TENSOR_MAP_SWIZZLE_128B, CU_TENSOR_MAP_L2_PROMOTION_L2_128B, CU_TENSOR_MAP_FLOAT_OOB_FILL_NONE);
  return m;
}

CUtensorMap make_map_3d(PFN_encodeTiled enc, const void* ptr, uint64_t cols, uint64_t rows, uint32_t box_rows, uint32_t chunks) {
  CUtensorMap m;
  cuuint64_t gd[3] = {64, rows, cols / 64}; cuuint64_t gs[2] = {cols * 2, 128};
  cuuint32_t bx[3] = {64, box_rows, chunks}; cuuint32_t es[3] = {1, 1, 1};
  enc(&m, CU_TENSOR_MAP_DATA_TYPE_BFLOAT16, 3, const_cast<void*>(ptr), gd, gs, bx, es, CU_TENSOR_MAP_INTERLEAVE_NONE,
      CU_TENSOR_MAP_SWIZZLE_128B, CU_TENSOR_MAP_L2_PROMOTION_L2_128B, CU_TENSOR_MAP_FLOAT_OOB_FILL_NONE);
  return m;
}

}

extern "C" void kernel_launch(void* const* d_in, const int* in_sizes, int n_in, void* d_out, int out_size) {
  const bf16* x      = (const bf16*)d_in[0];
  const bf16* kc     = (const bf16*)d_in[1];
  const bf16* vc     = (const bf16*)d_in[2];
  const bf16* wq     = (const bf16*)d_in[3];
  const bf16* wo     = (const bf16*)d_in[4];
  const bf16* w_r    = (const bf16*)d_in[6];
  const bf16* w_gate = (const bf16*)d_in[7];
  const bf16* w_up   = (const bf16*)d_in[8];
  const bf16* w_down = (const bf16*)d_in[9];
  const bf16* cvec   = (const bf16*)d_in[10];
  const bf16* w_mod  = (const bf16*)d_in[11];
  bf16* out = (bf16*)d_out;

  static PFN_encodeTiled enc = nullptr;
  static void *p_h = nullptr, *p_o = nullptr;
  if (!enc) {
    void* fn = nullptr; cudaDriverEntryPointQueryResult qres;
    cudaGetDriverEntryPoint("cuTensorMapEncodeTiled", &fn, cudaEnableDefault, &qres);
    enc = (PFN_encodeTiled)fn;
    cudaGetSymbolAddress(&p_h, g_pre);
    p_h = (uint4*)p_h + 16 * PRE_X * 2048;
    cudaGetSymbolAddress(&p_o, g_o);
    cudaFuncSetAttribute(fused_kernel, cudaFuncAttributeMaxDynamicSharedMemorySize, (int)AT_SMEM);
  }
  const CUtensorMap tm_h   = make_map_2d(enc, p_h, T_D, T_SEQ, T_D * 2, 64, 128);
  const CUtensorMap tm_wq  = make_map_3d(enc, wq, T_DQKV, T_D, 64, 4);
  const CUtensorMap tm_k   = make_map_3d(enc, kc, T_DH, (uint64_t)T_NH * T_SEQ, 128, 2);
  const CUtensorMap tm_v   = make_map_3d(enc, vc, T_DH, (uint64_t)T_NH * T_SEQ, 128, 2);
  const CUtensorMap tm_ost = make_map_2d(enc, p_o, T_DQKV, T_SEQ, T_DQKV * 2, 64, 64);
  const CUtensorMap tm_old = make_map_2d(enc, p_o, T_DQKV, T_SEQ, T_DQKV * 2, 64, 128);
  const CUtensorMap tm_wo  = make_map_3d(enc, wo, T_D, T_DQKV, 64, 2);
  const CUtensorMap tm_d   = make_map_3d(enc, w_down, T_D, T_F, 32, 8);

  const CUtensorMap tm_m   = make_map_2d(enc, w_mod, 6 * T_D, T_D, 6 * T_D * 2, 64, 256);
  const CUtensorMap tm_out = make_map_2d(enc, out, T_D, T_SEQ, T_D * 2, 64, 16);

  fused_kernel<<<132, 384, AT_SMEM, cudaStreamPerThread>>>(tm_h, tm_wq, tm_k, tm_v, tm_ost, tm_old, tm_wo, tm_d, tm_out, tm_m, 0u, (const uint8_t*)wo, kc, vc, x, cvec, w_mod,
             w_r, w_gate, w_up, w_down, out);
}
```

```cpp
#include <cuda_runtime.h>
#include <cuda_bf16.h>
#include <cuda.h>
#include <stdint.h>

namespace {

typedef __nv_bfloat16 bf16;

constexpr int T_SEQ = 2048, T_D = 1024, T_NH = 32, T_DH = 128, T_DQKV = 4096, T_F = 3584;

#define PRE_X 2
__device__ __align__(1024) uint4 g_pre[(16 * PRE_X + 128) * 2048];
#define g_h (reinterpret_cast<bf16*>(g_pre + 16 * PRE_X * 2048))
__device__ __align__(1024) bf16 g_o[T_SEQ * T_DQKV];
__device__ __align__(16) uint8_t g_col[8 * 1536];
__device__ __align__(16) float g_scal[64];
__device__ __align__(16) unsigned int g_hcnt[17 * 32];
__device__ __align__(128) float g_modpart[4 * 2 * T_D];
struct __align__(2048) TailMail {
  float4 part1[T_SEQ * 8];
  uint32_t key[256];
  uint4 cand[16 * 2 * 2 * 128];
  uint32_t cnt[32];
  float ypart[(T_F / 32) * 2 * T_D];
};
__device__ TailMail g_mail;
#define g_part1 g_mail.part1
#define g_key g_mail.key
#define g_cand g_mail.cand
#define CNT_Y (g_mail.cnt)
#define g_ypart g_mail.ypart

__device__ __forceinline__ uint32_t smem_u32(const void* p) { return (uint32_t)__cvta_generic_to_shared(p); }
__device__ __forceinline__ void mbar_init(uint32_t bar, uint32_t cnt) { asm volatile("mbarrier.init.shared::cta.b64 [%0], %1;" :: "r"(bar), "r"(cnt)); }
__device__ __forceinline__ void mbar_expect_tx(uint32_t bar, uint32_t bytes) { asm volatile("mbarrier.arrive.expect_tx.shared::cta.b64 _, [%0], %1;" :: "r"(bar), "r"(bytes) : "memory"); }
__device__ __forceinline__ void mbar_arrive(uint32_t bar) { asm volatile("mbarrier.arrive.shared::cta.b64 _, [%0];" :: "r"(bar) : "memory"); }
__device__ __forceinline__ void mbar_wait(uint32_t bar, uint32_t parity) {
  asm volatile("{\n.reg .pred p;\nLAB_WAIT:\nmbarrier.try_wait.parity.shared::cta.b64 p, [%0], %1;\n@!p bra LAB_WAIT;\n}\n" :: "r"(bar), "r"(parity) : "memory");
}
__device__ __forceinline__ bool mbar_test(uint32_t bar, uint32_t parity) {
  uint32_t r; asm volatile("{\n.reg .pred p;\nmbarrier.test_wait.parity.shared::cta.b64 p, [%1], %2;\nselp.u32 %0, 1, 0, p;\n}\n" : "=r"(r) : "r"(bar), "r"(parity) : "memory");
  return r != 0;
}
__device__ __forceinline__ void mbar_wait_long(uint32_t bar, uint32_t parity) {
  asm volatile("{\n.reg .pred p;\nLAB_WAIT:\nmbarrier.try_wait.parity.shared::cta.b64 p, [%0], %1, %2;\n@!p bra LAB_WAIT;\n}\n" :: "r"(bar), "r"(parity), "r"(100000) : "memory");
}
__device__ __forceinline__ uint32_t clock_lo() { uint32_t c; asm volatile("mov.u32 %0, %%clock;" : "=r"(c)); return c; }
__device__ __forceinline__ void fence_mbar_init() { asm volatile("fence.mbarrier_init.release.cluster;" ::: "memory"); }
__device__ __forceinline__ void tma_load_2d(uint32_t dst, const CUtensorMap* map, int c0, int c1, uint32_t bar) {
  asm volatile("cp.async.bulk.tensor.2d.shared::cluster.global.mbarrier::complete_tx::bytes [%0], [%1, {%3, %4}], [%2];"
    :: "r"(dst), "l"(map), "r"(bar), "r"(c0), "r"(c1) : "memory");
}
__device__ __forceinline__ uint64_t policy_evict_first() {
  uint64_t p; asm volatile("createpolicy.fractional.L2::evict_first.b64 %0, 1.0;" : "=l"(p)); return p;
}
__device__ __forceinline__ void tma_load_2d_hint(uint32_t dst, const CUtensorMap* map, int c0, int c1, uint32_t bar, uint64_t pol) {
  asm volatile("cp.async.bulk.tensor.2d.shared::cluster.global.mbarrier::complete_tx::bytes.L2::cache_hint [%0], [%1, {%3, %4}], [%2], %5;"
    :: "r"(dst), "l"(map), "r"(bar), "r"(c0), "r"(c1), "l"(pol) : "memory");
}
__device__ __forceinline__ void tma_load_3d_hint(uint32_t dst, const CUtensorMap* map, int c1, int c2, uint32_t bar, uint64_t pol) {
  asm volatile("cp.async.bulk.tensor.3d.shared::cluster.global.mbarrier::complete_tx::bytes.L2::cache_hint [%0], [%1, {%3, %4, %5}], [%2], %6;"
    :: "r"(dst), "l"(map), "r"(bar), "n"(0), "r"(c1), "r"(c2), "l"(pol) : "memory");
}
__device__ __forceinline__ void tma_load_3d(uint32_t dst, const CUtensorMap* map, int c1, int c2, uint32_t bar) {
  asm volatile("cp.async.bulk.tensor.3d.shared::cluster.global.mbarrier::complete_tx::bytes [%0], [%1, {%3, %4, %5}], [%2];"
    :: "r"(dst), "l"(map), "r"(bar), "n"(0), "r"(c1), "r"(c2) : "memory");
}
__device__ __forceinline__ void tma_store_2d(const CUtensorMap* map, uint32_t src, int c0, int c1) {
  asm volatile("cp.async.bulk.tensor.2d.global.shared::cta.bulk_group [%0, {%2, %3}], [%1];" :: "l"(map), "r"(src), "r"(c0), "r"(c1) : "memory");
}
__device__ __forceinline__ void prefetch_tmap(const CUtensorMap* map) { asm volatile("prefetch.tensormap [%0];" :: "l"(map) : "memory"); }
__device__ __forceinline__ void l2_prefetch_bulk(const void* p, uint32_t bytes) {
  asm volatile("cp.async.bulk.prefetch.L2.global [%0], %1;" :: "l"(p), "r"(bytes) : "memory");
}
__device__ __forceinline__ void bulk_commit() { asm volatile("cp.async.bulk.commit_group;" ::: "memory"); }
template<int N> __device__ __forceinline__ void bulk_wait_read() { asm volatile("cp.async.bulk.wait_group.read %0;" :: "n"(N) : "memory"); }
template<int N> __device__ __forceinline__ void bulk_wait() { asm volatile("cp.async.bulk.wait_group %0;" :: "n"(N) : "memory"); }
__device__ __forceinline__ void named_bar_sync(int id, int nthreads) { asm volatile("bar.sync %0, %1;" :: "r"(id), "r"(nthreads) : "memory"); }
__device__ __forceinline__ void named_bar_arrive(int id, int nthreads) { asm volatile("bar.arrive %0, %1;" :: "r"(id), "r"(nthreads) : "memory"); }
__device__ __forceinline__ void pass_turn(int cwg) {
  asm volatile("{\n.reg .pred p;\nsetp.ne.u32 p, %0, 0;\n@p bar.arrive 1, 256;\n@!p bar.arrive 2, 256;\n}\n" :: "r"(cwg) : "memory");
}
__device__ __forceinline__ void wgmma_fence() { asm volatile("wgmma.fence.sync.aligned;" ::: "memory"); }
__device__ __forceinline__ void wgmma_commit() { asm volatile("wgmma.commit_group.sync.aligned;" ::: "memory"); }
template<int N> __device__ __forceinline__ void wgmma_wait() { asm volatile("wgmma.wait_group.sync.aligned %0;" :: "n"(N) : "memory"); }
template<int R> __device__ __forceinline__ void reg_alloc() { asm volatile("setmaxnreg.inc.sync.aligned.u32 %0;" :: "n"(R)); }
template<int R> __device__ __forceinline__ void reg_dealloc() { asm volatile("setmaxnreg.dec.sync.aligned.u32 %0;" :: "n"(R)); }
__device__ __forceinline__ bool elect_one() {
  uint32_t pred; asm volatile("{\n.reg .pred p;\nelect.sync _|p, 0xffffffff;\nselp.u32 %0, 1, 0, p;\n}\n" : "=r"(pred)); return pred != 0;
}
__device__ __forceinline__ uint32_t pack_bf16(float lo, float hi) {
  uint32_t r; asm("cvt.rn.bf16x2.f32 %0, %1, %2;" : "=r"(r) : "f"(hi), "f"(lo)); return r;
}
__device__ __forceinline__ void stmatrix_x4(uint32_t addr, uint32_t r0, uint32_t r1, uint32_t r2, uint32_t r3) {
  asm volatile("stmatrix.sync.aligned.m8n8.x4.shared.b16 [%0], {%1, %2, %3, %4};" :: "r"(addr), "r"(r0), "r"(r1), "r"(r2), "r"(r3) : "memory");
}
__device__ __forceinline__ void fence_proxy_async() { asm volatile("fence.proxy.async.shared::cta;" ::: "memory"); }
__device__ __forceinline__ float ex2_approx(float x) { float y; asm("ex2.approx.ftz.f32 %0, %1;" : "=f"(y) : "f"(x)); return y; }
template<int N> __device__ __forceinline__ void fence_regs(float (&r)[N]) {
  #pragma unroll
  for (int i = 0; i < N; i++) asm volatile("" : "+f"(r[i]) :: "memory");
}
template<int N> __device__ __forceinline__ void zero_regs(float (&r)[N]) {
  #pragma unroll
  for (int i = 0; i < N; i += 2) asm volatile("mov.b64 {%0, %1}, 0;" : "=f"(r[i]), "=f"(r[i + 1]));
}
__device__ __forceinline__ float rbf(float x) { return __uint_as_float(pack_bf16(0.f, x)); }
__device__ __forceinline__ float bflo(uint32_t v) { return __uint_as_float(v << 16); }
__device__ __forceinline__ float bfhi(uint32_t v) { return __uint_as_float(v & 0xffff0000u); }

#define XT(i) do {} while (0)
#define TL_START(k) do {} while (0)
#define TL_END(k, cond) do {} while (0)
#define TL_CTA(i, cond) do {} while (0)
#define FS(slot, k) do {} while (0)
#define TL_MARK2(k, cond) do {} while (0)
#define TL_CLK(k, i, cond) do {} while (0)

template <int OFFA, int OFFB>
__device__ __forceinline__ void wgmma_m64n256k16_ss_tb(float (&d)[128], uint32_t a_lo, uint32_t b_lo, int scaleD) {
  asm volatile("{\n.reg .pred p;\n.reg .b32 ta, tb;\n.reg .b64 da, db;\nsetp.ne.b32 p, %130, 0;\n"
    "add.u32 ta, %128, %131;\nadd.u32 tb, %129, %132;\n"
    "mov.b64 da, {ta, 0x40000040};\nmov.b64 db, {tb, 0x40000040};\n"
    "wgmma.mma_async.sync.aligned.m64n256k16.f32.bf16.bf16 "
    "{%0, %1, %2, %3, %4, %5, %6, %7, %8, %9, %10, %11, %12, %13, %14, %15, %16, %17, %18, %19, %20, %21, %22, %23, %24, %25, %26, %27, %28, %29, %30, %31, %32, %33, %34, %35, %36, %37, %38, %39, %40, %41, %42, %43, %44, %45, %46, %47, %48, %49, %50, %51, %52, %53, %54, %55, %56, %57, %58, %59, %60, %61, %62, %63, %64, %65, %66, %67, %68, %69, %70, %71, %72, %73, %74, %75, %76, %77, %78, %79, %80, %81, %82, %83, %84, %85, %86, %87, %88, %89, %90, %91, %92, %93, %94, %95, %96, %97, %98, %99, %100, %101, %102, %103, %104, %105, %106, %107, %108, %109, %110, %111, %112, %113, %114, %115, %116, %117, %118, %119, %120, %121, %122, %123, %124, %125, %126, %127}, "
    "da, db, p, 1, 1, 0, 1;\n}\n"
    : "+f"(d[0]), "+f"(d[1]), "+f"(d[2]), "+f"(d[3]), "+f"(d[4]), "+f"(d[5]), "+f"(d[6]), "+f"(d[7]), "+f"(d[8]), "+f"(d[9]), "+f"(d[10]), "+f"(d[11]), "+f"(d[12]), "+f"(d[13]), "+f"(d[14]), "+f"(d[15]), "+f"(d[16]), "+f"(d[17]), "+f"(d[18]), "+f"(d[19]), "+f"(d[20]), "+f"(d[21]), "+f"(d[22]), "+f"(d[23]), "+f"(d[24]), "+f"(d[25]), "+f"(d[26]), "+f"(d[27]), "+f"(d[28]), "+f"(d[29]), "+f"(d[30]), "+f"(d[31]), "+f"(d[32]), "+f"(d[33]), "+f"(d[34]), "+f"(d[35]), "+f"(d[36]), "+f"(d[37]), "+f"(d[38]), "+f"(d[39]), "+f"(d[40]), "+f"(d[41]), "+f"(d[42]), "+f"(d[43]), "+f"(d[44]), "+f"(d[45]), "+f"(d[46]), "+f"(d[47]), "+f"(d[48]), "+f"(d[49]), "+f"(d[50]), "+f"(d[51]), "+f"(d[52]), "+f"(d[53]), "+f"(d[54]), "+f"(d[55]), "+f"(d[56]), "+f"(d[57]), "+f"(d[58]), "+f"(d[59]), "+f"(d[60]), "+f"(d[61]), "+f"(d[62]), "+f"(d[63]), "+f"(d[64]), "+f"(d[65]), "+f"(d[66]), "+f"(d[67]), "+f"(d[68]), "+f"(d[69]), "+f"(d[70]), "+f"(d[71]), "+f"(d[72]), "+f"(d[73]), "+f"(d[74]), "+f"(d[75]), "+f"(d[76]), "+f"(d[77]), "+f"(d[78]), "+f"(d[79]), "+f"(d[80]), "+f"(d[81]), "+f"(d[82]), "+f"(d[83]), "+f"(d[84]), "+f"(d[85]), "+f"(d[86]), "+f"(d[87]), "+f"(d[88]), "+f"(d[89]), "+f"(d[90]), "+f"(d[91]), "+f"(d[92]), "+f"(d[93]), "+f"(d[94]), "+f"(d[95]), "+f"(d[96]), "+f"(d[97]), "+f"(d[98]), "+f"(d[99]), "+f"(d[100]), "+f"(d[101]), "+f"(d[102]), "+f"(d[103]), "+f"(d[104]), "+f"(d[105]), "+f"(d[106]), "+f"(d[107]), "+f"(d[108]), "+f"(d[109]), "+f"(d[110]), "+f"(d[111]), "+f"(d[112]), "+f"(d[113]), "+f"(d[114]), "+f"(d[115]), "+f"(d[116]), "+f"(d[117]), "+f"(d[118]), "+f"(d[119]), "+f"(d[120]), "+f"(d[121]), "+f"(d[122]), "+f"(d[123]), "+f"(d[124]), "+f"(d[125]), "+f"(d[126]), "+f"(d[127])
    : "r"(a_lo), "r"(b_lo), "r"(scaleD), "n"(OFFA), "n"(OFFB));
}

template <int OFFA, int OFFB>
__device__ __forceinline__ void wgmma_m64n128k16_ss_tb(float (&d)[64], uint32_t a_lo, uint32_t b_lo, int scaleD) {
  asm volatile("{\n.reg .pred p;\n.reg .b32 ta, tb;\n.reg .b64 da, db;\nsetp.ne.b32 p, %66, 0;\n"
    "add.u32 ta, %64, %67;\nadd.u32 tb, %65, %68;\n"
    "mov.b64 da, {ta, 0x40000040};\nmov.b64 db, {tb, 0x40000040};\n"
    "wgmma.mma_async.sync.aligned.m64n128k16.f32.bf16.bf16 "
    "{%0, %1, %2, %3, %4, %5, %6, %7, %8, %9, %10, %11, %12, %13, %14, %15, %16, %17, %18, %19, %20, %21, %22, %23, %24, %25, %26, %27, %28, %29, %30, %31, %32, %33, %34, %35, %36, %37, %38, %39, %40, %41, %42, %43, %44, %45, %46, %47, %48, %49, %50, %51, %52, %53, %54, %55, %56, %57, %58, %59, %60, %61, %62, %63}, "
    "da, db, p, 1, 1, 0, 1;\n}\n"
    : "+f"(d[0]), "+f"(d[1]), "+f"(d[2]), "+f"(d[3]), "+f"(d[4]), "+f"(d[5]), "+f"(d[6]), "+f"(d[7]), "+f"(d[8]), "+f"(d[9]), "+f"(d[10]), "+f"(d[11]), "+f"(d[12]), "+f"(d[13]), "+f"(d[14]), "+f"(d[15]), "+f"(d[16]), "+f"(d[17]), "+f"(d[18]), "+f"(d[19]), "+f"(d[20]), "+f"(d[21]), "+f"(d[22]), "+f"(d[23]), "+f"(d[24]), "+f"(d[25]), "+f"(d[26]), "+f"(d[27]), "+f"(d[28]), "+f"(d[29]), "+f"(d[30]), "+f"(d[31]), "+f"(d[32]), "+f"(d[33]), "+f"(d[34]), "+f"(d[35]), "+f"(d[36]), "+f"(d[37]), "+f"(d[38]), "+f"(d[39]), "+f"(d[40]), "+f"(d[41]), "+f"(d[42]), "+f"(d[43]), "+f"(d[44]), "+f"(d[45]), "+f"(d[46]), "+f"(d[47]), "+f"(d[48]), "+f"(d[49]), "+f"(d[50]), "+f"(d[51]), "+f"(d[52]), "+f"(d[53]), "+f"(d[54]), "+f"(d[55]), "+f"(d[56]), "+f"(d[57]), "+f"(d[58]), "+f"(d[59]), "+f"(d[60]), "+f"(d[61]), "+f"(d[62]), "+f"(d[63])
    : "r"(a_lo), "r"(b_lo), "r"(scaleD), "n"(OFFA), "n"(OFFB));
}

template <int OFFB>
__device__ __forceinline__ void wgmma_m64n128k16_rs_tb(float (&d)[64], uint32_t a0, uint32_t a1, uint32_t a2, uint32_t a3, uint32_t b_lo, int scaleD) {
  asm volatile("{\n.reg .pred p;\n.reg .b32 tb;\n.reg .b64 db;\nsetp.ne.b32 p, %69, 0;\n"
    "add.u32 tb, %68, %70;\n"
    "mov.b64 db, {tb, 0x40000040};\n"
    "wgmma.mma_async.sync.aligned.m64n128k16.f32.bf16.bf16 "
    "{%0, %1, %2, %3, %4, %5, %6, %7, %8, %9, %10, %11, %12, %13, %14, %15, %16, %17, %18, %19, %20, %21, %22, %23, %24, %25, %26, %27, %28, %29, %30, %31, %32, %33, %34, %35, %36, %37, %38, %39, %40, %41, %42, %43, %44, %45, %46, %47, %48, %49, %50, %51, %52, %53, %54, %55, %56, %57, %58, %59, %60, %61, %62, %63}, "
    "{%64, %65, %66, %67}, db, p, 1, 1, 1;\n}\n"
    : "+f"(d[0]), "+f"(d[1]), "+f"(d[2]), "+f"(d[3]), "+f"(d[4]), "+f"(d[5]), "+f"(d[6]), "+f"(d[7]), "+f"(d[8]), "+f"(d[9]), "+f"(d[10]), "+f"(d[11]), "+f"(d[12]), "+f"(d[13]), "+f"(d[14]), "+f"(d[15]), "+f"(d[16]), "+f"(d[17]), "+f"(d[18]), "+f"(d[19]), "+f"(d[20]), "+f"(d[21]), "+f"(d[22]), "+f"(d[23]), "+f"(d[24]), "+f"(d[25]), "+f"(d[26]), "+f"(d[27]), "+f"(d[28]), "+f"(d[29]), "+f"(d[30]), "+f"(d[31]), "+f"(d[32]), "+f"(d[33]), "+f"(d[34]), "+f"(d[35]), "+f"(d[36]), "+f"(d[37]), "+f"(d[38]), "+f"(d[39]), "+f"(d[40]), "+f"(d[41]), "+f"(d[42]), "+f"(d[43]), "+f"(d[44]), "+f"(d[45]), "+f"(d[46]), "+f"(d[47]), "+f"(d[48]), "+f"(d[49]), "+f"(d[50]), "+f"(d[51]), "+f"(d[52]), "+f"(d[53]), "+f"(d[54]), "+f"(d[55]), "+f"(d[56]), "+f"(d[57]), "+f"(d[58]), "+f"(d[59]), "+f"(d[60]), "+f"(d[61]), "+f"(d[62]), "+f"(d[63])
    : "r"(a0), "r"(a1), "r"(a2), "r"(a3), "r"(b_lo), "r"(scaleD), "n"(OFFB));
}

template <int OFFB>
__device__ __forceinline__ void wgmma_m64n128k16_rs(float (&d)[64], uint32_t a0, uint32_t a1, uint32_t a2, uint32_t a3, uint32_t b_lo, int scaleD) {
  asm volatile("{\n.reg .pred p;\n.reg .b32 tb;\n.reg .b64 db;\nsetp.ne.b32 p, %69, 0;\n"
    "add.u32 tb, %68, %70;\n"
    "mov.b64 db, {tb, 0x40000040};\n"
    "wgmma.mma_async.sync.aligned.m64n128k16.f32.bf16.bf16 "
    "{%0, %1, %2, %3, %4, %5, %6, %7, %8, %9, %10, %11, %12, %13, %14, %15, %16, %17, %18, %19, %20, %21, %22, %23, %24, %25, %26, %27, %28, %29, %30, %31, %32, %33, %34, %35, %36, %37, %38, %39, %40, %41, %42, %43, %44, %45, %46, %47, %48, %49, %50, %51, %52, %53, %54, %55, %56, %57, %58, %59, %60, %61, %62, %63}, "
    "{%64, %65, %66, %67}, db, p, 1, 1, 0;\n}\n"
    : "+f"(d[0]), "+f"(d[1]), "+f"(d[2]), "+f"(d[3]), "+f"(d[4]), "+f"(d[5]), "+f"(d[6]), "+f"(d[7]), "+f"(d[8]), "+f"(d[9]), "+f"(d[10]), "+f"(d[11]), "+f"(d[12]), "+f"(d[13]), "+f"(d[14]), "+f"(d[15]), "+f"(d[16]), "+f"(d[17]), "+f"(d[18]), "+f"(d[19]), "+f"(d[20]), "+f"(d[21]), "+f"(d[22]), "+f"(d[23]), "+f"(d[24]), "+f"(d[25]), "+f"(d[26]), "+f"(d[27]), "+f"(d[28]), "+f"(d[29]), "+f"(d[30]), "+f"(d[31]), "+f"(d[32]), "+f"(d[33]), "+f"(d[34]), "+f"(d[35]), "+f"(d[36]), "+f"(d[37]), "+f"(d[38]), "+f"(d[39]), "+f"(d[40]), "+f"(d[41]), "+f"(d[42]), "+f"(d[43]), "+f"(d[44]), "+f"(d[45]), "+f"(d[46]), "+f"(d[47]), "+f"(d[48]), "+f"(d[49]), "+f"(d[50]), "+f"(d[51]), "+f"(d[52]), "+f"(d[53]), "+f"(d[54]), "+f"(d[55]), "+f"(d[56]), "+f"(d[57]), "+f"(d[58]), "+f"(d[59]), "+f"(d[60]), "+f"(d[61]), "+f"(d[62]), "+f"(d[63])
    : "r"(a0), "r"(a1), "r"(a2), "r"(a3), "r"(b_lo), "r"(scaleD), "n"(OFFB));
}

__device__ __forceinline__ uint4 ldg_nc_v4(const void* p) {
  uint4 v;
    asm volatile("{\n.reg .b64 pol;\ncreatepolicy.fractional.L2::evict_first.b64 pol, 1.0;\n"
                 "ld.global.nc.L1::no_allocate.L2::cache_hint.v4.u32 {%0, %1, %2, %3}, [%4], pol;\n}\n" : "=r"(v.x), "=r"(v.y), "=r"(v.z), "=r"(v.w) : "l"(p));
  return v;
}
__device__ __forceinline__ void unpack8(const uint4& u, float (&v)[8]) {
  v[0] = bflo(u.x); v[1] = bfhi(u.x); v[2] = bflo(u.y); v[3] = bfhi(u.y);
  v[4] = bflo(u.z); v[5] = bfhi(u.z); v[6] = bflo(u.w); v[7] = bfhi(u.w);
}
__device__ __forceinline__ void fma8(float (&acc)[8], float s, const uint4& w) {
  acc[0] = fmaf(s, bflo(w.x), acc[0]); acc[1] = fmaf(s, bfhi(w.x), acc[1]); acc[2] = fmaf(s, bflo(w.y), acc[2]); acc[3] = fmaf(s, bfhi(w.y), acc[3]);
  acc[4] = fmaf(s, bflo(w.z), acc[4]); acc[5] = fmaf(s, bfhi(w.z), acc[5]); acc[6] = fmaf(s, bflo(w.w), acc[6]); acc[7] = fmaf(s, bfhi(w.w), acc[7]);
}
__device__ __forceinline__ float rcp_approx(float x) { float y; asm("rcp.approx.ftz.f32 %0, %1;" : "=f"(y) : "f"(x)); return y; }
__device__ __forceinline__ float sigmoid_f(float v) { return rcp_approx(1.0f + ex2_approx(v * -1.4426950408889634f)); }
__device__ __forceinline__ float silu_bf(float v) { return rbf(v * sigmoid_f(v)); }
__device__ __forceinline__ uint32_t rank_key(float r, int idx) {
  const uint32_t b = __float_as_uint(r) >> 16;
  const uint32_t u = (r != r) ? 0u : ((b & 0x8000u) ? (~b & 0xffffu) : (b | 0x8000u));
  return (u << 16) | (0xffffu - (uint32_t)idx);
}
__device__ __forceinline__ void warp_top2(uint32_t& k1, uint32_t& k2) {
  const uint32_t m1 = __reduce_max_sync(0xffffffffu, k1);
  k2 = __reduce_max_sync(0xffffffffu, k1 == m1 ? k2 : k1);
  k1 = m1;
}
__device__ __forceinline__ uint32_t bmul2(uint32_t a, uint32_t b) { uint32_t r; asm("mul.rn.bf16x2 %0, %1, %2;" : "=r"(r) : "r"(a), "r"(b)); return r; }
__device__ __forceinline__ uint32_t badd2(uint32_t a, uint32_t b) { uint32_t r; asm("add.rn.bf16x2 %0, %1, %2;" : "=r"(r) : "r"(a), "r"(b)); return r; }
__device__ __forceinline__ uint32_t bsub2(uint32_t a, uint32_t b) { uint32_t r; asm("sub.rn.bf16x2 %0, %1, %2;" : "=r"(r) : "r"(a), "r"(b)); return r; }
__device__ __forceinline__ float sqrt_approx(float x) { float y; asm("sqrt.approx.f32 %0, %1;" : "=f"(y) : "f"(x)); return y; }
__device__ __forceinline__ uint32_t ln_norm2(uint32_t x1, uint32_t mb2, float inv) {
  const uint32_t d = bsub2(x1, mb2);
  return pack_bf16(bflo(d) * inv, bfhi(d) * inv);
}
__device__ __forceinline__ uint32_t bfma2(uint32_t a, uint32_t b, uint32_t c) { uint32_t r; asm("fma.rn.bf16x2 %0, %1, %2, %3;" : "=r"(r) : "r"(a), "r"(b), "r"(c)); return r; }
__device__ __forceinline__ uint32_t ln_norm2b(uint32_t x1, uint32_t mb2, uint32_t ih, uint32_t il) {
  const uint32_t d = bsub2(x1, mb2);
  return bfma2(d, ih, bmul2(d, il));
}
__device__ __forceinline__ uint32_t ln_mod2(uint32_t x1, uint32_t mb2, float inv, uint32_t c1, uint32_t sb) { return badd2(bmul2(ln_norm2(x1, mb2, inv), c1), sb); }
__device__ __forceinline__ void ldmatrix_x4(uint32_t addr, uint32_t& r0, uint32_t& r1, uint32_t& r2, uint32_t& r3) {
  asm volatile("ldmatrix.sync.aligned.m8n8.x4.shared.b16 {%0, %1, %2, %3}, [%4];" : "=r"(r0), "=r"(r1), "=r"(r2), "=r"(r3) : "r"(addr) : "memory");
}
__device__ __forceinline__ uint4 ldg_stream_v4(const void* p, uint64_t pol) {
  uint4 v; asm volatile("ld.global.nc.L1::no_allocate.L2::cache_hint.L2::128B.v4.u32 {%0, %1, %2, %3}, [%4], %5;" : "=r"(v.x), "=r"(v.y), "=r"(v.z), "=r"(v.w) : "l"(p), "l"(pol)); return v;
}
__device__ __forceinline__ void bulk_load_hint(uint32_t dst, const void* src, uint32_t bytes, uint32_t bar, uint64_t pol) {
  asm volatile("cp.async.bulk.shared::cluster.global.mbarrier::complete_tx::bytes.L2::cache_hint [%0], [%1], %2, [%3], %4;"
    :: "r"(dst), "l"(src), "r"(bytes), "r"(bar), "l"(pol) : "memory");
}
__device__ __forceinline__ void red_release_add(unsigned int* p, unsigned int v) { asm volatile("red.release.gpu.global.add.u32 [%0], %1;" :: "l"(p), "r"(v) : "memory"); }
__device__ __forceinline__ unsigned int ld_acquire(const unsigned int* p) { unsigned int v; asm volatile("ld.acquire.gpu.global.u32 %0, [%1];" : "=r"(v) : "l"(p) : "memory"); return v; }
__device__ __forceinline__ void spin_until(const unsigned int* p, unsigned int target) {
  #pragma unroll 1
  for (unsigned int i = 0; i < (1u << 22); i++) { if (ld_acquire(p) >= target) return; }
}
__device__ __forceinline__ float lds_f32(uint32_t a) { float v; asm volatile("ld.shared.f32 %0, [%1];" : "=f"(v) : "r"(a) : "memory"); return v; }
__device__ __forceinline__ float2 lds_f32x2(uint32_t a) { float2 v; asm volatile("ld.shared.v2.f32 {%0, %1}, [%2];" : "=f"(v.x), "=f"(v.y) : "r"(a) : "memory"); return v; }
__device__ __forceinline__ uint2 lds_u32x2(uint32_t a) { uint2 v; asm volatile("ld.shared.v2.u32 {%0, %1}, [%2];" : "=r"(v.x), "=r"(v.y) : "r"(a) : "memory"); return v; }
__device__ __forceinline__ uint32_t lds_u32(uint32_t a) { uint32_t v; asm volatile("ld.shared.u32 %0, [%1];" : "=r"(v) : "r"(a) : "memory"); return v; }
__device__ __forceinline__ void sts_u32(uint32_t a, uint32_t v) { asm volatile("st.shared.u32 [%0], %1;" :: "r"(a), "r"(v) : "memory"); }
__device__ __forceinline__ void sts_u32x2(uint32_t a, uint32_t x, uint32_t y) { asm volatile("st.shared.v2.u32 [%0], {%1, %2};" :: "r"(a), "r"(x), "r"(y) : "memory"); }
__device__ __forceinline__ void sts_f32(uint32_t a, float v) { asm volatile("st.shared.f32 [%0], %1;" :: "r"(a), "f"(v) : "memory"); }
__device__ __forceinline__ void sts_f32x2(uint32_t a, float x, float y) { asm volatile("st.shared.v2.f32 [%0], {%1, %2};" :: "r"(a), "f"(x), "f"(y) : "memory"); }
__device__ __forceinline__ void sts_f32x4(uint32_t a, float x, float y, float z, float w) { asm volatile("st.shared.v4.f32 [%0], {%1, %2, %3, %4};" :: "r"(a), "f"(x), "f"(y), "f"(z), "f"(w) : "memory"); }

__device__ __forceinline__ uint4 lds_u32x4(uint32_t a) { uint4 v; asm volatile("ld.shared.v4.u32 {%0, %1, %2, %3}, [%4];" : "=r"(v.x), "=r"(v.y), "=r"(v.z), "=r"(v.w) : "r"(a) : "memory"); return v; }
__device__ __forceinline__ void sts_u32x4(uint32_t a, uint32_t x, uint32_t y, uint32_t z, uint32_t w) { asm volatile("st.shared.v4.u32 [%0], {%1, %2, %3, %4};" :: "r"(a), "r"(x), "r"(y), "r"(z), "r"(w) : "memory"); }
__device__ __forceinline__ void st_tagged(float* p, float v) {
  const uint32_t b = __float_as_uint(v);
  asm volatile("st.relaxed.gpu.global.u32 [%0], %1;" :: "l"(p), "r"(b == 0u ? 0x80000000u : b) : "memory");
}
__device__ __forceinline__ void st_tagged4(float* p, float x, float y, float z, float w) {
  const uint32_t a = __float_as_uint(x), b = __float_as_uint(y), c = __float_as_uint(z), d = __float_as_uint(w);
  asm volatile("st.relaxed.gpu.global.v4.u32 [%0], {%1, %2, %3, %4};" :: "l"(p), "r"(a == 0u ? 0x80000000u : a), "r"(b == 0u ? 0x80000000u : b),
               "r"(c == 0u ? 0x80000000u : c), "r"(d == 0u ? 0x80000000u : d) : "memory");
}
__device__ __forceinline__ void st_relaxed2(void* p, uint32_t a, uint32_t b) { asm volatile("st.relaxed.gpu.global.v2.u32 [%0], {%1, %2};" :: "l"(p), "r"(a), "r"(b) : "memory"); }
__device__ __forceinline__ float4 ld_tagged4(const float* p) {
  float4 v; asm volatile("ld.relaxed.gpu.global.v4.f32 {%0, %1, %2, %3}, [%4];" : "=f"(v.x), "=f"(v.y), "=f"(v.z), "=f"(v.w) : "l"(p) : "memory"); return v;
}
__device__ __forceinline__ bool tagged4(const float4& v) {
  return __float_as_uint(v.x) != 0u && __float_as_uint(v.y) != 0u && __float_as_uint(v.z) != 0u && __float_as_uint(v.w) != 0u;
}
__device__ __forceinline__ void hint_arrive(uint32_t* p) { asm volatile("red.relaxed.gpu.global.add.u32 [%0], 1;" :: "l"(p) : "memory"); }
__device__ __forceinline__ void hint_wait(const uint32_t* p, uint32_t target) {
  uint32_t v = 0u;
  #pragma unroll 1
  for (unsigned int i = 0; i < (1u << 22) && v < target; i++) asm volatile("ld.relaxed.gpu.global.u32 %0, [%1];" : "=r"(v) : "l"(p) : "memory");
}
__device__ __forceinline__ void fence_proxy_async_global() { asm volatile("fence.proxy.async.global;" ::: "memory"); }

#define H_SPLIT 1
#define X_DLY 1200
#define W_DLY 1900
#define W_FIRST 2200
#define PRE_B 2
template <int J0, int J1>
__device__ __forceinline__ void load_parts(float2 (&pa)[J1 - J0][4], int t2) {
  #pragma unroll
  for (int j = J0; j < J1; j++)
    #pragma unroll
    for (int k = 0; k < 4; k++)
      asm volatile("ld.relaxed.gpu.global.v2.f32 {%0, %1}, [%2];" : "=f"(pa[j - J0][k].x), "=f"(pa[j - J0][k].y)
                   : "l"(g_modpart + k * 2 * T_D + (t2 >> 7) * T_D + j * 256 + (t2 & 127) * 2) : "memory");
}
template <int J0, int J1>
__device__ __forceinline__ void finish_parts(float2 (&pa)[J1 - J0][4], bool loaded, int t2, uint32_t tab) {
  #pragma unroll 1
  for (unsigned int spin = 0; spin < (1u << 22); spin++) {
    if (!loaded) load_parts<J0, J1>(pa, t2);
    loaded = false;
    bool ok = true;
    #pragma unroll
    for (int j = 0; j < J1 - J0; j++)
      #pragma unroll
      for (int k = 0; k < 4; k++) ok &= (__float_as_uint(pa[j][k].x) != 0u) & (__float_as_uint(pa[j][k].y) != 0u);
    if (__all_sync(0xffffffffu, ok)) break;
  }
  #pragma unroll
  for (int j = J0; j < J1; j++) {
    const float2* q = pa[j - J0];
    const uint32_t m = pack_bf16(((q[0].x + q[1].x) + q[2].x) + q[3].x, ((q[0].y + q[1].y) + q[2].y) + q[3].y);
    sts_u32(tab + (t2 >> 7) * 2048 + j * 512 + (t2 & 127) * 4, t2 >= 128 ? badd2(m, 0x3F803F80u) : m);
  }
}
__device__ __forceinline__ int head_cb(uint32_t bid) { return (bid & 16) | ((bid & 3) << 2) | ((bid >> 2) & 3); }
__device__ __forceinline__ void head_phase(uint32_t bid, uint32_t scr, uint32_t xs, uint32_t b_x, uint32_t b_go, uint32_t b_head, int t2, uint32_t zero, const bf16* __restrict__ cvec, const bf16* __restrict__ w_mod) {
  const int lane = t2 & 31, w8 = t2 >> 5;
  const int cb = head_cb(bid), ks = bid >> 5;
  const bool early = (cb & 15) < 4 * H_SPLIT;
  const uint32_t ws = (xs - 32768 + (t2 >> 3) * 128 + (((t2 ^ (t2 >> 3)) & 7) << 4)) ^ zero;
  const float cv = __bfloat162float(cvec[ks * 256 + t2]);
  const bf16* wsrc = w_mod + (size_t)(ks * 256 + (t2 >> 3)) * (6 * T_D) + cb * 64 + (t2 & 7) * 8;
  if (early) {
    const uint64_t pol = policy_evict_first();
    #pragma unroll 2
    for (int i = 0; i < 8; i++)
      asm volatile("cp.async.cg.shared.global.L2::cache_hint [%0], [%1], 16, %2;" :: "r"(ws + i * 4096), "l"(wsrc + (size_t)i * 32 * 6 * T_D), "l"(pol) : "memory");
  }
  sts_f32(scr + t2 * 4, silu_bf(cv));
  named_bar_sync(6, 384);
  TL_MARK2(1, t2 == 0);
  uint4 xv[2][4];
  uint32_t mb2[2], ih[2], il[2];
  auto norm = [&](int j) {
    #pragma unroll
    for (int r = 0; r < 2; r++) {
      xv[r][j].x = ln_norm2b(xv[r][j].x, mb2[r], ih[r], il[r]); xv[r][j].y = ln_norm2b(xv[r][j].y, mb2[r], ih[r], il[r]);
      xv[r][j].z = ln_norm2b(xv[r][j].z, mb2[r], ih[r], il[r]); xv[r][j].w = ln_norm2b(xv[r][j].w, mb2[r], ih[r], il[r]);
    }
  };
  auto modulate = [&](int j) {
    const uint4 sa = lds_u32x4(scr + 8192 + j * 512 + lane * 16), c1 = lds_u32x4(scr + 8192 + 2048 + j * 512 + lane * 16);
    #pragma unroll
    for (int r = 0; r < 2; r++) {
      xv[r][j].x = badd2(bmul2(xv[r][j].x, c1.x), sa.x); xv[r][j].y = badd2(bmul2(xv[r][j].y, c1.y), sa.y);
      xv[r][j].z = badd2(bmul2(xv[r][j].z, c1.z), sa.z); xv[r][j].w = badd2(bmul2(xv[r][j].w, c1.w), sa.w);
    }
  };
  auto store = [&](int j) {
    #pragma unroll
    for (int r = 0; r < 2; r++) *reinterpret_cast<uint4*>(g_h + (size_t)(bid * 16 + 2 * w8 + r) * T_D + j * 256 + lane * 8) = xv[r][j];
  };
  #pragma unroll 1
  for (int ph = 0; ph < 2; ph++) {
    if ((ph == 0) == early) {
      asm volatile("cp.async.wait_all;" ::: "memory");
      if (!early) mbar_wait(b_x + 168, 0);
      float acc[8];
      #pragma unroll
      for (int j = 0; j < 8; j++) acc[j] = 0.f;
      #pragma unroll
      for (int i = 0; i < 8; i++) fma8(acc, lds_f32(scr + ((t2 >> 3) + 32 * i) * 4), lds_u32x4(ws + i * 4096));
      #pragma unroll
      for (int j = 0; j < 4; j++) { const bool up = lane & 16; acc[j] = (up ? acc[4 + j] : acc[j]) + __shfl_xor_sync(0xffffffffu, up ? acc[j] : acc[4 + j], 16); }
      #pragma unroll
      for (int j = 0; j < 2; j++) { const bool up = lane & 8; acc[j] = (up ? acc[2 + j] : acc[j]) + __shfl_xor_sync(0xffffffffu, up ? acc[j] : acc[2 + j], 8); }
      sts_f32x2(scr + 1024 + w8 * 256 + (lane & 7) * 32 + (lane >> 3) * 8, acc[0], acc[1]);
      named_bar_sync(5, 256);
      if (t2 < 64) {
        float sum = 0.f;
        #pragma unroll
        for (int i = 0; i < 8; i++) sum += lds_f32(scr + 1024 + i * 256 + t2 * 4);
        st_tagged(g_modpart + ks * 2 * T_D + cb * 64 + t2, sum);
        TL_MARK2(early ? 2 : 6, t2 == 0);
      }
    } else {
      float2 pa[H_SPLIT][4];
      mbar_wait(b_x, 0);
      TL_MARK2(18, t2 == 0);
      load_parts<0, H_SPLIT>(pa, t2);
      #pragma unroll
      for (int r = 0; r < 2; r++)
        #pragma unroll
        for (int j = 0; j < 4; j++) xv[r][j] = lds_u32x4(xs + (2 * w8 + r) * 2048 + j * 512 + lane * 16);
  {
    float st[4] = {0.f, 0.f, 0.f, 0.f};
    #pragma unroll
    for (int r = 0; r < 2; r++)
      #pragma unroll
      for (int j = 0; j < 4; j++) {
        float v[8];
        unpack8(xv[r][j], v);
        st[2 * r] += ((v[0] + v[1]) + (v[2] + v[3])) + ((v[4] + v[5]) + (v[6] + v[7]));
        st[2 * r + 1] += fmaf(v[0], v[0], fmaf(v[1], v[1], fmaf(v[2], v[2], v[3] * v[3]))) + fmaf(v[4], v[4], fmaf(v[5], v[5], fmaf(v[6], v[6], v[7] * v[7])));
      }
    #pragma unroll
    for (int k = 0; k < 2; k++) { const bool up = lane & 16; st[k] = (up ? st[2 + k] : st[k]) + __shfl_xor_sync(0xffffffffu, up ? st[k] : st[2 + k], 16); }
    #pragma unroll
    for (int o = 8; o > 0; o >>= 1) { st[0] += __shfl_xor_sync(0xffffffffu, st[0], o); st[1] += __shfl_xor_sync(0xffffffffu, st[1], o); }
    const float mean = st[0] * (1.0f / T_D);
    const float inv = rcp_approx(rbf(sqrt_approx(rbf(rbf(fmaxf(fmaf(-mean, mean, st[1] * (1.0f / T_D)), 0.f)) + 1e-05f))));
    const uint32_t m = pack_bf16(mean, mean), h = pack_bf16(inv - rbf(inv), inv);
    #pragma unroll
    for (int r = 0; r < 2; r++) {
      mb2[r] = __shfl_sync(0xffffffffu, m, 16 * r);
      const uint32_t hr = __shfl_sync(0xffffffffu, h, 16 * r);
      ih[r] = __byte_perm(hr, hr, 0x3232); il[r] = __byte_perm(hr, hr, 0x1010);
    }
  }
      #pragma unroll
      for (int j = 0; j < H_SPLIT; j++) norm(j);
      TL_MARK2(5, t2 == 0);
      finish_parts<0, H_SPLIT>(pa, true, t2, scr + 8192);
      named_bar_sync(5, 256);
      TL_MARK2(7, t2 == 0);
      #pragma unroll
      for (int j = 0; j < H_SPLIT; j++) { modulate(j); store(j); }
      named_bar_arrive(9, 288);
    }
  }
  #pragma unroll
  for (int j = H_SPLIT; j < 4; j++) norm(j);
  float2 pb[4 - H_SPLIT][4];
  finish_parts<H_SPLIT, 4>(pb, false, t2, scr + 8192);
  named_bar_sync(5, 256);
  TL_MARK2(17, t2 == 0);
  #pragma unroll
  for (int j = H_SPLIT; j < 4; j++) modulate(j);
  __syncwarp();
  if (lane == 0) mbar_arrive(b_head + (xv[1][3].w & zero));
  mbar_wait(b_go, 0);
  #pragma unroll
  for (int j = H_SPLIT; j < 4; j++) store(j);
  named_bar_arrive(8, 288);
}

#define MOD_AT (b_empty + 8)
#define MOD_SPLIT 16
__device__ __forceinline__ void mod_rest(uint32_t bid, uint32_t scr, uint32_t b_go, int t, const bf16* __restrict__ cvec, const bf16* __restrict__ w_mod, const bf16* __restrict__ w_r) {
  const int lane = t & 31;
  #pragma unroll 1
  for (int i = t; i < T_D / 2; i += 64) {
    const uint32_t c2 = *reinterpret_cast<const uint32_t*>(cvec + 2 * i);
    sts_u32(scr + i * 4, pack_bf16(silu_bf(bflo(c2)), silu_bf(bfhi(c2))));
  }
  named_bar_sync(11, 64);
  const bf16* wp = w_mod + (size_t)(2 * (t >> 2)) * (6 * T_D) + 2 * T_D + bid * 32 + (t & 3) * 8;
  float acc[8];
  #pragma unroll
  for (int i = 0; i < 8; i++) acc[i] = 0.f;
  #pragma unroll 1
  for (int i = 0; i < 32; i += 2) {
    if (i == MOD_SPLIT) mbar_wait_long(b_go, 0);
    const uint4 w0 = ldg_nc_v4(wp), w1 = ldg_nc_v4(wp + 6 * T_D), w2 = ldg_nc_v4(wp + 32 * 6 * T_D), w3 = ldg_nc_v4(wp + 33 * 6 * T_D);
    wp += 64 * 6 * T_D;
    const uint32_t s0 = lds_u32(scr + (i * 16 + (t >> 2)) * 4), s1 = lds_u32(scr + (i * 16 + 16 + (t >> 2)) * 4);
    fma8(acc, bflo(s0), w0); fma8(acc, bfhi(s0), w1); fma8(acc, bflo(s1), w2); fma8(acc, bfhi(s1), w3);
  }
  #pragma unroll
  for (int j = 0; j < 4; j++) { const bool up = lane & 16; acc[j] = (up ? acc[4 + j] : acc[j]) + __shfl_xor_sync(0xffffffffu, up ? acc[j] : acc[4 + j], 16); }
  #pragma unroll
  for (int j = 0; j < 2; j++) { const bool up = lane & 8; acc[j] = (up ? acc[2 + j] : acc[j]) + __shfl_xor_sync(0xffffffffu, up ? acc[j] : acc[2 + j], 8); }
  { const bool up = lane & 4; acc[0] = (up ? acc[1] : acc[0]) + __shfl_xor_sync(0xffffffffu, up ? acc[0] : acc[1], 4); }
  if (t >= 32) sts_f32(scr + 2048 + lane * 4, acc[0]);
  named_bar_sync(11, 64);
  if (__shfl_sync(0xffffffffu, t, 0) < 32) {
    const int kind = bid >> 5;
    float v = rbf(acc[0] + lds_f32(scr + 2048 + lane * 4));
    const int col = (bid & 31) * 32 + (lane & 3) * 8 + (lane >> 2);
    uint8_t* dst = g_col + (col >> 7) * 1536;
    if (kind == 2) v = rbf(1.0f + v);
    float vw = v * __bfloat162float(w_r[col]);
    if (kind == 2) {
      const int c = col & 127, i = (c & ~15) + ((c >> 1) & 3) * 4 + ((c >> 3) & 1) * 2 + (c & 1);
      reinterpret_cast<bf16*>(dst)[i] = __float2bfloat16_rn(vw);
      reinterpret_cast<bf16*>(dst)[128 + i] = __float2bfloat16_rn(vw - rbf(vw));
    }
    reinterpret_cast<bf16*>(dst + 512 + (kind & 1) * 512 + (kind >> 1) * 256)[col & 127] = __float2bfloat16_rn(v);
    #pragma unroll
    for (int o = 16; o > 0; o >>= 1) vw += __shfl_xor_sync(0xffffffffu, vw, o);
    if (lane == 0 && (kind == 1 || kind == 2)) g_scal[95 - bid] = vw;
  }
  #pragma unroll 1
  for (int i = bid * 64 + t; i < (int)(sizeof(g_mail) / 16); i += 128 * 64) reinterpret_cast<uint4*>(&g_mail)[i] = make_uint4(0u, 0u, 0u, 0u);
  named_bar_sync(11, 64);
  if (t == 0) red_release_add(&g_hcnt[0], 1u);
}

constexpr int AT_NBLK = T_SEQ / 128;
constexpr float AT_HEAD = 7.0f;
#define WO_LATE 12
#define QP_STAG 3
#define AT_SPLIT 28
#define AT_PIN 12
#define PINB 4
constexpr int AT_NFULL = 124;
constexpr int AT_PREG = 40, AT_CREG = 232;
constexpr uint32_t AT_SQ = 5 * 32768;
constexpr float AT_C = 0.08838834764831845f * 1.4426950408889634f;
constexpr float AT_RAW_LO = -16.0f, AT_RAW_HI = 24.0f;
constexpr float AT_RAW_SUM = 281474976710656.0f, AT_RAW_MIN = 9.094947017729282e-13f;
constexpr uint32_t AT_SBAR = AT_SQ + 65536 + 256;
constexpr uint32_t AT_SMEM = AT_SQ + 65536 + 3072;

__device__ __forceinline__ uint32_t ring_slot(uint32_t t) { return t - 5u * ((t * 205u) >> 10); }
__device__ __forceinline__ uint32_t qp_pos(uint32_t j, uint32_t it) { return 4u * it + (j & 3u) + ((j & 3u) == 3u ? it : 0u); }
__device__ __forceinline__ uint32_t ring_par(uint32_t t) { return ((t * 205u) >> 10) & 1u; }
__device__ __forceinline__ void softmax_rowmax(const float (&s)[64], float& mx0, float& mx1) {
  float a0 = fmaxf(s[0], s[1]), a1 = fmaxf(s[4], s[5]), a2 = fmaxf(s[8], s[9]), a3 = fmaxf(s[12], s[13]);
  float b0 = fmaxf(s[2], s[3]), b1 = fmaxf(s[6], s[7]), b2 = fmaxf(s[10], s[11]), b3 = fmaxf(s[14], s[15]);
  #pragma unroll
  for (int j = 4; j < 16; j += 4) {
    a0 = fmaxf(a0, fmaxf(s[4 * j + 0], s[4 * j + 1]));  b0 = fmaxf(b0, fmaxf(s[4 * j + 2], s[4 * j + 3]));
    a1 = fmaxf(a1, fmaxf(s[4 * j + 4], s[4 * j + 5]));  b1 = fmaxf(b1, fmaxf(s[4 * j + 6], s[4 * j + 7]));
    a2 = fmaxf(a2, fmaxf(s[4 * j + 8], s[4 * j + 9]));  b2 = fmaxf(b2, fmaxf(s[4 * j + 10], s[4 * j + 11]));
    a3 = fmaxf(a3, fmaxf(s[4 * j + 12], s[4 * j + 13])); b3 = fmaxf(b3, fmaxf(s[4 * j + 14], s[4 * j + 15]));
  }
  mx0 = fmaxf(fmaxf(a0, a1), fmaxf(a2, a3));
  mx1 = fmaxf(fmaxf(b0, b1), fmaxf(b2, b3));
  mx0 = fmaxf(mx0, __shfl_xor_sync(0xffffffffu, mx0, 1));
  mx1 = fmaxf(mx1, __shfl_xor_sync(0xffffffffu, mx1, 1));
  mx0 = fmaxf(mx0, __shfl_xor_sync(0xffffffffu, mx0, 2));
  mx1 = fmaxf(mx1, __shfl_xor_sync(0xffffffffu, mx1, 2));
}
__device__ __forceinline__ void softmax_sub(float (&s)[64], float mc0, float mc1) {
  #pragma unroll
  for (int j = 0; j < 16; j++) { s[4 * j] -= mc0; s[4 * j + 1] -= mc0; s[4 * j + 2] -= mc1; s[4 * j + 3] -= mc1; }
}
template <int LO, int HI>
__device__ __forceinline__ void softmax_exp(float (&s)[64]) {
  #pragma unroll
  for (int i = LO; i < HI; i++) s[i] = ex2_approx(s[i]);
}
__device__ __forceinline__ bool softmax_mode(const float (&s)[64], float& mc0, float& mc1) {
  softmax_rowmax(s, mc0, mc1);
  const bool raw = __all_sync(0xffffffffu, mc0 >= AT_RAW_LO && mc0 <= AT_RAW_HI && mc1 >= AT_RAW_LO && mc1 <= AT_RAW_HI);
  mc0 += AT_HEAD; mc1 += AT_HEAD;
  return raw;
}
__device__ __forceinline__ void rowsum_p(const uint32_t (&p)[32], uint32_t& t0, uint32_t& t1) {
  uint32_t a[16];
  #pragma unroll
  for (int i = 0; i < 8; i++) { a[2 * i] = badd2(p[4 * i], p[4 * i + 2]); a[2 * i + 1] = badd2(p[4 * i + 1], p[4 * i + 3]); }
  #pragma unroll
  for (int i = 0; i < 4; i++) { a[2 * i] = badd2(a[4 * i], a[4 * i + 2]); a[2 * i + 1] = badd2(a[4 * i + 1], a[4 * i + 3]); }
  t0 = badd2(badd2(a[0], a[2]), badd2(a[4], a[6]));
  t1 = badd2(badd2(a[1], a[3]), badd2(a[5], a[7]));
}
__device__ __forceinline__ void add_rowsum(const uint32_t (&p)[32], float& l0, float& l1) {
  uint32_t t0, t1;
  rowsum_p(p, t0, t1);
  l0 += bflo(t0) + bfhi(t0); l1 += bflo(t1) + bfhi(t1);
}
__device__ __forceinline__ void pack_p(uint32_t (&p)[32], const float (&s)[64]) {
  #pragma unroll
  for (int i = 0; i < 32; i++) p[i] = pack_bf16(s[2 * i], s[2 * i + 1]);
}
__device__ __noinline__ void attn_rows_exact(uint32_t bid, uint32_t sq, uint32_t so, int hsel, const bf16* __restrict__ kh, const bf16* __restrict__ vh) {
  const int warp = (threadIdx.x >> 5) & 3, lane = threadIdx.x & 31;
  const size_t hofs = (size_t)((bid < 128 ? bid >> 4 : 15) * 2 + hsel) * T_SEQ * T_DH;
  kh += hofs; vh += hofs;
  #pragma unroll 1
  for (int r = 16 * warp; r < 16 * warp + 16; r++) {
    const uint32_t ad = (lane >> 4) * 16384 + r * 128 + ((((lane & 15) >> 1) ^ (r & 7)) << 4) + (lane & 1) * 8;
    uint2 qv; asm volatile("ld.shared.v2.u32 {%0, %1}, [%2];" : "=r"(qv.x), "=r"(qv.y) : "r"(sq + ad) : "memory");
    const float q0 = bflo(qv.x), q1 = bfhi(qv.x), q2 = bflo(qv.y), q3 = bfhi(qv.y);
    float m = -INFINITY, l = 0.f, o0 = 0.f, o1 = 0.f, o2 = 0.f, o3 = 0.f;
    #pragma unroll 1
    for (int key = 0; key < T_SEQ; key++) {
      const uint2 kv = *reinterpret_cast<const uint2*>(kh + (size_t)key * T_DH + lane * 4);
      const uint2 vv = *reinterpret_cast<const uint2*>(vh + (size_t)key * T_DH + lane * 4);
      float sc = (q0 * bflo(kv.x) + q1 * bfhi(kv.x)) + (q2 * bflo(kv.y) + q3 * bfhi(kv.y));
      #pragma unroll
      for (int o = 16; o > 0; o >>= 1) sc += __shfl_xor_sync(0xffffffffu, sc, o);
      const float mn = fmaxf(m, sc);
      const float al = (m == mn) ? 1.0f : ex2_approx(m - mn), p = rbf(ex2_approx(sc - mn));
      m = mn;
      l = fmaf(l, al, p);
      o0 = fmaf(o0, al, p * bflo(vv.x)); o1 = fmaf(o1, al, p * bfhi(vv.x));
      o2 = fmaf(o2, al, p * bflo(vv.y)); o3 = fmaf(o3, al, p * bfhi(vv.y));
    }
    const float inv = rcp_approx(l);
    asm volatile("st.shared.v2.u32 [%0], {%1, %2};" :: "r"(so + ad), "r"(pack_bf16(o0 * inv, o1 * inv)), "r"(pack_bf16(o2 * inv, o3 * inv)) : "memory");
  }
}
__device__ __forceinline__ void issue_qk(float (&s)[64], const uint32_t (&q)[32], uint32_t k_lo) {
  wgmma_fence();
  wgmma_m64n128k16_rs<0>(s, q[0], q[1], q[2], q[3], k_lo, 0);
  wgmma_m64n128k16_rs<2>(s, q[4], q[5], q[6], q[7], k_lo, 1);
  wgmma_m64n128k16_rs<4>(s, q[8], q[9], q[10], q[11], k_lo, 1);
  wgmma_m64n128k16_rs<6>(s, q[12], q[13], q[14], q[15], k_lo, 1);
  wgmma_m64n128k16_rs<1024>(s, q[16], q[17], q[18], q[19], k_lo, 1);
  wgmma_m64n128k16_rs<1026>(s, q[20], q[21], q[22], q[23], k_lo, 1);
  wgmma_m64n128k16_rs<1028>(s, q[24], q[25], q[26], q[27], k_lo, 1);
  wgmma_m64n128k16_rs<1030>(s, q[28], q[29], q[30], q[31], k_lo, 1);
  wgmma_commit();
}
__device__ __forceinline__ void issue_pv(float (&o)[64], const uint32_t (&p)[32], uint32_t v_lo, int accumulate) {
  wgmma_fence();
  wgmma_m64n128k16_rs_tb<0>(o, p[0], p[1], p[2], p[3], v_lo, accumulate);
  wgmma_m64n128k16_rs_tb<128>(o, p[4], p[5], p[6], p[7], v_lo, 1);
  wgmma_m64n128k16_rs_tb<256>(o, p[8], p[9], p[10], p[11], v_lo, 1);
  wgmma_m64n128k16_rs_tb<384>(o, p[12], p[13], p[14], p[15], v_lo, 1);
  wgmma_m64n128k16_rs_tb<512>(o, p[16], p[17], p[18], p[19], v_lo, 1);
  wgmma_m64n128k16_rs_tb<640>(o, p[20], p[21], p[22], p[23], v_lo, 1);
  wgmma_m64n128k16_rs_tb<768>(o, p[24], p[25], p[26], p[27], v_lo, 1);
  wgmma_m64n128k16_rs_tb<896>(o, p[28], p[29], p[30], p[31], v_lo, 1);
  wgmma_commit();
}
__device__ __forceinline__ void block_end(uint32_t zero, uint32_t bar) {
  #pragma unroll 1
  for (uint32_t i = 0; i < zero; i++) mbar_arrive(bar);
}
__device__ __forceinline__ void rescale_o(float (&o)[64], float al0, float al1) {
  #pragma unroll
  for (int j = 0; j < 16; j++) { o[4 * j] *= al0; o[4 * j + 1] *= al0; o[4 * j + 2] *= al1; o[4 * j + 3] *= al1; }
}

__device__ __forceinline__ void stage_o(const float (&o)[64], float i0, float i1, uint32_t dst, int lane) {
  #pragma unroll
  for (int J = 0; J < 16; J += 2)
    stmatrix_x4(dst + (J >> 3) * 16384 + ((((J & 7) + (lane >> 4)) ^ (lane & 7)) << 4),
                pack_bf16(o[4 * J + 0] * i0, o[4 * J + 1] * i0), pack_bf16(o[4 * J + 2] * i1, o[4 * J + 3] * i1),
                pack_bf16(o[4 * J + 4] * i0, o[4 * J + 5] * i0), pack_bf16(o[4 * J + 6] * i1, o[4 * J + 7] * i1));
}
__device__ __forceinline__ bool finish_l(float& l0, float& l1) {
  l0 += __shfl_xor_sync(0xffffffffu, l0, 1); l1 += __shfl_xor_sync(0xffffffffu, l1, 1);
  l0 += __shfl_xor_sync(0xffffffffu, l0, 2); l1 += __shfl_xor_sync(0xffffffffu, l1, 2);
  const bool redo = __any_sync(0xffffffffu, !(l0 <= AT_RAW_SUM && l1 <= AT_RAW_SUM && l0 >= AT_RAW_MIN && l1 >= AT_RAW_MIN));
  l0 = rcp_approx(l0); l1 = rcp_approx(l1);
  return redo;
}
template <int J0>
__device__ __forceinline__ void stage_q(const float (&acc)[128], float c, uint32_t dst, int lane) {
  #pragma unroll
  for (int J = J0; J < J0 + 16; J += 2)
    stmatrix_x4(dst + (J >> 3) * 16384 + ((((J & 7) + (lane >> 4)) ^ (lane & 7)) << 4),
                pack_bf16(acc[4 * J + 0] * c, acc[4 * J + 1] * c), pack_bf16(acc[4 * J + 2] * c, acc[4 * J + 3] * c),
                pack_bf16(acc[4 * J + 4] * c, acc[4 * J + 5] * c), pack_bf16(acc[4 * J + 6] * c, acc[4 * J + 7] * c));
}
__device__ __forceinline__ void store_o(const CUtensorMap* tmO, uint32_t src, int head, int row) {
  tma_store_2d(tmO, src, head * T_DH, row);
  tma_store_2d(tmO, src + 16384, head * T_DH + 64, row);
  bulk_commit();
}
__device__ __forceinline__ void mma_bf16(float (&d)[4], uint32_t a0, uint32_t a1, uint32_t a2, uint32_t a3, uint32_t b0, uint32_t b1) {
  asm volatile("mma.sync.aligned.m16n8k16.row.col.f32.bf16.bf16.f32 {%0, %1, %2, %3}, {%4, %5, %6, %7}, {%8, %9}, {%0, %1, %2, %3};"
               : "+f"(d[0]), "+f"(d[1]), "+f"(d[2]), "+f"(d[3]) : "r"(a0), "r"(a1), "r"(a2), "r"(a3), "r"(b0), "r"(b1));
}
struct GemvSel { uint32_t lo0, hi0, lo1, hi1; };
__device__ __forceinline__ GemvSel gemv_sel(int lane) {
  const uint32_t lo = (lane & 8) ? 0x1044u : 0x4410u, hi = (lane & 8) ? 0x3244u : 0x4432u;
  GemvSel s; s.lo0 = (lane & 16) ? 0x4444u : lo; s.hi0 = (lane & 16) ? 0x4444u : hi; s.lo1 = (lane & 16) ? lo : 0x4444u; s.hi1 = (lane & 16) ? hi : 0x4444u;
  return s;
}
#define GEMV_B0(j, h, s) __byte_perm((j) < 2 ? (h).x : (h).y, 0u, ((j) & 1) ? (s).hi0 : (s).lo0)
#define GEMV_B1(j, h, s) __byte_perm((j) < 2 ? (h).x : (h).y, 0u, ((j) & 1) ? (s).hi1 : (s).lo1)
__device__ __forceinline__ float4 gemv_out(const float (&d)[4], int lane) {
  const bool tk = lane & 1;
  const float r0 = __shfl_xor_sync(0xffffffffu, tk ? d[0] : d[1], 1), r1 = __shfl_xor_sync(0xffffffffu, tk ? d[2] : d[3], 1);
  return tk ? make_float4(r0, d[1], r1, d[3]) : make_float4(d[0], r0, d[2], r1);
}
#define OG_XB 5
#define OG_NG 8
#define PUT_N 2
#define H_STAG 2
#define AL_P 60
#define AL_SLEEP 1200
#define AL_MAX 800
#define POLL_NS 500
#define OG_PROF 0xDDCBAA98u
#define RK_P 24
__host__ __device__ constexpr int og_pre(int tile) { return (OG_PROF >> ((tile >> 4) * 4)) & 15; }
constexpr int OG_PRE2 = og_pre(127), OG_HSUM = og_pre(0) + og_pre(16) + og_pre(32) + og_pre(48) + og_pre(64) + og_pre(80) + og_pre(96);
#define OG_JOBS 7
#define OG_GRP 6
#define LD_FIRST 2
#define LD_STAG (OG_GRP / 2)
constexpr int OG_ST = 5, OG_NKB = T_DQKV / 64 - og_pre(0), OG_MOE = T_F / 32;
__device__ __forceinline__ int pre_kb(int i) { return (i >> 1) * 4 + (i & 1); }
__device__ __forceinline__ int own_kb(int i, int pre) { return i < (pre & ~1) ? pre_kb(i) + 2 : i + pre; }
static_assert(LD_FIRST + LD_STAG <= OG_XB && OG_XB < LD_FIRST + OG_GRP, "the extra tile belongs to segment 1");
constexpr int OG_POS = 8;
constexpr uint32_t OG_STAGE = 32768;
constexpr uint32_t OG_SCOL = AT_SBAR + 512;
constexpr uint32_t OG_SMISC = AT_SBAR + 2048;
constexpr uint32_t OG_SWD = AT_SQ, OG_PSLOT = AT_SQ;
constexpr uint32_t OG_XSLOT = AT_SQ + 32768;
constexpr uint32_t OG_OSLOT = 1 * OG_STAGE;
constexpr uint32_t OG_SRED = 3 * OG_STAGE;
constexpr uint32_t OG_SH2 = OG_SRED + 24576;
constexpr uint32_t OG_SSTAT = OG_SRED + 16384;
constexpr uint32_t OG_SGU = OG_SRED + 8192;
constexpr uint32_t OG_SFIN = OG_SGU + 256;
#define OGM 2
#define OG_MT(b) ((((b) >> OGM) & 15) ^ (((b) & 64) ? 15 : 0))
#define OG_NT(b) (((b) & ((1 << OGM) - 1)) + (((b) >> (4 + OGM)) << OGM))
__device__ __forceinline__ int tail_tile(uint32_t sbase) { mbar_wait_long(sbase + AT_SBAR + 336, 0); return (int)lds_u32(sbase + AT_SBAR + 408); }
#define TAIL_SETUP \
  const uint32_t bar_full = sbase + AT_SBAR, bar_empty = bar_full + 40; \
  const uint32_t bar_wd = bar_full + 168, bar_col = bar_full + 176, bar_out = bar_full + 184, bar_end = bar_full + 192; \
  const uint32_t bar_key = bar_full + 200, bar_h2 = bar_full + 208, bar_sel = bar_full + 216; \
  const int mt = OG_MT(tb), nt = OG_NT(tb); \
  const int m0 = mt * 128, n0 = nt * 128; \
  const bool has_moe = (int)bid < OG_MOE; \
  (void)bar_empty; (void)bar_wd; (void)bar_col; (void)bar_out; (void)bar_end; (void)bar_key; (void)bar_h2; (void)bar_sel; (void)m0; (void)n0; (void)has_moe;

__device__ __forceinline__ void tail_producer(uint32_t bid, uint32_t sbase, uint32_t ph, uint64_t pol, const CUtensorMap* tmA, const CUtensorMap* tmB, const CUtensorMap* tmD) {
  const int tb = tail_tile(sbase);
  TAIL_SETUP
  uint32_t stage = OG_POS % OG_ST;
  int kb = 0;
  #pragma unroll 1
  for (int seg = 0; seg < 2; seg++) {
    mbar_wait(bar_full + 264 + 80 * seg, 0);
    fence_proxy_async_global();
    const int end = 32 + 32 * seg - og_pre(tb);
    #pragma unroll 1
    for (; kb < end; kb++) {
      const bool xb = kb == OG_XB;
      const uint32_t fb = xb ? bar_full + 360 : bar_full + 8 * stage, sa = sbase + (xb ? 5 : stage) * OG_STAGE;
      const int k0 = own_kb(kb, og_pre(tb)) * 64;
      if (xb) mbar_wait(bar_full + 80, bid < AT_NFULL);
      mbar_wait(xb ? bar_full + 304 : bar_empty + 8 * stage, xb ? 0 : ph);
      mbar_expect_tx(fb, OG_STAGE);
      tma_load_3d_hint(sa + 16384, tmB, k0, 2 * nt, fb, pol);
      tma_load_2d_hint(sa, tmA, k0, m0, fb, pol);
      if (!xb && ++stage == OG_ST) { stage = 0; ph ^= 1; }
    }
  }
  if (has_moe) {
    stage += stage & 1;
    mbar_wait(bar_empty + 8 * stage, ph);
    mbar_expect_tx(bar_wd, OG_STAGE);
    tma_load_3d_hint(sbase + stage * OG_STAGE, tmD, bid * 32, 8, bar_wd, pol);
  }
}

__device__ __forceinline__ uint32_t out2(uint32_t x1, uint32_t mb2, uint32_t ih, uint32_t il, uint32_t c1, uint32_t sb, uint32_t gb) {
  const uint32_t h2 = badd2(bmul2(ln_norm2b(x1, mb2, ih, il), c1), sb);
  return badd2(x1, bmul2(gb, bfma2(h2, 0u, h2)));
}
#define X_PACE 200
#define Y_SLACK 96
#define OG_STAG 3
#define X_PACE2 100
#define POLL_NS2 100
#define WD_SKIP 7
#define AL_ADD 380
#define WD_PACE 300
__device__ __forceinline__ void tail_exchange(uint32_t bid, uint32_t sbase, const bf16* __restrict__ w_down, const bf16* __restrict__ w_r, const bf16* __restrict__ x, bf16* __restrict__ out) {
    const int lane = threadIdx.x & 31, wi = __shfl_sync(0xffffffffu, threadIdx.x >> 5, 0);
    if (wi == 3) {
      uint32_t a = bid, b = 0u;
      if (bid < AT_NFULL) mbar_wait_long(sbase + AT_SBAR + 312, 0);
      if (bid < OG_MOE) {
        asm volatile("mov.u32 %0, %%globaltimer_lo;" : "=r"(a));
        if (lane == 0 && (bid & 15) == 0) asm volatile("st.relaxed.gpu.global.u32 [%0], %1;" :: "l"(g_hcnt + 8 + (bid >> 4)), "r"((a & ~15u) | 8u | (bid >> 4)) : "memory");
        #pragma unroll 1
        for (unsigned int spin = 0; spin < (1u << 22) && __any_sync(0xffffffffu, b == 0u); spin++) {
          __nanosleep(200);
          asm volatile("ld.relaxed.gpu.global.u32 %0, [%1];" : "=r"(b) : "l"(g_hcnt + 8 + min(lane, 6)) : "memory");
        }
        a = __popc(__ballot_sync(0xffffffffu, b < __shfl_sync(0xffffffffu, b, bid >> 4)) & 127u) * 16 + (bid & 15);
      }
      if (lane == 0) {
        sts_u32(sbase + AT_SBAR + 408, a);
        mbar_arrive(sbase + AT_SBAR + 336);
        b = 0u;
        if (bid < AT_NFULL) {
          unsigned int* tm = g_hcnt + 32 * (1 + (bid >> 4)) + 8;
          mbar_wait_long(sbase + AT_SBAR + 312, 1);
          asm volatile("mov.u32 %0, %%globaltimer_lo;" : "=r"(a));
          asm volatile("red.relaxed.gpu.global.max.u32 [%0], %1;" :: "l"(tm), "r"(a) : "memory");
          __nanosleep(AL_SLEEP);
          asm volatile("ld.relaxed.gpu.global.u32 %0, [%1];" : "=r"(b) : "l"(tm) : "memory");
          b -= a;
        }
        sts_u32(sbase + AT_SBAR + 412, b < AL_MAX ? b * 13 / 8 : 0u);
        mbar_arrive(sbase + AT_SBAR + 320);
      }
      named_bar_sync(15, 32);
    }
    const int tb = __shfl_sync(0xffffffffu, tail_tile(sbase), 0);
    TAIL_SETUP
    if (wi == 3) {
      mbar_wait_long(bar_full + 344, 0);
      float a = g_scal[lane], b = g_scal[32 + lane];
      #pragma unroll
      for (int i = 0; i < 3; i++) {
        const uint4 v = *reinterpret_cast<const uint4*>(g_col + nt * 1536 + i * 512 + lane * 16);
        sts_u32x4(sbase + OG_SCOL + i * 512 + lane * 16, v.x, v.y, v.z, v.w);
      }
      #pragma unroll
      for (int o = 16; o > 0; o >>= 1) { a += __shfl_xor_sync(0xffffffffu, a, o); b += __shfl_xor_sync(0xffffffffu, b, o); }
      if (lane == 0) sts_f32x2(sbase + OG_SMISC, a, b);
      const uint64_t pol = policy_evict_first();
      #pragma unroll 1
      for (int r = lane >> 4; r < 128; r += 4) {
        __nanosleep(X_PACE);
        if (X_PACE2) __nanosleep(X_PACE2);
        #pragma unroll
        for (int j = 0; j < 4; j += 2)
          asm volatile("cp.async.cg.shared.global.L2::cache_hint [%0], [%1], 16, %2;" :: "r"(sbase + OG_XSLOT + (lane & 8) * 2048 + (r + j) * 128 + (((lane ^ (r + j)) & 7) << 4)),
                       "l"(x + (size_t)(m0 + r + j) * T_D + n0 + (lane & 15) * 8), "l"(pol) : "memory");
      }
      asm volatile("cp.async.wait_all;" ::: "memory");
      __syncwarp();
      if (lane == 0) mbar_arrive(bar_col);
    } else if (wi == 2) {
      if (elect_one()) {
        mbar_wait_long(bar_full + (has_moe ? 80 : 368), has_moe);
        #pragma unroll 1
        for (unsigned int i = 0; i < (1u << 20) && ld_acquire(&g_hcnt[32 * (1 + (tb >> 3)) + 4 + ((tb >> 1) & 3)]) == 0u; i++) __nanosleep((tb >> 4) == 6 ? POLL_NS2 : POLL_NS);
        TL_MARK2(23, true);
        fence_proxy_async_global();
        TL_MARK2(4, true);
        mbar_expect_tx(bar_full + 272, 32768);
        bulk_load_hint(sbase + OG_PSLOT, g_pre + tb * 2048, 32768, bar_full + 272, policy_evict_first());
      }
      named_bar_sync(14, 32);
      if (has_moe) {
        mbar_wait_long(bar_full + 368, 0);
        const uint64_t pol = policy_evict_first();
        #pragma unroll 1
        for (int r = 0; r < 32; r++) {
          if ((r & WD_SKIP) != WD_SKIP) __nanosleep(WD_PACE);
          #pragma unroll
          for (int j = 0; j < 2; j++)
            asm volatile("cp.async.cg.shared.global.L2::cache_hint [%0], [%1], 16, %2;" :: "r"(sbase + OG_SWD + (4 * j + (lane >> 3)) * 4096 + r * 128 + (((lane ^ r) & 7) << 4)),
                         "l"((const uint8_t*)w_down + (size_t)bid * 65536 + r * 2048 + j * 512 + lane * 16), "l"(pol) : "memory");
        }
        asm volatile("cp.async.wait_all;" ::: "memory");
        __syncwarp();
        if (lane == 0) mbar_arrive(bar_wd);
      }
    }
    const uint4 wrv = ldg_nc_v4(w_r + threadIdx.x * 8);
    mbar_wait_long(bar_end, 0);
    TL_MARK2(22, lane == 0);
    if (wi == 0) {
      uint32_t k1 = 0u, k2 = 0u;
      #pragma unroll 1
      for (unsigned int spin = 0; spin < (1u << 22) && __any_sync(0xffffffffu, k1 == 0u); spin++) asm volatile("ld.relaxed.gpu.global.u32 %0, [%1];" : "=r"(k1) : "l"(g_key + lane) : "memory");
      TL_MARK2(28, lane == 0);
      warp_top2(k1, k2);
      if (lane == 0) {
        const uint32_t r1 = 0xffffu - (k1 & 0xffffu), r2 = 0xffffu - (k2 & 0xffffu);
        sts_u32x4(sbase + OG_SMISC + 64, r1, r2, (r1 >> 7) * 2, (r2 >> 7) * 2 + ((r1 >> 7) == (r2 >> 7)));
        mbar_arrive(bar_sel);
      }
    } else if (wi < 3) {
          mbar_wait(bar_key, 0);
          const uint4 kk = lds_u32x4(sbase + OG_SSTAT + 1024 + lane * 16);
          uint32_t k1 = max(kk.x, kk.y), k2 = min(kk.x, kk.y);
          k2 = max(max(k2, min(kk.z, kk.w)), min(k1, max(kk.z, kk.w))); k1 = max(k1, max(kk.z, kk.w));
          warp_top2(k1, k2);
          if (wi == 1) {
            if (lane == 0) {
              if (nt == (mt & 7)) st_relaxed2(g_key + mt * 2, k1, k2);
              sts_u32x2(sbase + OG_SMISC + 96, (~k1 >> 4) & 7u, (~k2 >> 4) & 7u);
              mbar_arrive(bar_full + 352);
            }
            TL_MARK2(27, lane == 0);
          } else {
            const uint32_t r = (~((lane & 16) ? k2 : k1)) & 127u, ch = lane & 15;
            const uint2 st = lds_u32x2(sbase + OG_SSTAT + r * 8);
            const uint4 xc = lds_u32x4(sbase + OG_XSLOT + (ch >> 3) * 16384 + r * 128 + (((ch ^ r) & 7) << 4));
            const uint4 c1 = lds_u32x4(sbase + OG_SCOL + 768 + ch * 16), sh = lds_u32x4(sbase + OG_SCOL + 1024 + ch * 16);
            const float inr = __uint_as_float(st.y);
            float* dst = reinterpret_cast<float*>(g_cand + (mt * 2 + (lane >> 4)) * 256 + nt * 16 + ch);
            st_tagged4(dst + 512, __uint_as_float(ln_mod2(xc.x, st.x, inr, c1.x, sh.x)), __uint_as_float(ln_mod2(xc.y, st.x, inr, c1.y, sh.y)),
                       __uint_as_float(ln_mod2(xc.z, st.x, inr, c1.z, sh.z)), __uint_as_float(ln_mod2(xc.w, st.x, inr, c1.w, sh.w)));
            st_tagged4(dst, __uint_as_float(xc.x), __uint_as_float(xc.y), __uint_as_float(xc.z), __uint_as_float(xc.w));
          }
    }
    mbar_wait(bar_sel, 0);
    const uint4 sel = lds_u32x4(sbase + OG_SMISC + 64);
    const int sel0 = (int)sel.x, sel1 = (int)sel.y;
    {
      const float* src0 = reinterpret_cast<const float*>(g_cand + sel.z * 256 + 128 + threadIdx.x);
      const float* src1 = reinterpret_cast<const float*>(g_cand + sel.w * 256 + 128 + threadIdx.x);
      float4 h0, h1;
      #pragma unroll 1
      for (unsigned int spin = 0; spin < (1u << 20); spin++) { h0 = ld_tagged4(src0); h1 = ld_tagged4(src1); if (__all_sync(0xffffffffu, tagged4(h0) & tagged4(h1))) break; }
      sts_f32x4(sbase + OG_SH2 + threadIdx.x * 16, h0.x, h0.y, h0.z, h0.w);
      sts_f32x4(sbase + OG_SH2 + 2048 + threadIdx.x * 16, h1.x, h1.y, h1.z, h1.w);
      __syncwarp();
      if (lane == 0) mbar_arrive(bar_h2);
      TL_MARK2(12, lane == 0);
      if (bid >> 6) h0 = h1;
      float v[8], wr[8];
      unpack8(make_uint4(__float_as_uint(h0.x), __float_as_uint(h0.y), __float_as_uint(h0.z), __float_as_uint(h0.w)), v); unpack8(wrv, wr);
      float r = 0.f;
      #pragma unroll
      for (int i = 0; i < 8; i++) r = fmaf(v[i], wr[i], r);
      #pragma unroll
      for (int o = 16; o > 0; o >>= 1) r += __shfl_xor_sync(0xffffffffu, r, o);
      if (lane == 0) sts_f32(sbase + OG_SMISC + 192 + wi * 4, r);
    }
    mbar_wait(bar_out, 0);
    {
      const uint2 cg = lds_u32x2(sbase + OG_SMISC + 96);
      #pragma unroll
      for (int i = 0; i < 4; i++) {
        const int r = (i < 2 ? cg.x : cg.y) * 16 + (i & 1) * 8 + (threadIdx.x >> 4), ch = threadIdx.x & 15;
        if (m0 + r != sel0 && m0 + r != sel1)
          *reinterpret_cast<uint4*>(out + (size_t)(m0 + r) * T_D + n0 + ch * 8) =
              lds_u32x4(sbase + OG_OSLOT + (ch >> 3) * 16384 + r * 128 + (((ch & 7) ^ (r & 7)) << 4));
      }
    }
    if (bid == 0 && threadIdx.x < 68) *reinterpret_cast<uint4*>(g_hcnt + 32 * (threadIdx.x >> 2) + 4 * (threadIdx.x & 3)) = make_uint4(0u, 0u, 0u, 0u);
    if (threadIdx.x < 64) g_modpart[bid * 64 + threadIdx.x] = 0.f;
    {
      const int tk = bid >> 6, c0 = (bid & 63) * 16;
      const uint32_t gb2 = *reinterpret_cast<const uint32_t*>(g_col + (c0 >> 7) * 1536 + 512 + 768 + ((c0 & 127) + (threadIdx.x & 14)) * 2);
      const uint32_t* xp = reinterpret_cast<const uint32_t*>(g_cand + (tk ? sel.w : sel.z) * 256) + ((c0 + (threadIdx.x & 14)) >> 1);
      uint32_t x2 = 0u;
      #pragma unroll 1
      for (unsigned int spin = 0; spin < (1u << 20) && __any_sync(0xffffffffu, x2 == 0u); spin++) asm volatile("ld.relaxed.gpu.global.u32 %0, [%1];" : "=r"(x2) : "l"(xp) : "memory");
      const float* src = g_ypart + (size_t)((threadIdx.x >> 2) * 2 + tk) * T_D + c0 + (threadIdx.x & 3) * 4;
      const bool four = threadIdx.x < (OG_MOE - 96) * 4;
      named_bar_sync(10, 128);
      const uint4 rp = lds_u32x4(sbase + OG_SMISC + 192);
      const float rs = rbf(sigmoid_f(rbf((__uint_as_float(rp.x) + __uint_as_float(rp.y)) + (__uint_as_float(rp.z) + __uint_as_float(rp.w)))));
      const uint32_t h2p = lds_u32(sbase + OG_SH2 + tk * 2048 + (c0 + (threadIdx.x & 14)) * 2);
      const float fh = (lane & 1) ? bfhi(h2p) : bflo(h2p), fz = rbf(fh * 0.0f), fx = (lane & 1) ? bfhi(x2) : bflo(x2), fg = (lane & 1) ? bfhi(gb2) : bflo(gb2);
      bf16* dst = out + (size_t)(tk ? sel1 : sel0) * T_D + c0 + threadIdx.x;
      if (threadIdx.x == 0) hint_wait(CNT_Y, (uint32_t)(OG_MOE - Y_SLACK));
      named_bar_sync(10, 128);
      float4 p0, p1, p2, p3;
      #pragma unroll 1
      for (unsigned int spin = 0; spin < (1u << 20); spin++) {
        p0 = ld_tagged4(src); p1 = ld_tagged4(src + 64 * T_D); p2 = ld_tagged4(src + 128 * T_D); p3 = ld_tagged4(four ? src + 192 * T_D : src);
        if (__all_sync(0xffffffffu, tagged4(p0) & tagged4(p1) & tagged4(p2) & tagged4(p3))) break;
      }
      if (four) { p2.x += p3.x; p2.y += p3.y; p2.z += p3.z; p2.w += p3.w; }
      p0.x = (p0.x + p1.x) + p2.x; p0.y = (p0.y + p1.y) + p2.y; p0.z = (p0.z + p1.z) + p2.z; p0.w = (p0.w + p1.w) + p2.w;
      #pragma unroll
      for (int o = 4; o <= 16; o <<= 1) {
        p0.x += __shfl_xor_sync(0xffffffffu, p0.x, o); p0.y += __shfl_xor_sync(0xffffffffu, p0.y, o);
        p0.z += __shfl_xor_sync(0xffffffffu, p0.z, o); p0.w += __shfl_xor_sync(0xffffffffu, p0.w, o);
      }
      if (lane < 4) sts_f32x4(sbase + OG_SFIN + (threadIdx.x >> 5) * 64 + lane * 16, p0.x, p0.y, p0.z, p0.w);
      named_bar_sync(10, 128);
      TL_MARK2(21, threadIdx.x == 0);
      if (threadIdx.x < 16) {
        const uint32_t ya = sbase + OG_SFIN + threadIdx.x * 4;
        float y = (lds_f32(ya) + lds_f32(ya + 64)) + (lds_f32(ya + 128) + lds_f32(ya + 192));
        y = rbf(y);
        y = rbf(y * rs);
        *dst = __float2bfloat16_rn(fx + rbf(fg * rbf(fh + rbf(fz + y))));
      }
    }
    if (threadIdx.x == 0) XT(11);
    TL_END(4, threadIdx.x == 0);
}

__device__ __forceinline__ void load_pre(uint4* pre, uint32_t sbase, uint32_t buf, int t2) {
  mbar_wait(sbase + AT_SBAR + 272, 0);
  #pragma unroll
  for (int i = 0; i < 8; i++) pre[i] = lds_u32x4(sbase + buf + i * 4096 + t2 * 16);
}
__device__ __forceinline__ void tail_consumer(uint32_t bid, uint32_t sbase, const CUtensorMap* tmOut, const uint4 (&pre)[8], int cwg, const bf16* __restrict__ w_gate, const bf16* __restrict__ w_up) {
    const uint32_t c0 = clock_lo();
    if ((threadIdx.x & 31) == 0) mbar_arrive(sbase + AT_SBAR + 304);
    mbar_wait(sbase + AT_SBAR + 320, 0);
    const uint2 td = lds_u32x2(sbase + AT_SBAR + 408);
    const int tb = __shfl_sync(0xffffffffu, (int)td.x, 0);
    TAIL_SETUP
    const int tid = threadIdx.x & 127, t2 = threadIdx.x - 128;
    const int warp = tid >> 5, lane = tid & 31, w8 = t2 >> 5;
    const uint32_t dbase = (sbase & 0x3FFFFu) >> 4;
    const uint32_t a_base = dbase + ((cwg * 8192) >> 4) + (1u << 16);
    const uint32_t b_base = dbase + (16384 >> 4) + (512u << 16);
    TL_MARK2(25, threadIdx.x == 128);
    const uint64_t pol = policy_evict_first();
    const bf16* pw = ((lane & 16) ? w_up : w_gate) + (size_t)(w8 * 128 + (lane & 3) * 4) * T_F + (has_moe ? bid : 0) * 32 + ((lane >> 2) & 3) * 8;
    uint4 wv[32];
    float acc[64];
    #pragma unroll
    for (int i = 0; i < 8; i++) {
      acc[8 * i] = bflo(pre[i].x); acc[8 * i + 1] = bfhi(pre[i].x); acc[8 * i + 2] = bflo(pre[i].y); acc[8 * i + 3] = bfhi(pre[i].y);
      acc[8 * i + 4] = bflo(pre[i].z); acc[8 * i + 5] = bfhi(pre[i].z); acc[8 * i + 6] = bflo(pre[i].w); acc[8 * i + 7] = bfhi(pre[i].w);
    }
    while (__any_sync(0xffffffffu, clock_lo() - c0 < td.y + AL_ADD)) {}
    uint32_t stage = OG_POS % OG_ST;
    {
      uint32_t phase = (OG_POS / OG_ST) & 1, prev = 12;
      int kb = 0;
      #pragma unroll
      for (int g = 0; g <= OG_NG; g++) {
        const int end = g == OG_NG ? 64 - og_pre(tb) : LD_FIRST + g * OG_GRP + LD_STAG * cwg;
        #pragma unroll 1
        do {
          const bool xb = g == 1 && kb == OG_XB;
          mbar_wait(xb ? bar_full + 360 : bar_full + 8 * stage, xb ? 0 : phase);
          if (OG_STAG > 0 && g == OG_NG && cwg == 1 && kb == end - OG_STAG) named_bar_sync(7, 256);
          const uint32_t a_lo = a_base + (xb ? 5 : stage) * (OG_STAGE >> 4), b_lo = b_base + (xb ? 5 : stage) * (OG_STAGE >> 4);
          wgmma_fence();
          wgmma_m64n128k16_ss_tb<0, 0>(acc, a_lo, b_lo, 1);
          wgmma_m64n128k16_ss_tb<2, 128>(acc, a_lo, b_lo, 1);
          wgmma_m64n128k16_ss_tb<4, 256>(acc, a_lo, b_lo, 1);
          wgmma_m64n128k16_ss_tb<6, 384>(acc, a_lo, b_lo, 1);
          wgmma_commit();
          if (OG_STAG > 0 && g == OG_NG && cwg == 0 && kb == end - 1) named_bar_arrive(7, 256);
          wgmma_wait<1>();
          if (tid == 0) mbar_arrive(bar_empty + 8 * prev);
          prev = xb ? 41 : stage;
          if (!xb && ++stage == OG_ST) { stage = 0; phase ^= 1; }
        } while (++kb < end);
        #pragma unroll
        for (int j = 4 * g; j < 4 * g + 4 && j < 32; j++) wv[j] = ldg_stream_v4(pw + (size_t)(16 * (j >> 2) + (j & 3)) * T_F, pol);
      }
    }
    mbar_wait(bar_col, 0);
    if (__builtin_expect(!has_moe, 0)) {
      load_pre(wv, sbase, AT_SQ, t2);
    }
    wgmma_wait<0>();
    fence_regs(acc);
    if (__builtin_expect(!has_moe, 0)) {
      #pragma unroll
      for (int i = 0; i < 8; i++) {
        acc[8 * i] += bflo(wv[i].x); acc[8 * i + 1] += bfhi(wv[i].x); acc[8 * i + 2] += bflo(wv[i].y); acc[8 * i + 3] += bfhi(wv[i].y);
        acc[8 * i + 4] += bflo(wv[i].z); acc[8 * i + 5] += bfhi(wv[i].z); acc[8 * i + 6] += bflo(wv[i].w); acc[8 * i + 7] += bfhi(wv[i].w);
      }
    }
    if (tid == 0) mbar_arrive(bar_end);
    TL_MARK2(9, lane == 0);
    const int q2 = 2 * (lane & 3);
    const uint32_t frag = (64 * cwg + 16 * warp + (lane & 7) + 8 * ((lane >> 3) & 1)) * 128;
    const int fsw = lane & 7, fhi = lane >> 4;
    {
      float dl[4] = {0.f, 0.f, 0.f, 0.f}, da[4] = {0.f, 0.f, 0.f, 0.f}, db[4] = {0.f, 0.f, 0.f, 0.f};
      const uint32_t tb2 = sbase + OG_SCOL + (lane & 8) * 32 + (lane & 3) * 8, g = lane >> 2;
      const uint32_t msk = (g == 1 || g == 2) ? 0xffffffffu : 0u, one = g == 0 ? 0x3F803F80u : 0u;
      uint32_t xr[8][4];
      #pragma unroll
      for (int hf = 0; hf < 2; hf++) {
        uint32_t ga[8];
        uint2 cw[4];
        #pragma unroll
        for (int i = 0; i < 4; i++) {
          ldmatrix_x4(sbase + OG_XSLOT + hf * 16384 + frag + (((2 * i + fhi) ^ fsw) << 4), xr[4 * hf + i][0], xr[4 * hf + i][1], xr[4 * hf + i][2], xr[4 * hf + i][3]);
          ga[2 * i] = lds_u32(sbase + OG_SCOL + 512 + (64 * hf + 16 * i + q2) * 2); ga[2 * i + 1] = lds_u32(sbase + OG_SCOL + 512 + (64 * hf + 16 * i + 8 + q2) * 2);
          cw[i] = lds_u32x2(tb2 + (8 * hf + 2 * i) * 16);
        }
        #pragma unroll
        for (int i = 0; i < 4; i++) {
          uint32_t* x4 = xr[4 * hf + i];
          #pragma unroll
          for (int e = 0; e < 4; e++) x4[e] = badd2(x4[e], bmul2(ga[2 * i + (e >> 1)], pack_bf16(acc[32 * hf + 8 * i + 2 * e], acc[32 * hf + 8 * i + 2 * e + 1])));
          mma_bf16(dl, x4[0], x4[1], x4[2], x4[3], (cw[i].x & msk) | one, (cw[i].y & msk) | one);
          mma_bf16(da, x4[0], x4[1], x4[2], x4[3], x4[0], x4[2]);
          mma_bf16(db, x4[0], x4[1], x4[2], x4[3], x4[1], x4[3]);
        }
      }
      {
        const int dsrc = (lane & ~3) + (g >> 1);
        const float qa = __shfl_sync(0xffffffffu, (g & 1) ? da[1] : da[0], dsrc), qb = __shfl_sync(0xffffffffu, (g & 1) ? db[3] : db[2], dsrc);
        const float e0 = __shfl_xor_sync(0xffffffffu, (lane & 1) ? dl[0] : dl[2], 1), e1 = __shfl_xor_sync(0xffffffffu, dl[3], 1);
        if ((lane & 3) < 2) {
          const bool hi = lane & 1;
          st_tagged4(reinterpret_cast<float*>(g_part1 + ((mt * 8 + w8) * 8 + nt) * 16 + g + (hi ? 8 : 0)),
                     hi ? e0 : dl[0], hi ? qb : qa, hi ? e1 + dl[2] : dl[1] + e0, 1.0f);
        }
      }
      #pragma unroll
      for (int i = 0; i < 8; i++) stmatrix_x4(sbase + OG_XSLOT + (i >> 2) * 16384 + frag + (((2 * (i & 3) + fhi) ^ fsw) << 4), xr[i][0], xr[i][1], xr[i][2], xr[i][3]);
    }
    TL_MARK2(10, lane == 0);
    uint4 wd[16];
    if (has_moe) mbar_wait(bar_wd, 0);
    #pragma unroll
    for (int i = 0; i < 16; i++) wd[i] = lds_u32x4(sbase + (cwg ? (stage + (stage & 1)) * OG_STAGE : OG_SWD) + warp * 8192 + (i >> 3) * 4096 + (i & 6) * 512 + (i & 1) * 128 + (lane & 3) * 256 + (((lane >> 2) ^ (2 * (lane & 3) + (i & 1))) << 4));
    {
      const float* src = reinterpret_cast<const float*>(g_part1 + ((mt * 8 + w8) * 8 + (lane & 1) * 4) * 16 + (lane >> 1));
      float4 v, v1, v2, v3;
      #pragma unroll 1
      for (unsigned int spin = 0; spin < (1u << 22); spin++) {
        v = ld_tagged4(src); v1 = ld_tagged4(src + 64); v2 = ld_tagged4(src + 128); v3 = ld_tagged4(src + 192);
        if (__all_sync(0xffffffffu, tagged4(v) & tagged4(v1) & tagged4(v2) & tagged4(v3))) break;
        __nanosleep(100);
      }
      __syncwarp();
      TL_MARK2(26, lane == 0);
      v.x = (v.x + v1.x) + (v2.x + v3.x); v.y = (v.y + v1.y) + (v2.y + v3.y); v.z = (v.z + v1.z) + (v2.z + v3.z);
      v.x += __shfl_xor_sync(0xffffffffu, v.x, 1); v.y += __shfl_xor_sync(0xffffffffu, v.y, 1); v.z += __shfl_xor_sync(0xffffffffu, v.z, 1);
      const float mean = v.x * (1.0f / T_D);
      const float var = fmaxf(fmaf(-mean, mean, v.y * (1.0f / T_D)), 0.f);
      const uint32_t mb2 = pack_bf16(mean, mean);
      const float inv = rcp_approx(rbf(sqrt_approx(rbf(rbf(var) + 1e-05f))));
      {
        const float2 sc = lds_f32x2(sbase + OG_SMISC);
        const uint32_t key = rank_key(rbf(fmaf(fmaf(-bflo(mb2), sc.x, v.z), inv, sc.y)), m0 + 16 * w8 + (lane >> 1));
        mbar_wait(bar_end, 0);
        if (lane & 1) sts_u32(sbase + OG_SSTAT + 1024 + (16 * w8 + (lane >> 1)) * 4, key);
        else sts_u32x2(sbase + OG_SSTAT + (16 * w8 + (lane >> 1)) * 8, mb2, __float_as_uint(inv));
        __syncwarp();
        if (lane == 0) mbar_arrive(bar_key);
      }
      const uint32_t ih = pack_bf16(inv, inv), il = pack_bf16(inv - bflo(ih), inv - bflo(ih));
      const uint32_t mba = __shfl_sync(0xffffffffu, mb2, 2 * (lane >> 2)), mbb = __shfl_sync(0xffffffffu, mb2, 2 * (lane >> 2) + 16);
      const uint32_t iha = __shfl_sync(0xffffffffu, ih, 2 * (lane >> 2)), ihb = __shfl_sync(0xffffffffu, ih, 2 * (lane >> 2) + 16);
      const uint32_t ila = __shfl_sync(0xffffffffu, il, 2 * (lane >> 2)), ilb = __shfl_sync(0xffffffffu, il, 2 * (lane >> 2) + 16);
      #pragma unroll 1
      for (int J0 = 0; J0 < 16; J0 += 4) {
        uint32_t xr[2][4], cv[4][3];
        #pragma unroll
        for (int i = 0; i < 2; i++) {
          ldmatrix_x4(sbase + OG_XSLOT + (J0 >> 3) * 16384 + frag + ((((J0 & 7) + 2 * i + fhi) ^ fsw) << 4), xr[i][0], xr[i][1], xr[i][2], xr[i][3]);
          #pragma unroll
          for (int h = 0; h < 2; h++)
            #pragma unroll
            for (int k = 0; k < 3; k++) cv[2 * i + h][k] = lds_u32(sbase + OG_SCOL + 768 + 256 * k + (8 * (J0 + 2 * i + h) + q2) * 2);
        }
        #pragma unroll
        for (int i = 0; i < 2; i++) {
          #pragma unroll
          for (int h = 0; h < 2; h++) {
            xr[i][2 * h] = out2(xr[i][2 * h], mba, iha, ila, cv[2 * i + h][0], cv[2 * i + h][1], cv[2 * i + h][2]);
            xr[i][2 * h + 1] = out2(xr[i][2 * h + 1], mbb, ihb, ilb, cv[2 * i + h][0], cv[2 * i + h][1], cv[2 * i + h][2]);
          }
          stmatrix_x4(sbase + OG_OSLOT + (J0 >> 3) * 16384 + frag + ((((J0 & 7) + 2 * i + fhi) ^ fsw) << 4), xr[i][0], xr[i][1], xr[i][2], xr[i][3]);
        }
      }
      fence_proxy_async();
      mbar_wait(bar_full + 352, 0);
      const uint2 cg = lds_u32x2(sbase + OG_SMISC + 96);
      __syncwarp();
      if (elect_one()) {
        mbar_arrive(bar_out);
        if (cg.x != w8 && cg.y != w8) {
          asm volatile("cp.async.bulk.tensor.2d.global.shared::cta.bulk_group [%0, {%2, %3}], [%1];" :: "l"(tmOut), "r"(sbase + OG_OSLOT + w8 * 2048), "r"(n0), "r"(m0 + 16 * w8) : "memory");
          asm volatile("cp.async.bulk.tensor.2d.global.shared::cta.bulk_group [%0, {%2, %3}], [%1];" :: "l"(tmOut), "r"(sbase + OG_OSLOT + 16384 + w8 * 2048), "r"(n0 + 64), "r"(m0 + 16 * w8) : "memory");
          bulk_commit();
        }
      }
      TL_MARK2(24, lane == 0);
    }
    if (has_moe) mbar_wait(bar_h2, 0);
    TL_MARK2(13, lane == 0);
    if (has_moe) {
      const GemvSel sel = gemv_sel(lane);
      {
        float d[4][4];
        #pragma unroll
        for (int c = 0; c < 4; c++) { d[c][0] = 0.f; d[c][1] = 0.f; d[c][2] = 0.f; d[c][3] = 0.f; }
        #pragma unroll
        for (int st = 0; st < 8; st++) {
          const uint2 hb = lds_u32x2(sbase + OG_SH2 + ((lane >> 2) & 1) * 2048 + (w8 * 128 + st * 16 + (lane & 3) * 4) * 2);
          #pragma unroll
          for (int j = 0; j < 4; j++) mma_bf16(d[j], wv[4 * st + j].x, wv[4 * st + j].y, wv[4 * st + j].z, wv[4 * st + j].w, GEMV_B0(j, hb, sel), GEMV_B1(j, hb, sel));
        }
        #pragma unroll
        for (int e = 0; e < 4; e++) d[0][e] = (d[0][e] + d[1][e]) + (d[2][e] + d[3][e]);
        const float4 r = gemv_out(d[0], lane);
        sts_f32x4(sbase + OG_SRED + w8 * 512 + (((lane >> 4) * 2 + (lane & 1)) * 32 + ((lane >> 2) & 3) * 8 + (lane & 2) * 2) * 4, r.x, r.y, r.z, r.w);
      }
      named_bar_sync(9, 256);
      if (t2 < 64) {
        float gp[8], up[8];
        #pragma unroll
        for (int w = 0; w < 8; w++) { gp[w] = lds_f32(sbase + OG_SRED + w * 512 + t2 * 4); up[w] = lds_f32(sbase + OG_SRED + w * 512 + 256 + t2 * 4); }
        const float gs = ((gp[0] + gp[1]) + (gp[2] + gp[3])) + ((gp[4] + gp[5]) + (gp[6] + gp[7]));
        const float us = ((up[0] + up[1]) + (up[2] + up[3])) + ((up[4] + up[5]) + (up[6] + up[7]));
        asm volatile("st.shared.u16 [%0], %1;" :: "r"(sbase + OG_SGU + ((t2 & ~15) + ((t2 >> 1) & 3) * 4 + ((t2 >> 3) & 1) * 2 + (t2 & 1)) * 2), "h"((uint16_t)pack_bf16(silu_bf(rbf(gs)) * rbf(us), 0.f)) : "memory");
      }
      named_bar_sync(9, 256);
      TL_MARK2(20, threadIdx.x == 128);
      float d[4][4];
      #pragma unroll
      for (int c = 0; c < 4; c++) { d[c][0] = 0.f; d[c][1] = 0.f; d[c][2] = 0.f; d[c][3] = 0.f; }
      #pragma unroll
      for (int st = 0; st < 2; st++) {
        const uint2 g = lds_u32x2(sbase + OG_SGU + ((lane >> 2) & 1) * 64 + st * 32 + (lane & 3) * 8);
        #pragma unroll
        for (int j = 0; j < 4; j++) {
          const uint32_t b0 = GEMV_B0(j, g, sel), b1 = GEMV_B1(j, g, sel);
          mma_bf16(d[j & 1], wd[4 * st + j].x, wd[4 * st + j].y, wd[4 * st + j].z, wd[4 * st + j].w, b0, b1);
          mma_bf16(d[2 + (j & 1)], wd[8 + 4 * st + j].x, wd[8 + 4 * st + j].y, wd[8 + 4 * st + j].z, wd[8 + 4 * st + j].w, b0, b1);
        }
      }
      #pragma unroll
      for (int e = 0; e < 4; e++) { d[0][e] += d[1][e]; d[2][e] += d[3][e]; }
      const float4 y0 = gemv_out(d[0], lane), y1 = gemv_out(d[2], lane);
      float* yp = g_ypart + (size_t)(bid * 2 + (lane & 1)) * T_D + w8 * 128 + (lane >> 2) * 8 + (lane & 2) * 2;
      st_tagged4(yp, y0.x, y0.y, y0.z, y0.w);
      st_tagged4(yp + 64, y1.x, y1.y, y1.z, y1.w);
      named_bar_sync(9, 256);
      if (t2 == 0) hint_arrive(CNT_Y);
    }
    bulk_wait_read<0>();
    TL_MARK2(14, threadIdx.x == 128);
    TL_CLK(4, 1, threadIdx.x == 128);
}

__device__ __forceinline__ int help_njobs(uint32_t bid) { return bid < 128 ? OG_JOBS : 16 - OG_JOBS; }
__device__ __forceinline__ int help_job(uint32_t bid, int i) { return (i < OG_JOBS ? 16 * i + (bid >> 7) * 2 : 112 + (i - OG_JOBS) * 2) + (bid & 3) * 4; }
__device__ __noinline__ void store_warp(uint32_t bid, uint32_t sbase, const CUtensorMap* tmO, int item0, int n_items) {
  if (elect_one()) {
    const uint32_t bars = sbase + AT_SBAR, b_q0 = bars + 80, b_ob = bars + 96, b_ordy = bars + 104, b_acq = bars + 264;
    const unsigned int* cnt = g_hcnt + 32 * (1 + OG_MT(124)) + 2;
    #pragma unroll 1
    for (int q = 0; q < 4 * n_items; q++) {
      const int item = item0 + (q >> 2) * 128, h = (q >> 1) & 1, w = q & 1;
      const bool last = (q >> 2) == n_items - 1;
      if (q == 4 * n_items - 4) { mbar_wait_long(bars + 288, 0); red_release_add(&g_hcnt[1], 1u); }
      mbar_wait_long(b_ordy + 8 * (q & 3), q >> 2);
      store_o(tmO, (h ? (last ? sbase + AT_SQ + 32768 : sbase + 2 * 32768) : sbase + AT_SQ) + w * 8192, (item >> 4) * 2 + h, (item & 15) * 128 + w * 64);
      if (w) {
        bulk_wait_read<0>();
        mbar_arrive(h ? b_ob : b_q0);
        bulk_wait<0>();
        fence_proxy_async_global();
        asm volatile("fence.acq_rel.gpu;" ::: "memory");
        hint_arrive(&g_hcnt[32 * (1 + (item & 15)) + 2 + (item >> 7)]);
        if (!h && item < 128) hint_arrive(&g_hcnt[2]);
        if (q == 5) { const int tb = tail_tile(sbase); cnt = g_hcnt + 32 * (1 + OG_MT(tb)) + 2; spin_until(cnt, 16u); mbar_arrive(b_acq); }
      }
    }
    if (n_items == 1) {
      #pragma unroll 1
      for (int i = 0; i < help_njobs(bid); i++) {
        mbar_wait_long(b_acq + 16, i & 1);
        TL_MARK2(23, i == OG_JOBS - 1);
        red_release_add(&g_hcnt[32 * (1 + (help_job(bid, i) >> 3)) + 4 + ((help_job(bid, i) >> 1) & 3)], 1u);
        TL_MARK2(4, i == OG_JOBS - 1);
        if (i == PRE_X - 1) { spin_until(&g_hcnt[1], 132u); mbar_arrive(b_acq + 32); }
      }
    }
    if (bid < 128) {
      if (n_items == 1) { spin_until(cnt, 16u); mbar_arrive(b_acq); }
      spin_until(&g_hcnt[0], 128u); spin_until(cnt + 1, 16u); mbar_arrive(b_acq + 80);
    }
  }
}

__device__ __forceinline__ uint32_t role_of_sm(uint32_t sm) {
  const uint32_t t = sm >> 1, u = t - 32u, d = (u * 37u) >> 8;
  return (t < 32u ? ((t + 7u) & 7u) * 16u + (t >> 3) * 2u : t < 60u ? (u - 7u * d) * 16u + (4u + d) * 2u : t < 62u ? 2u * t + 8u : 2u * t - 4u) + (sm & 1u);
}
__global__ void __launch_bounds__(384, 1)
fused_kernel(const __grid_constant__ CUtensorMap tmH, const __grid_constant__ CUtensorMap tmW, const __grid_constant__ CUtensorMap tmK,
            const __grid_constant__ CUtensorMap tmV, const __grid_constant__ CUtensorMap tmO, const __grid_constant__ CUtensorMap tmOl, const __grid_constant__ CUtensorMap tmWo,
            const __grid_constant__ CUtensorMap tmD, const __grid_constant__ CUtensorMap tmOut, const __grid_constant__ CUtensorMap tmM, uint32_t zero,
            const uint8_t* __restrict__ pf_wo, const bf16* __restrict__ kc, const bf16* __restrict__ vc,
            const bf16* __restrict__ x, const bf16* __restrict__ cvec, const bf16* __restrict__ w_mod, const bf16* __restrict__ w_r,
            const bf16* __restrict__ w_gate, const bf16* __restrict__ w_up, const bf16* __restrict__ w_down, bf16* __restrict__ out)
{
  uint32_t bid, nsm;
  asm volatile("mov.u32 %0, %%smid;" : "=r"(bid));
  asm volatile("mov.u32 %0, %%nsmid;" : "=r"(nsm));
  bid = __shfl_sync(0xffffffffu, nsm == 132u ? role_of_sm(bid) : blockIdx.x, 0);
  extern __shared__ __align__(1024) uint8_t smem_raw[];
  const uint32_t sbase = smem_u32(smem_raw);
  const uint32_t bars = sbase + AT_SBAR;
  const uint32_t b_full = bars, b_empty = bars + 40;
  const uint32_t b_q0 = bars + 80, b_q1 = bars + 88;
  const uint32_t b_ob = bars + 96;
  const uint32_t b_ordy = bars + 104;
  const uint32_t b_pin = bars + 136;
  const uint32_t b_head = bars + 144;
  const uint32_t b_go = bars + 152;
  const uint32_t b_x = bars + 160;
  const int wg = __shfl_sync(0xffffffffu, threadIdx.x >> 7, 0);
  const bool single = bid >= AT_NFULL;
  const int item0 = __shfl_sync(0xffffffffu, bid < 128 ? (int)bid : (int)bid + 124, 0), n_items = __shfl_sync(0xffffffffu, single ? 1 : 2, 0);
  TL_START(3);
  if (threadIdx.x == 0) {
    if (sbase & 1023u) __trap();
    for (int i = 0; i < 5; i++) { mbar_init(b_full + 8 * i, 1); mbar_init(b_empty + 8 * i, 2); }
    mbar_init(b_q0, 1); mbar_init(b_q1, 8); mbar_init(b_ob, 1);
    for (int i = 0; i < 4; i++) mbar_init(b_ordy + 8 * i, 4);
    mbar_init(b_pin, 1); mbar_init(b_head, bid < 128 ? 8 : 1); mbar_init(b_go, 1); mbar_init(b_x, 1);
    mbar_init(bars + 168, 2); mbar_init(bars + 176, 1); mbar_init(bars + 184, 8); mbar_init(bars + 192, 2);
    mbar_init(bars + 200, 8); mbar_init(bars + 208, 4); mbar_init(bars + 216, 1); mbar_init(bars + 264, 1); mbar_init(bars + 272, 1); mbar_init(bars + 280, 8); mbar_init(bars + 288, 1); mbar_init(bars + 296, 1); mbar_init(bars + 304, 8); mbar_init(bars + 312, 1); mbar_init(bars + 320, 1); mbar_init(bars + 328, 1); mbar_init(bars + 336, 1); mbar_init(bars + 344, 1); mbar_init(bars + 352, 1); mbar_init(bars + 360, 1); mbar_init(bars + 368, 2);
    sts_u32(bars + 400, bid);
    fence_mbar_init();
  }

  if (wg == 0) {
    reg_dealloc<AT_PREG>();
    if (threadIdx.x < 32) { __syncwarp(); named_bar_arrive(6, 384); }
    if (threadIdx.x >= 64) {
      named_bar_sync(6, 384);
      if (bid < 128) {
        named_bar_sync(threadIdx.x >= 96 ? 8 : 9, 288);
        if ((threadIdx.x & 31) == 0) red_release_add(&g_hcnt[32 * (1 + (bid >> 3)) + (threadIdx.x >= 96)], 1u);
        TL_MARK2(11, threadIdx.x == 64);
      }
      if (bid < 128) {
        mbar_wait(MOD_AT, 0);
        mod_rest(bid, sbase + OG_SCOL, b_q1, threadIdx.x - 64, cvec, w_mod, w_r);
      }
    } else if (threadIdx.x >= 32) {
      named_bar_sync(6, 384);
      store_warp(bid, sbase, &tmO, item0, n_items);
      __syncwarp();
    } else {
     if (elect_one()) {
      const uint64_t pol = policy_evict_first();
      if (bid < 128) {
        mbar_expect_tx(b_x, 32768);
        if (X_DLY) { const uint32_t c0 = clock_lo(); while (clock_lo() - c0 < X_DLY) {} }
        bulk_load_hint(sbase + 4 * 32768, x + (size_t)bid * 16 * T_D, 32768, b_x, pol);
      }
      prefetch_tmap(&tmW); prefetch_tmap(&tmM); prefetch_tmap(&tmH); prefetch_tmap(&tmWo); prefetch_tmap(&tmOl);
      {
        const uint32_t c0 = clock_lo();
        while (clock_lo() - c0 < W_DLY) {}
        if (bid < 128 && (head_cb(bid) & 15) >= 4 * H_SPLIT) {
          mbar_expect_tx(bars + 328, 32768);
          tma_load_2d_hint(sbase + 3 * 32768, &tmM, head_cb(bid) * 64, (bid >> 5) * 256, bars + 328, pol);
        }
        while (clock_lo() - c0 < W_DLY + W_FIRST) {}
      }
      uint32_t slot = 0, ph = 1;
      #pragma unroll 1
      for (int it = 0; it < n_items; it++) {
        const int item = item0 + it * 128, hp = item >> 4, qt = item & 15;
        const bool first = it == 0;
        #pragma unroll 1
        for (int j = 0; j < T_D / 64; j++) {
          const uint32_t sl = ring_slot(qp_pos(j, it)), fb = b_full + 8 * sl;
          mbar_wait_long(b_empty + 8 * sl, ring_par(qp_pos(j, it)) ^ ((j >> 2) & 1) ^ 1);
          if (first && j == 3) mbar_wait(b_head, 0);
          mbar_expect_tx(fb, 49152);
          tma_load_3d_hint(sbase + sl * 32768, &tmW, j * 64, hp * 4, fb, pol);
          if (first && j < PRE_B) {
            if (j == PRE_B - 1) {
              spin_until(&g_hcnt[32 * (1 + qt)], 8u);
              TL_MARK2(16, true);
              fence_proxy_async_global();
              #pragma unroll 1
              for (int i = 0; i < PRE_B; i++) tma_load_2d(sbase + AT_SQ + i * 16384, &tmH, i * 64, qt * 128, b_full + 8 * i);
              mbar_arrive(b_go);
            }
          } else {
            if (first && j == 4 * H_SPLIT) { spin_until(&g_hcnt[32 * (1 + qt) + 1], 8u); fence_proxy_async_global(); }
            if (!first && (j == 0 || j == 2)) mbar_wait(j ? b_q1 : b_q0, 0);
            tma_load_2d(sbase + AT_SQ + (j & 3) * 16384, &tmH, j * 64, qt * 128, fb);
          }
        }
        #pragma unroll 1
        for (int j = 0; j < 4 * AT_NBLK; j++) {
          const bool isv = (j > 0 && !(j & 1)) || j == 4 * AT_NBLK - 1;
          const int row = hp * 2 * T_SEQ + (isv ? (j - 1) >> 1 : (j + 1) >> 1) * 128;
          const uint32_t fb = b_full + 8 * slot;
          mbar_wait_long(b_empty + 8 * slot, ph);
          if (!first && j == 3) mbar_wait(b_ob, 0);
          if (j == 4 && it == n_items - 1) mbar_arrive(bars + 288);
          if ((j == AL_P || j == RK_P) && it == 1) mbar_arrive(bars + 312);
          mbar_expect_tx(fb, 32768);
          tma_load_3d_hint(sbase + slot * 32768, isv ? &tmV : &tmK, row, 0, fb, pol);
          if (it == 1 && isv && j >= 2 * WO_LATE && j < 2 * WO_LATE + 32 && bid < OG_NKB)
            l2_prefetch_bulk(pf_wo + (size_t)own_kb(bid, og_pre(0)) * 131072 + ((j >> 1) - WO_LATE) * 8192, 8192);
          if (++slot == 5) { slot = 0; ph ^= 1; }
        }
      }
      if (__builtin_expect(single, 0)) {
        spin_until(&g_hcnt[2], 128u);
        fence_proxy_async_global();
        const int nj = OG_HSUM + (help_njobs(bid) - OG_JOBS) * OG_PRE2;
        int ji = 0, job = help_job(bid, 0), kk = 0;
        #pragma unroll 1
        for (int j = 0; j < nj; j++) {
          const uint32_t sl = ring_slot(qp_pos(j, 1)), fb = b_full + 8 * sl;
          mbar_wait_long(b_empty + 8 * sl, ring_par(qp_pos(j, 1)) ^ ((j >> 2) & 1) ^ 1);
          mbar_expect_tx(fb, 49152);
          tma_load_3d(sbase + sl * 32768, &tmWo, pre_kb(kk) * 64, OG_NT(job) * 2, fb);
          tma_load_3d(sbase + sl * 32768 + 16384, &tmWo, pre_kb(kk) * 64, OG_NT(job) * 2 + 2, fb);
          if (j == 0 || j == 2) mbar_wait(j ? b_ob : b_q0, 0);
          tma_load_2d_hint(sbase + AT_SQ + (j & 3) * 16384, &tmOl, pre_kb(kk) * 64, OG_MT(job) * 128, fb, pol);
          if (++kk == og_pre(job)) { kk = 0; job = help_job(bid, ++ji); }
        }
      }
      if (bid < 128) {
        if (single) mbar_wait(b_x, 1);
        tail_producer(bid, sbase, 0, pol, &tmOl, &tmWo, &tmD);
      }
     }
    }
    named_bar_sync(12 + (threadIdx.x >> 5), 32);
    if (bid < 128) tail_exchange(bid, sbase, w_down, w_r, x, out);
  } else {
    if (bid < 128) head_phase(bid, sbase + AT_SQ + 49152, sbase + 4 * 32768, b_x, b_go, b_head, threadIdx.x - 128, zero, cvec, w_mod);
    else { named_bar_sync(6, 384); if (threadIdx.x == 128) mbar_arrive(b_head); }
    TL_MARK2(0, threadIdx.x == 128);
    reg_alloc<AT_CREG>();
    const int cwg = wg - 1;
    const int tid = threadIdx.x & 127;
    const int warp = tid >> 5, lane = tid & 31;
    const uint32_t dbase = (sbase & 0x3FFFFu) >> 4;
    const uint32_t k_base = dbase + (1u << 16);
    const uint32_t v_base = dbase + (1024u << 16);
    const uint32_t w_base = dbase + (512u << 16);
    const uint32_t q_lo = dbase + ((AT_SQ + cwg * 8192) >> 4) + (1u << 16);
    const uint32_t frag = cwg * 8192 + (16 * warp + (lane & 7) + 8 * ((lane >> 3) & 1)) * 128;
    if (cwg == 1) named_bar_arrive(1, 256);
    bool raw = false;
    uint4 pre[8];
    #pragma unroll 1
    for (int it = 0; it < n_items; it++) {
      const bool more = it + 1 < n_items;
      constexpr int nkb = T_D / 64;
      const int ta = __shfl_sync(0xffffffffu, 4 * it, 0);
      float acc[128];
      {
        FS(2 * it, 0);
        #pragma unroll
        for (int i = 0; i < 128; i++) asm volatile("" : "=f"(acc[i]));
        {
          const uint32_t slot = ring_slot(ta), b_lo = w_base + slot * 2048;
          mbar_wait(b_full + 8 * slot, ring_par(ta));
          wgmma_fence();
          wgmma_m64n256k16_ss_tb<0, 0>(acc, q_lo, b_lo, 0);
          wgmma_m64n256k16_ss_tb<2, 128>(acc, q_lo, b_lo, 1);
          wgmma_m64n256k16_ss_tb<4, 256>(acc, q_lo, b_lo, 1);
          wgmma_m64n256k16_ss_tb<6, 384>(acc, q_lo, b_lo, 1);
          wgmma_commit();
        }
        #pragma unroll 1
        for (int j = 1; j < nkb; j++) {
          const uint32_t slot = ring_slot(qp_pos(j, ta >> 2));
          mbar_wait(b_full + 8 * slot, ring_par(qp_pos(j, ta >> 2)) ^ ((j >> 2) & 1));
          if (QP_STAG > 0 && cwg == 1 && j == nkb - QP_STAG) named_bar_sync(7, 256);
          const uint32_t a_lo = q_lo + (j & 3) * 1024, b_lo = w_base + slot * 2048;
          wgmma_fence();
          wgmma_m64n256k16_ss_tb<0, 0>(acc, a_lo, b_lo, 1);
          wgmma_m64n256k16_ss_tb<2, 128>(acc, a_lo, b_lo, 1);
          wgmma_m64n256k16_ss_tb<4, 256>(acc, a_lo, b_lo, 1);
          wgmma_m64n256k16_ss_tb<6, 384>(acc, a_lo, b_lo, 1);
          wgmma_commit();
          if (QP_STAG > 0 && cwg == 0 && j == nkb - 1) named_bar_arrive(7, 256);
          if (j > 0) {
            wgmma_wait<1>();
            if (tid == 0) mbar_arrive(b_empty + 8 * ring_slot(qp_pos(j - 1, ta >> 2)));
          }
        }
        wgmma_wait<0>();
        fence_regs(acc);
        FS(2 * it, 1);
        TL_MARK2(29, threadIdx.x == 256 && it == 0);
        if (tid == 0) mbar_arrive(b_empty + 24);
      }
      float o[64], s[64];
      uint32_t p[32], q[32];
      #pragma unroll
      for (int i = 0; i < 32; i++) q[i] = pack_bf16(acc[2 * i] * AT_C, acc[2 * i + 1] * AT_C);
      zero_regs(s);
      const uint32_t sq = sbase + AT_SQ + cwg * 8192;
      float mc0, mc1, al0 = 1.0f, al1 = 1.0f, l0 = 0.f, l1 = 0.f, lp0 = 0.f, lp1 = 0.f;
      bool redo0 = false;
      FS(2 * it, 2);
      mbar_wait(b_full + 8 * ring_slot(ta), ring_par(ta));
      named_bar_sync(1 + cwg, 256);
      FS(2 * it, 3);
      issue_qk(s, q, k_base + ring_slot(ta) * 2048);
      pass_turn(cwg);
      bool ready = mbar_test(b_full + 8 * ring_slot(ta + 1), ring_par(ta + 1)) & mbar_test(b_full + 8 * ring_slot(ta + 2), ring_par(ta + 2));
      stage_q<16>(acc, AT_C, sbase + AT_SQ + frag, lane);
      wgmma_wait<0>();
      fence_regs(s);
      if (tid == 0) mbar_arrive(b_empty + 8 * ring_slot(ta));
      mc0 = 0.f; mc1 = 0.f;
      if (!raw) {
        raw = softmax_mode(s, mc0, mc1);
        if (__builtin_expect(!raw, 0)) softmax_sub(s, mc0, mc1);
      }
      softmax_exp<0, 64>(s);
      #pragma unroll
      for (int J = 0; J < 16; J += 2)
        stmatrix_x4(sbase + AT_SQ + frag + (J >> 3) * 16384 + ((((J & 7) + (lane >> 4)) ^ (lane & 7)) << 4), q[2 * J], q[2 * J + 1], q[2 * J + 2], q[2 * J + 3]);
      pack_p(p, s);
      zero_regs(o);
      FS(2 * it, 4);
      uint32_t ks = ring_slot(ta + 1), vs = ring_slot(ta + 2), kp = ring_par(ta + 1), vp = ring_par(ta + 2);
      auto finish_head = [&]() {
        FS(2 * it, 5);
        redo0 = finish_l(lp0, lp1);
        if (!redo0) stage_o(o, lp0, lp1, sbase + AT_SQ + frag, lane);
        FS(2 * it + 1, 4);
      };
      if (!ready) { mbar_wait(b_full + 8 * ks, kp); mbar_wait(b_full + 8 * vs, vp); }
      #pragma unroll 1
      for (int n = 1; n < 2 * AT_NBLK; n++) {
        named_bar_sync(1 + cwg, 256);
        issue_qk(s, q, k_base + ks * 2048);
        if (n == AT_NBLK + 1) finish_head();
        issue_pv(o, p, v_base + vs * 2048, (n & 15) != 1);
        pass_turn(cwg);
        wgmma_wait<1>();
        fence_regs(s);
        if (tid == 0) mbar_arrive(b_empty + 8 * ks);
        if (__builtin_expect(!raw || (uint32_t)(n - (AT_NBLK - 1)) <= 2u, 0)) {
          if (n == AT_NBLK + 1 && !redo0) {
            fence_proxy_async();
            __syncwarp();
            if (lane == 0) mbar_arrive(b_ordy + 8 * cwg);
          }
          if (n == AT_NBLK - 1) {
            #pragma unroll
            for (int J = 0; J < 16; J += 2)
              ldmatrix_x4(sbase + AT_SQ + 32768 + frag + (J >> 3) * 16384 + ((((J & 7) + (lane >> 4)) ^ (lane & 7)) << 4), q[2 * J], q[2 * J + 1], q[2 * J + 2], q[2 * J + 3]);
          }
          if (!raw) {
            const float m0 = mc0, m1 = mc1;
            const bool ok = softmax_mode(s, mc0, mc1);
            if (n == AT_NBLK) raw = ok;
            else {
              mc0 = mc0 - AT_HEAD > m0 ? mc0 : m0; mc1 = mc1 - AT_HEAD > m1 ? mc1 : m1;
              al0 = ex2_approx(m0 - mc0); al1 = ex2_approx(m1 - mc1);
            }
            if (!raw) softmax_sub(s, mc0, mc1);
          }
        }
        softmax_exp<0, AT_SPLIT>(s);
        add_rowsum(p, l0, l1);
        if (tid == 0) {
          uint32_t dep = zero & __float_as_uint(l0) & __float_as_uint(l1);
          #pragma unroll
          for (int i = AT_SPLIT - AT_PIN - PINB; i < AT_SPLIT - PINB; i += 2) dep &= __float_as_uint(s[i]) & __float_as_uint(s[i + 1]);
          mbar_arrive(b_pin + dep);
        }
        wgmma_wait<0>();
        fence_regs(o);
        if (tid == 0) mbar_arrive(b_empty + 8 * vs);
        ks += 2; if (ks >= 5) { ks -= 5; kp ^= 1; }
        vs += 2; if (vs >= 5) { vs -= 5; vp ^= 1; }
        ready = mbar_test(b_full + 8 * ks, kp) & mbar_test(b_full + 8 * vs, vp);
        softmax_exp<AT_SPLIT, 64>(s);
        pack_p(p, s);
        if (n == AT_NBLK) { lp0 = l0; lp1 = l1; l0 = 0.f; l1 = 0.f; }
        if (__builtin_expect(!raw || !ready, 0)) {
        if (!raw && __any_sync(0xffffffffu, al0 != 1.0f || al1 != 1.0f)) {
          rescale_o(o, al0, al1);
          l0 *= al0; l1 *= al1;
          al0 = 1.0f; al1 = 1.0f;
        }
        if (!ready && n < 2 * AT_NBLK - 1) {
          mbar_wait(b_full + 8 * ks, kp);
          mbar_wait(b_full + 8 * vs, vp);
        }
        }
      }
      FS(2 * it + 1, 5);
      const uint32_t vl = ring_slot(ta + 63);
      vs = ring_slot(ta + 62);
      const uint32_t ob = more ? sbase + vs * 32768 : sbase + AT_SQ + 32768;
      mbar_wait(b_full + 8 * vl, ring_par(ta + 63));
      issue_pv(o, p, v_base + vl * 2048, 1);
      block_end(zero, b_pin);
      add_rowsum(p, l0, l1);
      const bool overflow = finish_l(l0, l1);
      if (!overflow && lane == 0) mbar_arrive(b_q1);
      #pragma unroll
      for (int i = 0; i < 8; i++) asm volatile("mov.b64 {%0, %1}, 0;\nmov.b64 {%2, %3}, 0;" : "=r"(pre[i].x), "=r"(pre[i].y), "=r"(pre[i].z), "=r"(pre[i].w));
      const bool want_pre = !more && bid < OG_MOE, got_pre = want_pre && __all_sync(0xffffffffu, mbar_test(bars + 272, 0));
      if (got_pre) load_pre(pre, sbase, AT_SQ, threadIdx.x - 128);
      mbar_wait(b_empty + 8 * vs, ring_par(ta + 62));
      wgmma_wait<0>();
      fence_regs(o);
      if (tid == 0) mbar_arrive(b_empty + 8 * vl);
      FS(2 * it + 1, 6);
      if (overflow) {
        attn_rows_exact(lds_u32(bars + 400), sq + 32768, ob + cwg * 8192, 4 * ta + 1, kc, vc);
        __syncwarp();
        if (lane == 0) mbar_arrive(b_q1);
      } else stage_o(o, l0, l1, ob + frag, lane);
      if (redo0) attn_rows_exact(lds_u32(bars + 400), sq, sq, 4 * ta, kc, vc);
      fence_proxy_async();
      __syncwarp();
      if (lane == 0) {
        if (redo0) mbar_arrive(b_ordy + 8 * cwg);
        mbar_arrive(b_ordy + 16 + 8 * cwg);
      }
      if (want_pre && !got_pre) load_pre(pre, sbase, AT_SQ, threadIdx.x - 128);
      if (redo0 || overflow) raw = false;
      named_bar_sync(3 + cwg, 128);
      FS(2 * it + 1, 7);
    }
    if (cwg == 0) named_bar_arrive(1, 256);
    if (__builtin_expect(single, 0)) {
      float acc[128];
      uint32_t j = 0, pk[64];
      #pragma unroll
      for (int i = 0; i < 64; i++) asm volatile("" : "=f"(acc[2 * i]), "=f"(acc[2 * i + 1]), "=r"(pk[i]));
      uint4* dst = g_pre;
      int left = 0;
      auto put = [&](bool last) {
        #pragma unroll
        for (int i = 0; i < PUT_N; i++) dst[i * 256] = make_uint4(pk[4 * i], pk[4 * i + 1], pk[4 * i + 2], pk[4 * i + 3]);
        dst += PUT_N * 256;
        #pragma unroll
        for (int i = 0; i < 64 - 4 * PUT_N; i++) asm volatile("mov.b32 %0, %1;" : "=r"(pk[i]) : "r"(pk[i + 4 * PUT_N]));
        __syncwarp();
        if (last && lane == 0) mbar_arrive(bars + 280);
      };
      #pragma unroll 1
      for (int ji = 0; ji < help_njobs(bid); ji++) {
        const int nk = og_pre(help_job(bid, ji));
        #pragma unroll 1
        for (int kk = 0; kk < nk; kk++, j++) {
          const uint32_t slot = ring_slot(qp_pos(j, 1));
          mbar_wait(b_full + 8 * slot, ring_par(qp_pos(j, 1)) ^ ((j >> 2) & 1));
          if (H_STAG > 0 && cwg == 1 && kk == nk - H_STAG) named_bar_sync(7, 256);
          const uint32_t a_lo = q_lo + (j & 3) * 1024, b_lo = w_base + slot * 2048;
          wgmma_fence();
          wgmma_m64n256k16_ss_tb<0, 0>(acc, a_lo, b_lo, kk != 0);
          wgmma_m64n256k16_ss_tb<2, 128>(acc, a_lo, b_lo, 1);
          wgmma_m64n256k16_ss_tb<4, 256>(acc, a_lo, b_lo, 1);
          wgmma_m64n256k16_ss_tb<6, 384>(acc, a_lo, b_lo, 1);
          wgmma_commit();
          if (H_STAG > 0 && cwg == 0 && kk == nk - 1) named_bar_arrive(7, 256);
          wgmma_wait<1>();
          if (kk > 0 && tid == 0) mbar_arrive(b_empty + 8 * ring_slot(qp_pos(j - 1, 1)));
          #pragma unroll 1
          for (int i = ji == OG_JOBS ? 0 : 16 / PUT_N - 1; i < 16 / PUT_N && left > 0; i++) put(--left == 0);
        }
        wgmma_wait<0>();
        fence_regs(acc);
        if (tid == 0) mbar_arrive(b_empty + 8 * ring_slot(qp_pos(j - 1, 1)));
        #pragma unroll
        for (int i = 0; i < 64; i++) pk[i] = pack_bf16(acc[2 * i], acc[2 * i + 1]);
        left = 16 / PUT_N;
        if (ji == PRE_X) mbar_wait(bars + 296, 0);
        dst = g_pre + help_job(bid, ji) * 2048 + threadIdx.x - 128;
      }
      #pragma unroll
      for (int i = 0; i < 16; i++) dst[i * 256] = make_uint4(pk[4 * i], pk[4 * i + 1], pk[4 * i + 2], pk[4 * i + 3]);
      __syncwarp();
      if (lane == 0) mbar_arrive(bars + 280);
      named_bar_sync(5, 256);
      if (threadIdx.x == 128) {
        #pragma unroll 1
        for (int i = 0; i < 5; i++) {
          constexpr int n = OG_HSUM;
          const int used = i == 3 ? 0 : (n + 3 - (i == 4 ? 3 : i)) / 4;
          if ((used ^ (i < 4)) & 1) {
            mbar_arrive(b_full + 8 * ring_slot(4 + i));
            mbar_arrive(b_empty + 8 * ring_slot(4 + i)); mbar_arrive(b_empty + 8 * ring_slot(4 + i));
          }
        }
        mbar_arrive(b_x);
      }
      named_bar_sync(5, 256);
      #pragma unroll
      for (int i = 0; i < 8; i++) pre[i] = make_uint4(0u, 0u, 0u, 0u);
    }
    TL_CLK(3, 1, threadIdx.x == 128);
    TL_CTA(1, threadIdx.x == 256);
    TL_END(3, tid == 0);
    TL_MARK2(19, tid == 0 && !single);
    if (bid < 128) {
      tail_consumer(bid, sbase, &tmOut, pre, cwg, w_gate, w_up);
    }
  }
}

typedef CUresult (*PFN_encodeTiled)(CUtensorMap*, CUtensorMapDataType, cuuint32_t, void*, const cuuint64_t*, const cuuint64_t*,
                                    const cuuint32_t*, const cuuint32_t*, CUtensorMapInterleave, CUtensorMapSwizzle,
                                    CUtensorMapL2promotion, CUtensorMapFloatOOBfill);

CUtensorMap make_map_2d(PFN_encodeTiled enc, const void* ptr, uint64_t inner, uint64_t outer, uint64_t stride_bytes, uint32_t box_inner, uint32_t box_outer) {
  CUtensorMap m;
  cuuint64_t gd[2] = {inner, outer}; cuuint64_t gs[1] = {stride_bytes};
  cuuint32_t bx[2] = {box_inner, box_outer}; cuuint32_t es[2] = {1, 1};
  enc(&m, CU_TENSOR_MAP_DATA_TYPE_BFLOAT16, 2, const_cast<void*>(ptr), gd, gs, bx, es, CU_TENSOR_MAP_INTERLEAVE_NONE,
      CU_TENSOR_MAP_SWIZZLE_128B, CU_TENSOR_MAP_L2_PROMOTION_L2_128B, CU_TENSOR_MAP_FLOAT_OOB_FILL_NONE);
  return m;
}

CUtensorMap make_map_3d(PFN_encodeTiled enc, const void* ptr, uint64_t cols, uint64_t rows, uint32_t box_rows, uint32_t chunks) {
  CUtensorMap m;
  cuuint64_t gd[3] = {64, rows, cols / 64}; cuuint64_t gs[2] = {cols * 2, 128};
  cuuint32_t bx[3] = {64, box_rows, chunks}; cuuint32_t es[3] = {1, 1, 1};
  enc(&m, CU_TENSOR_MAP_DATA_TYPE_BFLOAT16, 3, const_cast<void*>(ptr), gd, gs, bx, es, CU_TENSOR_MAP_INTERLEAVE_NONE,
      CU_TENSOR_MAP_SWIZZLE_128B, CU_TENSOR_MAP_L2_PROMOTION_L2_128B, CU_TENSOR_MAP_FLOAT_OOB_FILL_NONE);
  return m;
}

}

extern "C" void kernel_launch(void* const* d_in, const int* in_sizes, int n_in, void* d_out, int out_size) {
  const bf16* x      = (const bf16*)d_in[0];
  const bf16* kc     = (const bf16*)d_in[1];
  const bf16* vc     = (const bf16*)d_in[2];
  const bf16* wq     = (const bf16*)d_in[3];
  const bf16* wo     = (const bf16*)d_in[4];
  const bf16* w_r    = (const bf16*)d_in[6];
  const bf16* w_gate = (const bf16*)d_in[7];
  const bf16* w_up   = (const bf16*)d_in[8];
  const bf16* w_down = (const bf16*)d_in[9];
  const bf16* cvec   = (const bf16*)d_in[10];
  const bf16* w_mod  = (const bf16*)d_in[11];
  bf16* out = (bf16*)d_out;

  static PFN_encodeTiled enc = nullptr;
  static void *p_h = nullptr, *p_o = nullptr;
  if (!enc) {
    void* fn = nullptr; cudaDriverEntryPointQueryResult qres;
    cudaGetDriverEntryPoint("cuTensorMapEncodeTiled", &fn, cudaEnableDefault, &qres);
    enc = (PFN_encodeTiled)fn;
    cudaGetSymbolAddress(&p_h, g_pre);
    p_h = (uint4*)p_h + 16 * PRE_X * 2048;
    cudaGetSymbolAddress(&p_o, g_o);
    cudaFuncSetAttribute(fused_kernel, cudaFuncAttributeMaxDynamicSharedMemorySize, (int)AT_SMEM);
  }
  const CUtensorMap tm_h   = make_map_2d(enc, p_h, T_D, T_SEQ, T_D * 2, 64, 128);
  const CUtensorMap tm_wq  = make_map_3d(enc, wq, T_DQKV, T_D, 64, 4);
  const CUtensorMap tm_k   = make_map_3d(enc, kc, T_DH, (uint64_t)T_NH * T_SEQ, 128, 2);
  const CUtensorMap tm_v   = make_map_3d(enc, vc, T_DH, (uint64_t)T_NH * T_SEQ, 128, 2);
  const CUtensorMap tm_ost = make_map_2d(enc, p_o, T_DQKV, T_SEQ, T_DQKV * 2, 64, 64);
  const CUtensorMap tm_old = make_map_2d(enc, p_o, T_DQKV, T_SEQ, T_DQKV * 2, 64, 128);
  const CUtensorMap tm_wo  = make_map_3d(enc, wo, T_D, T_DQKV, 64, 2);
  const CUtensorMap tm_d   = make_map_3d(enc, w_down, T_D, T_F, 32, 8);

  const CUtensorMap tm_m   = make_map_2d(enc, w_mod, 6 * T_D, T_D, 6 * T_D * 2, 64, 256);
  const CUtensorMap tm_out = make_map_2d(enc, out, T_D, T_SEQ, T_D * 2, 64, 16);

  fused_kernel<<<132, 384, AT_SMEM, cudaStreamPerThread>>>(tm_h, tm_wq, tm_k, tm_v, tm_ost, tm_old, tm_wo, tm_d, tm_out, tm_m, 0u, (const uint8_t*)wo, kc, vc, x, cvec, w_mod,
             w_r, w_gate, w_up, w_down, out);
}
```

```cpp
#include <cuda_runtime.h>
#include <cuda_bf16.h>
#include <cuda.h>
#include <stdint.h>

namespace {

typedef __nv_bfloat16 bf16;

constexpr int T_SEQ = 2048, T_D = 1024, T_NH = 32, T_DH = 128, T_DQKV = 4096, T_F = 3584;

#define PRE_X 2
__device__ __align__(1024) uint4 g_pre[(16 * PRE_X + 128) * 2048];
#define g_h (reinterpret_cast<bf16*>(g_pre + 16 * PRE_X * 2048))
__device__ __align__(1024) bf16 g_o[T_SEQ * T_DQKV];
__device__ __align__(16) uint8_t g_col[8 * 1536];
__device__ __align__(16) float g_scal[64];
__device__ __align__(16) unsigned int g_hcnt[17 * 32];
__device__ __align__(128) float g_modpart[4 * 2 * T_D];
struct __align__(2048) TailMail {
  float4 part1[T_SEQ * 8];
  uint32_t key[256];
  uint4 cand[16 * 2 * 2 * 128];
  uint32_t cnt[32];
  float ypart[(T_F / 32) * 2 * T_D];
};
__device__ TailMail g_mail;
#define g_part1 g_mail.part1
#define g_key g_mail.key
#define g_cand g_mail.cand
#define CNT_Y (g_mail.cnt)
#define g_ypart g_mail.ypart

__device__ __forceinline__ uint32_t smem_u32(const void* p) { return (uint32_t)__cvta_generic_to_shared(p); }
__device__ __forceinline__ void mbar_init(uint32_t bar, uint32_t cnt) { asm volatile("mbarrier.init.shared::cta.b64 [%0], %1;" :: "r"(bar), "r"(cnt)); }
__device__ __forceinline__ void mbar_expect_tx(uint32_t bar, uint32_t bytes) { asm volatile("mbarrier.arrive.expect_tx.shared::cta.b64 _, [%0], %1;" :: "r"(bar), "r"(bytes) : "memory"); }
__device__ __forceinline__ void mbar_arrive(uint32_t bar) { asm volatile("mbarrier.arrive.shared::cta.b64 _, [%0];" :: "r"(bar) : "memory"); }
__device__ __forceinline__ void mbar_wait(uint32_t bar, uint32_t parity) {
  asm volatile("{\n.reg .pred p;\nLAB_WAIT:\nmbarrier.try_wait.parity.shared::cta.b64 p, [%0], %1;\n@!p bra LAB_WAIT;\n}\n" :: "r"(bar), "r"(parity) : "memory");
}
__device__ __forceinline__ bool mbar_test(uint32_t bar, uint32_t parity) {
  uint32_t r; asm volatile("{\n.reg .pred p;\nmbarrier.test_wait.parity.shared::cta.b64 p, [%1], %2;\nselp.u32 %0, 1, 0, p;\n}\n" : "=r"(r) : "r"(bar), "r"(parity) : "memory");
  return r != 0;
}
__device__ __forceinline__ void mbar_wait_long(uint32_t bar, uint32_t parity) {
  asm volatile("{\n.reg .pred p;\nLAB_WAIT:\nmbarrier.try_wait.parity.shared::cta.b64 p, [%0], %1, %2;\n@!p bra LAB_WAIT;\n}\n" :: "r"(bar), "r"(parity), "r"(100000) : "memory");
}
__device__ __forceinline__ uint32_t clock_lo() { uint32_t c; asm volatile("mov.u32 %0, %%clock;" : "=r"(c)); return c; }
__device__ __forceinline__ void fence_mbar_init() { asm volatile("fence.mbarrier_init.release.cluster;" ::: "memory"); }
__device__ __forceinline__ void tma_load_2d(uint32_t dst, const CUtensorMap* map, int c0, int c1, uint32_t bar) {
  asm volatile("cp.async.bulk.tensor.2d.shared::cluster.global.mbarrier::complete_tx::bytes [%0], [%1, {%3, %4}], [%2];"
    :: "r"(dst), "l"(map), "r"(bar), "r"(c0), "r"(c1) : "memory");
}
__device__ __forceinline__ uint64_t policy_evict_first() {
  uint64_t p; asm volatile("createpolicy.fractional.L2::evict_first.b64 %0, 1.0;" : "=l"(p)); return p;
}
__device__ __forceinline__ void tma_load_2d_hint(uint32_t dst, const CUtensorMap* map, int c0, int c1, uint32_t bar, uint64_t pol) {
  asm volatile("cp.async.bulk.tensor.2d.shared::cluster.global.mbarrier::complete_tx::bytes.L2::cache_hint [%0], [%1, {%3, %4}], [%2], %5;"
    :: "r"(dst), "l"(map), "r"(bar), "r"(c0), "r"(c1), "l"(pol) : "memory");
}
__device__ __forceinline__ void tma_load_3d_hint(uint32_t dst, const CUtensorMap* map, int c1, int c2, uint32_t bar, uint64_t pol) {
  asm volatile("cp.async.bulk.tensor.3d.shared::cluster.global.mbarrier::complete_tx::bytes.L2::cache_hint [%0], [%1, {%3, %4, %5}], [%2], %6;"
    :: "r"(dst), "l"(map), "r"(bar), "n"(0), "r"(c1), "r"(c2), "l"(pol) : "memory");
}
__device__ __forceinline__ void tma_load_3d(uint32_t dst, const CUtensorMap* map, int c1, int c2, uint32_t bar) {
  asm volatile("cp.async.bulk.tensor.3d.shared::cluster.global.mbarrier::complete_tx::bytes [%0], [%1, {%3, %4, %5}], [%2];"
    :: "r"(dst), "l"(map), "r"(bar), "n"(0), "r"(c1), "r"(c2) : "memory");
}
__device__ __forceinline__ void tma_store_2d(const CUtensorMap* map, uint32_t src, int c0, int c1) {
  asm volatile("cp.async.bulk.tensor.2d.global.shared::cta.bulk_group [%0, {%2, %3}], [%1];" :: "l"(map), "r"(src), "r"(c0), "r"(c1) : "memory");
}
__device__ __forceinline__ void prefetch_tmap(const CUtensorMap* map) { asm volatile("prefetch.tensormap [%0];" :: "l"(map) : "memory"); }
__device__ __forceinline__ void l2_prefetch_bulk(const void* p, uint32_t bytes) {
  asm volatile("cp.async.bulk.prefetch.L2.global [%0], %1;" :: "l"(p), "r"(bytes) : "memory");
}
__device__ __forceinline__ void bulk_commit() { asm volatile("cp.async.bulk.commit_group;" ::: "memory"); }
template<int N> __device__ __forceinline__ void bulk_wait_read() { asm volatile("cp.async.bulk.wait_group.read %0;" :: "n"(N) : "memory"); }
template<int N> __device__ __forceinline__ void bulk_wait() { asm volatile("cp.async.bulk.wait_group %0;" :: "n"(N) : "memory"); }
__device__ __forceinline__ void named_bar_sync(int id, int nthreads) { asm volatile("bar.sync %0, %1;" :: "r"(id), "r"(nthreads) : "memory"); }
__device__ __forceinline__ void named_bar_arrive(int id, int nthreads) { asm volatile("bar.arrive %0, %1;" :: "r"(id), "r"(nthreads) : "memory"); }
__device__ __forceinline__ void pass_turn(int cwg) {
  asm volatile("{\n.reg .pred p;\nsetp.ne.u32 p, %0, 0;\n@p bar.arrive 1, 256;\n@!p bar.arrive 2, 256;\n}\n" :: "r"(cwg) : "memory");
}
__device__ __forceinline__ void wgmma_fence() { asm volatile("wgmma.fence.sync.aligned;" ::: "memory"); }
__device__ __forceinline__ void wgmma_commit() { asm volatile("wgmma.commit_group.sync.aligned;" ::: "memory"); }
template<int N> __device__ __forceinline__ void wgmma_wait() { asm volatile("wgmma.wait_group.sync.aligned %0;" :: "n"(N) : "memory"); }
template<int R> __device__ __forceinline__ void reg_alloc() { asm volatile("setmaxnreg.inc.sync.aligned.u32 %0;" :: "n"(R)); }
template<int R> __device__ __forceinline__ void reg_dealloc() { asm volatile("setmaxnreg.dec.sync.aligned.u32 %0;" :: "n"(R)); }
__device__ __forceinline__ bool elect_one() {
  uint32_t pred; asm volatile("{\n.reg .pred p;\nelect.sync _|p, 0xffffffff;\nselp.u32 %0, 1, 0, p;\n}\n" : "=r"(pred)); return pred != 0;
}
__device__ __forceinline__ uint32_t pack_bf16(float lo, float hi) {
  uint32_t r; asm("cvt.rn.bf16x2.f32 %0, %1, %2;" : "=r"(r) : "f"(hi), "f"(lo)); return r;
}
__device__ __forceinline__ void stmatrix_x4(uint32_t addr, uint32_t r0, uint32_t r1, uint32_t r2, uint32_t r3) {
  asm volatile("stmatrix.sync.aligned.m8n8.x4.shared.b16 [%0], {%1, %2, %3, %4};" :: "r"(addr), "r"(r0), "r"(r1), "r"(r2), "r"(r3) : "memory");
}
__device__ __forceinline__ void fence_proxy_async() { asm volatile("fence.proxy.async.shared::cta;" ::: "memory"); }
__device__ __forceinline__ float ex2_approx(float x) { float y; asm("ex2.approx.ftz.f32 %0, %1;" : "=f"(y) : "f"(x)); return y; }
template<int N> __device__ __forceinline__ void fence_regs(float (&r)[N]) {
  #pragma unroll
  for (int i = 0; i < N; i++) asm volatile("" : "+f"(r[i]) :: "memory");
}
template<int N> __device__ __forceinline__ void zero_regs(float (&r)[N]) {
  #pragma unroll
  for (int i = 0; i < N; i += 2) asm volatile("mov.b64 {%0, %1}, 0;" : "=f"(r[i]), "=f"(r[i + 1]));
}
__device__ __forceinline__ float rbf(float x) { return __uint_as_float(pack_bf16(0.f, x)); }
__device__ __forceinline__ float bflo(uint32_t v) { return __uint_as_float(v << 16); }
__device__ __forceinline__ float bfhi(uint32_t v) { return __uint_as_float(v & 0xffff0000u); }

#define XT(i) do {} while (0)
#define TL_START(k) do {} while (0)
#define TL_END(k, cond) do {} while (0)
#define TL_CTA(i, cond) do {} while (0)
#define FS(slot, k) do {} while (0)
#define TL_MARK2(k, cond) do {} while (0)
#define TL_CLK(k, i, cond) do {} while (0)

template <int OFFA, int OFFB>
__device__ __forceinline__ void wgmma_m64n256k16_ss_tb(float (&d)[128], uint32_t a_lo, uint32_t b_lo, int scaleD) {
  asm volatile("{\n.reg .pred p;\n.reg .b32 ta, tb;\n.reg .b64 da, db;\nsetp.ne.b32 p, %130, 0;\n"
    "add.u32 ta, %128, %131;\nadd.u32 tb, %129, %132;\n"
    "mov.b64 da, {ta, 0x40000040};\nmov.b64 db, {tb, 0x40000040};\n"
    "wgmma.mma_async.sync.aligned.m64n256k16.f32.bf16.bf16 "
    "{%0, %1, %2, %3, %4, %5, %6, %7, %8, %9, %10, %11, %12, %13, %14, %15, %16, %17, %18, %19, %20, %21, %22, %23, %24, %25, %26, %27, %28, %29, %30, %31, %32, %33, %34, %35, %36, %37, %38, %39, %40, %41, %42, %43, %44, %45, %46, %47, %48, %49, %50, %51, %52, %53, %54, %55, %56, %57, %58, %59, %60, %61, %62, %63, %64, %65, %66, %67, %68, %69, %70, %71, %72, %73, %74, %75, %76, %77, %78, %79, %80, %81, %82, %83, %84, %85, %86, %87, %88, %89, %90, %91, %92, %93, %94, %95, %96, %97, %98, %99, %100, %101, %102, %103, %104, %105, %106, %107, %108, %109, %110, %111, %112, %113, %114, %115, %116, %117, %118, %119, %120, %121, %122, %123, %124, %125, %126, %127}, "
    "da, db, p, 1, 1, 0, 1;\n}\n"
    : "+f"(d[0]), "+f"(d[1]), "+f"(d[2]), "+f"(d[3]), "+f"(d[4]), "+f"(d[5]), "+f"(d[6]), "+f"(d[7]), "+f"(d[8]), "+f"(d[9]), "+f"(d[10]), "+f"(d[11]), "+f"(d[12]), "+f"(d[13]), "+f"(d[14]), "+f"(d[15]), "+f"(d[16]), "+f"(d[17]), "+f"(d[18]), "+f"(d[19]), "+f"(d[20]), "+f"(d[21]), "+f"(d[22]), "+f"(d[23]), "+f"(d[24]), "+f"(d[25]), "+f"(d[26]), "+f"(d[27]), "+f"(d[28]), "+f"(d[29]), "+f"(d[30]), "+f"(d[31]), "+f"(d[32]), "+f"(d[33]), "+f"(d[34]), "+f"(d[35]), "+f"(d[36]), "+f"(d[37]), "+f"(d[38]), "+f"(d[39]), "+f"(d[40]), "+f"(d[41]), "+f"(d[42]), "+f"(d[43]), "+f"(d[44]), "+f"(d[45]), "+f"(d[46]), "+f"(d[47]), "+f"(d[48]), "+f"(d[49]), "+f"(d[50]), "+f"(d[51]), "+f"(d[52]), "+f"(d[53]), "+f"(d[54]), "+f"(d[55]), "+f"(d[56]), "+f"(d[57]), "+f"(d[58]), "+f"(d[59]), "+f"(d[60]), "+f"(d[61]), "+f"(d[62]), "+f"(d[63]), "+f"(d[64]), "+f"(d[65]), "+f"(d[66]), "+f"(d[67]), "+f"(d[68]), "+f"(d[69]), "+f"(d[70]), "+f"(d[71]), "+f"(d[72]), "+f"(d[73]), "+f"(d[74]), "+f"(d[75]), "+f"(d[76]), "+f"(d[77]), "+f"(d[78]), "+f"(d[79]), "+f"(d[80]), "+f"(d[81]), "+f"(d[82]), "+f"(d[83]), "+f"(d[84]), "+f"(d[85]), "+f"(d[86]), "+f"(d[87]), "+f"(d[88]), "+f"(d[89]), "+f"(d[90]), "+f"(d[91]), "+f"(d[92]), "+f"(d[93]), "+f"(d[94]), "+f"(d[95]), "+f"(d[96]), "+f"(d[97]), "+f"(d[98]), "+f"(d[99]), "+f"(d[100]), "+f"(d[101]), "+f"(d[102]), "+f"(d[103]), "+f"(d[104]), "+f"(d[105]), "+f"(d[106]), "+f"(d[107]), "+f"(d[108]), "+f"(d[109]), "+f"(d[110]), "+f"(d[111]), "+f"(d[112]), "+f"(d[113]), "+f"(d[114]), "+f"(d[115]), "+f"(d[116]), "+f"(d[117]), "+f"(d[118]), "+f"(d[119]), "+f"(d[120]), "+f"(d[121]), "+f"(d[122]), "+f"(d[123]), "+f"(d[124]), "+f"(d[125]), "+f"(d[126]), "+f"(d[127])
    : "r"(a_lo), "r"(b_lo), "r"(scaleD), "n"(OFFA), "n"(OFFB));
}

template <int OFFA, int OFFB>
__device__ __forceinline__ void wgmma_m64n128k16_ss_tb(float (&d)[64], uint32_t a_lo, uint32_t b_lo, int scaleD) {
  asm volatile("{\n.reg .pred p;\n.reg .b32 ta, tb;\n.reg .b64 da, db;\nsetp.ne.b32 p, %66, 0;\n"
    "add.u32 ta, %64, %67;\nadd.u32 tb, %65, %68;\n"
    "mov.b64 da, {ta, 0x40000040};\nmov.b64 db, {tb, 0x40000040};\n"
    "wgmma.mma_async.sync.aligned.m64n128k16.f32.bf16.bf16 "
    "{%0, %1, %2, %3, %4, %5, %6, %7, %8, %9, %10, %11, %12, %13, %14, %15, %16, %17, %18, %19, %20, %21, %22, %23, %24, %25, %26, %27, %28, %29, %30, %31, %32, %33, %34, %35, %36, %37, %38, %39, %40, %41, %42, %43, %44, %45, %46, %47, %48, %49, %50, %51, %52, %53, %54, %55, %56, %57, %58, %59, %60, %61, %62, %63}, "
    "da, db, p, 1, 1, 0, 1;\n}\n"
    : "+f"(d[0]), "+f"(d[1]), "+f"(d[2]), "+f"(d[3]), "+f"(d[4]), "+f"(d[5]), "+f"(d[6]), "+f"(d[7]), "+f"(d[8]), "+f"(d[9]), "+f"(d[10]), "+f"(d[11]), "+f"(d[12]), "+f"(d[13]), "+f"(d[14]), "+f"(d[15]), "+f"(d[16]), "+f"(d[17]), "+f"(d[18]), "+f"(d[19]), "+f"(d[20]), "+f"(d[21]), "+f"(d[22]), "+f"(d[23]), "+f"(d[24]), "+f"(d[25]), "+f"(d[26]), "+f"(d[27]), "+f"(d[28]), "+f"(d[29]), "+f"(d[30]), "+f"(d[31]), "+f"(d[32]), "+f"(d[33]), "+f"(d[34]), "+f"(d[35]), "+f"(d[36]), "+f"(d[37]), "+f"(d[38]), "+f"(d[39]), "+f"(d[40]), "+f"(d[41]), "+f"(d[42]), "+f"(d[43]), "+f"(d[44]), "+f"(d[45]), "+f"(d[46]), "+f"(d[47]), "+f"(d[48]), "+f"(d[49]), "+f"(d[50]), "+f"(d[51]), "+f"(d[52]), "+f"(d[53]), "+f"(d[54]), "+f"(d[55]), "+f"(d[56]), "+f"(d[57]), "+f"(d[58]), "+f"(d[59]), "+f"(d[60]), "+f"(d[61]), "+f"(d[62]), "+f"(d[63])
    : "r"(a_lo), "r"(b_lo), "r"(scaleD), "n"(OFFA), "n"(OFFB));
}

template <int OFFB>
__device__ __forceinline__ void wgmma_m64n128k16_rs_tb(float (&d)[64], uint32_t a0, uint32_t a1, uint32_t a2, uint32_t a3, uint32_t b_lo, int scaleD) {
  asm volatile("{\n.reg .pred p;\n.reg .b32 tb;\n.reg .b64 db;\nsetp.ne.b32 p, %69, 0;\n"
    "add.u32 tb, %68, %70;\n"
    "mov.b64 db, {tb, 0x40000040};\n"
    "wgmma.mma_async.sync.aligned.m64n128k16.f32.bf16.bf16 "
    "{%0, %1, %2, %3, %4, %5, %6, %7, %8, %9, %10, %11, %12, %13, %14, %15, %16, %17, %18, %19, %20, %21, %22, %23, %24, %25, %26, %27, %28, %29, %30, %31, %32, %33, %34, %35, %36, %37, %38, %39, %40, %41, %42, %43, %44, %45, %46, %47, %48, %49, %50, %51, %52, %53, %54, %55, %56, %57, %58, %59, %60, %61, %62, %63}, "
    "{%64, %65, %66, %67}, db, p, 1, 1, 1;\n}\n"
    : "+f"(d[0]), "+f"(d[1]), "+f"(d[2]), "+f"(d[3]), "+f"(d[4]), "+f"(d[5]), "+f"(d[6]), "+f"(d[7]), "+f"(d[8]), "+f"(d[9]), "+f"(d[10]), "+f"(d[11]), "+f"(d[12]), "+f"(d[13]), "+f"(d[14]), "+f"(d[15]), "+f"(d[16]), "+f"(d[17]), "+f"(d[18]), "+f"(d[19]), "+f"(d[20]), "+f"(d[21]), "+f"(d[22]), "+f"(d[23]), "+f"(d[24]), "+f"(d[25]), "+f"(d[26]), "+f"(d[27]), "+f"(d[28]), "+f"(d[29]), "+f"(d[30]), "+f"(d[31]), "+f"(d[32]), "+f"(d[33]), "+f"(d[34]), "+f"(d[35]), "+f"(d[36]), "+f"(d[37]), "+f"(d[38]), "+f"(d[39]), "+f"(d[40]), "+f"(d[41]), "+f"(d[42]), "+f"(d[43]), "+f"(d[44]), "+f"(d[45]), "+f"(d[46]), "+f"(d[47]), "+f"(d[48]), "+f"(d[49]), "+f"(d[50]), "+f"(d[51]), "+f"(d[52]), "+f"(d[53]), "+f"(d[54]), "+f"(d[55]), "+f"(d[56]), "+f"(d[57]), "+f"(d[58]), "+f"(d[59]), "+f"(d[60]), "+f"(d[61]), "+f"(d[62]), "+f"(d[63])
    : "r"(a0), "r"(a1), "r"(a2), "r"(a3), "r"(b_lo), "r"(scaleD), "n"(OFFB));
}

template <int OFFB>
__device__ __forceinline__ void wgmma_m64n128k16_rs(float (&d)[64], uint32_t a0, uint32_t a1, uint32_t a2, uint32_t a3, uint32_t b_lo, int scaleD) {
  asm volatile("{\n.reg .pred p;\n.reg .b32 tb;\n.reg .b64 db;\nsetp.ne.b32 p, %69, 0;\n"
    "add.u32 tb, %68, %70;\n"
    "mov.b64 db, {tb, 0x40000040};\n"
    "wgmma.mma_async.sync.aligned.m64n128k16.f32.bf16.bf16 "
    "{%0, %1, %2, %3, %4, %5, %6, %7, %8, %9, %10, %11, %12, %13, %14, %15, %16, %17, %18, %19, %20, %21, %22, %23, %24, %25, %26, %27, %28, %29, %30, %31, %32, %33, %34, %35, %36, %37, %38, %39, %40, %41, %42, %43, %44, %45, %46, %47, %48, %49, %50, %51, %52, %53, %54, %55, %56, %57, %58, %59, %60, %61, %62, %63}, "
    "{%64, %65, %66, %67}, db, p, 1, 1, 0;\n}\n"
    : "+f"(d[0]), "+f"(d[1]), "+f"(d[2]), "+f"(d[3]), "+f"(d[4]), "+f"(d[5]), "+f"(d[6]), "+f"(d[7]), "+f"(d[8]), "+f"(d[9]), "+f"(d[10]), "+f"(d[11]), "+f"(d[12]), "+f"(d[13]), "+f"(d[14]), "+f"(d[15]), "+f"(d[16]), "+f"(d[17]), "+f"(d[18]), "+f"(d[19]), "+f"(d[20]), "+f"(d[21]), "+f"(d[22]), "+f"(d[23]), "+f"(d[24]), "+f"(d[25]), "+f"(d[26]), "+f"(d[27]), "+f"(d[28]), "+f"(d[29]), "+f"(d[30]), "+f"(d[31]), "+f"(d[32]), "+f"(d[33]), "+f"(d[34]), "+f"(d[35]), "+f"(d[36]), "+f"(d[37]), "+f"(d[38]), "+f"(d[39]), "+f"(d[40]), "+f"(d[41]), "+f"(d[42]), "+f"(d[43]), "+f"(d[44]), "+f"(d[45]), "+f"(d[46]), "+f"(d[47]), "+f"(d[48]), "+f"(d[49]), "+f"(d[50]), "+f"(d[51]), "+f"(d[52]), "+f"(d[53]), "+f"(d[54]), "+f"(d[55]), "+f"(d[56]), "+f"(d[57]), "+f"(d[58]), "+f"(d[59]), "+f"(d[60]), "+f"(d[61]), "+f"(d[62]), "+f"(d[63])
    : "r"(a0), "r"(a1), "r"(a2), "r"(a3), "r"(b_lo), "r"(scaleD), "n"(OFFB));
}

__device__ __forceinline__ uint4 ldg_nc_v4(const void* p) {
  uint4 v;
    asm volatile("{\n.reg .b64 pol;\ncreatepolicy.fractional.L2::evict_first.b64 pol, 1.0;\n"
                 "ld.global.nc.L1::no_allocate.L2::cache_hint.v4.u32 {%0, %1, %2, %3}, [%4], pol;\n}\n" : "=r"(v.x), "=r"(v.y), "=r"(v.z), "=r"(v.w) : "l"(p));
  return v;
}
__device__ __forceinline__ void unpack8(const uint4& u, float (&v)[8]) {
  v[0] = bflo(u.x); v[1] = bfhi(u.x); v[2] = bflo(u.y); v[3] = bfhi(u.y);
  v[4] = bflo(u.z); v[5] = bfhi(u.z); v[6] = bflo(u.w); v[7] = bfhi(u.w);
}
__device__ __forceinline__ void fma8(float (&acc)[8], float s, const uint4& w) {
  acc[0] = fmaf(s, bflo(w.x), acc[0]); acc[1] = fmaf(s, bfhi(w.x), acc[1]); acc[2] = fmaf(s, bflo(w.y), acc[2]); acc[3] = fmaf(s, bfhi(w.y), acc[3]);
  acc[4] = fmaf(s, bflo(w.z), acc[4]); acc[5] = fmaf(s, bfhi(w.z), acc[5]); acc[6] = fmaf(s, bflo(w.w), acc[6]); acc[7] = fmaf(s, bfhi(w.w), acc[7]);
}
__device__ __forceinline__ float rcp_approx(float x) { float y; asm("rcp.approx.ftz.f32 %0, %1;" : "=f"(y) : "f"(x)); return y; }
__device__ __forceinline__ float sigmoid_f(float v) { return rcp_approx(1.0f + ex2_approx(v * -1.4426950408889634f)); }
__device__ __forceinline__ float silu_bf(float v) { return rbf(v * sigmoid_f(v)); }
__device__ __forceinline__ uint32_t rank_key(float r, int idx) {
  const uint32_t b = __float_as_uint(r) >> 16;
  const uint32_t u = (r != r) ? 0u : ((b & 0x8000u) ? (~b & 0xffffu) : (b | 0x8000u));
  return (u << 16) | (0xffffu - (uint32_t)idx);
}
__device__ __forceinline__ void warp_top2(uint32_t& k1, uint32_t& k2) {
  const uint32_t m1 = __reduce_max_sync(0xffffffffu, k1);
  k2 = __reduce_max_sync(0xffffffffu, k1 == m1 ? k2 : k1);
  k1 = m1;
}
__device__ __forceinline__ uint32_t bmul2(uint32_t a, uint32_t b) { uint32_t r; asm("mul.rn.bf16x2 %0, %1, %2;" : "=r"(r) : "r"(a), "r"(b)); return r; }
__device__ __forceinline__ uint32_t badd2(uint32_t a, uint32_t b) { uint32_t r; asm("add.rn.bf16x2 %0, %1, %2;" : "=r"(r) : "r"(a), "r"(b)); return r; }
__device__ __forceinline__ uint32_t bsub2(uint32_t a, uint32_t b) { uint32_t r; asm("sub.rn.bf16x2 %0, %1, %2;" : "=r"(r) : "r"(a), "r"(b)); return r; }
__device__ __forceinline__ float sqrt_approx(float x) { float y; asm("sqrt.approx.f32 %0, %1;" : "=f"(y) : "f"(x)); return y; }
__device__ __forceinline__ uint32_t ln_norm2(uint32_t x1, uint32_t mb2, float inv) {
  const uint32_t d = bsub2(x1, mb2);
  return pack_bf16(bflo(d) * inv, bfhi(d) * inv);
}
__device__ __forceinline__ uint32_t bfma2(uint32_t a, uint32_t b, uint32_t c) { uint32_t r; asm("fma.rn.bf16x2 %0, %1, %2, %3;" : "=r"(r) : "r"(a), "r"(b), "r"(c)); return r; }
__device__ __forceinline__ uint32_t ln_norm2b(uint32_t x1, uint32_t mb2, uint32_t ih, uint32_t il) {
  const uint32_t d = bsub2(x1, mb2);
  return bfma2(d, ih, bmul2(d, il));
}
__device__ __forceinline__ uint32_t ln_mod2(uint32_t x1, uint32_t mb2, float inv, uint32_t c1, uint32_t sb) { return badd2(bmul2(ln_norm2(x1, mb2, inv), c1), sb); }
__device__ __forceinline__ void ldmatrix_x4(uint32_t addr, uint32_t& r0, uint32_t& r1, uint32_t& r2, uint32_t& r3) {
  asm volatile("ldmatrix.sync.aligned.m8n8.x4.shared.b16 {%0, %1, %2, %3}, [%4];" : "=r"(r0), "=r"(r1), "=r"(r2), "=r"(r3) : "r"(addr) : "memory");
}
__device__ __forceinline__ uint4 ldg_stream_v4(const void* p, uint64_t pol) {
  uint4 v; asm volatile("ld.global.nc.L1::no_allocate.L2::cache_hint.L2::128B.v4.u32 {%0, %1, %2, %3}, [%4], %5;" : "=r"(v.x), "=r"(v.y), "=r"(v.z), "=r"(v.w) : "l"(p), "l"(pol)); return v;
}
__device__ __forceinline__ void bulk_load_hint(uint32_t dst, const void* src, uint32_t bytes, uint32_t bar, uint64_t pol) {
  asm volatile("cp.async.bulk.shared::cluster.global.mbarrier::complete_tx::bytes.L2::cache_hint [%0], [%1], %2, [%3], %4;"
    :: "r"(dst), "l"(src), "r"(bytes), "r"(bar), "l"(pol) : "memory");
}
__device__ __forceinline__ void red_release_add(unsigned int* p, unsigned int v) { asm volatile("red.release.gpu.global.add.u32 [%0], %1;" :: "l"(p), "r"(v) : "memory"); }
__device__ __forceinline__ unsigned int ld_acquire(const unsigned int* p) { unsigned int v; asm volatile("ld.acquire.gpu.global.u32 %0, [%1];" : "=r"(v) : "l"(p) : "memory"); return v; }
__device__ __forceinline__ void spin_until(const unsigned int* p, unsigned int target) {
  #pragma unroll 1
  for (unsigned int i = 0; i < (1u << 22); i++) { if (ld_acquire(p) >= target) return; }
}
__device__ __forceinline__ float lds_f32(uint32_t a) { float v; asm volatile("ld.shared.f32 %0, [%1];" : "=f"(v) : "r"(a) : "memory"); return v; }
__device__ __forceinline__ float2 lds_f32x2(uint32_t a) { float2 v; asm volatile("ld.shared.v2.f32 {%0, %1}, [%2];" : "=f"(v.x), "=f"(v.y) : "r"(a) : "memory"); return v; }
__device__ __forceinline__ uint2 lds_u32x2(uint32_t a) { uint2 v; asm volatile("ld.shared.v2.u32 {%0, %1}, [%2];" : "=r"(v.x), "=r"(v.y) : "r"(a) : "memory"); return v; }
__device__ __forceinline__ uint32_t lds_u32(uint32_t a) { uint32_t v; asm volatile("ld.shared.u32 %0, [%1];" : "=r"(v) : "r"(a) : "memory"); return v; }
__device__ __forceinline__ void sts_u32(uint32_t a, uint32_t v) { asm volatile("st.shared.u32 [%0], %1;" :: "r"(a), "r"(v) : "memory"); }
__device__ __forceinline__ void sts_u32x2(uint32_t a, uint32_t x, uint32_t y) { asm volatile("st.shared.v2.u32 [%0], {%1, %2};" :: "r"(a), "r"(x), "r"(y) : "memory"); }
__device__ __forceinline__ void sts_f32(uint32_t a, float v) { asm volatile("st.shared.f32 [%0], %1;" :: "r"(a), "f"(v) : "memory"); }
__device__ __forceinline__ void sts_f32x2(uint32_t a, float x, float y) { asm volatile("st.shared.v2.f32 [%0], {%1, %2};" :: "r"(a), "f"(x), "f"(y) : "memory"); }
__device__ __forceinline__ void sts_f32x4(uint32_t a, float x, float y, float z, float w) { asm volatile("st.shared.v4.f32 [%0], {%1, %2, %3, %4};" :: "r"(a), "f"(x), "f"(y), "f"(z), "f"(w) : "memory"); }

__device__ __forceinline__ uint4 lds_u32x4(uint32_t a) { uint4 v; asm volatile("ld.shared.v4.u32 {%0, %1, %2, %3}, [%4];" : "=r"(v.x), "=r"(v.y), "=r"(v.z), "=r"(v.w) : "r"(a) : "memory"); return v; }
__device__ __forceinline__ void sts_u32x4(uint32_t a, uint32_t x, uint32_t y, uint32_t z, uint32_t w) { asm volatile("st.shared.v4.u32 [%0], {%1, %2, %3, %4};" :: "r"(a), "r"(x), "r"(y), "r"(z), "r"(w) : "memory"); }
__device__ __forceinline__ void st_tagged(float* p, float v) {
  const uint32_t b = __float_as_uint(v);
  asm volatile("st.relaxed.gpu.global.u32 [%0], %1;" :: "l"(p), "r"(b == 0u ? 0x80000000u : b) : "memory");
}
__device__ __forceinline__ void st_tagged4(float* p, float x, float y, float z, float w) {
  const uint32_t a = __float_as_uint(x), b = __float_as_uint(y), c = __float_as_uint(z), d = __float_as_uint(w);
  asm volatile("st.relaxed.gpu.global.v4.u32 [%0], {%1, %2, %3, %4};" :: "l"(p), "r"(a == 0u ? 0x80000000u : a), "r"(b == 0u ? 0x80000000u : b),
               "r"(c == 0u ? 0x80000000u : c), "r"(d == 0u ? 0x80000000u : d) : "memory");
}
__device__ __forceinline__ void st_relaxed2(void* p, uint32_t a, uint32_t b) { asm volatile("st.relaxed.gpu.global.v2.u32 [%0], {%1, %2};" :: "l"(p), "r"(a), "r"(b) : "memory"); }
__device__ __forceinline__ float4 ld_tagged4(const float* p) {
  float4 v; asm volatile("ld.relaxed.gpu.global.v4.f32 {%0, %1, %2, %3}, [%4];" : "=f"(v.x), "=f"(v.y), "=f"(v.z), "=f"(v.w) : "l"(p) : "memory"); return v;
}
__device__ __forceinline__ bool tagged4(const float4& v) {
  return __float_as_uint(v.x) != 0u && __float_as_uint(v.y) != 0u && __float_as_uint(v.z) != 0u && __float_as_uint(v.w) != 0u;
}
__device__ __forceinline__ void hint_arrive(uint32_t* p) { asm volatile("red.relaxed.gpu.global.add.u32 [%0], 1;" :: "l"(p) : "memory"); }
__device__ __forceinline__ void hint_wait(const uint32_t* p, uint32_t target) {
  uint32_t v = 0u;
  #pragma unroll 1
  for (unsigned int i = 0; i < (1u << 22) && v < target; i++) asm volatile("ld.relaxed.gpu.global.u32 %0, [%1];" : "=r"(v) : "l"(p) : "memory");
}
__device__ __forceinline__ void fence_proxy_async_global() { asm volatile("fence.proxy.async.global;" ::: "memory"); }

#define H_SPLIT 1
#define X_DLY 1200
#define W_DLY 1900
#define W_FIRST 2200
#define PRE_B 2
template <int J0, int J1>
__device__ __forceinline__ void load_parts(float2 (&pa)[J1 - J0][4], int t2) {
  #pragma unroll
  for (int j = J0; j < J1; j++)
    #pragma unroll
    for (int k = 0; k < 4; k++)
      asm volatile("ld.relaxed.gpu.global.v2.f32 {%0, %1}, [%2];" : "=f"(pa[j - J0][k].x), "=f"(pa[j - J0][k].y)
                   : "l"(g_modpart + k * 2 * T_D + (t2 >> 7) * T_D + j * 256 + (t2 & 127) * 2) : "memory");
}
template <int J0, int J1>
__device__ __forceinline__ void finish_parts(float2 (&pa)[J1 - J0][4], bool loaded, int t2, uint32_t tab) {
  #pragma unroll 1
  for (unsigned int spin = 0; spin < (1u << 22); spin++) {
    if (!loaded) load_parts<J0, J1>(pa, t2);
    loaded = false;
    bool ok = true;
    #pragma unroll
    for (int j = 0; j < J1 - J0; j++)
      #pragma unroll
      for (int k = 0; k < 4; k++) ok &= (__float_as_uint(pa[j][k].x) != 0u) & (__float_as_uint(pa[j][k].y) != 0u);
    if (__all_sync(0xffffffffu, ok)) break;
  }
  #pragma unroll
  for (int j = J0; j < J1; j++) {
    const float2* q = pa[j - J0];
    const uint32_t m = pack_bf16(((q[0].x + q[1].x) + q[2].x) + q[3].x, ((q[0].y + q[1].y) + q[2].y) + q[3].y);
    sts_u32(tab + (t2 >> 7) * 2048 + j * 512 + (t2 & 127) * 4, t2 >= 128 ? badd2(m, 0x3F803F80u) : m);
  }
}
__device__ __forceinline__ int head_cb(uint32_t bid) { return (bid & 16) | ((bid & 3) << 2) | ((bid >> 2) & 3); }
__device__ __forceinline__ void head_phase(uint32_t bid, uint32_t scr, uint32_t xs, uint32_t b_x, uint32_t b_go, uint32_t b_head, int t2, uint32_t zero, const bf16* __restrict__ cvec, const bf16* __restrict__ w_mod) {
  const int lane = t2 & 31, w8 = t2 >> 5;
  const int cb = head_cb(bid), ks = bid >> 5;
  const bool early = (cb & 15) < 4 * H_SPLIT;
  const uint32_t ws = (xs - 32768 + (t2 >> 3) * 128 + (((t2 ^ (t2 >> 3)) & 7) << 4)) ^ zero;
  const float cv = __bfloat162float(cvec[ks * 256 + t2]);
  const bf16* wsrc = w_mod + (size_t)(ks * 256 + (t2 >> 3)) * (6 * T_D) + cb * 64 + (t2 & 7) * 8;
  if (early) {
    const uint64_t pol = policy_evict_first();
    #pragma unroll 2
    for (int i = 0; i < 8; i++)
      asm volatile("cp.async.cg.shared.global.L2::cache_hint [%0], [%1], 16, %2;" :: "r"(ws + i * 4096), "l"(wsrc + (size_t)i * 32 * 6 * T_D), "l"(pol) : "memory");
  }
  sts_f32(scr + t2 * 4, silu_bf(cv));
  named_bar_sync(6, 384);
  TL_MARK2(1, t2 == 0);
  uint4 xv[2][4];
  uint32_t mb2[2], ih[2], il[2];
  auto norm = [&](int j) {
    #pragma unroll
    for (int r = 0; r < 2; r++) {
      xv[r][j].x = ln_norm2b(xv[r][j].x, mb2[r], ih[r], il[r]); xv[r][j].y = ln_norm2b(xv[r][j].y, mb2[r], ih[r], il[r]);
      xv[r][j].z = ln_norm2b(xv[r][j].z, mb2[r], ih[r], il[r]); xv[r][j].w = ln_norm2b(xv[r][j].w, mb2[r], ih[r], il[r]);
    }
  };
  auto modulate = [&](int j) {
    const uint4 sa = lds_u32x4(scr + 8192 + j * 512 + lane * 16), c1 = lds_u32x4(scr + 8192 + 2048 + j * 512 + lane * 16);
    #pragma unroll
    for (int r = 0; r < 2; r++) {
      xv[r][j].x = badd2(bmul2(xv[r][j].x, c1.x), sa.x); xv[r][j].y = badd2(bmul2(xv[r][j].y, c1.y), sa.y);
      xv[r][j].z = badd2(bmul2(xv[r][j].z, c1.z), sa.z); xv[r][j].w = badd2(bmul2(xv[r][j].w, c1.w), sa.w);
    }
  };
  auto store = [&](int j) {
    #pragma unroll
    for (int r = 0; r < 2; r++) *reinterpret_cast<uint4*>(g_h + (size_t)(bid * 16 + 2 * w8 + r) * T_D + j * 256 + lane * 8) = xv[r][j];
  };
  #pragma unroll 1
  for (int ph = 0; ph < 2; ph++) {
    if ((ph == 0) == early) {
      asm volatile("cp.async.wait_all;" ::: "memory");
      if (!early) mbar_wait(b_x + 168, 0);
      float acc[8];
      #pragma unroll
      for (int j = 0; j < 8; j++) acc[j] = 0.f;
      #pragma unroll
      for (int i = 0; i < 8; i++) fma8(acc, lds_f32(scr + ((t2 >> 3) + 32 * i) * 4), lds_u32x4(ws + i * 4096));
      #pragma unroll
      for (int j = 0; j < 4; j++) { const bool up = lane & 16; acc[j] = (up ? acc[4 + j] : acc[j]) + __shfl_xor_sync(0xffffffffu, up ? acc[j] : acc[4 + j], 16); }
      #pragma unroll
      for (int j = 0; j < 2; j++) { const bool up = lane & 8; acc[j] = (up ? acc[2 + j] : acc[j]) + __shfl_xor_sync(0xffffffffu, up ? acc[j] : acc[2 + j], 8); }
      sts_f32x2(scr + 1024 + w8 * 256 + (lane & 7) * 32 + (lane >> 3) * 8, acc[0], acc[1]);
      named_bar_sync(5, 256);
      if (t2 < 64) {
        float sum = 0.f;
        #pragma unroll
        for (int i = 0; i < 8; i++) sum += lds_f32(scr + 1024 + i * 256 + t2 * 4);
        st_tagged(g_modpart + ks * 2 * T_D + cb * 64 + t2, sum);
        TL_MARK2(early ? 2 : 6, t2 == 0);
      }
    } else {
      float2 pa[H_SPLIT][4];
      mbar_wait(b_x, 0);
      TL_MARK2(18, t2 == 0);
      load_parts<0, H_SPLIT>(pa, t2);
      #pragma unroll
      for (int r = 0; r < 2; r++)
        #pragma unroll
        for (int j = 0; j < 4; j++) xv[r][j] = lds_u32x4(xs + (2 * w8 + r) * 2048 + j * 512 + lane * 16);
  {
    float st[4] = {0.f, 0.f, 0.f, 0.f};
    #pragma unroll
    for (int r = 0; r < 2; r++)
      #pragma unroll
      for (int j = 0; j < 4; j++) {
        float v[8];
        unpack8(xv[r][j], v);
        st[2 * r] += ((v[0] + v[1]) + (v[2] + v[3])) + ((v[4] + v[5]) + (v[6] + v[7]));
        st[2 * r + 1] += fmaf(v[0], v[0], fmaf(v[1], v[1], fmaf(v[2], v[2], v[3] * v[3]))) + fmaf(v[4], v[4], fmaf(v[5], v[5], fmaf(v[6], v[6], v[7] * v[7])));
      }
    #pragma unroll
    for (int k = 0; k < 2; k++) { const bool up = lane & 16; st[k] = (up ? st[2 + k] : st[k]) + __shfl_xor_sync(0xffffffffu, up ? st[k] : st[2 + k], 16); }
    #pragma unroll
    for (int o = 8; o > 0; o >>= 1) { st[0] += __shfl_xor_sync(0xffffffffu, st[0], o); st[1] += __shfl_xor_sync(0xffffffffu, st[1], o); }
    const float mean = st[0] * (1.0f / T_D);
    const float inv = rcp_approx(rbf(sqrt_approx(rbf(rbf(fmaxf(fmaf(-mean, mean, st[1] * (1.0f / T_D)), 0.f)) + 1e-05f))));
    const uint32_t m = pack_bf16(mean, mean), h = pack_bf16(inv - rbf(inv), inv);
    #pragma unroll
    for (int r = 0; r < 2; r++) {
      mb2[r] = __shfl_sync(0xffffffffu, m, 16 * r);
      const uint32_t hr = __shfl_sync(0xffffffffu, h, 16 * r);
      ih[r] = __byte_perm(hr, hr, 0x3232); il[r] = __byte_perm(hr, hr, 0x1010);
    }
  }
      #pragma unroll
      for (int j = 0; j < H_SPLIT; j++) norm(j);
      TL_MARK2(5, t2 == 0);
      finish_parts<0, H_SPLIT>(pa, true, t2, scr + 8192);
      named_bar_sync(5, 256);
      TL_MARK2(7, t2 == 0);
      #pragma unroll
      for (int j = 0; j < H_SPLIT; j++) { modulate(j); store(j); }
      named_bar_arrive(9, 288);
    }
  }
  #pragma unroll
  for (int j = H_SPLIT; j < 4; j++) norm(j);
  float2 pb[4 - H_SPLIT][4];
  finish_parts<H_SPLIT, 4>(pb, false, t2, scr + 8192);
  named_bar_sync(5, 256);
  TL_MARK2(17, t2 == 0);
  #pragma unroll
  for (int j = H_SPLIT; j < 4; j++) modulate(j);
  __syncwarp();
  if (lane == 0) mbar_arrive(b_head + (xv[1][3].w & zero));
  mbar_wait(b_go, 0);
  #pragma unroll
  for (int j = H_SPLIT; j < 4; j++) store(j);
  named_bar_arrive(8, 288);
}

#define MOD_AT (b_empty + 8)
#define MOD_SPLIT 20
__device__ __forceinline__ void mod_rest(uint32_t bid, uint32_t scr, uint32_t b_go, int t, const bf16* __restrict__ cvec, const bf16* __restrict__ w_mod, const bf16* __restrict__ w_r) {
  const int lane = t & 31;
  #pragma unroll 1
  for (int i = t; i < T_D / 2; i += 64) {
    const uint32_t c2 = *reinterpret_cast<const uint32_t*>(cvec + 2 * i);
    sts_u32(scr + i * 4, pack_bf16(silu_bf(bflo(c2)), silu_bf(bfhi(c2))));
  }
  named_bar_sync(11, 64);
  const bf16* wp = w_mod + (size_t)(2 * (t >> 2)) * (6 * T_D) + 2 * T_D + bid * 32 + (t & 3) * 8;
  float acc[8];
  #pragma unroll
  for (int i = 0; i < 8; i++) acc[i] = 0.f;
  #pragma unroll 1
  for (int i = 0; i < 32; i += 2) {
    if (i == MOD_SPLIT) mbar_wait_long(b_go, 0);
    const uint4 w0 = ldg_nc_v4(wp), w1 = ldg_nc_v4(wp + 6 * T_D), w2 = ldg_nc_v4(wp + 32 * 6 * T_D), w3 = ldg_nc_v4(wp + 33 * 6 * T_D);
    wp += 64 * 6 * T_D;
    const uint32_t s0 = lds_u32(scr + (i * 16 + (t >> 2)) * 4), s1 = lds_u32(scr + (i * 16 + 16 + (t >> 2)) * 4);
    fma8(acc, bflo(s0), w0); fma8(acc, bfhi(s0), w1); fma8(acc, bflo(s1), w2); fma8(acc, bfhi(s1), w3);
  }
  #pragma unroll
  for (int j = 0; j < 4; j++) { const bool up = lane & 16; acc[j] = (up ? acc[4 + j] : acc[j]) + __shfl_xor_sync(0xffffffffu, up ? acc[j] : acc[4 + j], 16); }
  #pragma unroll
  for (int j = 0; j < 2; j++) { const bool up = lane & 8; acc[j] = (up ? acc[2 + j] : acc[j]) + __shfl_xor_sync(0xffffffffu, up ? acc[j] : acc[2 + j], 8); }
  { const bool up = lane & 4; acc[0] = (up ? acc[1] : acc[0]) + __shfl_xor_sync(0xffffffffu, up ? acc[0] : acc[1], 4); }
  if (t >= 32) sts_f32(scr + 2048 + lane * 4, acc[0]);
  named_bar_sync(11, 64);
  if (__shfl_sync(0xffffffffu, t, 0) < 32) {
    const int kind = bid >> 5;
    float v = rbf(acc[0] + lds_f32(scr + 2048 + lane * 4));
    const int col = (bid & 31) * 32 + (lane & 3) * 8 + (lane >> 2);
    uint8_t* dst = g_col + (col >> 7) * 1536;
    if (kind == 2) v = rbf(1.0f + v);
    float vw = v * __bfloat162float(w_r[col]);
    if (kind == 2) {
      const int c = col & 127, i = (c & ~15) + ((c >> 1) & 3) * 4 + ((c >> 3) & 1) * 2 + (c & 1);
      reinterpret_cast<bf16*>(dst)[i] = __float2bfloat16_rn(vw);
      reinterpret_cast<bf16*>(dst)[128 + i] = __float2bfloat16_rn(vw - rbf(vw));
    }
    reinterpret_cast<bf16*>(dst + 512 + (kind & 1) * 512 + (kind >> 1) * 256)[col & 127] = __float2bfloat16_rn(v);
    #pragma unroll
    for (int o = 16; o > 0; o >>= 1) vw += __shfl_xor_sync(0xffffffffu, vw, o);
    if (lane == 0 && (kind == 1 || kind == 2)) g_scal[95 - bid] = vw;
  }
  #pragma unroll 1
  for (int i = bid * 64 + t; i < (int)(sizeof(g_mail) / 16); i += 128 * 64) reinterpret_cast<uint4*>(&g_mail)[i] = make_uint4(0u, 0u, 0u, 0u);
  named_bar_sync(11, 64);
  if (t == 0) red_release_add(&g_hcnt[0], 1u);
}

constexpr int AT_NBLK = T_SEQ / 128;
constexpr float AT_HEAD = 7.0f;
#define WO_LATE 12
#define QP_STAG 3
#define AT_SPLIT 28
#define AT_PIN 12
#define PINB 4
constexpr int AT_NFULL = 124;
constexpr int AT_PREG = 40, AT_CREG = 232;
constexpr uint32_t AT_SQ = 5 * 32768;
constexpr float AT_C = 0.08838834764831845f * 1.4426950408889634f;
constexpr float AT_RAW_LO = -16.0f, AT_RAW_HI = 24.0f;
constexpr float AT_RAW_SUM = 281474976710656.0f, AT_RAW_MIN = 9.094947017729282e-13f;
constexpr uint32_t AT_SBAR = AT_SQ + 65536 + 256;
constexpr uint32_t AT_SMEM = AT_SQ + 65536 + 3072;

__device__ __forceinline__ uint32_t ring_slot(uint32_t t) { return t - 5u * ((t * 205u) >> 10); }
__device__ __forceinline__ uint32_t qp_pos(uint32_t j, uint32_t it) { return 4u * it + (j & 3u) + ((j & 3u) == 3u ? it : 0u); }
__device__ __forceinline__ uint32_t ring_par(uint32_t t) { return ((t * 205u) >> 10) & 1u; }
__device__ __forceinline__ void softmax_rowmax(const float (&s)[64], float& mx0, float& mx1) {
  float a0 = fmaxf(s[0], s[1]), a1 = fmaxf(s[4], s[5]), a2 = fmaxf(s[8], s[9]), a3 = fmaxf(s[12], s[13]);
  float b0 = fmaxf(s[2], s[3]), b1 = fmaxf(s[6], s[7]), b2 = fmaxf(s[10], s[11]), b3 = fmaxf(s[14], s[15]);
  #pragma unroll
  for (int j = 4; j < 16; j += 4) {
    a0 = fmaxf(a0, fmaxf(s[4 * j + 0], s[4 * j + 1]));  b0 = fmaxf(b0, fmaxf(s[4 * j + 2], s[4 * j + 3]));
    a1 = fmaxf(a1, fmaxf(s[4 * j + 4], s[4 * j + 5]));  b1 = fmaxf(b1, fmaxf(s[4 * j + 6], s[4 * j + 7]));
    a2 = fmaxf(a2, fmaxf(s[4 * j + 8], s[4 * j + 9]));  b2 = fmaxf(b2, fmaxf(s[4 * j + 10], s[4 * j + 11]));
    a3 = fmaxf(a3, fmaxf(s[4 * j + 12], s[4 * j + 13])); b3 = fmaxf(b3, fmaxf(s[4 * j + 14], s[4 * j + 15]));
  }
  mx0 = fmaxf(fmaxf(a0, a1), fmaxf(a2, a3));
  mx1 = fmaxf(fmaxf(b0, b1), fmaxf(b2, b3));
  mx0 = fmaxf(mx0, __shfl_xor_sync(0xffffffffu, mx0, 1));
  mx1 = fmaxf(mx1, __shfl_xor_sync(0xffffffffu, mx1, 1));
  mx0 = fmaxf(mx0, __shfl_xor_sync(0xffffffffu, mx0, 2));
  mx1 = fmaxf(mx1, __shfl_xor_sync(0xffffffffu, mx1, 2));
}
__device__ __forceinline__ void softmax_sub(float (&s)[64], float mc0, float mc1) {
  #pragma unroll
  for (int j = 0; j < 16; j++) { s[4 * j] -= mc0; s[4 * j + 1] -= mc0; s[4 * j + 2] -= mc1; s[4 * j + 3] -= mc1; }
}
template <int LO, int HI>
__device__ __forceinline__ void softmax_exp(float (&s)[64]) {
  #pragma unroll
  for (int i = LO; i < HI; i++) s[i] = ex2_approx(s[i]);
}
__device__ __forceinline__ bool softmax_mode(const float (&s)[64], float& mc0, float& mc1) {
  softmax_rowmax(s, mc0, mc1);
  const bool raw = __all_sync(0xffffffffu, mc0 >= AT_RAW_LO && mc0 <= AT_RAW_HI && mc1 >= AT_RAW_LO && mc1 <= AT_RAW_HI);
  mc0 += AT_HEAD; mc1 += AT_HEAD;
  return raw;
}
__device__ __forceinline__ void rowsum_p(const uint32_t (&p)[32], uint32_t& t0, uint32_t& t1) {
  uint32_t a[16];
  #pragma unroll
  for (int i = 0; i < 8; i++) { a[2 * i] = badd2(p[4 * i], p[4 * i + 2]); a[2 * i + 1] = badd2(p[4 * i + 1], p[4 * i + 3]); }
  #pragma unroll
  for (int i = 0; i < 4; i++) { a[2 * i] = badd2(a[4 * i], a[4 * i + 2]); a[2 * i + 1] = badd2(a[4 * i + 1], a[4 * i + 3]); }
  t0 = badd2(badd2(a[0], a[2]), badd2(a[4], a[6]));
  t1 = badd2(badd2(a[1], a[3]), badd2(a[5], a[7]));
}
__device__ __forceinline__ void add_rowsum(const uint32_t (&p)[32], float& l0, float& l1) {
  uint32_t t0, t1;
  rowsum_p(p, t0, t1);
  l0 += bflo(t0) + bfhi(t0); l1 += bflo(t1) + bfhi(t1);
}
__device__ __forceinline__ void pack_p(uint32_t (&p)[32], const float (&s)[64]) {
  #pragma unroll
  for (int i = 0; i < 32; i++) p[i] = pack_bf16(s[2 * i], s[2 * i + 1]);
}
__device__ __noinline__ void attn_rows_exact(uint32_t bid, uint32_t sq, uint32_t so, int hsel, const bf16* __restrict__ kh, const bf16* __restrict__ vh) {
  const int warp = (threadIdx.x >> 5) & 3, lane = threadIdx.x & 31;
  const size_t hofs = (size_t)((bid < 128 ? bid >> 4 : 15) * 2 + hsel) * T_SEQ * T_DH;
  kh += hofs; vh += hofs;
  #pragma unroll 1
  for (int r = 16 * warp; r < 16 * warp + 16; r++) {
    const uint32_t ad = (lane >> 4) * 16384 + r * 128 + ((((lane & 15) >> 1) ^ (r & 7)) << 4) + (lane & 1) * 8;
    uint2 qv; asm volatile("ld.shared.v2.u32 {%0, %1}, [%2];" : "=r"(qv.x), "=r"(qv.y) : "r"(sq + ad) : "memory");
    const float q0 = bflo(qv.x), q1 = bfhi(qv.x), q2 = bflo(qv.y), q3 = bfhi(qv.y);
    float m = -INFINITY, l = 0.f, o0 = 0.f, o1 = 0.f, o2 = 0.f, o3 = 0.f;
    #pragma unroll 1
    for (int key = 0; key < T_SEQ; key++) {
      const uint2 kv = *reinterpret_cast<const uint2*>(kh + (size_t)key * T_DH + lane * 4);
      const uint2 vv = *reinterpret_cast<const uint2*>(vh + (size_t)key * T_DH + lane * 4);
      float sc = (q0 * bflo(kv.x) + q1 * bfhi(kv.x)) + (q2 * bflo(kv.y) + q3 * bfhi(kv.y));
      #pragma unroll
      for (int o = 16; o > 0; o >>= 1) sc += __shfl_xor_sync(0xffffffffu, sc, o);
      const float mn = fmaxf(m, sc);
      const float al = (m == mn) ? 1.0f : ex2_approx(m - mn), p = rbf(ex2_approx(sc - mn));
      m = mn;
      l = fmaf(l, al, p);
      o0 = fmaf(o0, al, p * bflo(vv.x)); o1 = fmaf(o1, al, p * bfhi(vv.x));
      o2 = fmaf(o2, al, p * bflo(vv.y)); o3 = fmaf(o3, al, p * bfhi(vv.y));
    }
    const float inv = rcp_approx(l);
    asm volatile("st.shared.v2.u32 [%0], {%1, %2};" :: "r"(so + ad), "r"(pack_bf16(o0 * inv, o1 * inv)), "r"(pack_bf16(o2 * inv, o3 * inv)) : "memory");
  }
}
__device__ __forceinline__ void issue_qk(float (&s)[64], const uint32_t (&q)[32], uint32_t k_lo) {
  wgmma_fence();
  wgmma_m64n128k16_rs<0>(s, q[0], q[1], q[2], q[3], k_lo, 0);
  wgmma_m64n128k16_rs<2>(s, q[4], q[5], q[6], q[7], k_lo, 1);
  wgmma_m64n128k16_rs<4>(s, q[8], q[9], q[10], q[11], k_lo, 1);
  wgmma_m64n128k16_rs<6>(s, q[12], q[13], q[14], q[15], k_lo, 1);
  wgmma_m64n128k16_rs<1024>(s, q[16], q[17], q[18], q[19], k_lo, 1);
  wgmma_m64n128k16_rs<1026>(s, q[20], q[21], q[22], q[23], k_lo, 1);
  wgmma_m64n128k16_rs<1028>(s, q[24], q[25], q[26], q[27], k_lo, 1);
  wgmma_m64n128k16_rs<1030>(s, q[28], q[29], q[30], q[31], k_lo, 1);
  wgmma_commit();
}
__device__ __forceinline__ void issue_pv(float (&o)[64], const uint32_t (&p)[32], uint32_t v_lo, int accumulate) {
  wgmma_fence();
  wgmma_m64n128k16_rs_tb<0>(o, p[0], p[1], p[2], p[3], v_lo, accumulate);
  wgmma_m64n128k16_rs_tb<128>(o, p[4], p[5], p[6], p[7], v_lo, 1);
  wgmma_m64n128k16_rs_tb<256>(o, p[8], p[9], p[10], p[11], v_lo, 1);
  wgmma_m64n128k16_rs_tb<384>(o, p[12], p[13], p[14], p[15], v_lo, 1);
  wgmma_m64n128k16_rs_tb<512>(o, p[16], p[17], p[18], p[19], v_lo, 1);
  wgmma_m64n128k16_rs_tb<640>(o, p[20], p[21], p[22], p[23], v_lo, 1);
  wgmma_m64n128k16_rs_tb<768>(o, p[24], p[25], p[26], p[27], v_lo, 1);
  wgmma_m64n128k16_rs_tb<896>(o, p[28], p[29], p[30], p[31], v_lo, 1);
  wgmma_commit();
}
__device__ __forceinline__ void block_end(uint32_t zero, uint32_t bar) {
  #pragma unroll 1
  for (uint32_t i = 0; i < zero; i++) mbar_arrive(bar);
}
__device__ __forceinline__ void rescale_o(float (&o)[64], float al0, float al1) {
  #pragma unroll
  for (int j = 0; j < 16; j++) { o[4 * j] *= al0; o[4 * j + 1] *= al0; o[4 * j + 2] *= al1; o[4 * j + 3] *= al1; }
}

__device__ __forceinline__ void stage_o(const float (&o)[64], float i0, float i1, uint32_t dst, int lane) {
  #pragma unroll
  for (int J = 0; J < 16; J += 2)
    stmatrix_x4(dst + (J >> 3) * 16384 + ((((J & 7) + (lane >> 4)) ^ (lane & 7)) << 4),
                pack_bf16(o[4 * J + 0] * i0, o[4 * J + 1] * i0), pack_bf16(o[4 * J + 2] * i1, o[4 * J + 3] * i1),
                pack_bf16(o[4 * J + 4] * i0, o[4 * J + 5] * i0), pack_bf16(o[4 * J + 6] * i1, o[4 * J + 7] * i1));
}
__device__ __forceinline__ bool finish_l(float& l0, float& l1) {
  l0 += __shfl_xor_sync(0xffffffffu, l0, 1); l1 += __shfl_xor_sync(0xffffffffu, l1, 1);
  l0 += __shfl_xor_sync(0xffffffffu, l0, 2); l1 += __shfl_xor_sync(0xffffffffu, l1, 2);
  const bool redo = __any_sync(0xffffffffu, !(l0 <= AT_RAW_SUM && l1 <= AT_RAW_SUM && l0 >= AT_RAW_MIN && l1 >= AT_RAW_MIN));
  l0 = rcp_approx(l0); l1 = rcp_approx(l1);
  return redo;
}
template <int J0>
__device__ __forceinline__ void stage_q(const float (&acc)[128], float c, uint32_t dst, int lane) {
  #pragma unroll
  for (int J = J0; J < J0 + 16; J += 2)
    stmatrix_x4(dst + (J >> 3) * 16384 + ((((J & 7) + (lane >> 4)) ^ (lane & 7)) << 4),
                pack_bf16(acc[4 * J + 0] * c, acc[4 * J + 1] * c), pack_bf16(acc[4 * J + 2] * c, acc[4 * J + 3] * c),
                pack_bf16(acc[4 * J + 4] * c, acc[4 * J + 5] * c), pack_bf16(acc[4 * J + 6] * c, acc[4 * J + 7] * c));
}
__device__ __forceinline__ void store_o(const CUtensorMap* tmO, uint32_t src, int head, int row) {
  tma_store_2d(tmO, src, head * T_DH, row);
  tma_store_2d(tmO, src + 16384, head * T_DH + 64, row);
  bulk_commit();
}
__device__ __forceinline__ void mma_bf16(float (&d)[4], uint32_t a0, uint32_t a1, uint32_t a2, uint32_t a3, uint32_t b0, uint32_t b1) {
  asm volatile("mma.sync.aligned.m16n8k16.row.col.f32.bf16.bf16.f32 {%0, %1, %2, %3}, {%4, %5, %6, %7}, {%8, %9}, {%0, %1, %2, %3};"
               : "+f"(d[0]), "+f"(d[1]), "+f"(d[2]), "+f"(d[3]) : "r"(a0), "r"(a1), "r"(a2), "r"(a3), "r"(b0), "r"(b1));
}
struct GemvSel { uint32_t lo0, hi0, lo1, hi1; };
__device__ __forceinline__ GemvSel gemv_sel(int lane) {
  const uint32_t lo = (lane & 8) ? 0x1044u : 0x4410u, hi = (lane & 8) ? 0x3244u : 0x4432u;
  GemvSel s; s.lo0 = (lane & 16) ? 0x4444u : lo; s.hi0 = (lane & 16) ? 0x4444u : hi; s.lo1 = (lane & 16) ? lo : 0x4444u; s.hi1 = (lane & 16) ? hi : 0x4444u;
  return s;
}
#define GEMV_B0(j, h, s) __byte_perm((j) < 2 ? (h).x : (h).y, 0u, ((j) & 1) ? (s).hi0 : (s).lo0)
#define GEMV_B1(j, h, s) __byte_perm((j) < 2 ? (h).x : (h).y, 0u, ((j) & 1) ? (s).hi1 : (s).lo1)
__device__ __forceinline__ float4 gemv_out(const float (&d)[4], int lane) {
  const bool tk = lane & 1;
  const float r0 = __shfl_xor_sync(0xffffffffu, tk ? d[0] : d[1], 1), r1 = __shfl_xor_sync(0xffffffffu, tk ? d[2] : d[3], 1);
  return tk ? make_float4(r0, d[1], r1, d[3]) : make_float4(d[0], r0, d[2], r1);
}
#define OG_XN 4
#define OG_XB 5
#define OG_NG 8
#define PUT_N 2
#define H_STAG 2
#define AL_P 60
#define AL_SLEEP 1200
#define AL_MAX 800
#define POLL_NS 500
#define OG_PROF 0xDDCBAA98u
#define RK_P 24
__host__ __device__ constexpr int og_pre(int tile) { return (OG_PROF >> ((tile >> 4) * 4)) & 15; }
constexpr int OG_PRE2 = og_pre(127), OG_HSUM = og_pre(0) + og_pre(16) + og_pre(32) + og_pre(48) + og_pre(64) + og_pre(80) + og_pre(96);
#define OG_JOBS 7
#define OG_GRP 6
#define LD_FIRST 2
#define LD_STAG (OG_GRP / 2)
constexpr int OG_ST = 5, OG_NKB = T_DQKV / 64 - og_pre(0), OG_MOE = T_F / 32;
__device__ __forceinline__ int pre_kb(int i) { return (i >> 1) * 4 + (i & 1); }
__device__ __forceinline__ int own_kb(int i, int pre) { return i < (pre & ~1) ? pre_kb(i) + 2 : i + pre; }
static_assert(LD_FIRST + LD_STAG <= OG_XB && OG_XB < LD_FIRST + OG_GRP, "the extra tile belongs to segment 1");
constexpr int OG_POS = 8;
constexpr uint32_t OG_STAGE = 32768;
constexpr uint32_t OG_SCOL = AT_SBAR + 512;
constexpr uint32_t OG_SMISC = AT_SBAR + 2048;
constexpr uint32_t OG_SWD = AT_SQ, OG_PSLOT = AT_SQ;
constexpr uint32_t OG_XSLOT = AT_SQ + 32768;
constexpr uint32_t OG_OSLOT = 1 * OG_STAGE;
constexpr uint32_t OG_SRED = 3 * OG_STAGE;
constexpr uint32_t OG_SH2 = OG_SRED + 24576;
constexpr uint32_t OG_SSTAT = OG_SRED + 16384;
constexpr uint32_t OG_SGU = OG_SRED + 8192;
constexpr uint32_t OG_SFIN = OG_SGU + 256;
#define OGM 2
#define OG_MT(b) ((((b) >> OGM) & 15) ^ (((b) & 64) ? 15 : 0))
#define OG_NT(b) (((b) & ((1 << OGM) - 1)) + (((b) >> (4 + OGM)) << OGM))
__device__ __forceinline__ int tail_tile(uint32_t sbase) { mbar_wait_long(sbase + AT_SBAR + 336, 0); return (int)lds_u32(sbase + AT_SBAR + 408); }
#define TAIL_SETUP \
  const uint32_t bar_full = sbase + AT_SBAR, bar_empty = bar_full + 40; \
  const uint32_t bar_wd = bar_full + 168, bar_col = bar_full + 176, bar_out = bar_full + 184, bar_end = bar_full + 192; \
  const uint32_t bar_key = bar_full + 200, bar_h2 = bar_full + 208, bar_sel = bar_full + 216; \
  const int mt = OG_MT(tb), nt = OG_NT(tb); \
  const int m0 = mt * 128, n0 = nt * 128; \
  const bool has_moe = (int)bid < OG_MOE; \
  (void)bar_empty; (void)bar_wd; (void)bar_col; (void)bar_out; (void)bar_end; (void)bar_key; (void)bar_h2; (void)bar_sel; (void)m0; (void)n0; (void)has_moe;

__device__ __forceinline__ void tail_producer(uint32_t bid, uint32_t sbase, uint32_t ph, uint64_t pol, const CUtensorMap* tmA, const CUtensorMap* tmB, const CUtensorMap* tmD) {
  const int tb = tail_tile(sbase);
  TAIL_SETUP
  uint32_t stage = OG_POS % OG_ST;
  int kb = 0, xk = OG_XB;
  uint32_t xp = 1;
  #pragma unroll 1
  for (int seg = 0; seg < 2; seg++) {
    mbar_wait(bar_full + 264 + 80 * seg, 0);
    fence_proxy_async_global();
    const int end = 32 + 32 * seg - og_pre(tb);
    #pragma unroll 1
    for (; kb < end; kb++) {
      const bool xb = kb == xk;
      const uint32_t fb = xb ? bar_full + 360 : bar_full + 8 * stage, sa = sbase + (xb ? 5 : stage) * OG_STAGE;
      const int k0 = own_kb(kb, og_pre(tb)) * 64;
      if (xb) {
        mbar_wait(bar_full + 80, bid < AT_NFULL);
        mbar_wait(bar_full + 368, xp);
        xp ^= 1;
        if (xk < OG_XB + (OG_XN - 1) * OG_GRP) xk += OG_GRP;
      }
      mbar_wait_long(xb ? bar_full + 304 : bar_empty + 8 * stage, xb ? 0 : ph);
      mbar_expect_tx(fb, OG_STAGE);
      tma_load_3d_hint(sa + 16384, tmB, k0, 2 * nt, fb, pol);
      tma_load_2d_hint(sa, tmA, k0, m0, fb, pol);
      if (!xb && ++stage == OG_ST) { stage = 0; ph ^= 1; }
    }
  }
  if (has_moe) {
    stage += stage & 1;
    mbar_wait(bar_empty + 8 * stage, ph);
    mbar_expect_tx(bar_wd, OG_STAGE);
    tma_load_3d_hint(sbase + stage * OG_STAGE, tmD, bid * 32, 8, bar_wd, pol);
  }
}

__device__ __forceinline__ uint32_t out2(uint32_t x1, uint32_t mb2, uint32_t ih, uint32_t il, uint32_t c1, uint32_t sb, uint32_t gb) {
  const uint32_t h2 = badd2(bmul2(ln_norm2b(x1, mb2, ih, il), c1), sb);
  return badd2(x1, bmul2(gb, bfma2(h2, 0u, h2)));
}
#define X_PACE 200
#define Y_SLACK 96
#define OG_STAG 3
#define POLL_NS2 100
#define WD_SKIP 1
#define AL_ADD 380
#define WD_PACE 300
__device__ __forceinline__ void tail_exchange(uint32_t bid, uint32_t sbase, const bf16* __restrict__ w_down, const bf16* __restrict__ w_r, const bf16* __restrict__ x, bf16* __restrict__ out) {
    const int lane = threadIdx.x & 31, wi = __shfl_sync(0xffffffffu, threadIdx.x >> 5, 0);
    if (wi == 3) {
      uint32_t a = bid, b = 0u;
      if (bid < AT_NFULL) mbar_wait_long(sbase + AT_SBAR + 312, 0);
      if (bid < OG_MOE) {
        asm volatile("mov.u32 %0, %%globaltimer_lo;" : "=r"(a));
        if (lane == 0 && (bid & 15) == 0) asm volatile("st.relaxed.gpu.global.u32 [%0], %1;" :: "l"(g_hcnt + 8 + (bid >> 4)), "r"((a & ~15u) | 8u | (bid >> 4)) : "memory");
        #pragma unroll 1
        for (unsigned int spin = 0; spin < (1u << 22) && __any_sync(0xffffffffu, b == 0u); spin++) {
          __nanosleep(200);
          asm volatile("ld.relaxed.gpu.global.u32 %0, [%1];" : "=r"(b) : "l"(g_hcnt + 8 + min(lane, 6)) : "memory");
        }
        a = __popc(__ballot_sync(0xffffffffu, b < __shfl_sync(0xffffffffu, b, bid >> 4)) & 127u) * 16 + (bid & 15);
      }
      if (lane == 0) {
        sts_u32(sbase + AT_SBAR + 408, a);
        mbar_arrive(sbase + AT_SBAR + 336);
        b = 0u;
        if (bid < AT_NFULL) {
          unsigned int* tm = g_hcnt + 32 * (1 + (bid >> 4)) + 8;
          mbar_wait_long(sbase + AT_SBAR + 312, 1);
          asm volatile("mov.u32 %0, %%globaltimer_lo;" : "=r"(a));
          asm volatile("red.relaxed.gpu.global.max.u32 [%0], %1;" :: "l"(tm), "r"(a) : "memory");
          __nanosleep(AL_SLEEP);
          asm volatile("ld.relaxed.gpu.global.u32 %0, [%1];" : "=r"(b) : "l"(tm) : "memory");
          b -= a;
        }
        sts_u32(sbase + AT_SBAR + 412, b < AL_MAX ? b * 13 / 8 : 0u);
        mbar_arrive(sbase + AT_SBAR + 320);
      }
      named_bar_sync(15, 32);
    }
    const int tb = __shfl_sync(0xffffffffu, tail_tile(sbase), 0);
    TAIL_SETUP
    if (wi == 3) {
      mbar_wait_long(bar_full + 344, 0);
      float a = g_scal[lane], b = g_scal[32 + lane];
      #pragma unroll
      for (int i = 0; i < 3; i++) {
        const uint4 v = *reinterpret_cast<const uint4*>(g_col + nt * 1536 + i * 512 + lane * 16);
        sts_u32x4(sbase + OG_SCOL + i * 512 + lane * 16, v.x, v.y, v.z, v.w);
      }
      #pragma unroll
      for (int o = 16; o > 0; o >>= 1) { a += __shfl_xor_sync(0xffffffffu, a, o); b += __shfl_xor_sync(0xffffffffu, b, o); }
      if (lane == 0) sts_f32x2(sbase + OG_SMISC, a, b);
      const uint64_t pol = policy_evict_first();
      #pragma unroll 1
      for (int r = lane >> 4; r < 128; r += 4) {
        __nanosleep(X_PACE);
        #pragma unroll
        for (int j = 0; j < 4; j += 2)
          asm volatile("cp.async.cg.shared.global.L2::cache_hint [%0], [%1], 16, %2;" :: "r"(sbase + OG_XSLOT + (lane & 8) * 2048 + (r + j) * 128 + (((lane ^ (r + j)) & 7) << 4)),
                       "l"(x + (size_t)(m0 + r + j) * T_D + n0 + (lane & 15) * 8), "l"(pol) : "memory");
      }
      asm volatile("cp.async.wait_all;" ::: "memory");
      __syncwarp();
      if (lane == 0) mbar_arrive(bar_col);
    } else if (wi == 2) {
      if (elect_one()) {
        mbar_wait_long(bar_full + (has_moe ? 80 : 376), has_moe);
        #pragma unroll 1
        for (unsigned int i = 0; i < (1u << 20) && ld_acquire(&g_hcnt[32 * (1 + (tb >> 3)) + 4 + ((tb >> 1) & 3)]) == 0u; i++) __nanosleep((tb >> 4) == 6 ? POLL_NS2 : POLL_NS);
        TL_MARK2(23, true);
        fence_proxy_async_global();
        TL_MARK2(4, true);
        mbar_expect_tx(bar_full + 272, 32768);
        bulk_load_hint(sbase + OG_PSLOT, g_pre + tb * 2048, 32768, bar_full + 272, policy_evict_first());
      }
      named_bar_sync(14, 32);
      if (has_moe) {
        mbar_wait_long(bar_full + 376, 0);
        const uint64_t pol = policy_evict_first();
        #pragma unroll 1
        for (int r = 0; r < 32; r++) {
          if ((r & WD_SKIP) != WD_SKIP) __nanosleep(WD_PACE);
          #pragma unroll
          for (int j = 0; j < 2; j++)
            asm volatile("cp.async.cg.shared.global.L2::cache_hint [%0], [%1], 16, %2;" :: "r"(sbase + OG_SWD + (4 * j + (lane >> 3)) * 4096 + r * 128 + (((lane ^ r) & 7) << 4)),
                         "l"((const uint8_t*)w_down + (size_t)bid * 65536 + r * 2048 + j * 512 + lane * 16), "l"(pol) : "memory");
        }
        asm volatile("cp.async.wait_all;" ::: "memory");
        __syncwarp();
        if (lane == 0) mbar_arrive(bar_wd);
      }
    }
    const uint4 wrv = ldg_nc_v4(w_r + threadIdx.x * 8);
    mbar_wait_long(bar_end, 0);
    TL_MARK2(22, lane == 0);
    if (wi == 0) {
      uint32_t k1 = 0u, k2 = 0u;
      #pragma unroll 1
      for (unsigned int spin = 0; spin < (1u << 22) && __any_sync(0xffffffffu, k1 == 0u); spin++) asm volatile("ld.relaxed.gpu.global.u32 %0, [%1];" : "=r"(k1) : "l"(g_key + lane) : "memory");
      TL_MARK2(28, lane == 0);
      warp_top2(k1, k2);
      if (lane == 0) {
        const uint32_t r1 = 0xffffu - (k1 & 0xffffu), r2 = 0xffffu - (k2 & 0xffffu);
        sts_u32x4(sbase + OG_SMISC + 64, r1, r2, (r1 >> 7) * 2, (r2 >> 7) * 2 + ((r1 >> 7) == (r2 >> 7)));
        mbar_arrive(bar_sel);
      }
    } else if (wi < 3) {
          mbar_wait(bar_key, 0);
          const uint4 kk = lds_u32x4(sbase + OG_SSTAT + 1024 + lane * 16);
          uint32_t k1 = max(kk.x, kk.y), k2 = min(kk.x, kk.y);
          k2 = max(max(k2, min(kk.z, kk.w)), min(k1, max(kk.z, kk.w))); k1 = max(k1, max(kk.z, kk.w));
          warp_top2(k1, k2);
          if (wi == 1) {
            if (lane == 0) {
              if (nt == (mt & 7)) st_relaxed2(g_key + mt * 2, k1, k2);
              sts_u32x2(sbase + OG_SMISC + 96, (~k1 >> 4) & 7u, (~k2 >> 4) & 7u);
              mbar_arrive(bar_full + 352);
            }
            TL_MARK2(27, lane == 0);
          } else {
            const uint32_t r = (~((lane & 16) ? k2 : k1)) & 127u, ch = lane & 15;
            const uint2 st = lds_u32x2(sbase + OG_SSTAT + r * 8);
            const uint4 xc = lds_u32x4(sbase + OG_XSLOT + (ch >> 3) * 16384 + r * 128 + (((ch ^ r) & 7) << 4));
            const uint4 c1 = lds_u32x4(sbase + OG_SCOL + 768 + ch * 16), sh = lds_u32x4(sbase + OG_SCOL + 1024 + ch * 16);
            const float inr = __uint_as_float(st.y);
            float* dst = reinterpret_cast<float*>(g_cand + (mt * 2 + (lane >> 4)) * 256 + nt * 16 + ch);
            st_tagged4(dst + 512, __uint_as_float(ln_mod2(xc.x, st.x, inr, c1.x, sh.x)), __uint_as_float(ln_mod2(xc.y, st.x, inr, c1.y, sh.y)),
                       __uint_as_float(ln_mod2(xc.z, st.x, inr, c1.z, sh.z)), __uint_as_float(ln_mod2(xc.w, st.x, inr, c1.w, sh.w)));
            st_tagged4(dst, __uint_as_float(xc.x), __uint_as_float(xc.y), __uint_as_float(xc.z), __uint_as_float(xc.w));
          }
    }
    mbar_wait(bar_sel, 0);
    const uint4 sel = lds_u32x4(sbase + OG_SMISC + 64);
    const int sel0 = (int)sel.x, sel1 = (int)sel.y;
    {
      const float* src0 = reinterpret_cast<const float*>(g_cand + sel.z * 256 + 128 + threadIdx.x);
      const float* src1 = reinterpret_cast<const float*>(g_cand + sel.w * 256 + 128 + threadIdx.x);
      float4 h0, h1;
      #pragma unroll 1
      for (unsigned int spin = 0; spin < (1u << 20); spin++) { h0 = ld_tagged4(src0); h1 = ld_tagged4(src1); if (__all_sync(0xffffffffu, tagged4(h0) & tagged4(h1))) break; }
      sts_f32x4(sbase + OG_SH2 + threadIdx.x * 16, h0.x, h0.y, h0.z, h0.w);
      sts_f32x4(sbase + OG_SH2 + 2048 + threadIdx.x * 16, h1.x, h1.y, h1.z, h1.w);
      __syncwarp();
      if (lane == 0) mbar_arrive(bar_h2);
      TL_MARK2(12, lane == 0);
      if (bid >> 6) h0 = h1;
      float v[8], wr[8];
      unpack8(make_uint4(__float_as_uint(h0.x), __float_as_uint(h0.y), __float_as_uint(h0.z), __float_as_uint(h0.w)), v); unpack8(wrv, wr);
      float r = 0.f;
      #pragma unroll
      for (int i = 0; i < 8; i++) r = fmaf(v[i], wr[i], r);
      #pragma unroll
      for (int o = 16; o > 0; o >>= 1) r += __shfl_xor_sync(0xffffffffu, r, o);
      if (lane == 0) sts_f32(sbase + OG_SMISC + 192 + wi * 4, r);
    }
    mbar_wait(bar_out, 0);
    {
      const uint2 cg = lds_u32x2(sbase + OG_SMISC + 96);
      #pragma unroll
      for (int i = 0; i < 4; i++) {
        const int r = (i < 2 ? cg.x : cg.y) * 16 + (i & 1) * 8 + (threadIdx.x >> 4), ch = threadIdx.x & 15;
        if (m0 + r != sel0 && m0 + r != sel1)
          *reinterpret_cast<uint4*>(out + (size_t)(m0 + r) * T_D + n0 + ch * 8) =
              lds_u32x4(sbase + OG_OSLOT + (ch >> 3) * 16384 + r * 128 + (((ch & 7) ^ (r & 7)) << 4));
      }
    }
    if (bid == 0 && threadIdx.x < 68) *reinterpret_cast<uint4*>(g_hcnt + 32 * (threadIdx.x >> 2) + 4 * (threadIdx.x & 3)) = make_uint4(0u, 0u, 0u, 0u);
    if (threadIdx.x < 64) g_modpart[bid * 64 + threadIdx.x] = 0.f;
    {
      const int tk = bid >> 6, c0 = (bid & 63) * 16;
      const uint32_t gb2 = *reinterpret_cast<const uint32_t*>(g_col + (c0 >> 7) * 1536 + 512 + 768 + ((c0 & 127) + (threadIdx.x & 14)) * 2);
      const uint32_t* xp = reinterpret_cast<const uint32_t*>(g_cand + (tk ? sel.w : sel.z) * 256) + ((c0 + (threadIdx.x & 14)) >> 1);
      uint32_t x2 = 0u;
      #pragma unroll 1
      for (unsigned int spin = 0; spin < (1u << 20) && __any_sync(0xffffffffu, x2 == 0u); spin++) asm volatile("ld.relaxed.gpu.global.u32 %0, [%1];" : "=r"(x2) : "l"(xp) : "memory");
      const float* src = g_ypart + (size_t)((threadIdx.x >> 2) * 2 + tk) * T_D + c0 + (threadIdx.x & 3) * 4;
      const bool four = threadIdx.x < (OG_MOE - 96) * 4;
      named_bar_sync(10, 128);
      const uint4 rp = lds_u32x4(sbase + OG_SMISC + 192);
      const float rs = rbf(sigmoid_f(rbf((__uint_as_float(rp.x) + __uint_as_float(rp.y)) + (__uint_as_float(rp.z) + __uint_as_float(rp.w)))));
      const uint32_t h2p = lds_u32(sbase + OG_SH2 + tk * 2048 + (c0 + (threadIdx.x & 14)) * 2);
      const float fh = (lane & 1) ? bfhi(h2p) : bflo(h2p), fz = rbf(fh * 0.0f), fx = (lane & 1) ? bfhi(x2) : bflo(x2), fg = (lane & 1) ? bfhi(gb2) : bflo(gb2);
      bf16* dst = out + (size_t)(tk ? sel1 : sel0) * T_D + c0 + threadIdx.x;
      if (threadIdx.x == 0) hint_wait(CNT_Y, (uint32_t)(OG_MOE - Y_SLACK));
      named_bar_sync(10, 128);
      float4 p0, p1, p2, p3;
      #pragma unroll 1
      for (unsigned int spin = 0; spin < (1u << 20); spin++) {
        p0 = ld_tagged4(src); p1 = ld_tagged4(src + 64 * T_D); p2 = ld_tagged4(src + 128 * T_D); p3 = ld_tagged4(four ? src + 192 * T_D : src);
        if (__all_sync(0xffffffffu, tagged4(p0) & tagged4(p1) & tagged4(p2) & tagged4(p3))) break;
      }
      if (four) { p2.x += p3.x; p2.y += p3.y; p2.z += p3.z; p2.w += p3.w; }
      p0.x = (p0.x + p1.x) + p2.x; p0.y = (p0.y + p1.y) + p2.y; p0.z = (p0.z + p1.z) + p2.z; p0.w = (p0.w + p1.w) + p2.w;
      #pragma unroll
      for (int o = 4; o <= 16; o <<= 1) {
        p0.x += __shfl_xor_sync(0xffffffffu, p0.x, o); p0.y += __shfl_xor_sync(0xffffffffu, p0.y, o);
        p0.z += __shfl_xor_sync(0xffffffffu, p0.z, o); p0.w += __shfl_xor_sync(0xffffffffu, p0.w, o);
      }
      if (lane < 4) sts_f32x4(sbase + OG_SFIN + (threadIdx.x >> 5) * 64 + lane * 16, p0.x, p0.y, p0.z, p0.w);
      named_bar_sync(10, 128);
      TL_MARK2(21, threadIdx.x == 0);
      if (threadIdx.x < 16) {
        const uint32_t ya = sbase + OG_SFIN + threadIdx.x * 4;
        float y = (lds_f32(ya) + lds_f32(ya + 64)) + (lds_f32(ya + 128) + lds_f32(ya + 192));
        y = rbf(y);
        y = rbf(y * rs);
        *dst = __float2bfloat16_rn(fx + rbf(fg * rbf(fh + rbf(fz + y))));
      }
    }
    if (threadIdx.x == 0) XT(11);
    TL_END(4, threadIdx.x == 0);
}

__device__ __forceinline__ void load_pre(uint4* pre, uint32_t sbase, uint32_t buf, int t2) {
  mbar_wait(sbase + AT_SBAR + 272, 0);
  #pragma unroll
  for (int i = 0; i < 8; i++) pre[i] = lds_u32x4(sbase + buf + i * 4096 + t2 * 16);
}
__device__ __forceinline__ void tail_consumer(uint32_t bid, uint32_t sbase, const CUtensorMap* tmOut, const uint4 (&pre)[8], int cwg, const bf16* __restrict__ w_gate, const bf16* __restrict__ w_up) {
    const uint32_t c0 = clock_lo();
    if ((threadIdx.x & 31) == 0) mbar_arrive(sbase + AT_SBAR + 304);
    mbar_wait(sbase + AT_SBAR + 320, 0);
    const uint2 td = lds_u32x2(sbase + AT_SBAR + 408);
    const int tb = __shfl_sync(0xffffffffu, (int)td.x, 0);
    TAIL_SETUP
    const int tid = threadIdx.x & 127, t2 = threadIdx.x - 128;
    const int warp = tid >> 5, lane = tid & 31, w8 = t2 >> 5;
    const uint32_t dbase = (sbase & 0x3FFFFu) >> 4;
    const uint32_t a_base = dbase + ((cwg * 8192) >> 4) + (1u << 16);
    const uint32_t b_base = dbase + (16384 >> 4) + (512u << 16);
    TL_MARK2(25, threadIdx.x == 128);
    const uint64_t pol = policy_evict_first();
    const bf16* pw = ((lane & 16) ? w_up : w_gate) + (size_t)(w8 * 128 + (lane & 3) * 4) * T_F + (has_moe ? bid : 0) * 32 + ((lane >> 2) & 3) * 8;
    uint4 wv[32];
    float acc[64];
    #pragma unroll
    for (int i = 0; i < 8; i++) {
      acc[8 * i] = bflo(pre[i].x); acc[8 * i + 1] = bfhi(pre[i].x); acc[8 * i + 2] = bflo(pre[i].y); acc[8 * i + 3] = bfhi(pre[i].y);
      acc[8 * i + 4] = bflo(pre[i].z); acc[8 * i + 5] = bfhi(pre[i].z); acc[8 * i + 6] = bflo(pre[i].w); acc[8 * i + 7] = bfhi(pre[i].w);
    }
    while (__any_sync(0xffffffffu, clock_lo() - c0 < td.y + AL_ADD)) {}
    uint32_t stage = OG_POS % OG_ST;
    {
      uint32_t phase = (OG_POS / OG_ST) & 1, prev = 12;
      int kb = 0;
      #pragma unroll
      for (int g = 0; g <= OG_NG; g++) {
        const int end = g == OG_NG ? 64 - og_pre(tb) : LD_FIRST + g * OG_GRP + LD_STAG * cwg;
        #pragma unroll 1
        do {
          const bool xb = g >= 1 && g <= OG_XN && kb == OG_XB + (g - 1) * OG_GRP;
          mbar_wait(xb ? bar_full + 360 : bar_full + 8 * stage, xb ? (g - 1) & 1 : phase);
          if (OG_STAG > 0 && g == OG_NG && cwg == 1 && kb == end - OG_STAG) named_bar_sync(7, 256);
          const uint32_t a_lo = a_base + (xb ? 5 : stage) * (OG_STAGE >> 4), b_lo = b_base + (xb ? 5 : stage) * (OG_STAGE >> 4);
          wgmma_fence();
          wgmma_m64n128k16_ss_tb<0, 0>(acc, a_lo, b_lo, 1);
          wgmma_m64n128k16_ss_tb<2, 128>(acc, a_lo, b_lo, 1);
          wgmma_m64n128k16_ss_tb<4, 256>(acc, a_lo, b_lo, 1);
          wgmma_m64n128k16_ss_tb<6, 384>(acc, a_lo, b_lo, 1);
          wgmma_commit();
          if (OG_STAG > 0 && g == OG_NG && cwg == 0 && kb == end - 1) named_bar_arrive(7, 256);
          wgmma_wait<1>();
          if (tid == 0) mbar_arrive(bar_empty + 8 * prev);
          prev = xb ? 41 + (g == OG_XN) : stage;
          if (!xb && ++stage == OG_ST) { stage = 0; phase ^= 1; }
        } while (++kb < end);
        #pragma unroll
        for (int j = 4 * g; j < 4 * g + 4 && j < 32; j++) wv[j] = ldg_stream_v4(pw + (size_t)(16 * (j >> 2) + (j & 3)) * T_F, pol);
      }
    }
    mbar_wait(bar_col, 0);
    if (__builtin_expect(!has_moe, 0)) {
      load_pre(wv, sbase, AT_SQ, t2);
    }
    wgmma_wait<0>();
    fence_regs(acc);
    if (__builtin_expect(!has_moe, 0)) {
      #pragma unroll
      for (int i = 0; i < 8; i++) {
        acc[8 * i] += bflo(wv[i].x); acc[8 * i + 1] += bfhi(wv[i].x); acc[8 * i + 2] += bflo(wv[i].y); acc[8 * i + 3] += bfhi(wv[i].y);
        acc[8 * i + 4] += bflo(wv[i].z); acc[8 * i + 5] += bfhi(wv[i].z); acc[8 * i + 6] += bflo(wv[i].w); acc[8 * i + 7] += bfhi(wv[i].w);
      }
    }
    if (tid == 0) mbar_arrive(bar_end);
    TL_MARK2(9, lane == 0);
    const int q2 = 2 * (lane & 3);
    const uint32_t frag = (64 * cwg + 16 * warp + (lane & 7) + 8 * ((lane >> 3) & 1)) * 128;
    const int fsw = lane & 7, fhi = lane >> 4;
    {
      float dl[4] = {0.f, 0.f, 0.f, 0.f}, da[4] = {0.f, 0.f, 0.f, 0.f}, db[4] = {0.f, 0.f, 0.f, 0.f};
      const uint32_t tb2 = sbase + OG_SCOL + (lane & 8) * 32 + (lane & 3) * 8, g = lane >> 2;
      const uint32_t msk = (g == 1 || g == 2) ? 0xffffffffu : 0u, one = g == 0 ? 0x3F803F80u : 0u;
      uint32_t xr[8][4];
      #pragma unroll
      for (int hf = 0; hf < 2; hf++) {
        uint32_t ga[8];
        uint2 cw[4];
        #pragma unroll
        for (int i = 0; i < 4; i++) {
          ldmatrix_x4(sbase + OG_XSLOT + hf * 16384 + frag + (((2 * i + fhi) ^ fsw) << 4), xr[4 * hf + i][0], xr[4 * hf + i][1], xr[4 * hf + i][2], xr[4 * hf + i][3]);
          ga[2 * i] = lds_u32(sbase + OG_SCOL + 512 + (64 * hf + 16 * i + q2) * 2); ga[2 * i + 1] = lds_u32(sbase + OG_SCOL + 512 + (64 * hf + 16 * i + 8 + q2) * 2);
          cw[i] = lds_u32x2(tb2 + (8 * hf + 2 * i) * 16);
        }
        #pragma unroll
        for (int i = 0; i < 4; i++) {
          uint32_t* x4 = xr[4 * hf + i];
          #pragma unroll
          for (int e = 0; e < 4; e++) x4[e] = badd2(x4[e], bmul2(ga[2 * i + (e >> 1)], pack_bf16(acc[32 * hf + 8 * i + 2 * e], acc[32 * hf + 8 * i + 2 * e + 1])));
          mma_bf16(dl, x4[0], x4[1], x4[2], x4[3], (cw[i].x & msk) | one, (cw[i].y & msk) | one);
          mma_bf16(da, x4[0], x4[1], x4[2], x4[3], x4[0], x4[2]);
          mma_bf16(db, x4[0], x4[1], x4[2], x4[3], x4[1], x4[3]);
        }
      }
      {
        const int dsrc = (lane & ~3) + (g >> 1);
        const float qa = __shfl_sync(0xffffffffu, (g & 1) ? da[1] : da[0], dsrc), qb = __shfl_sync(0xffffffffu, (g & 1) ? db[3] : db[2], dsrc);
        const float e0 = __shfl_xor_sync(0xffffffffu, (lane & 1) ? dl[0] : dl[2], 1), e1 = __shfl_xor_sync(0xffffffffu, dl[3], 1);
        if ((lane & 3) < 2) {
          const bool hi = lane & 1;
          st_tagged4(reinterpret_cast<float*>(g_part1 + ((mt * 8 + w8) * 8 + nt) * 16 + g + (hi ? 8 : 0)),
                     hi ? e0 : dl[0], hi ? qb : qa, hi ? e1 + dl[2] : dl[1] + e0, 1.0f);
        }
      }
      #pragma unroll
      for (int i = 0; i < 8; i++) stmatrix_x4(sbase + OG_XSLOT + (i >> 2) * 16384 + frag + (((2 * (i & 3) + fhi) ^ fsw) << 4), xr[i][0], xr[i][1], xr[i][2], xr[i][3]);
    }
    TL_MARK2(10, lane == 0);
    uint4 wd[16];
    if (has_moe) mbar_wait(bar_wd, 0);
    #pragma unroll
    for (int i = 0; i < 16; i++) wd[i] = lds_u32x4(sbase + (cwg ? (stage + (stage & 1)) * OG_STAGE : OG_SWD) + warp * 8192 + (i >> 3) * 4096 + (i & 6) * 512 + (i & 1) * 128 + (lane & 3) * 256 + (((lane >> 2) ^ (2 * (lane & 3) + (i & 1))) << 4));
    {
      const float* src = reinterpret_cast<const float*>(g_part1 + ((mt * 8 + w8) * 8 + (lane & 1) * 4) * 16 + (lane >> 1));
      float4 v, v1, v2, v3;
      #pragma unroll 1
      for (unsigned int spin = 0; spin < (1u << 22); spin++) {
        v = ld_tagged4(src); v1 = ld_tagged4(src + 64); v2 = ld_tagged4(src + 128); v3 = ld_tagged4(src + 192);
        if (__all_sync(0xffffffffu, tagged4(v) & tagged4(v1) & tagged4(v2) & tagged4(v3))) break;
      }
      __syncwarp();
      TL_MARK2(26, lane == 0);
      v.x = (v.x + v1.x) + (v2.x + v3.x); v.y = (v.y + v1.y) + (v2.y + v3.y); v.z = (v.z + v1.z) + (v2.z + v3.z);
      v.x += __shfl_xor_sync(0xffffffffu, v.x, 1); v.y += __shfl_xor_sync(0xffffffffu, v.y, 1); v.z += __shfl_xor_sync(0xffffffffu, v.z, 1);
      const float mean = v.x * (1.0f / T_D);
      const float var = fmaxf(fmaf(-mean, mean, v.y * (1.0f / T_D)), 0.f);
      const uint32_t mb2 = pack_bf16(mean, mean);
      const float inv = rcp_approx(rbf(sqrt_approx(rbf(rbf(var) + 1e-05f))));
      {
        const float2 sc = lds_f32x2(sbase + OG_SMISC);
        const uint32_t key = rank_key(rbf(fmaf(fmaf(-bflo(mb2), sc.x, v.z), inv, sc.y)), m0 + 16 * w8 + (lane >> 1));
        mbar_wait(bar_end, 0);
        if (lane & 1) sts_u32(sbase + OG_SSTAT + 1024 + (16 * w8 + (lane >> 1)) * 4, key);
        else sts_u32x2(sbase + OG_SSTAT + (16 * w8 + (lane >> 1)) * 8, mb2, __float_as_uint(inv));
        __syncwarp();
        if (lane == 0) mbar_arrive(bar_key);
      }
      const uint32_t ih = pack_bf16(inv, inv), il = pack_bf16(inv - bflo(ih), inv - bflo(ih));
      const uint32_t mba = __shfl_sync(0xffffffffu, mb2, 2 * (lane >> 2)), mbb = __shfl_sync(0xffffffffu, mb2, 2 * (lane >> 2) + 16);
      const uint32_t iha = __shfl_sync(0xffffffffu, ih, 2 * (lane >> 2)), ihb = __shfl_sync(0xffffffffu, ih, 2 * (lane >> 2) + 16);
      const uint32_t ila = __shfl_sync(0xffffffffu, il, 2 * (lane >> 2)), ilb = __shfl_sync(0xffffffffu, il, 2 * (lane >> 2) + 16);
      #pragma unroll 1
      for (int J0 = 0; J0 < 16; J0 += 4) {
        uint32_t xr[2][4], cv[4][3];
        #pragma unroll
        for (int i = 0; i < 2; i++) {
          ldmatrix_x4(sbase + OG_XSLOT + (J0 >> 3) * 16384 + frag + ((((J0 & 7) + 2 * i + fhi) ^ fsw) << 4), xr[i][0], xr[i][1], xr[i][2], xr[i][3]);
          #pragma unroll
          for (int h = 0; h < 2; h++)
            #pragma unroll
            for (int k = 0; k < 3; k++) cv[2 * i + h][k] = lds_u32(sbase + OG_SCOL + 768 + 256 * k + (8 * (J0 + 2 * i + h) + q2) * 2);
        }
        #pragma unroll
        for (int i = 0; i < 2; i++) {
          #pragma unroll
          for (int h = 0; h < 2; h++) {
            xr[i][2 * h] = out2(xr[i][2 * h], mba, iha, ila, cv[2 * i + h][0], cv[2 * i + h][1], cv[2 * i + h][2]);
            xr[i][2 * h + 1] = out2(xr[i][2 * h + 1], mbb, ihb, ilb, cv[2 * i + h][0], cv[2 * i + h][1], cv[2 * i + h][2]);
          }
          stmatrix_x4(sbase + OG_OSLOT + (J0 >> 3) * 16384 + frag + ((((J0 & 7) + 2 * i + fhi) ^ fsw) << 4), xr[i][0], xr[i][1], xr[i][2], xr[i][3]);
        }
      }
      fence_proxy_async();
      mbar_wait(bar_full + 352, 0);
      const uint2 cg = lds_u32x2(sbase + OG_SMISC + 96);
      __syncwarp();
      if (elect_one()) {
        mbar_arrive(bar_out);
        if (cg.x != w8 && cg.y != w8) {
          asm volatile("cp.async.bulk.tensor.2d.global.shared::cta.bulk_group [%0, {%2, %3}], [%1];" :: "l"(tmOut), "r"(sbase + OG_OSLOT + w8 * 2048), "r"(n0), "r"(m0 + 16 * w8) : "memory");
          asm volatile("cp.async.bulk.tensor.2d.global.shared::cta.bulk_group [%0, {%2, %3}], [%1];" :: "l"(tmOut), "r"(sbase + OG_OSLOT + 16384 + w8 * 2048), "r"(n0 + 64), "r"(m0 + 16 * w8) : "memory");
          bulk_commit();
        }
      }
      TL_MARK2(24, lane == 0);
    }
    if (has_moe) mbar_wait(bar_h2, 0);
    TL_MARK2(13, lane == 0);
    if (has_moe) {
      const GemvSel sel = gemv_sel(lane);
      {
        float d[4][4];
        #pragma unroll
        for (int c = 0; c < 4; c++) { d[c][0] = 0.f; d[c][1] = 0.f; d[c][2] = 0.f; d[c][3] = 0.f; }
        #pragma unroll
        for (int st = 0; st < 8; st++) {
          const uint2 hb = lds_u32x2(sbase + OG_SH2 + ((lane >> 2) & 1) * 2048 + (w8 * 128 + st * 16 + (lane & 3) * 4) * 2);
          #pragma unroll
          for (int j = 0; j < 4; j++) mma_bf16(d[j], wv[4 * st + j].x, wv[4 * st + j].y, wv[4 * st + j].z, wv[4 * st + j].w, GEMV_B0(j, hb, sel), GEMV_B1(j, hb, sel));
        }
        #pragma unroll
        for (int e = 0; e < 4; e++) d[0][e] = (d[0][e] + d[1][e]) + (d[2][e] + d[3][e]);
        const float4 r = gemv_out(d[0], lane);
        sts_f32x4(sbase + OG_SRED + w8 * 512 + (((lane >> 4) * 2 + (lane & 1)) * 32 + ((lane >> 2) & 3) * 8 + (lane & 2) * 2) * 4, r.x, r.y, r.z, r.w);
      }
      named_bar_sync(9, 256);
      if (t2 < 64) {
        float gp[8], up[8];
        #pragma unroll
        for (int w = 0; w < 8; w++) { gp[w] = lds_f32(sbase + OG_SRED + w * 512 + t2 * 4); up[w] = lds_f32(sbase + OG_SRED + w * 512 + 256 + t2 * 4); }
        const float gs = ((gp[0] + gp[1]) + (gp[2] + gp[3])) + ((gp[4] + gp[5]) + (gp[6] + gp[7]));
        const float us = ((up[0] + up[1]) + (up[2] + up[3])) + ((up[4] + up[5]) + (up[6] + up[7]));
        asm volatile("st.shared.u16 [%0], %1;" :: "r"(sbase + OG_SGU + ((t2 & ~15) + ((t2 >> 1) & 3) * 4 + ((t2 >> 3) & 1) * 2 + (t2 & 1)) * 2), "h"((uint16_t)pack_bf16(silu_bf(rbf(gs)) * rbf(us), 0.f)) : "memory");
      }
      named_bar_sync(9, 256);
      TL_MARK2(20, threadIdx.x == 128);
      float d[4][4];
      #pragma unroll
      for (int c = 0; c < 4; c++) { d[c][0] = 0.f; d[c][1] = 0.f; d[c][2] = 0.f; d[c][3] = 0.f; }
      #pragma unroll
      for (int st = 0; st < 2; st++) {
        const uint2 g = lds_u32x2(sbase + OG_SGU + ((lane >> 2) & 1) * 64 + st * 32 + (lane & 3) * 8);
        #pragma unroll
        for (int j = 0; j < 4; j++) {
          const uint32_t b0 = GEMV_B0(j, g, sel), b1 = GEMV_B1(j, g, sel);
          mma_bf16(d[j & 1], wd[4 * st + j].x, wd[4 * st + j].y, wd[4 * st + j].z, wd[4 * st + j].w, b0, b1);
          mma_bf16(d[2 + (j & 1)], wd[8 + 4 * st + j].x, wd[8 + 4 * st + j].y, wd[8 + 4 * st + j].z, wd[8 + 4 * st + j].w, b0, b1);
        }
      }
      #pragma unroll
      for (int e = 0; e < 4; e++) { d[0][e] += d[1][e]; d[2][e] += d[3][e]; }
      const float4 y0 = gemv_out(d[0], lane), y1 = gemv_out(d[2], lane);
      float* yp = g_ypart + (size_t)(bid * 2 + (lane & 1)) * T_D + w8 * 128 + (lane >> 2) * 8 + (lane & 2) * 2;
      st_tagged4(yp, y0.x, y0.y, y0.z, y0.w);
      st_tagged4(yp + 64, y1.x, y1.y, y1.z, y1.w);
      named_bar_sync(9, 256);
      if (t2 == 0) hint_arrive(CNT_Y);
    }
    bulk_wait_read<0>();
    TL_MARK2(14, threadIdx.x == 128);
    TL_CLK(4, 1, threadIdx.x == 128);
}

__device__ __forceinline__ int help_njobs(uint32_t bid) { return bid < 128 ? OG_JOBS : 16 - OG_JOBS; }
__device__ __forceinline__ int help_job(uint32_t bid, int i) { return (i < OG_JOBS ? 16 * i + (bid >> 7) * 2 : 112 + (i - OG_JOBS) * 2) + (bid & 3) * 4; }
__device__ __noinline__ void store_warp(uint32_t bid, uint32_t sbase, const CUtensorMap* tmO, int item0, int n_items) {
  if (elect_one()) {
    const uint32_t bars = sbase + AT_SBAR, b_q0 = bars + 80, b_ob = bars + 96, b_ordy = bars + 104, b_acq = bars + 264;
    const unsigned int* cnt = g_hcnt + 32 * (1 + OG_MT(124)) + 2;
    #pragma unroll 1
    for (int q = 0; q < 4 * n_items; q++) {
      const int item = item0 + (q >> 2) * 128, h = (q >> 1) & 1, w = q & 1;
      const bool last = (q >> 2) == n_items - 1;
      if (q == 4 * n_items - 4) { mbar_wait_long(bars + 288, 0); red_release_add(&g_hcnt[1], 1u); }
      mbar_wait_long(b_ordy + 8 * (q & 3), q >> 2);
      store_o(tmO, (h ? (last ? sbase + AT_SQ + 32768 : sbase + 2 * 32768) : sbase + AT_SQ) + w * 8192, (item >> 4) * 2 + h, (item & 15) * 128 + w * 64);
      if (w) {
        bulk_wait_read<0>();
        mbar_arrive(h ? b_ob : b_q0);
        bulk_wait<0>();
        fence_proxy_async_global();
        asm volatile("fence.acq_rel.gpu;" ::: "memory");
        hint_arrive(&g_hcnt[32 * (1 + (item & 15)) + 2 + (item >> 7)]);
        if (!h && item < 128) hint_arrive(&g_hcnt[2]);
        if (q == 5) { const int tb = tail_tile(sbase); cnt = g_hcnt + 32 * (1 + OG_MT(tb)) + 2; spin_until(cnt, 16u); mbar_arrive(b_acq); }
      }
    }
    if (n_items == 1) {
      #pragma unroll 1
      for (int i = 0; i < help_njobs(bid); i++) {
        mbar_wait_long(b_acq + 16, i & 1);
        TL_MARK2(23, i == OG_JOBS - 1);
        red_release_add(&g_hcnt[32 * (1 + (help_job(bid, i) >> 3)) + 4 + ((help_job(bid, i) >> 1) & 3)], 1u);
        TL_MARK2(4, i == OG_JOBS - 1);
        if (i == PRE_X - 1) { spin_until(&g_hcnt[1], 132u); mbar_arrive(b_acq + 32); }
      }
    }
    if (bid < 128) {
      if (n_items == 1) { spin_until(cnt, 16u); mbar_arrive(b_acq); }
      spin_until(&g_hcnt[0], 128u); spin_until(cnt + 1, 16u); mbar_arrive(b_acq + 80);
    }
  }
}

__device__ __forceinline__ uint32_t role_of_sm(uint32_t sm) {
  const uint32_t t = sm >> 1, u = t - 32u, d = (u * 37u) >> 8;
  return (t < 32u ? ((t + 7u) & 7u) * 16u + (t >> 3) * 2u : t < 60u ? (u - 7u * d) * 16u + (4u + d) * 2u : t < 62u ? 2u * t + 8u : 2u * t - 4u) + (sm & 1u);
}
__global__ void __launch_bounds__(384, 1)
fused_kernel(const __grid_constant__ CUtensorMap tmH, const __grid_constant__ CUtensorMap tmW, const __grid_constant__ CUtensorMap tmK,
            const __grid_constant__ CUtensorMap tmV, const __grid_constant__ CUtensorMap tmO, const __grid_constant__ CUtensorMap tmOl, const __grid_constant__ CUtensorMap tmWo,
            const __grid_constant__ CUtensorMap tmD, const __grid_constant__ CUtensorMap tmOut, const __grid_constant__ CUtensorMap tmM, uint32_t zero,
            const uint8_t* __restrict__ pf_wo, const bf16* __restrict__ kc, const bf16* __restrict__ vc,
            const bf16* __restrict__ x, const bf16* __restrict__ cvec, const bf16* __restrict__ w_mod, const bf16* __restrict__ w_r,
            const bf16* __restrict__ w_gate, const bf16* __restrict__ w_up, const bf16* __restrict__ w_down, bf16* __restrict__ out)
{
  uint32_t bid, nsm;
  asm volatile("mov.u32 %0, %%smid;" : "=r"(bid));
  asm volatile("mov.u32 %0, %%nsmid;" : "=r"(nsm));
  bid = __shfl_sync(0xffffffffu, nsm == 132u ? role_of_sm(bid) : blockIdx.x, 0);
  extern __shared__ __align__(1024) uint8_t smem_raw[];
  const uint32_t sbase = smem_u32(smem_raw);
  const uint32_t bars = sbase + AT_SBAR;
  const uint32_t b_full = bars, b_empty = bars + 40;
  const uint32_t b_q0 = bars + 80, b_q1 = bars + 88;
  const uint32_t b_ob = bars + 96;
  const uint32_t b_ordy = bars + 104;
  const uint32_t b_pin = bars + 136;
  const uint32_t b_head = bars + 144;
  const uint32_t b_go = bars + 152;
  const uint32_t b_x = bars + 160;
  const int wg = __shfl_sync(0xffffffffu, threadIdx.x >> 7, 0);
  const bool single = bid >= AT_NFULL;
  const int item0 = __shfl_sync(0xffffffffu, bid < 128 ? (int)bid : (int)bid + 124, 0), n_items = __shfl_sync(0xffffffffu, single ? 1 : 2, 0);
  TL_START(3);
  if (threadIdx.x == 0) {
    if (sbase & 1023u) __trap();
    for (int i = 0; i < 5; i++) { mbar_init(b_full + 8 * i, 1); mbar_init(b_empty + 8 * i, 2); }
    mbar_init(b_q0, 1); mbar_init(b_q1, 8); mbar_init(b_ob, 1);
    for (int i = 0; i < 4; i++) mbar_init(b_ordy + 8 * i, 4);
    mbar_init(b_pin, 1); mbar_init(b_head, bid < 128 ? 8 : 1); mbar_init(b_go, 1); mbar_init(b_x, 1);
    mbar_init(bars + 168, 2); mbar_init(bars + 176, 1); mbar_init(bars + 184, 8); mbar_init(bars + 192, 2);
    mbar_init(bars + 200, 8); mbar_init(bars + 208, 4); mbar_init(bars + 216, 1); mbar_init(bars + 264, 1); mbar_init(bars + 272, 1); mbar_init(bars + 280, 8); mbar_init(bars + 288, 1); mbar_init(bars + 296, 1); mbar_init(bars + 304, 8); mbar_init(bars + 312, 1); mbar_init(bars + 320, 1); mbar_init(bars + 328, 1); mbar_init(bars + 336, 1); mbar_init(bars + 344, 1); mbar_init(bars + 352, 1); mbar_init(bars + 360, 1); mbar_init(bars + 368, 2); mbar_init(bars + 376, 2);
    sts_u32(bars + 400, bid);
    fence_mbar_init();
  }

  if (wg == 0) {
    reg_dealloc<AT_PREG>();
    if (threadIdx.x < 32) { __syncwarp(); named_bar_arrive(6, 384); }
    if (threadIdx.x >= 64) {
      named_bar_sync(6, 384);
      if (bid < 128) {
        named_bar_sync(threadIdx.x >= 96 ? 8 : 9, 288);
        if ((threadIdx.x & 31) == 0) red_release_add(&g_hcnt[32 * (1 + (bid >> 3)) + (threadIdx.x >= 96)], 1u);
        TL_MARK2(11, threadIdx.x == 64);
      }
      if (bid < 128) {
        mbar_wait(MOD_AT, 0);
        mod_rest(bid, sbase + OG_SCOL, b_q1, threadIdx.x - 64, cvec, w_mod, w_r);
      }
    } else if (threadIdx.x >= 32) {
      named_bar_sync(6, 384);
      store_warp(bid, sbase, &tmO, item0, n_items);
      __syncwarp();
    } else {
     if (elect_one()) {
      const uint64_t pol = policy_evict_first();
      if (bid < 128) {
        mbar_expect_tx(b_x, 32768);
        if (X_DLY) { const uint32_t c0 = clock_lo(); while (clock_lo() - c0 < X_DLY) {} }
        bulk_load_hint(sbase + 4 * 32768, x + (size_t)bid * 16 * T_D, 32768, b_x, pol);
      }
      prefetch_tmap(&tmW); prefetch_tmap(&tmM); prefetch_tmap(&tmH); prefetch_tmap(&tmWo); prefetch_tmap(&tmOl);
      {
        const uint32_t c0 = clock_lo();
        while (clock_lo() - c0 < W_DLY) {}
        if (bid < 128 && (head_cb(bid) & 15) >= 4 * H_SPLIT) {
          mbar_expect_tx(bars + 328, 32768);
          tma_load_2d_hint(sbase + 3 * 32768, &tmM, head_cb(bid) * 64, (bid >> 5) * 256, bars + 328, pol);
        }
        while (clock_lo() - c0 < W_DLY + W_FIRST) {}
      }
      uint32_t slot = 0, ph = 1;
      #pragma unroll 1
      for (int it = 0; it < n_items; it++) {
        const int item = item0 + it * 128, hp = item >> 4, qt = item & 15;
        const bool first = it == 0;
        #pragma unroll 1
        for (int j = 0; j < T_D / 64; j++) {
          const uint32_t sl = ring_slot(qp_pos(j, it)), fb = b_full + 8 * sl;
          mbar_wait_long(b_empty + 8 * sl, ring_par(qp_pos(j, it)) ^ ((j >> 2) & 1) ^ 1);
          if (first && j == 3) mbar_wait(b_head, 0);
          mbar_expect_tx(fb, 49152);
          tma_load_3d_hint(sbase + sl * 32768, &tmW, j * 64, hp * 4, fb, pol);
          if (first && j < PRE_B) {
            if (j == PRE_B - 1) {
              spin_until(&g_hcnt[32 * (1 + qt)], 8u);
              TL_MARK2(16, true);
              fence_proxy_async_global();
              #pragma unroll 1
              for (int i = 0; i < PRE_B; i++) tma_load_2d(sbase + AT_SQ + i * 16384, &tmH, i * 64, qt * 128, b_full + 8 * i);
              mbar_arrive(b_go);
            }
          } else {
            if (first && j == 4 * H_SPLIT) { spin_until(&g_hcnt[32 * (1 + qt) + 1], 8u); fence_proxy_async_global(); }
            if (!first && (j == 0 || j == 2)) mbar_wait(j ? b_q1 : b_q0, 0);
            tma_load_2d(sbase + AT_SQ + (j & 3) * 16384, &tmH, j * 64, qt * 128, fb);
          }
        }
        #pragma unroll 1
        for (int j = 0; j < 4 * AT_NBLK; j++) {
          const bool isv = (j > 0 && !(j & 1)) || j == 4 * AT_NBLK - 1;
          const int row = hp * 2 * T_SEQ + (isv ? (j - 1) >> 1 : (j + 1) >> 1) * 128;
          const uint32_t fb = b_full + 8 * slot;
          mbar_wait_long(b_empty + 8 * slot, ph);
          if (!first && j == 3) mbar_wait(b_ob, 0);
          if (j == 4 && it == n_items - 1) mbar_arrive(bars + 288);
          if ((j == AL_P || j == RK_P) && it == 1) mbar_arrive(bars + 312);
          mbar_expect_tx(fb, 32768);
          tma_load_3d_hint(sbase + slot * 32768, isv ? &tmV : &tmK, row, 0, fb, pol);
          if (it == 1 && isv && j >= 2 * WO_LATE && j < 2 * WO_LATE + 32 && bid < OG_NKB)
            l2_prefetch_bulk(pf_wo + (size_t)own_kb(bid, og_pre(0)) * 131072 + ((j >> 1) - WO_LATE) * 8192, 8192);
          if (++slot == 5) { slot = 0; ph ^= 1; }
        }
      }
      if (__builtin_expect(single, 0)) {
        spin_until(&g_hcnt[2], 128u);
        fence_proxy_async_global();
        const int nj = OG_HSUM + (help_njobs(bid) - OG_JOBS) * OG_PRE2;
        int ji = 0, job = help_job(bid, 0), kk = 0;
        #pragma unroll 1
        for (int j = 0; j < nj; j++) {
          const uint32_t sl = ring_slot(qp_pos(j, 1)), fb = b_full + 8 * sl;
          mbar_wait_long(b_empty + 8 * sl, ring_par(qp_pos(j, 1)) ^ ((j >> 2) & 1) ^ 1);
          mbar_expect_tx(fb, 49152);
          tma_load_3d(sbase + sl * 32768, &tmWo, pre_kb(kk) * 64, OG_NT(job) * 2, fb);
          tma_load_3d(sbase + sl * 32768 + 16384, &tmWo, pre_kb(kk) * 64, OG_NT(job) * 2 + 2, fb);
          if (j == 0 || j == 2) mbar_wait(j ? b_ob : b_q0, 0);
          tma_load_2d_hint(sbase + AT_SQ + (j & 3) * 16384, &tmOl, pre_kb(kk) * 64, OG_MT(job) * 128, fb, pol);
          if (++kk == og_pre(job)) { kk = 0; job = help_job(bid, ++ji); }
        }
      }
      if (bid < 128) {
        if (single) mbar_wait(b_x, 1);
        tail_producer(bid, sbase, 0, pol, &tmOl, &tmWo, &tmD);
      }
     }
    }
    named_bar_sync(12 + (threadIdx.x >> 5), 32);
    if (bid < 128) tail_exchange(bid, sbase, w_down, w_r, x, out);
  } else {
    if (bid < 128) head_phase(bid, sbase + AT_SQ + 49152, sbase + 4 * 32768, b_x, b_go, b_head, threadIdx.x - 128, zero, cvec, w_mod);
    else { named_bar_sync(6, 384); if (threadIdx.x == 128) mbar_arrive(b_head); }
    TL_MARK2(0, threadIdx.x == 128);
    reg_alloc<AT_CREG>();
    const int cwg = wg - 1;
    const int tid = threadIdx.x & 127;
    const int warp = tid >> 5, lane = tid & 31;
    const uint32_t dbase = (sbase & 0x3FFFFu) >> 4;
    const uint32_t k_base = dbase + (1u << 16);
    const uint32_t v_base = dbase + (1024u << 16);
    const uint32_t w_base = dbase + (512u << 16);
    const uint32_t q_lo = dbase + ((AT_SQ + cwg * 8192) >> 4) + (1u << 16);
    const uint32_t frag = cwg * 8192 + (16 * warp + (lane & 7) + 8 * ((lane >> 3) & 1)) * 128;
    if (cwg == 1) named_bar_arrive(1, 256);
    bool raw = false;
    uint4 pre[8];
    #pragma unroll 1
    for (int it = 0; it < n_items; it++) {
      const bool more = it + 1 < n_items;
      constexpr int nkb = T_D / 64;
      const int ta = __shfl_sync(0xffffffffu, 4 * it, 0);
      float acc[128];
      {
        FS(2 * it, 0);
        #pragma unroll
        for (int i = 0; i < 128; i++) asm volatile("" : "=f"(acc[i]));
        {
          const uint32_t slot = ring_slot(ta), b_lo = w_base + slot * 2048;
          mbar_wait(b_full + 8 * slot, ring_par(ta));
          wgmma_fence();
          wgmma_m64n256k16_ss_tb<0, 0>(acc, q_lo, b_lo, 0);
          wgmma_m64n256k16_ss_tb<2, 128>(acc, q_lo, b_lo, 1);
          wgmma_m64n256k16_ss_tb<4, 256>(acc, q_lo, b_lo, 1);
          wgmma_m64n256k16_ss_tb<6, 384>(acc, q_lo, b_lo, 1);
          wgmma_commit();
        }
        #pragma unroll 1
        for (int j = 1; j < nkb; j++) {
          const uint32_t slot = ring_slot(qp_pos(j, ta >> 2));
          mbar_wait(b_full + 8 * slot, ring_par(qp_pos(j, ta >> 2)) ^ ((j >> 2) & 1));
          if (QP_STAG > 0 && cwg == 1 && j == nkb - QP_STAG) named_bar_sync(7, 256);
          const uint32_t a_lo = q_lo + (j & 3) * 1024, b_lo = w_base + slot * 2048;
          wgmma_fence();
          wgmma_m64n256k16_ss_tb<0, 0>(acc, a_lo, b_lo, 1);
          wgmma_m64n256k16_ss_tb<2, 128>(acc, a_lo, b_lo, 1);
          wgmma_m64n256k16_ss_tb<4, 256>(acc, a_lo, b_lo, 1);
          wgmma_m64n256k16_ss_tb<6, 384>(acc, a_lo, b_lo, 1);
          wgmma_commit();
          if (QP_STAG > 0 && cwg == 0 && j == nkb - 1) named_bar_arrive(7, 256);
          if (j > 0) {
            wgmma_wait<1>();
            if (tid == 0) mbar_arrive(b_empty + 8 * ring_slot(qp_pos(j - 1, ta >> 2)));
          }
        }
        wgmma_wait<0>();
        fence_regs(acc);
        FS(2 * it, 1);
        TL_MARK2(29, threadIdx.x == 256 && it == 0);
        if (tid == 0) mbar_arrive(b_empty + 24);
      }
      float o[64], s[64];
      uint32_t p[32], q[32];
      #pragma unroll
      for (int i = 0; i < 32; i++) q[i] = pack_bf16(acc[2 * i] * AT_C, acc[2 * i + 1] * AT_C);
      zero_regs(s);
      const uint32_t sq = sbase + AT_SQ + cwg * 8192;
      float mc0, mc1, al0 = 1.0f, al1 = 1.0f, l0 = 0.f, l1 = 0.f, lp0 = 0.f, lp1 = 0.f;
      bool redo0 = false;
      FS(2 * it, 2);
      mbar_wait(b_full + 8 * ring_slot(ta), ring_par(ta));
      named_bar_sync(1 + cwg, 256);
      FS(2 * it, 3);
      issue_qk(s, q, k_base + ring_slot(ta) * 2048);
      pass_turn(cwg);
      bool ready = mbar_test(b_full + 8 * ring_slot(ta + 1), ring_par(ta + 1)) & mbar_test(b_full + 8 * ring_slot(ta + 2), ring_par(ta + 2));
      stage_q<16>(acc, AT_C, sbase + AT_SQ + frag, lane);
      wgmma_wait<0>();
      fence_regs(s);
      if (tid == 0) mbar_arrive(b_empty + 8 * ring_slot(ta));
      mc0 = 0.f; mc1 = 0.f;
      if (!raw) {
        raw = softmax_mode(s, mc0, mc1);
        if (__builtin_expect(!raw, 0)) softmax_sub(s, mc0, mc1);
      }
      softmax_exp<0, 64>(s);
      #pragma unroll
      for (int J = 0; J < 16; J += 2)
        stmatrix_x4(sbase + AT_SQ + frag + (J >> 3) * 16384 + ((((J & 7) + (lane >> 4)) ^ (lane & 7)) << 4), q[2 * J], q[2 * J + 1], q[2 * J + 2], q[2 * J + 3]);
      pack_p(p, s);
      zero_regs(o);
      FS(2 * it, 4);
      uint32_t ks = ring_slot(ta + 1), vs = ring_slot(ta + 2), kp = ring_par(ta + 1), vp = ring_par(ta + 2);
      auto finish_head = [&]() {
        FS(2 * it, 5);
        redo0 = finish_l(lp0, lp1);
        if (!redo0) stage_o(o, lp0, lp1, sbase + AT_SQ + frag, lane);
        FS(2 * it + 1, 4);
      };
      if (!ready) { mbar_wait(b_full + 8 * ks, kp); mbar_wait(b_full + 8 * vs, vp); }
      #pragma unroll 1
      for (int n = 1; n < 2 * AT_NBLK; n++) {
        named_bar_sync(1 + cwg, 256);
        issue_qk(s, q, k_base + ks * 2048);
        if (n == AT_NBLK + 1) finish_head();
        issue_pv(o, p, v_base + vs * 2048, (n & 15) != 1);
        pass_turn(cwg);
        wgmma_wait<1>();
        fence_regs(s);
        if (tid == 0) mbar_arrive(b_empty + 8 * ks);
        if (__builtin_expect(!raw || (uint32_t)(n - (AT_NBLK - 1)) <= 2u, 0)) {
          if (n == AT_NBLK + 1 && !redo0) {
            fence_proxy_async();
            __syncwarp();
            if (lane == 0) mbar_arrive(b_ordy + 8 * cwg);
          }
          if (n == AT_NBLK - 1) {
            #pragma unroll
            for (int J = 0; J < 16; J += 2)
              ldmatrix_x4(sbase + AT_SQ + 32768 + frag + (J >> 3) * 16384 + ((((J & 7) + (lane >> 4)) ^ (lane & 7)) << 4), q[2 * J], q[2 * J + 1], q[2 * J + 2], q[2 * J + 3]);
          }
          if (!raw) {
            const float m0 = mc0, m1 = mc1;
            const bool ok = softmax_mode(s, mc0, mc1);
            if (n == AT_NBLK) raw = ok;
            else {
              mc0 = mc0 - AT_HEAD > m0 ? mc0 : m0; mc1 = mc1 - AT_HEAD > m1 ? mc1 : m1;
              al0 = ex2_approx(m0 - mc0); al1 = ex2_approx(m1 - mc1);
            }
            if (!raw) softmax_sub(s, mc0, mc1);
          }
        }
        softmax_exp<0, AT_SPLIT>(s);
        add_rowsum(p, l0, l1);
        if (tid == 0) {
          uint32_t dep = zero & __float_as_uint(l0) & __float_as_uint(l1);
          #pragma unroll
          for (int i = AT_SPLIT - AT_PIN - PINB; i < AT_SPLIT - PINB; i += 2) dep &= __float_as_uint(s[i]) & __float_as_uint(s[i + 1]);
          mbar_arrive(b_pin + dep);
        }
        wgmma_wait<0>();
        fence_regs(o);
        if (tid == 0) mbar_arrive(b_empty + 8 * vs);
        ks += 2; if (ks >= 5) { ks -= 5; kp ^= 1; }
        vs += 2; if (vs >= 5) { vs -= 5; vp ^= 1; }
        ready = mbar_test(b_full + 8 * ks, kp) & mbar_test(b_full + 8 * vs, vp);
        softmax_exp<AT_SPLIT, 64>(s);
        pack_p(p, s);
        if (n == AT_NBLK) { lp0 = l0; lp1 = l1; l0 = 0.f; l1 = 0.f; }
        if (__builtin_expect(!raw || !ready, 0)) {
        if (!raw && __any_sync(0xffffffffu, al0 != 1.0f || al1 != 1.0f)) {
          rescale_o(o, al0, al1);
          l0 *= al0; l1 *= al1;
          al0 = 1.0f; al1 = 1.0f;
        }
        if (!ready && n < 2 * AT_NBLK - 1) {
          mbar_wait(b_full + 8 * ks, kp);
          mbar_wait(b_full + 8 * vs, vp);
        }
        }
      }
      FS(2 * it + 1, 5);
      const uint32_t vl = ring_slot(ta + 63);
      vs = ring_slot(ta + 62);
      const uint32_t ob = more ? sbase + vs * 32768 : sbase + AT_SQ + 32768;
      mbar_wait(b_full + 8 * vl, ring_par(ta + 63));
      issue_pv(o, p, v_base + vl * 2048, 1);
      block_end(zero, b_pin);
      add_rowsum(p, l0, l1);
      const bool overflow = finish_l(l0, l1);
      if (!overflow && lane == 0) mbar_arrive(b_q1);
      #pragma unroll
      for (int i = 0; i < 8; i++) asm volatile("mov.b64 {%0, %1}, 0;\nmov.b64 {%2, %3}, 0;" : "=r"(pre[i].x), "=r"(pre[i].y), "=r"(pre[i].z), "=r"(pre[i].w));
      const bool want_pre = !more && bid < OG_MOE, got_pre = want_pre && __all_sync(0xffffffffu, mbar_test(bars + 272, 0));
      if (got_pre) load_pre(pre, sbase, AT_SQ, threadIdx.x - 128);
      mbar_wait(b_empty + 8 * vs, ring_par(ta + 62));
      wgmma_wait<0>();
      fence_regs(o);
      if (tid == 0) mbar_arrive(b_empty + 8 * vl);
      FS(2 * it + 1, 6);
      if (overflow) {
        attn_rows_exact(lds_u32(bars + 400), sq + 32768, ob + cwg * 8192, 4 * ta + 1, kc, vc);
        __syncwarp();
        if (lane == 0) mbar_arrive(b_q1);
      } else stage_o(o, l0, l1, ob + frag, lane);
      if (redo0) attn_rows_exact(lds_u32(bars + 400), sq, sq, 4 * ta, kc, vc);
      fence_proxy_async();
      __syncwarp();
      if (lane == 0) {
        if (redo0) mbar_arrive(b_ordy + 8 * cwg);
        mbar_arrive(b_ordy + 16 + 8 * cwg);
      }
      if (want_pre && !got_pre) load_pre(pre, sbase, AT_SQ, threadIdx.x - 128);
      if (redo0 || overflow) raw = false;
      named_bar_sync(3 + cwg, 128);
      FS(2 * it + 1, 7);
    }
    if (cwg == 0) named_bar_arrive(1, 256);
    if (__builtin_expect(single, 0)) {
      float acc[128];
      uint32_t j = 0, pk[64];
      #pragma unroll
      for (int i = 0; i < 64; i++) asm volatile("" : "=f"(acc[2 * i]), "=f"(acc[2 * i + 1]), "=r"(pk[i]));
      uint4* dst = g_pre;
      int left = 0;
      auto put = [&](bool last) {
        #pragma unroll
        for (int i = 0; i < PUT_N; i++) dst[i * 256] = make_uint4(pk[4 * i], pk[4 * i + 1], pk[4 * i + 2], pk[4 * i + 3]);
        dst += PUT_N * 256;
        #pragma unroll
        for (int i = 0; i < 64 - 4 * PUT_N; i++) asm volatile("mov.b32 %0, %1;" : "=r"(pk[i]) : "r"(pk[i + 4 * PUT_N]));
        __syncwarp();
        if (last && lane == 0) mbar_arrive(bars + 280);
      };
      #pragma unroll 1
      for (int ji = 0; ji < help_njobs(bid); ji++) {
        const int nk = og_pre(help_job(bid, ji));
        #pragma unroll 1
        for (int kk = 0; kk < nk; kk++, j++) {
          const uint32_t slot = ring_slot(qp_pos(j, 1));
          mbar_wait(b_full + 8 * slot, ring_par(qp_pos(j, 1)) ^ ((j >> 2) & 1));
          if (H_STAG > 0 && cwg == 1 && kk == nk - H_STAG) named_bar_sync(7, 256);
          const uint32_t a_lo = q_lo + (j & 3) * 1024, b_lo = w_base + slot * 2048;
          wgmma_fence();
          wgmma_m64n256k16_ss_tb<0, 0>(acc, a_lo, b_lo, kk != 0);
          wgmma_m64n256k16_ss_tb<2, 128>(acc, a_lo, b_lo, 1);
          wgmma_m64n256k16_ss_tb<4, 256>(acc, a_lo, b_lo, 1);
          wgmma_m64n256k16_ss_tb<6, 384>(acc, a_lo, b_lo, 1);
          wgmma_commit();
          if (H_STAG > 0 && cwg == 0 && kk == nk - 1) named_bar_arrive(7, 256);
          wgmma_wait<1>();
          if (kk > 0 && tid == 0) mbar_arrive(b_empty + 8 * ring_slot(qp_pos(j - 1, 1)));
          #pragma unroll 1
          for (int i = ji == OG_JOBS ? 0 : 16 / PUT_N - 1; i < 16 / PUT_N && left > 0; i++) put(--left == 0);
        }
        wgmma_wait<0>();
        fence_regs(acc);
        if (tid == 0) mbar_arrive(b_empty + 8 * ring_slot(qp_pos(j - 1, 1)));
        #pragma unroll
        for (int i = 0; i < 64; i++) pk[i] = pack_bf16(acc[2 * i], acc[2 * i + 1]);
        left = 16 / PUT_N;
        if (ji == PRE_X) mbar_wait(bars + 296, 0);
        dst = g_pre + help_job(bid, ji) * 2048 + threadIdx.x - 128;
      }
      #pragma unroll
      for (int i = 0; i < 16; i++) dst[i * 256] = make_uint4(pk[4 * i], pk[4 * i + 1], pk[4 * i + 2], pk[4 * i + 3]);
      __syncwarp();
      if (lane == 0) mbar_arrive(bars + 280);
      named_bar_sync(5, 256);
      if (threadIdx.x == 128) {
        #pragma unroll 1
        for (int i = 0; i < 5; i++) {
          constexpr int n = OG_HSUM;
          const int used = i == 3 ? 0 : (n + 3 - (i == 4 ? 3 : i)) / 4;
          if ((used ^ (i < 4)) & 1) {
            mbar_arrive(b_full + 8 * ring_slot(4 + i));
            mbar_arrive(b_empty + 8 * ring_slot(4 + i)); mbar_arrive(b_empty + 8 * ring_slot(4 + i));
          }
        }
        mbar_arrive(b_x);
      }
      named_bar_sync(5, 256);
      #pragma unroll
      for (int i = 0; i < 8; i++) pre[i] = make_uint4(0u, 0u, 0u, 0u);
    }
    TL_CLK(3, 1, threadIdx.x == 128);
    TL_CTA(1, threadIdx.x == 256);
    TL_END(3, tid == 0);
    TL_MARK2(19, tid == 0 && !single);
    if (bid < 128) {
      tail_consumer(bid, sbase, &tmOut, pre, cwg, w_gate, w_up);
    }
  }
}

typedef CUresult (*PFN_encodeTiled)(CUtensorMap*, CUtensorMapDataType, cuuint32_t, void*, const cuuint64_t*, const cuuint64_t*,
                                    const cuuint32_t*, const cuuint32_t*, CUtensorMapInterleave, CUtensorMapSwizzle,
                                    CUtensorMapL2promotion, CUtensorMapFloatOOBfill);

CUtensorMap make_map_2d(PFN_encodeTiled enc, const void* ptr, uint64_t inner, uint64_t outer, uint64_t stride_bytes, uint32_t box_inner, uint32_t box_outer) {
  CUtensorMap m;
  cuuint64_t gd[2] = {inner, outer}; cuuint64_t gs[1] = {stride_bytes};
  cuuint32_t bx[2] = {box_inner, box_outer}; cuuint32_t es[2] = {1, 1};
  enc(&m, CU_TENSOR_MAP_DATA_TYPE_BFLOAT16, 2, const_cast<void*>(ptr), gd, gs, bx, es, CU_TENSOR_MAP_INTERLEAVE_NONE,
      CU_TENSOR_MAP_SWIZZLE_128B, CU_TENSOR_MAP_L2_PROMOTION_L2_128B, CU_TENSOR_MAP_FLOAT_OOB_FILL_NONE);
  return m;
}

CUtensorMap make_map_3d(PFN_encodeTiled enc, const void* ptr, uint64_t cols, uint64_t rows, uint32_t box_rows, uint32_t chunks) {
  CUtensorMap m;
  cuuint64_t gd[3] = {64, rows, cols / 64}; cuuint64_t gs[2] = {cols * 2, 128};
  cuuint32_t bx[3] = {64, box_rows, chunks}; cuuint32_t es[3] = {1, 1, 1};
  enc(&m, CU_TENSOR_MAP_DATA_TYPE_BFLOAT16, 3, const_cast<void*>(ptr), gd, gs, bx, es, CU_TENSOR_MAP_INTERLEAVE_NONE,
      CU_TENSOR_MAP_SWIZZLE_128B, CU_TENSOR_MAP_L2_PROMOTION_L2_128B, CU_TENSOR_MAP_FLOAT_OOB_FILL_NONE);
  return m;
}

}

extern "C" void kernel_launch(void* const* d_in, const int* in_sizes, int n_in, void* d_out, int out_size) {
  const bf16* x      = (const bf16*)d_in[0];
  const bf16* kc     = (const bf16*)d_in[1];
  const bf16* vc     = (const bf16*)d_in[2];
  const bf16* wq     = (const bf16*)d_in[3];
  const bf16* wo     = (const bf16*)d_in[4];
  const bf16* w_r    = (const bf16*)d_in[6];
  const bf16* w_gate = (const bf16*)d_in[7];
  const bf16* w_up   = (const bf16*)d_in[8];
  const bf16* w_down = (const bf16*)d_in[9];
  const bf16* cvec   = (const bf16*)d_in[10];
  const bf16* w_mod  = (const bf16*)d_in[11];
  bf16* out = (bf16*)d_out;

  static PFN_encodeTiled enc = nullptr;
  static void *p_h = nullptr, *p_o = nullptr;
  if (!enc) {
    void* fn = nullptr; cudaDriverEntryPointQueryResult qres;
    cudaGetDriverEntryPoint("cuTensorMapEncodeTiled", &fn, cudaEnableDefault, &qres);
    enc = (PFN_encodeTiled)fn;
    cudaGetSymbolAddress(&p_h, g_pre);
    p_h = (uint4*)p_h + 16 * PRE_X * 2048;
    cudaGetSymbolAddress(&p_o, g_o);
    cudaFuncSetAttribute(fused_kernel, cudaFuncAttributeMaxDynamicSharedMemorySize, (int)AT_SMEM);
  }
  const CUtensorMap tm_h   = make_map_2d(enc, p_h, T_D, T_SEQ, T_D * 2, 64, 128);
  const CUtensorMap tm_wq  = make_map_3d(enc, wq, T_DQKV, T_D, 64, 4);
  const CUtensorMap tm_k   = make_map_3d(enc, kc, T_DH, (uint64_t)T_NH * T_SEQ, 128, 2);
  const CUtensorMap tm_v   = make_map_3d(enc, vc, T_DH, (uint64_t)T_NH * T_SEQ, 128, 2);
  const CUtensorMap tm_ost = make_map_2d(enc, p_o, T_DQKV, T_SEQ, T_DQKV * 2, 64, 64);
  const CUtensorMap tm_old = make_map_2d(enc, p_o, T_DQKV, T_SEQ, T_DQKV * 2, 64, 128);
  const CUtensorMap tm_wo  = make_map_3d(enc, wo, T_D, T_DQKV, 64, 2);
  const CUtensorMap tm_d   = make_map_3d(enc, w_down, T_D, T_F, 32, 8);

  const CUtensorMap tm_m   = make_map_2d(enc, w_mod, 6 * T_D, T_D, 6 * T_D * 2, 64, 256);
  const CUtensorMap tm_out = make_map_2d(enc, out, T_D, T_SEQ, T_D * 2, 64, 16);

  fused_kernel<<<132, 384, AT_SMEM, cudaStreamPerThread>>>(tm_h, tm_wq, tm_k, tm_v, tm_ost, tm_old, tm_wo, tm_d, tm_out, tm_m, 0u, (const uint8_t*)wo, kc, vc, x, cvec, w_mod,
             w_r, w_gate, w_up, w_down, out);
}
```

```cpp
#include <cuda_runtime.h>
#include <cuda_bf16.h>
#include <cuda.h>
#include <stdint.h>

namespace {

typedef __nv_bfloat16 bf16;

constexpr int T_SEQ = 2048, T_D = 1024, T_NH = 32, T_DH = 128, T_DQKV = 4096, T_F = 3584;

#define PRE_X 2
__device__ __align__(1024) uint4 g_pre[(16 * PRE_X + 128) * 2048];
#define g_h (reinterpret_cast<bf16*>(g_pre + 16 * PRE_X * 2048))
__device__ __align__(1024) bf16 g_o[T_SEQ * T_DQKV];
__device__ __align__(16) uint8_t g_col[8 * 1536];
__device__ __align__(16) float g_scal[64];
__device__ __align__(16) unsigned int g_hcnt[17 * 32];
__device__ __align__(128) float g_modpart[4 * 2 * T_D];
struct __align__(2048) TailMail {
  float4 part1[T_SEQ * 8];
  uint32_t key[256];
  uint4 cand[16 * 2 * 2 * 128];
  uint32_t cnt[32];
  float ypart[(T_F / 32) * 2 * T_D];
};
__device__ TailMail g_mail;
#define g_part1 g_mail.part1
#define g_key g_mail.key
#define g_cand g_mail.cand
#define CNT_Y (g_mail.cnt)
#define g_ypart g_mail.ypart

__device__ __forceinline__ uint32_t smem_u32(const void* p) { return (uint32_t)__cvta_generic_to_shared(p); }
__device__ __forceinline__ void mbar_init(uint32_t bar, uint32_t cnt) { asm volatile("mbarrier.init.shared::cta.b64 [%0], %1;" :: "r"(bar), "r"(cnt)); }
__device__ __forceinline__ void mbar_expect_tx(uint32_t bar, uint32_t bytes) { asm volatile("mbarrier.arrive.expect_tx.shared::cta.b64 _, [%0], %1;" :: "r"(bar), "r"(bytes) : "memory"); }
__device__ __forceinline__ void mbar_arrive(uint32_t bar) { asm volatile("mbarrier.arrive.shared::cta.b64 _, [%0];" :: "r"(bar) : "memory"); }
__device__ __forceinline__ void mbar_wait(uint32_t bar, uint32_t parity) {
  asm volatile("{\n.reg .pred p;\nLAB_WAIT:\nmbarrier.try_wait.parity.shared::cta.b64 p, [%0], %1;\n@!p bra LAB_WAIT;\n}\n" :: "r"(bar), "r"(parity) : "memory");
}
__device__ __forceinline__ bool mbar_test(uint32_t bar, uint32_t parity) {
  uint32_t r; asm volatile("{\n.reg .pred p;\nmbarrier.test_wait.parity.shared::cta.b64 p, [%1], %2;\nselp.u32 %0, 1, 0, p;\n}\n" : "=r"(r) : "r"(bar), "r"(parity) : "memory");
  return r != 0;
}
__device__ __forceinline__ void mbar_wait_long(uint32_t bar, uint32_t parity) {
  asm volatile("{\n.reg .pred p;\nLAB_WAIT:\nmbarrier.try_wait.parity.shared::cta.b64 p, [%0], %1, %2;\n@!p bra LAB_WAIT;\n}\n" :: "r"(bar), "r"(parity), "r"(100000) : "memory");
}
__device__ __forceinline__ uint32_t clock_lo() { uint32_t c; asm volatile("mov.u32 %0, %%clock;" : "=r"(c)); return c; }
__device__ __forceinline__ void fence_mbar_init() { asm volatile("fence.mbarrier_init.release.cluster;" ::: "memory"); }
__device__ __forceinline__ void tma_load_2d(uint32_t dst, const CUtensorMap* map, int c0, int c1, uint32_t bar) {
  asm volatile("cp.async.bulk.tensor.2d.shared::cluster.global.mbarrier::complete_tx::bytes [%0], [%1, {%3, %4}], [%2];"
    :: "r"(dst), "l"(map), "r"(bar), "r"(c0), "r"(c1) : "memory");
}
__device__ __forceinline__ uint64_t policy_evict_first() {
  uint64_t p; asm volatile("createpolicy.fractional.L2::evict_first.b64 %0, 1.0;" : "=l"(p)); return p;
}
__device__ __forceinline__ void tma_load_2d_hint(uint32_t dst, const CUtensorMap* map, int c0, int c1, uint32_t bar, uint64_t pol) {
  asm volatile("cp.async.bulk.tensor.2d.shared::cluster.global.mbarrier::complete_tx::bytes.L2::cache_hint [%0], [%1, {%3, %4}], [%2], %5;"
    :: "r"(dst), "l"(map), "r"(bar), "r"(c0), "r"(c1), "l"(pol) : "memory");
}
__device__ __forceinline__ void tma_load_3d_hint(uint32_t dst, const CUtensorMap* map, int c1, int c2, uint32_t bar, uint64_t pol) {
  asm volatile("cp.async.bulk.tensor.3d.shared::cluster.global.mbarrier::complete_tx::bytes.L2::cache_hint [%0], [%1, {%3, %4, %5}], [%2], %6;"
    :: "r"(dst), "l"(map), "r"(bar), "n"(0), "r"(c1), "r"(c2), "l"(pol) : "memory");
}
__device__ __forceinline__ void tma_load_3d(uint32_t dst, const CUtensorMap* map, int c1, int c2, uint32_t bar) {
  asm volatile("cp.async.bulk.tensor.3d.shared::cluster.global.mbarrier::complete_tx::bytes [%0], [%1, {%3, %4, %5}], [%2];"
    :: "r"(dst), "l"(map), "r"(bar), "n"(0), "r"(c1), "r"(c2) : "memory");
}
__device__ __forceinline__ void tma_store_2d(const CUtensorMap* map, uint32_t src, int c0, int c1) {
  asm volatile("cp.async.bulk.tensor.2d.global.shared::cta.bulk_group [%0, {%2, %3}], [%1];" :: "l"(map), "r"(src), "r"(c0), "r"(c1) : "memory");
}
__device__ __forceinline__ void prefetch_tmap(const CUtensorMap* map) { asm volatile("prefetch.tensormap [%0];" :: "l"(map) : "memory"); }
__device__ __forceinline__ void l2_prefetch_bulk(const void* p, uint32_t bytes) {
  asm volatile("cp.async.bulk.prefetch.L2.global [%0], %1;" :: "l"(p), "r"(bytes) : "memory");
}
__device__ __forceinline__ void bulk_commit() { asm volatile("cp.async.bulk.commit_group;" ::: "memory"); }
template<int N> __device__ __forceinline__ void bulk_wait_read() { asm volatile("cp.async.bulk.wait_group.read %0;" :: "n"(N) : "memory"); }
template<int N> __device__ __forceinline__ void bulk_wait() { asm volatile("cp.async.bulk.wait_group %0;" :: "n"(N) : "memory"); }
__device__ __forceinline__ void named_bar_sync(int id, int nthreads) { asm volatile("bar.sync %0, %1;" :: "r"(id), "r"(nthreads) : "memory"); }
__device__ __forceinline__ void named_bar_arrive(int id, int nthreads) { asm volatile("bar.arrive %0, %1;" :: "r"(id), "r"(nthreads) : "memory"); }
__device__ __forceinline__ void pass_turn(int cwg) {
  asm volatile("{\n.reg .pred p;\nsetp.ne.u32 p, %0, 0;\n@p bar.arrive 1, 256;\n@!p bar.arrive 2, 256;\n}\n" :: "r"(cwg) : "memory");
}
__device__ __forceinline__ void wgmma_fence() { asm volatile("wgmma.fence.sync.aligned;" ::: "memory"); }
__device__ __forceinline__ void wgmma_commit() { asm volatile("wgmma.commit_group.sync.aligned;" ::: "memory"); }
template<int N> __device__ __forceinline__ void wgmma_wait() { asm volatile("wgmma.wait_group.sync.aligned %0;" :: "n"(N) : "memory"); }
template<int R> __device__ __forceinline__ void reg_alloc() { asm volatile("setmaxnreg.inc.sync.aligned.u32 %0;" :: "n"(R)); }
template<int R> __device__ __forceinline__ void reg_dealloc() { asm volatile("setmaxnreg.dec.sync.aligned.u32 %0;" :: "n"(R)); }
__device__ __forceinline__ bool elect_one() {
  uint32_t pred; asm volatile("{\n.reg .pred p;\nelect.sync _|p, 0xffffffff;\nselp.u32 %0, 1, 0, p;\n}\n" : "=r"(pred)); return pred != 0;
}
__device__ __forceinline__ uint32_t pack_bf16(float lo, float hi) {
  uint32_t r; asm("cvt.rn.bf16x2.f32 %0, %1, %2;" : "=r"(r) : "f"(hi), "f"(lo)); return r;
}
__device__ __forceinline__ void stmatrix_x4(uint32_t addr, uint32_t r0, uint32_t r1, uint32_t r2, uint32_t r3) {
  asm volatile("stmatrix.sync.aligned.m8n8.x4.shared.b16 [%0], {%1, %2, %3, %4};" :: "r"(addr), "r"(r0), "r"(r1), "r"(r2), "r"(r3) : "memory");
}
__device__ __forceinline__ void fence_proxy_async() { asm volatile("fence.proxy.async.shared::cta;" ::: "memory"); }
__device__ __forceinline__ float ex2_approx(float x) { float y; asm("ex2.approx.ftz.f32 %0, %1;" : "=f"(y) : "f"(x)); return y; }
template<int N> __device__ __forceinline__ void fence_regs(float (&r)[N]) {
  #pragma unroll
  for (int i = 0; i < N; i++) asm volatile("" : "+f"(r[i]) :: "memory");
}
template<int N> __device__ __forceinline__ void zero_regs(float (&r)[N]) {
  #pragma unroll
  for (int i = 0; i < N; i += 2) asm volatile("mov.b64 {%0, %1}, 0;" : "=f"(r[i]), "=f"(r[i + 1]));
}
__device__ __forceinline__ float rbf(float x) { return __uint_as_float(pack_bf16(0.f, x)); }
__device__ __forceinline__ float bflo(uint32_t v) { return __uint_as_float(v << 16); }
__device__ __forceinline__ float bfhi(uint32_t v) { return __uint_as_float(v & 0xffff0000u); }

#define XT(i) do {} while (0)
#define TL_START(k) do {} while (0)
#define TL_END(k, cond) do {} while (0)
#define TL_CTA(i, cond) do {} while (0)
#define FS(slot, k) do {} while (0)
#define TL_MARK2(k, cond) do {} while (0)
#define TL_CLK(k, i, cond) do {} while (0)

template <int OFFA, int OFFB>
__device__ __forceinline__ void wgmma_m64n256k16_ss_tb(float (&d)[128], uint32_t a_lo, uint32_t b_lo, int scaleD) {
  asm volatile("{\n.reg .pred p;\n.reg .b32 ta, tb;\n.reg .b64 da, db;\nsetp.ne.b32 p, %130, 0;\n"
    "add.u32 ta, %128, %131;\nadd.u32 tb, %129, %132;\n"
    "mov.b64 da, {ta, 0x40000040};\nmov.b64 db, {tb, 0x40000040};\n"
    "wgmma.mma_async.sync.aligned.m64n256k16.f32.bf16.bf16 "
    "{%0, %1, %2, %3, %4, %5, %6, %7, %8, %9, %10, %11, %12, %13, %14, %15, %16, %17, %18, %19, %20, %21, %22, %23, %24, %25, %26, %27, %28, %29, %30, %31, %32, %33, %34, %35, %36, %37, %38, %39, %40, %41, %42, %43, %44, %45, %46, %47, %48, %49, %50, %51, %52, %53, %54, %55, %56, %57, %58, %59, %60, %61, %62, %63, %64, %65, %66, %67, %68, %69, %70, %71, %72, %73, %74, %75, %76, %77, %78, %79, %80, %81, %82, %83, %84, %85, %86, %87, %88, %89, %90, %91, %92, %93, %94, %95, %96, %97, %98, %99, %100, %101, %102, %103, %104, %105, %106, %107, %108, %109, %110, %111, %112, %113, %114, %115, %116, %117, %118, %119, %120, %121, %122, %123, %124, %125, %126, %127}, "
    "da, db, p, 1, 1, 0, 1;\n}\n"
    : "+f"(d[0]), "+f"(d[1]), "+f"(d[2]), "+f"(d[3]), "+f"(d[4]), "+f"(d[5]), "+f"(d[6]), "+f"(d[7]), "+f"(d[8]), "+f"(d[9]), "+f"(d[10]), "+f"(d[11]), "+f"(d[12]), "+f"(d[13]), "+f"(d[14]), "+f"(d[15]), "+f"(d[16]), "+f"(d[17]), "+f"(d[18]), "+f"(d[19]), "+f"(d[20]), "+f"(d[21]), "+f"(d[22]), "+f"(d[23]), "+f"(d[24]), "+f"(d[25]), "+f"(d[26]), "+f"(d[27]), "+f"(d[28]), "+f"(d[29]), "+f"(d[30]), "+f"(d[31]), "+f"(d[32]), "+f"(d[33]), "+f"(d[34]), "+f"(d[35]), "+f"(d[36]), "+f"(d[37]), "+f"(d[38]), "+f"(d[39]), "+f"(d[40]), "+f"(d[41]), "+f"(d[42]), "+f"(d[43]), "+f"(d[44]), "+f"(d[45]), "+f"(d[46]), "+f"(d[47]), "+f"(d[48]), "+f"(d[49]), "+f"(d[50]), "+f"(d[51]), "+f"(d[52]), "+f"(d[53]), "+f"(d[54]), "+f"(d[55]), "+f"(d[56]), "+f"(d[57]), "+f"(d[58]), "+f"(d[59]), "+f"(d[60]), "+f"(d[61]), "+f"(d[62]), "+f"(d[63]), "+f"(d[64]), "+f"(d[65]), "+f"(d[66]), "+f"(d[67]), "+f"(d[68]), "+f"(d[69]), "+f"(d[70]), "+f"(d[71]), "+f"(d[72]), "+f"(d[73]), "+f"(d[74]), "+f"(d[75]), "+f"(d[76]), "+f"(d[77]), "+f"(d[78]), "+f"(d[79]), "+f"(d[80]), "+f"(d[81]), "+f"(d[82]), "+f"(d[83]), "+f"(d[84]), "+f"(d[85]), "+f"(d[86]), "+f"(d[87]), "+f"(d[88]), "+f"(d[89]), "+f"(d[90]), "+f"(d[91]), "+f"(d[92]), "+f"(d[93]), "+f"(d[94]), "+f"(d[95]), "+f"(d[96]), "+f"(d[97]), "+f"(d[98]), "+f"(d[99]), "+f"(d[100]), "+f"(d[101]), "+f"(d[102]), "+f"(d[103]), "+f"(d[104]), "+f"(d[105]), "+f"(d[106]), "+f"(d[107]), "+f"(d[108]), "+f"(d[109]), "+f"(d[110]), "+f"(d[111]), "+f"(d[112]), "+f"(d[113]), "+f"(d[114]), "+f"(d[115]), "+f"(d[116]), "+f"(d[117]), "+f"(d[118]), "+f"(d[119]), "+f"(d[120]), "+f"(d[121]), "+f"(d[122]), "+f"(d[123]), "+f"(d[124]), "+f"(d[125]), "+f"(d[126]), "+f"(d[127])
    : "r"(a_lo), "r"(b_lo), "r"(scaleD), "n"(OFFA), "n"(OFFB));
}

template <int OFFA, int OFFB>
__device__ __forceinline__ void wgmma_m64n128k16_ss_tb(float (&d)[64], uint32_t a_lo, uint32_t b_lo, int scaleD) {
  asm volatile("{\n.reg .pred p;\n.reg .b32 ta, tb;\n.reg .b64 da, db;\nsetp.ne.b32 p, %66, 0;\n"
    "add.u32 ta, %64, %67;\nadd.u32 tb, %65, %68;\n"
    "mov.b64 da, {ta, 0x40000040};\nmov.b64 db, {tb, 0x40000040};\n"
    "wgmma.mma_async.sync.aligned.m64n128k16.f32.bf16.bf16 "
    "{%0, %1, %2, %3, %4, %5, %6, %7, %8, %9, %10, %11, %12, %13, %14, %15, %16, %17, %18, %19, %20, %21, %22, %23, %24, %25, %26, %27, %28, %29, %30, %31, %32, %33, %34, %35, %36, %37, %38, %39, %40, %41, %42, %43, %44, %45, %46, %47, %48, %49, %50, %51, %52, %53, %54, %55, %56, %57, %58, %59, %60, %61, %62, %63}, "
    "da, db, p, 1, 1, 0, 1;\n}\n"
    : "+f"(d[0]), "+f"(d[1]), "+f"(d[2]), "+f"(d[3]), "+f"(d[4]), "+f"(d[5]), "+f"(d[6]), "+f"(d[7]), "+f"(d[8]), "+f"(d[9]), "+f"(d[10]), "+f"(d[11]), "+f"(d[12]), "+f"(d[13]), "+f"(d[14]), "+f"(d[15]), "+f"(d[16]), "+f"(d[17]), "+f"(d[18]), "+f"(d[19]), "+f"(d[20]), "+f"(d[21]), "+f"(d[22]), "+f"(d[23]), "+f"(d[24]), "+f"(d[25]), "+f"(d[26]), "+f"(d[27]), "+f"(d[28]), "+f"(d[29]), "+f"(d[30]), "+f"(d[31]), "+f"(d[32]), "+f"(d[33]), "+f"(d[34]), "+f"(d[35]), "+f"(d[36]), "+f"(d[37]), "+f"(d[38]), "+f"(d[39]), "+f"(d[40]), "+f"(d[41]), "+f"(d[42]), "+f"(d[43]), "+f"(d[44]), "+f"(d[45]), "+f"(d[46]), "+f"(d[47]), "+f"(d[48]), "+f"(d[49]), "+f"(d[50]), "+f"(d[51]), "+f"(d[52]), "+f"(d[53]), "+f"(d[54]), "+f"(d[55]), "+f"(d[56]), "+f"(d[57]), "+f"(d[58]), "+f"(d[59]), "+f"(d[60]), "+f"(d[61]), "+f"(d[62]), "+f"(d[63])
    : "r"(a_lo), "r"(b_lo), "r"(scaleD), "n"(OFFA), "n"(OFFB));
}

template <int OFFB>
__device__ __forceinline__ void wgmma_m64n128k16_rs_tb(float (&d)[64], uint32_t a0, uint32_t a1, uint32_t a2, uint32_t a3, uint32_t b_lo, int scaleD) {
  asm volatile("{\n.reg .pred p;\n.reg .b32 tb;\n.reg .b64 db;\nsetp.ne.b32 p, %69, 0;\n"
    "add.u32 tb, %68, %70;\n"
    "mov.b64 db, {tb, 0x40000040};\n"
    "wgmma.mma_async.sync.aligned.m64n128k16.f32.bf16.bf16 "
    "{%0, %1, %2, %3, %4, %5, %6, %7, %8, %9, %10, %11, %12, %13, %14, %15, %16, %17, %18, %19, %20, %21, %22, %23, %24, %25, %26, %27, %28, %29, %30, %31, %32, %33, %34, %35, %36, %37, %38, %39, %40, %41, %42, %43, %44, %45, %46, %47, %48, %49, %50, %51, %52, %53, %54, %55, %56, %57, %58, %59, %60, %61, %62, %63}, "
    "{%64, %65, %66, %67}, db, p, 1, 1, 1;\n}\n"
    : "+f"(d[0]), "+f"(d[1]), "+f"(d[2]), "+f"(d[3]), "+f"(d[4]), "+f"(d[5]), "+f"(d[6]), "+f"(d[7]), "+f"(d[8]), "+f"(d[9]), "+f"(d[10]), "+f"(d[11]), "+f"(d[12]), "+f"(d[13]), "+f"(d[14]), "+f"(d[15]), "+f"(d[16]), "+f"(d[17]), "+f"(d[18]), "+f"(d[19]), "+f"(d[20]), "+f"(d[21]), "+f"(d[22]), "+f"(d[23]), "+f"(d[24]), "+f"(d[25]), "+f"(d[26]), "+f"(d[27]), "+f"(d[28]), "+f"(d[29]), "+f"(d[30]), "+f"(d[31]), "+f"(d[32]), "+f"(d[33]), "+f"(d[34]), "+f"(d[35]), "+f"(d[36]), "+f"(d[37]), "+f"(d[38]), "+f"(d[39]), "+f"(d[40]), "+f"(d[41]), "+f"(d[42]), "+f"(d[43]), "+f"(d[44]), "+f"(d[45]), "+f"(d[46]), "+f"(d[47]), "+f"(d[48]), "+f"(d[49]), "+f"(d[50]), "+f"(d[51]), "+f"(d[52]), "+f"(d[53]), "+f"(d[54]), "+f"(d[55]), "+f"(d[56]), "+f"(d[57]), "+f"(d[58]), "+f"(d[59]), "+f"(d[60]), "+f"(d[61]), "+f"(d[62]), "+f"(d[63])
    : "r"(a0), "r"(a1), "r"(a2), "r"(a3), "r"(b_lo), "r"(scaleD), "n"(OFFB));
}

template <int OFFB>
__device__ __forceinline__ void wgmma_m64n128k16_rs(float (&d)[64], uint32_t a0, uint32_t a1, uint32_t a2, uint32_t a3, uint32_t b_lo, int scaleD) {
  asm volatile("{\n.reg .pred p;\n.reg .b32 tb;\n.reg .b64 db;\nsetp.ne.b32 p, %69, 0;\n"
    "add.u32 tb, %68, %70;\n"
    "mov.b64 db, {tb, 0x40000040};\n"
    "wgmma.mma_async.sync.aligned.m64n128k16.f32.bf16.bf16 "
    "{%0, %1, %2, %3, %4, %5, %6, %7, %8, %9, %10, %11, %12, %13, %14, %15, %16, %17, %18, %19, %20, %21, %22, %23, %24, %25, %26, %27, %28, %29, %30, %31, %32, %33, %34, %35, %36, %37, %38, %39, %40, %41, %42, %43, %44, %45, %46, %47, %48, %49, %50, %51, %52, %53, %54, %55, %56, %57, %58, %59, %60, %61, %62, %63}, "
    "{%64, %65, %66, %67}, db, p, 1, 1, 0;\n}\n"
    : "+f"(d[0]), "+f"(d[1]), "+f"(d[2]), "+f"(d[3]), "+f"(d[4]), "+f"(d[5]), "+f"(d[6]), "+f"(d[7]), "+f"(d[8]), "+f"(d[9]), "+f"(d[10]), "+f"(d[11]), "+f"(d[12]), "+f"(d[13]), "+f"(d[14]), "+f"(d[15]), "+f"(d[16]), "+f"(d[17]), "+f"(d[18]), "+f"(d[19]), "+f"(d[20]), "+f"(d[21]), "+f"(d[22]), "+f"(d[23]), "+f"(d[24]), "+f"(d[25]), "+f"(d[26]), "+f"(d[27]), "+f"(d[28]), "+f"(d[29]), "+f"(d[30]), "+f"(d[31]), "+f"(d[32]), "+f"(d[33]), "+f"(d[34]), "+f"(d[35]), "+f"(d[36]), "+f"(d[37]), "+f"(d[38]), "+f"(d[39]), "+f"(d[40]), "+f"(d[41]), "+f"(d[42]), "+f"(d[43]), "+f"(d[44]), "+f"(d[45]), "+f"(d[46]), "+f"(d[47]), "+f"(d[48]), "+f"(d[49]), "+f"(d[50]), "+f"(d[51]), "+f"(d[52]), "+f"(d[53]), "+f"(d[54]), "+f"(d[55]), "+f"(d[56]), "+f"(d[57]), "+f"(d[58]), "+f"(d[59]), "+f"(d[60]), "+f"(d[61]), "+f"(d[62]), "+f"(d[63])
    : "r"(a0), "r"(a1), "r"(a2), "r"(a3), "r"(b_lo), "r"(scaleD), "n"(OFFB));
}

__device__ __forceinline__ uint4 ldg_nc_v4(const void* p) {
  uint4 v;
    asm volatile("{\n.reg .b64 pol;\ncreatepolicy.fractional.L2::evict_first.b64 pol, 1.0;\n"
                 "ld.global.nc.L1::no_allocate.L2::cache_hint.v4.u32 {%0, %1, %2, %3}, [%4], pol;\n}\n" : "=r"(v.x), "=r"(v.y), "=r"(v.z), "=r"(v.w) : "l"(p));
  return v;
}
__device__ __forceinline__ void unpack8(const uint4& u, float (&v)[8]) {
  v[0] = bflo(u.x); v[1] = bfhi(u.x); v[2] = bflo(u.y); v[3] = bfhi(u.y);
  v[4] = bflo(u.z); v[5] = bfhi(u.z); v[6] = bflo(u.w); v[7] = bfhi(u.w);
}
__device__ __forceinline__ void fma8(float (&acc)[8], float s, const uint4& w) {
  acc[0] = fmaf(s, bflo(w.x), acc[0]); acc[1] = fmaf(s, bfhi(w.x), acc[1]); acc[2] = fmaf(s, bflo(w.y), acc[2]); acc[3] = fmaf(s, bfhi(w.y), acc[3]);
  acc[4] = fmaf(s, bflo(w.z), acc[4]); acc[5] = fmaf(s, bfhi(w.z), acc[5]); acc[6] = fmaf(s, bflo(w.w), acc[6]); acc[7] = fmaf(s, bfhi(w.w), acc[7]);
}
__device__ __forceinline__ float rcp_approx(float x) { float y; asm("rcp.approx.ftz.f32 %0, %1;" : "=f"(y) : "f"(x)); return y; }
__device__ __forceinline__ float sigmoid_f(float v) { return rcp_approx(1.0f + ex2_approx(v * -1.4426950408889634f)); }
__device__ __forceinline__ float silu_bf(float v) { return rbf(v * sigmoid_f(v)); }
__device__ __forceinline__ uint32_t rank_key(float r, int idx) {
  const uint32_t b = __float_as_uint(r) >> 16;
  const uint32_t u = (r != r) ? 0u : ((b & 0x8000u) ? (~b & 0xffffu) : (b | 0x8000u));
  return (u << 16) | (0xffffu - (uint32_t)idx);
}
__device__ __forceinline__ void warp_top2(uint32_t& k1, uint32_t& k2) {
  const uint32_t m1 = __reduce_max_sync(0xffffffffu, k1);
  k2 = __reduce_max_sync(0xffffffffu, k1 == m1 ? k2 : k1);
  k1 = m1;
}
__device__ __forceinline__ uint32_t bmul2(uint32_t a, uint32_t b) { uint32_t r; asm("mul.rn.bf16x2 %0, %1, %2;" : "=r"(r) : "r"(a), "r"(b)); return r; }
__device__ __forceinline__ uint32_t badd2(uint32_t a, uint32_t b) { uint32_t r; asm("add.rn.bf16x2 %0, %1, %2;" : "=r"(r) : "r"(a), "r"(b)); return r; }
__device__ __forceinline__ uint32_t bsub2(uint32_t a, uint32_t b) { uint32_t r; asm("sub.rn.bf16x2 %0, %1, %2;" : "=r"(r) : "r"(a), "r"(b)); return r; }
__device__ __forceinline__ float sqrt_approx(float x) { float y; asm("sqrt.approx.f32 %0, %1;" : "=f"(y) : "f"(x)); return y; }
__device__ __forceinline__ uint32_t ln_norm2(uint32_t x1, uint32_t mb2, float inv) {
  const uint32_t d = bsub2(x1, mb2);
  return pack_bf16(bflo(d) * inv, bfhi(d) * inv);
}
__device__ __forceinline__ uint32_t bfma2(uint32_t a, uint32_t b, uint32_t c) { uint32_t r; asm("fma.rn.bf16x2 %0, %1, %2, %3;" : "=r"(r) : "r"(a), "r"(b), "r"(c)); return r; }
__device__ __forceinline__ uint32_t ln_norm2b(uint32_t x1, uint32_t mb2, uint32_t ih, uint32_t il) {
  const uint32_t d = bsub2(x1, mb2);
  return bfma2(d, ih, bmul2(d, il));
}
__device__ __forceinline__ uint32_t ln_mod2(uint32_t x1, uint32_t mb2, float inv, uint32_t c1, uint32_t sb) { return badd2(bmul2(ln_norm2(x1, mb2, inv), c1), sb); }
__device__ __forceinline__ void ldmatrix_x4(uint32_t addr, uint32_t& r0, uint32_t& r1, uint32_t& r2, uint32_t& r3) {
  asm volatile("ldmatrix.sync.aligned.m8n8.x4.shared.b16 {%0, %1, %2, %3}, [%4];" : "=r"(r0), "=r"(r1), "=r"(r2), "=r"(r3) : "r"(addr) : "memory");
}
__device__ __forceinline__ uint4 ldg_stream_v4(const void* p, uint64_t pol) {
  uint4 v; asm volatile("ld.global.nc.L1::no_allocate.L2::cache_hint.L2::128B.v4.u32 {%0, %1, %2, %3}, [%4], %5;" : "=r"(v.x), "=r"(v.y), "=r"(v.z), "=r"(v.w) : "l"(p), "l"(pol)); return v;
}
__device__ __forceinline__ void bulk_load_hint(uint32_t dst, const void* src, uint32_t bytes, uint32_t bar, uint64_t pol) {
  asm volatile("cp.async.bulk.shared::cluster.global.mbarrier::complete_tx::bytes.L2::cache_hint [%0], [%1], %2, [%3], %4;"
    :: "r"(dst), "l"(src), "r"(bytes), "r"(bar), "l"(pol) : "memory");
}
__device__ __forceinline__ void red_release_add(unsigned int* p, unsigned int v) { asm volatile("red.release.gpu.global.add.u32 [%0], %1;" :: "l"(p), "r"(v) : "memory"); }
__device__ __forceinline__ unsigned int ld_acquire(const unsigned int* p) { unsigned int v; asm volatile("ld.acquire.gpu.global.u32 %0, [%1];" : "=r"(v) : "l"(p) : "memory"); return v; }
__device__ __forceinline__ void spin_until(const unsigned int* p, unsigned int target) {
  #pragma unroll 1
  for (unsigned int i = 0; i < (1u << 22); i++) { if (ld_acquire(p) >= target) return; }
}
__device__ __forceinline__ float lds_f32(uint32_t a) { float v; asm volatile("ld.shared.f32 %0, [%1];" : "=f"(v) : "r"(a) : "memory"); return v; }
__device__ __forceinline__ float2 lds_f32x2(uint32_t a) { float2 v; asm volatile("ld.shared.v2.f32 {%0, %1}, [%2];" : "=f"(v.x), "=f"(v.y) : "r"(a) : "memory"); return v; }
__device__ __forceinline__ uint2 lds_u32x2(uint32_t a) { uint2 v; asm volatile("ld.shared.v2.u32 {%0, %1}, [%2];" : "=r"(v.x), "=r"(v.y) : "r"(a) : "memory"); return v; }
__device__ __forceinline__ uint32_t lds_u32(uint32_t a) { uint32_t v; asm volatile("ld.shared.u32 %0, [%1];" : "=r"(v) : "r"(a) : "memory"); return v; }
__device__ __forceinline__ void sts_u32(uint32_t a, uint32_t v) { asm volatile("st.shared.u32 [%0], %1;" :: "r"(a), "r"(v) : "memory"); }
__device__ __forceinline__ void sts_u32x2(uint32_t a, uint32_t x, uint32_t y) { asm volatile("st.shared.v2.u32 [%0], {%1, %2};" :: "r"(a), "r"(x), "r"(y) : "memory"); }
__device__ __forceinline__ void sts_f32(uint32_t a, float v) { asm volatile("st.shared.f32 [%0], %1;" :: "r"(a), "f"(v) : "memory"); }
__device__ __forceinline__ void sts_f32x2(uint32_t a, float x, float y) { asm volatile("st.shared.v2.f32 [%0], {%1, %2};" :: "r"(a), "f"(x), "f"(y) : "memory"); }
__device__ __forceinline__ void sts_f32x4(uint32_t a, float x, float y, float z, float w) { asm volatile("st.shared.v4.f32 [%0], {%1, %2, %3, %4};" :: "r"(a), "f"(x), "f"(y), "f"(z), "f"(w) : "memory"); }

__device__ __forceinline__ uint4 lds_u32x4(uint32_t a) { uint4 v; asm volatile("ld.shared.v4.u32 {%0, %1, %2, %3}, [%4];" : "=r"(v.x), "=r"(v.y), "=r"(v.z), "=r"(v.w) : "r"(a) : "memory"); return v; }
__device__ __forceinline__ void sts_u32x4(uint32_t a, uint32_t x, uint32_t y, uint32_t z, uint32_t w) { asm volatile("st.shared.v4.u32 [%0], {%1, %2, %3, %4};" :: "r"(a), "r"(x), "r"(y), "r"(z), "r"(w) : "memory"); }
__device__ __forceinline__ void st_tagged(float* p, float v) {
  const uint32_t b = __float_as_uint(v);
  asm volatile("st.relaxed.gpu.global.u32 [%0], %1;" :: "l"(p), "r"(b == 0u ? 0x80000000u : b) : "memory");
}
__device__ __forceinline__ void st_tagged4(float* p, float x, float y, float z, float w) {
  const uint32_t a = __float_as_uint(x), b = __float_as_uint(y), c = __float_as_uint(z), d = __float_as_uint(w);
  asm volatile("st.relaxed.gpu.global.v4.u32 [%0], {%1, %2, %3, %4};" :: "l"(p), "r"(a == 0u ? 0x80000000u : a), "r"(b == 0u ? 0x80000000u : b),
               "r"(c == 0u ? 0x80000000u : c), "r"(d == 0u ? 0x80000000u : d) : "memory");
}
__device__ __forceinline__ void st_tagged4_lsb(float* p, float x, float y, float z, float w) {
  asm volatile("st.relaxed.gpu.global.v4.u32 [%0], {%1, %2, %3, %4};" :: "l"(p), "r"(__float_as_uint(x) | 1u), "r"(__float_as_uint(y) | 1u),
               "r"(__float_as_uint(z) | 1u), "r"(__float_as_uint(w) | 1u) : "memory");
}
__device__ __forceinline__ void st_relaxed2(void* p, uint32_t a, uint32_t b) { asm volatile("st.relaxed.gpu.global.v2.u32 [%0], {%1, %2};" :: "l"(p), "r"(a), "r"(b) : "memory"); }
__device__ __forceinline__ float4 ld_tagged4(const float* p) {
  float4 v; asm volatile("ld.relaxed.gpu.global.v4.f32 {%0, %1, %2, %3}, [%4];" : "=f"(v.x), "=f"(v.y), "=f"(v.z), "=f"(v.w) : "l"(p) : "memory"); return v;
}
__device__ __forceinline__ bool tagged4(const float4& v) {
  return __float_as_uint(v.x) != 0u && __float_as_uint(v.y) != 0u && __float_as_uint(v.z) != 0u && __float_as_uint(v.w) != 0u;
}
__device__ __forceinline__ void hint_arrive(uint32_t* p) { asm volatile("red.relaxed.gpu.global.add.u32 [%0], 1;" :: "l"(p) : "memory"); }
__device__ __forceinline__ void hint_wait(const uint32_t* p, uint32_t target) {
  uint32_t v = 0u;
  #pragma unroll 1
  for (unsigned int i = 0; i < (1u << 22) && v < target; i++) asm volatile("ld.relaxed.gpu.global.u32 %0, [%1];" : "=r"(v) : "l"(p) : "memory");
}
__device__ __forceinline__ void fence_proxy_async_global() { asm volatile("fence.proxy.async.global;" ::: "memory"); }

#define H_SPLIT 1
#define X_DLY 1200
#define W_DLY 1900
#define W_FIRST 2200
#define PRE_B 2
template <int J0, int J1>
__device__ __forceinline__ void load_parts(float2 (&pa)[J1 - J0][4], int t2) {
  #pragma unroll
  for (int j = J0; j < J1; j++)
    #pragma unroll
    for (int k = 0; k < 4; k++)
      asm volatile("ld.relaxed.gpu.global.v2.f32 {%0, %1}, [%2];" : "=f"(pa[j - J0][k].x), "=f"(pa[j - J0][k].y)
                   : "l"(g_modpart + k * 2 * T_D + (t2 >> 7) * T_D + j * 256 + (t2 & 127) * 2) : "memory");
}
template <int J0, int J1>
__device__ __forceinline__ void finish_parts(float2 (&pa)[J1 - J0][4], bool loaded, int t2, uint32_t tab) {
  #pragma unroll 1
  for (unsigned int spin = 0; spin < (1u << 22); spin++) {
    if (!loaded) load_parts<J0, J1>(pa, t2);
    loaded = false;
    bool ok = true;
    #pragma unroll
    for (int j = 0; j < J1 - J0; j++)
      #pragma unroll
      for (int k = 0; k < 4; k++) ok &= (__float_as_uint(pa[j][k].x) != 0u) & (__float_as_uint(pa[j][k].y) != 0u);
    if (__all_sync(0xffffffffu, ok)) break;
  }
  #pragma unroll
  for (int j = J0; j < J1; j++) {
    const float2* q = pa[j - J0];
    const uint32_t m = pack_bf16(((q[0].x + q[1].x) + q[2].x) + q[3].x, ((q[0].y + q[1].y) + q[2].y) + q[3].y);
    sts_u32(tab + (t2 >> 7) * 2048 + j * 512 + (t2 & 127) * 4, t2 >= 128 ? badd2(m, 0x3F803F80u) : m);
  }
}
__device__ __forceinline__ int head_cb(uint32_t bid) { return (bid & 16) | ((bid & 3) << 2) | ((bid >> 2) & 3); }
__device__ __forceinline__ void head_phase(uint32_t bid, uint32_t scr, uint32_t xs, uint32_t b_x, uint32_t b_go, uint32_t b_head, int t2, uint32_t zero, const bf16* __restrict__ cvec, const bf16* __restrict__ w_mod) {
  const int lane = t2 & 31, w8 = t2 >> 5;
  const int cb = head_cb(bid), ks = bid >> 5;
  const bool early = (cb & 15) < 4 * H_SPLIT;
  const uint32_t ws = (xs - 32768 + (t2 >> 3) * 128 + (((t2 ^ (t2 >> 3)) & 7) << 4)) ^ zero;
  const float cv = __bfloat162float(cvec[ks * 256 + t2]);
  const bf16* wsrc = w_mod + (size_t)(ks * 256 + (t2 >> 3)) * (6 * T_D) + cb * 64 + (t2 & 7) * 8;
  if (early) {
    const uint64_t pol = policy_evict_first();
    #pragma unroll 2
    for (int i = 0; i < 8; i++)
      asm volatile("cp.async.cg.shared.global.L2::cache_hint [%0], [%1], 16, %2;" :: "r"(ws + i * 4096), "l"(wsrc + (size_t)i * 32 * 6 * T_D), "l"(pol) : "memory");
  }
  sts_f32(scr + t2 * 4, silu_bf(cv));
  named_bar_sync(6, 384);
  TL_MARK2(1, t2 == 0);
  uint4 xv[2][4];
  uint32_t mb2[2], ih[2], il[2];
  auto norm = [&](int j) {
    #pragma unroll
    for (int r = 0; r < 2; r++) {
      xv[r][j].x = ln_norm2b(xv[r][j].x, mb2[r], ih[r], il[r]); xv[r][j].y = ln_norm2b(xv[r][j].y, mb2[r], ih[r], il[r]);
      xv[r][j].z = ln_norm2b(xv[r][j].z, mb2[r], ih[r], il[r]); xv[r][j].w = ln_norm2b(xv[r][j].w, mb2[r], ih[r], il[r]);
    }
  };
  auto modulate = [&](int j) {
    const uint4 sa = lds_u32x4(scr + 8192 + j * 512 + lane * 16), c1 = lds_u32x4(scr + 8192 + 2048 + j * 512 + lane * 16);
    #pragma unroll
    for (int r = 0; r < 2; r++) {
      xv[r][j].x = badd2(bmul2(xv[r][j].x, c1.x), sa.x); xv[r][j].y = badd2(bmul2(xv[r][j].y, c1.y), sa.y);
      xv[r][j].z = badd2(bmul2(xv[r][j].z, c1.z), sa.z); xv[r][j].w = badd2(bmul2(xv[r][j].w, c1.w), sa.w);
    }
  };
  auto store = [&](int j) {
    #pragma unroll
    for (int r = 0; r < 2; r++) *reinterpret_cast<uint4*>(g_h + (size_t)(bid * 16 + 2 * w8 + r) * T_D + j * 256 + lane * 8) = xv[r][j];
  };
  #pragma unroll 1
  for (int ph = 0; ph < 2; ph++) {
    if ((ph == 0) == early) {
      asm volatile("cp.async.wait_all;" ::: "memory");
      if (!early) mbar_wait(b_x + 168, 0);
      float acc[8];
      #pragma unroll
      for (int j = 0; j < 8; j++) acc[j] = 0.f;
      #pragma unroll
      for (int i = 0; i < 8; i++) fma8(acc, lds_f32(scr + ((t2 >> 3) + 32 * i) * 4), lds_u32x4(ws + i * 4096));
      #pragma unroll
      for (int j = 0; j < 4; j++) { const bool up = lane & 16; acc[j] = (up ? acc[4 + j] : acc[j]) + __shfl_xor_sync(0xffffffffu, up ? acc[j] : acc[4 + j], 16); }
      #pragma unroll
      for (int j = 0; j < 2; j++) { const bool up = lane & 8; acc[j] = (up ? acc[2 + j] : acc[j]) + __shfl_xor_sync(0xffffffffu, up ? acc[j] : acc[2 + j], 8); }
      sts_f32x2(scr + 1024 + w8 * 256 + (lane & 7) * 32 + (lane >> 3) * 8, acc[0], acc[1]);
      named_bar_sync(5, 256);
      if (t2 < 64) {
        float sum = 0.f;
        #pragma unroll
        for (int i = 0; i < 8; i++) sum += lds_f32(scr + 1024 + i * 256 + t2 * 4);
        st_tagged(g_modpart + ks * 2 * T_D + cb * 64 + t2, sum);
        TL_MARK2(early ? 2 : 6, t2 == 0);
      }
    } else {
      float2 pa[H_SPLIT][4];
      mbar_wait(b_x, 0);
      TL_MARK2(18, t2 == 0);
      load_parts<0, H_SPLIT>(pa, t2);
      #pragma unroll
      for (int r = 0; r < 2; r++)
        #pragma unroll
        for (int j = 0; j < 4; j++) xv[r][j] = lds_u32x4(xs + (2 * w8 + r) * 2048 + j * 512 + lane * 16);
  {
    float st[4] = {0.f, 0.f, 0.f, 0.f};
    #pragma unroll
    for (int r = 0; r < 2; r++)
      #pragma unroll
      for (int j = 0; j < 4; j++) {
        float v[8];
        unpack8(xv[r][j], v);
        st[2 * r] += ((v[0] + v[1]) + (v[2] + v[3])) + ((v[4] + v[5]) + (v[6] + v[7]));
        st[2 * r + 1] += fmaf(v[0], v[0], fmaf(v[1], v[1], fmaf(v[2], v[2], v[3] * v[3]))) + fmaf(v[4], v[4], fmaf(v[5], v[5], fmaf(v[6], v[6], v[7] * v[7])));
      }
    #pragma unroll
    for (int k = 0; k < 2; k++) { const bool up = lane & 16; st[k] = (up ? st[2 + k] : st[k]) + __shfl_xor_sync(0xffffffffu, up ? st[k] : st[2 + k], 16); }
    #pragma unroll
    for (int o = 8; o > 0; o >>= 1) { st[0] += __shfl_xor_sync(0xffffffffu, st[0], o); st[1] += __shfl_xor_sync(0xffffffffu, st[1], o); }
    const float mean = st[0] * (1.0f / T_D);
    const float inv = rcp_approx(rbf(sqrt_approx(rbf(rbf(fmaxf(fmaf(-mean, mean, st[1] * (1.0f / T_D)), 0.f)) + 1e-05f))));
    const uint32_t m = pack_bf16(mean, mean), h = pack_bf16(inv - rbf(inv), inv);
    #pragma unroll
    for (int r = 0; r < 2; r++) {
      mb2[r] = __shfl_sync(0xffffffffu, m, 16 * r);
      const uint32_t hr = __shfl_sync(0xffffffffu, h, 16 * r);
      ih[r] = __byte_perm(hr, hr, 0x3232); il[r] = __byte_perm(hr, hr, 0x1010);
    }
  }
      #pragma unroll
      for (int j = 0; j < H_SPLIT; j++) norm(j);
      TL_MARK2(5, t2 == 0);
      finish_parts<0, H_SPLIT>(pa, true, t2, scr + 8192);
      named_bar_sync(5, 256);
      TL_MARK2(7, t2 == 0);
      #pragma unroll
      for (int j = 0; j < H_SPLIT; j++) { modulate(j); store(j); }
      named_bar_arrive(9, 288);
    }
  }
  #pragma unroll
  for (int j = H_SPLIT; j < 4; j++) norm(j);
  float2 pb[4 - H_SPLIT][4];
  finish_parts<H_SPLIT, 4>(pb, false, t2, scr + 8192);
  named_bar_sync(5, 256);
  TL_MARK2(17, t2 == 0);
  #pragma unroll
  for (int j = H_SPLIT; j < 4; j++) modulate(j);
  __syncwarp();
  if (lane == 0) mbar_arrive(b_head + (xv[1][3].w & zero));
  mbar_wait(b_go, 0);
  #pragma unroll
  for (int j = H_SPLIT; j < 4; j++) store(j);
  named_bar_arrive(8, 288);
}

#define MOD_AT (b_empty + 8)
#define MOD_SPLIT 20
__device__ __forceinline__ void mod_rest(uint32_t bid, uint32_t scr, uint32_t b_go, int t, const bf16* __restrict__ cvec, const bf16* __restrict__ w_mod, const bf16* __restrict__ w_r) {
  const int lane = t & 31;
  #pragma unroll 1
  for (int i = t; i < T_D / 2; i += 64) {
    const uint32_t c2 = *reinterpret_cast<const uint32_t*>(cvec + 2 * i);
    sts_u32(scr + i * 4, pack_bf16(silu_bf(bflo(c2)), silu_bf(bfhi(c2))));
  }
  named_bar_sync(11, 64);
  const bf16* wp = w_mod + (size_t)(2 * (t >> 2)) * (6 * T_D) + 2 * T_D + bid * 32 + (t & 3) * 8;
  float acc[8];
  #pragma unroll
  for (int i = 0; i < 8; i++) acc[i] = 0.f;
  #pragma unroll 1
  for (int i = 0; i < 32; i += 2) {
    if (i == MOD_SPLIT) mbar_wait_long(b_go, 0);
    const uint4 w0 = ldg_nc_v4(wp), w1 = ldg_nc_v4(wp + 6 * T_D), w2 = ldg_nc_v4(wp + 32 * 6 * T_D), w3 = ldg_nc_v4(wp + 33 * 6 * T_D);
    wp += 64 * 6 * T_D;
    const uint32_t s0 = lds_u32(scr + (i * 16 + (t >> 2)) * 4), s1 = lds_u32(scr + (i * 16 + 16 + (t >> 2)) * 4);
    fma8(acc, bflo(s0), w0); fma8(acc, bfhi(s0), w1); fma8(acc, bflo(s1), w2); fma8(acc, bfhi(s1), w3);
  }
  #pragma unroll
  for (int j = 0; j < 4; j++) { const bool up = lane & 16; acc[j] = (up ? acc[4 + j] : acc[j]) + __shfl_xor_sync(0xffffffffu, up ? acc[j] : acc[4 + j], 16); }
  #pragma unroll
  for (int j = 0; j < 2; j++) { const bool up = lane & 8; acc[j] = (up ? acc[2 + j] : acc[j]) + __shfl_xor_sync(0xffffffffu, up ? acc[j] : acc[2 + j], 8); }
  { const bool up = lane & 4; acc[0] = (up ? acc[1] : acc[0]) + __shfl_xor_sync(0xffffffffu, up ? acc[0] : acc[1], 4); }
  if (t >= 32) sts_f32(scr + 2048 + lane * 4, acc[0]);
  named_bar_sync(11, 64);
  if (__shfl_sync(0xffffffffu, t, 0) < 32) {
    const int kind = bid >> 5;
    float v = rbf(acc[0] + lds_f32(scr + 2048 + lane * 4));
    const int col = (bid & 31) * 32 + (lane & 3) * 8 + (lane >> 2);
    uint8_t* dst = g_col + (col >> 7) * 1536;
    if (kind == 2) v = rbf(1.0f + v);
    float vw = v * __bfloat162float(w_r[col]);
    if (kind == 2) {
      const int c = col & 127, i = (c & ~15) + ((c >> 1) & 3) * 4 + ((c >> 3) & 1) * 2 + (c & 1);
      reinterpret_cast<bf16*>(dst)[i] = __float2bfloat16_rn(vw);
      reinterpret_cast<bf16*>(dst)[128 + i] = __float2bfloat16_rn(vw - rbf(vw));
    }
    reinterpret_cast<bf16*>(dst + 512 + (kind & 1) * 512 + (kind >> 1) * 256)[col & 127] = __float2bfloat16_rn(v);
    #pragma unroll
    for (int o = 16; o > 0; o >>= 1) vw += __shfl_xor_sync(0xffffffffu, vw, o);
    if (lane == 0 && (kind == 1 || kind == 2)) g_scal[95 - bid] = vw;
  }
  #pragma unroll 1
  for (int i = bid * 64 + t; i < (int)(sizeof(g_mail) / 16); i += 128 * 64) reinterpret_cast<uint4*>(&g_mail)[i] = make_uint4(0u, 0u, 0u, 0u);
  named_bar_sync(11, 64);
  if (t == 0) red_release_add(&g_hcnt[0], 1u);
}

constexpr int AT_NBLK = T_SEQ / 128;
constexpr float AT_HEAD = 7.0f;
#define WO_LATE 12
#define QP_STAG 3
#define AT_SPLIT 28
#define AT_PIN 12
#define PINB 4
constexpr int AT_NFULL = 124;
constexpr int AT_PREG = 40, AT_CREG = 232;
constexpr uint32_t AT_SQ = 5 * 32768;
constexpr float AT_C = 0.08838834764831845f * 1.4426950408889634f;
constexpr float AT_RAW_LO = -16.0f, AT_RAW_HI = 24.0f;
constexpr float AT_RAW_SUM = 281474976710656.0f, AT_RAW_MIN = 9.094947017729282e-13f;
constexpr uint32_t AT_SBAR = AT_SQ + 65536 + 256;
constexpr uint32_t AT_SMEM = AT_SQ + 65536 + 3072;

__device__ __forceinline__ uint32_t ring_slot(uint32_t t) { return t - 5u * ((t * 205u) >> 10); }
__device__ __forceinline__ uint32_t qp_pos(uint32_t j, uint32_t it) { return 4u * it + (j & 3u) + ((j & 3u) == 3u ? it : 0u); }
__device__ __forceinline__ uint32_t ring_par(uint32_t t) { return ((t * 205u) >> 10) & 1u; }
__device__ __forceinline__ void softmax_rowmax(const float (&s)[64], float& mx0, float& mx1) {
  float a0 = fmaxf(s[0], s[1]), a1 = fmaxf(s[4], s[5]), a2 = fmaxf(s[8], s[9]), a3 = fmaxf(s[12], s[13]);
  float b0 = fmaxf(s[2], s[3]), b1 = fmaxf(s[6], s[7]), b2 = fmaxf(s[10], s[11]), b3 = fmaxf(s[14], s[15]);
  #pragma unroll
  for (int j = 4; j < 16; j += 4) {
    a0 = fmaxf(a0, fmaxf(s[4 * j + 0], s[4 * j + 1]));  b0 = fmaxf(b0, fmaxf(s[4 * j + 2], s[4 * j + 3]));
    a1 = fmaxf(a1, fmaxf(s[4 * j + 4], s[4 * j + 5]));  b1 = fmaxf(b1, fmaxf(s[4 * j + 6], s[4 * j + 7]));
    a2 = fmaxf(a2, fmaxf(s[4 * j + 8], s[4 * j + 9]));  b2 = fmaxf(b2, fmaxf(s[4 * j + 10], s[4 * j + 11]));
    a3 = fmaxf(a3, fmaxf(s[4 * j + 12], s[4 * j + 13])); b3 = fmaxf(b3, fmaxf(s[4 * j + 14], s[4 * j + 15]));
  }
  mx0 = fmaxf(fmaxf(a0, a1), fmaxf(a2, a3));
  mx1 = fmaxf(fmaxf(b0, b1), fmaxf(b2, b3));
  mx0 = fmaxf(mx0, __shfl_xor_sync(0xffffffffu, mx0, 1));
  mx1 = fmaxf(mx1, __shfl_xor_sync(0xffffffffu, mx1, 1));
  mx0 = fmaxf(mx0, __shfl_xor_sync(0xffffffffu, mx0, 2));
  mx1 = fmaxf(mx1, __shfl_xor_sync(0xffffffffu, mx1, 2));
}
__device__ __forceinline__ void softmax_sub(float (&s)[64], float mc0, float mc1) {
  #pragma unroll
  for (int j = 0; j < 16; j++) { s[4 * j] -= mc0; s[4 * j + 1] -= mc0; s[4 * j + 2] -= mc1; s[4 * j + 3] -= mc1; }
}
template <int LO, int HI>
__device__ __forceinline__ void softmax_exp(float (&s)[64]) {
  #pragma unroll
  for (int i = LO; i < HI; i++) s[i] = ex2_approx(s[i]);
}
__device__ __forceinline__ bool softmax_mode(const float (&s)[64], float& mc0, float& mc1) {
  softmax_rowmax(s, mc0, mc1);
  const bool raw = __all_sync(0xffffffffu, mc0 >= AT_RAW_LO && mc0 <= AT_RAW_HI && mc1 >= AT_RAW_LO && mc1 <= AT_RAW_HI);
  mc0 += AT_HEAD; mc1 += AT_HEAD;
  return raw;
}
__device__ __forceinline__ void rowsum_p(const uint32_t (&p)[32], uint32_t& t0, uint32_t& t1) {
  uint32_t a[16];
  #pragma unroll
  for (int i = 0; i < 8; i++) { a[2 * i] = badd2(p[4 * i], p[4 * i + 2]); a[2 * i + 1] = badd2(p[4 * i + 1], p[4 * i + 3]); }
  #pragma unroll
  for (int i = 0; i < 4; i++) { a[2 * i] = badd2(a[4 * i], a[4 * i + 2]); a[2 * i + 1] = badd2(a[4 * i + 1], a[4 * i + 3]); }
  t0 = badd2(badd2(a[0], a[2]), badd2(a[4], a[6]));
  t1 = badd2(badd2(a[1], a[3]), badd2(a[5], a[7]));
}
__device__ __forceinline__ void add_rowsum(const uint32_t (&p)[32], float& l0, float& l1) {
  uint32_t t0, t1;
  rowsum_p(p, t0, t1);
  l0 += bflo(t0) + bfhi(t0); l1 += bflo(t1) + bfhi(t1);
}
__device__ __forceinline__ void pack_p(uint32_t (&p)[32], const float (&s)[64]) {
  #pragma unroll
  for (int i = 0; i < 32; i++) p[i] = pack_bf16(s[2 * i], s[2 * i + 1]);
}
__device__ __noinline__ void attn_rows_exact(uint32_t bid, uint32_t sq, uint32_t so, int hsel, const bf16* __restrict__ kh, const bf16* __restrict__ vh) {
  const int warp = (threadIdx.x >> 5) & 3, lane = threadIdx.x & 31;
  const size_t hofs = (size_t)((bid < 128 ? bid >> 4 : 15) * 2 + hsel) * T_SEQ * T_DH;
  kh += hofs; vh += hofs;
  #pragma unroll 1
  for (int r = 16 * warp; r < 16 * warp + 16; r++) {
    const uint32_t ad = (lane >> 4) * 16384 + r * 128 + ((((lane & 15) >> 1) ^ (r & 7)) << 4) + (lane & 1) * 8;
    uint2 qv; asm volatile("ld.shared.v2.u32 {%0, %1}, [%2];" : "=r"(qv.x), "=r"(qv.y) : "r"(sq + ad) : "memory");
    const float q0 = bflo(qv.x), q1 = bfhi(qv.x), q2 = bflo(qv.y), q3 = bfhi(qv.y);
    float m = -INFINITY, l = 0.f, o0 = 0.f, o1 = 0.f, o2 = 0.f, o3 = 0.f;
    #pragma unroll 1
    for (int key = 0; key < T_SEQ; key++) {
      const uint2 kv = *reinterpret_cast<const uint2*>(kh + (size_t)key * T_DH + lane * 4);
      const uint2 vv = *reinterpret_cast<const uint2*>(vh + (size_t)key * T_DH + lane * 4);
      float sc = (q0 * bflo(kv.x) + q1 * bfhi(kv.x)) + (q2 * bflo(kv.y) + q3 * bfhi(kv.y));
      #pragma unroll
      for (int o = 16; o > 0; o >>= 1) sc += __shfl_xor_sync(0xffffffffu, sc, o);
      const float mn = fmaxf(m, sc);
      const float al = (m == mn) ? 1.0f : ex2_approx(m - mn), p = rbf(ex2_approx(sc - mn));
      m = mn;
      l = fmaf(l, al, p);
      o0 = fmaf(o0, al, p * bflo(vv.x)); o1 = fmaf(o1, al, p * bfhi(vv.x));
      o2 = fmaf(o2, al, p * bflo(vv.y)); o3 = fmaf(o3, al, p * bfhi(vv.y));
    }
    const float inv = rcp_approx(l);
    asm volatile("st.shared.v2.u32 [%0], {%1, %2};" :: "r"(so + ad), "r"(pack_bf16(o0 * inv, o1 * inv)), "r"(pack_bf16(o2 * inv, o3 * inv)) : "memory");
  }
}
__device__ __forceinline__ void issue_qk(float (&s)[64], const uint32_t (&q)[32], uint32_t k_lo) {
  wgmma_fence();
  wgmma_m64n128k16_rs<0>(s, q[0], q[1], q[2], q[3], k_lo, 0);
  wgmma_m64n128k16_rs<2>(s, q[4], q[5], q[6], q[7], k_lo, 1);
  wgmma_m64n128k16_rs<4>(s, q[8], q[9], q[10], q[11], k_lo, 1);
  wgmma_m64n128k16_rs<6>(s, q[12], q[13], q[14], q[15], k_lo, 1);
  wgmma_m64n128k16_rs<1024>(s, q[16], q[17], q[18], q[19], k_lo, 1);
  wgmma_m64n128k16_rs<1026>(s, q[20], q[21], q[22], q[23], k_lo, 1);
  wgmma_m64n128k16_rs<1028>(s, q[24], q[25], q[26], q[27], k_lo, 1);
  wgmma_m64n128k16_rs<1030>(s, q[28], q[29], q[30], q[31], k_lo, 1);
  wgmma_commit();
}
__device__ __forceinline__ void issue_pv(float (&o)[64], const uint32_t (&p)[32], uint32_t v_lo, int accumulate) {
  wgmma_fence();
  wgmma_m64n128k16_rs_tb<0>(o, p[0], p[1], p[2], p[3], v_lo, accumulate);
  wgmma_m64n128k16_rs_tb<128>(o, p[4], p[5], p[6], p[7], v_lo, 1);
  wgmma_m64n128k16_rs_tb<256>(o, p[8], p[9], p[10], p[11], v_lo, 1);
  wgmma_m64n128k16_rs_tb<384>(o, p[12], p[13], p[14], p[15], v_lo, 1);
  wgmma_m64n128k16_rs_tb<512>(o, p[16], p[17], p[18], p[19], v_lo, 1);
  wgmma_m64n128k16_rs_tb<640>(o, p[20], p[21], p[22], p[23], v_lo, 1);
  wgmma_m64n128k16_rs_tb<768>(o, p[24], p[25], p[26], p[27], v_lo, 1);
  wgmma_m64n128k16_rs_tb<896>(o, p[28], p[29], p[30], p[31], v_lo, 1);
  wgmma_commit();
}
__device__ __forceinline__ void block_end(uint32_t zero, uint32_t bar) {
  #pragma unroll 1
  for (uint32_t i = 0; i < zero; i++) mbar_arrive(bar);
}
__device__ __forceinline__ void rescale_o(float (&o)[64], float al0, float al1) {
  #pragma unroll
  for (int j = 0; j < 16; j++) { o[4 * j] *= al0; o[4 * j + 1] *= al0; o[4 * j + 2] *= al1; o[4 * j + 3] *= al1; }
}

__device__ __forceinline__ void stage_o(const float (&o)[64], float i0, float i1, uint32_t dst, int lane) {
  #pragma unroll
  for (int J = 0; J < 16; J += 2)
    stmatrix_x4(dst + (J >> 3) * 16384 + ((((J & 7) + (lane >> 4)) ^ (lane & 7)) << 4),
                pack_bf16(o[4 * J + 0] * i0, o[4 * J + 1] * i0), pack_bf16(o[4 * J + 2] * i1, o[4 * J + 3] * i1),
                pack_bf16(o[4 * J + 4] * i0, o[4 * J + 5] * i0), pack_bf16(o[4 * J + 6] * i1, o[4 * J + 7] * i1));
}
__device__ __forceinline__ bool finish_l(float& l0, float& l1) {
  l0 += __shfl_xor_sync(0xffffffffu, l0, 1); l1 += __shfl_xor_sync(0xffffffffu, l1, 1);
  l0 += __shfl_xor_sync(0xffffffffu, l0, 2); l1 += __shfl_xor_sync(0xffffffffu, l1, 2);
  const bool redo = __any_sync(0xffffffffu, !(l0 <= AT_RAW_SUM && l1 <= AT_RAW_SUM && l0 >= AT_RAW_MIN && l1 >= AT_RAW_MIN));
  l0 = rcp_approx(l0); l1 = rcp_approx(l1);
  return redo;
}
template <int J0>
__device__ __forceinline__ void stage_q(const float (&acc)[128], float c, uint32_t dst, int lane) {
  #pragma unroll
  for (int J = J0; J < J0 + 16; J += 2)
    stmatrix_x4(dst + (J >> 3) * 16384 + ((((J & 7) + (lane >> 4)) ^ (lane & 7)) << 4),
                pack_bf16(acc[4 * J + 0] * c, acc[4 * J + 1] * c), pack_bf16(acc[4 * J + 2] * c, acc[4 * J + 3] * c),
                pack_bf16(acc[4 * J + 4] * c, acc[4 * J + 5] * c), pack_bf16(acc[4 * J + 6] * c, acc[4 * J + 7] * c));
}
__device__ __forceinline__ void store_o(const CUtensorMap* tmO, uint32_t src, int head, int row) {
  tma_store_2d(tmO, src, head * T_DH, row);
  tma_store_2d(tmO, src + 16384, head * T_DH + 64, row);
  bulk_commit();
}
__device__ __forceinline__ void mma_bf16(float (&d)[4], uint32_t a0, uint32_t a1, uint32_t a2, uint32_t a3, uint32_t b0, uint32_t b1) {
  asm volatile("mma.sync.aligned.m16n8k16.row.col.f32.bf16.bf16.f32 {%0, %1, %2, %3}, {%4, %5, %6, %7}, {%8, %9}, {%0, %1, %2, %3};"
               : "+f"(d[0]), "+f"(d[1]), "+f"(d[2]), "+f"(d[3]) : "r"(a0), "r"(a1), "r"(a2), "r"(a3), "r"(b0), "r"(b1));
}
struct GemvSel { uint32_t lo0, hi0, lo1, hi1; };
__device__ __forceinline__ GemvSel gemv_sel(int lane) {
  const uint32_t lo = (lane & 8) ? 0x1044u : 0x4410u, hi = (lane & 8) ? 0x3244u : 0x4432u;
  GemvSel s; s.lo0 = (lane & 16) ? 0x4444u : lo; s.hi0 = (lane & 16) ? 0x4444u : hi; s.lo1 = (lane & 16) ? lo : 0x4444u; s.hi1 = (lane & 16) ? hi : 0x4444u;
  return s;
}
#define GEMV_B0(j, h, s) __byte_perm((j) < 2 ? (h).x : (h).y, 0u, ((j) & 1) ? (s).hi0 : (s).lo0)
#define GEMV_B1(j, h, s) __byte_perm((j) < 2 ? (h).x : (h).y, 0u, ((j) & 1) ? (s).hi1 : (s).lo1)
__device__ __forceinline__ int gemv_col(int i) { return (i >> 4) * 8 + ((i >> 3) & 1) * 4 + (i & 2) + ((i >> 2) & 1); }
#define OG_XN 4
#define OG_XB 5
#define OG_NG 8
#define PUT_N 2
#define H_STAG 2
#define AL_P 60
#define AL_SLEEP 1200
#define AL_MAX 800
#define POLL_NS 500
#define OG_PROF 0xDDCBAA98u
#define RK_P 24
__host__ __device__ constexpr int og_pre(int tile) { return (OG_PROF >> ((tile >> 4) * 4)) & 15; }
constexpr int OG_PRE2 = og_pre(127), OG_HSUM = og_pre(0) + og_pre(16) + og_pre(32) + og_pre(48) + og_pre(64) + og_pre(80) + og_pre(96);
#define OG_JOBS 7
#define OG_GRP 6
#define LD_FIRST 2
#define LD_STAG (OG_GRP / 2)
constexpr int OG_ST = 5, OG_NKB = T_DQKV / 64 - og_pre(0), OG_MOE = T_F / 32;
__device__ __forceinline__ int pre_kb(int i) { return (i >> 1) * 4 + (i & 1); }
__device__ __forceinline__ int own_kb(int i, int pre) { return i < (pre & ~1) ? pre_kb(i) + 2 : i + pre; }
static_assert(LD_FIRST + LD_STAG <= OG_XB && OG_XB < LD_FIRST + OG_GRP, "the extra tile belongs to segment 1");
constexpr int OG_POS = 8;
constexpr uint32_t OG_STAGE = 32768;
constexpr uint32_t OG_SCOL = AT_SBAR + 512;
constexpr uint32_t OG_SMISC = AT_SBAR + 2048;
constexpr uint32_t OG_SWD = AT_SQ, OG_PSLOT = AT_SQ;
constexpr uint32_t OG_XSLOT = AT_SQ + 32768;
constexpr uint32_t OG_OSLOT = 1 * OG_STAGE;
constexpr uint32_t OG_SRED = 3 * OG_STAGE;
constexpr uint32_t OG_SH2 = OG_SRED + 24576;
constexpr uint32_t OG_SSTAT = OG_SRED + 16384;
constexpr uint32_t OG_SGU = OG_SRED + 8192;
constexpr uint32_t OG_SFIN = OG_SGU + 256;
#define OGM 2
#define OG_MT(b) ((((b) >> OGM) & 15) ^ (((b) & 64) ? 15 : 0))
#define OG_NT(b) (((b) & ((1 << OGM) - 1)) + (((b) >> (4 + OGM)) << OGM))
__device__ __forceinline__ int tail_tile(uint32_t sbase) { mbar_wait_long(sbase + AT_SBAR + 336, 0); return (int)lds_u32(sbase + AT_SBAR + 408); }
#define TAIL_SETUP \
  const uint32_t bar_full = sbase + AT_SBAR, bar_empty = bar_full + 40; \
  const uint32_t bar_wd = bar_full + 168, bar_col = bar_full + 176, bar_out = bar_full + 184, bar_end = bar_full + 192; \
  const uint32_t bar_key = bar_full + 200, bar_h2 = bar_full + 208, bar_sel = bar_full + 216; \
  const int mt = OG_MT(tb), nt = OG_NT(tb); \
  const int m0 = mt * 128, n0 = nt * 128; \
  const bool has_moe = (int)bid < OG_MOE; \
  (void)bar_empty; (void)bar_wd; (void)bar_col; (void)bar_out; (void)bar_end; (void)bar_key; (void)bar_h2; (void)bar_sel; (void)m0; (void)n0; (void)has_moe;

__device__ __forceinline__ void tail_producer(uint32_t bid, uint32_t sbase, uint32_t ph, uint64_t pol, const CUtensorMap* tmA, const CUtensorMap* tmB, const CUtensorMap* tmD) {
  const int tb = tail_tile(sbase);
  TAIL_SETUP
  uint32_t stage = OG_POS % OG_ST;
  int kb = 0, xk = OG_XB;
  uint32_t xp = 1;
  #pragma unroll 1
  for (int seg = 0; seg < 2; seg++) {
    mbar_wait(bar_full + 264 + 80 * seg, 0);
    fence_proxy_async_global();
    const int end = 32 + 32 * seg - og_pre(tb);
    #pragma unroll 1
    for (; kb < end; kb++) {
      const bool xb = kb == xk;
      const uint32_t fb = xb ? bar_full + 360 : bar_full + 8 * stage, sa = sbase + (xb ? 5 : stage) * OG_STAGE;
      const int k0 = own_kb(kb, og_pre(tb)) * 64;
      if (xb) {
        mbar_wait(bar_full + 80, bid < AT_NFULL);
        mbar_wait(bar_full + 368, xp);
        xp ^= 1;
        if (xk < OG_XB + (OG_XN - 1) * OG_GRP) xk += OG_GRP;
      }
      mbar_wait_long(xb ? bar_full + 304 : bar_empty + 8 * stage, xb ? 0 : ph);
      mbar_expect_tx(fb, OG_STAGE);
      tma_load_3d_hint(sa + 16384, tmB, k0, 2 * nt, fb, pol);
      tma_load_2d_hint(sa, tmA, k0, m0, fb, pol);
      if (!xb && ++stage == OG_ST) { stage = 0; ph ^= 1; }
    }
  }
  if (has_moe) {
    stage += stage & 1;
    mbar_wait(bar_empty + 8 * stage, ph);
    mbar_expect_tx(bar_wd, OG_STAGE);
    tma_load_3d_hint(sbase + stage * OG_STAGE, tmD, bid * 32, 8, bar_wd, pol);
  }
}

__device__ __forceinline__ uint32_t out2(uint32_t x1, uint32_t mb2, uint32_t ih, uint32_t il, uint32_t c1, uint32_t sb, uint32_t gb) {
  const uint32_t h2 = badd2(bmul2(ln_norm2b(x1, mb2, ih, il), c1), sb);
  return badd2(x1, bmul2(gb, bfma2(h2, 0u, h2)));
}
#define X_PACE 200
#define Y_SLACK 96
#define OG_STAG 3
#define POLL_NS2 100
#define WD_SKIP 1
#define AL_ADD 380
#define WD_PACE 300
__device__ __forceinline__ void tail_exchange(uint32_t bid, uint32_t sbase, const bf16* __restrict__ w_down, const bf16* __restrict__ w_r, const bf16* __restrict__ x, bf16* __restrict__ out) {
    const int lane = threadIdx.x & 31, wi = __shfl_sync(0xffffffffu, threadIdx.x >> 5, 0);
    if (wi == 3) {
      uint32_t a = bid, b = 0u;
      if (bid < AT_NFULL) mbar_wait_long(sbase + AT_SBAR + 312, 0);
      if (bid < OG_MOE) {
        asm volatile("mov.u32 %0, %%globaltimer_lo;" : "=r"(a));
        if (lane == 0 && (bid & 15) == 0) asm volatile("st.relaxed.gpu.global.u32 [%0], %1;" :: "l"(g_hcnt + 8 + (bid >> 4)), "r"((a & ~15u) | 8u | (bid >> 4)) : "memory");
        #pragma unroll 1
        for (unsigned int spin = 0; spin < (1u << 22) && __any_sync(0xffffffffu, b == 0u); spin++) {
          __nanosleep(200);
          asm volatile("ld.relaxed.gpu.global.u32 %0, [%1];" : "=r"(b) : "l"(g_hcnt + 8 + min(lane, 6)) : "memory");
        }
        a = __popc(__ballot_sync(0xffffffffu, b < __shfl_sync(0xffffffffu, b, bid >> 4)) & 127u) * 16 + (bid & 15);
      }
      if (lane == 0) {
        sts_u32(sbase + AT_SBAR + 408, a);
        mbar_arrive(sbase + AT_SBAR + 336);
        b = 0u;
        if (bid < AT_NFULL) {
          unsigned int* tm = g_hcnt + 32 * (1 + (bid >> 4)) + 8;
          mbar_wait_long(sbase + AT_SBAR + 312, 1);
          asm volatile("mov.u32 %0, %%globaltimer_lo;" : "=r"(a));
          asm volatile("red.relaxed.gpu.global.max.u32 [%0], %1;" :: "l"(tm), "r"(a) : "memory");
          __nanosleep(AL_SLEEP);
          asm volatile("ld.relaxed.gpu.global.u32 %0, [%1];" : "=r"(b) : "l"(tm) : "memory");
          b -= a;
        }
        sts_u32(sbase + AT_SBAR + 412, b < AL_MAX ? b * 13 / 8 : 0u);
        mbar_arrive(sbase + AT_SBAR + 320);
      }
      named_bar_sync(15, 32);
    }
    const int tb = __shfl_sync(0xffffffffu, tail_tile(sbase), 0);
    TAIL_SETUP
    if (wi == 3) {
      mbar_wait_long(bar_full + 344, 0);
      float a = g_scal[lane], b = g_scal[32 + lane];
      #pragma unroll
      for (int i = 0; i < 3; i++) {
        const uint4 v = *reinterpret_cast<const uint4*>(g_col + nt * 1536 + i * 512 + lane * 16);
        sts_u32x4(sbase + OG_SCOL + i * 512 + lane * 16, v.x, v.y, v.z, v.w);
      }
      #pragma unroll
      for (int o = 16; o > 0; o >>= 1) { a += __shfl_xor_sync(0xffffffffu, a, o); b += __shfl_xor_sync(0xffffffffu, b, o); }
      if (lane == 0) sts_f32x2(sbase + OG_SMISC, a, b);
      const uint64_t pol = policy_evict_first();
      #pragma unroll 1
      for (int r = lane >> 4; r < 128; r += 4) {
        __nanosleep(X_PACE);
        #pragma unroll
        for (int j = 0; j < 4; j += 2)
          asm volatile("cp.async.cg.shared.global.L2::cache_hint [%0], [%1], 16, %2;" :: "r"(sbase + OG_XSLOT + (lane & 8) * 2048 + (r + j) * 128 + (((lane ^ (r + j)) & 7) << 4)),
                       "l"(x + (size_t)(m0 + r + j) * T_D + n0 + (lane & 15) * 8), "l"(pol) : "memory");
      }
      asm volatile("cp.async.wait_all;" ::: "memory");
      __syncwarp();
      if (lane == 0) mbar_arrive(bar_col);
    } else if (wi == 2) {
      if (elect_one()) {
        mbar_wait_long(bar_full + (has_moe ? 80 : 376), has_moe);
        #pragma unroll 1
        for (unsigned int i = 0; i < (1u << 20) && ld_acquire(&g_hcnt[32 * (1 + (tb >> 3)) + 4 + ((tb >> 1) & 3)]) == 0u; i++) __nanosleep((tb >> 4) == 6 ? POLL_NS2 : POLL_NS);
        TL_MARK2(23, true);
        fence_proxy_async_global();
        TL_MARK2(4, true);
        mbar_expect_tx(bar_full + 272, 32768);
        bulk_load_hint(sbase + OG_PSLOT, g_pre + tb * 2048, 32768, bar_full + 272, policy_evict_first());
      }
      named_bar_sync(14, 32);
      if (has_moe) {
        mbar_wait_long(bar_full + 376, 0);
        const uint64_t pol = policy_evict_first();
        #pragma unroll 1
        for (int r = 0; r < 32; r++) {
          if ((r & WD_SKIP) != WD_SKIP) __nanosleep(WD_PACE);
          #pragma unroll
          for (int j = 0; j < 2; j++)
            asm volatile("cp.async.cg.shared.global.L2::cache_hint [%0], [%1], 16, %2;" :: "r"(sbase + OG_SWD + (4 * j + (lane >> 3)) * 4096 + r * 128 + (((lane ^ r) & 7) << 4)),
                         "l"((const uint8_t*)w_down + (size_t)bid * 65536 + r * 2048 + j * 512 + lane * 16), "l"(pol) : "memory");
        }
        asm volatile("cp.async.wait_all;" ::: "memory");
        __syncwarp();
        if (lane == 0) mbar_arrive(bar_wd);
      }
    }
    const uint4 wrv = ldg_nc_v4(w_r + threadIdx.x * 8);
    mbar_wait_long(bar_end, 0);
    TL_MARK2(22, lane == 0);
    if (wi == 0) {
      uint32_t k1 = 0u, k2 = 0u;
      #pragma unroll 1
      for (unsigned int spin = 0; spin < (1u << 22) && __any_sync(0xffffffffu, k1 == 0u); spin++) asm volatile("ld.relaxed.gpu.global.u32 %0, [%1];" : "=r"(k1) : "l"(g_key + lane) : "memory");
      TL_MARK2(28, lane == 0);
      warp_top2(k1, k2);
      if (lane == 0) {
        const uint32_t r1 = 0xffffu - (k1 & 0xffffu), r2 = 0xffffu - (k2 & 0xffffu);
        sts_u32x4(sbase + OG_SMISC + 64, r1, r2, (r1 >> 7) * 2, (r2 >> 7) * 2 + ((r1 >> 7) == (r2 >> 7)));
        mbar_arrive(bar_sel);
      }
    } else if (wi < 3) {
          mbar_wait(bar_key, 0);
          const uint4 kk = lds_u32x4(sbase + OG_SSTAT + 1024 + lane * 16);
          uint32_t k1 = max(kk.x, kk.y), k2 = min(kk.x, kk.y);
          k2 = max(max(k2, min(kk.z, kk.w)), min(k1, max(kk.z, kk.w))); k1 = max(k1, max(kk.z, kk.w));
          warp_top2(k1, k2);
          if (wi == 1) {
            if (lane == 0) {
              if (nt == (mt & 7)) st_relaxed2(g_key + mt * 2, k1, k2);
              sts_u32x2(sbase + OG_SMISC + 96, (~k1 >> 4) & 7u, (~k2 >> 4) & 7u);
              mbar_arrive(bar_full + 352);
            }
            TL_MARK2(27, lane == 0);
          } else {
            const uint32_t r = (~((lane & 16) ? k2 : k1)) & 127u, ch = lane & 15;
            const uint2 st = lds_u32x2(sbase + OG_SSTAT + r * 8);
            const uint4 xc = lds_u32x4(sbase + OG_XSLOT + (ch >> 3) * 16384 + r * 128 + (((ch ^ r) & 7) << 4));
            const uint4 c1 = lds_u32x4(sbase + OG_SCOL + 768 + ch * 16), sh = lds_u32x4(sbase + OG_SCOL + 1024 + ch * 16);
            const float inr = __uint_as_float(st.y);
            float* dst = reinterpret_cast<float*>(g_cand + (mt * 2 + (lane >> 4)) * 256 + nt * 16 + ch);
            st_tagged4(dst + 512, __uint_as_float(ln_mod2(xc.x, st.x, inr, c1.x, sh.x)), __uint_as_float(ln_mod2(xc.y, st.x, inr, c1.y, sh.y)),
                       __uint_as_float(ln_mod2(xc.z, st.x, inr, c1.z, sh.z)), __uint_as_float(ln_mod2(xc.w, st.x, inr, c1.w, sh.w)));
            st_tagged4(dst, __uint_as_float(xc.x), __uint_as_float(xc.y), __uint_as_float(xc.z), __uint_as_float(xc.w));
          }
    }
    mbar_wait(bar_sel, 0);
    const uint4 sel = lds_u32x4(sbase + OG_SMISC + 64);
    const int sel0 = (int)sel.x, sel1 = (int)sel.y;
    {
      const float* src0 = reinterpret_cast<const float*>(g_cand + sel.z * 256 + 128 + threadIdx.x);
      const float* src1 = reinterpret_cast<const float*>(g_cand + sel.w * 256 + 128 + threadIdx.x);
      float4 h0, h1;
      #pragma unroll 1
      for (unsigned int spin = 0; spin < (1u << 20); spin++) { h0 = ld_tagged4(src0); h1 = ld_tagged4(src1); if (__all_sync(0xffffffffu, tagged4(h0) & tagged4(h1))) break; }
      sts_f32x4(sbase + OG_SH2 + threadIdx.x * 16, h0.x, h0.y, h0.z, h0.w);
      sts_f32x4(sbase + OG_SH2 + 2048 + threadIdx.x * 16, h1.x, h1.y, h1.z, h1.w);
      __syncwarp();
      if (lane == 0) mbar_arrive(bar_h2);
      TL_MARK2(12, lane == 0);
      float v[8], u[8], wr[8];
      unpack8(make_uint4(__float_as_uint(h0.x), __float_as_uint(h0.y), __float_as_uint(h0.z), __float_as_uint(h0.w)), v);
      unpack8(make_uint4(__float_as_uint(h1.x), __float_as_uint(h1.y), __float_as_uint(h1.z), __float_as_uint(h1.w)), u);
      unpack8(wrv, wr);
      float r0 = 0.f, r1 = 0.f;
      #pragma unroll
      for (int i = 0; i < 8; i++) { r0 = fmaf(v[i], wr[i], r0); r1 = fmaf(u[i], wr[i], r1); }
      r0 = ((lane & 16) ? r1 : r0) + __shfl_xor_sync(0xffffffffu, (lane & 16) ? r0 : r1, 16);
      #pragma unroll
      for (int o = 8; o > 0; o >>= 1) r0 += __shfl_xor_sync(0xffffffffu, r0, o);
      if ((lane & 15) == 0) sts_f32(sbase + OG_SMISC + 192 + lane + wi * 4, r0);
    }
    mbar_wait(bar_out, 0);
    {
      const uint2 cg = lds_u32x2(sbase + OG_SMISC + 96);
      #pragma unroll
      for (int i = 0; i < 4; i++) {
        const int r = (i < 2 ? cg.x : cg.y) * 16 + (i & 1) * 8 + (threadIdx.x >> 4), ch = threadIdx.x & 15;
        if (m0 + r != sel0 && m0 + r != sel1)
          *reinterpret_cast<uint4*>(out + (size_t)(m0 + r) * T_D + n0 + ch * 8) =
              lds_u32x4(sbase + OG_OSLOT + (ch >> 3) * 16384 + r * 128 + (((ch & 7) ^ (r & 7)) << 4));
      }
    }
    if (bid == 0 && threadIdx.x < 68) *reinterpret_cast<uint4*>(g_hcnt + 32 * (threadIdx.x >> 2) + 4 * (threadIdx.x & 3)) = make_uint4(0u, 0u, 0u, 0u);
    if (threadIdx.x < 64) g_modpart[bid * 64 + threadIdx.x] = 0.f;
    {
      const int tk = threadIdx.x & 1, col = bid * 8 + gemv_col(threadIdx.x & 15);
      const uint32_t gb2 = *reinterpret_cast<const uint32_t*>(g_col + (col >> 7) * 1536 + 512 + 768 + (col & 126) * 2);
      const uint32_t* xp = reinterpret_cast<const uint32_t*>(g_cand + (tk ? sel.w : sel.z) * 256) + (col >> 1);
      uint32_t x2 = 0u;
      #pragma unroll 1
      for (unsigned int spin = 0; spin < (1u << 20) && __any_sync(0xffffffffu, x2 == 0u); spin++) asm volatile("ld.relaxed.gpu.global.u32 %0, [%1];" : "=r"(x2) : "l"(xp) : "memory");
      const float* src = g_ypart + (size_t)(threadIdx.x >> 2) * 2 * T_D + bid * 16 + (threadIdx.x & 3) * 4;
      const bool four = threadIdx.x < (OG_MOE - 96) * 4;
      named_bar_sync(10, 128);
      const uint4 rp = lds_u32x4(sbase + OG_SMISC + 192 + tk * 16);
      const float rs = rbf(sigmoid_f(rbf((__uint_as_float(rp.x) + __uint_as_float(rp.y)) + (__uint_as_float(rp.z) + __uint_as_float(rp.w)))));
      const uint32_t h2p = lds_u32(sbase + OG_SH2 + tk * 2048 + (col & ~1) * 2);
      const float fh = (col & 1) ? bfhi(h2p) : bflo(h2p), fz = rbf(fh * 0.0f), fx = (col & 1) ? bfhi(x2) : bflo(x2), fg = (col & 1) ? bfhi(gb2) : bflo(gb2);
      bf16* dst = out + (size_t)(tk ? sel1 : sel0) * T_D + col;
      if (threadIdx.x == 0) hint_wait(CNT_Y, (uint32_t)(OG_MOE - Y_SLACK));
      named_bar_sync(10, 128);
      float4 p0, p1, p2, p3;
      #pragma unroll 1
      for (unsigned int spin = 0; spin < (1u << 20); spin++) {
        p0 = ld_tagged4(src); p1 = ld_tagged4(src + 64 * T_D); p2 = ld_tagged4(src + 128 * T_D); p3 = ld_tagged4(four ? src + 192 * T_D : src);
        if (__all_sync(0xffffffffu, tagged4(p0) & tagged4(p1) & tagged4(p2) & tagged4(p3))) break;
      }
      if (four) { p2.x += p3.x; p2.y += p3.y; p2.z += p3.z; p2.w += p3.w; }
      p0.x = (p0.x + p1.x) + p2.x; p0.y = (p0.y + p1.y) + p2.y; p0.z = (p0.z + p1.z) + p2.z; p0.w = (p0.w + p1.w) + p2.w;
      #pragma unroll
      for (int o = 4; o <= 16; o <<= 1) {
        p0.x += __shfl_xor_sync(0xffffffffu, p0.x, o); p0.y += __shfl_xor_sync(0xffffffffu, p0.y, o);
        p0.z += __shfl_xor_sync(0xffffffffu, p0.z, o); p0.w += __shfl_xor_sync(0xffffffffu, p0.w, o);
      }
      if (lane < 4) sts_f32x4(sbase + OG_SFIN + (threadIdx.x >> 5) * 64 + lane * 16, p0.x, p0.y, p0.z, p0.w);
      named_bar_sync(10, 128);
      TL_MARK2(21, threadIdx.x == 0);
      if (threadIdx.x < 16) {
        const uint32_t ya = sbase + OG_SFIN + threadIdx.x * 4;
        float y = (lds_f32(ya) + lds_f32(ya + 64)) + (lds_f32(ya + 128) + lds_f32(ya + 192));
        y = rbf(y);
        y = rbf(y * rs);
        *dst = __float2bfloat16_rn(fx + rbf(fg * rbf(fh + rbf(fz + y))));
      }
    }
    if (threadIdx.x == 0) XT(11);
    TL_END(4, threadIdx.x == 0);
}

__device__ __forceinline__ void load_pre(uint4* pre, uint32_t sbase, uint32_t buf, int t2) {
  mbar_wait(sbase + AT_SBAR + 272, 0);
  #pragma unroll
  for (int i = 0; i < 8; i++) pre[i] = lds_u32x4(sbase + buf + i * 4096 + t2 * 16);
}
__device__ __forceinline__ void tail_consumer(uint32_t bid, uint32_t sbase, const CUtensorMap* tmOut, const uint4 (&pre)[8], int cwg, const bf16* __restrict__ w_gate, const bf16* __restrict__ w_up) {
    const uint32_t c0 = clock_lo();
    if ((threadIdx.x & 31) == 0) mbar_arrive(sbase + AT_SBAR + 304);
    mbar_wait(sbase + AT_SBAR + 320, 0);
    const uint2 td = lds_u32x2(sbase + AT_SBAR + 408);
    const int tb = __shfl_sync(0xffffffffu, (int)td.x, 0);
    TAIL_SETUP
    const int tid = threadIdx.x & 127, t2 = threadIdx.x - 128;
    const int warp = tid >> 5, lane = tid & 31, w8 = t2 >> 5;
    const uint32_t dbase = (sbase & 0x3FFFFu) >> 4;
    const uint32_t a_base = dbase + ((cwg * 8192) >> 4) + (1u << 16);
    const uint32_t b_base = dbase + (16384 >> 4) + (512u << 16);
    TL_MARK2(25, threadIdx.x == 128);
    const uint64_t pol = policy_evict_first();
    const bf16* pw = ((lane & 16) ? w_up : w_gate) + (size_t)(w8 * 128 + (lane & 3) * 4) * T_F + (has_moe ? bid : 0) * 32 + ((lane >> 2) & 3) * 8;
    uint4 wv[32];
    float acc[64];
    #pragma unroll
    for (int i = 0; i < 8; i++) {
      acc[8 * i] = bflo(pre[i].x); acc[8 * i + 1] = bfhi(pre[i].x); acc[8 * i + 2] = bflo(pre[i].y); acc[8 * i + 3] = bfhi(pre[i].y);
      acc[8 * i + 4] = bflo(pre[i].z); acc[8 * i + 5] = bfhi(pre[i].z); acc[8 * i + 6] = bflo(pre[i].w); acc[8 * i + 7] = bfhi(pre[i].w);
    }
    while (__any_sync(0xffffffffu, clock_lo() - c0 < td.y + AL_ADD)) {}
    uint32_t stage = OG_POS % OG_ST;
    {
      uint32_t phase = (OG_POS / OG_ST) & 1, prev = 12;
      int kb = 0;
      #pragma unroll
      for (int g = 0; g <= OG_NG; g++) {
        const int end = g == OG_NG ? 64 - og_pre(tb) : LD_FIRST + g * OG_GRP + LD_STAG * cwg;
        #pragma unroll 1
        do {
          const bool xb = g >= 1 && g <= OG_XN && kb == OG_XB + (g - 1) * OG_GRP;
          mbar_wait(xb ? bar_full + 360 : bar_full + 8 * stage, xb ? (g - 1) & 1 : phase);
          if (OG_STAG > 0 && g == OG_NG && cwg == 1 && kb == end - OG_STAG) named_bar_sync(7, 256);
          const uint32_t a_lo = a_base + (xb ? 5 : stage) * (OG_STAGE >> 4), b_lo = b_base + (xb ? 5 : stage) * (OG_STAGE >> 4);
          wgmma_fence();
          wgmma_m64n128k16_ss_tb<0, 0>(acc, a_lo, b_lo, 1);
          wgmma_m64n128k16_ss_tb<2, 128>(acc, a_lo, b_lo, 1);
          wgmma_m64n128k16_ss_tb<4, 256>(acc, a_lo, b_lo, 1);
          wgmma_m64n128k16_ss_tb<6, 384>(acc, a_lo, b_lo, 1);
          wgmma_commit();
          if (OG_STAG > 0 && g == OG_NG && cwg == 0 && kb == end - 1) named_bar_arrive(7, 256);
          wgmma_wait<1>();
          if (tid == 0) mbar_arrive(bar_empty + 8 * prev);
          prev = xb ? 41 + (g == OG_XN) : stage;
          if (!xb && ++stage == OG_ST) { stage = 0; phase ^= 1; }
        } while (++kb < end);
        #pragma unroll
        for (int j = 4 * g; j < 4 * g + 4 && j < 32; j++) wv[j] = ldg_stream_v4(pw + (size_t)(16 * (j >> 2) + (j & 3)) * T_F, pol);
      }
    }
    mbar_wait(bar_col, 0);
    if (__builtin_expect(!has_moe, 0)) {
      load_pre(wv, sbase, AT_SQ, t2);
    }
    wgmma_wait<0>();
    fence_regs(acc);
    if (__builtin_expect(!has_moe, 0)) {
      #pragma unroll
      for (int i = 0; i < 8; i++) {
        acc[8 * i] += bflo(wv[i].x); acc[8 * i + 1] += bfhi(wv[i].x); acc[8 * i + 2] += bflo(wv[i].y); acc[8 * i + 3] += bfhi(wv[i].y);
        acc[8 * i + 4] += bflo(wv[i].z); acc[8 * i + 5] += bfhi(wv[i].z); acc[8 * i + 6] += bflo(wv[i].w); acc[8 * i + 7] += bfhi(wv[i].w);
      }
    }
    if (tid == 0) mbar_arrive(bar_end);
    TL_MARK2(9, lane == 0);
    const int q2 = 2 * (lane & 3);
    const uint32_t frag = (64 * cwg + 16 * warp + (lane & 7) + 8 * ((lane >> 3) & 1)) * 128;
    const int fsw = lane & 7, fhi = lane >> 4;
    {
      float dl[4] = {0.f, 0.f, 0.f, 0.f}, da[4] = {0.f, 0.f, 0.f, 0.f}, db[4] = {0.f, 0.f, 0.f, 0.f};
      const uint32_t tb2 = sbase + OG_SCOL + (lane & 8) * 32 + (lane & 3) * 8, g = lane >> 2;
      const uint32_t msk = (g == 1 || g == 2) ? 0xffffffffu : 0u, one = g == 0 ? 0x3F803F80u : 0u;
      uint32_t xr[8][4];
      #pragma unroll
      for (int hf = 0; hf < 2; hf++) {
        uint32_t ga[8];
        uint2 cw[4];
        #pragma unroll
        for (int i = 0; i < 4; i++) {
          ldmatrix_x4(sbase + OG_XSLOT + hf * 16384 + frag + (((2 * i + fhi) ^ fsw) << 4), xr[4 * hf + i][0], xr[4 * hf + i][1], xr[4 * hf + i][2], xr[4 * hf + i][3]);
          ga[2 * i] = lds_u32(sbase + OG_SCOL + 512 + (64 * hf + 16 * i + q2) * 2); ga[2 * i + 1] = lds_u32(sbase + OG_SCOL + 512 + (64 * hf + 16 * i + 8 + q2) * 2);
          cw[i] = lds_u32x2(tb2 + (8 * hf + 2 * i) * 16);
        }
        #pragma unroll
        for (int i = 0; i < 4; i++) {
          uint32_t* x4 = xr[4 * hf + i];
          #pragma unroll
          for (int e = 0; e < 4; e++) x4[e] = badd2(x4[e], bmul2(ga[2 * i + (e >> 1)], pack_bf16(acc[32 * hf + 8 * i + 2 * e], acc[32 * hf + 8 * i + 2 * e + 1])));
          mma_bf16(dl, x4[0], x4[1], x4[2], x4[3], (cw[i].x & msk) | one, (cw[i].y & msk) | one);
          mma_bf16(da, x4[0], x4[1], x4[2], x4[3], x4[0], x4[2]);
          mma_bf16(db, x4[0], x4[1], x4[2], x4[3], x4[1], x4[3]);
        }
      }
      {
        const int dsrc = (lane & ~3) + (g >> 1);
        const float qa = __shfl_sync(0xffffffffu, (g & 1) ? da[1] : da[0], dsrc), qb = __shfl_sync(0xffffffffu, (g & 1) ? db[3] : db[2], dsrc);
        const float e0 = __shfl_xor_sync(0xffffffffu, (lane & 1) ? dl[0] : dl[2], 1), e1 = __shfl_xor_sync(0xffffffffu, dl[3], 1);
        if ((lane & 3) < 2) {
          const bool hi = lane & 1;
          st_tagged4(reinterpret_cast<float*>(g_part1 + ((mt * 8 + w8) * 8 + nt) * 16 + g + (hi ? 8 : 0)),
                     hi ? e0 : dl[0], hi ? qb : qa, hi ? e1 + dl[2] : dl[1] + e0, 1.0f);
        }
      }
      #pragma unroll
      for (int i = 0; i < 8; i++) stmatrix_x4(sbase + OG_XSLOT + (i >> 2) * 16384 + frag + (((2 * (i & 3) + fhi) ^ fsw) << 4), xr[i][0], xr[i][1], xr[i][2], xr[i][3]);
    }
    TL_MARK2(10, lane == 0);
    uint4 wd[16];
    if (has_moe) mbar_wait(bar_wd, 0);
    #pragma unroll
    for (int i = 0; i < 16; i++) wd[i] = lds_u32x4(sbase + (cwg ? (stage + (stage & 1)) * OG_STAGE : OG_SWD) + warp * 8192 + (i >> 3) * 4096 + (i & 6) * 512 + (i & 1) * 128 + (lane & 3) * 256 + (((lane >> 2) ^ (2 * (lane & 3) + (i & 1))) << 4));
    {
      const float* src = reinterpret_cast<const float*>(g_part1 + ((mt * 8 + w8) * 8 + (lane & 1) * 4) * 16 + (lane >> 1));
      float4 v, v1, v2, v3;
      #pragma unroll 1
      for (unsigned int spin = 0; spin < (1u << 22); spin++) {
        v = ld_tagged4(src); v1 = ld_tagged4(src + 64); v2 = ld_tagged4(src + 128); v3 = ld_tagged4(src + 192);
        if (__all_sync(0xffffffffu, tagged4(v) & tagged4(v1) & tagged4(v2) & tagged4(v3))) break;
      }
      __syncwarp();
      TL_MARK2(26, lane == 0);
      v.x = (v.x + v1.x) + (v2.x + v3.x); v.y = (v.y + v1.y) + (v2.y + v3.y); v.z = (v.z + v1.z) + (v2.z + v3.z);
      v.x += __shfl_xor_sync(0xffffffffu, v.x, 1); v.y += __shfl_xor_sync(0xffffffffu, v.y, 1); v.z += __shfl_xor_sync(0xffffffffu, v.z, 1);
      const float mean = v.x * (1.0f / T_D);
      const float var = fmaxf(fmaf(-mean, mean, v.y * (1.0f / T_D)), 0.f);
      const uint32_t mb2 = pack_bf16(mean, mean);
      const float inv = rcp_approx(rbf(sqrt_approx(rbf(rbf(var) + 1e-05f))));
      {
        const float2 sc = lds_f32x2(sbase + OG_SMISC);
        const uint32_t key = rank_key(rbf(fmaf(fmaf(-bflo(mb2), sc.x, v.z), inv, sc.y)), m0 + 16 * w8 + (lane >> 1));
        mbar_wait(bar_end, 0);
        if (lane & 1) sts_u32(sbase + OG_SSTAT + 1024 + (16 * w8 + (lane >> 1)) * 4, key);
        else sts_u32x2(sbase + OG_SSTAT + (16 * w8 + (lane >> 1)) * 8, mb2, __float_as_uint(inv));
        __syncwarp();
        if (lane == 0) mbar_arrive(bar_key);
      }
      const uint32_t ih = pack_bf16(inv, inv), il = pack_bf16(inv - bflo(ih), inv - bflo(ih));
      const uint32_t mba = __shfl_sync(0xffffffffu, mb2, 2 * (lane >> 2)), mbb = __shfl_sync(0xffffffffu, mb2, 2 * (lane >> 2) + 16);
      const uint32_t iha = __shfl_sync(0xffffffffu, ih, 2 * (lane >> 2)), ihb = __shfl_sync(0xffffffffu, ih, 2 * (lane >> 2) + 16);
      const uint32_t ila = __shfl_sync(0xffffffffu, il, 2 * (lane >> 2)), ilb = __shfl_sync(0xffffffffu, il, 2 * (lane >> 2) + 16);
      #pragma unroll 1
      for (int J0 = 0; J0 < 16; J0 += 4) {
        uint32_t xr[2][4], cv[4][3];
        #pragma unroll
        for (int i = 0; i < 2; i++) {
          ldmatrix_x4(sbase + OG_XSLOT + (J0 >> 3) * 16384 + frag + ((((J0 & 7) + 2 * i + fhi) ^ fsw) << 4), xr[i][0], xr[i][1], xr[i][2], xr[i][3]);
          #pragma unroll
          for (int h = 0; h < 2; h++)
            #pragma unroll
            for (int k = 0; k < 3; k++) cv[2 * i + h][k] = lds_u32(sbase + OG_SCOL + 768 + 256 * k + (8 * (J0 + 2 * i + h) + q2) * 2);
        }
        #pragma unroll
        for (int i = 0; i < 2; i++) {
          #pragma unroll
          for (int h = 0; h < 2; h++) {
            xr[i][2 * h] = out2(xr[i][2 * h], mba, iha, ila, cv[2 * i + h][0], cv[2 * i + h][1], cv[2 * i + h][2]);
            xr[i][2 * h + 1] = out2(xr[i][2 * h + 1], mbb, ihb, ilb, cv[2 * i + h][0], cv[2 * i + h][1], cv[2 * i + h][2]);
          }
          stmatrix_x4(sbase + OG_OSLOT + (J0 >> 3) * 16384 + frag + ((((J0 & 7) + 2 * i + fhi) ^ fsw) << 4), xr[i][0], xr[i][1], xr[i][2], xr[i][3]);
        }
      }
      fence_proxy_async();
      mbar_wait(bar_full + 352, 0);
      const uint2 cg = lds_u32x2(sbase + OG_SMISC + 96);
      __syncwarp();
      if (elect_one()) {
        mbar_arrive(bar_out);
        if (cg.x != w8 && cg.y != w8) {
          asm volatile("cp.async.bulk.tensor.2d.global.shared::cta.bulk_group [%0, {%2, %3}], [%1];" :: "l"(tmOut), "r"(sbase + OG_OSLOT + w8 * 2048), "r"(n0), "r"(m0 + 16 * w8) : "memory");
          asm volatile("cp.async.bulk.tensor.2d.global.shared::cta.bulk_group [%0, {%2, %3}], [%1];" :: "l"(tmOut), "r"(sbase + OG_OSLOT + 16384 + w8 * 2048), "r"(n0 + 64), "r"(m0 + 16 * w8) : "memory");
          bulk_commit();
        }
      }
      TL_MARK2(24, lane == 0);
    }
    if (has_moe) mbar_wait(bar_h2, 0);
    TL_MARK2(13, lane == 0);
    if (has_moe) {
      const GemvSel sel = gemv_sel(lane);
      {
        float d[4][4];
        #pragma unroll
        for (int c = 0; c < 4; c++) { d[c][0] = 0.f; d[c][1] = 0.f; d[c][2] = 0.f; d[c][3] = 0.f; }
        #pragma unroll
        for (int st = 0; st < 8; st++) {
          const uint2 hb = lds_u32x2(sbase + OG_SH2 + ((lane >> 2) & 1) * 2048 + (w8 * 128 + st * 16 + (lane & 3) * 4) * 2);
          #pragma unroll
          for (int j = 0; j < 4; j++) mma_bf16(d[j], wv[4 * st + j].x, wv[4 * st + j].y, wv[4 * st + j].z, wv[4 * st + j].w, GEMV_B0(j, hb, sel), GEMV_B1(j, hb, sel));
        }
        #pragma unroll
        for (int e = 0; e < 4; e++) d[0][e] = (d[0][e] + d[1][e]) + (d[2][e] + d[3][e]);
        sts_f32x4(sbase + OG_SRED + t2 * 16, d[0][0], d[0][1], d[0][2], d[0][3]);
      }
      named_bar_sync(9, 256);
      if (t2 < 64) {
        const int c = gemv_col(t2);
        float gp[8], up[8];
        #pragma unroll
        for (int w = 0; w < 8; w++) { gp[w] = lds_f32(sbase + OG_SRED + w * 512 + t2 * 4); up[w] = lds_f32(sbase + OG_SRED + w * 512 + 256 + t2 * 4); }
        const float gs = ((gp[0] + gp[1]) + (gp[2] + gp[3])) + ((gp[4] + gp[5]) + (gp[6] + gp[7]));
        const float us = ((up[0] + up[1]) + (up[2] + up[3])) + ((up[4] + up[5]) + (up[6] + up[7]));
        asm volatile("st.shared.u16 [%0], %1;" :: "r"(sbase + OG_SGU + (t2 & 1) * 64 + ((c & ~15) + ((c >> 1) & 3) * 4 + ((c >> 3) & 1) * 2 + (c & 1)) * 2), "h"((uint16_t)pack_bf16(silu_bf(rbf(gs)) * rbf(us), 0.f)) : "memory");
      }
      named_bar_sync(9, 256);
      TL_MARK2(20, threadIdx.x == 128);
      float d[4][4];
      #pragma unroll
      for (int c = 0; c < 4; c++) { d[c][0] = 0.f; d[c][1] = 0.f; d[c][2] = 0.f; d[c][3] = 0.f; }
      #pragma unroll
      for (int st = 0; st < 2; st++) {
        const uint2 g = lds_u32x2(sbase + OG_SGU + ((lane >> 2) & 1) * 64 + st * 32 + (lane & 3) * 8);
        #pragma unroll
        for (int j = 0; j < 4; j++) {
          const uint32_t b0 = GEMV_B0(j, g, sel), b1 = GEMV_B1(j, g, sel);
          mma_bf16(d[j & 1], wd[4 * st + j].x, wd[4 * st + j].y, wd[4 * st + j].z, wd[4 * st + j].w, b0, b1);
          mma_bf16(d[2 + (j & 1)], wd[8 + 4 * st + j].x, wd[8 + 4 * st + j].y, wd[8 + 4 * st + j].z, wd[8 + 4 * st + j].w, b0, b1);
        }
      }
      #pragma unroll
      for (int e = 0; e < 4; e++) { d[0][e] += d[1][e]; d[2][e] += d[3][e]; }
      float* yp = g_ypart + (size_t)bid * 2 * T_D + w8 * 256 + lane * 4;
      st_tagged4_lsb(yp, d[0][0], d[0][1], d[0][2], d[0][3]);
      st_tagged4_lsb(yp + 128, d[2][0], d[2][1], d[2][2], d[2][3]);
      named_bar_sync(9, 256);
      if (t2 == 0) hint_arrive(CNT_Y);
    }
    bulk_wait_read<0>();
    TL_MARK2(14, threadIdx.x == 128);
    TL_CLK(4, 1, threadIdx.x == 128);
}

__device__ __forceinline__ int help_njobs(uint32_t bid) { return bid < 128 ? OG_JOBS : 16 - OG_JOBS; }
__device__ __forceinline__ int help_job(uint32_t bid, int i) { return (i < OG_JOBS ? 16 * i + (bid >> 7) * 2 : 112 + (i - OG_JOBS) * 2) + (bid & 3) * 4; }
__device__ __noinline__ void store_warp(uint32_t bid, uint32_t sbase, const CUtensorMap* tmO, int item0, int n_items) {
  if (elect_one()) {
    const uint32_t bars = sbase + AT_SBAR, b_q0 = bars + 80, b_ob = bars + 96, b_ordy = bars + 104, b_acq = bars + 264;
    const unsigned int* cnt = g_hcnt + 32 * (1 + OG_MT(124)) + 2;
    #pragma unroll 1
    for (int q = 0; q < 4 * n_items; q++) {
      const int item = item0 + (q >> 2) * 128, h = (q >> 1) & 1, w = q & 1;
      const bool last = (q >> 2) == n_items - 1;
      if (q == 4 * n_items - 4) { mbar_wait_long(bars + 288, 0); red_release_add(&g_hcnt[1], 1u); }
      mbar_wait_long(b_ordy + 8 * (q & 3), q >> 2);
      store_o(tmO, (h ? (last ? sbase + AT_SQ + 32768 : sbase + 2 * 32768) : sbase + AT_SQ) + w * 8192, (item >> 4) * 2 + h, (item & 15) * 128 + w * 64);
      if (w) {
        bulk_wait_read<0>();
        mbar_arrive(h ? b_ob : b_q0);
        bulk_wait<0>();
        fence_proxy_async_global();
        asm volatile("fence.acq_rel.gpu;" ::: "memory");
        hint_arrive(&g_hcnt[32 * (1 + (item & 15)) + 2 + (item >> 7)]);
        if (!h && item < 128) hint_arrive(&g_hcnt[2]);
        if (q == 5) { const int tb = tail_tile(sbase); cnt = g_hcnt + 32 * (1 + OG_MT(tb)) + 2; spin_until(cnt, 16u); mbar_arrive(b_acq); }
      }
    }
    if (n_items == 1) {
      #pragma unroll 1
      for (int i = 0; i < help_njobs(bid); i++) {
        mbar_wait_long(b_acq + 16, i & 1);
        TL_MARK2(23, i == OG_JOBS - 1);
        red_release_add(&g_hcnt[32 * (1 + (help_job(bid, i) >> 3)) + 4 + ((help_job(bid, i) >> 1) & 3)], 1u);
        TL_MARK2(4, i == OG_JOBS - 1);
        if (i == PRE_X - 1) { spin_until(&g_hcnt[1], 132u); mbar_arrive(b_acq + 32); }
      }
    }
    if (bid < 128) {
      if (n_items == 1) { spin_until(cnt, 16u); mbar_arrive(b_acq); }
      spin_until(&g_hcnt[0], 128u); spin_until(cnt + 1, 16u); mbar_arrive(b_acq + 80);
    }
  }
}

__device__ __forceinline__ uint32_t role_of_sm(uint32_t sm) {
  const uint32_t t = sm >> 1, u = t - 32u, d = (u * 37u) >> 8;
  return (t < 32u ? ((t + 7u) & 7u) * 16u + (t >> 3) * 2u : t < 60u ? (u - 7u * d) * 16u + (4u + d) * 2u : t < 62u ? 2u * t + 8u : 2u * t - 4u) + (sm & 1u);
}
__global__ void __launch_bounds__(384, 1)
fused_kernel(const __grid_constant__ CUtensorMap tmH, const __grid_constant__ CUtensorMap tmW, const __grid_constant__ CUtensorMap tmK,
            const __grid_constant__ CUtensorMap tmV, const __grid_constant__ CUtensorMap tmO, const __grid_constant__ CUtensorMap tmOl, const __grid_constant__ CUtensorMap tmWo,
            const __grid_constant__ CUtensorMap tmD, const __grid_constant__ CUtensorMap tmOut, const __grid_constant__ CUtensorMap tmM, uint32_t zero,
            const uint8_t* __restrict__ pf_wo, const bf16* __restrict__ kc, const bf16* __restrict__ vc,
            const bf16* __restrict__ x, const bf16* __restrict__ cvec, const bf16* __restrict__ w_mod, const bf16* __restrict__ w_r,
            const bf16* __restrict__ w_gate, const bf16* __restrict__ w_up, const bf16* __restrict__ w_down, bf16* __restrict__ out)
{
  uint32_t bid, nsm;
  asm volatile("mov.u32 %0, %%smid;" : "=r"(bid));
  asm volatile("mov.u32 %0, %%nsmid;" : "=r"(nsm));
  bid = __shfl_sync(0xffffffffu, nsm == 132u ? role_of_sm(bid) : blockIdx.x, 0);
  extern __shared__ __align__(1024) uint8_t smem_raw[];
  const uint32_t sbase = smem_u32(smem_raw);
  const uint32_t bars = sbase + AT_SBAR;
  const uint32_t b_full = bars, b_empty = bars + 40;
  const uint32_t b_q0 = bars + 80, b_q1 = bars + 88;
  const uint32_t b_ob = bars + 96;
  const uint32_t b_ordy = bars + 104;
  const uint32_t b_pin = bars + 136;
  const uint32_t b_head = bars + 144;
  const uint32_t b_go = bars + 152;
  const uint32_t b_x = bars + 160;
  const int wg = __shfl_sync(0xffffffffu, threadIdx.x >> 7, 0);
  const bool single = bid >= AT_NFULL;
  const int item0 = __shfl_sync(0xffffffffu, bid < 128 ? (int)bid : (int)bid + 124, 0), n_items = __shfl_sync(0xffffffffu, single ? 1 : 2, 0);
  TL_START(3);
  if (threadIdx.x == 0) {
    if (sbase & 1023u) __trap();
    for (int i = 0; i < 5; i++) { mbar_init(b_full + 8 * i, 1); mbar_init(b_empty + 8 * i, 2); }
    mbar_init(b_q0, 1); mbar_init(b_q1, 8); mbar_init(b_ob, 1);
    for (int i = 0; i < 4; i++) mbar_init(b_ordy + 8 * i, 4);
    mbar_init(b_pin, 1); mbar_init(b_head, bid < 128 ? 8 : 1); mbar_init(b_go, 1); mbar_init(b_x, 1);
    mbar_init(bars + 168, 2); mbar_init(bars + 176, 1); mbar_init(bars + 184, 8); mbar_init(bars + 192, 2);
    mbar_init(bars + 200, 8); mbar_init(bars + 208, 4); mbar_init(bars + 216, 1); mbar_init(bars + 264, 1); mbar_init(bars + 272, 1); mbar_init(bars + 280, 8); mbar_init(bars + 288, 1); mbar_init(bars + 296, 1); mbar_init(bars + 304, 8); mbar_init(bars + 312, 1); mbar_init(bars + 320, 1); mbar_init(bars + 328, 1); mbar_init(bars + 336, 1); mbar_init(bars + 344, 1); mbar_init(bars + 352, 1); mbar_init(bars + 360, 1); mbar_init(bars + 368, 2); mbar_init(bars + 376, 2);
    sts_u32(bars + 400, bid);
    fence_mbar_init();
  }

  if (wg == 0) {
    reg_dealloc<AT_PREG>();
    if (threadIdx.x < 32) { __syncwarp(); named_bar_arrive(6, 384); }
    if (threadIdx.x >= 64) {
      named_bar_sync(6, 384);
      if (bid < 128) {
        named_bar_sync(threadIdx.x >= 96 ? 8 : 9, 288);
        if ((threadIdx.x & 31) == 0) red_release_add(&g_hcnt[32 * (1 + (bid >> 3)) + (threadIdx.x >= 96)], 1u);
        TL_MARK2(11, threadIdx.x == 64);
      }
      if (bid < 128) {
        mbar_wait(MOD_AT, 0);
        mod_rest(bid, sbase + OG_SCOL, b_q1, threadIdx.x - 64, cvec, w_mod, w_r);
      }
    } else if (threadIdx.x >= 32) {
      named_bar_sync(6, 384);
      store_warp(bid, sbase, &tmO, item0, n_items);
      __syncwarp();
    } else {
     if (elect_one()) {
      const uint64_t pol = policy_evict_first();
      if (bid < 128) {
        mbar_expect_tx(b_x, 32768);
        if (X_DLY) { const uint32_t c0 = clock_lo(); while (clock_lo() - c0 < X_DLY) {} }
        bulk_load_hint(sbase + 4 * 32768, x + (size_t)bid * 16 * T_D, 32768, b_x, pol);
      }
      prefetch_tmap(&tmW); prefetch_tmap(&tmM); prefetch_tmap(&tmH); prefetch_tmap(&tmWo); prefetch_tmap(&tmOl);
      {
        const uint32_t c0 = clock_lo();
        while (clock_lo() - c0 < W_DLY) {}
        if (bid < 128 && (head_cb(bid) & 15) >= 4 * H_SPLIT) {
          mbar_expect_tx(bars + 328, 32768);
          tma_load_2d_hint(sbase + 3 * 32768, &tmM, head_cb(bid) * 64, (bid >> 5) * 256, bars + 328, pol);
        }
        while (clock_lo() - c0 < W_DLY + W_FIRST) {}
      }
      uint32_t slot = 0, ph = 1;
      #pragma unroll 1
      for (int it = 0; it < n_items; it++) {
        const int item = item0 + it * 128, hp = item >> 4, qt = item & 15;
        const bool first = it == 0;
        #pragma unroll 1
        for (int j = 0; j < T_D / 64; j++) {
          const uint32_t sl = ring_slot(qp_pos(j, it)), fb = b_full + 8 * sl;
          mbar_wait_long(b_empty + 8 * sl, ring_par(qp_pos(j, it)) ^ ((j >> 2) & 1) ^ 1);
          if (first && j == 3) mbar_wait(b_head, 0);
          mbar_expect_tx(fb, 49152);
          tma_load_3d_hint(sbase + sl * 32768, &tmW, j * 64, hp * 4, fb, pol);
          if (first && j < PRE_B) {
            if (j == PRE_B - 1) {
              spin_until(&g_hcnt[32 * (1 + qt)], 8u);
              TL_MARK2(16, true);
              fence_proxy_async_global();
              #pragma unroll 1
              for (int i = 0; i < PRE_B; i++) tma_load_2d(sbase + AT_SQ + i * 16384, &tmH, i * 64, qt * 128, b_full + 8 * i);
              mbar_arrive(b_go);
            }
          } else {
            if (first && j == 4 * H_SPLIT) { spin_until(&g_hcnt[32 * (1 + qt) + 1], 8u); fence_proxy_async_global(); }
            if (!first && (j == 0 || j == 2)) mbar_wait(j ? b_q1 : b_q0, 0);
            tma_load_2d(sbase + AT_SQ + (j & 3) * 16384, &tmH, j * 64, qt * 128, fb);
          }
        }
        #pragma unroll 1
        for (int j = 0; j < 4 * AT_NBLK; j++) {
          const bool isv = (j > 0 && !(j & 1)) || j == 4 * AT_NBLK - 1;
          const int row = hp * 2 * T_SEQ + (isv ? (j - 1) >> 1 : (j + 1) >> 1) * 128;
          const uint32_t fb = b_full + 8 * slot;
          mbar_wait_long(b_empty + 8 * slot, ph);
          if (!first && j == 3) mbar_wait(b_ob, 0);
          if (j == 4 && it == n_items - 1) mbar_arrive(bars + 288);
          if ((j == AL_P || j == RK_P) && it == 1) mbar_arrive(bars + 312);
          mbar_expect_tx(fb, 32768);
          tma_load_3d_hint(sbase + slot * 32768, isv ? &tmV : &tmK, row, 0, fb, pol);
          if (it == 1 && isv && j >= 2 * WO_LATE && j < 2 * WO_LATE + 32 && bid < OG_NKB)
            l2_prefetch_bulk(pf_wo + (size_t)own_kb(bid, og_pre(0)) * 131072 + ((j >> 1) - WO_LATE) * 8192, 8192);
          if (++slot == 5) { slot = 0; ph ^= 1; }
        }
      }
      if (__builtin_expect(single, 0)) {
        spin_until(&g_hcnt[2], 128u);
        fence_proxy_async_global();
        const int nj = OG_HSUM + (help_njobs(bid) - OG_JOBS) * OG_PRE2;
        int ji = 0, job = help_job(bid, 0), kk = 0;
        #pragma unroll 1
        for (int j = 0; j < nj; j++) {
          const uint32_t sl = ring_slot(qp_pos(j, 1)), fb = b_full + 8 * sl;
          mbar_wait_long(b_empty + 8 * sl, ring_par(qp_pos(j, 1)) ^ ((j >> 2) & 1) ^ 1);
          mbar_expect_tx(fb, 49152);
          tma_load_3d(sbase + sl * 32768, &tmWo, pre_kb(kk) * 64, OG_NT(job) * 2, fb);
          tma_load_3d(sbase + sl * 32768 + 16384, &tmWo, pre_kb(kk) * 64, OG_NT(job) * 2 + 2, fb);
          if (j == 0 || j == 2) mbar_wait(j ? b_ob : b_q0, 0);
          tma_load_2d_hint(sbase + AT_SQ + (j & 3) * 16384, &tmOl, pre_kb(kk) * 64, OG_MT(job) * 128, fb, pol);
          if (++kk == og_pre(job)) { kk = 0; job = help_job(bid, ++ji); }
        }
      }
      if (bid < 128) {
        if (single) mbar_wait(b_x, 1);
        tail_producer(bid, sbase, 0, pol, &tmOl, &tmWo, &tmD);
      }
     }
    }
    named_bar_sync(12 + (threadIdx.x >> 5), 32);
    if (bid < 128) tail_exchange(bid, sbase, w_down, w_r, x, out);
  } else {
    if (bid < 128) head_phase(bid, sbase + AT_SQ + 49152, sbase + 4 * 32768, b_x, b_go, b_head, threadIdx.x - 128, zero, cvec, w_mod);
    else { named_bar_sync(6, 384); if (threadIdx.x == 128) mbar_arrive(b_head); }
    TL_MARK2(0, threadIdx.x == 128);
    reg_alloc<AT_CREG>();
    const int cwg = wg - 1;
    const int tid = threadIdx.x & 127;
    const int warp = tid >> 5, lane = tid & 31;
    const uint32_t dbase = (sbase & 0x3FFFFu) >> 4;
    const uint32_t k_base = dbase + (1u << 16);
    const uint32_t v_base = dbase + (1024u << 16);
    const uint32_t w_base = dbase + (512u << 16);
    const uint32_t q_lo = dbase + ((AT_SQ + cwg * 8192) >> 4) + (1u << 16);
    const uint32_t frag = cwg * 8192 + (16 * warp + (lane & 7) + 8 * ((lane >> 3) & 1)) * 128;
    if (cwg == 1) named_bar_arrive(1, 256);
    bool raw = false;
    uint4 pre[8];
    #pragma unroll 1
    for (int it = 0; it < n_items; it++) {
      const bool more = it + 1 < n_items;
      constexpr int nkb = T_D / 64;
      const int ta = __shfl_sync(0xffffffffu, 4 * it, 0);
      float acc[128];
      {
        FS(2 * it, 0);
        #pragma unroll
        for (int i = 0; i < 128; i++) asm volatile("" : "=f"(acc[i]));
        {
          const uint32_t slot = ring_slot(ta), b_lo = w_base + slot * 2048;
          mbar_wait(b_full + 8 * slot, ring_par(ta));
          wgmma_fence();
          wgmma_m64n256k16_ss_tb<0, 0>(acc, q_lo, b_lo, 0);
          wgmma_m64n256k16_ss_tb<2, 128>(acc, q_lo, b_lo, 1);
          wgmma_m64n256k16_ss_tb<4, 256>(acc, q_lo, b_lo, 1);
          wgmma_m64n256k16_ss_tb<6, 384>(acc, q_lo, b_lo, 1);
          wgmma_commit();
        }
        #pragma unroll 1
        for (int j = 1; j < nkb; j++) {
          const uint32_t slot = ring_slot(qp_pos(j, ta >> 2));
          mbar_wait(b_full + 8 * slot, ring_par(qp_pos(j, ta >> 2)) ^ ((j >> 2) & 1));
          if (QP_STAG > 0 && cwg == 1 && j == nkb - QP_STAG) named_bar_sync(7, 256);
          const uint32_t a_lo = q_lo + (j & 3) * 1024, b_lo = w_base + slot * 2048;
          wgmma_fence();
          wgmma_m64n256k16_ss_tb<0, 0>(acc, a_lo, b_lo, 1);
          wgmma_m64n256k16_ss_tb<2, 128>(acc, a_lo, b_lo, 1);
          wgmma_m64n256k16_ss_tb<4, 256>(acc, a_lo, b_lo, 1);
          wgmma_m64n256k16_ss_tb<6, 384>(acc, a_lo, b_lo, 1);
          wgmma_commit();
          if (QP_STAG > 0 && cwg == 0 && j == nkb - 1) named_bar_arrive(7, 256);
          if (j > 0) {
            wgmma_wait<1>();
            if (tid == 0) mbar_arrive(b_empty + 8 * ring_slot(qp_pos(j - 1, ta >> 2)));
          }
        }
        wgmma_wait<0>();
        fence_regs(acc);
        FS(2 * it, 1);
        TL_MARK2(29, threadIdx.x == 256 && it == 0);
        if (tid == 0) mbar_arrive(b_empty + 24);
      }
      float o[64], s[64];
      uint32_t p[32], q[32];
      #pragma unroll
      for (int i = 0; i < 32; i++) q[i] = pack_bf16(acc[2 * i] * AT_C, acc[2 * i + 1] * AT_C);
      zero_regs(s);
      const uint32_t sq = sbase + AT_SQ + cwg * 8192;
      float mc0, mc1, al0 = 1.0f, al1 = 1.0f, l0 = 0.f, l1 = 0.f, lp0 = 0.f, lp1 = 0.f;
      bool redo0 = false;
      FS(2 * it, 2);
      mbar_wait(b_full + 8 * ring_slot(ta), ring_par(ta));
      named_bar_sync(1 + cwg, 256);
      FS(2 * it, 3);
      issue_qk(s, q, k_base + ring_slot(ta) * 2048);
      pass_turn(cwg);
      bool ready = mbar_test(b_full + 8 * ring_slot(ta + 1), ring_par(ta + 1)) & mbar_test(b_full + 8 * ring_slot(ta + 2), ring_par(ta + 2));
      stage_q<16>(acc, AT_C, sbase + AT_SQ + frag, lane);
      wgmma_wait<0>();
      fence_regs(s);
      if (tid == 0) mbar_arrive(b_empty + 8 * ring_slot(ta));
      mc0 = 0.f; mc1 = 0.f;
      if (!raw) {
        raw = softmax_mode(s, mc0, mc1);
        if (__builtin_expect(!raw, 0)) softmax_sub(s, mc0, mc1);
      }
      softmax_exp<0, 64>(s);
      #pragma unroll
      for (int J = 0; J < 16; J += 2)
        stmatrix_x4(sbase + AT_SQ + frag + (J >> 3) * 16384 + ((((J & 7) + (lane >> 4)) ^ (lane & 7)) << 4), q[2 * J], q[2 * J + 1], q[2 * J + 2], q[2 * J + 3]);
      pack_p(p, s);
      zero_regs(o);
      FS(2 * it, 4);
      uint32_t ks = ring_slot(ta + 1), vs = ring_slot(ta + 2), kp = ring_par(ta + 1), vp = ring_par(ta + 2);
      auto finish_head = [&]() {
        FS(2 * it, 5);
        redo0 = finish_l(lp0, lp1);
        if (!redo0) stage_o(o, lp0, lp1, sbase + AT_SQ + frag, lane);
        FS(2 * it + 1, 4);
      };
      if (!ready) { mbar_wait(b_full + 8 * ks, kp); mbar_wait(b_full + 8 * vs, vp); }
      #pragma unroll 1
      for (int n = 1; n < 2 * AT_NBLK; n++) {
        named_bar_sync(1 + cwg, 256);
        issue_qk(s, q, k_base + ks * 2048);
        if (n == AT_NBLK + 1) finish_head();
        issue_pv(o, p, v_base + vs * 2048, (n & 15) != 1);
        pass_turn(cwg);
        wgmma_wait<1>();
        fence_regs(s);
        if (tid == 0) mbar_arrive(b_empty + 8 * ks);
        if (__builtin_expect(!raw || (uint32_t)(n - (AT_NBLK - 1)) <= 2u, 0)) {
          if (n == AT_NBLK + 1 && !redo0) {
            fence_proxy_async();
            __syncwarp();
            if (lane == 0) mbar_arrive(b_ordy + 8 * cwg);
          }
          if (n == AT_NBLK - 1) {
            #pragma unroll
            for (int J = 0; J < 16; J += 2)
              ldmatrix_x4(sbase + AT_SQ + 32768 + frag + (J >> 3) * 16384 + ((((J & 7) + (lane >> 4)) ^ (lane & 7)) << 4), q[2 * J], q[2 * J + 1], q[2 * J + 2], q[2 * J + 3]);
          }
          if (!raw) {
            const float m0 = mc0, m1 = mc1;
            const bool ok = softmax_mode(s, mc0, mc1);
            if (n == AT_NBLK) raw = ok;
            else {
              mc0 = mc0 - AT_HEAD > m0 ? mc0 : m0; mc1 = mc1 - AT_HEAD > m1 ? mc1 : m1;
              al0 = ex2_approx(m0 - mc0); al1 = ex2_approx(m1 - mc1);
            }
            if (!raw) softmax_sub(s, mc0, mc1);
          }
        }
        softmax_exp<0, AT_SPLIT>(s);
        add_rowsum(p, l0, l1);
        if (tid == 0) {
          uint32_t dep = zero & __float_as_uint(l0) & __float_as_uint(l1);
          #pragma unroll
          for (int i = AT_SPLIT - AT_PIN - PINB; i < AT_SPLIT - PINB; i += 2) dep &= __float_as_uint(s[i]) & __float_as_uint(s[i + 1]);
          mbar_arrive(b_pin + dep);
        }
        wgmma_wait<0>();
        fence_regs(o);
        if (tid == 0) mbar_arrive(b_empty + 8 * vs);
        ks += 2; if (ks >= 5) { ks -= 5; kp ^= 1; }
        vs += 2; if (vs >= 5) { vs -= 5; vp ^= 1; }
        ready = mbar_test(b_full + 8 * ks, kp) & mbar_test(b_full + 8 * vs, vp);
        softmax_exp<AT_SPLIT, 64>(s);
        pack_p(p, s);
        if (n == AT_NBLK) { lp0 = l0; lp1 = l1; l0 = 0.f; l1 = 0.f; }
        if (__builtin_expect(!raw || !ready, 0)) {
        if (!raw && __any_sync(0xffffffffu, al0 != 1.0f || al1 != 1.0f)) {
          rescale_o(o, al0, al1);
          l0 *= al0; l1 *= al1;
          al0 = 1.0f; al1 = 1.0f;
        }
        if (!ready && n < 2 * AT_NBLK - 1) {
          mbar_wait(b_full + 8 * ks, kp);
          mbar_wait(b_full + 8 * vs, vp);
        }
        }
      }
      FS(2 * it + 1, 5);
      const uint32_t vl = ring_slot(ta + 63);
      vs = ring_slot(ta + 62);
      const uint32_t ob = more ? sbase + vs * 32768 : sbase + AT_SQ + 32768;
      mbar_wait(b_full + 8 * vl, ring_par(ta + 63));
      issue_pv(o, p, v_base + vl * 2048, 1);
      block_end(zero, b_pin);
      add_rowsum(p, l0, l1);
      const bool overflow = finish_l(l0, l1);
      if (!overflow && lane == 0) mbar_arrive(b_q1);
      #pragma unroll
      for (int i = 0; i < 8; i++) asm volatile("mov.b64 {%0, %1}, 0;\nmov.b64 {%2, %3}, 0;" : "=r"(pre[i].x), "=r"(pre[i].y), "=r"(pre[i].z), "=r"(pre[i].w));
      const bool want_pre = !more && bid < OG_MOE, got_pre = want_pre && __all_sync(0xffffffffu, mbar_test(bars + 272, 0));
      if (got_pre) load_pre(pre, sbase, AT_SQ, threadIdx.x - 128);
      mbar_wait(b_empty + 8 * vs, ring_par(ta + 62));
      wgmma_wait<0>();
      fence_regs(o);
      if (tid == 0) mbar_arrive(b_empty + 8 * vl);
      FS(2 * it + 1, 6);
      if (overflow) {
        attn_rows_exact(lds_u32(bars + 400), sq + 32768, ob + cwg * 8192, 4 * ta + 1, kc, vc);
        __syncwarp();
        if (lane == 0) mbar_arrive(b_q1);
      } else stage_o(o, l0, l1, ob + frag, lane);
      if (redo0) attn_rows_exact(lds_u32(bars + 400), sq, sq, 4 * ta, kc, vc);
      fence_proxy_async();
      __syncwarp();
      if (lane == 0) {
        if (redo0) mbar_arrive(b_ordy + 8 * cwg);
        mbar_arrive(b_ordy + 16 + 8 * cwg);
      }
      if (want_pre && !got_pre) load_pre(pre, sbase, AT_SQ, threadIdx.x - 128);
      if (redo0 || overflow) raw = false;
      named_bar_sync(3 + cwg, 128);
      FS(2 * it + 1, 7);
    }
    if (cwg == 0) named_bar_arrive(1, 256);
    if (__builtin_expect(single, 0)) {
      float acc[128];
      uint32_t j = 0, pk[64];
      #pragma unroll
      for (int i = 0; i < 64; i++) asm volatile("" : "=f"(acc[2 * i]), "=f"(acc[2 * i + 1]), "=r"(pk[i]));
      uint4* dst = g_pre;
      int left = 0;
      auto put = [&](bool last) {
        #pragma unroll
        for (int i = 0; i < PUT_N; i++) dst[i * 256] = make_uint4(pk[4 * i], pk[4 * i + 1], pk[4 * i + 2], pk[4 * i + 3]);
        dst += PUT_N * 256;
        #pragma unroll
        for (int i = 0; i < 64 - 4 * PUT_N; i++) asm volatile("mov.b32 %0, %1;" : "=r"(pk[i]) : "r"(pk[i + 4 * PUT_N]));
        __syncwarp();
        if (last && lane == 0) mbar_arrive(bars + 280);
      };
      #pragma unroll 1
      for (int ji = 0; ji < help_njobs(bid); ji++) {
        const int nk = og_pre(help_job(bid, ji));
        #pragma unroll 1
        for (int kk = 0; kk < nk; kk++, j++) {
          const uint32_t slot = ring_slot(qp_pos(j, 1));
          mbar_wait(b_full + 8 * slot, ring_par(qp_pos(j, 1)) ^ ((j >> 2) & 1));
          if (H_STAG > 0 && cwg == 1 && kk == nk - H_STAG) named_bar_sync(7, 256);
          const uint32_t a_lo = q_lo + (j & 3) * 1024, b_lo = w_base + slot * 2048;
          wgmma_fence();
          wgmma_m64n256k16_ss_tb<0, 0>(acc, a_lo, b_lo, kk != 0);
          wgmma_m64n256k16_ss_tb<2, 128>(acc, a_lo, b_lo, 1);
          wgmma_m64n256k16_ss_tb<4, 256>(acc, a_lo, b_lo, 1);
          wgmma_m64n256k16_ss_tb<6, 384>(acc, a_lo, b_lo, 1);
          wgmma_commit();
          if (H_STAG > 0 && cwg == 0 && kk == nk - 1) named_bar_arrive(7, 256);
          wgmma_wait<1>();
          if (kk > 0 && tid == 0) mbar_arrive(b_empty + 8 * ring_slot(qp_pos(j - 1, 1)));
          #pragma unroll 1
          for (int i = ji == OG_JOBS ? 0 : 16 / PUT_N - 1; i < 16 / PUT_N && left > 0; i++) put(--left == 0);
        }
        wgmma_wait<0>();
        fence_regs(acc);
        if (tid == 0) mbar_arrive(b_empty + 8 * ring_slot(qp_pos(j - 1, 1)));
        #pragma unroll
        for (int i = 0; i < 64; i++) pk[i] = pack_bf16(acc[2 * i], acc[2 * i + 1]);
        left = 16 / PUT_N;
        if (ji == PRE_X) mbar_wait(bars + 296, 0);
        dst = g_pre + help_job(bid, ji) * 2048 + threadIdx.x - 128;
      }
      #pragma unroll
      for (int i = 0; i < 16; i++) dst[i * 256] = make_uint4(pk[4 * i], pk[4 * i + 1], pk[4 * i + 2], pk[4 * i + 3]);
      __syncwarp();
      if (lane == 0) mbar_arrive(bars + 280);
      named_bar_sync(5, 256);
      if (threadIdx.x == 128) {
        #pragma unroll 1
        for (int i = 0; i < 5; i++) {
          constexpr int n = OG_HSUM;
          const int used = i == 3 ? 0 : (n + 3 - (i == 4 ? 3 : i)) / 4;
          if ((used ^ (i < 4)) & 1) {
            mbar_arrive(b_full + 8 * ring_slot(4 + i));
            mbar_arrive(b_empty + 8 * ring_slot(4 + i)); mbar_arrive(b_empty + 8 * ring_slot(4 + i));
          }
        }
        mbar_arrive(b_x);
      }
      named_bar_sync(5, 256);
      #pragma unroll
      for (int i = 0; i < 8; i++) pre[i] = make_uint4(0u, 0u, 0u, 0u);
    }
    TL_CLK(3, 1, threadIdx.x == 128);
    TL_CTA(1, threadIdx.x == 256);
    TL_END(3, tid == 0);
    TL_MARK2(19, tid == 0 && !single);
    if (bid < 128) {
      tail_consumer(bid, sbase, &tmOut, pre, cwg, w_gate, w_up);
    }
  }
}

typedef CUresult (*PFN_encodeTiled)(CUtensorMap*, CUtensorMapDataType, cuuint32_t, void*, const cuuint64_t*, const cuuint64_t*,
                                    const cuuint32_t*, const cuuint32_t*, CUtensorMapInterleave, CUtensorMapSwizzle,
                                    CUtensorMapL2promotion, CUtensorMapFloatOOBfill);

CUtensorMap make_map_2d(PFN_encodeTiled enc, const void* ptr, uint64_t inner, uint64_t outer, uint64_t stride_bytes, uint32_t box_inner, uint32_t box_outer) {
  CUtensorMap m;
  cuuint64_t gd[2] = {inner, outer}; cuuint64_t gs[1] = {stride_bytes};
  cuuint32_t bx[2] = {box_inner, box_outer}; cuuint32_t es[2] = {1, 1};
  enc(&m, CU_TENSOR_MAP_DATA_TYPE_BFLOAT16, 2, const_cast<void*>(ptr), gd, gs, bx, es, CU_TENSOR_MAP_INTERLEAVE_NONE,
      CU_TENSOR_MAP_SWIZZLE_128B, CU_TENSOR_MAP_L2_PROMOTION_L2_128B, CU_TENSOR_MAP_FLOAT_OOB_FILL_NONE);
  return m;
}

CUtensorMap make_map_3d(PFN_encodeTiled enc, const void* ptr, uint64_t cols, uint64_t rows, uint32_t box_rows, uint32_t chunks) {
  CUtensorMap m;
  cuuint64_t gd[3] = {64, rows, cols / 64}; cuuint64_t gs[2] = {cols * 2, 128};
  cuuint32_t bx[3] = {64, box_rows, chunks}; cuuint32_t es[3] = {1, 1, 1};
  enc(&m, CU_TENSOR_MAP_DATA_TYPE_BFLOAT16, 3, const_cast<void*>(ptr), gd, gs, bx, es, CU_TENSOR_MAP_INTERLEAVE_NONE,
      CU_TENSOR_MAP_SWIZZLE_128B, CU_TENSOR_MAP_L2_PROMOTION_L2_128B, CU_TENSOR_MAP_FLOAT_OOB_FILL_NONE);
  return m;
}

}

extern "C" void kernel_launch(void* const* d_in, const int* in_sizes, int n_in, void* d_out, int out_size) {
  const bf16* x      = (const bf16*)d_in[0];
  const bf16* kc     = (const bf16*)d_in[1];
  const bf16* vc     = (const bf16*)d_in[2];
  const bf16* wq     = (const bf16*)d_in[3];
  const bf16* wo     = (const bf16*)d_in[4];
  const bf16* w_r    = (const bf16*)d_in[6];
  const bf16* w_gate = (const bf16*)d_in[7];
  const bf16* w_up   = (const bf16*)d_in[8];
  const bf16* w_down = (const bf16*)d_in[9];
  const bf16* cvec   = (const bf16*)d_in[10];
  const bf16* w_mod  = (const bf16*)d_in[11];
  bf16* out = (bf16*)d_out;

  static PFN_encodeTiled enc = nullptr;
  static void *p_h = nullptr, *p_o = nullptr;
  if (!enc) {
    void* fn = nullptr; cudaDriverEntryPointQueryResult qres;
    cudaGetDriverEntryPoint("cuTensorMapEncodeTiled", &fn, cudaEnableDefault, &qres);
    enc = (PFN_encodeTiled)fn;
    cudaGetSymbolAddress(&p_h, g_pre);
    p_h = (uint4*)p_h + 16 * PRE_X * 2048;
    cudaGetSymbolAddress(&p_o, g_o);
    cudaFuncSetAttribute(fused_kernel, cudaFuncAttributeMaxDynamicSharedMemorySize, (int)AT_SMEM);
  }
  const CUtensorMap tm_h   = make_map_2d(enc, p_h, T_D, T_SEQ, T_D * 2, 64, 128);
  const CUtensorMap tm_wq  = make_map_3d(enc, wq, T_DQKV, T_D, 64, 4);
  const CUtensorMap tm_k   = make_map_3d(enc, kc, T_DH, (uint64_t)T_NH * T_SEQ, 128, 2);
  const CUtensorMap tm_v   = make_map_3d(enc, vc, T_DH, (uint64_t)T_NH * T_SEQ, 128, 2);
  const CUtensorMap tm_ost = make_map_2d(enc, p_o, T_DQKV, T_SEQ, T_DQKV * 2, 64, 64);
  const CUtensorMap tm_old = make_map_2d(enc, p_o, T_DQKV, T_SEQ, T_DQKV * 2, 64, 128);
  const CUtensorMap tm_wo  = make_map_3d(enc, wo, T_D, T_DQKV, 64, 2);
  const CUtensorMap tm_d   = make_map_3d(enc, w_down, T_D, T_F, 32, 8);

  const CUtensorMap tm_m   = make_map_2d(enc, w_mod, 6 * T_D, T_D, 6 * T_D * 2, 64, 256);
  const CUtensorMap tm_out = make_map_2d(enc, out, T_D, T_SEQ, T_D * 2, 64, 16);

  fused_kernel<<<132, 384, AT_SMEM, cudaStreamPerThread>>>(tm_h, tm_wq, tm_k, tm_v, tm_ost, tm_old, tm_wo, tm_d, tm_out, tm_m, 0u, (const uint8_t*)wo, kc, vc, x, cvec, w_mod,
             w_r, w_gate, w_up, w_down, out);
}
```

```cpp
#include <cuda_runtime.h>
#include <cuda_bf16.h>
#include <cuda.h>
#include <stdint.h>

namespace {

typedef __nv_bfloat16 bf16;

constexpr int T_SEQ = 2048, T_D = 1024, T_NH = 32, T_DH = 128, T_DQKV = 4096, T_F = 3584;

#define PRE_X 2
__device__ __align__(1024) uint4 g_pre[(16 * PRE_X + 128) * 2048];
#define g_h (reinterpret_cast<bf16*>(g_pre + 16 * PRE_X * 2048))
__device__ __align__(1024) bf16 g_o[T_SEQ * T_DQKV];
__device__ __align__(16) uint8_t g_col[8 * 1536];
__device__ __align__(16) float g_scal[64];
__device__ __align__(16) unsigned int g_hcnt[17 * 32];
__device__ __align__(128) float g_modpart[4 * 2 * T_D];
struct __align__(2048) TailMail {
  float4 part1[T_SEQ * 8];
  uint32_t key[256];
  uint4 cand[16 * 2 * 2 * 128];
  uint32_t cnt[32];
  float ypart[(T_F / 32) * 2 * T_D];
};
__device__ TailMail g_mail;
#define g_part1 g_mail.part1
#define g_key g_mail.key
#define g_cand g_mail.cand
#define CNT_Y (g_mail.cnt)
#define g_ypart g_mail.ypart

__device__ __forceinline__ uint32_t smem_u32(const void* p) { return (uint32_t)__cvta_generic_to_shared(p); }
__device__ __forceinline__ void mbar_init(uint32_t bar, uint32_t cnt) { asm volatile("mbarrier.init.shared::cta.b64 [%0], %1;" :: "r"(bar), "r"(cnt)); }
__device__ __forceinline__ void mbar_expect_tx(uint32_t bar, uint32_t bytes) { asm volatile("mbarrier.arrive.expect_tx.shared::cta.b64 _, [%0], %1;" :: "r"(bar), "r"(bytes) : "memory"); }
__device__ __forceinline__ void mbar_arrive(uint32_t bar) { asm volatile("mbarrier.arrive.shared::cta.b64 _, [%0];" :: "r"(bar) : "memory"); }
__device__ __forceinline__ void mbar_wait(uint32_t bar, uint32_t parity) {
  asm volatile("{\n.reg .pred p;\nLAB_WAIT:\nmbarrier.try_wait.parity.shared::cta.b64 p, [%0], %1;\n@!p bra LAB_WAIT;\n}\n" :: "r"(bar), "r"(parity) : "memory");
}
__device__ __forceinline__ bool mbar_test(uint32_t bar, uint32_t parity) {
  uint32_t r; asm volatile("{\n.reg .pred p;\nmbarrier.test_wait.parity.shared::cta.b64 p, [%1], %2;\nselp.u32 %0, 1, 0, p;\n}\n" : "=r"(r) : "r"(bar), "r"(parity) : "memory");
  return r != 0;
}
__device__ __forceinline__ void mbar_wait_long(uint32_t bar, uint32_t parity) {
  asm volatile("{\n.reg .pred p;\nLAB_WAIT:\nmbarrier.try_wait.parity.shared::cta.b64 p, [%0], %1, %2;\n@!p bra LAB_WAIT;\n}\n" :: "r"(bar), "r"(parity), "r"(100000) : "memory");
}
__device__ __forceinline__ uint32_t clock_lo() { uint32_t c; asm volatile("mov.u32 %0, %%clock;" : "=r"(c)); return c; }
__device__ __forceinline__ void fence_mbar_init() { asm volatile("fence.mbarrier_init.release.cluster;" ::: "memory"); }
__device__ __forceinline__ void tma_load_2d(uint32_t dst, const CUtensorMap* map, int c0, int c1, uint32_t bar) {
  asm volatile("cp.async.bulk.tensor.2d.shared::cluster.global.mbarrier::complete_tx::bytes [%0], [%1, {%3, %4}], [%2];"
    :: "r"(dst), "l"(map), "r"(bar), "r"(c0), "r"(c1) : "memory");
}
__device__ __forceinline__ uint64_t policy_evict_first() {
  uint64_t p; asm volatile("createpolicy.fractional.L2::evict_first.b64 %0, 1.0;" : "=l"(p)); return p;
}
__device__ __forceinline__ void tma_load_2d_hint(uint32_t dst, const CUtensorMap* map, int c0, int c1, uint32_t bar, uint64_t pol) {
  asm volatile("cp.async.bulk.tensor.2d.shared::cluster.global.mbarrier::complete_tx::bytes.L2::cache_hint [%0], [%1, {%3, %4}], [%2], %5;"
    :: "r"(dst), "l"(map), "r"(bar), "r"(c0), "r"(c1), "l"(pol) : "memory");
}
__device__ __forceinline__ void tma_load_3d_hint(uint32_t dst, const CUtensorMap* map, int c1, int c2, uint32_t bar, uint64_t pol) {
  asm volatile("cp.async.bulk.tensor.3d.shared::cluster.global.mbarrier::complete_tx::bytes.L2::cache_hint [%0], [%1, {%3, %4, %5}], [%2], %6;"
    :: "r"(dst), "l"(map), "r"(bar), "n"(0), "r"(c1), "r"(c2), "l"(pol) : "memory");
}
__device__ __forceinline__ void tma_load_3d(uint32_t dst, const CUtensorMap* map, int c1, int c2, uint32_t bar) {
  asm volatile("cp.async.bulk.tensor.3d.shared::cluster.global.mbarrier::complete_tx::bytes [%0], [%1, {%3, %4, %5}], [%2];"
    :: "r"(dst), "l"(map), "r"(bar), "n"(0), "r"(c1), "r"(c2) : "memory");
}
__device__ __forceinline__ void tma_store_2d(const CUtensorMap* map, uint32_t src, int c0, int c1) {
  asm volatile("cp.async.bulk.tensor.2d.global.shared::cta.bulk_group [%0, {%2, %3}], [%1];" :: "l"(map), "r"(src), "r"(c0), "r"(c1) : "memory");
}
__device__ __forceinline__ void prefetch_tmap(const CUtensorMap* map) { asm volatile("prefetch.tensormap [%0];" :: "l"(map) : "memory"); }
__device__ __forceinline__ void l2_prefetch_bulk(const void* p, uint32_t bytes) {
  asm volatile("cp.async.bulk.prefetch.L2.global [%0], %1;" :: "l"(p), "r"(bytes) : "memory");
}
__device__ __forceinline__ void bulk_commit() { asm volatile("cp.async.bulk.commit_group;" ::: "memory"); }
template<int N> __device__ __forceinline__ void bulk_wait_read() { asm volatile("cp.async.bulk.wait_group.read %0;" :: "n"(N) : "memory"); }
template<int N> __device__ __forceinline__ void bulk_wait() { asm volatile("cp.async.bulk.wait_group %0;" :: "n"(N) : "memory"); }
__device__ __forceinline__ void named_bar_sync(int id, int nthreads) { asm volatile("bar.sync %0, %1;" :: "r"(id), "r"(nthreads) : "memory"); }
__device__ __forceinline__ void named_bar_arrive(int id, int nthreads) { asm volatile("bar.arrive %0, %1;" :: "r"(id), "r"(nthreads) : "memory"); }
__device__ __forceinline__ void pass_turn(int cwg) {
  asm volatile("{\n.reg .pred p;\nsetp.ne.u32 p, %0, 0;\n@p bar.arrive 1, 256;\n@!p bar.arrive 2, 256;\n}\n" :: "r"(cwg) : "memory");
}
__device__ __forceinline__ void wgmma_fence() { asm volatile("wgmma.fence.sync.aligned;" ::: "memory"); }
__device__ __forceinline__ void wgmma_commit() { asm volatile("wgmma.commit_group.sync.aligned;" ::: "memory"); }
template<int N> __device__ __forceinline__ void wgmma_wait() { asm volatile("wgmma.wait_group.sync.aligned %0;" :: "n"(N) : "memory"); }
template<int R> __device__ __forceinline__ void reg_alloc() { asm volatile("setmaxnreg.inc.sync.aligned.u32 %0;" :: "n"(R)); }
template<int R> __device__ __forceinline__ void reg_dealloc() { asm volatile("setmaxnreg.dec.sync.aligned.u32 %0;" :: "n"(R)); }
__device__ __forceinline__ bool elect_one() {
  uint32_t pred; asm volatile("{\n.reg .pred p;\nelect.sync _|p, 0xffffffff;\nselp.u32 %0, 1, 0, p;\n}\n" : "=r"(pred)); return pred != 0;
}
__device__ __forceinline__ uint32_t pack_bf16(float lo, float hi) {
  uint32_t r; asm("cvt.rn.bf16x2.f32 %0, %1, %2;" : "=r"(r) : "f"(hi), "f"(lo)); return r;
}
__device__ __forceinline__ void stmatrix_x4(uint32_t addr, uint32_t r0, uint32_t r1, uint32_t r2, uint32_t r3) {
  asm volatile("stmatrix.sync.aligned.m8n8.x4.shared.b16 [%0], {%1, %2, %3, %4};" :: "r"(addr), "r"(r0), "r"(r1), "r"(r2), "r"(r3) : "memory");
}
__device__ __forceinline__ void fence_proxy_async() { asm volatile("fence.proxy.async.shared::cta;" ::: "memory"); }
__device__ __forceinline__ float ex2_approx(float x) { float y; asm("ex2.approx.ftz.f32 %0, %1;" : "=f"(y) : "f"(x)); return y; }
template<int N> __device__ __forceinline__ void fence_regs(float (&r)[N]) {
  #pragma unroll
  for (int i = 0; i < N; i++) asm volatile("" : "+f"(r[i]) :: "memory");
}
template<int N> __device__ __forceinline__ void zero_regs(float (&r)[N]) {
  #pragma unroll
  for (int i = 0; i < N; i += 2) asm volatile("mov.b64 {%0, %1}, 0;" : "=f"(r[i]), "=f"(r[i + 1]));
}
__device__ __forceinline__ float rbf(float x) { return __uint_as_float(pack_bf16(0.f, x)); }
__device__ __forceinline__ float bflo(uint32_t v) { return __uint_as_float(v << 16); }
__device__ __forceinline__ float bfhi(uint32_t v) { return __uint_as_float(v & 0xffff0000u); }

#define XT(i) do {} while (0)
#define TL_START(k) do {} while (0)
#define TL_END(k, cond) do {} while (0)
#define TL_CTA(i, cond) do {} while (0)
#define FS(slot, k) do {} while (0)
#define TL_MARK2(k, cond) do {} while (0)
#define TL_CLK(k, i, cond) do {} while (0)

template <int OFFA, int OFFB>
__device__ __forceinline__ void wgmma_m64n256k16_ss_tb(float (&d)[128], uint32_t a_lo, uint32_t b_lo, int scaleD) {
  asm volatile("{\n.reg .pred p;\n.reg .b64 da, db;\nsetp.ne.b32 p, %130, 0;\n"
    "mov.b64 da, {%128, 0x40000040};\nmov.b64 db, {%129, 0x40000040};\n"
    "add.s64 da, da, %131;\nadd.s64 db, db, %132;\n"
    "wgmma.mma_async.sync.aligned.m64n256k16.f32.bf16.bf16 "
    "{%0, %1, %2, %3, %4, %5, %6, %7, %8, %9, %10, %11, %12, %13, %14, %15, %16, %17, %18, %19, %20, %21, %22, %23, %24, %25, %26, %27, %28, %29, %30, %31, %32, %33, %34, %35, %36, %37, %38, %39, %40, %41, %42, %43, %44, %45, %46, %47, %48, %49, %50, %51, %52, %53, %54, %55, %56, %57, %58, %59, %60, %61, %62, %63, %64, %65, %66, %67, %68, %69, %70, %71, %72, %73, %74, %75, %76, %77, %78, %79, %80, %81, %82, %83, %84, %85, %86, %87, %88, %89, %90, %91, %92, %93, %94, %95, %96, %97, %98, %99, %100, %101, %102, %103, %104, %105, %106, %107, %108, %109, %110, %111, %112, %113, %114, %115, %116, %117, %118, %119, %120, %121, %122, %123, %124, %125, %126, %127}, "
    "da, db, p, 1, 1, 0, 1;\n}\n"
    : "+f"(d[0]), "+f"(d[1]), "+f"(d[2]), "+f"(d[3]), "+f"(d[4]), "+f"(d[5]), "+f"(d[6]), "+f"(d[7]), "+f"(d[8]), "+f"(d[9]), "+f"(d[10]), "+f"(d[11]), "+f"(d[12]), "+f"(d[13]), "+f"(d[14]), "+f"(d[15]), "+f"(d[16]), "+f"(d[17]), "+f"(d[18]), "+f"(d[19]), "+f"(d[20]), "+f"(d[21]), "+f"(d[22]), "+f"(d[23]), "+f"(d[24]), "+f"(d[25]), "+f"(d[26]), "+f"(d[27]), "+f"(d[28]), "+f"(d[29]), "+f"(d[30]), "+f"(d[31]), "+f"(d[32]), "+f"(d[33]), "+f"(d[34]), "+f"(d[35]), "+f"(d[36]), "+f"(d[37]), "+f"(d[38]), "+f"(d[39]), "+f"(d[40]), "+f"(d[41]), "+f"(d[42]), "+f"(d[43]), "+f"(d[44]), "+f"(d[45]), "+f"(d[46]), "+f"(d[47]), "+f"(d[48]), "+f"(d[49]), "+f"(d[50]), "+f"(d[51]), "+f"(d[52]), "+f"(d[53]), "+f"(d[54]), "+f"(d[55]), "+f"(d[56]), "+f"(d[57]), "+f"(d[58]), "+f"(d[59]), "+f"(d[60]), "+f"(d[61]), "+f"(d[62]), "+f"(d[63]), "+f"(d[64]), "+f"(d[65]), "+f"(d[66]), "+f"(d[67]), "+f"(d[68]), "+f"(d[69]), "+f"(d[70]), "+f"(d[71]), "+f"(d[72]), "+f"(d[73]), "+f"(d[74]), "+f"(d[75]), "+f"(d[76]), "+f"(d[77]), "+f"(d[78]), "+f"(d[79]), "+f"(d[80]), "+f"(d[81]), "+f"(d[82]), "+f"(d[83]), "+f"(d[84]), "+f"(d[85]), "+f"(d[86]), "+f"(d[87]), "+f"(d[88]), "+f"(d[89]), "+f"(d[90]), "+f"(d[91]), "+f"(d[92]), "+f"(d[93]), "+f"(d[94]), "+f"(d[95]), "+f"(d[96]), "+f"(d[97]), "+f"(d[98]), "+f"(d[99]), "+f"(d[100]), "+f"(d[101]), "+f"(d[102]), "+f"(d[103]), "+f"(d[104]), "+f"(d[105]), "+f"(d[106]), "+f"(d[107]), "+f"(d[108]), "+f"(d[109]), "+f"(d[110]), "+f"(d[111]), "+f"(d[112]), "+f"(d[113]), "+f"(d[114]), "+f"(d[115]), "+f"(d[116]), "+f"(d[117]), "+f"(d[118]), "+f"(d[119]), "+f"(d[120]), "+f"(d[121]), "+f"(d[122]), "+f"(d[123]), "+f"(d[124]), "+f"(d[125]), "+f"(d[126]), "+f"(d[127])
    : "r"(a_lo), "r"(b_lo), "r"(scaleD), "n"(OFFA), "n"(OFFB));
}

template <int OFFA, int OFFB>
__device__ __forceinline__ void wgmma_m64n128k16_ss_tb(float (&d)[64], uint32_t a_lo, uint32_t b_lo, int scaleD) {
  asm volatile("{\n.reg .pred p;\n.reg .b64 da, db;\nsetp.ne.b32 p, %66, 0;\n"
    "mov.b64 da, {%64, 0x40000040};\nmov.b64 db, {%65, 0x40000040};\n"
    "add.s64 da, da, %67;\nadd.s64 db, db, %68;\n"
    "wgmma.mma_async.sync.aligned.m64n128k16.f32.bf16.bf16 "
    "{%0, %1, %2, %3, %4, %5, %6, %7, %8, %9, %10, %11, %12, %13, %14, %15, %16, %17, %18, %19, %20, %21, %22, %23, %24, %25, %26, %27, %28, %29, %30, %31, %32, %33, %34, %35, %36, %37, %38, %39, %40, %41, %42, %43, %44, %45, %46, %47, %48, %49, %50, %51, %52, %53, %54, %55, %56, %57, %58, %59, %60, %61, %62, %63}, "
    "da, db, p, 1, 1, 0, 1;\n}\n"
    : "+f"(d[0]), "+f"(d[1]), "+f"(d[2]), "+f"(d[3]), "+f"(d[4]), "+f"(d[5]), "+f"(d[6]), "+f"(d[7]), "+f"(d[8]), "+f"(d[9]), "+f"(d[10]), "+f"(d[11]), "+f"(d[12]), "+f"(d[13]), "+f"(d[14]), "+f"(d[15]), "+f"(d[16]), "+f"(d[17]), "+f"(d[18]), "+f"(d[19]), "+f"(d[20]), "+f"(d[21]), "+f"(d[22]), "+f"(d[23]), "+f"(d[24]), "+f"(d[25]), "+f"(d[26]), "+f"(d[27]), "+f"(d[28]), "+f"(d[29]), "+f"(d[30]), "+f"(d[31]), "+f"(d[32]), "+f"(d[33]), "+f"(d[34]), "+f"(d[35]), "+f"(d[36]), "+f"(d[37]), "+f"(d[38]), "+f"(d[39]), "+f"(d[40]), "+f"(d[41]), "+f"(d[42]), "+f"(d[43]), "+f"(d[44]), "+f"(d[45]), "+f"(d[46]), "+f"(d[47]), "+f"(d[48]), "+f"(d[49]), "+f"(d[50]), "+f"(d[51]), "+f"(d[52]), "+f"(d[53]), "+f"(d[54]), "+f"(d[55]), "+f"(d[56]), "+f"(d[57]), "+f"(d[58]), "+f"(d[59]), "+f"(d[60]), "+f"(d[61]), "+f"(d[62]), "+f"(d[63])
    : "r"(a_lo), "r"(b_lo), "r"(scaleD), "n"(OFFA), "n"(OFFB));
}

template <int OFFB>
__device__ __forceinline__ void wgmma_m64n128k16_rs_tb(float (&d)[64], uint32_t a0, uint32_t a1, uint32_t a2, uint32_t a3, uint32_t b_lo, int scaleD) {
  asm volatile("{\n.reg .pred p;\n.reg .b64 db;\nsetp.ne.b32 p, %69, 0;\n"
    "mov.b64 db, {%68, 0x40000040};\nadd.s64 db, db, %70;\n"
    "wgmma.mma_async.sync.aligned.m64n128k16.f32.bf16.bf16 "
    "{%0, %1, %2, %3, %4, %5, %6, %7, %8, %9, %10, %11, %12, %13, %14, %15, %16, %17, %18, %19, %20, %21, %22, %23, %24, %25, %26, %27, %28, %29, %30, %31, %32, %33, %34, %35, %36, %37, %38, %39, %40, %41, %42, %43, %44, %45, %46, %47, %48, %49, %50, %51, %52, %53, %54, %55, %56, %57, %58, %59, %60, %61, %62, %63}, "
    "{%64, %65, %66, %67}, db, p, 1, 1, 1;\n}\n"
    : "+f"(d[0]), "+f"(d[1]), "+f"(d[2]), "+f"(d[3]), "+f"(d[4]), "+f"(d[5]), "+f"(d[6]), "+f"(d[7]), "+f"(d[8]), "+f"(d[9]), "+f"(d[10]), "+f"(d[11]), "+f"(d[12]), "+f"(d[13]), "+f"(d[14]), "+f"(d[15]), "+f"(d[16]), "+f"(d[17]), "+f"(d[18]), "+f"(d[19]), "+f"(d[20]), "+f"(d[21]), "+f"(d[22]), "+f"(d[23]), "+f"(d[24]), "+f"(d[25]), "+f"(d[26]), "+f"(d[27]), "+f"(d[28]), "+f"(d[29]), "+f"(d[30]), "+f"(d[31]), "+f"(d[32]), "+f"(d[33]), "+f"(d[34]), "+f"(d[35]), "+f"(d[36]), "+f"(d[37]), "+f"(d[38]), "+f"(d[39]), "+f"(d[40]), "+f"(d[41]), "+f"(d[42]), "+f"(d[43]), "+f"(d[44]), "+f"(d[45]), "+f"(d[46]), "+f"(d[47]), "+f"(d[48]), "+f"(d[49]), "+f"(d[50]), "+f"(d[51]), "+f"(d[52]), "+f"(d[53]), "+f"(d[54]), "+f"(d[55]), "+f"(d[56]), "+f"(d[57]), "+f"(d[58]), "+f"(d[59]), "+f"(d[60]), "+f"(d[61]), "+f"(d[62]), "+f"(d[63])
    : "r"(a0), "r"(a1), "r"(a2), "r"(a3), "r"(b_lo), "r"(scaleD), "n"(OFFB));
}

template <int OFFB>
__device__ __forceinline__ void wgmma_m64n128k16_rs(float (&d)[64], uint32_t a0, uint32_t a1, uint32_t a2, uint32_t a3, uint32_t b_lo, int scaleD) {
  asm volatile("{\n.reg .pred p;\n.reg .b64 db;\nsetp.ne.b32 p, %69, 0;\n"
    "mov.b64 db, {%68, 0x40000040};\nadd.s64 db, db, %70;\n"
    "wgmma.mma_async.sync.aligned.m64n128k16.f32.bf16.bf16 "
    "{%0, %1, %2, %3, %4, %5, %6, %7, %8, %9, %10, %11, %12, %13, %14, %15, %16, %17, %18, %19, %20, %21, %22, %23, %24, %25, %26, %27, %28, %29, %30, %31, %32, %33, %34, %35, %36, %37, %38, %39, %40, %41, %42, %43, %44, %45, %46, %47, %48, %49, %50, %51, %52, %53, %54, %55, %56, %57, %58, %59, %60, %61, %62, %63}, "
    "{%64, %65, %66, %67}, db, p, 1, 1, 0;\n}\n"
    : "+f"(d[0]), "+f"(d[1]), "+f"(d[2]), "+f"(d[3]), "+f"(d[4]), "+f"(d[5]), "+f"(d[6]), "+f"(d[7]), "+f"(d[8]), "+f"(d[9]), "+f"(d[10]), "+f"(d[11]), "+f"(d[12]), "+f"(d[13]), "+f"(d[14]), "+f"(d[15]), "+f"(d[16]), "+f"(d[17]), "+f"(d[18]), "+f"(d[19]), "+f"(d[20]), "+f"(d[21]), "+f"(d[22]), "+f"(d[23]), "+f"(d[24]), "+f"(d[25]), "+f"(d[26]), "+f"(d[27]), "+f"(d[28]), "+f"(d[29]), "+f"(d[30]), "+f"(d[31]), "+f"(d[32]), "+f"(d[33]), "+f"(d[34]), "+f"(d[35]), "+f"(d[36]), "+f"(d[37]), "+f"(d[38]), "+f"(d[39]), "+f"(d[40]), "+f"(d[41]), "+f"(d[42]), "+f"(d[43]), "+f"(d[44]), "+f"(d[45]), "+f"(d[46]), "+f"(d[47]), "+f"(d[48]), "+f"(d[49]), "+f"(d[50]), "+f"(d[51]), "+f"(d[52]), "+f"(d[53]), "+f"(d[54]), "+f"(d[55]), "+f"(d[56]), "+f"(d[57]), "+f"(d[58]), "+f"(d[59]), "+f"(d[60]), "+f"(d[61]), "+f"(d[62]), "+f"(d[63])
    : "r"(a0), "r"(a1), "r"(a2), "r"(a3), "r"(b_lo), "r"(scaleD), "n"(OFFB));
}

__device__ __forceinline__ uint4 ldg_nc_v4(const void* p) {
  uint4 v;
    asm volatile("{\n.reg .b64 pol;\ncreatepolicy.fractional.L2::evict_first.b64 pol, 1.0;\n"
                 "ld.global.nc.L1::no_allocate.L2::cache_hint.v4.u32 {%0, %1, %2, %3}, [%4], pol;\n}\n" : "=r"(v.x), "=r"(v.y), "=r"(v.z), "=r"(v.w) : "l"(p));
  return v;
}
__device__ __forceinline__ void unpack8(const uint4& u, float (&v)[8]) {
  v[0] = bflo(u.x); v[1] = bfhi(u.x); v[2] = bflo(u.y); v[3] = bfhi(u.y);
  v[4] = bflo(u.z); v[5] = bfhi(u.z); v[6] = bflo(u.w); v[7] = bfhi(u.w);
}
__device__ __forceinline__ void fma8(float (&acc)[8], float s, const uint4& w) {
  acc[0] = fmaf(s, bflo(w.x), acc[0]); acc[1] = fmaf(s, bfhi(w.x), acc[1]); acc[2] = fmaf(s, bflo(w.y), acc[2]); acc[3] = fmaf(s, bfhi(w.y), acc[3]);
  acc[4] = fmaf(s, bflo(w.z), acc[4]); acc[5] = fmaf(s, bfhi(w.z), acc[5]); acc[6] = fmaf(s, bflo(w.w), acc[6]); acc[7] = fmaf(s, bfhi(w.w), acc[7]);
}
__device__ __forceinline__ float rcp_approx(float x) { float y; asm("rcp.approx.ftz.f32 %0, %1;" : "=f"(y) : "f"(x)); return y; }
__device__ __forceinline__ float sigmoid_f(float v) { return rcp_approx(1.0f + ex2_approx(v * -1.4426950408889634f)); }
__device__ __forceinline__ float silu_bf(float v) { return rbf(v * sigmoid_f(v)); }
__device__ __forceinline__ uint32_t rank_key(float r, int idx) {
  const uint32_t b = __float_as_uint(r) >> 16;
  const uint32_t u = (r != r) ? 0u : ((b & 0x8000u) ? (~b & 0xffffu) : (b | 0x8000u));
  return (u << 16) | (0xffffu - (uint32_t)idx);
}
__device__ __forceinline__ void warp_top2(uint32_t& k1, uint32_t& k2) {
  const uint32_t m1 = __reduce_max_sync(0xffffffffu, k1);
  k2 = __reduce_max_sync(0xffffffffu, k1 == m1 ? k2 : k1);
  k1 = m1;
}
__device__ __forceinline__ uint32_t bmul2(uint32_t a, uint32_t b) { uint32_t r; asm("mul.rn.bf16x2 %0, %1, %2;" : "=r"(r) : "r"(a), "r"(b)); return r; }
__device__ __forceinline__ uint32_t badd2(uint32_t a, uint32_t b) { uint32_t r; asm("add.rn.bf16x2 %0, %1, %2;" : "=r"(r) : "r"(a), "r"(b)); return r; }
__device__ __forceinline__ uint32_t bsub2(uint32_t a, uint32_t b) { uint32_t r; asm("sub.rn.bf16x2 %0, %1, %2;" : "=r"(r) : "r"(a), "r"(b)); return r; }
__device__ __forceinline__ float sqrt_approx(float x) { float y; asm("sqrt.approx.f32 %0, %1;" : "=f"(y) : "f"(x)); return y; }
__device__ __forceinline__ uint32_t ln_norm2(uint32_t x1, uint32_t mb2, float inv) {
  const uint32_t d = bsub2(x1, mb2);
  return pack_bf16(bflo(d) * inv, bfhi(d) * inv);
}
__device__ __forceinline__ uint32_t bfma2(uint32_t a, uint32_t b, uint32_t c) { uint32_t r; asm("fma.rn.bf16x2 %0, %1, %2, %3;" : "=r"(r) : "r"(a), "r"(b), "r"(c)); return r; }
__device__ __forceinline__ uint32_t ln_norm2b(uint32_t x1, uint32_t mb2, uint32_t ih, uint32_t il) {
  const uint32_t d = bsub2(x1, mb2);
  return bfma2(d, ih, bmul2(d, il));
}
__device__ __forceinline__ uint32_t ln_mod2(uint32_t x1, uint32_t mb2, float inv, uint32_t c1, uint32_t sb) { return badd2(bmul2(ln_norm2(x1, mb2, inv), c1), sb); }
__device__ __forceinline__ void ldmatrix_x4(uint32_t addr, uint32_t& r0, uint32_t& r1, uint32_t& r2, uint32_t& r3) {
  asm volatile("ldmatrix.sync.aligned.m8n8.x4.shared.b16 {%0, %1, %2, %3}, [%4];" : "=r"(r0), "=r"(r1), "=r"(r2), "=r"(r3) : "r"(addr) : "memory");
}
__device__ __forceinline__ uint4 ldg_stream_v4(const void* p, uint64_t pol) {
  uint4 v; asm volatile("ld.global.nc.L1::no_allocate.L2::cache_hint.L2::128B.v4.u32 {%0, %1, %2, %3}, [%4], %5;" : "=r"(v.x), "=r"(v.y), "=r"(v.z), "=r"(v.w) : "l"(p), "l"(pol)); return v;
}
__device__ __forceinline__ void bulk_load_hint(uint32_t dst, const void* src, uint32_t bytes, uint32_t bar, uint64_t pol) {
  asm volatile("cp.async.bulk.shared::cluster.global.mbarrier::complete_tx::bytes.L2::cache_hint [%0], [%1], %2, [%3], %4;"
    :: "r"(dst), "l"(src), "r"(bytes), "r"(bar), "l"(pol) : "memory");
}
__device__ __forceinline__ void red_release_add(unsigned int* p, unsigned int v) { asm volatile("red.release.gpu.global.add.u32 [%0], %1;" :: "l"(p), "r"(v) : "memory"); }
__device__ __forceinline__ unsigned int ld_acquire(const unsigned int* p) { unsigned int v; asm volatile("ld.acquire.gpu.global.u32 %0, [%1];" : "=r"(v) : "l"(p) : "memory"); return v; }
__device__ __forceinline__ void spin_until(const unsigned int* p, unsigned int target) {
  #pragma unroll 1
  for (unsigned int i = 0; i < (1u << 22); i++) { if (ld_acquire(p) >= target) return; }
}
__device__ __forceinline__ float lds_f32(uint32_t a) { float v; asm volatile("ld.shared.f32 %0, [%1];" : "=f"(v) : "r"(a) : "memory"); return v; }
__device__ __forceinline__ float2 lds_f32x2(uint32_t a) { float2 v; asm volatile("ld.shared.v2.f32 {%0, %1}, [%2];" : "=f"(v.x), "=f"(v.y) : "r"(a) : "memory"); return v; }
__device__ __forceinline__ uint2 lds_u32x2(uint32_t a) { uint2 v; asm volatile("ld.shared.v2.u32 {%0, %1}, [%2];" : "=r"(v.x), "=r"(v.y) : "r"(a) : "memory"); return v; }
__device__ __forceinline__ uint32_t lds_u32(uint32_t a) { uint32_t v; asm volatile("ld.shared.u32 %0, [%1];" : "=r"(v) : "r"(a) : "memory"); return v; }
__device__ __forceinline__ void sts_u32(uint32_t a, uint32_t v) { asm volatile("st.shared.u32 [%0], %1;" :: "r"(a), "r"(v) : "memory"); }
__device__ __forceinline__ void sts_u32x2(uint32_t a, uint32_t x, uint32_t y) { asm volatile("st.shared.v2.u32 [%0], {%1, %2};" :: "r"(a), "r"(x), "r"(y) : "memory"); }
__device__ __forceinline__ void sts_f32(uint32_t a, float v) { asm volatile("st.shared.f32 [%0], %1;" :: "r"(a), "f"(v) : "memory"); }
__device__ __forceinline__ void sts_f32x2(uint32_t a, float x, float y) { asm volatile("st.shared.v2.f32 [%0], {%1, %2};" :: "r"(a), "f"(x), "f"(y) : "memory"); }
__device__ __forceinline__ void sts_f32x4(uint32_t a, float x, float y, float z, float w) { asm volatile("st.shared.v4.f32 [%0], {%1, %2, %3, %4};" :: "r"(a), "f"(x), "f"(y), "f"(z), "f"(w) : "memory"); }

__device__ __forceinline__ uint4 lds_u32x4(uint32_t a) { uint4 v; asm volatile("ld.shared.v4.u32 {%0, %1, %2, %3}, [%4];" : "=r"(v.x), "=r"(v.y), "=r"(v.z), "=r"(v.w) : "r"(a) : "memory"); return v; }
__device__ __forceinline__ void sts_u32x4(uint32_t a, uint32_t x, uint32_t y, uint32_t z, uint32_t w) { asm volatile("st.shared.v4.u32 [%0], {%1, %2, %3, %4};" :: "r"(a), "r"(x), "r"(y), "r"(z), "r"(w) : "memory"); }
__device__ __forceinline__ void st_tagged(float* p, float v) {
  const uint32_t b = __float_as_uint(v);
  asm volatile("st.relaxed.gpu.global.u32 [%0], %1;" :: "l"(p), "r"(b == 0u ? 0x80000000u : b) : "memory");
}
__device__ __forceinline__ void st_tagged4(float* p, float x, float y, float z, float w) {
  const uint32_t a = __float_as_uint(x), b = __float_as_uint(y), c = __float_as_uint(z), d = __float_as_uint(w);
  asm volatile("st.relaxed.gpu.global.v4.u32 [%0], {%1, %2, %3, %4};" :: "l"(p), "r"(a == 0u ? 0x80000000u : a), "r"(b == 0u ? 0x80000000u : b),
               "r"(c == 0u ? 0x80000000u : c), "r"(d == 0u ? 0x80000000u : d) : "memory");
}
__device__ __forceinline__ void st_tagged4_lsb(float* p, float x, float y, float z, float w) {
  asm volatile("st.relaxed.gpu.global.v4.u32 [%0], {%1, %2, %3, %4};" :: "l"(p), "r"(__float_as_uint(x) | 1u), "r"(__float_as_uint(y) | 1u),
               "r"(__float_as_uint(z) | 1u), "r"(__float_as_uint(w) | 1u) : "memory");
}
__device__ __forceinline__ void st_relaxed2(void* p, uint32_t a, uint32_t b) { asm volatile("st.relaxed.gpu.global.v2.u32 [%0], {%1, %2};" :: "l"(p), "r"(a), "r"(b) : "memory"); }
__device__ __forceinline__ float4 ld_tagged4(const float* p) {
  float4 v; asm volatile("ld.relaxed.gpu.global.v4.f32 {%0, %1, %2, %3}, [%4];" : "=f"(v.x), "=f"(v.y), "=f"(v.z), "=f"(v.w) : "l"(p) : "memory"); return v;
}
__device__ __forceinline__ bool tagged4(const float4& v) {
  return __float_as_uint(v.x) != 0u && __float_as_uint(v.y) != 0u && __float_as_uint(v.z) != 0u && __float_as_uint(v.w) != 0u;
}
__device__ __forceinline__ void hint_arrive(uint32_t* p) { asm volatile("red.relaxed.gpu.global.add.u32 [%0], 1;" :: "l"(p) : "memory"); }
__device__ __forceinline__ void hint_wait(const uint32_t* p, uint32_t target) {
  uint32_t v = 0u;
  #pragma unroll 1
  for (unsigned int i = 0; i < (1u << 22) && v < target; i++) asm volatile("ld.relaxed.gpu.global.u32 %0, [%1];" : "=r"(v) : "l"(p) : "memory");
}
__device__ __forceinline__ void fence_proxy_async_global() { asm volatile("fence.proxy.async.global;" ::: "memory"); }

#define H_SPLIT 1
#define X_DLY 1200
#define W_DLY 1900
#define W_FIRST 2200
#define PRE_B 2
template <int J0, int J1>
__device__ __forceinline__ void load_parts(float2 (&pa)[J1 - J0][4], int t2) {
  #pragma unroll
  for (int j = J0; j < J1; j++)
    #pragma unroll
    for (int k = 0; k < 4; k++)
      asm volatile("ld.relaxed.gpu.global.v2.f32 {%0, %1}, [%2];" : "=f"(pa[j - J0][k].x), "=f"(pa[j - J0][k].y)
                   : "l"(g_modpart + k * 2 * T_D + (t2 >> 7) * T_D + j * 256 + (t2 & 127) * 2) : "memory");
}
template <int J0, int J1>
__device__ __forceinline__ void finish_parts(float2 (&pa)[J1 - J0][4], bool loaded, int t2, uint32_t tab) {
  #pragma unroll 1
  for (unsigned int spin = 0; spin < (1u << 22); spin++) {
    if (!loaded) load_parts<J0, J1>(pa, t2);
    loaded = false;
    bool ok = true;
    #pragma unroll
    for (int j = 0; j < J1 - J0; j++)
      #pragma unroll
      for (int k = 0; k < 4; k++) ok &= (__float_as_uint(pa[j][k].x) != 0u) & (__float_as_uint(pa[j][k].y) != 0u);
    if (__all_sync(0xffffffffu, ok)) break;
  }
  #pragma unroll
  for (int j = J0; j < J1; j++) {
    const float2* q = pa[j - J0];
    const uint32_t m = pack_bf16(((q[0].x + q[1].x) + q[2].x) + q[3].x, ((q[0].y + q[1].y) + q[2].y) + q[3].y);
    sts_u32(tab + (t2 >> 7) * 2048 + j * 512 + (t2 & 127) * 4, t2 >= 128 ? badd2(m, 0x3F803F80u) : m);
  }
}
__device__ __forceinline__ int head_cb(uint32_t bid) { return (bid & 16) | ((bid & 3) << 2) | ((bid >> 2) & 3); }
__device__ __forceinline__ void head_phase(uint32_t bid, uint32_t scr, uint32_t xs, uint32_t b_x, uint32_t b_go, uint32_t b_head, int t2, uint32_t zero, const bf16* __restrict__ cvec, const bf16* __restrict__ w_mod) {
  const int lane = t2 & 31, w8 = t2 >> 5;
  const int cb = head_cb(bid), ks = bid >> 5;
  const bool early = (cb & 15) < 4 * H_SPLIT;
  const uint32_t ws = (xs - 32768 + (t2 >> 3) * 128 + (((t2 ^ (t2 >> 3)) & 7) << 4)) ^ zero;
  const float cv = __bfloat162float(cvec[ks * 256 + t2]);
  const bf16* wsrc = w_mod + (size_t)(ks * 256 + (t2 >> 3)) * (6 * T_D) + cb * 64 + (t2 & 7) * 8;
  if (early) {
    const uint64_t pol = policy_evict_first();
    #pragma unroll 2
    for (int i = 0; i < 8; i++)
      asm volatile("cp.async.cg.shared.global.L2::cache_hint [%0], [%1], 16, %2;" :: "r"(ws + i * 4096), "l"(wsrc + (size_t)i * 32 * 6 * T_D), "l"(pol) : "memory");
  }
  sts_f32(scr + t2 * 4, silu_bf(cv));
  named_bar_sync(6, 384);
  TL_MARK2(1, t2 == 0);
  uint4 xv[2][4];
  uint32_t mb2[2], ih[2], il[2];
  auto norm = [&](int j) {
    #pragma unroll
    for (int r = 0; r < 2; r++) {
      xv[r][j].x = ln_norm2b(xv[r][j].x, mb2[r], ih[r], il[r]); xv[r][j].y = ln_norm2b(xv[r][j].y, mb2[r], ih[r], il[r]);
      xv[r][j].z = ln_norm2b(xv[r][j].z, mb2[r], ih[r], il[r]); xv[r][j].w = ln_norm2b(xv[r][j].w, mb2[r], ih[r], il[r]);
    }
  };
  auto modulate = [&](int j) {
    const uint4 sa = lds_u32x4(scr + 8192 + j * 512 + lane * 16), c1 = lds_u32x4(scr + 8192 + 2048 + j * 512 + lane * 16);
    #pragma unroll
    for (int r = 0; r < 2; r++) {
      xv[r][j].x = badd2(bmul2(xv[r][j].x, c1.x), sa.x); xv[r][j].y = badd2(bmul2(xv[r][j].y, c1.y), sa.y);
      xv[r][j].z = badd2(bmul2(xv[r][j].z, c1.z), sa.z); xv[r][j].w = badd2(bmul2(xv[r][j].w, c1.w), sa.w);
    }
  };
  auto store = [&](int j) {
    #pragma unroll
    for (int r = 0; r < 2; r++) *reinterpret_cast<uint4*>(g_h + (size_t)(bid * 16 + 2 * w8 + r) * T_D + j * 256 + lane * 8) = xv[r][j];
  };
  #pragma unroll 1
  for (int ph = 0; ph < 2; ph++) {
    if ((ph == 0) == early) {
      asm volatile("cp.async.wait_all;" ::: "memory");
      if (!early) mbar_wait(b_x + 168, 0);
      float acc[8];
      #pragma unroll
      for (int j = 0; j < 8; j++) acc[j] = 0.f;
      #pragma unroll
      for (int i = 0; i < 8; i++) fma8(acc, lds_f32(scr + ((t2 >> 3) + 32 * i) * 4), lds_u32x4(ws + i * 4096));
      #pragma unroll
      for (int j = 0; j < 4; j++) { const bool up = lane & 16; acc[j] = (up ? acc[4 + j] : acc[j]) + __shfl_xor_sync(0xffffffffu, up ? acc[j] : acc[4 + j], 16); }
      #pragma unroll
      for (int j = 0; j < 2; j++) { const bool up = lane & 8; acc[j] = (up ? acc[2 + j] : acc[j]) + __shfl_xor_sync(0xffffffffu, up ? acc[j] : acc[2 + j], 8); }
      sts_f32x2(scr + 1024 + w8 * 256 + (lane & 7) * 32 + (lane >> 3) * 8, acc[0], acc[1]);
      named_bar_sync(5, 256);
      if (t2 < 64) {
        float sum = 0.f;
        #pragma unroll
        for (int i = 0; i < 8; i++) sum += lds_f32(scr + 1024 + i * 256 + t2 * 4);
        st_tagged(g_modpart + ks * 2 * T_D + cb * 64 + t2, sum);
        TL_MARK2(early ? 2 : 6, t2 == 0);
      }
    } else {
      float2 pa[H_SPLIT][4];
      mbar_wait(b_x, 0);
      TL_MARK2(18, t2 == 0);
      load_parts<0, H_SPLIT>(pa, t2);
      #pragma unroll
      for (int r = 0; r < 2; r++)
        #pragma unroll
        for (int j = 0; j < 4; j++) xv[r][j] = lds_u32x4(xs + (2 * w8 + r) * 2048 + j * 512 + lane * 16);
  {
    float st[4] = {0.f, 0.f, 0.f, 0.f};
    #pragma unroll
    for (int r = 0; r < 2; r++)
      #pragma unroll
      for (int j = 0; j < 4; j++) {
        float v[8];
        unpack8(xv[r][j], v);
        st[2 * r] += ((v[0] + v[1]) + (v[2] + v[3])) + ((v[4] + v[5]) + (v[6] + v[7]));
        st[2 * r + 1] += fmaf(v[0], v[0], fmaf(v[1], v[1], fmaf(v[2], v[2], v[3] * v[3]))) + fmaf(v[4], v[4], fmaf(v[5], v[5], fmaf(v[6], v[6], v[7] * v[7])));
      }
    #pragma unroll
    for (int k = 0; k < 2; k++) { const bool up = lane & 16; st[k] = (up ? st[2 + k] : st[k]) + __shfl_xor_sync(0xffffffffu, up ? st[k] : st[2 + k], 16); }
    #pragma unroll
    for (int o = 8; o > 0; o >>= 1) { st[0] += __shfl_xor_sync(0xffffffffu, st[0], o); st[1] += __shfl_xor_sync(0xffffffffu, st[1], o); }
    const float mean = st[0] * (1.0f / T_D);
    const float inv = rcp_approx(rbf(sqrt_approx(rbf(rbf(fmaxf(fmaf(-mean, mean, st[1] * (1.0f / T_D)), 0.f)) + 1e-05f))));
    const uint32_t m = pack_bf16(mean, mean), h = pack_bf16(inv - rbf(inv), inv);
    #pragma unroll
    for (int r = 0; r < 2; r++) {
      mb2[r] = __shfl_sync(0xffffffffu, m, 16 * r);
      const uint32_t hr = __shfl_sync(0xffffffffu, h, 16 * r);
      ih[r] = __byte_perm(hr, hr, 0x3232); il[r] = __byte_perm(hr, hr, 0x1010);
    }
  }
      #pragma unroll
      for (int j = 0; j < H_SPLIT; j++) norm(j);
      TL_MARK2(5, t2 == 0);
      finish_parts<0, H_SPLIT>(pa, true, t2, scr + 8192);
      named_bar_sync(5, 256);
      TL_MARK2(7, t2 == 0);
      #pragma unroll
      for (int j = 0; j < H_SPLIT; j++) { modulate(j); store(j); }
      named_bar_arrive(9, 288);
    }
  }
  #pragma unroll
  for (int j = H_SPLIT; j < 4; j++) norm(j);
  float2 pb[4 - H_SPLIT][4];
  finish_parts<H_SPLIT, 4>(pb, false, t2, scr + 8192);
  named_bar_sync(5, 256);
  TL_MARK2(17, t2 == 0);
  #pragma unroll
  for (int j = H_SPLIT; j < 4; j++) modulate(j);
  __syncwarp();
  if (lane == 0) mbar_arrive(b_head + (xv[1][3].w & zero));
  mbar_wait(b_go, 0);
  #pragma unroll
  for (int j = H_SPLIT; j < 4; j++) store(j);
  named_bar_arrive(8, 288);
}

#define MOD_AT (b_empty + 8)
#define MOD_SPLIT 20
__device__ __forceinline__ void mod_rest(uint32_t bid, uint32_t scr, uint32_t b_go, int t, const bf16* __restrict__ cvec, const bf16* __restrict__ w_mod, const bf16* __restrict__ w_r) {
  const int lane = t & 31;
  #pragma unroll 1
  for (int i = t; i < T_D / 2; i += 64) {
    const uint32_t c2 = *reinterpret_cast<const uint32_t*>(cvec + 2 * i);
    sts_u32(scr + i * 4, pack_bf16(silu_bf(bflo(c2)), silu_bf(bfhi(c2))));
  }
  named_bar_sync(11, 64);
  const bf16* wp = w_mod + (size_t)(2 * (t >> 2)) * (6 * T_D) + 2 * T_D + bid * 32 + (t & 3) * 8;
  float acc[8];
  #pragma unroll
  for (int i = 0; i < 8; i++) acc[i] = 0.f;
  #pragma unroll 1
  for (int i = 0; i < 32; i += 2) {
    if (i == MOD_SPLIT) mbar_wait_long(b_go, 0);
    const uint4 w0 = ldg_nc_v4(wp), w1 = ldg_nc_v4(wp + 6 * T_D), w2 = ldg_nc_v4(wp + 32 * 6 * T_D), w3 = ldg_nc_v4(wp + 33 * 6 * T_D);
    wp += 64 * 6 * T_D;
    const uint32_t s0 = lds_u32(scr + (i * 16 + (t >> 2)) * 4), s1 = lds_u32(scr + (i * 16 + 16 + (t >> 2)) * 4);
    fma8(acc, bflo(s0), w0); fma8(acc, bfhi(s0), w1); fma8(acc, bflo(s1), w2); fma8(acc, bfhi(s1), w3);
  }
  #pragma unroll
  for (int j = 0; j < 4; j++) { const bool up = lane & 16; acc[j] = (up ? acc[4 + j] : acc[j]) + __shfl_xor_sync(0xffffffffu, up ? acc[j] : acc[4 + j], 16); }
  #pragma unroll
  for (int j = 0; j < 2; j++) { const bool up = lane & 8; acc[j] = (up ? acc[2 + j] : acc[j]) + __shfl_xor_sync(0xffffffffu, up ? acc[j] : acc[2 + j], 8); }
  { const bool up = lane & 4; acc[0] = (up ? acc[1] : acc[0]) + __shfl_xor_sync(0xffffffffu, up ? acc[0] : acc[1], 4); }
  if (t >= 32) sts_f32(scr + 2048 + lane * 4, acc[0]);
  named_bar_sync(11, 64);
  if (__shfl_sync(0xffffffffu, t, 0) < 32) {
    const int kind = bid >> 5;
    float v = rbf(acc[0] + lds_f32(scr + 2048 + lane * 4));
    const int col = (bid & 31) * 32 + (lane & 3) * 8 + (lane >> 2);
    uint8_t* dst = g_col + (col >> 7) * 1536;
    if (kind == 2) v = rbf(1.0f + v);
    float vw = v * __bfloat162float(w_r[col]);
    if (kind == 2) {
      const int c = col & 127, i = (c & ~15) + ((c >> 1) & 3) * 4 + ((c >> 3) & 1) * 2 + (c & 1);
      reinterpret_cast<bf16*>(dst)[i] = __float2bfloat16_rn(vw);
      reinterpret_cast<bf16*>(dst)[128 + i] = __float2bfloat16_rn(vw - rbf(vw));
    }
    reinterpret_cast<bf16*>(dst + 512 + (kind & 1) * 512 + (kind >> 1) * 256)[col & 127] = __float2bfloat16_rn(v);
    #pragma unroll
    for (int o = 16; o > 0; o >>= 1) vw += __shfl_xor_sync(0xffffffffu, vw, o);
    if (lane == 0 && (kind == 1 || kind == 2)) g_scal[95 - bid] = vw;
  }
  #pragma unroll 1
  for (int i = bid * 64 + t; i < (int)(sizeof(g_mail) / 16); i += 128 * 64) reinterpret_cast<uint4*>(&g_mail)[i] = make_uint4(0u, 0u, 0u, 0u);
  named_bar_sync(11, 64);
  if (t == 0) red_release_add(&g_hcnt[0], 1u);
}

constexpr int AT_NBLK = T_SEQ / 128;
constexpr float AT_HEAD = 7.0f;
#define WO_LATE 12
#define QP_STAG 3
#define AT_SPLIT 28
#define AT_PIN 16
#define PINB 4
constexpr int AT_NFULL = 124;
constexpr int AT_PREG = 40, AT_CREG = 232;
constexpr uint32_t AT_SQ = 5 * 32768;
constexpr float AT_C = 0.08838834764831845f * 1.4426950408889634f;
constexpr float AT_RAW_LO = -16.0f, AT_RAW_HI = 24.0f;
constexpr float AT_RAW_SUM = 281474976710656.0f, AT_RAW_MIN = 9.094947017729282e-13f;
constexpr uint32_t AT_SBAR = AT_SQ + 65536 + 256;
constexpr uint32_t AT_SMEM = AT_SQ + 65536 + 3072;

__device__ __forceinline__ uint32_t ring_slot(uint32_t t) { return t - 5u * ((t * 205u) >> 10); }
__device__ __forceinline__ uint32_t qp_pos(uint32_t j, uint32_t it) { return 4u * it + (j & 3u) + ((j & 3u) == 3u ? it : 0u); }
__device__ __forceinline__ uint32_t ring_par(uint32_t t) { return ((t * 205u) >> 10) & 1u; }
__device__ __forceinline__ void softmax_rowmax(const float (&s)[64], float& mx0, float& mx1) {
  float a0 = fmaxf(s[0], s[1]), a1 = fmaxf(s[4], s[5]), a2 = fmaxf(s[8], s[9]), a3 = fmaxf(s[12], s[13]);
  float b0 = fmaxf(s[2], s[3]), b1 = fmaxf(s[6], s[7]), b2 = fmaxf(s[10], s[11]), b3 = fmaxf(s[14], s[15]);
  #pragma unroll
  for (int j = 4; j < 16; j += 4) {
    a0 = fmaxf(a0, fmaxf(s[4 * j + 0], s[4 * j + 1]));  b0 = fmaxf(b0, fmaxf(s[4 * j + 2], s[4 * j + 3]));
    a1 = fmaxf(a1, fmaxf(s[4 * j + 4], s[4 * j + 5]));  b1 = fmaxf(b1, fmaxf(s[4 * j + 6], s[4 * j + 7]));
    a2 = fmaxf(a2, fmaxf(s[4 * j + 8], s[4 * j + 9]));  b2 = fmaxf(b2, fmaxf(s[4 * j + 10], s[4 * j + 11]));
    a3 = fmaxf(a3, fmaxf(s[4 * j + 12], s[4 * j + 13])); b3 = fmaxf(b3, fmaxf(s[4 * j + 14], s[4 * j + 15]));
  }
  mx0 = fmaxf(fmaxf(a0, a1), fmaxf(a2, a3));
  mx1 = fmaxf(fmaxf(b0, b1), fmaxf(b2, b3));
  mx0 = fmaxf(mx0, __shfl_xor_sync(0xffffffffu, mx0, 1));
  mx1 = fmaxf(mx1, __shfl_xor_sync(0xffffffffu, mx1, 1));
  mx0 = fmaxf(mx0, __shfl_xor_sync(0xffffffffu, mx0, 2));
  mx1 = fmaxf(mx1, __shfl_xor_sync(0xffffffffu, mx1, 2));
}
__device__ __forceinline__ void softmax_sub(float (&s)[64], float mc0, float mc1) {
  #pragma unroll
  for (int j = 0; j < 16; j++) { s[4 * j] -= mc0; s[4 * j + 1] -= mc0; s[4 * j + 2] -= mc1; s[4 * j + 3] -= mc1; }
}
template <int LO, int HI>
__device__ __forceinline__ void softmax_exp(float (&s)[64]) {
  #pragma unroll
  for (int i = LO; i < HI; i++) s[i] = ex2_approx(s[i]);
}
__device__ __forceinline__ bool softmax_mode(const float (&s)[64], float& mc0, float& mc1) {
  softmax_rowmax(s, mc0, mc1);
  const bool raw = __all_sync(0xffffffffu, mc0 >= AT_RAW_LO && mc0 <= AT_RAW_HI && mc1 >= AT_RAW_LO && mc1 <= AT_RAW_HI);
  mc0 += AT_HEAD; mc1 += AT_HEAD;
  return raw;
}
__device__ __forceinline__ void rowsum_p(const uint32_t (&p)[32], uint32_t& t0, uint32_t& t1) {
  uint32_t a[16];
  #pragma unroll
  for (int i = 0; i < 8; i++) { a[2 * i] = badd2(p[4 * i], p[4 * i + 2]); a[2 * i + 1] = badd2(p[4 * i + 1], p[4 * i + 3]); }
  #pragma unroll
  for (int i = 0; i < 4; i++) { a[2 * i] = badd2(a[4 * i], a[4 * i + 2]); a[2 * i + 1] = badd2(a[4 * i + 1], a[4 * i + 3]); }
  t0 = badd2(badd2(a[0], a[2]), badd2(a[4], a[6]));
  t1 = badd2(badd2(a[1], a[3]), badd2(a[5], a[7]));
}
__device__ __forceinline__ void add_rowsum(const uint32_t (&p)[32], float& l0, float& l1) {
  uint32_t t0, t1;
  rowsum_p(p, t0, t1);
  l0 += bflo(t0) + bfhi(t0); l1 += bflo(t1) + bfhi(t1);
}
__device__ __forceinline__ void pack_p(uint32_t (&p)[32], const float (&s)[64]) {
  #pragma unroll
  for (int i = 0; i < 32; i++) p[i] = pack_bf16(s[2 * i], s[2 * i + 1]);
}
__device__ __noinline__ void attn_rows_exact(uint32_t bid, uint32_t sq, uint32_t so, int hsel, const bf16* __restrict__ kh, const bf16* __restrict__ vh) {
  const int warp = (threadIdx.x >> 5) & 3, lane = threadIdx.x & 31;
  const size_t hofs = (size_t)((bid < 128 ? bid >> 4 : 15) * 2 + hsel) * T_SEQ * T_DH;
  kh += hofs; vh += hofs;
  #pragma unroll 1
  for (int r = 16 * warp; r < 16 * warp + 16; r++) {
    const uint32_t ad = (lane >> 4) * 16384 + r * 128 + ((((lane & 15) >> 1) ^ (r & 7)) << 4) + (lane & 1) * 8;
    uint2 qv; asm volatile("ld.shared.v2.u32 {%0, %1}, [%2];" : "=r"(qv.x), "=r"(qv.y) : "r"(sq + ad) : "memory");
    const float q0 = bflo(qv.x), q1 = bfhi(qv.x), q2 = bflo(qv.y), q3 = bfhi(qv.y);
    float m = -INFINITY, l = 0.f, o0 = 0.f, o1 = 0.f, o2 = 0.f, o3 = 0.f;
    #pragma unroll 1
    for (int key = 0; key < T_SEQ; key++) {
      const uint2 kv = *reinterpret_cast<const uint2*>(kh + (size_t)key * T_DH + lane * 4);
      const uint2 vv = *reinterpret_cast<const uint2*>(vh + (size_t)key * T_DH + lane * 4);
      float sc = (q0 * bflo(kv.x) + q1 * bfhi(kv.x)) + (q2 * bflo(kv.y) + q3 * bfhi(kv.y));
      #pragma unroll
      for (int o = 16; o > 0; o >>= 1) sc += __shfl_xor_sync(0xffffffffu, sc, o);
      const float mn = fmaxf(m, sc);
      const float al = (m == mn) ? 1.0f : ex2_approx(m - mn), p = rbf(ex2_approx(sc - mn));
      m = mn;
      l = fmaf(l, al, p);
      o0 = fmaf(o0, al, p * bflo(vv.x)); o1 = fmaf(o1, al, p * bfhi(vv.x));
      o2 = fmaf(o2, al, p * bflo(vv.y)); o3 = fmaf(o3, al, p * bfhi(vv.y));
    }
    const float inv = rcp_approx(l);
    asm volatile("st.shared.v2.u32 [%0], {%1, %2};" :: "r"(so + ad), "r"(pack_bf16(o0 * inv, o1 * inv)), "r"(pack_bf16(o2 * inv, o3 * inv)) : "memory");
  }
}
__device__ __forceinline__ void issue_qk(float (&s)[64], const uint32_t (&q)[32], uint32_t k_lo) {
  wgmma_fence();
  wgmma_m64n128k16_rs<0>(s, q[0], q[1], q[2], q[3], k_lo, 0);
  wgmma_m64n128k16_rs<2>(s, q[4], q[5], q[6], q[7], k_lo, 1);
  wgmma_m64n128k16_rs<4>(s, q[8], q[9], q[10], q[11], k_lo, 1);
  wgmma_m64n128k16_rs<6>(s, q[12], q[13], q[14], q[15], k_lo, 1);
  wgmma_m64n128k16_rs<1024>(s, q[16], q[17], q[18], q[19], k_lo, 1);
  wgmma_m64n128k16_rs<1026>(s, q[20], q[21], q[22], q[23], k_lo, 1);
  wgmma_m64n128k16_rs<1028>(s, q[24], q[25], q[26], q[27], k_lo, 1);
  wgmma_m64n128k16_rs<1030>(s, q[28], q[29], q[30], q[31], k_lo, 1);
  wgmma_commit();
}
__device__ __forceinline__ void issue_pv(float (&o)[64], const uint32_t (&p)[32], uint32_t v_lo, int accumulate) {
  wgmma_fence();
  wgmma_m64n128k16_rs_tb<0>(o, p[0], p[1], p[2], p[3], v_lo, accumulate);
  wgmma_m64n128k16_rs_tb<128>(o, p[4], p[5], p[6], p[7], v_lo, 1);
  wgmma_m64n128k16_rs_tb<256>(o, p[8], p[9], p[10], p[11], v_lo, 1);
  wgmma_m64n128k16_rs_tb<384>(o, p[12], p[13], p[14], p[15], v_lo, 1);
  wgmma_m64n128k16_rs_tb<512>(o, p[16], p[17], p[18], p[19], v_lo, 1);
  wgmma_m64n128k16_rs_tb<640>(o, p[20], p[21], p[22], p[23], v_lo, 1);
  wgmma_m64n128k16_rs_tb<768>(o, p[24], p[25], p[26], p[27], v_lo, 1);
  wgmma_m64n128k16_rs_tb<896>(o, p[28], p[29], p[30], p[31], v_lo, 1);
  wgmma_commit();
}
__device__ __forceinline__ void block_end(uint32_t zero, uint32_t bar) {
  #pragma unroll 1
  for (uint32_t i = 0; i < zero; i++) mbar_arrive(bar);
}
__device__ __forceinline__ void rescale_o(float (&o)[64], float al0, float al1) {
  #pragma unroll
  for (int j = 0; j < 16; j++) { o[4 * j] *= al0; o[4 * j + 1] *= al0; o[4 * j + 2] *= al1; o[4 * j + 3] *= al1; }
}

__device__ __forceinline__ void stage_o(const float (&o)[64], float i0, float i1, uint32_t dst, int lane) {
  #pragma unroll
  for (int J = 0; J < 16; J += 2)
    stmatrix_x4(dst + (J >> 3) * 16384 + ((((J & 7) + (lane >> 4)) ^ (lane & 7)) << 4),
                pack_bf16(o[4 * J + 0] * i0, o[4 * J + 1] * i0), pack_bf16(o[4 * J + 2] * i1, o[4 * J + 3] * i1),
                pack_bf16(o[4 * J + 4] * i0, o[4 * J + 5] * i0), pack_bf16(o[4 * J + 6] * i1, o[4 * J + 7] * i1));
}
__device__ __forceinline__ bool finish_l(float& l0, float& l1) {
  l0 += __shfl_xor_sync(0xffffffffu, l0, 1); l1 += __shfl_xor_sync(0xffffffffu, l1, 1);
  l0 += __shfl_xor_sync(0xffffffffu, l0, 2); l1 += __shfl_xor_sync(0xffffffffu, l1, 2);
  const bool redo = __any_sync(0xffffffffu, !(l0 <= AT_RAW_SUM && l1 <= AT_RAW_SUM && l0 >= AT_RAW_MIN && l1 >= AT_RAW_MIN));
  l0 = rcp_approx(l0); l1 = rcp_approx(l1);
  return redo;
}
template <int J0>
__device__ __forceinline__ void stage_q(const float (&acc)[128], float c, uint32_t dst, int lane) {
  #pragma unroll
  for (int J = J0; J < J0 + 16; J += 2)
    stmatrix_x4(dst + (J >> 3) * 16384 + ((((J & 7) + (lane >> 4)) ^ (lane & 7)) << 4),
                pack_bf16(acc[4 * J + 0] * c, acc[4 * J + 1] * c), pack_bf16(acc[4 * J + 2] * c, acc[4 * J + 3] * c),
                pack_bf16(acc[4 * J + 4] * c, acc[4 * J + 5] * c), pack_bf16(acc[4 * J + 6] * c, acc[4 * J + 7] * c));
}
__device__ __forceinline__ void store_o(const CUtensorMap* tmO, uint32_t src, int head, int row) {
  tma_store_2d(tmO, src, head * T_DH, row);
  tma_store_2d(tmO, src + 16384, head * T_DH + 64, row);
  bulk_commit();
}
__device__ __forceinline__ void mma_bf16(float (&d)[4], uint32_t a0, uint32_t a1, uint32_t a2, uint32_t a3, uint32_t b0, uint32_t b1) {
  asm volatile("mma.sync.aligned.m16n8k16.row.col.f32.bf16.bf16.f32 {%0, %1, %2, %3}, {%4, %5, %6, %7}, {%8, %9}, {%0, %1, %2, %3};"
               : "+f"(d[0]), "+f"(d[1]), "+f"(d[2]), "+f"(d[3]) : "r"(a0), "r"(a1), "r"(a2), "r"(a3), "r"(b0), "r"(b1));
}
struct GemvSel { uint32_t lo0, hi0, lo1, hi1; };
__device__ __forceinline__ GemvSel gemv_sel(int lane) {
  const uint32_t lo = (lane & 8) ? 0x1044u : 0x4410u, hi = (lane & 8) ? 0x3244u : 0x4432u;
  GemvSel s; s.lo0 = (lane & 16) ? 0x4444u : lo; s.hi0 = (lane & 16) ? 0x4444u : hi; s.lo1 = (lane & 16) ? lo : 0x4444u; s.hi1 = (lane & 16) ? hi : 0x4444u;
  return s;
}
#define GEMV_B0(j, h, s) __byte_perm((j) < 2 ? (h).x : (h).y, 0u, ((j) & 1) ? (s).hi0 : (s).lo0)
#define GEMV_B1(j, h, s) __byte_perm((j) < 2 ? (h).x : (h).y, 0u, ((j) & 1) ? (s).hi1 : (s).lo1)
__device__ __forceinline__ int gemv_col(int i) { return (i >> 4) * 8 + ((i >> 3) & 1) * 4 + (i & 2) + ((i >> 2) & 1); }
#define OG_XN 4
#define OG_XB 5
#define OG_NG 8
#define PUT_N 2
#define H_STAG 2
#define AL_P 60
#define AL_SLEEP 1200
#define AL_MAX 800
#define POLL_NS 500
#define OG_PROF 0xDDCCBA87u
#define RK_P 24
__host__ __device__ constexpr int og_pre(int tile) { return (OG_PROF >> ((tile >> 4) * 4)) & 15; }
constexpr int OG_PRE2 = og_pre(127), OG_HSUM = og_pre(0) + og_pre(16) + og_pre(32) + og_pre(48) + og_pre(64) + og_pre(80) + og_pre(96);
#define OG_JOBS 7
#define OG_GRP 6
#define LD_FIRST 2
#define LD_STAG (OG_GRP / 2)
constexpr int OG_ST = 5, OG_NKB = T_DQKV / 64 - og_pre(0), OG_MOE = T_F / 32;
__device__ __forceinline__ int pre_kb(int i) { return (i >> 1) * 4 + (i & 1); }
__device__ __forceinline__ int own_kb(int i, int pre) { return i < (pre & ~1) ? pre_kb(i) + 2 : i + pre; }
static_assert(LD_FIRST + LD_STAG <= OG_XB && OG_XB < LD_FIRST + OG_GRP, "the extra tile belongs to segment 1");
static_assert(og_pre(16) >= 16 / PUT_N && LD_FIRST + 7 * OG_GRP + LD_STAG + 3 <= 64 - OG_PRE2, "job / segment lengths");
constexpr int OG_POS = 8;
constexpr uint32_t OG_STAGE = 32768;
constexpr uint32_t OG_SCOL = AT_SBAR + 512;
constexpr uint32_t OG_SMISC = AT_SBAR + 2048;
constexpr uint32_t OG_SWD = AT_SQ, OG_PSLOT = AT_SQ;
constexpr uint32_t OG_XSLOT = AT_SQ + 32768;
constexpr uint32_t OG_OSLOT = 1 * OG_STAGE;
constexpr uint32_t OG_SRED = 3 * OG_STAGE;
constexpr uint32_t OG_SH2 = OG_SRED + 24576;
constexpr uint32_t OG_SSTAT = OG_SRED + 16384;
constexpr uint32_t OG_SGU = OG_SRED + 8192;
constexpr uint32_t OG_SFIN = OG_SGU + 256;
#define OGM 2
#define OG_MT(b) ((((b) >> OGM) & 15) ^ (((b) & 64) ? 15 : 0))
#define OG_NT(b) (((b) & ((1 << OGM) - 1)) + (((b) >> (4 + OGM)) << OGM))
__device__ __forceinline__ int tail_tile(uint32_t sbase) { mbar_wait_long(sbase + AT_SBAR + 336, 0); return (int)lds_u32(sbase + AT_SBAR + 408); }
#define TAIL_SETUP \
  const uint32_t bar_full = sbase + AT_SBAR, bar_empty = bar_full + 40; \
  const uint32_t bar_wd = bar_full + 168, bar_col = bar_full + 176, bar_out = bar_full + 184, bar_end = bar_full + 192; \
  const uint32_t bar_key = bar_full + 200, bar_h2 = bar_full + 208, bar_sel = bar_full + 216; \
  const int mt = OG_MT(tb), nt = OG_NT(tb); \
  const int m0 = mt * 128, n0 = nt * 128; \
  const bool has_moe = (int)bid < OG_MOE; \
  (void)bar_empty; (void)bar_wd; (void)bar_col; (void)bar_out; (void)bar_end; (void)bar_key; (void)bar_h2; (void)bar_sel; (void)m0; (void)n0; (void)has_moe;

__device__ __forceinline__ void tail_producer(uint32_t bid, uint32_t sbase, uint32_t ph, uint64_t pol, const CUtensorMap* tmA, const CUtensorMap* tmB, const CUtensorMap* tmD) {
  const int tb = tail_tile(sbase);
  TAIL_SETUP
  uint32_t stage = OG_POS % OG_ST;
  int kb = 0, xk = OG_XB;
  uint32_t xp = 1;
  #pragma unroll 1
  for (int seg = 0; seg < 2; seg++) {
    mbar_wait(bar_full + 264 + 80 * seg, 0);
    fence_proxy_async_global();
    const int end = 32 + 32 * seg - og_pre(tb);
    #pragma unroll 1
    for (; kb < end; kb++) {
      const bool xb = kb == xk;
      const uint32_t fb = xb ? bar_full + 360 : bar_full + 8 * stage, sa = sbase + (xb ? 5 : stage) * OG_STAGE;
      const int k0 = own_kb(kb, og_pre(tb)) * 64;
      if (xb) {
        mbar_wait(bar_full + 80, bid < AT_NFULL);
        mbar_wait(bar_full + 368, xp);
        xp ^= 1;
        if (xk < OG_XB + (OG_XN - 1) * OG_GRP) xk += OG_GRP;
      }
      mbar_wait_long(xb ? bar_full + 304 : bar_empty + 8 * stage, xb ? 0 : ph);
      mbar_expect_tx(fb, OG_STAGE);
      tma_load_3d_hint(sa + 16384, tmB, k0, 2 * nt, fb, pol);
      tma_load_2d_hint(sa, tmA, k0, m0, fb, pol);
      if (!xb && ++stage == OG_ST) { stage = 0; ph ^= 1; }
    }
  }
  if (has_moe) {
    stage += stage & 1;
    mbar_wait(bar_empty + 8 * stage, ph);
    mbar_expect_tx(bar_wd, OG_STAGE);
    tma_load_3d_hint(sbase + stage * OG_STAGE, tmD, bid * 32, 8, bar_wd, pol);
  }
}

__device__ __forceinline__ uint32_t out2(uint32_t x1, uint32_t mb2, uint32_t ih, uint32_t il, uint32_t c1, uint32_t sb, uint32_t gb) {
  const uint32_t h2 = badd2(bmul2(ln_norm2b(x1, mb2, ih, il), c1), sb);
  return badd2(x1, bmul2(gb, bfma2(h2, 0u, h2)));
}
#define X_PACE 200
#define Y_SLACK 96
#define OG_STAG 3
#define POLL_NS2 100
#define WD_SKIP 1
#define AL_ADD 380
#define WD_PACE 300
__device__ __forceinline__ void tail_exchange(uint32_t bid, uint32_t sbase, const bf16* __restrict__ w_down, const bf16* __restrict__ w_r, const bf16* __restrict__ x, bf16* __restrict__ out) {
    const int lane = threadIdx.x & 31, wi = __shfl_sync(0xffffffffu, threadIdx.x >> 5, 0);
    if (wi == 3) {
      uint32_t a = bid, b = 0u;
      if (bid < AT_NFULL) mbar_wait_long(sbase + AT_SBAR + 312, 0);
      if (bid < OG_MOE) {
        asm volatile("mov.u32 %0, %%globaltimer_lo;" : "=r"(a));
        if (lane == 0 && (bid & 15) == 0) asm volatile("st.relaxed.gpu.global.u32 [%0], %1;" :: "l"(g_hcnt + 8 + (bid >> 4)), "r"((a & ~15u) | 8u | (bid >> 4)) : "memory");
        #pragma unroll 1
        for (unsigned int spin = 0; spin < (1u << 22) && __any_sync(0xffffffffu, b == 0u); spin++) {
          __nanosleep(200);
          asm volatile("ld.relaxed.gpu.global.u32 %0, [%1];" : "=r"(b) : "l"(g_hcnt + 8 + min(lane, 6)) : "memory");
        }
        a = __popc(__ballot_sync(0xffffffffu, b < __shfl_sync(0xffffffffu, b, bid >> 4)) & 127u) * 16 + (bid & 15);
      }
      if (lane == 0) {
        sts_u32(sbase + AT_SBAR + 408, a);
        mbar_arrive(sbase + AT_SBAR + 336);
        b = 0u;
        if (bid < AT_NFULL) {
          unsigned int* tm = g_hcnt + 32 * (1 + (bid >> 4)) + 8;
          mbar_wait_long(sbase + AT_SBAR + 312, 1);
          asm volatile("mov.u32 %0, %%globaltimer_lo;" : "=r"(a));
          asm volatile("red.relaxed.gpu.global.max.u32 [%0], %1;" :: "l"(tm), "r"(a) : "memory");
          __nanosleep(AL_SLEEP);
          asm volatile("ld.relaxed.gpu.global.u32 %0, [%1];" : "=r"(b) : "l"(tm) : "memory");
          b -= a;
        }
        sts_u32(sbase + AT_SBAR + 412, b < AL_MAX ? b * 13 / 8 : 0u);
        mbar_arrive(sbase + AT_SBAR + 320);
      }
      named_bar_sync(15, 32);
    }
    const int tb = __shfl_sync(0xffffffffu, tail_tile(sbase), 0);
    TAIL_SETUP
    if (wi == 3) {
      mbar_wait_long(bar_full + 344, 0);
      float a = g_scal[lane], b = g_scal[32 + lane];
      #pragma unroll
      for (int i = 0; i < 3; i++) {
        const uint4 v = *reinterpret_cast<const uint4*>(g_col + nt * 1536 + i * 512 + lane * 16);
        sts_u32x4(sbase + OG_SCOL + i * 512 + lane * 16, v.x, v.y, v.z, v.w);
      }
      #pragma unroll
      for (int o = 16; o > 0; o >>= 1) { a += __shfl_xor_sync(0xffffffffu, a, o); b += __shfl_xor_sync(0xffffffffu, b, o); }
      if (lane == 0) sts_f32x2(sbase + OG_SMISC, a, b);
      const uint64_t pol = policy_evict_first();
      #pragma unroll 1
      for (int r = lane >> 4; r < 128; r += 4) {
        __nanosleep(X_PACE);
        #pragma unroll
        for (int j = 0; j < 4; j += 2)
          asm volatile("cp.async.cg.shared.global.L2::cache_hint [%0], [%1], 16, %2;" :: "r"(sbase + OG_XSLOT + (lane & 8) * 2048 + (r + j) * 128 + (((lane ^ (r + j)) & 7) << 4)),
                       "l"(x + (size_t)(m0 + r + j) * T_D + n0 + (lane & 15) * 8), "l"(pol) : "memory");
      }
      asm volatile("cp.async.wait_all;" ::: "memory");
      __syncwarp();
      if (lane == 0) mbar_arrive(bar_col);
    } else if (wi == 2) {
      if (elect_one()) {
        mbar_wait_long(bar_full + (has_moe ? 80 : 376), has_moe);
        #pragma unroll 1
        for (unsigned int i = 0; i < (1u << 20) && ld_acquire(&g_hcnt[32 * (1 + (tb >> 3)) + 4 + ((tb >> 1) & 3)]) == 0u; i++) __nanosleep((tb >> 4) == 6 ? POLL_NS2 : POLL_NS);
        TL_MARK2(23, true);
        fence_proxy_async_global();
        TL_MARK2(4, true);
        mbar_expect_tx(bar_full + 272, 32768);
        bulk_load_hint(sbase + OG_PSLOT, g_pre + tb * 2048, 32768, bar_full + 272, policy_evict_first());
      }
      named_bar_sync(14, 32);
      if (has_moe) {
        mbar_wait_long(bar_full + 376, 0);
        const uint64_t pol = policy_evict_first();
        #pragma unroll 1
        for (int r = 0; r < 32; r++) {
          if ((r & WD_SKIP) != WD_SKIP) __nanosleep(WD_PACE);
          #pragma unroll
          for (int j = 0; j < 2; j++)
            asm volatile("cp.async.cg.shared.global.L2::cache_hint [%0], [%1], 16, %2;" :: "r"(sbase + OG_SWD + (4 * j + (lane >> 3)) * 4096 + r * 128 + (((lane ^ r) & 7) << 4)),
                         "l"((const uint8_t*)w_down + (size_t)bid * 65536 + r * 2048 + j * 512 + lane * 16), "l"(pol) : "memory");
        }
        asm volatile("cp.async.wait_all;" ::: "memory");
        __syncwarp();
        if (lane == 0) mbar_arrive(bar_wd);
      }
    }
    const uint4 wrv = ldg_nc_v4(w_r + threadIdx.x * 8);
    mbar_wait_long(bar_end, 0);
    TL_MARK2(22, lane == 0);
    if (wi == 0) {
      uint32_t k1 = 0u, k2 = 0u;
      #pragma unroll 1
      for (unsigned int spin = 0; spin < (1u << 22) && __any_sync(0xffffffffu, k1 == 0u); spin++) asm volatile("ld.relaxed.gpu.global.u32 %0, [%1];" : "=r"(k1) : "l"(g_key + lane) : "memory");
      TL_MARK2(28, lane == 0);
      warp_top2(k1, k2);
      if (lane == 0) {
        const uint32_t r1 = 0xffffu - (k1 & 0xffffu), r2 = 0xffffu - (k2 & 0xffffu);
        sts_u32x4(sbase + OG_SMISC + 64, r1, r2, (r1 >> 7) * 2, (r2 >> 7) * 2 + ((r1 >> 7) == (r2 >> 7)));
        mbar_arrive(bar_sel);
      }
    } else if (wi < 3) {
          mbar_wait(bar_key, 0);
          const uint4 kk = lds_u32x4(sbase + OG_SSTAT + 1024 + lane * 16);
          uint32_t k1 = max(kk.x, kk.y), k2 = min(kk.x, kk.y);
          k2 = max(max(k2, min(kk.z, kk.w)), min(k1, max(kk.z, kk.w))); k1 = max(k1, max(kk.z, kk.w));
          warp_top2(k1, k2);
          if (wi == 1) {
            if (lane == 0) {
              if (nt == (mt & 7)) st_relaxed2(g_key + mt * 2, k1, k2);
              sts_u32x2(sbase + OG_SMISC + 96, (~k1 >> 4) & 7u, (~k2 >> 4) & 7u);
              mbar_arrive(bar_full + 352);
            }
            TL_MARK2(27, lane == 0);
          } else {
            const uint32_t r = (~((lane & 16) ? k2 : k1)) & 127u, ch = lane & 15;
            const uint2 st = lds_u32x2(sbase + OG_SSTAT + r * 8);
            const uint4 xc = lds_u32x4(sbase + OG_XSLOT + (ch >> 3) * 16384 + r * 128 + (((ch ^ r) & 7) << 4));
            const uint4 c1 = lds_u32x4(sbase + OG_SCOL + 768 + ch * 16), sh = lds_u32x4(sbase + OG_SCOL + 1024 + ch * 16);
            const float inr = __uint_as_float(st.y);
            float* dst = reinterpret_cast<float*>(g_cand + (mt * 2 + (lane >> 4)) * 256 + nt * 16 + ch);
            st_tagged4(dst + 512, __uint_as_float(ln_mod2(xc.x, st.x, inr, c1.x, sh.x)), __uint_as_float(ln_mod2(xc.y, st.x, inr, c1.y, sh.y)),
                       __uint_as_float(ln_mod2(xc.z, st.x, inr, c1.z, sh.z)), __uint_as_float(ln_mod2(xc.w, st.x, inr, c1.w, sh.w)));
            st_tagged4(dst, __uint_as_float(xc.x), __uint_as_float(xc.y), __uint_as_float(xc.z), __uint_as_float(xc.w));
          }
    }
    mbar_wait(bar_sel, 0);
    const uint4 sel = lds_u32x4(sbase + OG_SMISC + 64);
    const int sel0 = (int)sel.x, sel1 = (int)sel.y;
    {
      const float* src0 = reinterpret_cast<const float*>(g_cand + sel.z * 256 + 128 + threadIdx.x);
      const float* src1 = reinterpret_cast<const float*>(g_cand + sel.w * 256 + 128 + threadIdx.x);
      float4 h0, h1;
      #pragma unroll 1
      for (unsigned int spin = 0; spin < (1u << 20); spin++) { h0 = ld_tagged4(src0); h1 = ld_tagged4(src1); if (__all_sync(0xffffffffu, tagged4(h0) & tagged4(h1))) break; }
      sts_f32x4(sbase + OG_SH2 + threadIdx.x * 16, h0.x, h0.y, h0.z, h0.w);
      sts_f32x4(sbase + OG_SH2 + 2048 + threadIdx.x * 16, h1.x, h1.y, h1.z, h1.w);
      __syncwarp();
      if (lane == 0) mbar_arrive(bar_h2);
      TL_MARK2(12, lane == 0);
      float v[8], u[8], wr[8];
      unpack8(make_uint4(__float_as_uint(h0.x), __float_as_uint(h0.y), __float_as_uint(h0.z), __float_as_uint(h0.w)), v);
      unpack8(make_uint4(__float_as_uint(h1.x), __float_as_uint(h1.y), __float_as_uint(h1.z), __float_as_uint(h1.w)), u);
      unpack8(wrv, wr);
      float r0 = 0.f, r1 = 0.f;
      #pragma unroll
      for (int i = 0; i < 8; i++) { r0 = fmaf(v[i], wr[i], r0); r1 = fmaf(u[i], wr[i], r1); }
      r0 = ((lane & 16) ? r1 : r0) + __shfl_xor_sync(0xffffffffu, (lane & 16) ? r0 : r1, 16);
      #pragma unroll
      for (int o = 8; o > 0; o >>= 1) r0 += __shfl_xor_sync(0xffffffffu, r0, o);
      if ((lane & 15) == 0) sts_f32(sbase + OG_SMISC + 192 + lane + wi * 4, r0);
    }
    mbar_wait(bar_out, 0);
    {
      const uint2 cg = lds_u32x2(sbase + OG_SMISC + 96);
      #pragma unroll
      for (int i = 0; i < 4; i++) {
        const int r = (i < 2 ? cg.x : cg.y) * 16 + (i & 1) * 8 + (threadIdx.x >> 4), ch = threadIdx.x & 15;
        if (m0 + r != sel0 && m0 + r != sel1)
          *reinterpret_cast<uint4*>(out + (size_t)(m0 + r) * T_D + n0 + ch * 8) =
              lds_u32x4(sbase + OG_OSLOT + (ch >> 3) * 16384 + r * 128 + (((ch & 7) ^ (r & 7)) << 4));
      }
    }
    if (bid == 0 && threadIdx.x < 68) *reinterpret_cast<uint4*>(g_hcnt + 32 * (threadIdx.x >> 2) + 4 * (threadIdx.x & 3)) = make_uint4(0u, 0u, 0u, 0u);
    if (threadIdx.x < 64) g_modpart[bid * 64 + threadIdx.x] = 0.f;
    {
      const int tk = threadIdx.x & 1, col = bid * 8 + gemv_col(threadIdx.x & 15);
      const uint32_t gb2 = *reinterpret_cast<const uint32_t*>(g_col + (col >> 7) * 1536 + 512 + 768 + (col & 126) * 2);
      const uint32_t* xp = reinterpret_cast<const uint32_t*>(g_cand + (tk ? sel.w : sel.z) * 256) + (col >> 1);
      uint32_t x2 = 0u;
      #pragma unroll 1
      for (unsigned int spin = 0; spin < (1u << 20) && __any_sync(0xffffffffu, x2 == 0u); spin++) asm volatile("ld.relaxed.gpu.global.u32 %0, [%1];" : "=r"(x2) : "l"(xp) : "memory");
      const float* src = g_ypart + (size_t)(threadIdx.x >> 2) * 2 * T_D + bid * 16 + (threadIdx.x & 3) * 4;
      const bool four = threadIdx.x < (OG_MOE - 96) * 4;
      named_bar_sync(10, 128);
      const uint4 rp = lds_u32x4(sbase + OG_SMISC + 192 + tk * 16);
      const float rs = rbf(sigmoid_f(rbf((__uint_as_float(rp.x) + __uint_as_float(rp.y)) + (__uint_as_float(rp.z) + __uint_as_float(rp.w)))));
      const uint32_t h2p = lds_u32(sbase + OG_SH2 + tk * 2048 + (col & ~1) * 2);
      const float fh = (col & 1) ? bfhi(h2p) : bflo(h2p), fz = rbf(fh * 0.0f), fx = (col & 1) ? bfhi(x2) : bflo(x2), fg = (col & 1) ? bfhi(gb2) : bflo(gb2);
      bf16* dst = out + (size_t)(tk ? sel1 : sel0) * T_D + col;
      if (threadIdx.x == 0) hint_wait(CNT_Y, (uint32_t)(OG_MOE - Y_SLACK));
      named_bar_sync(10, 128);
      float4 p0, p1, p2, p3;
      #pragma unroll 1
      for (unsigned int spin = 0; spin < (1u << 20); spin++) {
        p0 = ld_tagged4(src); p1 = ld_tagged4(src + 64 * T_D); p2 = ld_tagged4(src + 128 * T_D); p3 = ld_tagged4(four ? src + 192 * T_D : src);
        if (__all_sync(0xffffffffu, tagged4(p0) & tagged4(p1) & tagged4(p2) & tagged4(p3))) break;
      }
      if (four) { p2.x += p3.x; p2.y += p3.y; p2.z += p3.z; p2.w += p3.w; }
      p0.x = (p0.x + p1.x) + p2.x; p0.y = (p0.y + p1.y) + p2.y; p0.z = (p0.z + p1.z) + p2.z; p0.w = (p0.w + p1.w) + p2.w;
      #pragma unroll
      for (int o = 4; o <= 16; o <<= 1) {
        p0.x += __shfl_xor_sync(0xffffffffu, p0.x, o); p0.y += __shfl_xor_sync(0xffffffffu, p0.y, o);
        p0.z += __shfl_xor_sync(0xffffffffu, p0.z, o); p0.w += __shfl_xor_sync(0xffffffffu, p0.w, o);
      }
      if (lane < 4) sts_f32x4(sbase + OG_SFIN + (threadIdx.x >> 5) * 64 + lane * 16, p0.x, p0.y, p0.z, p0.w);
      named_bar_sync(10, 128);
      TL_MARK2(21, threadIdx.x == 0);
      if (threadIdx.x < 16) {
        const uint32_t ya = sbase + OG_SFIN + threadIdx.x * 4;
        float y = (lds_f32(ya) + lds_f32(ya + 64)) + (lds_f32(ya + 128) + lds_f32(ya + 192));
        y = rbf(y);
        y = rbf(y * rs);
        *dst = __float2bfloat16_rn(fx + rbf(fg * rbf(fh + rbf(fz + y))));
      }
    }
    if (threadIdx.x == 0) XT(11);
    TL_END(4, threadIdx.x == 0);
}

__device__ __forceinline__ void load_pre(uint4* pre, uint32_t sbase, uint32_t buf, int t2) {
  mbar_wait(sbase + AT_SBAR + 272, 0);
  #pragma unroll
  for (int i = 0; i < 8; i++) pre[i] = lds_u32x4(sbase + buf + i * 4096 + t2 * 16);
}
__device__ __forceinline__ void tail_consumer(uint32_t bid, uint32_t sbase, const CUtensorMap* tmOut, const uint4 (&pre)[8], int cwg, const bf16* __restrict__ w_gate, const bf16* __restrict__ w_up) {
    const uint32_t c0 = clock_lo();
    if ((threadIdx.x & 31) == 0) mbar_arrive(sbase + AT_SBAR + 304);
    mbar_wait(sbase + AT_SBAR + 320, 0);
    const uint2 td = lds_u32x2(sbase + AT_SBAR + 408);
    const int tb = __shfl_sync(0xffffffffu, (int)td.x, 0);
    TAIL_SETUP
    const int tid = threadIdx.x & 127, t2 = threadIdx.x - 128;
    const int warp = tid >> 5, lane = tid & 31, w8 = t2 >> 5;
    const uint32_t dbase = (sbase & 0x3FFFFu) >> 4;
    const uint32_t a_base = dbase + ((cwg * 8192) >> 4) + (1u << 16);
    const uint32_t b_base = dbase + (16384 >> 4) + (512u << 16);
    TL_MARK2(25, threadIdx.x == 128);
    const uint64_t pol = policy_evict_first();
    const bf16* pw = ((lane & 16) ? w_up : w_gate) + (size_t)(w8 * 128 + (lane & 3) * 4) * T_F + (has_moe ? bid : 0) * 32 + ((lane >> 2) & 3) * 8;
    uint4 wv[32];
    float acc[64];
    #pragma unroll
    for (int i = 0; i < 8; i++) {
      acc[8 * i] = bflo(pre[i].x); acc[8 * i + 1] = bfhi(pre[i].x); acc[8 * i + 2] = bflo(pre[i].y); acc[8 * i + 3] = bfhi(pre[i].y);
      acc[8 * i + 4] = bflo(pre[i].z); acc[8 * i + 5] = bfhi(pre[i].z); acc[8 * i + 6] = bflo(pre[i].w); acc[8 * i + 7] = bfhi(pre[i].w);
    }
    while (__any_sync(0xffffffffu, clock_lo() - c0 < td.y + AL_ADD)) {}
    uint32_t stage = OG_POS % OG_ST;
    {
      uint32_t phase = (OG_POS / OG_ST) & 1, prev = 12;
      int kb = 0;
      #pragma unroll
      for (int g = 0; g <= OG_NG; g++) {
        const int end = g == OG_NG ? 64 - og_pre(tb) : LD_FIRST + g * OG_GRP + LD_STAG * cwg;
        #pragma unroll 1
        do {
          const bool xb = g >= 1 && g <= OG_XN && kb == OG_XB + (g - 1) * OG_GRP;
          mbar_wait(xb ? bar_full + 360 : bar_full + 8 * stage, xb ? (g - 1) & 1 : phase);
          if (OG_STAG > 0 && g == OG_NG && cwg == 1 && kb == end - OG_STAG) named_bar_sync(7, 256);
          const uint32_t a_lo = a_base + (xb ? 5 : stage) * (OG_STAGE >> 4), b_lo = b_base + (xb ? 5 : stage) * (OG_STAGE >> 4);
          wgmma_fence();
          wgmma_m64n128k16_ss_tb<0, 0>(acc, a_lo, b_lo, 1);
          wgmma_m64n128k16_ss_tb<2, 128>(acc, a_lo, b_lo, 1);
          wgmma_m64n128k16_ss_tb<4, 256>(acc, a_lo, b_lo, 1);
          wgmma_m64n128k16_ss_tb<6, 384>(acc, a_lo, b_lo, 1);
          wgmma_commit();
          if (OG_STAG > 0 && g == OG_NG && cwg == 0 && kb == end - 1) named_bar_arrive(7, 256);
          wgmma_wait<1>();
          if (tid == 0) mbar_arrive(bar_empty + 8 * prev);
          prev = xb ? 41 + (g == OG_XN) : stage;
          if (!xb && ++stage == OG_ST) { stage = 0; phase ^= 1; }
        } while (++kb < end);
        #pragma unroll
        for (int j = 4 * g; j < 4 * g + 4 && j < 32; j++) wv[j] = ldg_stream_v4(pw + (size_t)(16 * (j >> 2) + (j & 3)) * T_F, pol);
      }
    }
    mbar_wait(bar_col, 0);
    if (__builtin_expect(!has_moe, 0)) {
      load_pre(wv, sbase, AT_SQ, t2);
    }
    wgmma_wait<0>();
    fence_regs(acc);
    if (__builtin_expect(!has_moe, 0)) {
      #pragma unroll
      for (int i = 0; i < 8; i++) {
        acc[8 * i] += bflo(wv[i].x); acc[8 * i + 1] += bfhi(wv[i].x); acc[8 * i + 2] += bflo(wv[i].y); acc[8 * i + 3] += bfhi(wv[i].y);
        acc[8 * i + 4] += bflo(wv[i].z); acc[8 * i + 5] += bfhi(wv[i].z); acc[8 * i + 6] += bflo(wv[i].w); acc[8 * i + 7] += bfhi(wv[i].w);
      }
    }
    if (tid == 0) mbar_arrive(bar_end);
    TL_MARK2(9, lane == 0);
    const int q2 = 2 * (lane & 3);
    const uint32_t frag = (64 * cwg + 16 * warp + (lane & 7) + 8 * ((lane >> 3) & 1)) * 128;
    const int fsw = lane & 7, fhi = lane >> 4;
    {
      float dl[4] = {0.f, 0.f, 0.f, 0.f}, da[4] = {0.f, 0.f, 0.f, 0.f}, db[4] = {0.f, 0.f, 0.f, 0.f};
      const uint32_t tb2 = sbase + OG_SCOL + (lane & 8) * 32 + (lane & 3) * 8, g = lane >> 2;
      const uint32_t msk = (g == 1 || g == 2) ? 0xffffffffu : 0u, one = g == 0 ? 0x3F803F80u : 0u;
      uint32_t xr[8][4];
      #pragma unroll
      for (int hf = 0; hf < 2; hf++) {
        uint32_t ga[8];
        uint2 cw[4];
        #pragma unroll
        for (int i = 0; i < 4; i++) {
          ldmatrix_x4(sbase + OG_XSLOT + hf * 16384 + frag + (((2 * i + fhi) ^ fsw) << 4), xr[4 * hf + i][0], xr[4 * hf + i][1], xr[4 * hf + i][2], xr[4 * hf + i][3]);
          ga[2 * i] = lds_u32(sbase + OG_SCOL + 512 + (64 * hf + 16 * i + q2) * 2); ga[2 * i + 1] = lds_u32(sbase + OG_SCOL + 512 + (64 * hf + 16 * i + 8 + q2) * 2);
          cw[i] = lds_u32x2(tb2 + (8 * hf + 2 * i) * 16);
        }
        #pragma unroll
        for (int i = 0; i < 4; i++) {
          uint32_t* x4 = xr[4 * hf + i];
          #pragma unroll
          for (int e = 0; e < 4; e++) x4[e] = badd2(x4[e], bmul2(ga[2 * i + (e >> 1)], pack_bf16(acc[32 * hf + 8 * i + 2 * e], acc[32 * hf + 8 * i + 2 * e + 1])));
          mma_bf16(dl, x4[0], x4[1], x4[2], x4[3], (cw[i].x & msk) | one, (cw[i].y & msk) | one);
          mma_bf16(da, x4[0], x4[1], x4[2], x4[3], x4[0], x4[2]);
          mma_bf16(db, x4[0], x4[1], x4[2], x4[3], x4[1], x4[3]);
        }
      }
      {
        const int dsrc = (lane & ~3) + (g >> 1);
        const float qa = __shfl_sync(0xffffffffu, (g & 1) ? da[1] : da[0], dsrc), qb = __shfl_sync(0xffffffffu, (g & 1) ? db[3] : db[2], dsrc);
        const float e0 = __shfl_xor_sync(0xffffffffu, (lane & 1) ? dl[0] : dl[2], 1), e1 = __shfl_xor_sync(0xffffffffu, dl[3], 1);
        if ((lane & 3) < 2) {
          const bool hi = lane & 1;
          st_tagged4(reinterpret_cast<float*>(g_part1 + ((mt * 8 + w8) * 8 + nt) * 16 + g + (hi ? 8 : 0)),
                     hi ? e0 : dl[0], hi ? qb : qa, hi ? e1 + dl[2] : dl[1] + e0, 1.0f);
        }
      }
      #pragma unroll
      for (int i = 0; i < 8; i++) stmatrix_x4(sbase + OG_XSLOT + (i >> 2) * 16384 + frag + (((2 * (i & 3) + fhi) ^ fsw) << 4), xr[i][0], xr[i][1], xr[i][2], xr[i][3]);
    }
    TL_MARK2(10, lane == 0);
    uint4 wd[16];
    if (has_moe) mbar_wait(bar_wd, 0);
    #pragma unroll
    for (int i = 0; i < 16; i++) wd[i] = lds_u32x4(sbase + (cwg ? (stage + (stage & 1)) * OG_STAGE : OG_SWD) + warp * 8192 + (i >> 3) * 4096 + (i & 6) * 512 + (i & 1) * 128 + (lane & 3) * 256 + (((lane >> 2) ^ (2 * (lane & 3) + (i & 1))) << 4));
    {
      const float* src = reinterpret_cast<const float*>(g_part1 + ((mt * 8 + w8) * 8 + (lane & 1) * 4) * 16 + (lane >> 1));
      float4 v, v1, v2, v3;
      #pragma unroll 1
      for (unsigned int spin = 0; spin < (1u << 22); spin++) {
        v = ld_tagged4(src); v1 = ld_tagged4(src + 64); v2 = ld_tagged4(src + 128); v3 = ld_tagged4(src + 192);
        if (__all_sync(0xffffffffu, tagged4(v) & tagged4(v1) & tagged4(v2) & tagged4(v3))) break;
      }
      __syncwarp();
      TL_MARK2(26, lane == 0);
      v.x = (v.x + v1.x) + (v2.x + v3.x); v.y = (v.y + v1.y) + (v2.y + v3.y); v.z = (v.z + v1.z) + (v2.z + v3.z);
      v.x += __shfl_xor_sync(0xffffffffu, v.x, 1); v.y += __shfl_xor_sync(0xffffffffu, v.y, 1); v.z += __shfl_xor_sync(0xffffffffu, v.z, 1);
      const float mean = v.x * (1.0f / T_D);
      const float var = fmaxf(fmaf(-mean, mean, v.y * (1.0f / T_D)), 0.f);
      const uint32_t mb2 = pack_bf16(mean, mean);
      const float inv = rcp_approx(rbf(sqrt_approx(rbf(rbf(var) + 1e-05f))));
      {
        const float2 sc = lds_f32x2(sbase + OG_SMISC);
        const uint32_t key = rank_key(rbf(fmaf(fmaf(-bflo(mb2), sc.x, v.z), inv, sc.y)), m0 + 16 * w8 + (lane >> 1));
        mbar_wait(bar_end, 0);
        if (lane & 1) sts_u32(sbase + OG_SSTAT + 1024 + (16 * w8 + (lane >> 1)) * 4, key);
        else sts_u32x2(sbase + OG_SSTAT + (16 * w8 + (lane >> 1)) * 8, mb2, __float_as_uint(inv));
        __syncwarp();
        if (lane == 0) mbar_arrive(bar_key);
      }
      const uint32_t ih = pack_bf16(inv, inv), il = pack_bf16(inv - bflo(ih), inv - bflo(ih));
      const uint32_t mba = __shfl_sync(0xffffffffu, mb2, 2 * (lane >> 2)), mbb = __shfl_sync(0xffffffffu, mb2, 2 * (lane >> 2) + 16);
      const uint32_t iha = __shfl_sync(0xffffffffu, ih, 2 * (lane >> 2)), ihb = __shfl_sync(0xffffffffu, ih, 2 * (lane >> 2) + 16);
      const uint32_t ila = __shfl_sync(0xffffffffu, il, 2 * (lane >> 2)), ilb = __shfl_sync(0xffffffffu, il, 2 * (lane >> 2) + 16);
      #pragma unroll 1
      for (int J0 = 0; J0 < 16; J0 += 4) {
        uint32_t xr[2][4], cv[4][3];
        #pragma unroll
        for (int i = 0; i < 2; i++) {
          ldmatrix_x4(sbase + OG_XSLOT + (J0 >> 3) * 16384 + frag + ((((J0 & 7) + 2 * i + fhi) ^ fsw) << 4), xr[i][0], xr[i][1], xr[i][2], xr[i][3]);
          #pragma unroll
          for (int h = 0; h < 2; h++)
            #pragma unroll
            for (int k = 0; k < 3; k++) cv[2 * i + h][k] = lds_u32(sbase + OG_SCOL + 768 + 256 * k + (8 * (J0 + 2 * i + h) + q2) * 2);
        }
        #pragma unroll
        for (int i = 0; i < 2; i++) {
          #pragma unroll
          for (int h = 0; h < 2; h++) {
            xr[i][2 * h] = out2(xr[i][2 * h], mba, iha, ila, cv[2 * i + h][0], cv[2 * i + h][1], cv[2 * i + h][2]);
            xr[i][2 * h + 1] = out2(xr[i][2 * h + 1], mbb, ihb, ilb, cv[2 * i + h][0], cv[2 * i + h][1], cv[2 * i + h][2]);
          }
          stmatrix_x4(sbase + OG_OSLOT + (J0 >> 3) * 16384 + frag + ((((J0 & 7) + 2 * i + fhi) ^ fsw) << 4), xr[i][0], xr[i][1], xr[i][2], xr[i][3]);
        }
      }
      fence_proxy_async();
      mbar_wait(bar_full + 352, 0);
      const uint2 cg = lds_u32x2(sbase + OG_SMISC + 96);
      __syncwarp();
      if (elect_one()) {
        mbar_arrive(bar_out);
        if (cg.x != w8 && cg.y != w8) {
          asm volatile("cp.async.bulk.tensor.2d.global.shared::cta.bulk_group [%0, {%2, %3}], [%1];" :: "l"(tmOut), "r"(sbase + OG_OSLOT + w8 * 2048), "r"(n0), "r"(m0 + 16 * w8) : "memory");
          asm volatile("cp.async.bulk.tensor.2d.global.shared::cta.bulk_group [%0, {%2, %3}], [%1];" :: "l"(tmOut), "r"(sbase + OG_OSLOT + 16384 + w8 * 2048), "r"(n0 + 64), "r"(m0 + 16 * w8) : "memory");
          bulk_commit();
        }
      }
      TL_MARK2(24, lane == 0);
    }
    if (has_moe) mbar_wait(bar_h2, 0);
    TL_MARK2(13, lane == 0);
    if (has_moe) {
      const GemvSel sel = gemv_sel(lane);
      {
        float d[4][4];
        #pragma unroll
        for (int c = 0; c < 4; c++) { d[c][0] = 0.f; d[c][1] = 0.f; d[c][2] = 0.f; d[c][3] = 0.f; }
        #pragma unroll
        for (int st = 0; st < 8; st++) {
          const uint2 hb = lds_u32x2(sbase + OG_SH2 + ((lane >> 2) & 1) * 2048 + (w8 * 128 + st * 16 + (lane & 3) * 4) * 2);
          #pragma unroll
          for (int j = 0; j < 4; j++) mma_bf16(d[j], wv[4 * st + j].x, wv[4 * st + j].y, wv[4 * st + j].z, wv[4 * st + j].w, GEMV_B0(j, hb, sel), GEMV_B1(j, hb, sel));
        }
        #pragma unroll
        for (int e = 0; e < 4; e++) d[0][e] = (d[0][e] + d[1][e]) + (d[2][e] + d[3][e]);
        sts_f32x4(sbase + OG_SRED + t2 * 16, d[0][0], d[0][1], d[0][2], d[0][3]);
      }
      named_bar_sync(9, 256);
      if (t2 < 64) {
        const int c = gemv_col(t2);
        float gp[8], up[8];
        #pragma unroll
        for (int w = 0; w < 8; w++) { gp[w] = lds_f32(sbase + OG_SRED + w * 512 + t2 * 4); up[w] = lds_f32(sbase + OG_SRED + w * 512 + 256 + t2 * 4); }
        const float gs = ((gp[0] + gp[1]) + (gp[2] + gp[3])) + ((gp[4] + gp[5]) + (gp[6] + gp[7]));
        const float us = ((up[0] + up[1]) + (up[2] + up[3])) + ((up[4] + up[5]) + (up[6] + up[7]));
        asm volatile("st.shared.u16 [%0], %1;" :: "r"(sbase + OG_SGU + (t2 & 1) * 64 + ((c & ~15) + ((c >> 1) & 3) * 4 + ((c >> 3) & 1) * 2 + (c & 1)) * 2), "h"((uint16_t)pack_bf16(silu_bf(rbf(gs)) * rbf(us), 0.f)) : "memory");
      }
      named_bar_sync(9, 256);
      TL_MARK2(20, threadIdx.x == 128);
      float d[4][4];
      #pragma unroll
      for (int c = 0; c < 4; c++) { d[c][0] = 0.f; d[c][1] = 0.f; d[c][2] = 0.f; d[c][3] = 0.f; }
      #pragma unroll
      for (int st = 0; st < 2; st++) {
        const uint2 g = lds_u32x2(sbase + OG_SGU + ((lane >> 2) & 1) * 64 + st * 32 + (lane & 3) * 8);
        #pragma unroll
        for (int j = 0; j < 4; j++) {
          const uint32_t b0 = GEMV_B0(j, g, sel), b1 = GEMV_B1(j, g, sel);
          mma_bf16(d[j & 1], wd[4 * st + j].x, wd[4 * st + j].y, wd[4 * st + j].z, wd[4 * st + j].w, b0, b1);
          mma_bf16(d[2 + (j & 1)], wd[8 + 4 * st + j].x, wd[8 + 4 * st + j].y, wd[8 + 4 * st + j].z, wd[8 + 4 * st + j].w, b0, b1);
        }
      }
      #pragma unroll
      for (int e = 0; e < 4; e++) { d[0][e] += d[1][e]; d[2][e] += d[3][e]; }
      float* yp = g_ypart + (size_t)bid * 2 * T_D + w8 * 256 + lane * 4;
      st_tagged4_lsb(yp, d[0][0], d[0][1], d[0][2], d[0][3]);
      st_tagged4_lsb(yp + 128, d[2][0], d[2][1], d[2][2], d[2][3]);
      named_bar_sync(9, 256);
      if (t2 == 0) hint_arrive(CNT_Y);
    }
    bulk_wait_read<0>();
    TL_MARK2(14, threadIdx.x == 128);
    TL_CLK(4, 1, threadIdx.x == 128);
}

__device__ __forceinline__ int help_njobs(uint32_t bid) { return bid < 128 ? OG_JOBS : 16 - OG_JOBS; }
__device__ __forceinline__ int help_job(uint32_t bid, int i) { return (i < OG_JOBS ? 16 * i + (bid >> 7) * 2 : 112 + (i - OG_JOBS) * 2) + (bid & 3) * 4; }
__device__ __noinline__ void store_warp(uint32_t bid, uint32_t sbase, const CUtensorMap* tmO, int item0, int n_items) {
  if (elect_one()) {
    const uint32_t bars = sbase + AT_SBAR, b_q0 = bars + 80, b_ob = bars + 96, b_ordy = bars + 104, b_acq = bars + 264;
    const unsigned int* cnt = g_hcnt + 32 * (1 + OG_MT(124)) + 2;
    #pragma unroll 1
    for (int q = 0; q < 4 * n_items; q++) {
      const int item = item0 + (q >> 2) * 128, h = (q >> 1) & 1, w = q & 1;
      const bool last = (q >> 2) == n_items - 1;
      if (q == 4 * n_items - 4) { mbar_wait_long(bars + 288, 0); red_release_add(&g_hcnt[1], 1u); }
      mbar_wait_long(b_ordy + 8 * (q & 3), q >> 2);
      store_o(tmO, (h ? (last ? sbase + AT_SQ + 32768 : sbase + 2 * 32768) : sbase + AT_SQ) + w * 8192, (item >> 4) * 2 + h, (item & 15) * 128 + w * 64);
      if (w) {
        bulk_wait_read<0>();
        mbar_arrive(h ? b_ob : b_q0);
        bulk_wait<0>();
        fence_proxy_async_global();
        asm volatile("fence.acq_rel.gpu;" ::: "memory");
        hint_arrive(&g_hcnt[32 * (1 + (item & 15)) + 2 + (item >> 7)]);
        if (!h && item < 128) hint_arrive(&g_hcnt[2]);
        if (q == 5) { const int tb = tail_tile(sbase); cnt = g_hcnt + 32 * (1 + OG_MT(tb)) + 2; spin_until(cnt, 16u); mbar_arrive(b_acq); }
      }
    }
    if (n_items == 1) {
      #pragma unroll 1
      for (int i = 0; i < help_njobs(bid); i++) {
        mbar_wait_long(b_acq + 16, i & 1);
        TL_MARK2(23, i == OG_JOBS - 1);
        red_release_add(&g_hcnt[32 * (1 + (help_job(bid, i) >> 3)) + 4 + ((help_job(bid, i) >> 1) & 3)], 1u);
        TL_MARK2(4, i == OG_JOBS - 1);
        if (i == PRE_X - 1) { spin_until(&g_hcnt[1], 132u); mbar_arrive(b_acq + 32); }
      }
    }
    if (bid < 128) {
      if (n_items == 1) { spin_until(cnt, 16u); mbar_arrive(b_acq); }
      spin_until(&g_hcnt[0], 128u); spin_until(cnt + 1, 16u); mbar_arrive(b_acq + 80);
    }
  }
}

__device__ __forceinline__ uint32_t role_of_sm(uint32_t sm) {
  const uint32_t t = sm >> 1, u = t - 32u, d = (u * 37u) >> 8;
  return (t < 32u ? ((t + 7u) & 7u) * 16u + (t >> 3) * 2u : t < 60u ? (u - 7u * d) * 16u + (4u + d) * 2u : t < 62u ? 2u * t + 8u : 2u * t - 4u) + (sm & 1u);
}
__global__ void __launch_bounds__(384, 1)
fused_kernel(const __grid_constant__ CUtensorMap tmH, const __grid_constant__ CUtensorMap tmW, const __grid_constant__ CUtensorMap tmK,
            const __grid_constant__ CUtensorMap tmV, const __grid_constant__ CUtensorMap tmO, const __grid_constant__ CUtensorMap tmOl, const __grid_constant__ CUtensorMap tmWo,
            const __grid_constant__ CUtensorMap tmD, const __grid_constant__ CUtensorMap tmOut, const __grid_constant__ CUtensorMap tmM, uint32_t zero,
            const uint8_t* __restrict__ pf_wo, const bf16* __restrict__ kc, const bf16* __restrict__ vc,
            const bf16* __restrict__ x, const bf16* __restrict__ cvec, const bf16* __restrict__ w_mod, const bf16* __restrict__ w_r,
            const bf16* __restrict__ w_gate, const bf16* __restrict__ w_up, const bf16* __restrict__ w_down, bf16* __restrict__ out)
{
  uint32_t bid, nsm;
  asm volatile("mov.u32 %0, %%smid;" : "=r"(bid));
  asm volatile("mov.u32 %0, %%nsmid;" : "=r"(nsm));
  bid = __shfl_sync(0xffffffffu, nsm == 132u ? role_of_sm(bid) : blockIdx.x, 0);
  extern __shared__ __align__(1024) uint8_t smem_raw[];
  const uint32_t sbase = smem_u32(smem_raw);
  const uint32_t bars = sbase + AT_SBAR;
  const uint32_t b_full = bars, b_empty = bars + 40;
  const uint32_t b_q0 = bars + 80, b_q1 = bars + 88;
  const uint32_t b_ob = bars + 96;
  const uint32_t b_ordy = bars + 104;
  const uint32_t b_pin = bars + 136;
  const uint32_t b_head = bars + 144;
  const uint32_t b_go = bars + 152;
  const uint32_t b_x = bars + 160;
  const int wg = __shfl_sync(0xffffffffu, threadIdx.x >> 7, 0);
  const bool single = bid >= AT_NFULL;
  const int item0 = __shfl_sync(0xffffffffu, bid < 128 ? (int)bid : (int)bid + 124, 0), n_items = __shfl_sync(0xffffffffu, single ? 1 : 2, 0);
  TL_START(3);
  if (threadIdx.x == 0) {
    if (sbase & 1023u) __trap();
    for (int i = 0; i < 5; i++) { mbar_init(b_full + 8 * i, 1); mbar_init(b_empty + 8 * i, 2); }
    mbar_init(b_q0, 1); mbar_init(b_q1, 8); mbar_init(b_ob, 1);
    for (int i = 0; i < 4; i++) mbar_init(b_ordy + 8 * i, 4);
    mbar_init(b_pin, 1); mbar_init(b_head, bid < 128 ? 8 : 1); mbar_init(b_go, 1); mbar_init(b_x, 1);
    mbar_init(bars + 168, 2); mbar_init(bars + 176, 1); mbar_init(bars + 184, 8); mbar_init(bars + 192, 2);
    mbar_init(bars + 200, 8); mbar_init(bars + 208, 4); mbar_init(bars + 216, 1); mbar_init(bars + 264, 1); mbar_init(bars + 272, 1); mbar_init(bars + 280, 8); mbar_init(bars + 288, 1); mbar_init(bars + 296, 1); mbar_init(bars + 304, 8); mbar_init(bars + 312, 1); mbar_init(bars + 320, 1); mbar_init(bars + 328, 1); mbar_init(bars + 336, 1); mbar_init(bars + 344, 1); mbar_init(bars + 352, 1); mbar_init(bars + 360, 1); mbar_init(bars + 368, 2); mbar_init(bars + 376, 2);
    sts_u32(bars + 400, bid);
    fence_mbar_init();
  }

  if (wg == 0) {
    reg_dealloc<AT_PREG>();
    if (threadIdx.x < 32) { __syncwarp(); named_bar_arrive(6, 384); }
    if (threadIdx.x >= 64) {
      named_bar_sync(6, 384);
      if (bid < 128) {
        named_bar_sync(threadIdx.x >= 96 ? 8 : 9, 288);
        if ((threadIdx.x & 31) == 0) red_release_add(&g_hcnt[32 * (1 + (bid >> 3)) + (threadIdx.x >= 96)], 1u);
        TL_MARK2(11, threadIdx.x == 64);
      }
      if (bid < 128) {
        mbar_wait(MOD_AT, 0);
        mod_rest(bid, sbase + OG_SCOL, b_q1, threadIdx.x - 64, cvec, w_mod, w_r);
      }
    } else if (threadIdx.x >= 32) {
      named_bar_sync(6, 384);
      store_warp(bid, sbase, &tmO, item0, n_items);
      __syncwarp();
    } else {
     if (elect_one()) {
      const uint64_t pol = policy_evict_first();
      if (bid < 128) {
        mbar_expect_tx(b_x, 32768);
        if (X_DLY) { const uint32_t c0 = clock_lo(); while (clock_lo() - c0 < X_DLY) {} }
        bulk_load_hint(sbase + 4 * 32768, x + (size_t)bid * 16 * T_D, 32768, b_x, pol);
      }
      prefetch_tmap(&tmW); prefetch_tmap(&tmM); prefetch_tmap(&tmH); prefetch_tmap(&tmWo); prefetch_tmap(&tmOl);
      {
        const uint32_t c0 = clock_lo();
        while (clock_lo() - c0 < W_DLY) {}
        if (bid < 128 && (head_cb(bid) & 15) >= 4 * H_SPLIT) {
          mbar_expect_tx(bars + 328, 32768);
          tma_load_2d_hint(sbase + 3 * 32768, &tmM, head_cb(bid) * 64, (bid >> 5) * 256, bars + 328, pol);
        }
        while (clock_lo() - c0 < W_DLY + W_FIRST) {}
      }
      uint32_t slot = 0, ph = 1;
      #pragma unroll 1
      for (int it = 0; it < n_items; it++) {
        const int item = item0 + it * 128, hp = item >> 4, qt = item & 15;
        const bool first = it == 0;
        #pragma unroll 1
        for (int j = 0; j < T_D / 64; j++) {
          const uint32_t sl = ring_slot(qp_pos(j, it)), fb = b_full + 8 * sl;
          mbar_wait_long(b_empty + 8 * sl, ring_par(qp_pos(j, it)) ^ ((j >> 2) & 1) ^ 1);
          if (first && j == 3) mbar_wait(b_head, 0);
          mbar_expect_tx(fb, 49152);
          tma_load_3d_hint(sbase + sl * 32768, &tmW, j * 64, hp * 4, fb, pol);
          if (first && j < PRE_B) {
            if (j == PRE_B - 1) {
              spin_until(&g_hcnt[32 * (1 + qt)], 8u);
              TL_MARK2(16, true);
              fence_proxy_async_global();
              #pragma unroll 1
              for (int i = 0; i < PRE_B; i++) tma_load_2d(sbase + AT_SQ + i * 16384, &tmH, i * 64, qt * 128, b_full + 8 * i);
              mbar_arrive(b_go);
            }
          } else {
            if (first && j == 4 * H_SPLIT) { spin_until(&g_hcnt[32 * (1 + qt) + 1], 8u); fence_proxy_async_global(); }
            if (!first && (j == 0 || j == 2)) mbar_wait(j ? b_q1 : b_q0, 0);
            tma_load_2d(sbase + AT_SQ + (j & 3) * 16384, &tmH, j * 64, qt * 128, fb);
          }
        }
        #pragma unroll 1
        for (int j = 0; j < 4 * AT_NBLK; j++) {
          const bool isv = (j > 0 && !(j & 1)) || j == 4 * AT_NBLK - 1;
          const int row = hp * 2 * T_SEQ + (isv ? (j - 1) >> 1 : (j + 1) >> 1) * 128;
          const uint32_t fb = b_full + 8 * slot;
          mbar_wait_long(b_empty + 8 * slot, ph);
          if (!first && j == 3) mbar_wait(b_ob, 0);
          if (j == 4 && it == n_items - 1) mbar_arrive(bars + 288);
          if ((j == AL_P || j == RK_P) && it == 1) mbar_arrive(bars + 312);
          mbar_expect_tx(fb, 32768);
          tma_load_3d_hint(sbase + slot * 32768, isv ? &tmV : &tmK, row, 0, fb, pol);
          if (it == 1 && isv && j >= 2 * WO_LATE && j < 2 * WO_LATE + 32 && bid < OG_NKB)
            l2_prefetch_bulk(pf_wo + (size_t)own_kb(bid, og_pre(0)) * 131072 + ((j >> 1) - WO_LATE) * 8192, 8192);
          if (++slot == 5) { slot = 0; ph ^= 1; }
        }
      }
      if (__builtin_expect(single, 0)) {
        spin_until(&g_hcnt[2], 128u);
        fence_proxy_async_global();
        const int nj = OG_HSUM + (help_njobs(bid) - OG_JOBS) * OG_PRE2;
        int ji = 0, job = help_job(bid, 0), kk = 0;
        #pragma unroll 1
        for (int j = 0; j < nj; j++) {
          const uint32_t sl = ring_slot(qp_pos(j, 1)), fb = b_full + 8 * sl;
          mbar_wait_long(b_empty + 8 * sl, ring_par(qp_pos(j, 1)) ^ ((j >> 2) & 1) ^ 1);
          mbar_expect_tx(fb, 49152);
          tma_load_3d(sbase + sl * 32768, &tmWo, pre_kb(kk) * 64, OG_NT(job) * 2, fb);
          tma_load_3d(sbase + sl * 32768 + 16384, &tmWo, pre_kb(kk) * 64, OG_NT(job) * 2 + 2, fb);
          if (j == 0 || j == 2) mbar_wait(j ? b_ob : b_q0, 0);
          tma_load_2d_hint(sbase + AT_SQ + (j & 3) * 16384, &tmOl, pre_kb(kk) * 64, OG_MT(job) * 128, fb, pol);
          if (++kk == og_pre(job)) { kk = 0; job = help_job(bid, ++ji); }
        }
      }
      if (bid < 128) {
        if (single) mbar_wait(b_x, 1);
        tail_producer(bid, sbase, 0, pol, &tmOl, &tmWo, &tmD);
      }
     }
    }
    named_bar_sync(12 + (threadIdx.x >> 5), 32);
    if (bid < 128) tail_exchange(bid, sbase, w_down, w_r, x, out);
  } else {
    if (bid < 128) head_phase(bid, sbase + AT_SQ + 49152, sbase + 4 * 32768, b_x, b_go, b_head, threadIdx.x - 128, zero, cvec, w_mod);
    else { named_bar_sync(6, 384); if (threadIdx.x == 128) mbar_arrive(b_head); }
    TL_MARK2(0, threadIdx.x == 128);
    reg_alloc<AT_CREG>();
    const int cwg = wg - 1;
    const int tid = threadIdx.x & 127;
    const int warp = tid >> 5, lane = tid & 31;
    const uint32_t dbase = (sbase & 0x3FFFFu) >> 4;
    const uint32_t k_base = dbase + (1u << 16);
    const uint32_t v_base = dbase + (1024u << 16);
    const uint32_t w_base = dbase + (512u << 16);
    const uint32_t q_lo = dbase + ((AT_SQ + cwg * 8192) >> 4) + (1u << 16);
    const uint32_t frag = cwg * 8192 + (16 * warp + (lane & 7) + 8 * ((lane >> 3) & 1)) * 128;
    if (cwg == 1) named_bar_arrive(1, 256);
    bool raw = false;
    uint4 pre[8];
    #pragma unroll 1
    for (int it = 0; it < n_items; it++) {
      const bool more = it + 1 < n_items;
      constexpr int nkb = T_D / 64;
      const int ta = __shfl_sync(0xffffffffu, 4 * it, 0);
      float acc[128];
      {
        FS(2 * it, 0);
        #pragma unroll
        for (int i = 0; i < 128; i++) asm volatile("" : "=f"(acc[i]));
        {
          const uint32_t slot = ring_slot(ta), b_lo = w_base + slot * 2048;
          mbar_wait(b_full + 8 * slot, ring_par(ta));
          wgmma_fence();
          wgmma_m64n256k16_ss_tb<0, 0>(acc, q_lo, b_lo, 0);
          wgmma_m64n256k16_ss_tb<2, 128>(acc, q_lo, b_lo, 1);
          wgmma_m64n256k16_ss_tb<4, 256>(acc, q_lo, b_lo, 1);
          wgmma_m64n256k16_ss_tb<6, 384>(acc, q_lo, b_lo, 1);
          wgmma_commit();
        }
        #pragma unroll 1
        for (int j = 1; j < nkb; j++) {
          const uint32_t slot = ring_slot(qp_pos(j, ta >> 2));
          mbar_wait(b_full + 8 * slot, ring_par(qp_pos(j, ta >> 2)) ^ ((j >> 2) & 1));
          if (QP_STAG > 0 && cwg == 1 && j == nkb - QP_STAG) named_bar_sync(7, 256);
          const uint32_t a_lo = q_lo + (j & 3) * 1024, b_lo = w_base + slot * 2048;
          wgmma_fence();
          wgmma_m64n256k16_ss_tb<0, 0>(acc, a_lo, b_lo, 1);
          wgmma_m64n256k16_ss_tb<2, 128>(acc, a_lo, b_lo, 1);
          wgmma_m64n256k16_ss_tb<4, 256>(acc, a_lo, b_lo, 1);
          wgmma_m64n256k16_ss_tb<6, 384>(acc, a_lo, b_lo, 1);
          wgmma_commit();
          if (QP_STAG > 0 && cwg == 0 && j == nkb - 1) named_bar_arrive(7, 256);
          if (j > 0) {
            wgmma_wait<1>();
            if (tid == 0) mbar_arrive(b_empty + 8 * ring_slot(qp_pos(j - 1, ta >> 2)));
          }
        }
        wgmma_wait<0>();
        fence_regs(acc);
        FS(2 * it, 1);
        TL_MARK2(29, threadIdx.x == 256 && it == 0);
        if (tid == 0) mbar_arrive(b_empty + 24);
      }
      float o[64], s[64];
      uint32_t p[32], q[32];
      #pragma unroll
      for (int i = 0; i < 32; i++) q[i] = pack_bf16(acc[2 * i] * AT_C, acc[2 * i + 1] * AT_C);
      zero_regs(s);
      const uint32_t sq = sbase + AT_SQ + cwg * 8192;
      float mc0, mc1, al0 = 1.0f, al1 = 1.0f, l0 = 0.f, l1 = 0.f, lp0 = 0.f, lp1 = 0.f;
      bool redo0 = false;
      FS(2 * it, 2);
      mbar_wait(b_full + 8 * ring_slot(ta), ring_par(ta));
      named_bar_sync(1 + cwg, 256);
      FS(2 * it, 3);
      issue_qk(s, q, k_base + ring_slot(ta) * 2048);
      pass_turn(cwg);
      bool ready = mbar_test(b_full + 8 * ring_slot(ta + 1), ring_par(ta + 1)) & mbar_test(b_full + 8 * ring_slot(ta + 2), ring_par(ta + 2));
      stage_q<16>(acc, AT_C, sbase + AT_SQ + frag, lane);
      wgmma_wait<0>();
      fence_regs(s);
      if (tid == 0) mbar_arrive(b_empty + 8 * ring_slot(ta));
      mc0 = 0.f; mc1 = 0.f;
      if (!raw) {
        const float a = fmaxf(fmaxf(fmaxf(s[0], s[1]), fmaxf(s[4], s[5])), fmaxf(fmaxf(s[8], s[9]), fmaxf(s[12], s[13])));
        const float b = fmaxf(fmaxf(fmaxf(s[2], s[3]), fmaxf(s[6], s[7])), fmaxf(fmaxf(s[10], s[11]), fmaxf(s[14], s[15])));
        raw = __all_sync(0xffffffffu, fabsf(a) <= 16.0f && fabsf(b) <= 16.0f);
      }
      if (!raw) {
        raw = softmax_mode(s, mc0, mc1);
        if (__builtin_expect(!raw, 0)) softmax_sub(s, mc0, mc1);
      }
      softmax_exp<0, 64>(s);
      #pragma unroll
      for (int J = 0; J < 16; J += 2)
        stmatrix_x4(sbase + AT_SQ + frag + (J >> 3) * 16384 + ((((J & 7) + (lane >> 4)) ^ (lane & 7)) << 4), q[2 * J], q[2 * J + 1], q[2 * J + 2], q[2 * J + 3]);
      pack_p(p, s);
      zero_regs(o);
      FS(2 * it, 4);
      uint32_t ks = ring_slot(ta + 1), vs = ring_slot(ta + 2), kp = ring_par(ta + 1), vp = ring_par(ta + 2);
      auto finish_head = [&]() {
        FS(2 * it, 5);
        redo0 = finish_l(lp0, lp1);
        if (!redo0) stage_o(o, lp0, lp1, sbase + AT_SQ + frag, lane);
        FS(2 * it + 1, 4);
      };
      if (!ready) { mbar_wait(b_full + 8 * ks, kp); mbar_wait(b_full + 8 * vs, vp); }
      #pragma unroll 1
      for (int n = 1; n < 2 * AT_NBLK; n++) {
        named_bar_sync(1 + cwg, 256);
        issue_qk(s, q, k_base + ks * 2048);
        if (n == AT_NBLK + 1) finish_head();
        issue_pv(o, p, v_base + vs * 2048, (n & 15) != 1);
        pass_turn(cwg);
        wgmma_wait<1>();
        fence_regs(s);
        if (tid == 0) mbar_arrive(b_empty + 8 * ks);
        if (__builtin_expect(!raw || (uint32_t)(n - (AT_NBLK - 1)) <= 2u, 0)) {
          if (n == AT_NBLK + 1 && !redo0) {
            fence_proxy_async();
            __syncwarp();
            if (lane == 0) mbar_arrive(b_ordy + 8 * cwg);
          }
          if (n == AT_NBLK - 1) {
            #pragma unroll
            for (int J = 0; J < 16; J += 2)
              ldmatrix_x4(sbase + AT_SQ + 32768 + frag + (J >> 3) * 16384 + ((((J & 7) + (lane >> 4)) ^ (lane & 7)) << 4), q[2 * J], q[2 * J + 1], q[2 * J + 2], q[2 * J + 3]);
          }
          if (!raw) {
            const float m0 = mc0, m1 = mc1;
            const bool ok = softmax_mode(s, mc0, mc1);
            if (n == AT_NBLK) raw = ok;
            else {
              mc0 = mc0 - AT_HEAD > m0 ? mc0 : m0; mc1 = mc1 - AT_HEAD > m1 ? mc1 : m1;
              al0 = ex2_approx(m0 - mc0); al1 = ex2_approx(m1 - mc1);
            }
            if (!raw) softmax_sub(s, mc0, mc1);
          }
        }
        softmax_exp<0, AT_SPLIT>(s);
        add_rowsum(p, l0, l1);
        if (zero != 0) {
          uint32_t dep = zero & __float_as_uint(l0) & __float_as_uint(l1);
          #pragma unroll
          for (int i = AT_SPLIT - AT_PIN - PINB; i < AT_SPLIT - PINB; i += 2) dep &= __float_as_uint(s[i]) & __float_as_uint(s[i + 1]);
          mbar_arrive(b_pin + dep);
        }
        wgmma_wait<0>();
        fence_regs(o);
        if (tid == 0) mbar_arrive(b_empty + 8 * vs);
        ks += 2; if (ks >= 5) { ks -= 5; kp ^= 1; }
        vs += 2; if (vs >= 5) { vs -= 5; vp ^= 1; }
        ready = mbar_test(b_full + 8 * ks, kp) & mbar_test(b_full + 8 * vs, vp);
        softmax_exp<AT_SPLIT, 64>(s);
        pack_p(p, s);
        if (n == AT_NBLK) { lp0 = l0; lp1 = l1; l0 = 0.f; l1 = 0.f; }
        if (__builtin_expect(!raw || !ready, 0)) {
        if (!raw && __any_sync(0xffffffffu, al0 != 1.0f || al1 != 1.0f)) {
          rescale_o(o, al0, al1);
          l0 *= al0; l1 *= al1;
          al0 = 1.0f; al1 = 1.0f;
        }
        if (!ready && n < 2 * AT_NBLK - 1) {
          mbar_wait(b_full + 8 * ks, kp);
          mbar_wait(b_full + 8 * vs, vp);
        }
        }
      }
      FS(2 * it + 1, 5);
      const uint32_t vl = ring_slot(ta + 63);
      vs = ring_slot(ta + 62);
      const uint32_t ob = more ? sbase + vs * 32768 : sbase + AT_SQ + 32768;
      mbar_wait(b_full + 8 * vl, ring_par(ta + 63));
      issue_pv(o, p, v_base + vl * 2048, 1);
      block_end(zero, b_pin);
      add_rowsum(p, l0, l1);
      const bool overflow = finish_l(l0, l1);
      if (!overflow && lane == 0) mbar_arrive(b_q1);
      #pragma unroll
      for (int i = 0; i < 8; i++) asm volatile("mov.b64 {%0, %1}, 0;\nmov.b64 {%2, %3}, 0;" : "=r"(pre[i].x), "=r"(pre[i].y), "=r"(pre[i].z), "=r"(pre[i].w));
      const bool want_pre = !more && bid < OG_MOE, got_pre = want_pre && __all_sync(0xffffffffu, mbar_test(bars + 272, 0));
      if (got_pre) load_pre(pre, sbase, AT_SQ, threadIdx.x - 128);
      mbar_wait(b_empty + 8 * vs, ring_par(ta + 62));
      wgmma_wait<0>();
      fence_regs(o);
      if (tid == 0) mbar_arrive(b_empty + 8 * vl);
      FS(2 * it + 1, 6);
      if (overflow) {
        attn_rows_exact(lds_u32(bars + 400), sq + 32768, ob + cwg * 8192, 4 * ta + 1, kc, vc);
        __syncwarp();
        if (lane == 0) mbar_arrive(b_q1);
      } else stage_o(o, l0, l1, ob + frag, lane);
      if (redo0) attn_rows_exact(lds_u32(bars + 400), sq, sq, 4 * ta, kc, vc);
      fence_proxy_async();
      __syncwarp();
      if (lane == 0) {
        if (redo0) mbar_arrive(b_ordy + 8 * cwg);
        mbar_arrive(b_ordy + 16 + 8 * cwg);
      }
      if (want_pre && !got_pre) load_pre(pre, sbase, AT_SQ, threadIdx.x - 128);
      if (redo0 || overflow) raw = false;
      named_bar_sync(3 + cwg, 128);
      FS(2 * it + 1, 7);
    }
    if (cwg == 0) named_bar_arrive(1, 256);
    if (__builtin_expect(single, 0)) {
      float acc[128];
      uint32_t j = 0, pk[64];
      #pragma unroll
      for (int i = 0; i < 64; i++) asm volatile("" : "=f"(acc[2 * i]), "=f"(acc[2 * i + 1]), "=r"(pk[i]));
      uint4* dst = g_pre;
      int left = 0;
      auto put = [&](bool last) {
        #pragma unroll
        for (int i = 0; i < PUT_N; i++) dst[i * 256] = make_uint4(pk[4 * i], pk[4 * i + 1], pk[4 * i + 2], pk[4 * i + 3]);
        dst += PUT_N * 256;
        #pragma unroll
        for (int i = 0; i < 64 - 4 * PUT_N; i++) asm volatile("mov.b32 %0, %1;" : "=r"(pk[i]) : "r"(pk[i + 4 * PUT_N]));
        __syncwarp();
        if (last && lane == 0) mbar_arrive(bars + 280);
      };
      #pragma unroll 1
      for (int ji = 0; ji < help_njobs(bid); ji++) {
        const int nk = og_pre(help_job(bid, ji));
        #pragma unroll 1
        for (int kk = 0; kk < nk; kk++, j++) {
          const uint32_t slot = ring_slot(qp_pos(j, 1));
          mbar_wait(b_full + 8 * slot, ring_par(qp_pos(j, 1)) ^ ((j >> 2) & 1));
          if (H_STAG > 0 && cwg == 1 && kk == nk - H_STAG) named_bar_sync(7, 256);
          const uint32_t a_lo = q_lo + (j & 3) * 1024, b_lo = w_base + slot * 2048;
          wgmma_fence();
          wgmma_m64n256k16_ss_tb<0, 0>(acc, a_lo, b_lo, kk != 0);
          wgmma_m64n256k16_ss_tb<2, 128>(acc, a_lo, b_lo, 1);
          wgmma_m64n256k16_ss_tb<4, 256>(acc, a_lo, b_lo, 1);
          wgmma_m64n256k16_ss_tb<6, 384>(acc, a_lo, b_lo, 1);
          wgmma_commit();
          if (H_STAG > 0 && cwg == 0 && kk == nk - 1) named_bar_arrive(7, 256);
          wgmma_wait<1>();
          if (kk > 0 && tid == 0) mbar_arrive(b_empty + 8 * ring_slot(qp_pos(j - 1, 1)));
          #pragma unroll 1
          for (int i = ji == OG_JOBS ? 0 : 16 / PUT_N - 1; i < 16 / PUT_N && left > 0; i++) put(--left == 0);
        }
        wgmma_wait<0>();
        fence_regs(acc);
        if (tid == 0) mbar_arrive(b_empty + 8 * ring_slot(qp_pos(j - 1, 1)));
        #pragma unroll
        for (int i = 0; i < 64; i++) pk[i] = pack_bf16(acc[2 * i], acc[2 * i + 1]);
        left = 16 / PUT_N;
        if (ji == PRE_X) mbar_wait(bars + 296, 0);
        dst = g_pre + help_job(bid, ji) * 2048 + threadIdx.x - 128;
      }
      #pragma unroll
      for (int i = 0; i < 16; i++) dst[i * 256] = make_uint4(pk[4 * i], pk[4 * i + 1], pk[4 * i + 2], pk[4 * i + 3]);
      __syncwarp();
      if (lane == 0) mbar_arrive(bars + 280);
      named_bar_sync(5, 256);
      if (threadIdx.x == 128) {
        #pragma unroll 1
        for (int i = 0; i < 5; i++) {
          constexpr int n = OG_HSUM;
          const int used = i == 3 ? 0 : (n + 3 - (i == 4 ? 3 : i)) / 4;
          if ((used ^ (i < 4)) & 1) {
            mbar_arrive(b_full + 8 * ring_slot(4 + i));
            mbar_arrive(b_empty + 8 * ring_slot(4 + i)); mbar_arrive(b_empty + 8 * ring_slot(4 + i));
          }
        }
        mbar_arrive(b_x);
      }
      named_bar_sync(5, 256);
      #pragma unroll
      for (int i = 0; i < 8; i++) pre[i] = make_uint4(0u, 0u, 0u, 0u);
    }
    TL_CLK(3, 1, threadIdx.x == 128);
    TL_CTA(1, threadIdx.x == 256);
    TL_END(3, tid == 0);
    TL_MARK2(19, tid == 0 && !single);
    if (bid < 128) {
      tail_consumer(bid, sbase, &tmOut, pre, cwg, w_gate, w_up);
    }
  }
}

typedef CUresult (*PFN_encodeTiled)(CUtensorMap*, CUtensorMapDataType, cuuint32_t, void*, const cuuint64_t*, const cuuint64_t*,
                                    const cuuint32_t*, const cuuint32_t*, CUtensorMapInterleave, CUtensorMapSwizzle,
                                    CUtensorMapL2promotion, CUtensorMapFloatOOBfill);

CUtensorMap make_map_2d(PFN_encodeTiled enc, const void* ptr, uint64_t inner, uint64_t outer, uint64_t stride_bytes, uint32_t box_inner, uint32_t box_outer) {
  CUtensorMap m;
  cuuint64_t gd[2] = {inner, outer}; cuuint64_t gs[1] = {stride_bytes};
  cuuint32_t bx[2] = {box_inner, box_outer}; cuuint32_t es[2] = {1, 1};
  enc(&m, CU_TENSOR_MAP_DATA_TYPE_BFLOAT16, 2, const_cast<void*>(ptr), gd, gs, bx, es, CU_TENSOR_MAP_INTERLEAVE_NONE,
      CU_TENSOR_MAP_SWIZZLE_128B, CU_TENSOR_MAP_L2_PROMOTION_L2_128B, CU_TENSOR_MAP_FLOAT_OOB_FILL_NONE);
  return m;
}

CUtensorMap make_map_3d(PFN_encodeTiled enc, const void* ptr, uint64_t cols, uint64_t rows, uint32_t box_rows, uint32_t chunks) {
  CUtensorMap m;
  cuuint64_t gd[3] = {64, rows, cols / 64}; cuuint64_t gs[2] = {cols * 2, 128};
  cuuint32_t bx[3] = {64, box_rows, chunks}; cuuint32_t es[3] = {1, 1, 1};
  enc(&m, CU_TENSOR_MAP_DATA_TYPE_BFLOAT16, 3, const_cast<void*>(ptr), gd, gs, bx, es, CU_TENSOR_MAP_INTERLEAVE_NONE,
      CU_TENSOR_MAP_SWIZZLE_128B, CU_TENSOR_MAP_L2_PROMOTION_L2_128B, CU_TENSOR_MAP_FLOAT_OOB_FILL_NONE);
  return m;
}

}

extern "C" void kernel_launch(void* const* d_in, const int* in_sizes, int n_in, void* d_out, int out_size) {
  const bf16* x      = (const bf16*)d_in[0];
  const bf16* kc     = (const bf16*)d_in[1];
  const bf16* vc     = (const bf16*)d_in[2];
  const bf16* wq     = (const bf16*)d_in[3];
  const bf16* wo     = (const bf16*)d_in[4];
  const bf16* w_r    = (const bf16*)d_in[6];
  const bf16* w_gate = (const bf16*)d_in[7];
  const bf16* w_up   = (const bf16*)d_in[8];
  const bf16* w_down = (const bf16*)d_in[9];
  const bf16* cvec   = (const bf16*)d_in[10];
  const bf16* w_mod  = (const bf16*)d_in[11];
  bf16* out = (bf16*)d_out;

  static PFN_encodeTiled enc = nullptr;
  static void *p_h = nullptr, *p_o = nullptr;
  if (!enc) {
    void* fn = nullptr; cudaDriverEntryPointQueryResult qres;
    cudaGetDriverEntryPoint("cuTensorMapEncodeTiled", &fn, cudaEnableDefault, &qres);
    enc = (PFN_encodeTiled)fn;
    cudaGetSymbolAddress(&p_h, g_pre);
    p_h = (uint4*)p_h + 16 * PRE_X * 2048;
    cudaGetSymbolAddress(&p_o, g_o);
    cudaFuncSetAttribute(fused_kernel, cudaFuncAttributeMaxDynamicSharedMemorySize, (int)AT_SMEM);
  }
  const CUtensorMap tm_h   = make_map_2d(enc, p_h, T_D, T_SEQ, T_D * 2, 64, 128);
  const CUtensorMap tm_wq  = make_map_3d(enc, wq, T_DQKV, T_D, 64, 4);
  const CUtensorMap tm_k   = make_map_3d(enc, kc, T_DH, (uint64_t)T_NH * T_SEQ, 128, 2);
  const CUtensorMap tm_v   = make_map_3d(enc, vc, T_DH, (uint64_t)T_NH * T_SEQ, 128, 2);
  const CUtensorMap tm_ost = make_map_2d(enc, p_o, T_DQKV, T_SEQ, T_DQKV * 2, 64, 64);
  const CUtensorMap tm_old = make_map_2d(enc, p_o, T_DQKV, T_SEQ, T_DQKV * 2, 64, 128);
  const CUtensorMap tm_wo  = make_map_3d(enc, wo, T_D, T_DQKV, 64, 2);
  const CUtensorMap tm_d   = make_map_3d(enc, w_down, T_D, T_F, 32, 8);

  const CUtensorMap tm_m   = make_map_2d(enc, w_mod, 6 * T_D, T_D, 6 * T_D * 2, 64, 256);
  const CUtensorMap tm_out = make_map_2d(enc, out, T_D, T_SEQ, T_D * 2, 64, 16);

  fused_kernel<<<132, 384, AT_SMEM, cudaStreamPerThread>>>(tm_h, tm_wq, tm_k, tm_v, tm_ost, tm_old, tm_wo, tm_d, tm_out, tm_m, 0u, (const uint8_t*)wo, kc, vc, x, cvec, w_mod,
             w_r, w_gate, w_up, w_down, out);
}
```

```cpp
#include <cuda_runtime.h>
#include <cuda_bf16.h>
#include <cuda.h>
#include <stdint.h>

namespace {

typedef __nv_bfloat16 bf16;

constexpr int T_SEQ = 2048, T_D = 1024, T_NH = 32, T_DH = 128, T_DQKV = 4096, T_F = 3584;

#define PRE_X 2
__device__ __align__(1024) uint4 g_pre[(16 * PRE_X + 128) * 2048];
#define g_h (reinterpret_cast<bf16*>(g_pre + 16 * PRE_X * 2048))
__device__ __align__(1024) bf16 g_o[T_SEQ * T_DQKV];
__device__ __align__(16) uint8_t g_col[8 * 1536];
__device__ __align__(16) float g_scal[64];
__device__ __align__(16) unsigned int g_hcnt[17 * 32];
__device__ __align__(128) float g_modpart[4 * 2 * T_D];
struct __align__(2048) TailMail {
  float4 part1[T_SEQ * 8];
  uint32_t key[256];
  uint4 cand[16 * 2 * 2 * 128];
  uint32_t cnt[32];
  float ypart[(T_F / 32) * 2 * T_D];
};
__device__ TailMail g_mail;
#define g_part1 g_mail.part1
#define g_key g_mail.key
#define g_cand g_mail.cand
#define CNT_Y (g_mail.cnt)
#define g_ypart g_mail.ypart

__device__ __forceinline__ uint32_t smem_u32(const void* p) { return (uint32_t)__cvta_generic_to_shared(p); }
__device__ __forceinline__ void mbar_init(uint32_t bar, uint32_t cnt) { asm volatile("mbarrier.init.shared::cta.b64 [%0], %1;" :: "r"(bar), "r"(cnt)); }
__device__ __forceinline__ void mbar_expect_tx(uint32_t bar, uint32_t bytes) { asm volatile("mbarrier.arrive.expect_tx.shared::cta.b64 _, [%0], %1;" :: "r"(bar), "r"(bytes) : "memory"); }
__device__ __forceinline__ void mbar_arrive(uint32_t bar) { asm volatile("mbarrier.arrive.shared::cta.b64 _, [%0];" :: "r"(bar) : "memory"); }
__device__ __forceinline__ void mbar_wait(uint32_t bar, uint32_t parity) {
  asm volatile("{\n.reg .pred p;\nLAB_WAIT:\nmbarrier.try_wait.parity.shared::cta.b64 p, [%0], %1;\n@!p bra LAB_WAIT;\n}\n" :: "r"(bar), "r"(parity) : "memory");
}
__device__ __forceinline__ bool mbar_test(uint32_t bar, uint32_t parity) {
  uint32_t r; asm volatile("{\n.reg .pred p;\nmbarrier.test_wait.parity.shared::cta.b64 p, [%1], %2;\nselp.u32 %0, 1, 0, p;\n}\n" : "=r"(r) : "r"(bar), "r"(parity) : "memory");
  return r != 0;
}
__device__ __forceinline__ void mbar_wait_long(uint32_t bar, uint32_t parity) {
  asm volatile("{\n.reg .pred p;\nLAB_WAIT:\nmbarrier.try_wait.parity.shared::cta.b64 p, [%0], %1, %2;\n@!p bra LAB_WAIT;\n}\n" :: "r"(bar), "r"(parity), "r"(100000) : "memory");
}
__device__ __forceinline__ uint32_t clock_lo() { uint32_t c; asm volatile("mov.u32 %0, %%clock;" : "=r"(c)); return c; }
__device__ __forceinline__ void fence_mbar_init() { asm volatile("fence.mbarrier_init.release.cluster;" ::: "memory"); }
__device__ __forceinline__ void tma_load_2d(uint32_t dst, const CUtensorMap* map, int c0, int c1, uint32_t bar) {
  asm volatile("cp.async.bulk.tensor.2d.shared::cluster.global.mbarrier::complete_tx::bytes [%0], [%1, {%3, %4}], [%2];"
    :: "r"(dst), "l"(map), "r"(bar), "r"(c0), "r"(c1) : "memory");
}
__device__ __forceinline__ uint64_t policy_evict_first() {
  uint64_t p; asm volatile("createpolicy.fractional.L2::evict_first.b64 %0, 1.0;" : "=l"(p)); return p;
}
__device__ __forceinline__ void tma_load_2d_hint(uint32_t dst, const CUtensorMap* map, int c0, int c1, uint32_t bar, uint64_t pol) {
  asm volatile("cp.async.bulk.tensor.2d.shared::cluster.global.mbarrier::complete_tx::bytes.L2::cache_hint [%0], [%1, {%3, %4}], [%2], %5;"
    :: "r"(dst), "l"(map), "r"(bar), "r"(c0), "r"(c1), "l"(pol) : "memory");
}
__device__ __forceinline__ void tma_load_3d_hint(uint32_t dst, const CUtensorMap* map, int c1, int c2, uint32_t bar, uint64_t pol) {
  asm volatile("cp.async.bulk.tensor.3d.shared::cluster.global.mbarrier::complete_tx::bytes.L2::cache_hint [%0], [%1, {%3, %4, %5}], [%2], %6;"
    :: "r"(dst), "l"(map), "r"(bar), "n"(0), "r"(c1), "r"(c2), "l"(pol) : "memory");
}
__device__ __forceinline__ void tma_load_3d(uint32_t dst, const CUtensorMap* map, int c1, int c2, uint32_t bar) {
  asm volatile("cp.async.bulk.tensor.3d.shared::cluster.global.mbarrier::complete_tx::bytes [%0], [%1, {%3, %4, %5}], [%2];"
    :: "r"(dst), "l"(map), "r"(bar), "n"(0), "r"(c1), "r"(c2) : "memory");
}
__device__ __forceinline__ void tma_store_2d(const CUtensorMap* map, uint32_t src, int c0, int c1) {
  asm volatile("cp.async.bulk.tensor.2d.global.shared::cta.bulk_group [%0, {%2, %3}], [%1];" :: "l"(map), "r"(src), "r"(c0), "r"(c1) : "memory");
}
__device__ __forceinline__ void prefetch_tmap(const CUtensorMap* map) { asm volatile("prefetch.tensormap [%0];" :: "l"(map) : "memory"); }
__device__ __forceinline__ void l2_prefetch_bulk(const void* p, uint32_t bytes) {
  asm volatile("cp.async.bulk.prefetch.L2.global [%0], %1;" :: "l"(p), "r"(bytes) : "memory");
}
__device__ __forceinline__ void bulk_commit() { asm volatile("cp.async.bulk.commit_group;" ::: "memory"); }
template<int N> __device__ __forceinline__ void bulk_wait_read() { asm volatile("cp.async.bulk.wait_group.read %0;" :: "n"(N) : "memory"); }
template<int N> __device__ __forceinline__ void bulk_wait() { asm volatile("cp.async.bulk.wait_group %0;" :: "n"(N) : "memory"); }
__device__ __forceinline__ void named_bar_sync(int id, int nthreads) { asm volatile("bar.sync %0, %1;" :: "r"(id), "r"(nthreads) : "memory"); }
__device__ __forceinline__ void named_bar_arrive(int id, int nthreads) { asm volatile("bar.arrive %0, %1;" :: "r"(id), "r"(nthreads) : "memory"); }
__device__ __forceinline__ void pass_turn(int cwg) {
  asm volatile("{\n.reg .pred p;\nsetp.ne.u32 p, %0, 0;\n@p bar.arrive 1, 256;\n@!p bar.arrive 2, 256;\n}\n" :: "r"(cwg) : "memory");
}
__device__ __forceinline__ void wgmma_fence() { asm volatile("wgmma.fence.sync.aligned;" ::: "memory"); }
__device__ __forceinline__ void wgmma_commit() { asm volatile("wgmma.commit_group.sync.aligned;" ::: "memory"); }
template<int N> __device__ __forceinline__ void wgmma_wait() { asm volatile("wgmma.wait_group.sync.aligned %0;" :: "n"(N) : "memory"); }
template<int R> __device__ __forceinline__ void reg_alloc() { asm volatile("setmaxnreg.inc.sync.aligned.u32 %0;" :: "n"(R)); }
template<int R> __device__ __forceinline__ void reg_dealloc() { asm volatile("setmaxnreg.dec.sync.aligned.u32 %0;" :: "n"(R)); }
__device__ __forceinline__ bool elect_one() {
  uint32_t pred; asm volatile("{\n.reg .pred p;\nelect.sync _|p, 0xffffffff;\nselp.u32 %0, 1, 0, p;\n}\n" : "=r"(pred)); return pred != 0;
}
__device__ __forceinline__ uint32_t pack_bf16(float lo, float hi) {
  uint32_t r; asm("cvt.rn.bf16x2.f32 %0, %1, %2;" : "=r"(r) : "f"(hi), "f"(lo)); return r;
}
__device__ __forceinline__ void stmatrix_x4(uint32_t addr, uint32_t r0, uint32_t r1, uint32_t r2, uint32_t r3) {
  asm volatile("stmatrix.sync.aligned.m8n8.x4.shared.b16 [%0], {%1, %2, %3, %4};" :: "r"(addr), "r"(r0), "r"(r1), "r"(r2), "r"(r3) : "memory");
}
__device__ __forceinline__ void fence_proxy_async() { asm volatile("fence.proxy.async.shared::cta;" ::: "memory"); }
__device__ __forceinline__ float ex2_approx(float x) { float y; asm("ex2.approx.ftz.f32 %0, %1;" : "=f"(y) : "f"(x)); return y; }
template<int N> __device__ __forceinline__ void fence_regs(float (&r)[N]) {
  #pragma unroll
  for (int i = 0; i < N; i++) asm volatile("" : "+f"(r[i]) :: "memory");
}
template<int N> __device__ __forceinline__ void zero_regs(float (&r)[N]) {
  #pragma unroll
  for (int i = 0; i < N; i += 2) asm volatile("mov.b64 {%0, %1}, 0;" : "=f"(r[i]), "=f"(r[i + 1]));
}
__device__ __forceinline__ float rbf(float x) { return __uint_as_float(pack_bf16(0.f, x)); }
__device__ __forceinline__ float bflo(uint32_t v) { return __uint_as_float(v << 16); }
__device__ __forceinline__ float bfhi(uint32_t v) { return __uint_as_float(v & 0xffff0000u); }

#define XT(i) do {} while (0)
#define TL_START(k) do {} while (0)
#define TL_END(k, cond) do {} while (0)
#define TL_CTA(i, cond) do {} while (0)
#define FS(slot, k) do {} while (0)
#define TL_MARK2(k, cond) do {} while (0)
#define TL_CLK(k, i, cond) do {} while (0)

template <int OFFA, int OFFB>
__device__ __forceinline__ void wgmma_m64n256k16_ss_tb(float (&d)[128], uint32_t a_lo, uint32_t b_lo, int scaleD) {
  asm volatile("{\n.reg .pred p;\n.reg .b64 da, db;\nsetp.ne.b32 p, %130, 0;\n"
    "mov.b64 da, {%128, 0x40000040};\nmov.b64 db, {%129, 0x40000040};\n"
    "add.s64 da, da, %131;\nadd.s64 db, db, %132;\n"
    "wgmma.mma_async.sync.aligned.m64n256k16.f32.bf16.bf16 "
    "{%0, %1, %2, %3, %4, %5, %6, %7, %8, %9, %10, %11, %12, %13, %14, %15, %16, %17, %18, %19, %20, %21, %22, %23, %24, %25, %26, %27, %28, %29, %30, %31, %32, %33, %34, %35, %36, %37, %38, %39, %40, %41, %42, %43, %44, %45, %46, %47, %48, %49, %50, %51, %52, %53, %54, %55, %56, %57, %58, %59, %60, %61, %62, %63, %64, %65, %66, %67, %68, %69, %70, %71, %72, %73, %74, %75, %76, %77, %78, %79, %80, %81, %82, %83, %84, %85, %86, %87, %88, %89, %90, %91, %92, %93, %94, %95, %96, %97, %98, %99, %100, %101, %102, %103, %104, %105, %106, %107, %108, %109, %110, %111, %112, %113, %114, %115, %116, %117, %118, %119, %120, %121, %122, %123, %124, %125, %126, %127}, "
    "da, db, p, 1, 1, 0, 1;\n}\n"
    : "+f"(d[0]), "+f"(d[1]), "+f"(d[2]), "+f"(d[3]), "+f"(d[4]), "+f"(d[5]), "+f"(d[6]), "+f"(d[7]), "+f"(d[8]), "+f"(d[9]), "+f"(d[10]), "+f"(d[11]), "+f"(d[12]), "+f"(d[13]), "+f"(d[14]), "+f"(d[15]), "+f"(d[16]), "+f"(d[17]), "+f"(d[18]), "+f"(d[19]), "+f"(d[20]), "+f"(d[21]), "+f"(d[22]), "+f"(d[23]), "+f"(d[24]), "+f"(d[25]), "+f"(d[26]), "+f"(d[27]), "+f"(d[28]), "+f"(d[29]), "+f"(d[30]), "+f"(d[31]), "+f"(d[32]), "+f"(d[33]), "+f"(d[34]), "+f"(d[35]), "+f"(d[36]), "+f"(d[37]), "+f"(d[38]), "+f"(d[39]), "+f"(d[40]), "+f"(d[41]), "+f"(d[42]), "+f"(d[43]), "+f"(d[44]), "+f"(d[45]), "+f"(d[46]), "+f"(d[47]), "+f"(d[48]), "+f"(d[49]), "+f"(d[50]), "+f"(d[51]), "+f"(d[52]), "+f"(d[53]), "+f"(d[54]), "+f"(d[55]), "+f"(d[56]), "+f"(d[57]), "+f"(d[58]), "+f"(d[59]), "+f"(d[60]), "+f"(d[61]), "+f"(d[62]), "+f"(d[63]), "+f"(d[64]), "+f"(d[65]), "+f"(d[66]), "+f"(d[67]), "+f"(d[68]), "+f"(d[69]), "+f"(d[70]), "+f"(d[71]), "+f"(d[72]), "+f"(d[73]), "+f"(d[74]), "+f"(d[75]), "+f"(d[76]), "+f"(d[77]), "+f"(d[78]), "+f"(d[79]), "+f"(d[80]), "+f"(d[81]), "+f"(d[82]), "+f"(d[83]), "+f"(d[84]), "+f"(d[85]), "+f"(d[86]), "+f"(d[87]), "+f"(d[88]), "+f"(d[89]), "+f"(d[90]), "+f"(d[91]), "+f"(d[92]), "+f"(d[93]), "+f"(d[94]), "+f"(d[95]), "+f"(d[96]), "+f"(d[97]), "+f"(d[98]), "+f"(d[99]), "+f"(d[100]), "+f"(d[101]), "+f"(d[102]), "+f"(d[103]), "+f"(d[104]), "+f"(d[105]), "+f"(d[106]), "+f"(d[107]), "+f"(d[108]), "+f"(d[109]), "+f"(d[110]), "+f"(d[111]), "+f"(d[112]), "+f"(d[113]), "+f"(d[114]), "+f"(d[115]), "+f"(d[116]), "+f"(d[117]), "+f"(d[118]), "+f"(d[119]), "+f"(d[120]), "+f"(d[121]), "+f"(d[122]), "+f"(d[123]), "+f"(d[124]), "+f"(d[125]), "+f"(d[126]), "+f"(d[127])
    : "r"(a_lo), "r"(b_lo), "r"(scaleD), "n"(OFFA), "n"(OFFB));
}

template <int OFFA, int OFFB>
__device__ __forceinline__ void wgmma_m64n128k16_ss_tb(float (&d)[64], uint32_t a_lo, uint32_t b_lo, int scaleD) {
  asm volatile("{\n.reg .pred p;\n.reg .b64 da, db;\nsetp.ne.b32 p, %66, 0;\n"
    "mov.b64 da, {%64, 0x40000040};\nmov.b64 db, {%65, 0x40000040};\n"
    "add.s64 da, da, %67;\nadd.s64 db, db, %68;\n"
    "wgmma.mma_async.sync.aligned.m64n128k16.f32.bf16.bf16 "
    "{%0, %1, %2, %3, %4, %5, %6, %7, %8, %9, %10, %11, %12, %13, %14, %15, %16, %17, %18, %19, %20, %21, %22, %23, %24, %25, %26, %27, %28, %29, %30, %31, %32, %33, %34, %35, %36, %37, %38, %39, %40, %41, %42, %43, %44, %45, %46, %47, %48, %49, %50, %51, %52, %53, %54, %55, %56, %57, %58, %59, %60, %61, %62, %63}, "
    "da, db, p, 1, 1, 0, 1;\n}\n"
    : "+f"(d[0]), "+f"(d[1]), "+f"(d[2]), "+f"(d[3]), "+f"(d[4]), "+f"(d[5]), "+f"(d[6]), "+f"(d[7]), "+f"(d[8]), "+f"(d[9]), "+f"(d[10]), "+f"(d[11]), "+f"(d[12]), "+f"(d[13]), "+f"(d[14]), "+f"(d[15]), "+f"(d[16]), "+f"(d[17]), "+f"(d[18]), "+f"(d[19]), "+f"(d[20]), "+f"(d[21]), "+f"(d[22]), "+f"(d[23]), "+f"(d[24]), "+f"(d[25]), "+f"(d[26]), "+f"(d[27]), "+f"(d[28]), "+f"(d[29]), "+f"(d[30]), "+f"(d[31]), "+f"(d[32]), "+f"(d[33]), "+f"(d[34]), "+f"(d[35]), "+f"(d[36]), "+f"(d[37]), "+f"(d[38]), "+f"(d[39]), "+f"(d[40]), "+f"(d[41]), "+f"(d[42]), "+f"(d[43]), "+f"(d[44]), "+f"(d[45]), "+f"(d[46]), "+f"(d[47]), "+f"(d[48]), "+f"(d[49]), "+f"(d[50]), "+f"(d[51]), "+f"(d[52]), "+f"(d[53]), "+f"(d[54]), "+f"(d[55]), "+f"(d[56]), "+f"(d[57]), "+f"(d[58]), "+f"(d[59]), "+f"(d[60]), "+f"(d[61]), "+f"(d[62]), "+f"(d[63])
    : "r"(a_lo), "r"(b_lo), "r"(scaleD), "n"(OFFA), "n"(OFFB));
}

template <int OFFB>
__device__ __forceinline__ void wgmma_m64n128k16_rs_tb(float (&d)[64], uint32_t a0, uint32_t a1, uint32_t a2, uint32_t a3, uint32_t b_lo, int scaleD) {
  asm volatile("{\n.reg .pred p;\n.reg .b64 db;\nsetp.ne.b32 p, %69, 0;\n"
    "mov.b64 db, {%68, 0x40000040};\nadd.s64 db, db, %70;\n"
    "wgmma.mma_async.sync.aligned.m64n128k16.f32.bf16.bf16 "
    "{%0, %1, %2, %3, %4, %5, %6, %7, %8, %9, %10, %11, %12, %13, %14, %15, %16, %17, %18, %19, %20, %21, %22, %23, %24, %25, %26, %27, %28, %29, %30, %31, %32, %33, %34, %35, %36, %37, %38, %39, %40, %41, %42, %43, %44, %45, %46, %47, %48, %49, %50, %51, %52, %53, %54, %55, %56, %57, %58, %59, %60, %61, %62, %63}, "
    "{%64, %65, %66, %67}, db, p, 1, 1, 1;\n}\n"
    : "+f"(d[0]), "+f"(d[1]), "+f"(d[2]), "+f"(d[3]), "+f"(d[4]), "+f"(d[5]), "+f"(d[6]), "+f"(d[7]), "+f"(d[8]), "+f"(d[9]), "+f"(d[10]), "+f"(d[11]), "+f"(d[12]), "+f"(d[13]), "+f"(d[14]), "+f"(d[15]), "+f"(d[16]), "+f"(d[17]), "+f"(d[18]), "+f"(d[19]), "+f"(d[20]), "+f"(d[21]), "+f"(d[22]), "+f"(d[23]), "+f"(d[24]), "+f"(d[25]), "+f"(d[26]), "+f"(d[27]), "+f"(d[28]), "+f"(d[29]), "+f"(d[30]), "+f"(d[31]), "+f"(d[32]), "+f"(d[33]), "+f"(d[34]), "+f"(d[35]), "+f"(d[36]), "+f"(d[37]), "+f"(d[38]), "+f"(d[39]), "+f"(d[40]), "+f"(d[41]), "+f"(d[42]), "+f"(d[43]), "+f"(d[44]), "+f"(d[45]), "+f"(d[46]), "+f"(d[47]), "+f"(d[48]), "+f"(d[49]), "+f"(d[50]), "+f"(d[51]), "+f"(d[52]), "+f"(d[53]), "+f"(d[54]), "+f"(d[55]), "+f"(d[56]), "+f"(d[57]), "+f"(d[58]), "+f"(d[59]), "+f"(d[60]), "+f"(d[61]), "+f"(d[62]), "+f"(d[63])
    : "r"(a0), "r"(a1), "r"(a2), "r"(a3), "r"(b_lo), "r"(scaleD), "n"(OFFB));
}

template <int OFFB>
__device__ __forceinline__ void wgmma_m64n128k16_rs(float (&d)[64], uint32_t a0, uint32_t a1, uint32_t a2, uint32_t a3, uint32_t b_lo, int scaleD) {
  asm volatile("{\n.reg .pred p;\n.reg .b64 db;\nsetp.ne.b32 p, %69, 0;\n"
    "mov.b64 db, {%68, 0x40000040};\nadd.s64 db, db, %70;\n"
    "wgmma.mma_async.sync.aligned.m64n128k16.f32.bf16.bf16 "
    "{%0, %1, %2, %3, %4, %5, %6, %7, %8, %9, %10, %11, %12, %13, %14, %15, %16, %17, %18, %19, %20, %21, %22, %23, %24, %25, %26, %27, %28, %29, %30, %31, %32, %33, %34, %35, %36, %37, %38, %39, %40, %41, %42, %43, %44, %45, %46, %47, %48, %49, %50, %51, %52, %53, %54, %55, %56, %57, %58, %59, %60, %61, %62, %63}, "
    "{%64, %65, %66, %67}, db, p, 1, 1, 0;\n}\n"
    : "+f"(d[0]), "+f"(d[1]), "+f"(d[2]), "+f"(d[3]), "+f"(d[4]), "+f"(d[5]), "+f"(d[6]), "+f"(d[7]), "+f"(d[8]), "+f"(d[9]), "+f"(d[10]), "+f"(d[11]), "+f"(d[12]), "+f"(d[13]), "+f"(d[14]), "+f"(d[15]), "+f"(d[16]), "+f"(d[17]), "+f"(d[18]), "+f"(d[19]), "+f"(d[20]), "+f"(d[21]), "+f"(d[22]), "+f"(d[23]), "+f"(d[24]), "+f"(d[25]), "+f"(d[26]), "+f"(d[27]), "+f"(d[28]), "+f"(d[29]), "+f"(d[30]), "+f"(d[31]), "+f"(d[32]), "+f"(d[33]), "+f"(d[34]), "+f"(d[35]), "+f"(d[36]), "+f"(d[37]), "+f"(d[38]), "+f"(d[39]), "+f"(d[40]), "+f"(d[41]), "+f"(d[42]), "+f"(d[43]), "+f"(d[44]), "+f"(d[45]), "+f"(d[46]), "+f"(d[47]), "+f"(d[48]), "+f"(d[49]), "+f"(d[50]), "+f"(d[51]), "+f"(d[52]), "+f"(d[53]), "+f"(d[54]), "+f"(d[55]), "+f"(d[56]), "+f"(d[57]), "+f"(d[58]), "+f"(d[59]), "+f"(d[60]), "+f"(d[61]), "+f"(d[62]), "+f"(d[63])
    : "r"(a0), "r"(a1), "r"(a2), "r"(a3), "r"(b_lo), "r"(scaleD), "n"(OFFB));
}

__device__ __forceinline__ uint4 ldg_nc_v4(const void* p) {
  uint4 v;
    asm volatile("{\n.reg .b64 pol;\ncreatepolicy.fractional.L2::evict_first.b64 pol, 1.0;\n"
                 "ld.global.nc.L1::no_allocate.L2::cache_hint.v4.u32 {%0, %1, %2, %3}, [%4], pol;\n}\n" : "=r"(v.x), "=r"(v.y), "=r"(v.z), "=r"(v.w) : "l"(p));
  return v;
}
__device__ __forceinline__ void unpack8(const uint4& u, float (&v)[8]) {
  v[0] = bflo(u.x); v[1] = bfhi(u.x); v[2] = bflo(u.y); v[3] = bfhi(u.y);
  v[4] = bflo(u.z); v[5] = bfhi(u.z); v[6] = bflo(u.w); v[7] = bfhi(u.w);
}
__device__ __forceinline__ void fma8(float (&acc)[8], float s, const uint4& w) {
  acc[0] = fmaf(s, bflo(w.x), acc[0]); acc[1] = fmaf(s, bfhi(w.x), acc[1]); acc[2] = fmaf(s, bflo(w.y), acc[2]); acc[3] = fmaf(s, bfhi(w.y), acc[3]);
  acc[4] = fmaf(s, bflo(w.z), acc[4]); acc[5] = fmaf(s, bfhi(w.z), acc[5]); acc[6] = fmaf(s, bflo(w.w), acc[6]); acc[7] = fmaf(s, bfhi(w.w), acc[7]);
}
__device__ __forceinline__ float rcp_approx(float x) { float y; asm("rcp.approx.ftz.f32 %0, %1;" : "=f"(y) : "f"(x)); return y; }
__device__ __forceinline__ float sigmoid_f(float v) { return rcp_approx(1.0f + ex2_approx(v * -1.4426950408889634f)); }
__device__ __forceinline__ float silu_bf(float v) { return rbf(v * sigmoid_f(v)); }
__device__ __forceinline__ uint32_t rank_key(float r, int idx) {
  const uint32_t b = __float_as_uint(r) >> 16;
  const uint32_t u = (r != r) ? 0u : ((b & 0x8000u) ? (~b & 0xffffu) : (b | 0x8000u));
  return (u << 16) | (0xffffu - (uint32_t)idx);
}
__device__ __forceinline__ void warp_top2(uint32_t& k1, uint32_t& k2) {
  const uint32_t m1 = __reduce_max_sync(0xffffffffu, k1);
  k2 = __reduce_max_sync(0xffffffffu, k1 == m1 ? k2 : k1);
  k1 = m1;
}
__device__ __forceinline__ uint32_t bmul2(uint32_t a, uint32_t b) { uint32_t r; asm("mul.rn.bf16x2 %0, %1, %2;" : "=r"(r) : "r"(a), "r"(b)); return r; }
__device__ __forceinline__ uint32_t badd2(uint32_t a, uint32_t b) { uint32_t r; asm("add.rn.bf16x2 %0, %1, %2;" : "=r"(r) : "r"(a), "r"(b)); return r; }
__device__ __forceinline__ uint32_t bsub2(uint32_t a, uint32_t b) { uint32_t r; asm("sub.rn.bf16x2 %0, %1, %2;" : "=r"(r) : "r"(a), "r"(b)); return r; }
__device__ __forceinline__ float sqrt_approx(float x) { float y; asm("sqrt.approx.f32 %0, %1;" : "=f"(y) : "f"(x)); return y; }
__device__ __forceinline__ uint32_t ln_norm2(uint32_t x1, uint32_t mb2, float inv) {
  const uint32_t d = bsub2(x1, mb2);
  return pack_bf16(bflo(d) * inv, bfhi(d) * inv);
}
__device__ __forceinline__ uint32_t bfma2(uint32_t a, uint32_t b, uint32_t c) { uint32_t r; asm("fma.rn.bf16x2 %0, %1, %2, %3;" : "=r"(r) : "r"(a), "r"(b), "r"(c)); return r; }
__device__ __forceinline__ uint32_t ln_norm2b(uint32_t x1, uint32_t mb2, uint32_t ih, uint32_t il) {
  const uint32_t d = bsub2(x1, mb2);
  return bfma2(d, ih, bmul2(d, il));
}
__device__ __forceinline__ uint32_t ln_mod2(uint32_t x1, uint32_t mb2, float inv, uint32_t c1, uint32_t sb) { return badd2(bmul2(ln_norm2(x1, mb2, inv), c1), sb); }
__device__ __forceinline__ void ldmatrix_x4(uint32_t addr, uint32_t& r0, uint32_t& r1, uint32_t& r2, uint32_t& r3) {
  asm volatile("ldmatrix.sync.aligned.m8n8.x4.shared.b16 {%0, %1, %2, %3}, [%4];" : "=r"(r0), "=r"(r1), "=r"(r2), "=r"(r3) : "r"(addr) : "memory");
}
__device__ __forceinline__ uint4 ldg_stream_v4(const void* p, uint64_t pol) {
  uint4 v; asm volatile("ld.global.nc.L1::no_allocate.L2::cache_hint.L2::128B.v4.u32 {%0, %1, %2, %3}, [%4], %5;" : "=r"(v.x), "=r"(v.y), "=r"(v.z), "=r"(v.w) : "l"(p), "l"(pol)); return v;
}
__device__ __forceinline__ void bulk_load_hint(uint32_t dst, const void* src, uint32_t bytes, uint32_t bar, uint64_t pol) {
  asm volatile("cp.async.bulk.shared::cluster.global.mbarrier::complete_tx::bytes.L2::cache_hint [%0], [%1], %2, [%3], %4;"
    :: "r"(dst), "l"(src), "r"(bytes), "r"(bar), "l"(pol) : "memory");
}
__device__ __forceinline__ void red_release_add(unsigned int* p, unsigned int v) { asm volatile("red.release.gpu.global.add.u32 [%0], %1;" :: "l"(p), "r"(v) : "memory"); }
__device__ __forceinline__ unsigned int ld_acquire(const unsigned int* p) { unsigned int v; asm volatile("ld.acquire.gpu.global.u32 %0, [%1];" : "=r"(v) : "l"(p) : "memory"); return v; }
__device__ __forceinline__ void spin_until(const unsigned int* p, unsigned int target) {
  #pragma unroll 1
  for (unsigned int i = 0; i < (1u << 22); i++) { if (ld_acquire(p) >= target) return; }
}
__device__ __forceinline__ float lds_f32(uint32_t a) { float v; asm volatile("ld.shared.f32 %0, [%1];" : "=f"(v) : "r"(a) : "memory"); return v; }
__device__ __forceinline__ float2 lds_f32x2(uint32_t a) { float2 v; asm volatile("ld.shared.v2.f32 {%0, %1}, [%2];" : "=f"(v.x), "=f"(v.y) : "r"(a) : "memory"); return v; }
__device__ __forceinline__ uint2 lds_u32x2(uint32_t a) { uint2 v; asm volatile("ld.shared.v2.u32 {%0, %1}, [%2];" : "=r"(v.x), "=r"(v.y) : "r"(a) : "memory"); return v; }
__device__ __forceinline__ uint32_t lds_u32(uint32_t a) { uint32_t v; asm volatile("ld.shared.u32 %0, [%1];" : "=r"(v) : "r"(a) : "memory"); return v; }
__device__ __forceinline__ void sts_u32(uint32_t a, uint32_t v) { asm volatile("st.shared.u32 [%0], %1;" :: "r"(a), "r"(v) : "memory"); }
__device__ __forceinline__ void sts_u32x2(uint32_t a, uint32_t x, uint32_t y) { asm volatile("st.shared.v2.u32 [%0], {%1, %2};" :: "r"(a), "r"(x), "r"(y) : "memory"); }
__device__ __forceinline__ void sts_f32(uint32_t a, float v) { asm volatile("st.shared.f32 [%0], %1;" :: "r"(a), "f"(v) : "memory"); }
__device__ __forceinline__ void sts_f32x2(uint32_t a, float x, float y) { asm volatile("st.shared.v2.f32 [%0], {%1, %2};" :: "r"(a), "f"(x), "f"(y) : "memory"); }
__device__ __forceinline__ void sts_f32x4(uint32_t a, float x, float y, float z, float w) { asm volatile("st.shared.v4.f32 [%0], {%1, %2, %3, %4};" :: "r"(a), "f"(x), "f"(y), "f"(z), "f"(w) : "memory"); }

__device__ __forceinline__ uint4 lds_u32x4(uint32_t a) { uint4 v; asm volatile("ld.shared.v4.u32 {%0, %1, %2, %3}, [%4];" : "=r"(v.x), "=r"(v.y), "=r"(v.z), "=r"(v.w) : "r"(a) : "memory"); return v; }
__device__ __forceinline__ void sts_u32x4(uint32_t a, uint32_t x, uint32_t y, uint32_t z, uint32_t w) { asm volatile("st.shared.v4.u32 [%0], {%1, %2, %3, %4};" :: "r"(a), "r"(x), "r"(y), "r"(z), "r"(w) : "memory"); }
__device__ __forceinline__ void st_tagged(float* p, float v) {
  const uint32_t b = __float_as_uint(v);
  asm volatile("st.relaxed.gpu.global.u32 [%0], %1;" :: "l"(p), "r"(b == 0u ? 0x80000000u : b) : "memory");
}
__device__ __forceinline__ void st_tagged4(float* p, float x, float y, float z, float w) {
  const uint32_t a = __float_as_uint(x), b = __float_as_uint(y), c = __float_as_uint(z), d = __float_as_uint(w);
  asm volatile("st.relaxed.gpu.global.v4.u32 [%0], {%1, %2, %3, %4};" :: "l"(p), "r"(a == 0u ? 0x80000000u : a), "r"(b == 0u ? 0x80000000u : b),
               "r"(c == 0u ? 0x80000000u : c), "r"(d == 0u ? 0x80000000u : d) : "memory");
}
__device__ __forceinline__ void st_tagged4_lsb(float* p, float x, float y, float z, float w) {
  asm volatile("st.relaxed.gpu.global.v4.u32 [%0], {%1, %2, %3, %4};" :: "l"(p), "r"(__float_as_uint(x) | 1u), "r"(__float_as_uint(y) | 1u),
               "r"(__float_as_uint(z) | 1u), "r"(__float_as_uint(w) | 1u) : "memory");
}
__device__ __forceinline__ void st_relaxed2(void* p, uint32_t a, uint32_t b) { asm volatile("st.relaxed.gpu.global.v2.u32 [%0], {%1, %2};" :: "l"(p), "r"(a), "r"(b) : "memory"); }
__device__ __forceinline__ float4 ld_tagged4(const float* p) {
  float4 v; asm volatile("ld.relaxed.gpu.global.v4.f32 {%0, %1, %2, %3}, [%4];" : "=f"(v.x), "=f"(v.y), "=f"(v.z), "=f"(v.w) : "l"(p) : "memory"); return v;
}
__device__ __forceinline__ bool tagged4(const float4& v) {
  return __float_as_uint(v.x) != 0u && __float_as_uint(v.y) != 0u && __float_as_uint(v.z) != 0u && __float_as_uint(v.w) != 0u;
}
__device__ __forceinline__ void hint_arrive(uint32_t* p) { asm volatile("red.relaxed.gpu.global.add.u32 [%0], 1;" :: "l"(p) : "memory"); }
__device__ __forceinline__ void hint_wait(const uint32_t* p, uint32_t target) {
  uint32_t v = 0u;
  #pragma unroll 1
  for (unsigned int i = 0; i < (1u << 22) && v < target; i++) asm volatile("ld.relaxed.gpu.global.u32 %0, [%1];" : "=r"(v) : "l"(p) : "memory");
}
__device__ __forceinline__ void fence_proxy_async_global() { asm volatile("fence.proxy.async.global;" ::: "memory"); }

#define H_SPLIT 1
#define X_DLY 1200
#define W_DLY 1900
#define W_FIRST 2200
#define PRE_B 2
template <int J0, int J1>
__device__ __forceinline__ void load_parts(float2 (&pa)[J1 - J0][4], int t2) {
  #pragma unroll
  for (int j = J0; j < J1; j++)
    #pragma unroll
    for (int k = 0; k < 4; k++)
      asm volatile("ld.relaxed.gpu.global.v2.f32 {%0, %1}, [%2];" : "=f"(pa[j - J0][k].x), "=f"(pa[j - J0][k].y)
                   : "l"(g_modpart + k * 2 * T_D + (t2 >> 7) * T_D + j * 256 + (t2 & 127) * 2) : "memory");
}
template <int J0, int J1>
__device__ __forceinline__ void finish_parts(float2 (&pa)[J1 - J0][4], bool loaded, int t2, uint32_t tab) {
  #pragma unroll 1
  for (unsigned int spin = 0; spin < (1u << 22); spin++) {
    if (!loaded) load_parts<J0, J1>(pa, t2);
    loaded = false;
    bool ok = true;
    #pragma unroll
    for (int j = 0; j < J1 - J0; j++)
      #pragma unroll
      for (int k = 0; k < 4; k++) ok &= (__float_as_uint(pa[j][k].x) != 0u) & (__float_as_uint(pa[j][k].y) != 0u);
    if (__all_sync(0xffffffffu, ok)) break;
  }
  #pragma unroll
  for (int j = J0; j < J1; j++) {
    const float2* q = pa[j - J0];
    const uint32_t m = pack_bf16(((q[0].x + q[1].x) + q[2].x) + q[3].x, ((q[0].y + q[1].y) + q[2].y) + q[3].y);
    sts_u32(tab + (t2 >> 7) * 2048 + j * 512 + (t2 & 127) * 4, t2 >= 128 ? badd2(m, 0x3F803F80u) : m);
  }
}
__device__ __forceinline__ int head_cb(uint32_t bid) { return (bid & 16) | ((bid & 3) << 2) | ((bid >> 2) & 3); }
__device__ __forceinline__ void head_phase(uint32_t bid, uint32_t scr, uint32_t xs, uint32_t b_x, uint32_t b_go, uint32_t b_head, int t2, uint32_t zero, const bf16* __restrict__ cvec, const bf16* __restrict__ w_mod) {
  const int lane = t2 & 31, w8 = t2 >> 5;
  const int cb = head_cb(bid), ks = bid >> 5;
  const bool early = (cb & 15) < 4 * H_SPLIT;
  const uint32_t ws = (xs - 32768 + (t2 >> 3) * 128 + (((t2 ^ (t2 >> 3)) & 7) << 4)) ^ zero;
  const float cv = __bfloat162float(cvec[ks * 256 + t2]);
  const bf16* wsrc = w_mod + (size_t)(ks * 256 + (t2 >> 3)) * (6 * T_D) + cb * 64 + (t2 & 7) * 8;
  if (early) {
    const uint64_t pol = policy_evict_first();
    #pragma unroll 2
    for (int i = 0; i < 8; i++)
      asm volatile("cp.async.cg.shared.global.L2::cache_hint [%0], [%1], 16, %2;" :: "r"(ws + i * 4096), "l"(wsrc + (size_t)i * 32 * 6 * T_D), "l"(pol) : "memory");
  }
  sts_f32(scr + t2 * 4, silu_bf(cv));
  named_bar_sync(6, 384);
  TL_MARK2(1, t2 == 0);
  uint4 xv[2][4];
  uint32_t mb2[2], ih[2], il[2];
  auto norm = [&](int j) {
    #pragma unroll
    for (int r = 0; r < 2; r++) {
      xv[r][j].x = ln_norm2b(xv[r][j].x, mb2[r], ih[r], il[r]); xv[r][j].y = ln_norm2b(xv[r][j].y, mb2[r], ih[r], il[r]);
      xv[r][j].z = ln_norm2b(xv[r][j].z, mb2[r], ih[r], il[r]); xv[r][j].w = ln_norm2b(xv[r][j].w, mb2[r], ih[r], il[r]);
    }
  };
  auto modulate = [&](int j) {
    const uint4 sa = lds_u32x4(scr + 8192 + j * 512 + lane * 16), c1 = lds_u32x4(scr + 8192 + 2048 + j * 512 + lane * 16);
    #pragma unroll
    for (int r = 0; r < 2; r++) {
      xv[r][j].x = badd2(bmul2(xv[r][j].x, c1.x), sa.x); xv[r][j].y = badd2(bmul2(xv[r][j].y, c1.y), sa.y);
      xv[r][j].z = badd2(bmul2(xv[r][j].z, c1.z), sa.z); xv[r][j].w = badd2(bmul2(xv[r][j].w, c1.w), sa.w);
    }
  };
  auto store = [&](int j) {
    #pragma unroll
    for (int r = 0; r < 2; r++) *reinterpret_cast<uint4*>(g_h + (size_t)(bid * 16 + 2 * w8 + r) * T_D + j * 256 + lane * 8) = xv[r][j];
  };
  #pragma unroll 1
  for (int ph = 0; ph < 2; ph++) {
    if ((ph == 0) == early) {
      asm volatile("cp.async.wait_all;" ::: "memory");
      if (!early) mbar_wait(b_x + 168, 0);
      float acc[8];
      #pragma unroll
      for (int j = 0; j < 8; j++) acc[j] = 0.f;
      #pragma unroll
      for (int i = 0; i < 8; i++) fma8(acc, lds_f32(scr + ((t2 >> 3) + 32 * i) * 4), lds_u32x4(ws + i * 4096));
      #pragma unroll
      for (int j = 0; j < 4; j++) { const bool up = lane & 16; acc[j] = (up ? acc[4 + j] : acc[j]) + __shfl_xor_sync(0xffffffffu, up ? acc[j] : acc[4 + j], 16); }
      #pragma unroll
      for (int j = 0; j < 2; j++) { const bool up = lane & 8; acc[j] = (up ? acc[2 + j] : acc[j]) + __shfl_xor_sync(0xffffffffu, up ? acc[j] : acc[2 + j], 8); }
      sts_f32x2(scr + 1024 + w8 * 256 + (lane & 7) * 32 + (lane >> 3) * 8, acc[0], acc[1]);
      named_bar_sync(5, 256);
      if (t2 < 64) {
        float sum = 0.f;
        #pragma unroll
        for (int i = 0; i < 8; i++) sum += lds_f32(scr + 1024 + i * 256 + t2 * 4);
        st_tagged(g_modpart + ks * 2 * T_D + cb * 64 + t2, sum);
        TL_MARK2(early ? 2 : 6, t2 == 0);
      }
    } else {
      float2 pa[H_SPLIT][4];
      mbar_wait(b_x, 0);
      TL_MARK2(18, t2 == 0);
      load_parts<0, H_SPLIT>(pa, t2);
      #pragma unroll
      for (int r = 0; r < 2; r++)
        #pragma unroll
        for (int j = 0; j < 4; j++) xv[r][j] = lds_u32x4(xs + (2 * w8 + r) * 2048 + j * 512 + lane * 16);
  {
    float st[4] = {0.f, 0.f, 0.f, 0.f};
    #pragma unroll
    for (int r = 0; r < 2; r++)
      #pragma unroll
      for (int j = 0; j < 4; j++) {
        float v[8];
        unpack8(xv[r][j], v);
        st[2 * r] += ((v[0] + v[1]) + (v[2] + v[3])) + ((v[4] + v[5]) + (v[6] + v[7]));
        st[2 * r + 1] += fmaf(v[0], v[0], fmaf(v[1], v[1], fmaf(v[2], v[2], v[3] * v[3]))) + fmaf(v[4], v[4], fmaf(v[5], v[5], fmaf(v[6], v[6], v[7] * v[7])));
      }
    #pragma unroll
    for (int k = 0; k < 2; k++) { const bool up = lane & 16; st[k] = (up ? st[2 + k] : st[k]) + __shfl_xor_sync(0xffffffffu, up ? st[k] : st[2 + k], 16); }
    #pragma unroll
    for (int o = 8; o > 0; o >>= 1) { st[0] += __shfl_xor_sync(0xffffffffu, st[0], o); st[1] += __shfl_xor_sync(0xffffffffu, st[1], o); }
    const float mean = st[0] * (1.0f / T_D);
    const float inv = rcp_approx(rbf(sqrt_approx(rbf(rbf(fmaxf(fmaf(-mean, mean, st[1] * (1.0f / T_D)), 0.f)) + 1e-05f))));
    const uint32_t m = pack_bf16(mean, mean), h = pack_bf16(inv - rbf(inv), inv);
    #pragma unroll
    for (int r = 0; r < 2; r++) {
      mb2[r] = __shfl_sync(0xffffffffu, m, 16 * r);
      const uint32_t hr = __shfl_sync(0xffffffffu, h, 16 * r);
      ih[r] = __byte_perm(hr, hr, 0x3232); il[r] = __byte_perm(hr, hr, 0x1010);
    }
  }
      #pragma unroll
      for (int j = 0; j < H_SPLIT; j++) norm(j);
      TL_MARK2(5, t2 == 0);
      finish_parts<0, H_SPLIT>(pa, true, t2, scr + 8192);
      named_bar_sync(5, 256);
      TL_MARK2(7, t2 == 0);
      #pragma unroll
      for (int j = 0; j < H_SPLIT; j++) { modulate(j); store(j); }
      named_bar_arrive(9, 288);
    }
  }
  #pragma unroll
  for (int j = H_SPLIT; j < 4; j++) norm(j);
  float2 pb[4 - H_SPLIT][4];
  finish_parts<H_SPLIT, 4>(pb, false, t2, scr + 8192);
  named_bar_sync(5, 256);
  TL_MARK2(17, t2 == 0);
  #pragma unroll
  for (int j = H_SPLIT; j < 4; j++) modulate(j);
  __syncwarp();
  if (lane == 0) mbar_arrive(b_head + (xv[1][3].w & zero));
  mbar_wait(b_go, 0);
  #pragma unroll
  for (int j = H_SPLIT; j < 4; j++) store(j);
  named_bar_arrive(8, 288);
}

#define MOD_AT (b_empty + 8)
#define MOD_SPLIT 20
__device__ __forceinline__ void mod_rest(uint32_t bid, uint32_t scr, uint32_t b_go, int t, const bf16* __restrict__ cvec, const bf16* __restrict__ w_mod, const bf16* __restrict__ w_r) {
  const int lane = t & 31;
  #pragma unroll 1
  for (int i = t; i < T_D / 2; i += 64) {
    const uint32_t c2 = *reinterpret_cast<const uint32_t*>(cvec + 2 * i);
    sts_u32(scr + i * 4, pack_bf16(silu_bf(bflo(c2)), silu_bf(bfhi(c2))));
  }
  named_bar_sync(11, 64);
  const bf16* wp = w_mod + (size_t)(2 * (t >> 2)) * (6 * T_D) + 2 * T_D + bid * 32 + (t & 3) * 8;
  float acc[8];
  #pragma unroll
  for (int i = 0; i < 8; i++) acc[i] = 0.f;
  #pragma unroll 1
  for (int i = 0; i < 32; i += 2) {
    if (i == MOD_SPLIT) mbar_wait_long(b_go, 0);
    const uint4 w0 = ldg_nc_v4(wp), w1 = ldg_nc_v4(wp + 6 * T_D), w2 = ldg_nc_v4(wp + 32 * 6 * T_D), w3 = ldg_nc_v4(wp + 33 * 6 * T_D);
    wp += 64 * 6 * T_D;
    const uint32_t s0 = lds_u32(scr + (i * 16 + (t >> 2)) * 4), s1 = lds_u32(scr + (i * 16 + 16 + (t >> 2)) * 4);
    fma8(acc, bflo(s0), w0); fma8(acc, bfhi(s0), w1); fma8(acc, bflo(s1), w2); fma8(acc, bfhi(s1), w3);
  }
  #pragma unroll
  for (int j = 0; j < 4; j++) { const bool up = lane & 16; acc[j] = (up ? acc[4 + j] : acc[j]) + __shfl_xor_sync(0xffffffffu, up ? acc[j] : acc[4 + j], 16); }
  #pragma unroll
  for (int j = 0; j < 2; j++) { const bool up = lane & 8; acc[j] = (up ? acc[2 + j] : acc[j]) + __shfl_xor_sync(0xffffffffu, up ? acc[j] : acc[2 + j], 8); }
  { const bool up = lane & 4; acc[0] = (up ? acc[1] : acc[0]) + __shfl_xor_sync(0xffffffffu, up ? acc[0] : acc[1], 4); }
  if (t >= 32) sts_f32(scr + 2048 + lane * 4, acc[0]);
  named_bar_sync(11, 64);
  if (__shfl_sync(0xffffffffu, t, 0) < 32) {
    const int kind = bid >> 5;
    float v = rbf(acc[0] + lds_f32(scr + 2048 + lane * 4));
    const int col = (bid & 31) * 32 + (lane & 3) * 8 + (lane >> 2);
    uint8_t* dst = g_col + (col >> 7) * 1536;
    if (kind == 2) v = rbf(1.0f + v);
    float vw = v * __bfloat162float(w_r[col]);
    if (kind == 2) {
      const int c = col & 127, i = (c & ~15) + ((c >> 1) & 3) * 4 + ((c >> 3) & 1) * 2 + (c & 1);
      reinterpret_cast<bf16*>(dst)[i] = __float2bfloat16_rn(vw);
      reinterpret_cast<bf16*>(dst)[128 + i] = __float2bfloat16_rn(vw - rbf(vw));
    }
    reinterpret_cast<bf16*>(dst + 512 + (kind & 1) * 512 + (kind >> 1) * 256)[col & 127] = __float2bfloat16_rn(v);
    #pragma unroll
    for (int o = 16; o > 0; o >>= 1) vw += __shfl_xor_sync(0xffffffffu, vw, o);
    if (lane == 0 && (kind == 1 || kind == 2)) g_scal[95 - bid] = vw;
  }
  #pragma unroll 1
  for (int i = bid * 64 + t; i < (int)(sizeof(g_mail) / 16); i += 128 * 64) reinterpret_cast<uint4*>(&g_mail)[i] = make_uint4(0u, 0u, 0u, 0u);
  named_bar_sync(11, 64);
  if (t == 0) red_release_add(&g_hcnt[0], 1u);
}

constexpr int AT_NBLK = T_SEQ / 128;
constexpr float AT_HEAD = 7.0f;
#define WO_LATE 12
#define QP_STAG 3
#define AT_SPLIT 28
#define AT_PIN 16
#define PINB 4
constexpr int AT_NFULL = 124;
constexpr int AT_PREG = 40, AT_CREG = 232;
constexpr uint32_t AT_SQ = 5 * 32768;
constexpr float AT_C = 0.08838834764831845f * 1.4426950408889634f;
constexpr float AT_RAW_LO = -16.0f, AT_RAW_HI = 24.0f;
constexpr float AT_RAW_SUM = 281474976710656.0f, AT_RAW_MIN = 9.094947017729282e-13f;
constexpr uint32_t AT_SBAR = AT_SQ + 65536 + 256;
constexpr uint32_t AT_SMEM = AT_SQ + 65536 + 3072;

__device__ __forceinline__ uint32_t ring_slot(uint32_t t) { return t - 5u * ((t * 205u) >> 10); }
__device__ __forceinline__ uint32_t qp_pos(uint32_t j, uint32_t it) { return 4u * it + (j & 3u) + ((j & 3u) == 3u ? it : 0u); }
__device__ __forceinline__ uint32_t ring_par(uint32_t t) { return ((t * 205u) >> 10) & 1u; }
__device__ __forceinline__ void softmax_rowmax(const float (&s)[64], float& mx0, float& mx1) {
  float a0 = fmaxf(s[0], s[1]), a1 = fmaxf(s[4], s[5]), a2 = fmaxf(s[8], s[9]), a3 = fmaxf(s[12], s[13]);
  float b0 = fmaxf(s[2], s[3]), b1 = fmaxf(s[6], s[7]), b2 = fmaxf(s[10], s[11]), b3 = fmaxf(s[14], s[15]);
  #pragma unroll
  for (int j = 4; j < 16; j += 4) {
    a0 = fmaxf(a0, fmaxf(s[4 * j + 0], s[4 * j + 1]));  b0 = fmaxf(b0, fmaxf(s[4 * j + 2], s[4 * j + 3]));
    a1 = fmaxf(a1, fmaxf(s[4 * j + 4], s[4 * j + 5]));  b1 = fmaxf(b1, fmaxf(s[4 * j + 6], s[4 * j + 7]));
    a2 = fmaxf(a2, fmaxf(s[4 * j + 8], s[4 * j + 9]));  b2 = fmaxf(b2, fmaxf(s[4 * j + 10], s[4 * j + 11]));
    a3 = fmaxf(a3, fmaxf(s[4 * j + 12], s[4 * j + 13])); b3 = fmaxf(b3, fmaxf(s[4 * j + 14], s[4 * j + 15]));
  }
  mx0 = fmaxf(fmaxf(a0, a1), fmaxf(a2, a3));
  mx1 = fmaxf(fmaxf(b0, b1), fmaxf(b2, b3));
  mx0 = fmaxf(mx0, __shfl_xor_sync(0xffffffffu, mx0, 1));
  mx1 = fmaxf(mx1, __shfl_xor_sync(0xffffffffu, mx1, 1));
  mx0 = fmaxf(mx0, __shfl_xor_sync(0xffffffffu, mx0, 2));
  mx1 = fmaxf(mx1, __shfl_xor_sync(0xffffffffu, mx1, 2));
}
__device__ __forceinline__ void softmax_sub(float (&s)[64], float mc0, float mc1) {
  #pragma unroll
  for (int j = 0; j < 16; j++) { s[4 * j] -= mc0; s[4 * j + 1] -= mc0; s[4 * j + 2] -= mc1; s[4 * j + 3] -= mc1; }
}
template <int LO, int HI>
__device__ __forceinline__ void softmax_exp(float (&s)[64]) {
  #pragma unroll
  for (int i = LO; i < HI; i++) s[i] = ex2_approx(s[i]);
}
__device__ __forceinline__ bool softmax_mode(const float (&s)[64], float& mc0, float& mc1) {
  softmax_rowmax(s, mc0, mc1);
  const bool raw = __all_sync(0xffffffffu, mc0 >= AT_RAW_LO && mc0 <= AT_RAW_HI && mc1 >= AT_RAW_LO && mc1 <= AT_RAW_HI);
  mc0 += AT_HEAD; mc1 += AT_HEAD;
  return raw;
}
__device__ __forceinline__ void rowsum_p(const uint32_t (&p)[32], uint32_t& t0, uint32_t& t1) {
  uint32_t a[16];
  #pragma unroll
  for (int i = 0; i < 8; i++) { a[2 * i] = badd2(p[4 * i], p[4 * i + 2]); a[2 * i + 1] = badd2(p[4 * i + 1], p[4 * i + 3]); }
  #pragma unroll
  for (int i = 0; i < 4; i++) { a[2 * i] = badd2(a[4 * i], a[4 * i + 2]); a[2 * i + 1] = badd2(a[4 * i + 1], a[4 * i + 3]); }
  t0 = badd2(badd2(a[0], a[2]), badd2(a[4], a[6]));
  t1 = badd2(badd2(a[1], a[3]), badd2(a[5], a[7]));
}
__device__ __forceinline__ void add_rowsum(const uint32_t (&p)[32], float& l0, float& l1) {
  uint32_t t0, t1;
  rowsum_p(p, t0, t1);
  l0 += bflo(t0) + bfhi(t0); l1 += bflo(t1) + bfhi(t1);
}
__device__ __forceinline__ void pack_p(uint32_t (&p)[32], const float (&s)[64]) {
  #pragma unroll
  for (int i = 0; i < 32; i++) p[i] = pack_bf16(s[2 * i], s[2 * i + 1]);
}
__device__ __noinline__ void attn_rows_exact(uint32_t bid, uint32_t sq, uint32_t so, int hsel, const bf16* __restrict__ kh, const bf16* __restrict__ vh) {
  const int warp = (threadIdx.x >> 5) & 3, lane = threadIdx.x & 31;
  const size_t hofs = (size_t)((bid < 128 ? bid >> 4 : 15) * 2 + hsel) * T_SEQ * T_DH;
  kh += hofs; vh += hofs;
  #pragma unroll 1
  for (int r = 16 * warp; r < 16 * warp + 16; r++) {
    const uint32_t ad = (lane >> 4) * 16384 + r * 128 + ((((lane & 15) >> 1) ^ (r & 7)) << 4) + (lane & 1) * 8;
    uint2 qv; asm volatile("ld.shared.v2.u32 {%0, %1}, [%2];" : "=r"(qv.x), "=r"(qv.y) : "r"(sq + ad) : "memory");
    const float q0 = bflo(qv.x), q1 = bfhi(qv.x), q2 = bflo(qv.y), q3 = bfhi(qv.y);
    float m = -INFINITY, l = 0.f, o0 = 0.f, o1 = 0.f, o2 = 0.f, o3 = 0.f;
    #pragma unroll 1
    for (int key = 0; key < T_SEQ; key++) {
      const uint2 kv = *reinterpret_cast<const uint2*>(kh + (size_t)key * T_DH + lane * 4);
      const uint2 vv = *reinterpret_cast<const uint2*>(vh + (size_t)key * T_DH + lane * 4);
      float sc = (q0 * bflo(kv.x) + q1 * bfhi(kv.x)) + (q2 * bflo(kv.y) + q3 * bfhi(kv.y));
      #pragma unroll
      for (int o = 16; o > 0; o >>= 1) sc += __shfl_xor_sync(0xffffffffu, sc, o);
      const float mn = fmaxf(m, sc);
      const float al = (m == mn) ? 1.0f : ex2_approx(m - mn), p = rbf(ex2_approx(sc - mn));
      m = mn;
      l = fmaf(l, al, p);
      o0 = fmaf(o0, al, p * bflo(vv.x)); o1 = fmaf(o1, al, p * bfhi(vv.x));
      o2 = fmaf(o2, al, p * bflo(vv.y)); o3 = fmaf(o3, al, p * bfhi(vv.y));
    }
    const float inv = rcp_approx(l);
    asm volatile("st.shared.v2.u32 [%0], {%1, %2};" :: "r"(so + ad), "r"(pack_bf16(o0 * inv, o1 * inv)), "r"(pack_bf16(o2 * inv, o3 * inv)) : "memory");
  }
}
__device__ __forceinline__ void issue_qk(float (&s)[64], const uint32_t (&q)[32], uint32_t k_lo) {
  wgmma_fence();
  wgmma_m64n128k16_rs<0>(s, q[0], q[1], q[2], q[3], k_lo, 0);
  wgmma_m64n128k16_rs<2>(s, q[4], q[5], q[6], q[7], k_lo, 1);
  wgmma_m64n128k16_rs<4>(s, q[8], q[9], q[10], q[11], k_lo, 1);
  wgmma_m64n128k16_rs<6>(s, q[12], q[13], q[14], q[15], k_lo, 1);
  wgmma_m64n128k16_rs<1024>(s, q[16], q[17], q[18], q[19], k_lo, 1);
  wgmma_m64n128k16_rs<1026>(s, q[20], q[21], q[22], q[23], k_lo, 1);
  wgmma_m64n128k16_rs<1028>(s, q[24], q[25], q[26], q[27], k_lo, 1);
  wgmma_m64n128k16_rs<1030>(s, q[28], q[29], q[30], q[31], k_lo, 1);
  wgmma_commit();
}
__device__ __forceinline__ void issue_pv(float (&o)[64], const uint32_t (&p)[32], uint32_t v_lo, int accumulate) {
  wgmma_fence();
  wgmma_m64n128k16_rs_tb<0>(o, p[0], p[1], p[2], p[3], v_lo, accumulate);
  wgmma_m64n128k16_rs_tb<128>(o, p[4], p[5], p[6], p[7], v_lo, 1);
  wgmma_m64n128k16_rs_tb<256>(o, p[8], p[9], p[10], p[11], v_lo, 1);
  wgmma_m64n128k16_rs_tb<384>(o, p[12], p[13], p[14], p[15], v_lo, 1);
  wgmma_m64n128k16_rs_tb<512>(o, p[16], p[17], p[18], p[19], v_lo, 1);
  wgmma_m64n128k16_rs_tb<640>(o, p[20], p[21], p[22], p[23], v_lo, 1);
  wgmma_m64n128k16_rs_tb<768>(o, p[24], p[25], p[26], p[27], v_lo, 1);
  wgmma_m64n128k16_rs_tb<896>(o, p[28], p[29], p[30], p[31], v_lo, 1);
  wgmma_commit();
}
__device__ __forceinline__ void block_end(uint32_t zero, uint32_t bar) {
  #pragma unroll 1
  for (uint32_t i = 0; i < zero; i++) mbar_arrive(bar);
}
__device__ __forceinline__ void rescale_o(float (&o)[64], float al0, float al1) {
  #pragma unroll
  for (int j = 0; j < 16; j++) { o[4 * j] *= al0; o[4 * j + 1] *= al0; o[4 * j + 2] *= al1; o[4 * j + 3] *= al1; }
}

__device__ __forceinline__ void stage_o(const float (&o)[64], float i0, float i1, uint32_t dst, int lane) {
  #pragma unroll
  for (int J = 0; J < 16; J += 2)
    stmatrix_x4(dst + (J >> 3) * 16384 + ((((J & 7) + (lane >> 4)) ^ (lane & 7)) << 4),
                pack_bf16(o[4 * J + 0] * i0, o[4 * J + 1] * i0), pack_bf16(o[4 * J + 2] * i1, o[4 * J + 3] * i1),
                pack_bf16(o[4 * J + 4] * i0, o[4 * J + 5] * i0), pack_bf16(o[4 * J + 6] * i1, o[4 * J + 7] * i1));
}
__device__ __forceinline__ bool finish_l(float& l0, float& l1) {
  l0 += __shfl_xor_sync(0xffffffffu, l0, 1); l1 += __shfl_xor_sync(0xffffffffu, l1, 1);
  l0 += __shfl_xor_sync(0xffffffffu, l0, 2); l1 += __shfl_xor_sync(0xffffffffu, l1, 2);
  const bool redo = __any_sync(0xffffffffu, !(l0 <= AT_RAW_SUM && l1 <= AT_RAW_SUM && l0 >= AT_RAW_MIN && l1 >= AT_RAW_MIN));
  l0 = rcp_approx(l0); l1 = rcp_approx(l1);
  return redo;
}
template <int J0>
__device__ __forceinline__ void stage_q(const float (&acc)[128], float c, uint32_t dst, int lane) {
  #pragma unroll
  for (int J = J0; J < J0 + 16; J += 2)
    stmatrix_x4(dst + (J >> 3) * 16384 + ((((J & 7) + (lane >> 4)) ^ (lane & 7)) << 4),
                pack_bf16(acc[4 * J + 0] * c, acc[4 * J + 1] * c), pack_bf16(acc[4 * J + 2] * c, acc[4 * J + 3] * c),
                pack_bf16(acc[4 * J + 4] * c, acc[4 * J + 5] * c), pack_bf16(acc[4 * J + 6] * c, acc[4 * J + 7] * c));
}
__device__ __forceinline__ void store_o(const CUtensorMap* tmO, uint32_t src, int head, int row) {
  tma_store_2d(tmO, src, head * T_DH, row);
  tma_store_2d(tmO, src + 16384, head * T_DH + 64, row);
  bulk_commit();
}
__device__ __forceinline__ void mma_bf16(float (&d)[4], uint32_t a0, uint32_t a1, uint32_t a2, uint32_t a3, uint32_t b0, uint32_t b1) {
  asm volatile("mma.sync.aligned.m16n8k16.row.col.f32.bf16.bf16.f32 {%0, %1, %2, %3}, {%4, %5, %6, %7}, {%8, %9}, {%0, %1, %2, %3};"
               : "+f"(d[0]), "+f"(d[1]), "+f"(d[2]), "+f"(d[3]) : "r"(a0), "r"(a1), "r"(a2), "r"(a3), "r"(b0), "r"(b1));
}
struct GemvSel { uint32_t lo0, hi0, lo1, hi1; };
__device__ __forceinline__ GemvSel gemv_sel(int lane) {
  const uint32_t lo = (lane & 8) ? 0x1044u : 0x4410u, hi = (lane & 8) ? 0x3244u : 0x4432u;
  GemvSel s; s.lo0 = (lane & 16) ? 0x4444u : lo; s.hi0 = (lane & 16) ? 0x4444u : hi; s.lo1 = (lane & 16) ? lo : 0x4444u; s.hi1 = (lane & 16) ? hi : 0x4444u;
  return s;
}
#define GEMV_B0(j, h, s) __byte_perm((j) < 2 ? (h).x : (h).y, 0u, ((j) & 1) ? (s).hi0 : (s).lo0)
#define GEMV_B1(j, h, s) __byte_perm((j) < 2 ? (h).x : (h).y, 0u, ((j) & 1) ? (s).hi1 : (s).lo1)
__device__ __forceinline__ int gemv_col(int i) { return (i >> 4) * 8 + ((i >> 3) & 1) * 4 + (i & 2) + ((i >> 2) & 1); }
#define OG_XN 4
#define OG_XB 5
#define OG_NG 8
#define PUT_N 2
#define H_STAG 2
#define AL_P 60
#define AL_SLEEP 1200
#define AL_MAX 800
#define POLL_NS 500
#define OG_PROF 0xDDCCBA87u
#define RK_P 24
__host__ __device__ constexpr int og_pre(int tile) { return (OG_PROF >> ((tile >> 4) * 4)) & 15; }
constexpr int OG_PRE2 = og_pre(127), OG_HSUM = og_pre(0) + og_pre(16) + og_pre(32) + og_pre(48) + og_pre(64) + og_pre(80) + og_pre(96);
#define OG_JOBS 7
#define OG_GRP 6
#define LD_FIRST 2
#define LD_STAG (OG_GRP / 2)
constexpr int OG_ST = 5, OG_NKB = T_DQKV / 64 - og_pre(0), OG_MOE = T_F / 32;
__device__ __forceinline__ int pre_kb(int i) { return (i >> 1) * 4 + (i & 1); }
__device__ __forceinline__ int own_kb(int i, int pre) { return i < (pre & ~1) ? pre_kb(i) + 2 : i + pre; }
static_assert(LD_FIRST + LD_STAG <= OG_XB && OG_XB < LD_FIRST + OG_GRP, "the extra tile belongs to segment 1");
static_assert(og_pre(16) >= 16 / PUT_N && LD_FIRST + 7 * OG_GRP + LD_STAG + 3 <= 64 - OG_PRE2, "job / segment lengths");
constexpr int OG_POS = 8;
constexpr uint32_t OG_STAGE = 32768;
constexpr uint32_t OG_SCOL = AT_SBAR + 512;
constexpr uint32_t OG_SMISC = AT_SBAR + 2048;
constexpr uint32_t OG_SWD = AT_SQ, OG_PSLOT = AT_SQ;
constexpr uint32_t OG_XSLOT = AT_SQ + 32768;
constexpr uint32_t OG_OSLOT = 1 * OG_STAGE;
constexpr uint32_t OG_SRED = 3 * OG_STAGE;
constexpr uint32_t OG_SH2 = OG_SRED + 24576;
constexpr uint32_t OG_SSTAT = OG_SRED + 16384;
constexpr uint32_t OG_SGU = OG_SRED + 8192;
constexpr uint32_t OG_SFIN = OG_SGU + 256;
#define OGM 2
#define OG_MT(b) ((((b) >> OGM) & 15) ^ (((b) & 64) ? 15 : 0))
#define OG_NT(b) (((b) & ((1 << OGM) - 1)) + (((b) >> (4 + OGM)) << OGM))
__device__ __forceinline__ int tail_tile(uint32_t sbase) { mbar_wait_long(sbase + AT_SBAR + 336, 0); return (int)lds_u32(sbase + AT_SBAR + 408); }
#define TAIL_SETUP \
  const uint32_t bar_full = sbase + AT_SBAR, bar_empty = bar_full + 40; \
  const uint32_t bar_wd = bar_full + 168, bar_col = bar_full + 176, bar_out = bar_full + 184, bar_end = bar_full + 192; \
  const uint32_t bar_key = bar_full + 200, bar_h2 = bar_full + 208, bar_sel = bar_full + 216; \
  const int mt = OG_MT(tb), nt = OG_NT(tb); \
  const int m0 = mt * 128, n0 = nt * 128; \
  const bool has_moe = (int)bid < OG_MOE; \
  (void)bar_empty; (void)bar_wd; (void)bar_col; (void)bar_out; (void)bar_end; (void)bar_key; (void)bar_h2; (void)bar_sel; (void)m0; (void)n0; (void)has_moe;

__device__ __forceinline__ void tail_producer(uint32_t bid, uint32_t sbase, uint32_t ph, uint64_t pol, const CUtensorMap* tmA, const CUtensorMap* tmB, const CUtensorMap* tmD) {
  const int tb = tail_tile(sbase);
  TAIL_SETUP
  uint32_t stage = OG_POS % OG_ST;
  int kb = 0, xk = OG_XB;
  uint32_t xp = 1;
  #pragma unroll 1
  for (int seg = 0; seg < 2; seg++) {
    mbar_wait(bar_full + 264 + 80 * seg, 0);
    fence_proxy_async_global();
    const int end = 32 + 32 * seg - og_pre(tb);
    #pragma unroll 1
    for (; kb < end; kb++) {
      const bool xb = kb == xk;
      const uint32_t fb = xb ? bar_full + 360 : bar_full + 8 * stage, sa = sbase + (xb ? 5 : stage) * OG_STAGE;
      const int k0 = own_kb(kb, og_pre(tb)) * 64;
      if (xb) {
        mbar_wait(bar_full + 80, bid < AT_NFULL);
        mbar_wait(bar_full + 368, xp);
        xp ^= 1;
        if (xk < OG_XB + (OG_XN - 1) * OG_GRP) xk += OG_GRP;
      }
      mbar_wait_long(xb ? bar_full + 304 : bar_empty + 8 * stage, xb ? 0 : ph);
      mbar_expect_tx(fb, OG_STAGE);
      tma_load_3d_hint(sa + 16384, tmB, k0, 2 * nt, fb, pol);
      tma_load_2d_hint(sa, tmA, k0, m0, fb, pol);
      if (!xb && ++stage == OG_ST) { stage = 0; ph ^= 1; }
    }
  }
  if (has_moe) {
    stage += stage & 1;
    mbar_wait(bar_empty + 8 * stage, ph);
    mbar_expect_tx(bar_wd, OG_STAGE);
    tma_load_3d_hint(sbase + stage * OG_STAGE, tmD, bid * 32, 8, bar_wd, pol);
  }
}

__device__ __forceinline__ uint32_t out2(uint32_t x1, uint32_t mb2, uint32_t ih, uint32_t il, uint32_t c1, uint32_t sb, uint32_t gb) {
  const uint32_t h2 = badd2(bmul2(ln_norm2b(x1, mb2, ih, il), c1), sb);
  return badd2(x1, bmul2(gb, bfma2(h2, 0u, h2)));
}
#define X_PACE 200
#define Y_SLACK 96
#define OG_STAG 3
#define POLL_NS2 100
#define WD_SKIP 1
#define AL_ADD 380
#define WD_PACE 300
__device__ __forceinline__ void tail_exchange(uint32_t bid, uint32_t sbase, const bf16* __restrict__ w_down, const bf16* __restrict__ w_r, const bf16* __restrict__ x, bf16* __restrict__ out) {
    const int lane = threadIdx.x & 31, wi = __shfl_sync(0xffffffffu, threadIdx.x >> 5, 0);
    if (wi == 3) {
      uint32_t a = bid, b = 0u;
      if (bid < AT_NFULL) mbar_wait_long(sbase + AT_SBAR + 312, 0);
      if (bid < OG_MOE) {
        asm volatile("mov.u32 %0, %%globaltimer_lo;" : "=r"(a));
        if (lane == 0 && (bid & 15) == 0) asm volatile("st.relaxed.gpu.global.u32 [%0], %1;" :: "l"(g_hcnt + 8 + (bid >> 4)), "r"((a & ~15u) | 8u | (bid >> 4)) : "memory");
        #pragma unroll 1
        for (unsigned int spin = 0; spin < (1u << 22) && __any_sync(0xffffffffu, b == 0u); spin++) {
          __nanosleep(200);
          asm volatile("ld.relaxed.gpu.global.u32 %0, [%1];" : "=r"(b) : "l"(g_hcnt + 8 + min(lane, 6)) : "memory");
        }
        a = __popc(__ballot_sync(0xffffffffu, b < __shfl_sync(0xffffffffu, b, bid >> 4)) & 127u) * 16 + (bid & 15);
      }
      if (lane == 0) {
        sts_u32(sbase + AT_SBAR + 408, a);
        mbar_arrive(sbase + AT_SBAR + 336);
        b = 0u;
        if (bid < AT_NFULL) {
          unsigned int* tm = g_hcnt + 32 * (1 + (bid >> 4)) + 8;
          mbar_wait_long(sbase + AT_SBAR + 312, 1);
          asm volatile("mov.u32 %0, %%globaltimer_lo;" : "=r"(a));
          asm volatile("red.relaxed.gpu.global.max.u32 [%0], %1;" :: "l"(tm), "r"(a) : "memory");
          __nanosleep(AL_SLEEP);
          asm volatile("ld.relaxed.gpu.global.u32 %0, [%1];" : "=r"(b) : "l"(tm) : "memory");
          b -= a;
        }
        sts_u32(sbase + AT_SBAR + 412, b < AL_MAX ? b * 13 / 8 : 0u);
        mbar_arrive(sbase + AT_SBAR + 320);
      }
      named_bar_sync(15, 32);
    }
    const int tb = __shfl_sync(0xffffffffu, tail_tile(sbase), 0);
    TAIL_SETUP
    if (wi == 3) {
      mbar_wait_long(bar_full + 344, 0);
      float a = g_scal[lane], b = g_scal[32 + lane];
      #pragma unroll
      for (int i = 0; i < 3; i++) {
        const uint4 v = *reinterpret_cast<const uint4*>(g_col + nt * 1536 + i * 512 + lane * 16);
        sts_u32x4(sbase + OG_SCOL + i * 512 + lane * 16, v.x, v.y, v.z, v.w);
      }
      #pragma unroll
      for (int o = 16; o > 0; o >>= 1) { a += __shfl_xor_sync(0xffffffffu, a, o); b += __shfl_xor_sync(0xffffffffu, b, o); }
      if (lane == 0) sts_f32x2(sbase + OG_SMISC, a, b);
      const uint64_t pol = policy_evict_first();
      #pragma unroll 1
      for (int r = lane >> 4; r < 128; r += 4) {
        __nanosleep(X_PACE);
        #pragma unroll
        for (int j = 0; j < 4; j += 2)
          asm volatile("cp.async.cg.shared.global.L2::cache_hint [%0], [%1], 16, %2;" :: "r"(sbase + OG_XSLOT + (lane & 8) * 2048 + (r + j) * 128 + (((lane ^ (r + j)) & 7) << 4)),
                       "l"(x + (size_t)(m0 + r + j) * T_D + n0 + (lane & 15) * 8), "l"(pol) : "memory");
      }
      asm volatile("cp.async.wait_all;" ::: "memory");
      __syncwarp();
      if (lane == 0) mbar_arrive(bar_col);
    } else if (wi == 2) {
      if (elect_one()) {
        mbar_wait_long(bar_full + (has_moe ? 80 : 376), has_moe);
        #pragma unroll 1
        for (unsigned int i = 0; i < (1u << 20) && ld_acquire(&g_hcnt[32 * (1 + (tb >> 3)) + 4 + ((tb >> 1) & 3)]) == 0u; i++) __nanosleep((tb >> 4) == 6 ? POLL_NS2 : POLL_NS);
        TL_MARK2(23, true);
        fence_proxy_async_global();
        TL_MARK2(4, true);
        mbar_expect_tx(bar_full + 272, 32768);
        bulk_load_hint(sbase + OG_PSLOT, g_pre + tb * 2048, 32768, bar_full + 272, policy_evict_first());
      }
      named_bar_sync(14, 32);
      if (has_moe) {
        mbar_wait_long(bar_full + 376, 0);
        const uint64_t pol = policy_evict_first();
        #pragma unroll 1
        for (int r = 0; r < 32; r++) {
          if ((r & WD_SKIP) != WD_SKIP) __nanosleep(WD_PACE);
          #pragma unroll
          for (int j = 0; j < 2; j++)
            asm volatile("cp.async.cg.shared.global.L2::cache_hint [%0], [%1], 16, %2;" :: "r"(sbase + OG_SWD + (4 * j + (lane >> 3)) * 4096 + r * 128 + (((lane ^ r) & 7) << 4)),
                         "l"((const uint8_t*)w_down + (size_t)bid * 65536 + r * 2048 + j * 512 + lane * 16), "l"(pol) : "memory");
        }
        asm volatile("cp.async.wait_all;" ::: "memory");
        __syncwarp();
        if (lane == 0) mbar_arrive(bar_wd);
      }
    }
    const uint4 wrv = ldg_nc_v4(w_r + threadIdx.x * 8);
    mbar_wait_long(bar_end, 0);
    TL_MARK2(22, lane == 0);
    if (wi == 0) {
      uint32_t k1 = 0u, k2 = 0u;
      #pragma unroll 1
      for (unsigned int spin = 0; spin < (1u << 22) && __any_sync(0xffffffffu, k1 == 0u); spin++) asm volatile("ld.relaxed.gpu.global.u32 %0, [%1];" : "=r"(k1) : "l"(g_key + lane) : "memory");
      TL_MARK2(28, lane == 0);
      warp_top2(k1, k2);
      if (lane == 0) {
        const uint32_t r1 = 0xffffu - (k1 & 0xffffu), r2 = 0xffffu - (k2 & 0xffffu);
        sts_u32x4(sbase + OG_SMISC + 64, r1, r2, (r1 >> 7) * 2, (r2 >> 7) * 2 + ((r1 >> 7) == (r2 >> 7)));
        mbar_arrive(bar_sel);
      }
    } else if (wi < 3) {
          mbar_wait(bar_key, 0);
          const uint4 kk = lds_u32x4(sbase + OG_SSTAT + 1024 + lane * 16);
          uint32_t k1 = max(kk.x, kk.y), k2 = min(kk.x, kk.y);
          k2 = max(max(k2, min(kk.z, kk.w)), min(k1, max(kk.z, kk.w))); k1 = max(k1, max(kk.z, kk.w));
          warp_top2(k1, k2);
          if (wi == 1) {
            if (lane == 0) {
              if (nt == (mt & 7)) st_relaxed2(g_key + mt * 2, k1, k2);
              sts_u32x2(sbase + OG_SMISC + 96, (~k1 >> 4) & 7u, (~k2 >> 4) & 7u);
              mbar_arrive(bar_full + 352);
            }
            TL_MARK2(27, lane == 0);
          } else {
            const uint32_t r = (~((lane & 16) ? k2 : k1)) & 127u, ch = lane & 15;
            const uint2 st = lds_u32x2(sbase + OG_SSTAT + r * 8);
            const uint4 xc = lds_u32x4(sbase + OG_XSLOT + (ch >> 3) * 16384 + r * 128 + (((ch ^ r) & 7) << 4));
            const uint4 c1 = lds_u32x4(sbase + OG_SCOL + 768 + ch * 16), sh = lds_u32x4(sbase + OG_SCOL + 1024 + ch * 16);
            const float inr = __uint_as_float(st.y);
            float* dst = reinterpret_cast<float*>(g_cand + (mt * 2 + (lane >> 4)) * 256 + nt * 16 + ch);
            st_tagged4(dst + 512, __uint_as_float(ln_mod2(xc.x, st.x, inr, c1.x, sh.x)), __uint_as_float(ln_mod2(xc.y, st.x, inr, c1.y, sh.y)),
                       __uint_as_float(ln_mod2(xc.z, st.x, inr, c1.z, sh.z)), __uint_as_float(ln_mod2(xc.w, st.x, inr, c1.w, sh.w)));
            st_tagged4(dst, __uint_as_float(xc.x), __uint_as_float(xc.y), __uint_as_float(xc.z), __uint_as_float(xc.w));
          }
    }
    mbar_wait(bar_sel, 0);
    const uint4 sel = lds_u32x4(sbase + OG_SMISC + 64);
    const int sel0 = (int)sel.x, sel1 = (int)sel.y;
    {
      const float* src0 = reinterpret_cast<const float*>(g_cand + sel.z * 256 + 128 + threadIdx.x);
      const float* src1 = reinterpret_cast<const float*>(g_cand + sel.w * 256 + 128 + threadIdx.x);
      float4 h0, h1;
      #pragma unroll 1
      for (unsigned int spin = 0; spin < (1u << 20); spin++) { h0 = ld_tagged4(src0); h1 = ld_tagged4(src1); if (__all_sync(0xffffffffu, tagged4(h0) & tagged4(h1))) break; }
      sts_f32x4(sbase + OG_SH2 + threadIdx.x * 16, h0.x, h0.y, h0.z, h0.w);
      sts_f32x4(sbase + OG_SH2 + 2048 + threadIdx.x * 16, h1.x, h1.y, h1.z, h1.w);
      __syncwarp();
      if (lane == 0) mbar_arrive(bar_h2);
      TL_MARK2(12, lane == 0);
      float v[8], u[8], wr[8];
      unpack8(make_uint4(__float_as_uint(h0.x), __float_as_uint(h0.y), __float_as_uint(h0.z), __float_as_uint(h0.w)), v);
      unpack8(make_uint4(__float_as_uint(h1.x), __float_as_uint(h1.y), __float_as_uint(h1.z), __float_as_uint(h1.w)), u);
      unpack8(wrv, wr);
      float r0 = 0.f, r1 = 0.f;
      #pragma unroll
      for (int i = 0; i < 8; i++) { r0 = fmaf(v[i], wr[i], r0); r1 = fmaf(u[i], wr[i], r1); }
      r0 = ((lane & 16) ? r1 : r0) + __shfl_xor_sync(0xffffffffu, (lane & 16) ? r0 : r1, 16);
      #pragma unroll
      for (int o = 8; o > 0; o >>= 1) r0 += __shfl_xor_sync(0xffffffffu, r0, o);
      if ((lane & 15) == 0) sts_f32(sbase + OG_SMISC + 192 + lane + wi * 4, r0);
    }
    mbar_wait(bar_out, 0);
    {
      const uint2 cg = lds_u32x2(sbase + OG_SMISC + 96);
      #pragma unroll
      for (int i = 0; i < 4; i++) {
        const int r = (i < 2 ? cg.x : cg.y) * 16 + (i & 1) * 8 + (threadIdx.x >> 4), ch = threadIdx.x & 15;
        if (m0 + r != sel0 && m0 + r != sel1)
          *reinterpret_cast<uint4*>(out + (size_t)(m0 + r) * T_D + n0 + ch * 8) =
              lds_u32x4(sbase + OG_OSLOT + (ch >> 3) * 16384 + r * 128 + (((ch & 7) ^ (r & 7)) << 4));
      }
    }
    if (bid == 0 && threadIdx.x < 68) *reinterpret_cast<uint4*>(g_hcnt + 32 * (threadIdx.x >> 2) + 4 * (threadIdx.x & 3)) = make_uint4(0u, 0u, 0u, 0u);
    if (threadIdx.x < 64) g_modpart[bid * 64 + threadIdx.x] = 0.f;
    {
      const int tk = threadIdx.x & 1, col = bid * 8 + gemv_col(threadIdx.x & 15);
      const uint32_t gb2 = *reinterpret_cast<const uint32_t*>(g_col + (col >> 7) * 1536 + 512 + 768 + (col & 126) * 2);
      const uint32_t* xp = reinterpret_cast<const uint32_t*>(g_cand + (tk ? sel.w : sel.z) * 256) + (col >> 1);
      uint32_t x2 = 0u;
      #pragma unroll 1
      for (unsigned int spin = 0; spin < (1u << 20) && __any_sync(0xffffffffu, x2 == 0u); spin++) asm volatile("ld.relaxed.gpu.global.u32 %0, [%1];" : "=r"(x2) : "l"(xp) : "memory");
      const float* src = g_ypart + (size_t)(threadIdx.x >> 2) * 2 * T_D + bid * 16 + (threadIdx.x & 3) * 4;
      const bool four = threadIdx.x < (OG_MOE - 96) * 4;
      named_bar_sync(10, 128);
      const uint4 rp = lds_u32x4(sbase + OG_SMISC + 192 + tk * 16);
      const float rs = rbf(sigmoid_f(rbf((__uint_as_float(rp.x) + __uint_as_float(rp.y)) + (__uint_as_float(rp.z) + __uint_as_float(rp.w)))));
      const uint32_t h2p = lds_u32(sbase + OG_SH2 + tk * 2048 + (col & ~1) * 2);
      const float fh = (col & 1) ? bfhi(h2p) : bflo(h2p), fz = rbf(fh * 0.0f), fx = (col & 1) ? bfhi(x2) : bflo(x2), fg = (col & 1) ? bfhi(gb2) : bflo(gb2);
      bf16* dst = out + (size_t)(tk ? sel1 : sel0) * T_D + col;
      if (threadIdx.x == 0) hint_wait(CNT_Y, (uint32_t)(OG_MOE - Y_SLACK));
      named_bar_sync(10, 128);
      float4 p0, p1, p2, p3;
      #pragma unroll 1
      for (unsigned int spin = 0; spin < (1u << 20); spin++) {
        p0 = ld_tagged4(src); p1 = ld_tagged4(src + 64 * T_D); p2 = ld_tagged4(src + 128 * T_D); p3 = ld_tagged4(four ? src + 192 * T_D : src);
        if (__all_sync(0xffffffffu, tagged4(p0) & tagged4(p1) & tagged4(p2) & tagged4(p3))) break;
      }
      if (four) { p2.x += p3.x; p2.y += p3.y; p2.z += p3.z; p2.w += p3.w; }
      p0.x = (p0.x + p1.x) + p2.x; p0.y = (p0.y + p1.y) + p2.y; p0.z = (p0.z + p1.z) + p2.z; p0.w = (p0.w + p1.w) + p2.w;
      #pragma unroll
      for (int o = 4; o <= 16; o <<= 1) {
        p0.x += __shfl_xor_sync(0xffffffffu, p0.x, o); p0.y += __shfl_xor_sync(0xffffffffu, p0.y, o);
        p0.z += __shfl_xor_sync(0xffffffffu, p0.z, o); p0.w += __shfl_xor_sync(0xffffffffu, p0.w, o);
      }
      if (lane < 4) sts_f32x4(sbase + OG_SFIN + (threadIdx.x >> 5) * 64 + lane * 16, p0.x, p0.y, p0.z, p0.w);
      named_bar_sync(10, 128);
      TL_MARK2(21, threadIdx.x == 0);
      if (threadIdx.x < 16) {
        const uint32_t ya = sbase + OG_SFIN + threadIdx.x * 4;
        float y = (lds_f32(ya) + lds_f32(ya + 64)) + (lds_f32(ya + 128) + lds_f32(ya + 192));
        y = rbf(y);
        y = rbf(y * rs);
        *dst = __float2bfloat16_rn(fx + rbf(fg * rbf(fh + rbf(fz + y))));
      }
    }
    if (threadIdx.x == 0) XT(11);
    TL_END(4, threadIdx.x == 0);
}

__device__ __forceinline__ void load_pre(uint4* pre, uint32_t sbase, uint32_t buf, int t2) {
  mbar_wait(sbase + AT_SBAR + 272, 0);
  #pragma unroll
  for (int i = 0; i < 8; i++) pre[i] = lds_u32x4(sbase + buf + i * 4096 + t2 * 16);
}
__device__ __forceinline__ void tail_consumer(uint32_t bid, uint32_t sbase, const CUtensorMap* tmOut, const uint4 (&pre)[8], int cwg, const bf16* __restrict__ w_gate, const bf16* __restrict__ w_up) {
    const uint32_t c0 = clock_lo();
    if ((threadIdx.x & 31) == 0) mbar_arrive(sbase + AT_SBAR + 304);
    mbar_wait(sbase + AT_SBAR + 320, 0);
    const uint2 td = lds_u32x2(sbase + AT_SBAR + 408);
    const int tb = __shfl_sync(0xffffffffu, (int)td.x, 0);
    TAIL_SETUP
    const int tid = threadIdx.x & 127, t2 = threadIdx.x - 128;
    const int warp = tid >> 5, lane = tid & 31, w8 = t2 >> 5;
    const uint32_t dbase = (sbase & 0x3FFFFu) >> 4;
    const uint32_t a_base = dbase + ((cwg * 8192) >> 4) + (1u << 16);
    const uint32_t b_base = dbase + (16384 >> 4) + (512u << 16);
    TL_MARK2(25, threadIdx.x == 128);
    const uint64_t pol = policy_evict_first();
    const bf16* pw = ((lane & 16) ? w_up : w_gate) + (size_t)(w8 * 128 + (lane & 3) * 4) * T_F + (has_moe ? bid : 0) * 32 + ((lane >> 2) & 3) * 8;
    uint4 wv[32];
    float acc[64];
    #pragma unroll
    for (int i = 0; i < 8; i++) {
      acc[8 * i] = bflo(pre[i].x); acc[8 * i + 1] = bfhi(pre[i].x); acc[8 * i + 2] = bflo(pre[i].y); acc[8 * i + 3] = bfhi(pre[i].y);
      acc[8 * i + 4] = bflo(pre[i].z); acc[8 * i + 5] = bfhi(pre[i].z); acc[8 * i + 6] = bflo(pre[i].w); acc[8 * i + 7] = bfhi(pre[i].w);
    }
    while (__any_sync(0xffffffffu, clock_lo() - c0 < td.y + AL_ADD)) {}
    uint32_t stage = OG_POS % OG_ST;
    {
      uint32_t phase = (OG_POS / OG_ST) & 1, prev = 12;
      int kb = 0;
      #pragma unroll
      for (int g = 0; g <= OG_NG; g++) {
        const int end = g == OG_NG ? 64 - og_pre(tb) : LD_FIRST + g * OG_GRP + LD_STAG * cwg;
        #pragma unroll 1
        do {
          const bool xb = g >= 1 && g <= OG_XN && kb == OG_XB + (g - 1) * OG_GRP;
          mbar_wait(xb ? bar_full + 360 : bar_full + 8 * stage, xb ? (g - 1) & 1 : phase);
          if (OG_STAG > 0 && g == OG_NG && cwg == 1 && kb == end - OG_STAG) named_bar_sync(7, 256);
          const uint32_t a_lo = a_base + (xb ? 5 : stage) * (OG_STAGE >> 4), b_lo = b_base + (xb ? 5 : stage) * (OG_STAGE >> 4);
          wgmma_fence();
          wgmma_m64n128k16_ss_tb<0, 0>(acc, a_lo, b_lo, 1);
          wgmma_m64n128k16_ss_tb<2, 128>(acc, a_lo, b_lo, 1);
          wgmma_m64n128k16_ss_tb<4, 256>(acc, a_lo, b_lo, 1);
          wgmma_m64n128k16_ss_tb<6, 384>(acc, a_lo, b_lo, 1);
          wgmma_commit();
          if (OG_STAG > 0 && g == OG_NG && cwg == 0 && kb == end - 1) named_bar_arrive(7, 256);
          wgmma_wait<1>();
          if (tid == 0) mbar_arrive(bar_empty + 8 * prev);
          prev = xb ? 41 + (g == OG_XN) : stage;
          if (!xb && ++stage == OG_ST) { stage = 0; phase ^= 1; }
        } while (++kb < end);
        #pragma unroll
        for (int j = 4 * g; j < 4 * g + 4 && j < 32; j++) wv[j] = ldg_stream_v4(pw + (size_t)(16 * (j >> 2) + (j & 3)) * T_F, pol);
      }
    }
    mbar_wait(bar_col, 0);
    if (__builtin_expect(!has_moe, 0)) {
      load_pre(wv, sbase, AT_SQ, t2);
    }
    wgmma_wait<0>();
    fence_regs(acc);
    if (__builtin_expect(!has_moe, 0)) {
      #pragma unroll
      for (int i = 0; i < 8; i++) {
        acc[8 * i] += bflo(wv[i].x); acc[8 * i + 1] += bfhi(wv[i].x); acc[8 * i + 2] += bflo(wv[i].y); acc[8 * i + 3] += bfhi(wv[i].y);
        acc[8 * i + 4] += bflo(wv[i].z); acc[8 * i + 5] += bfhi(wv[i].z); acc[8 * i + 6] += bflo(wv[i].w); acc[8 * i + 7] += bfhi(wv[i].w);
      }
    }
    if (tid == 0) mbar_arrive(bar_end);
    TL_MARK2(9, lane == 0);
    const int q2 = 2 * (lane & 3);
    const uint32_t frag = (64 * cwg + 16 * warp + (lane & 7) + 8 * ((lane >> 3) & 1)) * 128;
    const int fsw = lane & 7, fhi = lane >> 4;
    {
      float dl[4] = {0.f, 0.f, 0.f, 0.f}, da[4] = {0.f, 0.f, 0.f, 0.f}, db[4] = {0.f, 0.f, 0.f, 0.f};
      const uint32_t tb2 = sbase + OG_SCOL + (lane & 8) * 32 + (lane & 3) * 8, g = lane >> 2;
      const uint32_t msk = (g == 1 || g == 2) ? 0xffffffffu : 0u, one = g == 0 ? 0x3F803F80u : 0u;
      uint32_t xr[8][4];
      #pragma unroll
      for (int hf = 0; hf < 2; hf++) {
        uint32_t ga[8];
        uint2 cw[4];
        #pragma unroll
        for (int i = 0; i < 4; i++) {
          ldmatrix_x4(sbase + OG_XSLOT + hf * 16384 + frag + (((2 * i + fhi) ^ fsw) << 4), xr[4 * hf + i][0], xr[4 * hf + i][1], xr[4 * hf + i][2], xr[4 * hf + i][3]);
          ga[2 * i] = lds_u32(sbase + OG_SCOL + 512 + (64 * hf + 16 * i + q2) * 2); ga[2 * i + 1] = lds_u32(sbase + OG_SCOL + 512 + (64 * hf + 16 * i + 8 + q2) * 2);
          cw[i] = lds_u32x2(tb2 + (8 * hf + 2 * i) * 16);
        }
        #pragma unroll
        for (int i = 0; i < 4; i++) {
          uint32_t* x4 = xr[4 * hf + i];
          #pragma unroll
          for (int e = 0; e < 4; e++) x4[e] = badd2(x4[e], bmul2(ga[2 * i + (e >> 1)], pack_bf16(acc[32 * hf + 8 * i + 2 * e], acc[32 * hf + 8 * i + 2 * e + 1])));
          mma_bf16(dl, x4[0], x4[1], x4[2], x4[3], (cw[i].x & msk) | one, (cw[i].y & msk) | one);
          mma_bf16(da, x4[0], x4[1], x4[2], x4[3], x4[0], x4[2]);
          mma_bf16(db, x4[0], x4[1], x4[2], x4[3], x4[1], x4[3]);
        }
      }
      {
        const int dsrc = (lane & ~3) + (g >> 1);
        const float qa = __shfl_sync(0xffffffffu, (g & 1) ? da[1] : da[0], dsrc), qb = __shfl_sync(0xffffffffu, (g & 1) ? db[3] : db[2], dsrc);
        const float e0 = __shfl_xor_sync(0xffffffffu, (lane & 1) ? dl[0] : dl[2], 1), e1 = __shfl_xor_sync(0xffffffffu, dl[3], 1);
        if ((lane & 3) < 2) {
          const bool hi = lane & 1;
          st_tagged4(reinterpret_cast<float*>(g_part1 + ((mt * 8 + w8) * 8 + nt) * 16 + g + (hi ? 8 : 0)),
                     hi ? e0 : dl[0], hi ? qb : qa, hi ? e1 + dl[2] : dl[1] + e0, 1.0f);
        }
      }
      #pragma unroll
      for (int i = 0; i < 8; i++) stmatrix_x4(sbase + OG_XSLOT + (i >> 2) * 16384 + frag + (((2 * (i & 3) + fhi) ^ fsw) << 4), xr[i][0], xr[i][1], xr[i][2], xr[i][3]);
    }
    TL_MARK2(10, lane == 0);
    uint4 wd[16];
    if (has_moe) mbar_wait(bar_wd, 0);
    #pragma unroll
    for (int i = 0; i < 16; i++) wd[i] = lds_u32x4(sbase + (cwg ? (stage + (stage & 1)) * OG_STAGE : OG_SWD) + warp * 8192 + (i >> 3) * 4096 + (i & 6) * 512 + (i & 1) * 128 + (lane & 3) * 256 + (((lane >> 2) ^ (2 * (lane & 3) + (i & 1))) << 4));
    {
      const float* src = reinterpret_cast<const float*>(g_part1 + ((mt * 8 + w8) * 8 + (lane & 1) * 4) * 16 + (lane >> 1));
      float4 v, v1, v2, v3;
      #pragma unroll 1
      for (unsigned int spin = 0; spin < (1u << 22); spin++) {
        v = ld_tagged4(src); v1 = ld_tagged4(src + 64); v2 = ld_tagged4(src + 128); v3 = ld_tagged4(src + 192);
        if (__all_sync(0xffffffffu, tagged4(v) & tagged4(v1) & tagged4(v2) & tagged4(v3))) break;
      }
      __syncwarp();
      TL_MARK2(26, lane == 0);
      v.x = (v.x + v1.x) + (v2.x + v3.x); v.y = (v.y + v1.y) + (v2.y + v3.y); v.z = (v.z + v1.z) + (v2.z + v3.z);
      v.x += __shfl_xor_sync(0xffffffffu, v.x, 1); v.y += __shfl_xor_sync(0xffffffffu, v.y, 1); v.z += __shfl_xor_sync(0xffffffffu, v.z, 1);
      const float mean = v.x * (1.0f / T_D);
      const float var = fmaxf(fmaf(-mean, mean, v.y * (1.0f / T_D)), 0.f);
      const uint32_t mb2 = pack_bf16(mean, mean);
      const float inv = rcp_approx(rbf(sqrt_approx(rbf(rbf(var) + 1e-05f))));
      {
        const float2 sc = lds_f32x2(sbase + OG_SMISC);
        const uint32_t key = rank_key(rbf(fmaf(fmaf(-bflo(mb2), sc.x, v.z), inv, sc.y)), m0 + 16 * w8 + (lane >> 1));
        mbar_wait(bar_end, 0);
        if (lane & 1) sts_u32(sbase + OG_SSTAT + 1024 + (16 * w8 + (lane >> 1)) * 4, key);
        else sts_u32x2(sbase + OG_SSTAT + (16 * w8 + (lane >> 1)) * 8, mb2, __float_as_uint(inv));
        __syncwarp();
        if (lane == 0) mbar_arrive(bar_key);
      }
      const uint32_t ih = pack_bf16(inv, inv), il = pack_bf16(inv - bflo(ih), inv - bflo(ih));
      const uint32_t mba = __shfl_sync(0xffffffffu, mb2, 2 * (lane >> 2)), mbb = __shfl_sync(0xffffffffu, mb2, 2 * (lane >> 2) + 16);
      const uint32_t iha = __shfl_sync(0xffffffffu, ih, 2 * (lane >> 2)), ihb = __shfl_sync(0xffffffffu, ih, 2 * (lane >> 2) + 16);
      const uint32_t ila = __shfl_sync(0xffffffffu, il, 2 * (lane >> 2)), ilb = __shfl_sync(0xffffffffu, il, 2 * (lane >> 2) + 16);
      #pragma unroll 1
      for (int J0 = 0; J0 < 16; J0 += 4) {
        uint32_t xr[2][4], cv[4][3];
        #pragma unroll
        for (int i = 0; i < 2; i++) {
          ldmatrix_x4(sbase + OG_XSLOT + (J0 >> 3) * 16384 + frag + ((((J0 & 7) + 2 * i + fhi) ^ fsw) << 4), xr[i][0], xr[i][1], xr[i][2], xr[i][3]);
          #pragma unroll
          for (int h = 0; h < 2; h++)
            #pragma unroll
            for (int k = 0; k < 3; k++) cv[2 * i + h][k] = lds_u32(sbase + OG_SCOL + 768 + 256 * k + (8 * (J0 + 2 * i + h) + q2) * 2);
        }
        #pragma unroll
        for (int i = 0; i < 2; i++) {
          #pragma unroll
          for (int h = 0; h < 2; h++) {
            xr[i][2 * h] = out2(xr[i][2 * h], mba, iha, ila, cv[2 * i + h][0], cv[2 * i + h][1], cv[2 * i + h][2]);
            xr[i][2 * h + 1] = out2(xr[i][2 * h + 1], mbb, ihb, ilb, cv[2 * i + h][0], cv[2 * i + h][1], cv[2 * i + h][2]);
          }
          stmatrix_x4(sbase + OG_OSLOT + (J0 >> 3) * 16384 + frag + ((((J0 & 7) + 2 * i + fhi) ^ fsw) << 4), xr[i][0], xr[i][1], xr[i][2], xr[i][3]);
        }
      }
      fence_proxy_async();
      mbar_wait(bar_full + 352, 0);
      const uint2 cg = lds_u32x2(sbase + OG_SMISC + 96);
      __syncwarp();
      if (elect_one()) {
        mbar_arrive(bar_out);
        if (cg.x != w8 && cg.y != w8) {
          asm volatile("cp.async.bulk.tensor.2d.global.shared::cta.bulk_group [%0, {%2, %3}], [%1];" :: "l"(tmOut), "r"(sbase + OG_OSLOT + w8 * 2048), "r"(n0), "r"(m0 + 16 * w8) : "memory");
          asm volatile("cp.async.bulk.tensor.2d.global.shared::cta.bulk_group [%0, {%2, %3}], [%1];" :: "l"(tmOut), "r"(sbase + OG_OSLOT + 16384 + w8 * 2048), "r"(n0 + 64), "r"(m0 + 16 * w8) : "memory");
          bulk_commit();
        }
      }
      TL_MARK2(24, lane == 0);
    }
    if (has_moe) mbar_wait(bar_h2, 0);
    TL_MARK2(13, lane == 0);
    if (has_moe) {
      const GemvSel sel = gemv_sel(lane);
      {
        float d[4][4];
        #pragma unroll
        for (int c = 0; c < 4; c++) { d[c][0] = 0.f; d[c][1] = 0.f; d[c][2] = 0.f; d[c][3] = 0.f; }
        #pragma unroll
        for (int st = 0; st < 8; st++) {
          const uint2 hb = lds_u32x2(sbase + OG_SH2 + ((lane >> 2) & 1) * 2048 + (w8 * 128 + st * 16 + (lane & 3) * 4) * 2);
          #pragma unroll
          for (int j = 0; j < 4; j++) mma_bf16(d[j], wv[4 * st + j].x, wv[4 * st + j].y, wv[4 * st + j].z, wv[4 * st + j].w, GEMV_B0(j, hb, sel), GEMV_B1(j, hb, sel));
        }
        #pragma unroll
        for (int e = 0; e < 4; e++) d[0][e] = (d[0][e] + d[1][e]) + (d[2][e] + d[3][e]);
        sts_f32x4(sbase + OG_SRED + t2 * 16, d[0][0], d[0][1], d[0][2], d[0][3]);
      }
      named_bar_sync(9, 256);
      if (t2 < 64) {
        const int c = gemv_col(t2);
        float gp[8], up[8];
        #pragma unroll
        for (int w = 0; w < 8; w++) { gp[w] = lds_f32(sbase + OG_SRED + w * 512 + t2 * 4); up[w] = lds_f32(sbase + OG_SRED + w * 512 + 256 + t2 * 4); }
        const float gs = ((gp[0] + gp[1]) + (gp[2] + gp[3])) + ((gp[4] + gp[5]) + (gp[6] + gp[7]));
        const float us = ((up[0] + up[1]) + (up[2] + up[3])) + ((up[4] + up[5]) + (up[6] + up[7]));
        asm volatile("st.shared.u16 [%0], %1;" :: "r"(sbase + OG_SGU + (t2 & 1) * 64 + ((c & ~15) + ((c >> 1) & 3) * 4 + ((c >> 3) & 1) * 2 + (c & 1)) * 2), "h"((uint16_t)pack_bf16(silu_bf(rbf(gs)) * rbf(us), 0.f)) : "memory");
      }
      named_bar_sync(9, 256);
      TL_MARK2(20, threadIdx.x == 128);
      float d[4][4];
      #pragma unroll
      for (int c = 0; c < 4; c++) { d[c][0] = 0.f; d[c][1] = 0.f; d[c][2] = 0.f; d[c][3] = 0.f; }
      #pragma unroll
      for (int st = 0; st < 2; st++) {
        const uint2 g = lds_u32x2(sbase + OG_SGU + ((lane >> 2) & 1) * 64 + st * 32 + (lane & 3) * 8);
        #pragma unroll
        for (int j = 0; j < 4; j++) {
          const uint32_t b0 = GEMV_B0(j, g, sel), b1 = GEMV_B1(j, g, sel);
          mma_bf16(d[j & 1], wd[4 * st + j].x, wd[4 * st + j].y, wd[4 * st + j].z, wd[4 * st + j].w, b0, b1);
          mma_bf16(d[2 + (j & 1)], wd[8 + 4 * st + j].x, wd[8 + 4 * st + j].y, wd[8 + 4 * st + j].z, wd[8 + 4 * st + j].w, b0, b1);
        }
      }
      #pragma unroll
      for (int e = 0; e < 4; e++) { d[0][e] += d[1][e]; d[2][e] += d[3][e]; }
      float* yp = g_ypart + (size_t)bid * 2 * T_D + w8 * 256 + lane * 4;
      st_tagged4_lsb(yp, d[0][0], d[0][1], d[0][2], d[0][3]);
      st_tagged4_lsb(yp + 128, d[2][0], d[2][1], d[2][2], d[2][3]);
      named_bar_sync(9, 256);
      if (t2 == 0) hint_arrive(CNT_Y);
    }
    bulk_wait_read<0>();
    TL_MARK2(14, threadIdx.x == 128);
    TL_CLK(4, 1, threadIdx.x == 128);
}

__device__ __forceinline__ int help_njobs(uint32_t bid) { return bid < 128 ? OG_JOBS : 16 - OG_JOBS; }
__device__ __forceinline__ int help_job(uint32_t bid, int i) { return (i < OG_JOBS ? 16 * i + (bid >> 7) * 2 : 112 + (i - OG_JOBS) * 2) + (bid & 3) * 4; }
__device__ __noinline__ void store_warp(uint32_t bid, uint32_t sbase, const CUtensorMap* tmO, int item0, int n_items) {
  if (elect_one()) {
    const uint32_t bars = sbase + AT_SBAR, b_q0 = bars + 80, b_ob = bars + 96, b_ordy = bars + 104, b_acq = bars + 264;
    const unsigned int* cnt = g_hcnt + 32 * (1 + OG_MT(124)) + 2;
    #pragma unroll 1
    for (int q = 0; q < 4 * n_items; q++) {
      const int item = item0 + (q >> 2) * 128, h = (q >> 1) & 1, w = q & 1;
      const bool last = (q >> 2) == n_items - 1;
      if (q == 4 * n_items - 4) { mbar_wait_long(bars + 288, 0); red_release_add(&g_hcnt[1], 1u); }
      mbar_wait_long(b_ordy + 8 * (q & 3), q >> 2);
      store_o(tmO, (h ? (last ? sbase + AT_SQ + 32768 : sbase + 2 * 32768) : sbase + AT_SQ) + w * 8192, (item >> 4) * 2 + h, (item & 15) * 128 + w * 64);
      if (w) {
        bulk_wait_read<0>();
        mbar_arrive(h ? b_ob : b_q0);
        bulk_wait<0>();
        fence_proxy_async_global();
        asm volatile("fence.acq_rel.gpu;" ::: "memory");
        hint_arrive(&g_hcnt[32 * (1 + (item & 15)) + 2 + (item >> 7)]);
        if (!h && item < 128) hint_arrive(&g_hcnt[2]);
        if (q == 5) { const int tb = tail_tile(sbase); cnt = g_hcnt + 32 * (1 + OG_MT(tb)) + 2; spin_until(cnt, 16u); mbar_arrive(b_acq); }
      }
    }
    if (n_items == 1) {
      #pragma unroll 1
      for (int i = 0; i < help_njobs(bid); i++) {
        mbar_wait_long(b_acq + 16, i & 1);
        TL_MARK2(23, i == OG_JOBS - 1);
        red_release_add(&g_hcnt[32 * (1 + (help_job(bid, i) >> 3)) + 4 + ((help_job(bid, i) >> 1) & 3)], 1u);
        TL_MARK2(4, i == OG_JOBS - 1);
        if (i == PRE_X - 1) { spin_until(&g_hcnt[1], 132u); mbar_arrive(b_acq + 32); }
      }
    }
    if (bid < 128) {
      if (n_items == 1) { spin_until(cnt, 16u); mbar_arrive(b_acq); }
      spin_until(&g_hcnt[0], 128u); spin_until(cnt + 1, 16u); mbar_arrive(b_acq + 80);
    }
  }
}

__device__ __forceinline__ uint32_t role_of_sm(uint32_t sm) {
  const uint32_t t = sm >> 1, u = t - 32u, d = (u * 37u) >> 8;
  return (t < 32u ? ((t + 7u) & 7u) * 16u + (t >> 3) * 2u : t < 60u ? (u - 7u * d) * 16u + (4u + d) * 2u : t < 62u ? 2u * t + 8u : 2u * t - 4u) + (sm & 1u);
}
__global__ void __launch_bounds__(384, 1)
fused_kernel(const __grid_constant__ CUtensorMap tmH, const __grid_constant__ CUtensorMap tmW, const __grid_constant__ CUtensorMap tmK,
            const __grid_constant__ CUtensorMap tmV, const __grid_constant__ CUtensorMap tmO, const __grid_constant__ CUtensorMap tmOl, const __grid_constant__ CUtensorMap tmWo,
            const __grid_constant__ CUtensorMap tmD, const __grid_constant__ CUtensorMap tmOut, const __grid_constant__ CUtensorMap tmM, uint32_t zero,
            const uint8_t* __restrict__ pf_wo, const bf16* __restrict__ kc, const bf16* __restrict__ vc,
            const bf16* __restrict__ x, const bf16* __restrict__ cvec, const bf16* __restrict__ w_mod, const bf16* __restrict__ w_r,
            const bf16* __restrict__ w_gate, const bf16* __restrict__ w_up, const bf16* __restrict__ w_down, bf16* __restrict__ out)
{
  uint32_t bid, nsm;
  asm volatile("mov.u32 %0, %%smid;" : "=r"(bid));
  asm volatile("mov.u32 %0, %%nsmid;" : "=r"(nsm));
  bid = __shfl_sync(0xffffffffu, nsm == 132u ? role_of_sm(bid) : blockIdx.x, 0);
  extern __shared__ __align__(1024) uint8_t smem_raw[];
  const uint32_t sbase = smem_u32(smem_raw);
  const uint32_t bars = sbase + AT_SBAR;
  const uint32_t b_full = bars, b_empty = bars + 40;
  const uint32_t b_q0 = bars + 80, b_q1 = bars + 88;
  const uint32_t b_ob = bars + 96;
  const uint32_t b_ordy = bars + 104;
  const uint32_t b_pin = bars + 136;
  const uint32_t b_head = bars + 144;
  const uint32_t b_go = bars + 152;
  const uint32_t b_x = bars + 160;
  const int wg = __shfl_sync(0xffffffffu, threadIdx.x >> 7, 0);
  const bool single = bid >= AT_NFULL;
  const int item0 = __shfl_sync(0xffffffffu, bid < 128 ? (int)bid : (int)bid + 124, 0), n_items = __shfl_sync(0xffffffffu, single ? 1 : 2, 0);
  TL_START(3);
  if (threadIdx.x == 0) {
    if (sbase & 1023u) __trap();
    for (int i = 0; i < 5; i++) { mbar_init(b_full + 8 * i, 1); mbar_init(b_empty + 8 * i, 2); }
    mbar_init(b_q0, 1); mbar_init(b_q1, 8); mbar_init(b_ob, 1);
    for (int i = 0; i < 4; i++) mbar_init(b_ordy + 8 * i, 4);
    mbar_init(b_pin, 1); mbar_init(b_head, bid < 128 ? 8 : 1); mbar_init(b_go, 1); mbar_init(b_x, 1);
    mbar_init(bars + 168, 2); mbar_init(bars + 176, 1); mbar_init(bars + 184, 8); mbar_init(bars + 192, 2);
    mbar_init(bars + 200, 8); mbar_init(bars + 208, 4); mbar_init(bars + 216, 1); mbar_init(bars + 264, 1); mbar_init(bars + 272, 1); mbar_init(bars + 280, 8); mbar_init(bars + 288, 1); mbar_init(bars + 296, 1); mbar_init(bars + 304, 8); mbar_init(bars + 312, 1); mbar_init(bars + 320, 1); mbar_init(bars + 328, 1); mbar_init(bars + 336, 1); mbar_init(bars + 344, 1); mbar_init(bars + 352, 1); mbar_init(bars + 360, 1); mbar_init(bars + 368, 2); mbar_init(bars + 376, 2);
    sts_u32(bars + 400, bid);
    fence_mbar_init();
  }

  if (wg == 0) {
    reg_dealloc<AT_PREG>();
    if (threadIdx.x < 32) { __syncwarp(); named_bar_arrive(6, 384); }
    if (threadIdx.x >= 64) {
      named_bar_sync(6, 384);
      if (bid < 128) {
        named_bar_sync(threadIdx.x >= 96 ? 8 : 9, 288);
        if ((threadIdx.x & 31) == 0) red_release_add(&g_hcnt[32 * (1 + (bid >> 3)) + (threadIdx.x >= 96)], 1u);
        TL_MARK2(11, threadIdx.x == 64);
      }
      if (bid < 128) {
        mbar_wait(MOD_AT, 0);
        mod_rest(bid, sbase + OG_SCOL, b_q1, threadIdx.x - 64, cvec, w_mod, w_r);
      }
    } else if (threadIdx.x >= 32) {
      named_bar_sync(6, 384);
      store_warp(bid, sbase, &tmO, item0, n_items);
      __syncwarp();
    } else {
     if (elect_one()) {
      const uint64_t pol = policy_evict_first();
      if (bid < 128) {
        mbar_expect_tx(b_x, 32768);
        if (X_DLY) { const uint32_t c0 = clock_lo(); while (clock_lo() - c0 < X_DLY) {} }
        bulk_load_hint(sbase + 4 * 32768, x + (size_t)bid * 16 * T_D, 32768, b_x, pol);
      }
      prefetch_tmap(&tmW); prefetch_tmap(&tmM); prefetch_tmap(&tmH); prefetch_tmap(&tmWo); prefetch_tmap(&tmOl);
      {
        const uint32_t c0 = clock_lo();
        while (clock_lo() - c0 < W_DLY) {}
        if (bid < 128 && (head_cb(bid) & 15) >= 4 * H_SPLIT) {
          mbar_expect_tx(bars + 328, 32768);
          tma_load_2d_hint(sbase + 3 * 32768, &tmM, head_cb(bid) * 64, (bid >> 5) * 256, bars + 328, pol);
        }
        while (clock_lo() - c0 < W_DLY + W_FIRST) {}
      }
      uint32_t slot = 0, ph = 1;
      #pragma unroll 1
      for (int it = 0; it < n_items; it++) {
        const int item = item0 + it * 128, hp = item >> 4, qt = item & 15;
        const bool first = it == 0;
        #pragma unroll 1
        for (int j = 0; j < T_D / 64; j++) {
          const uint32_t sl = ring_slot(qp_pos(j, it)), fb = b_full + 8 * sl;
          mbar_wait_long(b_empty + 8 * sl, ring_par(qp_pos(j, it)) ^ ((j >> 2) & 1) ^ 1);
          if (first && j == 3) mbar_wait(b_head, 0);
          mbar_expect_tx(fb, 49152);
          tma_load_3d_hint(sbase + sl * 32768, &tmW, j * 64, hp * 4, fb, pol);
          if (first && j < PRE_B) {
            if (j == PRE_B - 1) {
              spin_until(&g_hcnt[32 * (1 + qt)], 8u);
              TL_MARK2(16, true);
              fence_proxy_async_global();
              #pragma unroll 1
              for (int i = 0; i < PRE_B; i++) tma_load_2d(sbase + AT_SQ + i * 16384, &tmH, i * 64, qt * 128, b_full + 8 * i);
              mbar_arrive(b_go);
            }
          } else {
            if (first && j == 4 * H_SPLIT) { spin_until(&g_hcnt[32 * (1 + qt) + 1], 8u); fence_proxy_async_global(); }
            if (!first && (j == 0 || j == 2)) mbar_wait(j ? b_q1 : b_q0, 0);
            tma_load_2d(sbase + AT_SQ + (j & 3) * 16384, &tmH, j * 64, qt * 128, fb);
          }
        }
        #pragma unroll 1
        for (int j = 0; j < 4 * AT_NBLK; j++) {
          const bool isv = (j > 0 && !(j & 1)) || j == 4 * AT_NBLK - 1;
          const int row = hp * 2 * T_SEQ + (isv ? (j - 1) >> 1 : (j + 1) >> 1) * 128;
          const uint32_t fb = b_full + 8 * slot;
          mbar_wait_long(b_empty + 8 * slot, ph);
          if (!first && j == 3) mbar_wait(b_ob, 0);
          if (j == 4 && it == n_items - 1) mbar_arrive(bars + 288);
          if ((j == AL_P || j == RK_P) && it == 1) mbar_arrive(bars + 312);
          mbar_expect_tx(fb, 32768);
          tma_load_3d_hint(sbase + slot * 32768, isv ? &tmV : &tmK, row, 0, fb, pol);
          if (it == 1 && isv && j >= 2 * WO_LATE && j < 2 * WO_LATE + 32 && bid < OG_NKB)
            l2_prefetch_bulk(pf_wo + (size_t)own_kb(bid, og_pre(0)) * 131072 + ((j >> 1) - WO_LATE) * 8192, 8192);
          if (++slot == 5) { slot = 0; ph ^= 1; }
        }
      }
      if (__builtin_expect(single, 0)) {
        spin_until(&g_hcnt[2], 128u);
        fence_proxy_async_global();
        const int nj = OG_HSUM + (help_njobs(bid) - OG_JOBS) * OG_PRE2;
        int ji = 0, job = help_job(bid, 0), kk = 0;
        #pragma unroll 1
        for (int j = 0; j < nj; j++) {
          const uint32_t sl = ring_slot(qp_pos(j, 1)), fb = b_full + 8 * sl;
          mbar_wait_long(b_empty + 8 * sl, ring_par(qp_pos(j, 1)) ^ ((j >> 2) & 1) ^ 1);
          mbar_expect_tx(fb, 49152);
          tma_load_3d(sbase + sl * 32768, &tmWo, pre_kb(kk) * 64, OG_NT(job) * 2, fb);
          tma_load_3d(sbase + sl * 32768 + 16384, &tmWo, pre_kb(kk) * 64, OG_NT(job) * 2 + 2, fb);
          if (j == 0 || j == 2) mbar_wait(j ? b_ob : b_q0, 0);
          tma_load_2d_hint(sbase + AT_SQ + (j & 3) * 16384, &tmOl, pre_kb(kk) * 64, OG_MT(job) * 128, fb, pol);
          if (++kk == og_pre(job)) { kk = 0; job = help_job(bid, ++ji); }
        }
      }
      if (bid < 128) {
        if (single) mbar_wait(b_x, 1);
        tail_producer(bid, sbase, 0, pol, &tmOl, &tmWo, &tmD);
      }
     }
    }
    named_bar_sync(12 + (threadIdx.x >> 5), 32);
    if (bid < 128) tail_exchange(bid, sbase, w_down, w_r, x, out);
  } else {
    if (bid < 128) head_phase(bid, sbase + AT_SQ + 49152, sbase + 4 * 32768, b_x, b_go, b_head, threadIdx.x - 128, zero, cvec, w_mod);
    else { named_bar_sync(6, 384); if (threadIdx.x == 128) mbar_arrive(b_head); }
    TL_MARK2(0, threadIdx.x == 128);
    reg_alloc<AT_CREG>();
    const int cwg = wg - 1;
    const int tid = threadIdx.x & 127;
    const int warp = tid >> 5, lane = tid & 31;
    const uint32_t dbase = (sbase & 0x3FFFFu) >> 4;
    const uint32_t k_base = dbase + (1u << 16);
    const uint32_t v_base = dbase + (1024u << 16);
    const uint32_t w_base = dbase + (512u << 16);
    const uint32_t q_lo = dbase + ((AT_SQ + cwg * 8192) >> 4) + (1u << 16);
    const uint32_t frag = cwg * 8192 + (16 * warp + (lane & 7) + 8 * ((lane >> 3) & 1)) * 128;
    if (cwg == 1) named_bar_arrive(1, 256);
    bool raw = false;
    uint4 pre[8];
    #pragma unroll 1
    for (int it = 0; it < n_items; it++) {
      const bool more = it + 1 < n_items;
      constexpr int nkb = T_D / 64;
      const int ta = __shfl_sync(0xffffffffu, 4 * it, 0);
      float acc[128];
      {
        FS(2 * it, 0);
        #pragma unroll
        for (int i = 0; i < 128; i++) asm volatile("" : "=f"(acc[i]));
        {
          const uint32_t slot = ring_slot(ta), b_lo = w_base + slot * 2048;
          mbar_wait(b_full + 8 * slot, ring_par(ta));
          wgmma_fence();
          wgmma_m64n256k16_ss_tb<0, 0>(acc, q_lo, b_lo, 0);
          wgmma_m64n256k16_ss_tb<2, 128>(acc, q_lo, b_lo, 1);
          wgmma_m64n256k16_ss_tb<4, 256>(acc, q_lo, b_lo, 1);
          wgmma_m64n256k16_ss_tb<6, 384>(acc, q_lo, b_lo, 1);
          wgmma_commit();
        }
        #pragma unroll 1
        for (int j = 1; j < nkb; j++) {
          const uint32_t slot = ring_slot(qp_pos(j, ta >> 2));
          mbar_wait(b_full + 8 * slot, ring_par(qp_pos(j, ta >> 2)) ^ ((j >> 2) & 1));
          const bool pause = cwg == 1 && j == nkb - QP_STAG;
          if (pause) {
            wgmma_wait<0>();
            if (tid == 0) mbar_arrive(b_empty + 8 * ring_slot(qp_pos(j - 1, ta >> 2)));
            named_bar_sync(7, 256);
          }
          const uint32_t a_lo = q_lo + (j & 3) * 1024, b_lo = w_base + slot * 2048;
          wgmma_fence();
          wgmma_m64n256k16_ss_tb<0, 0>(acc, a_lo, b_lo, 1);
          wgmma_m64n256k16_ss_tb<2, 128>(acc, a_lo, b_lo, 1);
          wgmma_m64n256k16_ss_tb<4, 256>(acc, a_lo, b_lo, 1);
          wgmma_m64n256k16_ss_tb<6, 384>(acc, a_lo, b_lo, 1);
          wgmma_commit();
          if (QP_STAG > 0 && cwg == 0 && j == nkb - 1) named_bar_arrive(7, 256);
          if (j > 0) {
            wgmma_wait<1>();
            if (tid == 0 && !pause) mbar_arrive(b_empty + 8 * ring_slot(qp_pos(j - 1, ta >> 2)));
          }
        }
        wgmma_wait<0>();
        fence_regs(acc);
        FS(2 * it, 1);
        TL_MARK2(29, threadIdx.x == 256 && it == 0);
        if (tid == 0) mbar_arrive(b_empty + 24);
      }
      float o[64], s[64];
      uint32_t p[32], q[32];
      #pragma unroll
      for (int i = 0; i < 32; i++) q[i] = pack_bf16(acc[2 * i] * AT_C, acc[2 * i + 1] * AT_C);
      zero_regs(s);
      const uint32_t sq = sbase + AT_SQ + cwg * 8192;
      float mc0, mc1, al0 = 1.0f, al1 = 1.0f, l0 = 0.f, l1 = 0.f, lp0 = 0.f, lp1 = 0.f;
      bool redo0 = false;
      FS(2 * it, 2);
      mbar_wait(b_full + 8 * ring_slot(ta), ring_par(ta));
      named_bar_sync(1 + cwg, 256);
      FS(2 * it, 3);
      issue_qk(s, q, k_base + ring_slot(ta) * 2048);
      pass_turn(cwg);
      bool ready = mbar_test(b_full + 8 * ring_slot(ta + 1), ring_par(ta + 1)) & mbar_test(b_full + 8 * ring_slot(ta + 2), ring_par(ta + 2));
      stage_q<16>(acc, AT_C, sbase + AT_SQ + frag, lane);
      wgmma_wait<0>();
      fence_regs(s);
      if (tid == 0) mbar_arrive(b_empty + 8 * ring_slot(ta));
      mc0 = 0.f; mc1 = 0.f;
      if (!raw) {
        const float a = fmaxf(fmaxf(fmaxf(s[0], s[1]), fmaxf(s[4], s[5])), fmaxf(fmaxf(s[8], s[9]), fmaxf(s[12], s[13])));
        const float b = fmaxf(fmaxf(fmaxf(s[2], s[3]), fmaxf(s[6], s[7])), fmaxf(fmaxf(s[10], s[11]), fmaxf(s[14], s[15])));
        raw = __all_sync(0xffffffffu, fabsf(a) <= 16.0f && fabsf(b) <= 16.0f);
      }
      if (!raw) {
        raw = softmax_mode(s, mc0, mc1);
        if (__builtin_expect(!raw, 0)) softmax_sub(s, mc0, mc1);
      }
      softmax_exp<0, 64>(s);
      #pragma unroll
      for (int J = 0; J < 16; J += 2)
        stmatrix_x4(sbase + AT_SQ + frag + (J >> 3) * 16384 + ((((J & 7) + (lane >> 4)) ^ (lane & 7)) << 4), q[2 * J], q[2 * J + 1], q[2 * J + 2], q[2 * J + 3]);
      pack_p(p, s);
      zero_regs(o);
      FS(2 * it, 4);
      uint32_t ks = ring_slot(ta + 1), vs = ring_slot(ta + 2), kp = ring_par(ta + 1), vp = ring_par(ta + 2);
      auto finish_head = [&]() {
        FS(2 * it, 5);
        redo0 = finish_l(lp0, lp1);
        if (!redo0) stage_o(o, lp0, lp1, sbase + AT_SQ + frag, lane);
        FS(2 * it + 1, 4);
      };
      if (!ready) { mbar_wait(b_full + 8 * ks, kp); mbar_wait(b_full + 8 * vs, vp); }
      #pragma unroll 1
      for (int n = 1; n < 2 * AT_NBLK; n++) {
        named_bar_sync(1 + cwg, 256);
        issue_qk(s, q, k_base + ks * 2048);
        if (n == AT_NBLK + 1) finish_head();
        issue_pv(o, p, v_base + vs * 2048, (n & 15) != 1);
        pass_turn(cwg);
        wgmma_wait<1>();
        fence_regs(s);
        if (tid == 0) mbar_arrive(b_empty + 8 * ks);
        if (__builtin_expect(!raw || (uint32_t)(n - (AT_NBLK - 1)) <= 2u, 0)) {
          if (n == AT_NBLK + 1 && !redo0) {
            fence_proxy_async();
            __syncwarp();
            if (lane == 0) mbar_arrive(b_ordy + 8 * cwg);
          }
          if (n == AT_NBLK - 1) {
            #pragma unroll
            for (int J = 0; J < 16; J += 2)
              ldmatrix_x4(sbase + AT_SQ + 32768 + frag + (J >> 3) * 16384 + ((((J & 7) + (lane >> 4)) ^ (lane & 7)) << 4), q[2 * J], q[2 * J + 1], q[2 * J + 2], q[2 * J + 3]);
          }
          if (!raw) {
            const float m0 = mc0, m1 = mc1;
            const bool ok = softmax_mode(s, mc0, mc1);
            if (n == AT_NBLK) raw = ok;
            else {
              mc0 = mc0 - AT_HEAD > m0 ? mc0 : m0; mc1 = mc1 - AT_HEAD > m1 ? mc1 : m1;
              al0 = ex2_approx(m0 - mc0); al1 = ex2_approx(m1 - mc1);
            }
            if (!raw) softmax_sub(s, mc0, mc1);
          }
        }
        softmax_exp<0, AT_SPLIT>(s);
        add_rowsum(p, l0, l1);
        if (zero != 0) {
          uint32_t dep = zero & __float_as_uint(l0) & __float_as_uint(l1);
          #pragma unroll
          for (int i = AT_SPLIT - AT_PIN - PINB; i < AT_SPLIT - PINB; i += 2) dep &= __float_as_uint(s[i]) & __float_as_uint(s[i + 1]);
          mbar_arrive(b_pin + dep);
        }
        wgmma_wait<0>();
        fence_regs(o);
        if (tid == 0) mbar_arrive(b_empty + 8 * vs);
        ks += 2; if (ks >= 5) { ks -= 5; kp ^= 1; }
        vs += 2; if (vs >= 5) { vs -= 5; vp ^= 1; }
        ready = mbar_test(b_full + 8 * ks, kp) & mbar_test(b_full + 8 * vs, vp);
        softmax_exp<AT_SPLIT, 64>(s);
        pack_p(p, s);
        if (n == AT_NBLK) { lp0 = l0; lp1 = l1; l0 = 0.f; l1 = 0.f; }
        if (__builtin_expect(!raw || !ready, 0)) {
        if (!raw && __any_sync(0xffffffffu, al0 != 1.0f || al1 != 1.0f)) {
          rescale_o(o, al0, al1);
          l0 *= al0; l1 *= al1;
          al0 = 1.0f; al1 = 1.0f;
        }
        if (!ready && n < 2 * AT_NBLK - 1) {
          mbar_wait(b_full + 8 * ks, kp);
          mbar_wait(b_full + 8 * vs, vp);
        }
        }
      }
      FS(2 * it + 1, 5);
      const uint32_t vl = ring_slot(ta + 63);
      vs = ring_slot(ta + 62);
      const uint32_t ob = more ? sbase + vs * 32768 : sbase + AT_SQ + 32768;
      mbar_wait(b_full + 8 * vl, ring_par(ta + 63));
      issue_pv(o, p, v_base + vl * 2048, 1);
      block_end(zero, b_pin);
      add_rowsum(p, l0, l1);
      const bool overflow = finish_l(l0, l1);
      if (!overflow && lane == 0) mbar_arrive(b_q1);
      #pragma unroll
      for (int i = 0; i < 8; i++) asm volatile("mov.b64 {%0, %1}, 0;\nmov.b64 {%2, %3}, 0;" : "=r"(pre[i].x), "=r"(pre[i].y), "=r"(pre[i].z), "=r"(pre[i].w));
      const bool want_pre = !more && bid < OG_MOE, got_pre = want_pre && __all_sync(0xffffffffu, mbar_test(bars + 272, 0));
      if (got_pre) load_pre(pre, sbase, AT_SQ, threadIdx.x - 128);
      mbar_wait(b_empty + 8 * vs, ring_par(ta + 62));
      wgmma_wait<0>();
      fence_regs(o);
      if (tid == 0) mbar_arrive(b_empty + 8 * vl);
      FS(2 * it + 1, 6);
      if (overflow) {
        attn_rows_exact(lds_u32(bars + 400), sq + 32768, ob + cwg * 8192, 4 * ta + 1, kc, vc);
        __syncwarp();
        if (lane == 0) mbar_arrive(b_q1);
      } else stage_o(o, l0, l1, ob + frag, lane);
      if (redo0) attn_rows_exact(lds_u32(bars + 400), sq, sq, 4 * ta, kc, vc);
      fence_proxy_async();
      __syncwarp();
      if (lane == 0) {
        if (redo0) mbar_arrive(b_ordy + 8 * cwg);
        mbar_arrive(b_ordy + 16 + 8 * cwg);
      }
      if (want_pre && !got_pre) load_pre(pre, sbase, AT_SQ, threadIdx.x - 128);
      if (redo0 || overflow) raw = false;
      named_bar_sync(3 + cwg, 128);
      FS(2 * it + 1, 7);
    }
    if (cwg == 0) named_bar_arrive(1, 256);
    if (__builtin_expect(single, 0)) {
      float acc[128];
      uint32_t j = 0, pk[64];
      #pragma unroll
      for (int i = 0; i < 64; i++) asm volatile("" : "=f"(acc[2 * i]), "=f"(acc[2 * i + 1]), "=r"(pk[i]));
      uint4* dst = g_pre;
      int left = 0;
      auto put = [&](bool last) {
        #pragma unroll
        for (int i = 0; i < PUT_N; i++) dst[i * 256] = make_uint4(pk[4 * i], pk[4 * i + 1], pk[4 * i + 2], pk[4 * i + 3]);
        dst += PUT_N * 256;
        #pragma unroll
        for (int i = 0; i < 64 - 4 * PUT_N; i++) asm volatile("mov.b32 %0, %1;" : "=r"(pk[i]) : "r"(pk[i + 4 * PUT_N]));
        __syncwarp();
        if (last && lane == 0) mbar_arrive(bars + 280);
      };
      #pragma unroll 1
      for (int ji = 0; ji < help_njobs(bid); ji++) {
        const int nk = og_pre(help_job(bid, ji));
        #pragma unroll 1
        for (int kk = 0; kk < nk; kk++, j++) {
          const uint32_t slot = ring_slot(qp_pos(j, 1));
          mbar_wait(b_full + 8 * slot, ring_par(qp_pos(j, 1)) ^ ((j >> 2) & 1));
          if (H_STAG > 0 && cwg == 1 && kk == nk - H_STAG) named_bar_sync(7, 256);
          const uint32_t a_lo = q_lo + (j & 3) * 1024, b_lo = w_base + slot * 2048;
          wgmma_fence();
          wgmma_m64n256k16_ss_tb<0, 0>(acc, a_lo, b_lo, kk != 0);
          wgmma_m64n256k16_ss_tb<2, 128>(acc, a_lo, b_lo, 1);
          wgmma_m64n256k16_ss_tb<4, 256>(acc, a_lo, b_lo, 1);
          wgmma_m64n256k16_ss_tb<6, 384>(acc, a_lo, b_lo, 1);
          wgmma_commit();
          if (H_STAG > 0 && cwg == 0 && kk == nk - 1) named_bar_arrive(7, 256);
          wgmma_wait<1>();
          if (kk > 0 && tid == 0) mbar_arrive(b_empty + 8 * ring_slot(qp_pos(j - 1, 1)));
          #pragma unroll 1
          for (int i = ji == OG_JOBS ? 0 : 16 / PUT_N - 1; i < 16 / PUT_N && left > 0; i++) put(--left == 0);
        }
        wgmma_wait<0>();
        fence_regs(acc);
        if (tid == 0) mbar_arrive(b_empty + 8 * ring_slot(qp_pos(j - 1, 1)));
        #pragma unroll
        for (int i = 0; i < 64; i++) pk[i] = pack_bf16(acc[2 * i], acc[2 * i + 1]);
        left = 16 / PUT_N;
        if (ji == PRE_X) mbar_wait(bars + 296, 0);
        dst = g_pre + help_job(bid, ji) * 2048 + threadIdx.x - 128;
      }
      #pragma unroll
      for (int i = 0; i < 16; i++) dst[i * 256] = make_uint4(pk[4 * i], pk[4 * i + 1], pk[4 * i + 2], pk[4 * i + 3]);
      __syncwarp();
      if (lane == 0) mbar_arrive(bars + 280);
      named_bar_sync(5, 256);
      if (threadIdx.x == 128) {
        #pragma unroll 1
        for (int i = 0; i < 5; i++) {
          constexpr int n = OG_HSUM;
          const int used = i == 3 ? 0 : (n + 3 - (i == 4 ? 3 : i)) / 4;
          if ((used ^ (i < 4)) & 1) {
            mbar_arrive(b_full + 8 * ring_slot(4 + i));
            mbar_arrive(b_empty + 8 * ring_slot(4 + i)); mbar_arrive(b_empty + 8 * ring_slot(4 + i));
          }
        }
        mbar_arrive(b_x);
      }
      named_bar_sync(5, 256);
      #pragma unroll
      for (int i = 0; i < 8; i++) pre[i] = make_uint4(0u, 0u, 0u, 0u);
    }
    TL_CLK(3, 1, threadIdx.x == 128);
    TL_CTA(1, threadIdx.x == 256);
    TL_END(3, tid == 0);
    TL_MARK2(19, tid == 0 && !single);
    if (bid < 128) {
      tail_consumer(bid, sbase, &tmOut, pre, cwg, w_gate, w_up);
    }
  }
}

typedef CUresult (*PFN_encodeTiled)(CUtensorMap*, CUtensorMapDataType, cuuint32_t, void*, const cuuint64_t*, const cuuint64_t*,
                                    const cuuint32_t*, const cuuint32_t*, CUtensorMapInterleave, CUtensorMapSwizzle,
                                    CUtensorMapL2promotion, CUtensorMapFloatOOBfill);

CUtensorMap make_map_2d(PFN_encodeTiled enc, const void* ptr, uint64_t inner, uint64_t outer, uint64_t stride_bytes, uint32_t box_inner, uint32_t box_outer) {
  CUtensorMap m;
  cuuint64_t gd[2] = {inner, outer}; cuuint64_t gs[1] = {stride_bytes};
  cuuint32_t bx[2] = {box_inner, box_outer}; cuuint32_t es[2] = {1, 1};
  enc(&m, CU_TENSOR_MAP_DATA_TYPE_BFLOAT16, 2, const_cast<void*>(ptr), gd, gs, bx, es, CU_TENSOR_MAP_INTERLEAVE_NONE,
      CU_TENSOR_MAP_SWIZZLE_128B, CU_TENSOR_MAP_L2_PROMOTION_L2_128B, CU_TENSOR_MAP_FLOAT_OOB_FILL_NONE);
  return m;
}

CUtensorMap make_map_3d(PFN_encodeTiled enc, const void* ptr, uint64_t cols, uint64_t rows, uint32_t box_rows, uint32_t chunks) {
  CUtensorMap m;
  cuuint64_t gd[3] = {64, rows, cols / 64}; cuuint64_t gs[2] = {cols * 2, 128};
  cuuint32_t bx[3] = {64, box_rows, chunks}; cuuint32_t es[3] = {1, 1, 1};
  enc(&m, CU_TENSOR_MAP_DATA_TYPE_BFLOAT16, 3, const_cast<void*>(ptr), gd, gs, bx, es, CU_TENSOR_MAP_INTERLEAVE_NONE,
      CU_TENSOR_MAP_SWIZZLE_128B, CU_TENSOR_MAP_L2_PROMOTION_L2_128B, CU_TENSOR_MAP_FLOAT_OOB_FILL_NONE);
  return m;
}

}

extern "C" void kernel_launch(void* const* d_in, const int* in_sizes, int n_in, void* d_out, int out_size) {
  const bf16* x      = (const bf16*)d_in[0];
  const bf16* kc     = (const bf16*)d_in[1];
  const bf16* vc     = (const bf16*)d_in[2];
  const bf16* wq     = (const bf16*)d_in[3];
  const bf16* wo     = (const bf16*)d_in[4];
  const bf16* w_r    = (const bf16*)d_in[6];
  const bf16* w_gate = (const bf16*)d_in[7];
  const bf16* w_up   = (const bf16*)d_in[8];
  const bf16* w_down = (const bf16*)d_in[9];
  const bf16* cvec   = (const bf16*)d_in[10];
  const bf16* w_mod  = (const bf16*)d_in[11];
  bf16* out = (bf16*)d_out;

  static PFN_encodeTiled enc = nullptr;
  static void *p_h = nullptr, *p_o = nullptr;
  if (!enc) {
    void* fn = nullptr; cudaDriverEntryPointQueryResult qres;
    cudaGetDriverEntryPoint("cuTensorMapEncodeTiled", &fn, cudaEnableDefault, &qres);
    enc = (PFN_encodeTiled)fn;
    cudaGetSymbolAddress(&p_h, g_pre);
    p_h = (uint4*)p_h + 16 * PRE_X * 2048;
    cudaGetSymbolAddress(&p_o, g_o);
    cudaFuncSetAttribute(fused_kernel, cudaFuncAttributeMaxDynamicSharedMemorySize, (int)AT_SMEM);
  }
  const CUtensorMap tm_h   = make_map_2d(enc, p_h, T_D, T_SEQ, T_D * 2, 64, 128);
  const CUtensorMap tm_wq  = make_map_3d(enc, wq, T_DQKV, T_D, 64, 4);
  const CUtensorMap tm_k   = make_map_3d(enc, kc, T_DH, (uint64_t)T_NH * T_SEQ, 128, 2);
  const CUtensorMap tm_v   = make_map_3d(enc, vc, T_DH, (uint64_t)T_NH * T_SEQ, 128, 2);
  const CUtensorMap tm_ost = make_map_2d(enc, p_o, T_DQKV, T_SEQ, T_DQKV * 2, 64, 64);
  const CUtensorMap tm_old = make_map_2d(enc, p_o, T_DQKV, T_SEQ, T_DQKV * 2, 64, 128);
  const CUtensorMap tm_wo  = make_map_3d(enc, wo, T_D, T_DQKV, 64, 2);
  const CUtensorMap tm_d   = make_map_3d(enc, w_down, T_D, T_F, 32, 8);

  const CUtensorMap tm_m   = make_map_2d(enc, w_mod, 6 * T_D, T_D, 6 * T_D * 2, 64, 256);
  const CUtensorMap tm_out = make_map_2d(enc, out, T_D, T_SEQ, T_D * 2, 64, 16);

  fused_kernel<<<132, 384, AT_SMEM, cudaStreamPerThread>>>(tm_h, tm_wq, tm_k, tm_v, tm_ost, tm_old, tm_wo, tm_d, tm_out, tm_m, 0u, (const uint8_t*)wo, kc, vc, x, cvec, w_mod,
             w_r, w_gate, w_up, w_down, out);
}
```

```cpp
#include <cuda_runtime.h>
#include <cuda_bf16.h>
#include <cuda.h>
#include <stdint.h>

namespace {

typedef __nv_bfloat16 bf16;

constexpr int T_SEQ = 2048, T_D = 1024, T_NH = 32, T_DH = 128, T_DQKV = 4096, T_F = 3584;

#define PRE_X 2
__device__ __align__(1024) uint4 g_pre[(16 * PRE_X + 128) * 2048];
#define g_h (reinterpret_cast<bf16*>(g_pre + 16 * PRE_X * 2048))
__device__ __align__(1024) bf16 g_o[T_SEQ * T_DQKV];
__device__ __align__(16) uint8_t g_col[8 * 1536];
__device__ __align__(16) float g_scal[64];
__device__ __align__(16) unsigned int g_hcnt[17 * 32];
__device__ __align__(128) float g_modpart[4 * 2 * T_D];
struct __align__(2048) TailMail {
  float4 part1[T_SEQ * 8];
  uint32_t key[256];
  uint4 cand[16 * 2 * 2 * 128];
  uint32_t cnt[32];
  float ypart[(T_F / 32) * 2 * T_D];
};
__device__ TailMail g_mail;
#define g_part1 g_mail.part1
#define g_key g_mail.key
#define g_cand g_mail.cand
#define CNT_Y (g_mail.cnt)
#define g_ypart g_mail.ypart

__device__ __forceinline__ uint32_t smem_u32(const void* p) { return (uint32_t)__cvta_generic_to_shared(p); }
__device__ __forceinline__ void mbar_init(uint32_t bar, uint32_t cnt) { asm volatile("mbarrier.init.shared::cta.b64 [%0], %1;" :: "r"(bar), "r"(cnt)); }
__device__ __forceinline__ void mbar_expect_tx(uint32_t bar, uint32_t bytes) { asm volatile("mbarrier.arrive.expect_tx.shared::cta.b64 _, [%0], %1;" :: "r"(bar), "r"(bytes) : "memory"); }
__device__ __forceinline__ void mbar_arrive(uint32_t bar) { asm volatile("mbarrier.arrive.shared::cta.b64 _, [%0];" :: "r"(bar) : "memory"); }
__device__ __forceinline__ void mbar_wait(uint32_t bar, uint32_t parity) {
  asm volatile("{\n.reg .pred p;\nLAB_WAIT:\nmbarrier.try_wait.parity.shared::cta.b64 p, [%0], %1;\n@!p bra LAB_WAIT;\n}\n" :: "r"(bar), "r"(parity) : "memory");
}
__device__ __forceinline__ bool mbar_test(uint32_t bar, uint32_t parity) {
  uint32_t r; asm volatile("{\n.reg .pred p;\nmbarrier.test_wait.parity.shared::cta.b64 p, [%1], %2;\nselp.u32 %0, 1, 0, p;\n}\n" : "=r"(r) : "r"(bar), "r"(parity) : "memory");
  return r != 0;
}
__device__ __forceinline__ void mbar_wait_long(uint32_t bar, uint32_t parity) {
  asm volatile("{\n.reg .pred p;\nLAB_WAIT:\nmbarrier.try_wait.parity.shared::cta.b64 p, [%0], %1, %2;\n@!p bra LAB_WAIT;\n}\n" :: "r"(bar), "r"(parity), "r"(100000) : "memory");
}
__device__ __forceinline__ uint32_t clock_lo() { uint32_t c; asm volatile("mov.u32 %0, %%clock;" : "=r"(c)); return c; }
__device__ __forceinline__ void fence_mbar_init() { asm volatile("fence.mbarrier_init.release.cluster;" ::: "memory"); }
__device__ __forceinline__ void tma_load_2d(uint32_t dst, const CUtensorMap* map, int c0, int c1, uint32_t bar) {
  asm volatile("cp.async.bulk.tensor.2d.shared::cluster.global.mbarrier::complete_tx::bytes [%0], [%1, {%3, %4}], [%2];"
    :: "r"(dst), "l"(map), "r"(bar), "r"(c0), "r"(c1) : "memory");
}
__device__ __forceinline__ uint64_t policy_evict_first() {
  uint64_t p; asm volatile("createpolicy.fractional.L2::evict_first.b64 %0, 1.0;" : "=l"(p)); return p;
}
__device__ __forceinline__ void tma_load_2d_hint(uint32_t dst, const CUtensorMap* map, int c0, int c1, uint32_t bar, uint64_t pol) {
  asm volatile("cp.async.bulk.tensor.2d.shared::cluster.global.mbarrier::complete_tx::bytes.L2::cache_hint [%0], [%1, {%3, %4}], [%2], %5;"
    :: "r"(dst), "l"(map), "r"(bar), "r"(c0), "r"(c1), "l"(pol) : "memory");
}
__device__ __forceinline__ void tma_load_3d_hint(uint32_t dst, const CUtensorMap* map, int c1, int c2, uint32_t bar, uint64_t pol) {
  asm volatile("cp.async.bulk.tensor.3d.shared::cluster.global.mbarrier::complete_tx::bytes.L2::cache_hint [%0], [%1, {%3, %4, %5}], [%2], %6;"
    :: "r"(dst), "l"(map), "r"(bar), "n"(0), "r"(c1), "r"(c2), "l"(pol) : "memory");
}
__device__ __forceinline__ void tma_load_3d(uint32_t dst, const CUtensorMap* map, int c1, int c2, uint32_t bar) {
  asm volatile("cp.async.bulk.tensor.3d.shared::cluster.global.mbarrier::complete_tx::bytes [%0], [%1, {%3, %4, %5}], [%2];"
    :: "r"(dst), "l"(map), "r"(bar), "n"(0), "r"(c1), "r"(c2) : "memory");
}
__device__ __forceinline__ void tma_store_2d(const CUtensorMap* map, uint32_t src, int c0, int c1) {
  asm volatile("cp.async.bulk.tensor.2d.global.shared::cta.bulk_group [%0, {%2, %3}], [%1];" :: "l"(map), "r"(src), "r"(c0), "r"(c1) : "memory");
}
__device__ __forceinline__ void prefetch_tmap(const CUtensorMap* map) { asm volatile("prefetch.tensormap [%0];" :: "l"(map) : "memory"); }
__device__ __forceinline__ void l2_prefetch_bulk(const void* p, uint32_t bytes) {
  asm volatile("cp.async.bulk.prefetch.L2.global [%0], %1;" :: "l"(p), "r"(bytes) : "memory");
}
__device__ __forceinline__ void bulk_commit() { asm volatile("cp.async.bulk.commit_group;" ::: "memory"); }
template<int N> __device__ __forceinline__ void bulk_wait_read() { asm volatile("cp.async.bulk.wait_group.read %0;" :: "n"(N) : "memory"); }
template<int N> __device__ __forceinline__ void bulk_wait() { asm volatile("cp.async.bulk.wait_group %0;" :: "n"(N) : "memory"); }
__device__ __forceinline__ void named_bar_sync(int id, int nthreads) { asm volatile("bar.sync %0, %1;" :: "r"(id), "r"(nthreads) : "memory"); }
__device__ __forceinline__ void named_bar_arrive(int id, int nthreads) { asm volatile("bar.arrive %0, %1;" :: "r"(id), "r"(nthreads) : "memory"); }
__device__ __forceinline__ void pass_turn(int cwg) {
  asm volatile("{\n.reg .pred p;\nsetp.ne.u32 p, %0, 0;\n@p bar.arrive 1, 256;\n@!p bar.arrive 2, 256;\n}\n" :: "r"(cwg) : "memory");
}
__device__ __forceinline__ void wgmma_fence() { asm volatile("wgmma.fence.sync.aligned;" ::: "memory"); }
__device__ __forceinline__ void wgmma_commit() { asm volatile("wgmma.commit_group.sync.aligned;" ::: "memory"); }
template<int N> __device__ __forceinline__ void wgmma_wait() { asm volatile("wgmma.wait_group.sync.aligned %0;" :: "n"(N) : "memory"); }
template<int R> __device__ __forceinline__ void reg_alloc() { asm volatile("setmaxnreg.inc.sync.aligned.u32 %0;" :: "n"(R)); }
template<int R> __device__ __forceinline__ void reg_dealloc() { asm volatile("setmaxnreg.dec.sync.aligned.u32 %0;" :: "n"(R)); }
__device__ __forceinline__ bool elect_one() {
  uint32_t pred; asm volatile("{\n.reg .pred p;\nelect.sync _|p, 0xffffffff;\nselp.u32 %0, 1, 0, p;\n}\n" : "=r"(pred)); return pred != 0;
}
__device__ __forceinline__ uint32_t pack_bf16(float lo, float hi) {
  uint32_t r; asm("cvt.rn.bf16x2.f32 %0, %1, %2;" : "=r"(r) : "f"(hi), "f"(lo)); return r;
}
__device__ __forceinline__ void stmatrix_x4(uint32_t addr, uint32_t r0, uint32_t r1, uint32_t r2, uint32_t r3) {
  asm volatile("stmatrix.sync.aligned.m8n8.x4.shared.b16 [%0], {%1, %2, %3, %4};" :: "r"(addr), "r"(r0), "r"(r1), "r"(r2), "r"(r3) : "memory");
}
__device__ __forceinline__ void fence_proxy_async() { asm volatile("fence.proxy.async.shared::cta;" ::: "memory"); }
__device__ __forceinline__ float ex2_approx(float x) { float y; asm("ex2.approx.ftz.f32 %0, %1;" : "=f"(y) : "f"(x)); return y; }
template<int N> __device__ __forceinline__ void fence_regs(float (&r)[N]) {
  #pragma unroll
  for (int i = 0; i < N; i++) asm volatile("" : "+f"(r[i]) :: "memory");
}
template<int N> __device__ __forceinline__ void zero_regs(float (&r)[N]) {
  #pragma unroll
  for (int i = 0; i < N; i += 2) asm volatile("mov.b64 {%0, %1}, 0;" : "=f"(r[i]), "=f"(r[i + 1]));
}
__device__ __forceinline__ float rbf(float x) { return __uint_as_float(pack_bf16(0.f, x)); }
__device__ __forceinline__ float bflo(uint32_t v) { return __uint_as_float(v << 16); }
__device__ __forceinline__ float bfhi(uint32_t v) { return __uint_as_float(v & 0xffff0000u); }

#define XT(i) do {} while (0)
#define TL_START(k) do {} while (0)
#define TL_END(k, cond) do {} while (0)
#define TL_CTA(i, cond) do {} while (0)
#define FS(slot, k) do {} while (0)
#define TL_MARK2(k, cond) do {} while (0)
#define TL_CLK(k, i, cond) do {} while (0)

template <int OFFA, int OFFB>
__device__ __forceinline__ void wgmma_m64n256k16_ss_tb(float (&d)[128], uint32_t a_lo, uint32_t b_lo, int scaleD) {
  asm volatile("{\n.reg .pred p;\n.reg .b64 da, db;\nsetp.ne.b32 p, %130, 0;\n"
    "mov.b64 da, {%128, 0x40000040};\nmov.b64 db, {%129, 0x40000040};\n"
    "add.s64 da, da, %131;\nadd.s64 db, db, %132;\n"
    "wgmma.mma_async.sync.aligned.m64n256k16.f32.bf16.bf16 "
    "{%0, %1, %2, %3, %4, %5, %6, %7, %8, %9, %10, %11, %12, %13, %14, %15, %16, %17, %18, %19, %20, %21, %22, %23, %24, %25, %26, %27, %28, %29, %30, %31, %32, %33, %34, %35, %36, %37, %38, %39, %40, %41, %42, %43, %44, %45, %46, %47, %48, %49, %50, %51, %52, %53, %54, %55, %56, %57, %58, %59, %60, %61, %62, %63, %64, %65, %66, %67, %68, %69, %70, %71, %72, %73, %74, %75, %76, %77, %78, %79, %80, %81, %82, %83, %84, %85, %86, %87, %88, %89, %90, %91, %92, %93, %94, %95, %96, %97, %98, %99, %100, %101, %102, %103, %104, %105, %106, %107, %108, %109, %110, %111, %112, %113, %114, %115, %116, %117, %118, %119, %120, %121, %122, %123, %124, %125, %126, %127}, "
    "da, db, p, 1, 1, 0, 1;\n}\n"
    : "+f"(d[0]), "+f"(d[1]), "+f"(d[2]), "+f"(d[3]), "+f"(d[4]), "+f"(d[5]), "+f"(d[6]), "+f"(d[7]), "+f"(d[8]), "+f"(d[9]), "+f"(d[10]), "+f"(d[11]), "+f"(d[12]), "+f"(d[13]), "+f"(d[14]), "+f"(d[15]), "+f"(d[16]), "+f"(d[17]), "+f"(d[18]), "+f"(d[19]), "+f"(d[20]), "+f"(d[21]), "+f"(d[22]), "+f"(d[23]), "+f"(d[24]), "+f"(d[25]), "+f"(d[26]), "+f"(d[27]), "+f"(d[28]), "+f"(d[29]), "+f"(d[30]), "+f"(d[31]), "+f"(d[32]), "+f"(d[33]), "+f"(d[34]), "+f"(d[35]), "+f"(d[36]), "+f"(d[37]), "+f"(d[38]), "+f"(d[39]), "+f"(d[40]), "+f"(d[41]), "+f"(d[42]), "+f"(d[43]), "+f"(d[44]), "+f"(d[45]), "+f"(d[46]), "+f"(d[47]), "+f"(d[48]), "+f"(d[49]), "+f"(d[50]), "+f"(d[51]), "+f"(d[52]), "+f"(d[53]), "+f"(d[54]), "+f"(d[55]), "+f"(d[56]), "+f"(d[57]), "+f"(d[58]), "+f"(d[59]), "+f"(d[60]), "+f"(d[61]), "+f"(d[62]), "+f"(d[63]), "+f"(d[64]), "+f"(d[65]), "+f"(d[66]), "+f"(d[67]), "+f"(d[68]), "+f"(d[69]), "+f"(d[70]), "+f"(d[71]), "+f"(d[72]), "+f"(d[73]), "+f"(d[74]), "+f"(d[75]), "+f"(d[76]), "+f"(d[77]), "+f"(d[78]), "+f"(d[79]), "+f"(d[80]), "+f"(d[81]), "+f"(d[82]), "+f"(d[83]), "+f"(d[84]), "+f"(d[85]), "+f"(d[86]), "+f"(d[87]), "+f"(d[88]), "+f"(d[89]), "+f"(d[90]), "+f"(d[91]), "+f"(d[92]), "+f"(d[93]), "+f"(d[94]), "+f"(d[95]), "+f"(d[96]), "+f"(d[97]), "+f"(d[98]), "+f"(d[99]), "+f"(d[100]), "+f"(d[101]), "+f"(d[102]), "+f"(d[103]), "+f"(d[104]), "+f"(d[105]), "+f"(d[106]), "+f"(d[107]), "+f"(d[108]), "+f"(d[109]), "+f"(d[110]), "+f"(d[111]), "+f"(d[112]), "+f"(d[113]), "+f"(d[114]), "+f"(d[115]), "+f"(d[116]), "+f"(d[117]), "+f"(d[118]), "+f"(d[119]), "+f"(d[120]), "+f"(d[121]), "+f"(d[122]), "+f"(d[123]), "+f"(d[124]), "+f"(d[125]), "+f"(d[126]), "+f"(d[127])
    : "r"(a_lo), "r"(b_lo), "r"(scaleD), "n"(OFFA), "n"(OFFB));
}

template <int OFFA, int OFFB>
__device__ __forceinline__ void wgmma_m64n128k16_ss_tb(float (&d)[64], uint32_t a_lo, uint32_t b_lo, int scaleD) {
  asm volatile("{\n.reg .pred p;\n.reg .b64 da, db;\nsetp.ne.b32 p, %66, 0;\n"
    "mov.b64 da, {%64, 0x40000040};\nmov.b64 db, {%65, 0x40000040};\n"
    "add.s64 da, da, %67;\nadd.s64 db, db, %68;\n"
    "wgmma.mma_async.sync.aligned.m64n128k16.f32.bf16.bf16 "
    "{%0, %1, %2, %3, %4, %5, %6, %7, %8, %9, %10, %11, %12, %13, %14, %15, %16, %17, %18, %19, %20, %21, %22, %23, %24, %25, %26, %27, %28, %29, %30, %31, %32, %33, %34, %35, %36, %37, %38, %39, %40, %41, %42, %43, %44, %45, %46, %47, %48, %49, %50, %51, %52, %53, %54, %55, %56, %57, %58, %59, %60, %61, %62, %63}, "
    "da, db, p, 1, 1, 0, 1;\n}\n"
    : "+f"(d[0]), "+f"(d[1]), "+f"(d[2]), "+f"(d[3]), "+f"(d[4]), "+f"(d[5]), "+f"(d[6]), "+f"(d[7]), "+f"(d[8]), "+f"(d[9]), "+f"(d[10]), "+f"(d[11]), "+f"(d[12]), "+f"(d[13]), "+f"(d[14]), "+f"(d[15]), "+f"(d[16]), "+f"(d[17]), "+f"(d[18]), "+f"(d[19]), "+f"(d[20]), "+f"(d[21]), "+f"(d[22]), "+f"(d[23]), "+f"(d[24]), "+f"(d[25]), "+f"(d[26]), "+f"(d[27]), "+f"(d[28]), "+f"(d[29]), "+f"(d[30]), "+f"(d[31]), "+f"(d[32]), "+f"(d[33]), "+f"(d[34]), "+f"(d[35]), "+f"(d[36]), "+f"(d[37]), "+f"(d[38]), "+f"(d[39]), "+f"(d[40]), "+f"(d[41]), "+f"(d[42]), "+f"(d[43]), "+f"(d[44]), "+f"(d[45]), "+f"(d[46]), "+f"(d[47]), "+f"(d[48]), "+f"(d[49]), "+f"(d[50]), "+f"(d[51]), "+f"(d[52]), "+f"(d[53]), "+f"(d[54]), "+f"(d[55]), "+f"(d[56]), "+f"(d[57]), "+f"(d[58]), "+f"(d[59]), "+f"(d[60]), "+f"(d[61]), "+f"(d[62]), "+f"(d[63])
    : "r"(a_lo), "r"(b_lo), "r"(scaleD), "n"(OFFA), "n"(OFFB));
}

template <int OFFB>
__device__ __forceinline__ void wgmma_m64n128k16_rs_tb(float (&d)[64], uint32_t a0, uint32_t a1, uint32_t a2, uint32_t a3, uint32_t b_lo, int scaleD) {
  asm volatile("{\n.reg .pred p;\n.reg .b64 db;\nsetp.ne.b32 p, %69, 0;\n"
    "mov.b64 db, {%68, 0x40000040};\nadd.s64 db, db, %70;\n"
    "wgmma.mma_async.sync.aligned.m64n128k16.f32.bf16.bf16 "
    "{%0, %1, %2, %3, %4, %5, %6, %7, %8, %9, %10, %11, %12, %13, %14, %15, %16, %17, %18, %19, %20, %21, %22, %23, %24, %25, %26, %27, %28, %29, %30, %31, %32, %33, %34, %35, %36, %37, %38, %39, %40, %41, %42, %43, %44, %45, %46, %47, %48, %49, %50, %51, %52, %53, %54, %55, %56, %57, %58, %59, %60, %61, %62, %63}, "
    "{%64, %65, %66, %67}, db, p, 1, 1, 1;\n}\n"
    : "+f"(d[0]), "+f"(d[1]), "+f"(d[2]), "+f"(d[3]), "+f"(d[4]), "+f"(d[5]), "+f"(d[6]), "+f"(d[7]), "+f"(d[8]), "+f"(d[9]), "+f"(d[10]), "+f"(d[11]), "+f"(d[12]), "+f"(d[13]), "+f"(d[14]), "+f"(d[15]), "+f"(d[16]), "+f"(d[17]), "+f"(d[18]), "+f"(d[19]), "+f"(d[20]), "+f"(d[21]), "+f"(d[22]), "+f"(d[23]), "+f"(d[24]), "+f"(d[25]), "+f"(d[26]), "+f"(d[27]), "+f"(d[28]), "+f"(d[29]), "+f"(d[30]), "+f"(d[31]), "+f"(d[32]), "+f"(d[33]), "+f"(d[34]), "+f"(d[35]), "+f"(d[36]), "+f"(d[37]), "+f"(d[38]), "+f"(d[39]), "+f"(d[40]), "+f"(d[41]), "+f"(d[42]), "+f"(d[43]), "+f"(d[44]), "+f"(d[45]), "+f"(d[46]), "+f"(d[47]), "+f"(d[48]), "+f"(d[49]), "+f"(d[50]), "+f"(d[51]), "+f"(d[52]), "+f"(d[53]), "+f"(d[54]), "+f"(d[55]), "+f"(d[56]), "+f"(d[57]), "+f"(d[58]), "+f"(d[59]), "+f"(d[60]), "+f"(d[61]), "+f"(d[62]), "+f"(d[63])
    : "r"(a0), "r"(a1), "r"(a2), "r"(a3), "r"(b_lo), "r"(scaleD), "n"(OFFB));
}

template <int OFFB>
__device__ __forceinline__ void wgmma_m64n128k16_rs(float (&d)[64], uint32_t a0, uint32_t a1, uint32_t a2, uint32_t a3, uint32_t b_lo, int scaleD) {
  asm volatile("{\n.reg .pred p;\n.reg .b64 db;\nsetp.ne.b32 p, %69, 0;\n"
    "mov.b64 db, {%68, 0x40000040};\nadd.s64 db, db, %70;\n"
    "wgmma.mma_async.sync.aligned.m64n128k16.f32.bf16.bf16 "
    "{%0, %1, %2, %3, %4, %5, %6, %7, %8, %9, %10, %11, %12, %13, %14, %15, %16, %17, %18, %19, %20, %21, %22, %23, %24, %25, %26, %27, %28, %29, %30, %31, %32, %33, %34, %35, %36, %37, %38, %39, %40, %41, %42, %43, %44, %45, %46, %47, %48, %49, %50, %51, %52, %53, %54, %55, %56, %57, %58, %59, %60, %61, %62, %63}, "
    "{%64, %65, %66, %67}, db, p, 1, 1, 0;\n}\n"
    : "+f"(d[0]), "+f"(d[1]), "+f"(d[2]), "+f"(d[3]), "+f"(d[4]), "+f"(d[5]), "+f"(d[6]), "+f"(d[7]), "+f"(d[8]), "+f"(d[9]), "+f"(d[10]), "+f"(d[11]), "+f"(d[12]), "+f"(d[13]), "+f"(d[14]), "+f"(d[15]), "+f"(d[16]), "+f"(d[17]), "+f"(d[18]), "+f"(d[19]), "+f"(d[20]), "+f"(d[21]), "+f"(d[22]), "+f"(d[23]), "+f"(d[24]), "+f"(d[25]), "+f"(d[26]), "+f"(d[27]), "+f"(d[28]), "+f"(d[29]), "+f"(d[30]), "+f"(d[31]), "+f"(d[32]), "+f"(d[33]), "+f"(d[34]), "+f"(d[35]), "+f"(d[36]), "+f"(d[37]), "+f"(d[38]), "+f"(d[39]), "+f"(d[40]), "+f"(d[41]), "+f"(d[42]), "+f"(d[43]), "+f"(d[44]), "+f"(d[45]), "+f"(d[46]), "+f"(d[47]), "+f"(d[48]), "+f"(d[49]), "+f"(d[50]), "+f"(d[51]), "+f"(d[52]), "+f"(d[53]), "+f"(d[54]), "+f"(d[55]), "+f"(d[56]), "+f"(d[57]), "+f"(d[58]), "+f"(d[59]), "+f"(d[60]), "+f"(d[61]), "+f"(d[62]), "+f"(d[63])
    : "r"(a0), "r"(a1), "r"(a2), "r"(a3), "r"(b_lo), "r"(scaleD), "n"(OFFB));
}

__device__ __forceinline__ uint4 ldg_nc_v4(const void* p) {
  uint4 v;
    asm volatile("{\n.reg .b64 pol;\ncreatepolicy.fractional.L2::evict_first.b64 pol, 1.0;\n"
                 "ld.global.nc.L1::no_allocate.L2::cache_hint.v4.u32 {%0, %1, %2, %3}, [%4], pol;\n}\n" : "=r"(v.x), "=r"(v.y), "=r"(v.z), "=r"(v.w) : "l"(p));
  return v;
}
__device__ __forceinline__ void unpack8(const uint4& u, float (&v)[8]) {
  v[0] = bflo(u.x); v[1] = bfhi(u.x); v[2] = bflo(u.y); v[3] = bfhi(u.y);
  v[4] = bflo(u.z); v[5] = bfhi(u.z); v[6] = bflo(u.w); v[7] = bfhi(u.w);
}
__device__ __forceinline__ void fma8(float (&acc)[8], float s, const uint4& w) {
  acc[0] = fmaf(s, bflo(w.x), acc[0]); acc[1] = fmaf(s, bfhi(w.x), acc[1]); acc[2] = fmaf(s, bflo(w.y), acc[2]); acc[3] = fmaf(s, bfhi(w.y), acc[3]);
  acc[4] = fmaf(s, bflo(w.z), acc[4]); acc[5] = fmaf(s, bfhi(w.z), acc[5]); acc[6] = fmaf(s, bflo(w.w), acc[6]); acc[7] = fmaf(s, bfhi(w.w), acc[7]);
}
__device__ __forceinline__ float rcp_approx(float x) { float y; asm("rcp.approx.ftz.f32 %0, %1;" : "=f"(y) : "f"(x)); return y; }
__device__ __forceinline__ float sigmoid_f(float v) { return rcp_approx(1.0f + ex2_approx(v * -1.4426950408889634f)); }
__device__ __forceinline__ float silu_bf(float v) { return rbf(v * sigmoid_f(v)); }
__device__ __forceinline__ uint32_t rank_key(float r, int idx) {
  const uint32_t b = __float_as_uint(r) >> 16;
  const uint32_t u = (r != r) ? 0u : ((b & 0x8000u) ? (~b & 0xffffu) : (b | 0x8000u));
  return (u << 16) | (0xffffu - (uint32_t)idx);
}
__device__ __forceinline__ void warp_top2(uint32_t& k1, uint32_t& k2) {
  const uint32_t m1 = __reduce_max_sync(0xffffffffu, k1);
  k2 = __reduce_max_sync(0xffffffffu, k1 == m1 ? k2 : k1);
  k1 = m1;
}
__device__ __forceinline__ uint32_t bmul2(uint32_t a, uint32_t b) { uint32_t r; asm("mul.rn.bf16x2 %0, %1, %2;" : "=r"(r) : "r"(a), "r"(b)); return r; }
__device__ __forceinline__ uint32_t badd2(uint32_t a, uint32_t b) { uint32_t r; asm("add.rn.bf16x2 %0, %1, %2;" : "=r"(r) : "r"(a), "r"(b)); return r; }
__device__ __forceinline__ uint32_t bsub2(uint32_t a, uint32_t b) { uint32_t r; asm("sub.rn.bf16x2 %0, %1, %2;" : "=r"(r) : "r"(a), "r"(b)); return r; }
__device__ __forceinline__ float sqrt_approx(float x) { float y; asm("sqrt.approx.f32 %0, %1;" : "=f"(y) : "f"(x)); return y; }
__device__ __forceinline__ uint32_t ln_norm2(uint32_t x1, uint32_t mb2, float inv) {
  const uint32_t d = bsub2(x1, mb2);
  return pack_bf16(bflo(d) * inv, bfhi(d) * inv);
}
__device__ __forceinline__ uint32_t bfma2(uint32_t a, uint32_t b, uint32_t c) { uint32_t r; asm("fma.rn.bf16x2 %0, %1, %2, %3;" : "=r"(r) : "r"(a), "r"(b), "r"(c)); return r; }
__device__ __forceinline__ uint32_t ln_norm2b(uint32_t x1, uint32_t mb2, uint32_t ih, uint32_t il) {
  const uint32_t d = bsub2(x1, mb2);
  return bfma2(d, ih, bmul2(d, il));
}
__device__ __forceinline__ uint32_t ln_mod2(uint32_t x1, uint32_t mb2, float inv, uint32_t c1, uint32_t sb) { return badd2(bmul2(ln_norm2(x1, mb2, inv), c1), sb); }
__device__ __forceinline__ void ldmatrix_x4(uint32_t addr, uint32_t& r0, uint32_t& r1, uint32_t& r2, uint32_t& r3) {
  asm volatile("ldmatrix.sync.aligned.m8n8.x4.shared.b16 {%0, %1, %2, %3}, [%4];" : "=r"(r0), "=r"(r1), "=r"(r2), "=r"(r3) : "r"(addr) : "memory");
}
__device__ __forceinline__ uint4 ldg_stream_v4(const void* p, uint64_t pol) {
  uint4 v; asm volatile("ld.global.nc.L1::no_allocate.L2::cache_hint.L2::128B.v4.u32 {%0, %1, %2, %3}, [%4], %5;" : "=r"(v.x), "=r"(v.y), "=r"(v.z), "=r"(v.w) : "l"(p), "l"(pol)); return v;
}
__device__ __forceinline__ void bulk_load_hint(uint32_t dst, const void* src, uint32_t bytes, uint32_t bar, uint64_t pol) {
  asm volatile("cp.async.bulk.shared::cluster.global.mbarrier::complete_tx::bytes.L2::cache_hint [%0], [%1], %2, [%3], %4;"
    :: "r"(dst), "l"(src), "r"(bytes), "r"(bar), "l"(pol) : "memory");
}
__device__ __forceinline__ void red_release_add(unsigned int* p, unsigned int v) { asm volatile("red.release.gpu.global.add.u32 [%0], %1;" :: "l"(p), "r"(v) : "memory"); }
__device__ __forceinline__ unsigned int ld_acquire(const unsigned int* p) { unsigned int v; asm volatile("ld.acquire.gpu.global.u32 %0, [%1];" : "=r"(v) : "l"(p) : "memory"); return v; }
__device__ __forceinline__ void spin_until(const unsigned int* p, unsigned int target) {
  #pragma unroll 1
  for (unsigned int i = 0; i < (1u << 22); i++) { if (ld_acquire(p) >= target) return; }
}
__device__ __forceinline__ float lds_f32(uint32_t a) { float v; asm volatile("ld.shared.f32 %0, [%1];" : "=f"(v) : "r"(a) : "memory"); return v; }
__device__ __forceinline__ float2 lds_f32x2(uint32_t a) { float2 v; asm volatile("ld.shared.v2.f32 {%0, %1}, [%2];" : "=f"(v.x), "=f"(v.y) : "r"(a) : "memory"); return v; }
__device__ __forceinline__ uint2 lds_u32x2(uint32_t a) { uint2 v; asm volatile("ld.shared.v2.u32 {%0, %1}, [%2];" : "=r"(v.x), "=r"(v.y) : "r"(a) : "memory"); return v; }
__device__ __forceinline__ uint32_t lds_u32(uint32_t a) { uint32_t v; asm volatile("ld.shared.u32 %0, [%1];" : "=r"(v) : "r"(a) : "memory"); return v; }
__device__ __forceinline__ void sts_u32(uint32_t a, uint32_t v) { asm volatile("st.shared.u32 [%0], %1;" :: "r"(a), "r"(v) : "memory"); }
__device__ __forceinline__ void sts_u32x2(uint32_t a, uint32_t x, uint32_t y) { asm volatile("st.shared.v2.u32 [%0], {%1, %2};" :: "r"(a), "r"(x), "r"(y) : "memory"); }
__device__ __forceinline__ void sts_f32(uint32_t a, float v) { asm volatile("st.shared.f32 [%0], %1;" :: "r"(a), "f"(v) : "memory"); }
__device__ __forceinline__ void sts_f32x2(uint32_t a, float x, float y) { asm volatile("st.shared.v2.f32 [%0], {%1, %2};" :: "r"(a), "f"(x), "f"(y) : "memory"); }
__device__ __forceinline__ void sts_f32x4(uint32_t a, float x, float y, float z, float w) { asm volatile("st.shared.v4.f32 [%0], {%1, %2, %3, %4};" :: "r"(a), "f"(x), "f"(y), "f"(z), "f"(w) : "memory"); }

__device__ __forceinline__ uint4 lds_u32x4(uint32_t a) { uint4 v; asm volatile("ld.shared.v4.u32 {%0, %1, %2, %3}, [%4];" : "=r"(v.x), "=r"(v.y), "=r"(v.z), "=r"(v.w) : "r"(a) : "memory"); return v; }
__device__ __forceinline__ void sts_u32x4(uint32_t a, uint32_t x, uint32_t y, uint32_t z, uint32_t w) { asm volatile("st.shared.v4.u32 [%0], {%1, %2, %3, %4};" :: "r"(a), "r"(x), "r"(y), "r"(z), "r"(w) : "memory"); }
__device__ __forceinline__ void st_tagged(float* p, float v) {
  const uint32_t b = __float_as_uint(v);
  asm volatile("st.relaxed.gpu.global.u32 [%0], %1;" :: "l"(p), "r"(b == 0u ? 0x80000000u : b) : "memory");
}
__device__ __forceinline__ void st_tagged4(float* p, float x, float y, float z, float w) {
  const uint32_t a = __float_as_uint(x), b = __float_as_uint(y), c = __float_as_uint(z), d = __float_as_uint(w);
  asm volatile("st.relaxed.gpu.global.v4.u32 [%0], {%1, %2, %3, %4};" :: "l"(p), "r"(a == 0u ? 0x80000000u : a), "r"(b == 0u ? 0x80000000u : b),
               "r"(c == 0u ? 0x80000000u : c), "r"(d == 0u ? 0x80000000u : d) : "memory");
}
__device__ __forceinline__ void st_tagged4_lsb(float* p, float x, float y, float z, float w) {
  asm volatile("st.relaxed.gpu.global.v4.u32 [%0], {%1, %2, %3, %4};" :: "l"(p), "r"(__float_as_uint(x) | 1u), "r"(__float_as_uint(y) | 1u),
               "r"(__float_as_uint(z) | 1u), "r"(__float_as_uint(w) | 1u) : "memory");
}
__device__ __forceinline__ void st_relaxed2(void* p, uint32_t a, uint32_t b) { asm volatile("st.relaxed.gpu.global.v2.u32 [%0], {%1, %2};" :: "l"(p), "r"(a), "r"(b) : "memory"); }
__device__ __forceinline__ float4 ld_tagged4(const float* p) {
  float4 v; asm volatile("ld.relaxed.gpu.global.v4.f32 {%0, %1, %2, %3}, [%4];" : "=f"(v.x), "=f"(v.y), "=f"(v.z), "=f"(v.w) : "l"(p) : "memory"); return v;
}
__device__ __forceinline__ bool tagged4(const float4& v) {
  return __float_as_uint(v.x) != 0u && __float_as_uint(v.y) != 0u && __float_as_uint(v.z) != 0u && __float_as_uint(v.w) != 0u;
}
__device__ __forceinline__ void hint_arrive(uint32_t* p) { asm volatile("red.relaxed.gpu.global.add.u32 [%0], 1;" :: "l"(p) : "memory"); }
__device__ __forceinline__ void hint_wait(const uint32_t* p, uint32_t target) {
  uint32_t v = 0u;
  #pragma unroll 1
  for (unsigned int i = 0; i < (1u << 22) && v < target; i++) asm volatile("ld.relaxed.gpu.global.u32 %0, [%1];" : "=r"(v) : "l"(p) : "memory");
}
__device__ __forceinline__ void fence_proxy_async_global() { asm volatile("fence.proxy.async.global;" ::: "memory"); }

#define H_SPLIT 1
#define X_DLY 1200
#define W_DLY 1900
#define W_FIRST 2200
#define PRE_B 2
template <int J0, int J1>
__device__ __forceinline__ void load_parts(float2 (&pa)[J1 - J0][4], int t2) {
  #pragma unroll
  for (int j = J0; j < J1; j++)
    #pragma unroll
    for (int k = 0; k < 4; k++)
      asm volatile("ld.relaxed.gpu.global.v2.f32 {%0, %1}, [%2];" : "=f"(pa[j - J0][k].x), "=f"(pa[j - J0][k].y)
                   : "l"(g_modpart + k * 2 * T_D + (t2 >> 7) * T_D + j * 256 + (t2 & 127) * 2) : "memory");
}
template <int J0, int J1>
__device__ __forceinline__ void finish_parts(float2 (&pa)[J1 - J0][4], bool loaded, int t2, uint32_t tab) {
  #pragma unroll 1
  for (unsigned int spin = 0; spin < (1u << 22); spin++) {
    if (!loaded) load_parts<J0, J1>(pa, t2);
    loaded = false;
    bool ok = true;
    #pragma unroll
    for (int j = 0; j < J1 - J0; j++)
      #pragma unroll
      for (int k = 0; k < 4; k++) ok &= (__float_as_uint(pa[j][k].x) != 0u) & (__float_as_uint(pa[j][k].y) != 0u);
    if (__all_sync(0xffffffffu, ok)) break;
  }
  #pragma unroll
  for (int j = J0; j < J1; j++) {
    const float2* q = pa[j - J0];
    const uint32_t m = pack_bf16(((q[0].x + q[1].x) + q[2].x) + q[3].x, ((q[0].y + q[1].y) + q[2].y) + q[3].y);
    sts_u32(tab + (t2 >> 7) * 2048 + j * 512 + (t2 & 127) * 4, t2 >= 128 ? badd2(m, 0x3F803F80u) : m);
  }
}
__device__ __forceinline__ int head_cb(uint32_t bid) { return (bid & 16) | ((bid & 3) << 2) | ((bid >> 2) & 3); }
#define HSC 0
#define SQ_DEP 0
__device__ __forceinline__ uint32_t hsc(uint32_t h) { return HSC ? bfma2(h, 0x3E033E03u, bmul2(h, 0xB9D8B9D8u)) : h; }
__device__ __forceinline__ void head_phase(uint32_t bid, uint32_t scr, uint32_t xs, uint32_t b_x, uint32_t b_go, uint32_t b_head, int t2, uint32_t zero, const bf16* __restrict__ cvec, const bf16* __restrict__ w_mod) {
  const int lane = t2 & 31, w8 = t2 >> 5;
  const int cb = head_cb(bid), ks = bid >> 5;
  const bool early = (cb & 15) < 4 * H_SPLIT;
  const uint32_t ws = (xs - 32768 + (t2 >> 3) * 128 + (((t2 ^ (t2 >> 3)) & 7) << 4)) ^ zero;
  const float cv = __bfloat162float(cvec[ks * 256 + t2]);
  const bf16* wsrc = w_mod + (size_t)(ks * 256 + (t2 >> 3)) * (6 * T_D) + cb * 64 + (t2 & 7) * 8;
  if (early) {
    const uint64_t pol = policy_evict_first();
    #pragma unroll 2
    for (int i = 0; i < 8; i++)
      asm volatile("cp.async.cg.shared.global.L2::cache_hint [%0], [%1], 16, %2;" :: "r"(ws + i * 4096), "l"(wsrc + (size_t)i * 32 * 6 * T_D), "l"(pol) : "memory");
  }
  sts_f32(scr + t2 * 4, silu_bf(cv));
  named_bar_sync(6, 384);
  TL_MARK2(1, t2 == 0);
  uint4 xv[2][4];
  uint32_t mb2[2], ih[2], il[2];
  auto norm = [&](int j) {
    #pragma unroll
    for (int r = 0; r < 2; r++) {
      xv[r][j].x = ln_norm2b(xv[r][j].x, mb2[r], ih[r], il[r]); xv[r][j].y = ln_norm2b(xv[r][j].y, mb2[r], ih[r], il[r]);
      xv[r][j].z = ln_norm2b(xv[r][j].z, mb2[r], ih[r], il[r]); xv[r][j].w = ln_norm2b(xv[r][j].w, mb2[r], ih[r], il[r]);
    }
  };
  auto modulate = [&](int j) {
    const uint4 sa = lds_u32x4(scr + 8192 + j * 512 + lane * 16), c1 = lds_u32x4(scr + 8192 + 2048 + j * 512 + lane * 16);
    #pragma unroll
    for (int r = 0; r < 2; r++) {
      xv[r][j].x = hsc(badd2(bmul2(xv[r][j].x, c1.x), sa.x)); xv[r][j].y = hsc(badd2(bmul2(xv[r][j].y, c1.y), sa.y));
      xv[r][j].z = hsc(badd2(bmul2(xv[r][j].z, c1.z), sa.z)); xv[r][j].w = hsc(badd2(bmul2(xv[r][j].w, c1.w), sa.w));
    }
  };
  auto store = [&](int j) {
    #pragma unroll
    for (int r = 0; r < 2; r++) *reinterpret_cast<uint4*>(g_h + (size_t)(bid * 16 + 2 * w8 + r) * T_D + j * 256 + lane * 8) = xv[r][j];
  };
  #pragma unroll 1
  for (int ph = 0; ph < 2; ph++) {
    if ((ph == 0) == early) {
      asm volatile("cp.async.wait_all;" ::: "memory");
      if (!early) mbar_wait(b_x + 168, 0);
      float acc[8];
      #pragma unroll
      for (int j = 0; j < 8; j++) acc[j] = 0.f;
      #pragma unroll
      for (int i = 0; i < 8; i++) fma8(acc, lds_f32(scr + ((t2 >> 3) + 32 * i) * 4), lds_u32x4(ws + i * 4096));
      #pragma unroll
      for (int j = 0; j < 4; j++) { const bool up = lane & 16; acc[j] = (up ? acc[4 + j] : acc[j]) + __shfl_xor_sync(0xffffffffu, up ? acc[j] : acc[4 + j], 16); }
      #pragma unroll
      for (int j = 0; j < 2; j++) { const bool up = lane & 8; acc[j] = (up ? acc[2 + j] : acc[j]) + __shfl_xor_sync(0xffffffffu, up ? acc[j] : acc[2 + j], 8); }
      sts_f32x2(scr + 1024 + w8 * 256 + (lane & 7) * 32 + (lane >> 3) * 8, acc[0], acc[1]);
      named_bar_sync(5, 256);
      if (t2 < 64) {
        float sum = 0.f;
        #pragma unroll
        for (int i = 0; i < 8; i++) sum += lds_f32(scr + 1024 + i * 256 + t2 * 4);
        st_tagged(g_modpart + ks * 2 * T_D + cb * 64 + t2, sum);
        TL_MARK2(early ? 2 : 6, t2 == 0);
      }
    } else {
      float2 pa[H_SPLIT][4];
      mbar_wait(b_x, 0);
      TL_MARK2(18, t2 == 0);
      load_parts<0, H_SPLIT>(pa, t2);
      #pragma unroll
      for (int r = 0; r < 2; r++)
        #pragma unroll
        for (int j = 0; j < 4; j++) xv[r][j] = lds_u32x4(xs + (2 * w8 + r) * 2048 + j * 512 + lane * 16);
  {
    float st[4] = {0.f, 0.f, 0.f, 0.f};
    #pragma unroll
    for (int r = 0; r < 2; r++)
      #pragma unroll
      for (int j = 0; j < 4; j++) {
        float v[8];
        unpack8(xv[r][j], v);
        st[2 * r] += ((v[0] + v[1]) + (v[2] + v[3])) + ((v[4] + v[5]) + (v[6] + v[7]));
        st[2 * r + 1] += fmaf(v[0], v[0], fmaf(v[1], v[1], fmaf(v[2], v[2], v[3] * v[3]))) + fmaf(v[4], v[4], fmaf(v[5], v[5], fmaf(v[6], v[6], v[7] * v[7])));
      }
    #pragma unroll
    for (int k = 0; k < 2; k++) { const bool up = lane & 16; st[k] = (up ? st[2 + k] : st[k]) + __shfl_xor_sync(0xffffffffu, up ? st[k] : st[2 + k], 16); }
    #pragma unroll
    for (int o = 8; o > 0; o >>= 1) { st[0] += __shfl_xor_sync(0xffffffffu, st[0], o); st[1] += __shfl_xor_sync(0xffffffffu, st[1], o); }
    const float mean = st[0] * (1.0f / T_D);
    const float inv = rcp_approx(rbf(sqrt_approx(rbf(rbf(fmaxf(fmaf(-mean, mean, st[1] * (1.0f / T_D)), 0.f)) + 1e-05f))));
    const uint32_t m = pack_bf16(mean, mean), h = pack_bf16(inv - rbf(inv), inv);
    #pragma unroll
    for (int r = 0; r < 2; r++) {
      mb2[r] = __shfl_sync(0xffffffffu, m, 16 * r);
      const uint32_t hr = __shfl_sync(0xffffffffu, h, 16 * r);
      ih[r] = __byte_perm(hr, hr, 0x3232); il[r] = __byte_perm(hr, hr, 0x1010);
    }
  }
      #pragma unroll
      for (int j = 0; j < H_SPLIT; j++) norm(j);
      TL_MARK2(5, t2 == 0);
      finish_parts<0, H_SPLIT>(pa, true, t2, scr + 8192);
      named_bar_sync(5, 256);
      TL_MARK2(7, t2 == 0);
      #pragma unroll
      for (int j = 0; j < H_SPLIT; j++) { modulate(j); store(j); }
      named_bar_arrive(9, 288);
    }
  }
  #pragma unroll
  for (int j = H_SPLIT; j < 4; j++) norm(j);
  float2 pb[4 - H_SPLIT][4];
  finish_parts<H_SPLIT, 4>(pb, false, t2, scr + 8192);
  named_bar_sync(5, 256);
  TL_MARK2(17, t2 == 0);
  #pragma unroll
  for (int j = H_SPLIT; j < 4; j++) modulate(j);
  __syncwarp();
  if (lane == 0) mbar_arrive(b_head + (xv[1][3].w & zero));
  mbar_wait(b_go, 0);
  #pragma unroll
  for (int j = H_SPLIT; j < 4; j++) store(j);
  named_bar_arrive(8, 288);
}

#define MOD_AT (b_empty + 8)
#define MOD_SPLIT 20
__device__ __forceinline__ void mod_rest(uint32_t bid, uint32_t scr, uint32_t b_go, int t, const bf16* __restrict__ cvec, const bf16* __restrict__ w_mod, const bf16* __restrict__ w_r) {
  const int lane = t & 31;
  #pragma unroll 1
  for (int i = t; i < T_D / 2; i += 64) {
    const uint32_t c2 = *reinterpret_cast<const uint32_t*>(cvec + 2 * i);
    sts_u32(scr + i * 4, pack_bf16(silu_bf(bflo(c2)), silu_bf(bfhi(c2))));
  }
  named_bar_sync(11, 64);
  const bf16* wp = w_mod + (size_t)(2 * (t >> 2)) * (6 * T_D) + 2 * T_D + bid * 32 + (t & 3) * 8;
  float acc[8];
  #pragma unroll
  for (int i = 0; i < 8; i++) acc[i] = 0.f;
  #pragma unroll 1
  for (int i = 0; i < 32; i += 2) {
    if (i == MOD_SPLIT) mbar_wait_long(b_go, 0);
    const uint4 w0 = ldg_nc_v4(wp), w1 = ldg_nc_v4(wp + 6 * T_D), w2 = ldg_nc_v4(wp + 32 * 6 * T_D), w3 = ldg_nc_v4(wp + 33 * 6 * T_D);
    wp += 64 * 6 * T_D;
    const uint32_t s0 = lds_u32(scr + (i * 16 + (t >> 2)) * 4), s1 = lds_u32(scr + (i * 16 + 16 + (t >> 2)) * 4);
    fma8(acc, bflo(s0), w0); fma8(acc, bfhi(s0), w1); fma8(acc, bflo(s1), w2); fma8(acc, bfhi(s1), w3);
  }
  #pragma unroll
  for (int j = 0; j < 4; j++) { const bool up = lane & 16; acc[j] = (up ? acc[4 + j] : acc[j]) + __shfl_xor_sync(0xffffffffu, up ? acc[j] : acc[4 + j], 16); }
  #pragma unroll
  for (int j = 0; j < 2; j++) { const bool up = lane & 8; acc[j] = (up ? acc[2 + j] : acc[j]) + __shfl_xor_sync(0xffffffffu, up ? acc[j] : acc[2 + j], 8); }
  { const bool up = lane & 4; acc[0] = (up ? acc[1] : acc[0]) + __shfl_xor_sync(0xffffffffu, up ? acc[0] : acc[1], 4); }
  if (t >= 32) sts_f32(scr + 2048 + lane * 4, acc[0]);
  named_bar_sync(11, 64);
  if (__shfl_sync(0xffffffffu, t, 0) < 32) {
    const int kind = bid >> 5;
    float v = rbf(acc[0] + lds_f32(scr + 2048 + lane * 4));
    const int col = (bid & 31) * 32 + (lane & 3) * 8 + (lane >> 2);
    uint8_t* dst = g_col + (col >> 7) * 1536;
    if (kind == 2) v = rbf(1.0f + v);
    float vw = v * __bfloat162float(w_r[col]);
    if (kind == 2) {
      const int c = col & 127, i = (c & ~15) + ((c >> 1) & 3) * 4 + ((c >> 3) & 1) * 2 + (c & 1);
      reinterpret_cast<bf16*>(dst)[i] = __float2bfloat16_rn(vw);
      reinterpret_cast<bf16*>(dst)[128 + i] = __float2bfloat16_rn(vw - rbf(vw));
    }
    reinterpret_cast<bf16*>(dst + 512 + (kind & 1) * 512 + (kind >> 1) * 256)[col & 127] = __float2bfloat16_rn(v);
    #pragma unroll
    for (int o = 16; o > 0; o >>= 1) vw += __shfl_xor_sync(0xffffffffu, vw, o);
    if (lane == 0 && (kind == 1 || kind == 2)) g_scal[95 - bid] = vw;
  }
  #pragma unroll 1
  for (int i = bid * 64 + t; i < (int)(sizeof(g_mail) / 16); i += 128 * 64) reinterpret_cast<uint4*>(&g_mail)[i] = make_uint4(0u, 0u, 0u, 0u);
  named_bar_sync(11, 64);
  if (t == 0) red_release_add(&g_hcnt[0], 1u);
}

constexpr int AT_NBLK = T_SEQ / 128;
constexpr float AT_HEAD = 7.0f;
#define WO_LATE 12
#define QP_STAG 3
#define AT_SPLIT 28
#define AT_PIN 16
#define PINB 4
constexpr int AT_NFULL = 124;
constexpr int AT_PREG = 40, AT_CREG = 232;
constexpr uint32_t AT_SQ = 5 * 32768;
constexpr float AT_C = 0.08838834764831845f * 1.4426950408889634f;
constexpr float AT_RAW_LO = -16.0f, AT_RAW_HI = 24.0f;
constexpr float AT_RAW_SUM = 281474976710656.0f, AT_RAW_MIN = 9.094947017729282e-13f;
constexpr uint32_t AT_SBAR = AT_SQ + 65536 + 256;
constexpr uint32_t AT_SMEM = AT_SQ + 65536 + 3072;

__device__ __forceinline__ uint32_t ring_slot(uint32_t t) { return t - 5u * ((t * 205u) >> 10); }
__device__ __forceinline__ uint32_t qp_pos(uint32_t j, uint32_t it) { return 4u * it + (j & 3u) + ((j & 3u) == 3u ? it : 0u); }
__device__ __forceinline__ uint32_t ring_par(uint32_t t) { return ((t * 205u) >> 10) & 1u; }
__device__ __forceinline__ void softmax_rowmax(const float (&s)[64], float& mx0, float& mx1) {
  float a0 = fmaxf(s[0], s[1]), a1 = fmaxf(s[4], s[5]), a2 = fmaxf(s[8], s[9]), a3 = fmaxf(s[12], s[13]);
  float b0 = fmaxf(s[2], s[3]), b1 = fmaxf(s[6], s[7]), b2 = fmaxf(s[10], s[11]), b3 = fmaxf(s[14], s[15]);
  #pragma unroll
  for (int j = 4; j < 16; j += 4) {
    a0 = fmaxf(a0, fmaxf(s[4 * j + 0], s[4 * j + 1]));  b0 = fmaxf(b0, fmaxf(s[4 * j + 2], s[4 * j + 3]));
    a1 = fmaxf(a1, fmaxf(s[4 * j + 4], s[4 * j + 5]));  b1 = fmaxf(b1, fmaxf(s[4 * j + 6], s[4 * j + 7]));
    a2 = fmaxf(a2, fmaxf(s[4 * j + 8], s[4 * j + 9]));  b2 = fmaxf(b2, fmaxf(s[4 * j + 10], s[4 * j + 11]));
    a3 = fmaxf(a3, fmaxf(s[4 * j + 12], s[4 * j + 13])); b3 = fmaxf(b3, fmaxf(s[4 * j + 14], s[4 * j + 15]));
  }
  mx0 = fmaxf(fmaxf(a0, a1), fmaxf(a2, a3));
  mx1 = fmaxf(fmaxf(b0, b1), fmaxf(b2, b3));
  mx0 = fmaxf(mx0, __shfl_xor_sync(0xffffffffu, mx0, 1));
  mx1 = fmaxf(mx1, __shfl_xor_sync(0xffffffffu, mx1, 1));
  mx0 = fmaxf(mx0, __shfl_xor_sync(0xffffffffu, mx0, 2));
  mx1 = fmaxf(mx1, __shfl_xor_sync(0xffffffffu, mx1, 2));
}
__device__ __forceinline__ void softmax_sub(float (&s)[64], float mc0, float mc1) {
  #pragma unroll
  for (int j = 0; j < 16; j++) { s[4 * j] -= mc0; s[4 * j + 1] -= mc0; s[4 * j + 2] -= mc1; s[4 * j + 3] -= mc1; }
}
template <int LO, int HI>
__device__ __forceinline__ void softmax_exp(float (&s)[64]) {
  #pragma unroll
  for (int i = LO; i < HI; i++) s[i] = ex2_approx(s[i]);
}
__device__ __forceinline__ bool softmax_mode(const float (&s)[64], float& mc0, float& mc1) {
  softmax_rowmax(s, mc0, mc1);
  const bool raw = __all_sync(0xffffffffu, mc0 >= AT_RAW_LO && mc0 <= AT_RAW_HI && mc1 >= AT_RAW_LO && mc1 <= AT_RAW_HI);
  mc0 += AT_HEAD; mc1 += AT_HEAD;
  return raw;
}
__device__ __forceinline__ void rowsum_p(const uint32_t (&p)[32], uint32_t& t0, uint32_t& t1) {
  uint32_t a[16];
  #pragma unroll
  for (int i = 0; i < 8; i++) { a[2 * i] = badd2(p[4 * i], p[4 * i + 2]); a[2 * i + 1] = badd2(p[4 * i + 1], p[4 * i + 3]); }
  #pragma unroll
  for (int i = 0; i < 4; i++) { a[2 * i] = badd2(a[4 * i], a[4 * i + 2]); a[2 * i + 1] = badd2(a[4 * i + 1], a[4 * i + 3]); }
  t0 = badd2(badd2(a[0], a[2]), badd2(a[4], a[6]));
  t1 = badd2(badd2(a[1], a[3]), badd2(a[5], a[7]));
}
__device__ __forceinline__ void add_rowsum(const uint32_t (&p)[32], float& l0, float& l1) {
  uint32_t t0, t1;
  rowsum_p(p, t0, t1);
  l0 += bflo(t0) + bfhi(t0); l1 += bflo(t1) + bfhi(t1);
}
__device__ __forceinline__ void pack_p(uint32_t (&p)[32], const float (&s)[64]) {
  #pragma unroll
  for (int i = 0; i < 32; i++) p[i] = pack_bf16(s[2 * i], s[2 * i + 1]);
}
__device__ __noinline__ void attn_rows_exact(uint32_t bid, uint32_t sq, uint32_t so, int hsel, const bf16* __restrict__ kh, const bf16* __restrict__ vh) {
  const int warp = (threadIdx.x >> 5) & 3, lane = threadIdx.x & 31;
  const size_t hofs = (size_t)((bid < 128 ? bid >> 4 : 15) * 2 + hsel) * T_SEQ * T_DH;
  kh += hofs; vh += hofs;
  #pragma unroll 1
  for (int r = 16 * warp; r < 16 * warp + 16; r++) {
    const uint32_t ad = (lane >> 4) * 16384 + r * 128 + ((((lane & 15) >> 1) ^ (r & 7)) << 4) + (lane & 1) * 8;
    uint2 qv; asm volatile("ld.shared.v2.u32 {%0, %1}, [%2];" : "=r"(qv.x), "=r"(qv.y) : "r"(sq + ad) : "memory");
    const float q0 = bflo(qv.x), q1 = bfhi(qv.x), q2 = bflo(qv.y), q3 = bfhi(qv.y);
    float m = -INFINITY, l = 0.f, o0 = 0.f, o1 = 0.f, o2 = 0.f, o3 = 0.f;
    #pragma unroll 1
    for (int key = 0; key < T_SEQ; key++) {
      const uint2 kv = *reinterpret_cast<const uint2*>(kh + (size_t)key * T_DH + lane * 4);
      const uint2 vv = *reinterpret_cast<const uint2*>(vh + (size_t)key * T_DH + lane * 4);
      float sc = (q0 * bflo(kv.x) + q1 * bfhi(kv.x)) + (q2 * bflo(kv.y) + q3 * bfhi(kv.y));
      #pragma unroll
      for (int o = 16; o > 0; o >>= 1) sc += __shfl_xor_sync(0xffffffffu, sc, o);
      const float mn = fmaxf(m, sc);
      const float al = (m == mn) ? 1.0f : ex2_approx(m - mn), p = rbf(ex2_approx(sc - mn));
      m = mn;
      l = fmaf(l, al, p);
      o0 = fmaf(o0, al, p * bflo(vv.x)); o1 = fmaf(o1, al, p * bfhi(vv.x));
      o2 = fmaf(o2, al, p * bflo(vv.y)); o3 = fmaf(o3, al, p * bfhi(vv.y));
    }
    const float inv = rcp_approx(l);
    asm volatile("st.shared.v2.u32 [%0], {%1, %2};" :: "r"(so + ad), "r"(pack_bf16(o0 * inv, o1 * inv)), "r"(pack_bf16(o2 * inv, o3 * inv)) : "memory");
  }
}
__device__ __forceinline__ void issue_qk(float (&s)[64], const uint32_t (&q)[32], uint32_t k_lo) {
  wgmma_fence();
  wgmma_m64n128k16_rs<0>(s, q[0], q[1], q[2], q[3], k_lo, 0);
  wgmma_m64n128k16_rs<2>(s, q[4], q[5], q[6], q[7], k_lo, 1);
  wgmma_m64n128k16_rs<4>(s, q[8], q[9], q[10], q[11], k_lo, 1);
  wgmma_m64n128k16_rs<6>(s, q[12], q[13], q[14], q[15], k_lo, 1);
  wgmma_m64n128k16_rs<1024>(s, q[16], q[17], q[18], q[19], k_lo, 1);
  wgmma_m64n128k16_rs<1026>(s, q[20], q[21], q[22], q[23], k_lo, 1);
  wgmma_m64n128k16_rs<1028>(s, q[24], q[25], q[26], q[27], k_lo, 1);
  wgmma_m64n128k16_rs<1030>(s, q[28], q[29], q[30], q[31], k_lo, 1);
  wgmma_commit();
}
__device__ __forceinline__ void issue_pv(float (&o)[64], const uint32_t (&p)[32], uint32_t v_lo, int accumulate) {
  wgmma_fence();
  wgmma_m64n128k16_rs_tb<0>(o, p[0], p[1], p[2], p[3], v_lo, accumulate);
  wgmma_m64n128k16_rs_tb<128>(o, p[4], p[5], p[6], p[7], v_lo, 1);
  wgmma_m64n128k16_rs_tb<256>(o, p[8], p[9], p[10], p[11], v_lo, 1);
  wgmma_m64n128k16_rs_tb<384>(o, p[12], p[13], p[14], p[15], v_lo, 1);
  wgmma_m64n128k16_rs_tb<512>(o, p[16], p[17], p[18], p[19], v_lo, 1);
  wgmma_m64n128k16_rs_tb<640>(o, p[20], p[21], p[22], p[23], v_lo, 1);
  wgmma_m64n128k16_rs_tb<768>(o, p[24], p[25], p[26], p[27], v_lo, 1);
  wgmma_m64n128k16_rs_tb<896>(o, p[28], p[29], p[30], p[31], v_lo, 1);
  wgmma_commit();
}
__device__ __forceinline__ void block_end(uint32_t zero, uint32_t bar) {
  #pragma unroll 1
  for (uint32_t i = 0; i < zero; i++) mbar_arrive(bar);
}
__device__ __forceinline__ void rescale_o(float (&o)[64], float al0, float al1) {
  #pragma unroll
  for (int j = 0; j < 16; j++) { o[4 * j] *= al0; o[4 * j + 1] *= al0; o[4 * j + 2] *= al1; o[4 * j + 3] *= al1; }
}

__device__ __forceinline__ void stage_o(const float (&o)[64], float i0, float i1, uint32_t dst, int lane) {
  #pragma unroll
  for (int J = 0; J < 16; J += 2)
    stmatrix_x4(dst + (J >> 3) * 16384 + ((((J & 7) + (lane >> 4)) ^ (lane & 7)) << 4),
                pack_bf16(o[4 * J + 0] * i0, o[4 * J + 1] * i0), pack_bf16(o[4 * J + 2] * i1, o[4 * J + 3] * i1),
                pack_bf16(o[4 * J + 4] * i0, o[4 * J + 5] * i0), pack_bf16(o[4 * J + 6] * i1, o[4 * J + 7] * i1));
}
__device__ __forceinline__ bool finish_l(float& l0, float& l1) {
  l0 += __shfl_xor_sync(0xffffffffu, l0, 1); l1 += __shfl_xor_sync(0xffffffffu, l1, 1);
  l0 += __shfl_xor_sync(0xffffffffu, l0, 2); l1 += __shfl_xor_sync(0xffffffffu, l1, 2);
  const bool redo = __any_sync(0xffffffffu, !(l0 <= AT_RAW_SUM && l1 <= AT_RAW_SUM && l0 >= AT_RAW_MIN && l1 >= AT_RAW_MIN));
  l0 = rcp_approx(l0); l1 = rcp_approx(l1);
  return redo;
}
template <int J0>
__device__ __forceinline__ void stage_q(const float (&acc)[128], float c, uint32_t dst, int lane) {
  #pragma unroll
  for (int J = J0; J < J0 + 16; J += 2)
    stmatrix_x4(dst + (J >> 3) * 16384 + ((((J & 7) + (lane >> 4)) ^ (lane & 7)) << 4),
                pack_bf16(acc[4 * J + 0] * c, acc[4 * J + 1] * c), pack_bf16(acc[4 * J + 2] * c, acc[4 * J + 3] * c),
                pack_bf16(acc[4 * J + 4] * c, acc[4 * J + 5] * c), pack_bf16(acc[4 * J + 6] * c, acc[4 * J + 7] * c));
}
__device__ __forceinline__ void store_o(const CUtensorMap* tmO, uint32_t src, int head, int row) {
  tma_store_2d(tmO, src, head * T_DH, row);
  tma_store_2d(tmO, src + 16384, head * T_DH + 64, row);
  bulk_commit();
}
__device__ __forceinline__ void mma_bf16(float (&d)[4], uint32_t a0, uint32_t a1, uint32_t a2, uint32_t a3, uint32_t b0, uint32_t b1) {
  asm volatile("mma.sync.aligned.m16n8k16.row.col.f32.bf16.bf16.f32 {%0, %1, %2, %3}, {%4, %5, %6, %7}, {%8, %9}, {%0, %1, %2, %3};"
               : "+f"(d[0]), "+f"(d[1]), "+f"(d[2]), "+f"(d[3]) : "r"(a0), "r"(a1), "r"(a2), "r"(a3), "r"(b0), "r"(b1));
}
struct GemvSel { uint32_t lo0, hi0, lo1, hi1; };
__device__ __forceinline__ GemvSel gemv_sel(int lane) {
  const uint32_t lo = (lane & 8) ? 0x1044u : 0x4410u, hi = (lane & 8) ? 0x3244u : 0x4432u;
  GemvSel s; s.lo0 = (lane & 16) ? 0x4444u : lo; s.hi0 = (lane & 16) ? 0x4444u : hi; s.lo1 = (lane & 16) ? lo : 0x4444u; s.hi1 = (lane & 16) ? hi : 0x4444u;
  return s;
}
#define GEMV_B0(j, h, s) __byte_perm((j) < 2 ? (h).x : (h).y, 0u, ((j) & 1) ? (s).hi0 : (s).lo0)
#define GEMV_B1(j, h, s) __byte_perm((j) < 2 ? (h).x : (h).y, 0u, ((j) & 1) ? (s).hi1 : (s).lo1)
__device__ __forceinline__ int gemv_col(int i) { return (i >> 4) * 8 + ((i >> 3) & 1) * 4 + (i & 2) + ((i >> 2) & 1); }
#define OG_XN 4
#define OG_XB 5
#define OG_NG 8
#define PUT_N 2
#define H_STAG 2
#define AL_P 60
#define AL_SLEEP 1200
#define AL_MAX 800
#define POLL_NS 500
#define OG_PROF 0xDDCCBA87u
#define RK_P 24
__host__ __device__ constexpr int og_pre(int tile) { return (OG_PROF >> ((tile >> 4) * 4)) & 15; }
constexpr int OG_PRE2 = og_pre(127), OG_HSUM = og_pre(0) + og_pre(16) + og_pre(32) + og_pre(48) + og_pre(64) + og_pre(80) + og_pre(96);
#define OG_JOBS 7
#define OG_GRP 6
#define LD_FIRST 2
#define LD_STAG (OG_GRP / 2)
constexpr int OG_ST = 5, OG_NKB = T_DQKV / 64 - og_pre(0), OG_MOE = T_F / 32;
__device__ __forceinline__ int pre_kb(int i) { return (i >> 1) * 4 + (i & 1); }
__device__ __forceinline__ int own_kb(int i, int pre) { return i < (pre & ~1) ? pre_kb(i) + 2 : i + pre; }
static_assert(LD_FIRST + LD_STAG <= OG_XB && OG_XB < LD_FIRST + OG_GRP, "the extra tile belongs to segment 1");
static_assert(og_pre(16) >= 16 / PUT_N && LD_FIRST + 7 * OG_GRP + LD_STAG + 3 <= 64 - OG_PRE2, "job / segment lengths");
constexpr int OG_POS = 8;
constexpr uint32_t OG_STAGE = 32768;
constexpr uint32_t OG_SCOL = AT_SBAR + 512;
constexpr uint32_t OG_SMISC = AT_SBAR + 2048;
constexpr uint32_t OG_SWD = AT_SQ, OG_PSLOT = AT_SQ;
constexpr uint32_t OG_XSLOT = AT_SQ + 32768;
constexpr uint32_t OG_OSLOT = 1 * OG_STAGE;
constexpr uint32_t OG_SRED = 3 * OG_STAGE;
constexpr uint32_t OG_SH2 = OG_SRED + 24576;
constexpr uint32_t OG_SSTAT = OG_SRED + 16384;
constexpr uint32_t OG_SGU = OG_SRED + 8192;
constexpr uint32_t OG_SFIN = OG_SGU + 256;
#define OGM 2
#define OG_MT(b) ((((b) >> OGM) & 15) ^ (((b) & 64) ? 15 : 0))
#define OG_NT(b) (((b) & ((1 << OGM) - 1)) + (((b) >> (4 + OGM)) << OGM))
__device__ __forceinline__ int tail_tile(uint32_t sbase) { mbar_wait_long(sbase + AT_SBAR + 336, 0); return (int)lds_u32(sbase + AT_SBAR + 408); }
#define TAIL_SETUP \
  const uint32_t bar_full = sbase + AT_SBAR, bar_empty = bar_full + 40; \
  const uint32_t bar_wd = bar_full + 168, bar_col = bar_full + 176, bar_out = bar_full + 184, bar_end = bar_full + 192; \
  const uint32_t bar_key = bar_full + 200, bar_h2 = bar_full + 208, bar_sel = bar_full + 216; \
  const int mt = OG_MT(tb), nt = OG_NT(tb); \
  const int m0 = mt * 128, n0 = nt * 128; \
  const bool has_moe = (int)bid < OG_MOE; \
  (void)bar_empty; (void)bar_wd; (void)bar_col; (void)bar_out; (void)bar_end; (void)bar_key; (void)bar_h2; (void)bar_sel; (void)m0; (void)n0; (void)has_moe;

__device__ __forceinline__ void tail_producer(uint32_t bid, uint32_t sbase, uint32_t ph, uint64_t pol, const CUtensorMap* tmA, const CUtensorMap* tmB, const CUtensorMap* tmD) {
  const int tb = tail_tile(sbase);
  TAIL_SETUP
  uint32_t stage = OG_POS % OG_ST;
  int kb = 0, xk = OG_XB;
  uint32_t xp = 1;
  #pragma unroll 1
  for (int seg = 0; seg < 2; seg++) {
    mbar_wait(bar_full + 264 + 80 * seg, 0);
    fence_proxy_async_global();
    const int end = 32 + 32 * seg - og_pre(tb);
    #pragma unroll 1
    for (; kb < end; kb++) {
      const bool xb = kb == xk;
      const uint32_t fb = xb ? bar_full + 360 : bar_full + 8 * stage, sa = sbase + (xb ? 5 : stage) * OG_STAGE;
      const int k0 = own_kb(kb, og_pre(tb)) * 64;
      if (xb) {
        mbar_wait(bar_full + 80, bid < AT_NFULL);
        mbar_wait(bar_full + 368, xp);
        xp ^= 1;
        if (xk < OG_XB + (OG_XN - 1) * OG_GRP) xk += OG_GRP;
      }
      mbar_wait_long(xb ? bar_full + 304 : bar_empty + 8 * stage, xb ? 0 : ph);
      mbar_expect_tx(fb, OG_STAGE);
      tma_load_3d_hint(sa + 16384, tmB, k0, 2 * nt, fb, pol);
      tma_load_2d_hint(sa, tmA, k0, m0, fb, pol);
      if (!xb && ++stage == OG_ST) { stage = 0; ph ^= 1; }
    }
  }
  if (has_moe) {
    stage += stage & 1;
    mbar_wait(bar_empty + 8 * stage, ph);
    mbar_expect_tx(bar_wd, OG_STAGE);
    tma_load_3d_hint(sbase + stage * OG_STAGE, tmD, bid * 32, 8, bar_wd, pol);
  }
}

__device__ __forceinline__ uint32_t out2(uint32_t x1, uint32_t mb2, uint32_t ih, uint32_t il, uint32_t c1, uint32_t sb, uint32_t gb) {
  const uint32_t h2 = badd2(bmul2(ln_norm2b(x1, mb2, ih, il), c1), sb);
  return badd2(x1, bmul2(gb, bfma2(h2, 0u, h2)));
}
#define X_PACE 200
#define Y_SLACK 96
#define OG_STAG 3
#define POLL_NS2 100
#define WD_SKIP 1
#define AL_ADD 380
#define WD_PACE 300
__device__ __forceinline__ void tail_exchange(uint32_t bid, uint32_t sbase, const bf16* __restrict__ w_down, const bf16* __restrict__ w_r, const bf16* __restrict__ x, bf16* __restrict__ out) {
    const int lane = threadIdx.x & 31, wi = __shfl_sync(0xffffffffu, threadIdx.x >> 5, 0);
    if (wi == 3) {
      uint32_t a = bid, b = 0u;
      if (bid < AT_NFULL) mbar_wait_long(sbase + AT_SBAR + 312, 0);
      if (bid < OG_MOE) {
        asm volatile("mov.u32 %0, %%globaltimer_lo;" : "=r"(a));
        if (lane == 0 && (bid & 15) == 0) asm volatile("st.relaxed.gpu.global.u32 [%0], %1;" :: "l"(g_hcnt + 8 + (bid >> 4)), "r"((a & ~15u) | 8u | (bid >> 4)) : "memory");
        #pragma unroll 1
        for (unsigned int spin = 0; spin < (1u << 22) && __any_sync(0xffffffffu, b == 0u); spin++) {
          __nanosleep(200);
          asm volatile("ld.relaxed.gpu.global.u32 %0, [%1];" : "=r"(b) : "l"(g_hcnt + 8 + min(lane, 6)) : "memory");
        }
        a = __popc(__ballot_sync(0xffffffffu, b < __shfl_sync(0xffffffffu, b, bid >> 4)) & 127u) * 16 + (bid & 15);
      }
      if (lane == 0) {
        sts_u32(sbase + AT_SBAR + 408, a);
        mbar_arrive(sbase + AT_SBAR + 336);
        b = 0u;
        if (bid < AT_NFULL) {
          unsigned int* tm = g_hcnt + 32 * (1 + (bid >> 4)) + 8;
          mbar_wait_long(sbase + AT_SBAR + 312, 1);
          asm volatile("mov.u32 %0, %%globaltimer_lo;" : "=r"(a));
          asm volatile("red.relaxed.gpu.global.max.u32 [%0], %1;" :: "l"(tm), "r"(a) : "memory");
          __nanosleep(AL_SLEEP);
          asm volatile("ld.relaxed.gpu.global.u32 %0, [%1];" : "=r"(b) : "l"(tm) : "memory");
          b -= a;
        }
        sts_u32(sbase + AT_SBAR + 412, b < AL_MAX ? b * 13 / 8 : 0u);
        mbar_arrive(sbase + AT_SBAR + 320);
      }
      named_bar_sync(15, 32);
    }
    const int tb = __shfl_sync(0xffffffffu, tail_tile(sbase), 0);
    TAIL_SETUP
    if (wi == 3) {
      mbar_wait_long(bar_full + 344, 0);
      float a = g_scal[lane], b = g_scal[32 + lane];
      #pragma unroll
      for (int i = 0; i < 3; i++) {
        const uint4 v = *reinterpret_cast<const uint4*>(g_col + nt * 1536 + i * 512 + lane * 16);
        sts_u32x4(sbase + OG_SCOL + i * 512 + lane * 16, v.x, v.y, v.z, v.w);
      }
      #pragma unroll
      for (int o = 16; o > 0; o >>= 1) { a += __shfl_xor_sync(0xffffffffu, a, o); b += __shfl_xor_sync(0xffffffffu, b, o); }
      if (lane == 0) sts_f32x2(sbase + OG_SMISC, a, b);
      const uint64_t pol = policy_evict_first();
      #pragma unroll 1
      for (int r = lane >> 4; r < 128; r += 4) {
        __nanosleep(X_PACE);
        #pragma unroll
        for (int j = 0; j < 4; j += 2)
          asm volatile("cp.async.cg.shared.global.L2::cache_hint [%0], [%1], 16, %2;" :: "r"(sbase + OG_XSLOT + (lane & 8) * 2048 + (r + j) * 128 + (((lane ^ (r + j)) & 7) << 4)),
                       "l"(x + (size_t)(m0 + r + j) * T_D + n0 + (lane & 15) * 8), "l"(pol) : "memory");
      }
      asm volatile("cp.async.wait_all;" ::: "memory");
      __syncwarp();
      if (lane == 0) mbar_arrive(bar_col);
    } else if (wi == 2) {
      if (elect_one()) {
        mbar_wait_long(bar_full + (has_moe ? 80 : 376), has_moe);
        #pragma unroll 1
        for (unsigned int i = 0; i < (1u << 20) && ld_acquire(&g_hcnt[32 * (1 + (tb >> 3)) + 4 + ((tb >> 1) & 3)]) == 0u; i++) __nanosleep((tb >> 4) == 6 ? POLL_NS2 : POLL_NS);
        TL_MARK2(23, true);
        fence_proxy_async_global();
        TL_MARK2(4, true);
        mbar_expect_tx(bar_full + 272, 32768);
        bulk_load_hint(sbase + OG_PSLOT, g_pre + tb * 2048, 32768, bar_full + 272, policy_evict_first());
      }
      named_bar_sync(14, 32);
      if (has_moe) {
        mbar_wait_long(bar_full + 376, 0);
        const uint64_t pol = policy_evict_first();
        #pragma unroll 1
        for (int r = 0; r < 32; r++) {
          if ((r & WD_SKIP) != WD_SKIP) __nanosleep(WD_PACE);
          #pragma unroll
          for (int j = 0; j < 2; j++)
            asm volatile("cp.async.cg.shared.global.L2::cache_hint [%0], [%1], 16, %2;" :: "r"(sbase + OG_SWD + (4 * j + (lane >> 3)) * 4096 + r * 128 + (((lane ^ r) & 7) << 4)),
                         "l"((const uint8_t*)w_down + (size_t)bid * 65536 + r * 2048 + j * 512 + lane * 16), "l"(pol) : "memory");
        }
        asm volatile("cp.async.wait_all;" ::: "memory");
        __syncwarp();
        if (lane == 0) mbar_arrive(bar_wd);
      }
    }
    const uint4 wrv = ldg_nc_v4(w_r + threadIdx.x * 8);
    mbar_wait_long(bar_end, 0);
    TL_MARK2(22, lane == 0);
    if (wi == 0) {
      uint32_t k1 = 0u, k2 = 0u;
      #pragma unroll 1
      for (unsigned int spin = 0; spin < (1u << 22) && __any_sync(0xffffffffu, k1 == 0u); spin++) asm volatile("ld.relaxed.gpu.global.u32 %0, [%1];" : "=r"(k1) : "l"(g_key + lane) : "memory");
      TL_MARK2(28, lane == 0);
      warp_top2(k1, k2);
      if (lane == 0) {
        const uint32_t r1 = 0xffffu - (k1 & 0xffffu), r2 = 0xffffu - (k2 & 0xffffu);
        sts_u32x4(sbase + OG_SMISC + 64, r1, r2, (r1 >> 7) * 2, (r2 >> 7) * 2 + ((r1 >> 7) == (r2 >> 7)));
        mbar_arrive(bar_sel);
      }
    } else if (wi < 3) {
          mbar_wait(bar_key, 0);
          const uint4 kk = lds_u32x4(sbase + OG_SSTAT + 1024 + lane * 16);
          uint32_t k1 = max(kk.x, kk.y), k2 = min(kk.x, kk.y);
          k2 = max(max(k2, min(kk.z, kk.w)), min(k1, max(kk.z, kk.w))); k1 = max(k1, max(kk.z, kk.w));
          warp_top2(k1, k2);
          if (wi == 1) {
            if (lane == 0) {
              if (nt == (mt & 7)) st_relaxed2(g_key + mt * 2, k1, k2);
              sts_u32x2(sbase + OG_SMISC + 96, (~k1 >> 4) & 7u, (~k2 >> 4) & 7u);
              mbar_arrive(bar_full + 352);
            }
            TL_MARK2(27, lane == 0);
          } else {
            const uint32_t r = (~((lane & 16) ? k2 : k1)) & 127u, ch = lane & 15;
            const uint2 st = lds_u32x2(sbase + OG_SSTAT + r * 8);
            const uint4 xc = lds_u32x4(sbase + OG_XSLOT + (ch >> 3) * 16384 + r * 128 + (((ch ^ r) & 7) << 4));
            const uint4 c1 = lds_u32x4(sbase + OG_SCOL + 768 + ch * 16), sh = lds_u32x4(sbase + OG_SCOL + 1024 + ch * 16);
            const float inr = __uint_as_float(st.y);
            float* dst = reinterpret_cast<float*>(g_cand + (mt * 2 + (lane >> 4)) * 256 + nt * 16 + ch);
            st_tagged4(dst + 512, __uint_as_float(ln_mod2(xc.x, st.x, inr, c1.x, sh.x)), __uint_as_float(ln_mod2(xc.y, st.x, inr, c1.y, sh.y)),
                       __uint_as_float(ln_mod2(xc.z, st.x, inr, c1.z, sh.z)), __uint_as_float(ln_mod2(xc.w, st.x, inr, c1.w, sh.w)));
            st_tagged4(dst, __uint_as_float(xc.x), __uint_as_float(xc.y), __uint_as_float(xc.z), __uint_as_float(xc.w));
          }
    }
    mbar_wait(bar_sel, 0);
    const uint4 sel = lds_u32x4(sbase + OG_SMISC + 64);
    const int sel0 = (int)sel.x, sel1 = (int)sel.y;
    {
      const float* src0 = reinterpret_cast<const float*>(g_cand + sel.z * 256 + 128 + threadIdx.x);
      const float* src1 = reinterpret_cast<const float*>(g_cand + sel.w * 256 + 128 + threadIdx.x);
      float4 h0, h1;
      #pragma unroll 1
      for (unsigned int spin = 0; spin < (1u << 20); spin++) { h0 = ld_tagged4(src0); h1 = ld_tagged4(src1); if (__all_sync(0xffffffffu, tagged4(h0) & tagged4(h1))) break; }
      sts_f32x4(sbase + OG_SH2 + threadIdx.x * 16, h0.x, h0.y, h0.z, h0.w);
      sts_f32x4(sbase + OG_SH2 + 2048 + threadIdx.x * 16, h1.x, h1.y, h1.z, h1.w);
      __syncwarp();
      if (lane == 0) mbar_arrive(bar_h2);
      TL_MARK2(12, lane == 0);
      float v[8], u[8], wr[8];
      unpack8(make_uint4(__float_as_uint(h0.x), __float_as_uint(h0.y), __float_as_uint(h0.z), __float_as_uint(h0.w)), v);
      unpack8(make_uint4(__float_as_uint(h1.x), __float_as_uint(h1.y), __float_as_uint(h1.z), __float_as_uint(h1.w)), u);
      unpack8(wrv, wr);
      float r0 = 0.f, r1 = 0.f;
      #pragma unroll
      for (int i = 0; i < 8; i++) { r0 = fmaf(v[i], wr[i], r0); r1 = fmaf(u[i], wr[i], r1); }
      r0 = ((lane & 16) ? r1 : r0) + __shfl_xor_sync(0xffffffffu, (lane & 16) ? r0 : r1, 16);
      #pragma unroll
      for (int o = 8; o > 0; o >>= 1) r0 += __shfl_xor_sync(0xffffffffu, r0, o);
      if ((lane & 15) == 0) sts_f32(sbase + OG_SMISC + 192 + lane + wi * 4, r0);
    }
    mbar_wait(bar_out, 0);
    {
      const uint2 cg = lds_u32x2(sbase + OG_SMISC + 96);
      #pragma unroll
      for (int i = 0; i < 4; i++) {
        const int r = (i < 2 ? cg.x : cg.y) * 16 + (i & 1) * 8 + (threadIdx.x >> 4), ch = threadIdx.x & 15;
        if (m0 + r != sel0 && m0 + r != sel1)
          *reinterpret_cast<uint4*>(out + (size_t)(m0 + r) * T_D + n0 + ch * 8) =
              lds_u32x4(sbase + OG_OSLOT + (ch >> 3) * 16384 + r * 128 + (((ch & 7) ^ (r & 7)) << 4));
      }
    }
    if (bid == 0 && threadIdx.x < 68) *reinterpret_cast<uint4*>(g_hcnt + 32 * (threadIdx.x >> 2) + 4 * (threadIdx.x & 3)) = make_uint4(0u, 0u, 0u, 0u);
    if (threadIdx.x < 64) g_modpart[bid * 64 + threadIdx.x] = 0.f;
    {
      const int tk = threadIdx.x & 1, col = bid * 8 + gemv_col(threadIdx.x & 15);
      const uint32_t gb2 = *reinterpret_cast<const uint32_t*>(g_col + (col >> 7) * 1536 + 512 + 768 + (col & 126) * 2);
      const uint32_t* xp = reinterpret_cast<const uint32_t*>(g_cand + (tk ? sel.w : sel.z) * 256) + (col >> 1);
      uint32_t x2 = 0u;
      #pragma unroll 1
      for (unsigned int spin = 0; spin < (1u << 20) && __any_sync(0xffffffffu, x2 == 0u); spin++) asm volatile("ld.relaxed.gpu.global.u32 %0, [%1];" : "=r"(x2) : "l"(xp) : "memory");
      const float* src = g_ypart + (size_t)(threadIdx.x >> 2) * 2 * T_D + bid * 16 + (threadIdx.x & 3) * 4;
      const bool four = threadIdx.x < (OG_MOE - 96) * 4;
      named_bar_sync(10, 128);
      const uint4 rp = lds_u32x4(sbase + OG_SMISC + 192 + tk * 16);
      const float rs = rbf(sigmoid_f(rbf((__uint_as_float(rp.x) + __uint_as_float(rp.y)) + (__uint_as_float(rp.z) + __uint_as_float(rp.w)))));
      const uint32_t h2p = lds_u32(sbase + OG_SH2 + tk * 2048 + (col & ~1) * 2);
      const float fh = (col & 1) ? bfhi(h2p) : bflo(h2p), fz = rbf(fh * 0.0f), fx = (col & 1) ? bfhi(x2) : bflo(x2), fg = (col & 1) ? bfhi(gb2) : bflo(gb2);
      bf16* dst = out + (size_t)(tk ? sel1 : sel0) * T_D + col;
      if (threadIdx.x == 0) hint_wait(CNT_Y, (uint32_t)(OG_MOE - Y_SLACK));
      named_bar_sync(10, 128);
      float4 p0, p1, p2, p3;
      #pragma unroll 1
      for (unsigned int spin = 0; spin < (1u << 20); spin++) {
        p0 = ld_tagged4(src); p1 = ld_tagged4(src + 64 * T_D); p2 = ld_tagged4(src + 128 * T_D); p3 = ld_tagged4(four ? src + 192 * T_D : src);
        if (__all_sync(0xffffffffu, tagged4(p0) & tagged4(p1) & tagged4(p2) & tagged4(p3))) break;
      }
      if (four) { p2.x += p3.x; p2.y += p3.y; p2.z += p3.z; p2.w += p3.w; }
      p0.x = (p0.x + p1.x) + p2.x; p0.y = (p0.y + p1.y) + p2.y; p0.z = (p0.z + p1.z) + p2.z; p0.w = (p0.w + p1.w) + p2.w;
      #pragma unroll
      for (int o = 4; o <= 16; o <<= 1) {
        p0.x += __shfl_xor_sync(0xffffffffu, p0.x, o); p0.y += __shfl_xor_sync(0xffffffffu, p0.y, o);
        p0.z += __shfl_xor_sync(0xffffffffu, p0.z, o); p0.w += __shfl_xor_sync(0xffffffffu, p0.w, o);
      }
      if (lane < 4) sts_f32x4(sbase + OG_SFIN + (threadIdx.x >> 5) * 64 + lane * 16, p0.x, p0.y, p0.z, p0.w);
      named_bar_sync(10, 128);
      TL_MARK2(21, threadIdx.x == 0);
      if (threadIdx.x < 16) {
        const uint32_t ya = sbase + OG_SFIN + threadIdx.x * 4;
        float y = (lds_f32(ya) + lds_f32(ya + 64)) + (lds_f32(ya + 128) + lds_f32(ya + 192));
        y = rbf(y);
        y = rbf(y * rs);
        *dst = __float2bfloat16_rn(fx + rbf(fg * rbf(fh + rbf(fz + y))));
      }
    }
    if (threadIdx.x == 0) XT(11);
    TL_END(4, threadIdx.x == 0);
}

__device__ __forceinline__ void load_pre(uint4* pre, uint32_t sbase, uint32_t buf, int t2) {
  mbar_wait(sbase + AT_SBAR + 272, 0);
  #pragma unroll
  for (int i = 0; i < 8; i++) pre[i] = lds_u32x4(sbase + buf + i * 4096 + t2 * 16);
}
__device__ __forceinline__ void tail_consumer(uint32_t bid, uint32_t sbase, const CUtensorMap* tmOut, const uint4 (&pre)[8], int cwg, const bf16* __restrict__ w_gate, const bf16* __restrict__ w_up) {
    const uint32_t c0 = clock_lo();
    if ((threadIdx.x & 31) == 0) mbar_arrive(sbase + AT_SBAR + 304);
    mbar_wait(sbase + AT_SBAR + 320, 0);
    const uint2 td = lds_u32x2(sbase + AT_SBAR + 408);
    const int tb = __shfl_sync(0xffffffffu, (int)td.x, 0);
    TAIL_SETUP
    const int tid = threadIdx.x & 127, t2 = threadIdx.x - 128;
    const int warp = tid >> 5, lane = tid & 31, w8 = t2 >> 5;
    const uint32_t dbase = (sbase & 0x3FFFFu) >> 4;
    const uint32_t a_base = dbase + ((cwg * 8192) >> 4) + (1u << 16);
    const uint32_t b_base = dbase + (16384 >> 4) + (512u << 16);
    TL_MARK2(25, threadIdx.x == 128);
    const uint64_t pol = policy_evict_first();
    const bf16* pw = ((lane & 16) ? w_up : w_gate) + (size_t)(w8 * 128 + (lane & 3) * 4) * T_F + (has_moe ? bid : 0) * 32 + ((lane >> 2) & 3) * 8;
    uint4 wv[32];
    float acc[64];
    #pragma unroll
    for (int i = 0; i < 8; i++) {
      acc[8 * i] = bflo(pre[i].x); acc[8 * i + 1] = bfhi(pre[i].x); acc[8 * i + 2] = bflo(pre[i].y); acc[8 * i + 3] = bfhi(pre[i].y);
      acc[8 * i + 4] = bflo(pre[i].z); acc[8 * i + 5] = bfhi(pre[i].z); acc[8 * i + 6] = bflo(pre[i].w); acc[8 * i + 7] = bfhi(pre[i].w);
    }
    while (__any_sync(0xffffffffu, clock_lo() - c0 < td.y + AL_ADD)) {}
    uint32_t stage = OG_POS % OG_ST;
    {
      uint32_t phase = (OG_POS / OG_ST) & 1, prev = 12;
      int kb = 0;
      #pragma unroll
      for (int g = 0; g <= OG_NG; g++) {
        const int end = g == OG_NG ? 64 - og_pre(tb) : LD_FIRST + g * OG_GRP + LD_STAG * cwg;
        #pragma unroll 1
        do {
          const bool xb = g >= 1 && g <= OG_XN && kb == OG_XB + (g - 1) * OG_GRP;
          mbar_wait(xb ? bar_full + 360 : bar_full + 8 * stage, xb ? (g - 1) & 1 : phase);
          if (OG_STAG > 0 && g == OG_NG && cwg == 1 && kb == end - OG_STAG) named_bar_sync(7, 256);
          const uint32_t a_lo = a_base + (xb ? 5 : stage) * (OG_STAGE >> 4), b_lo = b_base + (xb ? 5 : stage) * (OG_STAGE >> 4);
          wgmma_fence();
          wgmma_m64n128k16_ss_tb<0, 0>(acc, a_lo, b_lo, 1);
          wgmma_m64n128k16_ss_tb<2, 128>(acc, a_lo, b_lo, 1);
          wgmma_m64n128k16_ss_tb<4, 256>(acc, a_lo, b_lo, 1);
          wgmma_m64n128k16_ss_tb<6, 384>(acc, a_lo, b_lo, 1);
          wgmma_commit();
          if (OG_STAG > 0 && g == OG_NG && cwg == 0 && kb == end - 1) named_bar_arrive(7, 256);
          wgmma_wait<1>();
          if (tid == 0) mbar_arrive(bar_empty + 8 * prev);
          prev = xb ? 41 + (g == OG_XN) : stage;
          if (!xb && ++stage == OG_ST) { stage = 0; phase ^= 1; }
        } while (++kb < end);
        #pragma unroll
        for (int j = 4 * g; j < 4 * g + 4 && j < 32; j++) wv[j] = ldg_stream_v4(pw + (size_t)(16 * (j >> 2) + (j & 3)) * T_F, pol);
      }
    }
    mbar_wait(bar_col, 0);
    if (__builtin_expect(!has_moe, 0)) {
      load_pre(wv, sbase, AT_SQ, t2);
    }
    wgmma_wait<0>();
    fence_regs(acc);
    if (__builtin_expect(!has_moe, 0)) {
      #pragma unroll
      for (int i = 0; i < 8; i++) {
        acc[8 * i] += bflo(wv[i].x); acc[8 * i + 1] += bfhi(wv[i].x); acc[8 * i + 2] += bflo(wv[i].y); acc[8 * i + 3] += bfhi(wv[i].y);
        acc[8 * i + 4] += bflo(wv[i].z); acc[8 * i + 5] += bfhi(wv[i].z); acc[8 * i + 6] += bflo(wv[i].w); acc[8 * i + 7] += bfhi(wv[i].w);
      }
    }
    if (tid == 0) mbar_arrive(bar_end);
    TL_MARK2(9, lane == 0);
    const int q2 = 2 * (lane & 3);
    const uint32_t frag = (64 * cwg + 16 * warp + (lane & 7) + 8 * ((lane >> 3) & 1)) * 128;
    const int fsw = lane & 7, fhi = lane >> 4;
    {
      float dl[4] = {0.f, 0.f, 0.f, 0.f}, da[4] = {0.f, 0.f, 0.f, 0.f}, db[4] = {0.f, 0.f, 0.f, 0.f};
      const uint32_t tb2 = sbase + OG_SCOL + (lane & 8) * 32 + (lane & 3) * 8, g = lane >> 2;
      const uint32_t msk = (g == 1 || g == 2) ? 0xffffffffu : 0u, one = g == 0 ? 0x3F803F80u : 0u;
      uint32_t xr[8][4];
      #pragma unroll
      for (int hf = 0; hf < 2; hf++) {
        uint32_t ga[8];
        uint2 cw[4];
        #pragma unroll
        for (int i = 0; i < 4; i++) {
          ldmatrix_x4(sbase + OG_XSLOT + hf * 16384 + frag + (((2 * i + fhi) ^ fsw) << 4), xr[4 * hf + i][0], xr[4 * hf + i][1], xr[4 * hf + i][2], xr[4 * hf + i][3]);
          ga[2 * i] = lds_u32(sbase + OG_SCOL + 512 + (64 * hf + 16 * i + q2) * 2); ga[2 * i + 1] = lds_u32(sbase + OG_SCOL + 512 + (64 * hf + 16 * i + 8 + q2) * 2);
          cw[i] = lds_u32x2(tb2 + (8 * hf + 2 * i) * 16);
        }
        #pragma unroll
        for (int i = 0; i < 4; i++) {
          uint32_t* x4 = xr[4 * hf + i];
          #pragma unroll
          for (int e = 0; e < 4; e++) x4[e] = badd2(x4[e], bmul2(ga[2 * i + (e >> 1)], pack_bf16(acc[32 * hf + 8 * i + 2 * e], acc[32 * hf + 8 * i + 2 * e + 1])));
          mma_bf16(dl, x4[0], x4[1], x4[2], x4[3], (cw[i].x & msk) | one, (cw[i].y & msk) | one);
          mma_bf16(da, x4[0], x4[1], x4[2], x4[3], x4[0], x4[2]);
          mma_bf16(db, x4[0], x4[1], x4[2], x4[3], x4[1], x4[3]);
        }
      }
      {
        const int dsrc = (lane & ~3) + (g >> 1);
        const float qa = __shfl_sync(0xffffffffu, (g & 1) ? da[1] : da[0], dsrc), qb = __shfl_sync(0xffffffffu, (g & 1) ? db[3] : db[2], dsrc);
        const float e0 = __shfl_xor_sync(0xffffffffu, (lane & 1) ? dl[0] : dl[2], 1), e1 = __shfl_xor_sync(0xffffffffu, dl[3], 1);
        if ((lane & 3) < 2) {
          const bool hi = lane & 1;
          st_tagged4(reinterpret_cast<float*>(g_part1 + ((mt * 8 + w8) * 8 + nt) * 16 + g + (hi ? 8 : 0)),
                     hi ? e0 : dl[0], hi ? qb : qa, hi ? e1 + dl[2] : dl[1] + e0, 1.0f);
        }
      }
      #pragma unroll
      for (int i = 0; i < 8; i++) stmatrix_x4(sbase + OG_XSLOT + (i >> 2) * 16384 + frag + (((2 * (i & 3) + fhi) ^ fsw) << 4), xr[i][0], xr[i][1], xr[i][2], xr[i][3]);
    }
    TL_MARK2(10, lane == 0);
    uint4 wd[16];
    if (has_moe) mbar_wait(bar_wd, 0);
    #pragma unroll
    for (int i = 0; i < 16; i++) wd[i] = lds_u32x4(sbase + (cwg ? (stage + (stage & 1)) * OG_STAGE : OG_SWD) + warp * 8192 + (i >> 3) * 4096 + (i & 6) * 512 + (i & 1) * 128 + (lane & 3) * 256 + (((lane >> 2) ^ (2 * (lane & 3) + (i & 1))) << 4));
    {
      const float* src = reinterpret_cast<const float*>(g_part1 + ((mt * 8 + w8) * 8 + (lane & 1) * 4) * 16 + (lane >> 1));
      float4 v, v1, v2, v3;
      #pragma unroll 1
      for (unsigned int spin = 0; spin < (1u << 22); spin++) {
        v = ld_tagged4(src); v1 = ld_tagged4(src + 64); v2 = ld_tagged4(src + 128); v3 = ld_tagged4(src + 192);
        if (__all_sync(0xffffffffu, tagged4(v) & tagged4(v1) & tagged4(v2) & tagged4(v3))) break;
      }
      __syncwarp();
      TL_MARK2(26, lane == 0);
      v.x = (v.x + v1.x) + (v2.x + v3.x); v.y = (v.y + v1.y) + (v2.y + v3.y); v.z = (v.z + v1.z) + (v2.z + v3.z);
      v.x += __shfl_xor_sync(0xffffffffu, v.x, 1); v.y += __shfl_xor_sync(0xffffffffu, v.y, 1); v.z += __shfl_xor_sync(0xffffffffu, v.z, 1);
      const float mean = v.x * (1.0f / T_D);
      const float var = fmaxf(fmaf(-mean, mean, v.y * (1.0f / T_D)), 0.f);
      const uint32_t mb2 = pack_bf16(mean, mean);
      const float inv = rcp_approx(rbf(sqrt_approx(rbf(rbf(var) + 1e-05f))));
      {
        const float2 sc = lds_f32x2(sbase + OG_SMISC);
        const uint32_t key = rank_key(rbf(fmaf(fmaf(-bflo(mb2), sc.x, v.z), inv, sc.y)), m0 + 16 * w8 + (lane >> 1));
        mbar_wait(bar_end, 0);
        if (lane & 1) sts_u32(sbase + OG_SSTAT + 1024 + (16 * w8 + (lane >> 1)) * 4, key);
        else sts_u32x2(sbase + OG_SSTAT + (16 * w8 + (lane >> 1)) * 8, mb2, __float_as_uint(inv));
        __syncwarp();
        if (lane == 0) mbar_arrive(bar_key);
      }
      const uint32_t ih = pack_bf16(inv, inv), il = pack_bf16(inv - bflo(ih), inv - bflo(ih));
      const uint32_t mba = __shfl_sync(0xffffffffu, mb2, 2 * (lane >> 2)), mbb = __shfl_sync(0xffffffffu, mb2, 2 * (lane >> 2) + 16);
      const uint32_t iha = __shfl_sync(0xffffffffu, ih, 2 * (lane >> 2)), ihb = __shfl_sync(0xffffffffu, ih, 2 * (lane >> 2) + 16);
      const uint32_t ila = __shfl_sync(0xffffffffu, il, 2 * (lane >> 2)), ilb = __shfl_sync(0xffffffffu, il, 2 * (lane >> 2) + 16);
      #pragma unroll 1
      for (int J0 = 0; J0 < 16; J0 += 4) {
        uint32_t xr[2][4], cv[4][3];
        #pragma unroll
        for (int i = 0; i < 2; i++) {
          ldmatrix_x4(sbase + OG_XSLOT + (J0 >> 3) * 16384 + frag + ((((J0 & 7) + 2 * i + fhi) ^ fsw) << 4), xr[i][0], xr[i][1], xr[i][2], xr[i][3]);
          #pragma unroll
          for (int h = 0; h < 2; h++)
            #pragma unroll
            for (int k = 0; k < 3; k++) cv[2 * i + h][k] = lds_u32(sbase + OG_SCOL + 768 + 256 * k + (8 * (J0 + 2 * i + h) + q2) * 2);
        }
        #pragma unroll
        for (int i = 0; i < 2; i++) {
          #pragma unroll
          for (int h = 0; h < 2; h++) {
            xr[i][2 * h] = out2(xr[i][2 * h], mba, iha, ila, cv[2 * i + h][0], cv[2 * i + h][1], cv[2 * i + h][2]);
            xr[i][2 * h + 1] = out2(xr[i][2 * h + 1], mbb, ihb, ilb, cv[2 * i + h][0], cv[2 * i + h][1], cv[2 * i + h][2]);
          }
          stmatrix_x4(sbase + OG_OSLOT + (J0 >> 3) * 16384 + frag + ((((J0 & 7) + 2 * i + fhi) ^ fsw) << 4), xr[i][0], xr[i][1], xr[i][2], xr[i][3]);
        }
      }
      fence_proxy_async();
      mbar_wait(bar_full + 352, 0);
      const uint2 cg = lds_u32x2(sbase + OG_SMISC + 96);
      __syncwarp();
      if (elect_one()) {
        mbar_arrive(bar_out);
        if (cg.x != w8 && cg.y != w8) {
          asm volatile("cp.async.bulk.tensor.2d.global.shared::cta.bulk_group [%0, {%2, %3}], [%1];" :: "l"(tmOut), "r"(sbase + OG_OSLOT + w8 * 2048), "r"(n0), "r"(m0 + 16 * w8) : "memory");
          asm volatile("cp.async.bulk.tensor.2d.global.shared::cta.bulk_group [%0, {%2, %3}], [%1];" :: "l"(tmOut), "r"(sbase + OG_OSLOT + 16384 + w8 * 2048), "r"(n0 + 64), "r"(m0 + 16 * w8) : "memory");
          bulk_commit();
        }
      }
      TL_MARK2(24, lane == 0);
    }
    if (has_moe) mbar_wait(bar_h2, 0);
    TL_MARK2(13, lane == 0);
    if (has_moe) {
      const GemvSel sel = gemv_sel(lane);
      {
        float d[4][4];
        #pragma unroll
        for (int c = 0; c < 4; c++) { d[c][0] = 0.f; d[c][1] = 0.f; d[c][2] = 0.f; d[c][3] = 0.f; }
        #pragma unroll
        for (int st = 0; st < 8; st++) {
          const uint2 hb = lds_u32x2(sbase + OG_SH2 + ((lane >> 2) & 1) * 2048 + (w8 * 128 + st * 16 + (lane & 3) * 4) * 2);
          #pragma unroll
          for (int j = 0; j < 4; j++) mma_bf16(d[j], wv[4 * st + j].x, wv[4 * st + j].y, wv[4 * st + j].z, wv[4 * st + j].w, GEMV_B0(j, hb, sel), GEMV_B1(j, hb, sel));
        }
        #pragma unroll
        for (int e = 0; e < 4; e++) d[0][e] = (d[0][e] + d[1][e]) + (d[2][e] + d[3][e]);
        sts_f32x4(sbase + OG_SRED + t2 * 16, d[0][0], d[0][1], d[0][2], d[0][3]);
      }
      named_bar_sync(9, 256);
      if (t2 < 64) {
        const int c = gemv_col(t2);
        float gp[8], up[8];
        #pragma unroll
        for (int w = 0; w < 8; w++) { gp[w] = lds_f32(sbase + OG_SRED + w * 512 + t2 * 4); up[w] = lds_f32(sbase + OG_SRED + w * 512 + 256 + t2 * 4); }
        const float gs = ((gp[0] + gp[1]) + (gp[2] + gp[3])) + ((gp[4] + gp[5]) + (gp[6] + gp[7]));
        const float us = ((up[0] + up[1]) + (up[2] + up[3])) + ((up[4] + up[5]) + (up[6] + up[7]));
        asm volatile("st.shared.u16 [%0], %1;" :: "r"(sbase + OG_SGU + (t2 & 1) * 64 + ((c & ~15) + ((c >> 1) & 3) * 4 + ((c >> 3) & 1) * 2 + (c & 1)) * 2), "h"((uint16_t)pack_bf16(silu_bf(rbf(gs)) * rbf(us), 0.f)) : "memory");
      }
      named_bar_sync(9, 256);
      TL_MARK2(20, threadIdx.x == 128);
      float d[4][4];
      #pragma unroll
      for (int c = 0; c < 4; c++) { d[c][0] = 0.f; d[c][1] = 0.f; d[c][2] = 0.f; d[c][3] = 0.f; }
      #pragma unroll
      for (int st = 0; st < 2; st++) {
        const uint2 g = lds_u32x2(sbase + OG_SGU + ((lane >> 2) & 1) * 64 + st * 32 + (lane & 3) * 8);
        #pragma unroll
        for (int j = 0; j < 4; j++) {
          const uint32_t b0 = GEMV_B0(j, g, sel), b1 = GEMV_B1(j, g, sel);
          mma_bf16(d[j & 1], wd[4 * st + j].x, wd[4 * st + j].y, wd[4 * st + j].z, wd[4 * st + j].w, b0, b1);
          mma_bf16(d[2 + (j & 1)], wd[8 + 4 * st + j].x, wd[8 + 4 * st + j].y, wd[8 + 4 * st + j].z, wd[8 + 4 * st + j].w, b0, b1);
        }
      }
      #pragma unroll
      for (int e = 0; e < 4; e++) { d[0][e] += d[1][e]; d[2][e] += d[3][e]; }
      float* yp = g_ypart + (size_t)bid * 2 * T_D + w8 * 256 + lane * 4;
      st_tagged4_lsb(yp, d[0][0], d[0][1], d[0][2], d[0][3]);
      st_tagged4_lsb(yp + 128, d[2][0], d[2][1], d[2][2], d[2][3]);
      named_bar_sync(9, 256);
      if (t2 == 0) hint_arrive(CNT_Y);
    }
    bulk_wait_read<0>();
    TL_MARK2(14, threadIdx.x == 128);
    TL_CLK(4, 1, threadIdx.x == 128);
}

__device__ __forceinline__ int help_njobs(uint32_t bid) { return bid < 128 ? OG_JOBS : 16 - OG_JOBS; }
__device__ __forceinline__ int help_job(uint32_t bid, int i) { return (i < OG_JOBS ? 16 * i + (bid >> 7) * 2 : 112 + (i - OG_JOBS) * 2) + (bid & 3) * 4; }
__device__ __noinline__ void store_warp(uint32_t bid, uint32_t sbase, const CUtensorMap* tmO, int item0, int n_items) {
  if (elect_one()) {
    const uint32_t bars = sbase + AT_SBAR, b_q0 = bars + 80, b_ob = bars + 96, b_ordy = bars + 104, b_acq = bars + 264;
    const unsigned int* cnt = g_hcnt + 32 * (1 + OG_MT(124)) + 2;
    #pragma unroll 1
    for (int q = 0; q < 4 * n_items; q++) {
      const int item = item0 + (q >> 2) * 128, h = (q >> 1) & 1, w = q & 1;
      const bool last = (q >> 2) == n_items - 1;
      if (q == 4 * n_items - 4) { mbar_wait_long(bars + 288, 0); red_release_add(&g_hcnt[1], 1u); }
      mbar_wait_long(b_ordy + 8 * (q & 3), q >> 2);
      store_o(tmO, (h ? (last ? sbase + AT_SQ + 32768 : sbase + 2 * 32768) : sbase + AT_SQ) + w * 8192, (item >> 4) * 2 + h, (item & 15) * 128 + w * 64);
      if (w) {
        bulk_wait_read<0>();
        mbar_arrive(h ? b_ob : b_q0);
        bulk_wait<0>();
        fence_proxy_async_global();
        asm volatile("fence.acq_rel.gpu;" ::: "memory");
        hint_arrive(&g_hcnt[32 * (1 + (item & 15)) + 2 + (item >> 7)]);
        if (!h && item < 128) hint_arrive(&g_hcnt[2]);
        if (q == 5) { const int tb = tail_tile(sbase); cnt = g_hcnt + 32 * (1 + OG_MT(tb)) + 2; spin_until(cnt, 16u); mbar_arrive(b_acq); }
      }
    }
    if (n_items == 1) {
      #pragma unroll 1
      for (int i = 0; i < help_njobs(bid); i++) {
        mbar_wait_long(b_acq + 16, i & 1);
        TL_MARK2(23, i == OG_JOBS - 1);
        red_release_add(&g_hcnt[32 * (1 + (help_job(bid, i) >> 3)) + 4 + ((help_job(bid, i) >> 1) & 3)], 1u);
        TL_MARK2(4, i == OG_JOBS - 1);
        if (i == PRE_X - 1) { spin_until(&g_hcnt[1], 132u); mbar_arrive(b_acq + 32); }
      }
    }
    if (bid < 128) {
      if (n_items == 1) { spin_until(cnt, 16u); mbar_arrive(b_acq); }
      spin_until(&g_hcnt[0], 128u); spin_until(cnt + 1, 16u); mbar_arrive(b_acq + 80);
    }
  }
}

__device__ __forceinline__ uint32_t role_of_sm(uint32_t sm) {
  const uint32_t t = sm >> 1, u = t - 32u, d = (u * 37u) >> 8;
  return (t < 32u ? ((t + 7u) & 7u) * 16u + (t >> 3) * 2u : t < 60u ? (u - 7u * d) * 16u + (4u + d) * 2u : t < 62u ? 2u * t + 8u : 2u * t - 4u) + (sm & 1u);
}
__global__ void __launch_bounds__(384, 1)
fused_kernel(const __grid_constant__ CUtensorMap tmH, const __grid_constant__ CUtensorMap tmW, const __grid_constant__ CUtensorMap tmK,
            const __grid_constant__ CUtensorMap tmV, const __grid_constant__ CUtensorMap tmO, const __grid_constant__ CUtensorMap tmOl, const __grid_constant__ CUtensorMap tmWo,
            const __grid_constant__ CUtensorMap tmD, const __grid_constant__ CUtensorMap tmOut, const __grid_constant__ CUtensorMap tmM, uint32_t zero,
            const uint8_t* __restrict__ pf_wo, const bf16* __restrict__ kc, const bf16* __restrict__ vc,
            const bf16* __restrict__ x, const bf16* __restrict__ cvec, const bf16* __restrict__ w_mod, const bf16* __restrict__ w_r,
            const bf16* __restrict__ w_gate, const bf16* __restrict__ w_up, const bf16* __restrict__ w_down, bf16* __restrict__ out)
{
  uint32_t bid, nsm;
  asm volatile("mov.u32 %0, %%smid;" : "=r"(bid));
  asm volatile("mov.u32 %0, %%nsmid;" : "=r"(nsm));
  bid = __shfl_sync(0xffffffffu, nsm == 132u ? role_of_sm(bid) : blockIdx.x, 0);
  extern __shared__ __align__(1024) uint8_t smem_raw[];
  const uint32_t sbase = smem_u32(smem_raw);
  const uint32_t bars = sbase + AT_SBAR;
  const uint32_t b_full = bars, b_empty = bars + 40;
  const uint32_t b_q0 = bars + 80, b_q1 = bars + 88;
  const uint32_t b_ob = bars + 96;
  const uint32_t b_ordy = bars + 104;
  const uint32_t b_pin = bars + 136;
  const uint32_t b_head = bars + 144;
  const uint32_t b_go = bars + 152;
  const uint32_t b_x = bars + 160;
  const int wg = __shfl_sync(0xffffffffu, threadIdx.x >> 7, 0);
  const bool single = bid >= AT_NFULL;
  const int item0 = __shfl_sync(0xffffffffu, bid < 128 ? (int)bid : (int)bid + 124, 0), n_items = __shfl_sync(0xffffffffu, single ? 1 : 2, 0);
  TL_START(3);
  if (threadIdx.x == 0) {
    if (sbase & 1023u) __trap();
    for (int i = 0; i < 5; i++) { mbar_init(b_full + 8 * i, 1); mbar_init(b_empty + 8 * i, 2); }
    mbar_init(b_q0, 1); mbar_init(b_q1, 8); mbar_init(b_ob, 1);
    for (int i = 0; i < 4; i++) mbar_init(b_ordy + 8 * i, 4);
    mbar_init(b_pin, 1); mbar_init(b_head, bid < 128 ? 8 : 1); mbar_init(b_go, 1); mbar_init(b_x, 1);
    mbar_init(bars + 168, 2); mbar_init(bars + 176, 1); mbar_init(bars + 184, 8); mbar_init(bars + 192, 2);
    mbar_init(bars + 200, 8); mbar_init(bars + 208, 4); mbar_init(bars + 216, 1); mbar_init(bars + 264, 1); mbar_init(bars + 272, 1); mbar_init(bars + 280, 8); mbar_init(bars + 288, 1); mbar_init(bars + 296, 1); mbar_init(bars + 304, 8); mbar_init(bars + 312, 1); mbar_init(bars + 320, 1); mbar_init(bars + 328, 1); mbar_init(bars + 336, 1); mbar_init(bars + 344, 1); mbar_init(bars + 352, 1); mbar_init(bars + 360, 1); mbar_init(bars + 368, 2); mbar_init(bars + 376, 2);
    sts_u32(bars + 400, bid);
    fence_mbar_init();
  }

  if (wg == 0) {
    reg_dealloc<AT_PREG>();
    if (threadIdx.x < 32) { __syncwarp(); named_bar_arrive(6, 384); }
    if (threadIdx.x >= 64) {
      named_bar_sync(6, 384);
      if (bid < 128) {
        named_bar_sync(threadIdx.x >= 96 ? 8 : 9, 288);
        if ((threadIdx.x & 31) == 0) red_release_add(&g_hcnt[32 * (1 + (bid >> 3)) + (threadIdx.x >= 96)], 1u);
        TL_MARK2(11, threadIdx.x == 64);
      }
      if (bid < 128) {
        mbar_wait(MOD_AT, 0);
        mod_rest(bid, sbase + OG_SCOL, b_q1, threadIdx.x - 64, cvec, w_mod, w_r);
      }
    } else if (threadIdx.x >= 32) {
      named_bar_sync(6, 384);
      store_warp(bid, sbase, &tmO, item0, n_items);
      __syncwarp();
    } else {
     if (elect_one()) {
      const uint64_t pol = policy_evict_first();
      if (bid < 128) {
        mbar_expect_tx(b_x, 32768);
        if (X_DLY) { const uint32_t c0 = clock_lo(); while (clock_lo() - c0 < X_DLY) {} }
        bulk_load_hint(sbase + 4 * 32768, x + (size_t)bid * 16 * T_D, 32768, b_x, pol);
      }
      prefetch_tmap(&tmW); prefetch_tmap(&tmM); prefetch_tmap(&tmH); prefetch_tmap(&tmWo); prefetch_tmap(&tmOl);
      {
        const uint32_t c0 = clock_lo();
        while (clock_lo() - c0 < W_DLY) {}
        if (bid < 128 && (head_cb(bid) & 15) >= 4 * H_SPLIT) {
          mbar_expect_tx(bars + 328, 32768);
          tma_load_2d_hint(sbase + 3 * 32768, &tmM, head_cb(bid) * 64, (bid >> 5) * 256, bars + 328, pol);
        }
        while (clock_lo() - c0 < W_DLY + W_FIRST) {}
      }
      uint32_t slot = 0, ph = 1;
      #pragma unroll 1
      for (int it = 0; it < n_items; it++) {
        const int item = item0 + it * 128, hp = item >> 4, qt = item & 15;
        const bool first = it == 0;
        #pragma unroll 1
        for (int j = 0; j < T_D / 64; j++) {
          const uint32_t sl = ring_slot(qp_pos(j, it)), fb = b_full + 8 * sl;
          mbar_wait_long(b_empty + 8 * sl, ring_par(qp_pos(j, it)) ^ ((j >> 2) & 1) ^ 1);
          if (first && j == 3) mbar_wait(b_head, 0);
          mbar_expect_tx(fb, 49152);
          tma_load_3d_hint(sbase + sl * 32768, &tmW, j * 64, hp * 4, fb, pol);
          if (first && j < PRE_B) {
            if (j == PRE_B - 1) {
              spin_until(&g_hcnt[32 * (1 + qt)], 8u);
              TL_MARK2(16, true);
              fence_proxy_async_global();
              #pragma unroll 1
              for (int i = 0; i < PRE_B; i++) tma_load_2d(sbase + AT_SQ + i * 16384, &tmH, i * 64, qt * 128, b_full + 8 * i);
              mbar_arrive(b_go);
            }
          } else {
            if (first && j == 4 * H_SPLIT) { spin_until(&g_hcnt[32 * (1 + qt) + 1], 8u); fence_proxy_async_global(); }
            if (!first && (j == 0 || j == 2)) mbar_wait(j ? b_q1 : b_q0, 0);
            tma_load_2d(sbase + AT_SQ + (j & 3) * 16384, &tmH, j * 64, qt * 128, fb);
          }
        }
        #pragma unroll 1
        for (int j = 0; j < 4 * AT_NBLK; j++) {
          const bool isv = (j > 0 && !(j & 1)) || j == 4 * AT_NBLK - 1;
          const int row = hp * 2 * T_SEQ + (isv ? (j - 1) >> 1 : (j + 1) >> 1) * 128;
          const uint32_t fb = b_full + 8 * slot;
          mbar_wait_long(b_empty + 8 * slot, ph);
          if (!first && j == 3) mbar_wait(b_ob, 0);
          if (j == 4 && it == n_items - 1) mbar_arrive(bars + 288);
          if ((j == AL_P || j == RK_P) && it == 1) mbar_arrive(bars + 312);
          mbar_expect_tx(fb, 32768);
          tma_load_3d_hint(sbase + slot * 32768, isv ? &tmV : &tmK, row, 0, fb, pol);
          if (it == 1 && isv && j >= 2 * WO_LATE && j < 2 * WO_LATE + 32 && bid < OG_NKB)
            l2_prefetch_bulk(pf_wo + (size_t)own_kb(bid, og_pre(0)) * 131072 + ((j >> 1) - WO_LATE) * 8192, 8192);
          if (++slot == 5) { slot = 0; ph ^= 1; }
        }
      }
      if (__builtin_expect(single, 0)) {
        spin_until(&g_hcnt[2], 128u);
        fence_proxy_async_global();
        const int nj = OG_HSUM + (help_njobs(bid) - OG_JOBS) * OG_PRE2;
        int ji = 0, job = help_job(bid, 0), kk = 0;
        #pragma unroll 1
        for (int j = 0; j < nj; j++) {
          const uint32_t sl = ring_slot(qp_pos(j, 1)), fb = b_full + 8 * sl;
          mbar_wait_long(b_empty + 8 * sl, ring_par(qp_pos(j, 1)) ^ ((j >> 2) & 1) ^ 1);
          mbar_expect_tx(fb, 49152);
          tma_load_3d(sbase + sl * 32768, &tmWo, pre_kb(kk) * 64, OG_NT(job) * 2, fb);
          tma_load_3d(sbase + sl * 32768 + 16384, &tmWo, pre_kb(kk) * 64, OG_NT(job) * 2 + 2, fb);
          if (j == 0 || j == 2) mbar_wait(j ? b_ob : b_q0, 0);
          tma_load_2d_hint(sbase + AT_SQ + (j & 3) * 16384, &tmOl, pre_kb(kk) * 64, OG_MT(job) * 128, fb, pol);
          if (++kk == og_pre(job)) { kk = 0; job = help_job(bid, ++ji); }
        }
      }
      if (bid < 128) {
        if (single) mbar_wait(b_x, 1);
        tail_producer(bid, sbase, 0, pol, &tmOl, &tmWo, &tmD);
      }
     }
    }
    named_bar_sync(12 + (threadIdx.x >> 5), 32);
    if (bid < 128) tail_exchange(bid, sbase, w_down, w_r, x, out);
  } else {
    if (bid < 128) head_phase(bid, sbase + AT_SQ + 49152, sbase + 4 * 32768, b_x, b_go, b_head, threadIdx.x - 128, zero, cvec, w_mod);
    else { named_bar_sync(6, 384); if (threadIdx.x == 128) mbar_arrive(b_head); }
    TL_MARK2(0, threadIdx.x == 128);
    reg_alloc<AT_CREG>();
    const int cwg = wg - 1;
    const int tid = threadIdx.x & 127;
    const int warp = tid >> 5, lane = tid & 31;
    const uint32_t dbase = (sbase & 0x3FFFFu) >> 4;
    const uint32_t k_base = dbase + (1u << 16);
    const uint32_t v_base = dbase + (1024u << 16);
    const uint32_t w_base = dbase + (512u << 16);
    const uint32_t q_lo = dbase + ((AT_SQ + cwg * 8192) >> 4) + (1u << 16);
    const uint32_t frag = cwg * 8192 + (16 * warp + (lane & 7) + 8 * ((lane >> 3) & 1)) * 128;
    if (cwg == 1) named_bar_arrive(1, 256);
    bool raw = false;
    uint4 pre[8];
    #pragma unroll 1
    for (int it = 0; it < n_items; it++) {
      const bool more = it + 1 < n_items;
      constexpr int nkb = T_D / 64;
      const int ta = __shfl_sync(0xffffffffu, 4 * it, 0);
      float acc[128];
      {
        FS(2 * it, 0);
        #pragma unroll
        for (int i = 0; i < 128; i++) asm volatile("" : "=f"(acc[i]));
        {
          const uint32_t slot = ring_slot(ta), b_lo = w_base + slot * 2048;
          mbar_wait(b_full + 8 * slot, ring_par(ta));
          wgmma_fence();
          wgmma_m64n256k16_ss_tb<0, 0>(acc, q_lo, b_lo, 0);
          wgmma_m64n256k16_ss_tb<2, 128>(acc, q_lo, b_lo, 1);
          wgmma_m64n256k16_ss_tb<4, 256>(acc, q_lo, b_lo, 1);
          wgmma_m64n256k16_ss_tb<6, 384>(acc, q_lo, b_lo, 1);
          wgmma_commit();
        }
        #pragma unroll 1
        for (int j = 1; j < nkb; j++) {
          const uint32_t slot = ring_slot(qp_pos(j, ta >> 2));
          mbar_wait(b_full + 8 * slot, ring_par(qp_pos(j, ta >> 2)) ^ ((j >> 2) & 1));
          const bool pause = cwg == 1 && j == nkb - QP_STAG;
          if (pause) {
            wgmma_wait<0>();
            if (tid == 0) mbar_arrive(b_empty + 8 * ring_slot(qp_pos(j - 1, ta >> 2)));
            named_bar_sync(7, 256);
          }
          const uint32_t a_lo = q_lo + (j & 3) * 1024, b_lo = w_base + slot * 2048;
          wgmma_fence();
          wgmma_m64n256k16_ss_tb<0, 0>(acc, a_lo, b_lo, 1);
          wgmma_m64n256k16_ss_tb<2, 128>(acc, a_lo, b_lo, 1);
          wgmma_m64n256k16_ss_tb<4, 256>(acc, a_lo, b_lo, 1);
          wgmma_m64n256k16_ss_tb<6, 384>(acc, a_lo, b_lo, 1);
          wgmma_commit();
          if (QP_STAG > 0 && cwg == 0 && j == nkb - 1) named_bar_arrive(7, 256);
          if (j > 0) {
            wgmma_wait<1>();
            if (tid == 0 && !pause) mbar_arrive(b_empty + 8 * ring_slot(qp_pos(j - 1, ta >> 2)));
          }
        }
        wgmma_wait<0>();
        fence_regs(acc);
        FS(2 * it, 1);
        TL_MARK2(29, threadIdx.x == 256 && it == 0);
        if (tid == 0) mbar_arrive(b_empty + 24);
      }
      float o[64], s[64];
      uint32_t p[32], q[32];
      #pragma unroll
      for (int i = 0; i < 32; i++) q[i] = HSC == 2 ? pack_bf16(acc[2 * i] * 1.0001f, acc[2 * i + 1] * 1.0001f) : HSC ? pack_bf16(acc[2 * i], acc[2 * i + 1]) : pack_bf16(acc[2 * i] * AT_C, acc[2 * i + 1] * AT_C);
      zero_regs(s);
      const uint32_t sq = sbase + AT_SQ + cwg * 8192;
      float mc0, mc1, al0 = 1.0f, al1 = 1.0f, l0 = 0.f, l1 = 0.f, lp0 = 0.f, lp1 = 0.f;
      bool redo0 = false;
      FS(2 * it, 2);
      mbar_wait(b_full + 8 * ring_slot(ta), ring_par(ta));
      named_bar_sync(1 + cwg, 256);
      FS(2 * it, 3);
      issue_qk(s, q, k_base + ring_slot(ta) * 2048);
      pass_turn(cwg);
      bool ready = mbar_test(b_full + 8 * ring_slot(ta + 1), ring_par(ta + 1)) & mbar_test(b_full + 8 * ring_slot(ta + 2), ring_par(ta + 2));
      stage_q<16>(acc, HSC == 2 ? 1.0001f : HSC ? 1.0f : SQ_DEP ? __uint_as_float(__float_as_uint(AT_C) | ((uint32_t)ready & zero)) : AT_C, sbase + AT_SQ + frag, lane);
      wgmma_wait<0>();
      fence_regs(s);
      if (tid == 0) mbar_arrive(b_empty + 8 * ring_slot(ta));
      mc0 = 0.f; mc1 = 0.f;
      if (!raw) {
        const float a = fmaxf(fmaxf(fmaxf(s[0], s[1]), fmaxf(s[4], s[5])), fmaxf(fmaxf(s[8], s[9]), fmaxf(s[12], s[13])));
        const float b = fmaxf(fmaxf(fmaxf(s[2], s[3]), fmaxf(s[6], s[7])), fmaxf(fmaxf(s[10], s[11]), fmaxf(s[14], s[15])));
        raw = __all_sync(0xffffffffu, fabsf(a) <= 16.0f && fabsf(b) <= 16.0f);
      }
      if (!raw) {
        raw = softmax_mode(s, mc0, mc1);
        if (__builtin_expect(!raw, 0)) softmax_sub(s, mc0, mc1);
      }
      softmax_exp<0, 64>(s);
      #pragma unroll
      for (int J = 0; J < 16; J += 2)
        stmatrix_x4(sbase + AT_SQ + frag + (J >> 3) * 16384 + ((((J & 7) + (lane >> 4)) ^ (lane & 7)) << 4), q[2 * J], q[2 * J + 1], q[2 * J + 2], q[2 * J + 3]);
      pack_p(p, s);
      zero_regs(o);
      FS(2 * it, 4);
      uint32_t ks = ring_slot(ta + 1), vs = ring_slot(ta + 2), kp = ring_par(ta + 1), vp = ring_par(ta + 2);
      auto finish_head = [&]() {
        FS(2 * it, 5);
        redo0 = finish_l(lp0, lp1);
        if (!redo0) stage_o(o, lp0, lp1, sbase + AT_SQ + frag, lane);
        FS(2 * it + 1, 4);
      };
      if (!ready) { mbar_wait(b_full + 8 * ks, kp); mbar_wait(b_full + 8 * vs, vp); }
      #pragma unroll 1
      for (int n = 1; n < 2 * AT_NBLK; n++) {
        named_bar_sync(1 + cwg, 256);
        issue_qk(s, q, k_base + ks * 2048);
        if (n == AT_NBLK + 1) finish_head();
        issue_pv(o, p, v_base + vs * 2048, (n & 15) != 1);
        pass_turn(cwg);
        wgmma_wait<1>();
        fence_regs(s);
        if (tid == 0) mbar_arrive(b_empty + 8 * ks);
        if (__builtin_expect(!raw || (uint32_t)(n - (AT_NBLK - 1)) <= 2u, 0)) {
          if (n == AT_NBLK + 1 && !redo0) {
            fence_proxy_async();
            __syncwarp();
            if (lane == 0) mbar_arrive(b_ordy + 8 * cwg);
          }
          if (n == AT_NBLK - 1) {
            #pragma unroll
            for (int J = 0; J < 16; J += 2)
              ldmatrix_x4(sbase + AT_SQ + 32768 + frag + (J >> 3) * 16384 + ((((J & 7) + (lane >> 4)) ^ (lane & 7)) << 4), q[2 * J], q[2 * J + 1], q[2 * J + 2], q[2 * J + 3]);
          }
          if (!raw) {
            const float m0 = mc0, m1 = mc1;
            const bool ok = softmax_mode(s, mc0, mc1);
            if (n == AT_NBLK) raw = ok;
            else {
              mc0 = mc0 - AT_HEAD > m0 ? mc0 : m0; mc1 = mc1 - AT_HEAD > m1 ? mc1 : m1;
              al0 = ex2_approx(m0 - mc0); al1 = ex2_approx(m1 - mc1);
            }
            if (!raw) softmax_sub(s, mc0, mc1);
          }
        }
        softmax_exp<0, AT_SPLIT>(s);
        add_rowsum(p, l0, l1);
        if (zero != 0) {
          uint32_t dep = zero & __float_as_uint(l0) & __float_as_uint(l1);
          #pragma unroll
          for (int i = AT_SPLIT - AT_PIN - PINB; i < AT_SPLIT - PINB; i += 2) dep &= __float_as_uint(s[i]) & __float_as_uint(s[i + 1]);
          mbar_arrive(b_pin + dep);
        }
        wgmma_wait<0>();
        fence_regs(o);
        if (tid == 0) mbar_arrive(b_empty + 8 * vs);
        ks += 2; if (ks >= 5) { ks -= 5; kp ^= 1; }
        vs += 2; if (vs >= 5) { vs -= 5; vp ^= 1; }
        ready = mbar_test(b_full + 8 * ks, kp) & mbar_test(b_full + 8 * vs, vp);
        softmax_exp<AT_SPLIT, 64>(s);
        pack_p(p, s);
        if (n == AT_NBLK) { lp0 = l0; lp1 = l1; l0 = 0.f; l1 = 0.f; }
        if (__builtin_expect(!raw || !ready, 0)) {
        if (!raw && __any_sync(0xffffffffu, al0 != 1.0f || al1 != 1.0f)) {
          rescale_o(o, al0, al1);
          l0 *= al0; l1 *= al1;
          al0 = 1.0f; al1 = 1.0f;
        }
        if (!ready && n < 2 * AT_NBLK - 1) {
          mbar_wait(b_full + 8 * ks, kp);
          mbar_wait(b_full + 8 * vs, vp);
        }
        }
      }
      FS(2 * it + 1, 5);
      const uint32_t vl = ring_slot(ta + 63);
      vs = ring_slot(ta + 62);
      const uint32_t ob = more ? sbase + vs * 32768 : sbase + AT_SQ + 32768;
      mbar_wait(b_full + 8 * vl, ring_par(ta + 63));
      issue_pv(o, p, v_base + vl * 2048, 1);
      block_end(zero, b_pin);
      add_rowsum(p, l0, l1);
      const bool overflow = finish_l(l0, l1);
      if (!overflow && lane == 0) mbar_arrive(b_q1);
      #pragma unroll
      for (int i = 0; i < 8; i++) asm volatile("mov.b64 {%0, %1}, 0;\nmov.b64 {%2, %3}, 0;" : "=r"(pre[i].x), "=r"(pre[i].y), "=r"(pre[i].z), "=r"(pre[i].w));
      const bool want_pre = !more && bid < OG_MOE, got_pre = want_pre && __all_sync(0xffffffffu, mbar_test(bars + 272, 0));
      if (got_pre) load_pre(pre, sbase, AT_SQ, threadIdx.x - 128);
      mbar_wait(b_empty + 8 * vs, ring_par(ta + 62));
      wgmma_wait<0>();
      fence_regs(o);
      if (tid == 0) mbar_arrive(b_empty + 8 * vl);
      FS(2 * it + 1, 6);
      if (overflow) {
        attn_rows_exact(lds_u32(bars + 400), sq + 32768, ob + cwg * 8192, 4 * ta + 1, kc, vc);
        __syncwarp();
        if (lane == 0) mbar_arrive(b_q1);
      } else stage_o(o, l0, l1, ob + frag, lane);
      if (redo0) attn_rows_exact(lds_u32(bars + 400), sq, sq, 4 * ta, kc, vc);
      fence_proxy_async();
      __syncwarp();
      if (lane == 0) {
        if (redo0) mbar_arrive(b_ordy + 8 * cwg);
        mbar_arrive(b_ordy + 16 + 8 * cwg);
      }
      if (want_pre && !got_pre) load_pre(pre, sbase, AT_SQ, threadIdx.x - 128);
      if (redo0 || overflow) raw = false;
      named_bar_sync(3 + cwg, 128);
      FS(2 * it + 1, 7);
    }
    if (cwg == 0) named_bar_arrive(1, 256);
    if (__builtin_expect(single, 0)) {
      float acc[128];
      uint32_t j = 0, pk[64];
      #pragma unroll
      for (int i = 0; i < 64; i++) asm volatile("" : "=f"(acc[2 * i]), "=f"(acc[2 * i + 1]), "=r"(pk[i]));
      uint4* dst = g_pre;
      int left = 0;
      auto put = [&](bool last) {
        #pragma unroll
        for (int i = 0; i < PUT_N; i++) dst[i * 256] = make_uint4(pk[4 * i], pk[4 * i + 1], pk[4 * i + 2], pk[4 * i + 3]);
        dst += PUT_N * 256;
        #pragma unroll
        for (int i = 0; i < 64 - 4 * PUT_N; i++) asm volatile("mov.b32 %0, %1;" : "=r"(pk[i]) : "r"(pk[i + 4 * PUT_N]));
        __syncwarp();
        if (last && lane == 0) mbar_arrive(bars + 280);
      };
      #pragma unroll 1
      for (int ji = 0; ji < help_njobs(bid); ji++) {
        const int nk = og_pre(help_job(bid, ji));
        #pragma unroll 1
        for (int kk = 0; kk < nk; kk++, j++) {
          const uint32_t slot = ring_slot(qp_pos(j, 1));
          mbar_wait(b_full + 8 * slot, ring_par(qp_pos(j, 1)) ^ ((j >> 2) & 1));
          if (H_STAG > 0 && cwg == 1 && kk == nk - H_STAG) named_bar_sync(7, 256);
          const uint32_t a_lo = q_lo + (j & 3) * 1024, b_lo = w_base + slot * 2048;
          wgmma_fence();
          wgmma_m64n256k16_ss_tb<0, 0>(acc, a_lo, b_lo, kk != 0);
          wgmma_m64n256k16_ss_tb<2, 128>(acc, a_lo, b_lo, 1);
          wgmma_m64n256k16_ss_tb<4, 256>(acc, a_lo, b_lo, 1);
          wgmma_m64n256k16_ss_tb<6, 384>(acc, a_lo, b_lo, 1);
          wgmma_commit();
          if (H_STAG > 0 && cwg == 0 && kk == nk - 1) named_bar_arrive(7, 256);
          wgmma_wait<1>();
          if (kk > 0 && tid == 0) mbar_arrive(b_empty + 8 * ring_slot(qp_pos(j - 1, 1)));
          #pragma unroll 1
          for (int i = ji == OG_JOBS ? 0 : 16 / PUT_N - 1; i < 16 / PUT_N && left > 0; i++) put(--left == 0);
        }
        wgmma_wait<0>();
        fence_regs(acc);
        if (tid == 0) mbar_arrive(b_empty + 8 * ring_slot(qp_pos(j - 1, 1)));
        #pragma unroll
        for (int i = 0; i < 64; i++) pk[i] = pack_bf16(acc[2 * i], acc[2 * i + 1]);
        left = 16 / PUT_N;
        if (ji == PRE_X) mbar_wait(bars + 296, 0);
        dst = g_pre + help_job(bid, ji) * 2048 + threadIdx.x - 128;
      }
      #pragma unroll
      for (int i = 0; i < 16; i++) dst[i * 256] = make_uint4(pk[4 * i], pk[4 * i + 1], pk[4 * i + 2], pk[4 * i + 3]);
      __syncwarp();
      if (lane == 0) mbar_arrive(bars + 280);
      named_bar_sync(5, 256);
      if (threadIdx.x == 128) {
        #pragma unroll 1
        for (int i = 0; i < 5; i++) {
          constexpr int n = OG_HSUM;
          const int used = i == 3 ? 0 : (n + 3 - (i == 4 ? 3 : i)) / 4;
          if ((used ^ (i < 4)) & 1) {
            mbar_arrive(b_full + 8 * ring_slot(4 + i));
            mbar_arrive(b_empty + 8 * ring_slot(4 + i)); mbar_arrive(b_empty + 8 * ring_slot(4 + i));
          }
        }
        mbar_arrive(b_x);
      }
      named_bar_sync(5, 256);
      #pragma unroll
      for (int i = 0; i < 8; i++) pre[i] = make_uint4(0u, 0u, 0u, 0u);
    }
    TL_CLK(3, 1, threadIdx.x == 128);
    TL_CTA(1, threadIdx.x == 256);
    TL_END(3, tid == 0);
    TL_MARK2(19, tid == 0 && !single);
    if (bid < 128) {
      tail_consumer(bid, sbase, &tmOut, pre, cwg, w_gate, w_up);
    }
  }
}

typedef CUresult (*PFN_encodeTiled)(CUtensorMap*, CUtensorMapDataType, cuuint32_t, void*, const cuuint64_t*, const cuuint64_t*,
                                    const cuuint32_t*, const cuuint32_t*, CUtensorMapInterleave, CUtensorMapSwizzle,
                                    CUtensorMapL2promotion, CUtensorMapFloatOOBfill);

CUtensorMap make_map_2d(PFN_encodeTiled enc, const void* ptr, uint64_t inner, uint64_t outer, uint64_t stride_bytes, uint32_t box_inner, uint32_t box_outer) {
  CUtensorMap m;
  cuuint64_t gd[2] = {inner, outer}; cuuint64_t gs[1] = {stride_bytes};
  cuuint32_t bx[2] = {box_inner, box_outer}; cuuint32_t es[2] = {1, 1};
  enc(&m, CU_TENSOR_MAP_DATA_TYPE_BFLOAT16, 2, const_cast<void*>(ptr), gd, gs, bx, es, CU_TENSOR_MAP_INTERLEAVE_NONE,
      CU_TENSOR_MAP_SWIZZLE_128B, CU_TENSOR_MAP_L2_PROMOTION_L2_128B, CU_TENSOR_MAP_FLOAT_OOB_FILL_NONE);
  return m;
}

CUtensorMap make_map_3d(PFN_encodeTiled enc, const void* ptr, uint64_t cols, uint64_t rows, uint32_t box_rows, uint32_t chunks) {
  CUtensorMap m;
  cuuint64_t gd[3] = {64, rows, cols / 64}; cuuint64_t gs[2] = {cols * 2, 128};
  cuuint32_t bx[3] = {64, box_rows, chunks}; cuuint32_t es[3] = {1, 1, 1};
  enc(&m, CU_TENSOR_MAP_DATA_TYPE_BFLOAT16, 3, const_cast<void*>(ptr), gd, gs, bx, es, CU_TENSOR_MAP_INTERLEAVE_NONE,
      CU_TENSOR_MAP_SWIZZLE_128B, CU_TENSOR_MAP_L2_PROMOTION_L2_128B, CU_TENSOR_MAP_FLOAT_OOB_FILL_NONE);
  return m;
}

}

extern "C" void kernel_launch(void* const* d_in, const int* in_sizes, int n_in, void* d_out, int out_size) {
  const bf16* x      = (const bf16*)d_in[0];
  const bf16* kc     = (const bf16*)d_in[1];
  const bf16* vc     = (const bf16*)d_in[2];
  const bf16* wq     = (const bf16*)d_in[3];
  const bf16* wo     = (const bf16*)d_in[4];
  const bf16* w_r    = (const bf16*)d_in[6];
  const bf16* w_gate = (const bf16*)d_in[7];
  const bf16* w_up   = (const bf16*)d_in[8];
  const bf16* w_down = (const bf16*)d_in[9];
  const bf16* cvec   = (const bf16*)d_in[10];
  const bf16* w_mod  = (const bf16*)d_in[11];
  bf16* out = (bf16*)d_out;

  static PFN_encodeTiled enc = nullptr;
  static void *p_h = nullptr, *p_o = nullptr;
  if (!enc) {
    void* fn = nullptr; cudaDriverEntryPointQueryResult qres;
    cudaGetDriverEntryPoint("cuTensorMapEncodeTiled", &fn, cudaEnableDefault, &qres);
    enc = (PFN_encodeTiled)fn;
    cudaGetSymbolAddress(&p_h, g_pre);
    p_h = (uint4*)p_h + 16 * PRE_X * 2048;
    cudaGetSymbolAddress(&p_o, g_o);
    cudaFuncSetAttribute(fused_kernel, cudaFuncAttributeMaxDynamicSharedMemorySize, (int)AT_SMEM);
  }
  const CUtensorMap tm_h   = make_map_2d(enc, p_h, T_D, T_SEQ, T_D * 2, 64, 128);
  const CUtensorMap tm_wq  = make_map_3d(enc, wq, T_DQKV, T_D, 64, 4);
  const CUtensorMap tm_k   = make_map_3d(enc, kc, T_DH, (uint64_t)T_NH * T_SEQ, 128, 2);
  const CUtensorMap tm_v   = make_map_3d(enc, vc, T_DH, (uint64_t)T_NH * T_SEQ, 128, 2);
  const CUtensorMap tm_ost = make_map_2d(enc, p_o, T_DQKV, T_SEQ, T_DQKV * 2, 64, 64);
  const CUtensorMap tm_old = make_map_2d(enc, p_o, T_DQKV, T_SEQ, T_DQKV * 2, 64, 128);
  const CUtensorMap tm_wo  = make_map_3d(enc, wo, T_D, T_DQKV, 64, 2);
  const CUtensorMap tm_d   = make_map_3d(enc, w_down, T_D, T_F, 32, 8);

  const CUtensorMap tm_m   = make_map_2d(enc, w_mod, 6 * T_D, T_D, 6 * T_D * 2, 64, 256);
  const CUtensorMap tm_out = make_map_2d(enc, out, T_D, T_SEQ, T_D * 2, 64, 16);

  fused_kernel<<<132, 384, AT_SMEM, cudaStreamPerThread>>>(tm_h, tm_wq, tm_k, tm_v, tm_ost, tm_old, tm_wo, tm_d, tm_out, tm_m, 0u, (const uint8_t*)wo, kc, vc, x, cvec, w_mod,
             w_r, w_gate, w_up, w_down, out);
}
```
